```python
import torch

def _softmax(x, axis=-1):
    return torch.softmax(x, dim=axis)
def _gelu(x):
    return torch.nn.functional.gelu(x, approximate="tanh")
def _silu(x):
    return torch.nn.functional.silu(x)
def _sigmoid(x):
    return torch.sigmoid(x)
def _layernorm(x, axis=-1, eps=1e-5):
    m = x.mean(dim=axis, keepdim=True)
    v = x.var(dim=axis, keepdim=True, unbiased=False)
    return (x - m) / torch.sqrt(v + eps)
def _scatter_add(tgt, idx, src, axis=0):
    return tgt.clone().index_add_(axis, idx, src)
def _segment_sum(src, seg, n):
    out = torch.zeros((n,) + src.shape[1:], dtype=src.dtype)
    return out.index_add_(0, seg, src)
def _pad(x, pw):
    flat = tuple(v for pair in reversed(pw) for v in pair)
    return torch.nn.functional.pad(x, flat)

kernel_name = 'concat_heads__ssm_conv_s4d__linear_attn_block__prompt'

def setup_inputs():

    _w = (lambda a: (lambda t: t.to(torch.bfloat16) if t.is_floating_point() else t)(torch.as_tensor(a)))
    def _A_setup():
        Bsz, L, D, N = 1, 2048, 640, 128
        return {
            "u": _w((lambda *s: torch.randn(*s, dtype=torch.bfloat16) * 0.05)(Bsz, L, D)),
            "log_A_real": _w((lambda *s: torch.randn(*s, dtype=torch.bfloat16) * 3.2)(D, N) * 0.5),
            "A_imag": _w((lambda *s: torch.randn(*s, dtype=torch.bfloat16) * 0.05)(D, N) * 3.14),
            "C_real": _w((lambda *s: torch.randn(*s, dtype=torch.bfloat16) * 0.2)(D, N) / N ** 0.5),
            "C_imag": _w((lambda *s: torch.randn(*s, dtype=torch.bfloat16) * 0.2)(D, N) / N ** 0.5),
            "log_dt": _w((lambda *s: torch.randn(*s, dtype=torch.bfloat16) * 0.05)(D) * 0.5 - 4.0),
            "D_skip": _w((lambda *s: torch.randn(*s, dtype=torch.bfloat16) * 0.05)(D)),
        }
    _A_in = _A_setup()

    def _B_setup():
        B, S, D = 1, 2048, 640
        return {
            "x": _w((lambda *s: torch.randn(*s, dtype=torch.bfloat16) * 0.05)(B, S, D)),
            "wqkv": _w((lambda *s: torch.randn(*s, dtype=torch.bfloat16) * 0.4)(D, 3 * D)),
            "wo": _w((lambda *s: torch.randn(*s, dtype=torch.bfloat16) * 0.05)(D, D)),
        }
    _B_in = _B_setup()

    return {
        "A_u": _A_in["u"],
        "A_log_A_real": _A_in["log_A_real"],
        "A_A_imag": _A_in["A_imag"],
        "A_C_real": _A_in["C_real"],
        "A_C_imag": _A_in["C_imag"],
        "A_log_dt": _A_in["log_dt"],
        "A_D_skip": _A_in["D_skip"],
        "B_x": _B_in["x"],
        "B_wqkv": _B_in["wqkv"],
        "B_wo": _B_in["wo"],
    }

def reference(A_u, A_log_A_real, A_A_imag, A_C_real, A_C_imag, A_log_dt, A_D_skip, B_x, B_wqkv, B_wo):
    def _A_ref(u, log_A_real, A_imag, C_real, C_imag, log_dt, D_skip):
        L = u.shape[1]
        dt = torch.exp(log_dt)
        A = -torch.exp(log_A_real) + 1j * A_imag
        C = (C_real + 1j * C_imag) * dt[:, None]
        pos = (lambda x, dt: x.to(dt))(torch.arange(L), log_dt.dtype)
        P = torch.exp((A * dt[:, None])[:, :, None] * pos[None, None, :])
        K = 2.0 * torch.einsum("dn,dnl->dl", C, P).real
        L2 = 2 * L
        u_t = (lambda x, *d: x.permute(*d))(u, 0, 2, 1)
        Kf = (lambda x, *a, **k: torch.fft.rfft(x.float(), *a, **k))(K, L2)
        Uf = (lambda x, *a, **k: torch.fft.rfft(x.float(), *a, **k))(u_t, L2)
        y = (lambda x, *a, **k: torch.fft.irfft(x, *a, **k).to(torch.bfloat16))(Uf * Kf[None, :, :], L2)[:, :, :L]
        y = (lambda x, *d: x.permute(*d))(y, 0, 2, 1)
        return y + u * D_skip[None, None, :]

    def _B_ref(x, wqkv, wo):
        B, S, D = x.shape
        H = 32; Dh = D // H
        qkv = (lambda x, *d: x.permute(*d))((x @ wqkv).reshape(B, S, 3, H, Dh), 2, 0, 3, 1, 4)
        q, k, v = qkv[0], qkv[1], qkv[2]
        phi = lambda t: torch.where(t > 0, t + 1, torch.exp(t)) + 1e-6
        pq, pk = phi(q), phi(k)
        kv = torch.einsum("bhsd,bhse->bhde", pk, v)
        z = torch.einsum("bhsd->bhd", pk)
        num = torch.einsum("bhqd,bhde->bhqe", pq, kv)
        den = torch.einsum("bhqd,bhd->bhq", pq, z)[..., None] + 1e-6
        o = num / den
        return (lambda x, *d: x.permute(*d))(o, 0, 2, 1, 3).reshape(B, S, D) @ wo

    a = _A_ref(A_u, A_log_A_real, A_A_imag, A_C_real, A_C_imag, A_log_dt, A_D_skip)
    b = _B_ref(B_x, B_wqkv, B_wo)
    return torch.concatenate([a, b], axis=-1)
```

```cpp
#include <cuda_runtime.h>
#include <cuda_bf16.h>
#include <cuda.h>
#include <stdint.h>

#define EN_ATT 1
#define EN_SSM 1

__device__ __align__(1024) __nv_bfloat16 g_uy[2 * 640 * 2048];
__device__ __align__(128) uint4 g_kvp[8 * 16 * 240];
__device__ __align__(128) uint4 g_o[128 * 1280];
__device__ __align__(128) unsigned g_flag[40 * 32];
__device__ unsigned g_epoch[128];
#define TS(i) do {} while (0)

constexpr uint32_t W_SLOT = 15360, OFF_X = 76800;
constexpr uint32_t WO_SLOT = 12800, OFF_KVS = 38400, OFF_KVB = 43008, OFF_PK = 80896, OFF_V = 101376, OFF_EXTRA = 102400;
constexpr uint32_t OFF_BAR = 125952, OFF_BLK = 128000, BLK = 20480;
constexpr uint32_t B_D = 4096, B_D3 = 3072, B_D9 = 6144, B_D7 = 8192, B_TBL = 14336, B_SP = 18752;
constexpr uint32_t SMEM_BYTES = OFF_BLK + 5 * BLK + 1024;
enum { BR_FULL = 0, BR_EMPTY = 5, BR_WO = 10, BR_OFULL = 18, BR_OEMPTY = 22, BR_GEMM = 26, BR_OSTG = 27, BR_UIN = 28,
       BR_U = 29, BR_DRDY = 30, BR_KGEN = 35, BR_YSTG = 36, BR_FREE = 41, BR_YIN = 46, BR_EPOCH = 47, BR_COUNT = 48 };
constexpr uint32_t OFF_EPOCH = OFF_BAR + 8 * BR_COUNT;

__device__ __forceinline__ long long clk64() { long long t; asm volatile("mov.u64 %0, %%clock64;" : "=l"(t) :: "memory"); return t; }
__device__ __forceinline__ uint32_t smem_u32(const void* p) { return (uint32_t)__cvta_generic_to_shared(p); }
__device__ __forceinline__ uint64_t mkdesc(uint32_t addr, uint32_t lbo, uint32_t sbo, uint32_t swz) {
  return (uint64_t)((addr & 0x3FFFF) >> 4) | ((uint64_t)(lbo >> 4) << 16) | ((uint64_t)(sbo >> 4) << 32) | ((uint64_t)swz << 62);
}
__device__ __forceinline__ void mbar_init(uint32_t bar, uint32_t cnt) { asm volatile("mbarrier.init.shared::cta.b64 [%0], %1;" :: "r"(bar), "r"(cnt) : "memory"); }
__device__ __forceinline__ void mbar_expect_tx(uint32_t bar, uint32_t bytes) { asm volatile("mbarrier.arrive.expect_tx.shared::cta.b64 _, [%0], %1;" :: "r"(bar), "r"(bytes) : "memory"); }
__device__ __forceinline__ void mbar_arrive(uint32_t bar) { asm volatile("mbarrier.arrive.shared::cta.b64 _, [%0];" :: "r"(bar) : "memory"); }
__device__ __forceinline__ void mbar_wait(uint32_t bar, uint32_t parity) {
  asm volatile("{\n.reg .pred p;\n.reg .u32 c;\nmov.u32 c, 0;\n"
    "WL:\nmbarrier.try_wait.parity.shared::cta.b64 p, [%0], %1;\n@p bra WD;\n"
    "add.u32 c, c, 1;\nsetp.lt.u32 p, c, 200000;\n@p bra WL;\nWD:\n}" :: "r"(bar), "r"(parity) : "memory");
}
__device__ __forceinline__ void poll_all(const unsigned* p, unsigned val) {
  asm volatile("{\n.reg .pred p;\n.reg .u32 c, v;\nmov.u32 c, 0;\n"
    "PL:\nld.relaxed.gpu.global.u32 v, [%0];\nsetp.eq.u32 p, v, %1;\nvote.sync.all.pred p, p, 0xffffffff;\n@p bra PD;\n"
    "add.u32 c, c, 1;\nsetp.lt.u32 p, c, 100000;\n@p bra PL;\nPD:\n}" :: "l"(p), "r"(val) : "memory");
}
__device__ __forceinline__ unsigned poll_bit(const unsigned* p, unsigned val, unsigned mask) {
  unsigned bal;
  asm volatile("{\n.reg .pred p;\n.reg .u32 c, v;\nmov.u32 c, 0;\n"
    "PL:\nld.relaxed.gpu.global.u32 v, [%1];\nsetp.eq.u32 p, v, %2;\nvote.sync.ballot.b32 %0, p, 0xffffffff;\n"
    "and.b32 v, %0, %3;\nsetp.ne.u32 p, v, 0;\n@p bra PD;\n"
    "add.u32 c, c, 1;\nsetp.lt.u32 p, c, 100000;\n@p bra PL;\nPD:\n}" : "=&r"(bal) : "l"(p), "r"(val), "r"(mask) : "memory");
  return bal;
}
__device__ __forceinline__ void fix128_w0(uint32_t* v, const void* p, uint32_t tag, uint32_t mask) {
  asm volatile("{\n.reg .pred p;\n.reg .u32 c, x;\n.reg .b128 t;\n.reg .b64 lo, hi;\nmov.u32 c, 0;\n"
    "FL:\nxor.b32 x, %0, %5;\nand.b32 x, x, %6;\nsetp.eq.u32 p, x, 0;\n@p bra FD;\n"
    "ld.relaxed.gpu.global.b128 t, [%4];\nmov.b128 {lo, hi}, t;\nmov.b64 {%0, %1}, lo;\nmov.b64 {%2, %3}, hi;\n"
    "add.u32 c, c, 1;\nsetp.lt.u32 p, c, 100000;\n@p bra FL;\nFD:\n}"
    : "+r"(v[0]), "+r"(v[1]), "+r"(v[2]), "+r"(v[3]) : "l"(p), "r"(tag), "r"(mask) : "memory");
}
__device__ __forceinline__ void fix128_w3(uint32_t* v, const void* p, uint32_t tag, uint32_t mask) {
  asm volatile("{\n.reg .pred p;\n.reg .u32 c, x;\n.reg .b128 t;\n.reg .b64 lo, hi;\nmov.u32 c, 0;\n"
    "FL:\nxor.b32 x, %3, %5;\nand.b32 x, x, %6;\nsetp.eq.u32 p, x, 0;\n@p bra FD;\n"
    "ld.relaxed.gpu.global.b128 t, [%4];\nmov.b128 {lo, hi}, t;\nmov.b64 {%0, %1}, lo;\nmov.b64 {%2, %3}, hi;\n"
    "add.u32 c, c, 1;\nsetp.lt.u32 p, c, 100000;\n@p bra FL;\nFD:\n}"
    : "+r"(v[0]), "+r"(v[1]), "+r"(v[2]), "+r"(v[3]) : "l"(p), "r"(tag), "r"(mask) : "memory");
}
__device__ __forceinline__ void fence_acq() { asm volatile("fence.acq_rel.gpu;" ::: "memory"); }
__device__ __forceinline__ bool elect_one() {
  uint32_t p; asm volatile("{\n.reg .pred P;\nelect.sync _|P, 0xffffffff;\nselp.u32 %0, 1, 0, P;\n}" : "=r"(p)); return p;
}
__device__ __forceinline__ void bar_sync(int id, int n) { asm volatile("bar.sync %0, %1;" :: "r"(id), "r"(n) : "memory"); }
__device__ __forceinline__ void fence_async() { asm volatile("fence.proxy.async.shared::cta;" ::: "memory"); }
__device__ __forceinline__ void fence_async_g() { asm volatile("fence.proxy.async.global;" ::: "memory"); }
__device__ __forceinline__ void tma2d(uint32_t dst, const CUtensorMap* m, uint32_t bar, int c0, int c1) {
  asm volatile("cp.async.bulk.tensor.2d.shared::cluster.global.mbarrier::complete_tx::bytes [%0], [%1, {%3, %4}], [%2];"
    :: "r"(dst), "l"(m), "r"(bar), "r"(c0), "r"(c1) : "memory");
}
__device__ __forceinline__ void tma3d(uint32_t dst, const CUtensorMap* m, uint32_t bar, int c0, int c1, int c2) {
  asm volatile("cp.async.bulk.tensor.3d.shared::cluster.global.mbarrier::complete_tx::bytes [%0], [%1, {%3, %4, %5}], [%2];"
    :: "r"(dst), "l"(m), "r"(bar), "r"(c0), "r"(c1), "r"(c2) : "memory");
}
__device__ __forceinline__ void tma2d_st(const CUtensorMap* m, uint32_t src, int c0, int c1) {
  asm volatile("cp.async.bulk.tensor.2d.global.shared::cta.bulk_group [%0, {%2, %3}], [%1];"
    :: "l"(m), "r"(src), "r"(c0), "r"(c1) : "memory");
}
__device__ __forceinline__ void bulk_ld(uint32_t dst, const void* src, uint32_t bytes, uint32_t bar) {
  asm volatile("cp.async.bulk.shared::cluster.global.mbarrier::complete_tx::bytes [%0], [%1], %2, [%3];"
    :: "r"(dst), "l"(src), "r"(bytes), "r"(bar) : "memory");
}
__device__ __forceinline__ void bulk_st(void* dst, uint32_t src, uint32_t bytes) {
  asm volatile("cp.async.bulk.global.shared::cta.bulk_group [%0], [%1], %2;" :: "l"(dst), "r"(src), "r"(bytes) : "memory");
}
__device__ __forceinline__ void bulk_commit() { asm volatile("cp.async.bulk.commit_group;" ::: "memory"); }
__device__ __forceinline__ void bulk_wait0() { asm volatile("cp.async.bulk.wait_group 0;" ::: "memory"); }
__device__ __forceinline__ void bulk_wait0_read() { asm volatile("cp.async.bulk.wait_group.read 0;" ::: "memory"); }
__device__ __forceinline__ unsigned ld_rlx(const unsigned* p) { unsigned v; asm volatile("ld.relaxed.gpu.global.u32 %0, [%1];" : "=r"(v) : "l"(p) : "memory"); return v; }
__device__ __forceinline__ unsigned ld_acq(const unsigned* p) { unsigned v; asm volatile("ld.acquire.gpu.global.u32 %0, [%1];" : "=r"(v) : "l"(p) : "memory"); return v; }
__device__ __forceinline__ void st_rlx(unsigned* p, unsigned v) { asm volatile("st.relaxed.gpu.global.u32 [%0], %1;" :: "l"(p), "r"(v) : "memory"); }
__device__ __forceinline__ void st_rel(unsigned* p, unsigned v) { asm volatile("st.release.gpu.global.u32 [%0], %1;" :: "l"(p), "r"(v) : "memory"); }
__device__ __forceinline__ void ld128_rlx(uint32_t* v, const void* p) {
  asm volatile("{\n.reg .b128 t;\n.reg .b64 lo, hi;\nld.relaxed.gpu.global.b128 t, [%4];\nmov.b128 {lo, hi}, t;\n"
    "mov.b64 {%0, %1}, lo;\nmov.b64 {%2, %3}, hi;\n}" : "=r"(v[0]), "=r"(v[1]), "=r"(v[2]), "=r"(v[3]) : "l"(p) : "memory");
}
__device__ __forceinline__ void st128_rlx(void* p, const uint32_t* v) {
  asm volatile("{\n.reg .b128 t;\n.reg .b64 lo, hi;\nmov.b64 lo, {%1, %2};\nmov.b64 hi, {%3, %4};\nmov.b128 t, {lo, hi};\n"
    "st.relaxed.gpu.global.b128 [%0], t;\n}" :: "l"(p), "r"(v[0]), "r"(v[1]), "r"(v[2]), "r"(v[3]) : "memory");
}
__device__ __forceinline__ uint32_t lds32(uint32_t a) { uint32_t v; asm volatile("ld.shared.u32 %0, [%1];" : "=r"(v) : "r"(a) : "memory"); return v; }
__device__ __forceinline__ uint32_t lds16(uint32_t a) { uint16_t v; asm volatile("ld.shared.u16 %0, [%1];" : "=h"(v) : "r"(a) : "memory"); return v; }
__device__ __forceinline__ float ldsf(uint32_t a) { float v; asm volatile("ld.shared.f32 %0, [%1];" : "=f"(v) : "r"(a) : "memory"); return v; }
__device__ __forceinline__ void lds128(uint32_t* v, uint32_t a) { asm volatile("ld.shared.v4.u32 {%0,%1,%2,%3}, [%4];" : "=r"(v[0]), "=r"(v[1]), "=r"(v[2]), "=r"(v[3]) : "r"(a) : "memory"); }
__device__ __forceinline__ void sts32(uint32_t a, uint32_t v) { asm volatile("st.shared.u32 [%0], %1;" :: "r"(a), "r"(v) : "memory"); }
__device__ __forceinline__ void sts16(uint32_t a, uint32_t v) { asm volatile("st.shared.u16 [%0], %1;" :: "r"(a), "h"((uint16_t)v) : "memory"); }
__device__ __forceinline__ void sts64f(uint32_t a, float x, float y) { asm volatile("st.shared.v2.f32 [%0], {%1,%2};" :: "r"(a), "f"(x), "f"(y) : "memory"); }
__device__ __forceinline__ void sts128(uint32_t a, uint32_t x, uint32_t y, uint32_t z, uint32_t w) { asm volatile("st.shared.v4.u32 [%0], {%1,%2,%3,%4};" :: "r"(a), "r"(x), "r"(y), "r"(z), "r"(w) : "memory"); }
__device__ __forceinline__ void stsm4(uint32_t a, uint32_t r0, uint32_t r1, uint32_t r2, uint32_t r3) {
  asm volatile("stmatrix.sync.aligned.m8n8.x4.shared.b16 [%0], {%1,%2,%3,%4};" :: "r"(a), "r"(r0), "r"(r1), "r"(r2), "r"(r3) : "memory");
}
__device__ __forceinline__ void stsm4t(uint32_t a, uint32_t r0, uint32_t r1, uint32_t r2, uint32_t r3) {
  asm volatile("stmatrix.sync.aligned.m8n8.x4.trans.shared.b16 [%0], {%1,%2,%3,%4};" :: "r"(a), "r"(r0), "r"(r1), "r"(r2), "r"(r3) : "memory");
}
__device__ __forceinline__ void ldsm4t(uint32_t* r, uint32_t a) {
  asm volatile("ldmatrix.sync.aligned.m8n8.x4.trans.shared.b16 {%0,%1,%2,%3}, [%4];" : "=r"(r[0]), "=r"(r[1]), "=r"(r[2]), "=r"(r[3]) : "r"(a) : "memory");
}
__device__ __forceinline__ uint32_t pack2(float lo, float hi) { uint32_t r; asm("cvt.rn.bf16x2.f32 %0, %1, %2;" : "=r"(r) : "f"(hi), "f"(lo)); return r; }
__device__ __forceinline__ float bf_lo(uint32_t v) { return __uint_as_float(v << 16); }
__device__ __forceinline__ float bf_hi(uint32_t v) { return __uint_as_float(v & 0xffff0000u); }
__device__ __forceinline__ float bf_round(float x) { return bf_lo(pack2(x, 0.f)); }
__device__ __forceinline__ float ex2(float x) { float r; asm("ex2.approx.ftz.f32 %0, %1;" : "=f"(r) : "f"(x)); return r; }
__device__ __forceinline__ float phi(float t) { float e = ex2(t * 1.44269504089f); return (t > 0.f ? t + 1.f : e) + 1e-6f; }
__device__ __forceinline__ void wg_fence() { asm volatile("wgmma.fence.sync.aligned;" ::: "memory"); }
__device__ __forceinline__ void wg_commit() { asm volatile("wgmma.commit_group.sync.aligned;" ::: "memory"); }
template <int N> __device__ __forceinline__ void wg_wait() { asm volatile("wgmma.wait_group.sync.aligned %0;" :: "n"(N) : "memory"); }
template <int N> __device__ __forceinline__ void pin(float* a) {
  #pragma unroll
  for (int i = 0; i < N; i++) asm volatile("" : "+f"(a[i]) :: "memory");
}
__device__ __forceinline__ int opaque(int v) { asm volatile("" : "+r"(v)); return v; }
template <int N> __device__ __forceinline__ void zero(float* a) {
  #pragma unroll
  for (int i = 0; i < N; i++) asm volatile("mov.b32 %0, 0;" : "=f"(a[i]));
}
template <int N> __device__ __forceinline__ void pinu(uint32_t* a) {
  #pragma unroll
  for (int i = 0; i < N; i++) asm volatile("" : "+r"(a[i]) :: "memory");
}
__device__ __forceinline__ void cexp_t(float lg2mag, float turns, float& re, float& im) {
  float m = ex2(lg2mag);
  float fr = (turns - __fadd_rn(__fadd_rn(turns, 12582912.f), -12582912.f)) * 6.283185307f;
  re = m * __cosf(fr); im = m * __sinf(fr);
}
__device__ __forceinline__ void cmul(float ar, float ai, float br, float bi, float& cr, float& ci) {
  cr = fmaf(ar, br, -ai * bi); ci = fmaf(ar, bi, ai * br);
}

__device__ __forceinline__ void wg_ss192_tb(float* d, uint64_t da, uint64_t db, int scale_d) {
  asm volatile("{\n.reg .pred p;\nsetp.ne.b32 p, %98, 0;\n"
    "wgmma.mma_async.sync.aligned.m64n192k16.f32.bf16.bf16 "
    "{%0, %1, %2, %3, %4, %5, %6, %7, %8, %9, %10, %11, %12, %13, %14, %15, %16, %17, %18, %19, %20, %21, %22, %23, %24, %25, %26, %27, %28, %29, %30, %31, %32, %33, %34, %35, %36, %37, %38, %39, %40, %41, %42, %43, %44, %45, %46, %47, %48, %49, %50, %51, %52, %53, %54, %55, %56, %57, %58, %59, %60, %61, %62, %63, %64, %65, %66, %67, %68, %69, %70, %71, %72, %73, %74, %75, %76, %77, %78, %79, %80, %81, %82, %83, %84, %85, %86, %87, %88, %89, %90, %91, %92, %93, %94, %95}, %96, %97, p, 1, 1, 0, 1;\n}\n"
    : "+f"(d[0]), "+f"(d[1]), "+f"(d[2]), "+f"(d[3]), "+f"(d[4]), "+f"(d[5]), "+f"(d[6]), "+f"(d[7]), "+f"(d[8]), "+f"(d[9]), "+f"(d[10]), "+f"(d[11]), "+f"(d[12]), "+f"(d[13]), "+f"(d[14]), "+f"(d[15]), "+f"(d[16]), "+f"(d[17]), "+f"(d[18]), "+f"(d[19]), "+f"(d[20]), "+f"(d[21]), "+f"(d[22]), "+f"(d[23]), "+f"(d[24]), "+f"(d[25]), "+f"(d[26]), "+f"(d[27]), "+f"(d[28]), "+f"(d[29]), "+f"(d[30]), "+f"(d[31]), "+f"(d[32]), "+f"(d[33]), "+f"(d[34]), "+f"(d[35]), "+f"(d[36]), "+f"(d[37]), "+f"(d[38]), "+f"(d[39]), "+f"(d[40]), "+f"(d[41]), "+f"(d[42]), "+f"(d[43]), "+f"(d[44]), "+f"(d[45]), "+f"(d[46]), "+f"(d[47]), "+f"(d[48]), "+f"(d[49]), "+f"(d[50]), "+f"(d[51]), "+f"(d[52]), "+f"(d[53]), "+f"(d[54]), "+f"(d[55]), "+f"(d[56]), "+f"(d[57]), "+f"(d[58]), "+f"(d[59]), "+f"(d[60]), "+f"(d[61]), "+f"(d[62]), "+f"(d[63]), "+f"(d[64]), "+f"(d[65]), "+f"(d[66]), "+f"(d[67]), "+f"(d[68]), "+f"(d[69]), "+f"(d[70]), "+f"(d[71]), "+f"(d[72]), "+f"(d[73]), "+f"(d[74]), "+f"(d[75]), "+f"(d[76]), "+f"(d[77]), "+f"(d[78]), "+f"(d[79]), "+f"(d[80]), "+f"(d[81]), "+f"(d[82]), "+f"(d[83]), "+f"(d[84]), "+f"(d[85]), "+f"(d[86]), "+f"(d[87]), "+f"(d[88]), "+f"(d[89]), "+f"(d[90]), "+f"(d[91]), "+f"(d[92]), "+f"(d[93]), "+f"(d[94]), "+f"(d[95])
    : "l"(da), "l"(db), "r"(scale_d));
}
__device__ __forceinline__ void wg_ss48_tb(float* d, uint64_t da, uint64_t db, int scale_d) {
  asm volatile("{\n.reg .pred p;\nsetp.ne.b32 p, %26, 0;\n"
    "wgmma.mma_async.sync.aligned.m64n48k16.f32.bf16.bf16 "
    "{%0, %1, %2, %3, %4, %5, %6, %7, %8, %9, %10, %11, %12, %13, %14, %15, %16, %17, %18, %19, %20, %21, %22, %23}, %24, %25, p, 1, 1, 0, 1;\n}\n"
    : "+f"(d[0]), "+f"(d[1]), "+f"(d[2]), "+f"(d[3]), "+f"(d[4]), "+f"(d[5]), "+f"(d[6]), "+f"(d[7]), "+f"(d[8]), "+f"(d[9]), "+f"(d[10]), "+f"(d[11]), "+f"(d[12]), "+f"(d[13]), "+f"(d[14]), "+f"(d[15]), "+f"(d[16]), "+f"(d[17]), "+f"(d[18]), "+f"(d[19]), "+f"(d[20]), "+f"(d[21]), "+f"(d[22]), "+f"(d[23])
    : "l"(da), "l"(db), "r"(scale_d));
}
__device__ __forceinline__ void wg_ss48_tt(float* d, uint64_t da, uint64_t db, int scale_d) {
  asm volatile("{\n.reg .pred p;\nsetp.ne.b32 p, %26, 0;\n"
    "wgmma.mma_async.sync.aligned.m64n48k16.f32.bf16.bf16 "
    "{%0, %1, %2, %3, %4, %5, %6, %7, %8, %9, %10, %11, %12, %13, %14, %15, %16, %17, %18, %19, %20, %21, %22, %23}, %24, %25, p, 1, 1, 1, 1;\n}\n"
    : "+f"(d[0]), "+f"(d[1]), "+f"(d[2]), "+f"(d[3]), "+f"(d[4]), "+f"(d[5]), "+f"(d[6]), "+f"(d[7]), "+f"(d[8]), "+f"(d[9]), "+f"(d[10]), "+f"(d[11]), "+f"(d[12]), "+f"(d[13]), "+f"(d[14]), "+f"(d[15]), "+f"(d[16]), "+f"(d[17]), "+f"(d[18]), "+f"(d[19]), "+f"(d[20]), "+f"(d[21]), "+f"(d[22]), "+f"(d[23])
    : "l"(da), "l"(db), "r"(scale_d));
}
__device__ __forceinline__ void wg_rs88_tb(float* d, const uint32_t* a, uint64_t db, int scale_d) {
  asm volatile("{\n.reg .pred p;\nsetp.ne.b32 p, %49, 0;\n"
    "wgmma.mma_async.sync.aligned.m64n88k16.f32.bf16.bf16 "
    "{%0, %1, %2, %3, %4, %5, %6, %7, %8, %9, %10, %11, %12, %13, %14, %15, %16, %17, %18, %19, %20, %21, %22, %23, %24, %25, %26, %27, %28, %29, %30, %31, %32, %33, %34, %35, %36, %37, %38, %39, %40, %41, %42, %43}, {%44, %45, %46, %47}, %48, p, 1, 1, 1;\n}\n"
    : "+f"(d[0]), "+f"(d[1]), "+f"(d[2]), "+f"(d[3]), "+f"(d[4]), "+f"(d[5]), "+f"(d[6]), "+f"(d[7]), "+f"(d[8]), "+f"(d[9]), "+f"(d[10]), "+f"(d[11]), "+f"(d[12]), "+f"(d[13]), "+f"(d[14]), "+f"(d[15]), "+f"(d[16]), "+f"(d[17]), "+f"(d[18]), "+f"(d[19]), "+f"(d[20]), "+f"(d[21]), "+f"(d[22]), "+f"(d[23]), "+f"(d[24]), "+f"(d[25]), "+f"(d[26]), "+f"(d[27]), "+f"(d[28]), "+f"(d[29]), "+f"(d[30]), "+f"(d[31]), "+f"(d[32]), "+f"(d[33]), "+f"(d[34]), "+f"(d[35]), "+f"(d[36]), "+f"(d[37]), "+f"(d[38]), "+f"(d[39]), "+f"(d[40]), "+f"(d[41]), "+f"(d[42]), "+f"(d[43])
    : "r"(a[0]), "r"(a[1]), "r"(a[2]), "r"(a[3]), "l"(db), "r"(scale_d));
}
__device__ __forceinline__ void wg_rs80_tb(float* d, const uint32_t* a, uint64_t db, int scale_d) {
  asm volatile("{\n.reg .pred p;\nsetp.ne.b32 p, %45, 0;\n"
    "wgmma.mma_async.sync.aligned.m64n80k16.f32.bf16.bf16 "
    "{%0, %1, %2, %3, %4, %5, %6, %7, %8, %9, %10, %11, %12, %13, %14, %15, %16, %17, %18, %19, %20, %21, %22, %23, %24, %25, %26, %27, %28, %29, %30, %31, %32, %33, %34, %35, %36, %37, %38, %39}, {%40, %41, %42, %43}, %44, p, 1, 1, 1;\n}\n"
    : "+f"(d[0]), "+f"(d[1]), "+f"(d[2]), "+f"(d[3]), "+f"(d[4]), "+f"(d[5]), "+f"(d[6]), "+f"(d[7]), "+f"(d[8]), "+f"(d[9]), "+f"(d[10]), "+f"(d[11]), "+f"(d[12]), "+f"(d[13]), "+f"(d[14]), "+f"(d[15]), "+f"(d[16]), "+f"(d[17]), "+f"(d[18]), "+f"(d[19]), "+f"(d[20]), "+f"(d[21]), "+f"(d[22]), "+f"(d[23]), "+f"(d[24]), "+f"(d[25]), "+f"(d[26]), "+f"(d[27]), "+f"(d[28]), "+f"(d[29]), "+f"(d[30]), "+f"(d[31]), "+f"(d[32]), "+f"(d[33]), "+f"(d[34]), "+f"(d[35]), "+f"(d[36]), "+f"(d[37]), "+f"(d[38]), "+f"(d[39])
    : "r"(a[0]), "r"(a[1]), "r"(a[2]), "r"(a[3]), "l"(db), "r"(scale_d));
}
__device__ __forceinline__ void wg_rs16(float* d, const uint32_t* a, uint64_t db, int scale_d) {
  asm volatile("{\n.reg .pred p;\nsetp.ne.b32 p, %13, 0;\n"
    "wgmma.mma_async.sync.aligned.m64n16k16.f32.bf16.bf16 "
    "{%0, %1, %2, %3, %4, %5, %6, %7}, {%8, %9, %10, %11}, %12, p, 1, 1, 0;\n}\n"
    : "+f"(d[0]), "+f"(d[1]), "+f"(d[2]), "+f"(d[3]), "+f"(d[4]), "+f"(d[5]), "+f"(d[6]), "+f"(d[7])
    : "r"(a[0]), "r"(a[1]), "r"(a[2]), "r"(a[3]), "l"(db), "r"(scale_d));
}
__device__ __forceinline__ void wg_rs32(float* d, const uint32_t* a, uint64_t db, int scale_d) {
  asm volatile("{\n.reg .pred p;\nsetp.ne.b32 p, %21, 0;\n"
    "wgmma.mma_async.sync.aligned.m64n32k16.f32.bf16.bf16 "
    "{%0, %1, %2, %3, %4, %5, %6, %7, %8, %9, %10, %11, %12, %13, %14, %15}, {%16, %17, %18, %19}, %20, p, 1, 1, 0;\n}\n"
    : "+f"(d[0]), "+f"(d[1]), "+f"(d[2]), "+f"(d[3]), "+f"(d[4]), "+f"(d[5]), "+f"(d[6]), "+f"(d[7]), "+f"(d[8]), "+f"(d[9]), "+f"(d[10]), "+f"(d[11]), "+f"(d[12]), "+f"(d[13]), "+f"(d[14]), "+f"(d[15])
    : "r"(a[0]), "r"(a[1]), "r"(a[2]), "r"(a[3]), "l"(db), "r"(scale_d));
}
__device__ __forceinline__ void wg_rs24_tb(float* d, const uint32_t* a, uint64_t db, int scale_d) {
  asm volatile("{\n.reg .pred p;\nsetp.ne.b32 p, %17, 0;\n"
    "wgmma.mma_async.sync.aligned.m64n24k16.f32.bf16.bf16 "
    "{%0, %1, %2, %3, %4, %5, %6, %7, %8, %9, %10, %11}, {%12, %13, %14, %15}, %16, p, 1, 1, 1;\n}\n"
    : "+f"(d[0]), "+f"(d[1]), "+f"(d[2]), "+f"(d[3]), "+f"(d[4]), "+f"(d[5]), "+f"(d[6]), "+f"(d[7]), "+f"(d[8]), "+f"(d[9]), "+f"(d[10]), "+f"(d[11])
    : "r"(a[0]), "r"(a[1]), "r"(a[2]), "r"(a[3]), "l"(db), "r"(scale_d));
}
__device__ __forceinline__ void wg_rs16_tb(float* d, const uint32_t* a, uint64_t db, int scale_d) {
  asm volatile("{\n.reg .pred p;\nsetp.ne.b32 p, %13, 0;\n"
    "wgmma.mma_async.sync.aligned.m64n16k16.f32.bf16.bf16 "
    "{%0, %1, %2, %3, %4, %5, %6, %7}, {%8, %9, %10, %11}, %12, p, 1, 1, 1;\n}\n"
    : "+f"(d[0]), "+f"(d[1]), "+f"(d[2]), "+f"(d[3]), "+f"(d[4]), "+f"(d[5]), "+f"(d[6]), "+f"(d[7])
    : "r"(a[0]), "r"(a[1]), "r"(a[2]), "r"(a[3]), "l"(db), "r"(scale_d));
}

struct Params {
  const __nv_bfloat16 *logA, *Aim, *Cr, *Ci, *logdt, *dskip;
};

template <bool FWD>
__device__ __forceinline__ void tile_transpose(uint32_t tc0, uint32_t tc1, uint32_t ct0, uint32_t ct1, int hw, int lane) {
  const int mi = lane >> 3, row = lane & 7;
  for (int gi = hw; gi < 40; gi += 3) {
    const int hh = gi / 20, rem = gi - hh * 20, q = rem / 10, cb = rem - q * 10;
    const uint32_t a_tc = (hh ? tc1 : tc0) + (8 * (4 * q + mi) + row) * 160 + cb * 16;
    const uint32_t a_ct = (hh ? ct1 : ct0) + (8 * cb + row) * 128 + (((4 * q + mi) ^ row) << 4);
    uint32_t r[4];
    ldsm4t(r, FWD ? a_tc : a_ct);
    stsm4(FWD ? a_ct : a_tc, r[0], r[1], r[2], r[3]);
  }
}

template <int NS>
__device__ __forceinline__ void load_toep(uint32_t* A, uint32_t addr) {
  uint32_t prev = lds32(addr - 32);
  #pragma unroll
  for (int s = 0; s < NS; s++) {
    uint32_t x = lds32(addr + 64 * s), y = lds32(addr + 64 * s + 32);
    A[4 * s] = x; A[4 * s + 1] = y; A[4 * s + 2] = prev; A[4 * s + 3] = x;
    prev = y;
  }
}

__global__ void __launch_bounds__(512, 1)
fused_kernel(const __grid_constant__ CUtensorMap mx, const __grid_constant__ CUtensorMap mw, const __grid_constant__ CUtensorMap mr,
             const __grid_constant__ CUtensorMap mwo, const __grid_constant__ CUtensorMap mu, const __grid_constant__ CUtensorMap msa,
             const __grid_constant__ CUtensorMap msb, const __grid_constant__ CUtensorMap mout, const Params prm) {
  extern __shared__ unsigned char smem_raw[];
  const uint32_t sb = (smem_u32(smem_raw) + 1023) & ~1023u;
  const int tid = threadIdx.x, lane = tid & 31;
  const int wg = __shfl_sync(0xffffffff, tid >> 7, 0), warp = __shfl_sync(0xffffffff, tid >> 5, 0);
  const int cta = blockIdx.x, r = cta >> 3, c = cta & 7;
  const uint32_t bars = sb + OFF_BAR;
#define BAR(i) (bars + 8 * (i))
  if (tid == 0) TS(0);

  auto issue1 = [&](int kb) {
    const uint32_t st = sb + (kb % 5) * W_SLOT, fb = BAR(BR_FULL + kb % 5);
    mbar_expect_tx(fb, (kb & 1) ? W_SLOT : W_SLOT + 16384);
    if (!(kb & 1)) tma2d(sb + OFF_X + ((kb >> 1) % 3) * 16384, &mx, fb, kb * 32, r * 128);
    tma3d(st, &mw, fb, c * 80, kb * 32, 0);
    tma3d(st + 12288, &mr, fb, c * 80 + 64, kb * 32, 0);
  };

  if (warp == 12) {
    if (elect_one()) {
      #pragma unroll
      for (int i = 0; i < BR_COUNT; i++) {
        int cnt = 1;
        if (i >= BR_EMPTY && i < BR_EMPTY + 5) cnt = 2;
        if (i >= BR_OEMPTY && i < BR_OEMPTY + 4) cnt = 8;
        if (i == BR_OSTG) cnt = 256;
        if (i >= BR_DRDY && i < BR_DRDY + 5) cnt = 96;
        if (i >= BR_YSTG && i < BR_YSTG + 5) cnt = 128;
        mbar_init(BAR(i), cnt);
      }
      asm volatile("fence.mbarrier_init.release.cluster;" ::: "memory");
      if (EN_ATT) issue1(0);
    }
  }
  __syncthreads();

  if (wg == 3) {
    asm volatile("setmaxnreg.dec.sync.aligned.u32 56;");
    if (warp == 12) {
      if (EN_ATT) {
      #pragma unroll
      for (int kb = 1; kb < 20; kb++) {
        if (kb >= 5) mbar_wait(BAR(BR_EMPTY + kb % 5), ((kb / 5) & 1) ^ 1);
        if (elect_one()) issue1(kb);
      }
      auto chunk_of = [&](int i) { return i == 0 ? c : (i == 7 ? (c ^ 1) : (((c & 6) + 1 + i) & 7)); };
      mbar_wait(BAR(BR_EPOCH), 0);
      const unsigned epoch = lds32(sb + OFF_EPOCH);
      const unsigned* fo = &g_flag[(24 + r) * 32 + (lane & 7)];
      unsigned seen = __ballot_sync(0xffffffff, ld_rlx(fo) == epoch);
      mbar_wait(BAR(BR_GEMM), 0);
      if (elect_one()) {
        #pragma unroll
        for (int i = 0; i < 3; i++) { mbar_expect_tx(BAR(BR_WO + i), WO_SLOT); tma3d(sb + i * WO_SLOT, &mwo, BAR(BR_WO + i), 0, chunk_of(i) * 80, c * 5); }
      }
      mbar_wait(BAR(BR_OSTG), 0);
      if (elect_one()) {
        bulk_st(&g_o[cta * 1280], sb + OFF_EXTRA, 20480);
        bulk_commit();
        #pragma unroll
        for (int i = 3; i < 8; i++) { mbar_expect_tx(BAR(BR_WO + i), WO_SLOT); tma3d(sb + i * WO_SLOT, &mwo, BAR(BR_WO + i), 0, chunk_of(i) * 80, c * 5); }
        bulk_wait0();
        st_rlx(&g_flag[(24 + r) * 32 + c], epoch);
        TS(20);
      }
      __syncwarp();
      #pragma unroll
      for (int i = 0; i < 7; i++) {
        const int src = chunk_of(i + 1);
        if (!((seen >> src) & 1)) seen = poll_bit(fo, epoch, 1u << src);
        if (i < 3) { if (EN_SSM) mbar_wait(BAR(BR_FREE + 4 - i), 0); }
        else if (i > 3) mbar_wait(BAR(BR_OEMPTY + i - 4), 0);
        if (elect_one()) {
          fence_async_g();
          const uint32_t slot = (i & 3) == 3 ? sb + OFF_EXTRA : sb + OFF_BLK + (4 - (i & 3)) * BLK;
          mbar_expect_tx(BAR(BR_OFULL + (i & 3)), 20480);
          bulk_ld(slot, &g_o[(r * 8 + src) * 1280], 20480, BAR(BR_OFULL + (i & 3)));
          if (i == 0) TS(21);
          if (i == 6) TS(22);
        }
        __syncwarp();
      }
      }
    } else {
      const int hw = warp - 13, ht = tid - 416;
      unsigned epoch = 0;
      if (hw == 0) {
        if (lane == 0) {
          if (EN_SSM) {
            mbar_expect_tx(BAR(BR_UIN), 20480);
            tma2d(sb + OFF_BLK + 4 * BLK + B_D, &mu, BAR(BR_UIN), c * 80, r * 128);
            tma2d(sb + OFF_BLK + 3 * BLK + B_D, &mu, BAR(BR_UIN), c * 80, r * 128 + 64);
          }
          epoch = ld_rlx(&g_epoch[cta]) + 1;
          st_rlx(&g_epoch[cta], epoch);
          sts32(sb + OFF_EPOCH, epoch);
          mbar_arrive(BAR(BR_EPOCH));
        }
        epoch = __shfl_sync(0xffffffff, epoch, 0);
      }
      if (EN_SSM) {
      mbar_wait(BAR(BR_UIN), 0);
      tile_transpose<true>(sb + OFF_BLK + 4 * BLK + B_D, sb + OFF_BLK + 3 * BLK + B_D, sb + OFF_BLK + 2 * BLK + B_D, sb + OFF_BLK + 1 * BLK + B_D, hw, lane);
      fence_async();
      bar_sync(5, 96);
      if (hw == 0) {
        if (lane == 0) {
          tma2d_st(&msa, sb + OFF_BLK + 2 * BLK + B_D, r * 128, c * 80);
          tma2d_st(&msa, sb + OFF_BLK + 1 * BLK + B_D, r * 128 + 64, c * 80);
          bulk_commit(); bulk_wait0();
          st_rel(&g_flag[(8 + c) * 32 + r], epoch);
          TS(30);
        }
        __syncwarp();
        poll_all(&g_flag[(8 + c) * 32 + (lane & 15)], epoch);
        fence_acq(); __syncwarp();
        if (lane == 0) {
          fence_async_g();
          mbar_expect_tx(BAR(BR_U), 20480);
          #pragma unroll
          for (int k = 4; k >= 0; k--) tma2d(sb + OFF_BLK + k * BLK, &msb, BAR(BR_U), 0, (c * 80 + r * 5 + k) * 32);
          TS(31);
        }
        __syncwarp();
      }
      mbar_wait(BAR(BR_U), 0);
      #pragma unroll 1
      for (int k = 4; k >= 0; k--) {
        if (k == 0) mbar_wait(BAR(BR_KGEN), 0);
        const uint32_t blk = sb + OFF_BLK + k * BLK;
        #pragma unroll 1
        for (int kap = ht; kap < 192; kap += 96) {
          float P[33];
          P[0] = 0.f;
          #pragma unroll
          for (int q = 0; q < 4; q++) {
            const int ch = kap - 3 + q;
            uint32_t v[4];
            lds128(v, blk + (uint32_t)((ch >> 3) * 128 + (((ch & 7) ^ ((ch >> 3) & 7)) << 4)));
            #pragma unroll
            for (int e = 0; e < 4; e++) {
              P[q * 8 + 2 * e + 1] = P[q * 8 + 2 * e] + bf_lo(v[e]);
              P[q * 8 + 2 * e + 2] = P[q * 8 + 2 * e + 1] + bf_hi(v[e]);
            }
          }
#define WIN(lo, hi, e) (P[25 + (e) - (lo)] - P[24 + (e) - (hi)])
#define WIN8(lo, hi) pack2(WIN(lo, hi, 0), WIN(lo, hi, 1)), pack2(WIN(lo, hi, 2), WIN(lo, hi, 3)), pack2(WIN(lo, hi, 4), WIN(lo, hi, 5)), pack2(WIN(lo, hi, 6), WIN(lo, hi, 7))
          sts128(blk + B_D + kap * 16, WIN8(6, 10));
          sts128(blk + B_D + B_D3 + kap * 16, WIN8(3, 5));
          if (kap < 128) {
            const uint32_t o = (kap & 1) * 1024 + (kap >> 1) * 16;
            sts128(blk + B_D + B_D9 + o, WIN8(12, 20));
            sts128(blk + B_D + B_D7 + o, WIN8(5, 11));
          }
        }
        fence_async();
        mbar_arrive(BAR(BR_DRDY + k));
      }
      if (ht == 0) TS(32);
      if (hw == 0) {
        #pragma unroll 1
        for (int k = 4; k >= 0; k--) {
          mbar_wait(BAR(BR_YSTG + k), 0);
          if (lane == 0) {
            tma2d_st(&msb, sb + OFF_BLK + k * BLK, 0, (640 + c * 80 + r * 5 + k) * 32);
            bulk_commit(); bulk_wait0_read();
            mbar_arrive(BAR(BR_FREE + k));
          }
          __syncwarp();
        }
        if (lane == 0) { bulk_wait0(); st_rel(&g_flag[(16 + c) * 32 + r], epoch); TS(33); }
        __syncwarp();
        poll_all(&g_flag[(16 + c) * 32 + (lane & 15)], epoch);
        (void)ld_acq(&g_flag[(16 + c) * 32 + (lane & 15)]); __syncwarp();
        if (lane == 0) {
          fence_async_g();
          mbar_expect_tx(BAR(BR_YIN), 20480);
          tma2d(sb + OFF_BLK + BLK, &msa, BAR(BR_YIN), r * 128, 640 + c * 80);
          tma2d(sb + OFF_BLK + BLK + 10240, &msa, BAR(BR_YIN), r * 128 + 64, 640 + c * 80);
          TS(34);
        }
        __syncwarp();
      }
      mbar_wait(BAR(BR_YIN), 0);
      tile_transpose<false>(sb + OFF_BLK, sb + OFF_BLK + 10240, sb + OFF_BLK + BLK, sb + OFF_BLK + BLK + 10240, hw, lane);
      fence_async();
      bar_sync(5, 96);
      if (ht == 0) {
        tma2d_st(&mout, sb + OFF_BLK, c * 80, r * 128);
        tma2d_st(&mout, sb + OFF_BLK + 10240, c * 80, r * 128 + 64);
        bulk_commit(); bulk_wait0_read();
        TS(35);
      }
      }
    }
  } else if (wg < 2) {
    asm volatile("setmaxnreg.inc.sync.aligned.u32 152;");
    if (EN_ATT) {
    const int w4 = warp & 3, g = lane >> 2, tq = lane & 3, t7 = tid & 127;
    float am[96], ar[24];
    {
      const uint64_t da0 = mkdesc(sb + OFF_X + wg * 8192, 16, 1024, 1);
      const uint64_t db0 = mkdesc(sb, 4096, 1024, 1);
      const uint64_t dr0 = mkdesc(sb + 12288, 1024, 256, 3);
      uint32_t s = 0, ph = 0, xo = 0;
      #pragma unroll 1
      for (int kb = 0; kb < 20; kb++) {
        mbar_wait(BAR(BR_FULL) + 8 * s, ph);
        if (kb == 0 && tid == 0) TS(1);
        wg_fence();
        const uint32_t wo_ = s * (W_SLOT >> 4);
        wg_ss192_tb(am, da0 + xo, db0 + wo_, kb != 0);
        wg_ss48_tb(ar, da0 + xo, dr0 + wo_, kb != 0);
        wg_ss192_tb(am, da0 + xo + 2, db0 + wo_ + 128, 1);
        wg_ss48_tb(ar, da0 + xo + 2, dr0 + wo_ + 32, 1);
        wg_commit();
        wg_wait<1>();
        if (t7 == 0 && kb > 0 && kb < 16) mbar_arrive(BAR(BR_EMPTY) + 8 * (s == 0 ? 4 : s - 1));
        if (++s == 5) { s = 0; ph ^= 1; }
        xo += (kb & 1) ? 1020 : 4;
        if (xo == 3072) xo = 0;
      }
      wg_wait<0>();
      pin<96>(am); pin<24>(ar);
    }
    if (tid == 0) TS(2);
#define QV(j, e) ((j) < 8 ? am[4 * (j) + (e)] : ar[4 * ((j) - 8) + (e)])
#define KV_(j, e) ((j) < 8 ? am[32 + 4 * (j) + (e)] : ar[8 + 4 * ((j) - 8) + (e)])
#define VV(j, e) ((j) < 8 ? am[64 + 4 * (j) + (e)] : ar[16 + 4 * ((j) - 8) + (e)])
    {
      bar_sync(1, 256);
      if (tid == 0) mbar_arrive(BAR(BR_GEMM));
      const uint32_t ro = (uint32_t)((lane >> 4) * 2048 + (wg * 64 + w4 * 16 + (lane & 15)) * 16);
      const uint32_t ones = (tq == 0) ? 0x00003f80u : 0u;
#define PV(j) pack2(VV(j, 0), VV(j, 1)), pack2(VV(j, 2), VV(j, 3))
#define PK(j) pack2(phi(KV_(j, 0)), phi(KV_(j, 1))), pack2(phi(KV_(j, 2)), phi(KV_(j, 3)))
      stsm4(sb + OFF_V + 0 * 2048 + ro, PV(0), PV(1));
      stsm4(sb + OFF_V + 2 * 2048 + ro, PV(2), PV(3));
      stsm4(sb + OFF_V + 4 * 2048 + ro, PV(4), ones, ones);
      stsm4(sb + OFF_V + 6 * 2048 + ro, PV(5), PV(6));
      stsm4(sb + OFF_V + 8 * 2048 + ro, PV(7), PV(8));
      stsm4(sb + OFF_V + 10 * 2048 + ro, PV(9), ones, ones);
      #pragma unroll
      for (int j = 0; j < 10; j += 2) stsm4(sb + OFF_PK + j * 2048 + ro, PK(j), PK(j + 1));
    }
    fence_async();
    bar_sync(1, 256);
    if (tid == 0) TS(3);
    mbar_wait(BAR(BR_EPOCH), 0);
    const unsigned epoch = lds32(sb + OFF_EPOCH);
    {
      float kv[24]; zero<24>(kv);
      const uint64_t da = mkdesc(sb + OFF_PK + wg * 5 * 2048, 128, 2048, 0);
      const uint64_t db = mkdesc(sb + OFF_V + wg * 6 * 2048, 128, 2048, 0);
      wg_fence();
      #pragma unroll
      for (int s = 0; s < 8; s++) wg_ss48_tt(kv, da + s * 16, db + s * 16, s != 0);
      wg_commit();
      #pragma unroll
      for (int i = 0; i < 4; i++) { const int q = tid + i * 256; if (q < 880) sts128(sb + OFF_KVB + q * 16, 0, 0, 0, 0); }
      if (tid < 240) sts16(sb + OFF_KVS + tid * 16 + 14, epoch);
      wg_wait<0>();
      pin<24>(kv);
      #pragma unroll
      for (int h = 0; h < 2; h++) {
        const int dl = w4 * 16 + g + 8 * h;
        if (dl < 40) {
          const int hl = dl >= 20;
          const uint32_t rowa = sb + OFF_KVS + (wg * 40 + dl) * 48;
          #pragma unroll
          for (int j = 0; j < 5; j++) {
            const int p = 8 * j + 2 * tq - 20 * hl;
            if (p >= 0 && p < 20) {
              const uint32_t v = pack2(kv[4 * j + 2 * h], kv[4 * j + 2 * h + 1]);
              sts16(rowa + 2 * (p + (p >= 7) + (p >= 14)), v);
              sts16(rowa + 2 * (p + 1 + (p >= 6) + (p >= 13)), v >> 16);
            }
          }
          if (tq == 0) sts16(rowa + 2 * 22, pack2(kv[20 + 2 * h], 0.f));
        }
      }
    }
    bar_sync(1, 256);
    if (tid < 240) { uint32_t v[4]; lds128(v, sb + OFF_KVS + tid * 16); st128_rlx(&g_kvp[(c * 16 + r) * 240 + tid], v); }
    bar_sync(1, 256);
    if (tid == 0) { st_rlx(&g_flag[c * 32 + r], epoch); TS(4); }
    uint32_t qa[20];
    pin<32>(am); pin<8>(ar);
    #pragma unroll
    for (int j = 0; j < 10; j++) { qa[2 * j] = pack2(phi(QV(j, 0)), phi(QV(j, 1))); qa[2 * j + 1] = pack2(phi(QV(j, 2)), phi(QV(j, 3))); }
    pinu<20>(qa);
    if (tid == 0) TS(5);
    {
      poll_all(&g_flag[c * 32 + (lane & 15)], epoch);
      if (tid == 0) TS(6);
      if (tid < 240) {
        uint32_t v[16][4];
        const uint4* src = &g_kvp[c * 16 * 240 + tid];
        #pragma unroll
        for (int i = 0; i < 16; i++) ld128_rlx(v[i], src + i * 240);
        float s[7] = {0.f, 0.f, 0.f, 0.f, 0.f, 0.f, 0.f};
        #pragma unroll
        for (int i = 0; i < 16; i++) {
          fix128_w3(v[i], src + i * 240, epoch << 16, 0xffff0000u);
          s[0] += bf_lo(v[i][0]); s[1] += bf_hi(v[i][0]); s[2] += bf_lo(v[i][1]); s[3] += bf_hi(v[i][1]);
          s[4] += bf_lo(v[i][2]); s[5] += bf_hi(v[i][2]); s[6] += bf_lo(v[i][3]);
        }
        const int d = tid / 3, vi = tid - d * 3, hd = d / 20;
        #pragma unroll
        for (int i = 0; i < 7; i++) {
          const int p = vi * 7 + i;
          const int n = p < 20 ? hd * 20 + p : 80 + hd;
          sts16(sb + OFF_KVB + (n >> 3) * 1280 + d * 16 + (n & 7) * 2, pack2(s[i], 0.f));
        }
      }
    }
    fence_async();
    bar_sync(1, 256);
    if (tid == 0) TS(7);
    uint32_t A0[20], A1[20];
    {
      float oa[44]; zero<44>(oa);
      const uint64_t db = mkdesc(sb + OFF_KVB, 128, 1280, 0);
      wg_fence();
      #pragma unroll
      for (int s = 0; s < 5; s++) wg_rs88_tb(oa, &qa[4 * s], db + s * 16, s != 0);
      wg_commit();
      wg_wait<0>();
      pin<44>(oa);
      float rc[4], rd[2][4];
      #pragma unroll
      for (int e = 0; e < 4; e++) rc[e] = __fdividef(1.f, oa[40 + e] + 1e-6f);
      #pragma unroll
      for (int h = 0; h < 4; h++) {
        rd[0][h] = __shfl_sync(0xffffffff, rc[h & 1], (lane & 28) | (h >> 1));
        rd[1][h] = __shfl_sync(0xffffffff, rc[2 + (h & 1)], (lane & 28) | (h >> 1));
      }
      #pragma unroll
      for (int j = 0; j < 10; j++) {
        #pragma unroll
        for (int h = 0; h < 2; h++) {
          float f;
          if (j == 2) f = tq < 2 ? rd[h][0] : rd[h][1];
          else if (j == 7) f = tq < 2 ? rd[h][2] : rd[h][3];
          else f = rd[h][(8 * j) / 20];
          A0[2 * j + h] = pack2(oa[4 * j + 2 * h] * f, oa[4 * j + 2 * h + 1] * f);
        }
      }
      #pragma unroll
      for (int s = 0; s < 5; s++) {
        A0[4 * s] = (A0[4 * s] & ~1u) | (epoch & 1u);
        sts128(sb + OFF_EXTRA + ((wg * 5 + s) * 128 + t7) * 16, A0[4 * s], A0[4 * s + 1], A0[4 * s + 2], A0[4 * s + 3]);
      }
    }
    fence_async();
    mbar_arrive(BAR(BR_OSTG));
    if (tid == 0) TS(8);
    float oc[40]; zero<40>(oc);
    {
      const uint64_t dw0 = mkdesc(sb, 2560, 256, 3);
      mbar_wait(BAR(BR_WO), 0);
      wg_fence();
      #pragma unroll
      for (int s = 0; s < 5; s++) wg_rs80_tb(oc, &A0[4 * s], dw0 + s * 32, s != 0);
      wg_commit();
      #pragma unroll
      for (int i = 0; i < 7; i++) {
        uint32_t* A = (i & 1) ? A0 : A1;
        const uint32_t slot = (i & 3) == 3 ? sb + OFF_EXTRA : sb + OFF_BLK + (4 - (i & 3)) * BLK;
        mbar_wait(BAR(BR_OFULL + (i & 3)), i >> 2);
        if (i == 0 && tid == 0) TS(9);
        if (i > 0) wg_wait<1>();
        #pragma unroll
        for (int s = 0; s < 5; s++) lds128(&A[4 * s], slot + ((wg * 5 + s) * 128 + t7) * 16);
        uint32_t bad = 0;
        #pragma unroll
        for (int s = 0; s < 5; s++) bad |= (A[4 * s] ^ epoch) & 1u;
        if (bad) {
          const int src = (i == 6) ? (c ^ 1) : (((c & 6) + 2 + i) & 7);
          #pragma unroll
          for (int s = 0; s < 5; s++) fix128_w0(&A[4 * s], &g_o[(r * 8 + src) * 1280 + (wg * 5 + s) * 128 + t7], epoch, 1u);
        }
        __syncwarp();
        if (i < 3 && lane == 0) mbar_arrive(BAR(BR_OEMPTY + i));
        mbar_wait(BAR(BR_WO + i + 1), 0);
        wg_fence();
        #pragma unroll
        for (int s = 0; s < 5; s++) wg_rs80_tb(oc, &A[4 * s], dw0 + (((i + 1) * WO_SLOT) >> 4) + s * 32, 1);
        wg_commit();
      }
      wg_wait<0>();
      pin<40>(oc);
    }
    if (tid == 0) TS(10);
    {
      bar_sync(2 + wg, 128);
      const uint32_t ob = sb + OFF_EXTRA + wg * 10240 + (w4 * 16 + (lane & 15)) * 160 + (lane >> 4) * 16;
      #pragma unroll
      for (int j = 0; j < 10; j += 2)
        stsm4(ob + j * 16, pack2(oc[4 * j], oc[4 * j + 1]), pack2(oc[4 * j + 2], oc[4 * j + 3]), pack2(oc[4 * j + 4], oc[4 * j + 5]), pack2(oc[4 * j + 6], oc[4 * j + 7]));
      fence_async();
      bar_sync(2 + wg, 128);
      if (t7 == 0) { tma2d_st(&mout, sb + OFF_EXTRA + wg * 10240, 640 + c * 80, r * 128 + wg * 64); bulk_commit(); bulk_wait0_read(); }
      if (tid == 0) TS(11);
    }
    }
  } else {
    asm volatile("setmaxnreg.inc.sync.aligned.u32 152;");
    if (EN_SSM) {
    const int w4 = warp & 3, g = lane >> 2, tq = lane & 3, t7 = tid & 127;
    const int d0 = c * 80 + r * 5;
    uint32_t pa, pc, pd, pdn;
    auto ldp = [&](int k) {
      const int o = (d0 + k) * 128 + opaque(t7);
      pa = (uint32_t)__bfloat16_as_ushort(prm.logA[o]) | ((uint32_t)__bfloat16_as_ushort(prm.Aim[o]) << 16);
      pc = (uint32_t)__bfloat16_as_ushort(prm.Cr[o]) | ((uint32_t)__bfloat16_as_ushort(prm.Ci[o]) << 16);
      pdn = (uint32_t)__bfloat16_as_ushort(prm.logdt[d0 + k]) | ((uint32_t)__bfloat16_as_ushort(prm.dskip[d0 + k]) << 16);
    };
    ldp(4);
    if (t7 < 32) {
      const __nv_bfloat16* pp = (t7 >> 3) == 0 ? prm.logA : (t7 >> 3) == 1 ? prm.Aim : (t7 >> 3) == 2 ? prm.Cr : prm.Ci;
      asm volatile("prefetch.global.L2 [%0];" :: "l"(pp + d0 * 128 + (t7 & 7) * 64));
    }
    #pragma unroll
    for (int k = 0; k < 5; k++)
      #pragma unroll
      for (int i = 0; i < 3; i++) sts128(sb + OFF_BLK + k * BLK + B_TBL + (i * 128 + t7) * 16, 0, 0, 0, 0);
    if (t7 < 72) sts128(sb + OFF_BLK - 1152 + t7 * 16, 0, 0, 0, 0);

    const uint32_t kg = sb + OFF_BLK + B_D;
    const uint32_t kcon = kg + 6704, kka = kg + 8752, kk2 = kka + 1028;
    uint32_t G[13]; float cn[4];
    auto pre = [&](uint32_t a_, uint32_t c_, uint32_t d_) {
      const float dt = bf_round(expf(bf_lo(d_)));
      const float lr = -bf_round(expf(bf_lo(a_))) * dt * 1.44269504089f;
      const float tn = bf_hi(a_) * dt * 0.15915494309f;
      float zr, zi, hr, hi_, gr = 2.f * bf_lo(c_) * dt, gi = 2.f * bf_hi(c_) * dt, g4r = 0.f, g4i = 0.f;
      cexp_t(lr, tn, zr, zi);
      cexp_t(lr * 512.f, tn * 512.f, hr, hi_);
      cexp_t(lr * 64.f, tn * 64.f, cn[2], cn[3]);
      cn[0] = lr * 8.f; cn[1] = tn * 8.f;
      float xr = gr, xi = gi;
      #pragma unroll
      for (int b = 0; b < 8; b++) {
        G[b] = pack2(xr, -xi);
        if (b == 4) { g4r = xr; g4i = xi; }
        if (b < 7) cmul(xr, xi, zr, zi, xr, xi);
      }
      cmul(g4r, g4i, hr, hi_, g4r, g4i); G[9] = pack2(g4r, -g4i);
      cmul(gr, gi, hr, hi_, gr, gi); G[8] = pack2(gr, -gi);
      cmul(gr, gi, hr, hi_, gr, gi); G[10] = pack2(gr, -gi);
      cmul(gr, gi, hr, hi_, gr, gi); G[11] = pack2(gr, -gi);
      cmul(gr, gi, hr, hi_, gr, gi); G[12] = pack2(gr, -gi);
    };
    auto pre_store = [&]() {
      const int tt = opaque(t7);
      #pragma unroll
      for (int b = 0; b < 13; b++) sts32(kg + (tt >> 2) * 208 + b * 16 + (tt & 3) * 4, G[b]);
      sts128(kcon + tt * 16, __float_as_uint(cn[0]), __float_as_uint(cn[1]), __float_as_uint(cn[2]), __float_as_uint(cn[3]));
    };
    auto build_tbl = [&](int k) {
      const int tt = opaque(t7);
      const uint32_t tb = sb + OFF_BLK + k * BLK + B_TBL, k3 = sb + OFF_BLK + k * BLK + B_SP;
      auto rnd = [](int l) { return l < 256 ? l : (l >= 511 ? 512 : ((l + ((l >> 1) & 1)) & ~1)); };
      #pragma unroll
      for (int i = 0; i < 5; i++) {
        const int o = tt + i * 128;
        if (o <= 515) {
          const uint32_t lo = o <= 514 ? lds16(kka + 2 * rnd(o)) : 0u, hi = o >= 1 ? lds16(kka + 2 * rnd(o - 1)) : 0u;
          sts32(tb + (64 + o) * 4, lo | (hi << 16));
        }
      }
      if (tt <= 64) {
        const int e = tt;
        uint32_t lo = e < 64 ? lds16(kk2 + 2 * (e + 1)) : 0u, hi = e >= 1 ? lds16(kk2 + 2 * e) : 0u;
        sts32(tb + (656 + e) * 4, lo | (hi << 16));
        lo = e < 64 ? lds16(kk2 + 132 + 2 * e) : 0u; hi = e >= 1 ? lds16(kk2 + 132 + 2 * (e - 1)) : 0u;
        sts32(tb + (784 + e) * 4, lo | (hi << 16));
      }
      if (tt >= 64) {
        const int e = tt - 64;
        uint32_t lo = lds16(k3 + 2 * (2 * e + 2)), hi = e >= 1 ? lds16(k3 + 2 * (2 * e)) : 0u;
        sts32(tb + (912 + e) * 4, lo | (hi << 16));
        lo = lds16(k3 + 2 * (2 * e + 1)); hi = e >= 1 ? lds16(k3 + 2 * (2 * e - 1)) : 0u;
        sts32(tb + (1040 + e) * 4, lo | (hi << 16));
      }
    };
    pre(pa, pc, pdn);
    pre_store();
    if (t7 == 0) TS(40);
    {
      const float ef = (float)(w4 * 16 + g);
      const uint64_t dg = mkdesc(kg, 208, 128, 0);
      #pragma unroll 1
      for (int k = 4; k >= 0; k--) {
        fence_async();
        bar_sync(4, 128);
        pd = pdn;
        ldp(k > 0 ? k - 1 : 0);
        uint32_t A[64];
        #pragma unroll
        for (int m = 0; m < 32; m++) {
          if ((m & 7) == 0 && m) __syncwarp();
          uint32_t cc[4];
          lds128(cc, kcon + (m * 4 + tq) * 16);
          float er, ei, fr, fi;
          cexp_t(__uint_as_float(cc[0]) * ef, __uint_as_float(cc[1]) * ef, er, ei);
          cmul(er, ei, __uint_as_float(cc[2]), __uint_as_float(cc[3]), fr, fi);
          A[2 * m] = pack2(er, ei); A[2 * m + 1] = pack2(fr, fi);
          if ((m & 3) == 3) pinu<8>(&A[2 * m - 6]);
        }
        float ka[8]; zero<8>(ka);
        wg_fence();
        #pragma unroll
        for (int s = 0; s < 16; s++) wg_rs16(ka, &A[4 * s], dg + s * 26, s != 0);
        wg_commit();
        if (k < 4) build_tbl(k + 1);
        pre(pa, pc, pdn);
        pinu<13>(G); pin<4>(cn);
        wg_wait<0>();
        pin<8>(ka);
        bar_sync(4, 128);
        {
          const uint32_t k3 = sb + OFF_BLK + k * BLK + B_SP;
          if (t7 == 0) ka[0] += bf_hi(pd);
          const int j0 = opaque(w4 * 16 + g);
          #pragma unroll
          for (int h = 0; h < 2; h++) {
            const int j = j0 + 8 * h;
            sts32(kka + (8 * j + 2 * tq) * 2, pack2(ka[2 * h], ka[2 * h + 1]));
            const uint32_t v = pack2(ka[4 + 2 * h], ka[5 + 2 * h]);
            if (tq == 0) { sts16(kk2 + 2 * j, v); sts16(kk2 + 132 + 2 * j, v >> 16); if (j == 0) sts16(kka + 1024, v); }
            if (tq == 1) { sts16(k3 + 2 * j, v); sts16(k3 + 128 + 2 * j, v >> 16); if (j == 0) sts16(kk2 + 128, v); }
            if (tq == 2 && j == 0) sts16(k3 + 256, v);
          }
        }
        pre_store();
      }
      bar_sync(4, 128);
      build_tbl(0);
      bar_sync(4, 128);
      if (t7 == 0) { mbar_arrive(BAR(BR_KGEN)); TS(41); }
    }
    mbar_wait(BAR(BR_U), 0);
    if (EN_ATT) mbar_wait(BAR(BR_GEMM), 0);
    if (t7 == 0) TS(42);
    const uint32_t lb = (uint32_t)((16 * w4 + g - 2 * tq - 48) * 4);
    #pragma unroll 1
    for (int k = 4; k >= 0; k--) {
      const uint32_t blk = sb + OFF_BLK + k * BLK, tb = blk + B_TBL + lb;
      const uint64_t dd = mkdesc(blk + B_D, 128, 1024, 0);
      const uint64_t du = mkdesc(blk + 96 - 32 * 36, 16, 1024, 1);
      float aC[8], a24[12], a16[8], aY[16];
      zero<8>(aC); zero<12>(a24); zero<8>(a16); zero<16>(aY);
      uint32_t A0[32], A1[32];
      mbar_wait(BAR(BR_DRDY + k), 0);
      load_toep<4>(A0, tb + 912 * 4); load_toep<4>(A0 + 16, tb + 1040 * 4);
      wg_fence();
      #pragma unroll
      for (int s = 0; s < 4; s++) wg_rs16_tb(aC, &A0[4 * s], dd + (B_D9 >> 4) + (3 - s) * 16, s != 0);
      #pragma unroll
      for (int s = 0; s < 4; s++) wg_rs16_tb(aC, &A0[16 + 4 * s], dd + (B_D7 >> 4) + (3 - s) * 16, 1);
      wg_commit();
      load_toep<8>(A1, tb + 656 * 4);
      wg_fence();
      #pragma unroll
      for (int s = 0; s < 4; s++) wg_rs24_tb(a24, &A1[4 * s], dd + (3 - s) * 16, s != 0);
      #pragma unroll
      for (int s = 0; s < 4; s++) wg_rs16_tb(a16, &A1[16 + 4 * s], dd + (3 - s) * 16, s != 0);
      wg_commit();
      wg_wait<1>();
      load_toep<8>(A0, tb + 784 * 4);
      wg_fence();
      #pragma unroll
      for (int s = 0; s < 4; s++) wg_rs24_tb(a24, &A0[4 * s], dd + (B_D3 >> 4) + (3 - s) * 16, 1);
      #pragma unroll
      for (int s = 0; s < 4; s++) wg_rs16_tb(a16, &A0[16 + 4 * s], dd + (B_D3 >> 4) + (3 - s) * 16, 1);
      wg_commit();
      #pragma unroll
      for (int b = 0; b < 5; b++) {
        uint32_t* A = (b & 1) ? A0 : A1;
        wg_wait<1>();
        if (b < 4) load_toep<8>(A, tb + (64 + 128 * b) * 4); else load_toep<5>(A, tb + (64 + 128 * b) * 4);
        wg_fence();
        #pragma unroll
        for (int s = 0; s < (b < 4 ? 8 : 5); s++) wg_rs32(aY, &A[4 * s], du + (36 - (8 * b + s)) * 2, (b | s) != 0);
        wg_commit();
        if (b == 1) {
          pin<8>(aC); pin<12>(a24); pin<8>(a16);
          bar_sync(4, 128);
          const float kc = bf_lo(lds16(blk + B_SP));
          const int ln = opaque(lane), gg = ln >> 2, q2 = (ln & 3) * 2;
          const uint32_t f1 = blk + B_D + (128 * w4 + ((8 * gg) ^ (8 * w4)) + q2) * 4;
          const uint32_t f2 = blk + B_D + 6144 + (256 * w4 + ((16 * gg) ^ (16 * (w4 & 1))) + q2) * 4;
          #pragma unroll
          for (int h = 0; h < 2; h++) {
            #pragma unroll
            for (int jp = 0; jp < 3; jp++) {
              float x = a24[4 * jp + 2 * h], y = a24[4 * jp + 2 * h + 1];
              if (jp > 0) { x += a16[4 * (jp - 1) + 2 * h]; y += a16[4 * (jp - 1) + 2 * h + 1]; }
              sts64f(f1 + (64 * h + 512 * jp) * 4, x, y);
            }
            #pragma unroll
            for (int n = 0; n < 2; n++) {
              const int s4 = 256 * w4 + 16 * gg + 128 * h + 8 * n + q2 - 4, s2 = s4 + 2;
              const uint32_t u4 = lds32(blk + (uint32_t)((2 * s4) ^ ((s4 >> 2) & 0x70)));
              const uint32_t u2 = lds32(blk + (uint32_t)((2 * s2) ^ ((s2 >> 2) & 0x70)));
              const float x = fmaf(kc, bf_lo(u4) + bf_hi(u4), aC[4 * n + 2 * h]);
              const float y = fmaf(kc, bf_hi(u4) + bf_lo(u2), aC[4 * n + 2 * h + 1]);
              sts64f(f2 + (128 * h + 8 * (n ^ h)) * 4, x, y);
            }
          }
        }
      }
      wg_wait<0>();
      pin<16>(aY);
      bar_sync(4, 128);
      {
        const int ln = opaque(lane), tt = ln & 3;
        const uint32_t b0 = (128 * tt + ((16 * w4) ^ (8 * tt)) + (ln >> 2)) * 4;
        #pragma unroll
        for (int n = 1; n < 4; n++)
          #pragma unroll
          for (int e = 0; e < 4; e++) {
            const uint32_t a = blk + B_D + (b0 ^ (32 * (e >> 1))) + (512 * (n - 1) + 64 * (e & 1)) * 4;
            aY[4 * n + e] += ldsf(a);
            if (n >= 2) aY[4 * n + e] += ldsf(a + 6144 - 2048);
          }
        const uint32_t ya = blk + (8 * (ln >> 4) + (ln & 7)) * 128 + (((2 * w4 + ((ln >> 3) & 1)) ^ (ln & 7)) << 4);
        #pragma unroll
        for (int n = 0; n < 4; n += 2)
          stsm4t(ya + n * 1024, pack2(aY[4 * n], aY[4 * n + 1]), pack2(aY[4 * n + 2], aY[4 * n + 3]),
                 pack2(aY[4 * n + 4], aY[4 * n + 5]), pack2(aY[4 * n + 6], aY[4 * n + 7]));
      }
      fence_async();
      mbar_arrive(BAR(BR_YSTG + k));
      if (t7 == 0) TS(47 - k);
    }
    }
  }
}

typedef CUresult (*EncFn)(CUtensorMap*, CUtensorMapDataType, cuuint32_t, void*, const cuuint64_t*, const cuuint64_t*, const cuuint32_t*,
                          const cuuint32_t*, CUtensorMapInterleave, CUtensorMapSwizzle, CUtensorMapL2promotion, CUtensorMapFloatOOBfill);
static CUtensorMap mkmap(EncFn enc, const void* base, int rank, const cuuint64_t* dims, const cuuint64_t* strides, const cuuint32_t* box, CUtensorMapSwizzle swz) {
  CUtensorMap m; cuuint32_t es[5] = {1, 1, 1, 1, 1};
  enc(&m, CU_TENSOR_MAP_DATA_TYPE_BFLOAT16, rank, const_cast<void*>(base), dims, strides, box, es, CU_TENSOR_MAP_INTERLEAVE_NONE, swz,
      CU_TENSOR_MAP_L2_PROMOTION_L2_128B, CU_TENSOR_MAP_FLOAT_OOB_FILL_NONE);
  return m;
}

extern "C" void kernel_launch(void* const* d_in, const int* in_sizes, int n_in, void* d_out, int out_size) {
  void* fn = nullptr; cudaDriverEntryPointQueryResult qr;
  cudaGetDriverEntryPoint("cuTensorMapEncodeTiled", &fn, cudaEnableDefault, &qr);
  EncFn enc = (EncFn)fn;
  void* uy = nullptr; cudaGetSymbolAddress(&uy, g_uy);
  const cuuint64_t dx[2] = {640, 2048}, sx[1] = {1280};
  const cuuint32_t bx[2] = {64, 128}, bu[2] = {80, 64};
  const cuuint64_t dw[3] = {640, 640, 3}, sw[2] = {3840, 1280};
  const cuuint32_t bw[3] = {64, 32, 3}, br[3] = {16, 32, 3};
  const cuuint64_t dwo[3] = {16, 640, 40}, swo[2] = {1280, 32};
  const cuuint32_t bwo[3] = {16, 80, 5};
  const cuuint64_t dsa[2] = {2048, 1280}, ssa[1] = {4096};
  const cuuint32_t bsa[2] = {64, 80};
  const cuuint64_t dsb[2] = {64, 40960}, ssb[1] = {128};
  const cuuint32_t bsb[2] = {64, 32};
  const cuuint64_t dout[2] = {1280, 2048}, sout[1] = {2560};
  CUtensorMap mx = mkmap(enc, d_in[7], 2, dx, sx, bx, CU_TENSOR_MAP_SWIZZLE_128B);
  CUtensorMap mw = mkmap(enc, d_in[8], 3, dw, sw, bw, CU_TENSOR_MAP_SWIZZLE_128B);
  CUtensorMap mr = mkmap(enc, d_in[8], 3, dw, sw, br, CU_TENSOR_MAP_SWIZZLE_32B);
  CUtensorMap mwo = mkmap(enc, d_in[9], 3, dwo, swo, bwo, CU_TENSOR_MAP_SWIZZLE_32B);
  CUtensorMap mu = mkmap(enc, d_in[0], 2, dx, sx, bu, CU_TENSOR_MAP_SWIZZLE_NONE);
  CUtensorMap msa = mkmap(enc, uy, 2, dsa, ssa, bsa, CU_TENSOR_MAP_SWIZZLE_128B);
  CUtensorMap msb = mkmap(enc, uy, 2, dsb, ssb, bsb, CU_TENSOR_MAP_SWIZZLE_128B);
  CUtensorMap mout = mkmap(enc, d_out, 2, dout, sout, bu, CU_TENSOR_MAP_SWIZZLE_NONE);
  Params prm;
  prm.logA = (const __nv_bfloat16*)d_in[1]; prm.Aim = (const __nv_bfloat16*)d_in[2];
  prm.Cr = (const __nv_bfloat16*)d_in[3]; prm.Ci = (const __nv_bfloat16*)d_in[4];
  prm.logdt = (const __nv_bfloat16*)d_in[5]; prm.dskip = (const __nv_bfloat16*)d_in[6];
  cudaFuncSetAttribute(fused_kernel, cudaFuncAttributeMaxDynamicSharedMemorySize, SMEM_BYTES);
  cudaLaunchConfig_t cfg = {};
  cfg.gridDim = dim3(128); cfg.blockDim = dim3(512); cfg.dynamicSmemBytes = SMEM_BYTES; cfg.stream = cudaStreamPerThread;
  cudaLaunchAttribute at[1];
  at[0].id = cudaLaunchAttributeClusterDimension; at[0].val.clusterDim.x = 2; at[0].val.clusterDim.y = 1; at[0].val.clusterDim.z = 1;
  cfg.attrs = at; cfg.numAttrs = 1;
  cudaLaunchKernelEx(&cfg, fused_kernel, mx, mw, mr, mwo, mu, msa, msb, mout, prm);
}
```

```cpp
#include <cuda_runtime.h>
#include <cuda_bf16.h>
#include <cuda.h>
#include <stdint.h>

#define EN_ATT 1
#define EN_SSM 1

__device__ __align__(1024) __nv_bfloat16 g_uy[2 * 640 * 2048];
__device__ __align__(128) uint4 g_kvp[8 * 16 * 240];
__device__ __align__(128) uint4 g_o[128 * 1280];
__device__ __align__(128) unsigned g_flag[40 * 32];
__device__ unsigned g_epoch[128];
#define TS(i) do {} while (0)
#define DUMP(lo, hi) do {} while (0)

constexpr uint32_t W_SLOT = 15360, OFF_X = 76800;
constexpr uint32_t OFF_WOM = 20480, OFF_KVS = 71680, OFF_PK = 80896, OFF_V = 101376, OFF_EXTRA = 102400, OFF_KVB = OFF_EXTRA;
constexpr uint32_t OFF_BAR = 125952, OFF_BLK = 128000, BLK = 20480;
constexpr uint32_t B_D = 4096, B_D3 = 3072, B_D9 = 6144, B_D7 = 8192, B_TBL = 14336, B_SP = 18752;
constexpr uint32_t SMEM_BYTES = OFF_BLK + 5 * BLK + 1024;
enum { BR_FULL = 0, BR_EMPTY = 5, BR_WO = 10, BR_PUB = 12, BR_OFULL = 18, BR_OEMPTY = 22, BR_GEMM = 26, BR_OSTG = 27, BR_UIN = 28,
       BR_U = 29, BR_DRDY = 30, BR_KGEN = 35, BR_YSTG = 36, BR_FREE = 41, BR_YIN = 46, BR_EPOCH = 47, BR_COUNT = 48 };
constexpr uint32_t OFF_EPOCH = OFF_BAR + 8 * BR_COUNT;

__device__ __forceinline__ long long clk64() { long long t; asm volatile("mov.u64 %0, %%clock64;" : "=l"(t) :: "memory"); return t; }
__device__ __forceinline__ uint32_t smem_u32(const void* p) { return (uint32_t)__cvta_generic_to_shared(p); }
__device__ __forceinline__ uint64_t mkdesc(uint32_t addr, uint32_t lbo, uint32_t sbo, uint32_t swz) {
  return (uint64_t)((addr & 0x3FFFF) >> 4) | ((uint64_t)(lbo >> 4) << 16) | ((uint64_t)(sbo >> 4) << 32) | ((uint64_t)swz << 62);
}
__device__ __forceinline__ void mbar_init(uint32_t bar, uint32_t cnt) { asm volatile("mbarrier.init.shared::cta.b64 [%0], %1;" :: "r"(bar), "r"(cnt) : "memory"); }
__device__ __forceinline__ void mbar_expect_tx(uint32_t bar, uint32_t bytes) { asm volatile("mbarrier.arrive.expect_tx.shared::cta.b64 _, [%0], %1;" :: "r"(bar), "r"(bytes) : "memory"); }
__device__ __forceinline__ void mbar_arrive(uint32_t bar) { asm volatile("mbarrier.arrive.shared::cta.b64 _, [%0];" :: "r"(bar) : "memory"); }
__device__ __forceinline__ void mbar_wait(uint32_t bar, uint32_t parity) {
  asm volatile("{\n.reg .pred p;\n.reg .u32 c;\nmov.u32 c, 0;\n"
    "WL:\nmbarrier.try_wait.parity.shared::cta.b64 p, [%0], %1;\n@p bra WD;\n"
    "add.u32 c, c, 1;\nsetp.lt.u32 p, c, 200000;\n@p bra WL;\nWD:\n}" :: "r"(bar), "r"(parity) : "memory");
}
__device__ __forceinline__ void poll_all(const unsigned* p, unsigned val) {
  asm volatile("{\n.reg .pred p;\n.reg .u32 c, v;\nmov.u32 c, 0;\n"
    "PL:\nld.relaxed.gpu.global.u32 v, [%0];\nsetp.eq.u32 p, v, %1;\nvote.sync.all.pred p, p, 0xffffffff;\n@p bra PD;\n"
    "add.u32 c, c, 1;\nsetp.lt.u32 p, c, 100000;\n@p bra PL;\nPD:\n}" :: "l"(p), "r"(val) : "memory");
}
__device__ __forceinline__ unsigned poll_bit(const unsigned* p, unsigned val, unsigned mask) {
  unsigned bal;
  asm volatile("{\n.reg .pred p;\n.reg .u32 c, v;\nmov.u32 c, 0;\n"
    "PL:\nld.relaxed.gpu.global.u32 v, [%1];\nsetp.eq.u32 p, v, %2;\nvote.sync.ballot.b32 %0, p, 0xffffffff;\n"
    "and.b32 v, %0, %3;\nsetp.ne.u32 p, v, 0;\n@p bra PD;\n"
    "add.u32 c, c, 1;\nsetp.lt.u32 p, c, 100000;\n@p bra PL;\nPD:\n}" : "=&r"(bal) : "l"(p), "r"(val), "r"(mask) : "memory");
  return bal;
}
__device__ __forceinline__ void fix128_w0(uint32_t* v, const void* p, uint32_t tag, uint32_t mask) {
  asm volatile("{\n.reg .pred p;\n.reg .u32 c, x;\n.reg .b128 t;\n.reg .b64 lo, hi;\nmov.u32 c, 0;\n"
    "FL:\nxor.b32 x, %0, %5;\nand.b32 x, x, %6;\nsetp.eq.u32 p, x, 0;\n@p bra FD;\n"
    "ld.relaxed.gpu.global.b128 t, [%4];\nmov.b128 {lo, hi}, t;\nmov.b64 {%0, %1}, lo;\nmov.b64 {%2, %3}, hi;\n"
    "add.u32 c, c, 1;\nsetp.lt.u32 p, c, 100000;\n@p bra FL;\nFD:\n}"
    : "+r"(v[0]), "+r"(v[1]), "+r"(v[2]), "+r"(v[3]) : "l"(p), "r"(tag), "r"(mask) : "memory");
}
__device__ __forceinline__ void fix128_w3(uint32_t* v, const void* p, uint32_t tag, uint32_t mask) {
  asm volatile("{\n.reg .pred p;\n.reg .u32 c, x;\n.reg .b128 t;\n.reg .b64 lo, hi;\nmov.u32 c, 0;\n"
    "FL:\nxor.b32 x, %3, %5;\nand.b32 x, x, %6;\nsetp.eq.u32 p, x, 0;\n@p bra FD;\n"
    "ld.relaxed.gpu.global.b128 t, [%4];\nmov.b128 {lo, hi}, t;\nmov.b64 {%0, %1}, lo;\nmov.b64 {%2, %3}, hi;\n"
    "add.u32 c, c, 1;\nsetp.lt.u32 p, c, 100000;\n@p bra FL;\nFD:\n}"
    : "+r"(v[0]), "+r"(v[1]), "+r"(v[2]), "+r"(v[3]) : "l"(p), "r"(tag), "r"(mask) : "memory");
}
__device__ __forceinline__ void fence_acq() { asm volatile("fence.acq_rel.gpu;" ::: "memory"); }
__device__ __forceinline__ bool elect_one() {
  uint32_t p; asm volatile("{\n.reg .pred P;\nelect.sync _|P, 0xffffffff;\nselp.u32 %0, 1, 0, P;\n}" : "=r"(p)); return p;
}
__device__ __forceinline__ void bar_sync(int id, int n) { asm volatile("bar.sync %0, %1;" :: "r"(id), "r"(n) : "memory"); }
__device__ __forceinline__ void fence_async() { asm volatile("fence.proxy.async.shared::cta;" ::: "memory"); }
__device__ __forceinline__ void fence_async_g() { asm volatile("fence.proxy.async.global;" ::: "memory"); }
__device__ __forceinline__ void tma2d(uint32_t dst, const CUtensorMap* m, uint32_t bar, int c0, int c1) {
  asm volatile("cp.async.bulk.tensor.2d.shared::cluster.global.mbarrier::complete_tx::bytes [%0], [%1, {%3, %4}], [%2];"
    :: "r"(dst), "l"(m), "r"(bar), "r"(c0), "r"(c1) : "memory");
}
__device__ __forceinline__ void tma3d(uint32_t dst, const CUtensorMap* m, uint32_t bar, int c0, int c1, int c2) {
  asm volatile("cp.async.bulk.tensor.3d.shared::cluster.global.mbarrier::complete_tx::bytes [%0], [%1, {%3, %4, %5}], [%2];"
    :: "r"(dst), "l"(m), "r"(bar), "r"(c0), "r"(c1), "r"(c2) : "memory");
}
__device__ __forceinline__ void tma2d_st(const CUtensorMap* m, uint32_t src, int c0, int c1) {
  asm volatile("cp.async.bulk.tensor.2d.global.shared::cta.bulk_group [%0, {%2, %3}], [%1];"
    :: "l"(m), "r"(src), "r"(c0), "r"(c1) : "memory");
}
__device__ __forceinline__ void bulk_ld(uint32_t dst, const void* src, uint32_t bytes, uint32_t bar) {
  asm volatile("cp.async.bulk.shared::cluster.global.mbarrier::complete_tx::bytes [%0], [%1], %2, [%3];"
    :: "r"(dst), "l"(src), "r"(bytes), "r"(bar) : "memory");
}
__device__ __forceinline__ void bulk_st(void* dst, uint32_t src, uint32_t bytes) {
  asm volatile("cp.async.bulk.global.shared::cta.bulk_group [%0], [%1], %2;" :: "l"(dst), "r"(src), "r"(bytes) : "memory");
}
__device__ __forceinline__ void bulk_commit() { asm volatile("cp.async.bulk.commit_group;" ::: "memory"); }
__device__ __forceinline__ void bulk_wait0() { asm volatile("cp.async.bulk.wait_group 0;" ::: "memory"); }
__device__ __forceinline__ void bulk_wait0_read() { asm volatile("cp.async.bulk.wait_group.read 0;" ::: "memory"); }
__device__ __forceinline__ unsigned ld_rlx(const unsigned* p) { unsigned v; asm volatile("ld.relaxed.gpu.global.u32 %0, [%1];" : "=r"(v) : "l"(p) : "memory"); return v; }
__device__ __forceinline__ unsigned ld_acq(const unsigned* p) { unsigned v; asm volatile("ld.acquire.gpu.global.u32 %0, [%1];" : "=r"(v) : "l"(p) : "memory"); return v; }
__device__ __forceinline__ void st_rlx(unsigned* p, unsigned v) { asm volatile("st.relaxed.gpu.global.u32 [%0], %1;" :: "l"(p), "r"(v) : "memory"); }
__device__ __forceinline__ void st_rel(unsigned* p, unsigned v) { asm volatile("st.release.gpu.global.u32 [%0], %1;" :: "l"(p), "r"(v) : "memory"); }
__device__ __forceinline__ void ld128_rlx(uint32_t* v, const void* p) {
  asm volatile("{\n.reg .b128 t;\n.reg .b64 lo, hi;\nld.relaxed.gpu.global.b128 t, [%4];\nmov.b128 {lo, hi}, t;\n"
    "mov.b64 {%0, %1}, lo;\nmov.b64 {%2, %3}, hi;\n}" : "=r"(v[0]), "=r"(v[1]), "=r"(v[2]), "=r"(v[3]) : "l"(p) : "memory");
}
__device__ __forceinline__ void st128_rlx(void* p, const uint32_t* v) {
  asm volatile("{\n.reg .b128 t;\n.reg .b64 lo, hi;\nmov.b64 lo, {%1, %2};\nmov.b64 hi, {%3, %4};\nmov.b128 t, {lo, hi};\n"
    "st.relaxed.gpu.global.b128 [%0], t;\n}" :: "l"(p), "r"(v[0]), "r"(v[1]), "r"(v[2]), "r"(v[3]) : "memory");
}
__device__ __forceinline__ uint32_t lds32(uint32_t a) { uint32_t v; asm volatile("ld.shared.u32 %0, [%1];" : "=r"(v) : "r"(a) : "memory"); return v; }
__device__ __forceinline__ uint32_t lds16(uint32_t a) { uint16_t v; asm volatile("ld.shared.u16 %0, [%1];" : "=h"(v) : "r"(a) : "memory"); return v; }
__device__ __forceinline__ float ldsf(uint32_t a) { float v; asm volatile("ld.shared.f32 %0, [%1];" : "=f"(v) : "r"(a) : "memory"); return v; }
__device__ __forceinline__ void lds128(uint32_t* v, uint32_t a) { asm volatile("ld.shared.v4.u32 {%0,%1,%2,%3}, [%4];" : "=r"(v[0]), "=r"(v[1]), "=r"(v[2]), "=r"(v[3]) : "r"(a) : "memory"); }
__device__ __forceinline__ void sts32(uint32_t a, uint32_t v) { asm volatile("st.shared.u32 [%0], %1;" :: "r"(a), "r"(v) : "memory"); }
__device__ __forceinline__ void sts16(uint32_t a, uint32_t v) { asm volatile("st.shared.u16 [%0], %1;" :: "r"(a), "h"((uint16_t)v) : "memory"); }
__device__ __forceinline__ void sts64f(uint32_t a, float x, float y) { asm volatile("st.shared.v2.f32 [%0], {%1,%2};" :: "r"(a), "f"(x), "f"(y) : "memory"); }
__device__ __forceinline__ void sts128(uint32_t a, uint32_t x, uint32_t y, uint32_t z, uint32_t w) { asm volatile("st.shared.v4.u32 [%0], {%1,%2,%3,%4};" :: "r"(a), "r"(x), "r"(y), "r"(z), "r"(w) : "memory"); }
__device__ __forceinline__ void stsm4(uint32_t a, uint32_t r0, uint32_t r1, uint32_t r2, uint32_t r3) {
  asm volatile("stmatrix.sync.aligned.m8n8.x4.shared.b16 [%0], {%1,%2,%3,%4};" :: "r"(a), "r"(r0), "r"(r1), "r"(r2), "r"(r3) : "memory");
}
__device__ __forceinline__ void stsm4t(uint32_t a, uint32_t r0, uint32_t r1, uint32_t r2, uint32_t r3) {
  asm volatile("stmatrix.sync.aligned.m8n8.x4.trans.shared.b16 [%0], {%1,%2,%3,%4};" :: "r"(a), "r"(r0), "r"(r1), "r"(r2), "r"(r3) : "memory");
}
__device__ __forceinline__ void ldsm4t(uint32_t* r, uint32_t a) {
  asm volatile("ldmatrix.sync.aligned.m8n8.x4.trans.shared.b16 {%0,%1,%2,%3}, [%4];" : "=r"(r[0]), "=r"(r[1]), "=r"(r[2]), "=r"(r[3]) : "r"(a) : "memory");
}
__device__ __forceinline__ uint32_t pack2(float lo, float hi) { uint32_t r; asm("cvt.rn.bf16x2.f32 %0, %1, %2;" : "=r"(r) : "f"(hi), "f"(lo)); return r; }
__device__ __forceinline__ float bf_lo(uint32_t v) { return __uint_as_float(v << 16); }
__device__ __forceinline__ float bf_hi(uint32_t v) { return __uint_as_float(v & 0xffff0000u); }
__device__ __forceinline__ float bf_round(float x) { return bf_lo(pack2(x, 0.f)); }
__device__ __forceinline__ float ex2(float x) { float r; asm("ex2.approx.ftz.f32 %0, %1;" : "=f"(r) : "f"(x)); return r; }
__device__ __forceinline__ float phi(float t, float l2e = 1.44269504089f) { float e = ex2(t * l2e); return (t > 0.f ? t + 1.f : e) + 1e-6f; }
__device__ __forceinline__ void wg_fence() { asm volatile("wgmma.fence.sync.aligned;" ::: "memory"); }
__device__ __forceinline__ void wg_commit() { asm volatile("wgmma.commit_group.sync.aligned;" ::: "memory"); }
template <int N> __device__ __forceinline__ void wg_wait() { asm volatile("wgmma.wait_group.sync.aligned %0;" :: "n"(N) : "memory"); }
template <int N> __device__ __forceinline__ void pin(float* a) {
  #pragma unroll
  for (int i = 0; i < N; i++) asm volatile("" : "+f"(a[i]) :: "memory");
}
__device__ __forceinline__ int opaque(int v) { asm volatile("" : "+r"(v)); return v; }
template <int N> __device__ __forceinline__ void zero(float* a) {
  #pragma unroll
  for (int i = 0; i < N; i++) asm volatile("mov.b32 %0, 0;" : "=f"(a[i]));
}
template <int N> __device__ __forceinline__ void pinu(uint32_t* a) {
  #pragma unroll
  for (int i = 0; i < N; i++) asm volatile("" : "+r"(a[i]) :: "memory");
}
__device__ __forceinline__ void cexp_t(float lg2mag, float turns, float& re, float& im) {
  float m = ex2(lg2mag);
  float fr = (turns - __fadd_rn(__fadd_rn(turns, 12582912.f), -12582912.f)) * 6.283185307f;
  re = m * __cosf(fr); im = m * __sinf(fr);
}
__device__ __forceinline__ void cmul(float ar, float ai, float br, float bi, float& cr, float& ci) {
  cr = fmaf(ar, br, -ai * bi); ci = fmaf(ar, bi, ai * br);
}

__device__ __forceinline__ void wg_ss192_tb(float* d, uint64_t da, uint64_t db, int scale_d) {
  asm volatile("{\n.reg .pred p;\nsetp.ne.b32 p, %98, 0;\n"
    "wgmma.mma_async.sync.aligned.m64n192k16.f32.bf16.bf16 "
    "{%0, %1, %2, %3, %4, %5, %6, %7, %8, %9, %10, %11, %12, %13, %14, %15, %16, %17, %18, %19, %20, %21, %22, %23, %24, %25, %26, %27, %28, %29, %30, %31, %32, %33, %34, %35, %36, %37, %38, %39, %40, %41, %42, %43, %44, %45, %46, %47, %48, %49, %50, %51, %52, %53, %54, %55, %56, %57, %58, %59, %60, %61, %62, %63, %64, %65, %66, %67, %68, %69, %70, %71, %72, %73, %74, %75, %76, %77, %78, %79, %80, %81, %82, %83, %84, %85, %86, %87, %88, %89, %90, %91, %92, %93, %94, %95}, %96, %97, p, 1, 1, 0, 1;\n}\n"
    : "+f"(d[0]), "+f"(d[1]), "+f"(d[2]), "+f"(d[3]), "+f"(d[4]), "+f"(d[5]), "+f"(d[6]), "+f"(d[7]), "+f"(d[8]), "+f"(d[9]), "+f"(d[10]), "+f"(d[11]), "+f"(d[12]), "+f"(d[13]), "+f"(d[14]), "+f"(d[15]), "+f"(d[16]), "+f"(d[17]), "+f"(d[18]), "+f"(d[19]), "+f"(d[20]), "+f"(d[21]), "+f"(d[22]), "+f"(d[23]), "+f"(d[24]), "+f"(d[25]), "+f"(d[26]), "+f"(d[27]), "+f"(d[28]), "+f"(d[29]), "+f"(d[30]), "+f"(d[31]), "+f"(d[32]), "+f"(d[33]), "+f"(d[34]), "+f"(d[35]), "+f"(d[36]), "+f"(d[37]), "+f"(d[38]), "+f"(d[39]), "+f"(d[40]), "+f"(d[41]), "+f"(d[42]), "+f"(d[43]), "+f"(d[44]), "+f"(d[45]), "+f"(d[46]), "+f"(d[47]), "+f"(d[48]), "+f"(d[49]), "+f"(d[50]), "+f"(d[51]), "+f"(d[52]), "+f"(d[53]), "+f"(d[54]), "+f"(d[55]), "+f"(d[56]), "+f"(d[57]), "+f"(d[58]), "+f"(d[59]), "+f"(d[60]), "+f"(d[61]), "+f"(d[62]), "+f"(d[63]), "+f"(d[64]), "+f"(d[65]), "+f"(d[66]), "+f"(d[67]), "+f"(d[68]), "+f"(d[69]), "+f"(d[70]), "+f"(d[71]), "+f"(d[72]), "+f"(d[73]), "+f"(d[74]), "+f"(d[75]), "+f"(d[76]), "+f"(d[77]), "+f"(d[78]), "+f"(d[79]), "+f"(d[80]), "+f"(d[81]), "+f"(d[82]), "+f"(d[83]), "+f"(d[84]), "+f"(d[85]), "+f"(d[86]), "+f"(d[87]), "+f"(d[88]), "+f"(d[89]), "+f"(d[90]), "+f"(d[91]), "+f"(d[92]), "+f"(d[93]), "+f"(d[94]), "+f"(d[95])
    : "l"(da), "l"(db), "r"(scale_d));
}
__device__ __forceinline__ void wg_ss48_tb(float* d, uint64_t da, uint64_t db, int scale_d) {
  asm volatile("{\n.reg .pred p;\nsetp.ne.b32 p, %26, 0;\n"
    "wgmma.mma_async.sync.aligned.m64n48k16.f32.bf16.bf16 "
    "{%0, %1, %2, %3, %4, %5, %6, %7, %8, %9, %10, %11, %12, %13, %14, %15, %16, %17, %18, %19, %20, %21, %22, %23}, %24, %25, p, 1, 1, 0, 1;\n}\n"
    : "+f"(d[0]), "+f"(d[1]), "+f"(d[2]), "+f"(d[3]), "+f"(d[4]), "+f"(d[5]), "+f"(d[6]), "+f"(d[7]), "+f"(d[8]), "+f"(d[9]), "+f"(d[10]), "+f"(d[11]), "+f"(d[12]), "+f"(d[13]), "+f"(d[14]), "+f"(d[15]), "+f"(d[16]), "+f"(d[17]), "+f"(d[18]), "+f"(d[19]), "+f"(d[20]), "+f"(d[21]), "+f"(d[22]), "+f"(d[23])
    : "l"(da), "l"(db), "r"(scale_d));
}
__device__ __forceinline__ void wg_ss48_tt(float* d, uint64_t da, uint64_t db, int scale_d) {
  asm volatile("{\n.reg .pred p;\nsetp.ne.b32 p, %26, 0;\n"
    "wgmma.mma_async.sync.aligned.m64n48k16.f32.bf16.bf16 "
    "{%0, %1, %2, %3, %4, %5, %6, %7, %8, %9, %10, %11, %12, %13, %14, %15, %16, %17, %18, %19, %20, %21, %22, %23}, %24, %25, p, 1, 1, 1, 1;\n}\n"
    : "+f"(d[0]), "+f"(d[1]), "+f"(d[2]), "+f"(d[3]), "+f"(d[4]), "+f"(d[5]), "+f"(d[6]), "+f"(d[7]), "+f"(d[8]), "+f"(d[9]), "+f"(d[10]), "+f"(d[11]), "+f"(d[12]), "+f"(d[13]), "+f"(d[14]), "+f"(d[15]), "+f"(d[16]), "+f"(d[17]), "+f"(d[18]), "+f"(d[19]), "+f"(d[20]), "+f"(d[21]), "+f"(d[22]), "+f"(d[23])
    : "l"(da), "l"(db), "r"(scale_d));
}
__device__ __forceinline__ void wg_rs88_tb(float* d, const uint32_t* a, uint64_t db, int scale_d) {
  asm volatile("{\n.reg .pred p;\nsetp.ne.b32 p, %49, 0;\n"
    "wgmma.mma_async.sync.aligned.m64n88k16.f32.bf16.bf16 "
    "{%0, %1, %2, %3, %4, %5, %6, %7, %8, %9, %10, %11, %12, %13, %14, %15, %16, %17, %18, %19, %20, %21, %22, %23, %24, %25, %26, %27, %28, %29, %30, %31, %32, %33, %34, %35, %36, %37, %38, %39, %40, %41, %42, %43}, {%44, %45, %46, %47}, %48, p, 1, 1, 1;\n}\n"
    : "+f"(d[0]), "+f"(d[1]), "+f"(d[2]), "+f"(d[3]), "+f"(d[4]), "+f"(d[5]), "+f"(d[6]), "+f"(d[7]), "+f"(d[8]), "+f"(d[9]), "+f"(d[10]), "+f"(d[11]), "+f"(d[12]), "+f"(d[13]), "+f"(d[14]), "+f"(d[15]), "+f"(d[16]), "+f"(d[17]), "+f"(d[18]), "+f"(d[19]), "+f"(d[20]), "+f"(d[21]), "+f"(d[22]), "+f"(d[23]), "+f"(d[24]), "+f"(d[25]), "+f"(d[26]), "+f"(d[27]), "+f"(d[28]), "+f"(d[29]), "+f"(d[30]), "+f"(d[31]), "+f"(d[32]), "+f"(d[33]), "+f"(d[34]), "+f"(d[35]), "+f"(d[36]), "+f"(d[37]), "+f"(d[38]), "+f"(d[39]), "+f"(d[40]), "+f"(d[41]), "+f"(d[42]), "+f"(d[43])
    : "r"(a[0]), "r"(a[1]), "r"(a[2]), "r"(a[3]), "l"(db), "r"(scale_d));
}
__device__ __forceinline__ void wg_rs64_tb(float* d, const uint32_t* a, uint64_t db, int scale_d) {
  asm volatile("{\n.reg .pred p;\nsetp.ne.b32 p, %37, 0;\n"
    "wgmma.mma_async.sync.aligned.m64n64k16.f32.bf16.bf16 "
    "{%0, %1, %2, %3, %4, %5, %6, %7, %8, %9, %10, %11, %12, %13, %14, %15, %16, %17, %18, %19, %20, %21, %22, %23, %24, %25, %26, %27, %28, %29, %30, %31}, {%32, %33, %34, %35}, %36, p, 1, 1, 1;\n}\n"
    : "+f"(d[0]), "+f"(d[1]), "+f"(d[2]), "+f"(d[3]), "+f"(d[4]), "+f"(d[5]), "+f"(d[6]), "+f"(d[7]), "+f"(d[8]), "+f"(d[9]), "+f"(d[10]), "+f"(d[11]), "+f"(d[12]), "+f"(d[13]), "+f"(d[14]), "+f"(d[15]), "+f"(d[16]), "+f"(d[17]), "+f"(d[18]), "+f"(d[19]), "+f"(d[20]), "+f"(d[21]), "+f"(d[22]), "+f"(d[23]), "+f"(d[24]), "+f"(d[25]), "+f"(d[26]), "+f"(d[27]), "+f"(d[28]), "+f"(d[29]), "+f"(d[30]), "+f"(d[31])
    : "r"(a[0]), "r"(a[1]), "r"(a[2]), "r"(a[3]), "l"(db), "r"(scale_d));
}
__device__ __forceinline__ void wg_rs16(float* d, const uint32_t* a, uint64_t db, int scale_d) {
  asm volatile("{\n.reg .pred p;\nsetp.ne.b32 p, %13, 0;\n"
    "wgmma.mma_async.sync.aligned.m64n16k16.f32.bf16.bf16 "
    "{%0, %1, %2, %3, %4, %5, %6, %7}, {%8, %9, %10, %11}, %12, p, 1, 1, 0;\n}\n"
    : "+f"(d[0]), "+f"(d[1]), "+f"(d[2]), "+f"(d[3]), "+f"(d[4]), "+f"(d[5]), "+f"(d[6]), "+f"(d[7])
    : "r"(a[0]), "r"(a[1]), "r"(a[2]), "r"(a[3]), "l"(db), "r"(scale_d));
}
__device__ __forceinline__ void wg_rs32(float* d, const uint32_t* a, uint64_t db, int scale_d) {
  asm volatile("{\n.reg .pred p;\nsetp.ne.b32 p, %21, 0;\n"
    "wgmma.mma_async.sync.aligned.m64n32k16.f32.bf16.bf16 "
    "{%0, %1, %2, %3, %4, %5, %6, %7, %8, %9, %10, %11, %12, %13, %14, %15}, {%16, %17, %18, %19}, %20, p, 1, 1, 0;\n}\n"
    : "+f"(d[0]), "+f"(d[1]), "+f"(d[2]), "+f"(d[3]), "+f"(d[4]), "+f"(d[5]), "+f"(d[6]), "+f"(d[7]), "+f"(d[8]), "+f"(d[9]), "+f"(d[10]), "+f"(d[11]), "+f"(d[12]), "+f"(d[13]), "+f"(d[14]), "+f"(d[15])
    : "r"(a[0]), "r"(a[1]), "r"(a[2]), "r"(a[3]), "l"(db), "r"(scale_d));
}
__device__ __forceinline__ void wg_rs24_tb(float* d, const uint32_t* a, uint64_t db, int scale_d) {
  asm volatile("{\n.reg .pred p;\nsetp.ne.b32 p, %17, 0;\n"
    "wgmma.mma_async.sync.aligned.m64n24k16.f32.bf16.bf16 "
    "{%0, %1, %2, %3, %4, %5, %6, %7, %8, %9, %10, %11}, {%12, %13, %14, %15}, %16, p, 1, 1, 1;\n}\n"
    : "+f"(d[0]), "+f"(d[1]), "+f"(d[2]), "+f"(d[3]), "+f"(d[4]), "+f"(d[5]), "+f"(d[6]), "+f"(d[7]), "+f"(d[8]), "+f"(d[9]), "+f"(d[10]), "+f"(d[11])
    : "r"(a[0]), "r"(a[1]), "r"(a[2]), "r"(a[3]), "l"(db), "r"(scale_d));
}
__device__ __forceinline__ void wg_rs16_tb(float* d, const uint32_t* a, uint64_t db, int scale_d) {
  asm volatile("{\n.reg .pred p;\nsetp.ne.b32 p, %13, 0;\n"
    "wgmma.mma_async.sync.aligned.m64n16k16.f32.bf16.bf16 "
    "{%0, %1, %2, %3, %4, %5, %6, %7}, {%8, %9, %10, %11}, %12, p, 1, 1, 1;\n}\n"
    : "+f"(d[0]), "+f"(d[1]), "+f"(d[2]), "+f"(d[3]), "+f"(d[4]), "+f"(d[5]), "+f"(d[6]), "+f"(d[7])
    : "r"(a[0]), "r"(a[1]), "r"(a[2]), "r"(a[3]), "l"(db), "r"(scale_d));
}

struct Params {
  const __nv_bfloat16 *logA, *Aim, *Cr, *Ci, *logdt, *dskip;
};

template <bool FWD>
__device__ __forceinline__ void tile_transpose(uint32_t tc0, uint32_t tc1, uint32_t ct0, uint32_t ct1, int hw, int lane) {
  const int mi = lane >> 3, row = lane & 7;
  for (int gi = hw; gi < 40; gi += 3) {
    const int hh = gi / 20, rem = gi - hh * 20, q = rem / 10, cb = rem - q * 10;
    const uint32_t a_tc = (hh ? tc1 : tc0) + (8 * (4 * q + mi) + row) * 160 + cb * 16;
    const uint32_t a_ct = (hh ? ct1 : ct0) + (8 * cb + row) * 128 + (((4 * q + mi) ^ row) << 4);
    uint32_t r[4];
    ldsm4t(r, FWD ? a_tc : a_ct);
    stsm4(FWD ? a_ct : a_tc, r[0], r[1], r[2], r[3]);
  }
}

template <int NS>
__device__ __forceinline__ void load_toep(uint32_t* A, uint32_t addr) {
  uint32_t prev = lds32(addr - 32);
  #pragma unroll
  for (int s = 0; s < NS; s++) {
    uint32_t x = lds32(addr + 64 * s), y = lds32(addr + 64 * s + 32);
    A[4 * s] = x; A[4 * s + 1] = y; A[4 * s + 2] = prev; A[4 * s + 3] = x;
    prev = y;
  }
}

__global__ void __launch_bounds__(512, 1)
fused_kernel(const __grid_constant__ CUtensorMap mx, const __grid_constant__ CUtensorMap mw, const __grid_constant__ CUtensorMap mr,
             const __grid_constant__ CUtensorMap mwo, const __grid_constant__ CUtensorMap mwr, const __grid_constant__ CUtensorMap mo64,
             const __grid_constant__ CUtensorMap mo16, const __grid_constant__ CUtensorMap mu, const __grid_constant__ CUtensorMap msa,
             const __grid_constant__ CUtensorMap msb, const __grid_constant__ CUtensorMap mout, const Params prm) {
  extern __shared__ unsigned char smem_raw[];
  const uint32_t sb = (smem_u32(smem_raw) + 1023) & ~1023u;
  const int tid = threadIdx.x, lane = tid & 31;
  const int wg = __shfl_sync(0xffffffff, tid >> 7, 0), warp = __shfl_sync(0xffffffff, tid >> 5, 0);
  const int cta = blockIdx.x, r = cta >> 3, c = cta & 7;
  const uint32_t bars = sb + OFF_BAR;
#define BAR(i) (bars + 8 * (i))

  auto issue1 = [&](int kb) {
    const uint32_t st = sb + (kb % 5) * W_SLOT, fb = BAR(BR_FULL + kb % 5);
    mbar_expect_tx(fb, (kb & 1) ? W_SLOT : W_SLOT + 16384);
    if (!(kb & 1)) tma2d(sb + OFF_X + ((kb >> 1) % 3) * 16384, &mx, fb, kb * 32, r * 128);
    tma3d(st, &mw, fb, c * 80, kb * 32, 0);
    tma3d(st + 12288, &mr, fb, c * 80 + 64, kb * 32, 0);
  };

  if (warp == 12) {
    if (elect_one()) {
      #pragma unroll
      for (int i = 0; i < BR_COUNT; i++) {
        int cnt = 1;
        if (i >= BR_EMPTY && i < BR_EMPTY + 5) cnt = 2;
        if (i >= BR_OEMPTY && i < BR_OEMPTY + 4) cnt = 8;
        if (i == BR_OSTG) cnt = 256;
        if (i >= BR_DRDY && i < BR_DRDY + 5) cnt = 96;
        if (i >= BR_YSTG && i < BR_YSTG + 5) cnt = 128;
        mbar_init(BAR(i), cnt);
      }
      asm volatile("fence.mbarrier_init.release.cluster;" ::: "memory");
      if (EN_ATT) issue1(0);
    }
  }
  __syncthreads();

  if (wg == 3) {
    asm volatile("setmaxnreg.dec.sync.aligned.u32 56;");
    if (warp == 12) {
      if (EN_ATT) {
      #pragma unroll
      for (int kb = 1; kb < 20; kb++) {
        if (kb >= 5) mbar_wait(BAR(BR_EMPTY + kb % 5), ((kb / 5) & 1) ^ 1);
        if (elect_one()) issue1(kb);
      }
      auto chunk_of = [&](int i) { return i == 0 ? c : (i == 7 ? (c ^ 1) : (((c & 6) + 1 + i) & 7)); };
      mbar_wait(BAR(BR_EPOCH), 0);
      const unsigned epoch = lds32(sb + OFF_EPOCH);
      const unsigned* fo = &g_flag[(24 + r) * 32 + (lane & 7)];
      unsigned seen = __ballot_sync(0xffffffff, ld_rlx(fo) == epoch);
      mbar_wait(BAR(BR_GEMM), 0);
      if (elect_one()) {
        mbar_expect_tx(BAR(BR_WO), 20480 + 5 * 10240);
        #pragma unroll
        for (int i = 0; i < 5; i++) tma2d(sb + OFF_WOM + i * 10240, &mwo, BAR(BR_WO), c * 64, i * 80);
        #pragma unroll
        for (int i = 0; i < 4; i++) tma2d(sb + i * 5120, &mwr, BAR(BR_WO), 512 + c * 16, i * 160);
      }
      mbar_wait(BAR(BR_PUB), 0);
      if (elect_one()) {
        mbar_expect_tx(BAR(BR_WO + 1), 3 * 10240);
        #pragma unroll
        for (int i = 5; i < 8; i++) tma2d(sb + OFF_WOM + i * 10240, &mwo, BAR(BR_WO + 1), c * 64, i * 80);
      }
      mbar_wait(BAR(BR_OSTG), 0);
      if (elect_one()) {
        bulk_st(&g_o[cta * 1280], sb + OFF_EXTRA, 20480);
        bulk_commit();
        bulk_wait0();
        st_rlx(&g_flag[(24 + r) * 32 + c], epoch);
        TS(20);
      }
      __syncwarp();
      #pragma unroll
      for (int i = 0; i < 7; i++) {
        const int src = chunk_of(i + 1);
        if (!((seen >> src) & 1)) seen = poll_bit(fo, epoch, 1u << src);
        if (i < 3) { if (EN_SSM) mbar_wait(BAR(BR_FREE + 4 - i), 0); }
        else if (i > 3) mbar_wait(BAR(BR_OEMPTY + i - 4), 0);
        if (elect_one()) {
          fence_async_g();
          const uint32_t slot = (i & 3) == 3 ? sb + OFF_EXTRA : sb + OFF_BLK + (4 - (i & 3)) * BLK;
          mbar_expect_tx(BAR(BR_OFULL + (i & 3)), 20480);
          bulk_ld(slot, &g_o[(r * 8 + src) * 1280], 20480, BAR(BR_OFULL + (i & 3)));
          if (i == 0) TS(21);
          if (i == 6) { TS(22); DUMP(20, 30); }
        }
        __syncwarp();
      }
      }
    } else {
      const int hw = warp - 13, ht = tid - 416;
      unsigned epoch = 0;
      if (hw == 0) {
        if (lane == 0) {
          if (EN_SSM) {
            mbar_expect_tx(BAR(BR_UIN), 20480);
            tma2d(sb + OFF_BLK + 4 * BLK + B_D, &mu, BAR(BR_UIN), c * 80, r * 128);
            tma2d(sb + OFF_BLK + 3 * BLK + B_D, &mu, BAR(BR_UIN), c * 80, r * 128 + 64);
          }
          epoch = ld_rlx(&g_epoch[cta]) + 1;
          st_rlx(&g_epoch[cta], epoch);
          sts32(sb + OFF_EPOCH, epoch);
          mbar_arrive(BAR(BR_EPOCH));
        }
        epoch = __shfl_sync(0xffffffff, epoch, 0);
      }
      if (EN_SSM) {
      mbar_wait(BAR(BR_UIN), 0);
      tile_transpose<true>(sb + OFF_BLK + 4 * BLK + B_D, sb + OFF_BLK + 3 * BLK + B_D, sb + OFF_BLK + 2 * BLK + B_D, sb + OFF_BLK + 1 * BLK + B_D, hw, lane);
      fence_async();
      bar_sync(5, 96);
      if (hw == 0) {
        if (lane == 0) {
          tma2d_st(&msa, sb + OFF_BLK + 2 * BLK + B_D, r * 128, c * 80);
          tma2d_st(&msa, sb + OFF_BLK + 1 * BLK + B_D, r * 128 + 64, c * 80);
          bulk_commit(); bulk_wait0();
          st_rel(&g_flag[(8 + c) * 32 + r], epoch);
          TS(30);
        }
        __syncwarp();
        poll_all(&g_flag[(8 + c) * 32 + (lane & 15)], epoch);
        fence_acq(); __syncwarp();
        if (lane == 0) {
          fence_async_g();
          mbar_expect_tx(BAR(BR_U), 20480);
          #pragma unroll
          for (int k = 4; k >= 0; k--) tma2d(sb + OFF_BLK + k * BLK, &msb, BAR(BR_U), 0, (c * 80 + r * 5 + k) * 32);
          TS(31);
        }
        __syncwarp();
      }
      mbar_wait(BAR(BR_U), 0);
      #pragma unroll 1
      for (int k = 4; k >= 0; k--) {
        if (k == 0) mbar_wait(BAR(BR_KGEN), 0);
        const uint32_t blk = sb + OFF_BLK + k * BLK;
        #pragma unroll 1
        for (int kap = ht; kap < 192; kap += 96) {
          float P[33];
          P[0] = 0.f;
          #pragma unroll
          for (int q = 0; q < 4; q++) {
            const int ch = kap - 3 + q;
            uint32_t v[4];
            lds128(v, blk + (uint32_t)((ch >> 3) * 128 + (((ch & 7) ^ ((ch >> 3) & 7)) << 4)));
            #pragma unroll
            for (int e = 0; e < 4; e++) {
              P[q * 8 + 2 * e + 1] = P[q * 8 + 2 * e] + bf_lo(v[e]);
              P[q * 8 + 2 * e + 2] = P[q * 8 + 2 * e + 1] + bf_hi(v[e]);
            }
          }
#define WIN(lo, hi, e) (P[25 + (e) - (lo)] - P[24 + (e) - (hi)])
#define WIN8(lo, hi) pack2(WIN(lo, hi, 0), WIN(lo, hi, 1)), pack2(WIN(lo, hi, 2), WIN(lo, hi, 3)), pack2(WIN(lo, hi, 4), WIN(lo, hi, 5)), pack2(WIN(lo, hi, 6), WIN(lo, hi, 7))
          sts128(blk + B_D + kap * 16, WIN8(6, 10));
          sts128(blk + B_D + B_D3 + kap * 16, WIN8(3, 5));
          if (kap < 128) {
            const uint32_t o = (kap & 1) * 1024 + (kap >> 1) * 16;
            sts128(blk + B_D + B_D9 + o, WIN8(12, 20));
            sts128(blk + B_D + B_D7 + o, WIN8(5, 11));
          }
        }
        fence_async();
        mbar_arrive(BAR(BR_DRDY + k));
      }
      if (ht == 0) TS(32);
      if (hw == 0) {
        #pragma unroll 1
        for (int k = 4; k >= 0; k--) {
          mbar_wait(BAR(BR_YSTG + k), 0);
          if (lane == 0) {
            tma2d_st(&msb, sb + OFF_BLK + k * BLK, 0, (640 + c * 80 + r * 5 + k) * 32);
            bulk_commit(); bulk_wait0_read();
            mbar_arrive(BAR(BR_FREE + k));
          }
          __syncwarp();
        }
        if (lane == 0) { bulk_wait0(); st_rel(&g_flag[(16 + c) * 32 + r], epoch); TS(33); }
        __syncwarp();
        poll_all(&g_flag[(16 + c) * 32 + (lane & 15)], epoch);
        (void)ld_acq(&g_flag[(16 + c) * 32 + (lane & 15)]); __syncwarp();
        if (lane == 0) {
          fence_async_g();
          mbar_expect_tx(BAR(BR_YIN), 20480);
          tma2d(sb + OFF_BLK + BLK, &msa, BAR(BR_YIN), r * 128, 640 + c * 80);
          tma2d(sb + OFF_BLK + BLK + 10240, &msa, BAR(BR_YIN), r * 128 + 64, 640 + c * 80);
          TS(34);
        }
        __syncwarp();
      }
      mbar_wait(BAR(BR_YIN), 0);
      tile_transpose<false>(sb + OFF_BLK, sb + OFF_BLK + 10240, sb + OFF_BLK + BLK, sb + OFF_BLK + BLK + 10240, hw, lane);
      fence_async();
      bar_sync(5, 96);
      if (ht == 0) {
        tma2d_st(&mout, sb + OFF_BLK, c * 80, r * 128);
        tma2d_st(&mout, sb + OFF_BLK + 10240, c * 80, r * 128 + 64);
        bulk_commit(); bulk_wait0_read();
        TS(35); DUMP(30, 40); DUMP(0, 1);
      }
      }
    }
  } else if (wg < 2) {
    asm volatile("setmaxnreg.inc.sync.aligned.u32 152;");
    if (EN_ATT) {
    const int w4 = warp & 3, g = lane >> 2, tq = lane & 3, t7 = tid & 127;
    float am[96], ar[24];
    {
      const uint64_t da0 = mkdesc(sb + OFF_X + wg * 8192, 16, 1024, 1);
      const uint64_t db0 = mkdesc(sb, 4096, 1024, 1);
      const uint64_t dr0 = mkdesc(sb + 12288, 1024, 256, 3);
      uint32_t s = 0, ph = 0, xo = 0;
      #pragma unroll 1
      for (int kb = 0; kb < 20; kb++) {
        mbar_wait(BAR(BR_FULL) + 8 * s, ph);
        if (kb == 0 && tid == 0) TS(1);
        wg_fence();
        const uint32_t wo_ = s * (W_SLOT >> 4);
        wg_ss192_tb(am, da0 + xo, db0 + wo_, kb != 0);
        wg_ss48_tb(ar, da0 + xo, dr0 + wo_, kb != 0);
        wg_ss192_tb(am, da0 + xo + 2, db0 + wo_ + 128, 1);
        wg_ss48_tb(ar, da0 + xo + 2, dr0 + wo_ + 32, 1);
        wg_commit();
        wg_wait<1>();
        if (t7 == 0 && kb > 0 && kb < 16) mbar_arrive(BAR(BR_EMPTY) + 8 * (s == 0 ? 4 : s - 1));
        if (++s == 5) { s = 0; ph ^= 1; }
        xo += (kb & 1) ? 1020 : 4;
        if (xo == 3072) xo = 0;
      }
      wg_wait<0>();
      pin<96>(am); pin<24>(ar);
    }
    if (tid == 0) TS(2);
#define QV(j, e) ((j) < 8 ? am[4 * (j) + (e)] : ar[4 * ((j) - 8) + (e)])
#define KV_(j, e) ((j) < 8 ? am[32 + 4 * (j) + (e)] : ar[8 + 4 * ((j) - 8) + (e)])
#define VV(j, e) ((j) < 8 ? am[64 + 4 * (j) + (e)] : ar[16 + 4 * ((j) - 8) + (e)])
    {
      bar_sync(1, 256);
      if (tid == 0) mbar_arrive(BAR(BR_GEMM));
      const uint32_t ro = (uint32_t)((lane >> 4) * 2048 + (wg * 64 + w4 * 16 + (lane & 15)) * 16);
      const uint32_t ones = (tq == 0) ? 0x00003f80u : 0u;
#define PV(j) pack2(VV(j, 0), VV(j, 1)), pack2(VV(j, 2), VV(j, 3))
#define PK(j) pack2(phi(KV_(j, 0)), phi(KV_(j, 1))), pack2(phi(KV_(j, 2)), phi(KV_(j, 3)))
      stsm4(sb + OFF_V + 0 * 2048 + ro, PV(0), PV(1));
      stsm4(sb + OFF_V + 2 * 2048 + ro, PV(2), PV(3));
      stsm4(sb + OFF_V + 4 * 2048 + ro, PV(4), ones, ones);
      stsm4(sb + OFF_V + 6 * 2048 + ro, PV(5), PV(6));
      stsm4(sb + OFF_V + 8 * 2048 + ro, PV(7), PV(8));
      stsm4(sb + OFF_V + 10 * 2048 + ro, PV(9), ones, ones);
      #pragma unroll
      for (int j = 0; j < 10; j += 2) stsm4(sb + OFF_PK + j * 2048 + ro, PK(j), PK(j + 1));
    }
    fence_async();
    bar_sync(1, 256);
    if (tid == 0) TS(3);
    mbar_wait(BAR(BR_EPOCH), 0);
    const unsigned epoch = lds32(sb + OFF_EPOCH);
    {
      float kv[24]; zero<24>(kv);
      const uint64_t da = mkdesc(sb + OFF_PK + wg * 5 * 2048, 128, 2048, 0);
      const uint64_t db = mkdesc(sb + OFF_V + wg * 6 * 2048, 128, 2048, 0);
      wg_fence();
      #pragma unroll
      for (int s = 0; s < 8; s++) wg_ss48_tt(kv, da + s * 16, db + s * 16, s != 0);
      wg_commit();
      wg_wait<0>();
      pin<24>(kv);
      if (tid == 0) TS(15);
      if (w4 < 3) {
        const uint32_t wb = sb + OFF_KVS + (wg * 3 + w4) * 1536;
        #pragma unroll
        for (int j = 0; j < 6; j += 2)
          stsm4(wb + (lane & 15) * 96 + (j + (lane >> 4)) * 16, pack2(kv[4 * j], kv[4 * j + 1]), pack2(kv[4 * j + 2], kv[4 * j + 3]),
                pack2(kv[4 * j + 4], kv[4 * j + 5]), pack2(kv[4 * j + 6], kv[4 * j + 7]));
        __syncwarp();
        const int dl = w4 * 16 + (lane & 15), hl = dl >= 20;
        if (dl < 40) {
          uint4* dst = &g_kvp[(c * 16 + r) * 240 + wg * 40 + dl];
          uint32_t v[4];
          lds128(v, wb + (lane & 15) * 96 + (3 * hl + (lane >> 4)) * 16);
          v[3] = (v[3] & ~1u) | (epoch & 1u);
          st128_rlx(dst + (lane >> 4) * 80, v);
          if (lane < 16) {
            v[0] = lds32(wb + lane * 96 + 32 + 8 * hl); v[1] = lds32(wb + lane * 96 + 36 + 8 * hl);
            v[2] = lds32(wb + lane * 96 + 80); v[3] = epoch & 1u;
            st128_rlx(dst + 160, v);
          }
        }
      }
    }
    bar_sync(1, 256);
    if (tid == 0) { st_rlx(&g_flag[c * 32 + r], epoch); mbar_arrive(BAR(BR_PUB)); TS(4); }
    const int kd = tid >= 160 ? tid - 160 : (tid >= 80 ? tid - 80 : tid), kvi = (tid >= 80) + (tid >= 160);
    const int khd = kd / 20, kt0 = 5 * (khd >> 1) + 2 * (khd & 1);
    if (tid < 240) {
      #pragma unroll
      for (int m = 0; m < 3; m++) {
        int q = kt0 + 3 + kvi + 3 * m; if (q >= 10) q -= 10;
        if (kvi + 3 * m < 7) sts128(sb + OFF_KVB + q * 1280 + kd * 16, 0, 0, 0, 0);
      }
    }
    uint32_t qa[20];
    {
      const float sc = 1.44269504089f + __uint_as_float(lds32(sb + OFF_EPOCH) ^ epoch);
      #pragma unroll
      for (int j = 0; j < 10; j++) { qa[2 * j] = pack2(phi(QV(j, 0), sc), phi(QV(j, 1), sc)); qa[2 * j + 1] = pack2(phi(QV(j, 2), sc), phi(QV(j, 3), sc)); }
    }
    if (tid == 0) TS(5);
    {
      poll_all(&g_flag[c * 32 + (lane & 15)], epoch);
      if (tid == 0) TS(6);
      if (tid < 240) {
        uint32_t v[16][4];
        const uint4* src = &g_kvp[c * 16 * 240 + tid];
        #pragma unroll
        for (int i = 0; i < 16; i++) ld128_rlx(v[i], src + i * 240);
        float s[8];
        uint32_t bad = 0;
        #pragma unroll
        for (int i = 0; i < 16; i++) {
          bad |= v[i][3] ^ epoch;
          #pragma unroll
          for (int e = 0; e < 4; e++) {
            s[2 * e] = i ? s[2 * e] + bf_lo(v[i][e]) : bf_lo(v[i][e]);
            s[2 * e + 1] = i ? s[2 * e + 1] + bf_hi(v[i][e]) : bf_hi(v[i][e]);
          }
        }
        if (__builtin_expect(bad & 1u, 0)) {
          #pragma unroll
          for (int e = 0; e < 8; e++) s[e] = 0.f;
          #pragma unroll 1
          for (int i = 0; i < 16; i++) {
            uint32_t w[4] = {0, 0, 0, ~epoch};
            fix128_w3(w, src + i * 240, epoch, 1u);
            #pragma unroll
            for (int e = 0; e < 4; e++) { s[2 * e] += bf_lo(w[e]); s[2 * e + 1] += bf_hi(w[e]); }
          }
        }
        if (tid == 0) TS(18);
        const uint32_t p0 = pack2(s[0], s[1]), p1 = pack2(s[2], s[3]), p2 = pack2(s[4], s[5]), p3 = pack2(s[6], s[7]);
        const uint32_t rb = sb + OFF_KVB + kd * 16;
        if (kvi < 2) sts128(rb + (kt0 + (khd & 1) + kvi) * 1280, p0, p1, p2, p3);
        else {
          const bool od = khd & 1;
          sts128(rb + (5 * (khd >> 1) + 2) * 1280, od ? 0u : p0, od ? 0u : p1, od ? p0 : 0u, od ? p1 : 0u);
          const uint32_t zz = (p2 & 0xffffu) << (16 * (khd & 1));
          sts128(rb + 10 * 1280, khd < 2 ? zz : 0u, khd < 2 ? 0u : zz, 0u, 0u);
        }
      }
    }
    fence_async();
    bar_sync(1, 256);
    if (tid == 0) TS(7);
    uint32_t A0[20], A1[20];
    {
      float oa[44]; zero<44>(oa);
      const uint64_t db = mkdesc(sb + OFF_KVB, 128, 1280, 0);
      wg_fence();
      #pragma unroll
      for (int s = 0; s < 5; s++) wg_rs88_tb(oa, &qa[4 * s], db + s * 16, s != 0);
      wg_commit();
      if (tid == 0) TS(12);
      wg_wait<0>();
      pin<44>(oa);
      if (tid == 0) TS(13);
      float rc[4], rd[2][4];
      #pragma unroll
      for (int e = 0; e < 4; e++) rc[e] = __fdividef(1.f, oa[40 + e] + 1e-6f);
      #pragma unroll
      for (int h = 0; h < 4; h++) {
        rd[0][h] = __shfl_sync(0xffffffff, rc[h & 1], (lane & 28) | (h >> 1));
        rd[1][h] = __shfl_sync(0xffffffff, rc[2 + (h & 1)], (lane & 28) | (h >> 1));
      }
      #pragma unroll
      for (int j = 0; j < 10; j++) {
        #pragma unroll
        for (int h = 0; h < 2; h++) {
          float f;
          if (j == 2) f = tq < 2 ? rd[h][0] : rd[h][1];
          else if (j == 7) f = tq < 2 ? rd[h][2] : rd[h][3];
          else f = rd[h][(8 * j) / 20];
          A0[2 * j + h] = pack2(oa[4 * j + 2 * h] * f, oa[4 * j + 2 * h + 1] * f);
        }
      }
      bar_sync(1, 256);
      #pragma unroll
      for (int s = 0; s < 5; s++) {
        A0[4 * s] = (A0[4 * s] & ~1u) | (epoch & 1u);
        sts128(sb + OFF_EXTRA + ((wg * 5 + s) * 128 + t7) * 16, A0[4 * s], A0[4 * s + 1], A0[4 * s + 2], A0[4 * s + 3]);
      }
    }
    if (tid == 0) TS(14);
    fence_async();
    mbar_arrive(BAR(BR_OSTG));
    if (tid == 0) TS(8);
    float oc[32], od[8]; zero<32>(oc); zero<8>(od);
    {
      const uint64_t dw0 = mkdesc(sb + OFF_WOM, 16, 1024, 1), dr0 = mkdesc(sb, 16, 256, 3);
      mbar_wait(BAR(BR_WO), 0);
      mbar_wait(BAR(BR_WO + 1), 0);
      wg_fence();
      #pragma unroll
      for (int s = 0; s < 5; s++) { wg_rs64_tb(oc, &A0[4 * s], dw0 + c * 640 + s * 128, s != 0); wg_rs16_tb(od, &A0[4 * s], dr0 + c * 160 + s * 32, s != 0); }
      wg_commit();
      #pragma unroll
      for (int i = 0; i < 7; i++) {
        uint32_t* A = (i & 1) ? A0 : A1;
        const uint32_t slot = (i & 3) == 3 ? sb + OFF_EXTRA : sb + OFF_BLK + (4 - (i & 3)) * BLK;
        const int src = (i == 6) ? (c ^ 1) : (((c & 6) + 2 + i) & 7);
        mbar_wait(BAR(BR_OFULL + (i & 3)), i >> 2);
        if (i == 0 && tid == 0) TS(9);
        if (i > 0) wg_wait<1>();
        #pragma unroll
        for (int s = 0; s < 5; s++) lds128(&A[4 * s], slot + ((wg * 5 + s) * 128 + t7) * 16);
        uint32_t bad = 0;
        #pragma unroll
        for (int s = 0; s < 5; s++) bad |= A[4 * s] ^ epoch;
        if (__builtin_expect(bad & 1u, 0)) {
          #pragma unroll
          for (int s = 0; s < 5; s++) fix128_w0(&A[4 * s], &g_o[(r * 8 + src) * 1280 + (wg * 5 + s) * 128 + t7], epoch, 1u);
        }
        __syncwarp();
        if (i < 3 && lane == 0) mbar_arrive(BAR(BR_OEMPTY + i));
        wg_fence();
        #pragma unroll
        for (int s = 0; s < 5; s++) { wg_rs64_tb(oc, &A[4 * s], dw0 + src * 640 + s * 128, 1); wg_rs16_tb(od, &A[4 * s], dr0 + src * 160 + s * 32, 1); }
        wg_commit();
      }
      bar_sync(2 + wg, 128);
      wg_wait<0>();
      pin<32>(oc); pin<8>(od);
    }
    if (tid == 0) TS(10);
    {
      const int row = w4 * 16 + (lane & 15);
      const uint32_t ob = sb + OFF_EXTRA + wg * 10240;
      #pragma unroll
      for (int j = 0; j < 8; j += 2)
        stsm4(ob + row * 128 + (((j + (lane >> 4)) ^ (row & 7)) << 4), pack2(oc[4 * j], oc[4 * j + 1]), pack2(oc[4 * j + 2], oc[4 * j + 3]),
              pack2(oc[4 * j + 4], oc[4 * j + 5]), pack2(oc[4 * j + 6], oc[4 * j + 7]));
      stsm4(ob + 8192 + row * 32 + (lane >> 4) * 16, pack2(od[0], od[1]), pack2(od[2], od[3]), pack2(od[4], od[5]), pack2(od[6], od[7]));
      fence_async();
      bar_sync(2 + wg, 128);
      if (t7 == 0) {
        tma2d_st(&mo64, ob, 640 + c * 64, r * 128 + wg * 64);
        tma2d_st(&mo16, ob + 8192, 1152 + c * 16, r * 128 + wg * 64);
        bulk_commit(); bulk_wait0_read();
      }
      if (tid == 0) { TS(11); DUMP(0, 20); }
    }
    }
  } else {
    asm volatile("setmaxnreg.inc.sync.aligned.u32 152;");
    if (EN_SSM) {
    const int w4 = warp & 3, g = lane >> 2, tq = lane & 3, t7 = tid & 127;
    const int d0 = c * 80 + r * 5;
    uint32_t pa, pc, pd, pdn;
    auto ldp = [&](int k) {
      const int o = (d0 + k) * 128 + opaque(t7);
      pa = (uint32_t)__bfloat16_as_ushort(prm.logA[o]) | ((uint32_t)__bfloat16_as_ushort(prm.Aim[o]) << 16);
      pc = (uint32_t)__bfloat16_as_ushort(prm.Cr[o]) | ((uint32_t)__bfloat16_as_ushort(prm.Ci[o]) << 16);
      pdn = (uint32_t)__bfloat16_as_ushort(prm.logdt[d0 + k]) | ((uint32_t)__bfloat16_as_ushort(prm.dskip[d0 + k]) << 16);
    };
    ldp(4);
    if (t7 < 32) {
      const __nv_bfloat16* pp = (t7 >> 3) == 0 ? prm.logA : (t7 >> 3) == 1 ? prm.Aim : (t7 >> 3) == 2 ? prm.Cr : prm.Ci;
      asm volatile("prefetch.global.L2 [%0];" :: "l"(pp + d0 * 128 + (t7 & 7) * 64));
    }
    #pragma unroll
    for (int k = 0; k < 5; k++)
      #pragma unroll
      for (int i = 0; i < 3; i++) sts128(sb + OFF_BLK + k * BLK + B_TBL + (i * 128 + t7) * 16, 0, 0, 0, 0);
    if (t7 < 72) sts128(sb + OFF_BLK - 1152 + t7 * 16, 0, 0, 0, 0);

    const uint32_t kg = sb + OFF_BLK + B_D;
    const uint32_t kcon = kg + 6704, kka = kg + 8752, kk2 = kka + 1028;
    uint32_t G[13]; float cn[4];
    auto pre = [&](uint32_t a_, uint32_t c_, uint32_t d_) {
      const float dt = bf_round(expf(bf_lo(d_)));
      const float lr = -bf_round(expf(bf_lo(a_))) * dt * 1.44269504089f;
      const float tn = bf_hi(a_) * dt * 0.15915494309f;
      float zr, zi, hr, hi_, gr = 2.f * bf_lo(c_) * dt, gi = 2.f * bf_hi(c_) * dt, g4r = 0.f, g4i = 0.f;
      cexp_t(lr, tn, zr, zi);
      cexp_t(lr * 512.f, tn * 512.f, hr, hi_);
      cexp_t(lr * 64.f, tn * 64.f, cn[2], cn[3]);
      cn[0] = lr * 8.f; cn[1] = tn * 8.f;
      float xr = gr, xi = gi;
      #pragma unroll
      for (int b = 0; b < 8; b++) {
        G[b] = pack2(xr, -xi);
        if (b == 4) { g4r = xr; g4i = xi; }
        if (b < 7) cmul(xr, xi, zr, zi, xr, xi);
      }
      cmul(g4r, g4i, hr, hi_, g4r, g4i); G[9] = pack2(g4r, -g4i);
      cmul(gr, gi, hr, hi_, gr, gi); G[8] = pack2(gr, -gi);
      cmul(gr, gi, hr, hi_, gr, gi); G[10] = pack2(gr, -gi);
      cmul(gr, gi, hr, hi_, gr, gi); G[11] = pack2(gr, -gi);
      cmul(gr, gi, hr, hi_, gr, gi); G[12] = pack2(gr, -gi);
    };
    auto pre_store = [&]() {
      const int tt = opaque(t7);
      #pragma unroll
      for (int b = 0; b < 13; b++) sts32(kg + (tt >> 2) * 208 + b * 16 + (tt & 3) * 4, G[b]);
      sts128(kcon + tt * 16, __float_as_uint(cn[0]), __float_as_uint(cn[1]), __float_as_uint(cn[2]), __float_as_uint(cn[3]));
    };
    auto build_tbl = [&](int k) {
      const int tt = opaque(t7);
      const uint32_t tb = sb + OFF_BLK + k * BLK + B_TBL, k3 = sb + OFF_BLK + k * BLK + B_SP;
      auto rnd = [](int l) { return l < 256 ? l : (l >= 511 ? 512 : ((l + ((l >> 1) & 1)) & ~1)); };
      #pragma unroll
      for (int i = 0; i < 5; i++) {
        const int o = tt + i * 128;
        if (o <= 515) {
          const uint32_t lo = o <= 514 ? lds16(kka + 2 * rnd(o)) : 0u, hi = o >= 1 ? lds16(kka + 2 * rnd(o - 1)) : 0u;
          sts32(tb + (64 + o) * 4, lo | (hi << 16));
        }
      }
      if (tt <= 64) {
        const int e = tt;
        uint32_t lo = e < 64 ? lds16(kk2 + 2 * (e + 1)) : 0u, hi = e >= 1 ? lds16(kk2 + 2 * e) : 0u;
        sts32(tb + (656 + e) * 4, lo | (hi << 16));
        lo = e < 64 ? lds16(kk2 + 132 + 2 * e) : 0u; hi = e >= 1 ? lds16(kk2 + 132 + 2 * (e - 1)) : 0u;
        sts32(tb + (784 + e) * 4, lo | (hi << 16));
      }
      if (tt >= 64) {
        const int e = tt - 64;
        uint32_t lo = lds16(k3 + 2 * (2 * e + 2)), hi = e >= 1 ? lds16(k3 + 2 * (2 * e)) : 0u;
        sts32(tb + (912 + e) * 4, lo | (hi << 16));
        lo = lds16(k3 + 2 * (2 * e + 1)); hi = e >= 1 ? lds16(k3 + 2 * (2 * e - 1)) : 0u;
        sts32(tb + (1040 + e) * 4, lo | (hi << 16));
      }
    };
    pre(pa, pc, pdn);
    pre_store();
    if (t7 == 0) TS(40);
    {
      const float ef = (float)(w4 * 16 + g);
      const uint64_t dg = mkdesc(kg, 208, 128, 0);
      #pragma unroll 1
      for (int k = 4; k >= 0; k--) {
        fence_async();
        bar_sync(4, 128);
        if (t7 == 0 && k == 3) TS(50);
        pd = pdn;
        ldp(k > 0 ? k - 1 : 0);
        uint32_t A[64];
        #pragma unroll
        for (int m = 0; m < 32; m++) {
          if ((m & 7) == 0 && m) __syncwarp();
          uint32_t cc[4];
          lds128(cc, kcon + (m * 4 + tq) * 16);
          float er, ei, fr, fi;
          cexp_t(__uint_as_float(cc[0]) * ef, __uint_as_float(cc[1]) * ef, er, ei);
          cmul(er, ei, __uint_as_float(cc[2]), __uint_as_float(cc[3]), fr, fi);
          A[2 * m] = pack2(er, ei); A[2 * m + 1] = pack2(fr, fi);
          if ((m & 3) == 3) pinu<8>(&A[2 * m - 6]);
        }
        float ka[8]; zero<8>(ka);
        wg_fence();
        if (t7 == 0 && k == 3) TS(51);
        #pragma unroll
        for (int s = 0; s < 16; s++) wg_rs16(ka, &A[4 * s], dg + s * 26, s != 0);
        wg_commit();
        if (t7 == 0 && k == 3) TS(52);
        if (k < 4) build_tbl(k + 1);
        if (t7 == 0 && k == 3) TS(53);
        pre(pa, pc, pdn);
        pinu<13>(G); pin<4>(cn);
        wg_wait<0>();
        pin<8>(ka);
        if (t7 == 0 && k == 3) TS(54);
        bar_sync(4, 128);
        if (t7 == 0 && k == 3) TS(55);
        {
          const uint32_t k3 = sb + OFF_BLK + k * BLK + B_SP;
          if (t7 == 0) ka[0] += bf_hi(pd);
          const int j0 = opaque(w4 * 16 + g);
          #pragma unroll
          for (int h = 0; h < 2; h++) {
            const int j = j0 + 8 * h;
            sts32(kka + (8 * j + 2 * tq) * 2, pack2(ka[2 * h], ka[2 * h + 1]));
            const uint32_t v = pack2(ka[4 + 2 * h], ka[5 + 2 * h]);
            if (tq == 0) { sts16(kk2 + 2 * j, v); sts16(kk2 + 132 + 2 * j, v >> 16); if (j == 0) sts16(kka + 1024, v); }
            if (tq == 1) { sts16(k3 + 2 * j, v); sts16(k3 + 128 + 2 * j, v >> 16); if (j == 0) sts16(kk2 + 128, v); }
            if (tq == 2 && j == 0) sts16(k3 + 256, v);
          }
        }
        pre_store();
        if (t7 == 0 && k == 3) TS(56);
      }
      bar_sync(4, 128);
      build_tbl(0);
      bar_sync(4, 128);
      if (t7 == 0) { mbar_arrive(BAR(BR_KGEN)); TS(41); }
    }
    mbar_wait(BAR(BR_U), 0);
    if (EN_ATT) mbar_wait(BAR(BR_GEMM), 0);
    if (t7 == 0) TS(42);
    const uint32_t lb = (uint32_t)((16 * w4 + g - 2 * tq - 48) * 4);
    #pragma unroll 1
    for (int k = 4; k >= 0; k--) {
      const uint32_t blk = sb + OFF_BLK + k * BLK, tb = blk + B_TBL + lb;
      const uint64_t dd = mkdesc(blk + B_D, 128, 1024, 0);
      const uint64_t du = mkdesc(blk + 96 - 32 * 36, 16, 1024, 1);
      float aC[8], a24[12], a16[8], aY[16];
      zero<8>(aC); zero<12>(a24); zero<8>(a16); zero<16>(aY);
      uint32_t A0[32], A1[32];
      mbar_wait(BAR(BR_DRDY + k), 0);
      if (t7 == 0 && k == 3) TS(57);
      load_toep<4>(A0, tb + 912 * 4); load_toep<4>(A0 + 16, tb + 1040 * 4);
      wg_fence();
      #pragma unroll
      for (int s = 0; s < 4; s++) wg_rs16_tb(aC, &A0[4 * s], dd + (B_D9 >> 4) + (3 - s) * 16, s != 0);
      #pragma unroll
      for (int s = 0; s < 4; s++) wg_rs16_tb(aC, &A0[16 + 4 * s], dd + (B_D7 >> 4) + (3 - s) * 16, 1);
      wg_commit();
      load_toep<8>(A1, tb + 656 * 4);
      wg_fence();
      #pragma unroll
      for (int s = 0; s < 4; s++) wg_rs24_tb(a24, &A1[4 * s], dd + (3 - s) * 16, s != 0);
      #pragma unroll
      for (int s = 0; s < 4; s++) wg_rs16_tb(a16, &A1[16 + 4 * s], dd + (3 - s) * 16, s != 0);
      wg_commit();
      wg_wait<1>();
      load_toep<8>(A0, tb + 784 * 4);
      wg_fence();
      #pragma unroll
      for (int s = 0; s < 4; s++) wg_rs24_tb(a24, &A0[4 * s], dd + (B_D3 >> 4) + (3 - s) * 16, 1);
      #pragma unroll
      for (int s = 0; s < 4; s++) wg_rs16_tb(a16, &A0[16 + 4 * s], dd + (B_D3 >> 4) + (3 - s) * 16, 1);
      wg_commit();
      #pragma unroll
      for (int b = 0; b < 5; b++) {
        uint32_t* A = (b & 1) ? A0 : A1;
        wg_wait<1>();
        if (b < 4) load_toep<8>(A, tb + (64 + 128 * b) * 4); else load_toep<5>(A, tb + (64 + 128 * b) * 4);
        wg_fence();
        #pragma unroll
        for (int s = 0; s < (b < 4 ? 8 : 5); s++) wg_rs32(aY, &A[4 * s], du + (36 - (8 * b + s)) * 2, (b | s) != 0);
        wg_commit();
        if (t7 == 0 && k == 3) TS(58 + b);
        if (b == 1) {
          pin<8>(aC); pin<12>(a24); pin<8>(a16);
          bar_sync(4, 128);
          const float kc = bf_lo(lds16(blk + B_SP));
          const int ln = opaque(lane), gg = ln >> 2, q2 = (ln & 3) * 2;
          const uint32_t f1 = blk + B_D + (128 * w4 + ((8 * gg) ^ (8 * w4)) + q2) * 4;
          const uint32_t f2 = blk + B_D + 6144 + (256 * w4 + ((16 * gg) ^ (16 * (w4 & 1))) + q2) * 4;
          #pragma unroll
          for (int h = 0; h < 2; h++) {
            #pragma unroll
            for (int jp = 0; jp < 3; jp++) {
              float x = a24[4 * jp + 2 * h], y = a24[4 * jp + 2 * h + 1];
              if (jp > 0) { x += a16[4 * (jp - 1) + 2 * h]; y += a16[4 * (jp - 1) + 2 * h + 1]; }
              sts64f(f1 + (64 * h + 512 * jp) * 4, x, y);
            }
            #pragma unroll
            for (int n = 0; n < 2; n++) {
              const int s4 = 256 * w4 + 16 * gg + 128 * h + 8 * n + q2 - 4, s2 = s4 + 2;
              const uint32_t u4 = lds32(blk + (uint32_t)((2 * s4) ^ ((s4 >> 2) & 0x70)));
              const uint32_t u2 = lds32(blk + (uint32_t)((2 * s2) ^ ((s2 >> 2) & 0x70)));
              const float x = fmaf(kc, bf_lo(u4) + bf_hi(u4), aC[4 * n + 2 * h]);
              const float y = fmaf(kc, bf_hi(u4) + bf_lo(u2), aC[4 * n + 2 * h + 1]);
              sts64f(f2 + (128 * h + 8 * (n ^ h)) * 4, x, y);
            }
          }
        }
      }
      wg_wait<0>();
      pin<16>(aY);
      if (t7 == 0 && k == 3) TS(63);
      bar_sync(4, 128);
      {
        const int ln = opaque(lane), tt = ln & 3;
        const uint32_t b0 = (128 * tt + ((16 * w4) ^ (8 * tt)) + (ln >> 2)) * 4;
        #pragma unroll
        for (int n = 1; n < 4; n++)
          #pragma unroll
          for (int e = 0; e < 4; e++) {
            const uint32_t a = blk + B_D + (b0 ^ (32 * (e >> 1))) + (512 * (n - 1) + 64 * (e & 1)) * 4;
            aY[4 * n + e] += ldsf(a);
            if (n >= 2) aY[4 * n + e] += ldsf(a + 6144 - 2048);
          }
        const uint32_t ya = blk + (8 * (ln >> 4) + (ln & 7)) * 128 + (((2 * w4 + ((ln >> 3) & 1)) ^ (ln & 7)) << 4);
        #pragma unroll
        for (int n = 0; n < 4; n += 2)
          stsm4t(ya + n * 1024, pack2(aY[4 * n], aY[4 * n + 1]), pack2(aY[4 * n + 2], aY[4 * n + 3]),
                 pack2(aY[4 * n + 4], aY[4 * n + 5]), pack2(aY[4 * n + 6], aY[4 * n + 7]));
      }
      fence_async();
      mbar_arrive(BAR(BR_YSTG + k));
      if (t7 == 0) TS(47 - k);
    }
    if (t7 == 0) DUMP(40, 64);
    }
  }
}

typedef CUresult (*EncFn)(CUtensorMap*, CUtensorMapDataType, cuuint32_t, void*, const cuuint64_t*, const cuuint64_t*, const cuuint32_t*,
                          const cuuint32_t*, CUtensorMapInterleave, CUtensorMapSwizzle, CUtensorMapL2promotion, CUtensorMapFloatOOBfill);
static CUtensorMap mkmap(EncFn enc, const void* base, int rank, const cuuint64_t* dims, const cuuint64_t* strides, const cuuint32_t* box, CUtensorMapSwizzle swz) {
  CUtensorMap m; cuuint32_t es[5] = {1, 1, 1, 1, 1};
  enc(&m, CU_TENSOR_MAP_DATA_TYPE_BFLOAT16, rank, const_cast<void*>(base), dims, strides, box, es, CU_TENSOR_MAP_INTERLEAVE_NONE, swz,
      CU_TENSOR_MAP_L2_PROMOTION_L2_128B, CU_TENSOR_MAP_FLOAT_OOB_FILL_NONE);
  return m;
}

extern "C" void kernel_launch(void* const* d_in, const int* in_sizes, int n_in, void* d_out, int out_size) {
  void* fn = nullptr; cudaDriverEntryPointQueryResult qr;
  cudaGetDriverEntryPoint("cuTensorMapEncodeTiled", &fn, cudaEnableDefault, &qr);
  EncFn enc = (EncFn)fn;
  void* uy = nullptr; cudaGetSymbolAddress(&uy, g_uy);
  const cuuint64_t dx[2] = {640, 2048}, sx[1] = {1280};
  const cuuint32_t bx[2] = {64, 128}, bu[2] = {80, 64};
  const cuuint64_t dw[3] = {640, 640, 3}, sw[2] = {3840, 1280};
  const cuuint32_t bw[3] = {64, 32, 3}, br[3] = {16, 32, 3};
  const cuuint64_t dwo[2] = {640, 640};
  const cuuint32_t bwo[2] = {64, 80}, bwr[2] = {16, 160}, bo64[2] = {64, 64}, bo16[2] = {16, 64};
  const cuuint64_t dsa[2] = {2048, 1280}, ssa[1] = {4096};
  const cuuint32_t bsa[2] = {64, 80};
  const cuuint64_t dsb[2] = {64, 40960}, ssb[1] = {128};
  const cuuint32_t bsb[2] = {64, 32};
  const cuuint64_t dout[2] = {1280, 2048}, sout[1] = {2560};
  CUtensorMap mx = mkmap(enc, d_in[7], 2, dx, sx, bx, CU_TENSOR_MAP_SWIZZLE_128B);
  CUtensorMap mw = mkmap(enc, d_in[8], 3, dw, sw, bw, CU_TENSOR_MAP_SWIZZLE_128B);
  CUtensorMap mr = mkmap(enc, d_in[8], 3, dw, sw, br, CU_TENSOR_MAP_SWIZZLE_32B);
  CUtensorMap mwo = mkmap(enc, d_in[9], 2, dwo, sx, bwo, CU_TENSOR_MAP_SWIZZLE_128B);
  CUtensorMap mwr = mkmap(enc, d_in[9], 2, dwo, sx, bwr, CU_TENSOR_MAP_SWIZZLE_32B);
  CUtensorMap mo64 = mkmap(enc, d_out, 2, dout, sout, bo64, CU_TENSOR_MAP_SWIZZLE_128B);
  CUtensorMap mo16 = mkmap(enc, d_out, 2, dout, sout, bo16, CU_TENSOR_MAP_SWIZZLE_NONE);
  CUtensorMap mu = mkmap(enc, d_in[0], 2, dx, sx, bu, CU_TENSOR_MAP_SWIZZLE_NONE);
  CUtensorMap msa = mkmap(enc, uy, 2, dsa, ssa, bsa, CU_TENSOR_MAP_SWIZZLE_128B);
  CUtensorMap msb = mkmap(enc, uy, 2, dsb, ssb, bsb, CU_TENSOR_MAP_SWIZZLE_128B);
  CUtensorMap mout = mkmap(enc, d_out, 2, dout, sout, bu, CU_TENSOR_MAP_SWIZZLE_NONE);
  Params prm;
  prm.logA = (const __nv_bfloat16*)d_in[1]; prm.Aim = (const __nv_bfloat16*)d_in[2];
  prm.Cr = (const __nv_bfloat16*)d_in[3]; prm.Ci = (const __nv_bfloat16*)d_in[4];
  prm.logdt = (const __nv_bfloat16*)d_in[5]; prm.dskip = (const __nv_bfloat16*)d_in[6];
  cudaFuncSetAttribute(fused_kernel, cudaFuncAttributeMaxDynamicSharedMemorySize, SMEM_BYTES);
  cudaLaunchConfig_t cfg = {};
  cfg.gridDim = dim3(128); cfg.blockDim = dim3(512); cfg.dynamicSmemBytes = SMEM_BYTES; cfg.stream = cudaStreamPerThread;
  cudaLaunchAttribute at[1];
  at[0].id = cudaLaunchAttributeClusterDimension; at[0].val.clusterDim.x = 2; at[0].val.clusterDim.y = 1; at[0].val.clusterDim.z = 1;
  cfg.attrs = at; cfg.numAttrs = 1;
  cudaLaunchKernelEx(&cfg, fused_kernel, mx, mw, mr, mwo, mwr, mo64, mo16, mu, msa, msb, mout, prm);
}
```

```cpp
#include <cuda_runtime.h>
#include <cuda_bf16.h>
#include <cuda_fp16.h>
#include <cuda.h>
#include <stdint.h>

#define EN_ATT 1
#define EN_SSM 1

__device__ __align__(1024) __nv_bfloat16 g_uy[2 * 640 * 2048];
__device__ __align__(128) uint4 g_kvp[8 * 16 * 240];
__device__ __align__(128) uint4 g_o[128 * 1280];
__device__ __align__(128) unsigned g_flag[40 * 32];
__device__ unsigned g_epoch[128];
#define TS(i) do {} while (0)
#define DUMP(lo, hi) do {} while (0)

constexpr uint32_t W_SLOT = 15360, OFF_X = 76800;
constexpr uint32_t OFF_WOM = 20480, OFF_KVS = 71680, OFF_PK = 80896, OFF_V = 101376, OFF_EXTRA = 102400, OFF_KVB = OFF_EXTRA;
constexpr uint32_t OFF_BAR = 125952, OFF_BLK = 128000, BLK = 20480;
constexpr uint32_t B_D = 4096, B_D3 = 3072, B_D9 = 6144, B_D7 = 8192, B_TBL = 14336, B_SP = 18768;
constexpr uint32_t SMEM_BYTES = OFF_BLK + 5 * BLK + 1024;
enum { BR_FULL = 0, BR_EMPTY = 5, BR_WO = 10, BR_PUB = 12, BR_OFULL = 18, BR_OEMPTY = 22, BR_GEMM = 26, BR_OSTG = 27, BR_UIN = 28,
       BR_U = 29, BR_DRDY = 30, BR_KGEN = 35, BR_YSTG = 36, BR_FREE = 41, BR_YIN = 46, BR_EPOCH = 47, BR_COUNT = 48 };
constexpr uint32_t OFF_EPOCH = OFF_BAR + 8 * BR_COUNT;

__device__ __forceinline__ long long clk64() { long long t; asm volatile("mov.u64 %0, %%clock64;" : "=l"(t) :: "memory"); return t; }
__device__ __forceinline__ uint32_t smem_u32(const void* p) { return (uint32_t)__cvta_generic_to_shared(p); }
__device__ __forceinline__ uint64_t mkdesc(uint32_t addr, uint32_t lbo, uint32_t sbo, uint32_t swz) {
  return (uint64_t)((addr & 0x3FFFF) >> 4) | ((uint64_t)(lbo >> 4) << 16) | ((uint64_t)(sbo >> 4) << 32) | ((uint64_t)swz << 62);
}
__device__ __forceinline__ void mbar_init(uint32_t bar, uint32_t cnt) { asm volatile("mbarrier.init.shared::cta.b64 [%0], %1;" :: "r"(bar), "r"(cnt) : "memory"); }
__device__ __forceinline__ void mbar_expect_tx(uint32_t bar, uint32_t bytes) { asm volatile("mbarrier.arrive.expect_tx.shared::cta.b64 _, [%0], %1;" :: "r"(bar), "r"(bytes) : "memory"); }
__device__ __forceinline__ void mbar_arrive(uint32_t bar) { asm volatile("mbarrier.arrive.shared::cta.b64 _, [%0];" :: "r"(bar) : "memory"); }
__device__ __forceinline__ void mbar_wait(uint32_t bar, uint32_t parity) {
  asm volatile("{\n.reg .pred p;\n.reg .u32 c;\nmov.u32 c, 0;\n"
    "WL:\nmbarrier.try_wait.parity.shared::cta.b64 p, [%0], %1;\n@p bra WD;\n"
    "add.u32 c, c, 1;\nsetp.lt.u32 p, c, 200000;\n@p bra WL;\nWD:\n}" :: "r"(bar), "r"(parity) : "memory");
}
__device__ __forceinline__ void poll_all(const unsigned* p, unsigned val) {
  asm volatile("{\n.reg .pred p;\n.reg .u32 c, v;\nmov.u32 c, 0;\n"
    "PL:\nld.relaxed.gpu.global.u32 v, [%0];\nsetp.eq.u32 p, v, %1;\nvote.sync.all.pred p, p, 0xffffffff;\n@p bra PD;\n"
    "add.u32 c, c, 1;\nsetp.lt.u32 p, c, 100000;\n@p bra PL;\nPD:\n}" :: "l"(p), "r"(val) : "memory");
}
__device__ __forceinline__ unsigned poll_bit(const unsigned* p, unsigned val, unsigned mask) {
  unsigned bal;
  asm volatile("{\n.reg .pred p;\n.reg .u32 c, v;\nmov.u32 c, 0;\n"
    "PL:\nld.relaxed.gpu.global.u32 v, [%1];\nsetp.eq.u32 p, v, %2;\nvote.sync.ballot.b32 %0, p, 0xffffffff;\n"
    "and.b32 v, %0, %3;\nsetp.ne.u32 p, v, 0;\n@p bra PD;\n"
    "add.u32 c, c, 1;\nsetp.lt.u32 p, c, 100000;\n@p bra PL;\nPD:\n}" : "=&r"(bal) : "l"(p), "r"(val), "r"(mask) : "memory");
  return bal;
}
__device__ __forceinline__ void fix128_w0(uint32_t* v, const void* p, uint32_t tag, uint32_t mask) {
  asm volatile("{\n.reg .pred p;\n.reg .u32 c, x;\n.reg .b128 t;\n.reg .b64 lo, hi;\nmov.u32 c, 0;\n"
    "FL:\nxor.b32 x, %0, %5;\nand.b32 x, x, %6;\nsetp.eq.u32 p, x, 0;\n@p bra FD;\n"
    "ld.relaxed.gpu.global.b128 t, [%4];\nmov.b128 {lo, hi}, t;\nmov.b64 {%0, %1}, lo;\nmov.b64 {%2, %3}, hi;\n"
    "add.u32 c, c, 1;\nsetp.lt.u32 p, c, 100000;\n@p bra FL;\nFD:\n}"
    : "+r"(v[0]), "+r"(v[1]), "+r"(v[2]), "+r"(v[3]) : "l"(p), "r"(tag), "r"(mask) : "memory");
}
__device__ __forceinline__ void fix128_w3(uint32_t* v, const void* p, uint32_t tag, uint32_t mask) {
  asm volatile("{\n.reg .pred p;\n.reg .u32 c, x;\n.reg .b128 t;\n.reg .b64 lo, hi;\nmov.u32 c, 0;\n"
    "FL:\nxor.b32 x, %3, %5;\nand.b32 x, x, %6;\nsetp.eq.u32 p, x, 0;\n@p bra FD;\n"
    "ld.relaxed.gpu.global.b128 t, [%4];\nmov.b128 {lo, hi}, t;\nmov.b64 {%0, %1}, lo;\nmov.b64 {%2, %3}, hi;\n"
    "add.u32 c, c, 1;\nsetp.lt.u32 p, c, 100000;\n@p bra FL;\nFD:\n}"
    : "+r"(v[0]), "+r"(v[1]), "+r"(v[2]), "+r"(v[3]) : "l"(p), "r"(tag), "r"(mask) : "memory");
}
__device__ __forceinline__ void fence_acq() { asm volatile("fence.acq_rel.gpu;" ::: "memory"); }
__device__ __forceinline__ bool elect_one() {
  uint32_t p; asm volatile("{\n.reg .pred P;\nelect.sync _|P, 0xffffffff;\nselp.u32 %0, 1, 0, P;\n}" : "=r"(p)); return p;
}
__device__ __forceinline__ void bar_sync(int id, int n) { asm volatile("bar.sync %0, %1;" :: "r"(id), "r"(n) : "memory"); }
__device__ __forceinline__ void fence_async() { asm volatile("fence.proxy.async.shared::cta;" ::: "memory"); }
__device__ __forceinline__ void fence_async_g() { asm volatile("fence.proxy.async.global;" ::: "memory"); }
__device__ __forceinline__ void tma2d(uint32_t dst, const CUtensorMap* m, uint32_t bar, int c0, int c1) {
  asm volatile("cp.async.bulk.tensor.2d.shared::cluster.global.mbarrier::complete_tx::bytes [%0], [%1, {%3, %4}], [%2];"
    :: "r"(dst), "l"(m), "r"(bar), "r"(c0), "r"(c1) : "memory");
}
__device__ __forceinline__ void tma3d(uint32_t dst, const CUtensorMap* m, uint32_t bar, int c0, int c1, int c2) {
  asm volatile("cp.async.bulk.tensor.3d.shared::cluster.global.mbarrier::complete_tx::bytes [%0], [%1, {%3, %4, %5}], [%2];"
    :: "r"(dst), "l"(m), "r"(bar), "r"(c0), "r"(c1), "r"(c2) : "memory");
}
__device__ __forceinline__ void tma2d_st(const CUtensorMap* m, uint32_t src, int c0, int c1) {
  asm volatile("cp.async.bulk.tensor.2d.global.shared::cta.bulk_group [%0, {%2, %3}], [%1];"
    :: "l"(m), "r"(src), "r"(c0), "r"(c1) : "memory");
}
__device__ __forceinline__ void bulk_ld(uint32_t dst, const void* src, uint32_t bytes, uint32_t bar) {
  asm volatile("cp.async.bulk.shared::cluster.global.mbarrier::complete_tx::bytes [%0], [%1], %2, [%3];"
    :: "r"(dst), "l"(src), "r"(bytes), "r"(bar) : "memory");
}
__device__ __forceinline__ void bulk_st(void* dst, uint32_t src, uint32_t bytes) {
  asm volatile("cp.async.bulk.global.shared::cta.bulk_group [%0], [%1], %2;" :: "l"(dst), "r"(src), "r"(bytes) : "memory");
}
__device__ __forceinline__ void bulk_commit() { asm volatile("cp.async.bulk.commit_group;" ::: "memory"); }
__device__ __forceinline__ void bulk_wait0() { asm volatile("cp.async.bulk.wait_group 0;" ::: "memory"); }
__device__ __forceinline__ void bulk_wait0_read() { asm volatile("cp.async.bulk.wait_group.read 0;" ::: "memory"); }
__device__ __forceinline__ unsigned ld_rlx(const unsigned* p) { unsigned v; asm volatile("ld.relaxed.gpu.global.u32 %0, [%1];" : "=r"(v) : "l"(p) : "memory"); return v; }
__device__ __forceinline__ unsigned ld_acq(const unsigned* p) { unsigned v; asm volatile("ld.acquire.gpu.global.u32 %0, [%1];" : "=r"(v) : "l"(p) : "memory"); return v; }
__device__ __forceinline__ void st_rlx(unsigned* p, unsigned v) { asm volatile("st.relaxed.gpu.global.u32 [%0], %1;" :: "l"(p), "r"(v) : "memory"); }
__device__ __forceinline__ void st_rel(unsigned* p, unsigned v) { asm volatile("st.release.gpu.global.u32 [%0], %1;" :: "l"(p), "r"(v) : "memory"); }
__device__ __forceinline__ void ld128_rlx(uint32_t* v, const void* p) {
  asm volatile("{\n.reg .b128 t;\n.reg .b64 lo, hi;\nld.relaxed.gpu.global.b128 t, [%4];\nmov.b128 {lo, hi}, t;\n"
    "mov.b64 {%0, %1}, lo;\nmov.b64 {%2, %3}, hi;\n}" : "=r"(v[0]), "=r"(v[1]), "=r"(v[2]), "=r"(v[3]) : "l"(p) : "memory");
}
__device__ __forceinline__ void st128_rlx(void* p, const uint32_t* v) {
  asm volatile("{\n.reg .b128 t;\n.reg .b64 lo, hi;\nmov.b64 lo, {%1, %2};\nmov.b64 hi, {%3, %4};\nmov.b128 t, {lo, hi};\n"
    "st.relaxed.gpu.global.b128 [%0], t;\n}" :: "l"(p), "r"(v[0]), "r"(v[1]), "r"(v[2]), "r"(v[3]) : "memory");
}
__device__ __forceinline__ uint32_t lds32(uint32_t a) { uint32_t v; asm volatile("ld.shared.u32 %0, [%1];" : "=r"(v) : "r"(a) : "memory"); return v; }
__device__ __forceinline__ uint32_t lds16(uint32_t a) { uint16_t v; asm volatile("ld.shared.u16 %0, [%1];" : "=h"(v) : "r"(a) : "memory"); return v; }
__device__ __forceinline__ float ldsf(uint32_t a) { float v; asm volatile("ld.shared.f32 %0, [%1];" : "=f"(v) : "r"(a) : "memory"); return v; }
__device__ __forceinline__ void lds128(uint32_t* v, uint32_t a) { asm volatile("ld.shared.v4.u32 {%0,%1,%2,%3}, [%4];" : "=r"(v[0]), "=r"(v[1]), "=r"(v[2]), "=r"(v[3]) : "r"(a) : "memory"); }
__device__ __forceinline__ void sts32(uint32_t a, uint32_t v) { asm volatile("st.shared.u32 [%0], %1;" :: "r"(a), "r"(v) : "memory"); }
__device__ __forceinline__ void sts16(uint32_t a, uint32_t v) { asm volatile("st.shared.u16 [%0], %1;" :: "r"(a), "h"((uint16_t)v) : "memory"); }
__device__ __forceinline__ void sts64f(uint32_t a, float x, float y) { asm volatile("st.shared.v2.f32 [%0], {%1,%2};" :: "r"(a), "f"(x), "f"(y) : "memory"); }
__device__ __forceinline__ void sts128(uint32_t a, uint32_t x, uint32_t y, uint32_t z, uint32_t w) { asm volatile("st.shared.v4.u32 [%0], {%1,%2,%3,%4};" :: "r"(a), "r"(x), "r"(y), "r"(z), "r"(w) : "memory"); }
__device__ __forceinline__ void stsm4(uint32_t a, uint32_t r0, uint32_t r1, uint32_t r2, uint32_t r3) {
  asm volatile("stmatrix.sync.aligned.m8n8.x4.shared.b16 [%0], {%1,%2,%3,%4};" :: "r"(a), "r"(r0), "r"(r1), "r"(r2), "r"(r3) : "memory");
}
__device__ __forceinline__ void stsm4t(uint32_t a, uint32_t r0, uint32_t r1, uint32_t r2, uint32_t r3) {
  asm volatile("stmatrix.sync.aligned.m8n8.x4.trans.shared.b16 [%0], {%1,%2,%3,%4};" :: "r"(a), "r"(r0), "r"(r1), "r"(r2), "r"(r3) : "memory");
}
__device__ __forceinline__ void ldsm4t(uint32_t* r, uint32_t a) {
  asm volatile("ldmatrix.sync.aligned.m8n8.x4.trans.shared.b16 {%0,%1,%2,%3}, [%4];" : "=r"(r[0]), "=r"(r[1]), "=r"(r[2]), "=r"(r[3]) : "r"(a) : "memory");
}
__device__ __forceinline__ uint32_t pack2(float lo, float hi) { uint32_t r; asm("cvt.rn.bf16x2.f32 %0, %1, %2;" : "=r"(r) : "f"(hi), "f"(lo)); return r; }
__device__ __forceinline__ uint32_t packh(float lo, float hi) { uint32_t r; asm("cvt.rn.f16x2.f32 %0, %1, %2;" : "=r"(r) : "f"(hi), "f"(lo)); return r; }
__device__ __forceinline__ uint32_t hcmul(uint32_t x, uint32_t zp, uint32_t zq) {
  const __half2 xx = *reinterpret_cast<__half2*>(&x);
  const __half2 r = __hfma2(__high2half2(xx), *reinterpret_cast<__half2*>(&zq), __hmul2(__low2half2(xx), *reinterpret_cast<__half2*>(&zp)));
  return *reinterpret_cast<const uint32_t*>(&r);
}
__device__ __forceinline__ void sts64(uint32_t a, uint32_t x, uint32_t y) { asm volatile("st.shared.v2.u32 [%0], {%1,%2};" :: "r"(a), "r"(x), "r"(y) : "memory"); }
__device__ __forceinline__ void lds64(uint32_t* v, uint32_t a) { asm volatile("ld.shared.v2.u32 {%0,%1}, [%2];" : "=r"(v[0]), "=r"(v[1]) : "r"(a) : "memory"); }
__device__ __forceinline__ float bf_lo(uint32_t v) { return __uint_as_float(v << 16); }
__device__ __forceinline__ float bf_hi(uint32_t v) { return __uint_as_float(v & 0xffff0000u); }
__device__ __forceinline__ float bf_round(float x) { return bf_lo(pack2(x, 0.f)); }
__device__ __forceinline__ float ex2(float x) { float r; asm("ex2.approx.ftz.f32 %0, %1;" : "=f"(r) : "f"(x)); return r; }
__device__ __forceinline__ float phi(float t, float l2e = 1.44269504089f) { float e = ex2(t * l2e); return (t > 0.f ? t + 1.f : e) + 1e-6f; }
__device__ __forceinline__ void wg_fence() { asm volatile("wgmma.fence.sync.aligned;" ::: "memory"); }
__device__ __forceinline__ void wg_commit() { asm volatile("wgmma.commit_group.sync.aligned;" ::: "memory"); }
template <int N> __device__ __forceinline__ void wg_wait() { asm volatile("wgmma.wait_group.sync.aligned %0;" :: "n"(N) : "memory"); }
template <int N> __device__ __forceinline__ void pin(float* a) {
  #pragma unroll
  for (int i = 0; i < N; i++) asm volatile("" : "+f"(a[i]) :: "memory");
}
__device__ __forceinline__ int opaque(int v) { asm volatile("" : "+r"(v)); return v; }
template <int N> __device__ __forceinline__ void zero(float* a) {
  #pragma unroll
  for (int i = 0; i < N; i++) asm volatile("mov.b32 %0, 0;" : "=f"(a[i]));
}
template <int N> __device__ __forceinline__ void pinu(uint32_t* a) {
  #pragma unroll
  for (int i = 0; i < N; i++) asm volatile("" : "+r"(a[i]) :: "memory");
}
__device__ __forceinline__ void cexp_t(float lg2mag, float turns, float& re, float& im) {
  float m = ex2(lg2mag);
  float fr = (turns - __fadd_rn(__fadd_rn(turns, 12582912.f), -12582912.f)) * 6.283185307f;
  re = m * __cosf(fr); im = m * __sinf(fr);
}
__device__ __forceinline__ void cmul(float ar, float ai, float br, float bi, float& cr, float& ci) {
  cr = fmaf(ar, br, -ai * bi); ci = fmaf(ar, bi, ai * br);
}

__device__ __forceinline__ void wg_ss192_tb(float* d, uint64_t da, uint64_t db, int scale_d) {
  asm volatile("{\n.reg .pred p;\nsetp.ne.b32 p, %98, 0;\n"
    "wgmma.mma_async.sync.aligned.m64n192k16.f32.bf16.bf16 "
    "{%0, %1, %2, %3, %4, %5, %6, %7, %8, %9, %10, %11, %12, %13, %14, %15, %16, %17, %18, %19, %20, %21, %22, %23, %24, %25, %26, %27, %28, %29, %30, %31, %32, %33, %34, %35, %36, %37, %38, %39, %40, %41, %42, %43, %44, %45, %46, %47, %48, %49, %50, %51, %52, %53, %54, %55, %56, %57, %58, %59, %60, %61, %62, %63, %64, %65, %66, %67, %68, %69, %70, %71, %72, %73, %74, %75, %76, %77, %78, %79, %80, %81, %82, %83, %84, %85, %86, %87, %88, %89, %90, %91, %92, %93, %94, %95}, %96, %97, p, 1, 1, 0, 1;\n}\n"
    : "+f"(d[0]), "+f"(d[1]), "+f"(d[2]), "+f"(d[3]), "+f"(d[4]), "+f"(d[5]), "+f"(d[6]), "+f"(d[7]), "+f"(d[8]), "+f"(d[9]), "+f"(d[10]), "+f"(d[11]), "+f"(d[12]), "+f"(d[13]), "+f"(d[14]), "+f"(d[15]), "+f"(d[16]), "+f"(d[17]), "+f"(d[18]), "+f"(d[19]), "+f"(d[20]), "+f"(d[21]), "+f"(d[22]), "+f"(d[23]), "+f"(d[24]), "+f"(d[25]), "+f"(d[26]), "+f"(d[27]), "+f"(d[28]), "+f"(d[29]), "+f"(d[30]), "+f"(d[31]), "+f"(d[32]), "+f"(d[33]), "+f"(d[34]), "+f"(d[35]), "+f"(d[36]), "+f"(d[37]), "+f"(d[38]), "+f"(d[39]), "+f"(d[40]), "+f"(d[41]), "+f"(d[42]), "+f"(d[43]), "+f"(d[44]), "+f"(d[45]), "+f"(d[46]), "+f"(d[47]), "+f"(d[48]), "+f"(d[49]), "+f"(d[50]), "+f"(d[51]), "+f"(d[52]), "+f"(d[53]), "+f"(d[54]), "+f"(d[55]), "+f"(d[56]), "+f"(d[57]), "+f"(d[58]), "+f"(d[59]), "+f"(d[60]), "+f"(d[61]), "+f"(d[62]), "+f"(d[63]), "+f"(d[64]), "+f"(d[65]), "+f"(d[66]), "+f"(d[67]), "+f"(d[68]), "+f"(d[69]), "+f"(d[70]), "+f"(d[71]), "+f"(d[72]), "+f"(d[73]), "+f"(d[74]), "+f"(d[75]), "+f"(d[76]), "+f"(d[77]), "+f"(d[78]), "+f"(d[79]), "+f"(d[80]), "+f"(d[81]), "+f"(d[82]), "+f"(d[83]), "+f"(d[84]), "+f"(d[85]), "+f"(d[86]), "+f"(d[87]), "+f"(d[88]), "+f"(d[89]), "+f"(d[90]), "+f"(d[91]), "+f"(d[92]), "+f"(d[93]), "+f"(d[94]), "+f"(d[95])
    : "l"(da), "l"(db), "r"(scale_d));
}
__device__ __forceinline__ void wg_ss48_tb(float* d, uint64_t da, uint64_t db, int scale_d) {
  asm volatile("{\n.reg .pred p;\nsetp.ne.b32 p, %26, 0;\n"
    "wgmma.mma_async.sync.aligned.m64n48k16.f32.bf16.bf16 "
    "{%0, %1, %2, %3, %4, %5, %6, %7, %8, %9, %10, %11, %12, %13, %14, %15, %16, %17, %18, %19, %20, %21, %22, %23}, %24, %25, p, 1, 1, 0, 1;\n}\n"
    : "+f"(d[0]), "+f"(d[1]), "+f"(d[2]), "+f"(d[3]), "+f"(d[4]), "+f"(d[5]), "+f"(d[6]), "+f"(d[7]), "+f"(d[8]), "+f"(d[9]), "+f"(d[10]), "+f"(d[11]), "+f"(d[12]), "+f"(d[13]), "+f"(d[14]), "+f"(d[15]), "+f"(d[16]), "+f"(d[17]), "+f"(d[18]), "+f"(d[19]), "+f"(d[20]), "+f"(d[21]), "+f"(d[22]), "+f"(d[23])
    : "l"(da), "l"(db), "r"(scale_d));
}
__device__ __forceinline__ void wg_ss48_tt(float* d, uint64_t da, uint64_t db, int scale_d) {
  asm volatile("{\n.reg .pred p;\nsetp.ne.b32 p, %26, 0;\n"
    "wgmma.mma_async.sync.aligned.m64n48k16.f32.bf16.bf16 "
    "{%0, %1, %2, %3, %4, %5, %6, %7, %8, %9, %10, %11, %12, %13, %14, %15, %16, %17, %18, %19, %20, %21, %22, %23}, %24, %25, p, 1, 1, 1, 1;\n}\n"
    : "+f"(d[0]), "+f"(d[1]), "+f"(d[2]), "+f"(d[3]), "+f"(d[4]), "+f"(d[5]), "+f"(d[6]), "+f"(d[7]), "+f"(d[8]), "+f"(d[9]), "+f"(d[10]), "+f"(d[11]), "+f"(d[12]), "+f"(d[13]), "+f"(d[14]), "+f"(d[15]), "+f"(d[16]), "+f"(d[17]), "+f"(d[18]), "+f"(d[19]), "+f"(d[20]), "+f"(d[21]), "+f"(d[22]), "+f"(d[23])
    : "l"(da), "l"(db), "r"(scale_d));
}
__device__ __forceinline__ void wg_rs88_tb(float* d, const uint32_t* a, uint64_t db, int scale_d) {
  asm volatile("{\n.reg .pred p;\nsetp.ne.b32 p, %49, 0;\n"
    "wgmma.mma_async.sync.aligned.m64n88k16.f32.bf16.bf16 "
    "{%0, %1, %2, %3, %4, %5, %6, %7, %8, %9, %10, %11, %12, %13, %14, %15, %16, %17, %18, %19, %20, %21, %22, %23, %24, %25, %26, %27, %28, %29, %30, %31, %32, %33, %34, %35, %36, %37, %38, %39, %40, %41, %42, %43}, {%44, %45, %46, %47}, %48, p, 1, 1, 1;\n}\n"
    : "+f"(d[0]), "+f"(d[1]), "+f"(d[2]), "+f"(d[3]), "+f"(d[4]), "+f"(d[5]), "+f"(d[6]), "+f"(d[7]), "+f"(d[8]), "+f"(d[9]), "+f"(d[10]), "+f"(d[11]), "+f"(d[12]), "+f"(d[13]), "+f"(d[14]), "+f"(d[15]), "+f"(d[16]), "+f"(d[17]), "+f"(d[18]), "+f"(d[19]), "+f"(d[20]), "+f"(d[21]), "+f"(d[22]), "+f"(d[23]), "+f"(d[24]), "+f"(d[25]), "+f"(d[26]), "+f"(d[27]), "+f"(d[28]), "+f"(d[29]), "+f"(d[30]), "+f"(d[31]), "+f"(d[32]), "+f"(d[33]), "+f"(d[34]), "+f"(d[35]), "+f"(d[36]), "+f"(d[37]), "+f"(d[38]), "+f"(d[39]), "+f"(d[40]), "+f"(d[41]), "+f"(d[42]), "+f"(d[43])
    : "r"(a[0]), "r"(a[1]), "r"(a[2]), "r"(a[3]), "l"(db), "r"(scale_d));
}
__device__ __forceinline__ void wg_rs64_tb(float* d, const uint32_t* a, uint64_t db, int scale_d) {
  asm volatile("{\n.reg .pred p;\nsetp.ne.b32 p, %37, 0;\n"
    "wgmma.mma_async.sync.aligned.m64n64k16.f32.bf16.bf16 "
    "{%0, %1, %2, %3, %4, %5, %6, %7, %8, %9, %10, %11, %12, %13, %14, %15, %16, %17, %18, %19, %20, %21, %22, %23, %24, %25, %26, %27, %28, %29, %30, %31}, {%32, %33, %34, %35}, %36, p, 1, 1, 1;\n}\n"
    : "+f"(d[0]), "+f"(d[1]), "+f"(d[2]), "+f"(d[3]), "+f"(d[4]), "+f"(d[5]), "+f"(d[6]), "+f"(d[7]), "+f"(d[8]), "+f"(d[9]), "+f"(d[10]), "+f"(d[11]), "+f"(d[12]), "+f"(d[13]), "+f"(d[14]), "+f"(d[15]), "+f"(d[16]), "+f"(d[17]), "+f"(d[18]), "+f"(d[19]), "+f"(d[20]), "+f"(d[21]), "+f"(d[22]), "+f"(d[23]), "+f"(d[24]), "+f"(d[25]), "+f"(d[26]), "+f"(d[27]), "+f"(d[28]), "+f"(d[29]), "+f"(d[30]), "+f"(d[31])
    : "r"(a[0]), "r"(a[1]), "r"(a[2]), "r"(a[3]), "l"(db), "r"(scale_d));
}
__device__ __forceinline__ void wg_rs16_h(float* d, const uint32_t* a, uint64_t db, int scale_d) {
  asm volatile("{\n.reg .pred p;\nsetp.ne.b32 p, %13, 0;\n"
    "wgmma.mma_async.sync.aligned.m64n16k16.f32.f16.f16 "
    "{%0, %1, %2, %3, %4, %5, %6, %7}, {%8, %9, %10, %11}, %12, p, 1, 1, 0;\n}\n"
    : "+f"(d[0]), "+f"(d[1]), "+f"(d[2]), "+f"(d[3]), "+f"(d[4]), "+f"(d[5]), "+f"(d[6]), "+f"(d[7])
    : "r"(a[0]), "r"(a[1]), "r"(a[2]), "r"(a[3]), "l"(db), "r"(scale_d));
}
__device__ __forceinline__ void wg_rs32(float* d, const uint32_t* a, uint64_t db, int scale_d) {
  asm volatile("{\n.reg .pred p;\nsetp.ne.b32 p, %21, 0;\n"
    "wgmma.mma_async.sync.aligned.m64n32k16.f32.bf16.bf16 "
    "{%0, %1, %2, %3, %4, %5, %6, %7, %8, %9, %10, %11, %12, %13, %14, %15}, {%16, %17, %18, %19}, %20, p, 1, 1, 0;\n}\n"
    : "+f"(d[0]), "+f"(d[1]), "+f"(d[2]), "+f"(d[3]), "+f"(d[4]), "+f"(d[5]), "+f"(d[6]), "+f"(d[7]), "+f"(d[8]), "+f"(d[9]), "+f"(d[10]), "+f"(d[11]), "+f"(d[12]), "+f"(d[13]), "+f"(d[14]), "+f"(d[15])
    : "r"(a[0]), "r"(a[1]), "r"(a[2]), "r"(a[3]), "l"(db), "r"(scale_d));
}
__device__ __forceinline__ void wg_rs24_tb(float* d, const uint32_t* a, uint64_t db, int scale_d) {
  asm volatile("{\n.reg .pred p;\nsetp.ne.b32 p, %17, 0;\n"
    "wgmma.mma_async.sync.aligned.m64n24k16.f32.bf16.bf16 "
    "{%0, %1, %2, %3, %4, %5, %6, %7, %8, %9, %10, %11}, {%12, %13, %14, %15}, %16, p, 1, 1, 1;\n}\n"
    : "+f"(d[0]), "+f"(d[1]), "+f"(d[2]), "+f"(d[3]), "+f"(d[4]), "+f"(d[5]), "+f"(d[6]), "+f"(d[7]), "+f"(d[8]), "+f"(d[9]), "+f"(d[10]), "+f"(d[11])
    : "r"(a[0]), "r"(a[1]), "r"(a[2]), "r"(a[3]), "l"(db), "r"(scale_d));
}
__device__ __forceinline__ void wg_rs16_tb(float* d, const uint32_t* a, uint64_t db, int scale_d) {
  asm volatile("{\n.reg .pred p;\nsetp.ne.b32 p, %13, 0;\n"
    "wgmma.mma_async.sync.aligned.m64n16k16.f32.bf16.bf16 "
    "{%0, %1, %2, %3, %4, %5, %6, %7}, {%8, %9, %10, %11}, %12, p, 1, 1, 1;\n}\n"
    : "+f"(d[0]), "+f"(d[1]), "+f"(d[2]), "+f"(d[3]), "+f"(d[4]), "+f"(d[5]), "+f"(d[6]), "+f"(d[7])
    : "r"(a[0]), "r"(a[1]), "r"(a[2]), "r"(a[3]), "l"(db), "r"(scale_d));
}

struct Params {
  const __nv_bfloat16 *logA, *Aim, *Cr, *Ci, *logdt, *dskip;
};

template <bool FWD>
__device__ __forceinline__ void tile_transpose(uint32_t tc0, uint32_t tc1, uint32_t ct0, uint32_t ct1, int hw, int lane) {
  const int mi = lane >> 3, row = lane & 7;
  for (int gi = hw; gi < 40; gi += 3) {
    const int hh = gi / 20, rem = gi - hh * 20, q = rem / 10, cb = rem - q * 10;
    const uint32_t a_tc = (hh ? tc1 : tc0) + (8 * (4 * q + mi) + row) * 160 + cb * 16;
    const uint32_t a_ct = (hh ? ct1 : ct0) + (8 * cb + row) * 128 + (((4 * q + mi) ^ row) << 4);
    uint32_t r[4];
    ldsm4t(r, FWD ? a_tc : a_ct);
    stsm4(FWD ? a_ct : a_tc, r[0], r[1], r[2], r[3]);
  }
}

template <int NS>
__device__ __forceinline__ void load_toep(uint32_t* A, uint32_t addr) {
  uint32_t prev = lds32(addr - 32);
  #pragma unroll
  for (int s = 0; s < NS; s++) {
    uint32_t x = lds32(addr + 64 * s), y = lds32(addr + 64 * s + 32);
    A[4 * s] = x; A[4 * s + 1] = y; A[4 * s + 2] = prev; A[4 * s + 3] = x;
    prev = y;
  }
}

__global__ void __launch_bounds__(512, 1)
fused_kernel(const __grid_constant__ CUtensorMap mx, const __grid_constant__ CUtensorMap mw, const __grid_constant__ CUtensorMap mr,
             const __grid_constant__ CUtensorMap mwo, const __grid_constant__ CUtensorMap mwr, const __grid_constant__ CUtensorMap mo64,
             const __grid_constant__ CUtensorMap mo16, const __grid_constant__ CUtensorMap mu, const __grid_constant__ CUtensorMap msa,
             const __grid_constant__ CUtensorMap msb, const __grid_constant__ CUtensorMap mout, const Params prm) {
  extern __shared__ unsigned char smem_raw[];
  const uint32_t sb = (smem_u32(smem_raw) + 1023) & ~1023u;
  const int tid = threadIdx.x, lane = tid & 31;
  const int wg = __shfl_sync(0xffffffff, tid >> 7, 0), warp = __shfl_sync(0xffffffff, tid >> 5, 0);
  const int cta = blockIdx.x, r = cta >> 3, c = cta & 7;
  const uint32_t bars = sb + OFF_BAR;
#define BAR(i) (bars + 8 * (i))

  auto issue1 = [&](int kb) {
    const uint32_t st = sb + (kb % 5) * W_SLOT, fb = BAR(BR_FULL + kb % 5);
    mbar_expect_tx(fb, (kb & 1) ? W_SLOT : W_SLOT + 16384);
    if (!(kb & 1)) tma2d(sb + OFF_X + ((kb >> 1) % 3) * 16384, &mx, fb, kb * 32, r * 128);
    tma3d(st, &mw, fb, c * 80, kb * 32, 0);
    tma3d(st + 12288, &mr, fb, c * 80 + 64, kb * 32, 0);
  };

  if (warp == 12) {
    if (elect_one()) {
      #pragma unroll
      for (int i = 0; i < BR_COUNT; i++) {
        int cnt = 1;
        if (i >= BR_EMPTY && i < BR_EMPTY + 5) cnt = 2;
        if (i >= BR_OEMPTY && i < BR_OEMPTY + 4) cnt = 8;
        if (i == BR_OSTG) cnt = 256;
        if (i >= BR_DRDY && i < BR_DRDY + 5) cnt = 96;
        if (i >= BR_YSTG && i < BR_YSTG + 5) cnt = 128;
        mbar_init(BAR(i), cnt);
      }
      asm volatile("fence.mbarrier_init.release.cluster;" ::: "memory");
      if (EN_ATT) issue1(0);
    }
  }
  __syncthreads();

  if (wg == 3) {
    asm volatile("setmaxnreg.dec.sync.aligned.u32 56;");
    if (warp == 12) {
      if (EN_ATT) {
      #pragma unroll
      for (int kb = 1; kb < 20; kb++) {
        if (kb >= 5) mbar_wait(BAR(BR_EMPTY + kb % 5), ((kb / 5) & 1) ^ 1);
        if (elect_one()) issue1(kb);
      }
      auto chunk_of = [&](int i) { return i == 0 ? c : (i == 7 ? (c ^ 1) : (((c & 6) + 1 + i) & 7)); };
      mbar_wait(BAR(BR_EPOCH), 0);
      const unsigned epoch = lds32(sb + OFF_EPOCH);
      const unsigned* fo = &g_flag[(24 + r) * 32 + (lane & 7)];
      unsigned seen = __ballot_sync(0xffffffff, ld_rlx(fo) == epoch);
      mbar_wait(BAR(BR_GEMM), 0);
      if (elect_one()) {
        mbar_expect_tx(BAR(BR_WO), 20480 + 5 * 10240);
        #pragma unroll
        for (int i = 0; i < 5; i++) tma2d(sb + OFF_WOM + i * 10240, &mwo, BAR(BR_WO), c * 64, i * 80);
        #pragma unroll
        for (int i = 0; i < 4; i++) tma2d(sb + i * 5120, &mwr, BAR(BR_WO), 512 + c * 16, i * 160);
      }
      mbar_wait(BAR(BR_PUB), 0);
      if (elect_one()) {
        mbar_expect_tx(BAR(BR_WO + 1), 3 * 10240);
        #pragma unroll
        for (int i = 5; i < 8; i++) tma2d(sb + OFF_WOM + i * 10240, &mwo, BAR(BR_WO + 1), c * 64, i * 80);
      }
      mbar_wait(BAR(BR_OSTG), 0);
      if (elect_one()) {
        bulk_st(&g_o[cta * 1280], sb + OFF_EXTRA, 20480);
        bulk_commit();
        bulk_wait0();
        st_rlx(&g_flag[(24 + r) * 32 + c], epoch);
        TS(20);
      }
      __syncwarp();
      #pragma unroll
      for (int i = 0; i < 7; i++) {
        const int src = chunk_of(i + 1);
        if (!((seen >> src) & 1)) seen = poll_bit(fo, epoch, 1u << src);
        if (i < 3) { if (EN_SSM) mbar_wait(BAR(BR_FREE + 4 - i), 0); }
        else if (i > 3) mbar_wait(BAR(BR_OEMPTY + i - 4), 0);
        if (elect_one()) {
          fence_async_g();
          const uint32_t slot = (i & 3) == 3 ? sb + OFF_EXTRA : sb + OFF_BLK + (4 - (i & 3)) * BLK;
          mbar_expect_tx(BAR(BR_OFULL + (i & 3)), 20480);
          bulk_ld(slot, &g_o[(r * 8 + src) * 1280], 20480, BAR(BR_OFULL + (i & 3)));
          if (i == 0) TS(21);
          if (i == 6) { TS(22); DUMP(20, 30); }
        }
        __syncwarp();
      }
      }
    } else {
      const int hw = warp - 13, ht = tid - 416;
      unsigned epoch = 0;
      if (hw == 0) {
        if (lane == 0) {
          if (EN_SSM) {
            mbar_expect_tx(BAR(BR_UIN), 20480);
            tma2d(sb + OFF_BLK + 4 * BLK + B_D, &mu, BAR(BR_UIN), c * 80, r * 128);
            tma2d(sb + OFF_BLK + 3 * BLK + B_D, &mu, BAR(BR_UIN), c * 80, r * 128 + 64);
          }
          epoch = ld_rlx(&g_epoch[cta]) + 1;
          st_rlx(&g_epoch[cta], epoch);
          sts32(sb + OFF_EPOCH, epoch);
          mbar_arrive(BAR(BR_EPOCH));
        }
        epoch = __shfl_sync(0xffffffff, epoch, 0);
      }
      if (EN_SSM) {
      mbar_wait(BAR(BR_UIN), 0);
      {
        const int mi = lane >> 3, rw = lane & 7;
        const uint32_t lo = (uint32_t)((8 * (rw >> 1) + 2 * mi + (rw & 1)) * 160);
        uint4* gp = reinterpret_cast<uint4*>(g_uy + (size_t)(c * 80 + (lane >> 2)) * 2048 + r * 128 + (lane & 3) * 8);
        #pragma unroll
        for (int i = 0; i < 14; i++) {
          const int gi = hw + 3 * i, q = gi & 3, cb = gi >> 2;
          if (gi < 40) {
            uint32_t v[4];
            ldsm4t(v, sb + OFF_BLK + (4 - (q >> 1)) * BLK + B_D + (q & 1) * 5120 + cb * 16 + lo);
            gp[cb * 2048 + q * 4] = make_uint4(v[0], v[1], v[2], v[3]);
          }
        }
      }
      __threadfence();
      bar_sync(5, 96);
      if (hw == 0) {
        if (lane == 0) { st_rlx(&g_flag[(8 + c) * 32 + r], epoch); TS(30); }
        __syncwarp();
        poll_all(&g_flag[(8 + c) * 32 + (lane & 15)], epoch);
        (void)ld_acq(&g_flag[(8 + c) * 32 + (lane & 15)]); __syncwarp();
        if (lane == 0) {
          fence_async_g();
          mbar_expect_tx(BAR(BR_U), 20480);
          #pragma unroll
          for (int k = 4; k >= 0; k--) tma2d(sb + OFF_BLK + k * BLK, &msb, BAR(BR_U), 0, (c * 80 + r * 5 + k) * 32);
          TS(31);
        }
        __syncwarp();
      }
      mbar_wait(BAR(BR_U), 0);
      #pragma unroll 1
      for (int k = 4; k >= 0; k--) {
        if (k == 1) mbar_wait(BAR(BR_KGEN), 0);
        const uint32_t blk = sb + OFF_BLK + k * BLK;
        #pragma unroll 1
        for (int kap = ht; kap < 192; kap += 96) {
          float P[33];
          P[0] = 0.f;
          #pragma unroll
          for (int q = 0; q < 4; q++) {
            const int ch = kap - 3 + q;
            uint32_t v[4];
            lds128(v, blk + (uint32_t)((ch >> 3) * 128 + (((ch & 7) ^ ((ch >> 3) & 7)) << 4)));
            #pragma unroll
            for (int e = 0; e < 4; e++) {
              P[q * 8 + 2 * e + 1] = P[q * 8 + 2 * e] + bf_lo(v[e]);
              P[q * 8 + 2 * e + 2] = P[q * 8 + 2 * e + 1] + bf_hi(v[e]);
            }
          }
#define WIN(lo, hi, e) (P[25 + (e) - (lo)] - P[24 + (e) - (hi)])
#define WIN8(lo, hi) pack2(WIN(lo, hi, 0), WIN(lo, hi, 1)), pack2(WIN(lo, hi, 2), WIN(lo, hi, 3)), pack2(WIN(lo, hi, 4), WIN(lo, hi, 5)), pack2(WIN(lo, hi, 6), WIN(lo, hi, 7))
          sts128(blk + B_D + kap * 16, WIN8(6, 10));
          sts128(blk + B_D + B_D3 + kap * 16, WIN8(3, 5));
          if (kap < 128) {
            const uint32_t o = (kap & 1) * 1024 + (kap >> 1) * 16;
            sts128(blk + B_D + B_D9 + o, WIN8(12, 20));
            sts128(blk + B_D + B_D7 + o, WIN8(5, 11));
          }
        }
        fence_async();
        mbar_arrive(BAR(BR_DRDY + k));
      }
      if (ht == 0) TS(32);
      if (hw == 0) {
        #pragma unroll 1
        for (int k = 4; k >= 0; k--) {
          mbar_wait(BAR(BR_YSTG + k), 0);
          if (lane == 0) {
            tma2d_st(&msb, sb + OFF_BLK + k * BLK, 0, (640 + c * 80 + r * 5 + k) * 32);
            bulk_commit(); bulk_wait0_read();
            mbar_arrive(BAR(BR_FREE + k));
          }
          __syncwarp();
        }
        if (lane == 0) { bulk_wait0(); st_rel(&g_flag[(16 + c) * 32 + r], epoch); TS(33); }
        __syncwarp();
        poll_all(&g_flag[(16 + c) * 32 + (lane & 15)], epoch);
        (void)ld_acq(&g_flag[(16 + c) * 32 + (lane & 15)]); __syncwarp();
        if (lane == 0) {
          fence_async_g();
          mbar_expect_tx(BAR(BR_YIN), 20480);
          tma2d(sb + OFF_BLK + BLK, &msa, BAR(BR_YIN), r * 128, 640 + c * 80);
          tma2d(sb + OFF_BLK + BLK + 10240, &msa, BAR(BR_YIN), r * 128 + 64, 640 + c * 80);
          TS(34);
        }
        __syncwarp();
      }
      mbar_wait(BAR(BR_YIN), 0);
      tile_transpose<false>(sb + OFF_BLK, sb + OFF_BLK + 10240, sb + OFF_BLK + BLK, sb + OFF_BLK + BLK + 10240, hw, lane);
      fence_async();
      bar_sync(5, 96);
      if (ht == 0) {
        tma2d_st(&mout, sb + OFF_BLK, c * 80, r * 128);
        tma2d_st(&mout, sb + OFF_BLK + 10240, c * 80, r * 128 + 64);
        bulk_commit(); bulk_wait0_read();
        TS(35); DUMP(30, 40); DUMP(0, 1);
      }
      }
    }
  } else if (wg < 2) {
    asm volatile("setmaxnreg.inc.sync.aligned.u32 152;");
    if (EN_ATT) {
    const int w4 = warp & 3, g = lane >> 2, tq = lane & 3, t7 = tid & 127;
    float am[96], ar[24];
    {
      const uint64_t da0 = mkdesc(sb + OFF_X + wg * 8192, 16, 1024, 1);
      const uint64_t db0 = mkdesc(sb, 4096, 1024, 1);
      const uint64_t dr0 = mkdesc(sb + 12288, 1024, 256, 3);
      uint32_t s = 0, ph = 0, xo = 0;
      #pragma unroll 1
      for (int kb = 0; kb < 20; kb++) {
        mbar_wait(BAR(BR_FULL) + 8 * s, ph);
        if (kb == 0 && tid == 0) TS(1);
        wg_fence();
        const uint32_t wo_ = s * (W_SLOT >> 4);
        wg_ss192_tb(am, da0 + xo, db0 + wo_, kb != 0);
        wg_ss48_tb(ar, da0 + xo, dr0 + wo_, kb != 0);
        wg_ss192_tb(am, da0 + xo + 2, db0 + wo_ + 128, 1);
        wg_ss48_tb(ar, da0 + xo + 2, dr0 + wo_ + 32, 1);
        wg_commit();
        wg_wait<1>();
        if (t7 == 0 && kb > 0 && kb < 16) mbar_arrive(BAR(BR_EMPTY) + 8 * (s == 0 ? 4 : s - 1));
        if (++s == 5) { s = 0; ph ^= 1; }
        xo += (kb & 1) ? 1020 : 4;
        if (xo == 3072) xo = 0;
      }
      wg_wait<0>();
      pin<96>(am); pin<24>(ar);
    }
    if (tid == 0) TS(2);
#define QV(j, e) ((j) < 8 ? am[4 * (j) + (e)] : ar[4 * ((j) - 8) + (e)])
#define KV_(j, e) ((j) < 8 ? am[32 + 4 * (j) + (e)] : ar[8 + 4 * ((j) - 8) + (e)])
#define VV(j, e) ((j) < 8 ? am[64 + 4 * (j) + (e)] : ar[16 + 4 * ((j) - 8) + (e)])
    {
      bar_sync(1, 256);
      if (tid == 0) mbar_arrive(BAR(BR_GEMM));
      const uint32_t ro = (uint32_t)((lane >> 4) * 2048 + (wg * 64 + w4 * 16 + (lane & 15)) * 16);
      const uint32_t ones = (tq == 0) ? 0x00003f80u : 0u;
#define PV(j) pack2(VV(j, 0), VV(j, 1)), pack2(VV(j, 2), VV(j, 3))
#define PK(j) pack2(phi(KV_(j, 0)), phi(KV_(j, 1))), pack2(phi(KV_(j, 2)), phi(KV_(j, 3)))
      stsm4(sb + OFF_V + 0 * 2048 + ro, PV(0), PV(1));
      stsm4(sb + OFF_V + 2 * 2048 + ro, PV(2), PV(3));
      stsm4(sb + OFF_V + 4 * 2048 + ro, PV(4), ones, ones);
      stsm4(sb + OFF_V + 6 * 2048 + ro, PV(5), PV(6));
      stsm4(sb + OFF_V + 8 * 2048 + ro, PV(7), PV(8));
      stsm4(sb + OFF_V + 10 * 2048 + ro, PV(9), ones, ones);
      #pragma unroll
      for (int j = 0; j < 10; j += 2) stsm4(sb + OFF_PK + j * 2048 + ro, PK(j), PK(j + 1));
    }
    fence_async();
    bar_sync(1, 256);
    if (tid == 0) TS(3);
    mbar_wait(BAR(BR_EPOCH), 0);
    const unsigned epoch = lds32(sb + OFF_EPOCH);
    {
      float kv[24]; zero<24>(kv);
      const uint64_t da = mkdesc(sb + OFF_PK + wg * 5 * 2048, 128, 2048, 0);
      const uint64_t db = mkdesc(sb + OFF_V + wg * 6 * 2048, 128, 2048, 0);
      wg_fence();
      #pragma unroll
      for (int s = 0; s < 8; s++) wg_ss48_tt(kv, da + s * 16, db + s * 16, s != 0);
      wg_commit();
      wg_wait<0>();
      pin<24>(kv);
      if (tid == 0) TS(15);
      if (w4 < 3) {
        const uint32_t wb = sb + OFF_KVS + (wg * 3 + w4) * 1536;
        #pragma unroll
        for (int j = 0; j < 6; j += 2)
          stsm4(wb + (lane & 15) * 96 + (j + (lane >> 4)) * 16, pack2(kv[4 * j], kv[4 * j + 1]), pack2(kv[4 * j + 2], kv[4 * j + 3]),
                pack2(kv[4 * j + 4], kv[4 * j + 5]), pack2(kv[4 * j + 6], kv[4 * j + 7]));
        __syncwarp();
        const int dl = w4 * 16 + (lane & 15), hl = dl >= 20;
        if (dl < 40) {
          uint4* dst = &g_kvp[(c * 16 + r) * 240 + wg * 40 + dl];
          uint32_t v[4];
          lds128(v, wb + (lane & 15) * 96 + (3 * hl + (lane >> 4)) * 16);
          v[3] = (v[3] & ~1u) | (epoch & 1u);
          st128_rlx(dst + (lane >> 4) * 80, v);
          if (lane < 16) {
            v[0] = lds32(wb + lane * 96 + 32 + 8 * hl); v[1] = lds32(wb + lane * 96 + 36 + 8 * hl);
            v[2] = lds32(wb + lane * 96 + 80); v[3] = epoch & 1u;
            st128_rlx(dst + 160, v);
          }
        }
      }
    }
    bar_sync(1, 256);
    if (tid == 0) { st_rlx(&g_flag[c * 32 + r], epoch); mbar_arrive(BAR(BR_PUB)); TS(4); }
    const int kd = tid >= 160 ? tid - 160 : (tid >= 80 ? tid - 80 : tid), kvi = (tid >= 80) + (tid >= 160);
    const int khd = kd / 20, kt0 = 5 * (khd >> 1) + 2 * (khd & 1);
    if (tid < 240) {
      #pragma unroll
      for (int m = 0; m < 3; m++) {
        int q = kt0 + 3 + kvi + 3 * m; if (q >= 10) q -= 10;
        if (kvi + 3 * m < 7) sts128(sb + OFF_KVB + q * 1280 + kd * 16, 0, 0, 0, 0);
      }
    }
    uint32_t qa[20];
    {
      const float sc = 1.44269504089f + __uint_as_float(lds32(sb + OFF_EPOCH) ^ epoch);
      #pragma unroll
      for (int j = 0; j < 10; j++) { qa[2 * j] = pack2(phi(QV(j, 0), sc), phi(QV(j, 1), sc)); qa[2 * j + 1] = pack2(phi(QV(j, 2), sc), phi(QV(j, 3), sc)); }
    }
    if (tid == 0) TS(5);
    {
      poll_all(&g_flag[c * 32 + (lane & 15)], epoch);
      if (tid == 0) TS(6);
      if (tid < 240) {
        uint32_t v[16][4];
        const uint4* src = &g_kvp[c * 16 * 240 + tid];
        #pragma unroll
        for (int i = 0; i < 16; i++) ld128_rlx(v[i], src + i * 240);
        float s[8];
        uint32_t bad = 0;
        #pragma unroll
        for (int i = 0; i < 16; i++) {
          bad |= v[i][3] ^ epoch;
          #pragma unroll
          for (int e = 0; e < 4; e++) {
            s[2 * e] = i ? s[2 * e] + bf_lo(v[i][e]) : bf_lo(v[i][e]);
            s[2 * e + 1] = i ? s[2 * e + 1] + bf_hi(v[i][e]) : bf_hi(v[i][e]);
          }
        }
        if (__builtin_expect(bad & 1u, 0)) {
          #pragma unroll
          for (int e = 0; e < 8; e++) s[e] = 0.f;
          #pragma unroll 1
          for (int i = 0; i < 16; i++) {
            uint32_t w[4] = {0, 0, 0, ~epoch};
            fix128_w3(w, src + i * 240, epoch, 1u);
            #pragma unroll
            for (int e = 0; e < 4; e++) { s[2 * e] += bf_lo(w[e]); s[2 * e + 1] += bf_hi(w[e]); }
          }
        }
        if (tid == 0) TS(18);
        const uint32_t p0 = pack2(s[0], s[1]), p1 = pack2(s[2], s[3]), p2 = pack2(s[4], s[5]), p3 = pack2(s[6], s[7]);
        const uint32_t rb = sb + OFF_KVB + kd * 16;
        if (kvi < 2) sts128(rb + (kt0 + (khd & 1) + kvi) * 1280, p0, p1, p2, p3);
        else {
          const bool od = khd & 1;
          sts128(rb + (5 * (khd >> 1) + 2) * 1280, od ? 0u : p0, od ? 0u : p1, od ? p0 : 0u, od ? p1 : 0u);
          const uint32_t zz = (p2 & 0xffffu) << (16 * (khd & 1));
          sts128(rb + 10 * 1280, khd < 2 ? zz : 0u, khd < 2 ? 0u : zz, 0u, 0u);
        }
      }
    }
    fence_async();
    bar_sync(1, 256);
    if (tid == 0) TS(7);
    uint32_t A0[20], A1[20];
    {
      float oa[44]; zero<44>(oa);
      const uint64_t db = mkdesc(sb + OFF_KVB, 128, 1280, 0);
      wg_fence();
      #pragma unroll
      for (int s = 0; s < 5; s++) wg_rs88_tb(oa, &qa[4 * s], db + s * 16, s != 0);
      wg_commit();
      if (tid == 0) TS(12);
      wg_wait<0>();
      pin<44>(oa);
      if (tid == 0) TS(13);
      float rc[4], rd[2][4];
      #pragma unroll
      for (int e = 0; e < 4; e++) rc[e] = __fdividef(1.f, oa[40 + e] + 1e-6f);
      #pragma unroll
      for (int h = 0; h < 4; h++) {
        rd[0][h] = __shfl_sync(0xffffffff, rc[h & 1], (lane & 28) | (h >> 1));
        rd[1][h] = __shfl_sync(0xffffffff, rc[2 + (h & 1)], (lane & 28) | (h >> 1));
      }
      #pragma unroll
      for (int j = 0; j < 10; j++) {
        #pragma unroll
        for (int h = 0; h < 2; h++) {
          float f;
          if (j == 2) f = tq < 2 ? rd[h][0] : rd[h][1];
          else if (j == 7) f = tq < 2 ? rd[h][2] : rd[h][3];
          else f = rd[h][(8 * j) / 20];
          A0[2 * j + h] = pack2(oa[4 * j + 2 * h] * f, oa[4 * j + 2 * h + 1] * f);
        }
      }
      bar_sync(1, 256);
      #pragma unroll
      for (int s = 0; s < 5; s++) {
        A0[4 * s] = (A0[4 * s] & ~1u) | (epoch & 1u);
        sts128(sb + OFF_EXTRA + ((wg * 5 + s) * 128 + t7) * 16, A0[4 * s], A0[4 * s + 1], A0[4 * s + 2], A0[4 * s + 3]);
      }
    }
    if (tid == 0) TS(14);
    fence_async();
    mbar_arrive(BAR(BR_OSTG));
    if (tid == 0) TS(8);
    float oc[32], od[8]; zero<32>(oc); zero<8>(od);
    {
      const uint64_t dw0 = mkdesc(sb + OFF_WOM, 16, 1024, 1), dr0 = mkdesc(sb, 16, 256, 3);
      mbar_wait(BAR(BR_WO), 0);
      mbar_wait(BAR(BR_WO + 1), 0);
      wg_fence();
      #pragma unroll
      for (int s = 0; s < 5; s++) { wg_rs64_tb(oc, &A0[4 * s], dw0 + c * 640 + s * 128, s != 0); wg_rs16_tb(od, &A0[4 * s], dr0 + c * 160 + s * 32, s != 0); }
      wg_commit();
      #pragma unroll
      for (int i = 0; i < 7; i++) {
        uint32_t* A = (i & 1) ? A0 : A1;
        const uint32_t slot = (i & 3) == 3 ? sb + OFF_EXTRA : sb + OFF_BLK + (4 - (i & 3)) * BLK;
        const int src = (i == 6) ? (c ^ 1) : (((c & 6) + 2 + i) & 7);
        mbar_wait(BAR(BR_OFULL + (i & 3)), i >> 2);
        if (i == 0 && tid == 0) TS(9);
        if (i > 0) wg_wait<1>();
        #pragma unroll
        for (int s = 0; s < 5; s++) lds128(&A[4 * s], slot + ((wg * 5 + s) * 128 + t7) * 16);
        uint32_t bad = 0;
        #pragma unroll
        for (int s = 0; s < 5; s++) bad |= A[4 * s] ^ epoch;
        if (__builtin_expect(bad & 1u, 0)) {
          #pragma unroll
          for (int s = 0; s < 5; s++) fix128_w0(&A[4 * s], &g_o[(r * 8 + src) * 1280 + (wg * 5 + s) * 128 + t7], epoch, 1u);
        }
        __syncwarp();
        if (i < 3 && lane == 0) mbar_arrive(BAR(BR_OEMPTY + i));
        wg_fence();
        #pragma unroll
        for (int s = 0; s < 5; s++) { wg_rs64_tb(oc, &A[4 * s], dw0 + src * 640 + s * 128, 1); wg_rs16_tb(od, &A[4 * s], dr0 + src * 160 + s * 32, 1); }
        wg_commit();
      }
      bar_sync(2 + wg, 128);
      wg_wait<0>();
      pin<32>(oc); pin<8>(od);
    }
    if (tid == 0) TS(10);
    {
      const int row = w4 * 16 + (lane & 15);
      const uint32_t ob = sb + OFF_EXTRA + wg * 10240;
      #pragma unroll
      for (int j = 0; j < 8; j += 2)
        stsm4(ob + row * 128 + (((j + (lane >> 4)) ^ (row & 7)) << 4), pack2(oc[4 * j], oc[4 * j + 1]), pack2(oc[4 * j + 2], oc[4 * j + 3]),
              pack2(oc[4 * j + 4], oc[4 * j + 5]), pack2(oc[4 * j + 6], oc[4 * j + 7]));
      stsm4(ob + 8192 + row * 32 + (lane >> 4) * 16, pack2(od[0], od[1]), pack2(od[2], od[3]), pack2(od[4], od[5]), pack2(od[6], od[7]));
      fence_async();
      bar_sync(2 + wg, 128);
      if (t7 == 0) {
        tma2d_st(&mo64, ob, 640 + c * 64, r * 128 + wg * 64);
        tma2d_st(&mo16, ob + 8192, 1152 + c * 16, r * 128 + wg * 64);
        bulk_commit(); bulk_wait0_read();
      }
      if (tid == 0) { TS(11); DUMP(0, 20); }
    }
    }
  } else {
    asm volatile("setmaxnreg.inc.sync.aligned.u32 152;");
    if (EN_SSM) {
    const int w4 = warp & 3, g = lane >> 2, tq = lane & 3, t7 = tid & 127;
    const int d0 = c * 80 + r * 5;
    {
      uint32_t pa[5], pc[5];
      #pragma unroll
      for (int k = 0; k < 5; k++) {
        const int o = (d0 + k) * 128 + t7;
        pa[k] = (uint32_t)__bfloat16_as_ushort(prm.logA[o]) | ((uint32_t)__bfloat16_as_ushort(prm.Aim[o]) << 16);
        pc[k] = (uint32_t)__bfloat16_as_ushort(prm.Cr[o]) | ((uint32_t)__bfloat16_as_ushort(prm.Ci[o]) << 16);
      }
      float ldt = 0.f, dsk = 0.f;
      if (t7 < 5) { ldt = __bfloat162float(prm.logdt[d0 + t7]); dsk = __bfloat162float(prm.dskip[d0 + t7]); }
      #pragma unroll
      for (int k = 0; k < 5; k++) {
        const uint32_t tz = sb + OFF_BLK + k * BLK + B_TBL;
        if (t7 < 32) sts128(tz + t7 * 16, 0, 0, 0, 0);
        if (t7 >= 96) sts128(tz + t7 * 16, 0, 0, 0, 0);
        sts128(tz + 2048 + t7 * 16, 0, 0, 0, 0);
        if (t7 < 21 || t7 >= 56) sts128(tz + 4096 + t7 * 16, 0, 0, 0, 0);
      }
      if (t7 < 72) sts128(sb + OFF_BLK - 1152 + t7 * 16, 0, 0, 0, 0);
      #pragma unroll
      for (int k = 0; k < 5; k++) {
        sts64(sb + OFF_BLK + k * BLK + B_TBL + 512 + t7 * 8, pa[k], pc[k]);
        const uint32_t m = __reduce_max_sync(0xffffffff, max(pc[k] & 0x7fffu, (pc[k] >> 16) & 0x7fffu));
        if (lane == 0) sts32(sb + OFF_BLK + k * BLK + B_SP + 16 + w4 * 4, m);
      }
      if (t7 < 5) sts64(sb + OFF_BLK + t7 * BLK + B_SP + 8, __float_as_uint(bf_round(expf(ldt))), __float_as_uint(dsk));
    }
    bar_sync(4, 128);
    if (t7 == 0) TS(40);
    {
      const uint32_t kg = sb + OFF_BLK + B_D, kx = sb + OFF_BLK + BLK + B_D, kz = kx + 4608, ky = kz + 4096;
      const uint64_t dg = mkdesc(kg, 208, 128, 0);
      #pragma unroll 1
      for (int k = 4; k >= 0; k--) {
        const uint32_t blk = sb + OFF_BLK + k * BLK;
        float fac, dsk;
        {
          const int tt = opaque(t7);
          uint32_t p[2], q[2], mm[4];
          lds64(p, blk + B_TBL + 512 + tt * 8); lds64(q, blk + B_SP + 8); lds128(mm, blk + B_SP + 16);
          const float dt = __uint_as_float(q[0]); dsk = __uint_as_float(q[1]);
          const uint32_t ex = min(max(max(max(mm[0], mm[1]), max(mm[2], mm[3])) >> 7, 1u), 253u);
          const float sc = __uint_as_float((254u - ex) << 23);
          fac = 2.f * dt * __uint_as_float(ex << 23);
          const float lr = -bf_round(expf(bf_lo(p[0]))) * dt * 1.44269504089f;
          const float tn = bf_hi(p[0]) * dt * 0.15915494309f;
          float z1r, z1i, z2r, z2i, z4r, z4i, xr[8], xi[8], yr, yi, gr[8], gi[8];
          cexp_t(lr, tn, z1r, z1i);
          cexp_t(lr * 8.f, tn * 8.f, xr[1], xi[1]);
          cexp_t(lr * 64.f, tn * 64.f, yr, yi);
          gr[0] = bf_lo(p[1]) * sc; gi[0] = bf_hi(p[1]) * sc;
          cmul(z1r, z1i, z1r, z1i, z2r, z2i); cmul(z2r, z2i, z2r, z2i, z4r, z4i);
          cmul(gr[0], gi[0], z1r, z1i, gr[1], gi[1]);
          cmul(gr[0], gi[0], z2r, z2i, gr[2], gi[2]); cmul(gr[1], gi[1], z2r, z2i, gr[3], gi[3]);
          #pragma unroll
          for (int b = 0; b < 4; b++) cmul(gr[b], gi[b], z4r, z4i, gr[4 + b], gi[4 + b]);
          cmul(xr[1], xi[1], xr[1], xi[1], xr[2], xi[2]); cmul(xr[2], xi[2], xr[1], xi[1], xr[3], xi[3]);
          cmul(xr[2], xi[2], xr[2], xi[2], xr[4], xi[4]);
          #pragma unroll
          for (int b = 1; b < 4; b++) cmul(xr[4], xi[4], xr[b], xi[b], xr[4 + b], xi[4 + b]);
          float w1r, w1i, w2r, w2i, w3r, w3i, hr, hi_, h2r, h2i, ar_, ai_, br_, bi_;
          cmul(yr, yi, yr, yi, w1r, w1i); cmul(w1r, w1i, w1r, w1i, w2r, w2i); cmul(w2r, w2i, w1r, w1i, w3r, w3i);
          cmul(w2r, w2i, w2r, w2i, hr, hi_); cmul(hr, hi_, hr, hi_, h2r, h2i);
          const uint32_t ga = kg + (tt >> 2) * 208 + (tt & 3) * 4;
          #pragma unroll
          for (int b = 0; b < 8; b++) sts32(ga + b * 16, packh(gr[b], -gi[b]));
          cmul(gr[0], gi[0], hr, hi_, ar_, ai_);   sts32(ga + 8 * 16, packh(ar_, -ai_));
          cmul(gr[4], gi[4], hr, hi_, br_, bi_);   sts32(ga + 9 * 16, packh(br_, -bi_));
          cmul(gr[0], gi[0], h2r, h2i, br_, bi_);  sts32(ga + 10 * 16, packh(br_, -bi_));
          cmul(ar_, ai_, h2r, h2i, ar_, ai_);      sts32(ga + 11 * 16, packh(ar_, -ai_));
          cmul(br_, bi_, h2r, h2i, br_, bi_);      sts32(ga + 12 * 16, packh(br_, -bi_));
          const uint32_t xa = kx + (tt & 3) * 144 + (tt >> 2) * 4;
          sts32(xa, 0x00003c00u);
          #pragma unroll
          for (int b = 1; b < 8; b++) sts32(xa + b * 576, packh(xr[b], xi[b]));
          const uint32_t zo = (uint32_t)((tt >> 3) * 64 + (tt & 3) * 16 + ((tt >> 2) & 1) * 8);
          sts64(kz + zo, 0x00003c00u, 0x3c000000u);
          sts64(kz + 1024 + zo, packh(w1r, w1i), packh(-w1i, w1r));
          sts64(kz + 2048 + zo, packh(w2r, w2i), packh(-w2i, w2r));
          sts64(kz + 3072 + zo, packh(w3r, w3i), packh(-w3i, w3r));
          sts64(ky + zo, packh(yr, yi), packh(-yi, yr));
        }
        fence_async();
        bar_sync(4, 128);
        if (t7 == 0 && k == 3) TS(50);
        uint32_t A[64];
        {
          const int ln = opaque(lane);
          const uint32_t xa = kx + ln * 144, za = kz + w4 * 1024 + (ln & 3) * 16, ya = ky + (ln & 3) * 16;
          #pragma unroll
          for (int s2 = 0; s2 < 8; s2++) {
            uint32_t x[4];
            lds128(x, xa + s2 * 16);
            #pragma unroll
            for (int u = 0; u < 2; u++) {
              const int s = 2 * s2 + u;
              uint32_t z[4], y[4];
              lds128(z, za + s * 64); lds128(y, ya + s * 64);
              A[4 * s] = hcmul(x[2 * u], z[0], z[1]);         A[4 * s + 1] = hcmul(A[4 * s], y[0], y[1]);
              A[4 * s + 2] = hcmul(x[2 * u + 1], z[2], z[3]); A[4 * s + 3] = hcmul(A[4 * s + 2], y[2], y[3]);
            }
          }
        }
        float ka[8]; zero<8>(ka);
        wg_fence();
        if (t7 == 0 && k == 3) TS(51);
        #pragma unroll
        for (int s = 0; s < 16; s++) wg_rs16_h(ka, &A[4 * s], dg + s * 26, s != 0);
        wg_commit();
        wg_wait<0>();
        pin<8>(ka);
        if (t7 == 0 && k == 3) TS(52);
        bar_sync(4, 128);
        {
          const int ln = opaque(lane), tt = ln & 3;
          const uint32_t tb = blk + B_TBL;
          #pragma unroll
          for (int e = 0; e < 8; e++) ka[e] *= fac;
          if (t7 == 0) ka[0] += dsk;
          #pragma unroll
          for (int h = 0; h < 2; h++) {
            const int j = w4 * 16 + (ln >> 2) + 8 * h;
            const uint32_t pa_ = tb + (64 + 8 * j + 2 * tt) * 4;
            const uint32_t v = pack2(ka[2 * h + 1], ka[2 * h]);
            if (w4 < 2) { sts32(pa_ + 4, v); sts16(pa_, v >> 16); sts16(pa_ + 10, v); }
            else {
              sts16(pa_, v >> 16); sts16(pa_ + 6, v >> 16);
              if (!(tt & 1)) {
                sts16(pa_ + 4, v >> 16); sts16(pa_ + 10, v >> 16);
                if (j != 32 || tt) { sts16(pa_ - 4, v >> 16); sts16(pa_ + 2, v >> 16); }
              }
            }
            const uint32_t u = pack2(ka[4 + 2 * h], ka[5 + 2 * h]);
            int ea = tt == 0 ? 655 + j : ((j & 1) ? 1040 + (j >> 1) : 911 + (j >> 1));
            const int eb = tt == 0 ? 784 + j : ea + 32;
            if (h == 0 && j == 0) ea = tt == 0 ? 64 + 511 : (tt == 1 ? 719 : 975);
            if (tt < 2 || (h == 0 && j == 0 && tt == 2)) { sts16(tb + ea * 4, u); sts16(tb + ea * 4 + 6, u); }
            if (tt < 2) { sts16(tb + eb * 4, u >> 16); sts16(tb + eb * 4 + 6, u >> 16); }
            if (h == 0 && j == 0) {
              if (tt == 0) { const uint32_t uu = (u & 0xffffu) * 0x10001u; sts32(tb + 576 * 4, uu); sts32(tb + 577 * 4, uu); sts32(tb + 578 * 4, uu); sts16(tb + 579 * 4 + 2, u); }
              if (tt == 1) sts32(blk + B_SP, u << 16);
            }
          }
        }
        if (t7 == 0 && k == 3) TS(53);
      }
      bar_sync(4, 128);
      if (t7 == 0) { mbar_arrive(BAR(BR_KGEN)); TS(41); }
    }
    mbar_wait(BAR(BR_U), 0);
    if (EN_ATT) mbar_wait(BAR(BR_GEMM), 0);
    if (t7 == 0) TS(42);
    const uint32_t lb = (uint32_t)((16 * w4 + g - 2 * tq - 48) * 4);
    float yv[16];
    zero<16>(yv);
    uint32_t A0[20], A1[16], A2[16];
    load_toep<4>(A0, sb + OFF_BLK + 4 * BLK + B_TBL + lb + 912 * 4);
    auto y_epilogue = [&](uint32_t blk, int k) {
      const int ln = opaque(lane), tt = ln & 3;
      const uint32_t b0 = (128 * tt + ((16 * w4) ^ (8 * tt)) + (ln >> 2)) * 4;
      #pragma unroll
      for (int n = 1; n < 4; n++)
        #pragma unroll
        for (int e = 0; e < 4; e++) {
          const uint32_t a = blk + B_D + (b0 ^ (32 * (e >> 1))) + (512 * (n - 1) + 64 * (e & 1)) * 4;
          yv[4 * n + e] += ldsf(a);
          if (n >= 2) yv[4 * n + e] += ldsf(a + 6144 - 2048);
        }
      const uint32_t ya = blk + (8 * (ln >> 4) + (ln & 7)) * 128 + (((2 * w4 + ((ln >> 3) & 1)) ^ (ln & 7)) << 4);
      #pragma unroll
      for (int n = 0; n < 4; n += 2)
        stsm4t(ya + n * 1024, pack2(yv[4 * n], yv[4 * n + 1]), pack2(yv[4 * n + 2], yv[4 * n + 3]),
               pack2(yv[4 * n + 4], yv[4 * n + 5]), pack2(yv[4 * n + 6], yv[4 * n + 7]));
      fence_async();
      mbar_arrive(BAR(BR_YSTG) + 8 * k);
      if (t7 == 0) TS(47 - k);
    };
    #pragma unroll 1
    for (int k = 4; k >= 0; k--) {
      const uint32_t blk = sb + OFF_BLK + k * BLK, tb = blk + B_TBL + lb;
      const uint64_t dd = mkdesc(blk + B_D, 128, 1024, 0);
      const uint64_t du = mkdesc(blk + 96 - 32 * 36, 16, 1024, 1);
      float aC[8], a24[12], a16[8], aY[16];
      zero<8>(aC); zero<12>(a24); zero<8>(a16); zero<16>(aY);
      mbar_wait(BAR(BR_DRDY) + 8 * k, 0);
      if (t7 == 0 && k == 3) TS(57);
#define GRP_BEGIN wg_wait<1>(); wg_fence();
#define FAR4(fn, acc, A, off, first) _Pragma("unroll") for (int s = 0; s < 4; s++) fn(acc, &A[4 * s], dd + ((off) >> 4) + (3 - s) * 16, !(first) || s != 0);
#define DEN(A, n, s0) _Pragma("unroll") for (int s = 0; s < (n); s++) wg_rs32(aY, &A[4 * s], du + (36 - ((s0) + s)) * 2, (s0) + s != 0);
      GRP_BEGIN load_toep<4>(A1, tb + 1040 * 4);      FAR4(wg_rs16_tb, aC, A0, B_D9, true)   wg_commit();
      GRP_BEGIN load_toep<4>(A2, tb + 656 * 4);       FAR4(wg_rs16_tb, aC, A1, B_D7, false)  wg_commit();
      if (k < 4) { bar_sync(4, 128); y_epilogue(blk + BLK, k + 1); }
      GRP_BEGIN load_toep<4>(A0, tb + 720 * 4);       FAR4(wg_rs24_tb, a24, A2, 0, true)     wg_commit();
      GRP_BEGIN load_toep<4>(A1, tb + 784 * 4);       FAR4(wg_rs16_tb, a16, A0, 0, true)     wg_commit();
      GRP_BEGIN load_toep<4>(A2, tb + 848 * 4);       FAR4(wg_rs24_tb, a24, A1, B_D3, false) wg_commit();
      GRP_BEGIN load_toep<5>(A0, tb + 64 * 4);        FAR4(wg_rs16_tb, a16, A2, B_D3, false) wg_commit();
      if (t7 == 0 && k == 3) TS(58);
      GRP_BEGIN load_toep<4>(A1, tb + (64 + 80) * 4);  DEN(A0, 5, 0)  wg_commit();
      GRP_BEGIN load_toep<4>(A2, tb + (64 + 144) * 4); DEN(A1, 4, 5)  wg_commit();
      if (t7 == 0 && k == 3) TS(59);
      {
        pin<8>(aC); pin<12>(a24); pin<8>(a16);
        bar_sync(4, 128);
        const float kc = ldsf(blk + B_SP);
        const int ln = opaque(lane), gg = ln >> 2, q2 = (ln & 3) * 2;
        const uint32_t f1 = blk + B_D + (128 * w4 + ((8 * gg) ^ (8 * w4)) + q2) * 4;
        const uint32_t f2 = blk + B_D + 6144 + (256 * w4 + ((16 * gg) ^ (16 * (w4 & 1))) + q2) * 4;
        #pragma unroll
        for (int h = 0; h < 2; h++) {
          #pragma unroll
          for (int jp = 0; jp < 3; jp++) {
            float x = a24[4 * jp + 2 * h], y = a24[4 * jp + 2 * h + 1];
            if (jp > 0) { x += a16[4 * (jp - 1) + 2 * h]; y += a16[4 * (jp - 1) + 2 * h + 1]; }
            sts64f(f1 + (64 * h + 512 * jp) * 4, x, y);
          }
          #pragma unroll
          for (int n = 0; n < 2; n++) {
            const int s4 = 256 * w4 + 16 * gg + 128 * h + 8 * n + q2 - 4, s2 = s4 + 2;
            const uint32_t u4 = lds32(blk + (uint32_t)((2 * s4) ^ ((s4 >> 2) & 0x70)));
            const uint32_t u2 = lds32(blk + (uint32_t)((2 * s2) ^ ((s2 >> 2) & 0x70)));
            const float x = fmaf(kc, bf_lo(u4) + bf_hi(u4), aC[4 * n + 2 * h]);
            const float y = fmaf(kc, bf_hi(u4) + bf_lo(u2), aC[4 * n + 2 * h + 1]);
            sts64f(f2 + (128 * h + 8 * (n ^ h)) * 4, x, y);
          }
        }
      }
      if (t7 == 0 && k == 3) TS(60);
      GRP_BEGIN load_toep<4>(A0, tb + (64 + 208) * 4); DEN(A2, 4, 9)  wg_commit();
      GRP_BEGIN load_toep<4>(A1, tb + (64 + 272) * 4); DEN(A0, 4, 13) wg_commit();
      GRP_BEGIN load_toep<4>(A2, tb + (64 + 336) * 4); DEN(A1, 4, 17) wg_commit();
      GRP_BEGIN load_toep<4>(A0, tb + (64 + 400) * 4); DEN(A2, 4, 21) wg_commit();
      GRP_BEGIN load_toep<4>(A1, tb + (64 + 464) * 4); DEN(A0, 4, 25) wg_commit();
      GRP_BEGIN load_toep<4>(A2, tb + (64 + 528) * 4); DEN(A1, 4, 29) wg_commit();
      GRP_BEGIN load_toep<4>(A0, tb - (k ? BLK : 0) + 912 * 4); DEN(A2, 4, 33) wg_commit();
      if (t7 == 0 && k == 3) TS(61);
      wg_wait<0>();
      pin<16>(aY);
      #pragma unroll
      for (int e = 0; e < 16; e++) yv[e] = aY[e];
    }
    bar_sync(4, 128);
    y_epilogue(sb + OFF_BLK, 0);
    if (t7 == 0) DUMP(40, 64);
    }
  }
}

typedef CUresult (*EncFn)(CUtensorMap*, CUtensorMapDataType, cuuint32_t, void*, const cuuint64_t*, const cuuint64_t*, const cuuint32_t*,
                          const cuuint32_t*, CUtensorMapInterleave, CUtensorMapSwizzle, CUtensorMapL2promotion, CUtensorMapFloatOOBfill);
static CUtensorMap mkmap(EncFn enc, const void* base, int rank, const cuuint64_t* dims, const cuuint64_t* strides, const cuuint32_t* box, CUtensorMapSwizzle swz) {
  CUtensorMap m; cuuint32_t es[5] = {1, 1, 1, 1, 1};
  enc(&m, CU_TENSOR_MAP_DATA_TYPE_BFLOAT16, rank, const_cast<void*>(base), dims, strides, box, es, CU_TENSOR_MAP_INTERLEAVE_NONE, swz,
      CU_TENSOR_MAP_L2_PROMOTION_L2_128B, CU_TENSOR_MAP_FLOAT_OOB_FILL_NONE);
  return m;
}

extern "C" void kernel_launch(void* const* d_in, const int* in_sizes, int n_in, void* d_out, int out_size) {
  void* fn = nullptr; cudaDriverEntryPointQueryResult qr;
  cudaGetDriverEntryPoint("cuTensorMapEncodeTiled", &fn, cudaEnableDefault, &qr);
  EncFn enc = (EncFn)fn;
  void* uy = nullptr; cudaGetSymbolAddress(&uy, g_uy);
  const cuuint64_t dx[2] = {640, 2048}, sx[1] = {1280};
  const cuuint32_t bx[2] = {64, 128}, bu[2] = {80, 64};
  const cuuint64_t dw[3] = {640, 640, 3}, sw[2] = {3840, 1280};
  const cuuint32_t bw[3] = {64, 32, 3}, br[3] = {16, 32, 3};
  const cuuint64_t dwo[2] = {640, 640};
  const cuuint32_t bwo[2] = {64, 80}, bwr[2] = {16, 160}, bo64[2] = {64, 64}, bo16[2] = {16, 64};
  const cuuint64_t dsa[2] = {2048, 1280}, ssa[1] = {4096};
  const cuuint32_t bsa[2] = {64, 80};
  const cuuint64_t dsb[2] = {64, 40960}, ssb[1] = {128};
  const cuuint32_t bsb[2] = {64, 32};
  const cuuint64_t dout[2] = {1280, 2048}, sout[1] = {2560};
  CUtensorMap mx = mkmap(enc, d_in[7], 2, dx, sx, bx, CU_TENSOR_MAP_SWIZZLE_128B);
  CUtensorMap mw = mkmap(enc, d_in[8], 3, dw, sw, bw, CU_TENSOR_MAP_SWIZZLE_128B);
  CUtensorMap mr = mkmap(enc, d_in[8], 3, dw, sw, br, CU_TENSOR_MAP_SWIZZLE_32B);
  CUtensorMap mwo = mkmap(enc, d_in[9], 2, dwo, sx, bwo, CU_TENSOR_MAP_SWIZZLE_128B);
  CUtensorMap mwr = mkmap(enc, d_in[9], 2, dwo, sx, bwr, CU_TENSOR_MAP_SWIZZLE_32B);
  CUtensorMap mo64 = mkmap(enc, d_out, 2, dout, sout, bo64, CU_TENSOR_MAP_SWIZZLE_128B);
  CUtensorMap mo16 = mkmap(enc, d_out, 2, dout, sout, bo16, CU_TENSOR_MAP_SWIZZLE_NONE);
  CUtensorMap mu = mkmap(enc, d_in[0], 2, dx, sx, bu, CU_TENSOR_MAP_SWIZZLE_NONE);
  CUtensorMap msa = mkmap(enc, uy, 2, dsa, ssa, bsa, CU_TENSOR_MAP_SWIZZLE_128B);
  CUtensorMap msb = mkmap(enc, uy, 2, dsb, ssb, bsb, CU_TENSOR_MAP_SWIZZLE_128B);
  CUtensorMap mout = mkmap(enc, d_out, 2, dout, sout, bu, CU_TENSOR_MAP_SWIZZLE_NONE);
  Params prm;
  prm.logA = (const __nv_bfloat16*)d_in[1]; prm.Aim = (const __nv_bfloat16*)d_in[2];
  prm.Cr = (const __nv_bfloat16*)d_in[3]; prm.Ci = (const __nv_bfloat16*)d_in[4];
  prm.logdt = (const __nv_bfloat16*)d_in[5]; prm.dskip = (const __nv_bfloat16*)d_in[6];
  cudaFuncSetAttribute(fused_kernel, cudaFuncAttributeMaxDynamicSharedMemorySize, SMEM_BYTES);
  cudaLaunchConfig_t cfg = {};
  cfg.gridDim = dim3(128); cfg.blockDim = dim3(512); cfg.dynamicSmemBytes = SMEM_BYTES; cfg.stream = cudaStreamPerThread;
  cudaLaunchAttribute at[1];
  at[0].id = cudaLaunchAttributeClusterDimension; at[0].val.clusterDim.x = 2; at[0].val.clusterDim.y = 1; at[0].val.clusterDim.z = 1;
  cfg.attrs = at; cfg.numAttrs = 1;
  cudaLaunchKernelEx(&cfg, fused_kernel, mx, mw, mr, mwo, mwr, mo64, mo16, mu, msa, msb, mout, prm);
}
```

```cpp
#include <cuda_runtime.h>
#include <cuda_bf16.h>
#include <cuda_fp16.h>
#include <cuda.h>
#include <stdint.h>

#define EN_ATT 1
#define EN_SSM 1

__device__ __align__(1024) __nv_bfloat16 g_uy[2 * 640 * 2048];
__device__ __align__(128) uint4 g_kvp[8 * 16 * 240];
__device__ __align__(128) uint4 g_o[128 * 1280];
__device__ __align__(128) unsigned g_flag[40 * 32];
__device__ unsigned g_epoch[128];
#define TS(i) do {} while (0)
#define DUMP(lo, hi) do {} while (0)

constexpr uint32_t W_SLOT = 15360, OFF_X = 76800;
constexpr uint32_t OFF_WOM = 20480, OFF_KVS = 71680, OFF_PK = 80896, OFF_V = 101376, OFF_EXTRA = 102400, OFF_KVB = OFF_EXTRA;
constexpr uint32_t OFF_BAR = 125952, OFF_BLK = 128000, BLK = 20480;
constexpr uint32_t B_D = 4096, B_D3 = 3072, B_D9 = 6144, B_D7 = 8192, B_TBL = 14336, B_SP = 18768;
constexpr uint32_t SMEM_BYTES = OFF_BLK + 5 * BLK + 1024;
enum { BR_FULL = 0, BR_EMPTY = 5, BR_WO = 10, BR_PUB = 12, BR_PAR = 13, BR_U2 = 14, BR_OFULL = 18, BR_OEMPTY = 22, BR_GEMM = 26, BR_OSTG = 27, BR_UIN = 28,
       BR_U = 29, BR_DRDY = 30, BR_KGEN = 35, BR_YSTG = 36, BR_FREE = 41, BR_YIN = 46, BR_EPOCH = 47, BR_COUNT = 48 };
constexpr uint32_t OFF_EPOCH = OFF_BAR + 8 * BR_COUNT;

__device__ __forceinline__ long long clk64() { long long t; asm volatile("mov.u64 %0, %%clock64;" : "=l"(t) :: "memory"); return t; }
__device__ __forceinline__ uint32_t smem_u32(const void* p) { return (uint32_t)__cvta_generic_to_shared(p); }
__device__ __forceinline__ uint64_t mkdesc(uint32_t addr, uint32_t lbo, uint32_t sbo, uint32_t swz) {
  return (uint64_t)((addr & 0x3FFFF) >> 4) | ((uint64_t)(lbo >> 4) << 16) | ((uint64_t)(sbo >> 4) << 32) | ((uint64_t)swz << 62);
}
__device__ __forceinline__ void mbar_init(uint32_t bar, uint32_t cnt) { asm volatile("mbarrier.init.shared::cta.b64 [%0], %1;" :: "r"(bar), "r"(cnt) : "memory"); }
__device__ __forceinline__ void mbar_expect_tx(uint32_t bar, uint32_t bytes) { asm volatile("mbarrier.arrive.expect_tx.shared::cta.b64 _, [%0], %1;" :: "r"(bar), "r"(bytes) : "memory"); }
__device__ __forceinline__ void mbar_arrive(uint32_t bar) { asm volatile("mbarrier.arrive.shared::cta.b64 _, [%0];" :: "r"(bar) : "memory"); }
__device__ __forceinline__ void mbar_wait(uint32_t bar, uint32_t parity) {
  asm volatile("{\n.reg .pred p;\n.reg .u32 c;\nmov.u32 c, 0;\n"
    "WL:\nmbarrier.try_wait.parity.shared::cta.b64 p, [%0], %1;\n@p bra WD;\n"
    "add.u32 c, c, 1;\nsetp.lt.u32 p, c, 200000;\n@p bra WL;\nWD:\n}" :: "r"(bar), "r"(parity) : "memory");
}
__device__ __forceinline__ void poll_all(const unsigned* p, unsigned val) {
  asm volatile("{\n.reg .pred p;\n.reg .u32 c, v;\nmov.u32 c, 0;\n"
    "PL:\nld.relaxed.gpu.global.u32 v, [%0];\nsetp.eq.u32 p, v, %1;\nvote.sync.all.pred p, p, 0xffffffff;\n@p bra PD;\n"
    "add.u32 c, c, 1;\nsetp.lt.u32 p, c, 100000;\n@p bra PL;\nPD:\n}" :: "l"(p), "r"(val) : "memory");
}
__device__ __forceinline__ unsigned poll_bit(const unsigned* p, unsigned val, unsigned mask) {
  unsigned bal;
  asm volatile("{\n.reg .pred p;\n.reg .u32 c, v;\nmov.u32 c, 0;\n"
    "PL:\nld.relaxed.gpu.global.u32 v, [%1];\nsetp.eq.u32 p, v, %2;\nvote.sync.ballot.b32 %0, p, 0xffffffff;\n"
    "and.b32 v, %0, %3;\nsetp.ne.u32 p, v, 0;\n@p bra PD;\n"
    "add.u32 c, c, 1;\nsetp.lt.u32 p, c, 100000;\n@p bra PL;\nPD:\n}" : "=&r"(bal) : "l"(p), "r"(val), "r"(mask) : "memory");
  return bal;
}
__device__ __forceinline__ void fix128_w0(uint32_t* v, const void* p, uint32_t tag, uint32_t mask) {
  asm volatile("{\n.reg .pred p;\n.reg .u32 c, x;\n.reg .b128 t;\n.reg .b64 lo, hi;\nmov.u32 c, 0;\n"
    "FL:\nxor.b32 x, %0, %5;\nand.b32 x, x, %6;\nsetp.eq.u32 p, x, 0;\n@p bra FD;\n"
    "ld.relaxed.gpu.global.b128 t, [%4];\nmov.b128 {lo, hi}, t;\nmov.b64 {%0, %1}, lo;\nmov.b64 {%2, %3}, hi;\n"
    "add.u32 c, c, 1;\nsetp.lt.u32 p, c, 100000;\n@p bra FL;\nFD:\n}"
    : "+r"(v[0]), "+r"(v[1]), "+r"(v[2]), "+r"(v[3]) : "l"(p), "r"(tag), "r"(mask) : "memory");
}
__device__ __forceinline__ void fix128_w3(uint32_t* v, const void* p, uint32_t tag, uint32_t mask) {
  asm volatile("{\n.reg .pred p;\n.reg .u32 c, x;\n.reg .b128 t;\n.reg .b64 lo, hi;\nmov.u32 c, 0;\n"
    "FL:\nxor.b32 x, %3, %5;\nand.b32 x, x, %6;\nsetp.eq.u32 p, x, 0;\n@p bra FD;\n"
    "ld.relaxed.gpu.global.b128 t, [%4];\nmov.b128 {lo, hi}, t;\nmov.b64 {%0, %1}, lo;\nmov.b64 {%2, %3}, hi;\n"
    "add.u32 c, c, 1;\nsetp.lt.u32 p, c, 100000;\n@p bra FL;\nFD:\n}"
    : "+r"(v[0]), "+r"(v[1]), "+r"(v[2]), "+r"(v[3]) : "l"(p), "r"(tag), "r"(mask) : "memory");
}
__device__ __forceinline__ void fence_acq() { asm volatile("fence.acq_rel.gpu;" ::: "memory"); }
__device__ __forceinline__ bool elect_one() {
  uint32_t p; asm volatile("{\n.reg .pred P;\nelect.sync _|P, 0xffffffff;\nselp.u32 %0, 1, 0, P;\n}" : "=r"(p)); return p;
}
__device__ __forceinline__ void bar_sync(int id, int n) { asm volatile("bar.sync %0, %1;" :: "r"(id), "r"(n) : "memory"); }
__device__ __forceinline__ void fence_async() { asm volatile("fence.proxy.async.shared::cta;" ::: "memory"); }
__device__ __forceinline__ void fence_async_g() { asm volatile("fence.proxy.async.global;" ::: "memory"); }
__device__ __forceinline__ void tma2d(uint32_t dst, const CUtensorMap* m, uint32_t bar, int c0, int c1) {
  asm volatile("cp.async.bulk.tensor.2d.shared::cluster.global.mbarrier::complete_tx::bytes [%0], [%1, {%3, %4}], [%2];"
    :: "r"(dst), "l"(m), "r"(bar), "r"(c0), "r"(c1) : "memory");
}
__device__ __forceinline__ void tma3d(uint32_t dst, const CUtensorMap* m, uint32_t bar, int c0, int c1, int c2) {
  asm volatile("cp.async.bulk.tensor.3d.shared::cluster.global.mbarrier::complete_tx::bytes [%0], [%1, {%3, %4, %5}], [%2];"
    :: "r"(dst), "l"(m), "r"(bar), "r"(c0), "r"(c1), "r"(c2) : "memory");
}
__device__ __forceinline__ void tma2d_st(const CUtensorMap* m, uint32_t src, int c0, int c1) {
  asm volatile("cp.async.bulk.tensor.2d.global.shared::cta.bulk_group [%0, {%2, %3}], [%1];"
    :: "l"(m), "r"(src), "r"(c0), "r"(c1) : "memory");
}
__device__ __forceinline__ void bulk_ld(uint32_t dst, const void* src, uint32_t bytes, uint32_t bar) {
  asm volatile("cp.async.bulk.shared::cluster.global.mbarrier::complete_tx::bytes [%0], [%1], %2, [%3];"
    :: "r"(dst), "l"(src), "r"(bytes), "r"(bar) : "memory");
}
__device__ __forceinline__ void bulk_st(void* dst, uint32_t src, uint32_t bytes) {
  asm volatile("cp.async.bulk.global.shared::cta.bulk_group [%0], [%1], %2;" :: "l"(dst), "r"(src), "r"(bytes) : "memory");
}
__device__ __forceinline__ void bulk_commit() { asm volatile("cp.async.bulk.commit_group;" ::: "memory"); }
__device__ __forceinline__ void bulk_wait0() { asm volatile("cp.async.bulk.wait_group 0;" ::: "memory"); }
__device__ __forceinline__ void bulk_wait0_read() { asm volatile("cp.async.bulk.wait_group.read 0;" ::: "memory"); }
__device__ __forceinline__ unsigned ld_rlx(const unsigned* p) { unsigned v; asm volatile("ld.relaxed.gpu.global.u32 %0, [%1];" : "=r"(v) : "l"(p) : "memory"); return v; }
__device__ __forceinline__ unsigned ld_acq(const unsigned* p) { unsigned v; asm volatile("ld.acquire.gpu.global.u32 %0, [%1];" : "=r"(v) : "l"(p) : "memory"); return v; }
__device__ __forceinline__ void st_rlx(unsigned* p, unsigned v) { asm volatile("st.relaxed.gpu.global.u32 [%0], %1;" :: "l"(p), "r"(v) : "memory"); }
__device__ __forceinline__ void st_rel(unsigned* p, unsigned v) { asm volatile("st.release.gpu.global.u32 [%0], %1;" :: "l"(p), "r"(v) : "memory"); }
__device__ __forceinline__ void ld128_rlx(uint32_t* v, const void* p) {
  asm volatile("{\n.reg .b128 t;\n.reg .b64 lo, hi;\nld.relaxed.gpu.global.b128 t, [%4];\nmov.b128 {lo, hi}, t;\n"
    "mov.b64 {%0, %1}, lo;\nmov.b64 {%2, %3}, hi;\n}" : "=r"(v[0]), "=r"(v[1]), "=r"(v[2]), "=r"(v[3]) : "l"(p) : "memory");
}
__device__ __forceinline__ void st128_rlx(void* p, const uint32_t* v) {
  asm volatile("{\n.reg .b128 t;\n.reg .b64 lo, hi;\nmov.b64 lo, {%1, %2};\nmov.b64 hi, {%3, %4};\nmov.b128 t, {lo, hi};\n"
    "st.relaxed.gpu.global.b128 [%0], t;\n}" :: "l"(p), "r"(v[0]), "r"(v[1]), "r"(v[2]), "r"(v[3]) : "memory");
}
__device__ __forceinline__ uint32_t lds32(uint32_t a) { uint32_t v; asm volatile("ld.shared.u32 %0, [%1];" : "=r"(v) : "r"(a) : "memory"); return v; }
__device__ __forceinline__ uint32_t lds32v(uint32_t a) { uint32_t v; asm volatile("ld.volatile.shared.u32 %0, [%1];" : "=r"(v) : "r"(a) : "memory"); return v; }
__device__ __forceinline__ uint32_t cpa(uint32_t a, uint32_t one) { uint32_t v; asm volatile("mul.lo.u32 %0, %1, %2;" : "=r"(v) : "r"(a), "r"(one)); return v; }
__device__ __forceinline__ uint32_t cpb(uint32_t a, uint32_t zero) { uint32_t v; asm volatile("or.b32 %0, %1, %2;" : "=r"(v) : "r"(a), "r"(zero)); return v; }
__device__ __forceinline__ uint32_t lds16(uint32_t a) { uint16_t v; asm volatile("ld.shared.u16 %0, [%1];" : "=h"(v) : "r"(a) : "memory"); return v; }
__device__ __forceinline__ float ldsf(uint32_t a) { float v; asm volatile("ld.shared.f32 %0, [%1];" : "=f"(v) : "r"(a) : "memory"); return v; }
__device__ __forceinline__ void lds128(uint32_t* v, uint32_t a) { asm volatile("ld.shared.v4.u32 {%0,%1,%2,%3}, [%4];" : "=r"(v[0]), "=r"(v[1]), "=r"(v[2]), "=r"(v[3]) : "r"(a) : "memory"); }
__device__ __forceinline__ void sts32(uint32_t a, uint32_t v) { asm volatile("st.shared.u32 [%0], %1;" :: "r"(a), "r"(v) : "memory"); }
__device__ __forceinline__ void sts16(uint32_t a, uint32_t v) { asm volatile("st.shared.u16 [%0], %1;" :: "r"(a), "h"((uint16_t)v) : "memory"); }
__device__ __forceinline__ void sts64f(uint32_t a, float x, float y) { asm volatile("st.shared.v2.f32 [%0], {%1,%2};" :: "r"(a), "f"(x), "f"(y) : "memory"); }
__device__ __forceinline__ void sts128(uint32_t a, uint32_t x, uint32_t y, uint32_t z, uint32_t w) { asm volatile("st.shared.v4.u32 [%0], {%1,%2,%3,%4};" :: "r"(a), "r"(x), "r"(y), "r"(z), "r"(w) : "memory"); }
__device__ __forceinline__ void stsm4(uint32_t a, uint32_t r0, uint32_t r1, uint32_t r2, uint32_t r3) {
  asm volatile("stmatrix.sync.aligned.m8n8.x4.shared.b16 [%0], {%1,%2,%3,%4};" :: "r"(a), "r"(r0), "r"(r1), "r"(r2), "r"(r3) : "memory");
}
__device__ __forceinline__ void stsm4t(uint32_t a, uint32_t r0, uint32_t r1, uint32_t r2, uint32_t r3) {
  asm volatile("stmatrix.sync.aligned.m8n8.x4.trans.shared.b16 [%0], {%1,%2,%3,%4};" :: "r"(a), "r"(r0), "r"(r1), "r"(r2), "r"(r3) : "memory");
}
__device__ __forceinline__ void ldsm4t(uint32_t* r, uint32_t a) {
  asm volatile("ldmatrix.sync.aligned.m8n8.x4.trans.shared.b16 {%0,%1,%2,%3}, [%4];" : "=r"(r[0]), "=r"(r[1]), "=r"(r[2]), "=r"(r[3]) : "r"(a) : "memory");
}
__device__ __forceinline__ uint32_t pack2(float lo, float hi) { uint32_t r; asm("cvt.rn.bf16x2.f32 %0, %1, %2;" : "=r"(r) : "f"(hi), "f"(lo)); return r; }
__device__ __forceinline__ uint32_t packh(float lo, float hi) { uint32_t r; asm("cvt.rn.f16x2.f32 %0, %1, %2;" : "=r"(r) : "f"(hi), "f"(lo)); return r; }
__device__ __forceinline__ uint32_t hcmul(uint32_t x, uint32_t zp, uint32_t zq) {
  const __half2 xx = *reinterpret_cast<__half2*>(&x);
  const __half2 r = __hfma2(__high2half2(xx), *reinterpret_cast<__half2*>(&zq), __hmul2(__low2half2(xx), *reinterpret_cast<__half2*>(&zp)));
  return *reinterpret_cast<const uint32_t*>(&r);
}
__device__ __forceinline__ void hcm2(uint32_t xr, uint32_t xi, uint32_t z, uint32_t& pr, uint32_t& pi) {
  const __half2 a = *reinterpret_cast<__half2*>(&xr), b = *reinterpret_cast<__half2*>(&xi), zz = *reinterpret_cast<__half2*>(&z);
  const __half2 re = __hfma2(__hneg2(b), __high2half2(zz), __hmul2(a, __low2half2(zz)));
  const __half2 im = __hfma2(a, __high2half2(zz), __hmul2(b, __low2half2(zz)));
  pr = *reinterpret_cast<const uint32_t*>(&re); pi = *reinterpret_cast<const uint32_t*>(&im);
}
__device__ __forceinline__ void sts64(uint32_t a, uint32_t x, uint32_t y) { asm volatile("st.shared.v2.u32 [%0], {%1,%2};" :: "r"(a), "r"(x), "r"(y) : "memory"); }
__device__ __forceinline__ void lds64(uint32_t* v, uint32_t a) { asm volatile("ld.shared.v2.u32 {%0,%1}, [%2];" : "=r"(v[0]), "=r"(v[1]) : "r"(a) : "memory"); }
__device__ __forceinline__ float bf_lo(uint32_t v) { return __uint_as_float(v << 16); }
__device__ __forceinline__ float bf_hi(uint32_t v) { return __uint_as_float(v & 0xffff0000u); }
__device__ __forceinline__ float bf_round(float x) { return bf_lo(pack2(x, 0.f)); }
__device__ __forceinline__ float ex2(float x) { float r; asm("ex2.approx.ftz.f32 %0, %1;" : "=f"(r) : "f"(x)); return r; }
__device__ __forceinline__ float phi(float t, float l2e = 1.44269504089f) { float e = ex2(t * l2e); return (t > 0.f ? t + 1.f : e) + 1e-6f; }
__device__ __forceinline__ void wg_fence() { asm volatile("wgmma.fence.sync.aligned;" ::: "memory"); }
__device__ __forceinline__ void wg_commit() { asm volatile("wgmma.commit_group.sync.aligned;" ::: "memory"); }
template <int N> __device__ __forceinline__ void wg_wait() { asm volatile("wgmma.wait_group.sync.aligned %0;" :: "n"(N) : "memory"); }
template <int N> __device__ __forceinline__ void pin(float* a) {
  #pragma unroll
  for (int i = 0; i < N; i++) asm volatile("" : "+f"(a[i]) :: "memory");
}
__device__ __forceinline__ int opaque(int v) { asm volatile("" : "+r"(v)); return v; }
template <int N> __device__ __forceinline__ void zero(float* a) {
  #pragma unroll
  for (int i = 0; i < N; i++) asm volatile("mov.b32 %0, 0;" : "=f"(a[i]));
}
template <int N> __device__ __forceinline__ void pinu(uint32_t* a) {
  #pragma unroll
  for (int i = 0; i < N; i++) asm volatile("" : "+r"(a[i]) :: "memory");
}
__device__ __forceinline__ void cexp_t(float lg2mag, float turns, float& re, float& im) {
  float m = ex2(lg2mag);
  float fr = (turns - __fadd_rn(__fadd_rn(turns, 12582912.f), -12582912.f)) * 6.283185307f;
  re = m * __cosf(fr); im = m * __sinf(fr);
}
__device__ __forceinline__ void cmul(float ar, float ai, float br, float bi, float& cr, float& ci) {
  cr = fmaf(ar, br, -ai * bi); ci = fmaf(ar, bi, ai * br);
}

__device__ __forceinline__ void wg_ss192_tb(float* d, uint64_t da, uint64_t db, int scale_d) {
  asm volatile("{\n.reg .pred p;\nsetp.ne.b32 p, %98, 0;\n"
    "wgmma.mma_async.sync.aligned.m64n192k16.f32.bf16.bf16 "
    "{%0, %1, %2, %3, %4, %5, %6, %7, %8, %9, %10, %11, %12, %13, %14, %15, %16, %17, %18, %19, %20, %21, %22, %23, %24, %25, %26, %27, %28, %29, %30, %31, %32, %33, %34, %35, %36, %37, %38, %39, %40, %41, %42, %43, %44, %45, %46, %47, %48, %49, %50, %51, %52, %53, %54, %55, %56, %57, %58, %59, %60, %61, %62, %63, %64, %65, %66, %67, %68, %69, %70, %71, %72, %73, %74, %75, %76, %77, %78, %79, %80, %81, %82, %83, %84, %85, %86, %87, %88, %89, %90, %91, %92, %93, %94, %95}, %96, %97, p, 1, 1, 0, 1;\n}\n"
    : "+f"(d[0]), "+f"(d[1]), "+f"(d[2]), "+f"(d[3]), "+f"(d[4]), "+f"(d[5]), "+f"(d[6]), "+f"(d[7]), "+f"(d[8]), "+f"(d[9]), "+f"(d[10]), "+f"(d[11]), "+f"(d[12]), "+f"(d[13]), "+f"(d[14]), "+f"(d[15]), "+f"(d[16]), "+f"(d[17]), "+f"(d[18]), "+f"(d[19]), "+f"(d[20]), "+f"(d[21]), "+f"(d[22]), "+f"(d[23]), "+f"(d[24]), "+f"(d[25]), "+f"(d[26]), "+f"(d[27]), "+f"(d[28]), "+f"(d[29]), "+f"(d[30]), "+f"(d[31]), "+f"(d[32]), "+f"(d[33]), "+f"(d[34]), "+f"(d[35]), "+f"(d[36]), "+f"(d[37]), "+f"(d[38]), "+f"(d[39]), "+f"(d[40]), "+f"(d[41]), "+f"(d[42]), "+f"(d[43]), "+f"(d[44]), "+f"(d[45]), "+f"(d[46]), "+f"(d[47]), "+f"(d[48]), "+f"(d[49]), "+f"(d[50]), "+f"(d[51]), "+f"(d[52]), "+f"(d[53]), "+f"(d[54]), "+f"(d[55]), "+f"(d[56]), "+f"(d[57]), "+f"(d[58]), "+f"(d[59]), "+f"(d[60]), "+f"(d[61]), "+f"(d[62]), "+f"(d[63]), "+f"(d[64]), "+f"(d[65]), "+f"(d[66]), "+f"(d[67]), "+f"(d[68]), "+f"(d[69]), "+f"(d[70]), "+f"(d[71]), "+f"(d[72]), "+f"(d[73]), "+f"(d[74]), "+f"(d[75]), "+f"(d[76]), "+f"(d[77]), "+f"(d[78]), "+f"(d[79]), "+f"(d[80]), "+f"(d[81]), "+f"(d[82]), "+f"(d[83]), "+f"(d[84]), "+f"(d[85]), "+f"(d[86]), "+f"(d[87]), "+f"(d[88]), "+f"(d[89]), "+f"(d[90]), "+f"(d[91]), "+f"(d[92]), "+f"(d[93]), "+f"(d[94]), "+f"(d[95])
    : "l"(da), "l"(db), "r"(scale_d));
}
__device__ __forceinline__ void wg_ss48_tb(float* d, uint64_t da, uint64_t db, int scale_d) {
  asm volatile("{\n.reg .pred p;\nsetp.ne.b32 p, %26, 0;\n"
    "wgmma.mma_async.sync.aligned.m64n48k16.f32.bf16.bf16 "
    "{%0, %1, %2, %3, %4, %5, %6, %7, %8, %9, %10, %11, %12, %13, %14, %15, %16, %17, %18, %19, %20, %21, %22, %23}, %24, %25, p, 1, 1, 0, 1;\n}\n"
    : "+f"(d[0]), "+f"(d[1]), "+f"(d[2]), "+f"(d[3]), "+f"(d[4]), "+f"(d[5]), "+f"(d[6]), "+f"(d[7]), "+f"(d[8]), "+f"(d[9]), "+f"(d[10]), "+f"(d[11]), "+f"(d[12]), "+f"(d[13]), "+f"(d[14]), "+f"(d[15]), "+f"(d[16]), "+f"(d[17]), "+f"(d[18]), "+f"(d[19]), "+f"(d[20]), "+f"(d[21]), "+f"(d[22]), "+f"(d[23])
    : "l"(da), "l"(db), "r"(scale_d));
}
__device__ __forceinline__ void wg_ss48_tt(float* d, uint64_t da, uint64_t db, int scale_d) {
  asm volatile("{\n.reg .pred p;\nsetp.ne.b32 p, %26, 0;\n"
    "wgmma.mma_async.sync.aligned.m64n48k16.f32.bf16.bf16 "
    "{%0, %1, %2, %3, %4, %5, %6, %7, %8, %9, %10, %11, %12, %13, %14, %15, %16, %17, %18, %19, %20, %21, %22, %23}, %24, %25, p, 1, 1, 1, 1;\n}\n"
    : "+f"(d[0]), "+f"(d[1]), "+f"(d[2]), "+f"(d[3]), "+f"(d[4]), "+f"(d[5]), "+f"(d[6]), "+f"(d[7]), "+f"(d[8]), "+f"(d[9]), "+f"(d[10]), "+f"(d[11]), "+f"(d[12]), "+f"(d[13]), "+f"(d[14]), "+f"(d[15]), "+f"(d[16]), "+f"(d[17]), "+f"(d[18]), "+f"(d[19]), "+f"(d[20]), "+f"(d[21]), "+f"(d[22]), "+f"(d[23])
    : "l"(da), "l"(db), "r"(scale_d));
}
__device__ __forceinline__ void wg_rs88_tb(float* d, const uint32_t* a, uint64_t db, int scale_d) {
  asm volatile("{\n.reg .pred p;\nsetp.ne.b32 p, %49, 0;\n"
    "wgmma.mma_async.sync.aligned.m64n88k16.f32.bf16.bf16 "
    "{%0, %1, %2, %3, %4, %5, %6, %7, %8, %9, %10, %11, %12, %13, %14, %15, %16, %17, %18, %19, %20, %21, %22, %23, %24, %25, %26, %27, %28, %29, %30, %31, %32, %33, %34, %35, %36, %37, %38, %39, %40, %41, %42, %43}, {%44, %45, %46, %47}, %48, p, 1, 1, 1;\n}\n"
    : "+f"(d[0]), "+f"(d[1]), "+f"(d[2]), "+f"(d[3]), "+f"(d[4]), "+f"(d[5]), "+f"(d[6]), "+f"(d[7]), "+f"(d[8]), "+f"(d[9]), "+f"(d[10]), "+f"(d[11]), "+f"(d[12]), "+f"(d[13]), "+f"(d[14]), "+f"(d[15]), "+f"(d[16]), "+f"(d[17]), "+f"(d[18]), "+f"(d[19]), "+f"(d[20]), "+f"(d[21]), "+f"(d[22]), "+f"(d[23]), "+f"(d[24]), "+f"(d[25]), "+f"(d[26]), "+f"(d[27]), "+f"(d[28]), "+f"(d[29]), "+f"(d[30]), "+f"(d[31]), "+f"(d[32]), "+f"(d[33]), "+f"(d[34]), "+f"(d[35]), "+f"(d[36]), "+f"(d[37]), "+f"(d[38]), "+f"(d[39]), "+f"(d[40]), "+f"(d[41]), "+f"(d[42]), "+f"(d[43])
    : "r"(a[0]), "r"(a[1]), "r"(a[2]), "r"(a[3]), "l"(db), "r"(scale_d));
}
__device__ __forceinline__ void wg_rs64_tb(float* d, const uint32_t* a, uint64_t db, int scale_d) {
  asm volatile("{\n.reg .pred p;\nsetp.ne.b32 p, %37, 0;\n"
    "wgmma.mma_async.sync.aligned.m64n64k16.f32.bf16.bf16 "
    "{%0, %1, %2, %3, %4, %5, %6, %7, %8, %9, %10, %11, %12, %13, %14, %15, %16, %17, %18, %19, %20, %21, %22, %23, %24, %25, %26, %27, %28, %29, %30, %31}, {%32, %33, %34, %35}, %36, p, 1, 1, 1;\n}\n"
    : "+f"(d[0]), "+f"(d[1]), "+f"(d[2]), "+f"(d[3]), "+f"(d[4]), "+f"(d[5]), "+f"(d[6]), "+f"(d[7]), "+f"(d[8]), "+f"(d[9]), "+f"(d[10]), "+f"(d[11]), "+f"(d[12]), "+f"(d[13]), "+f"(d[14]), "+f"(d[15]), "+f"(d[16]), "+f"(d[17]), "+f"(d[18]), "+f"(d[19]), "+f"(d[20]), "+f"(d[21]), "+f"(d[22]), "+f"(d[23]), "+f"(d[24]), "+f"(d[25]), "+f"(d[26]), "+f"(d[27]), "+f"(d[28]), "+f"(d[29]), "+f"(d[30]), "+f"(d[31])
    : "r"(a[0]), "r"(a[1]), "r"(a[2]), "r"(a[3]), "l"(db), "r"(scale_d));
}
__device__ __forceinline__ void wg_ss48_tt_h(float* d, uint64_t da, uint64_t db, int scale_d) {
  asm volatile("{\n.reg .pred p;\nsetp.ne.b32 p, %26, 0;\n"
    "wgmma.mma_async.sync.aligned.m64n48k16.f32.f16.f16 "
    "{%0, %1, %2, %3, %4, %5, %6, %7, %8, %9, %10, %11, %12, %13, %14, %15, %16, %17, %18, %19, %20, %21, %22, %23}, %24, %25, p, 1, 1, 1, 1;\n}\n"
    : "+f"(d[0]), "+f"(d[1]), "+f"(d[2]), "+f"(d[3]), "+f"(d[4]), "+f"(d[5]), "+f"(d[6]), "+f"(d[7]), "+f"(d[8]), "+f"(d[9]), "+f"(d[10]), "+f"(d[11]), "+f"(d[12]), "+f"(d[13]), "+f"(d[14]), "+f"(d[15]), "+f"(d[16]), "+f"(d[17]), "+f"(d[18]), "+f"(d[19]), "+f"(d[20]), "+f"(d[21]), "+f"(d[22]), "+f"(d[23])
    : "l"(da), "l"(db), "r"(scale_d));
}
__device__ __forceinline__ void wg_rs32(float* d, const uint32_t* a, uint64_t db, int scale_d) {
  asm volatile("{\n.reg .pred p;\nsetp.ne.b32 p, %21, 0;\n"
    "wgmma.mma_async.sync.aligned.m64n32k16.f32.bf16.bf16 "
    "{%0, %1, %2, %3, %4, %5, %6, %7, %8, %9, %10, %11, %12, %13, %14, %15}, {%16, %17, %18, %19}, %20, p, 1, 1, 0;\n}\n"
    : "+f"(d[0]), "+f"(d[1]), "+f"(d[2]), "+f"(d[3]), "+f"(d[4]), "+f"(d[5]), "+f"(d[6]), "+f"(d[7]), "+f"(d[8]), "+f"(d[9]), "+f"(d[10]), "+f"(d[11]), "+f"(d[12]), "+f"(d[13]), "+f"(d[14]), "+f"(d[15])
    : "r"(a[0]), "r"(a[1]), "r"(a[2]), "r"(a[3]), "l"(db), "r"(scale_d));
}
__device__ __forceinline__ void wg_rs24_tb(float* d, const uint32_t* a, uint64_t db, int scale_d) {
  asm volatile("{\n.reg .pred p;\nsetp.ne.b32 p, %17, 0;\n"
    "wgmma.mma_async.sync.aligned.m64n24k16.f32.bf16.bf16 "
    "{%0, %1, %2, %3, %4, %5, %6, %7, %8, %9, %10, %11}, {%12, %13, %14, %15}, %16, p, 1, 1, 1;\n}\n"
    : "+f"(d[0]), "+f"(d[1]), "+f"(d[2]), "+f"(d[3]), "+f"(d[4]), "+f"(d[5]), "+f"(d[6]), "+f"(d[7]), "+f"(d[8]), "+f"(d[9]), "+f"(d[10]), "+f"(d[11])
    : "r"(a[0]), "r"(a[1]), "r"(a[2]), "r"(a[3]), "l"(db), "r"(scale_d));
}
__device__ __forceinline__ void wg_rs16_tb(float* d, const uint32_t* a, uint64_t db, int scale_d) {
  asm volatile("{\n.reg .pred p;\nsetp.ne.b32 p, %13, 0;\n"
    "wgmma.mma_async.sync.aligned.m64n16k16.f32.bf16.bf16 "
    "{%0, %1, %2, %3, %4, %5, %6, %7}, {%8, %9, %10, %11}, %12, p, 1, 1, 1;\n}\n"
    : "+f"(d[0]), "+f"(d[1]), "+f"(d[2]), "+f"(d[3]), "+f"(d[4]), "+f"(d[5]), "+f"(d[6]), "+f"(d[7])
    : "r"(a[0]), "r"(a[1]), "r"(a[2]), "r"(a[3]), "l"(db), "r"(scale_d));
}

struct Params {
  const __nv_bfloat16 *logA, *Aim, *Cr, *Ci, *logdt, *dskip;
};

template <bool FWD>
__device__ __forceinline__ void tile_transpose(uint32_t tc0, uint32_t tc1, uint32_t ct0, uint32_t ct1, int hw, int lane) {
  const int mi = lane >> 3, row = lane & 7;
  for (int gi = hw; gi < 40; gi += 3) {
    const int hh = gi / 20, rem = gi - hh * 20, q = rem / 10, cb = rem - q * 10;
    const uint32_t a_tc = (hh ? tc1 : tc0) + (8 * (4 * q + mi) + row) * 160 + cb * 16;
    const uint32_t a_ct = (hh ? ct1 : ct0) + (8 * cb + row) * 128 + (((4 * q + mi) ^ row) << 4);
    uint32_t r[4];
    ldsm4t(r, FWD ? a_tc : a_ct);
    stsm4(FWD ? a_ct : a_tc, r[0], r[1], r[2], r[3]);
  }
}

template <int NS>
__device__ __forceinline__ void load_toep(uint32_t* A, uint32_t addr) {
  uint32_t prev = lds32(addr - 32);
  #pragma unroll
  for (int s = 0; s < NS; s++) {
    uint32_t x = lds32(addr + 64 * s), y = lds32(addr + 64 * s + 32);
    A[4 * s] = x; A[4 * s + 1] = y; A[4 * s + 2] = prev; A[4 * s + 3] = x;
    prev = y;
  }
}

__global__ void __launch_bounds__(512, 1)
fused_kernel(const __grid_constant__ CUtensorMap mx, const __grid_constant__ CUtensorMap mw, const __grid_constant__ CUtensorMap mr,
             const __grid_constant__ CUtensorMap mwo, const __grid_constant__ CUtensorMap mwr, const __grid_constant__ CUtensorMap mo64,
             const __grid_constant__ CUtensorMap mo16, const __grid_constant__ CUtensorMap mu, const __grid_constant__ CUtensorMap msa,
             const __grid_constant__ CUtensorMap msb, const __grid_constant__ CUtensorMap mout, const Params prm) {
  extern __shared__ unsigned char smem_raw[];
  const uint32_t sb = (smem_u32(smem_raw) + 1023) & ~1023u;
  const int tid = threadIdx.x, lane = tid & 31;
  const int wg = __shfl_sync(0xffffffff, tid >> 7, 0), warp = __shfl_sync(0xffffffff, tid >> 5, 0);
  const int cta = blockIdx.x, r = cta >> 3, c = cta & 7;
  const uint32_t bars = sb + OFF_BAR;
#define BAR(i) (bars + 8 * (i))

  auto issue1 = [&](int kb) {
    const uint32_t st = sb + (kb % 5) * W_SLOT, fb = BAR(BR_FULL + kb % 5);
    mbar_expect_tx(fb, (kb & 1) ? W_SLOT : W_SLOT + 16384);
    if (!(kb & 1)) tma2d(sb + OFF_X + ((kb >> 1) % 3) * 16384, &mx, fb, kb * 32, r * 128);
    tma3d(st, &mw, fb, c * 80, kb * 32, 0);
    tma3d(st + 12288, &mr, fb, c * 80 + 64, kb * 32, 0);
  };

  if (warp == 12) {
    if (elect_one()) {
      #pragma unroll
      for (int i = 0; i < BR_COUNT; i++) {
        int cnt = 1;
        if (i >= BR_EMPTY && i < BR_EMPTY + 5) cnt = 2;
        if (i >= BR_OEMPTY && i < BR_OEMPTY + 4) cnt = 8;
        if (i == BR_OSTG) cnt = 256;
        if (i >= BR_DRDY && i < BR_DRDY + 5) cnt = 96;
        if (i >= BR_YSTG && i < BR_YSTG + 5) cnt = 128;
        mbar_init(BAR(i), cnt);
      }
      asm volatile("fence.mbarrier_init.release.cluster;" ::: "memory");
      if (EN_SSM) mbar_expect_tx(BAR(BR_PAR), 5120);
    }
    __syncwarp();
    if (EN_SSM && lane < 20) {
      const int ai = lane & 3, k = lane >> 2;
      const __nv_bfloat16* pp = ai == 0 ? prm.logA : ai == 1 ? prm.Aim : ai == 2 ? prm.Cr : prm.Ci;
      bulk_ld(sb + OFF_BLK + k * BLK + B_TBL + 512 + ai * 256, pp + (c * 80 + r * 5 + k) * 128, 256, BAR(BR_PAR));
    }
    __syncwarp();
    if (EN_ATT && elect_one()) issue1(0);
  }
  float ldt = 0.f, dsk0 = 0.f;
  if (tid >= 256 && tid < 261) { ldt = __bfloat162float(prm.logdt[c * 80 + r * 5 + tid - 256]); dsk0 = __bfloat162float(prm.dskip[c * 80 + r * 5 + tid - 256]); }
  __syncthreads();

  if (wg == 3) {
    asm volatile("setmaxnreg.dec.sync.aligned.u32 56;");
    if (warp == 12) {
      if (EN_ATT) {
      #pragma unroll
      for (int kb = 1; kb < 20; kb++) {
        if (kb >= 5) mbar_wait(BAR(BR_EMPTY + kb % 5), ((kb / 5) & 1) ^ 1);
        if (elect_one()) issue1(kb);
      }
      auto chunk_of = [&](int i) { return i == 0 ? c : (i == 7 ? (c ^ 1) : (((c & 6) + 1 + i) & 7)); };
      mbar_wait(BAR(BR_EPOCH), 0);
      const unsigned epoch = lds32(sb + OFF_EPOCH);
      const unsigned* fo = &g_flag[(24 + r) * 32 + (lane & 7)];
      unsigned seen = __ballot_sync(0xffffffff, ld_rlx(fo) == epoch);
      mbar_wait(BAR(BR_GEMM), 0);
      if (elect_one()) {
        mbar_expect_tx(BAR(BR_WO), 20480 + 5 * 10240);
        #pragma unroll
        for (int i = 0; i < 5; i++) tma2d(sb + OFF_WOM + i * 10240, &mwo, BAR(BR_WO), c * 64, i * 80);
        #pragma unroll
        for (int i = 0; i < 4; i++) tma2d(sb + i * 5120, &mwr, BAR(BR_WO), 512 + c * 16, i * 160);
      }
      mbar_wait(BAR(BR_PUB), 0);
      if (elect_one()) {
        mbar_expect_tx(BAR(BR_WO + 1), 3 * 10240);
        #pragma unroll
        for (int i = 5; i < 8; i++) tma2d(sb + OFF_WOM + i * 10240, &mwo, BAR(BR_WO + 1), c * 64, i * 80);
      }
      mbar_wait(BAR(BR_OSTG), 0);
      if (elect_one()) {
        bulk_st(&g_o[cta * 1280], sb + OFF_EXTRA, 20480);
        bulk_commit();
        bulk_wait0();
        st_rlx(&g_flag[(24 + r) * 32 + c], epoch);
        TS(20);
      }
      __syncwarp();
      #pragma unroll
      for (int i = 0; i < 7; i++) {
        const int src = chunk_of(i + 1);
        if (!((seen >> src) & 1)) seen = poll_bit(fo, epoch, 1u << src);
        if (i < 3) { if (EN_SSM) mbar_wait(BAR(BR_FREE + 4 - i), 0); }
        else if (i > 3) mbar_wait(BAR(BR_OEMPTY + i - 4), 0);
        if (elect_one()) {
          fence_async_g();
          const uint32_t slot = (i & 3) == 3 ? sb + OFF_EXTRA : sb + OFF_BLK + (4 - (i & 3)) * BLK;
          mbar_expect_tx(BAR(BR_OFULL + (i & 3)), 20480);
          bulk_ld(slot, &g_o[(r * 8 + src) * 1280], 20480, BAR(BR_OFULL + (i & 3)));
          if (i == 0) TS(21);
          if (i == 6) { TS(22); DUMP(20, 30); }
        }
        __syncwarp();
      }
      }
    } else {
      const int hw = warp - 13, ht = tid - 416;
      unsigned epoch = 0;
      if (hw == 0) {
        if (lane == 0) {
          if (EN_SSM) {
            mbar_expect_tx(BAR(BR_UIN), 20480);
            tma2d(sb + OFF_BLK + 4 * BLK + B_D, &mu, BAR(BR_UIN), c * 80, r * 128);
            tma2d(sb + OFF_BLK + 3 * BLK + B_D, &mu, BAR(BR_UIN), c * 80, r * 128 + 64);
          }
          epoch = ld_rlx(&g_epoch[cta]) + 1;
          st_rlx(&g_epoch[cta], epoch);
          sts32(sb + OFF_EPOCH, epoch);
          mbar_arrive(BAR(BR_EPOCH));
        }
        epoch = __shfl_sync(0xffffffff, epoch, 0);
      }
      if (EN_SSM) {
      mbar_wait(BAR(BR_UIN), 0);
      if (ht == 0) TS(36);
      {
        const int mi = lane >> 3, rw = lane & 7;
        const uint32_t lo = (uint32_t)((8 * (rw >> 1) + 2 * mi + (rw & 1)) * 160);
        uint4* gp = reinterpret_cast<uint4*>(g_uy + (size_t)(c * 80 + hw * 8 + (lane >> 2)) * 2048 + r * 128 + (lane & 3) * 8);
        const uint32_t sa = sb + OFF_BLK + 3 * BLK + B_D + lo + hw * 16;
        #pragma unroll
        for (int i = 0; i < 4; i++) {
          if (i < 3 || hw == 0) {
            uint32_t v[4][4];
            #pragma unroll
            for (int q = 0; q < 4; q++) ldsm4t(v[q], sa + (1 - (q >> 1)) * BLK + (q & 1) * 5120 + i * 48);
            #pragma unroll
            for (int q = 0; q < 4; q++) gp[i * 6144 + q * 4] = make_uint4(v[q][0], v[q][1], v[q][2], v[q][3]);
          }
        }
      }
      if (ht == 0) TS(37);
      __threadfence();
      if (ht == 0) TS(38);
      bar_sync(5, 96);
      if (hw == 0) {
        if (lane == 0) { st_rlx(&g_flag[(8 + c) * 32 + r], epoch); TS(30); }
        __syncwarp();
        poll_all(&g_flag[(8 + c) * 32 + (lane & 15)], epoch);
        (void)ld_acq(&g_flag[(8 + c) * 32 + (lane & 15)]); __syncwarp();
        if (lane == 0) {
          fence_async_g();
          mbar_expect_tx(BAR(BR_U), 12288);
          #pragma unroll
          for (int k = 4; k >= 2; k--) tma2d(sb + OFF_BLK + k * BLK, &msb, BAR(BR_U), 0, (c * 80 + r * 5 + k) * 32);
          TS(31);
        }
        __syncwarp();
      }
      mbar_wait(BAR(BR_U), 0);
      if (ht == 0) TS(39);
      #pragma unroll 1
      for (int k = 4; k >= 0; k--) {
        if (k == 2) {
          mbar_wait(BAR(BR_KGEN), 0);
          if (ht == 0) {
            fence_async();
            mbar_expect_tx(BAR(BR_U2), 8192);
            tma2d(sb + OFF_BLK + BLK, &msb, BAR(BR_U2), 0, (c * 80 + r * 5 + 1) * 32);
            tma2d(sb + OFF_BLK, &msb, BAR(BR_U2), 0, (c * 80 + r * 5) * 32);
          }
          __syncwarp();
        }
        if (k == 1) mbar_wait(BAR(BR_U2), 0);
        const uint32_t blk = sb + OFF_BLK + k * BLK;
        #pragma unroll 1
        for (int kap = ht; kap < 192; kap += 96) {
          float P[33];
          P[0] = 0.f;
          #pragma unroll
          for (int q = 0; q < 4; q++) {
            const int ch = kap - 3 + q;
            uint32_t v[4];
            lds128(v, blk + (uint32_t)((ch >> 3) * 128 + (((ch & 7) ^ ((ch >> 3) & 7)) << 4)));
            #pragma unroll
            for (int e = 0; e < 4; e++) {
              P[q * 8 + 2 * e + 1] = P[q * 8 + 2 * e] + bf_lo(v[e]);
              P[q * 8 + 2 * e + 2] = P[q * 8 + 2 * e + 1] + bf_hi(v[e]);
            }
          }
#define WIN(lo, hi, e) (P[25 + (e) - (lo)] - P[24 + (e) - (hi)])
#define WIN8(lo, hi) pack2(WIN(lo, hi, 0), WIN(lo, hi, 1)), pack2(WIN(lo, hi, 2), WIN(lo, hi, 3)), pack2(WIN(lo, hi, 4), WIN(lo, hi, 5)), pack2(WIN(lo, hi, 6), WIN(lo, hi, 7))
          sts128(blk + B_D + kap * 16, WIN8(6, 10));
          sts128(blk + B_D + B_D3 + kap * 16, WIN8(3, 5));
          if (kap < 128) {
            const uint32_t o = (kap & 1) * 1024 + (kap >> 1) * 16;
            sts128(blk + B_D + B_D9 + o, WIN8(12, 20));
            sts128(blk + B_D + B_D7 + o, WIN8(5, 11));
          }
        }
        fence_async();
        mbar_arrive(BAR(BR_DRDY + k));
      }
      if (ht == 0) TS(32);
      if (hw == 0) {
        #pragma unroll 1
        for (int k = 4; k >= 0; k--) {
          mbar_wait(BAR(BR_YSTG + k), 0);
          if (lane == 0) {
            tma2d_st(&msb, sb + OFF_BLK + k * BLK, 0, (640 + c * 80 + r * 5 + k) * 32);
            bulk_commit(); bulk_wait0_read();
            mbar_arrive(BAR(BR_FREE + k));
          }
          __syncwarp();
        }
        if (lane == 0) { bulk_wait0(); st_rel(&g_flag[(16 + c) * 32 + r], epoch); TS(33); }
        __syncwarp();
        poll_all(&g_flag[(16 + c) * 32 + (lane & 15)], epoch);
        (void)ld_acq(&g_flag[(16 + c) * 32 + (lane & 15)]); __syncwarp();
        if (lane == 0) {
          fence_async_g();
          mbar_expect_tx(BAR(BR_YIN), 20480);
          tma2d(sb + OFF_BLK + BLK, &msa, BAR(BR_YIN), r * 128, 640 + c * 80);
          tma2d(sb + OFF_BLK + BLK + 10240, &msa, BAR(BR_YIN), r * 128 + 64, 640 + c * 80);
          TS(34);
        }
        __syncwarp();
      }
      mbar_wait(BAR(BR_YIN), 0);
      tile_transpose<false>(sb + OFF_BLK, sb + OFF_BLK + 10240, sb + OFF_BLK + BLK, sb + OFF_BLK + BLK + 10240, hw, lane);
      fence_async();
      bar_sync(5, 96);
      if (ht == 0) {
        tma2d_st(&mout, sb + OFF_BLK, c * 80, r * 128);
        tma2d_st(&mout, sb + OFF_BLK + 10240, c * 80, r * 128 + 64);
        bulk_commit(); bulk_wait0_read();
        TS(35); DUMP(30, 40); DUMP(0, 1);
      }
      }
    }
  } else if (wg < 2) {
    asm volatile("setmaxnreg.inc.sync.aligned.u32 152;");
    if (EN_ATT) {
    const int w4 = warp & 3, g = lane >> 2, tq = lane & 3, t7 = tid & 127;
    float am[96], ar[24];
    {
      const uint64_t da0 = mkdesc(sb + OFF_X + wg * 8192, 16, 1024, 1);
      const uint64_t db0 = mkdesc(sb, 4096, 1024, 1);
      const uint64_t dr0 = mkdesc(sb + 12288, 1024, 256, 3);
      uint32_t s = 0, ph = 0, xo = 0;
      #pragma unroll 1
      for (int kb = 0; kb < 20; kb++) {
        mbar_wait(BAR(BR_FULL) + 8 * s, ph);
        if (kb == 0 && tid == 0) TS(1);
        wg_fence();
        const uint32_t wo_ = s * (W_SLOT >> 4);
        wg_ss192_tb(am, da0 + xo, db0 + wo_, kb != 0);
        wg_ss48_tb(ar, da0 + xo, dr0 + wo_, kb != 0);
        wg_ss192_tb(am, da0 + xo + 2, db0 + wo_ + 128, 1);
        wg_ss48_tb(ar, da0 + xo + 2, dr0 + wo_ + 32, 1);
        wg_commit();
        wg_wait<1>();
        if (t7 == 0 && kb > 0 && kb < 16) mbar_arrive(BAR(BR_EMPTY) + 8 * (s == 0 ? 4 : s - 1));
        if (++s == 5) { s = 0; ph ^= 1; }
        xo += (kb & 1) ? 1020 : 4;
        if (xo == 3072) xo = 0;
      }
      wg_wait<0>();
      pin<96>(am); pin<24>(ar);
    }
    if (tid == 0) TS(2);
#define QV(j, e) ((j) < 8 ? am[4 * (j) + (e)] : ar[4 * ((j) - 8) + (e)])
#define KV_(j, e) ((j) < 8 ? am[32 + 4 * (j) + (e)] : ar[8 + 4 * ((j) - 8) + (e)])
#define VV(j, e) ((j) < 8 ? am[64 + 4 * (j) + (e)] : ar[16 + 4 * ((j) - 8) + (e)])
    {
      bar_sync(1, 256);
      if (tid == 0) mbar_arrive(BAR(BR_GEMM));
      const uint32_t ro = (uint32_t)((lane >> 4) * 2048 + (wg * 64 + w4 * 16 + (lane & 15)) * 16);
      const uint32_t ones = (tq == 0) ? 0x00003f80u : 0u;
#define PV(j) pack2(VV(j, 0), VV(j, 1)), pack2(VV(j, 2), VV(j, 3))
#define PK(j) pack2(phi(KV_(j, 0)), phi(KV_(j, 1))), pack2(phi(KV_(j, 2)), phi(KV_(j, 3)))
      stsm4(sb + OFF_V + 0 * 2048 + ro, PV(0), PV(1));
      stsm4(sb + OFF_V + 2 * 2048 + ro, PV(2), PV(3));
      stsm4(sb + OFF_V + 4 * 2048 + ro, PV(4), ones, ones);
      stsm4(sb + OFF_V + 6 * 2048 + ro, PV(5), PV(6));
      stsm4(sb + OFF_V + 8 * 2048 + ro, PV(7), PV(8));
      stsm4(sb + OFF_V + 10 * 2048 + ro, PV(9), ones, ones);
      #pragma unroll
      for (int j = 0; j < 10; j += 2) stsm4(sb + OFF_PK + j * 2048 + ro, PK(j), PK(j + 1));
    }
    fence_async();
    bar_sync(1, 256);
    if (tid == 0) TS(3);
    mbar_wait(BAR(BR_EPOCH), 0);
    const unsigned epoch = lds32(sb + OFF_EPOCH);
    {
      float kv[24]; zero<24>(kv);
      const uint64_t da = mkdesc(sb + OFF_PK + wg * 5 * 2048, 128, 2048, 0);
      const uint64_t db = mkdesc(sb + OFF_V + wg * 6 * 2048, 128, 2048, 0);
      wg_fence();
      #pragma unroll
      for (int s = 0; s < 8; s++) wg_ss48_tt(kv, da + s * 16, db + s * 16, s != 0);
      wg_commit();
      wg_wait<0>();
      pin<24>(kv);
      if (tid == 0) TS(15);
      if (w4 < 3) {
        const uint32_t wb = sb + OFF_KVS + (wg * 3 + w4) * 1536;
        #pragma unroll
        for (int j = 0; j < 6; j += 2)
          stsm4(wb + (lane & 15) * 96 + (j + (lane >> 4)) * 16, pack2(kv[4 * j], kv[4 * j + 1]), pack2(kv[4 * j + 2], kv[4 * j + 3]),
                pack2(kv[4 * j + 4], kv[4 * j + 5]), pack2(kv[4 * j + 6], kv[4 * j + 7]));
        __syncwarp();
        const int dl = w4 * 16 + (lane & 15), hl = dl >= 20;
        if (dl < 40) {
          uint4* dst = &g_kvp[(c * 16 + r) * 240 + wg * 40 + dl];
          uint32_t v[4];
          lds128(v, wb + (lane & 15) * 96 + (3 * hl + (lane >> 4)) * 16);
          v[3] = (v[3] & ~1u) | (epoch & 1u);
          st128_rlx(dst + (lane >> 4) * 80, v);
          if (lane < 16) {
            v[0] = lds32(wb + lane * 96 + 32 + 8 * hl); v[1] = lds32(wb + lane * 96 + 36 + 8 * hl);
            v[2] = lds32(wb + lane * 96 + 80); v[3] = epoch & 1u;
            st128_rlx(dst + 160, v);
          }
        }
      }
    }
    bar_sync(1, 256);
    if (tid == 0) { st_rlx(&g_flag[c * 32 + r], epoch); mbar_arrive(BAR(BR_PUB)); TS(4); }
    const int kd = tid >= 160 ? tid - 160 : (tid >= 80 ? tid - 80 : tid), kvi = (tid >= 80) + (tid >= 160);
    const int khd = kd / 20, kt0 = 5 * (khd >> 1) + 2 * (khd & 1);
    if (tid < 240) {
      #pragma unroll
      for (int m = 0; m < 3; m++) {
        int q = kt0 + 3 + kvi + 3 * m; if (q >= 10) q -= 10;
        if (kvi + 3 * m < 7) sts128(sb + OFF_KVB + q * 1280 + kd * 16, 0, 0, 0, 0);
      }
    }
    uint32_t qa[20];
    {
      const float sc = 1.44269504089f + __uint_as_float(lds32(sb + OFF_EPOCH) ^ epoch);
      #pragma unroll
      for (int j = 0; j < 10; j++) { qa[2 * j] = pack2(phi(QV(j, 0), sc), phi(QV(j, 1), sc)); qa[2 * j + 1] = pack2(phi(QV(j, 2), sc), phi(QV(j, 3), sc)); }
    }
    if (tid == 0) TS(5);
    {
      poll_all(&g_flag[c * 32 + (lane & 15)], epoch);
      if (tid == 0) TS(6);
      if (tid < 240) {
        uint32_t v[16][4];
        const uint4* src = &g_kvp[c * 16 * 240 + tid];
        #pragma unroll
        for (int i = 0; i < 16; i++) ld128_rlx(v[i], src + i * 240);
        float s[8];
        uint32_t bad = 0;
        #pragma unroll
        for (int i = 0; i < 16; i++) {
          bad |= v[i][3] ^ epoch;
          #pragma unroll
          for (int e = 0; e < 4; e++) {
            s[2 * e] = i ? s[2 * e] + bf_lo(v[i][e]) : bf_lo(v[i][e]);
            s[2 * e + 1] = i ? s[2 * e + 1] + bf_hi(v[i][e]) : bf_hi(v[i][e]);
          }
        }
        if (__builtin_expect(bad & 1u, 0)) {
          #pragma unroll
          for (int e = 0; e < 8; e++) s[e] = 0.f;
          #pragma unroll 1
          for (int i = 0; i < 16; i++) {
            uint32_t w[4] = {0, 0, 0, ~epoch};
            fix128_w3(w, src + i * 240, epoch, 1u);
            #pragma unroll
            for (int e = 0; e < 4; e++) { s[2 * e] += bf_lo(w[e]); s[2 * e + 1] += bf_hi(w[e]); }
          }
        }
        if (tid == 0) TS(18);
        const uint32_t p0 = pack2(s[0], s[1]), p1 = pack2(s[2], s[3]), p2 = pack2(s[4], s[5]), p3 = pack2(s[6], s[7]);
        const uint32_t rb = sb + OFF_KVB + kd * 16;
        if (kvi < 2) sts128(rb + (kt0 + (khd & 1) + kvi) * 1280, p0, p1, p2, p3);
        else {
          const bool od = khd & 1;
          sts128(rb + (5 * (khd >> 1) + 2) * 1280, od ? 0u : p0, od ? 0u : p1, od ? p0 : 0u, od ? p1 : 0u);
          const uint32_t zz = (p2 & 0xffffu) << (16 * (khd & 1));
          sts128(rb + 10 * 1280, khd < 2 ? zz : 0u, khd < 2 ? 0u : zz, 0u, 0u);
        }
      }
    }
    fence_async();
    bar_sync(1, 256);
    if (tid == 0) TS(7);
    uint32_t A0[20], A1[20];
    {
      float oa[44]; zero<44>(oa);
      const uint64_t db = mkdesc(sb + OFF_KVB, 128, 1280, 0);
      wg_fence();
      #pragma unroll
      for (int s = 0; s < 5; s++) wg_rs88_tb(oa, &qa[4 * s], db + s * 16, s != 0);
      wg_commit();
      if (tid == 0) TS(12);
      wg_wait<0>();
      pin<44>(oa);
      if (tid == 0) TS(13);
      float rc[4], rd[2][4];
      #pragma unroll
      for (int e = 0; e < 4; e++) rc[e] = __fdividef(1.f, oa[40 + e] + 1e-6f);
      #pragma unroll
      for (int h = 0; h < 4; h++) {
        rd[0][h] = __shfl_sync(0xffffffff, rc[h & 1], (lane & 28) | (h >> 1));
        rd[1][h] = __shfl_sync(0xffffffff, rc[2 + (h & 1)], (lane & 28) | (h >> 1));
      }
      #pragma unroll
      for (int j = 0; j < 10; j++) {
        #pragma unroll
        for (int h = 0; h < 2; h++) {
          float f;
          if (j == 2) f = tq < 2 ? rd[h][0] : rd[h][1];
          else if (j == 7) f = tq < 2 ? rd[h][2] : rd[h][3];
          else f = rd[h][(8 * j) / 20];
          A0[2 * j + h] = pack2(oa[4 * j + 2 * h] * f, oa[4 * j + 2 * h + 1] * f);
        }
      }
      bar_sync(1, 256);
      #pragma unroll
      for (int s = 0; s < 5; s++) {
        A0[4 * s] = (A0[4 * s] & ~1u) | (epoch & 1u);
        sts128(sb + OFF_EXTRA + ((wg * 5 + s) * 128 + t7) * 16, A0[4 * s], A0[4 * s + 1], A0[4 * s + 2], A0[4 * s + 3]);
      }
    }
    if (tid == 0) TS(14);
    fence_async();
    mbar_arrive(BAR(BR_OSTG));
    if (tid == 0) TS(8);
    float oc[32], od[8]; zero<32>(oc); zero<8>(od);
    {
      const uint64_t dw0 = mkdesc(sb + OFF_WOM, 16, 1024, 1), dr0 = mkdesc(sb, 16, 256, 3);
      mbar_wait(BAR(BR_WO), 0);
      mbar_wait(BAR(BR_WO + 1), 0);
      wg_fence();
      #pragma unroll
      for (int s = 0; s < 5; s++) { wg_rs64_tb(oc, &A0[4 * s], dw0 + c * 640 + s * 128, s != 0); wg_rs16_tb(od, &A0[4 * s], dr0 + c * 160 + s * 32, s != 0); }
      wg_commit();
      #pragma unroll
      for (int i = 0; i < 7; i++) {
        uint32_t* A = (i & 1) ? A0 : A1;
        const uint32_t slot = (i & 3) == 3 ? sb + OFF_EXTRA : sb + OFF_BLK + (4 - (i & 3)) * BLK;
        const int src = (i == 6) ? (c ^ 1) : (((c & 6) + 2 + i) & 7);
        mbar_wait(BAR(BR_OFULL + (i & 3)), i >> 2);
        if (i == 0 && tid == 0) TS(9);
        if (i > 0) wg_wait<1>();
        #pragma unroll
        for (int s = 0; s < 5; s++) lds128(&A[4 * s], slot + ((wg * 5 + s) * 128 + t7) * 16);
        uint32_t bad = 0;
        #pragma unroll
        for (int s = 0; s < 5; s++) bad |= A[4 * s] ^ epoch;
        if (__builtin_expect(bad & 1u, 0)) {
          #pragma unroll
          for (int s = 0; s < 5; s++) fix128_w0(&A[4 * s], &g_o[(r * 8 + src) * 1280 + (wg * 5 + s) * 128 + t7], epoch, 1u);
        }
        __syncwarp();
        if (i < 3 && lane == 0) mbar_arrive(BAR(BR_OEMPTY + i));
        wg_fence();
        #pragma unroll
        for (int s = 0; s < 5; s++) { wg_rs64_tb(oc, &A[4 * s], dw0 + src * 640 + s * 128, 1); wg_rs16_tb(od, &A[4 * s], dr0 + src * 160 + s * 32, 1); }
        wg_commit();
      }
      bar_sync(2 + wg, 128);
      wg_wait<0>();
      pin<32>(oc); pin<8>(od);
    }
    if (tid == 0) TS(10);
    {
      const int row = w4 * 16 + (lane & 15);
      const uint32_t ob = sb + OFF_EXTRA + wg * 10240;
      #pragma unroll
      for (int j = 0; j < 8; j += 2)
        stsm4(ob + row * 128 + (((j + (lane >> 4)) ^ (row & 7)) << 4), pack2(oc[4 * j], oc[4 * j + 1]), pack2(oc[4 * j + 2], oc[4 * j + 3]),
              pack2(oc[4 * j + 4], oc[4 * j + 5]), pack2(oc[4 * j + 6], oc[4 * j + 7]));
      stsm4(ob + 8192 + row * 32 + (lane >> 4) * 16, pack2(od[0], od[1]), pack2(od[2], od[3]), pack2(od[4], od[5]), pack2(od[6], od[7]));
      fence_async();
      bar_sync(2 + wg, 128);
      if (t7 == 0) {
        tma2d_st(&mo64, ob, 640 + c * 64, r * 128 + wg * 64);
        tma2d_st(&mo16, ob + 8192, 1152 + c * 16, r * 128 + wg * 64);
        bulk_commit(); bulk_wait0_read();
      }
      if (tid == 0) { TS(11); DUMP(0, 20); }
    }
    }
  } else {
    asm volatile("setmaxnreg.inc.sync.aligned.u32 152;");
    if (EN_SSM) {
    const int w4 = warp & 3, g = lane >> 2, tq = lane & 3, t7 = tid & 127;
    {
      #pragma unroll
      for (int k = 0; k < 5; k++) {
        const uint32_t tz = sb + OFF_BLK + k * BLK + B_TBL + t7 * 16;
        if (t7 < 32 || t7 >= 96) sts128(tz, 0, 0, 0, 0);
        sts128(tz + 2048, 0, 0, 0, 0);
        if (t7 < 21 || t7 >= 56) sts128(tz + 4096, 0, 0, 0, 0);
      }
      if (t7 < 72) sts128(sb + OFF_BLK - 1152 + t7 * 16, 0, 0, 0, 0);
      if (t7 < 5) sts64(sb + OFF_BLK + t7 * BLK + B_SP + 8, __float_as_uint(bf_round(expf(ldt))), __float_as_uint(dsk0));
      mbar_wait(BAR(BR_PAR), 0);
      #pragma unroll
      for (int k = 0; k < 5; k++) {
        const uint32_t v = lds32(sb + OFF_BLK + k * BLK + B_TBL + 1024 + t7 * 4);
        const uint32_t m = __reduce_max_sync(0xffffffff, max(v & 0x7fffu, (v >> 16) & 0x7fffu));
        if (lane == 0) sts32(sb + OFF_BLK + k * BLK + B_SP + 16 + w4 * 4, m);
      }
    }
    bar_sync(4, 128);
    if (t7 == 0) TS(40);
    {
      const uint32_t fa = sb + OFF_BLK + (w4 & 1) * BLK + (lane >> 3) * 256 + (lane & 7) * 16;
      const uint32_t ea = fa + (w4 >> 1) * 4096, ga = fa + 8192 + (w4 >> 1) * 3072;
      const uint64_t dE = mkdesc(sb + OFF_BLK, 128, 1024, 0), dG = mkdesc(sb + OFF_BLK + 8192, 128, 1024, 0);
      #pragma unroll 1
      for (int k = 4; k >= 0; k--) {
        const uint32_t blk = sb + OFF_BLK + k * BLK;
        float fac, dsk;
        {
          const uint32_t st = blk + B_TBL + 512 + t7 * 2;
          uint32_t q[2], mm[4];
          const uint32_t p0 = lds16(st), p1 = lds16(st + 256), p2 = lds16(st + 512), p3 = lds16(st + 768);
          lds64(q, blk + B_SP + 8); lds128(mm, blk + B_SP + 16);
          const float dt = __uint_as_float(q[0]); dsk = __uint_as_float(q[1]);
          const uint32_t ex = min(max(max(max(mm[0], mm[1]), max(mm[2], mm[3])) >> 7, 1u), 253u);
          const float sc = __uint_as_float((254u - ex) << 23);
          fac = 2.f * dt * __uint_as_float(ex << 23);
          const float lr = -bf_round(expf(bf_lo(p0))) * dt * 1.44269504089f;
          const float tn = bf_lo(p1) * dt * 0.15915494309f;
          float z1r, z1i, z2r, z2i, z4r, z4i, xr[8], xi[8], gr[8], gi[8], wr[9], wi[9];
          cexp_t(lr, -tn, z1r, z1i);
          cexp_t(lr * 8.f, tn * 8.f, xr[1], xi[1]);
          cexp_t(lr * 64.f, tn * 64.f, wr[0], wi[0]);
          xr[0] = 1.f; xi[0] = 0.f;
          cmul(xr[1], xi[1], xr[1], xi[1], xr[2], xi[2]); cmul(xr[2], xi[2], xr[1], xi[1], xr[3], xi[3]);
          cmul(xr[2], xi[2], xr[2], xi[2], xr[4], xi[4]);
          #pragma unroll
          for (int b = 1; b < 4; b++) cmul(xr[4], xi[4], xr[b], xi[b], xr[4 + b], xi[4 + b]);
          cmul(wr[0], wi[0], wr[0], wi[0], wr[1], wi[1]); cmul(wr[1], wi[1], wr[0], wi[0], wr[2], wi[2]);
          cmul(wr[1], wi[1], wr[1], wi[1], wr[3], wi[3]); cmul(wr[3], wi[3], wr[3], wi[3], wr[4], wi[4]);
          cmul(wr[4], wi[4], wr[3], wi[3], wr[5], wi[5]); cmul(wr[4], wi[4], wr[4], wi[4], wr[6], wi[6]);
          cmul(wr[6], wi[6], wr[4], wi[4], wr[7], wi[7]); cmul(wr[6], wi[6], wr[6], wi[6], wr[8], wi[8]);
          uint32_t R[4], I[4], PR[4], PI[4];
          #pragma unroll
          for (int b = 0; b < 4; b++) { R[b] = packh(xr[2 * b], xr[2 * b + 1]); I[b] = packh(xi[2 * b], xi[2 * b + 1]); }
          sts128(ea, R[0], R[1], R[2], R[3]); sts128(ea + 128, I[0], I[1], I[2], I[3]);
          #pragma unroll
          for (int i = 0; i < 3; i++) {
            const uint32_t z = packh(wr[i], wi[i]);
            #pragma unroll
            for (int b = 0; b < 4; b++) hcm2(R[b], I[b], z, PR[b], PI[b]);
            sts128(ea + (i + 1) * 1024, PR[0], PR[1], PR[2], PR[3]); sts128(ea + (i + 1) * 1024 + 128, PI[0], PI[1], PI[2], PI[3]);
          }
          gr[0] = bf_lo(p2) * sc; gi[0] = -bf_lo(p3) * sc;
          cmul(z1r, z1i, z1r, z1i, z2r, z2i); cmul(z2r, z2i, z2r, z2i, z4r, z4i);
          cmul(gr[0], gi[0], z1r, z1i, gr[1], gi[1]);
          cmul(gr[0], gi[0], z2r, z2i, gr[2], gi[2]); cmul(gr[1], gi[1], z2r, z2i, gr[3], gi[3]);
          #pragma unroll
          for (int b = 0; b < 4; b++) cmul(gr[b], gi[b], z4r, z4i, gr[4 + b], gi[4 + b]);
          sts128(ga, packh(gr[0], gr[1]), packh(gr[2], gr[3]), packh(gr[4], gr[5]), packh(gr[6], gr[7]));
          sts128(ga + 128, packh(gi[0], gi[1]), packh(gi[2], gi[3]), packh(gi[4], gi[5]), packh(gi[6], gi[7]));
          {
            const uint32_t z = packh(wr[3], -wi[3]), a4r = packh(gr[0], gr[4]), a4i = packh(gi[0], gi[4]);
            hcm2(packh(gr[0], gr[2]), packh(gi[0], gi[2]), z, PR[0], PI[0]);
            hcm2(packh(gr[4], gr[6]), packh(gi[4], gi[6]), z, PR[1], PI[1]);
            hcm2(a4r, a4i, packh(wr[4], -wi[4]), PR[2], PI[2]);
            hcm2(a4r, a4i, packh(wr[5], -wi[5]), PR[3], PI[3]);
            sts128(ga + 1024, PR[0], PR[1], PR[2], PR[3]); sts128(ga + 1024 + 128, PI[0], PI[1], PI[2], PI[3]);
            float hr, hi_;
            cmul(gr[0], gi[0], wr[3], -wi[3], hr, hi_);
            const uint32_t cr = packh(gr[0], hr), ci = packh(gi[0], hi_);
            #pragma unroll
            for (int i = 0; i < 3; i++) hcm2(cr, ci, packh(wr[6 + i], -wi[6 + i]), PR[i], PI[i]);
            sts128(ga + 2048, PR[0], PR[1], PR[2], 0u); sts128(ga + 2048 + 128, PI[0], PI[1], PI[2], 0u);
          }
        }
        fence_async();
        bar_sync(4, 128);
        if (t7 == 0 && k == 3) TS(50);
        float ka[24]; zero<24>(ka);
        wg_fence();
        #pragma unroll
        for (int s = 0; s < 8; s++) wg_ss48_tt_h(ka, dE + (s >> 2) * (BLK >> 4) + (s & 3) * 16, dG + (s >> 2) * (BLK >> 4) + (s & 3) * 16, s != 0);
        wg_commit();
        wg_wait<0>();
        pin<24>(ka);
        if (t7 == 0 && k == 3) TS(51);
        float kk[6];
        {
          const bool up = w4 >= 2;
          const uint32_t xa = sb + OFF_BLK + 2 * BLK + B_D + 7168 + t7 * 8;
          #pragma unroll
          for (int n = 0; n < 3; n++) {
            sts64f(xa + n * 1024, up ? ka[12 + 4 * n] : ka[4 * n + 2], up ? ka[13 + 4 * n] : ka[4 * n + 3]);
            kk[2 * n] = up ? ka[14 + 4 * n] : ka[4 * n]; kk[2 * n + 1] = up ? ka[15 + 4 * n] : ka[4 * n + 1];
          }
          bar_sync(4, 128);
          #pragma unroll
          for (int n = 0; n < 3; n++) {
            uint32_t o[2]; lds64(o, (xa ^ 512) + n * 1024);
            kk[2 * n] = (kk[2 * n] + __uint_as_float(o[0])) * fac; kk[2 * n + 1] = (kk[2 * n + 1] + __uint_as_float(o[1])) * fac;
          }
        }
        if (t7 == 0 && k == 3) TS(52);
        {
          const int j = (w4 & 1) * 16 + (w4 >> 1) * 8 + g;
          const uint32_t tb = blk + B_TBL;
          if (t7 == 0) kk[0] += dsk;
          const uint32_t pa_ = tb + (64 + 8 * j + 2 * tq) * 4;
          const uint32_t v = pack2(kk[1], kk[0]);
          sts32(pa_ + 4, v); sts16(pa_, v >> 16); sts16(pa_ + 10, v);
          const uint32_t u = pack2(kk[2], kk[3]), w = pack2(kk[4], kk[5]);
          if (tq < 2) {
            const uint32_t pb = tb + (64 + 256 + 8 * j + 4 * tq) * 4;
            sts16(pb, u); sts32(pb + 4, __byte_perm(u, 0, 0x1010)); sts32(pb + 8, __byte_perm(u, 0, 0x1032)); sts16(pb + 14, u >> 16);
            if (j | tq) { sts16(pb - 4, u); sts16(pb + 2, u); }
            const int i = 64 * tq + j;
            const uint32_t e0 = tb + (((i & 1) ? 1040 : 911) + (i >> 1)) * 4, e1 = i ? e0 : tb + 719 * 4;
            sts16(e1, w); sts16(e1 + 6, w); sts16(e0 + 64, w >> 16); sts16(e0 + 70, w >> 16);
            if (i == 0) sts32(blk + B_SP, w << 16);
          } else {
            const int i = 32 * (tq - 2) + j;
            const uint32_t e1 = tb + (i ? 655 + i : 64 + 511) * 4, e2 = tb + (784 + i) * 4;
            sts16(e1, u); sts16(e1 + 6, u); sts16(e2, u >> 16); sts16(e2 + 6, u >> 16);
            if (i == 0) {
              const uint32_t uu = __byte_perm(u, 0, 0x1010);
              sts32(tb + 576 * 4, uu); sts32(tb + 577 * 4, uu); sts32(tb + 578 * 4, uu); sts16(tb + 579 * 4 + 2, u);
              sts16(tb + 975 * 4, w);
            }
          }
        }
        if (t7 == 0 && k == 3) TS(53);
      }
      bar_sync(4, 128);
      if (t7 == 0) { mbar_arrive(BAR(BR_KGEN)); TS(41); }
    }
    mbar_wait(BAR(BR_U), 0);
    if (EN_ATT) mbar_wait(BAR(BR_GEMM), 0);
    if (t7 == 0) TS(42);
    const uint32_t lb = (uint32_t)((16 * w4 + g - 2 * tq - 48) * 4);
    float yv[16];
    zero<16>(yv);
    uint32_t A0[20], A1[16], A2[16];
    const uint32_t r0 = lds32(sb + OFF_BLK - 16), r1 = r0 + 1;
    load_toep<4>(A0, sb + OFF_BLK + 4 * BLK + B_TBL + lb + 912 * 4);
    auto y_epilogue = [&](uint32_t blk, int k) {
      const int ln = opaque(lane), tt = ln & 3;
      const uint32_t b0 = (128 * tt + ((16 * w4) ^ (8 * tt)) + (ln >> 2)) * 4;
      #pragma unroll
      for (int n = 1; n < 4; n++)
        #pragma unroll
        for (int e = 0; e < 4; e++) {
          const uint32_t a = blk + B_D + (b0 ^ (32 * (e >> 1))) + (512 * (n - 1) + 64 * (e & 1)) * 4;
          yv[4 * n + e] += ldsf(a);
          if (n >= 2) yv[4 * n + e] += ldsf(a + 6144 - 2048);
        }
      const uint32_t ya = blk + (8 * (ln >> 4) + (ln & 7)) * 128 + (((2 * w4 + ((ln >> 3) & 1)) ^ (ln & 7)) << 4);
      #pragma unroll
      for (int n = 0; n < 4; n += 2)
        stsm4t(ya + n * 1024, pack2(yv[4 * n], yv[4 * n + 1]), pack2(yv[4 * n + 2], yv[4 * n + 3]),
               pack2(yv[4 * n + 4], yv[4 * n + 5]), pack2(yv[4 * n + 6], yv[4 * n + 7]));
      fence_async();
      mbar_arrive(BAR(BR_YSTG) + 8 * k);
      if (t7 == 0) TS(47 - k);
    };
    #pragma unroll 1
    for (int k = 4; k >= 0; k--) {
      const uint32_t blk = sb + OFF_BLK + k * BLK, tb = blk + B_TBL + lb;
      const uint64_t dd = mkdesc(blk + B_D, 128, 1024, 0);
      const uint64_t du = mkdesc(blk + 96 - 32 * 36, 16, 1024, 1);
      float aC[8], a24[12], a16[8], aY[16];
      zero<8>(aC); zero<12>(a24); zero<8>(a16); zero<16>(aY);
      mbar_wait(BAR(BR_DRDY) + 8 * k, 0);
      if (k == 1) mbar_wait(BAR(BR_U2), 0);
      if (t7 == 0 && k == 3) TS(57);
#define GROUP(n, MMA, N, nn, naddr) { \
        wg_wait<1>(); wg_fence(); \
        const uint32_t na_ = (naddr); \
        _Pragma("unroll") for (int s = 0; s < (n); s++) { \
          MMA; \
          if (s == 0) { N[2] = lds32v(na_ - 32); N[0] = lds32v(na_); N[1] = lds32v(na_ + 32); N[4] = lds32v(na_ + 64); } \
          if (s == 1) { N[5] = lds32v(na_ + 96); N[8] = lds32v(na_ + 128); N[9] = lds32v(na_ + 160); N[12] = lds32v(na_ + 192); } \
          if (s == 2) { N[13] = lds32v(na_ + 224); if ((nn) > 4) { N[16] = lds32v(na_ + 256); N[17] = lds32v(na_ + 288); } \
                        N[3] = cpa(N[0], r1); N[6] = cpb(N[1], r0); N[7] = cpa(N[4], r1); } \
        } \
        wg_commit(); \
        N[10] = cpa(N[5], r1); N[11] = cpb(N[8], r0); N[14] = cpa(N[9], r1); N[15] = cpb(N[12], r0); \
        if ((nn) > 4) { N[18] = cpa(N[13], r1); N[19] = cpb(N[16], r0); } }
#define FAR(fn, acc, A, off, first) fn(acc, &A[4 * s], dd + ((off) >> 4) + (3 - s) * 16, !(first) || s != 0)
#define DEN(A, s0) wg_rs32(aY, &A[4 * s], du + (36 - ((s0) + s)) * 2, (s0) + s != 0)
      GROUP(4, FAR(wg_rs16_tb, aC, A0, B_D9, true), A1, 4, tb + 1040 * 4)
      GROUP(4, FAR(wg_rs16_tb, aC, A1, B_D7, false), A2, 4, tb + 656 * 4)
      if (k < 4) { bar_sync(4, 128); y_epilogue(blk + BLK, k + 1); }
      GROUP(4, FAR(wg_rs24_tb, a24, A2, 0, true), A0, 4, tb + 720 * 4)
      GROUP(4, FAR(wg_rs16_tb, a16, A0, 0, true), A1, 4, tb + 784 * 4)
      GROUP(4, FAR(wg_rs24_tb, a24, A1, B_D3, false), A2, 4, tb + 848 * 4)
      GROUP(4, FAR(wg_rs16_tb, a16, A2, B_D3, false), A0, 5, tb + 64 * 4)
      if (t7 == 0 && k == 3) TS(58);
      GROUP(5, DEN(A0, 0), A1, 4, tb + (64 + 80) * 4)
      GROUP(4, DEN(A1, 5), A2, 4, tb + (64 + 144) * 4)
      if (t7 == 0 && k == 3) TS(59);
      {
        pin<8>(aC); pin<12>(a24); pin<8>(a16);
        bar_sync(4, 128);
        const float kc = ldsf(blk + B_SP);
        const int ln = opaque(lane), gg = ln >> 2, q2 = (ln & 3) * 2;
        const uint32_t f1 = blk + B_D + (128 * w4 + ((8 * gg) ^ (8 * w4)) + q2) * 4;
        const uint32_t f2 = blk + B_D + 6144 + (256 * w4 + ((16 * gg) ^ (16 * (w4 & 1))) + q2) * 4;
        #pragma unroll
        for (int h = 0; h < 2; h++) {
          #pragma unroll
          for (int jp = 0; jp < 3; jp++) {
            float x = a24[4 * jp + 2 * h], y = a24[4 * jp + 2 * h + 1];
            if (jp > 0) { x += a16[4 * (jp - 1) + 2 * h]; y += a16[4 * (jp - 1) + 2 * h + 1]; }
            sts64f(f1 + (64 * h + 512 * jp) * 4, x, y);
          }
          #pragma unroll
          for (int n = 0; n < 2; n++) {
            const int s4 = 256 * w4 + 16 * gg + 128 * h + 8 * n + q2 - 4, s2 = s4 + 2;
            const uint32_t u4 = lds32(blk + (uint32_t)((2 * s4) ^ ((s4 >> 2) & 0x70)));
            const uint32_t u2 = lds32(blk + (uint32_t)((2 * s2) ^ ((s2 >> 2) & 0x70)));
            const float x = fmaf(kc, bf_lo(u4) + bf_hi(u4), aC[4 * n + 2 * h]);
            const float y = fmaf(kc, bf_hi(u4) + bf_lo(u2), aC[4 * n + 2 * h + 1]);
            sts64f(f2 + (128 * h + 8 * (n ^ h)) * 4, x, y);
          }
        }
      }
      if (t7 == 0 && k == 3) TS(60);
      GROUP(4, DEN(A2, 9), A0, 4, tb + (64 + 208) * 4)
      GROUP(4, DEN(A0, 13), A1, 4, tb + (64 + 272) * 4)
      GROUP(4, DEN(A1, 17), A2, 4, tb + (64 + 336) * 4)
      GROUP(4, DEN(A2, 21), A0, 4, tb + (64 + 400) * 4)
      GROUP(4, DEN(A0, 25), A1, 4, tb + (64 + 464) * 4)
      GROUP(4, DEN(A1, 29), A2, 4, tb + (64 + 528) * 4)
      GROUP(4, DEN(A2, 33), A0, 4, tb - (k ? BLK : 0) + 912 * 4)
      if (t7 == 0 && k == 3) TS(61);
      wg_wait<0>();
      pin<16>(aY);
      #pragma unroll
      for (int e = 0; e < 16; e++) yv[e] = aY[e];
    }
    bar_sync(4, 128);
    y_epilogue(sb + OFF_BLK, 0);
    if (t7 == 0) DUMP(40, 64);
    }
  }
}

typedef CUresult (*EncFn)(CUtensorMap*, CUtensorMapDataType, cuuint32_t, void*, const cuuint64_t*, const cuuint64_t*, const cuuint32_t*,
                          const cuuint32_t*, CUtensorMapInterleave, CUtensorMapSwizzle, CUtensorMapL2promotion, CUtensorMapFloatOOBfill);
static CUtensorMap mkmap(EncFn enc, const void* base, int rank, const cuuint64_t* dims, const cuuint64_t* strides, const cuuint32_t* box, CUtensorMapSwizzle swz) {
  CUtensorMap m; cuuint32_t es[5] = {1, 1, 1, 1, 1};
  enc(&m, CU_TENSOR_MAP_DATA_TYPE_BFLOAT16, rank, const_cast<void*>(base), dims, strides, box, es, CU_TENSOR_MAP_INTERLEAVE_NONE, swz,
      CU_TENSOR_MAP_L2_PROMOTION_L2_128B, CU_TENSOR_MAP_FLOAT_OOB_FILL_NONE);
  return m;
}

extern "C" void kernel_launch(void* const* d_in, const int* in_sizes, int n_in, void* d_out, int out_size) {
  void* fn = nullptr; cudaDriverEntryPointQueryResult qr;
  cudaGetDriverEntryPoint("cuTensorMapEncodeTiled", &fn, cudaEnableDefault, &qr);
  EncFn enc = (EncFn)fn;
  void* uy = nullptr; cudaGetSymbolAddress(&uy, g_uy);
  const cuuint64_t dx[2] = {640, 2048}, sx[1] = {1280};
  const cuuint32_t bx[2] = {64, 128}, bu[2] = {80, 64};
  const cuuint64_t dw[3] = {640, 640, 3}, sw[2] = {3840, 1280};
  const cuuint32_t bw[3] = {64, 32, 3}, br[3] = {16, 32, 3};
  const cuuint64_t dwo[2] = {640, 640};
  const cuuint32_t bwo[2] = {64, 80}, bwr[2] = {16, 160}, bo64[2] = {64, 64}, bo16[2] = {16, 64};
  const cuuint64_t dsa[2] = {2048, 1280}, ssa[1] = {4096};
  const cuuint32_t bsa[2] = {64, 80};
  const cuuint64_t dsb[2] = {64, 40960}, ssb[1] = {128};
  const cuuint32_t bsb[2] = {64, 32};
  const cuuint64_t dout[2] = {1280, 2048}, sout[1] = {2560};
  CUtensorMap mx = mkmap(enc, d_in[7], 2, dx, sx, bx, CU_TENSOR_MAP_SWIZZLE_128B);
  CUtensorMap mw = mkmap(enc, d_in[8], 3, dw, sw, bw, CU_TENSOR_MAP_SWIZZLE_128B);
  CUtensorMap mr = mkmap(enc, d_in[8], 3, dw, sw, br, CU_TENSOR_MAP_SWIZZLE_32B);
  CUtensorMap mwo = mkmap(enc, d_in[9], 2, dwo, sx, bwo, CU_TENSOR_MAP_SWIZZLE_128B);
  CUtensorMap mwr = mkmap(enc, d_in[9], 2, dwo, sx, bwr, CU_TENSOR_MAP_SWIZZLE_32B);
  CUtensorMap mo64 = mkmap(enc, d_out, 2, dout, sout, bo64, CU_TENSOR_MAP_SWIZZLE_128B);
  CUtensorMap mo16 = mkmap(enc, d_out, 2, dout, sout, bo16, CU_TENSOR_MAP_SWIZZLE_NONE);
  CUtensorMap mu = mkmap(enc, d_in[0], 2, dx, sx, bu, CU_TENSOR_MAP_SWIZZLE_NONE);
  CUtensorMap msa = mkmap(enc, uy, 2, dsa, ssa, bsa, CU_TENSOR_MAP_SWIZZLE_128B);
  CUtensorMap msb = mkmap(enc, uy, 2, dsb, ssb, bsb, CU_TENSOR_MAP_SWIZZLE_128B);
  CUtensorMap mout = mkmap(enc, d_out, 2, dout, sout, bu, CU_TENSOR_MAP_SWIZZLE_NONE);
  Params prm;
  prm.logA = (const __nv_bfloat16*)d_in[1]; prm.Aim = (const __nv_bfloat16*)d_in[2];
  prm.Cr = (const __nv_bfloat16*)d_in[3]; prm.Ci = (const __nv_bfloat16*)d_in[4];
  prm.logdt = (const __nv_bfloat16*)d_in[5]; prm.dskip = (const __nv_bfloat16*)d_in[6];
  cudaFuncSetAttribute(fused_kernel, cudaFuncAttributeMaxDynamicSharedMemorySize, SMEM_BYTES);
  cudaLaunchConfig_t cfg = {};
  cfg.gridDim = dim3(128); cfg.blockDim = dim3(512); cfg.dynamicSmemBytes = SMEM_BYTES; cfg.stream = cudaStreamPerThread;
  cudaLaunchAttribute at[1];
  at[0].id = cudaLaunchAttributeClusterDimension; at[0].val.clusterDim.x = 2; at[0].val.clusterDim.y = 1; at[0].val.clusterDim.z = 1;
  cfg.attrs = at; cfg.numAttrs = 1;
  cudaLaunchKernelEx(&cfg, fused_kernel, mx, mw, mr, mwo, mwr, mo64, mo16, mu, msa, msb, mout, prm);
}
```

```cpp
#include <cuda_runtime.h>
#include <cuda_bf16.h>
#include <cuda_fp16.h>
#include <cuda.h>
#include <stdint.h>

#define EN_ATT 1
#define EN_SSM 1

__device__ __align__(1024) __nv_bfloat16 g_uy[2 * 640 * 2048];
__device__ __align__(128) uint4 g_kvp[8 * 16 * 240];
__device__ __align__(128) uint4 g_o[128 * 1280];
__device__ __align__(128) unsigned g_flag[40 * 32];
__device__ unsigned g_epoch[128];
#define TS(i) do {} while (0)
#define DUMP(lo, hi) do {} while (0)

constexpr uint32_t W_SLOT = 15360, OFF_X = 76800;
constexpr uint32_t OFF_WOM = 20480, OFF_KVS = 71680, OFF_PK = 80896, OFF_V = 101376, OFF_EXTRA = 102400, OFF_KVB = OFF_EXTRA;
constexpr uint32_t OFF_BAR = 125952, OFF_BLK = 128000, BLK = 20480;
constexpr uint32_t B_D = 4096, B_D5 = 3088, B_D7 = 6176, B_D9 = 8224, B_TBL = 14400, B_SP = 18432;
constexpr int T_S = 576, T_F2 = 624, T_F3 = 816;
constexpr uint32_t SMEM_BYTES = OFF_BLK + 5 * BLK + 1024;
enum { BR_FULL = 0, BR_EMPTY = 5, BR_WO = 10, BR_PUB = 12, BR_PAR = 13, BR_U2 = 14, BR_OFULL = 18, BR_OEMPTY = 22, BR_GEMM = 26, BR_OSTG = 27, BR_UIN = 28,
       BR_U = 29, BR_DRDY = 30, BR_KGEN = 35, BR_YSTG = 36, BR_FREE = 41, BR_YIN = 46, BR_EPOCH = 47, BR_COUNT = 48 };
constexpr uint32_t OFF_EPOCH = OFF_BAR + 8 * BR_COUNT;

__device__ __forceinline__ long long clk64() { long long t; asm volatile("mov.u64 %0, %%clock64;" : "=l"(t) :: "memory"); return t; }
__device__ __forceinline__ uint32_t smem_u32(const void* p) { return (uint32_t)__cvta_generic_to_shared(p); }
__device__ __forceinline__ uint64_t mkdesc(uint32_t addr, uint32_t lbo, uint32_t sbo, uint32_t swz) {
  return (uint64_t)((addr & 0x3FFFF) >> 4) | ((uint64_t)(lbo >> 4) << 16) | ((uint64_t)(sbo >> 4) << 32) | ((uint64_t)swz << 62);
}
__device__ __forceinline__ void mbar_init(uint32_t bar, uint32_t cnt) { asm volatile("mbarrier.init.shared::cta.b64 [%0], %1;" :: "r"(bar), "r"(cnt) : "memory"); }
__device__ __forceinline__ void mbar_expect_tx(uint32_t bar, uint32_t bytes) { asm volatile("mbarrier.arrive.expect_tx.shared::cta.b64 _, [%0], %1;" :: "r"(bar), "r"(bytes) : "memory"); }
__device__ __forceinline__ void mbar_arrive(uint32_t bar) { asm volatile("mbarrier.arrive.shared::cta.b64 _, [%0];" :: "r"(bar) : "memory"); }
__device__ __forceinline__ void mbar_wait(uint32_t bar, uint32_t parity) {
  asm volatile("{\n.reg .pred p;\n.reg .u32 c;\nmov.u32 c, 0;\n"
    "WL:\nmbarrier.try_wait.parity.shared::cta.b64 p, [%0], %1;\n@p bra WD;\n"
    "add.u32 c, c, 1;\nsetp.lt.u32 p, c, 200000;\n@p bra WL;\nWD:\n}" :: "r"(bar), "r"(parity) : "memory");
}
__device__ __forceinline__ void poll_all(const unsigned* p, unsigned val) {
  asm volatile("{\n.reg .pred p;\n.reg .u32 c, v;\nmov.u32 c, 0;\n"
    "PL:\nld.relaxed.gpu.global.u32 v, [%0];\nsetp.eq.u32 p, v, %1;\nvote.sync.all.pred p, p, 0xffffffff;\n@p bra PD;\n"
    "add.u32 c, c, 1;\nsetp.lt.u32 p, c, 100000;\n@p bra PL;\nPD:\n}" :: "l"(p), "r"(val) : "memory");
}
__device__ __forceinline__ unsigned poll_bit(const unsigned* p, unsigned val, unsigned mask) {
  unsigned bal;
  asm volatile("{\n.reg .pred p;\n.reg .u32 c, v;\nmov.u32 c, 0;\n"
    "PL:\nld.relaxed.gpu.global.u32 v, [%1];\nsetp.eq.u32 p, v, %2;\nvote.sync.ballot.b32 %0, p, 0xffffffff;\n"
    "and.b32 v, %0, %3;\nsetp.ne.u32 p, v, 0;\n@p bra PD;\n"
    "add.u32 c, c, 1;\nsetp.lt.u32 p, c, 100000;\n@p bra PL;\nPD:\n}" : "=&r"(bal) : "l"(p), "r"(val), "r"(mask) : "memory");
  return bal;
}
__device__ __forceinline__ void fix128_w0(uint32_t* v, const void* p, uint32_t tag, uint32_t mask) {
  asm volatile("{\n.reg .pred p;\n.reg .u32 c, x;\n.reg .b128 t;\n.reg .b64 lo, hi;\nmov.u32 c, 0;\n"
    "FL:\nxor.b32 x, %0, %5;\nand.b32 x, x, %6;\nsetp.eq.u32 p, x, 0;\n@p bra FD;\n"
    "ld.relaxed.gpu.global.b128 t, [%4];\nmov.b128 {lo, hi}, t;\nmov.b64 {%0, %1}, lo;\nmov.b64 {%2, %3}, hi;\n"
    "add.u32 c, c, 1;\nsetp.lt.u32 p, c, 100000;\n@p bra FL;\nFD:\n}"
    : "+r"(v[0]), "+r"(v[1]), "+r"(v[2]), "+r"(v[3]) : "l"(p), "r"(tag), "r"(mask) : "memory");
}
__device__ __forceinline__ void fix128_w3(uint32_t* v, const void* p, uint32_t tag, uint32_t mask) {
  asm volatile("{\n.reg .pred p;\n.reg .u32 c, x;\n.reg .b128 t;\n.reg .b64 lo, hi;\nmov.u32 c, 0;\n"
    "FL:\nxor.b32 x, %3, %5;\nand.b32 x, x, %6;\nsetp.eq.u32 p, x, 0;\n@p bra FD;\n"
    "ld.relaxed.gpu.global.b128 t, [%4];\nmov.b128 {lo, hi}, t;\nmov.b64 {%0, %1}, lo;\nmov.b64 {%2, %3}, hi;\n"
    "add.u32 c, c, 1;\nsetp.lt.u32 p, c, 100000;\n@p bra FL;\nFD:\n}"
    : "+r"(v[0]), "+r"(v[1]), "+r"(v[2]), "+r"(v[3]) : "l"(p), "r"(tag), "r"(mask) : "memory");
}
__device__ __forceinline__ void fence_acq() { asm volatile("fence.acq_rel.gpu;" ::: "memory"); }
__device__ __forceinline__ bool elect_one() {
  uint32_t p; asm volatile("{\n.reg .pred P;\nelect.sync _|P, 0xffffffff;\nselp.u32 %0, 1, 0, P;\n}" : "=r"(p)); return p;
}
__device__ __forceinline__ void bar_sync(int id, int n) { asm volatile("bar.sync %0, %1;" :: "r"(id), "r"(n) : "memory"); }
__device__ __forceinline__ void fence_async() { asm volatile("fence.proxy.async.shared::cta;" ::: "memory"); }
__device__ __forceinline__ void fence_async_g() { asm volatile("fence.proxy.async.global;" ::: "memory"); }
__device__ __forceinline__ void tma2d(uint32_t dst, const CUtensorMap* m, uint32_t bar, int c0, int c1) {
  asm volatile("cp.async.bulk.tensor.2d.shared::cluster.global.mbarrier::complete_tx::bytes [%0], [%1, {%3, %4}], [%2];"
    :: "r"(dst), "l"(m), "r"(bar), "r"(c0), "r"(c1) : "memory");
}
__device__ __forceinline__ void tma3d(uint32_t dst, const CUtensorMap* m, uint32_t bar, int c0, int c1, int c2) {
  asm volatile("cp.async.bulk.tensor.3d.shared::cluster.global.mbarrier::complete_tx::bytes [%0], [%1, {%3, %4, %5}], [%2];"
    :: "r"(dst), "l"(m), "r"(bar), "r"(c0), "r"(c1), "r"(c2) : "memory");
}
__device__ __forceinline__ void tma2d_st(const CUtensorMap* m, uint32_t src, int c0, int c1) {
  asm volatile("cp.async.bulk.tensor.2d.global.shared::cta.bulk_group [%0, {%2, %3}], [%1];"
    :: "l"(m), "r"(src), "r"(c0), "r"(c1) : "memory");
}
__device__ __forceinline__ void bulk_ld(uint32_t dst, const void* src, uint32_t bytes, uint32_t bar) {
  asm volatile("cp.async.bulk.shared::cluster.global.mbarrier::complete_tx::bytes [%0], [%1], %2, [%3];"
    :: "r"(dst), "l"(src), "r"(bytes), "r"(bar) : "memory");
}
__device__ __forceinline__ void bulk_st(void* dst, uint32_t src, uint32_t bytes) {
  asm volatile("cp.async.bulk.global.shared::cta.bulk_group [%0], [%1], %2;" :: "l"(dst), "r"(src), "r"(bytes) : "memory");
}
__device__ __forceinline__ void bulk_commit() { asm volatile("cp.async.bulk.commit_group;" ::: "memory"); }
__device__ __forceinline__ void bulk_wait0() { asm volatile("cp.async.bulk.wait_group 0;" ::: "memory"); }
__device__ __forceinline__ void bulk_wait0_read() { asm volatile("cp.async.bulk.wait_group.read 0;" ::: "memory"); }
__device__ __forceinline__ unsigned ld_rlx(const unsigned* p) { unsigned v; asm volatile("ld.relaxed.gpu.global.u32 %0, [%1];" : "=r"(v) : "l"(p) : "memory"); return v; }
__device__ __forceinline__ unsigned ld_acq(const unsigned* p) { unsigned v; asm volatile("ld.acquire.gpu.global.u32 %0, [%1];" : "=r"(v) : "l"(p) : "memory"); return v; }
__device__ __forceinline__ void st_rlx(unsigned* p, unsigned v) { asm volatile("st.relaxed.gpu.global.u32 [%0], %1;" :: "l"(p), "r"(v) : "memory"); }
__device__ __forceinline__ void st_rel(unsigned* p, unsigned v) { asm volatile("st.release.gpu.global.u32 [%0], %1;" :: "l"(p), "r"(v) : "memory"); }
__device__ __forceinline__ void ld128_rlx(uint32_t* v, const void* p) {
  asm volatile("{\n.reg .b128 t;\n.reg .b64 lo, hi;\nld.relaxed.gpu.global.b128 t, [%4];\nmov.b128 {lo, hi}, t;\n"
    "mov.b64 {%0, %1}, lo;\nmov.b64 {%2, %3}, hi;\n}" : "=r"(v[0]), "=r"(v[1]), "=r"(v[2]), "=r"(v[3]) : "l"(p) : "memory");
}
__device__ __forceinline__ void st128_rlx(void* p, const uint32_t* v) {
  asm volatile("{\n.reg .b128 t;\n.reg .b64 lo, hi;\nmov.b64 lo, {%1, %2};\nmov.b64 hi, {%3, %4};\nmov.b128 t, {lo, hi};\n"
    "st.relaxed.gpu.global.b128 [%0], t;\n}" :: "l"(p), "r"(v[0]), "r"(v[1]), "r"(v[2]), "r"(v[3]) : "memory");
}
__device__ __forceinline__ uint32_t lds32(uint32_t a) { uint32_t v; asm volatile("ld.shared.u32 %0, [%1];" : "=r"(v) : "r"(a) : "memory"); return v; }
__device__ __forceinline__ uint32_t lds32v(uint32_t a) { uint32_t v; asm volatile("ld.volatile.shared.u32 %0, [%1];" : "=r"(v) : "r"(a) : "memory"); return v; }
__device__ __forceinline__ uint32_t cpa(uint32_t a, uint32_t one) { uint32_t v; asm volatile("mul.lo.u32 %0, %1, %2;" : "=r"(v) : "r"(a), "r"(one)); return v; }
__device__ __forceinline__ uint32_t cpb(uint32_t a, uint32_t zero) { uint32_t v; asm volatile("or.b32 %0, %1, %2;" : "=r"(v) : "r"(a), "r"(zero)); return v; }
__device__ __forceinline__ uint32_t lds16(uint32_t a) { uint16_t v; asm volatile("ld.shared.u16 %0, [%1];" : "=h"(v) : "r"(a) : "memory"); return v; }
__device__ __forceinline__ float ldsf(uint32_t a) { float v; asm volatile("ld.shared.f32 %0, [%1];" : "=f"(v) : "r"(a) : "memory"); return v; }
__device__ __forceinline__ void lds128(uint32_t* v, uint32_t a) { asm volatile("ld.shared.v4.u32 {%0,%1,%2,%3}, [%4];" : "=r"(v[0]), "=r"(v[1]), "=r"(v[2]), "=r"(v[3]) : "r"(a) : "memory"); }
__device__ __forceinline__ void sts32(uint32_t a, uint32_t v) { asm volatile("st.shared.u32 [%0], %1;" :: "r"(a), "r"(v) : "memory"); }
__device__ __forceinline__ void sts16(uint32_t a, uint32_t v) { asm volatile("st.shared.u16 [%0], %1;" :: "r"(a), "h"((uint16_t)v) : "memory"); }
__device__ __forceinline__ void sts64f(uint32_t a, float x, float y) { asm volatile("st.shared.v2.f32 [%0], {%1,%2};" :: "r"(a), "f"(x), "f"(y) : "memory"); }
__device__ __forceinline__ void sts128(uint32_t a, uint32_t x, uint32_t y, uint32_t z, uint32_t w) { asm volatile("st.shared.v4.u32 [%0], {%1,%2,%3,%4};" :: "r"(a), "r"(x), "r"(y), "r"(z), "r"(w) : "memory"); }
__device__ __forceinline__ void stsm4(uint32_t a, uint32_t r0, uint32_t r1, uint32_t r2, uint32_t r3) {
  asm volatile("stmatrix.sync.aligned.m8n8.x4.shared.b16 [%0], {%1,%2,%3,%4};" :: "r"(a), "r"(r0), "r"(r1), "r"(r2), "r"(r3) : "memory");
}
__device__ __forceinline__ void stsm4t(uint32_t a, uint32_t r0, uint32_t r1, uint32_t r2, uint32_t r3) {
  asm volatile("stmatrix.sync.aligned.m8n8.x4.trans.shared.b16 [%0], {%1,%2,%3,%4};" :: "r"(a), "r"(r0), "r"(r1), "r"(r2), "r"(r3) : "memory");
}
__device__ __forceinline__ void ldsm4t(uint32_t* r, uint32_t a) {
  asm volatile("ldmatrix.sync.aligned.m8n8.x4.trans.shared.b16 {%0,%1,%2,%3}, [%4];" : "=r"(r[0]), "=r"(r[1]), "=r"(r[2]), "=r"(r[3]) : "r"(a) : "memory");
}
__device__ __forceinline__ void ldsm4(uint32_t* r, uint32_t a) {
  asm volatile("ldmatrix.sync.aligned.m8n8.x4.shared.b16 {%0,%1,%2,%3}, [%4];" : "=r"(r[0]), "=r"(r[1]), "=r"(r[2]), "=r"(r[3]) : "r"(a) : "memory");
}
__device__ __forceinline__ void mma16816(float* d, const uint32_t* a, const uint32_t* b) {
  asm volatile("mma.sync.aligned.m16n8k16.row.col.f32.bf16.bf16.f32 {%0,%1,%2,%3}, {%4,%5,%6,%7}, {%8,%9}, {%0,%1,%2,%3};"
    : "+f"(d[0]), "+f"(d[1]), "+f"(d[2]), "+f"(d[3]) : "r"(a[0]), "r"(a[1]), "r"(a[2]), "r"(a[3]), "r"(b[0]), "r"(b[1]));
}
__device__ __forceinline__ uint32_t pack2(float lo, float hi) { uint32_t r; asm("cvt.rn.bf16x2.f32 %0, %1, %2;" : "=r"(r) : "f"(hi), "f"(lo)); return r; }
__device__ __forceinline__ uint32_t packh(float lo, float hi) { uint32_t r; asm("cvt.rn.f16x2.f32 %0, %1, %2;" : "=r"(r) : "f"(hi), "f"(lo)); return r; }
__device__ __forceinline__ uint32_t hcmul(uint32_t x, uint32_t zp, uint32_t zq) {
  const __half2 xx = *reinterpret_cast<__half2*>(&x);
  const __half2 r = __hfma2(__high2half2(xx), *reinterpret_cast<__half2*>(&zq), __hmul2(__low2half2(xx), *reinterpret_cast<__half2*>(&zp)));
  return *reinterpret_cast<const uint32_t*>(&r);
}
__device__ __forceinline__ void hcm2(uint32_t xr, uint32_t xi, uint32_t z, uint32_t& pr, uint32_t& pi) {
  const __half2 a = *reinterpret_cast<__half2*>(&xr), b = *reinterpret_cast<__half2*>(&xi), zz = *reinterpret_cast<__half2*>(&z);
  const __half2 re = __hfma2(__hneg2(b), __high2half2(zz), __hmul2(a, __low2half2(zz)));
  const __half2 im = __hfma2(a, __high2half2(zz), __hmul2(b, __low2half2(zz)));
  pr = *reinterpret_cast<const uint32_t*>(&re); pi = *reinterpret_cast<const uint32_t*>(&im);
}
__device__ __forceinline__ void sts64(uint32_t a, uint32_t x, uint32_t y) { asm volatile("st.shared.v2.u32 [%0], {%1,%2};" :: "r"(a), "r"(x), "r"(y) : "memory"); }
__device__ __forceinline__ void lds64(uint32_t* v, uint32_t a) { asm volatile("ld.shared.v2.u32 {%0,%1}, [%2];" : "=r"(v[0]), "=r"(v[1]) : "r"(a) : "memory"); }
__device__ __forceinline__ float bf_lo(uint32_t v) { return __uint_as_float(v << 16); }
__device__ __forceinline__ float bf_hi(uint32_t v) { return __uint_as_float(v & 0xffff0000u); }
__device__ __forceinline__ float bf_round(float x) { return bf_lo(pack2(x, 0.f)); }
__device__ __forceinline__ float ex2(float x) { float r; asm("ex2.approx.ftz.f32 %0, %1;" : "=f"(r) : "f"(x)); return r; }
__device__ __forceinline__ float phi(float t, float l2e = 1.44269504089f) { float e = ex2(t * l2e); return (t > 0.f ? t + 1.f : e) + 1e-6f; }
__device__ __forceinline__ void wg_fence() { asm volatile("wgmma.fence.sync.aligned;" ::: "memory"); }
__device__ __forceinline__ void wg_commit() { asm volatile("wgmma.commit_group.sync.aligned;" ::: "memory"); }
template <int N> __device__ __forceinline__ void wg_wait() { asm volatile("wgmma.wait_group.sync.aligned %0;" :: "n"(N) : "memory"); }
template <int N> __device__ __forceinline__ void pin(float* a) {
  #pragma unroll
  for (int i = 0; i < N; i++) asm volatile("" : "+f"(a[i]) :: "memory");
}
__device__ __forceinline__ int opaque(int v) { asm volatile("" : "+r"(v)); return v; }
template <int N> __device__ __forceinline__ void zero(float* a) {
  #pragma unroll
  for (int i = 0; i < N; i++) asm volatile("mov.b32 %0, 0;" : "=f"(a[i]));
}
template <int N> __device__ __forceinline__ void pinu(uint32_t* a) {
  #pragma unroll
  for (int i = 0; i < N; i++) asm volatile("" : "+r"(a[i]) :: "memory");
}
__device__ __forceinline__ void cexp_t(float lg2mag, float turns, float& re, float& im) {
  float m = ex2(lg2mag);
  float fr = (turns - __fadd_rn(__fadd_rn(turns, 12582912.f), -12582912.f)) * 6.283185307f;
  re = m * __cosf(fr); im = m * __sinf(fr);
}
__device__ __forceinline__ void cmul(float ar, float ai, float br, float bi, float& cr, float& ci) {
  cr = fmaf(ar, br, -ai * bi); ci = fmaf(ar, bi, ai * br);
}

__device__ __forceinline__ void wg_ss192_tb(float* d, uint64_t da, uint64_t db, int scale_d) {
  asm volatile("{\n.reg .pred p;\nsetp.ne.b32 p, %98, 0;\n"
    "wgmma.mma_async.sync.aligned.m64n192k16.f32.bf16.bf16 "
    "{%0, %1, %2, %3, %4, %5, %6, %7, %8, %9, %10, %11, %12, %13, %14, %15, %16, %17, %18, %19, %20, %21, %22, %23, %24, %25, %26, %27, %28, %29, %30, %31, %32, %33, %34, %35, %36, %37, %38, %39, %40, %41, %42, %43, %44, %45, %46, %47, %48, %49, %50, %51, %52, %53, %54, %55, %56, %57, %58, %59, %60, %61, %62, %63, %64, %65, %66, %67, %68, %69, %70, %71, %72, %73, %74, %75, %76, %77, %78, %79, %80, %81, %82, %83, %84, %85, %86, %87, %88, %89, %90, %91, %92, %93, %94, %95}, %96, %97, p, 1, 1, 0, 1;\n}\n"
    : "+f"(d[0]), "+f"(d[1]), "+f"(d[2]), "+f"(d[3]), "+f"(d[4]), "+f"(d[5]), "+f"(d[6]), "+f"(d[7]), "+f"(d[8]), "+f"(d[9]), "+f"(d[10]), "+f"(d[11]), "+f"(d[12]), "+f"(d[13]), "+f"(d[14]), "+f"(d[15]), "+f"(d[16]), "+f"(d[17]), "+f"(d[18]), "+f"(d[19]), "+f"(d[20]), "+f"(d[21]), "+f"(d[22]), "+f"(d[23]), "+f"(d[24]), "+f"(d[25]), "+f"(d[26]), "+f"(d[27]), "+f"(d[28]), "+f"(d[29]), "+f"(d[30]), "+f"(d[31]), "+f"(d[32]), "+f"(d[33]), "+f"(d[34]), "+f"(d[35]), "+f"(d[36]), "+f"(d[37]), "+f"(d[38]), "+f"(d[39]), "+f"(d[40]), "+f"(d[41]), "+f"(d[42]), "+f"(d[43]), "+f"(d[44]), "+f"(d[45]), "+f"(d[46]), "+f"(d[47]), "+f"(d[48]), "+f"(d[49]), "+f"(d[50]), "+f"(d[51]), "+f"(d[52]), "+f"(d[53]), "+f"(d[54]), "+f"(d[55]), "+f"(d[56]), "+f"(d[57]), "+f"(d[58]), "+f"(d[59]), "+f"(d[60]), "+f"(d[61]), "+f"(d[62]), "+f"(d[63]), "+f"(d[64]), "+f"(d[65]), "+f"(d[66]), "+f"(d[67]), "+f"(d[68]), "+f"(d[69]), "+f"(d[70]), "+f"(d[71]), "+f"(d[72]), "+f"(d[73]), "+f"(d[74]), "+f"(d[75]), "+f"(d[76]), "+f"(d[77]), "+f"(d[78]), "+f"(d[79]), "+f"(d[80]), "+f"(d[81]), "+f"(d[82]), "+f"(d[83]), "+f"(d[84]), "+f"(d[85]), "+f"(d[86]), "+f"(d[87]), "+f"(d[88]), "+f"(d[89]), "+f"(d[90]), "+f"(d[91]), "+f"(d[92]), "+f"(d[93]), "+f"(d[94]), "+f"(d[95])
    : "l"(da), "l"(db), "r"(scale_d));
}
__device__ __forceinline__ void wg_ss48_tb(float* d, uint64_t da, uint64_t db, int scale_d) {
  asm volatile("{\n.reg .pred p;\nsetp.ne.b32 p, %26, 0;\n"
    "wgmma.mma_async.sync.aligned.m64n48k16.f32.bf16.bf16 "
    "{%0, %1, %2, %3, %4, %5, %6, %7, %8, %9, %10, %11, %12, %13, %14, %15, %16, %17, %18, %19, %20, %21, %22, %23}, %24, %25, p, 1, 1, 0, 1;\n}\n"
    : "+f"(d[0]), "+f"(d[1]), "+f"(d[2]), "+f"(d[3]), "+f"(d[4]), "+f"(d[5]), "+f"(d[6]), "+f"(d[7]), "+f"(d[8]), "+f"(d[9]), "+f"(d[10]), "+f"(d[11]), "+f"(d[12]), "+f"(d[13]), "+f"(d[14]), "+f"(d[15]), "+f"(d[16]), "+f"(d[17]), "+f"(d[18]), "+f"(d[19]), "+f"(d[20]), "+f"(d[21]), "+f"(d[22]), "+f"(d[23])
    : "l"(da), "l"(db), "r"(scale_d));
}
__device__ __forceinline__ void wg_ss48_tt(float* d, uint64_t da, uint64_t db, int scale_d) {
  asm volatile("{\n.reg .pred p;\nsetp.ne.b32 p, %26, 0;\n"
    "wgmma.mma_async.sync.aligned.m64n48k16.f32.bf16.bf16 "
    "{%0, %1, %2, %3, %4, %5, %6, %7, %8, %9, %10, %11, %12, %13, %14, %15, %16, %17, %18, %19, %20, %21, %22, %23}, %24, %25, p, 1, 1, 1, 1;\n}\n"
    : "+f"(d[0]), "+f"(d[1]), "+f"(d[2]), "+f"(d[3]), "+f"(d[4]), "+f"(d[5]), "+f"(d[6]), "+f"(d[7]), "+f"(d[8]), "+f"(d[9]), "+f"(d[10]), "+f"(d[11]), "+f"(d[12]), "+f"(d[13]), "+f"(d[14]), "+f"(d[15]), "+f"(d[16]), "+f"(d[17]), "+f"(d[18]), "+f"(d[19]), "+f"(d[20]), "+f"(d[21]), "+f"(d[22]), "+f"(d[23])
    : "l"(da), "l"(db), "r"(scale_d));
}
__device__ __forceinline__ void wg_rs88_tb(float* d, const uint32_t* a, uint64_t db, int scale_d) {
  asm volatile("{\n.reg .pred p;\nsetp.ne.b32 p, %49, 0;\n"
    "wgmma.mma_async.sync.aligned.m64n88k16.f32.bf16.bf16 "
    "{%0, %1, %2, %3, %4, %5, %6, %7, %8, %9, %10, %11, %12, %13, %14, %15, %16, %17, %18, %19, %20, %21, %22, %23, %24, %25, %26, %27, %28, %29, %30, %31, %32, %33, %34, %35, %36, %37, %38, %39, %40, %41, %42, %43}, {%44, %45, %46, %47}, %48, p, 1, 1, 1;\n}\n"
    : "+f"(d[0]), "+f"(d[1]), "+f"(d[2]), "+f"(d[3]), "+f"(d[4]), "+f"(d[5]), "+f"(d[6]), "+f"(d[7]), "+f"(d[8]), "+f"(d[9]), "+f"(d[10]), "+f"(d[11]), "+f"(d[12]), "+f"(d[13]), "+f"(d[14]), "+f"(d[15]), "+f"(d[16]), "+f"(d[17]), "+f"(d[18]), "+f"(d[19]), "+f"(d[20]), "+f"(d[21]), "+f"(d[22]), "+f"(d[23]), "+f"(d[24]), "+f"(d[25]), "+f"(d[26]), "+f"(d[27]), "+f"(d[28]), "+f"(d[29]), "+f"(d[30]), "+f"(d[31]), "+f"(d[32]), "+f"(d[33]), "+f"(d[34]), "+f"(d[35]), "+f"(d[36]), "+f"(d[37]), "+f"(d[38]), "+f"(d[39]), "+f"(d[40]), "+f"(d[41]), "+f"(d[42]), "+f"(d[43])
    : "r"(a[0]), "r"(a[1]), "r"(a[2]), "r"(a[3]), "l"(db), "r"(scale_d));
}
__device__ __forceinline__ void wg_rs64_tb(float* d, const uint32_t* a, uint64_t db, int scale_d) {
  asm volatile("{\n.reg .pred p;\nsetp.ne.b32 p, %37, 0;\n"
    "wgmma.mma_async.sync.aligned.m64n64k16.f32.bf16.bf16 "
    "{%0, %1, %2, %3, %4, %5, %6, %7, %8, %9, %10, %11, %12, %13, %14, %15, %16, %17, %18, %19, %20, %21, %22, %23, %24, %25, %26, %27, %28, %29, %30, %31}, {%32, %33, %34, %35}, %36, p, 1, 1, 1;\n}\n"
    : "+f"(d[0]), "+f"(d[1]), "+f"(d[2]), "+f"(d[3]), "+f"(d[4]), "+f"(d[5]), "+f"(d[6]), "+f"(d[7]), "+f"(d[8]), "+f"(d[9]), "+f"(d[10]), "+f"(d[11]), "+f"(d[12]), "+f"(d[13]), "+f"(d[14]), "+f"(d[15]), "+f"(d[16]), "+f"(d[17]), "+f"(d[18]), "+f"(d[19]), "+f"(d[20]), "+f"(d[21]), "+f"(d[22]), "+f"(d[23]), "+f"(d[24]), "+f"(d[25]), "+f"(d[26]), "+f"(d[27]), "+f"(d[28]), "+f"(d[29]), "+f"(d[30]), "+f"(d[31])
    : "r"(a[0]), "r"(a[1]), "r"(a[2]), "r"(a[3]), "l"(db), "r"(scale_d));
}
__device__ __forceinline__ void wg_ss48_tt_h(float* d, uint64_t da, uint64_t db, int scale_d) {
  asm volatile("{\n.reg .pred p;\nsetp.ne.b32 p, %26, 0;\n"
    "wgmma.mma_async.sync.aligned.m64n48k16.f32.f16.f16 "
    "{%0, %1, %2, %3, %4, %5, %6, %7, %8, %9, %10, %11, %12, %13, %14, %15, %16, %17, %18, %19, %20, %21, %22, %23}, %24, %25, p, 1, 1, 1, 1;\n}\n"
    : "+f"(d[0]), "+f"(d[1]), "+f"(d[2]), "+f"(d[3]), "+f"(d[4]), "+f"(d[5]), "+f"(d[6]), "+f"(d[7]), "+f"(d[8]), "+f"(d[9]), "+f"(d[10]), "+f"(d[11]), "+f"(d[12]), "+f"(d[13]), "+f"(d[14]), "+f"(d[15]), "+f"(d[16]), "+f"(d[17]), "+f"(d[18]), "+f"(d[19]), "+f"(d[20]), "+f"(d[21]), "+f"(d[22]), "+f"(d[23])
    : "l"(da), "l"(db), "r"(scale_d));
}
__device__ __forceinline__ void wg_rs16_tb(float* d, const uint32_t* a, uint64_t db, int scale_d) {
  asm volatile("{\n.reg .pred p;\nsetp.ne.b32 p, %13, 0;\n"
    "wgmma.mma_async.sync.aligned.m64n16k16.f32.bf16.bf16 "
    "{%0, %1, %2, %3, %4, %5, %6, %7}, {%8, %9, %10, %11}, %12, p, 1, 1, 1;\n}\n"
    : "+f"(d[0]), "+f"(d[1]), "+f"(d[2]), "+f"(d[3]), "+f"(d[4]), "+f"(d[5]), "+f"(d[6]), "+f"(d[7])
    : "r"(a[0]), "r"(a[1]), "r"(a[2]), "r"(a[3]), "l"(db), "r"(scale_d));
}

struct Params {
  const __nv_bfloat16 *logA, *Aim, *Cr, *Ci, *logdt, *dskip;
};

template <bool FWD>
__device__ __forceinline__ void tile_transpose(uint32_t tc0, uint32_t tc1, uint32_t ct0, uint32_t ct1, int hw, int lane) {
  const int mi = lane >> 3, row = lane & 7;
  for (int gi = hw; gi < 40; gi += 3) {
    const int hh = gi / 20, rem = gi - hh * 20, q = rem / 10, cb = rem - q * 10;
    const uint32_t a_tc = (hh ? tc1 : tc0) + (8 * (4 * q + mi) + row) * 160 + cb * 16;
    const uint32_t a_ct = (hh ? ct1 : ct0) + (8 * cb + row) * 128 + (((4 * q + mi) ^ row) << 4);
    uint32_t r[4];
    ldsm4t(r, FWD ? a_tc : a_ct);
    stsm4(FWD ? a_ct : a_tc, r[0], r[1], r[2], r[3]);
  }
}

__device__ __forceinline__ void load_quad(uint32_t* A, uint32_t addr) {
  A[0] = lds32(addr); A[1] = lds32(addr + 32); A[2] = lds32(addr - 32); A[3] = lds32(addr);
}

__global__ void __launch_bounds__(512, 1)
fused_kernel(const __grid_constant__ CUtensorMap mx, const __grid_constant__ CUtensorMap mw, const __grid_constant__ CUtensorMap mr,
             const __grid_constant__ CUtensorMap mwo, const __grid_constant__ CUtensorMap mwr, const __grid_constant__ CUtensorMap mo64,
             const __grid_constant__ CUtensorMap mo16, const __grid_constant__ CUtensorMap mu, const __grid_constant__ CUtensorMap msa,
             const __grid_constant__ CUtensorMap msb, const __grid_constant__ CUtensorMap mout, const Params prm) {
  extern __shared__ unsigned char smem_raw[];
  const uint32_t sb = (smem_u32(smem_raw) + 1023) & ~1023u;
  const int tid = threadIdx.x, lane = tid & 31;
  const int wg = __shfl_sync(0xffffffff, tid >> 7, 0), warp = __shfl_sync(0xffffffff, tid >> 5, 0);
  const int cta = blockIdx.x, r = cta >> 3, c = cta & 7;
  const uint32_t bars = sb + OFF_BAR;
#define BAR(i) (bars + 8 * (i))

  auto issue1 = [&](int kb) {
    const uint32_t st = sb + (kb % 5) * W_SLOT, fb = BAR(BR_FULL + kb % 5);
    mbar_expect_tx(fb, (kb & 1) ? W_SLOT : W_SLOT + 16384);
    if (!(kb & 1)) tma2d(sb + OFF_X + ((kb >> 1) % 3) * 16384, &mx, fb, kb * 32, r * 128);
    tma3d(st, &mw, fb, c * 80, kb * 32, 0);
    tma3d(st + 12288, &mr, fb, c * 80 + 64, kb * 32, 0);
  };

  if (warp == 12) {
    if (elect_one()) {
      #pragma unroll
      for (int i = 0; i < BR_COUNT; i++) {
        int cnt = 1;
        if (i >= BR_EMPTY && i < BR_EMPTY + 5) cnt = 2;
        if (i >= BR_OEMPTY && i < BR_OEMPTY + 4) cnt = 8;
        if (i == BR_OSTG) cnt = 256;
        if (i >= BR_DRDY && i < BR_DRDY + 5) cnt = 96;
        if (i >= BR_YSTG && i < BR_YSTG + 5) cnt = i == BR_YSTG + 4 ? 128 : 32;
        mbar_init(BAR(i), cnt);
      }
      asm volatile("fence.mbarrier_init.release.cluster;" ::: "memory");
      if (EN_ATT) issue1(0);
    }
  }
  float ldt = 0.f, dsk0 = 0.f;
  uint4 pv[3];
  if (EN_SSM && wg == 2) {
    const int ai = warp & 3;
    const uint4* pp = reinterpret_cast<const uint4*>((ai == 0 ? prm.logA : ai == 1 ? prm.Aim : ai == 2 ? prm.Cr : prm.Ci) + (c * 80 + r * 5) * 128);
    pv[0] = __ldg(pp + lane); pv[1] = __ldg(pp + 32 + lane); pv[2] = __ldg(pp + 64 + (lane & 15));
    if (tid < 261) { ldt = __bfloat162float(prm.logdt[c * 80 + r * 5 + tid - 256]); dsk0 = __bfloat162float(prm.dskip[c * 80 + r * 5 + tid - 256]); }
  }
  __syncthreads();

  if (wg == 3) {
    asm volatile("setmaxnreg.dec.sync.aligned.u32 56;");
    if (warp == 12) {
      if (EN_ATT) {
      #pragma unroll
      for (int kb = 1; kb < 20; kb++) {
        if (kb >= 5) mbar_wait(BAR(BR_EMPTY + kb % 5), ((kb / 5) & 1) ^ 1);
        if (elect_one()) issue1(kb);
      }
      auto chunk_of = [&](int i) { return i == 0 ? c : (i == 7 ? (c ^ 1) : (((c & 6) + 1 + i) & 7)); };
      mbar_wait(BAR(BR_EPOCH), 0);
      const unsigned epoch = lds32(sb + OFF_EPOCH);
      const unsigned* fo = &g_flag[(24 + r) * 32 + (lane & 7)];
      unsigned seen = __ballot_sync(0xffffffff, ld_rlx(fo) == epoch);
      mbar_wait(BAR(BR_GEMM), 0);
      if (elect_one()) {
        mbar_expect_tx(BAR(BR_WO), 20480 + 5 * 10240);
        #pragma unroll
        for (int i = 0; i < 5; i++) tma2d(sb + OFF_WOM + i * 10240, &mwo, BAR(BR_WO), c * 64, i * 80);
        #pragma unroll
        for (int i = 0; i < 4; i++) tma2d(sb + i * 5120, &mwr, BAR(BR_WO), 512 + c * 16, i * 160);
      }
      mbar_wait(BAR(BR_PUB), 0);
      if (elect_one()) {
        mbar_expect_tx(BAR(BR_WO + 1), 3 * 10240);
        #pragma unroll
        for (int i = 5; i < 8; i++) tma2d(sb + OFF_WOM + i * 10240, &mwo, BAR(BR_WO + 1), c * 64, i * 80);
      }
      mbar_wait(BAR(BR_OSTG), 0);
      if (elect_one()) {
        bulk_st(&g_o[cta * 1280], sb + OFF_EXTRA, 20480);
        bulk_commit();
        bulk_wait0();
        st_rlx(&g_flag[(24 + r) * 32 + c], epoch);
        TS(20);
      }
      __syncwarp();
      #pragma unroll
      for (int i = 0; i < 7; i++) {
        const int src = chunk_of(i + 1);
        if (!((seen >> src) & 1)) seen = poll_bit(fo, epoch, 1u << src);
        if (i < 3) { if (EN_SSM) mbar_wait(BAR(BR_FREE + 4 - i), 0); }
        else if (i > 3) mbar_wait(BAR(BR_OEMPTY + i - 4), 0);
        if (elect_one()) {
          fence_async_g();
          const uint32_t slot = (i & 3) == 3 ? sb + OFF_EXTRA : sb + OFF_BLK + (4 - (i & 3)) * BLK;
          mbar_expect_tx(BAR(BR_OFULL + (i & 3)), 20480);
          bulk_ld(slot, &g_o[(r * 8 + src) * 1280], 20480, BAR(BR_OFULL + (i & 3)));
          if (i == 0) TS(21);
          if (i == 6) { TS(22); DUMP(20, 30); }
        }
        __syncwarp();
      }
      }
    } else {
      const int hw = warp - 13, ht = tid - 416;
      unsigned epoch = 0;
      if (hw == 0) {
        if (lane == 0) {
          if (EN_SSM) {
            mbar_expect_tx(BAR(BR_UIN), 20480);
            tma2d(sb + OFF_BLK + 4 * BLK + B_D, &mu, BAR(BR_UIN), c * 80, r * 128);
            tma2d(sb + OFF_BLK + 3 * BLK + B_D, &mu, BAR(BR_UIN), c * 80, r * 128 + 64);
          }
          epoch = ld_rlx(&g_epoch[cta]) + 1;
          st_rlx(&g_epoch[cta], epoch);
          sts32(sb + OFF_EPOCH, epoch);
          mbar_arrive(BAR(BR_EPOCH));
        }
        epoch = __shfl_sync(0xffffffff, epoch, 0);
      }
      if (EN_SSM) {
      mbar_wait(BAR(BR_UIN), 0);
      if (ht == 0) TS(36);
      {
        const int mi = lane >> 3, rw = lane & 7;
        const uint32_t lo = (uint32_t)((8 * (rw >> 1) + 2 * mi + (rw & 1)) * 160);
        uint4* gp = reinterpret_cast<uint4*>(g_uy + (size_t)(c * 80 + hw * 8 + (lane >> 2)) * 2048 + r * 128 + (lane & 3) * 8);
        const uint32_t sa = sb + OFF_BLK + 3 * BLK + B_D + lo + hw * 16;
        #pragma unroll
        for (int i = 0; i < 4; i++) {
          if (i < 3 || hw == 0) {
            uint32_t v[4][4];
            #pragma unroll
            for (int q = 0; q < 4; q++) ldsm4t(v[q], sa + (1 - (q >> 1)) * BLK + (q & 1) * 5120 + i * 48);
            #pragma unroll
            for (int q = 0; q < 4; q++) gp[i * 6144 + q * 4] = make_uint4(v[q][0], v[q][1], v[q][2], v[q][3]);
          }
        }
      }
      if (ht == 0) TS(37);
      __threadfence();
      if (ht == 0) TS(38);
      bar_sync(5, 96);
      if (hw == 0) {
        if (lane == 0) { st_rlx(&g_flag[(8 + c) * 32 + r], epoch); TS(30); }
        __syncwarp();
        poll_all(&g_flag[(8 + c) * 32 + (lane & 15)], epoch);
        (void)ld_acq(&g_flag[(8 + c) * 32 + (lane & 15)]); __syncwarp();
        if (lane == 0) {
          fence_async_g();
          mbar_expect_tx(BAR(BR_U), 12288);
          #pragma unroll
          for (int k = 4; k >= 2; k--) tma2d(sb + OFF_BLK + k * BLK, &msb, BAR(BR_U), 0, (c * 80 + r * 5 + k) * 32);
          TS(31);
        }
        __syncwarp();
      }
      mbar_wait(BAR(BR_U), 0);
      if (ht == 0) TS(39);
      #pragma unroll 1
      for (int k = 4; k >= 0; k--) {
        if (k == 2) {
          mbar_wait(BAR(BR_KGEN), 0);
          if (ht == 0) {
            fence_async();
            mbar_expect_tx(BAR(BR_U2), 8192);
            tma2d(sb + OFF_BLK + BLK, &msb, BAR(BR_U2), 0, (c * 80 + r * 5 + 1) * 32);
            tma2d(sb + OFF_BLK, &msb, BAR(BR_U2), 0, (c * 80 + r * 5) * 32);
          }
          __syncwarp();
        }
        if (k == 1) mbar_wait(BAR(BR_U2), 0);
        const uint32_t blk = sb + OFF_BLK + k * BLK;
        #pragma unroll 1
        for (int kap = ht; kap < 192; kap += 96) {
          float P[33];
          P[0] = 0.f;
          #pragma unroll
          for (int q = 0; q < 4; q++) {
            const int ch = kap - 3 + q;
            uint32_t v[4];
            lds128(v, blk + (uint32_t)((ch >> 3) * 128 + (((ch & 7) ^ ((ch >> 3) & 7)) << 4)));
            #pragma unroll
            for (int e = 0; e < 4; e++) {
              P[q * 8 + 2 * e + 1] = P[q * 8 + 2 * e] + bf_lo(v[e]);
              P[q * 8 + 2 * e + 2] = P[q * 8 + 2 * e + 1] + bf_hi(v[e]);
            }
          }
#define WIN(lo, hi, e) (P[25 + (e) - (lo)] - P[24 + (e) - (hi)])
#define WIN8(lo, hi) pack2(WIN(lo, hi, 0), WIN(lo, hi, 1)), pack2(WIN(lo, hi, 2), WIN(lo, hi, 3)), pack2(WIN(lo, hi, 4), WIN(lo, hi, 5)), pack2(WIN(lo, hi, 6), WIN(lo, hi, 7))
          const uint32_t o2 = blk + B_D + (kap & 1) * 1552 + (kap >> 1) * 16;
          sts128(o2, WIN8(3, 5));
          sts128(o2 + B_D5, WIN8(6, 10));
          if (kap < 128) {
            const uint32_t o = blk + B_D + (kap & 1) * 1024 + (kap >> 1) * 16;
            sts128(o + B_D7, WIN8(5, 11));
            sts128(o + B_D9, WIN8(12, 20));
          }
        }
        if (ht < 2) sts128(blk + B_D + ht * B_D5 + 1536, 0, 0, 0, 0);
        mbar_arrive(BAR(BR_DRDY + k));
      }
      if (ht == 0) TS(32);
      if (hw == 0) {
        #pragma unroll 1
        for (int k = 4; k >= 0; k--) {
          mbar_wait(BAR(BR_YSTG + k), 0);
          if (lane == 0) {
            tma2d_st(&msb, sb + OFF_BLK + k * BLK, 0, (640 + c * 80 + r * 5 + k) * 32);
            bulk_commit(); bulk_wait0_read();
            mbar_arrive(BAR(BR_FREE + k));
          }
          __syncwarp();
        }
        if (lane == 0) { bulk_wait0(); st_rel(&g_flag[(16 + c) * 32 + r], epoch); TS(33); }
        __syncwarp();
        poll_all(&g_flag[(16 + c) * 32 + (lane & 15)], epoch);
        (void)ld_acq(&g_flag[(16 + c) * 32 + (lane & 15)]); __syncwarp();
        if (lane == 0) {
          fence_async_g();
          mbar_expect_tx(BAR(BR_YIN), 20480);
          tma2d(sb + OFF_BLK + BLK, &msa, BAR(BR_YIN), r * 128, 640 + c * 80);
          tma2d(sb + OFF_BLK + BLK + 10240, &msa, BAR(BR_YIN), r * 128 + 64, 640 + c * 80);
          TS(34);
        }
        __syncwarp();
      }
      mbar_wait(BAR(BR_YIN), 0);
      tile_transpose<false>(sb + OFF_BLK, sb + OFF_BLK + 10240, sb + OFF_BLK + BLK, sb + OFF_BLK + BLK + 10240, hw, lane);
      fence_async();
      bar_sync(5, 96);
      if (ht == 0) {
        tma2d_st(&mout, sb + OFF_BLK, c * 80, r * 128);
        tma2d_st(&mout, sb + OFF_BLK + 10240, c * 80, r * 128 + 64);
        bulk_commit(); bulk_wait0_read();
        TS(35); DUMP(30, 40); DUMP(0, 1);
      }
      }
    }
  } else if (wg < 2) {
    asm volatile("setmaxnreg.inc.sync.aligned.u32 152;");
    if (EN_ATT) {
    const int w4 = warp & 3, g = lane >> 2, tq = lane & 3, t7 = tid & 127;
    float am[96], ar[24];
    {
      const uint64_t da0 = mkdesc(sb + OFF_X + wg * 8192, 16, 1024, 1);
      const uint64_t db0 = mkdesc(sb, 4096, 1024, 1);
      const uint64_t dr0 = mkdesc(sb + 12288, 1024, 256, 3);
      uint32_t s = 0, ph = 0, xo = 0;
      #pragma unroll 1
      for (int kb = 0; kb < 20; kb++) {
        mbar_wait(BAR(BR_FULL) + 8 * s, ph);
        if (kb == 0 && tid == 0) TS(1);
        wg_fence();
        const uint32_t wo_ = s * (W_SLOT >> 4);
        wg_ss192_tb(am, da0 + xo, db0 + wo_, kb != 0);
        wg_ss48_tb(ar, da0 + xo, dr0 + wo_, kb != 0);
        wg_ss192_tb(am, da0 + xo + 2, db0 + wo_ + 128, 1);
        wg_ss48_tb(ar, da0 + xo + 2, dr0 + wo_ + 32, 1);
        wg_commit();
        wg_wait<1>();
        if (t7 == 0 && kb > 0 && kb < 16) mbar_arrive(BAR(BR_EMPTY) + 8 * (s == 0 ? 4 : s - 1));
        if (++s == 5) { s = 0; ph ^= 1; }
        xo += (kb & 1) ? 1020 : 4;
        if (xo == 3072) xo = 0;
      }
      wg_wait<0>();
      pin<96>(am); pin<24>(ar);
    }
    if (tid == 0) TS(2);
#define QV(j, e) ((j) < 8 ? am[4 * (j) + (e)] : ar[4 * ((j) - 8) + (e)])
#define KV_(j, e) ((j) < 8 ? am[32 + 4 * (j) + (e)] : ar[8 + 4 * ((j) - 8) + (e)])
#define VV(j, e) ((j) < 8 ? am[64 + 4 * (j) + (e)] : ar[16 + 4 * ((j) - 8) + (e)])
    {
      bar_sync(1, 256);
      if (tid == 0) mbar_arrive(BAR(BR_GEMM));
      const uint32_t ro = (uint32_t)((lane >> 4) * 2048 + (wg * 64 + w4 * 16 + (lane & 15)) * 16);
      const uint32_t ones = (tq == 0) ? 0x00003f80u : 0u;
#define PV(j) pack2(VV(j, 0), VV(j, 1)), pack2(VV(j, 2), VV(j, 3))
#define PK(j) pack2(phi(KV_(j, 0)), phi(KV_(j, 1))), pack2(phi(KV_(j, 2)), phi(KV_(j, 3)))
      stsm4(sb + OFF_V + 0 * 2048 + ro, PV(0), PV(1));
      stsm4(sb + OFF_V + 2 * 2048 + ro, PV(2), PV(3));
      stsm4(sb + OFF_V + 4 * 2048 + ro, PV(4), ones, ones);
      stsm4(sb + OFF_V + 6 * 2048 + ro, PV(5), PV(6));
      stsm4(sb + OFF_V + 8 * 2048 + ro, PV(7), PV(8));
      stsm4(sb + OFF_V + 10 * 2048 + ro, PV(9), ones, ones);
      #pragma unroll
      for (int j = 0; j < 10; j += 2) stsm4(sb + OFF_PK + j * 2048 + ro, PK(j), PK(j + 1));
    }
    fence_async();
    bar_sync(1, 256);
    if (tid == 0) TS(3);
    mbar_wait(BAR(BR_EPOCH), 0);
    const unsigned epoch = lds32(sb + OFF_EPOCH);
    {
      float kv[24]; zero<24>(kv);
      const uint64_t da = mkdesc(sb + OFF_PK + wg * 5 * 2048, 128, 2048, 0);
      const uint64_t db = mkdesc(sb + OFF_V + wg * 6 * 2048, 128, 2048, 0);
      wg_fence();
      #pragma unroll
      for (int s = 0; s < 8; s++) wg_ss48_tt(kv, da + s * 16, db + s * 16, s != 0);
      wg_commit();
      wg_wait<0>();
      pin<24>(kv);
      if (tid == 0) TS(15);
      if (w4 < 3) {
        const uint32_t wb = sb + OFF_KVS + (wg * 3 + w4) * 1536;
        #pragma unroll
        for (int j = 0; j < 6; j += 2)
          stsm4(wb + (lane & 15) * 96 + (j + (lane >> 4)) * 16, pack2(kv[4 * j], kv[4 * j + 1]), pack2(kv[4 * j + 2], kv[4 * j + 3]),
                pack2(kv[4 * j + 4], kv[4 * j + 5]), pack2(kv[4 * j + 6], kv[4 * j + 7]));
        __syncwarp();
        const int dl = w4 * 16 + (lane & 15), hl = dl >= 20;
        if (dl < 40) {
          uint4* dst = &g_kvp[(c * 16 + r) * 240 + wg * 40 + dl];
          uint32_t v[4];
          lds128(v, wb + (lane & 15) * 96 + (3 * hl + (lane >> 4)) * 16);
          v[3] = (v[3] & ~1u) | (epoch & 1u);
          st128_rlx(dst + (lane >> 4) * 80, v);
          if (lane < 16) {
            v[0] = lds32(wb + lane * 96 + 32 + 8 * hl); v[1] = lds32(wb + lane * 96 + 36 + 8 * hl);
            v[2] = lds32(wb + lane * 96 + 80); v[3] = epoch & 1u;
            st128_rlx(dst + 160, v);
          }
        }
      }
    }
    bar_sync(1, 256);
    if (tid == 0) { st_rlx(&g_flag[c * 32 + r], epoch); mbar_arrive(BAR(BR_PUB)); TS(4); }
    const int kd = tid >= 160 ? tid - 160 : (tid >= 80 ? tid - 80 : tid), kvi = (tid >= 80) + (tid >= 160);
    const int khd = kd / 20, kt0 = 5 * (khd >> 1) + 2 * (khd & 1);
    if (tid < 240) {
      #pragma unroll
      for (int m = 0; m < 3; m++) {
        int q = kt0 + 3 + kvi + 3 * m; if (q >= 10) q -= 10;
        if (kvi + 3 * m < 7) sts128(sb + OFF_KVB + q * 1280 + kd * 16, 0, 0, 0, 0);
      }
    }
    uint32_t qa[20];
    {
      const float sc = 1.44269504089f + __uint_as_float(lds32(sb + OFF_EPOCH) ^ epoch);
      #pragma unroll
      for (int j = 0; j < 10; j++) { qa[2 * j] = pack2(phi(QV(j, 0), sc), phi(QV(j, 1), sc)); qa[2 * j + 1] = pack2(phi(QV(j, 2), sc), phi(QV(j, 3), sc)); }
    }
    if (tid == 0) TS(5);
    {
      poll_all(&g_flag[c * 32 + (lane & 15)], epoch);
      if (tid == 0) TS(6);
      if (tid < 240) {
        uint32_t v[16][4];
        const uint4* src = &g_kvp[c * 16 * 240 + tid];
        #pragma unroll
        for (int i = 0; i < 16; i++) ld128_rlx(v[i], src + i * 240);
        float s[8];
        uint32_t bad = 0;
        #pragma unroll
        for (int i = 0; i < 16; i++) {
          bad |= v[i][3] ^ epoch;
          #pragma unroll
          for (int e = 0; e < 4; e++) {
            s[2 * e] = i ? s[2 * e] + bf_lo(v[i][e]) : bf_lo(v[i][e]);
            s[2 * e + 1] = i ? s[2 * e + 1] + bf_hi(v[i][e]) : bf_hi(v[i][e]);
          }
        }
        if (__builtin_expect(bad & 1u, 0)) {
          #pragma unroll
          for (int e = 0; e < 8; e++) s[e] = 0.f;
          #pragma unroll 1
          for (int i = 0; i < 16; i++) {
            uint32_t w[4] = {0, 0, 0, ~epoch};
            fix128_w3(w, src + i * 240, epoch, 1u);
            #pragma unroll
            for (int e = 0; e < 4; e++) { s[2 * e] += bf_lo(w[e]); s[2 * e + 1] += bf_hi(w[e]); }
          }
        }
        if (tid == 0) TS(18);
        const uint32_t p0 = pack2(s[0], s[1]), p1 = pack2(s[2], s[3]), p2 = pack2(s[4], s[5]), p3 = pack2(s[6], s[7]);
        const uint32_t rb = sb + OFF_KVB + kd * 16;
        if (kvi < 2) sts128(rb + (kt0 + (khd & 1) + kvi) * 1280, p0, p1, p2, p3);
        else {
          const bool od = khd & 1;
          sts128(rb + (5 * (khd >> 1) + 2) * 1280, od ? 0u : p0, od ? 0u : p1, od ? p0 : 0u, od ? p1 : 0u);
          const uint32_t zz = (p2 & 0xffffu) << (16 * (khd & 1));
          sts128(rb + 10 * 1280, khd < 2 ? zz : 0u, khd < 2 ? 0u : zz, 0u, 0u);
        }
      }
    }
    fence_async();
    bar_sync(1, 256);
    if (tid == 0) TS(7);
    uint32_t A0[20], A1[20];
    {
      float oa[44]; zero<44>(oa);
      const uint64_t db = mkdesc(sb + OFF_KVB, 128, 1280, 0);
      wg_fence();
      #pragma unroll
      for (int s = 0; s < 5; s++) wg_rs88_tb(oa, &qa[4 * s], db + s * 16, s != 0);
      wg_commit();
      if (tid == 0) TS(12);
      wg_wait<0>();
      pin<44>(oa);
      if (tid == 0) TS(13);
      float rc[4], rd[2][4];
      #pragma unroll
      for (int e = 0; e < 4; e++) rc[e] = __fdividef(1.f, oa[40 + e] + 1e-6f);
      #pragma unroll
      for (int h = 0; h < 4; h++) {
        rd[0][h] = __shfl_sync(0xffffffff, rc[h & 1], (lane & 28) | (h >> 1));
        rd[1][h] = __shfl_sync(0xffffffff, rc[2 + (h & 1)], (lane & 28) | (h >> 1));
      }
      #pragma unroll
      for (int j = 0; j < 10; j++) {
        #pragma unroll
        for (int h = 0; h < 2; h++) {
          float f;
          if (j == 2) f = tq < 2 ? rd[h][0] : rd[h][1];
          else if (j == 7) f = tq < 2 ? rd[h][2] : rd[h][3];
          else f = rd[h][(8 * j) / 20];
          A0[2 * j + h] = pack2(oa[4 * j + 2 * h] * f, oa[4 * j + 2 * h + 1] * f);
        }
      }
      bar_sync(1, 256);
      #pragma unroll
      for (int s = 0; s < 5; s++) {
        A0[4 * s] = (A0[4 * s] & ~1u) | (epoch & 1u);
        sts128(sb + OFF_EXTRA + ((wg * 5 + s) * 128 + t7) * 16, A0[4 * s], A0[4 * s + 1], A0[4 * s + 2], A0[4 * s + 3]);
      }
    }
    if (tid == 0) TS(14);
    fence_async();
    mbar_arrive(BAR(BR_OSTG));
    if (tid == 0) TS(8);
    float oc[32], od[8]; zero<32>(oc); zero<8>(od);
    {
      const uint64_t dw0 = mkdesc(sb + OFF_WOM, 16, 1024, 1), dr0 = mkdesc(sb, 16, 256, 3);
      mbar_wait(BAR(BR_WO), 0);
      mbar_wait(BAR(BR_WO + 1), 0);
      wg_fence();
      #pragma unroll
      for (int s = 0; s < 5; s++) { wg_rs64_tb(oc, &A0[4 * s], dw0 + c * 640 + s * 128, s != 0); wg_rs16_tb(od, &A0[4 * s], dr0 + c * 160 + s * 32, s != 0); }
      wg_commit();
      #pragma unroll
      for (int i = 0; i < 7; i++) {
        uint32_t* A = (i & 1) ? A0 : A1;
        const uint32_t slot = (i & 3) == 3 ? sb + OFF_EXTRA : sb + OFF_BLK + (4 - (i & 3)) * BLK;
        const int src = (i == 6) ? (c ^ 1) : (((c & 6) + 2 + i) & 7);
        mbar_wait(BAR(BR_OFULL + (i & 3)), i >> 2);
        if (i == 0 && tid == 0) TS(9);
        if (i > 0) wg_wait<1>();
        #pragma unroll
        for (int s = 0; s < 5; s++) lds128(&A[4 * s], slot + ((wg * 5 + s) * 128 + t7) * 16);
        uint32_t bad = 0;
        #pragma unroll
        for (int s = 0; s < 5; s++) bad |= A[4 * s] ^ epoch;
        if (__builtin_expect(bad & 1u, 0)) {
          #pragma unroll
          for (int s = 0; s < 5; s++) fix128_w0(&A[4 * s], &g_o[(r * 8 + src) * 1280 + (wg * 5 + s) * 128 + t7], epoch, 1u);
        }
        __syncwarp();
        if (i < 3 && lane == 0) mbar_arrive(BAR(BR_OEMPTY + i));
        wg_fence();
        #pragma unroll
        for (int s = 0; s < 5; s++) { wg_rs64_tb(oc, &A[4 * s], dw0 + src * 640 + s * 128, 1); wg_rs16_tb(od, &A[4 * s], dr0 + src * 160 + s * 32, 1); }
        wg_commit();
      }
      bar_sync(2 + wg, 128);
      wg_wait<0>();
      pin<32>(oc); pin<8>(od);
    }
    if (tid == 0) TS(10);
    {
      const int row = w4 * 16 + (lane & 15);
      const uint32_t ob = sb + OFF_EXTRA + wg * 10240;
      #pragma unroll
      for (int j = 0; j < 8; j += 2)
        stsm4(ob + row * 128 + (((j + (lane >> 4)) ^ (row & 7)) << 4), pack2(oc[4 * j], oc[4 * j + 1]), pack2(oc[4 * j + 2], oc[4 * j + 3]),
              pack2(oc[4 * j + 4], oc[4 * j + 5]), pack2(oc[4 * j + 6], oc[4 * j + 7]));
      stsm4(ob + 8192 + row * 32 + (lane >> 4) * 16, pack2(od[0], od[1]), pack2(od[2], od[3]), pack2(od[4], od[5]), pack2(od[6], od[7]));
      fence_async();
      bar_sync(2 + wg, 128);
      if (t7 == 0) {
        tma2d_st(&mo64, ob, 640 + c * 64, r * 128 + wg * 64);
        tma2d_st(&mo16, ob + 8192, 1152 + c * 16, r * 128 + wg * 64);
        bulk_commit(); bulk_wait0_read();
      }
      if (tid == 0) { TS(11); DUMP(0, 20); }
    }
    }
  } else {
    asm volatile("setmaxnreg.inc.sync.aligned.u32 152;");
    if (EN_SSM) {
    const int w4 = warp & 3, g = lane >> 2, tq = lane & 3, t7 = tid & 127;
    {
      #pragma unroll
      for (int k = 0; k < 5; k++) {
        const uint32_t tz = sb + OFF_BLK + k * BLK + B_TBL + t7 * 16;
        if (t7 < 32 || t7 >= 96) sts128(tz, 0, 0, 0, 0);
        if (t7 < 124) sts128(tz + 2048, 0, 0, 0, 0);
        if (t7 < 16) sts128(sb + OFF_BLK + k * BLK - 256 + t7 * 16, 0, 0, 0, 0);
      }
      if (t7 < 5) sts64(sb + OFF_BLK + t7 * BLK + B_SP + 8, __float_as_uint(bf_round(expf(ldt))), __float_as_uint(dsk0));
      const uint32_t st = sb + OFF_BLK + (lane >> 4) * BLK + B_TBL + 512 + w4 * 256 + (lane & 15) * 16;
      #pragma unroll
      for (int i = 0; i < 3; i++) {
        if (i < 2 || lane < 16) sts128(st + 2 * i * BLK, pv[i].x, pv[i].y, pv[i].z, pv[i].w);
        if (w4 >= 2) {
          const uint32_t m2 = __vmaxu2(__vmaxu2(pv[i].x & 0x7fff7fffu, pv[i].y & 0x7fff7fffu), __vmaxu2(pv[i].z & 0x7fff7fffu, pv[i].w & 0x7fff7fffu));
          const uint32_t m = __reduce_max_sync(lane < 16 ? 0x0000ffffu : 0xffff0000u, max(m2 & 0xffffu, m2 >> 16));
          if ((lane & 15) == 0 && (i < 2 || lane == 0)) sts32(sb + OFF_BLK + (2 * i + (lane >> 4)) * BLK + B_SP + 8 + w4 * 4, m);
        }
      }
    }
    bar_sync(4, 128);
    if (t7 == 0) TS(40);
    {
      const uint32_t fa = sb + OFF_BLK + (w4 & 1) * BLK + (lane >> 3) * 256 + (lane & 7) * 16;
      const uint32_t ea = fa + (w4 >> 1) * 4096, ga = fa + 8192 + (w4 >> 1) * 3072;
      const uint64_t dE = mkdesc(sb + OFF_BLK, 128, 1024, 0), dG = mkdesc(sb + OFF_BLK + 8192, 128, 1024, 0);
      #pragma unroll 1
      for (int k = 4; k >= 0; k--) {
        const uint32_t blk = sb + OFF_BLK + k * BLK;
        float fac, dsk;
        {
          const uint32_t st = blk + B_TBL + 512 + t7 * 2;
          uint32_t q[2], mm[2];
          const uint32_t p0 = lds16(st), p1 = lds16(st + 256), p2 = lds16(st + 512), p3 = lds16(st + 768);
          lds64(q, blk + B_SP + 8); lds64(mm, blk + B_SP + 16);
          const float dt = __uint_as_float(q[0]); dsk = __uint_as_float(q[1]);
          const uint32_t ex = min(max(max(mm[0], mm[1]) >> 7, 1u), 253u);
          const float sc = __uint_as_float((254u - ex) << 23);
          fac = 2.f * dt * __uint_as_float(ex << 23);
          const float lr = -bf_round(expf(bf_lo(p0))) * dt * 1.44269504089f;
          const float tn = bf_lo(p1) * dt * 0.15915494309f;
          float z1r, z1i, z2r, z2i, z4r, z4i, xr[8], xi[8], gr[8], gi[8], wr[9], wi[9];
          cexp_t(lr, -tn, z1r, z1i);
          cexp_t(lr * 8.f, tn * 8.f, xr[1], xi[1]);
          cexp_t(lr * 64.f, tn * 64.f, wr[0], wi[0]);
          xr[0] = 1.f; xi[0] = 0.f;
          cmul(xr[1], xi[1], xr[1], xi[1], xr[2], xi[2]); cmul(xr[2], xi[2], xr[1], xi[1], xr[3], xi[3]);
          cmul(xr[2], xi[2], xr[2], xi[2], xr[4], xi[4]);
          #pragma unroll
          for (int b = 1; b < 4; b++) cmul(xr[4], xi[4], xr[b], xi[b], xr[4 + b], xi[4 + b]);
          cmul(wr[0], wi[0], wr[0], wi[0], wr[1], wi[1]); cmul(wr[1], wi[1], wr[0], wi[0], wr[2], wi[2]);
          cmul(wr[1], wi[1], wr[1], wi[1], wr[3], wi[3]); cmul(wr[3], wi[3], wr[3], wi[3], wr[4], wi[4]);
          cmul(wr[4], wi[4], wr[3], wi[3], wr[5], wi[5]); cmul(wr[4], wi[4], wr[4], wi[4], wr[6], wi[6]);
          cmul(wr[6], wi[6], wr[4], wi[4], wr[7], wi[7]); cmul(wr[6], wi[6], wr[6], wi[6], wr[8], wi[8]);
          uint32_t R[4], I[4], PR[4], PI[4];
          #pragma unroll
          for (int b = 0; b < 4; b++) { R[b] = packh(xr[2 * b], xr[2 * b + 1]); I[b] = packh(xi[2 * b], xi[2 * b + 1]); }
          sts128(ea, R[0], R[1], R[2], R[3]); sts128(ea + 128, I[0], I[1], I[2], I[3]);
          #pragma unroll
          for (int i = 0; i < 3; i++) {
            const uint32_t z = packh(wr[i], wi[i]);
            #pragma unroll
            for (int b = 0; b < 4; b++) hcm2(R[b], I[b], z, PR[b], PI[b]);
            sts128(ea + (i + 1) * 1024, PR[0], PR[1], PR[2], PR[3]); sts128(ea + (i + 1) * 1024 + 128, PI[0], PI[1], PI[2], PI[3]);
          }
          gr[0] = bf_lo(p2) * sc; gi[0] = -bf_lo(p3) * sc;
          cmul(z1r, z1i, z1r, z1i, z2r, z2i); cmul(z2r, z2i, z2r, z2i, z4r, z4i);
          cmul(gr[0], gi[0], z1r, z1i, gr[1], gi[1]);
          cmul(gr[0], gi[0], z2r, z2i, gr[2], gi[2]); cmul(gr[1], gi[1], z2r, z2i, gr[3], gi[3]);
          #pragma unroll
          for (int b = 0; b < 4; b++) cmul(gr[b], gi[b], z4r, z4i, gr[4 + b], gi[4 + b]);
          sts128(ga, packh(gr[0], gr[1]), packh(gr[2], gr[3]), packh(gr[4], gr[5]), packh(gr[6], gr[7]));
          sts128(ga + 128, packh(gi[0], gi[1]), packh(gi[2], gi[3]), packh(gi[4], gi[5]), packh(gi[6], gi[7]));
          {
            const uint32_t z = packh(wr[3], -wi[3]), a4r = packh(gr[0], gr[4]), a4i = packh(gi[0], gi[4]);
            hcm2(packh(gr[0], gr[2]), packh(gi[0], gi[2]), z, PR[0], PI[0]);
            hcm2(packh(gr[4], gr[6]), packh(gi[4], gi[6]), z, PR[1], PI[1]);
            hcm2(a4r, a4i, packh(wr[4], -wi[4]), PR[2], PI[2]);
            hcm2(a4r, a4i, packh(wr[5], -wi[5]), PR[3], PI[3]);
            sts128(ga + 1024, PR[0], PR[1], PR[2], PR[3]); sts128(ga + 1024 + 128, PI[0], PI[1], PI[2], PI[3]);
            float hr, hi_;
            cmul(gr[0], gi[0], wr[3], -wi[3], hr, hi_);
            const uint32_t cr = packh(gr[0], hr), ci = packh(gi[0], hi_);
            #pragma unroll
            for (int i = 0; i < 3; i++) hcm2(cr, ci, packh(wr[6 + i], -wi[6 + i]), PR[i], PI[i]);
            sts128(ga + 2048, PR[0], PR[1], PR[2], 0u); sts128(ga + 2048 + 128, PI[0], PI[1], PI[2], 0u);
          }
        }
        fence_async();
        bar_sync(4, 128);
        if (t7 == 0 && k == 3) TS(50);
        float ka[24]; zero<24>(ka);
        wg_fence();
        #pragma unroll
        for (int s = 0; s < 8; s++) wg_ss48_tt_h(ka, dE + (s >> 2) * (BLK >> 4) + (s & 3) * 16, dG + (s >> 2) * (BLK >> 4) + (s & 3) * 16, s != 0);
        wg_commit();
        wg_wait<0>();
        pin<24>(ka);
        if (t7 == 0 && k == 3) TS(51);
        float kk[6];
        {
          const bool up = w4 >= 2;
          const uint32_t xa = sb + OFF_BLK + 2 * BLK + B_D + 7168 + t7 * 8;
          #pragma unroll
          for (int n = 0; n < 3; n++) {
            sts64f(xa + n * 1024, up ? ka[12 + 4 * n] : ka[4 * n + 2], up ? ka[13 + 4 * n] : ka[4 * n + 3]);
            kk[2 * n] = up ? ka[14 + 4 * n] : ka[4 * n]; kk[2 * n + 1] = up ? ka[15 + 4 * n] : ka[4 * n + 1];
          }
          bar_sync(4, 128);
          #pragma unroll
          for (int n = 0; n < 3; n++) {
            uint32_t o[2]; lds64(o, (xa ^ 512) + n * 1024);
            kk[2 * n] = (kk[2 * n] + __uint_as_float(o[0])) * fac; kk[2 * n + 1] = (kk[2 * n + 1] + __uint_as_float(o[1])) * fac;
          }
        }
        if (t7 == 0 && k == 3) TS(52);
        {
          const int j = (w4 & 1) * 16 + (w4 >> 1) * 8 + g;
          const uint32_t tb = blk + B_TBL;
          if (t7 == 0) kk[0] += dsk;
          const uint32_t pa_ = tb + (16 + 8 * j + 2 * tq) * 4;
          const uint32_t v = pack2(kk[1], kk[0]);
          sts32(pa_ + 4, v); sts16(pa_, v >> 16); sts16(pa_ + 10, v);
          const uint32_t u = pack2(kk[2], kk[3]), w = pack2(kk[4], kk[5]);
          if (tq < 2) {
            const uint32_t pb = tb + (16 + 256 + 8 * j + 4 * tq) * 4;
            sts16(pb, u); sts32(pb + 4, __byte_perm(u, 0, 0x1010)); sts32(pb + 8, __byte_perm(u, 0, 0x1032)); sts16(pb + 14, u >> 16);
            if (j | tq) { sts16(pb - 4, u); sts16(pb + 2, u); }
            const int i = 64 * tq + j;
            const uint32_t e0 = tb + (T_F3 + (((i - 1) & 1) ? 80 : 0) + ((i - 1) >> 1)) * 4, e1 = i ? e0 : tb + (T_F2 + 144 + 31) * 4;
            sts16(e1, w); sts16(e1 + 6, w); sts16(e0 + 64, w >> 16); sts16(e0 + 70, w >> 16);
            if (i == 0) { sts16(tb + (T_S + 3) * 4, w); sts32(tb + (T_S + 4) * 4, __byte_perm(w, 0, 0x1010)); sts16(tb + (T_S + 5) * 4 + 2, w); }
          } else {
            const int i = 32 * (tq - 2) + j;
            const uint32_t e1 = tb + (i ? T_F2 + ((2 * i - 1) & 3) * 48 + ((2 * i - 1) >> 2) : 16 + 511) * 4;
            const uint32_t e2 = tb + (T_F2 + (i & 1) * 96 + (i >> 1)) * 4;
            sts16(e1, u); sts16(e1 + 6, u); sts16(e2, u >> 16); sts16(e2 + 6, u >> 16);
            if (i == 0) {
              const uint32_t uu = __byte_perm(u, 0, 0x1010);
              sts32(tb + 528 * 4, uu); sts32(tb + 529 * 4, uu); sts32(tb + 530 * 4, uu); sts16(tb + 531 * 4 + 2, u);
              sts16(tb + (T_F3 + 80 + 63) * 4, w);
            }
          }
        }
        if (t7 == 0 && k == 3) TS(53);
      }
      bar_sync(4, 128);
      if (t7 == 0) { mbar_arrive(BAR(BR_KGEN)); TS(41); }
    }
    mbar_wait(BAR(BR_U), 0);
    if (EN_ATT) mbar_wait(BAR(BR_GEMM), 0);
    if (t7 == 0) TS(42);
    #pragma unroll 1
    for (int pass = 0; pass < 2; pass++) {
      const int k = pass ? w4 : 4;
      const uint32_t blk = sb + OFF_BLK + k * BLK, tb = blk + B_TBL + (uint32_t)((g - 2 * tq) * 4);
      if (k < 2) mbar_wait(BAR(BR_U2), 0);
      float acc[16][4];
      zero<64>(&acc[0][0]);
      const int kl = 16 * (lane >> 4) + 2 * (lane & 7) + ((lane >> 3) & 1);
      {
        const int ds = pass ? 1 : 4;
        int s = pass ? 0 : w4;
        uint32_t A[4][4], Bl[4][4], Bh[4][4];
        uint32_t ub;
        auto ubase = [&](int sh) { const int q = kl - 2 * sh; return blk + (uint32_t)((q * 16) ^ ((q * 2) & 0x70)); };
        ub = ubase(s);
        #pragma unroll
        for (int m = 0; m < 4; m++) load_quad(A[m], tb + (16 + 16 * s + 128 * m) * 4);
        #pragma unroll
        for (int p = 0; p < 4; p++) ldsm4(Bl[p], (ub ^ ((p & 1) * 64)) + p * 512);
        #pragma unroll 1
        for (; s < 8; s += ds) {
          #pragma unroll
          for (int p = 0; p < 4; p++) ldsm4(Bh[p], (ub ^ ((p & 1) * 64)) + (4 + p) * 512);
          #pragma unroll
          for (int m = 0; m < 4; m++)
            #pragma unroll
            for (int cc = 0; cc < 8; cc++) mma16816(acc[cc + m], A[m], &Bl[cc >> 1][(cc & 1) * 2]);
          if (s < 2) {
            uint32_t E[2][4];
            load_quad(E[0], tb + (16 + 512 + 16 * s) * 4); load_quad(E[1], tb + (T_S + 16 * s) * 4);
            #pragma unroll
            for (int cc = 0; cc < 8; cc++) mma16816(acc[cc + 4], E[0], &Bl[cc >> 1][(cc & 1) * 2]);
            #pragma unroll
            for (int cc = 0; cc < 4; cc++) mma16816(acc[cc + 12], E[0], &Bh[cc >> 1][(cc & 1) * 2]);
            #pragma unroll
            for (int cc = 0; cc < 8; cc++) mma16816(acc[cc + 8], E[1], &Bl[cc >> 1][(cc & 1) * 2]);
          }
          const int sn = (s + ds) & 7;
          uint32_t An[4][4];
          ub = ubase(sn);
          #pragma unroll
          for (int m = 0; m < 4; m++) load_quad(An[m], tb + (16 + 16 * sn + 128 * m) * 4);
          #pragma unroll
          for (int p = 0; p < 4; p++) ldsm4(Bl[p], (ub ^ ((p & 1) * 64)) + p * 512);
          #pragma unroll
          for (int m = 0; m < 4; m++)
            #pragma unroll
            for (int cc = 0; cc < 8 - m; cc++) mma16816(acc[8 + cc + m], A[m], &Bh[cc >> 1][(cc & 1) * 2]);
          #pragma unroll
          for (int m = 0; m < 4; m++)
            #pragma unroll
            for (int e = 0; e < 4; e++) A[m][e] = An[m][e];
        }
      }
      if (t7 == 0) TS(57 + 3 * pass);
      mbar_wait(BAR(BR_DRDY) + 8 * k, 0);
      {
        const uint32_t dl = (uint32_t)(((lane >> 4) * 8 + (lane & 7)) * 16);
        const int ih = (lane >> 3) & 1;
        #pragma unroll 1
        for (int a = pass ? 0 : w4; a < 4; a += pass ? 1 : 4) {
          const uint32_t da = blk + B_D + (a & 1) * B_D5 + dl + ((a & 2) ? (ih ? 0 : 1536) : (ih ? 1552 : 0));
          const uint32_t ta = tb + (T_F2 + 48 * a - 32) * 4;
          uint32_t B[6][2], A[6][4];
          #pragma unroll
          for (int e = 0; e < 6; e++) { B[e][0] = lds32(ta + (e + 4) * 32); B[e][1] = lds32(ta + (e + 3) * 32); }
          #pragma unroll
          for (int kk = 0; kk < 6; kk++) ldsm4t(A[kk], da + kk * 256);
          #pragma unroll
          for (int e = 0; e < 6; e++)
            #pragma unroll
            for (int kk = 0; kk < 6; kk++) if (2 * kk + e + 4 < 16) mma16816(acc[2 * kk + e + 4], A[kk], B[e]);
        }
        #pragma unroll 1
        for (int b = pass ? 0 : w4 - 2; b < 2; b += pass ? 1 : 4) {
          if (b < 0) break;
          const uint32_t da = blk + B_D + B_D7 + b * 2048 + dl + ih * 1024;
          const uint32_t ta = tb + (T_F3 + 80 * b - 64) * 4;
          uint32_t B[8][2], A[4][4];
          #pragma unroll
          for (int e = 0; e < 8; e++) { B[e][0] = lds32(ta + (e + 8) * 32); B[e][1] = lds32(ta + (e + 7) * 32); }
          #pragma unroll
          for (int kk = 0; kk < 4; kk++) ldsm4t(A[kk], da + kk * 256);
          #pragma unroll
          for (int kk = 0; kk < 4; kk++)
            #pragma unroll
            for (int e = 0; e < 8; e++) if (2 * kk + e + 8 < 16) mma16816(acc[2 * kk + e + 8], A[kk], B[e]);
        }
      }
      if (t7 == 0) TS(58 + 3 * pass);
      const uint32_t ya = blk + (uint32_t)((kl * 16) ^ ((kl * 2) & 0x70));
      if (pass == 0) {
        bar_sync(4, 128);
        const uint32_t xw = blk + 4096 + w4 * 4096 + lane * 16, hi = w4 >> 1, od = w4 & 1;
        float h[8][4];
        #pragma unroll
        for (int i = 0; i < 8; i++) {
          sts128(xw + i * 512, __float_as_uint(hi ? acc[i][0] : acc[8 + i][0]), __float_as_uint(hi ? acc[i][1] : acc[8 + i][1]),
                 __float_as_uint(hi ? acc[i][2] : acc[8 + i][2]), __float_as_uint(hi ? acc[i][3] : acc[8 + i][3]));
          #pragma unroll
          for (int e = 0; e < 4; e++) h[i][e] = hi ? acc[8 + i][e] : acc[i][e];
        }
        bar_sync(4, 128);
        const uint32_t xr = blk + 4096 + (w4 ^ 2) * 4096 + lane * 16;
        #pragma unroll
        for (int i = 0; i < 8; i++) {
          uint32_t o[4]; lds128(o, xr + i * 512);
          #pragma unroll
          for (int e = 0; e < 4; e++) h[i][e] += __uint_as_float(o[e]);
        }
        #pragma unroll
        for (int i = 0; i < 4; i++)
          sts128(xr + i * 512, __float_as_uint(od ? h[i][0] : h[4 + i][0]), __float_as_uint(od ? h[i][1] : h[4 + i][1]),
                 __float_as_uint(od ? h[i][2] : h[4 + i][2]), __float_as_uint(od ? h[i][3] : h[4 + i][3]));
        bar_sync(4, 128);
        uint32_t y[8];
        #pragma unroll
        for (int i = 0; i < 4; i++) {
          uint32_t o[4]; lds128(o, blk + 4096 + (w4 ^ 3) * 4096 + lane * 16 + i * 512);
          y[2 * i] = pack2((od ? h[4 + i][0] : h[i][0]) + __uint_as_float(o[0]), (od ? h[4 + i][1] : h[i][1]) + __uint_as_float(o[1]));
          y[2 * i + 1] = pack2((od ? h[4 + i][2] : h[i][2]) + __uint_as_float(o[2]), (od ? h[4 + i][3] : h[i][3]) + __uint_as_float(o[3]));
        }
        stsm4t(ya + w4 * 1024, y[0], y[1], y[2], y[3]);
        stsm4t((ya ^ 64) + w4 * 1024 + 512, y[4], y[5], y[6], y[7]);
      } else {
        __syncwarp();
        #pragma unroll
        for (int p = 0; p < 8; p++)
          stsm4t((ya ^ ((p & 1) * 64)) + p * 512, pack2(acc[2 * p][0], acc[2 * p][1]), pack2(acc[2 * p][2], acc[2 * p][3]),
                 pack2(acc[2 * p + 1][0], acc[2 * p + 1][1]), pack2(acc[2 * p + 1][2], acc[2 * p + 1][3]));
      }
      fence_async();
      mbar_arrive(BAR(BR_YSTG) + 8 * k);
      if (t7 == 0) TS(59 + 3 * pass);
    }
    if (t7 == 0) DUMP(40, 64);
    }
  }
}

typedef CUresult (*EncFn)(CUtensorMap*, CUtensorMapDataType, cuuint32_t, void*, const cuuint64_t*, const cuuint64_t*, const cuuint32_t*,
                          const cuuint32_t*, CUtensorMapInterleave, CUtensorMapSwizzle, CUtensorMapL2promotion, CUtensorMapFloatOOBfill);
static CUtensorMap mkmap(EncFn enc, const void* base, int rank, const cuuint64_t* dims, const cuuint64_t* strides, const cuuint32_t* box, CUtensorMapSwizzle swz) {
  CUtensorMap m; cuuint32_t es[5] = {1, 1, 1, 1, 1};
  enc(&m, CU_TENSOR_MAP_DATA_TYPE_BFLOAT16, rank, const_cast<void*>(base), dims, strides, box, es, CU_TENSOR_MAP_INTERLEAVE_NONE, swz,
      CU_TENSOR_MAP_L2_PROMOTION_L2_128B, CU_TENSOR_MAP_FLOAT_OOB_FILL_NONE);
  return m;
}

extern "C" void kernel_launch(void* const* d_in, const int* in_sizes, int n_in, void* d_out, int out_size) {
  void* fn = nullptr; cudaDriverEntryPointQueryResult qr;
  cudaGetDriverEntryPoint("cuTensorMapEncodeTiled", &fn, cudaEnableDefault, &qr);
  EncFn enc = (EncFn)fn;
  void* uy = nullptr; cudaGetSymbolAddress(&uy, g_uy);
  const cuuint64_t dx[2] = {640, 2048}, sx[1] = {1280};
  const cuuint32_t bx[2] = {64, 128}, bu[2] = {80, 64};
  const cuuint64_t dw[3] = {640, 640, 3}, sw[2] = {3840, 1280};
  const cuuint32_t bw[3] = {64, 32, 3}, br[3] = {16, 32, 3};
  const cuuint64_t dwo[2] = {640, 640};
  const cuuint32_t bwo[2] = {64, 80}, bwr[2] = {16, 160}, bo64[2] = {64, 64}, bo16[2] = {16, 64};
  const cuuint64_t dsa[2] = {2048, 1280}, ssa[1] = {4096};
  const cuuint32_t bsa[2] = {64, 80};
  const cuuint64_t dsb[2] = {64, 40960}, ssb[1] = {128};
  const cuuint32_t bsb[2] = {64, 32};
  const cuuint64_t dout[2] = {1280, 2048}, sout[1] = {2560};
  CUtensorMap mx = mkmap(enc, d_in[7], 2, dx, sx, bx, CU_TENSOR_MAP_SWIZZLE_128B);
  CUtensorMap mw = mkmap(enc, d_in[8], 3, dw, sw, bw, CU_TENSOR_MAP_SWIZZLE_128B);
  CUtensorMap mr = mkmap(enc, d_in[8], 3, dw, sw, br, CU_TENSOR_MAP_SWIZZLE_32B);
  CUtensorMap mwo = mkmap(enc, d_in[9], 2, dwo, sx, bwo, CU_TENSOR_MAP_SWIZZLE_128B);
  CUtensorMap mwr = mkmap(enc, d_in[9], 2, dwo, sx, bwr, CU_TENSOR_MAP_SWIZZLE_32B);
  CUtensorMap mo64 = mkmap(enc, d_out, 2, dout, sout, bo64, CU_TENSOR_MAP_SWIZZLE_128B);
  CUtensorMap mo16 = mkmap(enc, d_out, 2, dout, sout, bo16, CU_TENSOR_MAP_SWIZZLE_NONE);
  CUtensorMap mu = mkmap(enc, d_in[0], 2, dx, sx, bu, CU_TENSOR_MAP_SWIZZLE_NONE);
  CUtensorMap msa = mkmap(enc, uy, 2, dsa, ssa, bsa, CU_TENSOR_MAP_SWIZZLE_128B);
  CUtensorMap msb = mkmap(enc, uy, 2, dsb, ssb, bsb, CU_TENSOR_MAP_SWIZZLE_128B);
  CUtensorMap mout = mkmap(enc, d_out, 2, dout, sout, bu, CU_TENSOR_MAP_SWIZZLE_NONE);
  Params prm;
  prm.logA = (const __nv_bfloat16*)d_in[1]; prm.Aim = (const __nv_bfloat16*)d_in[2];
  prm.Cr = (const __nv_bfloat16*)d_in[3]; prm.Ci = (const __nv_bfloat16*)d_in[4];
  prm.logdt = (const __nv_bfloat16*)d_in[5]; prm.dskip = (const __nv_bfloat16*)d_in[6];
  cudaFuncSetAttribute(fused_kernel, cudaFuncAttributeMaxDynamicSharedMemorySize, SMEM_BYTES);
  cudaLaunchConfig_t cfg = {};
  cfg.gridDim = dim3(128); cfg.blockDim = dim3(512); cfg.dynamicSmemBytes = SMEM_BYTES; cfg.stream = cudaStreamPerThread;
  cudaLaunchAttribute at[1];
  at[0].id = cudaLaunchAttributeClusterDimension; at[0].val.clusterDim.x = 2; at[0].val.clusterDim.y = 1; at[0].val.clusterDim.z = 1;
  cfg.attrs = at; cfg.numAttrs = 1;
  cudaLaunchKernelEx(&cfg, fused_kernel, mx, mw, mr, mwo, mwr, mo64, mo16, mu, msa, msb, mout, prm);
}
```

```cpp
#include <cuda_runtime.h>
#include <cuda_bf16.h>
#include <cuda_fp16.h>
#include <cuda.h>
#include <stdint.h>

#define U_PACE 250
#define EN_ATT 1
#define EN_SSM 1

__device__ __align__(1024) __nv_bfloat16 g_uy[2 * 640 * 2048];
__device__ __align__(128) uint4 g_kvp[8 * 16 * 240];
__device__ __align__(128) uint4 g_o[128 * 1280];
__device__ __align__(128) unsigned g_flag[40 * 32];
__device__ unsigned g_epoch[128];
#define TS(i) do {} while (0)
#define DUMP(lo, hi) do {} while (0)

constexpr uint32_t W_SLOT = 15360, OFF_X = 76800;
constexpr uint32_t OFF_WOM = 20480, OFF_KVS = 71680, OFF_PK = 80896, OFF_V = 101376, OFF_EXTRA = 102400, OFF_KVB = OFF_EXTRA;
constexpr uint32_t OFF_BAR = 125952, OFF_BLK = 128000, BLK = 20480;
constexpr uint32_t B_D = 4096, B_D5 = 3088, B_D7 = 6176, B_D9 = 8224, B_TBL = 14400, B_SP = 18432;
constexpr int T_S = 576, T_F2 = 624, T_F3 = 816;
constexpr uint32_t SMEM_BYTES = OFF_BLK + 5 * BLK + 1024;
enum { BR_FULL = 0, BR_EMPTY = 5, BR_WO = 10, BR_PUB = 12, BR_PAR = 13, BR_U2 = 14, BR_OFULL = 18, BR_OEMPTY = 22, BR_GEMM = 26, BR_OSTG = 27, BR_UIN = 28,
       BR_U = 29, BR_DRDY = 30, BR_KGEN = 35, BR_YSTG = 36, BR_FREE = 41, BR_YIN = 46, BR_EPOCH = 47, BR_COUNT = 48 };
constexpr uint32_t OFF_EPOCH = OFF_BAR + 8 * BR_COUNT;

__device__ __forceinline__ long long clk64() { long long t; asm volatile("mov.u64 %0, %%clock64;" : "=l"(t) :: "memory"); return t; }
__device__ __forceinline__ uint32_t smem_u32(const void* p) { return (uint32_t)__cvta_generic_to_shared(p); }
__device__ __forceinline__ uint64_t mkdesc(uint32_t addr, uint32_t lbo, uint32_t sbo, uint32_t swz) {
  return (uint64_t)((addr & 0x3FFFF) >> 4) | ((uint64_t)(lbo >> 4) << 16) | ((uint64_t)(sbo >> 4) << 32) | ((uint64_t)swz << 62);
}
__device__ __forceinline__ void mbar_init(uint32_t bar, uint32_t cnt) { asm volatile("mbarrier.init.shared::cta.b64 [%0], %1;" :: "r"(bar), "r"(cnt) : "memory"); }
__device__ __forceinline__ void mbar_expect_tx(uint32_t bar, uint32_t bytes) { asm volatile("mbarrier.arrive.expect_tx.shared::cta.b64 _, [%0], %1;" :: "r"(bar), "r"(bytes) : "memory"); }
__device__ __forceinline__ void mbar_arrive(uint32_t bar) { asm volatile("mbarrier.arrive.shared::cta.b64 _, [%0];" :: "r"(bar) : "memory"); }
__device__ __forceinline__ void mbar_wait(uint32_t bar, uint32_t parity) {
  asm volatile("{\n.reg .pred p;\n.reg .u32 c;\nmov.u32 c, 0;\n"
    "WL:\nmbarrier.try_wait.parity.shared::cta.b64 p, [%0], %1;\n@p bra WD;\n"
    "add.u32 c, c, 1;\nsetp.lt.u32 p, c, 200000;\n@p bra WL;\nWD:\n}" :: "r"(bar), "r"(parity) : "memory");
}
__device__ __forceinline__ void poll_all(const unsigned* p, unsigned val) {
  asm volatile("{\n.reg .pred p;\n.reg .u32 c, v;\nmov.u32 c, 0;\n"
    "PL:\nld.relaxed.gpu.global.u32 v, [%0];\nsetp.eq.u32 p, v, %1;\nvote.sync.all.pred p, p, 0xffffffff;\n@p bra PD;\n"
    "add.u32 c, c, 1;\nsetp.lt.u32 p, c, 100000;\n@p bra PL;\nPD:\n}" :: "l"(p), "r"(val) : "memory");
}
__device__ __forceinline__ unsigned poll_bit(const unsigned* p, unsigned val, unsigned mask) {
  unsigned bal;
  asm volatile("{\n.reg .pred p;\n.reg .u32 c, v;\nmov.u32 c, 0;\n"
    "PL:\nld.relaxed.gpu.global.u32 v, [%1];\nsetp.eq.u32 p, v, %2;\nvote.sync.ballot.b32 %0, p, 0xffffffff;\n"
    "and.b32 v, %0, %3;\nsetp.ne.u32 p, v, 0;\n@p bra PD;\n"
    "add.u32 c, c, 1;\nsetp.lt.u32 p, c, 100000;\n@p bra PL;\nPD:\n}" : "=&r"(bal) : "l"(p), "r"(val), "r"(mask) : "memory");
  return bal;
}
__device__ __forceinline__ void fix128_w0(uint32_t* v, const void* p, uint32_t tag, uint32_t mask) {
  asm volatile("{\n.reg .pred p;\n.reg .u32 c, x;\n.reg .b128 t;\n.reg .b64 lo, hi;\nmov.u32 c, 0;\n"
    "FL:\nxor.b32 x, %0, %5;\nand.b32 x, x, %6;\nsetp.eq.u32 p, x, 0;\n@p bra FD;\n"
    "ld.relaxed.gpu.global.b128 t, [%4];\nmov.b128 {lo, hi}, t;\nmov.b64 {%0, %1}, lo;\nmov.b64 {%2, %3}, hi;\n"
    "add.u32 c, c, 1;\nsetp.lt.u32 p, c, 100000;\n@p bra FL;\nFD:\n}"
    : "+r"(v[0]), "+r"(v[1]), "+r"(v[2]), "+r"(v[3]) : "l"(p), "r"(tag), "r"(mask) : "memory");
}
__device__ __forceinline__ void fix128_w3(uint32_t* v, const void* p, uint32_t tag, uint32_t mask) {
  asm volatile("{\n.reg .pred p;\n.reg .u32 c, x;\n.reg .b128 t;\n.reg .b64 lo, hi;\nmov.u32 c, 0;\n"
    "FL:\nxor.b32 x, %3, %5;\nand.b32 x, x, %6;\nsetp.eq.u32 p, x, 0;\n@p bra FD;\n"
    "ld.relaxed.gpu.global.b128 t, [%4];\nmov.b128 {lo, hi}, t;\nmov.b64 {%0, %1}, lo;\nmov.b64 {%2, %3}, hi;\n"
    "add.u32 c, c, 1;\nsetp.lt.u32 p, c, 100000;\n@p bra FL;\nFD:\n}"
    : "+r"(v[0]), "+r"(v[1]), "+r"(v[2]), "+r"(v[3]) : "l"(p), "r"(tag), "r"(mask) : "memory");
}
__device__ __forceinline__ void fence_acq() { asm volatile("fence.acq_rel.gpu;" ::: "memory"); }
__device__ __forceinline__ bool elect_one() {
  uint32_t p; asm volatile("{\n.reg .pred P;\nelect.sync _|P, 0xffffffff;\nselp.u32 %0, 1, 0, P;\n}" : "=r"(p)); return p;
}
__device__ __forceinline__ void bar_sync(int id, int n) { asm volatile("bar.sync %0, %1;" :: "r"(id), "r"(n) : "memory"); }
__device__ __forceinline__ void fence_async() { asm volatile("fence.proxy.async.shared::cta;" ::: "memory"); }
__device__ __forceinline__ void fence_async_g() { asm volatile("fence.proxy.async.global;" ::: "memory"); }
__device__ __forceinline__ void tma2d(uint32_t dst, const CUtensorMap* m, uint32_t bar, int c0, int c1) {
  asm volatile("cp.async.bulk.tensor.2d.shared::cluster.global.mbarrier::complete_tx::bytes [%0], [%1, {%3, %4}], [%2];"
    :: "r"(dst), "l"(m), "r"(bar), "r"(c0), "r"(c1) : "memory");
}
__device__ __forceinline__ void tma3d(uint32_t dst, const CUtensorMap* m, uint32_t bar, int c0, int c1, int c2) {
  asm volatile("cp.async.bulk.tensor.3d.shared::cluster.global.mbarrier::complete_tx::bytes [%0], [%1, {%3, %4, %5}], [%2];"
    :: "r"(dst), "l"(m), "r"(bar), "r"(c0), "r"(c1), "r"(c2) : "memory");
}
__device__ __forceinline__ void tma2d_st(const CUtensorMap* m, uint32_t src, int c0, int c1) {
  asm volatile("cp.async.bulk.tensor.2d.global.shared::cta.bulk_group [%0, {%2, %3}], [%1];"
    :: "l"(m), "r"(src), "r"(c0), "r"(c1) : "memory");
}
__device__ __forceinline__ void bulk_ld(uint32_t dst, const void* src, uint32_t bytes, uint32_t bar) {
  asm volatile("cp.async.bulk.shared::cluster.global.mbarrier::complete_tx::bytes [%0], [%1], %2, [%3];"
    :: "r"(dst), "l"(src), "r"(bytes), "r"(bar) : "memory");
}
__device__ __forceinline__ void bulk_st(void* dst, uint32_t src, uint32_t bytes) {
  asm volatile("cp.async.bulk.global.shared::cta.bulk_group [%0], [%1], %2;" :: "l"(dst), "r"(src), "r"(bytes) : "memory");
}
__device__ __forceinline__ void bulk_commit() { asm volatile("cp.async.bulk.commit_group;" ::: "memory"); }
__device__ __forceinline__ void bulk_wait0() { asm volatile("cp.async.bulk.wait_group 0;" ::: "memory"); }
__device__ __forceinline__ void bulk_wait0_read() { asm volatile("cp.async.bulk.wait_group.read 0;" ::: "memory"); }
__device__ __forceinline__ unsigned ld_rlx(const unsigned* p) { unsigned v; asm volatile("ld.relaxed.gpu.global.u32 %0, [%1];" : "=r"(v) : "l"(p) : "memory"); return v; }
__device__ __forceinline__ unsigned ld_acq(const unsigned* p) { unsigned v; asm volatile("ld.acquire.gpu.global.u32 %0, [%1];" : "=r"(v) : "l"(p) : "memory"); return v; }
__device__ __forceinline__ void st_rlx(unsigned* p, unsigned v) { asm volatile("st.relaxed.gpu.global.u32 [%0], %1;" :: "l"(p), "r"(v) : "memory"); }
__device__ __forceinline__ void st_rel(unsigned* p, unsigned v) { asm volatile("st.release.gpu.global.u32 [%0], %1;" :: "l"(p), "r"(v) : "memory"); }
__device__ __forceinline__ void ld128_rlx(uint32_t* v, const void* p) {
  asm volatile("{\n.reg .b128 t;\n.reg .b64 lo, hi;\nld.relaxed.gpu.global.b128 t, [%4];\nmov.b128 {lo, hi}, t;\n"
    "mov.b64 {%0, %1}, lo;\nmov.b64 {%2, %3}, hi;\n}" : "=r"(v[0]), "=r"(v[1]), "=r"(v[2]), "=r"(v[3]) : "l"(p) : "memory");
}
__device__ __forceinline__ void st128_rlx(void* p, const uint32_t* v) {
  asm volatile("{\n.reg .b128 t;\n.reg .b64 lo, hi;\nmov.b64 lo, {%1, %2};\nmov.b64 hi, {%3, %4};\nmov.b128 t, {lo, hi};\n"
    "st.relaxed.gpu.global.b128 [%0], t;\n}" :: "l"(p), "r"(v[0]), "r"(v[1]), "r"(v[2]), "r"(v[3]) : "memory");
}
__device__ __forceinline__ uint32_t lds32(uint32_t a) { uint32_t v; asm volatile("ld.shared.u32 %0, [%1];" : "=r"(v) : "r"(a) : "memory"); return v; }
__device__ __forceinline__ uint32_t lds32v(uint32_t a) { uint32_t v; asm volatile("ld.volatile.shared.u32 %0, [%1];" : "=r"(v) : "r"(a) : "memory"); return v; }
__device__ __forceinline__ uint32_t cpa(uint32_t a, uint32_t one) { uint32_t v; asm volatile("mul.lo.u32 %0, %1, %2;" : "=r"(v) : "r"(a), "r"(one)); return v; }
__device__ __forceinline__ uint32_t cpb(uint32_t a, uint32_t zero) { uint32_t v; asm volatile("or.b32 %0, %1, %2;" : "=r"(v) : "r"(a), "r"(zero)); return v; }
__device__ __forceinline__ uint32_t lds16(uint32_t a) { uint16_t v; asm volatile("ld.shared.u16 %0, [%1];" : "=h"(v) : "r"(a) : "memory"); return v; }
__device__ __forceinline__ float ldsf(uint32_t a) { float v; asm volatile("ld.shared.f32 %0, [%1];" : "=f"(v) : "r"(a) : "memory"); return v; }
__device__ __forceinline__ void lds128(uint32_t* v, uint32_t a) { asm volatile("ld.shared.v4.u32 {%0,%1,%2,%3}, [%4];" : "=r"(v[0]), "=r"(v[1]), "=r"(v[2]), "=r"(v[3]) : "r"(a) : "memory"); }
__device__ __forceinline__ void sts32(uint32_t a, uint32_t v) { asm volatile("st.shared.u32 [%0], %1;" :: "r"(a), "r"(v) : "memory"); }
__device__ __forceinline__ void sts16(uint32_t a, uint32_t v) { asm volatile("st.shared.u16 [%0], %1;" :: "r"(a), "h"((uint16_t)v) : "memory"); }
__device__ __forceinline__ void sts64f(uint32_t a, float x, float y) { asm volatile("st.shared.v2.f32 [%0], {%1,%2};" :: "r"(a), "f"(x), "f"(y) : "memory"); }
__device__ __forceinline__ void sts128(uint32_t a, uint32_t x, uint32_t y, uint32_t z, uint32_t w) { asm volatile("st.shared.v4.u32 [%0], {%1,%2,%3,%4};" :: "r"(a), "r"(x), "r"(y), "r"(z), "r"(w) : "memory"); }
__device__ __forceinline__ void stsm4(uint32_t a, uint32_t r0, uint32_t r1, uint32_t r2, uint32_t r3) {
  asm volatile("stmatrix.sync.aligned.m8n8.x4.shared.b16 [%0], {%1,%2,%3,%4};" :: "r"(a), "r"(r0), "r"(r1), "r"(r2), "r"(r3) : "memory");
}
__device__ __forceinline__ void stsm4t(uint32_t a, uint32_t r0, uint32_t r1, uint32_t r2, uint32_t r3) {
  asm volatile("stmatrix.sync.aligned.m8n8.x4.trans.shared.b16 [%0], {%1,%2,%3,%4};" :: "r"(a), "r"(r0), "r"(r1), "r"(r2), "r"(r3) : "memory");
}
__device__ __forceinline__ void ldsm4t(uint32_t* r, uint32_t a) {
  asm volatile("ldmatrix.sync.aligned.m8n8.x4.trans.shared.b16 {%0,%1,%2,%3}, [%4];" : "=r"(r[0]), "=r"(r[1]), "=r"(r[2]), "=r"(r[3]) : "r"(a) : "memory");
}
__device__ __forceinline__ void ldsm4(uint32_t* r, uint32_t a) {
  asm volatile("ldmatrix.sync.aligned.m8n8.x4.shared.b16 {%0,%1,%2,%3}, [%4];" : "=r"(r[0]), "=r"(r[1]), "=r"(r[2]), "=r"(r[3]) : "r"(a) : "memory");
}
__device__ __forceinline__ void mma16816(float* d, const uint32_t* a, const uint32_t* b) {
  asm volatile("mma.sync.aligned.m16n8k16.row.col.f32.bf16.bf16.f32 {%0,%1,%2,%3}, {%4,%5,%6,%7}, {%8,%9}, {%0,%1,%2,%3};"
    : "+f"(d[0]), "+f"(d[1]), "+f"(d[2]), "+f"(d[3]) : "r"(a[0]), "r"(a[1]), "r"(a[2]), "r"(a[3]), "r"(b[0]), "r"(b[1]));
}
__device__ __forceinline__ uint32_t pack2(float lo, float hi) { uint32_t r; asm("cvt.rn.bf16x2.f32 %0, %1, %2;" : "=r"(r) : "f"(hi), "f"(lo)); return r; }
__device__ __forceinline__ uint32_t packh(float lo, float hi) { uint32_t r; asm("cvt.rn.f16x2.f32 %0, %1, %2;" : "=r"(r) : "f"(hi), "f"(lo)); return r; }
__device__ __forceinline__ uint32_t hcmul(uint32_t x, uint32_t zp, uint32_t zq) {
  const __half2 xx = *reinterpret_cast<__half2*>(&x);
  const __half2 r = __hfma2(__high2half2(xx), *reinterpret_cast<__half2*>(&zq), __hmul2(__low2half2(xx), *reinterpret_cast<__half2*>(&zp)));
  return *reinterpret_cast<const uint32_t*>(&r);
}
__device__ __forceinline__ void hcm2(uint32_t xr, uint32_t xi, uint32_t z, uint32_t& pr, uint32_t& pi) {
  const __half2 a = *reinterpret_cast<__half2*>(&xr), b = *reinterpret_cast<__half2*>(&xi), zz = *reinterpret_cast<__half2*>(&z);
  const __half2 re = __hfma2(__hneg2(b), __high2half2(zz), __hmul2(a, __low2half2(zz)));
  const __half2 im = __hfma2(a, __high2half2(zz), __hmul2(b, __low2half2(zz)));
  pr = *reinterpret_cast<const uint32_t*>(&re); pi = *reinterpret_cast<const uint32_t*>(&im);
}
__device__ __forceinline__ void sts64(uint32_t a, uint32_t x, uint32_t y) { asm volatile("st.shared.v2.u32 [%0], {%1,%2};" :: "r"(a), "r"(x), "r"(y) : "memory"); }
__device__ __forceinline__ void lds64(uint32_t* v, uint32_t a) { asm volatile("ld.shared.v2.u32 {%0,%1}, [%2];" : "=r"(v[0]), "=r"(v[1]) : "r"(a) : "memory"); }
__device__ __forceinline__ float bf_lo(uint32_t v) { return __uint_as_float(v << 16); }
__device__ __forceinline__ float bf_hi(uint32_t v) { return __uint_as_float(v & 0xffff0000u); }
__device__ __forceinline__ float bf_round(float x) { return bf_lo(pack2(x, 0.f)); }
__device__ __forceinline__ float ex2(float x) { float r; asm("ex2.approx.ftz.f32 %0, %1;" : "=f"(r) : "f"(x)); return r; }
__device__ __forceinline__ float phi(float t, float l2e = 1.44269504089f) { float e = ex2(t * l2e); return (t > 0.f ? t + 1.f : e) + 1e-6f; }
__device__ __forceinline__ void wg_fence() { asm volatile("wgmma.fence.sync.aligned;" ::: "memory"); }
__device__ __forceinline__ void wg_commit() { asm volatile("wgmma.commit_group.sync.aligned;" ::: "memory"); }
template <int N> __device__ __forceinline__ void wg_wait() { asm volatile("wgmma.wait_group.sync.aligned %0;" :: "n"(N) : "memory"); }
template <int N> __device__ __forceinline__ void pin(float* a) {
  #pragma unroll
  for (int i = 0; i < N; i++) asm volatile("" : "+f"(a[i]) :: "memory");
}
__device__ __forceinline__ int opaque(int v) { asm volatile("" : "+r"(v)); return v; }
template <int N> __device__ __forceinline__ void zero(float* a) {
  #pragma unroll
  for (int i = 0; i < N; i++) asm volatile("mov.b32 %0, 0;" : "=f"(a[i]));
}
template <int N> __device__ __forceinline__ void pinu(uint32_t* a) {
  #pragma unroll
  for (int i = 0; i < N; i++) asm volatile("" : "+r"(a[i]) :: "memory");
}
__device__ __forceinline__ void cexp_t(float lg2mag, float turns, float& re, float& im) {
  float m = ex2(lg2mag);
  float fr = (turns - __fadd_rn(__fadd_rn(turns, 12582912.f), -12582912.f)) * 6.283185307f;
  re = m * __cosf(fr); im = m * __sinf(fr);
}
__device__ __forceinline__ void cmul(float ar, float ai, float br, float bi, float& cr, float& ci) {
  cr = fmaf(ar, br, -ai * bi); ci = fmaf(ar, bi, ai * br);
}

__device__ __forceinline__ void wg_ss192_tb(float* d, uint64_t da, uint64_t db, int scale_d) {
  asm volatile("{\n.reg .pred p;\nsetp.ne.b32 p, %98, 0;\n"
    "wgmma.mma_async.sync.aligned.m64n192k16.f32.bf16.bf16 "
    "{%0, %1, %2, %3, %4, %5, %6, %7, %8, %9, %10, %11, %12, %13, %14, %15, %16, %17, %18, %19, %20, %21, %22, %23, %24, %25, %26, %27, %28, %29, %30, %31, %32, %33, %34, %35, %36, %37, %38, %39, %40, %41, %42, %43, %44, %45, %46, %47, %48, %49, %50, %51, %52, %53, %54, %55, %56, %57, %58, %59, %60, %61, %62, %63, %64, %65, %66, %67, %68, %69, %70, %71, %72, %73, %74, %75, %76, %77, %78, %79, %80, %81, %82, %83, %84, %85, %86, %87, %88, %89, %90, %91, %92, %93, %94, %95}, %96, %97, p, 1, 1, 0, 1;\n}\n"
    : "+f"(d[0]), "+f"(d[1]), "+f"(d[2]), "+f"(d[3]), "+f"(d[4]), "+f"(d[5]), "+f"(d[6]), "+f"(d[7]), "+f"(d[8]), "+f"(d[9]), "+f"(d[10]), "+f"(d[11]), "+f"(d[12]), "+f"(d[13]), "+f"(d[14]), "+f"(d[15]), "+f"(d[16]), "+f"(d[17]), "+f"(d[18]), "+f"(d[19]), "+f"(d[20]), "+f"(d[21]), "+f"(d[22]), "+f"(d[23]), "+f"(d[24]), "+f"(d[25]), "+f"(d[26]), "+f"(d[27]), "+f"(d[28]), "+f"(d[29]), "+f"(d[30]), "+f"(d[31]), "+f"(d[32]), "+f"(d[33]), "+f"(d[34]), "+f"(d[35]), "+f"(d[36]), "+f"(d[37]), "+f"(d[38]), "+f"(d[39]), "+f"(d[40]), "+f"(d[41]), "+f"(d[42]), "+f"(d[43]), "+f"(d[44]), "+f"(d[45]), "+f"(d[46]), "+f"(d[47]), "+f"(d[48]), "+f"(d[49]), "+f"(d[50]), "+f"(d[51]), "+f"(d[52]), "+f"(d[53]), "+f"(d[54]), "+f"(d[55]), "+f"(d[56]), "+f"(d[57]), "+f"(d[58]), "+f"(d[59]), "+f"(d[60]), "+f"(d[61]), "+f"(d[62]), "+f"(d[63]), "+f"(d[64]), "+f"(d[65]), "+f"(d[66]), "+f"(d[67]), "+f"(d[68]), "+f"(d[69]), "+f"(d[70]), "+f"(d[71]), "+f"(d[72]), "+f"(d[73]), "+f"(d[74]), "+f"(d[75]), "+f"(d[76]), "+f"(d[77]), "+f"(d[78]), "+f"(d[79]), "+f"(d[80]), "+f"(d[81]), "+f"(d[82]), "+f"(d[83]), "+f"(d[84]), "+f"(d[85]), "+f"(d[86]), "+f"(d[87]), "+f"(d[88]), "+f"(d[89]), "+f"(d[90]), "+f"(d[91]), "+f"(d[92]), "+f"(d[93]), "+f"(d[94]), "+f"(d[95])
    : "l"(da), "l"(db), "r"(scale_d));
}
__device__ __forceinline__ void wg_ss48_tb(float* d, uint64_t da, uint64_t db, int scale_d) {
  asm volatile("{\n.reg .pred p;\nsetp.ne.b32 p, %26, 0;\n"
    "wgmma.mma_async.sync.aligned.m64n48k16.f32.bf16.bf16 "
    "{%0, %1, %2, %3, %4, %5, %6, %7, %8, %9, %10, %11, %12, %13, %14, %15, %16, %17, %18, %19, %20, %21, %22, %23}, %24, %25, p, 1, 1, 0, 1;\n}\n"
    : "+f"(d[0]), "+f"(d[1]), "+f"(d[2]), "+f"(d[3]), "+f"(d[4]), "+f"(d[5]), "+f"(d[6]), "+f"(d[7]), "+f"(d[8]), "+f"(d[9]), "+f"(d[10]), "+f"(d[11]), "+f"(d[12]), "+f"(d[13]), "+f"(d[14]), "+f"(d[15]), "+f"(d[16]), "+f"(d[17]), "+f"(d[18]), "+f"(d[19]), "+f"(d[20]), "+f"(d[21]), "+f"(d[22]), "+f"(d[23])
    : "l"(da), "l"(db), "r"(scale_d));
}
__device__ __forceinline__ void wg_ss48_tt(float* d, uint64_t da, uint64_t db, int scale_d) {
  asm volatile("{\n.reg .pred p;\nsetp.ne.b32 p, %26, 0;\n"
    "wgmma.mma_async.sync.aligned.m64n48k16.f32.bf16.bf16 "
    "{%0, %1, %2, %3, %4, %5, %6, %7, %8, %9, %10, %11, %12, %13, %14, %15, %16, %17, %18, %19, %20, %21, %22, %23}, %24, %25, p, 1, 1, 1, 1;\n}\n"
    : "+f"(d[0]), "+f"(d[1]), "+f"(d[2]), "+f"(d[3]), "+f"(d[4]), "+f"(d[5]), "+f"(d[6]), "+f"(d[7]), "+f"(d[8]), "+f"(d[9]), "+f"(d[10]), "+f"(d[11]), "+f"(d[12]), "+f"(d[13]), "+f"(d[14]), "+f"(d[15]), "+f"(d[16]), "+f"(d[17]), "+f"(d[18]), "+f"(d[19]), "+f"(d[20]), "+f"(d[21]), "+f"(d[22]), "+f"(d[23])
    : "l"(da), "l"(db), "r"(scale_d));
}
__device__ __forceinline__ void wg_rs88_tb(float* d, const uint32_t* a, uint64_t db, int scale_d) {
  asm volatile("{\n.reg .pred p;\nsetp.ne.b32 p, %49, 0;\n"
    "wgmma.mma_async.sync.aligned.m64n88k16.f32.bf16.bf16 "
    "{%0, %1, %2, %3, %4, %5, %6, %7, %8, %9, %10, %11, %12, %13, %14, %15, %16, %17, %18, %19, %20, %21, %22, %23, %24, %25, %26, %27, %28, %29, %30, %31, %32, %33, %34, %35, %36, %37, %38, %39, %40, %41, %42, %43}, {%44, %45, %46, %47}, %48, p, 1, 1, 1;\n}\n"
    : "+f"(d[0]), "+f"(d[1]), "+f"(d[2]), "+f"(d[3]), "+f"(d[4]), "+f"(d[5]), "+f"(d[6]), "+f"(d[7]), "+f"(d[8]), "+f"(d[9]), "+f"(d[10]), "+f"(d[11]), "+f"(d[12]), "+f"(d[13]), "+f"(d[14]), "+f"(d[15]), "+f"(d[16]), "+f"(d[17]), "+f"(d[18]), "+f"(d[19]), "+f"(d[20]), "+f"(d[21]), "+f"(d[22]), "+f"(d[23]), "+f"(d[24]), "+f"(d[25]), "+f"(d[26]), "+f"(d[27]), "+f"(d[28]), "+f"(d[29]), "+f"(d[30]), "+f"(d[31]), "+f"(d[32]), "+f"(d[33]), "+f"(d[34]), "+f"(d[35]), "+f"(d[36]), "+f"(d[37]), "+f"(d[38]), "+f"(d[39]), "+f"(d[40]), "+f"(d[41]), "+f"(d[42]), "+f"(d[43])
    : "r"(a[0]), "r"(a[1]), "r"(a[2]), "r"(a[3]), "l"(db), "r"(scale_d));
}
__device__ __forceinline__ void wg_rs64_tb(float* d, const uint32_t* a, uint64_t db, int scale_d) {
  asm volatile("{\n.reg .pred p;\nsetp.ne.b32 p, %37, 0;\n"
    "wgmma.mma_async.sync.aligned.m64n64k16.f32.bf16.bf16 "
    "{%0, %1, %2, %3, %4, %5, %6, %7, %8, %9, %10, %11, %12, %13, %14, %15, %16, %17, %18, %19, %20, %21, %22, %23, %24, %25, %26, %27, %28, %29, %30, %31}, {%32, %33, %34, %35}, %36, p, 1, 1, 1;\n}\n"
    : "+f"(d[0]), "+f"(d[1]), "+f"(d[2]), "+f"(d[3]), "+f"(d[4]), "+f"(d[5]), "+f"(d[6]), "+f"(d[7]), "+f"(d[8]), "+f"(d[9]), "+f"(d[10]), "+f"(d[11]), "+f"(d[12]), "+f"(d[13]), "+f"(d[14]), "+f"(d[15]), "+f"(d[16]), "+f"(d[17]), "+f"(d[18]), "+f"(d[19]), "+f"(d[20]), "+f"(d[21]), "+f"(d[22]), "+f"(d[23]), "+f"(d[24]), "+f"(d[25]), "+f"(d[26]), "+f"(d[27]), "+f"(d[28]), "+f"(d[29]), "+f"(d[30]), "+f"(d[31])
    : "r"(a[0]), "r"(a[1]), "r"(a[2]), "r"(a[3]), "l"(db), "r"(scale_d));
}
__device__ __forceinline__ void wg_ss48_tt_h(float* d, uint64_t da, uint64_t db, int scale_d) {
  asm volatile("{\n.reg .pred p;\nsetp.ne.b32 p, %26, 0;\n"
    "wgmma.mma_async.sync.aligned.m64n48k16.f32.f16.f16 "
    "{%0, %1, %2, %3, %4, %5, %6, %7, %8, %9, %10, %11, %12, %13, %14, %15, %16, %17, %18, %19, %20, %21, %22, %23}, %24, %25, p, 1, 1, 1, 1;\n}\n"
    : "+f"(d[0]), "+f"(d[1]), "+f"(d[2]), "+f"(d[3]), "+f"(d[4]), "+f"(d[5]), "+f"(d[6]), "+f"(d[7]), "+f"(d[8]), "+f"(d[9]), "+f"(d[10]), "+f"(d[11]), "+f"(d[12]), "+f"(d[13]), "+f"(d[14]), "+f"(d[15]), "+f"(d[16]), "+f"(d[17]), "+f"(d[18]), "+f"(d[19]), "+f"(d[20]), "+f"(d[21]), "+f"(d[22]), "+f"(d[23])
    : "l"(da), "l"(db), "r"(scale_d));
}
__device__ __forceinline__ void wg_rs16_tb(float* d, const uint32_t* a, uint64_t db, int scale_d) {
  asm volatile("{\n.reg .pred p;\nsetp.ne.b32 p, %13, 0;\n"
    "wgmma.mma_async.sync.aligned.m64n16k16.f32.bf16.bf16 "
    "{%0, %1, %2, %3, %4, %5, %6, %7}, {%8, %9, %10, %11}, %12, p, 1, 1, 1;\n}\n"
    : "+f"(d[0]), "+f"(d[1]), "+f"(d[2]), "+f"(d[3]), "+f"(d[4]), "+f"(d[5]), "+f"(d[6]), "+f"(d[7])
    : "r"(a[0]), "r"(a[1]), "r"(a[2]), "r"(a[3]), "l"(db), "r"(scale_d));
}

struct Params {
  const __nv_bfloat16 *logA, *Aim, *Cr, *Ci, *logdt, *dskip;
};

template <bool FWD>
__device__ __forceinline__ void tile_transpose(uint32_t tc0, uint32_t tc1, uint32_t ct0, uint32_t ct1, int hw, int lane) {
  const int mi = lane >> 3, row = lane & 7;
  for (int gi = hw; gi < 40; gi += 3) {
    const int hh = gi / 20, rem = gi - hh * 20, q = rem / 10, cb = rem - q * 10;
    const uint32_t a_tc = (hh ? tc1 : tc0) + (8 * (4 * q + mi) + row) * 160 + cb * 16;
    const uint32_t a_ct = (hh ? ct1 : ct0) + (8 * cb + row) * 128 + (((4 * q + mi) ^ row) << 4);
    uint32_t r[4];
    ldsm4t(r, FWD ? a_tc : a_ct);
    stsm4(FWD ? a_ct : a_tc, r[0], r[1], r[2], r[3]);
  }
}

__device__ __forceinline__ void load_quad(uint32_t* A, uint32_t addr) {
  A[0] = lds32v(addr); A[1] = lds32v(addr + 32); A[2] = lds32v(addr - 32); A[3] = lds32v(addr);
}

__global__ void __launch_bounds__(512, 1)
fused_kernel(const __grid_constant__ CUtensorMap mx, const __grid_constant__ CUtensorMap mw, const __grid_constant__ CUtensorMap mr,
             const __grid_constant__ CUtensorMap mwo, const __grid_constant__ CUtensorMap mwr, const __grid_constant__ CUtensorMap mo64,
             const __grid_constant__ CUtensorMap mo16, const __grid_constant__ CUtensorMap mu, const __grid_constant__ CUtensorMap msa,
             const __grid_constant__ CUtensorMap msb, const __grid_constant__ CUtensorMap mout, const Params prm) {
  extern __shared__ unsigned char smem_raw[];
  const uint32_t sb = (smem_u32(smem_raw) + 1023) & ~1023u;
  const int tid = threadIdx.x, lane = tid & 31;
  const int wg = __shfl_sync(0xffffffff, tid >> 7, 0), warp = __shfl_sync(0xffffffff, tid >> 5, 0);
  const int cta = blockIdx.x, r = cta >> 3, c = cta & 7;
  const uint32_t bars = sb + OFF_BAR;
#define BAR(i) (bars + 8 * (i))

  auto issue1 = [&](int kb) {
    const uint32_t st = sb + (kb % 5) * W_SLOT, fb = BAR(BR_FULL + kb % 5);
    mbar_expect_tx(fb, (kb & 1) ? W_SLOT : W_SLOT + 16384);
    if (!(kb & 1)) tma2d(sb + OFF_X + ((kb >> 1) % 3) * 16384, &mx, fb, kb * 32, r * 128);
    tma3d(st, &mw, fb, c * 80, kb * 32, 0);
    tma3d(st + 12288, &mr, fb, c * 80 + 64, kb * 32, 0);
  };

  if (warp == 12) {
    if (elect_one()) {
      #pragma unroll
      for (int i = 0; i < BR_COUNT; i++) {
        int cnt = 1;
        if (i >= BR_EMPTY && i < BR_EMPTY + 5) cnt = 2;
        if (i >= BR_OEMPTY && i < BR_OEMPTY + 4) cnt = 8;
        if (i == BR_OSTG) cnt = 256;
        if (i >= BR_DRDY && i < BR_DRDY + 5) cnt = 96;
        if (i >= BR_YSTG && i < BR_YSTG + 5) cnt = i == BR_YSTG + 4 ? 128 : 32;
        mbar_init(BAR(i), cnt);
      }
      asm volatile("fence.mbarrier_init.release.cluster;" ::: "memory");
      if (EN_ATT) issue1(0);
    }
  }
  if (warp == 13 && lane < 8) {
    const CUtensorMap* mp = lane == 0 ? &mu : lane == 1 ? &msb : lane == 2 ? &mwo : lane == 3 ? &mwr : lane == 4 ? &msa : lane == 5 ? &mout : lane == 6 ? &mo64 : &mo16;
    asm volatile("prefetch.tensormap [%0];" :: "l"(mp) : "memory");
  }
  unsigned short ldt = 0, dsk0 = 0;
  uint4 pv[3];
  if (EN_SSM && wg == 2) {
    const int ai = warp & 3;
    const uint4* pp = reinterpret_cast<const uint4*>((ai == 0 ? prm.logA : ai == 1 ? prm.Aim : ai == 2 ? prm.Cr : prm.Ci) + (c * 80 + r * 5) * 128);
    pv[0] = __ldg(pp + lane); pv[1] = __ldg(pp + 32 + lane); pv[2] = __ldg(pp + 64 + (lane & 15));
    const int kq = c * 80 + r * 5 + min(tid - 256, 4);
    ldt = __ldg(reinterpret_cast<const unsigned short*>(prm.logdt) + kq); dsk0 = __ldg(reinterpret_cast<const unsigned short*>(prm.dskip) + kq);
  }
  __syncthreads();

  if (wg == 3) {
    asm volatile("setmaxnreg.dec.sync.aligned.u32 56;");
    if (warp == 12) {
      if (EN_ATT) {
      #pragma unroll
      for (int kb = 1; kb < 20; kb++) {
        if (kb >= 5) mbar_wait(BAR(BR_EMPTY + kb % 5), ((kb / 5) & 1) ^ 1);
        if (elect_one()) issue1(kb);
      }
      auto chunk_of = [&](int i) { return i == 0 ? c : (i == 7 ? (c ^ 1) : (((c & 6) + 1 + i) & 7)); };
      mbar_wait(BAR(BR_EPOCH), 0);
      const unsigned epoch = lds32(sb + OFF_EPOCH);
      const unsigned* fo = &g_flag[(24 + r) * 32 + (lane & 7)];
      unsigned seen = __ballot_sync(0xffffffff, ld_rlx(fo) == epoch);
      mbar_wait(BAR(BR_GEMM), 0);
      if (elect_one()) {
        mbar_expect_tx(BAR(BR_WO), 20480 + 5 * 10240);
        #pragma unroll
        for (int i = 0; i < 5; i++) tma2d(sb + OFF_WOM + i * 10240, &mwo, BAR(BR_WO), c * 64, i * 80);
        #pragma unroll
        for (int i = 0; i < 4; i++) tma2d(sb + i * 5120, &mwr, BAR(BR_WO), 512 + c * 16, i * 160);
      }
      mbar_wait(BAR(BR_PUB), 0);
      if (elect_one()) {
        mbar_expect_tx(BAR(BR_WO + 1), 3 * 10240);
        #pragma unroll
        for (int i = 5; i < 8; i++) tma2d(sb + OFF_WOM + i * 10240, &mwo, BAR(BR_WO + 1), c * 64, i * 80);
      }
      mbar_wait(BAR(BR_OSTG), 0);
      if (elect_one()) {
        bulk_st(&g_o[cta * 1280], sb + OFF_EXTRA, 20480);
        bulk_commit();
        bulk_wait0();
        st_rlx(&g_flag[(24 + r) * 32 + c], epoch);
        TS(20);
      }
      __syncwarp();
      #pragma unroll
      for (int i = 0; i < 7; i++) {
        const int src = chunk_of(i + 1);
        if (!((seen >> src) & 1)) seen = poll_bit(fo, epoch, 1u << src);
        if (i < 3) { if (EN_SSM) mbar_wait(BAR(BR_FREE + 4 - i), 0); }
        else if (i > 3) mbar_wait(BAR(BR_OEMPTY + i - 4), 0);
        if (elect_one()) {
          fence_async_g();
          const uint32_t slot = (i & 3) == 3 ? sb + OFF_EXTRA : sb + OFF_BLK + (4 - (i & 3)) * BLK;
          mbar_expect_tx(BAR(BR_OFULL + (i & 3)), 20480);
          bulk_ld(slot, &g_o[(r * 8 + src) * 1280], 20480, BAR(BR_OFULL + (i & 3)));
          if (i == 0) TS(21);
          if (i == 6) { TS(22); DUMP(20, 30); }
        }
        __syncwarp();
      }
      }
    } else {
      const int hw = warp - 13, ht = tid - 416;
      unsigned epoch = 0;
      if (hw == 0) {
        if (lane == 0) {
          if (EN_SSM) {
            mbar_expect_tx(BAR(BR_UIN), 20480);
            tma2d(sb + OFF_BLK + 4 * BLK + B_D, &mu, BAR(BR_UIN), c * 80, r * 128);
            tma2d(sb + OFF_BLK + 3 * BLK + B_D, &mu, BAR(BR_UIN), c * 80, r * 128 + 64);
          }
          epoch = ld_rlx(&g_epoch[cta]) + 1;
          st_rlx(&g_epoch[cta], epoch);
          sts32(sb + OFF_EPOCH, epoch);
          mbar_arrive(BAR(BR_EPOCH));
        }
        epoch = __shfl_sync(0xffffffff, epoch, 0);
      }
      if (EN_SSM) {
      mbar_wait(BAR(BR_UIN), 0);
      if (ht == 0) TS(36);
      {
        const int mi = lane >> 3, rw = lane & 7;
        const uint32_t lo = (uint32_t)((8 * (rw >> 1) + 2 * mi + (rw & 1)) * 160);
        uint4* gp = reinterpret_cast<uint4*>(g_uy + (size_t)(c * 80 + hw * 8 + (lane >> 2)) * 2048 + r * 128 + (lane & 3) * 8);
        const uint32_t sa = sb + OFF_BLK + 3 * BLK + B_D + lo + hw * 16;
        #pragma unroll
        for (int i = 0; i < 4; i++) {
          if (i < 3 || hw == 0) {
            uint32_t v[4][4];
            #pragma unroll
            for (int q = 0; q < 4; q++) ldsm4t(v[q], sa + (1 - (q >> 1)) * BLK + (q & 1) * 5120 + i * 48);
            #pragma unroll
            for (int q = 0; q < 4; q++) {
              gp[i * 6144 + q * 4] = make_uint4(v[q][0], v[q][1], v[q][2], v[q][3]);
              if (q & 1) __nanosleep(U_PACE);
            }
          }
        }
      }
      if (ht == 0) TS(37);
      __threadfence();
      if (ht == 0) TS(38);
      bar_sync(5, 96);
      if (hw == 0) {
        if (lane == 0) { st_rlx(&g_flag[(8 + c) * 32 + r], epoch); TS(30); }
        __syncwarp();
        poll_all(&g_flag[(8 + c) * 32 + (lane & 15)], epoch);
        (void)ld_acq(&g_flag[(8 + c) * 32 + (lane & 15)]); __syncwarp();
        if (lane == 0) {
          fence_async_g();
          mbar_expect_tx(BAR(BR_U), 12288);
          #pragma unroll
          for (int k = 4; k >= 2; k--) tma2d(sb + OFF_BLK + k * BLK, &msb, BAR(BR_U), 0, (c * 80 + r * 5 + k) * 32);
          TS(31);
        }
        __syncwarp();
      }
      mbar_wait(BAR(BR_U), 0);
      if (ht == 0) TS(39);
      #pragma unroll 1
      for (int k = 4; k >= 0; k--) {
        if (k == 2) {
          mbar_wait(BAR(BR_KGEN), 0);
          if (ht == 0) {
            fence_async();
            mbar_expect_tx(BAR(BR_U2), 8192);
            tma2d(sb + OFF_BLK + BLK, &msb, BAR(BR_U2), 0, (c * 80 + r * 5 + 1) * 32);
            tma2d(sb + OFF_BLK, &msb, BAR(BR_U2), 0, (c * 80 + r * 5) * 32);
          }
          __syncwarp();
        }
        if (k == 1) mbar_wait(BAR(BR_U2), 0);
        const uint32_t blk = sb + OFF_BLK + k * BLK;
        #pragma unroll 1
        for (int kap = ht; kap < 192; kap += 96) {
          float P[33];
          P[0] = 0.f;
          #pragma unroll
          for (int q = 0; q < 4; q++) {
            const int ch = kap - 3 + q;
            uint32_t v[4];
            lds128(v, blk + (uint32_t)((ch >> 3) * 128 + (((ch & 7) ^ ((ch >> 3) & 7)) << 4)));
            #pragma unroll
            for (int e = 0; e < 4; e++) {
              P[q * 8 + 2 * e + 1] = P[q * 8 + 2 * e] + bf_lo(v[e]);
              P[q * 8 + 2 * e + 2] = P[q * 8 + 2 * e + 1] + bf_hi(v[e]);
            }
          }
#define WIN(lo, hi, e) (P[25 + (e) - (lo)] - P[24 + (e) - (hi)])
#define WIN8(lo, hi) pack2(WIN(lo, hi, 0), WIN(lo, hi, 1)), pack2(WIN(lo, hi, 2), WIN(lo, hi, 3)), pack2(WIN(lo, hi, 4), WIN(lo, hi, 5)), pack2(WIN(lo, hi, 6), WIN(lo, hi, 7))
          const uint32_t o2 = blk + B_D + (kap & 1) * 1552 + (kap >> 1) * 16;
          sts128(o2, WIN8(3, 5));
          sts128(o2 + B_D5, WIN8(6, 10));
          if (kap < 128) {
            const uint32_t o = blk + B_D + (kap & 1) * 1024 + (kap >> 1) * 16;
            sts128(o + B_D7, WIN8(5, 11));
            sts128(o + B_D9, WIN8(12, 20));
          }
        }
        if (ht < 2) sts128(blk + B_D + ht * B_D5 + 1536, 0, 0, 0, 0);
        mbar_arrive(BAR(BR_DRDY + k));
      }
      if (ht == 0) TS(32);
      if (hw == 0) {
        #pragma unroll 1
        for (int k = 4; k >= 0; k--) {
          mbar_wait(BAR(BR_YSTG + k), 0);
          if (lane == 0) {
            tma2d_st(&msb, sb + OFF_BLK + k * BLK, 0, (640 + c * 80 + r * 5 + k) * 32);
            bulk_commit(); bulk_wait0_read();
            mbar_arrive(BAR(BR_FREE + k));
          }
          __syncwarp();
        }
        if (lane == 0) { bulk_wait0(); st_rel(&g_flag[(16 + c) * 32 + r], epoch); TS(33); }
        __syncwarp();
        poll_all(&g_flag[(16 + c) * 32 + (lane & 15)], epoch);
        (void)ld_acq(&g_flag[(16 + c) * 32 + (lane & 15)]); __syncwarp();
        if (lane == 0) {
          fence_async_g();
          mbar_expect_tx(BAR(BR_YIN), 20480);
          tma2d(sb + OFF_BLK + BLK, &msa, BAR(BR_YIN), r * 128, 640 + c * 80);
          tma2d(sb + OFF_BLK + BLK + 10240, &msa, BAR(BR_YIN), r * 128 + 64, 640 + c * 80);
          TS(34);
        }
        __syncwarp();
      }
      mbar_wait(BAR(BR_YIN), 0);
      tile_transpose<false>(sb + OFF_BLK, sb + OFF_BLK + 10240, sb + OFF_BLK + BLK, sb + OFF_BLK + BLK + 10240, hw, lane);
      fence_async();
      bar_sync(5, 96);
      if (ht == 0) {
        tma2d_st(&mout, sb + OFF_BLK, c * 80, r * 128);
        tma2d_st(&mout, sb + OFF_BLK + 10240, c * 80, r * 128 + 64);
        bulk_commit(); bulk_wait0_read();
        TS(35); DUMP(30, 40); DUMP(0, 1);
      }
      }
    }
  } else if (wg < 2) {
    asm volatile("setmaxnreg.inc.sync.aligned.u32 152;");
    if (EN_ATT) {
    const int w4 = warp & 3, g = lane >> 2, tq = lane & 3, t7 = tid & 127;
    float am[96], ar[24];
    {
      const uint64_t da0 = mkdesc(sb + OFF_X + wg * 8192, 16, 1024, 1);
      const uint64_t db0 = mkdesc(sb, 4096, 1024, 1);
      const uint64_t dr0 = mkdesc(sb + 12288, 1024, 256, 3);
      uint32_t s = 0, ph = 0, xo = 0;
      #pragma unroll 1
      for (int kb = 0; kb < 20; kb++) {
        mbar_wait(BAR(BR_FULL) + 8 * s, ph);
        if (kb == 0 && tid == 0) TS(1);
        wg_fence();
        const uint32_t wo_ = s * (W_SLOT >> 4);
        wg_ss192_tb(am, da0 + xo, db0 + wo_, kb != 0);
        wg_ss48_tb(ar, da0 + xo, dr0 + wo_, kb != 0);
        wg_ss192_tb(am, da0 + xo + 2, db0 + wo_ + 128, 1);
        wg_ss48_tb(ar, da0 + xo + 2, dr0 + wo_ + 32, 1);
        wg_commit();
        wg_wait<1>();
        if (t7 == 0 && kb > 0 && kb < 16) mbar_arrive(BAR(BR_EMPTY) + 8 * (s == 0 ? 4 : s - 1));
        if (++s == 5) { s = 0; ph ^= 1; }
        xo += (kb & 1) ? 1020 : 4;
        if (xo == 3072) xo = 0;
      }
      wg_wait<0>();
      pin<96>(am); pin<24>(ar);
    }
    if (tid == 0) TS(2);
#define QV(j, e) ((j) < 8 ? am[4 * (j) + (e)] : ar[4 * ((j) - 8) + (e)])
#define KV_(j, e) ((j) < 8 ? am[32 + 4 * (j) + (e)] : ar[8 + 4 * ((j) - 8) + (e)])
#define VV(j, e) ((j) < 8 ? am[64 + 4 * (j) + (e)] : ar[16 + 4 * ((j) - 8) + (e)])
    {
      bar_sync(1, 256);
      if (tid == 0) mbar_arrive(BAR(BR_GEMM));
      const uint32_t ro = (uint32_t)((lane >> 4) * 2048 + (wg * 64 + w4 * 16 + (lane & 15)) * 16);
      const uint32_t ones = (tq == 0) ? 0x00003f80u : 0u;
#define PV(j) pack2(VV(j, 0), VV(j, 1)), pack2(VV(j, 2), VV(j, 3))
#define PK(j) pack2(phi(KV_(j, 0)), phi(KV_(j, 1))), pack2(phi(KV_(j, 2)), phi(KV_(j, 3)))
      stsm4(sb + OFF_V + 0 * 2048 + ro, PV(0), PV(1));
      stsm4(sb + OFF_V + 2 * 2048 + ro, PV(2), PV(3));
      stsm4(sb + OFF_V + 4 * 2048 + ro, PV(4), ones, ones);
      stsm4(sb + OFF_V + 6 * 2048 + ro, PV(5), PV(6));
      stsm4(sb + OFF_V + 8 * 2048 + ro, PV(7), PV(8));
      stsm4(sb + OFF_V + 10 * 2048 + ro, PV(9), ones, ones);
      #pragma unroll
      for (int j = 0; j < 10; j += 2) stsm4(sb + OFF_PK + j * 2048 + ro, PK(j), PK(j + 1));
    }
    fence_async();
    bar_sync(1, 256);
    if (tid == 0) TS(3);
    mbar_wait(BAR(BR_EPOCH), 0);
    const unsigned epoch = lds32(sb + OFF_EPOCH);
    {
      float kv[24]; zero<24>(kv);
      const uint64_t da = mkdesc(sb + OFF_PK + wg * 5 * 2048, 128, 2048, 0);
      const uint64_t db = mkdesc(sb + OFF_V + wg * 6 * 2048, 128, 2048, 0);
      wg_fence();
      #pragma unroll
      for (int s = 0; s < 8; s++) wg_ss48_tt(kv, da + s * 16, db + s * 16, s != 0);
      wg_commit();
      wg_wait<0>();
      pin<24>(kv);
      if (tid == 0) TS(15);
      if (w4 < 3) {
        const uint32_t wb = sb + OFF_KVS + (wg * 3 + w4) * 1536;
        #pragma unroll
        for (int j = 0; j < 6; j += 2)
          stsm4(wb + (lane & 15) * 96 + (j + (lane >> 4)) * 16, pack2(kv[4 * j], kv[4 * j + 1]), pack2(kv[4 * j + 2], kv[4 * j + 3]),
                pack2(kv[4 * j + 4], kv[4 * j + 5]), pack2(kv[4 * j + 6], kv[4 * j + 7]));
        __syncwarp();
        const int dl = w4 * 16 + (lane & 15), hl = dl >= 20;
        if (dl < 40) {
          uint4* dst = &g_kvp[(c * 16 + r) * 240 + wg * 40 + dl];
          uint32_t v[4];
          lds128(v, wb + (lane & 15) * 96 + (3 * hl + (lane >> 4)) * 16);
          v[3] = (v[3] & ~1u) | (epoch & 1u);
          st128_rlx(dst + (lane >> 4) * 80, v);
          if (lane < 16) {
            v[0] = lds32(wb + lane * 96 + 32 + 8 * hl); v[1] = lds32(wb + lane * 96 + 36 + 8 * hl);
            v[2] = lds32(wb + lane * 96 + 80); v[3] = epoch & 1u;
            st128_rlx(dst + 160, v);
          }
        }
      }
    }
    bar_sync(1, 256);
    if (tid == 0) { st_rlx(&g_flag[c * 32 + r], epoch); mbar_arrive(BAR(BR_PUB)); TS(4); }
    const int kd = tid >= 160 ? tid - 160 : (tid >= 80 ? tid - 80 : tid), kvi = (tid >= 80) + (tid >= 160);
    const int khd = kd / 20, kt0 = 5 * (khd >> 1) + 2 * (khd & 1);
    if (tid < 240) {
      #pragma unroll
      for (int m = 0; m < 3; m++) {
        int q = kt0 + 3 + kvi + 3 * m; if (q >= 10) q -= 10;
        if (kvi + 3 * m < 7) sts128(sb + OFF_KVB + q * 1280 + kd * 16, 0, 0, 0, 0);
      }
    }
    uint32_t qa[20];
    {
      const float sc = 1.44269504089f + __uint_as_float(lds32(sb + OFF_EPOCH) ^ epoch);
      #pragma unroll
      for (int j = 0; j < 10; j++) { qa[2 * j] = pack2(phi(QV(j, 0), sc), phi(QV(j, 1), sc)); qa[2 * j + 1] = pack2(phi(QV(j, 2), sc), phi(QV(j, 3), sc)); }
    }
    if (tid == 0) TS(5);
    {
      poll_all(&g_flag[c * 32 + (lane & 15)], epoch);
      if (tid == 0) TS(6);
      if (tid < 240) {
        uint32_t v[16][4];
        const uint4* src = &g_kvp[c * 16 * 240 + tid];
        #pragma unroll
        for (int i = 0; i < 16; i++) ld128_rlx(v[i], src + i * 240);
        float s[8];
        uint32_t bad = 0;
        #pragma unroll
        for (int i = 0; i < 16; i++) {
          bad |= v[i][3] ^ epoch;
          #pragma unroll
          for (int e = 0; e < 4; e++) {
            s[2 * e] = i ? s[2 * e] + bf_lo(v[i][e]) : bf_lo(v[i][e]);
            s[2 * e + 1] = i ? s[2 * e + 1] + bf_hi(v[i][e]) : bf_hi(v[i][e]);
          }
        }
        if (__builtin_expect(bad & 1u, 0)) {
          #pragma unroll
          for (int e = 0; e < 8; e++) s[e] = 0.f;
          #pragma unroll 1
          for (int i = 0; i < 16; i++) {
            uint32_t w[4] = {0, 0, 0, ~epoch};
            fix128_w3(w, src + i * 240, epoch, 1u);
            #pragma unroll
            for (int e = 0; e < 4; e++) { s[2 * e] += bf_lo(w[e]); s[2 * e + 1] += bf_hi(w[e]); }
          }
        }
        if (tid == 0) TS(18);
        const uint32_t p0 = pack2(s[0], s[1]), p1 = pack2(s[2], s[3]), p2 = pack2(s[4], s[5]), p3 = pack2(s[6], s[7]);
        const uint32_t rb = sb + OFF_KVB + kd * 16;
        if (kvi < 2) sts128(rb + (kt0 + (khd & 1) + kvi) * 1280, p0, p1, p2, p3);
        else {
          const bool od = khd & 1;
          sts128(rb + (5 * (khd >> 1) + 2) * 1280, od ? 0u : p0, od ? 0u : p1, od ? p0 : 0u, od ? p1 : 0u);
          const uint32_t zz = (p2 & 0xffffu) << (16 * (khd & 1));
          sts128(rb + 10 * 1280, khd < 2 ? zz : 0u, khd < 2 ? 0u : zz, 0u, 0u);
        }
      }
    }
    fence_async();
    bar_sync(1, 256);
    if (tid == 0) TS(7);
    uint32_t A0[20], A1[20];
    {
      float oa[44]; zero<44>(oa);
      const uint64_t db = mkdesc(sb + OFF_KVB, 128, 1280, 0);
      wg_fence();
      #pragma unroll
      for (int s = 0; s < 5; s++) wg_rs88_tb(oa, &qa[4 * s], db + s * 16, s != 0);
      wg_commit();
      if (tid == 0) TS(12);
      wg_wait<0>();
      pin<44>(oa);
      if (tid == 0) TS(13);
      float rc[4], rd[2][4];
      #pragma unroll
      for (int e = 0; e < 4; e++) rc[e] = __fdividef(1.f, oa[40 + e] + 1e-6f);
      #pragma unroll
      for (int h = 0; h < 4; h++) {
        rd[0][h] = __shfl_sync(0xffffffff, rc[h & 1], (lane & 28) | (h >> 1));
        rd[1][h] = __shfl_sync(0xffffffff, rc[2 + (h & 1)], (lane & 28) | (h >> 1));
      }
      #pragma unroll
      for (int j = 0; j < 10; j++) {
        #pragma unroll
        for (int h = 0; h < 2; h++) {
          float f;
          if (j == 2) f = tq < 2 ? rd[h][0] : rd[h][1];
          else if (j == 7) f = tq < 2 ? rd[h][2] : rd[h][3];
          else f = rd[h][(8 * j) / 20];
          A0[2 * j + h] = pack2(oa[4 * j + 2 * h] * f, oa[4 * j + 2 * h + 1] * f);
        }
      }
      bar_sync(1, 256);
      #pragma unroll
      for (int s = 0; s < 5; s++) {
        A0[4 * s] = (A0[4 * s] & ~1u) | (epoch & 1u);
        sts128(sb + OFF_EXTRA + ((wg * 5 + s) * 128 + t7) * 16, A0[4 * s], A0[4 * s + 1], A0[4 * s + 2], A0[4 * s + 3]);
      }
    }
    if (tid == 0) TS(14);
    fence_async();
    mbar_arrive(BAR(BR_OSTG));
    if (tid == 0) TS(8);
    float oc[32], od[8]; zero<32>(oc); zero<8>(od);
    {
      const uint64_t dw0 = mkdesc(sb + OFF_WOM, 16, 1024, 1), dr0 = mkdesc(sb, 16, 256, 3);
      mbar_wait(BAR(BR_WO), 0);
      mbar_wait(BAR(BR_WO + 1), 0);
      wg_fence();
      #pragma unroll
      for (int s = 0; s < 5; s++) { wg_rs64_tb(oc, &A0[4 * s], dw0 + c * 640 + s * 128, s != 0); wg_rs16_tb(od, &A0[4 * s], dr0 + c * 160 + s * 32, s != 0); }
      wg_commit();
      #pragma unroll
      for (int i = 0; i < 7; i++) {
        uint32_t* A = (i & 1) ? A0 : A1;
        const uint32_t slot = (i & 3) == 3 ? sb + OFF_EXTRA : sb + OFF_BLK + (4 - (i & 3)) * BLK;
        const int src = (i == 6) ? (c ^ 1) : (((c & 6) + 2 + i) & 7);
        mbar_wait(BAR(BR_OFULL + (i & 3)), i >> 2);
        if (i == 0 && tid == 0) TS(9);
        if (i > 0) wg_wait<1>();
        #pragma unroll
        for (int s = 0; s < 5; s++) lds128(&A[4 * s], slot + ((wg * 5 + s) * 128 + t7) * 16);
        uint32_t bad = 0;
        #pragma unroll
        for (int s = 0; s < 5; s++) bad |= A[4 * s] ^ epoch;
        if (__builtin_expect(bad & 1u, 0)) {
          #pragma unroll
          for (int s = 0; s < 5; s++) fix128_w0(&A[4 * s], &g_o[(r * 8 + src) * 1280 + (wg * 5 + s) * 128 + t7], epoch, 1u);
        }
        __syncwarp();
        if (i < 3 && lane == 0) mbar_arrive(BAR(BR_OEMPTY + i));
        wg_fence();
        #pragma unroll
        for (int s = 0; s < 5; s++) { wg_rs64_tb(oc, &A[4 * s], dw0 + src * 640 + s * 128, 1); wg_rs16_tb(od, &A[4 * s], dr0 + src * 160 + s * 32, 1); }
        wg_commit();
      }
      bar_sync(2 + wg, 128);
      wg_wait<0>();
      pin<32>(oc); pin<8>(od);
    }
    if (tid == 0) TS(10);
    {
      const int row = w4 * 16 + (lane & 15);
      const uint32_t ob = sb + OFF_EXTRA + wg * 10240;
      #pragma unroll
      for (int j = 0; j < 8; j += 2)
        stsm4(ob + row * 128 + (((j + (lane >> 4)) ^ (row & 7)) << 4), pack2(oc[4 * j], oc[4 * j + 1]), pack2(oc[4 * j + 2], oc[4 * j + 3]),
              pack2(oc[4 * j + 4], oc[4 * j + 5]), pack2(oc[4 * j + 6], oc[4 * j + 7]));
      stsm4(ob + 8192 + row * 32 + (lane >> 4) * 16, pack2(od[0], od[1]), pack2(od[2], od[3]), pack2(od[4], od[5]), pack2(od[6], od[7]));
      fence_async();
      bar_sync(2 + wg, 128);
      if (t7 == 0) {
        tma2d_st(&mo64, ob, 640 + c * 64, r * 128 + wg * 64);
        tma2d_st(&mo16, ob + 8192, 1152 + c * 16, r * 128 + wg * 64);
        bulk_commit(); bulk_wait0_read();
      }
      if (tid == 0) { TS(11); DUMP(0, 20); }
    }
    }
  } else {
    asm volatile("setmaxnreg.inc.sync.aligned.u32 152;");
    if (EN_SSM) {
    const int w4 = warp & 3, g = lane >> 2, tq = lane & 3, t7 = tid & 127;
    {
      #pragma unroll
      for (int k = 0; k < 5; k++) {
        const uint32_t tz = sb + OFF_BLK + k * BLK + B_TBL + t7 * 16;
        if (t7 < 32 || t7 >= 96) sts128(tz, 0, 0, 0, 0);
        if (t7 < 124) sts128(tz + 2048, 0, 0, 0, 0);
        if (t7 < 16) sts128(sb + OFF_BLK + k * BLK - 256 + t7 * 16, 0, 0, 0, 0);
      }
      if (t7 < 5) sts64(sb + OFF_BLK + t7 * BLK + B_SP + 8, __float_as_uint(bf_round(expf(bf_lo(ldt)))), (uint32_t)dsk0 << 16);
      const uint32_t st = sb + OFF_BLK + (lane >> 4) * BLK + B_TBL + 512 + w4 * 256 + (lane & 15) * 16;
      #pragma unroll
      for (int i = 0; i < 3; i++) {
        if (i < 2 || lane < 16) sts128(st + 2 * i * BLK, pv[i].x, pv[i].y, pv[i].z, pv[i].w);
        if (w4 >= 2) {
          const uint32_t m2 = __vmaxu2(__vmaxu2(pv[i].x & 0x7fff7fffu, pv[i].y & 0x7fff7fffu), __vmaxu2(pv[i].z & 0x7fff7fffu, pv[i].w & 0x7fff7fffu));
          const uint32_t m = __reduce_max_sync(lane < 16 ? 0x0000ffffu : 0xffff0000u, max(m2 & 0xffffu, m2 >> 16));
          if ((lane & 15) == 0 && (i < 2 || lane == 0)) sts32(sb + OFF_BLK + (2 * i + (lane >> 4)) * BLK + B_SP + 8 + w4 * 4, m);
        }
      }
    }
    bar_sync(4, 128);
    if (t7 == 0) TS(40);
    {
      const uint32_t fa = sb + OFF_BLK + (w4 & 1) * BLK + (lane >> 3) * 256 + (lane & 7) * 16;
      const uint32_t ea = fa + (w4 >> 1) * 4096, ga = fa + 8192 + (w4 >> 1) * 3072;
      const uint64_t dE = mkdesc(sb + OFF_BLK, 128, 1024, 0), dG = mkdesc(sb + OFF_BLK + 8192, 128, 1024, 0);
      #pragma unroll 1
      for (int k = 4; k >= 0; k--) {
        const uint32_t blk = sb + OFF_BLK + k * BLK;
        float fac, dsk;
        {
          const uint32_t st = blk + B_TBL + 512 + t7 * 2;
          uint32_t q[2], mm[2];
          const uint32_t p0 = lds16(st), p1 = lds16(st + 256), p2 = lds16(st + 512), p3 = lds16(st + 768);
          lds64(q, blk + B_SP + 8); lds64(mm, blk + B_SP + 16);
          const float dt = __uint_as_float(q[0]); dsk = __uint_as_float(q[1]);
          const uint32_t ex = min(max(max(mm[0], mm[1]) >> 7, 1u), 253u);
          const float sc = __uint_as_float((254u - ex) << 23);
          fac = 2.f * dt * __uint_as_float(ex << 23);
          const float lr = -bf_round(expf(bf_lo(p0))) * dt * 1.44269504089f;
          const float tn = bf_lo(p1) * dt * 0.15915494309f;
          float z1r, z1i, z2r, z2i, z4r, z4i, xr[8], xi[8], gr[8], gi[8], wr[9], wi[9];
          cexp_t(lr, -tn, z1r, z1i);
          cexp_t(lr * 8.f, tn * 8.f, xr[1], xi[1]);
          cexp_t(lr * 64.f, tn * 64.f, wr[0], wi[0]);
          xr[0] = 1.f; xi[0] = 0.f;
          cmul(xr[1], xi[1], xr[1], xi[1], xr[2], xi[2]); cmul(xr[2], xi[2], xr[1], xi[1], xr[3], xi[3]);
          cmul(xr[2], xi[2], xr[2], xi[2], xr[4], xi[4]);
          #pragma unroll
          for (int b = 1; b < 4; b++) cmul(xr[4], xi[4], xr[b], xi[b], xr[4 + b], xi[4 + b]);
          cmul(wr[0], wi[0], wr[0], wi[0], wr[1], wi[1]); cmul(wr[1], wi[1], wr[0], wi[0], wr[2], wi[2]);
          cmul(wr[1], wi[1], wr[1], wi[1], wr[3], wi[3]); cmul(wr[3], wi[3], wr[3], wi[3], wr[4], wi[4]);
          cmul(wr[4], wi[4], wr[3], wi[3], wr[5], wi[5]); cmul(wr[4], wi[4], wr[4], wi[4], wr[6], wi[6]);
          cmul(wr[6], wi[6], wr[4], wi[4], wr[7], wi[7]); cmul(wr[6], wi[6], wr[6], wi[6], wr[8], wi[8]);
          uint32_t R[4], I[4], PR[4], PI[4];
          #pragma unroll
          for (int b = 0; b < 4; b++) { R[b] = packh(xr[2 * b], xr[2 * b + 1]); I[b] = packh(xi[2 * b], xi[2 * b + 1]); }
          sts128(ea, R[0], R[1], R[2], R[3]); sts128(ea + 128, I[0], I[1], I[2], I[3]);
          #pragma unroll
          for (int i = 0; i < 3; i++) {
            const uint32_t z = packh(wr[i], wi[i]);
            #pragma unroll
            for (int b = 0; b < 4; b++) hcm2(R[b], I[b], z, PR[b], PI[b]);
            sts128(ea + (i + 1) * 1024, PR[0], PR[1], PR[2], PR[3]); sts128(ea + (i + 1) * 1024 + 128, PI[0], PI[1], PI[2], PI[3]);
          }
          gr[0] = bf_lo(p2) * sc; gi[0] = -bf_lo(p3) * sc;
          cmul(z1r, z1i, z1r, z1i, z2r, z2i); cmul(z2r, z2i, z2r, z2i, z4r, z4i);
          cmul(gr[0], gi[0], z1r, z1i, gr[1], gi[1]);
          cmul(gr[0], gi[0], z2r, z2i, gr[2], gi[2]); cmul(gr[1], gi[1], z2r, z2i, gr[3], gi[3]);
          #pragma unroll
          for (int b = 0; b < 4; b++) cmul(gr[b], gi[b], z4r, z4i, gr[4 + b], gi[4 + b]);
          sts128(ga, packh(gr[0], gr[1]), packh(gr[2], gr[3]), packh(gr[4], gr[5]), packh(gr[6], gr[7]));
          sts128(ga + 128, packh(gi[0], gi[1]), packh(gi[2], gi[3]), packh(gi[4], gi[5]), packh(gi[6], gi[7]));
          {
            const uint32_t z = packh(wr[3], -wi[3]), a4r = packh(gr[0], gr[4]), a4i = packh(gi[0], gi[4]);
            hcm2(packh(gr[0], gr[2]), packh(gi[0], gi[2]), z, PR[0], PI[0]);
            hcm2(packh(gr[4], gr[6]), packh(gi[4], gi[6]), z, PR[1], PI[1]);
            hcm2(a4r, a4i, packh(wr[4], -wi[4]), PR[2], PI[2]);
            hcm2(a4r, a4i, packh(wr[5], -wi[5]), PR[3], PI[3]);
            sts128(ga + 1024, PR[0], PR[1], PR[2], PR[3]); sts128(ga + 1024 + 128, PI[0], PI[1], PI[2], PI[3]);
            float hr, hi_;
            cmul(gr[0], gi[0], wr[3], -wi[3], hr, hi_);
            const uint32_t cr = packh(gr[0], hr), ci = packh(gi[0], hi_);
            #pragma unroll
            for (int i = 0; i < 3; i++) hcm2(cr, ci, packh(wr[6 + i], -wi[6 + i]), PR[i], PI[i]);
            sts128(ga + 2048, PR[0], PR[1], PR[2], 0u); sts128(ga + 2048 + 128, PI[0], PI[1], PI[2], 0u);
          }
        }
        fence_async();
        bar_sync(4, 128);
        if (t7 == 0 && k == 3) TS(50);
        float ka[24]; zero<24>(ka);
        wg_fence();
        #pragma unroll
        for (int s = 0; s < 8; s++) wg_ss48_tt_h(ka, dE + (s >> 2) * (BLK >> 4) + (s & 3) * 16, dG + (s >> 2) * (BLK >> 4) + (s & 3) * 16, s != 0);
        wg_commit();
        wg_wait<0>();
        pin<24>(ka);
        if (t7 == 0 && k == 3) TS(51);
        float kk[6];
        {
          const bool up = w4 >= 2;
          const uint32_t xa = sb + OFF_BLK + 2 * BLK + B_D + 7168 + t7 * 8;
          #pragma unroll
          for (int n = 0; n < 3; n++) {
            sts64f(xa + n * 1024, up ? ka[12 + 4 * n] : ka[4 * n + 2], up ? ka[13 + 4 * n] : ka[4 * n + 3]);
            kk[2 * n] = up ? ka[14 + 4 * n] : ka[4 * n]; kk[2 * n + 1] = up ? ka[15 + 4 * n] : ka[4 * n + 1];
          }
          bar_sync(4, 128);
          #pragma unroll
          for (int n = 0; n < 3; n++) {
            uint32_t o[2]; lds64(o, (xa ^ 512) + n * 1024);
            kk[2 * n] = (kk[2 * n] + __uint_as_float(o[0])) * fac; kk[2 * n + 1] = (kk[2 * n + 1] + __uint_as_float(o[1])) * fac;
          }
        }
        if (t7 == 0 && k == 3) TS(52);
        {
          const int j = (w4 & 1) * 16 + (w4 >> 1) * 8 + g;
          const uint32_t tb = blk + B_TBL;
          if (t7 == 0) kk[0] += dsk;
          const uint32_t pa_ = tb + (16 + 8 * j + 2 * tq) * 4;
          const uint32_t v = pack2(kk[1], kk[0]);
          sts32(pa_ + 4, v); sts16(pa_, v >> 16); sts16(pa_ + 10, v);
          const uint32_t u = pack2(kk[2], kk[3]), w = pack2(kk[4], kk[5]);
          if (tq < 2) {
            const uint32_t pb = tb + (16 + 256 + 8 * j + 4 * tq) * 4;
            sts16(pb, u); sts32(pb + 4, __byte_perm(u, 0, 0x1010)); sts32(pb + 8, __byte_perm(u, 0, 0x1032)); sts16(pb + 14, u >> 16);
            if (j | tq) { sts16(pb - 4, u); sts16(pb + 2, u); }
            const int i = 64 * tq + j;
            const uint32_t e0 = tb + (T_F3 + (((i - 1) & 1) ? 80 : 0) + ((i - 1) >> 1)) * 4, e1 = i ? e0 : tb + (T_F2 + 144 + 31) * 4;
            sts16(e1, w); sts16(e1 + 6, w); sts16(e0 + 64, w >> 16); sts16(e0 + 70, w >> 16);
            if (i == 0) { sts16(tb + (T_S + 3) * 4, w); sts32(tb + (T_S + 4) * 4, __byte_perm(w, 0, 0x1010)); sts16(tb + (T_S + 5) * 4 + 2, w); }
          } else {
            const int i = 32 * (tq - 2) + j;
            const uint32_t e1 = tb + (i ? T_F2 + ((2 * i - 1) & 3) * 48 + ((2 * i - 1) >> 2) : 16 + 511) * 4;
            const uint32_t e2 = tb + (T_F2 + (i & 1) * 96 + (i >> 1)) * 4;
            sts16(e1, u); sts16(e1 + 6, u); sts16(e2, u >> 16); sts16(e2 + 6, u >> 16);
            if (i == 0) {
              const uint32_t uu = __byte_perm(u, 0, 0x1010);
              sts32(tb + 528 * 4, uu); sts32(tb + 529 * 4, uu); sts32(tb + 530 * 4, uu); sts16(tb + 531 * 4 + 2, u);
              sts16(tb + (T_F3 + 80 + 63) * 4, w);
            }
          }
        }
        if (t7 == 0 && k == 3) TS(53);
      }
      bar_sync(4, 128);
      if (t7 == 0) { mbar_arrive(BAR(BR_KGEN)); TS(41); }
    }
    mbar_wait(BAR(BR_U), 0);
    if (EN_ATT) mbar_wait(BAR(BR_GEMM), 0);
    if (t7 == 0) TS(42);
    #pragma unroll 1
    for (int pass = 0; pass < 2; pass++) {
      const int k = pass ? w4 : 4;
      const uint32_t blk = sb + OFF_BLK + k * BLK, tb = blk + B_TBL + (uint32_t)((g - 2 * tq) * 4);
      if (k < 2) mbar_wait(BAR(BR_U2), 0);
      float acc[16][4];
      zero<64>(&acc[0][0]);
      const int kl = 16 * (lane >> 4) + 2 * (lane & 7) + ((lane >> 3) & 1);
      {
        auto ubase = [&](int sh) { const int q = kl - 2 * sh; return blk + (uint32_t)((q * 16) ^ ((q * 2) & 0x70)); };
#define LDQ(A, sh) _Pragma("unroll") for (int m = 0; m < 4; m++) load_quad(A[m], tb + (16 + 16 * (sh) + 128 * m) * 4);
#define LDB(B, ub, h) _Pragma("unroll") for (int p = 0; p < 4; p++) ldsm4(B[p], ((ub) ^ ((p & 1) * 64)) + (4 * (h) + p) * 512);
#define MLO(A, B) _Pragma("unroll") for (int m = 0; m < 4; m++) _Pragma("unroll") for (int cc = 0; cc < 8; cc++) mma16816(acc[cc + m], A[m], &B[cc >> 1][(cc & 1) * 2]);
#define MHI(A, B) _Pragma("unroll") for (int m = 0; m < 4; m++) _Pragma("unroll") for (int cc = 0; cc < 8 - m; cc++) mma16816(acc[8 + cc + m], A[m], &B[cc >> 1][(cc & 1) * 2]);
        int p_ = pass ? 0 : w4;
        const int pe = pass ? 4 : w4 + 1;
        uint32_t A[4][4], A2[4][4], Bl[4][4], Bh[4][4];
        uint32_t ub = ubase(p_ + 4);
        LDQ(A, p_ + 4) LDB(Bl, ub, 0)
        #pragma unroll 1
        for (; p_ < pe; p_++) {
          LDB(Bh, ub, 1)
          MLO(A, Bl)
          ub = ubase(p_);
          LDQ(A2, p_) LDB(Bl, ub, 0)
          MHI(A, Bh)
          LDB(Bh, ub, 1)
          load_quad(A[0], tb + (16 + 512 + 16 * (p_ & 1)) * 4); load_quad(A[1], tb + (T_S + 16 * (p_ & 1)) * 4);
          MLO(A2, Bl)
          if (p_ < 2) {
            #pragma unroll
            for (int cc = 0; cc < 8; cc++) mma16816(acc[cc + 4], A[0], &Bl[cc >> 1][(cc & 1) * 2]);
            #pragma unroll
            for (int cc = 0; cc < 4; cc++) mma16816(acc[cc + 12], A[0], &Bh[cc >> 1][(cc & 1) * 2]);
            #pragma unroll
            for (int cc = 0; cc < 8; cc++) mma16816(acc[cc + 8], A[1], &Bl[cc >> 1][(cc & 1) * 2]);
          }
          const int pn = ((p_ + 1) & 3) + 4;
          ub = ubase(pn);
          LDQ(A, pn) LDB(Bl, ub, 0)
          MHI(A2, Bh)
        }
      }
      if (t7 == 0) TS(57 + 3 * pass);
      mbar_wait(BAR(BR_DRDY) + 8 * k, 0);
      {
        const int ih = (lane >> 3) & 1;
        const uint32_t dl = blk + B_D + (uint32_t)(((lane >> 4) * 8 + (lane & 7)) * 16);
        const uint32_t d0_ = dl + ih * 1552, d8_ = dl + (ih ? 0 : 1536), d3_ = dl + B_D7 + ih * 1024;
        auto cls2 = [&](uint32_t da, uint32_t ta) {
          uint32_t B[6][2], A[6][4];
          #pragma unroll
          for (int e = 0; e < 6; e++) { B[e][0] = lds32v(ta + (e + 4) * 32); B[e][1] = lds32v(ta + (e + 3) * 32); }
          #pragma unroll
          for (int kk = 0; kk < 6; kk++) ldsm4t(A[kk], da + kk * 256);
          #pragma unroll
          for (int e = 0; e < 6; e++)
            #pragma unroll
            for (int kk = 0; kk < 6; kk++) if (2 * kk + e + 4 < 16) mma16816(acc[2 * kk + e + 4], A[kk], B[e]);
        };
        auto cls3 = [&](uint32_t da, uint32_t ta) {
          uint32_t B[8][2], A[4][4];
          #pragma unroll
          for (int e = 0; e < 8; e++) { B[e][0] = lds32v(ta + (e + 8) * 32); B[e][1] = lds32v(ta + (e + 7) * 32); }
          #pragma unroll
          for (int kk = 0; kk < 4; kk++) ldsm4t(A[kk], da + kk * 256);
          #pragma unroll
          for (int kk = 0; kk < 4; kk++)
            #pragma unroll
            for (int e = 0; e < 8; e++) if (2 * kk + e + 8 < 16) mma16816(acc[2 * kk + e + 8], A[kk], B[e]);
        };
        if (pass) {
          #pragma unroll
          for (int a = 0; a < 4; a++) cls2(((a & 2) ? d8_ : d0_) + (a & 1) * B_D5, tb + (T_F2 + 48 * a - 32) * 4);
          #pragma unroll
          for (int b = 0; b < 2; b++) cls3(d3_ + b * 2048, tb + (T_F3 + 80 * b - 64) * 4);
        } else {
          cls2(((w4 & 2) ? d8_ : d0_) + (w4 & 1) * B_D5, tb + (T_F2 + 48 * w4 - 32) * 4);
          if (w4 >= 2) cls3(d3_ + (w4 - 2) * 2048, tb + (T_F3 + 80 * (w4 - 2) - 64) * 4);
        }
      }
      if (t7 == 0) TS(58 + 3 * pass);
      const uint32_t ya = blk + (uint32_t)((kl * 16) ^ ((kl * 2) & 0x70));
#define STY(p) stsm4t((ya ^ (((p) & 1) * 64)) + (p) * 512, pack2(acc[2 * (p)][0], acc[2 * (p)][1]), pack2(acc[2 * (p)][2], acc[2 * (p)][3]), \
                      pack2(acc[2 * (p) + 1][0], acc[2 * (p) + 1][1]), pack2(acc[2 * (p) + 1][2], acc[2 * (p) + 1][3]))
      if (pass == 0) {
        const uint32_t xw = blk + 4096 + w4 * 4096 + lane * 16, xr = blk + 4096 + (w4 ^ 2) * 4096 + lane * 16, xq = blk + 4096 + (w4 ^ 3) * 4096 + lane * 16;
#define PUT(n, a, c0) _Pragma("unroll") for (int i = 0; i < (n); i++) sts128((a) + i * 512, __float_as_uint(acc[(c0) + i][0]), __float_as_uint(acc[(c0) + i][1]), __float_as_uint(acc[(c0) + i][2]), __float_as_uint(acc[(c0) + i][3]));
#define ADD(n, a, c0) _Pragma("unroll") for (int i = 0; i < (n); i++) { uint32_t o[4]; lds128(o, (a) + i * 512); _Pragma("unroll") for (int e = 0; e < 4; e++) acc[(c0) + i][e] += __uint_as_float(o[e]); }
#define RED(h, q) { PUT(8, xw, 8 - 8 * (h)) bar_sync(4, 128); ADD(8, xr, 8 * (h)) PUT(4, xr, 8 * (h) + 4 - 4 * (q)) bar_sync(4, 128); \
                    ADD(4, xq, 8 * (h) + 4 * (q)) STY(4 * (h) + 2 * (q)); STY(4 * (h) + 2 * (q) + 1); }
        bar_sync(4, 128);
        if (w4 == 0) RED(0, 0) else if (w4 == 1) RED(0, 1) else if (w4 == 2) RED(1, 0) else RED(1, 1)
      } else {
        __syncwarp();
        #pragma unroll
        for (int p = 0; p < 8; p++) STY(p);
      }
      fence_async();
      mbar_arrive(BAR(BR_YSTG) + 8 * k);
      if (t7 == 0) TS(59 + 3 * pass);
    }
    if (t7 == 0) DUMP(40, 64);
    }
  }
}

typedef CUresult (*EncFn)(CUtensorMap*, CUtensorMapDataType, cuuint32_t, void*, const cuuint64_t*, const cuuint64_t*, const cuuint32_t*,
                          const cuuint32_t*, CUtensorMapInterleave, CUtensorMapSwizzle, CUtensorMapL2promotion, CUtensorMapFloatOOBfill);
static CUtensorMap mkmap(EncFn enc, const void* base, int rank, const cuuint64_t* dims, const cuuint64_t* strides, const cuuint32_t* box, CUtensorMapSwizzle swz) {
  CUtensorMap m; cuuint32_t es[5] = {1, 1, 1, 1, 1};
  enc(&m, CU_TENSOR_MAP_DATA_TYPE_BFLOAT16, rank, const_cast<void*>(base), dims, strides, box, es, CU_TENSOR_MAP_INTERLEAVE_NONE, swz,
      CU_TENSOR_MAP_L2_PROMOTION_L2_128B, CU_TENSOR_MAP_FLOAT_OOB_FILL_NONE);
  return m;
}

extern "C" void kernel_launch(void* const* d_in, const int* in_sizes, int n_in, void* d_out, int out_size) {
  void* fn = nullptr; cudaDriverEntryPointQueryResult qr;
  cudaGetDriverEntryPoint("cuTensorMapEncodeTiled", &fn, cudaEnableDefault, &qr);
  EncFn enc = (EncFn)fn;
  void* uy = nullptr; cudaGetSymbolAddress(&uy, g_uy);
  const cuuint64_t dx[2] = {640, 2048}, sx[1] = {1280};
  const cuuint32_t bx[2] = {64, 128}, bu[2] = {80, 64};
  const cuuint64_t dw[3] = {640, 640, 3}, sw[2] = {3840, 1280};
  const cuuint32_t bw[3] = {64, 32, 3}, br[3] = {16, 32, 3};
  const cuuint64_t dwo[2] = {640, 640};
  const cuuint32_t bwo[2] = {64, 80}, bwr[2] = {16, 160}, bo64[2] = {64, 64}, bo16[2] = {16, 64};
  const cuuint64_t dsa[2] = {2048, 1280}, ssa[1] = {4096};
  const cuuint32_t bsa[2] = {64, 80};
  const cuuint64_t dsb[2] = {64, 40960}, ssb[1] = {128};
  const cuuint32_t bsb[2] = {64, 32};
  const cuuint64_t dout[2] = {1280, 2048}, sout[1] = {2560};
  CUtensorMap mx = mkmap(enc, d_in[7], 2, dx, sx, bx, CU_TENSOR_MAP_SWIZZLE_128B);
  CUtensorMap mw = mkmap(enc, d_in[8], 3, dw, sw, bw, CU_TENSOR_MAP_SWIZZLE_128B);
  CUtensorMap mr = mkmap(enc, d_in[8], 3, dw, sw, br, CU_TENSOR_MAP_SWIZZLE_32B);
  CUtensorMap mwo = mkmap(enc, d_in[9], 2, dwo, sx, bwo, CU_TENSOR_MAP_SWIZZLE_128B);
  CUtensorMap mwr = mkmap(enc, d_in[9], 2, dwo, sx, bwr, CU_TENSOR_MAP_SWIZZLE_32B);
  CUtensorMap mo64 = mkmap(enc, d_out, 2, dout, sout, bo64, CU_TENSOR_MAP_SWIZZLE_128B);
  CUtensorMap mo16 = mkmap(enc, d_out, 2, dout, sout, bo16, CU_TENSOR_MAP_SWIZZLE_NONE);
  CUtensorMap mu = mkmap(enc, d_in[0], 2, dx, sx, bu, CU_TENSOR_MAP_SWIZZLE_NONE);
  CUtensorMap msa = mkmap(enc, uy, 2, dsa, ssa, bsa, CU_TENSOR_MAP_SWIZZLE_128B);
  CUtensorMap msb = mkmap(enc, uy, 2, dsb, ssb, bsb, CU_TENSOR_MAP_SWIZZLE_128B);
  CUtensorMap mout = mkmap(enc, d_out, 2, dout, sout, bu, CU_TENSOR_MAP_SWIZZLE_NONE);
  Params prm;
  prm.logA = (const __nv_bfloat16*)d_in[1]; prm.Aim = (const __nv_bfloat16*)d_in[2];
  prm.Cr = (const __nv_bfloat16*)d_in[3]; prm.Ci = (const __nv_bfloat16*)d_in[4];
  prm.logdt = (const __nv_bfloat16*)d_in[5]; prm.dskip = (const __nv_bfloat16*)d_in[6];
  cudaFuncSetAttribute(fused_kernel, cudaFuncAttributeMaxDynamicSharedMemorySize, SMEM_BYTES);
  cudaLaunchConfig_t cfg = {};
  cfg.gridDim = dim3(128); cfg.blockDim = dim3(512); cfg.dynamicSmemBytes = SMEM_BYTES; cfg.stream = cudaStreamPerThread;
  cudaLaunchAttribute at[1];
  at[0].id = cudaLaunchAttributeClusterDimension; at[0].val.clusterDim.x = 2; at[0].val.clusterDim.y = 1; at[0].val.clusterDim.z = 1;
  cfg.attrs = at; cfg.numAttrs = 1;
  cudaLaunchKernelEx(&cfg, fused_kernel, mx, mw, mr, mwo, mwr, mo64, mo16, mu, msa, msb, mout, prm);
}
```

```cpp
#include <cuda_runtime.h>
#include <cuda_bf16.h>
#include <cuda_fp16.h>
#include <cuda.h>
#include <stdint.h>

#define U_PACE 250
#define EN_ATT 1
#define EN_SSM 1

__device__ __align__(1024) __nv_bfloat16 g_uy[2 * 640 * 2048];
__device__ __align__(128) uint4 g_kvp[8 * 16 * 240];
__device__ __align__(128) uint4 g_o[128 * 1280];
__device__ __align__(128) unsigned g_flag[40 * 32];
__device__ unsigned g_epoch[128];
#define TS(i) do {} while (0)
#define DUMP(lo, hi) do {} while (0)

constexpr uint32_t W_SLOT = 15360, OFF_X = 76800;
constexpr uint32_t OFF_WOM = 20480, OFF_KVS = 71680, OFF_PK = 80896, OFF_V = 101376, OFF_EXTRA = 102400, OFF_KVB = OFF_EXTRA;
constexpr uint32_t OFF_BAR = 125952, OFF_BLK = 128000, BLK = 20480;
constexpr uint32_t B_D = 4096, B_D5 = 3088, B_D7 = 6176, B_D9 = 8224, B_TBL = 14400, B_SP = 18432;
constexpr int T_S = 576, T_F2 = 624, T_F3 = 816;
constexpr uint32_t SMEM_BYTES = OFF_BLK + 5 * BLK + 1024;
enum { BR_FULL = 0, BR_EMPTY = 5, BR_WO = 10, BR_PUB = 12, BR_PAR = 13, BR_U2 = 14, BR_OFULL = 18, BR_OEMPTY = 22, BR_GEMM = 26, BR_OSTG = 27, BR_UIN = 28,
       BR_U = 29, BR_DRDY = 30, BR_KGEN = 35, BR_YSTG = 36, BR_FREE = 41, BR_YIN = 46, BR_EPOCH = 47, BR_COUNT = 48 };
constexpr uint32_t OFF_EPOCH = OFF_BAR + 8 * BR_COUNT;

__device__ __forceinline__ long long clk64() { long long t; asm volatile("mov.u64 %0, %%clock64;" : "=l"(t) :: "memory"); return t; }
__device__ __forceinline__ uint32_t smem_u32(const void* p) { return (uint32_t)__cvta_generic_to_shared(p); }
__device__ __forceinline__ uint64_t mkdesc(uint32_t addr, uint32_t lbo, uint32_t sbo, uint32_t swz) {
  return (uint64_t)((addr & 0x3FFFF) >> 4) | ((uint64_t)(lbo >> 4) << 16) | ((uint64_t)(sbo >> 4) << 32) | ((uint64_t)swz << 62);
}
__device__ __forceinline__ void mbar_init(uint32_t bar, uint32_t cnt) { asm volatile("mbarrier.init.shared::cta.b64 [%0], %1;" :: "r"(bar), "r"(cnt) : "memory"); }
__device__ __forceinline__ void mbar_expect_tx(uint32_t bar, uint32_t bytes) { asm volatile("mbarrier.arrive.expect_tx.shared::cta.b64 _, [%0], %1;" :: "r"(bar), "r"(bytes) : "memory"); }
__device__ __forceinline__ void mbar_arrive(uint32_t bar) { asm volatile("mbarrier.arrive.shared::cta.b64 _, [%0];" :: "r"(bar) : "memory"); }
__device__ __forceinline__ void mbar_wait(uint32_t bar, uint32_t parity) {
  asm volatile("{\n.reg .pred p;\n.reg .u32 c;\nmov.u32 c, 0;\n"
    "WL:\nmbarrier.try_wait.parity.shared::cta.b64 p, [%0], %1;\n@p bra WD;\n"
    "add.u32 c, c, 1;\nsetp.lt.u32 p, c, 200000;\n@p bra WL;\nWD:\n}" :: "r"(bar), "r"(parity) : "memory");
}
__device__ __forceinline__ void poll_all(const unsigned* p, unsigned val) {
  asm volatile("{\n.reg .pred p;\n.reg .u32 c, v;\nmov.u32 c, 0;\n"
    "PL:\nld.relaxed.gpu.global.u32 v, [%0];\nsetp.eq.u32 p, v, %1;\nvote.sync.all.pred p, p, 0xffffffff;\n@p bra PD;\n"
    "add.u32 c, c, 1;\nsetp.lt.u32 p, c, 100000;\n@p bra PL;\nPD:\n}" :: "l"(p), "r"(val) : "memory");
}
__device__ __forceinline__ unsigned poll_bit(const unsigned* p, unsigned val, unsigned mask) {
  unsigned bal;
  asm volatile("{\n.reg .pred p;\n.reg .u32 c, v;\nmov.u32 c, 0;\n"
    "PL:\nld.relaxed.gpu.global.u32 v, [%1];\nsetp.eq.u32 p, v, %2;\nvote.sync.ballot.b32 %0, p, 0xffffffff;\n"
    "and.b32 v, %0, %3;\nsetp.ne.u32 p, v, 0;\n@p bra PD;\n"
    "add.u32 c, c, 1;\nsetp.lt.u32 p, c, 100000;\n@p bra PL;\nPD:\n}" : "=&r"(bal) : "l"(p), "r"(val), "r"(mask) : "memory");
  return bal;
}
__device__ __forceinline__ void fix128_w0(uint32_t* v, const void* p, uint32_t tag, uint32_t mask) {
  asm volatile("{\n.reg .pred p;\n.reg .u32 c, x;\n.reg .b128 t;\n.reg .b64 lo, hi;\nmov.u32 c, 0;\n"
    "FL:\nxor.b32 x, %0, %5;\nand.b32 x, x, %6;\nsetp.eq.u32 p, x, 0;\n@p bra FD;\n"
    "ld.relaxed.gpu.global.b128 t, [%4];\nmov.b128 {lo, hi}, t;\nmov.b64 {%0, %1}, lo;\nmov.b64 {%2, %3}, hi;\n"
    "add.u32 c, c, 1;\nsetp.lt.u32 p, c, 100000;\n@p bra FL;\nFD:\n}"
    : "+r"(v[0]), "+r"(v[1]), "+r"(v[2]), "+r"(v[3]) : "l"(p), "r"(tag), "r"(mask) : "memory");
}
__device__ __forceinline__ void fix128_w3(uint32_t* v, const void* p, uint32_t tag, uint32_t mask) {
  asm volatile("{\n.reg .pred p;\n.reg .u32 c, x;\n.reg .b128 t;\n.reg .b64 lo, hi;\nmov.u32 c, 0;\n"
    "FL:\nxor.b32 x, %3, %5;\nand.b32 x, x, %6;\nsetp.eq.u32 p, x, 0;\n@p bra FD;\n"
    "ld.relaxed.gpu.global.b128 t, [%4];\nmov.b128 {lo, hi}, t;\nmov.b64 {%0, %1}, lo;\nmov.b64 {%2, %3}, hi;\n"
    "add.u32 c, c, 1;\nsetp.lt.u32 p, c, 100000;\n@p bra FL;\nFD:\n}"
    : "+r"(v[0]), "+r"(v[1]), "+r"(v[2]), "+r"(v[3]) : "l"(p), "r"(tag), "r"(mask) : "memory");
}
__device__ __forceinline__ void fence_acq() { asm volatile("fence.acq_rel.gpu;" ::: "memory"); }
__device__ __forceinline__ bool elect_one() {
  uint32_t p; asm volatile("{\n.reg .pred P;\nelect.sync _|P, 0xffffffff;\nselp.u32 %0, 1, 0, P;\n}" : "=r"(p)); return p;
}
__device__ __forceinline__ void bar_sync(int id, int n) { asm volatile("bar.sync %0, %1;" :: "r"(id), "r"(n) : "memory"); }
__device__ __forceinline__ void fence_async() { asm volatile("fence.proxy.async.shared::cta;" ::: "memory"); }
__device__ __forceinline__ void fence_async_g() { asm volatile("fence.proxy.async.global;" ::: "memory"); }
__device__ __forceinline__ void tma2d(uint32_t dst, const CUtensorMap* m, uint32_t bar, int c0, int c1) {
  asm volatile("cp.async.bulk.tensor.2d.shared::cluster.global.mbarrier::complete_tx::bytes [%0], [%1, {%3, %4}], [%2];"
    :: "r"(dst), "l"(m), "r"(bar), "r"(c0), "r"(c1) : "memory");
}
__device__ __forceinline__ void tma3d(uint32_t dst, const CUtensorMap* m, uint32_t bar, int c0, int c1, int c2) {
  asm volatile("cp.async.bulk.tensor.3d.shared::cluster.global.mbarrier::complete_tx::bytes [%0], [%1, {%3, %4, %5}], [%2];"
    :: "r"(dst), "l"(m), "r"(bar), "r"(c0), "r"(c1), "r"(c2) : "memory");
}
__device__ __forceinline__ void tma4d(uint32_t dst, const CUtensorMap* m, uint32_t bar, int c0, int c1, int c2, int c3) {
  asm volatile("cp.async.bulk.tensor.4d.shared::cluster.global.mbarrier::complete_tx::bytes [%0], [%1, {%3, %4, %5, %6}], [%2];"
    :: "r"(dst), "l"(m), "r"(bar), "r"(c0), "r"(c1), "r"(c2), "r"(c3) : "memory");
}
__device__ __forceinline__ void tma2d_st(const CUtensorMap* m, uint32_t src, int c0, int c1) {
  asm volatile("cp.async.bulk.tensor.2d.global.shared::cta.bulk_group [%0, {%2, %3}], [%1];"
    :: "l"(m), "r"(src), "r"(c0), "r"(c1) : "memory");
}
__device__ __forceinline__ void bulk_ld(uint32_t dst, const void* src, uint32_t bytes, uint32_t bar) {
  asm volatile("cp.async.bulk.shared::cluster.global.mbarrier::complete_tx::bytes [%0], [%1], %2, [%3];"
    :: "r"(dst), "l"(src), "r"(bytes), "r"(bar) : "memory");
}
__device__ __forceinline__ void bulk_st(void* dst, uint32_t src, uint32_t bytes) {
  asm volatile("cp.async.bulk.global.shared::cta.bulk_group [%0], [%1], %2;" :: "l"(dst), "r"(src), "r"(bytes) : "memory");
}
__device__ __forceinline__ void bulk_commit() { asm volatile("cp.async.bulk.commit_group;" ::: "memory"); }
__device__ __forceinline__ void bulk_wait0() { asm volatile("cp.async.bulk.wait_group 0;" ::: "memory"); }
__device__ __forceinline__ void bulk_wait0_read() { asm volatile("cp.async.bulk.wait_group.read 0;" ::: "memory"); }
__device__ __forceinline__ unsigned ld_rlx(const unsigned* p) { unsigned v; asm volatile("ld.relaxed.gpu.global.u32 %0, [%1];" : "=r"(v) : "l"(p) : "memory"); return v; }
__device__ __forceinline__ unsigned ld_acq(const unsigned* p) { unsigned v; asm volatile("ld.acquire.gpu.global.u32 %0, [%1];" : "=r"(v) : "l"(p) : "memory"); return v; }
__device__ __forceinline__ void st_rlx(unsigned* p, unsigned v) { asm volatile("st.relaxed.gpu.global.u32 [%0], %1;" :: "l"(p), "r"(v) : "memory"); }
__device__ __forceinline__ void st_rel(unsigned* p, unsigned v) { asm volatile("st.release.gpu.global.u32 [%0], %1;" :: "l"(p), "r"(v) : "memory"); }
__device__ __forceinline__ void ld128_rlx(uint32_t* v, const void* p) {
  asm volatile("{\n.reg .b128 t;\n.reg .b64 lo, hi;\nld.relaxed.gpu.global.b128 t, [%4];\nmov.b128 {lo, hi}, t;\n"
    "mov.b64 {%0, %1}, lo;\nmov.b64 {%2, %3}, hi;\n}" : "=r"(v[0]), "=r"(v[1]), "=r"(v[2]), "=r"(v[3]) : "l"(p) : "memory");
}
__device__ __forceinline__ void st128_rlx(void* p, const uint32_t* v) {
  asm volatile("{\n.reg .b128 t;\n.reg .b64 lo, hi;\nmov.b64 lo, {%1, %2};\nmov.b64 hi, {%3, %4};\nmov.b128 t, {lo, hi};\n"
    "st.relaxed.gpu.global.b128 [%0], t;\n}" :: "l"(p), "r"(v[0]), "r"(v[1]), "r"(v[2]), "r"(v[3]) : "memory");
}
__device__ __forceinline__ uint32_t lds32(uint32_t a) { uint32_t v; asm volatile("ld.shared.u32 %0, [%1];" : "=r"(v) : "r"(a) : "memory"); return v; }
__device__ __forceinline__ uint32_t lds32v(uint32_t a) { uint32_t v; asm volatile("ld.volatile.shared.u32 %0, [%1];" : "=r"(v) : "r"(a) : "memory"); return v; }
__device__ __forceinline__ uint32_t cpa(uint32_t a, uint32_t one) { uint32_t v; asm volatile("mul.lo.u32 %0, %1, %2;" : "=r"(v) : "r"(a), "r"(one)); return v; }
__device__ __forceinline__ uint32_t cpb(uint32_t a, uint32_t zero) { uint32_t v; asm volatile("or.b32 %0, %1, %2;" : "=r"(v) : "r"(a), "r"(zero)); return v; }
__device__ __forceinline__ uint32_t lds16(uint32_t a) { uint16_t v; asm volatile("ld.shared.u16 %0, [%1];" : "=h"(v) : "r"(a) : "memory"); return v; }
__device__ __forceinline__ float ldsf(uint32_t a) { float v; asm volatile("ld.shared.f32 %0, [%1];" : "=f"(v) : "r"(a) : "memory"); return v; }
__device__ __forceinline__ void lds128(uint32_t* v, uint32_t a) { asm volatile("ld.shared.v4.u32 {%0,%1,%2,%3}, [%4];" : "=r"(v[0]), "=r"(v[1]), "=r"(v[2]), "=r"(v[3]) : "r"(a) : "memory"); }
__device__ __forceinline__ void sts32(uint32_t a, uint32_t v) { asm volatile("st.shared.u32 [%0], %1;" :: "r"(a), "r"(v) : "memory"); }
__device__ __forceinline__ void sts16(uint32_t a, uint32_t v) { asm volatile("st.shared.u16 [%0], %1;" :: "r"(a), "h"((uint16_t)v) : "memory"); }
__device__ __forceinline__ void sts64f(uint32_t a, float x, float y) { asm volatile("st.shared.v2.f32 [%0], {%1,%2};" :: "r"(a), "f"(x), "f"(y) : "memory"); }
__device__ __forceinline__ void sts128(uint32_t a, uint32_t x, uint32_t y, uint32_t z, uint32_t w) { asm volatile("st.shared.v4.u32 [%0], {%1,%2,%3,%4};" :: "r"(a), "r"(x), "r"(y), "r"(z), "r"(w) : "memory"); }
__device__ __forceinline__ void stsm4(uint32_t a, uint32_t r0, uint32_t r1, uint32_t r2, uint32_t r3) {
  asm volatile("stmatrix.sync.aligned.m8n8.x4.shared.b16 [%0], {%1,%2,%3,%4};" :: "r"(a), "r"(r0), "r"(r1), "r"(r2), "r"(r3) : "memory");
}
__device__ __forceinline__ void stsm4t(uint32_t a, uint32_t r0, uint32_t r1, uint32_t r2, uint32_t r3) {
  asm volatile("stmatrix.sync.aligned.m8n8.x4.trans.shared.b16 [%0], {%1,%2,%3,%4};" :: "r"(a), "r"(r0), "r"(r1), "r"(r2), "r"(r3) : "memory");
}
__device__ __forceinline__ void ldsm4t(uint32_t* r, uint32_t a) {
  asm volatile("ldmatrix.sync.aligned.m8n8.x4.trans.shared.b16 {%0,%1,%2,%3}, [%4];" : "=r"(r[0]), "=r"(r[1]), "=r"(r[2]), "=r"(r[3]) : "r"(a) : "memory");
}
__device__ __forceinline__ void ldsm4(uint32_t* r, uint32_t a) {
  asm volatile("ldmatrix.sync.aligned.m8n8.x4.shared.b16 {%0,%1,%2,%3}, [%4];" : "=r"(r[0]), "=r"(r[1]), "=r"(r[2]), "=r"(r[3]) : "r"(a) : "memory");
}
__device__ __forceinline__ void mma16816(float* d, const uint32_t* a, const uint32_t* b) {
  asm volatile("mma.sync.aligned.m16n8k16.row.col.f32.bf16.bf16.f32 {%0,%1,%2,%3}, {%4,%5,%6,%7}, {%8,%9}, {%0,%1,%2,%3};"
    : "+f"(d[0]), "+f"(d[1]), "+f"(d[2]), "+f"(d[3]) : "r"(a[0]), "r"(a[1]), "r"(a[2]), "r"(a[3]), "r"(b[0]), "r"(b[1]));
}
__device__ __forceinline__ uint32_t pack2(float lo, float hi) { uint32_t r; asm("cvt.rn.bf16x2.f32 %0, %1, %2;" : "=r"(r) : "f"(hi), "f"(lo)); return r; }
__device__ __forceinline__ uint32_t packh(float lo, float hi) { uint32_t r; asm("cvt.rn.f16x2.f32 %0, %1, %2;" : "=r"(r) : "f"(hi), "f"(lo)); return r; }
__device__ __forceinline__ uint32_t hcmul(uint32_t x, uint32_t zp, uint32_t zq) {
  const __half2 xx = *reinterpret_cast<__half2*>(&x);
  const __half2 r = __hfma2(__high2half2(xx), *reinterpret_cast<__half2*>(&zq), __hmul2(__low2half2(xx), *reinterpret_cast<__half2*>(&zp)));
  return *reinterpret_cast<const uint32_t*>(&r);
}
__device__ __forceinline__ void hcm2(uint32_t xr, uint32_t xi, uint32_t z, uint32_t& pr, uint32_t& pi) {
  const __half2 a = *reinterpret_cast<__half2*>(&xr), b = *reinterpret_cast<__half2*>(&xi), zz = *reinterpret_cast<__half2*>(&z);
  const __half2 re = __hfma2(__hneg2(b), __high2half2(zz), __hmul2(a, __low2half2(zz)));
  const __half2 im = __hfma2(a, __high2half2(zz), __hmul2(b, __low2half2(zz)));
  pr = *reinterpret_cast<const uint32_t*>(&re); pi = *reinterpret_cast<const uint32_t*>(&im);
}
__device__ __forceinline__ void sts64(uint32_t a, uint32_t x, uint32_t y) { asm volatile("st.shared.v2.u32 [%0], {%1,%2};" :: "r"(a), "r"(x), "r"(y) : "memory"); }
__device__ __forceinline__ void lds64(uint32_t* v, uint32_t a) { asm volatile("ld.shared.v2.u32 {%0,%1}, [%2];" : "=r"(v[0]), "=r"(v[1]) : "r"(a) : "memory"); }
__device__ __forceinline__ float bf_lo(uint32_t v) { return __uint_as_float(v << 16); }
__device__ __forceinline__ float bf_hi(uint32_t v) { return __uint_as_float(v & 0xffff0000u); }
__device__ __forceinline__ float bf_round(float x) { return bf_lo(pack2(x, 0.f)); }
__device__ __forceinline__ float ex2(float x) { float r; asm("ex2.approx.ftz.f32 %0, %1;" : "=f"(r) : "f"(x)); return r; }
__device__ __forceinline__ float phi(float t, float l2e = 1.44269504089f) { float e = ex2(t * l2e); return (t > 0.f ? t + 1.f : e) + 1e-6f; }
__device__ __forceinline__ void wg_fence() { asm volatile("wgmma.fence.sync.aligned;" ::: "memory"); }
__device__ __forceinline__ void wg_commit() { asm volatile("wgmma.commit_group.sync.aligned;" ::: "memory"); }
template <int N> __device__ __forceinline__ void wg_wait() { asm volatile("wgmma.wait_group.sync.aligned %0;" :: "n"(N) : "memory"); }
template <int N> __device__ __forceinline__ void pin(float* a) {
  #pragma unroll
  for (int i = 0; i < N; i++) asm volatile("" : "+f"(a[i]) :: "memory");
}
__device__ __forceinline__ int opaque(int v) { asm volatile("" : "+r"(v)); return v; }
template <int N> __device__ __forceinline__ void zero(float* a) {
  #pragma unroll
  for (int i = 0; i < N; i++) asm volatile("mov.b32 %0, 0;" : "=f"(a[i]));
}
template <int N> __device__ __forceinline__ void pinu(uint32_t* a) {
  #pragma unroll
  for (int i = 0; i < N; i++) asm volatile("" : "+r"(a[i]) :: "memory");
}
__device__ __forceinline__ void cexp_t(float lg2mag, float turns, float& re, float& im) {
  float m = ex2(lg2mag);
  float fr = (turns - __fadd_rn(__fadd_rn(turns, 12582912.f), -12582912.f)) * 6.283185307f;
  re = m * __cosf(fr); im = m * __sinf(fr);
}
__device__ __forceinline__ void cmul(float ar, float ai, float br, float bi, float& cr, float& ci) {
  cr = fmaf(ar, br, -ai * bi); ci = fmaf(ar, bi, ai * br);
}

__device__ __forceinline__ void wg_ss192_tb(float* d, uint64_t da, uint64_t db, int scale_d) {
  asm volatile("{\n.reg .pred p;\nsetp.ne.b32 p, %98, 0;\n"
    "wgmma.mma_async.sync.aligned.m64n192k16.f32.bf16.bf16 "
    "{%0, %1, %2, %3, %4, %5, %6, %7, %8, %9, %10, %11, %12, %13, %14, %15, %16, %17, %18, %19, %20, %21, %22, %23, %24, %25, %26, %27, %28, %29, %30, %31, %32, %33, %34, %35, %36, %37, %38, %39, %40, %41, %42, %43, %44, %45, %46, %47, %48, %49, %50, %51, %52, %53, %54, %55, %56, %57, %58, %59, %60, %61, %62, %63, %64, %65, %66, %67, %68, %69, %70, %71, %72, %73, %74, %75, %76, %77, %78, %79, %80, %81, %82, %83, %84, %85, %86, %87, %88, %89, %90, %91, %92, %93, %94, %95}, %96, %97, p, 1, 1, 0, 1;\n}\n"
    : "+f"(d[0]), "+f"(d[1]), "+f"(d[2]), "+f"(d[3]), "+f"(d[4]), "+f"(d[5]), "+f"(d[6]), "+f"(d[7]), "+f"(d[8]), "+f"(d[9]), "+f"(d[10]), "+f"(d[11]), "+f"(d[12]), "+f"(d[13]), "+f"(d[14]), "+f"(d[15]), "+f"(d[16]), "+f"(d[17]), "+f"(d[18]), "+f"(d[19]), "+f"(d[20]), "+f"(d[21]), "+f"(d[22]), "+f"(d[23]), "+f"(d[24]), "+f"(d[25]), "+f"(d[26]), "+f"(d[27]), "+f"(d[28]), "+f"(d[29]), "+f"(d[30]), "+f"(d[31]), "+f"(d[32]), "+f"(d[33]), "+f"(d[34]), "+f"(d[35]), "+f"(d[36]), "+f"(d[37]), "+f"(d[38]), "+f"(d[39]), "+f"(d[40]), "+f"(d[41]), "+f"(d[42]), "+f"(d[43]), "+f"(d[44]), "+f"(d[45]), "+f"(d[46]), "+f"(d[47]), "+f"(d[48]), "+f"(d[49]), "+f"(d[50]), "+f"(d[51]), "+f"(d[52]), "+f"(d[53]), "+f"(d[54]), "+f"(d[55]), "+f"(d[56]), "+f"(d[57]), "+f"(d[58]), "+f"(d[59]), "+f"(d[60]), "+f"(d[61]), "+f"(d[62]), "+f"(d[63]), "+f"(d[64]), "+f"(d[65]), "+f"(d[66]), "+f"(d[67]), "+f"(d[68]), "+f"(d[69]), "+f"(d[70]), "+f"(d[71]), "+f"(d[72]), "+f"(d[73]), "+f"(d[74]), "+f"(d[75]), "+f"(d[76]), "+f"(d[77]), "+f"(d[78]), "+f"(d[79]), "+f"(d[80]), "+f"(d[81]), "+f"(d[82]), "+f"(d[83]), "+f"(d[84]), "+f"(d[85]), "+f"(d[86]), "+f"(d[87]), "+f"(d[88]), "+f"(d[89]), "+f"(d[90]), "+f"(d[91]), "+f"(d[92]), "+f"(d[93]), "+f"(d[94]), "+f"(d[95])
    : "l"(da), "l"(db), "r"(scale_d));
}
__device__ __forceinline__ void wg_ss48_tb(float* d, uint64_t da, uint64_t db, int scale_d) {
  asm volatile("{\n.reg .pred p;\nsetp.ne.b32 p, %26, 0;\n"
    "wgmma.mma_async.sync.aligned.m64n48k16.f32.bf16.bf16 "
    "{%0, %1, %2, %3, %4, %5, %6, %7, %8, %9, %10, %11, %12, %13, %14, %15, %16, %17, %18, %19, %20, %21, %22, %23}, %24, %25, p, 1, 1, 0, 1;\n}\n"
    : "+f"(d[0]), "+f"(d[1]), "+f"(d[2]), "+f"(d[3]), "+f"(d[4]), "+f"(d[5]), "+f"(d[6]), "+f"(d[7]), "+f"(d[8]), "+f"(d[9]), "+f"(d[10]), "+f"(d[11]), "+f"(d[12]), "+f"(d[13]), "+f"(d[14]), "+f"(d[15]), "+f"(d[16]), "+f"(d[17]), "+f"(d[18]), "+f"(d[19]), "+f"(d[20]), "+f"(d[21]), "+f"(d[22]), "+f"(d[23])
    : "l"(da), "l"(db), "r"(scale_d));
}
__device__ __forceinline__ void wg_ss48_tt(float* d, uint64_t da, uint64_t db, int scale_d) {
  asm volatile("{\n.reg .pred p;\nsetp.ne.b32 p, %26, 0;\n"
    "wgmma.mma_async.sync.aligned.m64n48k16.f32.bf16.bf16 "
    "{%0, %1, %2, %3, %4, %5, %6, %7, %8, %9, %10, %11, %12, %13, %14, %15, %16, %17, %18, %19, %20, %21, %22, %23}, %24, %25, p, 1, 1, 1, 1;\n}\n"
    : "+f"(d[0]), "+f"(d[1]), "+f"(d[2]), "+f"(d[3]), "+f"(d[4]), "+f"(d[5]), "+f"(d[6]), "+f"(d[7]), "+f"(d[8]), "+f"(d[9]), "+f"(d[10]), "+f"(d[11]), "+f"(d[12]), "+f"(d[13]), "+f"(d[14]), "+f"(d[15]), "+f"(d[16]), "+f"(d[17]), "+f"(d[18]), "+f"(d[19]), "+f"(d[20]), "+f"(d[21]), "+f"(d[22]), "+f"(d[23])
    : "l"(da), "l"(db), "r"(scale_d));
}
__device__ __forceinline__ void wg_rs88_tb(float* d, const uint32_t* a, uint64_t db, int scale_d) {
  asm volatile("{\n.reg .pred p;\nsetp.ne.b32 p, %49, 0;\n"
    "wgmma.mma_async.sync.aligned.m64n88k16.f32.bf16.bf16 "
    "{%0, %1, %2, %3, %4, %5, %6, %7, %8, %9, %10, %11, %12, %13, %14, %15, %16, %17, %18, %19, %20, %21, %22, %23, %24, %25, %26, %27, %28, %29, %30, %31, %32, %33, %34, %35, %36, %37, %38, %39, %40, %41, %42, %43}, {%44, %45, %46, %47}, %48, p, 1, 1, 1;\n}\n"
    : "+f"(d[0]), "+f"(d[1]), "+f"(d[2]), "+f"(d[3]), "+f"(d[4]), "+f"(d[5]), "+f"(d[6]), "+f"(d[7]), "+f"(d[8]), "+f"(d[9]), "+f"(d[10]), "+f"(d[11]), "+f"(d[12]), "+f"(d[13]), "+f"(d[14]), "+f"(d[15]), "+f"(d[16]), "+f"(d[17]), "+f"(d[18]), "+f"(d[19]), "+f"(d[20]), "+f"(d[21]), "+f"(d[22]), "+f"(d[23]), "+f"(d[24]), "+f"(d[25]), "+f"(d[26]), "+f"(d[27]), "+f"(d[28]), "+f"(d[29]), "+f"(d[30]), "+f"(d[31]), "+f"(d[32]), "+f"(d[33]), "+f"(d[34]), "+f"(d[35]), "+f"(d[36]), "+f"(d[37]), "+f"(d[38]), "+f"(d[39]), "+f"(d[40]), "+f"(d[41]), "+f"(d[42]), "+f"(d[43])
    : "r"(a[0]), "r"(a[1]), "r"(a[2]), "r"(a[3]), "l"(db), "r"(scale_d));
}
__device__ __forceinline__ void wg_rs64_tb(float* d, const uint32_t* a, uint64_t db, int scale_d) {
  asm volatile("{\n.reg .pred p;\nsetp.ne.b32 p, %37, 0;\n"
    "wgmma.mma_async.sync.aligned.m64n64k16.f32.bf16.bf16 "
    "{%0, %1, %2, %3, %4, %5, %6, %7, %8, %9, %10, %11, %12, %13, %14, %15, %16, %17, %18, %19, %20, %21, %22, %23, %24, %25, %26, %27, %28, %29, %30, %31}, {%32, %33, %34, %35}, %36, p, 1, 1, 1;\n}\n"
    : "+f"(d[0]), "+f"(d[1]), "+f"(d[2]), "+f"(d[3]), "+f"(d[4]), "+f"(d[5]), "+f"(d[6]), "+f"(d[7]), "+f"(d[8]), "+f"(d[9]), "+f"(d[10]), "+f"(d[11]), "+f"(d[12]), "+f"(d[13]), "+f"(d[14]), "+f"(d[15]), "+f"(d[16]), "+f"(d[17]), "+f"(d[18]), "+f"(d[19]), "+f"(d[20]), "+f"(d[21]), "+f"(d[22]), "+f"(d[23]), "+f"(d[24]), "+f"(d[25]), "+f"(d[26]), "+f"(d[27]), "+f"(d[28]), "+f"(d[29]), "+f"(d[30]), "+f"(d[31])
    : "r"(a[0]), "r"(a[1]), "r"(a[2]), "r"(a[3]), "l"(db), "r"(scale_d));
}
__device__ __forceinline__ void wg_ss48_tt_h(float* d, uint64_t da, uint64_t db, int scale_d) {
  asm volatile("{\n.reg .pred p;\nsetp.ne.b32 p, %26, 0;\n"
    "wgmma.mma_async.sync.aligned.m64n48k16.f32.f16.f16 "
    "{%0, %1, %2, %3, %4, %5, %6, %7, %8, %9, %10, %11, %12, %13, %14, %15, %16, %17, %18, %19, %20, %21, %22, %23}, %24, %25, p, 1, 1, 1, 1;\n}\n"
    : "+f"(d[0]), "+f"(d[1]), "+f"(d[2]), "+f"(d[3]), "+f"(d[4]), "+f"(d[5]), "+f"(d[6]), "+f"(d[7]), "+f"(d[8]), "+f"(d[9]), "+f"(d[10]), "+f"(d[11]), "+f"(d[12]), "+f"(d[13]), "+f"(d[14]), "+f"(d[15]), "+f"(d[16]), "+f"(d[17]), "+f"(d[18]), "+f"(d[19]), "+f"(d[20]), "+f"(d[21]), "+f"(d[22]), "+f"(d[23])
    : "l"(da), "l"(db), "r"(scale_d));
}
__device__ __forceinline__ void wg_rs16_tb(float* d, const uint32_t* a, uint64_t db, int scale_d) {
  asm volatile("{\n.reg .pred p;\nsetp.ne.b32 p, %13, 0;\n"
    "wgmma.mma_async.sync.aligned.m64n16k16.f32.bf16.bf16 "
    "{%0, %1, %2, %3, %4, %5, %6, %7}, {%8, %9, %10, %11}, %12, p, 1, 1, 1;\n}\n"
    : "+f"(d[0]), "+f"(d[1]), "+f"(d[2]), "+f"(d[3]), "+f"(d[4]), "+f"(d[5]), "+f"(d[6]), "+f"(d[7])
    : "r"(a[0]), "r"(a[1]), "r"(a[2]), "r"(a[3]), "l"(db), "r"(scale_d));
}

struct Params {
  const __nv_bfloat16 *u, *logA, *Aim, *Cr, *Ci, *logdt, *dskip;
};

template <bool FWD>
__device__ __forceinline__ void tile_transpose(uint32_t tc0, uint32_t tc1, uint32_t ct0, uint32_t ct1, int hw, int lane) {
  const int mi = lane >> 3, row = lane & 7;
  for (int gi = hw; gi < 40; gi += 3) {
    const int hh = gi / 20, rem = gi - hh * 20, q = rem / 10, cb = rem - q * 10;
    const uint32_t a_tc = (hh ? tc1 : tc0) + (8 * (4 * q + mi) + row) * 160 + cb * 16;
    const uint32_t a_ct = (hh ? ct1 : ct0) + (8 * cb + row) * 128 + (((4 * q + mi) ^ row) << 4);
    uint32_t r[4];
    ldsm4t(r, FWD ? a_tc : a_ct);
    stsm4(FWD ? a_ct : a_tc, r[0], r[1], r[2], r[3]);
  }
}

__device__ __forceinline__ void load_quad(uint32_t* A, uint32_t addr) {
  A[0] = lds32v(addr); A[1] = lds32v(addr + 32); A[2] = lds32v(addr - 32); A[3] = lds32v(addr);
}

__global__ void __launch_bounds__(512, 1)
fused_kernel(const __grid_constant__ CUtensorMap mx, const __grid_constant__ CUtensorMap mw, const __grid_constant__ CUtensorMap mr,
             const __grid_constant__ CUtensorMap mwo, const __grid_constant__ CUtensorMap mwr, const __grid_constant__ CUtensorMap mo64,
             const __grid_constant__ CUtensorMap mo16, const __grid_constant__ CUtensorMap mw64, const __grid_constant__ CUtensorMap msa,
             const __grid_constant__ CUtensorMap msb, const __grid_constant__ CUtensorMap mout, const Params prm) {
  extern __shared__ unsigned char smem_raw[];
  const uint32_t sb = (smem_u32(smem_raw) + 1023) & ~1023u;
  const int tid = threadIdx.x, lane = tid & 31;
  const int wg = __shfl_sync(0xffffffff, tid >> 7, 0), warp = __shfl_sync(0xffffffff, tid >> 5, 0);
  const int cta = blockIdx.x, r = cta >> 3, c = cta & 7;
  const uint32_t bars = sb + OFF_BAR;
#define BAR(i) (bars + 8 * (i))

  const bool sw64 = ((c + 1) & 2) != 0;
  const CUtensorMap* mwp = sw64 ? &mw64 : &mw;
  const int mcol = (c * 80 + (c & 1) * 16) >> (sw64 ? 5 : 6), rcol = c * 80 + ((c & 1) ? 0 : 64);
  auto issue1 = [&](int kb) {
    const uint32_t st = sb + (kb % 5) * W_SLOT, fb = BAR(BR_FULL + kb % 5);
    mbar_expect_tx(fb, (kb & 1) ? W_SLOT : W_SLOT + 16384);
    if (!(kb & 1)) tma2d(sb + OFF_X + ((kb >> 1) % 3) * 16384, &mx, fb, kb * 32, r * 128);
    tma4d(st, mwp, fb, 0, kb * 32, mcol, 0);
    tma3d(st + 12288, &mr, fb, rcol, kb * 32, 0);
  };

  if (warp == 12) {
    if (elect_one()) {
      #pragma unroll
      for (int i = 0; i < BR_COUNT; i++) {
        int cnt = 1;
        if (i >= BR_EMPTY && i < BR_EMPTY + 5) cnt = 2;
        if (i >= BR_OEMPTY && i < BR_OEMPTY + 4) cnt = 8;
        if (i == BR_OSTG) cnt = 256;
        if (i >= BR_DRDY && i < BR_DRDY + 5) cnt = 96;
        if (i >= BR_YSTG && i < BR_YSTG + 5) cnt = i == BR_YSTG + 4 ? 128 : 32;
        mbar_init(BAR(i), cnt);
      }
      asm volatile("fence.mbarrier_init.release.cluster;" ::: "memory");
      if (EN_ATT) issue1(0);
    }
  }
  if (warp == 13 && lane < 8) {
    const CUtensorMap* mp = lane <= 1 ? &msb : lane == 2 ? &mwo : lane == 3 ? &mwr : lane == 4 ? &msa : lane == 5 ? &mout : lane == 6 ? &mo64 : &mo16;
    asm volatile("prefetch.tensormap [%0];" :: "l"(mp) : "memory");
  }
  unsigned short ldt = 0, dsk0 = 0;
  uint4 pv[3];
  if (EN_SSM && wg == 2) {
    const int ai = warp & 3;
    const uint4* pp = reinterpret_cast<const uint4*>((ai == 0 ? prm.logA : ai == 1 ? prm.Aim : ai == 2 ? prm.Cr : prm.Ci) + (c * 80 + r * 5) * 128);
    pv[0] = __ldg(pp + lane); pv[1] = __ldg(pp + 32 + lane); pv[2] = __ldg(pp + 64 + (lane & 15));
    const int kq = c * 80 + r * 5 + min(tid - 256, 4);
    ldt = __ldg(reinterpret_cast<const unsigned short*>(prm.logdt) + kq); dsk0 = __ldg(reinterpret_cast<const unsigned short*>(prm.dskip) + kq);
  }
  __syncthreads();

  if (wg == 3) {
    asm volatile("setmaxnreg.dec.sync.aligned.u32 56;");
    if (warp == 12) {
      if (EN_ATT) {
      #pragma unroll
      for (int kb = 1; kb < 20; kb++) {
        if (kb >= 5) mbar_wait(BAR(BR_EMPTY + kb % 5), ((kb / 5) & 1) ^ 1);
        if (elect_one()) issue1(kb);
      }
      auto chunk_of = [&](int i) { return i == 0 ? c : (i == 7 ? (c ^ 1) : (((c & 6) + 1 + i) & 7)); };
      mbar_wait(BAR(BR_EPOCH), 0);
      const unsigned epoch = lds32(sb + OFF_EPOCH);
      const unsigned* fo = &g_flag[(24 + r) * 32 + (lane & 7)];
      unsigned seen = __ballot_sync(0xffffffff, ld_rlx(fo) == epoch);
      mbar_wait(BAR(BR_GEMM), 0);
      if (elect_one()) {
        mbar_expect_tx(BAR(BR_WO), 20480 + 5 * 10240);
        #pragma unroll
        for (int i = 0; i < 5; i++) tma2d(sb + OFF_WOM + i * 10240, &mwo, BAR(BR_WO), c * 64, i * 80);
        #pragma unroll
        for (int i = 0; i < 4; i++) tma2d(sb + i * 5120, &mwr, BAR(BR_WO), 512 + c * 16, i * 160);
      }
      mbar_wait(BAR(BR_PUB), 0);
      if (elect_one()) {
        mbar_expect_tx(BAR(BR_WO + 1), 3 * 10240);
        #pragma unroll
        for (int i = 5; i < 8; i++) tma2d(sb + OFF_WOM + i * 10240, &mwo, BAR(BR_WO + 1), c * 64, i * 80);
      }
      mbar_wait(BAR(BR_OSTG), 0);
      if (elect_one()) {
        bulk_st(&g_o[cta * 1280], sb + OFF_EXTRA, 20480);
        bulk_commit();
        bulk_wait0();
        st_rlx(&g_flag[(24 + r) * 32 + c], epoch);
        TS(20);
      }
      __syncwarp();
      #pragma unroll
      for (int i = 0; i < 7; i++) {
        const int src = chunk_of(i + 1);
        if (!((seen >> src) & 1)) seen = poll_bit(fo, epoch, 1u << src);
        if (i < 3) { if (EN_SSM) mbar_wait(BAR(BR_FREE + 4 - i), 0); }
        else if (i > 3) mbar_wait(BAR(BR_OEMPTY + i - 4), 0);
        if (elect_one()) {
          fence_async_g();
          const uint32_t slot = (i & 3) == 3 ? sb + OFF_EXTRA : sb + OFF_BLK + (4 - (i & 3)) * BLK;
          mbar_expect_tx(BAR(BR_OFULL + (i & 3)), 20480);
          bulk_ld(slot, &g_o[(r * 8 + src) * 1280], 20480, BAR(BR_OFULL + (i & 3)));
          if (i == 0) TS(21);
          if (i == 6) { TS(22); DUMP(20, 30); }
        }
        __syncwarp();
      }
      }
    } else {
      const int hw = warp - 13, ht = tid - 416;
      unsigned epoch = 0;
      if (EN_SSM && ht < 80) {
        const int rr = ht / 10, cq = ht - rr * 10;
        const char* gs = reinterpret_cast<const char*>(prm.u) + (size_t)(r * 128 + rr) * 1280 + c * 160 + cq * 16;
        const uint32_t ds = sb + OFF_BLK + 4 * BLK + B_D + ht * 16;
        #pragma unroll
        for (int i = 0; i < 16; i++)
          asm volatile("cp.async.cg.shared.global [%0], [%1], 16;" :: "r"(ds - (i >> 3) * BLK + (i & 7) * 1280), "l"(gs + i * 10240) : "memory");
      }
      if (hw == 0) {
        if (lane == 0) {
          epoch = ld_rlx(&g_epoch[cta]) + 1;
          st_rlx(&g_epoch[cta], epoch);
          sts32(sb + OFF_EPOCH, epoch);
          mbar_arrive(BAR(BR_EPOCH));
        }
        epoch = __shfl_sync(0xffffffff, epoch, 0);
      }
      if (EN_SSM) {
      asm volatile("cp.async.wait_all;" ::: "memory");
      bar_sync(5, 96);
      if (ht == 0) TS(36);
      {
        const int mi = lane >> 3, rw = lane & 7;
        const uint32_t lo = (uint32_t)((8 * (rw >> 1) + 2 * mi + (rw & 1)) * 160);
        uint4* gp = reinterpret_cast<uint4*>(g_uy + (size_t)(c * 80 + hw * 8 + (lane >> 2)) * 2048 + r * 128 + (lane & 3) * 8);
        const uint32_t sa = sb + OFF_BLK + 3 * BLK + B_D + lo + hw * 16;
        #pragma unroll
        for (int i = 0; i < 4; i++) {
          if (i < 3 || hw == 0) {
            uint32_t v[4][4];
            #pragma unroll
            for (int q = 0; q < 4; q++) ldsm4t(v[q], sa + (1 - (q >> 1)) * BLK + (q & 1) * 5120 + i * 48);
            #pragma unroll
            for (int q = 0; q < 4; q++) {
              gp[i * 6144 + q * 4] = make_uint4(v[q][0], v[q][1], v[q][2], v[q][3]);
              if (q & 1) __nanosleep(U_PACE);
            }
          }
        }
      }
      if (ht == 0) TS(37);
      bar_sync(5, 96);
      if (ht == 0) TS(38);
      if (hw == 0) {
        if (lane == 0) { st_rel(&g_flag[(8 + c) * 32 + r], epoch); TS(30); }
        __syncwarp();
        poll_all(&g_flag[(8 + c) * 32 + (lane & 15)], epoch);
        (void)ld_acq(&g_flag[(8 + c) * 32 + (lane & 15)]); __syncwarp();
        if (lane == 0) {
          fence_async_g();
          mbar_expect_tx(BAR(BR_U), 12288);
          #pragma unroll
          for (int k = 4; k >= 2; k--) tma2d(sb + OFF_BLK + k * BLK, &msb, BAR(BR_U), 0, (c * 80 + r * 5 + k) * 32);
          TS(31);
        }
        __syncwarp();
      }
      mbar_wait(BAR(BR_U), 0);
      if (ht == 0) TS(39);
      #pragma unroll 1
      for (int k = 4; k >= 0; k--) {
        if (k == 2) {
          mbar_wait(BAR(BR_KGEN), 0);
          if (ht == 0) {
            fence_async();
            mbar_expect_tx(BAR(BR_U2), 8192);
            tma2d(sb + OFF_BLK + BLK, &msb, BAR(BR_U2), 0, (c * 80 + r * 5 + 1) * 32);
            tma2d(sb + OFF_BLK, &msb, BAR(BR_U2), 0, (c * 80 + r * 5) * 32);
          }
          __syncwarp();
        }
        if (k == 1) mbar_wait(BAR(BR_U2), 0);
        const uint32_t blk = sb + OFF_BLK + k * BLK;
        #pragma unroll 1
        for (int kap = ht; kap < 192; kap += 96) {
          float P[33];
          P[0] = 0.f;
          #pragma unroll
          for (int q = 0; q < 4; q++) {
            const int ch = kap - 3 + q;
            uint32_t v[4];
            lds128(v, blk + (uint32_t)((ch >> 3) * 128 + (((ch & 7) ^ ((ch >> 3) & 7)) << 4)));
            #pragma unroll
            for (int e = 0; e < 4; e++) {
              P[q * 8 + 2 * e + 1] = P[q * 8 + 2 * e] + bf_lo(v[e]);
              P[q * 8 + 2 * e + 2] = P[q * 8 + 2 * e + 1] + bf_hi(v[e]);
            }
          }
#define WIN(lo, hi, e) (P[25 + (e) - (lo)] - P[24 + (e) - (hi)])
#define WIN8(lo, hi) pack2(WIN(lo, hi, 0), WIN(lo, hi, 1)), pack2(WIN(lo, hi, 2), WIN(lo, hi, 3)), pack2(WIN(lo, hi, 4), WIN(lo, hi, 5)), pack2(WIN(lo, hi, 6), WIN(lo, hi, 7))
          const uint32_t o2 = blk + B_D + (kap & 1) * 1552 + (kap >> 1) * 16;
          sts128(o2, WIN8(3, 5));
          sts128(o2 + B_D5, WIN8(6, 10));
          if (kap < 128) {
            const uint32_t o = blk + B_D + (kap & 1) * 1024 + (kap >> 1) * 16;
            sts128(o + B_D7, WIN8(5, 11));
            sts128(o + B_D9, WIN8(12, 20));
          }
        }
        if (ht < 2) sts128(blk + B_D + ht * B_D5 + 1536, 0, 0, 0, 0);
        mbar_arrive(BAR(BR_DRDY + k));
      }
      if (ht == 0) TS(32);
      if (hw == 0) {
        #pragma unroll 1
        for (int k = 4; k >= 0; k--) {
          mbar_wait(BAR(BR_YSTG + k), 0);
          if (lane == 0) {
            tma2d_st(&msb, sb + OFF_BLK + k * BLK, 0, (640 + c * 80 + r * 5 + k) * 32);
            bulk_commit(); bulk_wait0_read();
            mbar_arrive(BAR(BR_FREE + k));
          }
          __syncwarp();
        }
        if (lane == 0) { bulk_wait0(); st_rel(&g_flag[(16 + c) * 32 + r], epoch); TS(33); }
        __syncwarp();
        poll_all(&g_flag[(16 + c) * 32 + (lane & 15)], epoch);
        (void)ld_acq(&g_flag[(16 + c) * 32 + (lane & 15)]); __syncwarp();
        if (lane == 0) {
          fence_async_g();
          mbar_expect_tx(BAR(BR_YIN), 20480);
          tma2d(sb + OFF_BLK + BLK, &msa, BAR(BR_YIN), r * 128, 640 + c * 80);
          tma2d(sb + OFF_BLK + BLK + 10240, &msa, BAR(BR_YIN), r * 128 + 64, 640 + c * 80);
          TS(34);
        }
        __syncwarp();
      }
      mbar_wait(BAR(BR_YIN), 0);
      tile_transpose<false>(sb + OFF_BLK, sb + OFF_BLK + 10240, sb + OFF_BLK + BLK, sb + OFF_BLK + BLK + 10240, hw, lane);
      fence_async();
      bar_sync(5, 96);
      if (ht == 0) {
        tma2d_st(&mout, sb + OFF_BLK, c * 80, r * 128);
        tma2d_st(&mout, sb + OFF_BLK + 10240, c * 80, r * 128 + 64);
        bulk_commit(); bulk_wait0_read();
        TS(35); DUMP(30, 40); DUMP(0, 1);
      }
      }
    }
  } else if (wg < 2) {
    asm volatile("setmaxnreg.inc.sync.aligned.u32 152;");
    if (EN_ATT) {
    const int w4 = warp & 3, g = lane >> 2, tq = lane & 3, t7 = tid & 127;
    float am[96], ar[24];
    {
      const uint64_t da0 = mkdesc(sb + OFF_X + wg * 8192, 16, 1024, 1);
      const uint64_t db0 = sw64 ? mkdesc(sb, 2048, 512, 2) : mkdesc(sb, 4096, 1024, 1);
      const uint32_t kst = sw64 ? 64 : 128;
      const uint64_t dr0 = mkdesc(sb + 12288, 1024, 256, 3);
      uint32_t s = 0, ph = 0, xo = 0;
      #pragma unroll 1
      for (int kb = 0; kb < 20; kb++) {
        mbar_wait(BAR(BR_FULL) + 8 * s, ph);
        if (kb == 0 && tid == 0) TS(1);
        wg_fence();
        const uint32_t wo_ = s * (W_SLOT >> 4);
        wg_ss192_tb(am, da0 + xo, db0 + wo_, kb != 0);
        wg_ss48_tb(ar, da0 + xo, dr0 + wo_, kb != 0);
        wg_ss192_tb(am, da0 + xo + 2, db0 + wo_ + kst, 1);
        wg_ss48_tb(ar, da0 + xo + 2, dr0 + wo_ + 32, 1);
        wg_commit();
        wg_wait<1>();
        if (t7 == 0 && kb > 0 && kb < 16) mbar_arrive(BAR(BR_EMPTY) + 8 * (s == 0 ? 4 : s - 1));
        if (++s == 5) { s = 0; ph ^= 1; }
        xo += (kb & 1) ? 1020 : 4;
        if (xo == 3072) xo = 0;
      }
      wg_wait<0>();
      pin<96>(am); pin<24>(ar);
    }
    if (tid == 0) TS(2);
#define QV(j, e) ((j) < 8 ? am[4 * (j) + (e)] : ar[4 * ((j) - 8) + (e)])
#define KV_(j, e) ((j) < 8 ? am[32 + 4 * (j) + (e)] : ar[8 + 4 * ((j) - 8) + (e)])
#define VV(j, e) ((j) < 8 ? am[64 + 4 * (j) + (e)] : ar[16 + 4 * ((j) - 8) + (e)])
    {
      bar_sync(1, 256);
      if (tid == 0) mbar_arrive(BAR(BR_GEMM));
      const uint32_t ro = (uint32_t)((wg * 64 + w4 * 16 + (lane & 15)) * 16);
      const int l0 = 2 * (c & 1) + (lane >> 4);
      const uint32_t ones = (tq == 0) ? 0x00003f80u : 0u;
#define PV(j) pack2(VV(j, 0), VV(j, 1)), pack2(VV(j, 2), VV(j, 3))
#define PK(j) pack2(phi(KV_(j, 0)), phi(KV_(j, 1))), pack2(phi(KV_(j, 2)), phi(KV_(j, 3)))
      stsm4(sb + OFF_V + (5 + 6 * (lane >> 4)) * 2048 + ro, ones, ones, ones, ones);
      #pragma unroll
      for (int j = 0; j < 10; j += 2) {
        const int l = (j == 8 && (c & 1)) ? l0 - 2 : l0 + j;
        stsm4(sb + OFF_V + (l + (l >= 5)) * 2048 + ro, PV(j), PV(j + 1));
      }
      #pragma unroll
      for (int j = 0; j < 10; j += 2) {
        const int l = (j == 8 && (c & 1)) ? l0 - 2 : l0 + j;
        stsm4(sb + OFF_PK + l * 2048 + ro, PK(j), PK(j + 1));
      }
    }
    fence_async();
    bar_sync(1, 256);
    if (tid == 0) TS(3);
    mbar_wait(BAR(BR_EPOCH), 0);
    const unsigned epoch = lds32(sb + OFF_EPOCH);
    {
      float kv[24]; zero<24>(kv);
      const uint64_t da = mkdesc(sb + OFF_PK + wg * 5 * 2048, 128, 2048, 0);
      const uint64_t db = mkdesc(sb + OFF_V + wg * 6 * 2048, 128, 2048, 0);
      wg_fence();
      #pragma unroll
      for (int s = 0; s < 8; s++) wg_ss48_tt(kv, da + s * 16, db + s * 16, s != 0);
      wg_commit();
      wg_wait<0>();
      pin<24>(kv);
      if (tid == 0) TS(15);
      if (w4 < 3) {
        const uint32_t wb = sb + OFF_KVS + (wg * 3 + w4) * 1536;
        #pragma unroll
        for (int j = 0; j < 6; j += 2)
          stsm4(wb + (lane & 15) * 96 + (j + (lane >> 4)) * 16, pack2(kv[4 * j], kv[4 * j + 1]), pack2(kv[4 * j + 2], kv[4 * j + 3]),
                pack2(kv[4 * j + 4], kv[4 * j + 5]), pack2(kv[4 * j + 6], kv[4 * j + 7]));
        __syncwarp();
        const int dl = w4 * 16 + (lane & 15), hl = dl >= 20;
        if (dl < 40) {
          uint4* dst = &g_kvp[(c * 16 + r) * 240 + wg * 40 + dl];
          uint32_t v[4];
          lds128(v, wb + (lane & 15) * 96 + (3 * hl + (lane >> 4)) * 16);
          v[3] = (v[3] & ~1u) | (epoch & 1u);
          st128_rlx(dst + (lane >> 4) * 80, v);
          if (lane < 16) {
            v[0] = lds32(wb + lane * 96 + 32 + 8 * hl); v[1] = lds32(wb + lane * 96 + 36 + 8 * hl);
            v[2] = lds32(wb + lane * 96 + 80); v[3] = epoch & 1u;
            st128_rlx(dst + 160, v);
          }
        }
      }
    }
    bar_sync(1, 256);
    if (tid == 0) { st_rlx(&g_flag[c * 32 + r], epoch); mbar_arrive(BAR(BR_PUB)); TS(4); }
    const int kd = tid >= 160 ? tid - 160 : (tid >= 80 ? tid - 80 : tid), kvi = (tid >= 80) + (tid >= 160);
    const int khd = kd / 20, kt0 = 5 * (khd >> 1) + 2 * (khd & 1);
    if (tid < 240) {
      #pragma unroll
      for (int m = 0; m < 3; m++) {
        int q = kt0 + 3 + kvi + 3 * m; if (q >= 10) q -= 10;
        if (kvi + 3 * m < 7) sts128(sb + OFF_KVB + q * 1280 + kd * 16, 0, 0, 0, 0);
      }
    }
    uint32_t qa[20];
    {
      const float sc = 1.44269504089f + __uint_as_float(lds32(sb + OFF_EPOCH) ^ epoch);
      #pragma unroll
      for (int j = 0; j < 10; j++) { qa[2 * j] = pack2(phi(QV(j, 0), sc), phi(QV(j, 1), sc)); qa[2 * j + 1] = pack2(phi(QV(j, 2), sc), phi(QV(j, 3), sc)); }
    }
    if (tid == 0) TS(5);
    {
      poll_all(&g_flag[c * 32 + (lane & 15)], epoch);
      if (tid == 0) TS(6);
      if (tid < 240) {
        uint32_t v[16][4];
        const uint4* src = &g_kvp[c * 16 * 240 + tid];
        #pragma unroll
        for (int i = 0; i < 16; i++) ld128_rlx(v[i], src + i * 240);
        float s[8];
        uint32_t bad = 0;
        #pragma unroll
        for (int i = 0; i < 16; i++) {
          bad |= v[i][3] ^ epoch;
          #pragma unroll
          for (int e = 0; e < 4; e++) {
            s[2 * e] = i ? s[2 * e] + bf_lo(v[i][e]) : bf_lo(v[i][e]);
            s[2 * e + 1] = i ? s[2 * e + 1] + bf_hi(v[i][e]) : bf_hi(v[i][e]);
          }
        }
        if (__builtin_expect(bad & 1u, 0)) {
          #pragma unroll
          for (int e = 0; e < 8; e++) s[e] = 0.f;
          #pragma unroll 1
          for (int i = 0; i < 16; i++) {
            uint32_t w[4] = {0, 0, 0, ~epoch};
            fix128_w3(w, src + i * 240, epoch, 1u);
            #pragma unroll
            for (int e = 0; e < 4; e++) { s[2 * e] += bf_lo(w[e]); s[2 * e + 1] += bf_hi(w[e]); }
          }
        }
        if (tid == 0) TS(18);
        const uint32_t p0 = pack2(s[0], s[1]), p1 = pack2(s[2], s[3]), p2 = pack2(s[4], s[5]), p3 = pack2(s[6], s[7]);
        const uint32_t rb = sb + OFF_KVB + kd * 16;
        if (kvi < 2) sts128(rb + (kt0 + (khd & 1) + kvi) * 1280, p0, p1, p2, p3);
        else {
          const bool od = khd & 1;
          sts128(rb + (5 * (khd >> 1) + 2) * 1280, od ? 0u : p0, od ? 0u : p1, od ? p0 : 0u, od ? p1 : 0u);
          const uint32_t zz = (p2 & 0xffffu) << (16 * (khd & 1));
          sts128(rb + 10 * 1280, khd < 2 ? zz : 0u, khd < 2 ? 0u : zz, 0u, 0u);
        }
      }
    }
    fence_async();
    bar_sync(1, 256);
    if (tid == 0) TS(7);
    uint32_t A0[20], A1[20];
    {
      float oa[44]; zero<44>(oa);
      const uint64_t db = mkdesc(sb + OFF_KVB, 128, 1280, 0);
      wg_fence();
      #pragma unroll
      for (int s = 0; s < 5; s++) wg_rs88_tb(oa, &qa[4 * s], db + ((s == 4 && (c & 1)) ? 0 : (s + (c & 1)) * 16), s != 0);
      wg_commit();
      if (tid == 0) TS(12);
      wg_wait<0>();
      pin<44>(oa);
      if (tid == 0) TS(13);
      float rc[4], rd[2][4];
      #pragma unroll
      for (int e = 0; e < 4; e++) rc[e] = __fdividef(1.f, oa[40 + e] + 1e-6f);
      #pragma unroll
      for (int h = 0; h < 4; h++) {
        rd[0][h] = __shfl_sync(0xffffffff, rc[h & 1], (lane & 28) | (h >> 1));
        rd[1][h] = __shfl_sync(0xffffffff, rc[2 + (h & 1)], (lane & 28) | (h >> 1));
      }
      #pragma unroll
      for (int j = 0; j < 10; j++) {
        #pragma unroll
        for (int h = 0; h < 2; h++) {
          float f;
          if (j == 2) f = tq < 2 ? rd[h][0] : rd[h][1];
          else if (j == 7) f = tq < 2 ? rd[h][2] : rd[h][3];
          else f = rd[h][(8 * j) / 20];
          A0[2 * j + h] = pack2(oa[4 * j + 2 * h] * f, oa[4 * j + 2 * h + 1] * f);
        }
      }
      bar_sync(1, 256);
      #pragma unroll
      for (int s = 0; s < 5; s++) {
        A0[4 * s] = (A0[4 * s] & ~1u) | (epoch & 1u);
        sts128(sb + OFF_EXTRA + ((wg * 5 + s) * 128 + t7) * 16, A0[4 * s], A0[4 * s + 1], A0[4 * s + 2], A0[4 * s + 3]);
      }
    }
    if (tid == 0) TS(14);
    fence_async();
    mbar_arrive(BAR(BR_OSTG));
    if (tid == 0) TS(8);
    float oc[32], od[8]; zero<32>(oc); zero<8>(od);
    {
      const uint64_t dw0 = mkdesc(sb + OFF_WOM, 16, 1024, 1), dr0 = mkdesc(sb, 16, 256, 3);
      mbar_wait(BAR(BR_WO), 0);
      mbar_wait(BAR(BR_WO + 1), 0);
      wg_fence();
      #pragma unroll
      for (int s = 0; s < 5; s++) { wg_rs64_tb(oc, &A0[4 * s], dw0 + c * 640 + s * 128, s != 0); wg_rs16_tb(od, &A0[4 * s], dr0 + c * 160 + s * 32, s != 0); }
      wg_commit();
      #pragma unroll
      for (int i = 0; i < 7; i++) {
        uint32_t* A = (i & 1) ? A0 : A1;
        const uint32_t slot = (i & 3) == 3 ? sb + OFF_EXTRA : sb + OFF_BLK + (4 - (i & 3)) * BLK;
        const int src = (i == 6) ? (c ^ 1) : (((c & 6) + 2 + i) & 7);
        mbar_wait(BAR(BR_OFULL + (i & 3)), i >> 2);
        if (i == 0 && tid == 0) TS(9);
        if (i > 0) wg_wait<1>();
        #pragma unroll
        for (int s = 0; s < 5; s++) lds128(&A[4 * s], slot + ((wg * 5 + s) * 128 + t7) * 16);
        uint32_t bad = 0;
        #pragma unroll
        for (int s = 0; s < 5; s++) bad |= A[4 * s] ^ epoch;
        if (__builtin_expect(bad & 1u, 0)) {
          #pragma unroll
          for (int s = 0; s < 5; s++) fix128_w0(&A[4 * s], &g_o[(r * 8 + src) * 1280 + (wg * 5 + s) * 128 + t7], epoch, 1u);
        }
        __syncwarp();
        if (i < 3 && lane == 0) mbar_arrive(BAR(BR_OEMPTY + i));
        wg_fence();
        #pragma unroll
        for (int s = 0; s < 5; s++) { wg_rs64_tb(oc, &A[4 * s], dw0 + src * 640 + s * 128, 1); wg_rs16_tb(od, &A[4 * s], dr0 + src * 160 + s * 32, 1); }
        wg_commit();
      }
      bar_sync(2 + wg, 128);
      wg_wait<0>();
      pin<32>(oc); pin<8>(od);
    }
    if (tid == 0) TS(10);
    {
      const int row = w4 * 16 + (lane & 15);
      const uint32_t ob = sb + OFF_EXTRA + wg * 10240;
      #pragma unroll
      for (int j = 0; j < 8; j += 2)
        stsm4(ob + row * 128 + (((j + (lane >> 4)) ^ (row & 7)) << 4), pack2(oc[4 * j], oc[4 * j + 1]), pack2(oc[4 * j + 2], oc[4 * j + 3]),
              pack2(oc[4 * j + 4], oc[4 * j + 5]), pack2(oc[4 * j + 6], oc[4 * j + 7]));
      stsm4(ob + 8192 + row * 32 + (lane >> 4) * 16, pack2(od[0], od[1]), pack2(od[2], od[3]), pack2(od[4], od[5]), pack2(od[6], od[7]));
      fence_async();
      bar_sync(2 + wg, 128);
      if (t7 == 0) {
        tma2d_st(&mo64, ob, 640 + c * 64, r * 128 + wg * 64);
        tma2d_st(&mo16, ob + 8192, 1152 + c * 16, r * 128 + wg * 64);
        bulk_commit(); bulk_wait0_read();
      }
      if (tid == 0) { TS(11); DUMP(0, 20); }
    }
    }
  } else {
    asm volatile("setmaxnreg.inc.sync.aligned.u32 152;");
    if (EN_SSM) {
    const int w4 = warp & 3, g = lane >> 2, tq = lane & 3, t7 = tid & 127;
    {
      #pragma unroll
      for (int k = 0; k < 5; k++) {
        const uint32_t tz = sb + OFF_BLK + k * BLK + B_TBL + t7 * 16;
        if (t7 < 32 || t7 >= 96) sts128(tz, 0, 0, 0, 0);
        if (t7 < 124) sts128(tz + 2048, 0, 0, 0, 0);
        if (t7 < 16) sts128(sb + OFF_BLK + k * BLK - 256 + t7 * 16, 0, 0, 0, 0);
      }
      if (t7 < 5) sts64(sb + OFF_BLK + t7 * BLK + B_SP + 8, __float_as_uint(bf_round(expf(bf_lo(ldt)))), (uint32_t)dsk0 << 16);
      const uint32_t st = sb + OFF_BLK + (lane >> 4) * BLK + B_TBL + 512 + w4 * 256 + (lane & 15) * 16;
      #pragma unroll
      for (int i = 0; i < 3; i++) {
        if (i < 2 || lane < 16) sts128(st + 2 * i * BLK, pv[i].x, pv[i].y, pv[i].z, pv[i].w);
        if (w4 >= 2) {
          const uint32_t m2 = __vmaxu2(__vmaxu2(pv[i].x & 0x7fff7fffu, pv[i].y & 0x7fff7fffu), __vmaxu2(pv[i].z & 0x7fff7fffu, pv[i].w & 0x7fff7fffu));
          const uint32_t m = __reduce_max_sync(lane < 16 ? 0x0000ffffu : 0xffff0000u, max(m2 & 0xffffu, m2 >> 16));
          if ((lane & 15) == 0 && (i < 2 || lane == 0)) sts32(sb + OFF_BLK + (2 * i + (lane >> 4)) * BLK + B_SP + 8 + w4 * 4, m);
        }
      }
    }
    bar_sync(4, 128);
    if (t7 == 0) TS(40);
    {
      const uint32_t fa = sb + OFF_BLK + (w4 & 1) * BLK + (lane >> 3) * 256 + (lane & 7) * 16;
      const uint32_t ea = fa + (w4 >> 1) * 4096, ga = fa + 8192 + (w4 >> 1) * 3072;
      const uint64_t dE = mkdesc(sb + OFF_BLK, 128, 1024, 0), dG = mkdesc(sb + OFF_BLK + 8192, 128, 1024, 0);
      #pragma unroll 1
      for (int k = 4; k >= 0; k--) {
        const uint32_t blk = sb + OFF_BLK + k * BLK;
        float fac, dsk;
        {
          const uint32_t st = blk + B_TBL + 512 + t7 * 2;
          uint32_t q[2], mm[2];
          const uint32_t p0 = lds16(st), p1 = lds16(st + 256), p2 = lds16(st + 512), p3 = lds16(st + 768);
          lds64(q, blk + B_SP + 8); lds64(mm, blk + B_SP + 16);
          const float dt = __uint_as_float(q[0]); dsk = __uint_as_float(q[1]);
          const uint32_t ex = min(max(max(mm[0], mm[1]) >> 7, 1u), 253u);
          const float sc = __uint_as_float((254u - ex) << 23);
          fac = 2.f * dt * __uint_as_float(ex << 23);
          const float lr = -bf_round(expf(bf_lo(p0))) * dt * 1.44269504089f;
          const float tn = bf_lo(p1) * dt * 0.15915494309f;
          float z1r, z1i, z2r, z2i, z4r, z4i, xr[8], xi[8], gr[8], gi[8], wr[9], wi[9];
          cexp_t(lr, -tn, z1r, z1i);
          cexp_t(lr * 8.f, tn * 8.f, xr[1], xi[1]);
          cexp_t(lr * 64.f, tn * 64.f, wr[0], wi[0]);
          xr[0] = 1.f; xi[0] = 0.f;
          cmul(xr[1], xi[1], xr[1], xi[1], xr[2], xi[2]); cmul(xr[2], xi[2], xr[1], xi[1], xr[3], xi[3]);
          cmul(xr[2], xi[2], xr[2], xi[2], xr[4], xi[4]);
          #pragma unroll
          for (int b = 1; b < 4; b++) cmul(xr[4], xi[4], xr[b], xi[b], xr[4 + b], xi[4 + b]);
          cmul(wr[0], wi[0], wr[0], wi[0], wr[1], wi[1]); cmul(wr[1], wi[1], wr[0], wi[0], wr[2], wi[2]);
          cmul(wr[1], wi[1], wr[1], wi[1], wr[3], wi[3]); cmul(wr[3], wi[3], wr[3], wi[3], wr[4], wi[4]);
          cmul(wr[4], wi[4], wr[3], wi[3], wr[5], wi[5]); cmul(wr[4], wi[4], wr[4], wi[4], wr[6], wi[6]);
          cmul(wr[6], wi[6], wr[4], wi[4], wr[7], wi[7]); cmul(wr[6], wi[6], wr[6], wi[6], wr[8], wi[8]);
          uint32_t R[4], I[4], PR[4], PI[4];
          #pragma unroll
          for (int b = 0; b < 4; b++) { R[b] = packh(xr[2 * b], xr[2 * b + 1]); I[b] = packh(xi[2 * b], xi[2 * b + 1]); }
          sts128(ea, R[0], R[1], R[2], R[3]); sts128(ea + 128, I[0], I[1], I[2], I[3]);
          #pragma unroll
          for (int i = 0; i < 3; i++) {
            const uint32_t z = packh(wr[i], wi[i]);
            #pragma unroll
            for (int b = 0; b < 4; b++) hcm2(R[b], I[b], z, PR[b], PI[b]);
            sts128(ea + (i + 1) * 1024, PR[0], PR[1], PR[2], PR[3]); sts128(ea + (i + 1) * 1024 + 128, PI[0], PI[1], PI[2], PI[3]);
          }
          gr[0] = bf_lo(p2) * sc; gi[0] = -bf_lo(p3) * sc;
          cmul(z1r, z1i, z1r, z1i, z2r, z2i); cmul(z2r, z2i, z2r, z2i, z4r, z4i);
          cmul(gr[0], gi[0], z1r, z1i, gr[1], gi[1]);
          cmul(gr[0], gi[0], z2r, z2i, gr[2], gi[2]); cmul(gr[1], gi[1], z2r, z2i, gr[3], gi[3]);
          #pragma unroll
          for (int b = 0; b < 4; b++) cmul(gr[b], gi[b], z4r, z4i, gr[4 + b], gi[4 + b]);
          sts128(ga, packh(gr[0], gr[1]), packh(gr[2], gr[3]), packh(gr[4], gr[5]), packh(gr[6], gr[7]));
          sts128(ga + 128, packh(gi[0], gi[1]), packh(gi[2], gi[3]), packh(gi[4], gi[5]), packh(gi[6], gi[7]));
          {
            const uint32_t z = packh(wr[3], -wi[3]), a4r = packh(gr[0], gr[4]), a4i = packh(gi[0], gi[4]);
            hcm2(packh(gr[0], gr[2]), packh(gi[0], gi[2]), z, PR[0], PI[0]);
            hcm2(packh(gr[4], gr[6]), packh(gi[4], gi[6]), z, PR[1], PI[1]);
            hcm2(a4r, a4i, packh(wr[4], -wi[4]), PR[2], PI[2]);
            hcm2(a4r, a4i, packh(wr[5], -wi[5]), PR[3], PI[3]);
            sts128(ga + 1024, PR[0], PR[1], PR[2], PR[3]); sts128(ga + 1024 + 128, PI[0], PI[1], PI[2], PI[3]);
            float hr, hi_;
            cmul(gr[0], gi[0], wr[3], -wi[3], hr, hi_);
            const uint32_t cr = packh(gr[0], hr), ci = packh(gi[0], hi_);
            #pragma unroll
            for (int i = 0; i < 3; i++) hcm2(cr, ci, packh(wr[6 + i], -wi[6 + i]), PR[i], PI[i]);
            sts128(ga + 2048, PR[0], PR[1], PR[2], 0u); sts128(ga + 2048 + 128, PI[0], PI[1], PI[2], 0u);
          }
        }
        fence_async();
        bar_sync(4, 128);
        if (t7 == 0 && k == 3) TS(50);
        float ka[24]; zero<24>(ka);
        wg_fence();
        #pragma unroll
        for (int s = 0; s < 8; s++) wg_ss48_tt_h(ka, dE + (s >> 2) * (BLK >> 4) + (s & 3) * 16, dG + (s >> 2) * (BLK >> 4) + (s & 3) * 16, s != 0);
        wg_commit();
        wg_wait<0>();
        pin<24>(ka);
        if (t7 == 0 && k == 3) TS(51);
        float kk[6];
        {
          const bool up = w4 >= 2;
          const uint32_t xa = sb + OFF_BLK + 2 * BLK + B_D + 7168 + t7 * 8;
          #pragma unroll
          for (int n = 0; n < 3; n++) {
            sts64f(xa + n * 1024, up ? ka[12 + 4 * n] : ka[4 * n + 2], up ? ka[13 + 4 * n] : ka[4 * n + 3]);
            kk[2 * n] = up ? ka[14 + 4 * n] : ka[4 * n]; kk[2 * n + 1] = up ? ka[15 + 4 * n] : ka[4 * n + 1];
          }
          bar_sync(4, 128);
          #pragma unroll
          for (int n = 0; n < 3; n++) {
            uint32_t o[2]; lds64(o, (xa ^ 512) + n * 1024);
            kk[2 * n] = (kk[2 * n] + __uint_as_float(o[0])) * fac; kk[2 * n + 1] = (kk[2 * n + 1] + __uint_as_float(o[1])) * fac;
          }
        }
        if (t7 == 0 && k == 3) TS(52);
        {
          const int j = (w4 & 1) * 16 + (w4 >> 1) * 8 + g;
          const uint32_t tb = blk + B_TBL;
          if (t7 == 0) kk[0] += dsk;
          const uint32_t pa_ = tb + (16 + 8 * j + 2 * tq) * 4;
          const uint32_t v = pack2(kk[1], kk[0]);
          sts32(pa_ + 4, v); sts16(pa_, v >> 16); sts16(pa_ + 10, v);
          const uint32_t u = pack2(kk[2], kk[3]), w = pack2(kk[4], kk[5]);
          if (tq < 2) {
            const uint32_t pb = tb + (16 + 256 + 8 * j + 4 * tq) * 4;
            sts16(pb, u); sts32(pb + 4, __byte_perm(u, 0, 0x1010)); sts32(pb + 8, __byte_perm(u, 0, 0x1032)); sts16(pb + 14, u >> 16);
            if (j | tq) { sts16(pb - 4, u); sts16(pb + 2, u); }
            const int i = 64 * tq + j;
            const uint32_t e0 = tb + (T_F3 + (((i - 1) & 1) ? 80 : 0) + ((i - 1) >> 1)) * 4, e1 = i ? e0 : tb + (T_F2 + 144 + 31) * 4;
            sts16(e1, w); sts16(e1 + 6, w); sts16(e0 + 64, w >> 16); sts16(e0 + 70, w >> 16);
            if (i == 0) { sts16(tb + (T_S + 3) * 4, w); sts32(tb + (T_S + 4) * 4, __byte_perm(w, 0, 0x1010)); sts16(tb + (T_S + 5) * 4 + 2, w); }
          } else {
            const int i = 32 * (tq - 2) + j;
            const uint32_t e1 = tb + (i ? T_F2 + ((2 * i - 1) & 3) * 48 + ((2 * i - 1) >> 2) : 16 + 511) * 4;
            const uint32_t e2 = tb + (T_F2 + (i & 1) * 96 + (i >> 1)) * 4;
            sts16(e1, u); sts16(e1 + 6, u); sts16(e2, u >> 16); sts16(e2 + 6, u >> 16);
            if (i == 0) {
              const uint32_t uu = __byte_perm(u, 0, 0x1010);
              sts32(tb + 528 * 4, uu); sts32(tb + 529 * 4, uu); sts32(tb + 530 * 4, uu); sts16(tb + 531 * 4 + 2, u);
              sts16(tb + (T_F3 + 80 + 63) * 4, w);
            }
          }
        }
        if (t7 == 0 && k == 3) TS(53);
      }
      bar_sync(4, 128);
      if (t7 == 0) { mbar_arrive(BAR(BR_KGEN)); TS(41); }
    }
    mbar_wait(BAR(BR_U), 0);
    if (EN_ATT) mbar_wait(BAR(BR_GEMM), 0);
    if (t7 == 0) TS(42);
    #pragma unroll 1
    for (int pass = 0; pass < 2; pass++) {
      const int k = pass ? w4 : 4;
      const uint32_t blk = sb + OFF_BLK + k * BLK, tb = blk + B_TBL + (uint32_t)((g - 2 * tq) * 4);
      if (k < 2) mbar_wait(BAR(BR_U2), 0);
      float acc[16][4];
      zero<64>(&acc[0][0]);
      const int kl = 16 * (lane >> 4) + 2 * (lane & 7) + ((lane >> 3) & 1);
      {
        auto ubase = [&](int sh) { const int q = kl - 2 * sh; return blk + (uint32_t)((q * 16) ^ ((q * 2) & 0x70)); };
#define LDQ(A, sh) _Pragma("unroll") for (int m = 0; m < 4; m++) load_quad(A[m], tb + (16 + 16 * (sh) + 128 * m) * 4);
#define LDB(B, ub, h) _Pragma("unroll") for (int p = 0; p < 4; p++) ldsm4(B[p], ((ub) ^ ((p & 1) * 64)) + (4 * (h) + p) * 512);
#define MLO(A, B) _Pragma("unroll") for (int m = 0; m < 4; m++) _Pragma("unroll") for (int cc = 0; cc < 8; cc++) mma16816(acc[cc + m], A[m], &B[cc >> 1][(cc & 1) * 2]);
#define MHI(A, B) _Pragma("unroll") for (int m = 0; m < 4; m++) _Pragma("unroll") for (int cc = 0; cc < 8 - m; cc++) mma16816(acc[8 + cc + m], A[m], &B[cc >> 1][(cc & 1) * 2]);
        int p_ = pass ? 0 : w4;
        const int pe = pass ? 4 : w4 + 1;
        uint32_t A[4][4], A2[4][4], Bl[4][4], Bh[4][4];
        uint32_t ub = ubase(p_ + 4);
        LDQ(A, p_ + 4) LDB(Bl, ub, 0)
        #pragma unroll 1
        for (; p_ < pe; p_++) {
          LDB(Bh, ub, 1)
          MLO(A, Bl)
          ub = ubase(p_);
          LDQ(A2, p_) LDB(Bl, ub, 0)
          MHI(A, Bh)
          LDB(Bh, ub, 1)
          load_quad(A[0], tb + (16 + 512 + 16 * (p_ & 1)) * 4); load_quad(A[1], tb + (T_S + 16 * (p_ & 1)) * 4);
          MLO(A2, Bl)
          if (p_ < 2) {
            #pragma unroll
            for (int cc = 0; cc < 8; cc++) mma16816(acc[cc + 4], A[0], &Bl[cc >> 1][(cc & 1) * 2]);
            #pragma unroll
            for (int cc = 0; cc < 4; cc++) mma16816(acc[cc + 12], A[0], &Bh[cc >> 1][(cc & 1) * 2]);
            #pragma unroll
            for (int cc = 0; cc < 8; cc++) mma16816(acc[cc + 8], A[1], &Bl[cc >> 1][(cc & 1) * 2]);
          }
          const int pn = ((p_ + 1) & 3) + 4;
          ub = ubase(pn);
          LDQ(A, pn) LDB(Bl, ub, 0)
          MHI(A2, Bh)
        }
      }
      if (t7 == 0) TS(57 + 3 * pass);
      mbar_wait(BAR(BR_DRDY) + 8 * k, 0);
      {
        const int ih = (lane >> 3) & 1;
        const uint32_t dl = blk + B_D + (uint32_t)(((lane >> 4) * 8 + (lane & 7)) * 16);
        const uint32_t d0_ = dl + ih * 1552, d8_ = dl + (ih ? 0 : 1536), d3_ = dl + B_D7 + ih * 1024;
        auto cls2 = [&](uint32_t da, uint32_t ta) {
          uint32_t B[6][2], A[6][4];
          #pragma unroll
          for (int e = 0; e < 6; e++) { B[e][0] = lds32v(ta + (e + 4) * 32); B[e][1] = lds32v(ta + (e + 3) * 32); }
          #pragma unroll
          for (int kk = 0; kk < 6; kk++) ldsm4t(A[kk], da + kk * 256);
          #pragma unroll
          for (int e = 0; e < 6; e++)
            #pragma unroll
            for (int kk = 0; kk < 6; kk++) if (2 * kk + e + 4 < 16) mma16816(acc[2 * kk + e + 4], A[kk], B[e]);
        };
        auto cls3 = [&](uint32_t da, uint32_t ta) {
          uint32_t B[8][2], A[4][4];
          #pragma unroll
          for (int e = 0; e < 8; e++) { B[e][0] = lds32v(ta + (e + 8) * 32); B[e][1] = lds32v(ta + (e + 7) * 32); }
          #pragma unroll
          for (int kk = 0; kk < 4; kk++) ldsm4t(A[kk], da + kk * 256);
          #pragma unroll
          for (int kk = 0; kk < 4; kk++)
            #pragma unroll
            for (int e = 0; e < 8; e++) if (2 * kk + e + 8 < 16) mma16816(acc[2 * kk + e + 8], A[kk], B[e]);
        };
        if (pass) {
          #pragma unroll
          for (int a = 0; a < 4; a++) cls2(((a & 2) ? d8_ : d0_) + (a & 1) * B_D5, tb + (T_F2 + 48 * a - 32) * 4);
          #pragma unroll
          for (int b = 0; b < 2; b++) cls3(d3_ + b * 2048, tb + (T_F3 + 80 * b - 64) * 4);
        } else {
          cls2(((w4 & 2) ? d8_ : d0_) + (w4 & 1) * B_D5, tb + (T_F2 + 48 * w4 - 32) * 4);
          if (w4 >= 2) cls3(d3_ + (w4 - 2) * 2048, tb + (T_F3 + 80 * (w4 - 2) - 64) * 4);
        }
      }
      if (t7 == 0) TS(58 + 3 * pass);
      const uint32_t ya = blk + (uint32_t)((kl * 16) ^ ((kl * 2) & 0x70));
#define STY(p) stsm4t((ya ^ (((p) & 1) * 64)) + (p) * 512, pack2(acc[2 * (p)][0], acc[2 * (p)][1]), pack2(acc[2 * (p)][2], acc[2 * (p)][3]), \
                      pack2(acc[2 * (p) + 1][0], acc[2 * (p) + 1][1]), pack2(acc[2 * (p) + 1][2], acc[2 * (p) + 1][3]))
      if (pass == 0) {
        const uint32_t xw = blk + 4096 + w4 * 4096 + lane * 16, xr = blk + 4096 + (w4 ^ 2) * 4096 + lane * 16, xq = blk + 4096 + (w4 ^ 3) * 4096 + lane * 16;
#define PUT(n, a, c0) _Pragma("unroll") for (int i = 0; i < (n); i++) sts128((a) + i * 512, __float_as_uint(acc[(c0) + i][0]), __float_as_uint(acc[(c0) + i][1]), __float_as_uint(acc[(c0) + i][2]), __float_as_uint(acc[(c0) + i][3]));
#define ADD(n, a, c0) _Pragma("unroll") for (int i = 0; i < (n); i++) { uint32_t o[4]; lds128(o, (a) + i * 512); _Pragma("unroll") for (int e = 0; e < 4; e++) acc[(c0) + i][e] += __uint_as_float(o[e]); }
#define RED(h, q) { PUT(8, xw, 8 - 8 * (h)) bar_sync(4, 128); ADD(8, xr, 8 * (h)) PUT(4, xr, 8 * (h) + 4 - 4 * (q)) bar_sync(4, 128); \
                    ADD(4, xq, 8 * (h) + 4 * (q)) STY(4 * (h) + 2 * (q)); STY(4 * (h) + 2 * (q) + 1); }
        bar_sync(4, 128);
        if (w4 == 0) RED(0, 0) else if (w4 == 1) RED(0, 1) else if (w4 == 2) RED(1, 0) else RED(1, 1)
      } else {
        __syncwarp();
        #pragma unroll
        for (int p = 0; p < 8; p++) STY(p);
      }
      fence_async();
      mbar_arrive(BAR(BR_YSTG) + 8 * k);
      if (t7 == 0) TS(59 + 3 * pass);
    }
    if (t7 == 0) DUMP(40, 64);
    }
  }
}

typedef CUresult (*EncFn)(CUtensorMap*, CUtensorMapDataType, cuuint32_t, void*, const cuuint64_t*, const cuuint64_t*, const cuuint32_t*,
                          const cuuint32_t*, CUtensorMapInterleave, CUtensorMapSwizzle, CUtensorMapL2promotion, CUtensorMapFloatOOBfill);
static CUtensorMap mkmap(EncFn enc, const void* base, int rank, const cuuint64_t* dims, const cuuint64_t* strides, const cuuint32_t* box, CUtensorMapSwizzle swz) {
  CUtensorMap m; cuuint32_t es[5] = {1, 1, 1, 1, 1};
  enc(&m, CU_TENSOR_MAP_DATA_TYPE_BFLOAT16, rank, const_cast<void*>(base), dims, strides, box, es, CU_TENSOR_MAP_INTERLEAVE_NONE, swz,
      CU_TENSOR_MAP_L2_PROMOTION_L2_128B, CU_TENSOR_MAP_FLOAT_OOB_FILL_NONE);
  return m;
}

extern "C" void kernel_launch(void* const* d_in, const int* in_sizes, int n_in, void* d_out, int out_size) {
  void* fn = nullptr; cudaDriverEntryPointQueryResult qr;
  cudaGetDriverEntryPoint("cuTensorMapEncodeTiled", &fn, cudaEnableDefault, &qr);
  EncFn enc = (EncFn)fn;
  void* uy = nullptr; cudaGetSymbolAddress(&uy, g_uy);
  const cuuint64_t dx[2] = {640, 2048}, sx[1] = {1280};
  const cuuint32_t bx[2] = {64, 128}, bu[2] = {80, 64};
  const cuuint64_t dw[3] = {640, 640, 3}, sw[2] = {3840, 1280};
  const cuuint32_t br[3] = {16, 32, 3};
  const cuuint64_t dwa[4] = {64, 640, 10, 3}, swa[3] = {3840, 128, 1280}, dwb[4] = {32, 640, 20, 3}, swb[3] = {3840, 64, 1280};
  const cuuint32_t bwa[4] = {64, 32, 1, 3}, bwb[4] = {32, 32, 2, 3};
  const cuuint64_t dwo[2] = {640, 640};
  const cuuint32_t bwo[2] = {64, 80}, bwr[2] = {16, 160}, bo64[2] = {64, 64}, bo16[2] = {16, 64};
  const cuuint64_t dsa[2] = {2048, 1280}, ssa[1] = {4096};
  const cuuint32_t bsa[2] = {64, 80};
  const cuuint64_t dsb[2] = {64, 40960}, ssb[1] = {128};
  const cuuint32_t bsb[2] = {64, 32};
  const cuuint64_t dout[2] = {1280, 2048}, sout[1] = {2560};
  CUtensorMap mx = mkmap(enc, d_in[7], 2, dx, sx, bx, CU_TENSOR_MAP_SWIZZLE_128B);
  CUtensorMap mw = mkmap(enc, d_in[8], 4, dwa, swa, bwa, CU_TENSOR_MAP_SWIZZLE_128B);
  CUtensorMap mw64 = mkmap(enc, d_in[8], 4, dwb, swb, bwb, CU_TENSOR_MAP_SWIZZLE_64B);
  CUtensorMap mr = mkmap(enc, d_in[8], 3, dw, sw, br, CU_TENSOR_MAP_SWIZZLE_32B);
  CUtensorMap mwo = mkmap(enc, d_in[9], 2, dwo, sx, bwo, CU_TENSOR_MAP_SWIZZLE_128B);
  CUtensorMap mwr = mkmap(enc, d_in[9], 2, dwo, sx, bwr, CU_TENSOR_MAP_SWIZZLE_32B);
  CUtensorMap mo64 = mkmap(enc, d_out, 2, dout, sout, bo64, CU_TENSOR_MAP_SWIZZLE_128B);
  CUtensorMap mo16 = mkmap(enc, d_out, 2, dout, sout, bo16, CU_TENSOR_MAP_SWIZZLE_NONE);
  CUtensorMap msa = mkmap(enc, uy, 2, dsa, ssa, bsa, CU_TENSOR_MAP_SWIZZLE_128B);
  CUtensorMap msb = mkmap(enc, uy, 2, dsb, ssb, bsb, CU_TENSOR_MAP_SWIZZLE_128B);
  CUtensorMap mout = mkmap(enc, d_out, 2, dout, sout, bu, CU_TENSOR_MAP_SWIZZLE_NONE);
  Params prm;
  prm.u = (const __nv_bfloat16*)d_in[0];
  prm.logA = (const __nv_bfloat16*)d_in[1]; prm.Aim = (const __nv_bfloat16*)d_in[2];
  prm.Cr = (const __nv_bfloat16*)d_in[3]; prm.Ci = (const __nv_bfloat16*)d_in[4];
  prm.logdt = (const __nv_bfloat16*)d_in[5]; prm.dskip = (const __nv_bfloat16*)d_in[6];
  cudaFuncSetAttribute(fused_kernel, cudaFuncAttributeMaxDynamicSharedMemorySize, SMEM_BYTES);
  cudaLaunchConfig_t cfg = {};
  cfg.gridDim = dim3(128); cfg.blockDim = dim3(512); cfg.dynamicSmemBytes = SMEM_BYTES; cfg.stream = cudaStreamPerThread;
  cudaLaunchAttribute at[1];
  at[0].id = cudaLaunchAttributeClusterDimension; at[0].val.clusterDim.x = 2; at[0].val.clusterDim.y = 1; at[0].val.clusterDim.z = 1;
  cfg.attrs = at; cfg.numAttrs = 1;
  cudaLaunchKernelEx(&cfg, fused_kernel, mx, mw, mr, mwo, mwr, mo64, mo16, mw64, msa, msb, mout, prm);
}
```

```cpp
#include <cuda_runtime.h>
#include <cuda_bf16.h>
#include <cuda_fp16.h>
#include <cuda.h>
#include <stdint.h>

#define U_PACE 250
#define EN_ATT 1
#define EN_SSM 1

__device__ __align__(1024) __nv_bfloat16 g_uy[2 * 640 * 2048];
__device__ __align__(128) uint4 g_kvp[8 * 16 * 240];
__device__ __align__(128) uint4 g_o[128 * 1280];
__device__ __align__(128) unsigned g_flag[40 * 32];
__device__ unsigned g_epoch[128];
#define TS(i) do {} while (0)
#define DUMP(lo, hi) do {} while (0)

constexpr uint32_t W_SLOT = 15360, OFF_X = 76800;
constexpr uint32_t OFF_WOM = 20480, OFF_KVS = 71680, OFF_PK = 80896, OFF_V = 101376, OFF_EXTRA = 102400, OFF_KVB = OFF_EXTRA;
constexpr uint32_t OFF_BAR = 125952, OFF_BLK = 128000, BLK = 20480;
constexpr uint32_t B_D = 4096, B_D5 = 3088, B_D7 = 6176, B_D9 = 8224, B_TBL = 14400, B_SP = 18432;
constexpr int T_S = 576, T_F2 = 624, T_F3 = 816;
constexpr uint32_t SMEM_BYTES = OFF_BLK + 5 * BLK + 1024;
enum { BR_FULL = 0, BR_EMPTY = 5, BR_WO = 10, BR_PUB = 12, BR_PAR = 13, BR_U2 = 14, BR_OFULL = 18, BR_OEMPTY = 22, BR_GEMM = 26, BR_OSTG = 27, BR_UIN = 28,
       BR_U = 29, BR_DRDY = 30, BR_KGEN = 35, BR_YSTG = 36, BR_FREE = 41, BR_YIN = 46, BR_EPOCH = 47, BR_COUNT = 48 };
constexpr uint32_t OFF_EPOCH = OFF_BAR + 8 * BR_COUNT;

__device__ __forceinline__ long long clk64() { long long t; asm volatile("mov.u64 %0, %%clock64;" : "=l"(t) :: "memory"); return t; }
__device__ __forceinline__ uint32_t smem_u32(const void* p) { return (uint32_t)__cvta_generic_to_shared(p); }
__device__ __forceinline__ uint64_t mkdesc(uint32_t addr, uint32_t lbo, uint32_t sbo, uint32_t swz) {
  return (uint64_t)((addr & 0x3FFFF) >> 4) | ((uint64_t)(lbo >> 4) << 16) | ((uint64_t)(sbo >> 4) << 32) | ((uint64_t)swz << 62);
}
__device__ __forceinline__ void mbar_init(uint32_t bar, uint32_t cnt) { asm volatile("mbarrier.init.shared::cta.b64 [%0], %1;" :: "r"(bar), "r"(cnt) : "memory"); }
__device__ __forceinline__ void mbar_expect_tx(uint32_t bar, uint32_t bytes) { asm volatile("mbarrier.arrive.expect_tx.shared::cta.b64 _, [%0], %1;" :: "r"(bar), "r"(bytes) : "memory"); }
__device__ __forceinline__ void mbar_arrive(uint32_t bar) { asm volatile("mbarrier.arrive.shared::cta.b64 _, [%0];" :: "r"(bar) : "memory"); }
__device__ __forceinline__ void mbar_wait(uint32_t bar, uint32_t parity) {
  asm volatile("{\n.reg .pred p;\n.reg .u32 c;\nmov.u32 c, 0;\n"
    "WL:\nmbarrier.try_wait.parity.shared::cta.b64 p, [%0], %1;\n@p bra WD;\n"
    "add.u32 c, c, 1;\nsetp.lt.u32 p, c, 200000;\n@p bra WL;\nWD:\n}" :: "r"(bar), "r"(parity) : "memory");
}
__device__ __forceinline__ void poll_all(const unsigned* p, unsigned val) {
  asm volatile("{\n.reg .pred p;\n.reg .u32 c, v;\nmov.u32 c, 0;\n"
    "PL:\nld.relaxed.gpu.global.u32 v, [%0];\nsetp.eq.u32 p, v, %1;\nvote.sync.all.pred p, p, 0xffffffff;\n@p bra PD;\n"
    "add.u32 c, c, 1;\nsetp.lt.u32 p, c, 100000;\n@p bra PL;\nPD:\n}" :: "l"(p), "r"(val) : "memory");
}
__device__ __forceinline__ void poll_all_acq(const unsigned* p, unsigned val) {
  asm volatile("{\n.reg .pred p;\n.reg .u32 c, v;\nmov.u32 c, 0;\n"
    "PL:\nld.acquire.gpu.global.u32 v, [%0];\nsetp.eq.u32 p, v, %1;\nvote.sync.all.pred p, p, 0xffffffff;\n@p bra PD;\n"
    "add.u32 c, c, 1;\nsetp.lt.u32 p, c, 100000;\n@p bra PL;\nPD:\n}" :: "l"(p), "r"(val) : "memory");
}
__device__ __forceinline__ unsigned poll_bit(const unsigned* p, unsigned val, unsigned mask) {
  unsigned bal;
  asm volatile("{\n.reg .pred p;\n.reg .u32 c, v;\nmov.u32 c, 0;\n"
    "PL:\nld.relaxed.gpu.global.u32 v, [%1];\nsetp.eq.u32 p, v, %2;\nvote.sync.ballot.b32 %0, p, 0xffffffff;\n"
    "and.b32 v, %0, %3;\nsetp.ne.u32 p, v, 0;\n@p bra PD;\n"
    "add.u32 c, c, 1;\nsetp.lt.u32 p, c, 100000;\n@p bra PL;\nPD:\n}" : "=&r"(bal) : "l"(p), "r"(val), "r"(mask) : "memory");
  return bal;
}
__device__ __forceinline__ void fix128_w0(uint32_t* v, const void* p, uint32_t tag, uint32_t mask) {
  asm volatile("{\n.reg .pred p;\n.reg .u32 c, x;\n.reg .b128 t;\n.reg .b64 lo, hi;\nmov.u32 c, 0;\n"
    "FL:\nxor.b32 x, %0, %5;\nand.b32 x, x, %6;\nsetp.eq.u32 p, x, 0;\n@p bra FD;\n"
    "ld.relaxed.gpu.global.b128 t, [%4];\nmov.b128 {lo, hi}, t;\nmov.b64 {%0, %1}, lo;\nmov.b64 {%2, %3}, hi;\n"
    "add.u32 c, c, 1;\nsetp.lt.u32 p, c, 100000;\n@p bra FL;\nFD:\n}"
    : "+r"(v[0]), "+r"(v[1]), "+r"(v[2]), "+r"(v[3]) : "l"(p), "r"(tag), "r"(mask) : "memory");
}
__device__ __forceinline__ void fix128_w3(uint32_t* v, const void* p, uint32_t tag, uint32_t mask) {
  asm volatile("{\n.reg .pred p;\n.reg .u32 c, x;\n.reg .b128 t;\n.reg .b64 lo, hi;\nmov.u32 c, 0;\n"
    "FL:\nxor.b32 x, %3, %5;\nand.b32 x, x, %6;\nsetp.eq.u32 p, x, 0;\n@p bra FD;\n"
    "ld.relaxed.gpu.global.b128 t, [%4];\nmov.b128 {lo, hi}, t;\nmov.b64 {%0, %1}, lo;\nmov.b64 {%2, %3}, hi;\n"
    "add.u32 c, c, 1;\nsetp.lt.u32 p, c, 100000;\n@p bra FL;\nFD:\n}"
    : "+r"(v[0]), "+r"(v[1]), "+r"(v[2]), "+r"(v[3]) : "l"(p), "r"(tag), "r"(mask) : "memory");
}
__device__ __forceinline__ void fence_acq() { asm volatile("fence.acq_rel.gpu;" ::: "memory"); }
__device__ __forceinline__ bool elect_one() {
  uint32_t p; asm volatile("{\n.reg .pred P;\nelect.sync _|P, 0xffffffff;\nselp.u32 %0, 1, 0, P;\n}" : "=r"(p)); return p;
}
__device__ __forceinline__ void bar_sync(int id, int n) { asm volatile("bar.sync %0, %1;" :: "r"(id), "r"(n) : "memory"); }
__device__ __forceinline__ void fence_async() { asm volatile("fence.proxy.async.shared::cta;" ::: "memory"); }
__device__ __forceinline__ void fence_async_g() { asm volatile("fence.proxy.async.global;" ::: "memory"); }
__device__ __forceinline__ void tma2d(uint32_t dst, const CUtensorMap* m, uint32_t bar, int c0, int c1) {
  asm volatile("cp.async.bulk.tensor.2d.shared::cluster.global.mbarrier::complete_tx::bytes [%0], [%1, {%3, %4}], [%2];"
    :: "r"(dst), "l"(m), "r"(bar), "r"(c0), "r"(c1) : "memory");
}
__device__ __forceinline__ void tma3d(uint32_t dst, const CUtensorMap* m, uint32_t bar, int c0, int c1, int c2) {
  asm volatile("cp.async.bulk.tensor.3d.shared::cluster.global.mbarrier::complete_tx::bytes [%0], [%1, {%3, %4, %5}], [%2];"
    :: "r"(dst), "l"(m), "r"(bar), "r"(c0), "r"(c1), "r"(c2) : "memory");
}
__device__ __forceinline__ void tma4d(uint32_t dst, const CUtensorMap* m, uint32_t bar, int c0, int c1, int c2, int c3) {
  asm volatile("cp.async.bulk.tensor.4d.shared::cluster.global.mbarrier::complete_tx::bytes [%0], [%1, {%3, %4, %5, %6}], [%2];"
    :: "r"(dst), "l"(m), "r"(bar), "r"(c0), "r"(c1), "r"(c2), "r"(c3) : "memory");
}
__device__ __forceinline__ void tma2d_st(const CUtensorMap* m, uint32_t src, int c0, int c1) {
  asm volatile("cp.async.bulk.tensor.2d.global.shared::cta.bulk_group [%0, {%2, %3}], [%1];"
    :: "l"(m), "r"(src), "r"(c0), "r"(c1) : "memory");
}
__device__ __forceinline__ void bulk_ld(uint32_t dst, const void* src, uint32_t bytes, uint32_t bar) {
  asm volatile("cp.async.bulk.shared::cluster.global.mbarrier::complete_tx::bytes [%0], [%1], %2, [%3];"
    :: "r"(dst), "l"(src), "r"(bytes), "r"(bar) : "memory");
}
__device__ __forceinline__ void bulk_st(void* dst, uint32_t src, uint32_t bytes) {
  asm volatile("cp.async.bulk.global.shared::cta.bulk_group [%0], [%1], %2;" :: "l"(dst), "r"(src), "r"(bytes) : "memory");
}
__device__ __forceinline__ void bulk_commit() { asm volatile("cp.async.bulk.commit_group;" ::: "memory"); }
__device__ __forceinline__ void bulk_wait0() { asm volatile("cp.async.bulk.wait_group 0;" ::: "memory"); }
__device__ __forceinline__ void bulk_wait0_read() { asm volatile("cp.async.bulk.wait_group.read 0;" ::: "memory"); }
__device__ __forceinline__ unsigned ld_rlx(const unsigned* p) { unsigned v; asm volatile("ld.relaxed.gpu.global.u32 %0, [%1];" : "=r"(v) : "l"(p) : "memory"); return v; }
__device__ __forceinline__ unsigned ld_acq(const unsigned* p) { unsigned v; asm volatile("ld.acquire.gpu.global.u32 %0, [%1];" : "=r"(v) : "l"(p) : "memory"); return v; }
__device__ __forceinline__ void st_rlx(unsigned* p, unsigned v) { asm volatile("st.relaxed.gpu.global.u32 [%0], %1;" :: "l"(p), "r"(v) : "memory"); }
__device__ __forceinline__ void st_rel(unsigned* p, unsigned v) { asm volatile("st.release.gpu.global.u32 [%0], %1;" :: "l"(p), "r"(v) : "memory"); }
__device__ __forceinline__ void ld128_rlx(uint32_t* v, const void* p) {
  asm volatile("{\n.reg .b128 t;\n.reg .b64 lo, hi;\nld.relaxed.gpu.global.b128 t, [%4];\nmov.b128 {lo, hi}, t;\n"
    "mov.b64 {%0, %1}, lo;\nmov.b64 {%2, %3}, hi;\n}" : "=r"(v[0]), "=r"(v[1]), "=r"(v[2]), "=r"(v[3]) : "l"(p) : "memory");
}
__device__ __forceinline__ void st128_rlx(void* p, const uint32_t* v) {
  asm volatile("{\n.reg .b128 t;\n.reg .b64 lo, hi;\nmov.b64 lo, {%1, %2};\nmov.b64 hi, {%3, %4};\nmov.b128 t, {lo, hi};\n"
    "st.relaxed.gpu.global.b128 [%0], t;\n}" :: "l"(p), "r"(v[0]), "r"(v[1]), "r"(v[2]), "r"(v[3]) : "memory");
}
__device__ __forceinline__ uint32_t lds32(uint32_t a) { uint32_t v; asm volatile("ld.shared.u32 %0, [%1];" : "=r"(v) : "r"(a) : "memory"); return v; }
__device__ __forceinline__ uint32_t lds32v(uint32_t a) { uint32_t v; asm volatile("ld.volatile.shared.u32 %0, [%1];" : "=r"(v) : "r"(a) : "memory"); return v; }
__device__ __forceinline__ uint32_t cpa(uint32_t a, uint32_t one) { uint32_t v; asm volatile("mul.lo.u32 %0, %1, %2;" : "=r"(v) : "r"(a), "r"(one)); return v; }
__device__ __forceinline__ uint32_t cpb(uint32_t a, uint32_t zero) { uint32_t v; asm volatile("or.b32 %0, %1, %2;" : "=r"(v) : "r"(a), "r"(zero)); return v; }
__device__ __forceinline__ uint32_t lds16(uint32_t a) { uint16_t v; asm volatile("ld.shared.u16 %0, [%1];" : "=h"(v) : "r"(a) : "memory"); return v; }
__device__ __forceinline__ float ldsf(uint32_t a) { float v; asm volatile("ld.shared.f32 %0, [%1];" : "=f"(v) : "r"(a) : "memory"); return v; }
__device__ __forceinline__ void lds128(uint32_t* v, uint32_t a) { asm volatile("ld.shared.v4.u32 {%0,%1,%2,%3}, [%4];" : "=r"(v[0]), "=r"(v[1]), "=r"(v[2]), "=r"(v[3]) : "r"(a) : "memory"); }
__device__ __forceinline__ void sts32(uint32_t a, uint32_t v) { asm volatile("st.shared.u32 [%0], %1;" :: "r"(a), "r"(v) : "memory"); }
__device__ __forceinline__ void sts16(uint32_t a, uint32_t v) { asm volatile("st.shared.u16 [%0], %1;" :: "r"(a), "h"((uint16_t)v) : "memory"); }
__device__ __forceinline__ void sts64f(uint32_t a, float x, float y) { asm volatile("st.shared.v2.f32 [%0], {%1,%2};" :: "r"(a), "f"(x), "f"(y) : "memory"); }
__device__ __forceinline__ void sts128(uint32_t a, uint32_t x, uint32_t y, uint32_t z, uint32_t w) { asm volatile("st.shared.v4.u32 [%0], {%1,%2,%3,%4};" :: "r"(a), "r"(x), "r"(y), "r"(z), "r"(w) : "memory"); }
__device__ __forceinline__ void stsm4(uint32_t a, uint32_t r0, uint32_t r1, uint32_t r2, uint32_t r3) {
  asm volatile("stmatrix.sync.aligned.m8n8.x4.shared.b16 [%0], {%1,%2,%3,%4};" :: "r"(a), "r"(r0), "r"(r1), "r"(r2), "r"(r3) : "memory");
}
__device__ __forceinline__ void stsm4t(uint32_t a, uint32_t r0, uint32_t r1, uint32_t r2, uint32_t r3) {
  asm volatile("stmatrix.sync.aligned.m8n8.x4.trans.shared.b16 [%0], {%1,%2,%3,%4};" :: "r"(a), "r"(r0), "r"(r1), "r"(r2), "r"(r3) : "memory");
}
__device__ __forceinline__ void ldsm4t(uint32_t* r, uint32_t a) {
  asm volatile("ldmatrix.sync.aligned.m8n8.x4.trans.shared.b16 {%0,%1,%2,%3}, [%4];" : "=r"(r[0]), "=r"(r[1]), "=r"(r[2]), "=r"(r[3]) : "r"(a) : "memory");
}
__device__ __forceinline__ void ldsm4(uint32_t* r, uint32_t a) {
  asm volatile("ldmatrix.sync.aligned.m8n8.x4.shared.b16 {%0,%1,%2,%3}, [%4];" : "=r"(r[0]), "=r"(r[1]), "=r"(r[2]), "=r"(r[3]) : "r"(a) : "memory");
}
__device__ __forceinline__ void mma16816(float* d, const uint32_t* a, const uint32_t* b) {
  asm volatile("mma.sync.aligned.m16n8k16.row.col.f32.bf16.bf16.f32 {%0,%1,%2,%3}, {%4,%5,%6,%7}, {%8,%9}, {%0,%1,%2,%3};"
    : "+f"(d[0]), "+f"(d[1]), "+f"(d[2]), "+f"(d[3]) : "r"(a[0]), "r"(a[1]), "r"(a[2]), "r"(a[3]), "r"(b[0]), "r"(b[1]));
}
__device__ __forceinline__ uint32_t pack2(float lo, float hi) { uint32_t r; asm("cvt.rn.bf16x2.f32 %0, %1, %2;" : "=r"(r) : "f"(hi), "f"(lo)); return r; }
__device__ __forceinline__ uint32_t packh(float lo, float hi) { uint32_t r; asm("cvt.rn.f16x2.f32 %0, %1, %2;" : "=r"(r) : "f"(hi), "f"(lo)); return r; }
__device__ __forceinline__ uint32_t hcmul(uint32_t x, uint32_t zp, uint32_t zq) {
  const __half2 xx = *reinterpret_cast<__half2*>(&x);
  const __half2 r = __hfma2(__high2half2(xx), *reinterpret_cast<__half2*>(&zq), __hmul2(__low2half2(xx), *reinterpret_cast<__half2*>(&zp)));
  return *reinterpret_cast<const uint32_t*>(&r);
}
__device__ __forceinline__ void hcm2(uint32_t xr, uint32_t xi, uint32_t z, uint32_t& pr, uint32_t& pi) {
  const __half2 a = *reinterpret_cast<__half2*>(&xr), b = *reinterpret_cast<__half2*>(&xi), zz = *reinterpret_cast<__half2*>(&z);
  const __half2 re = __hfma2(__hneg2(b), __high2half2(zz), __hmul2(a, __low2half2(zz)));
  const __half2 im = __hfma2(a, __high2half2(zz), __hmul2(b, __low2half2(zz)));
  pr = *reinterpret_cast<const uint32_t*>(&re); pi = *reinterpret_cast<const uint32_t*>(&im);
}
__device__ __forceinline__ void sts64(uint32_t a, uint32_t x, uint32_t y) { asm volatile("st.shared.v2.u32 [%0], {%1,%2};" :: "r"(a), "r"(x), "r"(y) : "memory"); }
__device__ __forceinline__ void lds64(uint32_t* v, uint32_t a) { asm volatile("ld.shared.v2.u32 {%0,%1}, [%2];" : "=r"(v[0]), "=r"(v[1]) : "r"(a) : "memory"); }
__device__ __forceinline__ float bf_lo(uint32_t v) { return __uint_as_float(v << 16); }
__device__ __forceinline__ float bf_hi(uint32_t v) { return __uint_as_float(v & 0xffff0000u); }
__device__ __forceinline__ float bf_round(float x) { return bf_lo(pack2(x, 0.f)); }
__device__ __forceinline__ float ex2(float x) { float r; asm("ex2.approx.ftz.f32 %0, %1;" : "=f"(r) : "f"(x)); return r; }
__device__ __forceinline__ float phi(float t, float l2e = 1.44269504089f) { float e = ex2(t * l2e); return (t > 0.f ? t + 1.f : e) + 1e-6f; }
__device__ __forceinline__ void wg_fence() { asm volatile("wgmma.fence.sync.aligned;" ::: "memory"); }
__device__ __forceinline__ void wg_commit() { asm volatile("wgmma.commit_group.sync.aligned;" ::: "memory"); }
template <int N> __device__ __forceinline__ void wg_wait() { asm volatile("wgmma.wait_group.sync.aligned %0;" :: "n"(N) : "memory"); }
template <int N> __device__ __forceinline__ void pin(float* a) {
  #pragma unroll
  for (int i = 0; i < N; i++) asm volatile("" : "+f"(a[i]) :: "memory");
}
__device__ __forceinline__ int opaque(int v) { asm volatile("" : "+r"(v)); return v; }
template <int N> __device__ __forceinline__ void zero(float* a) {
  #pragma unroll
  for (int i = 0; i < N; i++) asm volatile("mov.b32 %0, 0;" : "=f"(a[i]));
}
template <int N> __device__ __forceinline__ void pinu(uint32_t* a) {
  #pragma unroll
  for (int i = 0; i < N; i++) asm volatile("" : "+r"(a[i]) :: "memory");
}
__device__ __forceinline__ void cexp_t(float lg2mag, float turns, float& re, float& im) {
  float m = ex2(lg2mag);
  float fr = (turns - __fadd_rn(__fadd_rn(turns, 12582912.f), -12582912.f)) * 6.283185307f;
  re = m * __cosf(fr); im = m * __sinf(fr);
}
__device__ __forceinline__ void cmul(float ar, float ai, float br, float bi, float& cr, float& ci) {
  cr = fmaf(ar, br, -ai * bi); ci = fmaf(ar, bi, ai * br);
}

__device__ __forceinline__ void wg_ss192_tb(float* d, uint64_t da, uint64_t db, int scale_d) {
  asm volatile("{\n.reg .pred p;\nsetp.ne.b32 p, %98, 0;\n"
    "wgmma.mma_async.sync.aligned.m64n192k16.f32.bf16.bf16 "
    "{%0, %1, %2, %3, %4, %5, %6, %7, %8, %9, %10, %11, %12, %13, %14, %15, %16, %17, %18, %19, %20, %21, %22, %23, %24, %25, %26, %27, %28, %29, %30, %31, %32, %33, %34, %35, %36, %37, %38, %39, %40, %41, %42, %43, %44, %45, %46, %47, %48, %49, %50, %51, %52, %53, %54, %55, %56, %57, %58, %59, %60, %61, %62, %63, %64, %65, %66, %67, %68, %69, %70, %71, %72, %73, %74, %75, %76, %77, %78, %79, %80, %81, %82, %83, %84, %85, %86, %87, %88, %89, %90, %91, %92, %93, %94, %95}, %96, %97, p, 1, 1, 0, 1;\n}\n"
    : "+f"(d[0]), "+f"(d[1]), "+f"(d[2]), "+f"(d[3]), "+f"(d[4]), "+f"(d[5]), "+f"(d[6]), "+f"(d[7]), "+f"(d[8]), "+f"(d[9]), "+f"(d[10]), "+f"(d[11]), "+f"(d[12]), "+f"(d[13]), "+f"(d[14]), "+f"(d[15]), "+f"(d[16]), "+f"(d[17]), "+f"(d[18]), "+f"(d[19]), "+f"(d[20]), "+f"(d[21]), "+f"(d[22]), "+f"(d[23]), "+f"(d[24]), "+f"(d[25]), "+f"(d[26]), "+f"(d[27]), "+f"(d[28]), "+f"(d[29]), "+f"(d[30]), "+f"(d[31]), "+f"(d[32]), "+f"(d[33]), "+f"(d[34]), "+f"(d[35]), "+f"(d[36]), "+f"(d[37]), "+f"(d[38]), "+f"(d[39]), "+f"(d[40]), "+f"(d[41]), "+f"(d[42]), "+f"(d[43]), "+f"(d[44]), "+f"(d[45]), "+f"(d[46]), "+f"(d[47]), "+f"(d[48]), "+f"(d[49]), "+f"(d[50]), "+f"(d[51]), "+f"(d[52]), "+f"(d[53]), "+f"(d[54]), "+f"(d[55]), "+f"(d[56]), "+f"(d[57]), "+f"(d[58]), "+f"(d[59]), "+f"(d[60]), "+f"(d[61]), "+f"(d[62]), "+f"(d[63]), "+f"(d[64]), "+f"(d[65]), "+f"(d[66]), "+f"(d[67]), "+f"(d[68]), "+f"(d[69]), "+f"(d[70]), "+f"(d[71]), "+f"(d[72]), "+f"(d[73]), "+f"(d[74]), "+f"(d[75]), "+f"(d[76]), "+f"(d[77]), "+f"(d[78]), "+f"(d[79]), "+f"(d[80]), "+f"(d[81]), "+f"(d[82]), "+f"(d[83]), "+f"(d[84]), "+f"(d[85]), "+f"(d[86]), "+f"(d[87]), "+f"(d[88]), "+f"(d[89]), "+f"(d[90]), "+f"(d[91]), "+f"(d[92]), "+f"(d[93]), "+f"(d[94]), "+f"(d[95])
    : "l"(da), "l"(db), "r"(scale_d));
}
__device__ __forceinline__ void wg_ss48_tb(float* d, uint64_t da, uint64_t db, int scale_d) {
  asm volatile("{\n.reg .pred p;\nsetp.ne.b32 p, %26, 0;\n"
    "wgmma.mma_async.sync.aligned.m64n48k16.f32.bf16.bf16 "
    "{%0, %1, %2, %3, %4, %5, %6, %7, %8, %9, %10, %11, %12, %13, %14, %15, %16, %17, %18, %19, %20, %21, %22, %23}, %24, %25, p, 1, 1, 0, 1;\n}\n"
    : "+f"(d[0]), "+f"(d[1]), "+f"(d[2]), "+f"(d[3]), "+f"(d[4]), "+f"(d[5]), "+f"(d[6]), "+f"(d[7]), "+f"(d[8]), "+f"(d[9]), "+f"(d[10]), "+f"(d[11]), "+f"(d[12]), "+f"(d[13]), "+f"(d[14]), "+f"(d[15]), "+f"(d[16]), "+f"(d[17]), "+f"(d[18]), "+f"(d[19]), "+f"(d[20]), "+f"(d[21]), "+f"(d[22]), "+f"(d[23])
    : "l"(da), "l"(db), "r"(scale_d));
}
__device__ __forceinline__ void wg_ss48_tt(float* d, uint64_t da, uint64_t db, int scale_d) {
  asm volatile("{\n.reg .pred p;\nsetp.ne.b32 p, %26, 0;\n"
    "wgmma.mma_async.sync.aligned.m64n48k16.f32.bf16.bf16 "
    "{%0, %1, %2, %3, %4, %5, %6, %7, %8, %9, %10, %11, %12, %13, %14, %15, %16, %17, %18, %19, %20, %21, %22, %23}, %24, %25, p, 1, 1, 1, 1;\n}\n"
    : "+f"(d[0]), "+f"(d[1]), "+f"(d[2]), "+f"(d[3]), "+f"(d[4]), "+f"(d[5]), "+f"(d[6]), "+f"(d[7]), "+f"(d[8]), "+f"(d[9]), "+f"(d[10]), "+f"(d[11]), "+f"(d[12]), "+f"(d[13]), "+f"(d[14]), "+f"(d[15]), "+f"(d[16]), "+f"(d[17]), "+f"(d[18]), "+f"(d[19]), "+f"(d[20]), "+f"(d[21]), "+f"(d[22]), "+f"(d[23])
    : "l"(da), "l"(db), "r"(scale_d));
}
__device__ __forceinline__ void wg_rs88_tb(float* d, const uint32_t* a, uint64_t db, int scale_d) {
  asm volatile("{\n.reg .pred p;\nsetp.ne.b32 p, %49, 0;\n"
    "wgmma.mma_async.sync.aligned.m64n88k16.f32.bf16.bf16 "
    "{%0, %1, %2, %3, %4, %5, %6, %7, %8, %9, %10, %11, %12, %13, %14, %15, %16, %17, %18, %19, %20, %21, %22, %23, %24, %25, %26, %27, %28, %29, %30, %31, %32, %33, %34, %35, %36, %37, %38, %39, %40, %41, %42, %43}, {%44, %45, %46, %47}, %48, p, 1, 1, 1;\n}\n"
    : "+f"(d[0]), "+f"(d[1]), "+f"(d[2]), "+f"(d[3]), "+f"(d[4]), "+f"(d[5]), "+f"(d[6]), "+f"(d[7]), "+f"(d[8]), "+f"(d[9]), "+f"(d[10]), "+f"(d[11]), "+f"(d[12]), "+f"(d[13]), "+f"(d[14]), "+f"(d[15]), "+f"(d[16]), "+f"(d[17]), "+f"(d[18]), "+f"(d[19]), "+f"(d[20]), "+f"(d[21]), "+f"(d[22]), "+f"(d[23]), "+f"(d[24]), "+f"(d[25]), "+f"(d[26]), "+f"(d[27]), "+f"(d[28]), "+f"(d[29]), "+f"(d[30]), "+f"(d[31]), "+f"(d[32]), "+f"(d[33]), "+f"(d[34]), "+f"(d[35]), "+f"(d[36]), "+f"(d[37]), "+f"(d[38]), "+f"(d[39]), "+f"(d[40]), "+f"(d[41]), "+f"(d[42]), "+f"(d[43])
    : "r"(a[0]), "r"(a[1]), "r"(a[2]), "r"(a[3]), "l"(db), "r"(scale_d));
}
__device__ __forceinline__ void wg_rs64_tb(float* d, const uint32_t* a, uint64_t db, int scale_d) {
  asm volatile("{\n.reg .pred p;\nsetp.ne.b32 p, %37, 0;\n"
    "wgmma.mma_async.sync.aligned.m64n64k16.f32.bf16.bf16 "
    "{%0, %1, %2, %3, %4, %5, %6, %7, %8, %9, %10, %11, %12, %13, %14, %15, %16, %17, %18, %19, %20, %21, %22, %23, %24, %25, %26, %27, %28, %29, %30, %31}, {%32, %33, %34, %35}, %36, p, 1, 1, 1;\n}\n"
    : "+f"(d[0]), "+f"(d[1]), "+f"(d[2]), "+f"(d[3]), "+f"(d[4]), "+f"(d[5]), "+f"(d[6]), "+f"(d[7]), "+f"(d[8]), "+f"(d[9]), "+f"(d[10]), "+f"(d[11]), "+f"(d[12]), "+f"(d[13]), "+f"(d[14]), "+f"(d[15]), "+f"(d[16]), "+f"(d[17]), "+f"(d[18]), "+f"(d[19]), "+f"(d[20]), "+f"(d[21]), "+f"(d[22]), "+f"(d[23]), "+f"(d[24]), "+f"(d[25]), "+f"(d[26]), "+f"(d[27]), "+f"(d[28]), "+f"(d[29]), "+f"(d[30]), "+f"(d[31])
    : "r"(a[0]), "r"(a[1]), "r"(a[2]), "r"(a[3]), "l"(db), "r"(scale_d));
}
__device__ __forceinline__ void wg_ss48_tt_h(float* d, uint64_t da, uint64_t db, int scale_d) {
  asm volatile("{\n.reg .pred p;\nsetp.ne.b32 p, %26, 0;\n"
    "wgmma.mma_async.sync.aligned.m64n48k16.f32.f16.f16 "
    "{%0, %1, %2, %3, %4, %5, %6, %7, %8, %9, %10, %11, %12, %13, %14, %15, %16, %17, %18, %19, %20, %21, %22, %23}, %24, %25, p, 1, 1, 1, 1;\n}\n"
    : "+f"(d[0]), "+f"(d[1]), "+f"(d[2]), "+f"(d[3]), "+f"(d[4]), "+f"(d[5]), "+f"(d[6]), "+f"(d[7]), "+f"(d[8]), "+f"(d[9]), "+f"(d[10]), "+f"(d[11]), "+f"(d[12]), "+f"(d[13]), "+f"(d[14]), "+f"(d[15]), "+f"(d[16]), "+f"(d[17]), "+f"(d[18]), "+f"(d[19]), "+f"(d[20]), "+f"(d[21]), "+f"(d[22]), "+f"(d[23])
    : "l"(da), "l"(db), "r"(scale_d));
}
__device__ __forceinline__ void wg_rs16_tb(float* d, const uint32_t* a, uint64_t db, int scale_d) {
  asm volatile("{\n.reg .pred p;\nsetp.ne.b32 p, %13, 0;\n"
    "wgmma.mma_async.sync.aligned.m64n16k16.f32.bf16.bf16 "
    "{%0, %1, %2, %3, %4, %5, %6, %7}, {%8, %9, %10, %11}, %12, p, 1, 1, 1;\n}\n"
    : "+f"(d[0]), "+f"(d[1]), "+f"(d[2]), "+f"(d[3]), "+f"(d[4]), "+f"(d[5]), "+f"(d[6]), "+f"(d[7])
    : "r"(a[0]), "r"(a[1]), "r"(a[2]), "r"(a[3]), "l"(db), "r"(scale_d));
}

struct Params {
  const __nv_bfloat16 *u, *logA, *Aim, *Cr, *Ci, *logdt, *dskip;
};

__device__ __forceinline__ void load_quad(uint32_t* A, uint32_t addr) {
  A[0] = lds32v(addr); A[1] = lds32v(addr + 32); A[2] = lds32v(addr - 32); A[3] = lds32v(addr);
}

__global__ void __launch_bounds__(512, 1)
fused_kernel(const __grid_constant__ CUtensorMap mx, const __grid_constant__ CUtensorMap mw, const __grid_constant__ CUtensorMap mr,
             const __grid_constant__ CUtensorMap mwo, const __grid_constant__ CUtensorMap mwr, const __grid_constant__ CUtensorMap mo64,
             const __grid_constant__ CUtensorMap mo16, const __grid_constant__ CUtensorMap mw64, const __grid_constant__ CUtensorMap msa,
             const __grid_constant__ CUtensorMap msb, const __grid_constant__ CUtensorMap mout, const Params prm) {
  extern __shared__ unsigned char smem_raw[];
  const uint32_t sb = (smem_u32(smem_raw) + 1023) & ~1023u;
  const int tid = threadIdx.x, lane = tid & 31;
  const int wg = __shfl_sync(0xffffffff, tid >> 7, 0), warp = __shfl_sync(0xffffffff, tid >> 5, 0);
  const int cta = blockIdx.x, r = cta >> 3, c = cta & 7;
  const uint32_t bars = sb + OFF_BAR;
#define BAR(i) (bars + 8 * (i))

  const bool sw64 = ((c + 1) & 2) != 0;
  const CUtensorMap* mwp = sw64 ? &mw64 : &mw;
  const int mcol = (c * 80 + (c & 1) * 16) >> (sw64 ? 5 : 6), rcol = c * 80 + ((c & 1) ? 0 : 64);
  auto issue1 = [&](int kb) {
    const uint32_t st = sb + (kb % 5) * W_SLOT, fb = BAR(BR_FULL + kb % 5);
    mbar_expect_tx(fb, (kb & 1) ? W_SLOT : W_SLOT + 16384);
    if (!(kb & 1)) tma2d(sb + OFF_X + ((kb >> 1) % 3) * 16384, &mx, fb, kb * 32, r * 128);
    tma4d(st, mwp, fb, 0, kb * 32, mcol, 0);
    tma3d(st + 12288, &mr, fb, rcol, kb * 32, 0);
  };

  if (warp == 12) {
    if (elect_one()) {
      #pragma unroll
      for (int i = 0; i < BR_COUNT; i++) {
        int cnt = 1;
        if (i >= BR_EMPTY && i < BR_EMPTY + 5) cnt = 2;
        if (i >= BR_OEMPTY && i < BR_OEMPTY + 4) cnt = 8;
        if (i == BR_OSTG) cnt = 256;
        if (i >= BR_DRDY && i < BR_DRDY + 5) cnt = 96;
        if (i >= BR_YSTG && i < BR_YSTG + 5) cnt = i == BR_YSTG + 4 ? 128 : 32;
        mbar_init(BAR(i), cnt);
      }
      asm volatile("fence.mbarrier_init.release.cluster;" ::: "memory");
      if (EN_ATT) issue1(0);
    }
  }
  if (warp == 13 && lane < 8) {
    const CUtensorMap* mp = lane <= 1 ? &msb : lane == 2 ? &mwo : lane == 3 ? &mwr : lane == 4 ? &msa : lane == 5 ? &mout : lane == 6 ? &mo64 : &mo16;
    asm volatile("prefetch.tensormap [%0];" :: "l"(mp) : "memory");
  }
  unsigned short ldt = 0, dsk0 = 0;
  uint4 pv[3];
  if (EN_SSM && wg == 2) {
    const int ai = warp & 3;
    const uint4* pp = reinterpret_cast<const uint4*>((ai == 0 ? prm.logA : ai == 1 ? prm.Aim : ai == 2 ? prm.Cr : prm.Ci) + (c * 80 + r * 5) * 128);
    pv[0] = __ldg(pp + lane); pv[1] = __ldg(pp + 32 + lane); pv[2] = __ldg(pp + 64 + (lane & 15));
    const int kq = c * 80 + r * 5 + min(tid - 256, 4);
    ldt = __ldg(reinterpret_cast<const unsigned short*>(prm.logdt) + kq); dsk0 = __ldg(reinterpret_cast<const unsigned short*>(prm.dskip) + kq);
  }
  __syncthreads();

  if (wg == 3) {
    asm volatile("setmaxnreg.dec.sync.aligned.u32 56;");
    if (warp == 12) {
      if (EN_ATT) {
      #pragma unroll
      for (int kb = 1; kb < 20; kb++) {
        if (kb >= 5) mbar_wait(BAR(BR_EMPTY + kb % 5), ((kb / 5) & 1) ^ 1);
        if (elect_one()) issue1(kb);
      }
      auto chunk_of = [&](int i) { return i == 0 ? c : (i == 7 ? (c ^ 1) : (((c & 6) + 1 + i) & 7)); };
      mbar_wait(BAR(BR_EPOCH), 0);
      const unsigned epoch = lds32(sb + OFF_EPOCH);
      const unsigned* fo = &g_flag[(24 + r) * 32 + (lane & 7)];
      unsigned seen = __ballot_sync(0xffffffff, ld_rlx(fo) == epoch);
      mbar_wait(BAR(BR_GEMM), 0);
      if (elect_one()) {
        mbar_expect_tx(BAR(BR_WO), 20480 + 5 * 10240);
        #pragma unroll
        for (int i = 0; i < 5; i++) tma2d(sb + OFF_WOM + i * 10240, &mwo, BAR(BR_WO), c * 64, i * 80);
        #pragma unroll
        for (int i = 0; i < 4; i++) tma2d(sb + i * 5120, &mwr, BAR(BR_WO), 512 + c * 16, i * 160);
      }
      mbar_wait(BAR(BR_PUB), 0);
      if (elect_one()) {
        mbar_expect_tx(BAR(BR_WO + 1), 3 * 10240);
        #pragma unroll
        for (int i = 5; i < 8; i++) tma2d(sb + OFF_WOM + i * 10240, &mwo, BAR(BR_WO + 1), c * 64, i * 80);
      }
      mbar_wait(BAR(BR_OSTG), 0);
      if (elect_one()) {
        bulk_st(&g_o[cta * 1280], sb + OFF_EXTRA, 20480);
        bulk_commit();
        bulk_wait0();
        st_rlx(&g_flag[(24 + r) * 32 + c], epoch);
        TS(20);
      }
      __syncwarp();
      #pragma unroll
      for (int i = 0; i < 7; i++) {
        const int src = chunk_of(i + 1);
        if (!((seen >> src) & 1)) seen = poll_bit(fo, epoch, 1u << src);
        if (i < 2) { if (EN_SSM) mbar_wait(BAR(BR_FREE + 4 - i), 0); }
        else if (i > 3) mbar_wait(BAR(BR_OEMPTY + i - 4), 0);
        if (elect_one()) {
          fence_async_g();
          const uint32_t slot = (i & 3) == 3 ? sb + OFF_EXTRA : sb + OFF_BLK + (4 - (i & 3)) * BLK;
          mbar_expect_tx(BAR(BR_OFULL + (i & 3)), 20480);
          bulk_ld(slot, &g_o[(r * 8 + src) * 1280], 20480, BAR(BR_OFULL + (i & 3)));
          if (i == 0) TS(21);
          if (i == 6) { TS(22); DUMP(20, 30); }
        }
        __syncwarp();
      }
      }
    } else {
      const int hw = warp - 13, ht = tid - 416;
      unsigned epoch = 0;
      if (EN_SSM && ht < 80) {
        const int rr = ht / 10, cq = ht - rr * 10;
        const char* gs = reinterpret_cast<const char*>(prm.u) + (size_t)(r * 128 + rr) * 1280 + c * 160 + cq * 16;
        const uint32_t ds = sb + OFF_BLK + 4 * BLK + B_D + ht * 16;
        #pragma unroll
        for (int i = 0; i < 16; i++)
          asm volatile("cp.async.cg.shared.global [%0], [%1], 16;" :: "r"(ds - (i >> 3) * BLK + (i & 7) * 1280), "l"(gs + i * 10240) : "memory");
      }
      if (hw == 0) {
        if (lane == 0) {
          epoch = ld_rlx(&g_epoch[cta]) + 1;
          st_rlx(&g_epoch[cta], epoch);
          sts32(sb + OFF_EPOCH, epoch);
          mbar_arrive(BAR(BR_EPOCH));
        }
        epoch = __shfl_sync(0xffffffff, epoch, 0);
      }
      if (EN_SSM) {
      asm volatile("cp.async.wait_all;" ::: "memory");
      bar_sync(5, 96);
      if (ht == 0) TS(36);
      {
        const int mi = lane >> 3, rw = lane & 7;
        const uint32_t lo = (uint32_t)((8 * (rw >> 1) + 2 * mi + (rw & 1)) * 160);
        uint4* gp = reinterpret_cast<uint4*>(g_uy + (size_t)(c * 80 + hw * 8 + (lane >> 2)) * 2048 + r * 128 + (lane & 3) * 8);
        const uint32_t sa = sb + OFF_BLK + 3 * BLK + B_D + lo + hw * 16;
        #pragma unroll
        for (int i = 0; i < 4; i++) {
          if (i < 3 || hw == 0) {
            uint32_t v[4][4];
            #pragma unroll
            for (int q = 0; q < 4; q++) ldsm4t(v[q], sa + (1 - (q >> 1)) * BLK + (q & 1) * 5120 + i * 48);
            #pragma unroll
            for (int q = 0; q < 4; q++) {
              gp[i * 6144 + q * 4] = make_uint4(v[q][0], v[q][1], v[q][2], v[q][3]);
              if (q & 1) __nanosleep(U_PACE);
            }
          }
        }
      }
      if (ht == 0) TS(37);
      bar_sync(5, 96);
      if (ht == 0) TS(38);
      if (hw == 0) {
        if (lane == 0) { st_rel(&g_flag[(8 + c) * 32 + r], epoch); TS(30); }
        __syncwarp();
        poll_all_acq(&g_flag[(8 + c) * 32 + (lane & 15)], epoch);
        if (lane == 0) {
          fence_async_g();
          mbar_expect_tx(BAR(BR_U), 12288);
          #pragma unroll
          for (int k = 4; k >= 2; k--) tma2d(sb + OFF_BLK + k * BLK, &msb, BAR(BR_U), 0, (c * 80 + r * 5 + k) * 32);
          TS(31);
        }
        __syncwarp();
      }
      mbar_wait(BAR(BR_U), 0);
      if (ht == 0) TS(39);
      #pragma unroll 1
      for (int k = 4; k >= 0; k--) {
        if (k == 2) {
          mbar_wait(BAR(BR_KGEN), 0);
          if (ht == 0) {
            fence_async();
            mbar_expect_tx(BAR(BR_U2), 8192);
            tma2d(sb + OFF_BLK + BLK, &msb, BAR(BR_U2), 0, (c * 80 + r * 5 + 1) * 32);
            tma2d(sb + OFF_BLK, &msb, BAR(BR_U2), 0, (c * 80 + r * 5) * 32);
          }
          __syncwarp();
        }
        if (k == 1) mbar_wait(BAR(BR_U2), 0);
        const uint32_t blk = sb + OFF_BLK + k * BLK;
        #pragma unroll 1
        for (int kap = ht; kap < 192; kap += 96) {
          float P[33];
          P[0] = 0.f;
          #pragma unroll
          for (int q = 0; q < 4; q++) {
            const int ch = kap - 3 + q;
            uint32_t v[4];
            lds128(v, blk + (uint32_t)((ch >> 3) * 128 + (((ch & 7) ^ ((ch >> 3) & 7)) << 4)));
            #pragma unroll
            for (int e = 0; e < 4; e++) {
              P[q * 8 + 2 * e + 1] = P[q * 8 + 2 * e] + bf_lo(v[e]);
              P[q * 8 + 2 * e + 2] = P[q * 8 + 2 * e + 1] + bf_hi(v[e]);
            }
          }
#define WIN(lo, hi, e) (P[25 + (e) - (lo)] - P[24 + (e) - (hi)])
#define WIN8(lo, hi) pack2(WIN(lo, hi, 0), WIN(lo, hi, 1)), pack2(WIN(lo, hi, 2), WIN(lo, hi, 3)), pack2(WIN(lo, hi, 4), WIN(lo, hi, 5)), pack2(WIN(lo, hi, 6), WIN(lo, hi, 7))
          const uint32_t o2 = blk + B_D + (kap & 1) * 1552 + (kap >> 1) * 16;
          sts128(o2, WIN8(3, 5));
          sts128(o2 + B_D5, WIN8(6, 10));
          if (kap < 128) {
            const uint32_t o = blk + B_D + (kap & 1) * 1024 + (kap >> 1) * 16;
            sts128(o + B_D7, WIN8(5, 11));
            sts128(o + B_D9, WIN8(12, 20));
          }
        }
        if (ht < 2) sts128(blk + B_D + ht * B_D5 + 1536, 0, 0, 0, 0);
        mbar_arrive(BAR(BR_DRDY + k));
      }
      if (ht == 0) TS(32);
      if (hw == 0) {
        mbar_wait(BAR(BR_YSTG + 4), 0);
        if (elect_one()) {
          tma2d_st(&msb, sb + OFF_BLK + 4 * BLK, 0, (640 + c * 80 + r * 5 + 4) * 32);
          bulk_commit(); bulk_wait0_read();
          mbar_arrive(BAR(BR_FREE + 4));
        }
        __syncwarp();
        #pragma unroll
        for (int k = 3; k >= 0; k--) {
          mbar_wait(BAR(BR_YSTG + k), 0);
          if (elect_one()) tma2d_st(&msb, sb + OFF_BLK + k * BLK, 0, (640 + c * 80 + r * 5 + k) * 32);
        }
        if (elect_one()) {
          bulk_commit(); bulk_wait0_read();
          mbar_arrive(BAR(BR_FREE + 3));
          mbar_expect_tx(BAR(BR_YIN), 20480);
          bulk_wait0();
          st_rel(&g_flag[(16 + c) * 32 + r], epoch);
          TS(33);
        }
        __syncwarp();
        poll_all_acq(&g_flag[(16 + c) * 32 + (lane & 15)], epoch);
        if (elect_one()) {
          fence_async_g();
          tma2d(sb + OFF_BLK + BLK, &msa, BAR(BR_YIN), r * 128, 640 + c * 80);
          tma2d(sb + OFF_BLK + BLK + 10240, &msa, BAR(BR_YIN), r * 128 + 64, 640 + c * 80);
          TS(34);
        }
        __syncwarp();
      }
      {
        const int mi = lane >> 3, rw = lane & 7;
        const uint32_t sa = sb + OFF_BLK + BLK + (hw * 8 + rw) * 128 + ((mi ^ rw) << 4);
        const uint32_t da = sb + OFF_BLK + (8 * mi + rw) * 160 + hw * 16;
        mbar_wait(BAR(BR_YIN), 0);
        #pragma unroll
        for (int i = 0; i < 4; i++) {
          if (i < 3 || hw == 0) {
            uint32_t v[4][4];
            #pragma unroll
            for (int q = 0; q < 4; q++) ldsm4t(v[q], (sa ^ ((q & 1) * 64)) + (q >> 1) * 10240 + i * 3072);
            #pragma unroll
            for (int q = 0; q < 4; q++) stsm4(da + q * 5120 + i * 48, v[q][0], v[q][1], v[q][2], v[q][3]);
          }
        }
      }
      fence_async();
      bar_sync(5, 96);
      if (hw == 0 && elect_one()) {
        tma2d_st(&mout, sb + OFF_BLK, c * 80, r * 128);
        tma2d_st(&mout, sb + OFF_BLK + 10240, c * 80, r * 128 + 64);
        bulk_commit(); bulk_wait0_read();
        TS(35); DUMP(30, 40); DUMP(0, 1);
      }
      }
    }
  } else if (wg < 2) {
    asm volatile("setmaxnreg.inc.sync.aligned.u32 152;");
    if (EN_ATT) {
    const int w4 = warp & 3, g = lane >> 2, tq = lane & 3, t7 = tid & 127;
    float am[96], ar[24];
    {
      const uint64_t da0 = mkdesc(sb + OFF_X + wg * 8192, 16, 1024, 1);
      const uint64_t db0 = sw64 ? mkdesc(sb, 2048, 512, 2) : mkdesc(sb, 4096, 1024, 1);
      const uint32_t kst = sw64 ? 64 : 128;
      const uint64_t dr0 = mkdesc(sb + 12288, 1024, 256, 3);
      uint32_t s = 0, ph = 0, xo = 0;
      #pragma unroll 1
      for (int kb = 0; kb < 20; kb++) {
        mbar_wait(BAR(BR_FULL) + 8 * s, ph);
        if (kb == 0 && tid == 0) TS(1);
        wg_fence();
        const uint32_t wo_ = s * (W_SLOT >> 4);
        wg_ss192_tb(am, da0 + xo, db0 + wo_, kb != 0);
        wg_ss48_tb(ar, da0 + xo, dr0 + wo_, kb != 0);
        wg_ss192_tb(am, da0 + xo + 2, db0 + wo_ + kst, 1);
        wg_ss48_tb(ar, da0 + xo + 2, dr0 + wo_ + 32, 1);
        wg_commit();
        wg_wait<1>();
        if (t7 == 0 && kb > 0 && kb < 16) mbar_arrive(BAR(BR_EMPTY) + 8 * (s == 0 ? 4 : s - 1));
        if (++s == 5) { s = 0; ph ^= 1; }
        xo += (kb & 1) ? 1020 : 4;
        if (xo == 3072) xo = 0;
      }
      wg_wait<0>();
      pin<96>(am); pin<24>(ar);
    }
    if (tid == 0) TS(2);
#define QV(j, e) ((j) < 8 ? am[4 * (j) + (e)] : ar[4 * ((j) - 8) + (e)])
#define KV_(j, e) ((j) < 8 ? am[32 + 4 * (j) + (e)] : ar[8 + 4 * ((j) - 8) + (e)])
#define VV(j, e) ((j) < 8 ? am[64 + 4 * (j) + (e)] : ar[16 + 4 * ((j) - 8) + (e)])
    {
      bar_sync(1, 256);
      if (tid == 0) mbar_arrive(BAR(BR_GEMM));
      const uint32_t ro = (uint32_t)((wg * 64 + w4 * 16 + (lane & 15)) * 16);
      const int l0 = 2 * (c & 1) + (lane >> 4);
      const uint32_t ones = (tq == 0) ? 0x00003f80u : 0u;
#define PV(j) pack2(VV(j, 0), VV(j, 1)), pack2(VV(j, 2), VV(j, 3))
#define PK(j) pack2(phi(KV_(j, 0)), phi(KV_(j, 1))), pack2(phi(KV_(j, 2)), phi(KV_(j, 3)))
      stsm4(sb + OFF_V + (5 + 6 * (lane >> 4)) * 2048 + ro, ones, ones, ones, ones);
      #pragma unroll
      for (int j = 0; j < 10; j += 2) {
        const int l = (j == 8 && (c & 1)) ? l0 - 2 : l0 + j;
        stsm4(sb + OFF_V + (l + (l >= 5)) * 2048 + ro, PV(j), PV(j + 1));
      }
      #pragma unroll
      for (int j = 0; j < 10; j += 2) {
        const int l = (j == 8 && (c & 1)) ? l0 - 2 : l0 + j;
        stsm4(sb + OFF_PK + l * 2048 + ro, PK(j), PK(j + 1));
      }
    }
    fence_async();
    bar_sync(1, 256);
    if (tid == 0) TS(3);
    mbar_wait(BAR(BR_EPOCH), 0);
    const unsigned epoch = lds32(sb + OFF_EPOCH);
    {
      float kv[24]; zero<24>(kv);
      const uint64_t da = mkdesc(sb + OFF_PK + wg * 5 * 2048, 128, 2048, 0);
      const uint64_t db = mkdesc(sb + OFF_V + wg * 6 * 2048, 128, 2048, 0);
      wg_fence();
      #pragma unroll
      for (int s = 0; s < 8; s++) wg_ss48_tt(kv, da + s * 16, db + s * 16, s != 0);
      wg_commit();
      wg_wait<0>();
      pin<24>(kv);
      if (tid == 0) TS(15);
      if (w4 < 3) {
        const uint32_t wb = sb + OFF_KVS + (wg * 3 + w4) * 1536;
        #pragma unroll
        for (int j = 0; j < 6; j += 2)
          stsm4(wb + (lane & 15) * 96 + (j + (lane >> 4)) * 16, pack2(kv[4 * j], kv[4 * j + 1]), pack2(kv[4 * j + 2], kv[4 * j + 3]),
                pack2(kv[4 * j + 4], kv[4 * j + 5]), pack2(kv[4 * j + 6], kv[4 * j + 7]));
        __syncwarp();
        const int dl = w4 * 16 + (lane & 15), hl = dl >= 20;
        if (dl < 40) {
          uint4* dst = &g_kvp[(c * 16 + r) * 240 + wg * 40 + dl];
          uint32_t v[4];
          lds128(v, wb + (lane & 15) * 96 + (3 * hl + (lane >> 4)) * 16);
          v[3] = (v[3] & ~1u) | (epoch & 1u);
          st128_rlx(dst + (lane >> 4) * 80, v);
          if (lane < 16) {
            v[0] = lds32(wb + lane * 96 + 32 + 8 * hl); v[1] = lds32(wb + lane * 96 + 36 + 8 * hl);
            v[2] = lds32(wb + lane * 96 + 80); v[3] = epoch & 1u;
            st128_rlx(dst + 160, v);
          }
        }
      }
    }
    bar_sync(1, 256);
    if (tid == 0) { st_rlx(&g_flag[c * 32 + r], epoch); mbar_arrive(BAR(BR_PUB)); TS(4); }
    const int kd = tid >= 160 ? tid - 160 : (tid >= 80 ? tid - 80 : tid), kvi = (tid >= 80) + (tid >= 160);
    const int khd = kd / 20, kt0 = 5 * (khd >> 1) + 2 * (khd & 1);
    if (tid < 240) {
      #pragma unroll
      for (int m = 0; m < 3; m++) {
        int q = kt0 + 3 + kvi + 3 * m; if (q >= 10) q -= 10;
        if (kvi + 3 * m < 7) sts128(sb + OFF_KVB + q * 1280 + kd * 16, 0, 0, 0, 0);
      }
    }
    uint32_t qa[20];
    {
      const float sc = 1.44269504089f + __uint_as_float(lds32(sb + OFF_EPOCH) ^ epoch);
      #pragma unroll
      for (int j = 0; j < 10; j++) { qa[2 * j] = pack2(phi(QV(j, 0), sc), phi(QV(j, 1), sc)); qa[2 * j + 1] = pack2(phi(QV(j, 2), sc), phi(QV(j, 3), sc)); }
    }
    if (tid == 0) TS(5);
    {
      poll_all(&g_flag[c * 32 + (lane & 15)], epoch);
      if (tid == 0) TS(6);
      if (tid < 240) {
        uint32_t v[16][4];
        const uint4* src = &g_kvp[c * 16 * 240 + tid];
        #pragma unroll
        for (int i = 0; i < 16; i++) ld128_rlx(v[i], src + i * 240);
        float s[8];
        uint32_t bad = 0;
        #pragma unroll
        for (int i = 0; i < 16; i++) {
          bad |= v[i][3] ^ epoch;
          #pragma unroll
          for (int e = 0; e < 4; e++) {
            s[2 * e] = i ? s[2 * e] + bf_lo(v[i][e]) : bf_lo(v[i][e]);
            s[2 * e + 1] = i ? s[2 * e + 1] + bf_hi(v[i][e]) : bf_hi(v[i][e]);
          }
        }
        if (__builtin_expect(bad & 1u, 0)) {
          #pragma unroll
          for (int e = 0; e < 8; e++) s[e] = 0.f;
          #pragma unroll 1
          for (int i = 0; i < 16; i++) {
            uint32_t w[4] = {0, 0, 0, ~epoch};
            fix128_w3(w, src + i * 240, epoch, 1u);
            #pragma unroll
            for (int e = 0; e < 4; e++) { s[2 * e] += bf_lo(w[e]); s[2 * e + 1] += bf_hi(w[e]); }
          }
        }
        if (tid == 0) TS(18);
        const uint32_t p0 = pack2(s[0], s[1]), p1 = pack2(s[2], s[3]), p2 = pack2(s[4], s[5]), p3 = pack2(s[6], s[7]);
        const uint32_t rb = sb + OFF_KVB + kd * 16;
        if (kvi < 2) sts128(rb + (kt0 + (khd & 1) + kvi) * 1280, p0, p1, p2, p3);
        else {
          const bool od = khd & 1;
          sts128(rb + (5 * (khd >> 1) + 2) * 1280, od ? 0u : p0, od ? 0u : p1, od ? p0 : 0u, od ? p1 : 0u);
          const uint32_t zz = (p2 & 0xffffu) << (16 * (khd & 1));
          sts128(rb + 10 * 1280, khd < 2 ? zz : 0u, khd < 2 ? 0u : zz, 0u, 0u);
        }
      }
    }
    fence_async();
    bar_sync(1, 256);
    if (tid == 0) TS(7);
    uint32_t A0[20], A1[20];
    {
      float oa[44]; zero<44>(oa);
      const uint64_t db = mkdesc(sb + OFF_KVB, 128, 1280, 0);
      wg_fence();
      #pragma unroll
      for (int s = 0; s < 5; s++) wg_rs88_tb(oa, &qa[4 * s], db + ((s == 4 && (c & 1)) ? 0 : (s + (c & 1)) * 16), s != 0);
      wg_commit();
      if (tid == 0) TS(12);
      wg_wait<0>();
      pin<44>(oa);
      if (tid == 0) TS(13);
      float rc[4], rd[2][4];
      #pragma unroll
      for (int e = 0; e < 4; e++) rc[e] = __fdividef(1.f, oa[40 + e] + 1e-6f);
      #pragma unroll
      for (int h = 0; h < 4; h++) {
        rd[0][h] = __shfl_sync(0xffffffff, rc[h & 1], (lane & 28) | (h >> 1));
        rd[1][h] = __shfl_sync(0xffffffff, rc[2 + (h & 1)], (lane & 28) | (h >> 1));
      }
      #pragma unroll
      for (int j = 0; j < 10; j++) {
        #pragma unroll
        for (int h = 0; h < 2; h++) {
          float f;
          if (j == 2) f = tq < 2 ? rd[h][0] : rd[h][1];
          else if (j == 7) f = tq < 2 ? rd[h][2] : rd[h][3];
          else f = rd[h][(8 * j) / 20];
          A0[2 * j + h] = pack2(oa[4 * j + 2 * h] * f, oa[4 * j + 2 * h + 1] * f);
        }
      }
      bar_sync(1, 256);
      #pragma unroll
      for (int s = 0; s < 5; s++) {
        A0[4 * s] = (A0[4 * s] & ~1u) | (epoch & 1u);
        sts128(sb + OFF_EXTRA + ((wg * 5 + s) * 128 + t7) * 16, A0[4 * s], A0[4 * s + 1], A0[4 * s + 2], A0[4 * s + 3]);
      }
    }
    if (tid == 0) TS(14);
    fence_async();
    mbar_arrive(BAR(BR_OSTG));
    if (tid == 0) TS(8);
    float oc[32], od[8]; zero<32>(oc); zero<8>(od);
    {
      const uint64_t dw0 = mkdesc(sb + OFF_WOM, 16, 1024, 1), dr0 = mkdesc(sb, 16, 256, 3);
      mbar_wait(BAR(BR_WO), 0);
      mbar_wait(BAR(BR_WO + 1), 0);
      wg_fence();
      #pragma unroll
      for (int s = 0; s < 5; s++) { wg_rs64_tb(oc, &A0[4 * s], dw0 + c * 640 + s * 128, s != 0); wg_rs16_tb(od, &A0[4 * s], dr0 + c * 160 + s * 32, s != 0); }
      wg_commit();
      #pragma unroll
      for (int i = 0; i < 7; i++) {
        uint32_t* A = (i & 1) ? A0 : A1;
        const uint32_t slot = (i & 3) == 3 ? sb + OFF_EXTRA : sb + OFF_BLK + (4 - (i & 3)) * BLK;
        const int src = (i == 6) ? (c ^ 1) : (((c & 6) + 2 + i) & 7);
        mbar_wait(BAR(BR_OFULL + (i & 3)), i >> 2);
        if (i == 0 && tid == 0) TS(9);
        if (i > 0) wg_wait<1>();
        #pragma unroll
        for (int s = 0; s < 5; s++) lds128(&A[4 * s], slot + ((wg * 5 + s) * 128 + t7) * 16);
        uint32_t bad = 0;
        #pragma unroll
        for (int s = 0; s < 5; s++) bad |= A[4 * s] ^ epoch;
        if (__builtin_expect(bad & 1u, 0)) {
          #pragma unroll
          for (int s = 0; s < 5; s++) fix128_w0(&A[4 * s], &g_o[(r * 8 + src) * 1280 + (wg * 5 + s) * 128 + t7], epoch, 1u);
        }
        __syncwarp();
        if (i < 3 && lane == 0) mbar_arrive(BAR(BR_OEMPTY + i));
        wg_fence();
        #pragma unroll
        for (int s = 0; s < 5; s++) { wg_rs64_tb(oc, &A[4 * s], dw0 + src * 640 + s * 128, 1); wg_rs16_tb(od, &A[4 * s], dr0 + src * 160 + s * 32, 1); }
        wg_commit();
      }
      bar_sync(2 + wg, 128);
      wg_wait<0>();
      pin<32>(oc); pin<8>(od);
    }
    if (tid == 0) TS(10);
    {
      const int row = w4 * 16 + (lane & 15);
      const uint32_t ob = sb + OFF_EXTRA + wg * 10240;
      #pragma unroll
      for (int j = 0; j < 8; j += 2)
        stsm4(ob + row * 128 + (((j + (lane >> 4)) ^ (row & 7)) << 4), pack2(oc[4 * j], oc[4 * j + 1]), pack2(oc[4 * j + 2], oc[4 * j + 3]),
              pack2(oc[4 * j + 4], oc[4 * j + 5]), pack2(oc[4 * j + 6], oc[4 * j + 7]));
      stsm4(ob + 8192 + row * 32 + (lane >> 4) * 16, pack2(od[0], od[1]), pack2(od[2], od[3]), pack2(od[4], od[5]), pack2(od[6], od[7]));
      fence_async();
      bar_sync(2 + wg, 128);
      if (t7 == 0) {
        tma2d_st(&mo64, ob, 640 + c * 64, r * 128 + wg * 64);
        tma2d_st(&mo16, ob + 8192, 1152 + c * 16, r * 128 + wg * 64);
        bulk_commit(); bulk_wait0_read();
      }
      if (tid == 0) { TS(11); DUMP(0, 20); }
    }
    }
  } else {
    asm volatile("setmaxnreg.inc.sync.aligned.u32 152;");
    if (EN_SSM) {
    const int w4 = warp & 3, g = lane >> 2, tq = lane & 3, t7 = tid & 127;
    {
      #pragma unroll
      for (int k = 0; k < 5; k++) {
        const uint32_t tz = sb + OFF_BLK + k * BLK + B_TBL + t7 * 16;
        if (t7 < 32 || t7 >= 96) sts128(tz, 0, 0, 0, 0);
        if (t7 < 124) sts128(tz + 2048, 0, 0, 0, 0);
        if (t7 < 16) sts128(sb + OFF_BLK + k * BLK - 256 + t7 * 16, 0, 0, 0, 0);
      }
      if (t7 < 5) sts64(sb + OFF_BLK + t7 * BLK + B_SP + 8, __float_as_uint(bf_round(expf(bf_lo(ldt)))), (uint32_t)dsk0 << 16);
      const uint32_t st = sb + OFF_BLK + (lane >> 4) * BLK + B_TBL + 512 + w4 * 256 + (lane & 15) * 16;
      #pragma unroll
      for (int i = 0; i < 3; i++) {
        if (i < 2 || lane < 16) sts128(st + 2 * i * BLK, pv[i].x, pv[i].y, pv[i].z, pv[i].w);
        if (w4 >= 2) {
          const uint32_t m2 = __vmaxu2(__vmaxu2(pv[i].x & 0x7fff7fffu, pv[i].y & 0x7fff7fffu), __vmaxu2(pv[i].z & 0x7fff7fffu, pv[i].w & 0x7fff7fffu));
          const uint32_t m = __reduce_max_sync(lane < 16 ? 0x0000ffffu : 0xffff0000u, max(m2 & 0xffffu, m2 >> 16));
          if ((lane & 15) == 0 && (i < 2 || lane == 0)) sts32(sb + OFF_BLK + (2 * i + (lane >> 4)) * BLK + B_SP + 8 + w4 * 4, m);
        }
      }
    }
    bar_sync(4, 128);
    if (t7 == 0) TS(40);
    {
      const uint32_t fa = sb + OFF_BLK + (w4 & 1) * BLK + (lane >> 3) * 256 + (lane & 7) * 16;
      const uint32_t ea = fa + (w4 >> 1) * 4096, ga = fa + 8192 + (w4 >> 1) * 3072;
      const uint64_t dE = mkdesc(sb + OFF_BLK, 128, 1024, 0), dG = mkdesc(sb + OFF_BLK + 8192, 128, 1024, 0);
      #pragma unroll 1
      for (int k = 4; k >= 0; k--) {
        const uint32_t blk = sb + OFF_BLK + k * BLK;
        float fac, dsk;
        {
          const uint32_t st = blk + B_TBL + 512 + t7 * 2;
          uint32_t q[2], mm[2];
          const uint32_t p0 = lds16(st), p1 = lds16(st + 256), p2 = lds16(st + 512), p3 = lds16(st + 768);
          lds64(q, blk + B_SP + 8); lds64(mm, blk + B_SP + 16);
          const float dt = __uint_as_float(q[0]); dsk = __uint_as_float(q[1]);
          const uint32_t ex = min(max(max(mm[0], mm[1]) >> 7, 1u), 253u);
          const float sc = __uint_as_float((254u - ex) << 23);
          fac = 2.f * dt * __uint_as_float(ex << 23);
          const float lr = -bf_round(expf(bf_lo(p0))) * dt * 1.44269504089f;
          const float tn = bf_lo(p1) * dt * 0.15915494309f;
          float z1r, z1i, z2r, z2i, z4r, z4i, xr[8], xi[8], gr[8], gi[8], wr[9], wi[9];
          cexp_t(lr, -tn, z1r, z1i);
          cexp_t(lr * 8.f, tn * 8.f, xr[1], xi[1]);
          cexp_t(lr * 64.f, tn * 64.f, wr[0], wi[0]);
          xr[0] = 1.f; xi[0] = 0.f;
          cmul(xr[1], xi[1], xr[1], xi[1], xr[2], xi[2]); cmul(xr[2], xi[2], xr[1], xi[1], xr[3], xi[3]);
          cmul(xr[2], xi[2], xr[2], xi[2], xr[4], xi[4]);
          #pragma unroll
          for (int b = 1; b < 4; b++) cmul(xr[4], xi[4], xr[b], xi[b], xr[4 + b], xi[4 + b]);
          cmul(wr[0], wi[0], wr[0], wi[0], wr[1], wi[1]); cmul(wr[1], wi[1], wr[0], wi[0], wr[2], wi[2]);
          cmul(wr[1], wi[1], wr[1], wi[1], wr[3], wi[3]); cmul(wr[3], wi[3], wr[3], wi[3], wr[4], wi[4]);
          cmul(wr[4], wi[4], wr[3], wi[3], wr[5], wi[5]); cmul(wr[4], wi[4], wr[4], wi[4], wr[6], wi[6]);
          cmul(wr[6], wi[6], wr[4], wi[4], wr[7], wi[7]); cmul(wr[6], wi[6], wr[6], wi[6], wr[8], wi[8]);
          uint32_t R[4], I[4], PR[4], PI[4];
          #pragma unroll
          for (int b = 0; b < 4; b++) { R[b] = packh(xr[2 * b], xr[2 * b + 1]); I[b] = packh(xi[2 * b], xi[2 * b + 1]); }
          sts128(ea, R[0], R[1], R[2], R[3]); sts128(ea + 128, I[0], I[1], I[2], I[3]);
          #pragma unroll
          for (int i = 0; i < 3; i++) {
            const uint32_t z = packh(wr[i], wi[i]);
            #pragma unroll
            for (int b = 0; b < 4; b++) hcm2(R[b], I[b], z, PR[b], PI[b]);
            sts128(ea + (i + 1) * 1024, PR[0], PR[1], PR[2], PR[3]); sts128(ea + (i + 1) * 1024 + 128, PI[0], PI[1], PI[2], PI[3]);
          }
          gr[0] = bf_lo(p2) * sc; gi[0] = -bf_lo(p3) * sc;
          cmul(z1r, z1i, z1r, z1i, z2r, z2i); cmul(z2r, z2i, z2r, z2i, z4r, z4i);
          cmul(gr[0], gi[0], z1r, z1i, gr[1], gi[1]);
          cmul(gr[0], gi[0], z2r, z2i, gr[2], gi[2]); cmul(gr[1], gi[1], z2r, z2i, gr[3], gi[3]);
          #pragma unroll
          for (int b = 0; b < 4; b++) cmul(gr[b], gi[b], z4r, z4i, gr[4 + b], gi[4 + b]);
          sts128(ga, packh(gr[0], gr[1]), packh(gr[2], gr[3]), packh(gr[4], gr[5]), packh(gr[6], gr[7]));
          sts128(ga + 128, packh(gi[0], gi[1]), packh(gi[2], gi[3]), packh(gi[4], gi[5]), packh(gi[6], gi[7]));
          {
            const uint32_t z = packh(wr[3], -wi[3]), a4r = packh(gr[0], gr[4]), a4i = packh(gi[0], gi[4]);
            hcm2(packh(gr[0], gr[2]), packh(gi[0], gi[2]), z, PR[0], PI[0]);
            hcm2(packh(gr[4], gr[6]), packh(gi[4], gi[6]), z, PR[1], PI[1]);
            hcm2(a4r, a4i, packh(wr[4], -wi[4]), PR[2], PI[2]);
            hcm2(a4r, a4i, packh(wr[5], -wi[5]), PR[3], PI[3]);
            sts128(ga + 1024, PR[0], PR[1], PR[2], PR[3]); sts128(ga + 1024 + 128, PI[0], PI[1], PI[2], PI[3]);
            float hr, hi_;
            cmul(gr[0], gi[0], wr[3], -wi[3], hr, hi_);
            const uint32_t cr = packh(gr[0], hr), ci = packh(gi[0], hi_);
            #pragma unroll
            for (int i = 0; i < 3; i++) hcm2(cr, ci, packh(wr[6 + i], -wi[6 + i]), PR[i], PI[i]);
            sts128(ga + 2048, PR[0], PR[1], PR[2], 0u); sts128(ga + 2048 + 128, PI[0], PI[1], PI[2], 0u);
          }
        }
        fence_async();
        bar_sync(4, 128);
        if (t7 == 0 && k == 3) TS(50);
        float ka[24]; zero<24>(ka);
        wg_fence();
        #pragma unroll
        for (int s = 0; s < 8; s++) wg_ss48_tt_h(ka, dE + (s >> 2) * (BLK >> 4) + (s & 3) * 16, dG + (s >> 2) * (BLK >> 4) + (s & 3) * 16, s != 0);
        wg_commit();
        wg_wait<0>();
        pin<24>(ka);
        if (t7 == 0 && k == 3) TS(51);
        float kk[6];
        {
          const bool up = w4 >= 2;
          const uint32_t xa = sb + OFF_BLK + 2 * BLK + B_D + 7168 + t7 * 8;
          #pragma unroll
          for (int n = 0; n < 3; n++) {
            sts64f(xa + n * 1024, up ? ka[12 + 4 * n] : ka[4 * n + 2], up ? ka[13 + 4 * n] : ka[4 * n + 3]);
            kk[2 * n] = up ? ka[14 + 4 * n] : ka[4 * n]; kk[2 * n + 1] = up ? ka[15 + 4 * n] : ka[4 * n + 1];
          }
          bar_sync(4, 128);
          #pragma unroll
          for (int n = 0; n < 3; n++) {
            uint32_t o[2]; lds64(o, (xa ^ 512) + n * 1024);
            kk[2 * n] = (kk[2 * n] + __uint_as_float(o[0])) * fac; kk[2 * n + 1] = (kk[2 * n + 1] + __uint_as_float(o[1])) * fac;
          }
        }
        if (t7 == 0 && k == 3) TS(52);
        {
          const int j = (w4 & 1) * 16 + (w4 >> 1) * 8 + g;
          const uint32_t tb = blk + B_TBL;
          if (t7 == 0) kk[0] += dsk;
          const uint32_t pa_ = tb + (16 + 8 * j + 2 * tq) * 4;
          const uint32_t v = pack2(kk[1], kk[0]);
          sts32(pa_ + 4, v); sts16(pa_, v >> 16); sts16(pa_ + 10, v);
          const uint32_t u = pack2(kk[2], kk[3]), w = pack2(kk[4], kk[5]);
          if (tq < 2) {
            const uint32_t pb = tb + (16 + 256 + 8 * j + 4 * tq) * 4;
            sts16(pb, u); sts32(pb + 4, __byte_perm(u, 0, 0x1010)); sts32(pb + 8, __byte_perm(u, 0, 0x1032)); sts16(pb + 14, u >> 16);
            if (j | tq) { sts16(pb - 4, u); sts16(pb + 2, u); }
            const int i = 64 * tq + j;
            const uint32_t e0 = tb + (T_F3 + (((i - 1) & 1) ? 80 : 0) + ((i - 1) >> 1)) * 4, e1 = i ? e0 : tb + (T_F2 + 144 + 31) * 4;
            sts16(e1, w); sts16(e1 + 6, w); sts16(e0 + 64, w >> 16); sts16(e0 + 70, w >> 16);
            if (i == 0) { sts16(tb + (T_S + 3) * 4, w); sts32(tb + (T_S + 4) * 4, __byte_perm(w, 0, 0x1010)); sts16(tb + (T_S + 5) * 4 + 2, w); }
          } else {
            const int i = 32 * (tq - 2) + j;
            const uint32_t e1 = tb + (i ? T_F2 + ((2 * i - 1) & 3) * 48 + ((2 * i - 1) >> 2) : 16 + 511) * 4;
            const uint32_t e2 = tb + (T_F2 + (i & 1) * 96 + (i >> 1)) * 4;
            sts16(e1, u); sts16(e1 + 6, u); sts16(e2, u >> 16); sts16(e2 + 6, u >> 16);
            if (i == 0) {
              const uint32_t uu = __byte_perm(u, 0, 0x1010);
              sts32(tb + 528 * 4, uu); sts32(tb + 529 * 4, uu); sts32(tb + 530 * 4, uu); sts16(tb + 531 * 4 + 2, u);
              sts16(tb + (T_F3 + 80 + 63) * 4, w);
            }
          }
        }
        if (t7 == 0 && k == 3) TS(53);
      }
      bar_sync(4, 128);
      if (t7 == 0) { mbar_arrive(BAR(BR_KGEN)); TS(41); }
    }
    mbar_wait(BAR(BR_U), 0);
    if (EN_ATT) mbar_wait(BAR(BR_GEMM), 0);
    if (t7 == 0) TS(42);
    #pragma unroll 1
    for (int pass = 0; pass < 2; pass++) {
      const int k = pass ? w4 : 4;
      const uint32_t blk = sb + OFF_BLK + k * BLK, tb = blk + B_TBL + (uint32_t)((g - 2 * tq) * 4);
      if (k < 2) mbar_wait(BAR(BR_U2), 0);
      float acc[16][4];
      zero<64>(&acc[0][0]);
      const int kl = 16 * (lane >> 4) + 2 * (lane & 7) + ((lane >> 3) & 1);
      {
        auto ubase = [&](int sh) { const int q = kl - 2 * sh; return blk + (uint32_t)((q * 16) ^ ((q * 2) & 0x70)); };
#define LDQ(A, sh) _Pragma("unroll") for (int m = 0; m < 4; m++) load_quad(A[m], tb + (16 + 16 * (sh) + 128 * m) * 4);
#define LDB(B, ub, h) _Pragma("unroll") for (int p = 0; p < 4; p++) ldsm4(B[p], ((ub) ^ ((p & 1) * 64)) + (4 * (h) + p) * 512);
#define MLO(A, B) _Pragma("unroll") for (int m = 0; m < 4; m++) _Pragma("unroll") for (int cc = 0; cc < 8; cc++) mma16816(acc[cc + m], A[m], &B[cc >> 1][(cc & 1) * 2]);
#define MHI(A, B) _Pragma("unroll") for (int m = 0; m < 4; m++) _Pragma("unroll") for (int cc = 0; cc < 8 - m; cc++) mma16816(acc[8 + cc + m], A[m], &B[cc >> 1][(cc & 1) * 2]);
        int p_ = pass ? 0 : w4;
        const int pe = pass ? 4 : w4 + 1;
        uint32_t A[4][4], A2[4][4], Bl[4][4], Bh[4][4];
        uint32_t ub = ubase(p_ + 4);
        LDQ(A, p_ + 4) LDB(Bl, ub, 0)
        #pragma unroll 1
        for (; p_ < pe; p_++) {
          LDB(Bh, ub, 1)
          MLO(A, Bl)
          ub = ubase(p_);
          LDQ(A2, p_) LDB(Bl, ub, 0)
          MHI(A, Bh)
          LDB(Bh, ub, 1)
          load_quad(A[0], tb + (16 + 512 + 16 * (p_ & 1)) * 4); load_quad(A[1], tb + (T_S + 16 * (p_ & 1)) * 4);
          MLO(A2, Bl)
          if (p_ < 2) {
            #pragma unroll
            for (int cc = 0; cc < 8; cc++) mma16816(acc[cc + 4], A[0], &Bl[cc >> 1][(cc & 1) * 2]);
            #pragma unroll
            for (int cc = 0; cc < 4; cc++) mma16816(acc[cc + 12], A[0], &Bh[cc >> 1][(cc & 1) * 2]);
            #pragma unroll
            for (int cc = 0; cc < 8; cc++) mma16816(acc[cc + 8], A[1], &Bl[cc >> 1][(cc & 1) * 2]);
          }
          const int pn = ((p_ + 1) & 3) + 4;
          ub = ubase(pn);
          LDQ(A, pn) LDB(Bl, ub, 0)
          MHI(A2, Bh)
        }
      }
      if (t7 == 0) TS(57 + 3 * pass);
      mbar_wait(BAR(BR_DRDY) + 8 * k, 0);
      {
        const int ih = (lane >> 3) & 1;
        const uint32_t dl = blk + B_D + (uint32_t)(((lane >> 4) * 8 + (lane & 7)) * 16);
        const uint32_t d0_ = dl + ih * 1552, d8_ = dl + (ih ? 0 : 1536), d3_ = dl + B_D7 + ih * 1024;
        auto cls2 = [&](uint32_t da, uint32_t ta) {
          uint32_t B[6][2], A[6][4];
          #pragma unroll
          for (int e = 0; e < 6; e++) { B[e][0] = lds32v(ta + (e + 4) * 32); B[e][1] = lds32v(ta + (e + 3) * 32); }
          #pragma unroll
          for (int kk = 0; kk < 6; kk++) ldsm4t(A[kk], da + kk * 256);
          #pragma unroll
          for (int e = 0; e < 6; e++)
            #pragma unroll
            for (int kk = 0; kk < 6; kk++) if (2 * kk + e + 4 < 16) mma16816(acc[2 * kk + e + 4], A[kk], B[e]);
        };
        auto cls3 = [&](uint32_t da, uint32_t ta) {
          uint32_t B[8][2], A[4][4];
          #pragma unroll
          for (int e = 0; e < 8; e++) { B[e][0] = lds32v(ta + (e + 8) * 32); B[e][1] = lds32v(ta + (e + 7) * 32); }
          #pragma unroll
          for (int kk = 0; kk < 4; kk++) ldsm4t(A[kk], da + kk * 256);
          #pragma unroll
          for (int kk = 0; kk < 4; kk++)
            #pragma unroll
            for (int e = 0; e < 8; e++) if (2 * kk + e + 8 < 16) mma16816(acc[2 * kk + e + 8], A[kk], B[e]);
        };
        if (pass) {
          #pragma unroll
          for (int a = 0; a < 4; a++) cls2(((a & 2) ? d8_ : d0_) + (a & 1) * B_D5, tb + (T_F2 + 48 * a - 32) * 4);
          #pragma unroll
          for (int b = 0; b < 2; b++) cls3(d3_ + b * 2048, tb + (T_F3 + 80 * b - 64) * 4);
        } else {
          cls2(((w4 & 2) ? d8_ : d0_) + (w4 & 1) * B_D5, tb + (T_F2 + 48 * w4 - 32) * 4);
          if (w4 >= 2) cls3(d3_ + (w4 - 2) * 2048, tb + (T_F3 + 80 * (w4 - 2) - 64) * 4);
        }
      }
      if (t7 == 0) TS(58 + 3 * pass);
      const uint32_t ya = blk + (uint32_t)((kl * 16) ^ ((kl * 2) & 0x70));
#define STY(p) stsm4t((ya ^ (((p) & 1) * 64)) + (p) * 512, pack2(acc[2 * (p)][0], acc[2 * (p)][1]), pack2(acc[2 * (p)][2], acc[2 * (p)][3]), \
                      pack2(acc[2 * (p) + 1][0], acc[2 * (p) + 1][1]), pack2(acc[2 * (p) + 1][2], acc[2 * (p) + 1][3]))
      if (pass == 0) {
        const uint32_t xw = blk + 4096 + w4 * 4096 + lane * 16, xr = blk + 4096 + (w4 ^ 2) * 4096 + lane * 16, xq = blk + 4096 + (w4 ^ 3) * 4096 + lane * 16;
#define PUT(n, a, c0) _Pragma("unroll") for (int i = 0; i < (n); i++) sts128((a) + i * 512, __float_as_uint(acc[(c0) + i][0]), __float_as_uint(acc[(c0) + i][1]), __float_as_uint(acc[(c0) + i][2]), __float_as_uint(acc[(c0) + i][3]));
#define ADD(n, a, c0) _Pragma("unroll") for (int i = 0; i < (n); i++) { uint32_t o[4]; lds128(o, (a) + i * 512); _Pragma("unroll") for (int e = 0; e < 4; e++) acc[(c0) + i][e] += __uint_as_float(o[e]); }
#define RED(h, q) { PUT(8, xw, 8 - 8 * (h)) bar_sync(4, 128); ADD(8, xr, 8 * (h)) PUT(4, xr, 8 * (h) + 4 - 4 * (q)) bar_sync(4, 128); \
                    ADD(4, xq, 8 * (h) + 4 * (q)) STY(4 * (h) + 2 * (q)); STY(4 * (h) + 2 * (q) + 1); }
        bar_sync(4, 128);
        if (t7 == 0) TS(54);
        if (w4 == 0) RED(0, 0) else if (w4 == 1) RED(0, 1) else if (w4 == 2) RED(1, 0) else RED(1, 1)
      } else {
        __syncwarp();
        #pragma unroll
        for (int p = 0; p < 8; p++) STY(p);
      }
      if (t7 == 0 && !pass) TS(55);
      fence_async();
      mbar_arrive(BAR(BR_YSTG) + 8 * k);
      if (t7 == 0) TS(59 + 3 * pass);
    }
    if (t7 == 0) DUMP(40, 64);
    }
  }
}

typedef CUresult (*EncFn)(CUtensorMap*, CUtensorMapDataType, cuuint32_t, void*, const cuuint64_t*, const cuuint64_t*, const cuuint32_t*,
                          const cuuint32_t*, CUtensorMapInterleave, CUtensorMapSwizzle, CUtensorMapL2promotion, CUtensorMapFloatOOBfill);
static CUtensorMap mkmap(EncFn enc, const void* base, int rank, const cuuint64_t* dims, const cuuint64_t* strides, const cuuint32_t* box, CUtensorMapSwizzle swz) {
  CUtensorMap m; cuuint32_t es[5] = {1, 1, 1, 1, 1};
  enc(&m, CU_TENSOR_MAP_DATA_TYPE_BFLOAT16, rank, const_cast<void*>(base), dims, strides, box, es, CU_TENSOR_MAP_INTERLEAVE_NONE, swz,
      CU_TENSOR_MAP_L2_PROMOTION_L2_128B, CU_TENSOR_MAP_FLOAT_OOB_FILL_NONE);
  return m;
}

extern "C" void kernel_launch(void* const* d_in, const int* in_sizes, int n_in, void* d_out, int out_size) {
  void* fn = nullptr; cudaDriverEntryPointQueryResult qr;
  cudaGetDriverEntryPoint("cuTensorMapEncodeTiled", &fn, cudaEnableDefault, &qr);
  EncFn enc = (EncFn)fn;
  void* uy = nullptr; cudaGetSymbolAddress(&uy, g_uy);
  const cuuint64_t dx[2] = {640, 2048}, sx[1] = {1280};
  const cuuint32_t bx[2] = {64, 128}, bu[2] = {80, 64};
  const cuuint64_t dw[3] = {640, 640, 3}, sw[2] = {3840, 1280};
  const cuuint32_t br[3] = {16, 32, 3};
  const cuuint64_t dwa[4] = {64, 640, 10, 3}, swa[3] = {3840, 128, 1280}, dwb[4] = {32, 640, 20, 3}, swb[3] = {3840, 64, 1280};
  const cuuint32_t bwa[4] = {64, 32, 1, 3}, bwb[4] = {32, 32, 2, 3};
  const cuuint64_t dwo[2] = {640, 640};
  const cuuint32_t bwo[2] = {64, 80}, bwr[2] = {16, 160}, bo64[2] = {64, 64}, bo16[2] = {16, 64};
  const cuuint64_t dsa[2] = {2048, 1280}, ssa[1] = {4096};
  const cuuint32_t bsa[2] = {64, 80};
  const cuuint64_t dsb[2] = {64, 40960}, ssb[1] = {128};
  const cuuint32_t bsb[2] = {64, 32};
  const cuuint64_t dout[2] = {1280, 2048}, sout[1] = {2560};
  CUtensorMap mx = mkmap(enc, d_in[7], 2, dx, sx, bx, CU_TENSOR_MAP_SWIZZLE_128B);
  CUtensorMap mw = mkmap(enc, d_in[8], 4, dwa, swa, bwa, CU_TENSOR_MAP_SWIZZLE_128B);
  CUtensorMap mw64 = mkmap(enc, d_in[8], 4, dwb, swb, bwb, CU_TENSOR_MAP_SWIZZLE_64B);
  CUtensorMap mr = mkmap(enc, d_in[8], 3, dw, sw, br, CU_TENSOR_MAP_SWIZZLE_32B);
  CUtensorMap mwo = mkmap(enc, d_in[9], 2, dwo, sx, bwo, CU_TENSOR_MAP_SWIZZLE_128B);
  CUtensorMap mwr = mkmap(enc, d_in[9], 2, dwo, sx, bwr, CU_TENSOR_MAP_SWIZZLE_32B);
  CUtensorMap mo64 = mkmap(enc, d_out, 2, dout, sout, bo64, CU_TENSOR_MAP_SWIZZLE_128B);
  CUtensorMap mo16 = mkmap(enc, d_out, 2, dout, sout, bo16, CU_TENSOR_MAP_SWIZZLE_NONE);
  CUtensorMap msa = mkmap(enc, uy, 2, dsa, ssa, bsa, CU_TENSOR_MAP_SWIZZLE_128B);
  CUtensorMap msb = mkmap(enc, uy, 2, dsb, ssb, bsb, CU_TENSOR_MAP_SWIZZLE_128B);
  CUtensorMap mout = mkmap(enc, d_out, 2, dout, sout, bu, CU_TENSOR_MAP_SWIZZLE_NONE);
  Params prm;
  prm.u = (const __nv_bfloat16*)d_in[0];
  prm.logA = (const __nv_bfloat16*)d_in[1]; prm.Aim = (const __nv_bfloat16*)d_in[2];
  prm.Cr = (const __nv_bfloat16*)d_in[3]; prm.Ci = (const __nv_bfloat16*)d_in[4];
  prm.logdt = (const __nv_bfloat16*)d_in[5]; prm.dskip = (const __nv_bfloat16*)d_in[6];
  cudaFuncSetAttribute(fused_kernel, cudaFuncAttributeMaxDynamicSharedMemorySize, SMEM_BYTES);
  cudaLaunchConfig_t cfg = {};
  cfg.gridDim = dim3(128); cfg.blockDim = dim3(512); cfg.dynamicSmemBytes = SMEM_BYTES; cfg.stream = cudaStreamPerThread;
  cudaLaunchAttribute at[1];
  at[0].id = cudaLaunchAttributeClusterDimension; at[0].val.clusterDim.x = 2; at[0].val.clusterDim.y = 1; at[0].val.clusterDim.z = 1;
  cfg.attrs = at; cfg.numAttrs = 1;
  cudaLaunchKernelEx(&cfg, fused_kernel, mx, mw, mr, mwo, mwr, mo64, mo16, mw64, msa, msb, mout, prm);
}
```

```cpp
#include <cuda_runtime.h>
#include <cuda_bf16.h>
#include <cuda_fp16.h>
#include <cuda.h>
#include <stdint.h>

#define U_PACE 250
#define EN_ATT 1
#define EN_SSM 1

__device__ __align__(1024) __nv_bfloat16 g_uy[2 * 640 * 2048];
__device__ __align__(128) uint4 g_kvp[8 * 16 * 240];
__device__ __align__(128) uint4 g_o[128 * 1280];
__device__ __align__(128) unsigned g_flag[40 * 32];
__device__ unsigned g_epoch[128];
#define TS(i) do {} while (0)
#define DUMP(lo, hi) do {} while (0)

constexpr uint32_t SB0 = 1024;
constexpr uint32_t W_SLOT = 15360, OFF_X = 76800;
constexpr uint32_t OFF_WOM = 20480, OFF_KVP = 30720, OFF_KVS = 71680, OFF_PK = 80896, OFF_V = 101376, OFF_EXTRA = 102400, OFF_KVB = OFF_EXTRA;
constexpr uint32_t OFF_BAR = 125952, OFF_BLK = 128000, BLK = 20480;
constexpr uint32_t B_D = 4096, B_D5 = 3088, B_D7 = 6176, B_D9 = 8224, B_TBL = 14400, B_SP = 18432;
constexpr int T_S = 576, T_F2 = 624, T_F3 = 816;
constexpr uint32_t SMEM_BYTES = OFF_BLK + 5 * BLK;
enum { BR_FULL = 0, BR_WO = 5, BR_PUB = 7, BR_KVP = 8, BR_U = 9, BR_U2 = 10, BR_GEMM = 11, BR_KGEN = 12, BR_YIN = 13, BR_EPOCH = 14,
       BR_FREE = 15, BR_OFULL = 17, BR_EMPTY = 21, BR_OEMPTY = 26, BR_Y4 = 30, BR_Y03 = 31, BR_OSTG = 32, BR_DRDY = 33, BR_COUNT = 38 };
constexpr uint32_t OFF_EPOCH = OFF_BAR + 8 * BR_COUNT;
enum { M_X, M_W128, M_W64, M_WR, M_WO, M_WOR, M_O64, M_O16, M_SA, M_SB, M_OUT, M_COUNT };

__device__ __forceinline__ long long clk64() { long long t; asm volatile("mov.u64 %0, %%clock64;" : "=l"(t) :: "memory"); return t; }
__device__ __forceinline__ uint32_t smem_u32(const void* p) { return (uint32_t)__cvta_generic_to_shared(p); }
__host__ __device__ constexpr uint64_t mkdesc(uint32_t addr, uint32_t lbo, uint32_t sbo, uint32_t swz) {
  return (uint64_t)((addr & 0x3FFFF) >> 4) | ((uint64_t)(lbo >> 4) << 16) | ((uint64_t)(sbo >> 4) << 32) | ((uint64_t)swz << 62);
}
__device__ __forceinline__ void mbar_init(uint32_t bar, uint32_t cnt) { asm volatile("mbarrier.init.shared::cta.b64 [%0], %1;" :: "r"(bar), "r"(cnt) : "memory"); }
__device__ __forceinline__ void mbar_expect_tx(uint32_t bar, uint32_t bytes) { asm volatile("mbarrier.arrive.expect_tx.shared::cta.b64 _, [%0], %1;" :: "r"(bar), "r"(bytes) : "memory"); }
__device__ __forceinline__ void mbar_arrive(uint32_t bar) { asm volatile("mbarrier.arrive.shared::cta.b64 _, [%0];" :: "r"(bar) : "memory"); }
__device__ __forceinline__ void mbar_wait(uint32_t bar, uint32_t parity) {
  asm volatile("{\n.reg .pred p;\n.reg .u32 c;\nmov.u32 c, 0;\n"
    "WL:\nmbarrier.try_wait.parity.shared::cta.b64 p, [%0], %1;\n@p bra WD;\n"
    "add.u32 c, c, 1;\nsetp.lt.u32 p, c, 200000;\n@p bra WL;\nWD:\n}" :: "r"(bar), "r"(parity) : "memory");
}
__device__ __forceinline__ void poll_all(const unsigned* p, unsigned val) {
  asm volatile("{\n.reg .pred p;\n.reg .u32 c, v;\nmov.u32 c, 0;\n"
    "PL:\nld.relaxed.gpu.global.u32 v, [%0];\nsetp.eq.u32 p, v, %1;\nvote.sync.all.pred p, p, 0xffffffff;\n@p bra PD;\n"
    "add.u32 c, c, 1;\nsetp.lt.u32 p, c, 100000;\n@p bra PL;\nPD:\n}" :: "l"(p), "r"(val) : "memory");
}
__device__ __forceinline__ void poll_all_acq(const unsigned* p, unsigned val) {
  asm volatile("{\n.reg .pred p;\n.reg .u32 c, v;\nmov.u32 c, 0;\n"
    "PL:\nld.acquire.gpu.global.u32 v, [%0];\nsetp.eq.u32 p, v, %1;\nvote.sync.all.pred p, p, 0xffffffff;\n@p bra PD;\n"
    "add.u32 c, c, 1;\nsetp.lt.u32 p, c, 100000;\n@p bra PL;\nPD:\n}" :: "l"(p), "r"(val) : "memory");
}
__device__ __forceinline__ unsigned poll_bit(const unsigned* p, unsigned val, unsigned mask) {
  unsigned bal;
  asm volatile("{\n.reg .pred p;\n.reg .u32 c, v;\nmov.u32 c, 0;\n"
    "PL:\nld.relaxed.gpu.global.u32 v, [%1];\nsetp.eq.u32 p, v, %2;\nvote.sync.ballot.b32 %0, p, 0xffffffff;\n"
    "and.b32 v, %0, %3;\nsetp.ne.u32 p, v, 0;\n@p bra PD;\n"
    "add.u32 c, c, 1;\nsetp.lt.u32 p, c, 100000;\n@p bra PL;\nPD:\n}" : "=&r"(bal) : "l"(p), "r"(val), "r"(mask) : "memory");
  return bal;
}
__device__ __forceinline__ void fix128_w0(uint32_t* v, const void* p, uint32_t tag, uint32_t mask) {
  asm volatile("{\n.reg .pred p;\n.reg .u32 c, x;\n.reg .b128 t;\n.reg .b64 lo, hi;\nmov.u32 c, 0;\n"
    "FL:\nxor.b32 x, %0, %5;\nand.b32 x, x, %6;\nsetp.eq.u32 p, x, 0;\n@p bra FD;\n"
    "ld.relaxed.gpu.global.b128 t, [%4];\nmov.b128 {lo, hi}, t;\nmov.b64 {%0, %1}, lo;\nmov.b64 {%2, %3}, hi;\n"
    "add.u32 c, c, 1;\nsetp.lt.u32 p, c, 100000;\n@p bra FL;\nFD:\n}"
    : "+r"(v[0]), "+r"(v[1]), "+r"(v[2]), "+r"(v[3]) : "l"(p), "r"(tag), "r"(mask) : "memory");
}
__device__ __forceinline__ void fix128_w3(uint32_t* v, const void* p, uint32_t tag, uint32_t mask) {
  asm volatile("{\n.reg .pred p;\n.reg .u32 c, x;\n.reg .b128 t;\n.reg .b64 lo, hi;\nmov.u32 c, 0;\n"
    "FL:\nxor.b32 x, %3, %5;\nand.b32 x, x, %6;\nsetp.eq.u32 p, x, 0;\n@p bra FD;\n"
    "ld.relaxed.gpu.global.b128 t, [%4];\nmov.b128 {lo, hi}, t;\nmov.b64 {%0, %1}, lo;\nmov.b64 {%2, %3}, hi;\n"
    "add.u32 c, c, 1;\nsetp.lt.u32 p, c, 100000;\n@p bra FL;\nFD:\n}"
    : "+r"(v[0]), "+r"(v[1]), "+r"(v[2]), "+r"(v[3]) : "l"(p), "r"(tag), "r"(mask) : "memory");
}
__device__ __forceinline__ void fence_acq() { asm volatile("fence.acq_rel.gpu;" ::: "memory"); }
__device__ __forceinline__ bool elect_one() {
  uint32_t p; asm volatile("{\n.reg .pred P;\nelect.sync _|P, 0xffffffff;\nselp.u32 %0, 1, 0, P;\n}" : "=r"(p)); return p;
}
__device__ __forceinline__ void bar_sync(int id, int n) { asm volatile("bar.sync %0, %1;" :: "r"(id), "r"(n) : "memory"); }
__device__ __forceinline__ void fence_async() { asm volatile("fence.proxy.async.shared::cta;" ::: "memory"); }
__device__ __forceinline__ void fence_async_g() { asm volatile("fence.proxy.async.global;" ::: "memory"); }
__device__ __forceinline__ void tma2d(uint32_t dst, const CUtensorMap* m, uint32_t bar, int c0, int c1) {
  asm volatile("cp.async.bulk.tensor.2d.shared::cluster.global.mbarrier::complete_tx::bytes [%0], [%1, {%3, %4}], [%2];"
    :: "r"(dst), "l"(m), "r"(bar), "r"(c0), "r"(c1) : "memory");
}
__device__ __forceinline__ void tma3d(uint32_t dst, const CUtensorMap* m, uint32_t bar, int c0, int c1, int c2) {
  asm volatile("cp.async.bulk.tensor.3d.shared::cluster.global.mbarrier::complete_tx::bytes [%0], [%1, {%3, %4, %5}], [%2];"
    :: "r"(dst), "l"(m), "r"(bar), "r"(c0), "r"(c1), "r"(c2) : "memory");
}
__device__ __forceinline__ void tma4d(uint32_t dst, const CUtensorMap* m, uint32_t bar, int c0, int c1, int c2, int c3) {
  asm volatile("cp.async.bulk.tensor.4d.shared::cluster.global.mbarrier::complete_tx::bytes [%0], [%1, {%3, %4, %5, %6}], [%2];"
    :: "r"(dst), "l"(m), "r"(bar), "r"(c0), "r"(c1), "r"(c2), "r"(c3) : "memory");
}
__device__ __forceinline__ void tma2d_st(const CUtensorMap* m, uint32_t src, int c0, int c1) {
  asm volatile("cp.async.bulk.tensor.2d.global.shared::cta.bulk_group [%0, {%2, %3}], [%1];"
    :: "l"(m), "r"(src), "r"(c0), "r"(c1) : "memory");
}
__device__ __forceinline__ void bulk_ld(uint32_t dst, const void* src, uint32_t bytes, uint32_t bar) {
  asm volatile("cp.async.bulk.shared::cluster.global.mbarrier::complete_tx::bytes [%0], [%1], %2, [%3];"
    :: "r"(dst), "l"(src), "r"(bytes), "r"(bar) : "memory");
}
__device__ __forceinline__ void bulk_st(void* dst, uint32_t src, uint32_t bytes) {
  asm volatile("cp.async.bulk.global.shared::cta.bulk_group [%0], [%1], %2;" :: "l"(dst), "r"(src), "r"(bytes) : "memory");
}
__device__ __forceinline__ void bulk_commit() { asm volatile("cp.async.bulk.commit_group;" ::: "memory"); }
__device__ __forceinline__ void bulk_wait0() { asm volatile("cp.async.bulk.wait_group 0;" ::: "memory"); }
__device__ __forceinline__ void bulk_wait0_read() { asm volatile("cp.async.bulk.wait_group.read 0;" ::: "memory"); }
__device__ __forceinline__ unsigned ld_rlx(const unsigned* p) { unsigned v; asm volatile("ld.relaxed.gpu.global.u32 %0, [%1];" : "=r"(v) : "l"(p) : "memory"); return v; }
__device__ __forceinline__ unsigned ld_acq(const unsigned* p) { unsigned v; asm volatile("ld.acquire.gpu.global.u32 %0, [%1];" : "=r"(v) : "l"(p) : "memory"); return v; }
__device__ __forceinline__ void st_rlx(unsigned* p, unsigned v) { asm volatile("st.relaxed.gpu.global.u32 [%0], %1;" :: "l"(p), "r"(v) : "memory"); }
__device__ __forceinline__ void st_rel(unsigned* p, unsigned v) { asm volatile("st.release.gpu.global.u32 [%0], %1;" :: "l"(p), "r"(v) : "memory"); }
__device__ __forceinline__ void ld128_rlx(uint32_t* v, const void* p) {
  asm volatile("{\n.reg .b128 t;\n.reg .b64 lo, hi;\nld.relaxed.gpu.global.b128 t, [%4];\nmov.b128 {lo, hi}, t;\n"
    "mov.b64 {%0, %1}, lo;\nmov.b64 {%2, %3}, hi;\n}" : "=r"(v[0]), "=r"(v[1]), "=r"(v[2]), "=r"(v[3]) : "l"(p) : "memory");
}
__device__ __forceinline__ void st128_rlx(void* p, const uint32_t* v) {
  asm volatile("{\n.reg .b128 t;\n.reg .b64 lo, hi;\nmov.b64 lo, {%1, %2};\nmov.b64 hi, {%3, %4};\nmov.b128 t, {lo, hi};\n"
    "st.relaxed.gpu.global.b128 [%0], t;\n}" :: "l"(p), "r"(v[0]), "r"(v[1]), "r"(v[2]), "r"(v[3]) : "memory");
}
__device__ __forceinline__ uint32_t lds32(uint32_t a) { uint32_t v; asm volatile("ld.shared.u32 %0, [%1];" : "=r"(v) : "r"(a) : "memory"); return v; }
__device__ __forceinline__ uint32_t lds32v(uint32_t a) { uint32_t v; asm volatile("ld.volatile.shared.u32 %0, [%1];" : "=r"(v) : "r"(a) : "memory"); return v; }
__device__ __forceinline__ uint32_t cpa(uint32_t a, uint32_t one) { uint32_t v; asm volatile("mul.lo.u32 %0, %1, %2;" : "=r"(v) : "r"(a), "r"(one)); return v; }
__device__ __forceinline__ uint32_t cpb(uint32_t a, uint32_t zero) { uint32_t v; asm volatile("or.b32 %0, %1, %2;" : "=r"(v) : "r"(a), "r"(zero)); return v; }
__device__ __forceinline__ uint32_t lds16(uint32_t a) { uint16_t v; asm volatile("ld.shared.u16 %0, [%1];" : "=h"(v) : "r"(a) : "memory"); return v; }
__device__ __forceinline__ float ldsf(uint32_t a) { float v; asm volatile("ld.shared.f32 %0, [%1];" : "=f"(v) : "r"(a) : "memory"); return v; }
__device__ __forceinline__ void lds128(uint32_t* v, uint32_t a) { asm volatile("ld.shared.v4.u32 {%0,%1,%2,%3}, [%4];" : "=r"(v[0]), "=r"(v[1]), "=r"(v[2]), "=r"(v[3]) : "r"(a) : "memory"); }
__device__ __forceinline__ void sts32(uint32_t a, uint32_t v) { asm volatile("st.shared.u32 [%0], %1;" :: "r"(a), "r"(v) : "memory"); }
__device__ __forceinline__ void sts16(uint32_t a, uint32_t v) { asm volatile("st.shared.u16 [%0], %1;" :: "r"(a), "h"((uint16_t)v) : "memory"); }
__device__ __forceinline__ void sts64f(uint32_t a, float x, float y) { asm volatile("st.shared.v2.f32 [%0], {%1,%2};" :: "r"(a), "f"(x), "f"(y) : "memory"); }
__device__ __forceinline__ void sts128(uint32_t a, uint32_t x, uint32_t y, uint32_t z, uint32_t w) { asm volatile("st.shared.v4.u32 [%0], {%1,%2,%3,%4};" :: "r"(a), "r"(x), "r"(y), "r"(z), "r"(w) : "memory"); }
__device__ __forceinline__ void stsm4(uint32_t a, uint32_t r0, uint32_t r1, uint32_t r2, uint32_t r3) {
  asm volatile("stmatrix.sync.aligned.m8n8.x4.shared.b16 [%0], {%1,%2,%3,%4};" :: "r"(a), "r"(r0), "r"(r1), "r"(r2), "r"(r3) : "memory");
}
__device__ __forceinline__ void stsm4t(uint32_t a, uint32_t r0, uint32_t r1, uint32_t r2, uint32_t r3) {
  asm volatile("stmatrix.sync.aligned.m8n8.x4.trans.shared.b16 [%0], {%1,%2,%3,%4};" :: "r"(a), "r"(r0), "r"(r1), "r"(r2), "r"(r3) : "memory");
}
__device__ __forceinline__ void ldsm4t(uint32_t* r, uint32_t a) {
  asm volatile("ldmatrix.sync.aligned.m8n8.x4.trans.shared.b16 {%0,%1,%2,%3}, [%4];" : "=r"(r[0]), "=r"(r[1]), "=r"(r[2]), "=r"(r[3]) : "r"(a) : "memory");
}
__device__ __forceinline__ void ldsm4(uint32_t* r, uint32_t a) {
  asm volatile("ldmatrix.sync.aligned.m8n8.x4.shared.b16 {%0,%1,%2,%3}, [%4];" : "=r"(r[0]), "=r"(r[1]), "=r"(r[2]), "=r"(r[3]) : "r"(a) : "memory");
}
__device__ __forceinline__ void mma16816(float* d, const uint32_t* a, const uint32_t* b) {
  asm volatile("mma.sync.aligned.m16n8k16.row.col.f32.bf16.bf16.f32 {%0,%1,%2,%3}, {%4,%5,%6,%7}, {%8,%9}, {%0,%1,%2,%3};"
    : "+f"(d[0]), "+f"(d[1]), "+f"(d[2]), "+f"(d[3]) : "r"(a[0]), "r"(a[1]), "r"(a[2]), "r"(a[3]), "r"(b[0]), "r"(b[1]));
}
__device__ __forceinline__ uint32_t pack2(float lo, float hi) { uint32_t r; asm("cvt.rn.bf16x2.f32 %0, %1, %2;" : "=r"(r) : "f"(hi), "f"(lo)); return r; }
__device__ __forceinline__ uint32_t packh(float lo, float hi) { uint32_t r; asm("cvt.rn.f16x2.f32 %0, %1, %2;" : "=r"(r) : "f"(hi), "f"(lo)); return r; }
__device__ __forceinline__ uint32_t hcmul(uint32_t x, uint32_t zp, uint32_t zq) {
  const __half2 xx = *reinterpret_cast<__half2*>(&x);
  const __half2 r = __hfma2(__high2half2(xx), *reinterpret_cast<__half2*>(&zq), __hmul2(__low2half2(xx), *reinterpret_cast<__half2*>(&zp)));
  return *reinterpret_cast<const uint32_t*>(&r);
}
__device__ __forceinline__ void hcm2(uint32_t xr, uint32_t xi, uint32_t z, uint32_t& pr, uint32_t& pi) {
  const __half2 a = *reinterpret_cast<__half2*>(&xr), b = *reinterpret_cast<__half2*>(&xi), zz = *reinterpret_cast<__half2*>(&z);
  const __half2 re = __hfma2(__hneg2(b), __high2half2(zz), __hmul2(a, __low2half2(zz)));
  const __half2 im = __hfma2(a, __high2half2(zz), __hmul2(b, __low2half2(zz)));
  pr = *reinterpret_cast<const uint32_t*>(&re); pi = *reinterpret_cast<const uint32_t*>(&im);
}
__device__ __forceinline__ void sts64(uint32_t a, uint32_t x, uint32_t y) { asm volatile("st.shared.v2.u32 [%0], {%1,%2};" :: "r"(a), "r"(x), "r"(y) : "memory"); }
__device__ __forceinline__ void lds64(uint32_t* v, uint32_t a) { asm volatile("ld.shared.v2.u32 {%0,%1}, [%2];" : "=r"(v[0]), "=r"(v[1]) : "r"(a) : "memory"); }
__device__ __forceinline__ float bf_lo(uint32_t v) { return __uint_as_float(v << 16); }
__device__ __forceinline__ float bf_hi(uint32_t v) { return __uint_as_float(v & 0xffff0000u); }
__device__ __forceinline__ float bf_round(float x) { return bf_lo(pack2(x, 0.f)); }
__device__ __forceinline__ float ex2(float x) { float r; asm("ex2.approx.ftz.f32 %0, %1;" : "=f"(r) : "f"(x)); return r; }
__device__ __forceinline__ float phi(float t, float l2e = 1.44269504089f) { float e = ex2(t * l2e); return (t > 0.f ? t + 1.f : e) + 1e-6f; }
__device__ __forceinline__ void wg_fence() { asm volatile("wgmma.fence.sync.aligned;" ::: "memory"); }
__device__ __forceinline__ void wg_commit() { asm volatile("wgmma.commit_group.sync.aligned;" ::: "memory"); }
template <int N> __device__ __forceinline__ void wg_wait() { asm volatile("wgmma.wait_group.sync.aligned %0;" :: "n"(N) : "memory"); }
template <int N> __device__ __forceinline__ void pin(float* a) {
  #pragma unroll
  for (int i = 0; i < N; i++) asm volatile("" : "+f"(a[i]) :: "memory");
}
__device__ __forceinline__ int opaque(int v) { asm volatile("" : "+r"(v)); return v; }
template <int N> __device__ __forceinline__ void zero(float* a) {
  #pragma unroll
  for (int i = 0; i < N; i++) asm volatile("mov.b32 %0, 0;" : "=f"(a[i]));
}
template <int N> __device__ __forceinline__ void pinu(uint32_t* a) {
  #pragma unroll
  for (int i = 0; i < N; i++) asm volatile("" : "+r"(a[i]) :: "memory");
}
__device__ __forceinline__ void cexp_t(float lg2mag, float turns, float& re, float& im) {
  float m = ex2(lg2mag);
  float fr = (turns - __fadd_rn(__fadd_rn(turns, 12582912.f), -12582912.f)) * 6.283185307f;
  re = m * __cosf(fr); im = m * __sinf(fr);
}
__device__ __forceinline__ void cmul(float ar, float ai, float br, float bi, float& cr, float& ci) {
  cr = fmaf(ar, br, -ai * bi); ci = fmaf(ar, bi, ai * br);
}

__device__ __forceinline__ void wg_ss192_tb(float* d, uint64_t da, uint64_t db, int scale_d) {
  asm volatile("{\n.reg .pred p;\nsetp.ne.b32 p, %98, 0;\n"
    "wgmma.mma_async.sync.aligned.m64n192k16.f32.bf16.bf16 "
    "{%0, %1, %2, %3, %4, %5, %6, %7, %8, %9, %10, %11, %12, %13, %14, %15, %16, %17, %18, %19, %20, %21, %22, %23, %24, %25, %26, %27, %28, %29, %30, %31, %32, %33, %34, %35, %36, %37, %38, %39, %40, %41, %42, %43, %44, %45, %46, %47, %48, %49, %50, %51, %52, %53, %54, %55, %56, %57, %58, %59, %60, %61, %62, %63, %64, %65, %66, %67, %68, %69, %70, %71, %72, %73, %74, %75, %76, %77, %78, %79, %80, %81, %82, %83, %84, %85, %86, %87, %88, %89, %90, %91, %92, %93, %94, %95}, %96, %97, p, 1, 1, 0, 1;\n}\n"
    : "+f"(d[0]), "+f"(d[1]), "+f"(d[2]), "+f"(d[3]), "+f"(d[4]), "+f"(d[5]), "+f"(d[6]), "+f"(d[7]), "+f"(d[8]), "+f"(d[9]), "+f"(d[10]), "+f"(d[11]), "+f"(d[12]), "+f"(d[13]), "+f"(d[14]), "+f"(d[15]), "+f"(d[16]), "+f"(d[17]), "+f"(d[18]), "+f"(d[19]), "+f"(d[20]), "+f"(d[21]), "+f"(d[22]), "+f"(d[23]), "+f"(d[24]), "+f"(d[25]), "+f"(d[26]), "+f"(d[27]), "+f"(d[28]), "+f"(d[29]), "+f"(d[30]), "+f"(d[31]), "+f"(d[32]), "+f"(d[33]), "+f"(d[34]), "+f"(d[35]), "+f"(d[36]), "+f"(d[37]), "+f"(d[38]), "+f"(d[39]), "+f"(d[40]), "+f"(d[41]), "+f"(d[42]), "+f"(d[43]), "+f"(d[44]), "+f"(d[45]), "+f"(d[46]), "+f"(d[47]), "+f"(d[48]), "+f"(d[49]), "+f"(d[50]), "+f"(d[51]), "+f"(d[52]), "+f"(d[53]), "+f"(d[54]), "+f"(d[55]), "+f"(d[56]), "+f"(d[57]), "+f"(d[58]), "+f"(d[59]), "+f"(d[60]), "+f"(d[61]), "+f"(d[62]), "+f"(d[63]), "+f"(d[64]), "+f"(d[65]), "+f"(d[66]), "+f"(d[67]), "+f"(d[68]), "+f"(d[69]), "+f"(d[70]), "+f"(d[71]), "+f"(d[72]), "+f"(d[73]), "+f"(d[74]), "+f"(d[75]), "+f"(d[76]), "+f"(d[77]), "+f"(d[78]), "+f"(d[79]), "+f"(d[80]), "+f"(d[81]), "+f"(d[82]), "+f"(d[83]), "+f"(d[84]), "+f"(d[85]), "+f"(d[86]), "+f"(d[87]), "+f"(d[88]), "+f"(d[89]), "+f"(d[90]), "+f"(d[91]), "+f"(d[92]), "+f"(d[93]), "+f"(d[94]), "+f"(d[95])
    : "l"(da), "l"(db), "r"(scale_d));
}
__device__ __forceinline__ void wg_ss48_tb(float* d, uint64_t da, uint64_t db, int scale_d) {
  asm volatile("{\n.reg .pred p;\nsetp.ne.b32 p, %26, 0;\n"
    "wgmma.mma_async.sync.aligned.m64n48k16.f32.bf16.bf16 "
    "{%0, %1, %2, %3, %4, %5, %6, %7, %8, %9, %10, %11, %12, %13, %14, %15, %16, %17, %18, %19, %20, %21, %22, %23}, %24, %25, p, 1, 1, 0, 1;\n}\n"
    : "+f"(d[0]), "+f"(d[1]), "+f"(d[2]), "+f"(d[3]), "+f"(d[4]), "+f"(d[5]), "+f"(d[6]), "+f"(d[7]), "+f"(d[8]), "+f"(d[9]), "+f"(d[10]), "+f"(d[11]), "+f"(d[12]), "+f"(d[13]), "+f"(d[14]), "+f"(d[15]), "+f"(d[16]), "+f"(d[17]), "+f"(d[18]), "+f"(d[19]), "+f"(d[20]), "+f"(d[21]), "+f"(d[22]), "+f"(d[23])
    : "l"(da), "l"(db), "r"(scale_d));
}
__device__ __forceinline__ void wg_ss48_tt(float* d, uint64_t da, uint64_t db, int scale_d) {
  asm volatile("{\n.reg .pred p;\nsetp.ne.b32 p, %26, 0;\n"
    "wgmma.mma_async.sync.aligned.m64n48k16.f32.bf16.bf16 "
    "{%0, %1, %2, %3, %4, %5, %6, %7, %8, %9, %10, %11, %12, %13, %14, %15, %16, %17, %18, %19, %20, %21, %22, %23}, %24, %25, p, 1, 1, 1, 1;\n}\n"
    : "+f"(d[0]), "+f"(d[1]), "+f"(d[2]), "+f"(d[3]), "+f"(d[4]), "+f"(d[5]), "+f"(d[6]), "+f"(d[7]), "+f"(d[8]), "+f"(d[9]), "+f"(d[10]), "+f"(d[11]), "+f"(d[12]), "+f"(d[13]), "+f"(d[14]), "+f"(d[15]), "+f"(d[16]), "+f"(d[17]), "+f"(d[18]), "+f"(d[19]), "+f"(d[20]), "+f"(d[21]), "+f"(d[22]), "+f"(d[23])
    : "l"(da), "l"(db), "r"(scale_d));
}
__device__ __forceinline__ void wg_rs88_tb(float* d, const uint32_t* a, uint64_t db, int scale_d) {
  asm volatile("{\n.reg .pred p;\nsetp.ne.b32 p, %49, 0;\n"
    "wgmma.mma_async.sync.aligned.m64n88k16.f32.bf16.bf16 "
    "{%0, %1, %2, %3, %4, %5, %6, %7, %8, %9, %10, %11, %12, %13, %14, %15, %16, %17, %18, %19, %20, %21, %22, %23, %24, %25, %26, %27, %28, %29, %30, %31, %32, %33, %34, %35, %36, %37, %38, %39, %40, %41, %42, %43}, {%44, %45, %46, %47}, %48, p, 1, 1, 1;\n}\n"
    : "+f"(d[0]), "+f"(d[1]), "+f"(d[2]), "+f"(d[3]), "+f"(d[4]), "+f"(d[5]), "+f"(d[6]), "+f"(d[7]), "+f"(d[8]), "+f"(d[9]), "+f"(d[10]), "+f"(d[11]), "+f"(d[12]), "+f"(d[13]), "+f"(d[14]), "+f"(d[15]), "+f"(d[16]), "+f"(d[17]), "+f"(d[18]), "+f"(d[19]), "+f"(d[20]), "+f"(d[21]), "+f"(d[22]), "+f"(d[23]), "+f"(d[24]), "+f"(d[25]), "+f"(d[26]), "+f"(d[27]), "+f"(d[28]), "+f"(d[29]), "+f"(d[30]), "+f"(d[31]), "+f"(d[32]), "+f"(d[33]), "+f"(d[34]), "+f"(d[35]), "+f"(d[36]), "+f"(d[37]), "+f"(d[38]), "+f"(d[39]), "+f"(d[40]), "+f"(d[41]), "+f"(d[42]), "+f"(d[43])
    : "r"(a[0]), "r"(a[1]), "r"(a[2]), "r"(a[3]), "l"(db), "r"(scale_d));
}
__device__ __forceinline__ void wg_rs64_tb(float* d, const uint32_t* a, uint64_t db, int scale_d) {
  asm volatile("{\n.reg .pred p;\nsetp.ne.b32 p, %37, 0;\n"
    "wgmma.mma_async.sync.aligned.m64n64k16.f32.bf16.bf16 "
    "{%0, %1, %2, %3, %4, %5, %6, %7, %8, %9, %10, %11, %12, %13, %14, %15, %16, %17, %18, %19, %20, %21, %22, %23, %24, %25, %26, %27, %28, %29, %30, %31}, {%32, %33, %34, %35}, %36, p, 1, 1, 1;\n}\n"
    : "+f"(d[0]), "+f"(d[1]), "+f"(d[2]), "+f"(d[3]), "+f"(d[4]), "+f"(d[5]), "+f"(d[6]), "+f"(d[7]), "+f"(d[8]), "+f"(d[9]), "+f"(d[10]), "+f"(d[11]), "+f"(d[12]), "+f"(d[13]), "+f"(d[14]), "+f"(d[15]), "+f"(d[16]), "+f"(d[17]), "+f"(d[18]), "+f"(d[19]), "+f"(d[20]), "+f"(d[21]), "+f"(d[22]), "+f"(d[23]), "+f"(d[24]), "+f"(d[25]), "+f"(d[26]), "+f"(d[27]), "+f"(d[28]), "+f"(d[29]), "+f"(d[30]), "+f"(d[31])
    : "r"(a[0]), "r"(a[1]), "r"(a[2]), "r"(a[3]), "l"(db), "r"(scale_d));
}
__device__ __forceinline__ void wg_ss48_tt_h(float* d, uint64_t da, uint64_t db, int scale_d) {
  asm volatile("{\n.reg .pred p;\nsetp.ne.b32 p, %26, 0;\n"
    "wgmma.mma_async.sync.aligned.m64n48k16.f32.f16.f16 "
    "{%0, %1, %2, %3, %4, %5, %6, %7, %8, %9, %10, %11, %12, %13, %14, %15, %16, %17, %18, %19, %20, %21, %22, %23}, %24, %25, p, 1, 1, 1, 1;\n}\n"
    : "+f"(d[0]), "+f"(d[1]), "+f"(d[2]), "+f"(d[3]), "+f"(d[4]), "+f"(d[5]), "+f"(d[6]), "+f"(d[7]), "+f"(d[8]), "+f"(d[9]), "+f"(d[10]), "+f"(d[11]), "+f"(d[12]), "+f"(d[13]), "+f"(d[14]), "+f"(d[15]), "+f"(d[16]), "+f"(d[17]), "+f"(d[18]), "+f"(d[19]), "+f"(d[20]), "+f"(d[21]), "+f"(d[22]), "+f"(d[23])
    : "l"(da), "l"(db), "r"(scale_d));
}
__device__ __forceinline__ void wg_rs16_tb(float* d, const uint32_t* a, uint64_t db, int scale_d) {
  asm volatile("{\n.reg .pred p;\nsetp.ne.b32 p, %13, 0;\n"
    "wgmma.mma_async.sync.aligned.m64n16k16.f32.bf16.bf16 "
    "{%0, %1, %2, %3, %4, %5, %6, %7}, {%8, %9, %10, %11}, %12, p, 1, 1, 1;\n}\n"
    : "+f"(d[0]), "+f"(d[1]), "+f"(d[2]), "+f"(d[3]), "+f"(d[4]), "+f"(d[5]), "+f"(d[6]), "+f"(d[7])
    : "r"(a[0]), "r"(a[1]), "r"(a[2]), "r"(a[3]), "l"(db), "r"(scale_d));
}

struct Params {
  CUtensorMap m[M_COUNT];
  const __nv_bfloat16 *u, *par[4], *logdt, *dskip;
};

#define CHUNK(i) ((i) == 0 ? c : ((i) == 7 ? (c ^ 1) : (((c & 6) + 1 + (i)) & 7)))
#define SLOT(sl) ((sl) == 0 ? OFF_EXTRA : OFF_BLK + (5 - (sl)) * BLK)
__device__ __forceinline__ void load_quad(uint32_t* A, uint32_t addr) {
  A[0] = lds32v(addr); A[1] = lds32v(addr + 32); A[2] = lds32v(addr - 32); A[3] = lds32v(addr);
}

__global__ void __launch_bounds__(512, 1) fused_kernel(const __grid_constant__ Params prm) {
  extern __shared__ unsigned char smem_raw[];
  const uint32_t sb = __shfl_sync(0xffffffff, smem_u32(smem_raw), 0);
  const int tid = threadIdx.x, lane = tid & 31;
  const int warp = __shfl_sync(0xffffffff, tid >> 5, 0), wg = warp >> 2, w4 = warp & 3;
  const int cta = blockIdx.x, r = cta >> 3, c = cta & 7;
  if ((sb & 0xffffffu) != SB0) return;
#define BAR(i) (sb + OFF_BAR + 8 * (i))
  const bool sw64 = ((c + 1) & 2) != 0;

  if (wg == 3) {
    asm volatile("setmaxnreg.dec.sync.aligned.u32 56;");
    {
      const int i = tid - 384;
      if (i < BR_COUNT) {
        mbar_init(BAR(i), i < BR_EMPTY ? 1 : i < BR_OEMPTY ? 2 : i < BR_Y4 ? 8 : i < BR_OSTG ? 128 : i == BR_OSTG ? 256 : 96);
        asm volatile("fence.mbarrier_init.release.cluster;" ::: "memory");
      }
      if (i >= 64 && i < 64 + M_COUNT) asm volatile("prefetch.tensormap [%0];" :: "l"(&prm.m[i - 64]) : "memory");
    }
    if (warp == 12) {
      __syncwarp();
      {
        const CUtensorMap* mwp = &prm.m[sw64 ? M_W64 : M_W128];
        const int mcol = (c * 80 + (c & 1) * 16) >> (sw64 ? 5 : 6), rcol = c * 80 + ((c & 1) ? 0 : 64);
        uint32_t s = 0, ph = 1, xs = 0;
        #pragma unroll 1
        for (int kb = 0; kb < 20; kb++) {
          if (kb == 2) bar_sync(0, 512);
          if (kb >= 5) mbar_wait(BAR(BR_EMPTY) + 8 * s, ph);
          if (EN_ATT && elect_one()) {
            const uint32_t st = sb + s * W_SLOT, fb = BAR(BR_FULL) + 8 * s;
            mbar_expect_tx(fb, (kb & 1) ? W_SLOT : W_SLOT + 16384);
            if (!(kb & 1)) tma2d(sb + OFF_X + xs, &prm.m[M_X], fb, kb * 32, r * 128);
            tma4d(st, mwp, fb, 0, kb * 32, mcol, 0);
            tma3d(st + 12288, &prm.m[M_WR], fb, rcol, kb * 32, 0);
          }
          if (!EN_ATT && kb == 2) break;
          if (++s == 5) { s = 0; ph ^= 1; }
          if (kb & 1) { xs += 16384; if (xs == 49152) xs = 0; }
        }
      }
      if (EN_ATT) {
      mbar_wait(BAR(BR_EPOCH), 0);
      const unsigned epoch = lds32(sb + OFF_EPOCH);
      const unsigned* fo = &g_flag[(24 + r) * 32 + (lane & 7)];
      unsigned seen = __ballot_sync(0xffffffff, ld_rlx(fo) == epoch) | ld_rlx(&g_flag[c * 32 + 16]);
      mbar_wait(BAR(BR_GEMM), 0);
      if (elect_one()) {
        mbar_arrive(BAR(BR_OFULL));
        mbar_expect_tx(BAR(BR_WO), 20480 + 10240);
        tma2d(sb + OFF_WOM, &prm.m[M_WO], BAR(BR_WO), c * 64, c * 80);
        #pragma unroll 1
        for (int i = 0; i < 4; i++) tma2d(sb + i * 5120, &prm.m[M_WOR], BAR(BR_WO), 512 + c * 16, i * 160);
        mbar_expect_tx(BAR(BR_KVP), 61440);
        mbar_expect_tx(BAR(BR_WO + 1), 7 * 10240);
      }
      mbar_wait(BAR(BR_PUB), 0);
      poll_all(&g_flag[c * 32 + (lane & 15)], epoch);
      if (elect_one()) { TS(23); bulk_ld(sb + OFF_KVP, &g_kvp[c * 16 * 240], 61440, BAR(BR_KVP)); }
      mbar_wait(BAR(BR_OSTG), 0);
      if (elect_one()) {
        bulk_st(&g_o[cta * 1280], sb + OFF_EXTRA, 20480);
        bulk_commit();
        #pragma unroll 1
        for (int i = 1; i < 8; i++) tma2d(sb + OFF_WOM + i * 10240, &prm.m[M_WO], BAR(BR_WO + 1), c * 64, CHUNK(i) * 80);
        bulk_wait0();
        st_rlx(&g_flag[(24 + r) * 32 + c], epoch);
        TS(20);
      }
      __syncwarp();
      #pragma unroll 1
      for (int i = 1; i < 8; i++) {
        const int src = CHUNK(i), sl = i & 3;
        if (!((seen >> src) & 1)) seen = poll_bit(fo, epoch, 1u << src);
        if (i >= 4) mbar_wait(BAR(BR_OEMPTY) + 8 * sl, 0);
        else if (EN_SSM && i < 3) mbar_wait(BAR(BR_FREE - 1) + 8 * i, 0);
        if (elect_one()) {
          mbar_expect_tx(BAR(BR_OFULL) + 8 * sl, 20480);
          bulk_ld(sb + SLOT(sl), &g_o[(r * 8 + src) * 1280], 20480, BAR(BR_OFULL) + 8 * sl);
          if (i == 1) TS(21);
        }
        __syncwarp();
      }
      if (lane == 0) { TS(22); DUMP(20, 30); }
      }
    } else {
      const int hw = warp - 13, ht = tid - 416;
      unsigned epoch = 0;
      if (EN_SSM && ht < 80) {
        const int rr = ht / 10;
        const char* gs = reinterpret_cast<const char*>(prm.u) + (size_t)(r * 128 + rr) * 1280 + c * 160 + (ht - rr * 10) * 16;
        uint32_t ds = sb + OFF_BLK + 3 * BLK + B_D + ht * 16;
        #pragma unroll 1
        for (int i = 0; i < 16; i++) {
          asm volatile("cp.async.cg.shared.global [%0], [%1], 16;" :: "r"(ds), "l"(gs) : "memory");
          ds += i == 7 ? BLK - 7 * 1280 : 1280; gs += 10240;
        }
      }
      bar_sync(0, 512);
      if (hw == 0) {
        if (lane == 0) {
          epoch = ld_rlx(&g_epoch[cta]) + 1;
          st_rlx(&g_epoch[cta], epoch);
          sts32(sb + OFF_EPOCH, epoch);
          mbar_arrive(BAR(BR_EPOCH));
        }
        epoch = __shfl_sync(0xffffffff, epoch, 0);
      }
      if (EN_SSM) {
      const int mi = lane >> 3, rw = lane & 7, ch0 = c * 80 + r * 5;
      asm volatile("cp.async.wait_all;" ::: "memory");
      bar_sync(5, 96);
      if (ht == 0) TS(36);
      {
        uint4* gp = reinterpret_cast<uint4*>(g_uy + (size_t)(c * 80 + hw * 8 + (lane >> 2)) * 2048 + r * 128 + (lane & 3) * 8);
        uint32_t sa = sb + OFF_BLK + 3 * BLK + B_D + (8 * (rw >> 1) + 2 * mi + (rw & 1)) * 160 + hw * 16;
        #pragma unroll 1
        for (int i = hw; i < 10; i += 3) {
          uint32_t v[4][4];
          #pragma unroll
          for (int q = 0; q < 4; q++) ldsm4t(v[q], sa + (q >> 1) * BLK + (q & 1) * 5120);
          #pragma unroll
          for (int q = 0; q < 4; q++) {
            gp[q * 4] = make_uint4(v[q][0], v[q][1], v[q][2], v[q][3]);
            if (q & 1) __nanosleep(U_PACE);
          }
          gp += 6144; sa += 48;
        }
      }
      bar_sync(5, 96);
      if (hw == 0) {
        if (lane == 0) { st_rel(&g_flag[(8 + c) * 32 + r], epoch); TS(30); }
        __syncwarp();
        poll_all_acq(&g_flag[(8 + c) * 32 + (lane & 15)], epoch);
      }
      #pragma unroll 1
      for (int k = 4; k >= 0; k--) {
        const uint32_t blk = sb + OFF_BLK + k * BLK;
        if (k == 2) mbar_wait(BAR(BR_KGEN), 0);
        if (hw == 0 && !(k & 1) && k && elect_one()) {
          const uint32_t br = BAR(k == 4 ? BR_U : BR_U2);
          fence_async_g();
          mbar_expect_tx(br, k == 4 ? 12288 : 8192);
          #pragma unroll 1
          for (int q = k == 4 ? 4 : 1; q >= k - 2; q--) tma2d(sb + OFF_BLK + q * BLK, &prm.m[M_SB], br, 0, (ch0 + q) * 32);
          TS(31);
        }
        mbar_wait(BAR(k >= 2 ? BR_U : BR_U2), 0);
        #pragma unroll 1
        for (int kap = ht; kap < 192; kap += 96) {
          float P[33];
          P[0] = 0.f;
          #pragma unroll
          for (int q = 0; q < 4; q++) {
            const int ch = kap - 3 + q;
            uint32_t v[4];
            lds128(v, blk + (uint32_t)((ch * 16) ^ ((ch * 2) & 0x70)));
            #pragma unroll
            for (int e = 0; e < 4; e++) {
              P[q * 8 + 2 * e + 1] = (q == 0 && e < 2) ? 0.f : P[q * 8 + 2 * e] + bf_lo(v[e]);
              P[q * 8 + 2 * e + 2] = (q == 0 && e < 2) ? 0.f : P[q * 8 + 2 * e + 1] + bf_hi(v[e]);
            }
          }
#define WIN(lo, hi, e) (P[25 + (e) - (lo)] - P[24 + (e) - (hi)])
#define WIN8(lo, hi) pack2(WIN(lo, hi, 0), WIN(lo, hi, 1)), pack2(WIN(lo, hi, 2), WIN(lo, hi, 3)), pack2(WIN(lo, hi, 4), WIN(lo, hi, 5)), pack2(WIN(lo, hi, 6), WIN(lo, hi, 7))
          const uint32_t o2 = blk + B_D + (kap & 1) * 1552 + (kap >> 1) * 16;
          sts128(o2, WIN8(3, 5));
          sts128(o2 + B_D5, WIN8(6, 10));
          if (kap < 128) {
            const uint32_t o = blk + B_D + (kap & 1) * 1024 + (kap >> 1) * 16;
            sts128(o + B_D7, WIN8(5, 11));
            sts128(o + B_D9, WIN8(12, 20));
          }
        }
        if (ht < 2) sts128(blk + B_D + ht * B_D5 + 1536, 0, 0, 0, 0);
        mbar_arrive(BAR(BR_DRDY) + 8 * k);
      }
      if (ht == 0) TS(32);
      if (hw == 0) {
        #pragma unroll 1
        for (int p = 0; p < 2; p++) {
          mbar_wait(BAR(BR_Y4) + 8 * p, 0);
          if (elect_one()) {
            #pragma unroll 1
            for (int k = 4 - p; k >= 4 - 4 * p; k--) tma2d_st(&prm.m[M_SB], sb + OFF_BLK + k * BLK, 0, (640 + ch0 + k) * 32);
            bulk_commit(); bulk_wait0_read();
            mbar_arrive(BAR(BR_FREE) + 8 * p);
          }
          __syncwarp();
        }
        if (elect_one()) {
          mbar_expect_tx(BAR(BR_YIN), 20480);
          bulk_wait0();
          st_rel(&g_flag[(16 + c) * 32 + r], epoch);
          TS(33);
        }
        __syncwarp();
        poll_all_acq(&g_flag[(16 + c) * 32 + (lane & 15)], epoch);
        if (elect_one()) {
          fence_async_g();
          tma2d(sb + OFF_BLK + BLK, &prm.m[M_SA], BAR(BR_YIN), r * 128, 640 + c * 80);
          tma2d(sb + OFF_BLK + BLK + 10240, &prm.m[M_SA], BAR(BR_YIN), r * 128 + 64, 640 + c * 80);
          TS(34);
        }
      }
      {
        uint32_t sa = sb + OFF_BLK + BLK + (hw * 8 + rw) * 128 + ((mi ^ rw) << 4);
        uint32_t da = sb + OFF_BLK + (8 * mi + rw) * 160 + hw * 16;
        mbar_wait(BAR(BR_YIN), 0);
        #pragma unroll 1
        for (int i = hw; i < 10; i += 3) {
          uint32_t v[4][4];
          #pragma unroll
          for (int q = 0; q < 4; q++) ldsm4t(v[q], (sa ^ ((q & 1) * 64)) + (q >> 1) * 10240);
          #pragma unroll
          for (int q = 0; q < 4; q++) stsm4(da + q * 5120, v[q][0], v[q][1], v[q][2], v[q][3]);
          sa += 3072; da += 48;
        }
      }
      fence_async();
      bar_sync(5, 96);
      if (hw == 0 && elect_one()) {
        tma2d_st(&prm.m[M_OUT], sb + OFF_BLK, c * 80, r * 128);
        bulk_commit(); bulk_wait0_read();
        TS(35); DUMP(30, 40); DUMP(0, 1);
      }
      }
    }
  } else if (wg < 2) {
    asm volatile("setmaxnreg.inc.sync.aligned.u32 152;");
    bar_sync(0, 512);
    if (EN_ATT) {
    const int tq = lane & 3, t7 = tid & 127;
    float am[96], ar[24];
    {
      const uint64_t da0 = mkdesc(SB0 + OFF_X, 16, 1024, 1) + wg * 512;
      const uint64_t db0 = sw64 ? mkdesc(SB0, 2048, 512, 2) : mkdesc(SB0, 4096, 1024, 1);
      const uint32_t kst = sw64 ? 64 : 128;
      constexpr uint64_t dr0 = mkdesc(SB0 + 12288, 1024, 256, 3);
      uint32_t s = 0, ph = 0, xo = 0;
      #pragma unroll 1
      for (int kb = 0; kb < 20; kb++) {
        mbar_wait(BAR(BR_FULL) + 8 * s, ph);
        if (kb == 0 && tid == 0) TS(1);
        wg_fence();
        const uint32_t wo_ = s * (W_SLOT >> 4);
        wg_ss192_tb(am, da0 + xo, db0 + wo_, kb != 0);
        wg_ss48_tb(ar, da0 + xo, dr0 + wo_, kb != 0);
        wg_ss192_tb(am, da0 + xo + 2, db0 + wo_ + kst, 1);
        wg_ss48_tb(ar, da0 + xo + 2, dr0 + wo_ + 32, 1);
        wg_commit();
        wg_wait<1>();
        if (t7 == 0 && kb > 0 && kb < 16) mbar_arrive(BAR(BR_EMPTY) + 8 * (s == 0 ? 4 : s - 1));
        if (++s == 5) { s = 0; ph ^= 1; }
        xo += (kb & 1) ? 1020 : 4;
        if (xo == 3072) xo = 0;
      }
      wg_wait<0>();
      pin<96>(am); pin<24>(ar);
    }
    if (tid == 0) TS(2);
#define QV(j, e) ((j) < 8 ? am[4 * (j) + (e)] : ar[4 * ((j) - 8) + (e)])
#define KV_(j, e) ((j) < 8 ? am[32 + 4 * (j) + (e)] : ar[8 + 4 * ((j) - 8) + (e)])
#define VV(j, e) ((j) < 8 ? am[64 + 4 * (j) + (e)] : ar[16 + 4 * ((j) - 8) + (e)])
    {
      bar_sync(1, 256);
      if (tid == 0) mbar_arrive(BAR(BR_GEMM));
      const uint32_t ro = sb + (uint32_t)((warp * 16 + (lane & 15)) * 16);
      const int l0 = 2 * (c & 1) + (lane >> 4);
      const uint32_t ones = (tq == 0) ? 0x00003f80u : 0u;
#define PV(j) pack2(VV(j, 0), VV(j, 1)), pack2(VV(j, 2), VV(j, 3))
#define PK(j) pack2(phi(KV_(j, 0)), phi(KV_(j, 1))), pack2(phi(KV_(j, 2)), phi(KV_(j, 3)))
      stsm4(ro + OFF_V + (5 + 6 * (lane >> 4)) * 2048, ones, ones, ones, ones);
      #pragma unroll
      for (int j = 0; j < 10; j += 2) {
        const int l = (j == 8 && (c & 1)) ? l0 - 2 : l0 + j;
        stsm4(ro + OFF_V + (l + (l >= 5)) * 2048, PV(j), PV(j + 1));
        stsm4(ro + OFF_PK + l * 2048, PK(j), PK(j + 1));
      }
    }
    fence_async();
    bar_sync(1, 256);
    if (tid == 0) TS(3);
    mbar_wait(BAR(BR_EPOCH), 0);
    const unsigned epoch = lds32(sb + OFF_EPOCH);
    {
      float kv[24]; zero<24>(kv);
      const uint64_t da = mkdesc(SB0 + OFF_PK, 128, 2048, 0) + wg * 640, db = mkdesc(SB0 + OFF_V, 128, 2048, 0) + wg * 768;
      wg_fence();
      #pragma unroll
      for (int s = 0; s < 8; s++) wg_ss48_tt(kv, da + s * 16, db + s * 16, s != 0);
      wg_commit();
      wg_wait<0>();
      pin<24>(kv);
      if (tid == 0) TS(15);
      if (w4 < 3) {
        const uint32_t wb = sb + OFF_KVS + (wg * 3 + w4) * 1536 + (lane & 15) * 96;
        #pragma unroll
        for (int j = 0; j < 6; j += 2)
          stsm4(wb + (j + (lane >> 4)) * 16, pack2(kv[4 * j], kv[4 * j + 1]), pack2(kv[4 * j + 2], kv[4 * j + 3]),
                pack2(kv[4 * j + 4], kv[4 * j + 5]), pack2(kv[4 * j + 6], kv[4 * j + 7]));
        __syncwarp();
        const int dl = w4 * 16 + (lane & 15), hl = dl >= 20;
        if (dl < 40) {
          uint4* dst = &g_kvp[(c * 16 + r) * 240 + wg * 40 + dl];
          uint32_t v[4], z[4];
          lds128(v, wb + (3 * hl + (lane >> 4)) * 16);
          lds64(z, wb + 32 + 8 * hl); z[2] = lds32(wb + 80); z[3] = epoch & 1u;
          v[3] = (v[3] & ~1u) | z[3];
          st128_rlx(dst + (lane >> 4) * 80, v);
          if (lane < 16) st128_rlx(dst + 160, z);
        }
      }
    }
    fence_async();
    bar_sync(1, 256);
    if (tid == 0) { st_rlx(&g_flag[c * 32 + r], epoch); mbar_arrive(BAR(BR_PUB)); TS(4); }
    const int kvi = (tid >= 80) + (tid >= 160) + (tid >= 240), kd = tid - 80 * kvi;
    const int khd = kd / 20, kt0 = 5 * (khd >> 1) + 2 * (khd & 1);
    const uint32_t rb = sb + OFF_KVB + kd * 16;
    if (kvi < 3) {
      #pragma unroll 1
      for (int m = kvi; m < 7; m += 3) { const int q = kt0 + 3 + m; sts128(rb + (q >= 10 ? q - 10 : q) * 1280, 0, 0, 0, 0); }
    }
    uint32_t qa[20];
    {
      const float sc = 1.44269504089f + __uint_as_float(lds32(sb + OFF_EPOCH) ^ epoch);
      #pragma unroll
      for (int j = 0; j < 10; j++) { qa[2 * j] = pack2(phi(QV(j, 0), sc), phi(QV(j, 1), sc)); qa[2 * j + 1] = pack2(phi(QV(j, 2), sc), phi(QV(j, 3), sc)); }
    }
    if (tid == 0) TS(5);
    mbar_wait(BAR(BR_KVP), 0);
    if (tid == 0) TS(6);
    if (kvi < 3) {
      float s[8];
      zero<8>(s);
      #pragma unroll 2
      for (int i = 0; i < 16; i++) {
        uint32_t w[4];
        lds128(w, sb + OFF_KVP + tid * 16 + i * 3840);
        if (__builtin_expect((w[3] ^ epoch) & 1u, 0)) fix128_w3(w, &g_kvp[(c * 16 + i) * 240 + tid], epoch, 1u);
        #pragma unroll
        for (int e = 0; e < 4; e++) { s[2 * e] += bf_lo(w[e]); s[2 * e + 1] += bf_hi(w[e]); }
      }
      const uint32_t p0 = pack2(s[0], s[1]), p1 = pack2(s[2], s[3]), p2 = pack2(s[4], s[5]), p3 = pack2(s[6], s[7]);
      if (kvi < 2) sts128(rb + (kt0 + (khd & 1) + kvi) * 1280, p0, p1, p2, p3);
      else {
        const bool od = khd & 1;
        sts128(rb + (5 * (khd >> 1) + 2) * 1280, od ? 0u : p0, od ? 0u : p1, od ? p0 : 0u, od ? p1 : 0u);
        const uint32_t zz = (p2 & 0xffffu) << (16 * (khd & 1));
        sts128(rb + 10 * 1280, khd < 2 ? zz : 0u, khd < 2 ? 0u : zz, 0u, 0u);
      }
    }
    fence_async();
    bar_sync(1, 256);
    if (tid == 0) TS(7);
    const uint32_t fo = sb + (wg * 640 + t7) * 16;
    {
      float oa[44]; zero<44>(oa);
      constexpr uint64_t db = mkdesc(SB0 + OFF_KVB, 128, 1280, 0);
      wg_fence();
      #pragma unroll
      for (int s = 0; s < 5; s++) wg_rs88_tb(oa, &qa[4 * s], db + ((s == 4 && (c & 1)) ? 0 : (s + (c & 1)) * 16), s != 0);
      wg_commit();
      wg_wait<0>();
      pin<44>(oa);
      if (tid == 0) TS(13);
      float rc[4], rd[2][4];
      #pragma unroll
      for (int e = 0; e < 4; e++) asm("rcp.approx.ftz.f32 %0, %1;" : "=f"(rc[e]) : "f"(oa[40 + e] + 1e-6f));
      #pragma unroll
      for (int h = 0; h < 4; h++) {
        rd[0][h] = __shfl_sync(0xffffffff, rc[h & 1], (lane & 28) | (h >> 1));
        rd[1][h] = __shfl_sync(0xffffffff, rc[2 + (h & 1)], (lane & 28) | (h >> 1));
      }
      #pragma unroll
      for (int j = 0; j < 10; j++) {
        #pragma unroll
        for (int h = 0; h < 2; h++) {
          float f;
          if (j == 2) f = tq < 2 ? rd[h][0] : rd[h][1];
          else if (j == 7) f = tq < 2 ? rd[h][2] : rd[h][3];
          else f = rd[h][(8 * j) / 20];
          qa[2 * j + h] = pack2(oa[4 * j + 2 * h] * f, oa[4 * j + 2 * h + 1] * f);
        }
      }
      bar_sync(1, 256);
      #pragma unroll
      for (int s = 0; s < 5; s++)
        sts128(fo + OFF_EXTRA + s * 2048, (qa[4 * s] & ~1u) | (epoch & 1u), qa[4 * s + 1], qa[4 * s + 2], qa[4 * s + 3]);
    }
    fence_async();
    mbar_arrive(BAR(BR_OSTG));
    if (tid == 0) TS(8);
    float oc[32], od[8]; zero<32>(oc); zero<8>(od);
    {
      constexpr uint64_t dw0 = mkdesc(SB0 + OFF_WOM, 16, 1024, 1), dr0 = mkdesc(SB0, 16, 256, 3);
      uint32_t A[2][20];
      wg_fence();
      wg_rs64_tb(oc, qa, dw0, 0); wg_rs16_tb(od, qa, dr0, 0);
      wg_commit();
      #pragma unroll 1
      for (int i2 = 0; i2 < 8; i2 += 2) {
        #pragma unroll
        for (int b = 0; b < 2; b++) {
          const int i = i2 + b, sl = i & 3, src = CHUNK(i);
          mbar_wait(BAR(BR_OFULL) + 8 * sl, i >> 2);
          if (i == 1 && tid == 0) TS(9);
          wg_wait<1>();
          const uint32_t sa = fo + SLOT(sl);
          #pragma unroll
          for (int s = 0; s < 5; s++) lds128(&A[b][4 * s], sa + s * 2048);
          const uint32_t bad = ((A[b][0] ^ epoch) | (A[b][4] ^ epoch) | (A[b][8] ^ epoch) | (A[b][12] ^ epoch) | (A[b][16] ^ epoch)) & 1u;
          if (__builtin_expect(bad, 0)) {
            #pragma unroll 1
            for (int s = 0; s < 5; s++) {
              uint32_t w[4] = {~epoch, 0, 0, 0};
              fix128_w0(w, &g_o[(r * 8 + src) * 1280 + wg * 640 + s * 128 + t7], epoch, 1u);
              sts128(sa + s * 2048, w[0], w[1], w[2], w[3]);
            }
            #pragma unroll
            for (int s = 0; s < 5; s++) lds128(&A[b][4 * s], sa + s * 2048);
            fence_async();
          }
          __syncwarp();
          if (lane == 0) mbar_arrive(BAR(BR_OEMPTY) + 8 * sl);
          mbar_wait(BAR(BR_WO + b), 0);
          wg_fence();
          #pragma unroll
          for (int s = 0; s < 5; s++) { wg_rs64_tb(oc, &A[b][4 * s], dw0 + i * 640 + s * 128, (i | s) != 0); wg_rs16_tb(od, &A[b][4 * s], dr0 + src * 160 + s * 32, (i | s) != 0); }
          wg_commit();
        }
      }
      bar_sync(2 + wg, 128);
      wg_wait<0>();
      pin<32>(oc); pin<8>(od);
    }
    if (tid == 0) TS(10);
    {
      const int row = w4 * 16 + (lane & 15);
      const uint32_t ob = sb + OFF_EXTRA + wg * 10240;
      #pragma unroll
      for (int j = 0; j < 8; j += 2)
        stsm4(ob + row * 128 + (((j + (lane >> 4)) ^ (row & 7)) << 4), pack2(oc[4 * j], oc[4 * j + 1]), pack2(oc[4 * j + 2], oc[4 * j + 3]),
              pack2(oc[4 * j + 4], oc[4 * j + 5]), pack2(oc[4 * j + 6], oc[4 * j + 7]));
      stsm4(ob + 8192 + row * 32 + (lane >> 4) * 16, pack2(od[0], od[1]), pack2(od[2], od[3]), pack2(od[4], od[5]), pack2(od[6], od[7]));
      fence_async();
      bar_sync(2 + wg, 128);
      if (w4 == 0 && elect_one()) {
        tma2d_st(&prm.m[M_O64], ob, 640 + c * 64, r * 128 + wg * 64);
        tma2d_st(&prm.m[M_O16], ob + 8192, 1152 + c * 16, r * 128 + wg * 64);
        bulk_commit(); bulk_wait0_read();
        if (wg == 0) { TS(11); DUMP(0, 20); }
      }
    }
    }
  } else {
    uint4 pv[3];
    const uint4* pp = reinterpret_cast<const uint4*>(prm.par[w4] + (c * 80 + r * 5) * 128);
    pv[0] = __ldg(pp + lane); pv[1] = __ldg(pp + 32 + lane); pv[2] = __ldg(pp + 64 + (lane & 15));
    const int kq = c * 80 + r * 5 + min(lane, 4);
    const unsigned short ldt = __ldg(reinterpret_cast<const unsigned short*>(prm.logdt) + kq), dsk0 = __ldg(reinterpret_cast<const unsigned short*>(prm.dskip) + kq);
    asm volatile("setmaxnreg.inc.sync.aligned.u32 152;");
    bar_sync(0, 512);
    if (EN_SSM) {
    const int g = lane >> 2, tq = lane & 3, t7 = tid & 127;
    {
      #pragma unroll 1
      for (int k = 0; k < 5; k++) {
        const uint32_t tz = sb + OFF_BLK + k * BLK + B_TBL + t7 * 16;
        if (t7 < 32 || t7 >= 96) sts128(tz, 0, 0, 0, 0);
        if (t7 < 124) sts128(tz + 2048, 0, 0, 0, 0);
        if (t7 < 16) sts128(sb + OFF_BLK + k * BLK - 256 + t7 * 16, 0, 0, 0, 0);
      }
      if (t7 < 5) sts64(sb + OFF_BLK + t7 * BLK + B_SP + 8, __float_as_uint(bf_round(expf(bf_lo(ldt)))), (uint32_t)dsk0 << 16);
      const uint32_t st = sb + OFF_BLK + (lane >> 4) * BLK + B_TBL + 512 + w4 * 256 + (lane & 15) * 16;
      #pragma unroll
      for (int i = 0; i < 3; i++) {
        if (i < 2 || lane < 16) sts128(st + 2 * i * BLK, pv[i].x, pv[i].y, pv[i].z, pv[i].w);
        if (w4 >= 2) {
          const uint32_t m2 = __vmaxu2(__vmaxu2(pv[i].x & 0x7fff7fffu, pv[i].y & 0x7fff7fffu), __vmaxu2(pv[i].z & 0x7fff7fffu, pv[i].w & 0x7fff7fffu));
          const uint32_t m = __reduce_max_sync(lane < 16 ? 0x0000ffffu : 0xffff0000u, max(m2 & 0xffffu, m2 >> 16));
          if ((lane & 15) == 0 && (i < 2 || lane == 0)) sts32(sb + OFF_BLK + (2 * i + (lane >> 4)) * BLK + B_SP + 8 + w4 * 4, m);
        }
      }
    }
    bar_sync(4, 128);
    if (t7 == 0) TS(40);
    {
      const uint32_t fa = sb + OFF_BLK + (w4 & 1) * BLK + (lane >> 3) * 256 + (lane & 7) * 16;
      const uint32_t ea = fa + (w4 >> 1) * 4096, ga = fa + 8192 + (w4 >> 1) * 3072;
      constexpr uint64_t dE = mkdesc(SB0 + OFF_BLK, 128, 1024, 0), dG = mkdesc(SB0 + OFF_BLK + 8192, 128, 1024, 0);
      #pragma unroll 1
      for (int k = 4; k >= 0; k--) {
        const uint32_t blk = sb + OFF_BLK + k * BLK;
        float fac, dsk;
        {
          const uint32_t st = blk + B_TBL + 512 + t7 * 2;
          uint32_t q[2], mm[2];
          const uint32_t p0 = lds16(st), p1 = lds16(st + 256), p2 = lds16(st + 512), p3 = lds16(st + 768);
          lds64(q, blk + B_SP + 8); lds64(mm, blk + B_SP + 16);
          const float dt = __uint_as_float(q[0]); dsk = __uint_as_float(q[1]);
          const uint32_t ex = min(max(max(mm[0], mm[1]) >> 7, 1u), 253u);
          const float sc = __uint_as_float((254u - ex) << 23);
          fac = 2.f * dt * __uint_as_float(ex << 23);
          const float lr = -bf_round(expf(bf_lo(p0))) * dt * 1.44269504089f;
          const float tn = bf_lo(p1) * dt * 0.15915494309f;
          float z1r, z1i, z2r, z2i, z4r, z4i, xr[8], xi[8], gr[8], gi[8], wr[9], wi[9];
          cexp_t(lr, -tn, z1r, z1i);
          cexp_t(lr * 8.f, tn * 8.f, xr[1], xi[1]);
          cexp_t(lr * 64.f, tn * 64.f, wr[0], wi[0]);
          xr[0] = 1.f; xi[0] = 0.f;
          cmul(xr[1], xi[1], xr[1], xi[1], xr[2], xi[2]); cmul(xr[2], xi[2], xr[1], xi[1], xr[3], xi[3]);
          cmul(xr[2], xi[2], xr[2], xi[2], xr[4], xi[4]);
          #pragma unroll
          for (int b = 1; b < 4; b++) cmul(xr[4], xi[4], xr[b], xi[b], xr[4 + b], xi[4 + b]);
          cmul(wr[0], wi[0], wr[0], wi[0], wr[1], wi[1]); cmul(wr[1], wi[1], wr[0], wi[0], wr[2], wi[2]);
          cmul(wr[1], wi[1], wr[1], wi[1], wr[3], wi[3]); cmul(wr[3], wi[3], wr[3], wi[3], wr[4], wi[4]);
          cmul(wr[4], wi[4], wr[3], wi[3], wr[5], wi[5]); cmul(wr[4], wi[4], wr[4], wi[4], wr[6], wi[6]);
          cmul(wr[6], wi[6], wr[4], wi[4], wr[7], wi[7]); cmul(wr[6], wi[6], wr[6], wi[6], wr[8], wi[8]);
          uint32_t R[4], I[4], PR[4], PI[4];
          #pragma unroll
          for (int b = 0; b < 4; b++) { R[b] = packh(xr[2 * b], xr[2 * b + 1]); I[b] = packh(xi[2 * b], xi[2 * b + 1]); }
          sts128(ea, R[0], R[1], R[2], R[3]); sts128(ea + 128, I[0], I[1], I[2], I[3]);
          #pragma unroll
          for (int i = 0; i < 3; i++) {
            const uint32_t z = packh(wr[i], wi[i]);
            #pragma unroll
            for (int b = 0; b < 4; b++) hcm2(R[b], I[b], z, PR[b], PI[b]);
            sts128(ea + (i + 1) * 1024, PR[0], PR[1], PR[2], PR[3]); sts128(ea + (i + 1) * 1024 + 128, PI[0], PI[1], PI[2], PI[3]);
          }
          gr[0] = bf_lo(p2) * sc; gi[0] = -bf_lo(p3) * sc;
          cmul(z1r, z1i, z1r, z1i, z2r, z2i); cmul(z2r, z2i, z2r, z2i, z4r, z4i);
          cmul(gr[0], gi[0], z1r, z1i, gr[1], gi[1]);
          cmul(gr[0], gi[0], z2r, z2i, gr[2], gi[2]); cmul(gr[1], gi[1], z2r, z2i, gr[3], gi[3]);
          #pragma unroll
          for (int b = 0; b < 4; b++) cmul(gr[b], gi[b], z4r, z4i, gr[4 + b], gi[4 + b]);
          sts128(ga, packh(gr[0], gr[1]), packh(gr[2], gr[3]), packh(gr[4], gr[5]), packh(gr[6], gr[7]));
          sts128(ga + 128, packh(gi[0], gi[1]), packh(gi[2], gi[3]), packh(gi[4], gi[5]), packh(gi[6], gi[7]));
          {
            const uint32_t z = packh(wr[3], -wi[3]), a4r = packh(gr[0], gr[4]), a4i = packh(gi[0], gi[4]);
            hcm2(packh(gr[0], gr[2]), packh(gi[0], gi[2]), z, PR[0], PI[0]);
            hcm2(packh(gr[4], gr[6]), packh(gi[4], gi[6]), z, PR[1], PI[1]);
            hcm2(a4r, a4i, packh(wr[4], -wi[4]), PR[2], PI[2]);
            hcm2(a4r, a4i, packh(wr[5], -wi[5]), PR[3], PI[3]);
            sts128(ga + 1024, PR[0], PR[1], PR[2], PR[3]); sts128(ga + 1024 + 128, PI[0], PI[1], PI[2], PI[3]);
            float hr, hi_;
            cmul(gr[0], gi[0], wr[3], -wi[3], hr, hi_);
            const uint32_t cr = packh(gr[0], hr), ci = packh(gi[0], hi_);
            #pragma unroll
            for (int i = 0; i < 3; i++) hcm2(cr, ci, packh(wr[6 + i], -wi[6 + i]), PR[i], PI[i]);
            sts128(ga + 2048, PR[0], PR[1], PR[2], 0u); sts128(ga + 2048 + 128, PI[0], PI[1], PI[2], 0u);
          }
        }
        fence_async();
        bar_sync(4, 128);
        if (t7 == 0 && k == 3) TS(50);
        float ka[24]; zero<24>(ka);
        wg_fence();
        #pragma unroll
        for (int s = 0; s < 8; s++) wg_ss48_tt_h(ka, dE + (s >> 2) * (BLK >> 4) + (s & 3) * 16, dG + (s >> 2) * (BLK >> 4) + (s & 3) * 16, s != 0);
        wg_commit();
        wg_wait<0>();
        pin<24>(ka);
        if (t7 == 0 && k == 3) TS(51);
        float kk[6];
        {
          const bool up = w4 >= 2;
          const uint32_t xa = sb + OFF_BLK + 2 * BLK + B_D + 7168 + t7 * 8;
          #pragma unroll
          for (int n = 0; n < 3; n++) {
            sts64f(xa + n * 1024, up ? ka[12 + 4 * n] : ka[4 * n + 2], up ? ka[13 + 4 * n] : ka[4 * n + 3]);
            kk[2 * n] = up ? ka[14 + 4 * n] : ka[4 * n]; kk[2 * n + 1] = up ? ka[15 + 4 * n] : ka[4 * n + 1];
          }
          bar_sync(4, 128);
          #pragma unroll
          for (int n = 0; n < 3; n++) {
            uint32_t o[2]; lds64(o, (xa ^ 512) + n * 1024);
            kk[2 * n] = (kk[2 * n] + __uint_as_float(o[0])) * fac; kk[2 * n + 1] = (kk[2 * n + 1] + __uint_as_float(o[1])) * fac;
          }
        }
        if (t7 == 0 && k == 3) TS(52);
        {
          const int j = (w4 & 1) * 16 + (w4 >> 1) * 8 + g;
          const uint32_t tb = blk + B_TBL;
          if (t7 == 0) kk[0] += dsk;
          const uint32_t pa_ = tb + (16 + 8 * j + 2 * tq) * 4;
          const uint32_t v = pack2(kk[1], kk[0]);
          sts32(pa_ + 4, v); sts16(pa_, v >> 16); sts16(pa_ + 10, v);
          const uint32_t u = pack2(kk[2], kk[3]), w = pack2(kk[4], kk[5]);
          if (tq < 2) {
            const uint32_t pb = tb + (16 + 256 + 8 * j + 4 * tq) * 4;
            sts16(pb, u); sts32(pb + 4, __byte_perm(u, 0, 0x1010)); sts32(pb + 8, __byte_perm(u, 0, 0x1032)); sts16(pb + 14, u >> 16);
            if (j | tq) { sts16(pb - 4, u); sts16(pb + 2, u); }
            const int i = 64 * tq + j;
            const uint32_t e0 = tb + (T_F3 + (((i - 1) & 1) ? 80 : 0) + ((i - 1) >> 1)) * 4, e1 = i ? e0 : tb + (T_F2 + 144 + 31) * 4;
            sts16(e1, w); sts16(e1 + 6, w); sts16(e0 + 64, w >> 16); sts16(e0 + 70, w >> 16);
            if (i == 0) { sts16(tb + (T_S + 3) * 4, w); sts32(tb + (T_S + 4) * 4, __byte_perm(w, 0, 0x1010)); sts16(tb + (T_S + 5) * 4 + 2, w); }
          } else {
            const int i = 32 * (tq - 2) + j;
            const uint32_t e1 = tb + (i ? T_F2 + ((2 * i - 1) & 3) * 48 + ((2 * i - 1) >> 2) : 16 + 511) * 4;
            const uint32_t e2 = tb + (T_F2 + (i & 1) * 96 + (i >> 1)) * 4;
            sts16(e1, u); sts16(e1 + 6, u); sts16(e2, u >> 16); sts16(e2 + 6, u >> 16);
            if (i == 0) {
              const uint32_t uu = __byte_perm(u, 0, 0x1010);
              sts32(tb + 528 * 4, uu); sts32(tb + 529 * 4, uu); sts32(tb + 530 * 4, uu); sts16(tb + 531 * 4 + 2, u);
              sts16(tb + (T_F3 + 80 + 63) * 4, w);
            }
          }
        }
        if (t7 == 0 && k == 3) TS(53);
      }
      bar_sync(4, 128);
      if (t7 == 0) { mbar_arrive(BAR(BR_KGEN)); TS(41); }
    }
    mbar_wait(BAR(BR_U), 0);
    if (EN_ATT) mbar_wait(BAR(BR_GEMM), 0);
    if (t7 == 0) TS(42);
    #pragma unroll 1
    for (int pass = 0; pass < 2; pass++) {
      const int k = pass ? w4 : 4;
      const uint32_t blk = sb + OFF_BLK + k * BLK, tb = blk + B_TBL + (uint32_t)((g - 2 * tq) * 4);
      if (k < 2) mbar_wait(BAR(BR_U2), 0);
      float acc[16][4];
      zero<64>(&acc[0][0]);
      const int kl = 16 * (lane >> 4) + 2 * (lane & 7) + ((lane >> 3) & 1);
      {
        auto ubase = [&](int sh) { const int q = kl - 2 * sh; return blk + (uint32_t)((q * 16) ^ ((q * 2) & 0x70)); };
#define LDQ(A, sh) _Pragma("unroll") for (int m = 0; m < 4; m++) load_quad(A[m], tb + (16 + 16 * (sh) + 128 * m) * 4);
#define LDB(B, ub, h) _Pragma("unroll") for (int p = 0; p < 4; p++) ldsm4(B[p], ((ub) ^ ((p & 1) * 64)) + (4 * (h) + p) * 512);
#define MLO(A, B) _Pragma("unroll") for (int m = 0; m < 4; m++) _Pragma("unroll") for (int cc = 0; cc < 8; cc++) mma16816(acc[cc + m], A[m], &B[cc >> 1][(cc & 1) * 2]);
#define MHI(A, B) _Pragma("unroll") for (int m = 0; m < 4; m++) _Pragma("unroll") for (int cc = 0; cc < 8 - m; cc++) mma16816(acc[8 + cc + m], A[m], &B[cc >> 1][(cc & 1) * 2]);
        int p_ = pass ? 0 : w4;
        const int pe = pass ? 4 : w4 + 1;
        uint32_t A[4][4], A2[4][4], Bl[4][4], Bh[4][4];
        uint32_t ub = ubase(p_ + 4);
        LDQ(A, p_ + 4) LDB(Bl, ub, 0)
        #pragma unroll 1
        for (; p_ < pe; p_++) {
          LDB(Bh, ub, 1)
          MLO(A, Bl)
          ub = ubase(p_);
          LDQ(A2, p_) LDB(Bl, ub, 0)
          MHI(A, Bh)
          LDB(Bh, ub, 1)
          load_quad(A[0], tb + (16 + 512 + 16 * (p_ & 1)) * 4); load_quad(A[1], tb + (T_S + 16 * (p_ & 1)) * 4);
          MLO(A2, Bl)
          if (p_ < 2) {
            #pragma unroll
            for (int cc = 0; cc < 8; cc++) mma16816(acc[cc + 4], A[0], &Bl[cc >> 1][(cc & 1) * 2]);
            #pragma unroll
            for (int cc = 0; cc < 4; cc++) mma16816(acc[cc + 12], A[0], &Bh[cc >> 1][(cc & 1) * 2]);
            #pragma unroll
            for (int cc = 0; cc < 8; cc++) mma16816(acc[cc + 8], A[1], &Bl[cc >> 1][(cc & 1) * 2]);
          }
          const int pn = ((p_ + 1) & 3) + 4;
          ub = ubase(pn);
          LDQ(A, pn) LDB(Bl, ub, 0)
          MHI(A2, Bh)
        }
      }
      if (t7 == 0) TS(57 + 3 * pass);
      mbar_wait(BAR(BR_DRDY) + 8 * k, 0);
      {
        const int ih = (lane >> 3) & 1;
        const uint32_t dl = blk + B_D + (uint32_t)(((lane >> 4) * 8 + (lane & 7)) * 16);
        const uint32_t d0_ = dl + ih * 1552, d8_ = dl + (ih ? 0 : 1536), d3_ = dl + B_D7 + ih * 1024;
        auto cls2 = [&](uint32_t da, uint32_t ta) {
          uint32_t B[6][2], A[6][4];
          #pragma unroll
          for (int e = 0; e < 6; e++) { B[e][0] = lds32v(ta + (e + 4) * 32); B[e][1] = lds32v(ta + (e + 3) * 32); }
          #pragma unroll
          for (int kk = 0; kk < 6; kk++) ldsm4t(A[kk], da + kk * 256);
          #pragma unroll
          for (int e = 0; e < 6; e++)
            #pragma unroll
            for (int kk = 0; kk < 6; kk++) if (2 * kk + e + 4 < 16) mma16816(acc[2 * kk + e + 4], A[kk], B[e]);
        };
        auto cls3 = [&](uint32_t da, uint32_t ta) {
          uint32_t B[8][2], A[4][4];
          #pragma unroll
          for (int e = 0; e < 8; e++) { B[e][0] = lds32v(ta + (e + 8) * 32); B[e][1] = lds32v(ta + (e + 7) * 32); }
          #pragma unroll
          for (int kk = 0; kk < 4; kk++) ldsm4t(A[kk], da + kk * 256);
          #pragma unroll
          for (int kk = 0; kk < 4; kk++)
            #pragma unroll
            for (int e = 0; e < 8; e++) if (2 * kk + e + 8 < 16) mma16816(acc[2 * kk + e + 8], A[kk], B[e]);
        };
        #pragma unroll 1
        for (int a = pass ? 0 : w4; a < (pass ? 4 : w4 + 1); a++) cls2(((a & 2) ? d8_ : d0_) + (a & 1) * B_D5, tb + (T_F2 + 48 * a - 32) * 4);
        #pragma unroll 1
        for (int b = pass ? 0 : (w4 & 1); b < (pass ? 2 : w4 - 1); b++) cls3(d3_ + b * 2048, tb + (T_F3 + 80 * b - 64) * 4);
      }
      if (t7 == 0) TS(58 + 3 * pass);
      const uint32_t ya = blk + (uint32_t)((kl * 16) ^ ((kl * 2) & 0x70));
#define STY(p) stsm4t((ya ^ (((p) & 1) * 64)) + (p) * 512, pack2(acc[2 * (p)][0], acc[2 * (p)][1]), pack2(acc[2 * (p)][2], acc[2 * (p)][3]), \
                      pack2(acc[2 * (p) + 1][0], acc[2 * (p) + 1][1]), pack2(acc[2 * (p) + 1][2], acc[2 * (p) + 1][3]))
      if (pass == 0) {
        const uint32_t xw = blk + 4096 + w4 * 4096 + lane * 16, xr = blk + 4096 + w4 * 1024 + lane * 16;
        #pragma unroll
        for (int h = 0; h < 2; h++) {
          bar_sync(4, 128);
          #pragma unroll
          for (int i = 0; i < 8; i++)
            sts128(xw + i * 512, __float_as_uint(acc[8 * h + i][0]), __float_as_uint(acc[8 * h + i][1]), __float_as_uint(acc[8 * h + i][2]), __float_as_uint(acc[8 * h + i][3]));
          bar_sync(4, 128);
          float y[8];
          #pragma unroll
          for (int i = 0; i < 8; i++) {
            uint32_t o[4]; lds128(o, xr + (i >> 1) * 4096 + (i & 1) * 512);
            #pragma unroll
            for (int e = 0; e < 4; e++) y[4 * (i & 1) + e] = i < 2 ? __uint_as_float(o[e]) : y[4 * (i & 1) + e] + __uint_as_float(o[e]);
          }
          stsm4t((ya ^ ((w4 & 1) * 64)) + (4 * h + w4) * 512, pack2(y[0], y[1]), pack2(y[2], y[3]), pack2(y[4], y[5]), pack2(y[6], y[7]));
        }
      } else {
        __syncwarp();
        #pragma unroll
        for (int p = 0; p < 8; p++) STY(p);
      }
      if (t7 == 0 && !pass) TS(55);
      fence_async();
      mbar_arrive(BAR(BR_Y4) + 8 * pass);
      if (t7 == 0) TS(59 + 3 * pass);
    }
    if (t7 == 0) DUMP(40, 64);
    }
  }
}

typedef CUresult (*EncFn)(CUtensorMap*, CUtensorMapDataType, cuuint32_t, void*, const cuuint64_t*, const cuuint64_t*, const cuuint32_t*,
                          const cuuint32_t*, CUtensorMapInterleave, CUtensorMapSwizzle, CUtensorMapL2promotion, CUtensorMapFloatOOBfill);
static void mkmap(EncFn enc, CUtensorMap* m, const void* base, int rank, const cuuint64_t* dims, const cuuint64_t* strides, const cuuint32_t* box, CUtensorMapSwizzle swz) {
  cuuint32_t es[5] = {1, 1, 1, 1, 1};
  enc(m, CU_TENSOR_MAP_DATA_TYPE_BFLOAT16, rank, const_cast<void*>(base), dims, strides, box, es, CU_TENSOR_MAP_INTERLEAVE_NONE, swz,
      CU_TENSOR_MAP_L2_PROMOTION_L2_128B, CU_TENSOR_MAP_FLOAT_OOB_FILL_NONE);
}

extern "C" void kernel_launch(void* const* d_in, const int* in_sizes, int n_in, void* d_out, int out_size) {
  void* fn = nullptr; cudaDriverEntryPointQueryResult qr;
  cudaGetDriverEntryPoint("cuTensorMapEncodeTiled", &fn, cudaEnableDefault, &qr);
  EncFn enc = (EncFn)fn;
  void* uy = nullptr; cudaGetSymbolAddress(&uy, g_uy);
  const cuuint64_t dx[2] = {640, 2048}, sx[1] = {1280};
  const cuuint32_t bx[2] = {64, 128}, bu[2] = {80, 128};
  const cuuint64_t dw[3] = {640, 640, 3}, sw[2] = {3840, 1280};
  const cuuint32_t br[3] = {16, 32, 3};
  const cuuint64_t dwa[4] = {64, 640, 10, 3}, swa[3] = {3840, 128, 1280}, dwb[4] = {32, 640, 20, 3}, swb[3] = {3840, 64, 1280};
  const cuuint32_t bwa[4] = {64, 32, 1, 3}, bwb[4] = {32, 32, 2, 3};
  const cuuint64_t dwo[2] = {640, 640};
  const cuuint32_t bwo[2] = {64, 80}, bwr[2] = {16, 160}, bo64[2] = {64, 64}, bo16[2] = {16, 64};
  const cuuint64_t dsa[2] = {2048, 1280}, ssa[1] = {4096};
  const cuuint32_t bsa[2] = {64, 80};
  const cuuint64_t dsb[2] = {64, 40960}, ssb[1] = {128};
  const cuuint32_t bsb[2] = {64, 32};
  const cuuint64_t dout[2] = {1280, 2048}, sout[1] = {2560};
  Params prm;
  mkmap(enc, &prm.m[M_X], d_in[7], 2, dx, sx, bx, CU_TENSOR_MAP_SWIZZLE_128B);
  mkmap(enc, &prm.m[M_W128], d_in[8], 4, dwa, swa, bwa, CU_TENSOR_MAP_SWIZZLE_128B);
  mkmap(enc, &prm.m[M_W64], d_in[8], 4, dwb, swb, bwb, CU_TENSOR_MAP_SWIZZLE_64B);
  mkmap(enc, &prm.m[M_WR], d_in[8], 3, dw, sw, br, CU_TENSOR_MAP_SWIZZLE_32B);
  mkmap(enc, &prm.m[M_WO], d_in[9], 2, dwo, sx, bwo, CU_TENSOR_MAP_SWIZZLE_128B);
  mkmap(enc, &prm.m[M_WOR], d_in[9], 2, dwo, sx, bwr, CU_TENSOR_MAP_SWIZZLE_32B);
  mkmap(enc, &prm.m[M_O64], d_out, 2, dout, sout, bo64, CU_TENSOR_MAP_SWIZZLE_128B);
  mkmap(enc, &prm.m[M_O16], d_out, 2, dout, sout, bo16, CU_TENSOR_MAP_SWIZZLE_NONE);
  mkmap(enc, &prm.m[M_SA], uy, 2, dsa, ssa, bsa, CU_TENSOR_MAP_SWIZZLE_128B);
  mkmap(enc, &prm.m[M_SB], uy, 2, dsb, ssb, bsb, CU_TENSOR_MAP_SWIZZLE_128B);
  mkmap(enc, &prm.m[M_OUT], d_out, 2, dout, sout, bu, CU_TENSOR_MAP_SWIZZLE_NONE);
  prm.u = (const __nv_bfloat16*)d_in[0];
  for (int i = 0; i < 4; i++) prm.par[i] = (const __nv_bfloat16*)d_in[1 + i];
  prm.logdt = (const __nv_bfloat16*)d_in[5]; prm.dskip = (const __nv_bfloat16*)d_in[6];
  cudaFuncSetAttribute(fused_kernel, cudaFuncAttributeMaxDynamicSharedMemorySize, SMEM_BYTES);
  cudaLaunchConfig_t cfg = {};
  cfg.gridDim = dim3(128); cfg.blockDim = dim3(512); cfg.dynamicSmemBytes = SMEM_BYTES; cfg.stream = cudaStreamPerThread;
  cudaLaunchAttribute at[1];
  at[0].id = cudaLaunchAttributeClusterDimension; at[0].val.clusterDim.x = 2; at[0].val.clusterDim.y = 1; at[0].val.clusterDim.z = 1;
  cfg.attrs = at; cfg.numAttrs = 1;
  cudaLaunchKernelEx(&cfg, fused_kernel, prm);
}
```

```cpp
#include <cuda_runtime.h>
#include <cuda_bf16.h>
#include <cuda_fp16.h>
#include <cuda.h>
#include <stdint.h>

#define U_PACE 250
#define U_DELAY 0
#define U_LPACE 0
#define EN_ATT 1
#define EN_SSM 1

__device__ __align__(1024) __nv_bfloat16 g_uy[2 * 640 * 2048];
__device__ __align__(128) uint4 g_kvp[8 * 16 * 240];
__device__ __align__(128) uint4 g_o[128 * 1280];
__device__ __align__(128) unsigned g_flag[4 * 128 * 32];
__device__ unsigned g_epoch[128];
#define TS(i) do {} while (0)
#define DUMP(lo, hi) do {} while (0)
#define FIXCNT

constexpr uint32_t SB0 = 1024;
constexpr uint32_t W_SLOT = 15360, OFF_X = 76800;
constexpr uint32_t OFF_WOR = 81920, OFF_KVP = 10240, OFF_KVS = 71680, OFF_PK = 10240, OFF_V = 30720, OFF_EXTRA = 102400, OFF_KVB = OFF_EXTRA;
constexpr uint32_t OFF_BAR = 125952, OFF_BLK = 128000, BLK = 20480;
constexpr uint32_t B_D = 4096, B_D5 = 3088, B_D7 = 6176, B_D9 = 8224, B_TBL = 14400, B_SP = 18432;
constexpr int T_S = 576, T_F2 = 624, T_F3 = 816;
constexpr uint32_t SMEM_BYTES = OFF_BLK + 5 * BLK;
enum { BR_FULL = 0, BR_WO = 5, BR_PUB = 7, BR_KVP = 8, BR_U = 9, BR_U2 = 10, BR_GEMM = 11, BR_KGEN = 12, BR_YIN = 13, BR_EPOCH = 14,
       BR_FREE = 15, BR_RETRY = 17, BR_OFULL = 18, BR_EMPTY = 26, BR_OEMPTY = 31, BR_Y4 = 38, BR_Y03 = 39, BR_OSTG = 40, BR_DRDY = 41, BR_COUNT = 46 };
constexpr uint32_t OFF_EPOCH = OFF_BAR + 8 * BR_COUNT;
enum { M_X, M_W128, M_W64, M_WR, M_WO, M_O64, M_O16, M_SA, M_SB, M_OUT, M_COUNT };

__device__ __forceinline__ long long clk64() { long long t; asm volatile("mov.u64 %0, %%clock64;" : "=l"(t) :: "memory"); return t; }
__device__ __forceinline__ uint32_t smem_u32(const void* p) { return (uint32_t)__cvta_generic_to_shared(p); }
__host__ __device__ constexpr uint64_t mkdesc(uint32_t addr, uint32_t lbo, uint32_t sbo, uint32_t swz) {
  return (uint64_t)((addr & 0x3FFFF) >> 4) | ((uint64_t)(lbo >> 4) << 16) | ((uint64_t)(sbo >> 4) << 32) | ((uint64_t)swz << 62);
}
__device__ __forceinline__ void mbar_init(uint32_t bar, uint32_t cnt) { asm volatile("mbarrier.init.shared::cta.b64 [%0], %1;" :: "r"(bar), "r"(cnt) : "memory"); }
__device__ __forceinline__ void mbar_expect_tx(uint32_t bar, uint32_t bytes) { asm volatile("mbarrier.arrive.expect_tx.shared::cta.b64 _, [%0], %1;" :: "r"(bar), "r"(bytes) : "memory"); }
__device__ __forceinline__ void mbar_arrive(uint32_t bar) { asm volatile("mbarrier.arrive.shared::cta.b64 _, [%0];" :: "r"(bar) : "memory"); }
__device__ __forceinline__ void mbar_wait(uint32_t bar, uint32_t parity) {
  asm volatile("{\n.reg .pred p;\n.reg .u32 c;\nmov.u32 c, 0;\n"
    "WL:\nmbarrier.try_wait.parity.shared::cta.b64 p, [%0], %1;\n@p bra WD;\n"
    "add.u32 c, c, 1;\nsetp.lt.u32 p, c, 200000;\n@p bra WL;\nWD:\n}" :: "r"(bar), "r"(parity) : "memory");
}
__device__ __forceinline__ void poll_all(const unsigned* p, unsigned val) {
  asm volatile("{\n.reg .pred p;\n.reg .u32 c, v;\nmov.u32 c, 0;\n"
    "PL:\nld.relaxed.gpu.global.u32 v, [%0];\nsetp.eq.u32 p, v, %1;\nvote.sync.all.pred p, p, 0xffffffff;\n@p bra PD;\n"
    "add.u32 c, c, 1;\nsetp.lt.u32 p, c, 100000;\n@p bra PL;\nPD:\n}" :: "l"(p), "r"(val) : "memory");
}
__device__ __forceinline__ void poll_all_acq(const unsigned* p, unsigned val) {
  asm volatile("{\n.reg .pred p;\n.reg .u32 c, v;\nmov.u32 c, 0;\n"
    "PL:\nld.acquire.gpu.global.u32 v, [%0];\nsetp.eq.u32 p, v, %1;\nvote.sync.all.pred p, p, 0xffffffff;\n@p bra PD;\n"
    "add.u32 c, c, 1;\nsetp.lt.u32 p, c, 100000;\n@p bra PL;\nPD:\n}" :: "l"(p), "r"(val) : "memory");
}
__device__ __forceinline__ unsigned poll_bit(const unsigned* p, unsigned val, unsigned mask) {
  unsigned bal;
  asm volatile("{\n.reg .pred p;\n.reg .u32 c, v;\nmov.u32 c, 0;\n"
    "PL:\nld.relaxed.gpu.global.u32 v, [%1];\nsetp.eq.u32 p, v, %2;\nvote.sync.ballot.b32 %0, p, 0xffffffff;\n"
    "and.b32 v, %0, %3;\nsetp.ne.u32 p, v, 0;\n@p bra PD;\n"
    "add.u32 c, c, 1;\nsetp.lt.u32 p, c, 100000;\n@p bra PL;\nPD:\n}" : "=&r"(bal) : "l"(p), "r"(val), "r"(mask) : "memory");
  return bal;
}
__device__ __forceinline__ void fix128_w0(uint32_t* v, const void* p, uint32_t tag, uint32_t mask) {
  asm volatile("{\n.reg .pred p;\n.reg .u32 c, x;\n.reg .b128 t;\n.reg .b64 lo, hi;\nmov.u32 c, 0;\n"
    "FL:\nxor.b32 x, %0, %5;\nand.b32 x, x, %6;\nsetp.eq.u32 p, x, 0;\n@p bra FD;\n"
    "ld.relaxed.gpu.global.b128 t, [%4];\nmov.b128 {lo, hi}, t;\nmov.b64 {%0, %1}, lo;\nmov.b64 {%2, %3}, hi;\n"
    "add.u32 c, c, 1;\nsetp.lt.u32 p, c, 100000;\n@p bra FL;\nFD:\n}"
    : "+r"(v[0]), "+r"(v[1]), "+r"(v[2]), "+r"(v[3]) : "l"(p), "r"(tag), "r"(mask) : "memory");
}
__device__ __forceinline__ void fix128_w3(uint32_t* v, const void* p, uint32_t tag, uint32_t mask) {
  asm volatile("{\n.reg .pred p;\n.reg .u32 c, x;\n.reg .b128 t;\n.reg .b64 lo, hi;\nmov.u32 c, 0;\n"
    "FL:\nxor.b32 x, %3, %5;\nand.b32 x, x, %6;\nsetp.eq.u32 p, x, 0;\n@p bra FD;\n"
    "ld.relaxed.gpu.global.b128 t, [%4];\nmov.b128 {lo, hi}, t;\nmov.b64 {%0, %1}, lo;\nmov.b64 {%2, %3}, hi;\n"
    "add.u32 c, c, 1;\nsetp.lt.u32 p, c, 100000;\n@p bra FL;\nFD:\n}"
    : "+r"(v[0]), "+r"(v[1]), "+r"(v[2]), "+r"(v[3]) : "l"(p), "r"(tag), "r"(mask) : "memory");
}
__device__ __forceinline__ void fence_acq() { asm volatile("fence.acq_rel.gpu;" ::: "memory"); }
__device__ __forceinline__ bool elect_one() {
  uint32_t p; asm volatile("{\n.reg .pred P;\nelect.sync _|P, 0xffffffff;\nselp.u32 %0, 1, 0, P;\n}" : "=r"(p)); return p;
}
__device__ __forceinline__ void bar_sync(int id, int n) { asm volatile("bar.sync %0, %1;" :: "r"(id), "r"(n) : "memory"); }
__device__ __forceinline__ void fence_async() { asm volatile("fence.proxy.async.shared::cta;" ::: "memory"); }
__device__ __forceinline__ void fence_async_g() { asm volatile("fence.proxy.async.global;" ::: "memory"); }
__device__ __forceinline__ void tma2d(uint32_t dst, const CUtensorMap* m, uint32_t bar, int c0, int c1) {
  asm volatile("cp.async.bulk.tensor.2d.shared::cluster.global.mbarrier::complete_tx::bytes [%0], [%1, {%3, %4}], [%2];"
    :: "r"(dst), "l"(m), "r"(bar), "r"(c0), "r"(c1) : "memory");
}
__device__ __forceinline__ void tma3d(uint32_t dst, const CUtensorMap* m, uint32_t bar, int c0, int c1, int c2) {
  asm volatile("cp.async.bulk.tensor.3d.shared::cluster.global.mbarrier::complete_tx::bytes [%0], [%1, {%3, %4, %5}], [%2];"
    :: "r"(dst), "l"(m), "r"(bar), "r"(c0), "r"(c1), "r"(c2) : "memory");
}
__device__ __forceinline__ void tma4d(uint32_t dst, const CUtensorMap* m, uint32_t bar, int c0, int c1, int c2, int c3) {
  asm volatile("cp.async.bulk.tensor.4d.shared::cluster.global.mbarrier::complete_tx::bytes [%0], [%1, {%3, %4, %5, %6}], [%2];"
    :: "r"(dst), "l"(m), "r"(bar), "r"(c0), "r"(c1), "r"(c2), "r"(c3) : "memory");
}
__device__ __forceinline__ void tma2d_st(const CUtensorMap* m, uint32_t src, int c0, int c1) {
  asm volatile("cp.async.bulk.tensor.2d.global.shared::cta.bulk_group [%0, {%2, %3}], [%1];"
    :: "l"(m), "r"(src), "r"(c0), "r"(c1) : "memory");
}
__device__ __forceinline__ void bulk_ld(uint32_t dst, const void* src, uint32_t bytes, uint32_t bar) {
  asm volatile("cp.async.bulk.shared::cluster.global.mbarrier::complete_tx::bytes [%0], [%1], %2, [%3];"
    :: "r"(dst), "l"(src), "r"(bytes), "r"(bar) : "memory");
}
__device__ __forceinline__ void bulk_st(void* dst, uint32_t src, uint32_t bytes) {
  asm volatile("cp.async.bulk.global.shared::cta.bulk_group [%0], [%1], %2;" :: "l"(dst), "r"(src), "r"(bytes) : "memory");
}
__device__ __forceinline__ void bulk_commit() { asm volatile("cp.async.bulk.commit_group;" ::: "memory"); }
__device__ __forceinline__ void bulk_wait0() { asm volatile("cp.async.bulk.wait_group 0;" ::: "memory"); }
__device__ __forceinline__ void bulk_wait0_read() { asm volatile("cp.async.bulk.wait_group.read 0;" ::: "memory"); }
__device__ __forceinline__ unsigned ld_rlx(const unsigned* p) { unsigned v; asm volatile("ld.relaxed.gpu.global.u32 %0, [%1];" : "=r"(v) : "l"(p) : "memory"); return v; }
__device__ __forceinline__ unsigned ld_acq(const unsigned* p) { unsigned v; asm volatile("ld.acquire.gpu.global.u32 %0, [%1];" : "=r"(v) : "l"(p) : "memory"); return v; }
__device__ __forceinline__ void st_rlx(unsigned* p, unsigned v) { asm volatile("st.relaxed.gpu.global.u32 [%0], %1;" :: "l"(p), "r"(v) : "memory"); }
__device__ __forceinline__ void st_rel(unsigned* p, unsigned v) { asm volatile("st.release.gpu.global.u32 [%0], %1;" :: "l"(p), "r"(v) : "memory"); }
__device__ __forceinline__ void ld128_rlx(uint32_t* v, const void* p) {
  asm volatile("{\n.reg .b128 t;\n.reg .b64 lo, hi;\nld.relaxed.gpu.global.b128 t, [%4];\nmov.b128 {lo, hi}, t;\n"
    "mov.b64 {%0, %1}, lo;\nmov.b64 {%2, %3}, hi;\n}" : "=r"(v[0]), "=r"(v[1]), "=r"(v[2]), "=r"(v[3]) : "l"(p) : "memory");
}
__device__ __forceinline__ void st128_rlx(void* p, const uint32_t* v) {
  asm volatile("{\n.reg .b128 t;\n.reg .b64 lo, hi;\nmov.b64 lo, {%1, %2};\nmov.b64 hi, {%3, %4};\nmov.b128 t, {lo, hi};\n"
    "st.relaxed.gpu.global.b128 [%0], t;\n}" :: "l"(p), "r"(v[0]), "r"(v[1]), "r"(v[2]), "r"(v[3]) : "memory");
}
__device__ __forceinline__ uint32_t lds32(uint32_t a) { uint32_t v; asm volatile("ld.shared.u32 %0, [%1];" : "=r"(v) : "r"(a) : "memory"); return v; }
__device__ __forceinline__ uint32_t lds32v(uint32_t a) { uint32_t v; asm volatile("ld.volatile.shared.u32 %0, [%1];" : "=r"(v) : "r"(a) : "memory"); return v; }
__device__ __forceinline__ uint32_t cpa(uint32_t a, uint32_t one) { uint32_t v; asm volatile("mul.lo.u32 %0, %1, %2;" : "=r"(v) : "r"(a), "r"(one)); return v; }
__device__ __forceinline__ uint32_t cpb(uint32_t a, uint32_t zero) { uint32_t v; asm volatile("or.b32 %0, %1, %2;" : "=r"(v) : "r"(a), "r"(zero)); return v; }
__device__ __forceinline__ uint32_t lds16(uint32_t a) { uint16_t v; asm volatile("ld.shared.u16 %0, [%1];" : "=h"(v) : "r"(a) : "memory"); return v; }
__device__ __forceinline__ float ldsf(uint32_t a) { float v; asm volatile("ld.shared.f32 %0, [%1];" : "=f"(v) : "r"(a) : "memory"); return v; }
__device__ __forceinline__ void lds128(uint32_t* v, uint32_t a) { asm volatile("ld.shared.v4.u32 {%0,%1,%2,%3}, [%4];" : "=r"(v[0]), "=r"(v[1]), "=r"(v[2]), "=r"(v[3]) : "r"(a) : "memory"); }
__device__ __forceinline__ void sts32(uint32_t a, uint32_t v) { asm volatile("st.shared.u32 [%0], %1;" :: "r"(a), "r"(v) : "memory"); }
__device__ __forceinline__ void sts16(uint32_t a, uint32_t v) { asm volatile("st.shared.u16 [%0], %1;" :: "r"(a), "h"((uint16_t)v) : "memory"); }
__device__ __forceinline__ void sts64f(uint32_t a, float x, float y) { asm volatile("st.shared.v2.f32 [%0], {%1,%2};" :: "r"(a), "f"(x), "f"(y) : "memory"); }
__device__ __forceinline__ void sts128(uint32_t a, uint32_t x, uint32_t y, uint32_t z, uint32_t w) { asm volatile("st.shared.v4.u32 [%0], {%1,%2,%3,%4};" :: "r"(a), "r"(x), "r"(y), "r"(z), "r"(w) : "memory"); }
__device__ __forceinline__ void stsm4(uint32_t a, uint32_t r0, uint32_t r1, uint32_t r2, uint32_t r3) {
  asm volatile("stmatrix.sync.aligned.m8n8.x4.shared.b16 [%0], {%1,%2,%3,%4};" :: "r"(a), "r"(r0), "r"(r1), "r"(r2), "r"(r3) : "memory");
}
__device__ __forceinline__ void stsm4t(uint32_t a, uint32_t r0, uint32_t r1, uint32_t r2, uint32_t r3) {
  asm volatile("stmatrix.sync.aligned.m8n8.x4.trans.shared.b16 [%0], {%1,%2,%3,%4};" :: "r"(a), "r"(r0), "r"(r1), "r"(r2), "r"(r3) : "memory");
}
__device__ __forceinline__ void ldsm4t(uint32_t* r, uint32_t a) {
  asm volatile("ldmatrix.sync.aligned.m8n8.x4.trans.shared.b16 {%0,%1,%2,%3}, [%4];" : "=r"(r[0]), "=r"(r[1]), "=r"(r[2]), "=r"(r[3]) : "r"(a) : "memory");
}
__device__ __forceinline__ void ldsm4(uint32_t* r, uint32_t a) {
  asm volatile("ldmatrix.sync.aligned.m8n8.x4.shared.b16 {%0,%1,%2,%3}, [%4];" : "=r"(r[0]), "=r"(r[1]), "=r"(r[2]), "=r"(r[3]) : "r"(a) : "memory");
}
__device__ __forceinline__ void mma16816(float* d, const uint32_t* a, const uint32_t* b) {
  asm volatile("mma.sync.aligned.m16n8k16.row.col.f32.bf16.bf16.f32 {%0,%1,%2,%3}, {%4,%5,%6,%7}, {%8,%9}, {%0,%1,%2,%3};"
    : "+f"(d[0]), "+f"(d[1]), "+f"(d[2]), "+f"(d[3]) : "r"(a[0]), "r"(a[1]), "r"(a[2]), "r"(a[3]), "r"(b[0]), "r"(b[1]));
}
__device__ __forceinline__ uint32_t pack2(float lo, float hi) { uint32_t r; asm("cvt.rn.bf16x2.f32 %0, %1, %2;" : "=r"(r) : "f"(hi), "f"(lo)); return r; }
__device__ __forceinline__ uint32_t packh(float lo, float hi) { uint32_t r; asm("cvt.rn.f16x2.f32 %0, %1, %2;" : "=r"(r) : "f"(hi), "f"(lo)); return r; }
__device__ __forceinline__ uint32_t hcmul(uint32_t x, uint32_t zp, uint32_t zq) {
  const __half2 xx = *reinterpret_cast<__half2*>(&x);
  const __half2 r = __hfma2(__high2half2(xx), *reinterpret_cast<__half2*>(&zq), __hmul2(__low2half2(xx), *reinterpret_cast<__half2*>(&zp)));
  return *reinterpret_cast<const uint32_t*>(&r);
}
__device__ __forceinline__ void hcm2(uint32_t xr, uint32_t xi, uint32_t z, uint32_t& pr, uint32_t& pi) {
  const __half2 a = *reinterpret_cast<__half2*>(&xr), b = *reinterpret_cast<__half2*>(&xi), zz = *reinterpret_cast<__half2*>(&z);
  const __half2 re = __hfma2(__hneg2(b), __high2half2(zz), __hmul2(a, __low2half2(zz)));
  const __half2 im = __hfma2(a, __high2half2(zz), __hmul2(b, __low2half2(zz)));
  pr = *reinterpret_cast<const uint32_t*>(&re); pi = *reinterpret_cast<const uint32_t*>(&im);
}
__device__ __forceinline__ void sts64(uint32_t a, uint32_t x, uint32_t y) { asm volatile("st.shared.v2.u32 [%0], {%1,%2};" :: "r"(a), "r"(x), "r"(y) : "memory"); }
__device__ __forceinline__ void lds64(uint32_t* v, uint32_t a) { asm volatile("ld.shared.v2.u32 {%0,%1}, [%2];" : "=r"(v[0]), "=r"(v[1]) : "r"(a) : "memory"); }
__device__ __forceinline__ float bf_lo(uint32_t v) { return __uint_as_float(v << 16); }
__device__ __forceinline__ float bf_hi(uint32_t v) { return __uint_as_float(v & 0xffff0000u); }
__device__ __forceinline__ float bf_round(float x) { return bf_lo(pack2(x, 0.f)); }
__device__ __forceinline__ float ex2(float x) { float r; asm("ex2.approx.ftz.f32 %0, %1;" : "=f"(r) : "f"(x)); return r; }
__device__ __forceinline__ float phi(float t, float l2e = 1.44269504089f) { float e = ex2(t * l2e); return (t > 0.f ? t + 1.f : e) + 1e-6f; }
__device__ __forceinline__ void wg_fence() { asm volatile("wgmma.fence.sync.aligned;" ::: "memory"); }
__device__ __forceinline__ void wg_commit() { asm volatile("wgmma.commit_group.sync.aligned;" ::: "memory"); }
template <int N> __device__ __forceinline__ void wg_wait() { asm volatile("wgmma.wait_group.sync.aligned %0;" :: "n"(N) : "memory"); }
template <int N> __device__ __forceinline__ void pin(float* a) {
  #pragma unroll
  for (int i = 0; i < N; i++) asm volatile("" : "+f"(a[i]) :: "memory");
}
__device__ __forceinline__ int opaque(int v) { asm volatile("" : "+r"(v)); return v; }
template <int N> __device__ __forceinline__ void zero(float* a) {
  #pragma unroll
  for (int i = 0; i < N; i++) asm volatile("mov.b32 %0, 0;" : "=f"(a[i]));
}
template <int N> __device__ __forceinline__ void pinu(uint32_t* a) {
  #pragma unroll
  for (int i = 0; i < N; i++) asm volatile("" : "+r"(a[i]) :: "memory");
}
__device__ __forceinline__ void cexp_t(float lg2mag, float turns, float& re, float& im) {
  float m = ex2(lg2mag);
  float fr = (turns - __fadd_rn(__fadd_rn(turns, 12582912.f), -12582912.f)) * 6.283185307f;
  re = m * __cosf(fr); im = m * __sinf(fr);
}
__device__ __forceinline__ void cmul(float ar, float ai, float br, float bi, float& cr, float& ci) {
  cr = fmaf(ar, br, -ai * bi); ci = fmaf(ar, bi, ai * br);
}

__device__ __forceinline__ void wg_ss192_tb(float* d, uint64_t da, uint64_t db, int scale_d) {
  asm volatile("{\n.reg .pred p;\nsetp.ne.b32 p, %98, 0;\n"
    "wgmma.mma_async.sync.aligned.m64n192k16.f32.bf16.bf16 "
    "{%0, %1, %2, %3, %4, %5, %6, %7, %8, %9, %10, %11, %12, %13, %14, %15, %16, %17, %18, %19, %20, %21, %22, %23, %24, %25, %26, %27, %28, %29, %30, %31, %32, %33, %34, %35, %36, %37, %38, %39, %40, %41, %42, %43, %44, %45, %46, %47, %48, %49, %50, %51, %52, %53, %54, %55, %56, %57, %58, %59, %60, %61, %62, %63, %64, %65, %66, %67, %68, %69, %70, %71, %72, %73, %74, %75, %76, %77, %78, %79, %80, %81, %82, %83, %84, %85, %86, %87, %88, %89, %90, %91, %92, %93, %94, %95}, %96, %97, p, 1, 1, 0, 1;\n}\n"
    : "+f"(d[0]), "+f"(d[1]), "+f"(d[2]), "+f"(d[3]), "+f"(d[4]), "+f"(d[5]), "+f"(d[6]), "+f"(d[7]), "+f"(d[8]), "+f"(d[9]), "+f"(d[10]), "+f"(d[11]), "+f"(d[12]), "+f"(d[13]), "+f"(d[14]), "+f"(d[15]), "+f"(d[16]), "+f"(d[17]), "+f"(d[18]), "+f"(d[19]), "+f"(d[20]), "+f"(d[21]), "+f"(d[22]), "+f"(d[23]), "+f"(d[24]), "+f"(d[25]), "+f"(d[26]), "+f"(d[27]), "+f"(d[28]), "+f"(d[29]), "+f"(d[30]), "+f"(d[31]), "+f"(d[32]), "+f"(d[33]), "+f"(d[34]), "+f"(d[35]), "+f"(d[36]), "+f"(d[37]), "+f"(d[38]), "+f"(d[39]), "+f"(d[40]), "+f"(d[41]), "+f"(d[42]), "+f"(d[43]), "+f"(d[44]), "+f"(d[45]), "+f"(d[46]), "+f"(d[47]), "+f"(d[48]), "+f"(d[49]), "+f"(d[50]), "+f"(d[51]), "+f"(d[52]), "+f"(d[53]), "+f"(d[54]), "+f"(d[55]), "+f"(d[56]), "+f"(d[57]), "+f"(d[58]), "+f"(d[59]), "+f"(d[60]), "+f"(d[61]), "+f"(d[62]), "+f"(d[63]), "+f"(d[64]), "+f"(d[65]), "+f"(d[66]), "+f"(d[67]), "+f"(d[68]), "+f"(d[69]), "+f"(d[70]), "+f"(d[71]), "+f"(d[72]), "+f"(d[73]), "+f"(d[74]), "+f"(d[75]), "+f"(d[76]), "+f"(d[77]), "+f"(d[78]), "+f"(d[79]), "+f"(d[80]), "+f"(d[81]), "+f"(d[82]), "+f"(d[83]), "+f"(d[84]), "+f"(d[85]), "+f"(d[86]), "+f"(d[87]), "+f"(d[88]), "+f"(d[89]), "+f"(d[90]), "+f"(d[91]), "+f"(d[92]), "+f"(d[93]), "+f"(d[94]), "+f"(d[95])
    : "l"(da), "l"(db), "r"(scale_d));
}
__device__ __forceinline__ void wg_ss48_tb(float* d, uint64_t da, uint64_t db, int scale_d) {
  asm volatile("{\n.reg .pred p;\nsetp.ne.b32 p, %26, 0;\n"
    "wgmma.mma_async.sync.aligned.m64n48k16.f32.bf16.bf16 "
    "{%0, %1, %2, %3, %4, %5, %6, %7, %8, %9, %10, %11, %12, %13, %14, %15, %16, %17, %18, %19, %20, %21, %22, %23}, %24, %25, p, 1, 1, 0, 1;\n}\n"
    : "+f"(d[0]), "+f"(d[1]), "+f"(d[2]), "+f"(d[3]), "+f"(d[4]), "+f"(d[5]), "+f"(d[6]), "+f"(d[7]), "+f"(d[8]), "+f"(d[9]), "+f"(d[10]), "+f"(d[11]), "+f"(d[12]), "+f"(d[13]), "+f"(d[14]), "+f"(d[15]), "+f"(d[16]), "+f"(d[17]), "+f"(d[18]), "+f"(d[19]), "+f"(d[20]), "+f"(d[21]), "+f"(d[22]), "+f"(d[23])
    : "l"(da), "l"(db), "r"(scale_d));
}
__device__ __forceinline__ void wg_ss48_tt(float* d, uint64_t da, uint64_t db, int scale_d) {
  asm volatile("{\n.reg .pred p;\nsetp.ne.b32 p, %26, 0;\n"
    "wgmma.mma_async.sync.aligned.m64n48k16.f32.bf16.bf16 "
    "{%0, %1, %2, %3, %4, %5, %6, %7, %8, %9, %10, %11, %12, %13, %14, %15, %16, %17, %18, %19, %20, %21, %22, %23}, %24, %25, p, 1, 1, 1, 1;\n}\n"
    : "+f"(d[0]), "+f"(d[1]), "+f"(d[2]), "+f"(d[3]), "+f"(d[4]), "+f"(d[5]), "+f"(d[6]), "+f"(d[7]), "+f"(d[8]), "+f"(d[9]), "+f"(d[10]), "+f"(d[11]), "+f"(d[12]), "+f"(d[13]), "+f"(d[14]), "+f"(d[15]), "+f"(d[16]), "+f"(d[17]), "+f"(d[18]), "+f"(d[19]), "+f"(d[20]), "+f"(d[21]), "+f"(d[22]), "+f"(d[23])
    : "l"(da), "l"(db), "r"(scale_d));
}
__device__ __forceinline__ void wg_rs88_tb(float* d, const uint32_t* a, uint64_t db, int scale_d) {
  asm volatile("{\n.reg .pred p;\nsetp.ne.b32 p, %49, 0;\n"
    "wgmma.mma_async.sync.aligned.m64n88k16.f32.bf16.bf16 "
    "{%0, %1, %2, %3, %4, %5, %6, %7, %8, %9, %10, %11, %12, %13, %14, %15, %16, %17, %18, %19, %20, %21, %22, %23, %24, %25, %26, %27, %28, %29, %30, %31, %32, %33, %34, %35, %36, %37, %38, %39, %40, %41, %42, %43}, {%44, %45, %46, %47}, %48, p, 1, 1, 1;\n}\n"
    : "+f"(d[0]), "+f"(d[1]), "+f"(d[2]), "+f"(d[3]), "+f"(d[4]), "+f"(d[5]), "+f"(d[6]), "+f"(d[7]), "+f"(d[8]), "+f"(d[9]), "+f"(d[10]), "+f"(d[11]), "+f"(d[12]), "+f"(d[13]), "+f"(d[14]), "+f"(d[15]), "+f"(d[16]), "+f"(d[17]), "+f"(d[18]), "+f"(d[19]), "+f"(d[20]), "+f"(d[21]), "+f"(d[22]), "+f"(d[23]), "+f"(d[24]), "+f"(d[25]), "+f"(d[26]), "+f"(d[27]), "+f"(d[28]), "+f"(d[29]), "+f"(d[30]), "+f"(d[31]), "+f"(d[32]), "+f"(d[33]), "+f"(d[34]), "+f"(d[35]), "+f"(d[36]), "+f"(d[37]), "+f"(d[38]), "+f"(d[39]), "+f"(d[40]), "+f"(d[41]), "+f"(d[42]), "+f"(d[43])
    : "r"(a[0]), "r"(a[1]), "r"(a[2]), "r"(a[3]), "l"(db), "r"(scale_d));
}
__device__ __forceinline__ void wg_ss80_tb(float* d, uint64_t da, uint64_t db, int scale_d) {
  asm volatile("{\n.reg .pred p;\nsetp.ne.b32 p, %42, 0;\n"
    "wgmma.mma_async.sync.aligned.m64n80k16.f32.bf16.bf16 "
    "{%0, %1, %2, %3, %4, %5, %6, %7, %8, %9, %10, %11, %12, %13, %14, %15, %16, %17, %18, %19, %20, %21, %22, %23, %24, %25, %26, %27, %28, %29, %30, %31, %32, %33, %34, %35, %36, %37, %38, %39}, %40, %41, p, 1, 1, 0, 1;\n}\n"
    : "+f"(d[0]), "+f"(d[1]), "+f"(d[2]), "+f"(d[3]), "+f"(d[4]), "+f"(d[5]), "+f"(d[6]), "+f"(d[7]), "+f"(d[8]), "+f"(d[9]), "+f"(d[10]), "+f"(d[11]), "+f"(d[12]), "+f"(d[13]), "+f"(d[14]), "+f"(d[15]), "+f"(d[16]), "+f"(d[17]), "+f"(d[18]), "+f"(d[19]), "+f"(d[20]), "+f"(d[21]), "+f"(d[22]), "+f"(d[23]), "+f"(d[24]), "+f"(d[25]), "+f"(d[26]), "+f"(d[27]), "+f"(d[28]), "+f"(d[29]), "+f"(d[30]), "+f"(d[31]), "+f"(d[32]), "+f"(d[33]), "+f"(d[34]), "+f"(d[35]), "+f"(d[36]), "+f"(d[37]), "+f"(d[38]), "+f"(d[39])
    : "l"(da), "l"(db), "r"(scale_d));
}
__device__ __forceinline__ void wg_ss48_tt_h(float* d, uint64_t da, uint64_t db, int scale_d) {
  asm volatile("{\n.reg .pred p;\nsetp.ne.b32 p, %26, 0;\n"
    "wgmma.mma_async.sync.aligned.m64n48k16.f32.f16.f16 "
    "{%0, %1, %2, %3, %4, %5, %6, %7, %8, %9, %10, %11, %12, %13, %14, %15, %16, %17, %18, %19, %20, %21, %22, %23}, %24, %25, p, 1, 1, 1, 1;\n}\n"
    : "+f"(d[0]), "+f"(d[1]), "+f"(d[2]), "+f"(d[3]), "+f"(d[4]), "+f"(d[5]), "+f"(d[6]), "+f"(d[7]), "+f"(d[8]), "+f"(d[9]), "+f"(d[10]), "+f"(d[11]), "+f"(d[12]), "+f"(d[13]), "+f"(d[14]), "+f"(d[15]), "+f"(d[16]), "+f"(d[17]), "+f"(d[18]), "+f"(d[19]), "+f"(d[20]), "+f"(d[21]), "+f"(d[22]), "+f"(d[23])
    : "l"(da), "l"(db), "r"(scale_d));
}

struct Params {
  CUtensorMap m[M_COUNT];
  const __nv_bfloat16 *u, *par[4], *logdt, *dskip, *wo;
};

#define CHUNK(i) ((i) == 0 ? c : ((i) == 7 ? (c ^ 1) : (((c & 6) + 1 + (i)) & 7)))
#define FLAG(kind, rr, cc) (&g_flag[((kind) * 128 + (rr) * 8 + (cc)) * 32])
#define SLOT(i) ((i) == 0 || (i) == 6 ? OFF_EXTRA : OFF_BLK + ((i) == 7 ? 4 : 5 - (i)) * BLK)
__device__ __forceinline__ void load_quad(uint32_t* A, uint32_t addr) {
  A[0] = lds32v(addr); A[1] = lds32v(addr + 32); A[2] = lds32v(addr - 32); A[3] = lds32v(addr);
}

__global__ void __launch_bounds__(512, 1) fused_kernel(const __grid_constant__ Params prm) {
  extern __shared__ unsigned char smem_raw[];
  const uint32_t sb = __shfl_sync(0xffffffff, smem_u32(smem_raw), 0);
  const int tid = threadIdx.x, lane = tid & 31;
  const int warp = __shfl_sync(0xffffffff, tid >> 5, 0), wg = warp >> 2, w4 = warp & 3;
  const int cta = blockIdx.x, r = cta >> 3, c = cta & 7;
  if ((sb & 0xffffffu) != SB0) return;
#define BAR(i) (sb + OFF_BAR + 8 * (i))
  const bool sw64 = ((c + 1) & 2) != 0;

  if (wg == 3) {
    if (warp == 13 && elect_one()) {
      #pragma unroll
      for (int i = M_W128; i <= M_WR; i++) asm volatile("prefetch.tensormap [%0];" :: "l"(&prm.m[i]) : "memory");
    }
    asm volatile("setmaxnreg.dec.sync.aligned.u32 56;");
    if (warp == 12) {
      if (elect_one()) {
        #pragma unroll
        for (int i = 0; i < 5; i++) mbar_init(BAR(BR_FULL + i), 1);
        asm volatile("fence.mbarrier_init.release.cluster;" ::: "memory");
      }
      {
        const CUtensorMap* mwp = &prm.m[sw64 ? M_W64 : M_W128];
        const int mcol = (c * 80 + (c & 1) * 16) >> (sw64 ? 5 : 6), rcol = c * 80 + ((c & 1) ? 0 : 64);
        uint32_t s = 0, ph = 1, xs = 0;
        #pragma unroll 1
        for (int kb = 0; kb < 20; kb++) {
          if (kb == 2) bar_sync(0, 512);
          if (kb >= 5) mbar_wait(BAR(BR_EMPTY) + 8 * s, ph);
          if (EN_ATT && elect_one()) {
            const uint32_t st = sb + s * W_SLOT, fb = BAR(BR_FULL) + 8 * s;
            mbar_expect_tx(fb, (kb & 1) ? W_SLOT : W_SLOT + 16384);
            if (!(kb & 1)) tma2d(sb + OFF_X + xs, &prm.m[M_X], fb, kb * 32, r * 128);
            tma4d(st, mwp, fb, 0, kb * 32, mcol, 0);
            tma3d(st + 12288, &prm.m[M_WR], fb, rcol, kb * 32, 0);
          }
          if (!EN_ATT && kb == 2) break;
          if (++s == 5) { s = 0; ph ^= 1; }
          if (kb & 1) { xs += 16384; if (xs == 49152) xs = 0; }
        }
      }
      if (EN_ATT) {
      mbar_wait(BAR(BR_EPOCH), 0);
      const unsigned epoch = lds32(sb + OFF_EPOCH);
      const unsigned* fo = FLAG(3, r, lane & 7);
      unsigned seen = __ballot_sync(0xffffffff, ld_rlx(lane < 16 ? fo : FLAG(0, lane & 15, c)) == epoch) & 0xffu;
      mbar_wait(BAR(BR_GEMM), 0);
      if (elect_one()) {
        mbar_expect_tx(BAR(BR_WO), 10240);
        tma2d(sb, &prm.m[M_WO], BAR(BR_WO), c * 64, c * 80);
        mbar_expect_tx(BAR(BR_KVP), 61440);
        mbar_expect_tx(BAR(BR_WO + 1), 7 * 10240);
      }
      {
        const char* gs = reinterpret_cast<const char*>(prm.wo) + (size_t)((lane >> 3) + ((lane >> 1) & 3) * 160) * 1280 + 1024 + c * 32 + (lane & 1) * 16;
        uint32_t ds = sb + OFF_WOR + (lane >> 3) * 128 + (((lane & 7) ^ (lane >> 3)) << 4);
        #pragma unroll 2
        for (int i = 0; i < 40; i++) {
          asm volatile("cp.async.cg.shared.global [%0], [%1], 16;" :: "r"(ds), "l"(gs) : "memory");
          ds = (ds + 512) ^ 64; gs += 5120;
        }
      }
      mbar_wait(BAR(BR_PUB), 0);
      poll_all(FLAG(0, lane & 15, c), epoch);
      if (elect_one()) { TS(23); bulk_ld(sb + OFF_KVP, &g_kvp[c * 16 * 240], 61440, BAR(BR_KVP)); }
      asm volatile("cp.async.wait_all;" ::: "memory");
      fence_async();
      mbar_arrive(BAR(BR_WO));
      mbar_wait(BAR(BR_OSTG), 0);
      if (elect_one()) {
        bulk_st(&g_o[cta * 1280], sb + OFF_EXTRA, 20480);
        bulk_commit();
        mbar_arrive(BAR(BR_OFULL));
        #pragma unroll 1
        for (int i = 1; i < 8; i++) tma2d(sb + i * 10240, &prm.m[M_WO], BAR(BR_WO + 1), c * 64, CHUNK(i) * 80);
        bulk_wait0();
        st_rlx(FLAG(3, r, c), epoch);
        TS(20);
      }
      __syncwarp();
      #pragma unroll 1
      for (int i = 1; i < 8; i++) {
        const int src = CHUNK(i);
        if (!((seen >> src) & 1)) seen = poll_bit(fo, epoch, 1u << src);
        if (i >= 6) mbar_wait(BAR(BR_OEMPTY - 6) + 8 * i, 0);
        else if (EN_SSM && i < 3) mbar_wait(BAR(BR_FREE - 1) + 8 * i, 0);
        if (elect_one()) {
          mbar_expect_tx(BAR(BR_OFULL) + 8 * i, 20480);
          bulk_ld(sb + SLOT(i), &g_o[(r * 8 + src) * 1280], 20480, BAR(BR_OFULL) + 8 * i);
          if (i == 1) TS(21);
          if (i == 7) TS(22);
        }
        __syncwarp();
      }
      if (lane == 0) { DUMP(20, 30); }
      }
    } else {
      const int hw = warp - 13, ht = tid - 416;
      unsigned epoch = 0;
      if (hw == 2 && elect_one()) {
        #pragma unroll
        for (int i = 5; i < BR_COUNT; i++) mbar_init(BAR(i), i == BR_WO ? 33 : i < BR_EMPTY ? 1 : i < BR_OEMPTY ? 2 : i < BR_Y4 ? 8 : i < BR_OSTG ? 128 : i == BR_OSTG ? 256 : 96);
        asm volatile("fence.mbarrier_init.release.cluster;" ::: "memory");
      }
      bar_sync(0, 512);
      if (hw == 1 && elect_one()) {
        #pragma unroll
        for (int i = M_WO; i < M_COUNT; i++) asm volatile("prefetch.tensormap [%0];" :: "l"(&prm.m[i]) : "memory");
      }
      if (U_DELAY) __nanosleep(U_DELAY);
      if (EN_SSM && ht < 80) {
        const int rr = ht / 10;
        const char* gs = reinterpret_cast<const char*>(prm.u) + (size_t)(r * 128 + rr) * 1280 + c * 160 + (ht - rr * 10) * 16;
        uint32_t ds = sb + OFF_BLK + 3 * BLK + B_D + ht * 16;
        #pragma unroll 1
        for (int i = 0; i < 16; i++) {
          asm volatile("cp.async.cg.shared.global [%0], [%1], 16;" :: "r"(ds), "l"(gs) : "memory");
          ds += i == 7 ? BLK - 7 * 1280 : 1280; gs += 10240;
          if (U_LPACE) __nanosleep(U_LPACE);
        }
      }
      if (hw == 0) {
        if (lane == 0) {
          epoch = ld_rlx(&g_epoch[cta]) + 1;
          st_rlx(&g_epoch[cta], epoch);
          sts32(sb + OFF_EPOCH, epoch);
          mbar_arrive(BAR(BR_EPOCH));
        }
        epoch = __shfl_sync(0xffffffff, epoch, 0);
      }
      if (EN_SSM) {
      const int mi = lane >> 3, rw = lane & 7, ch0 = c * 80 + r * 5;
      asm volatile("cp.async.wait_all;" ::: "memory");
      bar_sync(5, 96);
      if (ht == 0) TS(36);
      {
        uint4* gp = reinterpret_cast<uint4*>(g_uy + (size_t)(c * 80 + hw * 8 + (lane >> 2)) * 2048 + r * 128 + (lane & 3) * 8);
        uint32_t sa = sb + OFF_BLK + 3 * BLK + B_D + (8 * (rw >> 1) + 2 * mi + (rw & 1)) * 160 + hw * 16;
        #pragma unroll 1
        for (int i = hw; i < 10; i += 3) {
          uint32_t v[4][4];
          #pragma unroll
          for (int q = 0; q < 4; q++) ldsm4t(v[q], sa + (q >> 1) * BLK + (q & 1) * 5120);
          #pragma unroll
          for (int q = 0; q < 4; q++) {
            gp[q * 4] = make_uint4(v[q][0], v[q][1], v[q][2], v[q][3]);
            if (q & 1) __nanosleep(U_PACE);
          }
          gp += 6144; sa += 48;
        }
      }
      bar_sync(5, 96);
      if (hw == 0) {
        if (lane == 0) { st_rel(FLAG(1, r, c), epoch); TS(30); }
        __syncwarp();
        poll_all_acq(FLAG(1, lane & 15, c), epoch);
      }
      #pragma unroll 1
      for (int k = 4; k >= 0; k--) {
        const uint32_t blk = sb + OFF_BLK + k * BLK;
        if (k == 2) mbar_wait(BAR(BR_KGEN), 0);
        if (hw == 0 && !(k & 1) && k && elect_one()) {
          const uint32_t br = BAR(k == 4 ? BR_U : BR_U2);
          fence_async_g();
          mbar_expect_tx(br, k == 4 ? 12288 : 8192);
          #pragma unroll 1
          for (int q = k == 4 ? 4 : 1; q >= k - 2; q--) tma2d(sb + OFF_BLK + q * BLK, &prm.m[M_SB], br, 0, (ch0 + q) * 32);
          TS(31);
        }
        mbar_wait(BAR(k >= 2 ? BR_U : BR_U2), 0);
        #pragma unroll 1
        for (int kap = ht; kap < 192; kap += 96) {
          float P[33];
          P[0] = 0.f;
          #pragma unroll
          for (int q = 0; q < 4; q++) {
            const int ch = kap - 3 + q;
            uint32_t v[4];
            lds128(v, blk + (uint32_t)((ch * 16) ^ ((ch * 2) & 0x70)));
            #pragma unroll
            for (int e = 0; e < 4; e++) {
              P[q * 8 + 2 * e + 1] = (q == 0 && e < 2) ? 0.f : P[q * 8 + 2 * e] + bf_lo(v[e]);
              P[q * 8 + 2 * e + 2] = (q == 0 && e < 2) ? 0.f : P[q * 8 + 2 * e + 1] + bf_hi(v[e]);
            }
          }
#define WIN(lo, hi, e) (P[25 + (e) - (lo)] - P[24 + (e) - (hi)])
#define WIN8(lo, hi) pack2(WIN(lo, hi, 0), WIN(lo, hi, 1)), pack2(WIN(lo, hi, 2), WIN(lo, hi, 3)), pack2(WIN(lo, hi, 4), WIN(lo, hi, 5)), pack2(WIN(lo, hi, 6), WIN(lo, hi, 7))
          const uint32_t o2 = blk + B_D + (kap & 1) * 1552 + (kap >> 1) * 16;
          sts128(o2, WIN8(3, 5));
          sts128(o2 + B_D5, WIN8(6, 10));
          if (kap < 128) {
            const uint32_t o = blk + B_D + (kap & 1) * 1024 + (kap >> 1) * 16;
            sts128(o + B_D7, WIN8(5, 11));
            sts128(o + B_D9, WIN8(12, 20));
          }
        }
        if (ht < 2) sts128(blk + B_D + ht * B_D5 + 1536, 0, 0, 0, 0);
        mbar_arrive(BAR(BR_DRDY) + 8 * k);
      }
      if (ht == 0) TS(32);
      if (hw == 0) {
        #pragma unroll 1
        for (int p = 0; p < 2; p++) {
          mbar_wait(BAR(BR_Y4) + 8 * p, 0);
          if (elect_one()) {
            #pragma unroll 1
            for (int k = 4 - p; k >= 4 - 4 * p; k--) tma2d_st(&prm.m[M_SB], sb + OFF_BLK + k * BLK, 0, (640 + ch0 + k) * 32);
            bulk_commit(); bulk_wait0_read();
            mbar_arrive(BAR(BR_FREE) + 8 * p);
          }
          __syncwarp();
        }
        if (elect_one()) {
          mbar_expect_tx(BAR(BR_YIN), 20480);
          bulk_wait0();
          st_rel(FLAG(2, r, c), epoch);
          TS(33);
        }
        __syncwarp();
        poll_all_acq(FLAG(2, lane & 15, c), epoch);
        if (EN_ATT) mbar_wait(BAR(BR_OEMPTY + 5), 0);
        if (elect_one()) {
          fence_async_g();
          tma2d(sb + OFF_BLK + BLK, &prm.m[M_SA], BAR(BR_YIN), r * 128, 640 + c * 80);
          tma2d(sb + OFF_BLK + BLK + 10240, &prm.m[M_SA], BAR(BR_YIN), r * 128 + 64, 640 + c * 80);
          TS(34);
        }
      }
      {
        uint32_t sa = sb + OFF_BLK + BLK + (hw * 8 + rw) * 128 + ((mi ^ rw) << 4);
        uint32_t da = sb + OFF_BLK + (8 * mi + rw) * 160 + hw * 16;
        mbar_wait(BAR(BR_YIN), 0);
        #pragma unroll 1
        for (int i = hw; i < 10; i += 3) {
          uint32_t v[4][4];
          #pragma unroll
          for (int q = 0; q < 4; q++) ldsm4t(v[q], (sa ^ ((q & 1) * 64)) + (q >> 1) * 10240);
          #pragma unroll
          for (int q = 0; q < 4; q++) stsm4(da + q * 5120, v[q][0], v[q][1], v[q][2], v[q][3]);
          sa += 3072; da += 48;
        }
      }
      fence_async();
      bar_sync(5, 96);
      if (hw == 0 && elect_one()) {
        tma2d_st(&prm.m[M_OUT], sb + OFF_BLK, c * 80, r * 128);
        bulk_commit(); bulk_wait0_read();
        TS(35); DUMP(30, 40); DUMP(0, 1);
      }
      }
    }
  } else if (wg < 2) {
    asm volatile("setmaxnreg.inc.sync.aligned.u32 152;");
    bar_sync(0, 512);
    if (EN_ATT) {
    const int tq = lane & 3, t7 = tid & 127;
    float am[96], ar[24];
    {
      const uint64_t da0 = mkdesc(SB0 + OFF_X, 16, 1024, 1) + wg * 512;
      const uint64_t db0 = sw64 ? mkdesc(SB0, 2048, 512, 2) : mkdesc(SB0, 4096, 1024, 1);
      const uint32_t kst = sw64 ? 64 : 128;
      constexpr uint64_t dr0 = mkdesc(SB0 + 12288, 1024, 256, 3);
      uint32_t s = 0, ph = 0, xo = 0;
      #pragma unroll 1
      for (int kb = 0; kb < 20; kb++) {
        mbar_wait(BAR(BR_FULL) + 8 * s, ph);
        if (kb == 0 && tid == 0) TS(1);
        wg_fence();
        const uint32_t wo_ = s * (W_SLOT >> 4);
        wg_ss192_tb(am, da0 + xo, db0 + wo_, kb != 0);
        wg_ss48_tb(ar, da0 + xo, dr0 + wo_, kb != 0);
        wg_ss192_tb(am, da0 + xo + 2, db0 + wo_ + kst, 1);
        wg_ss48_tb(ar, da0 + xo + 2, dr0 + wo_ + 32, 1);
        wg_commit();
        wg_wait<1>();
        if (t7 == 0 && kb > 0 && kb < 16) mbar_arrive(BAR(BR_EMPTY) + 8 * (s == 0 ? 4 : s - 1));
        if (++s == 5) { s = 0; ph ^= 1; }
        xo += (kb & 1) ? 1020 : 4;
        if (xo == 3072) xo = 0;
      }
      wg_wait<0>();
      pin<96>(am); pin<24>(ar);
    }
    if (tid == 0) TS(2);
#define QV(j, e) ((j) < 8 ? am[4 * (j) + (e)] : ar[4 * ((j) - 8) + (e)])
#define KV_(j, e) ((j) < 8 ? am[32 + 4 * (j) + (e)] : ar[8 + 4 * ((j) - 8) + (e)])
#define VV(j, e) ((j) < 8 ? am[64 + 4 * (j) + (e)] : ar[16 + 4 * ((j) - 8) + (e)])
    {
      bar_sync(1, 256);
      if (tid == 0) mbar_arrive(BAR(BR_GEMM));
      const uint32_t ro = sb + (uint32_t)((warp * 16 + (lane & 15)) * 16);
      const int l0 = 2 * (c & 1) + (lane >> 4);
      const uint32_t ones = (tq == 0) ? 0x00003f80u : 0u;
#define PV(j) pack2(VV(j, 0), VV(j, 1)), pack2(VV(j, 2), VV(j, 3))
#define PK(j) pack2(phi(KV_(j, 0)), phi(KV_(j, 1))), pack2(phi(KV_(j, 2)), phi(KV_(j, 3)))
      stsm4(ro + OFF_V + (5 + 6 * (lane >> 4)) * 2048, ones, ones, ones, ones);
      #pragma unroll
      for (int j = 0; j < 10; j += 2) {
        const int l = (j == 8 && (c & 1)) ? l0 - 2 : l0 + j;
        stsm4(ro + OFF_V + (l + (l >= 5)) * 2048, PV(j), PV(j + 1));
        stsm4(ro + OFF_PK + l * 2048, PK(j), PK(j + 1));
      }
    }
    fence_async();
    bar_sync(1, 256);
    if (tid == 0) TS(3);
    mbar_wait(BAR(BR_EPOCH), 0);
    const unsigned epoch = lds32(sb + OFF_EPOCH);
    {
      float kv[24]; zero<24>(kv);
      const uint64_t da = mkdesc(SB0 + OFF_PK, 128, 2048, 0) + wg * 640, db = mkdesc(SB0 + OFF_V, 128, 2048, 0) + wg * 768;
      wg_fence();
      #pragma unroll
      for (int s = 0; s < 8; s++) wg_ss48_tt(kv, da + s * 16, db + s * 16, s != 0);
      wg_commit();
      wg_wait<0>();
      pin<24>(kv);
      if (tid == 0) TS(15);
      if (w4 < 3) {
        const uint32_t wb = sb + OFF_KVS + (wg * 3 + w4) * 1536 + (lane & 15) * 96;
        #pragma unroll
        for (int j = 0; j < 6; j += 2)
          stsm4(wb + (j + (lane >> 4)) * 16, pack2(kv[4 * j], kv[4 * j + 1]), pack2(kv[4 * j + 2], kv[4 * j + 3]),
                pack2(kv[4 * j + 4], kv[4 * j + 5]), pack2(kv[4 * j + 6], kv[4 * j + 7]));
        __syncwarp();
        const int dl = w4 * 16 + (lane & 15), hl = dl >= 20;
        if (dl < 40) {
          uint4* dst = &g_kvp[(c * 16 + r) * 240 + wg * 40 + dl];
          uint32_t v[4], z[4];
          lds128(v, wb + (3 * hl + (lane >> 4)) * 16);
          lds64(z, wb + 32 + 8 * hl); z[2] = lds32(wb + 80); z[3] = epoch & 1u;
          v[3] = (v[3] & ~1u) | z[3];
          st128_rlx(dst + (lane >> 4) * 80, v);
          if (lane < 16) st128_rlx(dst + 160, z);
        }
      }
    }
    fence_async();
    bar_sync(1, 256);
    if (tid == 0) { st_rlx(FLAG(0, r, c), epoch); mbar_arrive(BAR(BR_PUB)); TS(4); }
    const int kvi = (tid >= 80) + (tid >= 160) + (tid >= 240), kd = tid - 80 * kvi;
    const int khd = kd / 20, kt0 = 5 * (khd >> 1) + 2 * (khd & 1);
    const uint32_t rb = sb + OFF_KVB + kd * 16;
    if (kvi < 3) {
      #pragma unroll 1
      for (int m = kvi; m < 7; m += 3) { const int q = kt0 + 3 + m; sts128(rb + (q >= 10 ? q - 10 : q) * 1280, 0, 0, 0, 0); }
    }
    uint32_t qa[20];
    {
      const float sc = 1.44269504089f + __uint_as_float(lds32(sb + OFF_EPOCH) ^ epoch);
      #pragma unroll
      for (int j = 0; j < 10; j++) { qa[2 * j] = pack2(phi(QV(j, 0), sc), phi(QV(j, 1), sc)); qa[2 * j + 1] = pack2(phi(QV(j, 2), sc), phi(QV(j, 3), sc)); }
    }
    if (tid == 0) TS(5);
    mbar_wait(BAR(BR_KVP), 0);
    if (tid == 0) TS(6);
    if (kvi < 3) {
      float s[8];
      zero<8>(s);
      uint32_t bad = 0;
      #pragma unroll 4
      for (int i = 0; i < 16; i++) {
        uint32_t w[4];
        lds128(w, sb + OFF_KVP + tid * 16 + i * 3840);
        bad |= w[3] ^ epoch;
        #pragma unroll
        for (int e = 0; e < 4; e++) { s[2 * e] += bf_lo(w[e]); s[2 * e + 1] += bf_hi(w[e]); }
      }
      if (__builtin_expect(bad & 1u, 0)) {
        zero<8>(s);
        #pragma unroll 1
        for (int i = 0; i < 16; i++) {
          uint32_t w[4] = {0, 0, 0, ~epoch};
          fix128_w3(w, &g_kvp[(c * 16 + i) * 240 + tid], epoch, 1u);
          #pragma unroll
          for (int e = 0; e < 4; e++) { s[2 * e] += bf_lo(w[e]); s[2 * e + 1] += bf_hi(w[e]); }
        }
        FIXCNT
      }
      const uint32_t p0 = pack2(s[0], s[1]), p1 = pack2(s[2], s[3]), p2 = pack2(s[4], s[5]), p3 = pack2(s[6], s[7]);
      if (kvi < 2) sts128(rb + (kt0 + (khd & 1) + kvi) * 1280, p0, p1, p2, p3);
      else {
        const bool od = khd & 1;
        sts128(rb + (5 * (khd >> 1) + 2) * 1280, od ? 0u : p0, od ? 0u : p1, od ? p0 : 0u, od ? p1 : 0u);
        const uint32_t zz = (p2 & 0xffffu) << (16 * (khd & 1));
        sts128(rb + 10 * 1280, khd < 2 ? zz : 0u, khd < 2 ? 0u : zz, 0u, 0u);
      }
    }
    fence_async();
    bar_sync(1, 256);
    if (tid == 0) TS(7);
    {
      float oa[44]; zero<44>(oa);
      constexpr uint64_t db = mkdesc(SB0 + OFF_KVB, 128, 1280, 0);
      wg_fence();
      #pragma unroll
      for (int s = 0; s < 5; s++) wg_rs88_tb(oa, &qa[4 * s], db + ((s == 4 && (c & 1)) ? 0 : (s + (c & 1)) * 16), s != 0);
      wg_commit();
      wg_wait<0>();
      pin<44>(oa);
      if (tid == 0) TS(13);
      float rc[4], rd[2][4];
      #pragma unroll
      for (int e = 0; e < 4; e++) asm("rcp.approx.ftz.f32 %0, %1;" : "=f"(rc[e]) : "f"(oa[40 + e] + 1e-6f));
      #pragma unroll
      for (int h = 0; h < 4; h++) {
        rd[0][h] = __shfl_sync(0xffffffff, rc[h & 1], (lane & 28) | (h >> 1));
        rd[1][h] = __shfl_sync(0xffffffff, rc[2 + (h & 1)], (lane & 28) | (h >> 1));
      }
      #pragma unroll
      for (int j = 0; j < 10; j++) {
        #pragma unroll
        for (int h = 0; h < 2; h++) {
          float f;
          if (j == 2) f = tq < 2 ? rd[h][0] : rd[h][1];
          else if (j == 7) f = tq < 2 ? rd[h][2] : rd[h][3];
          else f = rd[h][(8 * j) / 20];
          qa[2 * j + h] = pack2(oa[4 * j + 2 * h] * f, oa[4 * j + 2 * h + 1] * f);
        }
      }
      const uint32_t m0 = (lane & 7) == ((2 * w4) & 7), m1 = (lane & 7) == 2 * w4 + 1;
      const uint32_t oa_ = sb + OFF_EXTRA + (lane >> 4) * 2048 + (warp * 16 + (lane & 15)) * 16;
      bar_sync(1, 256);
#define TAG(v, m) (((v) & ~(m)) | (epoch & (m)))
      #pragma unroll
      for (int s = 0; s < 5; s++) stsm4(oa_ + s * 4096, TAG(qa[4 * s], m0), TAG(qa[4 * s + 1], m1), TAG(qa[4 * s + 2], m0), TAG(qa[4 * s + 3], m1));
    }
    fence_async();
    mbar_arrive(BAR(BR_OSTG));
    if (tid == 0) TS(8);
    float oc[40]; zero<40>(oc);
    {
      constexpr uint64_t dw0 = mkdesc(SB0, OFF_WOR, 1024, 1);
      const uint64_t da0 = mkdesc(SB0, 2048, 128, 0) + wg * 64;
      const uint32_t ck = sb + tid * 32 + ((lane >> 2) << 2);
      uint32_t bad = 0;
      mbar_wait(BAR(BR_WO), 0);
      wg_fence();
      wg_ss80_tb(oc, da0, dw0, 0);
      wg_commit();
      #pragma unroll 1
      for (int n = 0; n < 64; n++) {
        const int i = n & 7, src = CHUNK(i);
        const uint32_t so = n < 8 ? SLOT(i) : SLOT(2);
        const uint64_t da = da0 + (so >> 4), dw = dw0 + (int64_t)(i * 640 + (((src & 1) - i) * 640 + (src >> 1) * 2) * 65536);
        if (__builtin_expect(n >= 8, 0)) {
          wg_wait<0>();
          bar_sync(1, 256);
          if (tid == 0) { mbar_expect_tx(BAR(BR_RETRY), 20480); bulk_ld(sb + so, &g_o[(r * 8 + src) * 1280], 20480, BAR(BR_RETRY)); }
        }
        mbar_wait(BAR(n < 8 ? BR_OFULL + i : BR_RETRY), n < 8 ? 0 : n & 1);
        if (n == 1) { mbar_wait(BAR(BR_WO + 1), 0); if (tid == 0) TS(9); }
        wg_fence();
        #pragma unroll
        for (int s = 0; s < 5; s++) wg_ss80_tb(oc, da + s * 256, dw + s * 128, (i | s) != 0);
        wg_commit();
        bad |= (lds32(ck + so) ^ epoch) | (lds32(ck + so + 8192) ^ epoch) | (lds32(ck + so + (wg ? 0 : 16384)) ^ epoch);
        if (n == 0) wg_wait<0>(); else wg_wait<1>();
        __syncwarp();
        if (lane == 0 && n != 1 && n < 8) mbar_arrive(BAR(BR_OEMPTY) + 8 * (n ? n - 1 : 0));
        if (i == 7) {
          uint32_t any;
          asm volatile("{\n.reg .pred p;\nsetp.ne.u32 p, %1, 0;\nbarrier.red.or.pred p, 1, 256, p;\nselp.u32 %0, 1, 0, p;\n}" : "=r"(any) : "r"(bad & 1u) : "memory");
          if (!any) break;
          bad = 0;
          FIXCNT
        }
      }
      wg_wait<0>();
      pin<40>(oc);
    }
    if (tid == 0) TS(10);
    {
      const int row = w4 * 16 + (lane & 15);
      const uint32_t ob = sb + SLOT(3) + wg * 10240;
      #pragma unroll
      for (int j = 0; j < 8; j += 2)
        stsm4(ob + row * 128 + (((j + (lane >> 4)) ^ (row & 7)) << 4), pack2(oc[4 * j], oc[4 * j + 1]), pack2(oc[4 * j + 2], oc[4 * j + 3]),
              pack2(oc[4 * j + 4], oc[4 * j + 5]), pack2(oc[4 * j + 6], oc[4 * j + 7]));
      stsm4(ob + 8192 + row * 32 + (lane >> 4) * 16, pack2(oc[32], oc[33]), pack2(oc[34], oc[35]), pack2(oc[36], oc[37]), pack2(oc[38], oc[39]));
      fence_async();
      bar_sync(2 + wg, 128);
      if (w4 == 0 && elect_one()) {
        tma2d_st(&prm.m[M_O64], ob, 640 + c * 64, r * 128 + wg * 64);
        tma2d_st(&prm.m[M_O16], ob + 8192, 1152 + c * 16, r * 128 + wg * 64);
        bulk_commit(); bulk_wait0_read();
        if (wg == 0) { TS(11); DUMP(0, 20); }
      }
    }
    }
  } else {
    uint4 pv[3];
    const uint4* pp = reinterpret_cast<const uint4*>(prm.par[w4] + (c * 80 + r * 5) * 128);
    pv[0] = __ldg(pp + lane); pv[1] = __ldg(pp + 32 + lane); pv[2] = __ldg(pp + 64 + (lane & 15));
    const int kq = c * 80 + r * 5 + min(lane, 4);
    const unsigned short ldt = __ldg(reinterpret_cast<const unsigned short*>(prm.logdt) + kq), dsk0 = __ldg(reinterpret_cast<const unsigned short*>(prm.dskip) + kq);
    asm volatile("setmaxnreg.inc.sync.aligned.u32 152;");
    bar_sync(0, 512);
    if (EN_SSM) {
    const int g = lane >> 2, tq = lane & 3, t7 = tid & 127;
    {
      #pragma unroll 1
      for (int k = 0; k < 5; k++) {
        const uint32_t tz = sb + OFF_BLK + k * BLK + B_TBL + t7 * 16;
        if (t7 < 32 || t7 >= 96) sts128(tz, 0, 0, 0, 0);
        if (t7 < 124) sts128(tz + 2048, 0, 0, 0, 0);
        if (t7 < 16) sts128(sb + OFF_BLK + k * BLK - 256 + t7 * 16, 0, 0, 0, 0);
      }
      if (t7 < 5) sts64(sb + OFF_BLK + t7 * BLK + B_SP + 8, __float_as_uint(bf_round(expf(bf_lo(ldt)))), (uint32_t)dsk0 << 16);
      const uint32_t st = sb + OFF_BLK + (lane >> 4) * BLK + B_TBL + 512 + w4 * 256 + (lane & 15) * 16;
      #pragma unroll
      for (int i = 0; i < 3; i++) {
        if (i < 2 || lane < 16) sts128(st + 2 * i * BLK, pv[i].x, pv[i].y, pv[i].z, pv[i].w);
        if (w4 >= 2) {
          const uint32_t m2 = __vmaxu2(__vmaxu2(pv[i].x & 0x7fff7fffu, pv[i].y & 0x7fff7fffu), __vmaxu2(pv[i].z & 0x7fff7fffu, pv[i].w & 0x7fff7fffu));
          const uint32_t m = __reduce_max_sync(lane < 16 ? 0x0000ffffu : 0xffff0000u, max(m2 & 0xffffu, m2 >> 16));
          if ((lane & 15) == 0 && (i < 2 || lane == 0)) sts32(sb + OFF_BLK + (2 * i + (lane >> 4)) * BLK + B_SP + 8 + w4 * 4, m);
        }
      }
    }
    bar_sync(4, 128);
    if (t7 == 0) TS(40);
    {
      const uint32_t fa = sb + OFF_BLK + (w4 & 1) * BLK + (lane >> 3) * 256 + (lane & 7) * 16;
      const uint32_t ea = fa + (w4 >> 1) * 4096, ga = fa + 8192 + (w4 >> 1) * 3072;
      constexpr uint64_t dE = mkdesc(SB0 + OFF_BLK, 128, 1024, 0), dG = mkdesc(SB0 + OFF_BLK + 8192, 128, 1024, 0);
      #pragma unroll 1
      for (int k = 4; k >= 0; k--) {
        const uint32_t blk = sb + OFF_BLK + k * BLK;
        float fac, dsk;
        {
          const uint32_t st = blk + B_TBL + 512 + t7 * 2;
          uint32_t q[2], mm[2];
          const uint32_t p0 = lds16(st), p1 = lds16(st + 256), p2 = lds16(st + 512), p3 = lds16(st + 768);
          lds64(q, blk + B_SP + 8); lds64(mm, blk + B_SP + 16);
          const float dt = __uint_as_float(q[0]); dsk = __uint_as_float(q[1]);
          const uint32_t ex = min(max(max(mm[0], mm[1]) >> 7, 1u), 253u);
          const float sc = __uint_as_float((254u - ex) << 23);
          fac = 2.f * dt * __uint_as_float(ex << 23);
          const float lr = -bf_round(expf(bf_lo(p0))) * dt * 1.44269504089f;
          const float tn = bf_lo(p1) * dt * 0.15915494309f;
          float z1r, z1i, z2r, z2i, z4r, z4i, xr[8], xi[8], gr[8], gi[8], wr[9], wi[9];
          cexp_t(lr, -tn, z1r, z1i);
          cexp_t(lr * 8.f, tn * 8.f, xr[1], xi[1]);
          cexp_t(lr * 64.f, tn * 64.f, wr[0], wi[0]);
          xr[0] = 1.f; xi[0] = 0.f;
          cmul(xr[1], xi[1], xr[1], xi[1], xr[2], xi[2]); cmul(xr[2], xi[2], xr[1], xi[1], xr[3], xi[3]);
          cmul(xr[2], xi[2], xr[2], xi[2], xr[4], xi[4]);
          #pragma unroll
          for (int b = 1; b < 4; b++) cmul(xr[4], xi[4], xr[b], xi[b], xr[4 + b], xi[4 + b]);
          cmul(wr[0], wi[0], wr[0], wi[0], wr[1], wi[1]); cmul(wr[1], wi[1], wr[0], wi[0], wr[2], wi[2]);
          cmul(wr[1], wi[1], wr[1], wi[1], wr[3], wi[3]); cmul(wr[3], wi[3], wr[3], wi[3], wr[4], wi[4]);
          cmul(wr[4], wi[4], wr[3], wi[3], wr[5], wi[5]); cmul(wr[4], wi[4], wr[4], wi[4], wr[6], wi[6]);
          cmul(wr[6], wi[6], wr[4], wi[4], wr[7], wi[7]); cmul(wr[6], wi[6], wr[6], wi[6], wr[8], wi[8]);
          uint32_t R[4], I[4], PR[4], PI[4];
          #pragma unroll
          for (int b = 0; b < 4; b++) { R[b] = packh(xr[2 * b], xr[2 * b + 1]); I[b] = packh(xi[2 * b], xi[2 * b + 1]); }
          sts128(ea, R[0], R[1], R[2], R[3]); sts128(ea + 128, I[0], I[1], I[2], I[3]);
          #pragma unroll
          for (int i = 0; i < 3; i++) {
            const uint32_t z = packh(wr[i], wi[i]);
            #pragma unroll
            for (int b = 0; b < 4; b++) hcm2(R[b], I[b], z, PR[b], PI[b]);
            sts128(ea + (i + 1) * 1024, PR[0], PR[1], PR[2], PR[3]); sts128(ea + (i + 1) * 1024 + 128, PI[0], PI[1], PI[2], PI[3]);
          }
          gr[0] = bf_lo(p2) * sc; gi[0] = -bf_lo(p3) * sc;
          cmul(z1r, z1i, z1r, z1i, z2r, z2i); cmul(z2r, z2i, z2r, z2i, z4r, z4i);
          cmul(gr[0], gi[0], z1r, z1i, gr[1], gi[1]);
          cmul(gr[0], gi[0], z2r, z2i, gr[2], gi[2]); cmul(gr[1], gi[1], z2r, z2i, gr[3], gi[3]);
          #pragma unroll
          for (int b = 0; b < 4; b++) cmul(gr[b], gi[b], z4r, z4i, gr[4 + b], gi[4 + b]);
          sts128(ga, packh(gr[0], gr[1]), packh(gr[2], gr[3]), packh(gr[4], gr[5]), packh(gr[6], gr[7]));
          sts128(ga + 128, packh(gi[0], gi[1]), packh(gi[2], gi[3]), packh(gi[4], gi[5]), packh(gi[6], gi[7]));
          {
            const uint32_t z = packh(wr[3], -wi[3]), a4r = packh(gr[0], gr[4]), a4i = packh(gi[0], gi[4]);
            hcm2(packh(gr[0], gr[2]), packh(gi[0], gi[2]), z, PR[0], PI[0]);
            hcm2(packh(gr[4], gr[6]), packh(gi[4], gi[6]), z, PR[1], PI[1]);
            hcm2(a4r, a4i, packh(wr[4], -wi[4]), PR[2], PI[2]);
            hcm2(a4r, a4i, packh(wr[5], -wi[5]), PR[3], PI[3]);
            sts128(ga + 1024, PR[0], PR[1], PR[2], PR[3]); sts128(ga + 1024 + 128, PI[0], PI[1], PI[2], PI[3]);
            float hr, hi_;
            cmul(gr[0], gi[0], wr[3], -wi[3], hr, hi_);
            const uint32_t cr = packh(gr[0], hr), ci = packh(gi[0], hi_);
            #pragma unroll
            for (int i = 0; i < 3; i++) hcm2(cr, ci, packh(wr[6 + i], -wi[6 + i]), PR[i], PI[i]);
            sts128(ga + 2048, PR[0], PR[1], PR[2], 0u); sts128(ga + 2048 + 128, PI[0], PI[1], PI[2], 0u);
          }
        }
        fence_async();
        bar_sync(4, 128);
        if (t7 == 0 && k == 3) TS(50);
        float ka[24]; zero<24>(ka);
        wg_fence();
        #pragma unroll
        for (int s = 0; s < 8; s++) wg_ss48_tt_h(ka, dE + (s >> 2) * (BLK >> 4) + (s & 3) * 16, dG + (s >> 2) * (BLK >> 4) + (s & 3) * 16, s != 0);
        wg_commit();
        wg_wait<0>();
        pin<24>(ka);
        if (t7 == 0 && k == 3) TS(51);
        float kk[6];
        {
          const bool up = w4 >= 2;
          const uint32_t xa = sb + OFF_BLK + 2 * BLK + B_D + 7168 + t7 * 8;
          #pragma unroll
          for (int n = 0; n < 3; n++) {
            sts64f(xa + n * 1024, up ? ka[12 + 4 * n] : ka[4 * n + 2], up ? ka[13 + 4 * n] : ka[4 * n + 3]);
            kk[2 * n] = up ? ka[14 + 4 * n] : ka[4 * n]; kk[2 * n + 1] = up ? ka[15 + 4 * n] : ka[4 * n + 1];
          }
          bar_sync(4, 128);
          #pragma unroll
          for (int n = 0; n < 3; n++) {
            uint32_t o[2]; lds64(o, (xa ^ 512) + n * 1024);
            kk[2 * n] = (kk[2 * n] + __uint_as_float(o[0])) * fac; kk[2 * n + 1] = (kk[2 * n + 1] + __uint_as_float(o[1])) * fac;
          }
        }
        if (t7 == 0 && k == 3) TS(52);
        {
          const int j = (w4 & 1) * 16 + (w4 >> 1) * 8 + g;
          const uint32_t tb = blk + B_TBL;
          if (t7 == 0) kk[0] += dsk;
          const uint32_t pa_ = tb + (16 + 8 * j + 2 * tq) * 4;
          const uint32_t v = pack2(kk[1], kk[0]);
          sts32(pa_ + 4, v); sts16(pa_, v >> 16); sts16(pa_ + 10, v);
          const uint32_t u = pack2(kk[2], kk[3]), w = pack2(kk[4], kk[5]);
          if (tq < 2) {
            const uint32_t pb = tb + (16 + 256 + 8 * j + 4 * tq) * 4;
            sts16(pb, u); sts32(pb + 4, __byte_perm(u, 0, 0x1010)); sts32(pb + 8, __byte_perm(u, 0, 0x1032)); sts16(pb + 14, u >> 16);
            if (j | tq) { sts16(pb - 4, u); sts16(pb + 2, u); }
            const int i = 64 * tq + j;
            const uint32_t e0 = tb + (T_F3 + (((i - 1) & 1) ? 80 : 0) + ((i - 1) >> 1)) * 4, e1 = i ? e0 : tb + (T_F2 + 144 + 31) * 4;
            sts16(e1, w); sts16(e1 + 6, w); sts16(e0 + 64, w >> 16); sts16(e0 + 70, w >> 16);
            if (i == 0) { sts16(tb + (T_S + 3) * 4, w); sts32(tb + (T_S + 4) * 4, __byte_perm(w, 0, 0x1010)); sts16(tb + (T_S + 5) * 4 + 2, w); }
          } else {
            const int i = 32 * (tq - 2) + j;
            const uint32_t e1 = tb + (i ? T_F2 + ((2 * i - 1) & 3) * 48 + ((2 * i - 1) >> 2) : 16 + 511) * 4;
            const uint32_t e2 = tb + (T_F2 + (i & 1) * 96 + (i >> 1)) * 4;
            sts16(e1, u); sts16(e1 + 6, u); sts16(e2, u >> 16); sts16(e2 + 6, u >> 16);
            if (i == 0) {
              const uint32_t uu = __byte_perm(u, 0, 0x1010);
              sts32(tb + 528 * 4, uu); sts32(tb + 529 * 4, uu); sts32(tb + 530 * 4, uu); sts16(tb + 531 * 4 + 2, u);
              sts16(tb + (T_F3 + 80 + 63) * 4, w);
            }
          }
        }
        if (t7 == 0 && k == 3) TS(53);
      }
      bar_sync(4, 128);
      if (t7 == 0) { mbar_arrive(BAR(BR_KGEN)); TS(41); }
    }
    mbar_wait(BAR(BR_U), 0);
    if (EN_ATT) mbar_wait(BAR(BR_GEMM), 0);
    if (t7 == 0) TS(42);
    #pragma unroll 1
    for (int pass = 0; pass < 2; pass++) {
      const int k = pass ? w4 : 4;
      const uint32_t blk = sb + OFF_BLK + k * BLK, tb = blk + B_TBL + (uint32_t)((g - 2 * tq) * 4);
      if (k < 2) mbar_wait(BAR(BR_U2), 0);
      float acc[16][4];
      zero<64>(&acc[0][0]);
      const int kl = 16 * (lane >> 4) + 2 * (lane & 7) + ((lane >> 3) & 1);
      {
        auto ubase = [&](int sh) { const int q = kl - 2 * sh; return blk + (uint32_t)((q * 16) ^ ((q * 2) & 0x70)); };
#define LDQ(A, sh) _Pragma("unroll") for (int m = 0; m < 4; m++) load_quad(A[m], tb + (16 + 16 * (sh) + 128 * m) * 4);
#define LDB(B, ub, h) _Pragma("unroll") for (int p = 0; p < 4; p++) ldsm4(B[p], ((ub) ^ ((p & 1) * 64)) + (4 * (h) + p) * 512);
#define MLO(A, B) _Pragma("unroll") for (int m = 0; m < 4; m++) _Pragma("unroll") for (int cc = 0; cc < 8; cc++) mma16816(acc[cc + m], A[m], &B[cc >> 1][(cc & 1) * 2]);
#define MHI(A, B) _Pragma("unroll") for (int m = 0; m < 4; m++) _Pragma("unroll") for (int cc = 0; cc < 8 - m; cc++) mma16816(acc[8 + cc + m], A[m], &B[cc >> 1][(cc & 1) * 2]);
        int p_ = pass ? 0 : w4;
        const int pe = pass ? 4 : w4 + 1;
        uint32_t A[4][4], A2[4][4], Bl[4][4], Bh[4][4];
        uint32_t ub = ubase(p_ + 4);
        LDQ(A, p_ + 4) LDB(Bl, ub, 0)
        #pragma unroll 1
        for (; p_ < pe; p_++) {
          LDB(Bh, ub, 1)
          MLO(A, Bl)
          ub = ubase(p_);
          LDQ(A2, p_) LDB(Bl, ub, 0)
          MHI(A, Bh)
          LDB(Bh, ub, 1)
          load_quad(A[0], tb + (16 + 512 + 16 * (p_ & 1)) * 4); load_quad(A[1], tb + (T_S + 16 * (p_ & 1)) * 4);
          MLO(A2, Bl)
          if (p_ < 2) {
            #pragma unroll
            for (int cc = 0; cc < 8; cc++) mma16816(acc[cc + 4], A[0], &Bl[cc >> 1][(cc & 1) * 2]);
            #pragma unroll
            for (int cc = 0; cc < 4; cc++) mma16816(acc[cc + 12], A[0], &Bh[cc >> 1][(cc & 1) * 2]);
            #pragma unroll
            for (int cc = 0; cc < 8; cc++) mma16816(acc[cc + 8], A[1], &Bl[cc >> 1][(cc & 1) * 2]);
          }
          const int pn = ((p_ + 1) & 3) + 4;
          ub = ubase(pn);
          LDQ(A, pn) LDB(Bl, ub, 0)
          MHI(A2, Bh)
        }
      }
      if (t7 == 0) TS(57 + 3 * pass);
      mbar_wait(BAR(BR_DRDY) + 8 * k, 0);
      {
        const int ih = (lane >> 3) & 1;
        const uint32_t dl = blk + B_D + (uint32_t)(((lane >> 4) * 8 + (lane & 7)) * 16);
        const uint32_t d0_ = dl + ih * 1552, d8_ = dl + (ih ? 0 : 1536), d3_ = dl + B_D7 + ih * 1024;
        auto cls2 = [&](uint32_t da, uint32_t ta) {
          uint32_t B[6][2], A[6][4];
          #pragma unroll
          for (int e = 0; e < 6; e++) { B[e][0] = lds32v(ta + (e + 4) * 32); B[e][1] = lds32v(ta + (e + 3) * 32); }
          #pragma unroll
          for (int kk = 0; kk < 6; kk++) ldsm4t(A[kk], da + kk * 256);
          #pragma unroll
          for (int e = 0; e < 6; e++)
            #pragma unroll
            for (int kk = 0; kk < 6; kk++) if (2 * kk + e + 4 < 16) mma16816(acc[2 * kk + e + 4], A[kk], B[e]);
        };
        auto cls3 = [&](uint32_t da, uint32_t ta) {
          uint32_t B[8][2], A[4][4];
          #pragma unroll
          for (int e = 0; e < 8; e++) { B[e][0] = lds32v(ta + (e + 8) * 32); B[e][1] = lds32v(ta + (e + 7) * 32); }
          #pragma unroll
          for (int kk = 0; kk < 4; kk++) ldsm4t(A[kk], da + kk * 256);
          #pragma unroll
          for (int kk = 0; kk < 4; kk++)
            #pragma unroll
            for (int e = 0; e < 8; e++) if (2 * kk + e + 8 < 16) mma16816(acc[2 * kk + e + 8], A[kk], B[e]);
        };
        #pragma unroll 1
        for (int a = pass ? 0 : w4; a < (pass ? 4 : w4 + 1); a++) cls2(((a & 2) ? d8_ : d0_) + (a & 1) * B_D5, tb + (T_F2 + 48 * a - 32) * 4);
        #pragma unroll 1
        for (int b = pass ? 0 : (w4 & 1); b < (pass ? 2 : w4 - 1); b++) cls3(d3_ + b * 2048, tb + (T_F3 + 80 * b - 64) * 4);
      }
      if (t7 == 0) TS(58 + 3 * pass);
      const uint32_t ya = blk + (uint32_t)((kl * 16) ^ ((kl * 2) & 0x70));
#define STY(p) stsm4t((ya ^ (((p) & 1) * 64)) + (p) * 512, pack2(acc[2 * (p)][0], acc[2 * (p)][1]), pack2(acc[2 * (p)][2], acc[2 * (p)][3]), \
                      pack2(acc[2 * (p) + 1][0], acc[2 * (p) + 1][1]), pack2(acc[2 * (p) + 1][2], acc[2 * (p) + 1][3]))
      if (pass == 0) {
        const uint32_t xw = blk + 4096 + w4 * 4096 + lane * 16, xr = blk + 4096 + w4 * 1024 + lane * 16;
        #pragma unroll
        for (int h = 0; h < 2; h++) {
          bar_sync(4, 128);
          #pragma unroll
          for (int i = 0; i < 8; i++)
            sts128(xw + i * 512, __float_as_uint(acc[8 * h + i][0]), __float_as_uint(acc[8 * h + i][1]), __float_as_uint(acc[8 * h + i][2]), __float_as_uint(acc[8 * h + i][3]));
          bar_sync(4, 128);
          float y[8];
          #pragma unroll
          for (int i = 0; i < 8; i++) {
            uint32_t o[4]; lds128(o, xr + (i >> 1) * 4096 + (i & 1) * 512);
            #pragma unroll
            for (int e = 0; e < 4; e++) y[4 * (i & 1) + e] = i < 2 ? __uint_as_float(o[e]) : y[4 * (i & 1) + e] + __uint_as_float(o[e]);
          }
          stsm4t((ya ^ ((w4 & 1) * 64)) + (4 * h + w4) * 512, pack2(y[0], y[1]), pack2(y[2], y[3]), pack2(y[4], y[5]), pack2(y[6], y[7]));
        }
      } else {
        __syncwarp();
        #pragma unroll
        for (int p = 0; p < 8; p++) STY(p);
      }
      if (t7 == 0 && !pass) TS(55);
      fence_async();
      mbar_arrive(BAR(BR_Y4) + 8 * pass);
      if (t7 == 0) TS(59 + 3 * pass);
    }
    if (t7 == 0) DUMP(40, 64);
    }
  }
}

typedef CUresult (*EncFn)(CUtensorMap*, CUtensorMapDataType, cuuint32_t, void*, const cuuint64_t*, const cuuint64_t*, const cuuint32_t*,
                          const cuuint32_t*, CUtensorMapInterleave, CUtensorMapSwizzle, CUtensorMapL2promotion, CUtensorMapFloatOOBfill);
static void mkmap(EncFn enc, CUtensorMap* m, const void* base, int rank, const cuuint64_t* dims, const cuuint64_t* strides, const cuuint32_t* box, CUtensorMapSwizzle swz) {
  cuuint32_t es[5] = {1, 1, 1, 1, 1};
  enc(m, CU_TENSOR_MAP_DATA_TYPE_BFLOAT16, rank, const_cast<void*>(base), dims, strides, box, es, CU_TENSOR_MAP_INTERLEAVE_NONE, swz,
      CU_TENSOR_MAP_L2_PROMOTION_L2_128B, CU_TENSOR_MAP_FLOAT_OOB_FILL_NONE);
}

extern "C" void kernel_launch(void* const* d_in, const int* in_sizes, int n_in, void* d_out, int out_size) {
  void* fn = nullptr; cudaDriverEntryPointQueryResult qr;
  cudaGetDriverEntryPoint("cuTensorMapEncodeTiled", &fn, cudaEnableDefault, &qr);
  EncFn enc = (EncFn)fn;
  void* uy = nullptr; cudaGetSymbolAddress(&uy, g_uy);
  const cuuint64_t dx[2] = {640, 2048}, sx[1] = {1280};
  const cuuint32_t bx[2] = {64, 128}, bu[2] = {80, 128};
  const cuuint64_t dw[3] = {640, 640, 3}, sw[2] = {3840, 1280};
  const cuuint32_t br[3] = {16, 32, 3};
  const cuuint64_t dwa[4] = {64, 640, 10, 3}, swa[3] = {3840, 128, 1280}, dwb[4] = {32, 640, 20, 3}, swb[3] = {3840, 64, 1280};
  const cuuint32_t bwa[4] = {64, 32, 1, 3}, bwb[4] = {32, 32, 2, 3};
  const cuuint64_t dwo[2] = {640, 640};
  const cuuint32_t bwo[2] = {64, 80}, bo64[2] = {64, 64}, bo16[2] = {16, 64};
  const cuuint64_t dsa[2] = {2048, 1280}, ssa[1] = {4096};
  const cuuint32_t bsa[2] = {64, 80};
  const cuuint64_t dsb[2] = {64, 40960}, ssb[1] = {128};
  const cuuint32_t bsb[2] = {64, 32};
  const cuuint64_t dout[2] = {1280, 2048}, sout[1] = {2560};
  Params prm;
  mkmap(enc, &prm.m[M_X], d_in[7], 2, dx, sx, bx, CU_TENSOR_MAP_SWIZZLE_128B);
  mkmap(enc, &prm.m[M_W128], d_in[8], 4, dwa, swa, bwa, CU_TENSOR_MAP_SWIZZLE_128B);
  mkmap(enc, &prm.m[M_W64], d_in[8], 4, dwb, swb, bwb, CU_TENSOR_MAP_SWIZZLE_64B);
  mkmap(enc, &prm.m[M_WR], d_in[8], 3, dw, sw, br, CU_TENSOR_MAP_SWIZZLE_32B);
  mkmap(enc, &prm.m[M_WO], d_in[9], 2, dwo, sx, bwo, CU_TENSOR_MAP_SWIZZLE_128B);
  mkmap(enc, &prm.m[M_O64], d_out, 2, dout, sout, bo64, CU_TENSOR_MAP_SWIZZLE_128B);
  mkmap(enc, &prm.m[M_O16], d_out, 2, dout, sout, bo16, CU_TENSOR_MAP_SWIZZLE_NONE);
  mkmap(enc, &prm.m[M_SA], uy, 2, dsa, ssa, bsa, CU_TENSOR_MAP_SWIZZLE_128B);
  mkmap(enc, &prm.m[M_SB], uy, 2, dsb, ssb, bsb, CU_TENSOR_MAP_SWIZZLE_128B);
  mkmap(enc, &prm.m[M_OUT], d_out, 2, dout, sout, bu, CU_TENSOR_MAP_SWIZZLE_NONE);
  prm.u = (const __nv_bfloat16*)d_in[0]; prm.wo = (const __nv_bfloat16*)d_in[9];
  for (int i = 0; i < 4; i++) prm.par[i] = (const __nv_bfloat16*)d_in[1 + i];
  prm.logdt = (const __nv_bfloat16*)d_in[5]; prm.dskip = (const __nv_bfloat16*)d_in[6];
  cudaFuncSetAttribute(fused_kernel, cudaFuncAttributeMaxDynamicSharedMemorySize, SMEM_BYTES);
  cudaLaunchConfig_t cfg = {};
  cfg.gridDim = dim3(128); cfg.blockDim = dim3(512); cfg.dynamicSmemBytes = SMEM_BYTES; cfg.stream = cudaStreamPerThread;
  cudaLaunchAttribute at[1];
  at[0].id = cudaLaunchAttributeClusterDimension; at[0].val.clusterDim.x = 2; at[0].val.clusterDim.y = 1; at[0].val.clusterDim.z = 1;
  cfg.attrs = at; cfg.numAttrs = 1;
  cudaLaunchKernelEx(&cfg, fused_kernel, prm);
}
```

```cpp
#include <cuda_runtime.h>
#include <cuda_bf16.h>
#include <cuda_fp16.h>
#include <cuda.h>
#include <stdint.h>

#define U_PACE 250
#define U_DELAY 0
#define U_LPACE 0
#define EN_ATT 1
#define EN_SSM 1

__device__ __align__(1024) __nv_bfloat16 g_uy[2 * 640 * 2048];
__device__ __align__(128) uint4 g_kvp[8 * 16 * 240];
__device__ __align__(128) uint4 g_o[128 * 1280];
__device__ __align__(128) unsigned g_flag[4 * 128 * 32];
__device__ unsigned g_epoch[128];
#define TS(i) do {} while (0)
#define DUMP(lo, hi) do {} while (0)
#define FIXCNT

constexpr uint32_t SB0 = 1024;
constexpr uint32_t W_SLOT = 15360, OFF_X = 76800;
constexpr uint32_t OFF_WOR = 81920, OFF_KVP = 10240, OFF_KVS = 71680, OFF_PK = 10240, OFF_V = 30720, OFF_EXTRA = 102400, OFF_KVB = OFF_EXTRA;
constexpr uint32_t OFF_BAR = 125952, OFF_BLK = 128000, BLK = 20480;
constexpr uint32_t B_D = 4096, B_D5 = 3088, B_D7 = 6176, B_D9 = 8224, B_TBL = 14400, B_SP = 18432;
constexpr int T_S = 576, T_F2 = 624, T_F3 = 816;
constexpr uint32_t SMEM_BYTES = OFF_BLK + 5 * BLK;
enum { BR_FULL = 0, BR_WO = 5, BR_PUB = 7, BR_KVP = 8, BR_U = 9, BR_U2 = 10, BR_GEMM = 11, BR_KGEN = 12, BR_YIN = 13, BR_EPOCH = 14,
       BR_FREE = 15, BR_RETRY = 17, BR_OFULL = 18, BR_EMPTY = 26, BR_OEMPTY = 31, BR_Y4 = 38, BR_Y03 = 39, BR_OSTG = 40, BR_DRDY = 41, BR_COUNT = 46 };
constexpr uint32_t OFF_EPOCH = OFF_BAR + 8 * BR_COUNT;
enum { M_X, M_W128, M_W64, M_WR, M_WO, M_O64, M_O16, M_SA, M_SB, M_OUT, M_COUNT };

__device__ __forceinline__ long long clk64() { long long t; asm volatile("mov.u64 %0, %%clock64;" : "=l"(t) :: "memory"); return t; }
__device__ __forceinline__ uint32_t smem_u32(const void* p) { return (uint32_t)__cvta_generic_to_shared(p); }
__host__ __device__ constexpr uint64_t mkdesc(uint32_t addr, uint32_t lbo, uint32_t sbo, uint32_t swz) {
  return (uint64_t)((addr & 0x3FFFF) >> 4) | ((uint64_t)(lbo >> 4) << 16) | ((uint64_t)(sbo >> 4) << 32) | ((uint64_t)swz << 62);
}
__device__ __forceinline__ uint64_t desc2(uint32_t lo, uint32_t hi) { uint64_t d; asm("mov.b64 %0, {%1, %2};" : "=l"(d) : "r"(lo), "r"(hi)); return d; }
__device__ __forceinline__ void mbar_init(uint32_t bar, uint32_t cnt) { asm volatile("mbarrier.init.shared::cta.b64 [%0], %1;" :: "r"(bar), "r"(cnt) : "memory"); }
__device__ __forceinline__ void mbar_expect_tx(uint32_t bar, uint32_t bytes) { asm volatile("mbarrier.arrive.expect_tx.shared::cta.b64 _, [%0], %1;" :: "r"(bar), "r"(bytes) : "memory"); }
__device__ __forceinline__ void mbar_arrive(uint32_t bar) { asm volatile("mbarrier.arrive.shared::cta.b64 _, [%0];" :: "r"(bar) : "memory"); }
__device__ __forceinline__ void mbar_wait(uint32_t bar, uint32_t parity) {
  asm volatile("{\n.reg .pred p;\n.reg .u32 c;\nmov.u32 c, 0;\n"
    "WL:\nmbarrier.try_wait.parity.shared::cta.b64 p, [%0], %1;\n@p bra WD;\n"
    "add.u32 c, c, 1;\nsetp.lt.u32 p, c, 200000;\n@p bra WL;\nWD:\n}" :: "r"(bar), "r"(parity) : "memory");
}
__device__ __forceinline__ void poll_all(const unsigned* p, unsigned val) {
  asm volatile("{\n.reg .pred p;\n.reg .u32 c, v;\nmov.u32 c, 0;\n"
    "PL:\nld.relaxed.gpu.global.u32 v, [%0];\nsetp.eq.u32 p, v, %1;\nvote.sync.all.pred p, p, 0xffffffff;\n@p bra PD;\n"
    "add.u32 c, c, 1;\nsetp.lt.u32 p, c, 100000;\n@p bra PL;\nPD:\n}" :: "l"(p), "r"(val) : "memory");
}
__device__ __forceinline__ void poll_all_acq(const unsigned* p, unsigned val) {
  asm volatile("{\n.reg .pred p;\n.reg .u32 c, v;\nmov.u32 c, 0;\n"
    "PL:\nld.acquire.gpu.global.u32 v, [%0];\nsetp.eq.u32 p, v, %1;\nvote.sync.all.pred p, p, 0xffffffff;\n@p bra PD;\n"
    "add.u32 c, c, 1;\nsetp.lt.u32 p, c, 100000;\n@p bra PL;\nPD:\n}" :: "l"(p), "r"(val) : "memory");
}
__device__ __forceinline__ unsigned poll_bit(const unsigned* p, unsigned val, unsigned mask) {
  unsigned bal;
  asm volatile("{\n.reg .pred p;\n.reg .u32 c, v;\nmov.u32 c, 0;\n"
    "PL:\nld.relaxed.gpu.global.u32 v, [%1];\nsetp.eq.u32 p, v, %2;\nvote.sync.ballot.b32 %0, p, 0xffffffff;\n"
    "and.b32 v, %0, %3;\nsetp.ne.u32 p, v, 0;\n@p bra PD;\n"
    "add.u32 c, c, 1;\nsetp.lt.u32 p, c, 100000;\n@p bra PL;\nPD:\n}" : "=&r"(bal) : "l"(p), "r"(val), "r"(mask) : "memory");
  return bal;
}
__device__ __forceinline__ void fix128_w0(uint32_t* v, const void* p, uint32_t tag, uint32_t mask) {
  asm volatile("{\n.reg .pred p;\n.reg .u32 c, x;\n.reg .b128 t;\n.reg .b64 lo, hi;\nmov.u32 c, 0;\n"
    "FL:\nxor.b32 x, %0, %5;\nand.b32 x, x, %6;\nsetp.eq.u32 p, x, 0;\n@p bra FD;\n"
    "ld.relaxed.gpu.global.b128 t, [%4];\nmov.b128 {lo, hi}, t;\nmov.b64 {%0, %1}, lo;\nmov.b64 {%2, %3}, hi;\n"
    "add.u32 c, c, 1;\nsetp.lt.u32 p, c, 100000;\n@p bra FL;\nFD:\n}"
    : "+r"(v[0]), "+r"(v[1]), "+r"(v[2]), "+r"(v[3]) : "l"(p), "r"(tag), "r"(mask) : "memory");
}
__device__ __forceinline__ void fix128_w3(uint32_t* v, const void* p, uint32_t tag, uint32_t mask) {
  asm volatile("{\n.reg .pred p;\n.reg .u32 c, x;\n.reg .b128 t;\n.reg .b64 lo, hi;\nmov.u32 c, 0;\n"
    "FL:\nxor.b32 x, %3, %5;\nand.b32 x, x, %6;\nsetp.eq.u32 p, x, 0;\n@p bra FD;\n"
    "ld.relaxed.gpu.global.b128 t, [%4];\nmov.b128 {lo, hi}, t;\nmov.b64 {%0, %1}, lo;\nmov.b64 {%2, %3}, hi;\n"
    "add.u32 c, c, 1;\nsetp.lt.u32 p, c, 100000;\n@p bra FL;\nFD:\n}"
    : "+r"(v[0]), "+r"(v[1]), "+r"(v[2]), "+r"(v[3]) : "l"(p), "r"(tag), "r"(mask) : "memory");
}
__device__ __forceinline__ void fence_acq() { asm volatile("fence.acq_rel.gpu;" ::: "memory"); }
__device__ __forceinline__ bool elect_one() {
  uint32_t p; asm volatile("{\n.reg .pred P;\nelect.sync _|P, 0xffffffff;\nselp.u32 %0, 1, 0, P;\n}" : "=r"(p)); return p;
}
__device__ __forceinline__ void bar_sync(int id, int n) { asm volatile("bar.sync %0, %1;" :: "r"(id), "r"(n) : "memory"); }
__device__ __forceinline__ void fence_async() { asm volatile("fence.proxy.async.shared::cta;" ::: "memory"); }
__device__ __forceinline__ void fence_async_g() { asm volatile("fence.proxy.async.global;" ::: "memory"); }
__device__ __forceinline__ void tma2d(uint32_t dst, const CUtensorMap* m, uint32_t bar, int c0, int c1) {
  asm volatile("cp.async.bulk.tensor.2d.shared::cluster.global.mbarrier::complete_tx::bytes [%0], [%1, {%3, %4}], [%2];"
    :: "r"(dst), "l"(m), "r"(bar), "r"(c0), "r"(c1) : "memory");
}
__device__ __forceinline__ void tma3d(uint32_t dst, const CUtensorMap* m, uint32_t bar, int c0, int c1, int c2) {
  asm volatile("cp.async.bulk.tensor.3d.shared::cluster.global.mbarrier::complete_tx::bytes [%0], [%1, {%3, %4, %5}], [%2];"
    :: "r"(dst), "l"(m), "r"(bar), "r"(c0), "r"(c1), "r"(c2) : "memory");
}
__device__ __forceinline__ void tma4d(uint32_t dst, const CUtensorMap* m, uint32_t bar, int c0, int c1, int c2, int c3) {
  asm volatile("cp.async.bulk.tensor.4d.shared::cluster.global.mbarrier::complete_tx::bytes [%0], [%1, {%3, %4, %5, %6}], [%2];"
    :: "r"(dst), "l"(m), "r"(bar), "r"(c0), "r"(c1), "r"(c2), "r"(c3) : "memory");
}
__device__ __forceinline__ void tma2d_st(const CUtensorMap* m, uint32_t src, int c0, int c1) {
  asm volatile("cp.async.bulk.tensor.2d.global.shared::cta.bulk_group [%0, {%2, %3}], [%1];"
    :: "l"(m), "r"(src), "r"(c0), "r"(c1) : "memory");
}
__device__ __forceinline__ void bulk_ld(uint32_t dst, const void* src, uint32_t bytes, uint32_t bar) {
  asm volatile("cp.async.bulk.shared::cluster.global.mbarrier::complete_tx::bytes [%0], [%1], %2, [%3];"
    :: "r"(dst), "l"(src), "r"(bytes), "r"(bar) : "memory");
}
__device__ __forceinline__ void bulk_st(void* dst, uint32_t src, uint32_t bytes) {
  asm volatile("cp.async.bulk.global.shared::cta.bulk_group [%0], [%1], %2;" :: "l"(dst), "r"(src), "r"(bytes) : "memory");
}
__device__ __forceinline__ void bulk_commit() { asm volatile("cp.async.bulk.commit_group;" ::: "memory"); }
__device__ __forceinline__ void bulk_wait0() { asm volatile("cp.async.bulk.wait_group 0;" ::: "memory"); }
__device__ __forceinline__ void bulk_wait0_read() { asm volatile("cp.async.bulk.wait_group.read 0;" ::: "memory"); }
__device__ __forceinline__ unsigned ld_rlx(const unsigned* p) { unsigned v; asm volatile("ld.relaxed.gpu.global.u32 %0, [%1];" : "=r"(v) : "l"(p) : "memory"); return v; }
__device__ __forceinline__ unsigned ld_acq(const unsigned* p) { unsigned v; asm volatile("ld.acquire.gpu.global.u32 %0, [%1];" : "=r"(v) : "l"(p) : "memory"); return v; }
__device__ __forceinline__ void st_rlx(unsigned* p, unsigned v) { asm volatile("st.relaxed.gpu.global.u32 [%0], %1;" :: "l"(p), "r"(v) : "memory"); }
__device__ __forceinline__ void st_rel(unsigned* p, unsigned v) { asm volatile("st.release.gpu.global.u32 [%0], %1;" :: "l"(p), "r"(v) : "memory"); }
__device__ __forceinline__ void ld128_rlx(uint32_t* v, const void* p) {
  asm volatile("{\n.reg .b128 t;\n.reg .b64 lo, hi;\nld.relaxed.gpu.global.b128 t, [%4];\nmov.b128 {lo, hi}, t;\n"
    "mov.b64 {%0, %1}, lo;\nmov.b64 {%2, %3}, hi;\n}" : "=r"(v[0]), "=r"(v[1]), "=r"(v[2]), "=r"(v[3]) : "l"(p) : "memory");
}
__device__ __forceinline__ void st128_rlx(void* p, const uint32_t* v) {
  asm volatile("{\n.reg .b128 t;\n.reg .b64 lo, hi;\nmov.b64 lo, {%1, %2};\nmov.b64 hi, {%3, %4};\nmov.b128 t, {lo, hi};\n"
    "st.relaxed.gpu.global.b128 [%0], t;\n}" :: "l"(p), "r"(v[0]), "r"(v[1]), "r"(v[2]), "r"(v[3]) : "memory");
}
__device__ __forceinline__ uint32_t lds32(uint32_t a) { uint32_t v; asm volatile("ld.shared.u32 %0, [%1];" : "=r"(v) : "r"(a) : "memory"); return v; }
__device__ __forceinline__ uint32_t lds32v(uint32_t a) { uint32_t v; asm volatile("ld.volatile.shared.u32 %0, [%1];" : "=r"(v) : "r"(a) : "memory"); return v; }
__device__ __forceinline__ uint32_t cpa(uint32_t a, uint32_t one) { uint32_t v; asm volatile("mul.lo.u32 %0, %1, %2;" : "=r"(v) : "r"(a), "r"(one)); return v; }
__device__ __forceinline__ uint32_t cpb(uint32_t a, uint32_t zero) { uint32_t v; asm volatile("or.b32 %0, %1, %2;" : "=r"(v) : "r"(a), "r"(zero)); return v; }
__device__ __forceinline__ uint32_t lds16(uint32_t a) { uint16_t v; asm volatile("ld.shared.u16 %0, [%1];" : "=h"(v) : "r"(a) : "memory"); return v; }
__device__ __forceinline__ float ldsf(uint32_t a) { float v; asm volatile("ld.shared.f32 %0, [%1];" : "=f"(v) : "r"(a) : "memory"); return v; }
__device__ __forceinline__ void lds128(uint32_t* v, uint32_t a) { asm volatile("ld.shared.v4.u32 {%0,%1,%2,%3}, [%4];" : "=r"(v[0]), "=r"(v[1]), "=r"(v[2]), "=r"(v[3]) : "r"(a) : "memory"); }
__device__ __forceinline__ void sts32(uint32_t a, uint32_t v) { asm volatile("st.shared.u32 [%0], %1;" :: "r"(a), "r"(v) : "memory"); }
__device__ __forceinline__ void sts16(uint32_t a, uint32_t v) { asm volatile("st.shared.u16 [%0], %1;" :: "r"(a), "h"((uint16_t)v) : "memory"); }
__device__ __forceinline__ void sts64f(uint32_t a, float x, float y) { asm volatile("st.shared.v2.f32 [%0], {%1,%2};" :: "r"(a), "f"(x), "f"(y) : "memory"); }
__device__ __forceinline__ void sts128(uint32_t a, uint32_t x, uint32_t y, uint32_t z, uint32_t w) { asm volatile("st.shared.v4.u32 [%0], {%1,%2,%3,%4};" :: "r"(a), "r"(x), "r"(y), "r"(z), "r"(w) : "memory"); }
__device__ __forceinline__ void stsm4(uint32_t a, uint32_t r0, uint32_t r1, uint32_t r2, uint32_t r3) {
  asm volatile("stmatrix.sync.aligned.m8n8.x4.shared.b16 [%0], {%1,%2,%3,%4};" :: "r"(a), "r"(r0), "r"(r1), "r"(r2), "r"(r3) : "memory");
}
__device__ __forceinline__ void stsm4t(uint32_t a, uint32_t r0, uint32_t r1, uint32_t r2, uint32_t r3) {
  asm volatile("stmatrix.sync.aligned.m8n8.x4.trans.shared.b16 [%0], {%1,%2,%3,%4};" :: "r"(a), "r"(r0), "r"(r1), "r"(r2), "r"(r3) : "memory");
}
__device__ __forceinline__ void ldsm4t(uint32_t* r, uint32_t a) {
  asm volatile("ldmatrix.sync.aligned.m8n8.x4.trans.shared.b16 {%0,%1,%2,%3}, [%4];" : "=r"(r[0]), "=r"(r[1]), "=r"(r[2]), "=r"(r[3]) : "r"(a) : "memory");
}
__device__ __forceinline__ void ldsm4(uint32_t* r, uint32_t a) {
  asm volatile("ldmatrix.sync.aligned.m8n8.x4.shared.b16 {%0,%1,%2,%3}, [%4];" : "=r"(r[0]), "=r"(r[1]), "=r"(r[2]), "=r"(r[3]) : "r"(a) : "memory");
}
__device__ __forceinline__ void mma16816(float* d, const uint32_t* a, const uint32_t* b) {
  asm volatile("mma.sync.aligned.m16n8k16.row.col.f32.bf16.bf16.f32 {%0,%1,%2,%3}, {%4,%5,%6,%7}, {%8,%9}, {%0,%1,%2,%3};"
    : "+f"(d[0]), "+f"(d[1]), "+f"(d[2]), "+f"(d[3]) : "r"(a[0]), "r"(a[1]), "r"(a[2]), "r"(a[3]), "r"(b[0]), "r"(b[1]));
}
__device__ __forceinline__ uint32_t pack2(float lo, float hi) { uint32_t r; asm("cvt.rn.bf16x2.f32 %0, %1, %2;" : "=r"(r) : "f"(hi), "f"(lo)); return r; }
__device__ __forceinline__ uint32_t packh(float lo, float hi) { uint32_t r; asm("cvt.rn.f16x2.f32 %0, %1, %2;" : "=r"(r) : "f"(hi), "f"(lo)); return r; }
__device__ __forceinline__ uint32_t hcmul(uint32_t x, uint32_t zp, uint32_t zq) {
  const __half2 xx = *reinterpret_cast<__half2*>(&x);
  const __half2 r = __hfma2(__high2half2(xx), *reinterpret_cast<__half2*>(&zq), __hmul2(__low2half2(xx), *reinterpret_cast<__half2*>(&zp)));
  return *reinterpret_cast<const uint32_t*>(&r);
}
__device__ __forceinline__ void hcm2(uint32_t xr, uint32_t xi, uint32_t z, uint32_t& pr, uint32_t& pi) {
  const __half2 a = *reinterpret_cast<__half2*>(&xr), b = *reinterpret_cast<__half2*>(&xi), zz = *reinterpret_cast<__half2*>(&z);
  const __half2 re = __hfma2(__hneg2(b), __high2half2(zz), __hmul2(a, __low2half2(zz)));
  const __half2 im = __hfma2(a, __high2half2(zz), __hmul2(b, __low2half2(zz)));
  pr = *reinterpret_cast<const uint32_t*>(&re); pi = *reinterpret_cast<const uint32_t*>(&im);
}
__device__ __forceinline__ void sts64(uint32_t a, uint32_t x, uint32_t y) { asm volatile("st.shared.v2.u32 [%0], {%1,%2};" :: "r"(a), "r"(x), "r"(y) : "memory"); }
__device__ __forceinline__ void lds64(uint32_t* v, uint32_t a) { asm volatile("ld.shared.v2.u32 {%0,%1}, [%2];" : "=r"(v[0]), "=r"(v[1]) : "r"(a) : "memory"); }
__device__ __forceinline__ float bf_lo(uint32_t v) { return __uint_as_float(v << 16); }
__device__ __forceinline__ float bf_hi(uint32_t v) { return __uint_as_float(v & 0xffff0000u); }
__device__ __forceinline__ float bf_round(float x) { return bf_lo(pack2(x, 0.f)); }
__device__ __forceinline__ float ex2(float x) { float r; asm("ex2.approx.ftz.f32 %0, %1;" : "=f"(r) : "f"(x)); return r; }
__device__ __forceinline__ float phi(float t, float l2e = 1.44269504089f) { float e = ex2(t * l2e); return (t > 0.f ? t + 1.f : e) + 1e-6f; }
__device__ __forceinline__ void wg_fence() { asm volatile("wgmma.fence.sync.aligned;" ::: "memory"); }
__device__ __forceinline__ void wg_commit() { asm volatile("wgmma.commit_group.sync.aligned;" ::: "memory"); }
template <int N> __device__ __forceinline__ void wg_wait() { asm volatile("wgmma.wait_group.sync.aligned %0;" :: "n"(N) : "memory"); }
template <int N> __device__ __forceinline__ void pin(float* a) {
  #pragma unroll
  for (int i = 0; i < N; i++) asm volatile("" : "+f"(a[i]) :: "memory");
}
__device__ __forceinline__ int opaque(int v) { asm volatile("" : "+r"(v)); return v; }
template <int N> __device__ __forceinline__ void zero(float* a) {
  #pragma unroll
  for (int i = 0; i < N; i++) asm volatile("mov.b32 %0, 0;" : "=f"(a[i]));
}
template <int N> __device__ __forceinline__ void pinu(uint32_t* a) {
  #pragma unroll
  for (int i = 0; i < N; i++) asm volatile("" : "+r"(a[i]) :: "memory");
}
__device__ __forceinline__ void cexp_t(float lg2mag, float turns, float& re, float& im) {
  float m = ex2(lg2mag);
  float fr = (turns - __fadd_rn(__fadd_rn(turns, 12582912.f), -12582912.f)) * 6.283185307f;
  re = m * __cosf(fr); im = m * __sinf(fr);
}
__device__ __forceinline__ void cmul(float ar, float ai, float br, float bi, float& cr, float& ci) {
  cr = fmaf(ar, br, -ai * bi); ci = fmaf(ar, bi, ai * br);
}

__device__ __forceinline__ void wg_ss192_tb(float* d, uint64_t da, uint64_t db, int scale_d) {
  asm volatile("{\n.reg .pred p;\nsetp.ne.b32 p, %98, 0;\n"
    "wgmma.mma_async.sync.aligned.m64n192k16.f32.bf16.bf16 "
    "{%0, %1, %2, %3, %4, %5, %6, %7, %8, %9, %10, %11, %12, %13, %14, %15, %16, %17, %18, %19, %20, %21, %22, %23, %24, %25, %26, %27, %28, %29, %30, %31, %32, %33, %34, %35, %36, %37, %38, %39, %40, %41, %42, %43, %44, %45, %46, %47, %48, %49, %50, %51, %52, %53, %54, %55, %56, %57, %58, %59, %60, %61, %62, %63, %64, %65, %66, %67, %68, %69, %70, %71, %72, %73, %74, %75, %76, %77, %78, %79, %80, %81, %82, %83, %84, %85, %86, %87, %88, %89, %90, %91, %92, %93, %94, %95}, %96, %97, p, 1, 1, 0, 1;\n}\n"
    : "+f"(d[0]), "+f"(d[1]), "+f"(d[2]), "+f"(d[3]), "+f"(d[4]), "+f"(d[5]), "+f"(d[6]), "+f"(d[7]), "+f"(d[8]), "+f"(d[9]), "+f"(d[10]), "+f"(d[11]), "+f"(d[12]), "+f"(d[13]), "+f"(d[14]), "+f"(d[15]), "+f"(d[16]), "+f"(d[17]), "+f"(d[18]), "+f"(d[19]), "+f"(d[20]), "+f"(d[21]), "+f"(d[22]), "+f"(d[23]), "+f"(d[24]), "+f"(d[25]), "+f"(d[26]), "+f"(d[27]), "+f"(d[28]), "+f"(d[29]), "+f"(d[30]), "+f"(d[31]), "+f"(d[32]), "+f"(d[33]), "+f"(d[34]), "+f"(d[35]), "+f"(d[36]), "+f"(d[37]), "+f"(d[38]), "+f"(d[39]), "+f"(d[40]), "+f"(d[41]), "+f"(d[42]), "+f"(d[43]), "+f"(d[44]), "+f"(d[45]), "+f"(d[46]), "+f"(d[47]), "+f"(d[48]), "+f"(d[49]), "+f"(d[50]), "+f"(d[51]), "+f"(d[52]), "+f"(d[53]), "+f"(d[54]), "+f"(d[55]), "+f"(d[56]), "+f"(d[57]), "+f"(d[58]), "+f"(d[59]), "+f"(d[60]), "+f"(d[61]), "+f"(d[62]), "+f"(d[63]), "+f"(d[64]), "+f"(d[65]), "+f"(d[66]), "+f"(d[67]), "+f"(d[68]), "+f"(d[69]), "+f"(d[70]), "+f"(d[71]), "+f"(d[72]), "+f"(d[73]), "+f"(d[74]), "+f"(d[75]), "+f"(d[76]), "+f"(d[77]), "+f"(d[78]), "+f"(d[79]), "+f"(d[80]), "+f"(d[81]), "+f"(d[82]), "+f"(d[83]), "+f"(d[84]), "+f"(d[85]), "+f"(d[86]), "+f"(d[87]), "+f"(d[88]), "+f"(d[89]), "+f"(d[90]), "+f"(d[91]), "+f"(d[92]), "+f"(d[93]), "+f"(d[94]), "+f"(d[95])
    : "l"(da), "l"(db), "r"(scale_d));
}
__device__ __forceinline__ void wg_ss48_tb(float* d, uint64_t da, uint64_t db, int scale_d) {
  asm volatile("{\n.reg .pred p;\nsetp.ne.b32 p, %26, 0;\n"
    "wgmma.mma_async.sync.aligned.m64n48k16.f32.bf16.bf16 "
    "{%0, %1, %2, %3, %4, %5, %6, %7, %8, %9, %10, %11, %12, %13, %14, %15, %16, %17, %18, %19, %20, %21, %22, %23}, %24, %25, p, 1, 1, 0, 1;\n}\n"
    : "+f"(d[0]), "+f"(d[1]), "+f"(d[2]), "+f"(d[3]), "+f"(d[4]), "+f"(d[5]), "+f"(d[6]), "+f"(d[7]), "+f"(d[8]), "+f"(d[9]), "+f"(d[10]), "+f"(d[11]), "+f"(d[12]), "+f"(d[13]), "+f"(d[14]), "+f"(d[15]), "+f"(d[16]), "+f"(d[17]), "+f"(d[18]), "+f"(d[19]), "+f"(d[20]), "+f"(d[21]), "+f"(d[22]), "+f"(d[23])
    : "l"(da), "l"(db), "r"(scale_d));
}
__device__ __forceinline__ void wg_ss48_tt(float* d, uint64_t da, uint64_t db, int scale_d) {
  asm volatile("{\n.reg .pred p;\nsetp.ne.b32 p, %26, 0;\n"
    "wgmma.mma_async.sync.aligned.m64n48k16.f32.bf16.bf16 "
    "{%0, %1, %2, %3, %4, %5, %6, %7, %8, %9, %10, %11, %12, %13, %14, %15, %16, %17, %18, %19, %20, %21, %22, %23}, %24, %25, p, 1, 1, 1, 1;\n}\n"
    : "+f"(d[0]), "+f"(d[1]), "+f"(d[2]), "+f"(d[3]), "+f"(d[4]), "+f"(d[5]), "+f"(d[6]), "+f"(d[7]), "+f"(d[8]), "+f"(d[9]), "+f"(d[10]), "+f"(d[11]), "+f"(d[12]), "+f"(d[13]), "+f"(d[14]), "+f"(d[15]), "+f"(d[16]), "+f"(d[17]), "+f"(d[18]), "+f"(d[19]), "+f"(d[20]), "+f"(d[21]), "+f"(d[22]), "+f"(d[23])
    : "l"(da), "l"(db), "r"(scale_d));
}
__device__ __forceinline__ void wg_rs88_tb(float* d, const uint32_t* a, uint64_t db, int scale_d) {
  asm volatile("{\n.reg .pred p;\nsetp.ne.b32 p, %49, 0;\n"
    "wgmma.mma_async.sync.aligned.m64n88k16.f32.bf16.bf16 "
    "{%0, %1, %2, %3, %4, %5, %6, %7, %8, %9, %10, %11, %12, %13, %14, %15, %16, %17, %18, %19, %20, %21, %22, %23, %24, %25, %26, %27, %28, %29, %30, %31, %32, %33, %34, %35, %36, %37, %38, %39, %40, %41, %42, %43}, {%44, %45, %46, %47}, %48, p, 1, 1, 1;\n}\n"
    : "+f"(d[0]), "+f"(d[1]), "+f"(d[2]), "+f"(d[3]), "+f"(d[4]), "+f"(d[5]), "+f"(d[6]), "+f"(d[7]), "+f"(d[8]), "+f"(d[9]), "+f"(d[10]), "+f"(d[11]), "+f"(d[12]), "+f"(d[13]), "+f"(d[14]), "+f"(d[15]), "+f"(d[16]), "+f"(d[17]), "+f"(d[18]), "+f"(d[19]), "+f"(d[20]), "+f"(d[21]), "+f"(d[22]), "+f"(d[23]), "+f"(d[24]), "+f"(d[25]), "+f"(d[26]), "+f"(d[27]), "+f"(d[28]), "+f"(d[29]), "+f"(d[30]), "+f"(d[31]), "+f"(d[32]), "+f"(d[33]), "+f"(d[34]), "+f"(d[35]), "+f"(d[36]), "+f"(d[37]), "+f"(d[38]), "+f"(d[39]), "+f"(d[40]), "+f"(d[41]), "+f"(d[42]), "+f"(d[43])
    : "r"(a[0]), "r"(a[1]), "r"(a[2]), "r"(a[3]), "l"(db), "r"(scale_d));
}
__device__ __forceinline__ void wg_ss80_tb(float* d, uint64_t da, uint64_t db, int scale_d) {
  asm volatile("{\n.reg .pred p;\nsetp.ne.b32 p, %42, 0;\n"
    "wgmma.mma_async.sync.aligned.m64n80k16.f32.bf16.bf16 "
    "{%0, %1, %2, %3, %4, %5, %6, %7, %8, %9, %10, %11, %12, %13, %14, %15, %16, %17, %18, %19, %20, %21, %22, %23, %24, %25, %26, %27, %28, %29, %30, %31, %32, %33, %34, %35, %36, %37, %38, %39}, %40, %41, p, 1, 1, 0, 1;\n}\n"
    : "+f"(d[0]), "+f"(d[1]), "+f"(d[2]), "+f"(d[3]), "+f"(d[4]), "+f"(d[5]), "+f"(d[6]), "+f"(d[7]), "+f"(d[8]), "+f"(d[9]), "+f"(d[10]), "+f"(d[11]), "+f"(d[12]), "+f"(d[13]), "+f"(d[14]), "+f"(d[15]), "+f"(d[16]), "+f"(d[17]), "+f"(d[18]), "+f"(d[19]), "+f"(d[20]), "+f"(d[21]), "+f"(d[22]), "+f"(d[23]), "+f"(d[24]), "+f"(d[25]), "+f"(d[26]), "+f"(d[27]), "+f"(d[28]), "+f"(d[29]), "+f"(d[30]), "+f"(d[31]), "+f"(d[32]), "+f"(d[33]), "+f"(d[34]), "+f"(d[35]), "+f"(d[36]), "+f"(d[37]), "+f"(d[38]), "+f"(d[39])
    : "l"(da), "l"(db), "r"(scale_d));
}
__device__ __forceinline__ void wg_ss48_tt_h(float* d, uint64_t da, uint64_t db, int scale_d) {
  asm volatile("{\n.reg .pred p;\nsetp.ne.b32 p, %26, 0;\n"
    "wgmma.mma_async.sync.aligned.m64n48k16.f32.f16.f16 "
    "{%0, %1, %2, %3, %4, %5, %6, %7, %8, %9, %10, %11, %12, %13, %14, %15, %16, %17, %18, %19, %20, %21, %22, %23}, %24, %25, p, 1, 1, 1, 1;\n}\n"
    : "+f"(d[0]), "+f"(d[1]), "+f"(d[2]), "+f"(d[3]), "+f"(d[4]), "+f"(d[5]), "+f"(d[6]), "+f"(d[7]), "+f"(d[8]), "+f"(d[9]), "+f"(d[10]), "+f"(d[11]), "+f"(d[12]), "+f"(d[13]), "+f"(d[14]), "+f"(d[15]), "+f"(d[16]), "+f"(d[17]), "+f"(d[18]), "+f"(d[19]), "+f"(d[20]), "+f"(d[21]), "+f"(d[22]), "+f"(d[23])
    : "l"(da), "l"(db), "r"(scale_d));
}

struct Params {
  CUtensorMap m[M_COUNT];
  const __nv_bfloat16 *u, *par[4], *logdt, *dskip, *wo;
};

#define CHUNK(i) ((i) == 0 ? c : ((i) == 7 ? (c ^ 1) : (((c & 6) + 1 + (i)) & 7)))
#define FLAG(kind, rr, cc) (&g_flag[((kind) * 128 + (rr) * 8 + (cc)) * 32])
#define SLOT(i) ((i) == 0 || (i) == 6 ? OFF_EXTRA : OFF_BLK + ((i) == 7 ? 4 : 5 - (i)) * BLK)
__device__ __forceinline__ void load_quad(uint32_t* A, uint32_t addr) {
  A[0] = lds32v(addr); A[1] = lds32v(addr + 32); A[2] = lds32v(addr - 32); A[3] = lds32v(addr);
}

__global__ void __launch_bounds__(512, 1) fused_kernel(const __grid_constant__ Params prm) {
  extern __shared__ unsigned char smem_raw[];
  const uint32_t sb = __shfl_sync(0xffffffff, smem_u32(smem_raw), 0);
  const int tid = threadIdx.x, lane = tid & 31;
  const int warp = __shfl_sync(0xffffffff, tid >> 5, 0), wg = warp >> 2, w4 = warp & 3;
  const int cta = blockIdx.x, r = cta >> 3, c = cta & 7;
  if ((sb & 0xffffffu) != SB0) return;
#define BAR(i) (sb + OFF_BAR + 8 * (i))
  const bool sw64 = ((c + 1) & 2) != 0;

  if (wg == 3) {
    if (warp == 13 && elect_one()) {
      #pragma unroll
      for (int i = M_W128; i <= M_WR; i++) asm volatile("prefetch.tensormap [%0];" :: "l"(&prm.m[i]) : "memory");
    }
    asm volatile("setmaxnreg.dec.sync.aligned.u32 56;");
    if (warp == 12) {
      if (elect_one()) {
        #pragma unroll
        for (int i = 0; i < 5; i++) mbar_init(BAR(BR_FULL + i), 1);
        asm volatile("fence.mbarrier_init.release.cluster;" ::: "memory");
      }
      {
        const CUtensorMap* mwp = &prm.m[sw64 ? M_W64 : M_W128];
        const int mcol = (c * 80 + (c & 1) * 16) >> (sw64 ? 5 : 6), rcol = c * 80 + ((c & 1) ? 0 : 64);
        uint32_t s = 0, ph = 1, xs = 0;
        #pragma unroll 1
        for (int kb = 0; kb < 20; kb++) {
          if (kb == 2) bar_sync(0, 512);
          if (kb >= 5) mbar_wait(BAR(BR_EMPTY) + 8 * s, ph);
          if (EN_ATT && elect_one()) {
            const uint32_t st = sb + s * W_SLOT, fb = BAR(BR_FULL) + 8 * s;
            mbar_expect_tx(fb, (kb & 1) ? W_SLOT : W_SLOT + 16384);
            if (!(kb & 1)) tma2d(sb + OFF_X + xs, &prm.m[M_X], fb, kb * 32, r * 128);
            tma4d(st, mwp, fb, 0, kb * 32, mcol, 0);
            tma3d(st + 12288, &prm.m[M_WR], fb, rcol, kb * 32, 0);
          }
          if (!EN_ATT && kb == 2) break;
          if (++s == 5) { s = 0; ph ^= 1; }
          if (kb & 1) { xs += 16384; if (xs == 49152) xs = 0; }
        }
      }
      if (EN_ATT) {
      mbar_wait(BAR(BR_EPOCH), 0);
      const unsigned epoch = lds32(sb + OFF_EPOCH);
      const unsigned* fo = FLAG(3, r, lane & 7);
      unsigned seen = __ballot_sync(0xffffffff, ld_rlx(lane < 16 ? fo : FLAG(0, lane & 15, c)) == epoch) & 0xffu;
      mbar_wait(BAR(BR_GEMM), 0);
      if (elect_one()) {
        mbar_expect_tx(BAR(BR_WO), 10240);
        tma2d(sb, &prm.m[M_WO], BAR(BR_WO), c * 64, c * 80);
        mbar_expect_tx(BAR(BR_KVP), 61440);
        mbar_expect_tx(BAR(BR_WO + 1), 7 * 10240);
      }
      {
        uint32_t ds = sb + OFF_WOR + (lane >> 3) * 128 + (((lane & 7) ^ (lane >> 3)) << 4);
        #pragma unroll 1
        for (int h = 0; h < 2; h++) {
          const int i = (lane & 6) + h;
          const char* gs = reinterpret_cast<const char*>(prm.wo) + (size_t)((lane >> 3) + CHUNK(i) * 80) * 1280 + 1024 + c * 32 + (lane & 1) * 16;
          #pragma unroll 2
          for (int q = 0; q < 20; q++) {
            asm volatile("cp.async.cg.shared.global [%0], [%1], 16;" :: "r"(ds), "l"(gs) : "memory");
            ds = (ds + 512) ^ 64; gs += 5120;
          }
        }
      }
      mbar_wait(BAR(BR_PUB), 0);
      poll_all(FLAG(0, lane & 15, c), epoch);
      if (elect_one()) { TS(23); bulk_ld(sb + OFF_KVP, &g_kvp[c * 16 * 240], 61440, BAR(BR_KVP)); }
      asm volatile("cp.async.wait_all;" ::: "memory");
      fence_async();
      mbar_arrive(BAR(BR_WO));
      mbar_wait(BAR(BR_OSTG), 0);
      if (elect_one()) {
        bulk_st(&g_o[cta * 1280], sb + OFF_EXTRA, 20480);
        bulk_commit();
        mbar_arrive(BAR(BR_OFULL));
        #pragma unroll 1
        for (int i = 1; i < 8; i++) tma2d(sb + i * 10240, &prm.m[M_WO], BAR(BR_WO + 1), c * 64, CHUNK(i) * 80);
        bulk_wait0();
        st_rlx(FLAG(3, r, c), epoch);
        TS(20);
      }
      __syncwarp();
      #pragma unroll 1
      for (int i = 1; i < 8; i++) {
        const int src = CHUNK(i);
        if (!((seen >> src) & 1)) seen = poll_bit(fo, epoch, 1u << src);
        if (i >= 6) mbar_wait(BAR(BR_OEMPTY - 6) + 8 * i, 0);
        else if (EN_SSM && i < 3) mbar_wait(BAR(BR_FREE - 1) + 8 * i, 0);
        if (elect_one()) {
          mbar_expect_tx(BAR(BR_OFULL) + 8 * i, 20480);
          bulk_ld(sb + SLOT(i), &g_o[(r * 8 + src) * 1280], 20480, BAR(BR_OFULL) + 8 * i);
          if (i == 1) TS(21);
          if (i == 7) TS(22);
        }
        __syncwarp();
      }
      if (lane == 0) { DUMP(20, 30); }
      }
    } else {
      const int hw = warp - 13, ht = tid - 416;
      unsigned epoch = 0;
      if (hw == 2 && elect_one()) {
        #pragma unroll
        for (int i = 5; i < BR_COUNT; i++) mbar_init(BAR(i), i == BR_WO ? 33 : i < BR_EMPTY ? 1 : i < BR_OEMPTY ? 2 : i < BR_Y4 ? 8 : i < BR_OSTG ? 128 : i == BR_OSTG ? 256 : 96);
        asm volatile("fence.mbarrier_init.release.cluster;" ::: "memory");
      }
      bar_sync(0, 512);
      if (hw == 1 && elect_one()) {
        #pragma unroll
        for (int i = M_WO; i < M_COUNT; i++) asm volatile("prefetch.tensormap [%0];" :: "l"(&prm.m[i]) : "memory");
      }
      if (U_DELAY) __nanosleep(U_DELAY);
      if (EN_SSM && ht < 80) {
        const int rr = ht / 10;
        const char* gs = reinterpret_cast<const char*>(prm.u) + (size_t)(r * 128 + rr) * 1280 + c * 160 + (ht - rr * 10) * 16;
        uint32_t ds = sb + OFF_BLK + 3 * BLK + B_D + ht * 16;
        #pragma unroll 1
        for (int i = 0; i < 16; i++) {
          asm volatile("cp.async.cg.shared.global [%0], [%1], 16;" :: "r"(ds), "l"(gs) : "memory");
          ds += i == 7 ? BLK - 7 * 1280 : 1280; gs += 10240;
          if (U_LPACE) __nanosleep(U_LPACE);
        }
      }
      if (hw == 0) {
        if (lane == 0) {
          epoch = ld_rlx(&g_epoch[cta]) + 1;
          st_rlx(&g_epoch[cta], epoch);
          sts32(sb + OFF_EPOCH, epoch);
          mbar_arrive(BAR(BR_EPOCH));
        }
        epoch = __shfl_sync(0xffffffff, epoch, 0);
      }
      if (EN_SSM) {
      const int mi = lane >> 3, rw = lane & 7, ch0 = c * 80 + r * 5;
      asm volatile("cp.async.wait_all;" ::: "memory");
      bar_sync(5, 96);
      if (ht == 0) TS(36);
      {
        uint4* gp = reinterpret_cast<uint4*>(g_uy + (size_t)(c * 80 + hw * 8 + (lane >> 2)) * 2048 + r * 128 + (lane & 3) * 8);
        uint32_t sa = sb + OFF_BLK + 3 * BLK + B_D + (8 * (rw >> 1) + 2 * mi + (rw & 1)) * 160 + hw * 16;
        #pragma unroll 1
        for (int i = hw; i < 10; i += 3) {
          uint32_t v[4][4];
          #pragma unroll
          for (int q = 0; q < 4; q++) ldsm4t(v[q], sa + (q >> 1) * BLK + (q & 1) * 5120);
          #pragma unroll
          for (int q = 0; q < 4; q++) {
            gp[q * 4] = make_uint4(v[q][0], v[q][1], v[q][2], v[q][3]);
            if (q & 1) __nanosleep(U_PACE);
          }
          gp += 6144; sa += 48;
        }
      }
      bar_sync(5, 96);
      if (hw == 0) {
        if (lane == 0) { st_rel(FLAG(1, r, c), epoch); TS(30); }
        __syncwarp();
        poll_all_acq(FLAG(1, lane & 15, c), epoch);
      }
      #pragma unroll 1
      for (int k = 4; k >= 0; k--) {
        const uint32_t blk = sb + OFF_BLK + k * BLK;
        if (k == 2) mbar_wait(BAR(BR_KGEN), 0);
        if (hw == 0 && !(k & 1) && k && elect_one()) {
          const uint32_t br = BAR(k == 4 ? BR_U : BR_U2);
          fence_async_g();
          mbar_expect_tx(br, k == 4 ? 12288 : 8192);
          #pragma unroll 1
          for (int q = k == 4 ? 4 : 1; q >= k - 2; q--) tma2d(sb + OFF_BLK + q * BLK, &prm.m[M_SB], br, 0, (ch0 + q) * 32);
          TS(31);
        }
        mbar_wait(BAR(k >= 2 ? BR_U : BR_U2), 0);
        #pragma unroll 1
        for (int kap = ht; kap < 192; kap += 96) {
          float P[33];
          P[0] = 0.f;
          #pragma unroll
          for (int q = 0; q < 4; q++) {
            const int ch = kap - 3 + q;
            uint32_t v[4];
            lds128(v, blk + (uint32_t)((ch * 16) ^ ((ch * 2) & 0x70)));
            #pragma unroll
            for (int e = 0; e < 4; e++) {
              P[q * 8 + 2 * e + 1] = (q == 0 && e < 2) ? 0.f : P[q * 8 + 2 * e] + bf_lo(v[e]);
              P[q * 8 + 2 * e + 2] = (q == 0 && e < 2) ? 0.f : P[q * 8 + 2 * e + 1] + bf_hi(v[e]);
            }
          }
#define WIN(lo, hi, e) (P[25 + (e) - (lo)] - P[24 + (e) - (hi)])
#define WIN8(lo, hi) pack2(WIN(lo, hi, 0), WIN(lo, hi, 1)), pack2(WIN(lo, hi, 2), WIN(lo, hi, 3)), pack2(WIN(lo, hi, 4), WIN(lo, hi, 5)), pack2(WIN(lo, hi, 6), WIN(lo, hi, 7))
          const uint32_t o2 = blk + B_D + (kap & 1) * 1552 + (kap >> 1) * 16;
          sts128(o2, WIN8(3, 5));
          sts128(o2 + B_D5, WIN8(6, 10));
          if (kap < 128) {
            const uint32_t o = blk + B_D + (kap & 1) * 1024 + (kap >> 1) * 16;
            sts128(o + B_D7, WIN8(5, 11));
            sts128(o + B_D9, WIN8(12, 20));
          }
        }
        if (ht < 2) sts128(blk + B_D + ht * B_D5 + 1536, 0, 0, 0, 0);
        mbar_arrive(BAR(BR_DRDY) + 8 * k);
      }
      if (ht == 0) TS(32);
      if (hw == 0) {
        #pragma unroll 1
        for (int p = 0; p < 2; p++) {
          mbar_wait(BAR(BR_Y4) + 8 * p, 0);
          if (elect_one()) {
            #pragma unroll 1
            for (int k = 4 - p; k >= 4 - 4 * p; k--) tma2d_st(&prm.m[M_SB], sb + OFF_BLK + k * BLK, 0, (640 + ch0 + k) * 32);
            bulk_commit(); bulk_wait0_read();
            mbar_arrive(BAR(BR_FREE) + 8 * p);
          }
          __syncwarp();
        }
        if (elect_one()) {
          mbar_expect_tx(BAR(BR_YIN), 20480);
          bulk_wait0();
          st_rel(FLAG(2, r, c), epoch);
          TS(33);
        }
        __syncwarp();
        poll_all_acq(FLAG(2, lane & 15, c), epoch);
        if (EN_ATT) mbar_wait(BAR(BR_OEMPTY + 5), 0);
        if (elect_one()) {
          fence_async_g();
          tma2d(sb + OFF_BLK + BLK, &prm.m[M_SA], BAR(BR_YIN), r * 128, 640 + c * 80);
          tma2d(sb + OFF_BLK + BLK + 10240, &prm.m[M_SA], BAR(BR_YIN), r * 128 + 64, 640 + c * 80);
          TS(34);
        }
      }
      {
        uint32_t sa = sb + OFF_BLK + BLK + (hw * 8 + rw) * 128 + ((mi ^ rw) << 4);
        uint32_t da = sb + OFF_BLK + (8 * mi + rw) * 160 + hw * 16;
        mbar_wait(BAR(BR_YIN), 0);
        #pragma unroll 1
        for (int i = hw; i < 10; i += 3) {
          uint32_t v[4][4];
          #pragma unroll
          for (int q = 0; q < 4; q++) ldsm4t(v[q], (sa ^ ((q & 1) * 64)) + (q >> 1) * 10240);
          #pragma unroll
          for (int q = 0; q < 4; q++) stsm4(da + q * 5120, v[q][0], v[q][1], v[q][2], v[q][3]);
          sa += 3072; da += 48;
        }
      }
      fence_async();
      bar_sync(5, 96);
      if (hw == 0 && elect_one()) {
        tma2d_st(&prm.m[M_OUT], sb + OFF_BLK, c * 80, r * 128);
        bulk_commit(); bulk_wait0_read();
        TS(35); DUMP(30, 40); DUMP(0, 1);
      }
      }
    }
  } else if (wg < 2) {
    asm volatile("setmaxnreg.inc.sync.aligned.u32 152;");
    bar_sync(0, 512);
    if (EN_ATT) {
    const int tq = lane & 3, t7 = tid & 127;
    float am[96], ar[24];
    {
      constexpr uint64_t da0 = mkdesc(SB0 + OFF_X, 16, 1024, 1), dr0 = mkdesc(SB0 + 12288, 1024, 256, 3);
      const uint64_t db0 = sw64 ? mkdesc(SB0, 2048, 512, 2) : mkdesc(SB0, 4096, 1024, 1);
      const uint32_t kst = sw64 ? 64 : 128, bh = db0 >> 32;
      uint32_t s = 0, ph = 0, xo = 0;
      #pragma unroll 1
      for (int kb = 0; kb < 20; kb++) {
        const uint32_t wo_ = s * (W_SLOT >> 4), al = (uint32_t)da0 + wg * 512 + xo, bl = (uint32_t)db0 + wo_, rl = (uint32_t)dr0 + wo_;
        mbar_wait(BAR(BR_FULL) + 8 * s, ph);
        if (kb == 0 && tid == 0) TS(1);
        wg_fence();
        wg_ss192_tb(am, desc2(al, da0 >> 32), desc2(bl, bh), kb != 0);
        wg_ss48_tb(ar, desc2(al, da0 >> 32), desc2(rl, dr0 >> 32), kb != 0);
        wg_ss192_tb(am, desc2(al + 2, da0 >> 32), desc2(bl + kst, bh), 1);
        wg_ss48_tb(ar, desc2(al + 2, da0 >> 32), desc2(rl + 32, dr0 >> 32), 1);
        wg_commit();
        wg_wait<1>();
        if (t7 == 0 && kb > 0 && kb < 16) mbar_arrive(BAR(BR_EMPTY) + 8 * (s == 0 ? 4 : s - 1));
        if (++s == 5) { s = 0; ph ^= 1; }
        xo += (kb & 1) ? 1020 : 4;
        if (xo == 3072) xo = 0;
      }
      wg_wait<0>();
      pin<96>(am); pin<24>(ar);
    }
    if (tid == 0) TS(2);
#define QV(j, e) ((j) < 8 ? am[4 * (j) + (e)] : ar[4 * ((j) - 8) + (e)])
#define KV_(j, e) ((j) < 8 ? am[32 + 4 * (j) + (e)] : ar[8 + 4 * ((j) - 8) + (e)])
#define VV(j, e) ((j) < 8 ? am[64 + 4 * (j) + (e)] : ar[16 + 4 * ((j) - 8) + (e)])
    {
      bar_sync(1, 256);
      if (tid == 0) mbar_arrive(BAR(BR_GEMM));
      const uint32_t ro = sb + (uint32_t)((warp * 16 + (lane & 15)) * 16);
      const int l0 = 2 * (c & 1) + (lane >> 4);
      const uint32_t ones = (tq == 0) ? 0x00003f80u : 0u;
#define PV(j) pack2(VV(j, 0), VV(j, 1)), pack2(VV(j, 2), VV(j, 3))
#define PK(j) pack2(phi(KV_(j, 0)), phi(KV_(j, 1))), pack2(phi(KV_(j, 2)), phi(KV_(j, 3)))
      stsm4(ro + OFF_V + (5 + 6 * (lane >> 4)) * 2048, ones, ones, ones, ones);
      #pragma unroll
      for (int j = 0; j < 10; j += 2) {
        const int l = (j == 8 && (c & 1)) ? l0 - 2 : l0 + j;
        stsm4(ro + OFF_V + (l + (l >= 5)) * 2048, PV(j), PV(j + 1));
        stsm4(ro + OFF_PK + l * 2048, PK(j), PK(j + 1));
      }
    }
    fence_async();
    bar_sync(1, 256);
    if (tid == 0) TS(3);
    mbar_wait(BAR(BR_EPOCH), 0);
    const unsigned epoch = lds32(sb + OFF_EPOCH);
    {
      float kv[24]; zero<24>(kv);
      constexpr uint64_t da = mkdesc(SB0 + OFF_PK, 128, 2048, 0), db = mkdesc(SB0 + OFF_V, 128, 2048, 0);
      wg_fence();
      #pragma unroll
      for (int s = 0; s < 8; s++) wg_ss48_tt(kv, desc2((uint32_t)da + wg * 640 + s * 16, da >> 32), desc2((uint32_t)db + wg * 768 + s * 16, db >> 32), s != 0);
      wg_commit();
      wg_wait<0>();
      pin<24>(kv);
      if (tid == 0) TS(15);
      if (w4 < 3) {
        const uint32_t wb = sb + OFF_KVS + (wg * 3 + w4) * 1536 + (lane & 15) * 96;
        #pragma unroll
        for (int j = 0; j < 6; j += 2)
          stsm4(wb + (j + (lane >> 4)) * 16, pack2(kv[4 * j], kv[4 * j + 1]), pack2(kv[4 * j + 2], kv[4 * j + 3]),
                pack2(kv[4 * j + 4], kv[4 * j + 5]), pack2(kv[4 * j + 6], kv[4 * j + 7]));
        __syncwarp();
        const int dl = w4 * 16 + (lane & 15), hl = dl >= 20;
        if (dl < 40) {
          uint4* dst = &g_kvp[(c * 16 + r) * 240 + wg * 40 + dl];
          uint32_t v[4], z[4];
          lds128(v, wb + (3 * hl + (lane >> 4)) * 16);
          lds64(z, wb + 32 + 8 * hl); z[2] = lds32(wb + 80); z[3] = epoch & 1u;
          v[3] = (v[3] & ~1u) | z[3];
          st128_rlx(dst + (lane >> 4) * 80, v);
          if (lane < 16) st128_rlx(dst + 160, z);
        }
      }
    }
    fence_async();
    bar_sync(1, 256);
    if (tid == 0) { st_rlx(FLAG(0, r, c), epoch); mbar_arrive(BAR(BR_PUB)); TS(4); }
    const int kvi = (tid >= 80) + (tid >= 160) + (tid >= 240), kd = tid - 80 * kvi;
    const int khd = kd / 20, kt0 = 5 * (khd >> 1) + 2 * (khd & 1);
    const uint32_t rb = sb + OFF_KVB + kd * 16;
    if (kvi < 3) {
      #pragma unroll 1
      for (int m = kvi; m < 7; m += 3) { const int q = kt0 + 3 + m; sts128(rb + (q >= 10 ? q - 10 : q) * 1280, 0, 0, 0, 0); }
    }
    uint32_t qa[20];
    {
      const float sc = 1.44269504089f + __uint_as_float(lds32(sb + OFF_EPOCH) ^ epoch);
      #pragma unroll
      for (int j = 0; j < 10; j++) { qa[2 * j] = pack2(phi(QV(j, 0), sc), phi(QV(j, 1), sc)); qa[2 * j + 1] = pack2(phi(QV(j, 2), sc), phi(QV(j, 3), sc)); }
    }
    if (tid == 0) TS(5);
    mbar_wait(BAR(BR_KVP), 0);
    if (tid == 0) TS(6);
    if (kvi < 3) {
      float s[8];
      zero<8>(s);
      uint32_t bad = 0;
      #pragma unroll 4
      for (int i = 0; i < 16; i++) {
        uint32_t w[4];
        lds128(w, sb + OFF_KVP + tid * 16 + i * 3840);
        bad |= w[3] ^ epoch;
        #pragma unroll
        for (int e = 0; e < 4; e++) { s[2 * e] += bf_lo(w[e]); s[2 * e + 1] += bf_hi(w[e]); }
      }
      if (__builtin_expect(bad & 1u, 0)) {
        zero<8>(s);
        #pragma unroll 1
        for (int i = 0; i < 16; i++) {
          uint32_t w[4] = {0, 0, 0, ~epoch};
          fix128_w3(w, &g_kvp[(c * 16 + i) * 240 + tid], epoch, 1u);
          #pragma unroll
          for (int e = 0; e < 4; e++) { s[2 * e] += bf_lo(w[e]); s[2 * e + 1] += bf_hi(w[e]); }
        }
        FIXCNT
      }
      const uint32_t p0 = pack2(s[0], s[1]), p1 = pack2(s[2], s[3]), p2 = pack2(s[4], s[5]), p3 = pack2(s[6], s[7]);
      if (kvi < 2) sts128(rb + (kt0 + (khd & 1) + kvi) * 1280, p0, p1, p2, p3);
      else {
        const bool od = khd & 1;
        sts128(rb + (5 * (khd >> 1) + 2) * 1280, od ? 0u : p0, od ? 0u : p1, od ? p0 : 0u, od ? p1 : 0u);
        const uint32_t zz = (p2 & 0xffffu) << (16 * (khd & 1));
        sts128(rb + 10 * 1280, khd < 2 ? zz : 0u, khd < 2 ? 0u : zz, 0u, 0u);
      }
    }
    fence_async();
    bar_sync(1, 256);
    if (tid == 0) TS(7);
    {
      float oa[44]; zero<44>(oa);
      constexpr uint64_t db = mkdesc(SB0 + OFF_KVB, 128, 1280, 0);
      wg_fence();
      #pragma unroll
      for (int s = 0; s < 5; s++) wg_rs88_tb(oa, &qa[4 * s], desc2((uint32_t)db + ((s == 4 && (c & 1)) ? 0 : (s + (c & 1)) * 16), db >> 32), s != 0);
      wg_commit();
      wg_wait<0>();
      pin<44>(oa);
      if (tid == 0) TS(13);
      float rc[4], rd[2][4];
      #pragma unroll
      for (int e = 0; e < 4; e++) asm("rcp.approx.ftz.f32 %0, %1;" : "=f"(rc[e]) : "f"(oa[40 + e] + 1e-6f));
      #pragma unroll
      for (int h = 0; h < 4; h++) {
        rd[0][h] = __shfl_sync(0xffffffff, rc[h & 1], (lane & 28) | (h >> 1));
        rd[1][h] = __shfl_sync(0xffffffff, rc[2 + (h & 1)], (lane & 28) | (h >> 1));
      }
      #pragma unroll
      for (int j = 0; j < 10; j++) {
        #pragma unroll
        for (int h = 0; h < 2; h++) {
          float f;
          if (j == 2) f = tq < 2 ? rd[h][0] : rd[h][1];
          else if (j == 7) f = tq < 2 ? rd[h][2] : rd[h][3];
          else f = rd[h][(8 * j) / 20];
          qa[2 * j + h] = pack2(oa[4 * j + 2 * h] * f, oa[4 * j + 2 * h + 1] * f);
        }
      }
      const uint32_t m0 = (lane & 7) == ((2 * w4) & 7), m1 = (lane & 7) == 2 * w4 + 1;
      const uint32_t oa_ = sb + OFF_EXTRA + (lane >> 4) * 2048 + (warp * 16 + (lane & 15)) * 16;
      bar_sync(1, 256);
#define TAG(v, m) (((v) & ~(m)) | (epoch & (m)))
      #pragma unroll
      for (int s = 0; s < 5; s++) stsm4(oa_ + s * 4096, TAG(qa[4 * s], m0), TAG(qa[4 * s + 1], m1), TAG(qa[4 * s + 2], m0), TAG(qa[4 * s + 3], m1));
    }
    fence_async();
    mbar_arrive(BAR(BR_OSTG));
    if (tid == 0) TS(8);
    float oc[40]; zero<40>(oc);
    {
      constexpr uint64_t dw0 = mkdesc(SB0, OFF_WOR, 1024, 1), da0 = mkdesc(SB0, 2048, 128, 0);
      const uint32_t ck = sb + tid * 32 + ((lane >> 2) << 2), ck2 = ck + (wg ? 0 : 16384);
      uint32_t bad = 0;
      auto tile = [&](int i, uint32_t so) {
        const uint32_t al = (uint32_t)da0 + wg * 64 + (so >> 4), wl = (uint32_t)dw0 + i * 640 - (i >> 1) * (1278 << 16);
        wg_fence();
        #pragma unroll
        for (int s = 0; s < 5; s++) wg_ss80_tb(oc, desc2(al + s * 256, da0 >> 32), desc2(wl + s * 128, dw0 >> 32), (i | s) != 0);
        wg_commit();
        bad |= (lds32(ck + so) ^ epoch) | (lds32(ck + so + 8192) ^ epoch) | (lds32(ck2 + so) ^ epoch);
      };
      mbar_wait(BAR(BR_WO), 0);
      mbar_wait(BAR(BR_OFULL), 0);
      tile(0, SLOT(0));
      mbar_wait(BAR(BR_WO + 1), 0);
      #pragma unroll 1
      for (int i = 1; i < 8; i++) {
        if (i == 1) { wg_wait<0>(); if (lane == 0) mbar_arrive(BAR(BR_OEMPTY)); }
        mbar_wait(BAR(BR_OFULL) + 8 * i, 0);
        if (i == 1 && tid == 0) TS(9);
        tile(i, SLOT(i));
        wg_wait<1>();
        if (lane == 0 && i > 1) mbar_arrive(BAR(BR_OEMPTY - 1) + 8 * i);
      }
      #pragma unroll 1
      for (int n = 0; n < 56; n++) {
        const int i = n & 7;
        if (i == 0) {
          uint32_t any;
          asm volatile("{\n.reg .pred p;\nsetp.ne.u32 p, %1, 0;\nbarrier.red.or.pred p, 1, 256, p;\nselp.u32 %0, 1, 0, p;\n}" : "=r"(any) : "r"(bad & 1u) : "memory");
          if (!any) break;
          bad = 0;
          FIXCNT
        }
        wg_wait<0>();
        bar_sync(1, 256);
        if (tid == 0) { mbar_expect_tx(BAR(BR_RETRY), 20480); bulk_ld(sb + SLOT(2), &g_o[(r * 8 + CHUNK(i)) * 1280], 20480, BAR(BR_RETRY)); }
        mbar_wait(BAR(BR_RETRY), n & 1);
        tile(i, SLOT(2));
      }
      wg_wait<0>();
      pin<40>(oc);
    }
    if (tid == 0) TS(10);
    {
      const int row = w4 * 16 + (lane & 15);
      const uint32_t ob = sb + SLOT(3) + wg * 10240;
      #pragma unroll
      for (int j = 0; j < 8; j += 2)
        stsm4(ob + row * 128 + (((j + (lane >> 4)) ^ (row & 7)) << 4), pack2(oc[4 * j], oc[4 * j + 1]), pack2(oc[4 * j + 2], oc[4 * j + 3]),
              pack2(oc[4 * j + 4], oc[4 * j + 5]), pack2(oc[4 * j + 6], oc[4 * j + 7]));
      stsm4(ob + 8192 + row * 32 + (lane >> 4) * 16, pack2(oc[32], oc[33]), pack2(oc[34], oc[35]), pack2(oc[36], oc[37]), pack2(oc[38], oc[39]));
      fence_async();
      bar_sync(2 + wg, 128);
      if (w4 == 0 && elect_one()) {
        tma2d_st(&prm.m[M_O64], ob, 640 + c * 64, r * 128 + wg * 64);
        tma2d_st(&prm.m[M_O16], ob + 8192, 1152 + c * 16, r * 128 + wg * 64);
        bulk_commit(); bulk_wait0_read();
        if (wg == 0) { TS(11); DUMP(0, 20); }
      }
    }
    }
  } else {
    uint4 pv[3];
    const uint4* pp = reinterpret_cast<const uint4*>(prm.par[w4] + (c * 80 + r * 5) * 128);
    pv[0] = __ldg(pp + lane); pv[1] = __ldg(pp + 32 + lane); pv[2] = __ldg(pp + 64 + (lane & 15));
    const int kq = c * 80 + r * 5 + min(lane, 4);
    const unsigned short ldt = __ldg(reinterpret_cast<const unsigned short*>(prm.logdt) + kq), dsk0 = __ldg(reinterpret_cast<const unsigned short*>(prm.dskip) + kq);
    asm volatile("setmaxnreg.inc.sync.aligned.u32 152;");
    bar_sync(0, 512);
    if (EN_SSM) {
    const int g = lane >> 2, tq = lane & 3, t7 = tid & 127;
    {
      #pragma unroll 1
      for (int k = 0; k < 5; k++) {
        const uint32_t tz = sb + OFF_BLK + k * BLK + B_TBL + t7 * 16;
        if (t7 < 32 || t7 >= 96) sts128(tz, 0, 0, 0, 0);
        if (t7 < 124) sts128(tz + 2048, 0, 0, 0, 0);
        if (t7 < 16) sts128(sb + OFF_BLK + k * BLK - 256 + t7 * 16, 0, 0, 0, 0);
      }
      if (t7 < 5) sts64(sb + OFF_BLK + t7 * BLK + B_SP + 8, __float_as_uint(bf_round(expf(bf_lo(ldt)))), (uint32_t)dsk0 << 16);
      const uint32_t st = sb + OFF_BLK + (lane >> 4) * BLK + B_TBL + 512 + w4 * 256 + (lane & 15) * 16;
      #pragma unroll
      for (int i = 0; i < 3; i++) {
        if (i < 2 || lane < 16) sts128(st + 2 * i * BLK, pv[i].x, pv[i].y, pv[i].z, pv[i].w);
        if (w4 >= 2) {
          const uint32_t m2 = __vmaxu2(__vmaxu2(pv[i].x & 0x7fff7fffu, pv[i].y & 0x7fff7fffu), __vmaxu2(pv[i].z & 0x7fff7fffu, pv[i].w & 0x7fff7fffu));
          const uint32_t m = __reduce_max_sync(lane < 16 ? 0x0000ffffu : 0xffff0000u, max(m2 & 0xffffu, m2 >> 16));
          if ((lane & 15) == 0 && (i < 2 || lane == 0)) sts32(sb + OFF_BLK + (2 * i + (lane >> 4)) * BLK + B_SP + 8 + w4 * 4, m);
        }
      }
    }
    bar_sync(4, 128);
    if (t7 == 0) TS(40);
    {
      const uint32_t fa = sb + OFF_BLK + (w4 & 1) * BLK + (lane >> 3) * 256 + (lane & 7) * 16;
      const uint32_t ea = fa + (w4 >> 1) * 4096, ga = fa + 8192 + (w4 >> 1) * 3072;
      constexpr uint64_t dE = mkdesc(SB0 + OFF_BLK, 128, 1024, 0), dG = mkdesc(SB0 + OFF_BLK + 8192, 128, 1024, 0);
      #pragma unroll 1
      for (int k = 4; k >= 0; k--) {
        const uint32_t blk = sb + OFF_BLK + k * BLK;
        float fac, dsk;
        {
          const uint32_t st = blk + B_TBL + 512 + t7 * 2;
          uint32_t q[2], mm[2];
          const uint32_t p0 = lds16(st), p1 = lds16(st + 256), p2 = lds16(st + 512), p3 = lds16(st + 768);
          lds64(q, blk + B_SP + 8); lds64(mm, blk + B_SP + 16);
          const float dt = __uint_as_float(q[0]); dsk = __uint_as_float(q[1]);
          const uint32_t ex = min(max(max(mm[0], mm[1]) >> 7, 1u), 253u);
          const float sc = __uint_as_float((254u - ex) << 23);
          fac = 2.f * dt * __uint_as_float(ex << 23);
          const float lr = -bf_round(expf(bf_lo(p0))) * dt * 1.44269504089f;
          const float tn = bf_lo(p1) * dt * 0.15915494309f;
          float z1r, z1i, z2r, z2i, z4r, z4i, xr[8], xi[8], gr[8], gi[8], wr[9], wi[9];
          cexp_t(lr, -tn, z1r, z1i);
          cexp_t(lr * 8.f, tn * 8.f, xr[1], xi[1]);
          cexp_t(lr * 64.f, tn * 64.f, wr[0], wi[0]);
          xr[0] = 1.f; xi[0] = 0.f;
          cmul(xr[1], xi[1], xr[1], xi[1], xr[2], xi[2]); cmul(xr[2], xi[2], xr[1], xi[1], xr[3], xi[3]);
          cmul(xr[2], xi[2], xr[2], xi[2], xr[4], xi[4]);
          #pragma unroll
          for (int b = 1; b < 4; b++) cmul(xr[4], xi[4], xr[b], xi[b], xr[4 + b], xi[4 + b]);
          cmul(wr[0], wi[0], wr[0], wi[0], wr[1], wi[1]); cmul(wr[1], wi[1], wr[0], wi[0], wr[2], wi[2]);
          cmul(wr[1], wi[1], wr[1], wi[1], wr[3], wi[3]); cmul(wr[3], wi[3], wr[3], wi[3], wr[4], wi[4]);
          cmul(wr[4], wi[4], wr[3], wi[3], wr[5], wi[5]); cmul(wr[4], wi[4], wr[4], wi[4], wr[6], wi[6]);
          cmul(wr[6], wi[6], wr[4], wi[4], wr[7], wi[7]); cmul(wr[6], wi[6], wr[6], wi[6], wr[8], wi[8]);
          uint32_t R[4], I[4], PR[4], PI[4];
          #pragma unroll
          for (int b = 0; b < 4; b++) { R[b] = packh(xr[2 * b], xr[2 * b + 1]); I[b] = packh(xi[2 * b], xi[2 * b + 1]); }
          sts128(ea, R[0], R[1], R[2], R[3]); sts128(ea + 128, I[0], I[1], I[2], I[3]);
          #pragma unroll
          for (int i = 0; i < 3; i++) {
            const uint32_t z = packh(wr[i], wi[i]);
            #pragma unroll
            for (int b = 0; b < 4; b++) hcm2(R[b], I[b], z, PR[b], PI[b]);
            sts128(ea + (i + 1) * 1024, PR[0], PR[1], PR[2], PR[3]); sts128(ea + (i + 1) * 1024 + 128, PI[0], PI[1], PI[2], PI[3]);
          }
          gr[0] = bf_lo(p2) * sc; gi[0] = -bf_lo(p3) * sc;
          cmul(z1r, z1i, z1r, z1i, z2r, z2i); cmul(z2r, z2i, z2r, z2i, z4r, z4i);
          cmul(gr[0], gi[0], z1r, z1i, gr[1], gi[1]);
          cmul(gr[0], gi[0], z2r, z2i, gr[2], gi[2]); cmul(gr[1], gi[1], z2r, z2i, gr[3], gi[3]);
          #pragma unroll
          for (int b = 0; b < 4; b++) cmul(gr[b], gi[b], z4r, z4i, gr[4 + b], gi[4 + b]);
          sts128(ga, packh(gr[0], gr[1]), packh(gr[2], gr[3]), packh(gr[4], gr[5]), packh(gr[6], gr[7]));
          sts128(ga + 128, packh(gi[0], gi[1]), packh(gi[2], gi[3]), packh(gi[4], gi[5]), packh(gi[6], gi[7]));
          {
            const uint32_t z = packh(wr[3], -wi[3]), a4r = packh(gr[0], gr[4]), a4i = packh(gi[0], gi[4]);
            hcm2(packh(gr[0], gr[2]), packh(gi[0], gi[2]), z, PR[0], PI[0]);
            hcm2(packh(gr[4], gr[6]), packh(gi[4], gi[6]), z, PR[1], PI[1]);
            hcm2(a4r, a4i, packh(wr[4], -wi[4]), PR[2], PI[2]);
            hcm2(a4r, a4i, packh(wr[5], -wi[5]), PR[3], PI[3]);
            sts128(ga + 1024, PR[0], PR[1], PR[2], PR[3]); sts128(ga + 1024 + 128, PI[0], PI[1], PI[2], PI[3]);
            float hr, hi_;
            cmul(gr[0], gi[0], wr[3], -wi[3], hr, hi_);
            const uint32_t cr = packh(gr[0], hr), ci = packh(gi[0], hi_);
            #pragma unroll
            for (int i = 0; i < 3; i++) hcm2(cr, ci, packh(wr[6 + i], -wi[6 + i]), PR[i], PI[i]);
            sts128(ga + 2048, PR[0], PR[1], PR[2], 0u); sts128(ga + 2048 + 128, PI[0], PI[1], PI[2], 0u);
          }
        }
        fence_async();
        bar_sync(4, 128);
        if (t7 == 0 && k == 3) TS(50);
        float ka[24]; zero<24>(ka);
        wg_fence();
        #pragma unroll
        for (int s = 0; s < 8; s++) wg_ss48_tt_h(ka, dE + (s >> 2) * (BLK >> 4) + (s & 3) * 16, dG + (s >> 2) * (BLK >> 4) + (s & 3) * 16, s != 0);
        wg_commit();
        wg_wait<0>();
        pin<24>(ka);
        if (t7 == 0 && k == 3) TS(51);
        float kk[6];
        {
          const bool up = w4 >= 2;
          const uint32_t xa = sb + OFF_BLK + 2 * BLK + B_D + 7168 + t7 * 8;
          #pragma unroll
          for (int n = 0; n < 3; n++) {
            sts64f(xa + n * 1024, up ? ka[12 + 4 * n] : ka[4 * n + 2], up ? ka[13 + 4 * n] : ka[4 * n + 3]);
            kk[2 * n] = up ? ka[14 + 4 * n] : ka[4 * n]; kk[2 * n + 1] = up ? ka[15 + 4 * n] : ka[4 * n + 1];
          }
          bar_sync(4, 128);
          #pragma unroll
          for (int n = 0; n < 3; n++) {
            uint32_t o[2]; lds64(o, (xa ^ 512) + n * 1024);
            kk[2 * n] = (kk[2 * n] + __uint_as_float(o[0])) * fac; kk[2 * n + 1] = (kk[2 * n + 1] + __uint_as_float(o[1])) * fac;
          }
        }
        if (t7 == 0 && k == 3) TS(52);
        {
          const int j = (w4 & 1) * 16 + (w4 >> 1) * 8 + g;
          const uint32_t tb = blk + B_TBL;
          if (t7 == 0) kk[0] += dsk;
          const uint32_t pa_ = tb + (16 + 8 * j + 2 * tq) * 4;
          const uint32_t v = pack2(kk[1], kk[0]);
          sts32(pa_ + 4, v); sts16(pa_, v >> 16); sts16(pa_ + 10, v);
          const uint32_t u = pack2(kk[2], kk[3]), w = pack2(kk[4], kk[5]);
          if (tq < 2) {
            const uint32_t pb = tb + (16 + 256 + 8 * j + 4 * tq) * 4;
            sts16(pb, u); sts32(pb + 4, __byte_perm(u, 0, 0x1010)); sts32(pb + 8, __byte_perm(u, 0, 0x1032)); sts16(pb + 14, u >> 16);
            if (j | tq) { sts16(pb - 4, u); sts16(pb + 2, u); }
            const int i = 64 * tq + j;
            const uint32_t e0 = tb + (T_F3 + (((i - 1) & 1) ? 80 : 0) + ((i - 1) >> 1)) * 4, e1 = i ? e0 : tb + (T_F2 + 144 + 31) * 4;
            sts16(e1, w); sts16(e1 + 6, w); sts16(e0 + 64, w >> 16); sts16(e0 + 70, w >> 16);
            if (i == 0) { sts16(tb + (T_S + 3) * 4, w); sts32(tb + (T_S + 4) * 4, __byte_perm(w, 0, 0x1010)); sts16(tb + (T_S + 5) * 4 + 2, w); }
          } else {
            const int i = 32 * (tq - 2) + j;
            const uint32_t e1 = tb + (i ? T_F2 + ((2 * i - 1) & 3) * 48 + ((2 * i - 1) >> 2) : 16 + 511) * 4;
            const uint32_t e2 = tb + (T_F2 + (i & 1) * 96 + (i >> 1)) * 4;
            sts16(e1, u); sts16(e1 + 6, u); sts16(e2, u >> 16); sts16(e2 + 6, u >> 16);
            if (i == 0) {
              const uint32_t uu = __byte_perm(u, 0, 0x1010);
              sts32(tb + 528 * 4, uu); sts32(tb + 529 * 4, uu); sts32(tb + 530 * 4, uu); sts16(tb + 531 * 4 + 2, u);
              sts16(tb + (T_F3 + 80 + 63) * 4, w);
            }
          }
        }
        if (t7 == 0 && k == 3) TS(53);
      }
      bar_sync(4, 128);
      if (t7 == 0) { mbar_arrive(BAR(BR_KGEN)); TS(41); }
    }
    mbar_wait(BAR(BR_U), 0);
    if (EN_ATT) mbar_wait(BAR(BR_GEMM), 0);
    if (t7 == 0) TS(42);
    #pragma unroll 1
    for (int pass = 0; pass < 2; pass++) {
      const int k = pass ? w4 : 4;
      const uint32_t blk = sb + OFF_BLK + k * BLK, tb = blk + B_TBL + (uint32_t)((g - 2 * tq) * 4);
      if (k < 2) mbar_wait(BAR(BR_U2), 0);
      float acc[16][4];
      zero<64>(&acc[0][0]);
      const int kl = 16 * (lane >> 4) + 2 * (lane & 7) + ((lane >> 3) & 1);
      {
        auto ubase = [&](int sh) { const int q = kl - 2 * sh; return blk + (uint32_t)((q * 16) ^ ((q * 2) & 0x70)); };
#define LDQ(A, sh) _Pragma("unroll") for (int m = 0; m < 4; m++) load_quad(A[m], tb + (16 + 16 * (sh) + 128 * m) * 4);
#define LDB(B, ub, h) _Pragma("unroll") for (int p = 0; p < 4; p++) ldsm4(B[p], ((ub) ^ ((p & 1) * 64)) + (4 * (h) + p) * 512);
#define MLO(A, B) _Pragma("unroll") for (int m = 0; m < 4; m++) _Pragma("unroll") for (int cc = 0; cc < 8; cc++) mma16816(acc[cc + m], A[m], &B[cc >> 1][(cc & 1) * 2]);
#define MHI(A, B) _Pragma("unroll") for (int m = 0; m < 4; m++) _Pragma("unroll") for (int cc = 0; cc < 8 - m; cc++) mma16816(acc[8 + cc + m], A[m], &B[cc >> 1][(cc & 1) * 2]);
        int p_ = pass ? 0 : w4;
        const int pe = pass ? 4 : w4 + 1;
        uint32_t A[4][4], A2[4][4], Bl[4][4], Bh[4][4];
        uint32_t ub = ubase(p_ + 4);
        LDQ(A, p_ + 4) LDB(Bl, ub, 0)
        #pragma unroll 1
        for (; p_ < pe; p_++) {
          LDB(Bh, ub, 1)
          MLO(A, Bl)
          ub = ubase(p_);
          LDQ(A2, p_) LDB(Bl, ub, 0)
          MHI(A, Bh)
          LDB(Bh, ub, 1)
          load_quad(A[0], tb + (16 + 512 + 16 * (p_ & 1)) * 4); load_quad(A[1], tb + (T_S + 16 * (p_ & 1)) * 4);
          MLO(A2, Bl)
          if (p_ < 2) {
            #pragma unroll
            for (int cc = 0; cc < 8; cc++) mma16816(acc[cc + 4], A[0], &Bl[cc >> 1][(cc & 1) * 2]);
            #pragma unroll
            for (int cc = 0; cc < 4; cc++) mma16816(acc[cc + 12], A[0], &Bh[cc >> 1][(cc & 1) * 2]);
            #pragma unroll
            for (int cc = 0; cc < 8; cc++) mma16816(acc[cc + 8], A[1], &Bl[cc >> 1][(cc & 1) * 2]);
          }
          const int pn = ((p_ + 1) & 3) + 4;
          ub = ubase(pn);
          LDQ(A, pn) LDB(Bl, ub, 0)
          MHI(A2, Bh)
        }
      }
      if (t7 == 0) TS(57 + 3 * pass);
      mbar_wait(BAR(BR_DRDY) + 8 * k, 0);
      {
        const int ih = (lane >> 3) & 1;
        const uint32_t dl = blk + B_D + (uint32_t)(((lane >> 4) * 8 + (lane & 7)) * 16);
        const uint32_t d0_ = dl + ih * 1552, d8_ = dl + (ih ? 0 : 1536), d3_ = dl + B_D7 + ih * 1024;
        auto cls2 = [&](uint32_t da, uint32_t ta) {
          uint32_t B[6][2], A[6][4];
          #pragma unroll
          for (int e = 0; e < 6; e++) { B[e][0] = lds32v(ta + (e + 4) * 32); B[e][1] = lds32v(ta + (e + 3) * 32); }
          #pragma unroll
          for (int kk = 0; kk < 6; kk++) ldsm4t(A[kk], da + kk * 256);
          #pragma unroll
          for (int e = 0; e < 6; e++)
            #pragma unroll
            for (int kk = 0; kk < 6; kk++) if (2 * kk + e + 4 < 16) mma16816(acc[2 * kk + e + 4], A[kk], B[e]);
        };
        auto cls3 = [&](uint32_t da, uint32_t ta) {
          uint32_t B[8][2], A[4][4];
          #pragma unroll
          for (int e = 0; e < 8; e++) { B[e][0] = lds32v(ta + (e + 8) * 32); B[e][1] = lds32v(ta + (e + 7) * 32); }
          #pragma unroll
          for (int kk = 0; kk < 4; kk++) ldsm4t(A[kk], da + kk * 256);
          #pragma unroll
          for (int kk = 0; kk < 4; kk++)
            #pragma unroll
            for (int e = 0; e < 8; e++) if (2 * kk + e + 8 < 16) mma16816(acc[2 * kk + e + 8], A[kk], B[e]);
        };
        #pragma unroll 1
        for (int a = pass ? 0 : w4; a < (pass ? 4 : w4 + 1); a++) cls2(((a & 2) ? d8_ : d0_) + (a & 1) * B_D5, tb + (T_F2 + 48 * a - 32) * 4);
        #pragma unroll 1
        for (int b = pass ? 0 : (w4 & 1); b < (pass ? 2 : w4 - 1); b++) cls3(d3_ + b * 2048, tb + (T_F3 + 80 * b - 64) * 4);
      }
      if (t7 == 0) TS(58 + 3 * pass);
      const uint32_t ya = blk + (uint32_t)((kl * 16) ^ ((kl * 2) & 0x70));
#define STY(p) stsm4t((ya ^ (((p) & 1) * 64)) + (p) * 512, pack2(acc[2 * (p)][0], acc[2 * (p)][1]), pack2(acc[2 * (p)][2], acc[2 * (p)][3]), \
                      pack2(acc[2 * (p) + 1][0], acc[2 * (p) + 1][1]), pack2(acc[2 * (p) + 1][2], acc[2 * (p) + 1][3]))
      if (pass == 0) {
        const uint32_t xw = blk + 4096 + w4 * 4096 + lane * 16, xr = blk + 4096 + w4 * 1024 + lane * 16;
        #pragma unroll
        for (int h = 0; h < 2; h++) {
          bar_sync(4, 128);
          #pragma unroll
          for (int i = 0; i < 8; i++)
            sts128(xw + i * 512, __float_as_uint(acc[8 * h + i][0]), __float_as_uint(acc[8 * h + i][1]), __float_as_uint(acc[8 * h + i][2]), __float_as_uint(acc[8 * h + i][3]));
          bar_sync(4, 128);
          float y[8];
          #pragma unroll
          for (int i = 0; i < 8; i++) {
            uint32_t o[4]; lds128(o, xr + (i >> 1) * 4096 + (i & 1) * 512);
            #pragma unroll
            for (int e = 0; e < 4; e++) y[4 * (i & 1) + e] = i < 2 ? __uint_as_float(o[e]) : y[4 * (i & 1) + e] + __uint_as_float(o[e]);
          }
          stsm4t((ya ^ ((w4 & 1) * 64)) + (4 * h + w4) * 512, pack2(y[0], y[1]), pack2(y[2], y[3]), pack2(y[4], y[5]), pack2(y[6], y[7]));
        }
      } else {
        __syncwarp();
        #pragma unroll
        for (int p = 0; p < 8; p++) STY(p);
      }
      if (t7 == 0 && !pass) TS(55);
      fence_async();
      mbar_arrive(BAR(BR_Y4) + 8 * pass);
      if (t7 == 0) TS(59 + 3 * pass);
    }
    if (t7 == 0) DUMP(40, 64);
    }
  }
}

typedef CUresult (*EncFn)(CUtensorMap*, CUtensorMapDataType, cuuint32_t, void*, const cuuint64_t*, const cuuint64_t*, const cuuint32_t*,
                          const cuuint32_t*, CUtensorMapInterleave, CUtensorMapSwizzle, CUtensorMapL2promotion, CUtensorMapFloatOOBfill);
static void mkmap(EncFn enc, CUtensorMap* m, const void* base, int rank, const cuuint64_t* dims, const cuuint64_t* strides, const cuuint32_t* box, CUtensorMapSwizzle swz) {
  cuuint32_t es[5] = {1, 1, 1, 1, 1};
  enc(m, CU_TENSOR_MAP_DATA_TYPE_BFLOAT16, rank, const_cast<void*>(base), dims, strides, box, es, CU_TENSOR_MAP_INTERLEAVE_NONE, swz,
      CU_TENSOR_MAP_L2_PROMOTION_L2_128B, CU_TENSOR_MAP_FLOAT_OOB_FILL_NONE);
}

extern "C" void kernel_launch(void* const* d_in, const int* in_sizes, int n_in, void* d_out, int out_size) {
  void* fn = nullptr; cudaDriverEntryPointQueryResult qr;
  cudaGetDriverEntryPoint("cuTensorMapEncodeTiled", &fn, cudaEnableDefault, &qr);
  EncFn enc = (EncFn)fn;
  void* uy = nullptr; cudaGetSymbolAddress(&uy, g_uy);
  const cuuint64_t dx[2] = {640, 2048}, sx[1] = {1280};
  const cuuint32_t bx[2] = {64, 128}, bu[2] = {80, 128};
  const cuuint64_t dw[3] = {640, 640, 3}, sw[2] = {3840, 1280};
  const cuuint32_t br[3] = {16, 32, 3};
  const cuuint64_t dwa[4] = {64, 640, 10, 3}, swa[3] = {3840, 128, 1280}, dwb[4] = {32, 640, 20, 3}, swb[3] = {3840, 64, 1280};
  const cuuint32_t bwa[4] = {64, 32, 1, 3}, bwb[4] = {32, 32, 2, 3};
  const cuuint64_t dwo[2] = {640, 640};
  const cuuint32_t bwo[2] = {64, 80}, bo64[2] = {64, 64}, bo16[2] = {16, 64};
  const cuuint64_t dsa[2] = {2048, 1280}, ssa[1] = {4096};
  const cuuint32_t bsa[2] = {64, 80};
  const cuuint64_t dsb[2] = {64, 40960}, ssb[1] = {128};
  const cuuint32_t bsb[2] = {64, 32};
  const cuuint64_t dout[2] = {1280, 2048}, sout[1] = {2560};
  Params prm;
  mkmap(enc, &prm.m[M_X], d_in[7], 2, dx, sx, bx, CU_TENSOR_MAP_SWIZZLE_128B);
  mkmap(enc, &prm.m[M_W128], d_in[8], 4, dwa, swa, bwa, CU_TENSOR_MAP_SWIZZLE_128B);
  mkmap(enc, &prm.m[M_W64], d_in[8], 4, dwb, swb, bwb, CU_TENSOR_MAP_SWIZZLE_64B);
  mkmap(enc, &prm.m[M_WR], d_in[8], 3, dw, sw, br, CU_TENSOR_MAP_SWIZZLE_32B);
  mkmap(enc, &prm.m[M_WO], d_in[9], 2, dwo, sx, bwo, CU_TENSOR_MAP_SWIZZLE_128B);
  mkmap(enc, &prm.m[M_O64], d_out, 2, dout, sout, bo64, CU_TENSOR_MAP_SWIZZLE_128B);
  mkmap(enc, &prm.m[M_O16], d_out, 2, dout, sout, bo16, CU_TENSOR_MAP_SWIZZLE_NONE);
  mkmap(enc, &prm.m[M_SA], uy, 2, dsa, ssa, bsa, CU_TENSOR_MAP_SWIZZLE_128B);
  mkmap(enc, &prm.m[M_SB], uy, 2, dsb, ssb, bsb, CU_TENSOR_MAP_SWIZZLE_128B);
  mkmap(enc, &prm.m[M_OUT], d_out, 2, dout, sout, bu, CU_TENSOR_MAP_SWIZZLE_NONE);
  prm.u = (const __nv_bfloat16*)d_in[0]; prm.wo = (const __nv_bfloat16*)d_in[9];
  for (int i = 0; i < 4; i++) prm.par[i] = (const __nv_bfloat16*)d_in[1 + i];
  prm.logdt = (const __nv_bfloat16*)d_in[5]; prm.dskip = (const __nv_bfloat16*)d_in[6];
  cudaFuncSetAttribute(fused_kernel, cudaFuncAttributeMaxDynamicSharedMemorySize, SMEM_BYTES);
  cudaLaunchConfig_t cfg = {};
  cfg.gridDim = dim3(128); cfg.blockDim = dim3(512); cfg.dynamicSmemBytes = SMEM_BYTES; cfg.stream = cudaStreamPerThread;
  cudaLaunchAttribute at[1];
  at[0].id = cudaLaunchAttributeClusterDimension; at[0].val.clusterDim.x = 2; at[0].val.clusterDim.y = 1; at[0].val.clusterDim.z = 1;
  cfg.attrs = at; cfg.numAttrs = 1;
  cudaLaunchKernelEx(&cfg, fused_kernel, prm);
}
```

```cpp
#include <cuda_runtime.h>
#include <cuda_bf16.h>
#include <cuda_fp16.h>
#include <cuda.h>
#include <stdint.h>

#define U_AFTER 4
#define EN_ATT 1
#define EN_SSM 1

__device__ __align__(1024) __nv_bfloat16 g_uy[2 * 640 * 2048];
__device__ __align__(128) uint4 g_kvp[8 * 16 * 240];
__device__ __align__(128) uint4 g_o[128 * 1280];
__device__ __align__(128) unsigned g_flag[4 * 128 * 32];
__device__ unsigned g_epoch[128];
#define TS(i) do {} while (0)
#define DUMP(lo, hi) do {} while (0)
#define FIXCNT

constexpr uint32_t SB0 = 1024;
constexpr uint32_t W_SLOT = 15360, OFF_X = 76800;
constexpr uint32_t OFF_WOR = 81920, OFF_KVP = 10240, OFF_KVS = 71680, OFF_PK = 10240, OFF_V = 30720, OFF_EXTRA = 102400, OFF_KVB = OFF_EXTRA;
constexpr uint32_t OFF_BAR = 125952, OFF_BLK = 128000, BLK = 20480;
constexpr uint32_t B_D = 4096, B_D5 = 3088, B_D7 = 6176, B_D9 = 8224, B_TBL = 14400, B_SP = 18432;
constexpr int T_S = 576, T_F2 = 624, T_F3 = 816;
constexpr uint32_t SMEM_BYTES = OFF_BLK + 5 * BLK;
enum { BR_FULL = 0, BR_WO = 5, BR_PUB = 7, BR_KVP = 8, BR_U = 9, BR_SUM = 10, BR_GEMM = 11, BR_KGEN = 12, BR_YIN = 13, BR_EPOCH = 14,
       BR_FREE = 15, BR_RETRY = 17, BR_OFULL = 18, BR_EMPTY = 26, BR_OEMPTY = 31, BR_Y = 38, BR_OSTG = 40, BR_DRDY = 41, BR_COUNT = 42 };
constexpr uint32_t OFF_EPOCH = OFF_BAR + 8 * BR_COUNT;
enum { M_X, M_W128, M_W64, M_WR, M_WO, M_O64, M_O16, M_SA, M_SB, M_OUT, M_COUNT };

__device__ __forceinline__ long long clk64() { long long t; asm volatile("mov.u64 %0, %%clock64;" : "=l"(t) :: "memory"); return t; }
__device__ __forceinline__ uint32_t smem_u32(const void* p) { return (uint32_t)__cvta_generic_to_shared(p); }
__host__ __device__ constexpr uint64_t mkdesc(uint32_t addr, uint32_t lbo, uint32_t sbo, uint32_t swz) {
  return (uint64_t)((addr & 0x3FFFF) >> 4) | ((uint64_t)(lbo >> 4) << 16) | ((uint64_t)(sbo >> 4) << 32) | ((uint64_t)swz << 62);
}
__device__ __forceinline__ uint64_t desc2(uint32_t lo, uint32_t hi) { uint64_t d; asm("mov.b64 %0, {%1, %2};" : "=l"(d) : "r"(lo), "r"(hi)); return d; }
__device__ __forceinline__ void mbar_init(uint32_t bar, uint32_t cnt) { asm volatile("mbarrier.init.shared::cta.b64 [%0], %1;" :: "r"(bar), "r"(cnt) : "memory"); }
__device__ __forceinline__ void mbar_expect_tx(uint32_t bar, uint32_t bytes) { asm volatile("mbarrier.arrive.expect_tx.shared::cta.b64 _, [%0], %1;" :: "r"(bar), "r"(bytes) : "memory"); }
__device__ __forceinline__ void mbar_arrive(uint32_t bar) { asm volatile("mbarrier.arrive.shared::cta.b64 _, [%0];" :: "r"(bar) : "memory"); }
__device__ __forceinline__ void mbar_wait(uint32_t bar, uint32_t parity) {
  asm volatile("{\n.reg .pred p;\n.reg .u32 c;\nmov.u32 c, 0;\n"
    "WL:\nmbarrier.try_wait.parity.shared::cta.b64 p, [%0], %1;\n@p bra WD;\n"
    "add.u32 c, c, 1;\nsetp.lt.u32 p, c, 200000;\n@p bra WL;\nWD:\n}" :: "r"(bar), "r"(parity) : "memory");
}
__device__ __forceinline__ void poll_all(const unsigned* p, unsigned val) {
  asm volatile("{\n.reg .pred p;\n.reg .u32 c, v;\nmov.u32 c, 0;\n"
    "PL:\nld.relaxed.gpu.global.u32 v, [%0];\nsetp.eq.u32 p, v, %1;\nvote.sync.all.pred p, p, 0xffffffff;\n@p bra PD;\n"
    "add.u32 c, c, 1;\nsetp.lt.u32 p, c, 100000;\n@p bra PL;\nPD:\n}" :: "l"(p), "r"(val) : "memory");
}
__device__ __forceinline__ void poll_all_acq(const unsigned* p, unsigned val) {
  asm volatile("{\n.reg .pred p;\n.reg .u32 c, v;\nmov.u32 c, 0;\n"
    "PL:\nld.acquire.gpu.global.u32 v, [%0];\nsetp.eq.u32 p, v, %1;\nvote.sync.all.pred p, p, 0xffffffff;\n@p bra PD;\n"
    "add.u32 c, c, 1;\nsetp.lt.u32 p, c, 100000;\n@p bra PL;\nPD:\n}" :: "l"(p), "r"(val) : "memory");
}
__device__ __forceinline__ unsigned poll_bit(const unsigned* p, unsigned val, unsigned mask) {
  unsigned bal;
  asm volatile("{\n.reg .pred p;\n.reg .u32 c, v;\nmov.u32 c, 0;\n"
    "PL:\nld.relaxed.gpu.global.u32 v, [%1];\nsetp.eq.u32 p, v, %2;\nvote.sync.ballot.b32 %0, p, 0xffffffff;\n"
    "and.b32 v, %0, %3;\nsetp.ne.u32 p, v, 0;\n@p bra PD;\n"
    "add.u32 c, c, 1;\nsetp.lt.u32 p, c, 100000;\n@p bra PL;\nPD:\n}" : "=&r"(bal) : "l"(p), "r"(val), "r"(mask) : "memory");
  return bal;
}
__device__ __forceinline__ void fix128_w0(uint32_t* v, const void* p, uint32_t tag, uint32_t mask) {
  asm volatile("{\n.reg .pred p;\n.reg .u32 c, x;\n.reg .b128 t;\n.reg .b64 lo, hi;\nmov.u32 c, 0;\n"
    "FL:\nxor.b32 x, %0, %5;\nand.b32 x, x, %6;\nsetp.eq.u32 p, x, 0;\n@p bra FD;\n"
    "ld.relaxed.gpu.global.b128 t, [%4];\nmov.b128 {lo, hi}, t;\nmov.b64 {%0, %1}, lo;\nmov.b64 {%2, %3}, hi;\n"
    "add.u32 c, c, 1;\nsetp.lt.u32 p, c, 100000;\n@p bra FL;\nFD:\n}"
    : "+r"(v[0]), "+r"(v[1]), "+r"(v[2]), "+r"(v[3]) : "l"(p), "r"(tag), "r"(mask) : "memory");
}
__device__ __forceinline__ void fix128_w3(uint32_t* v, const void* p, uint32_t tag, uint32_t mask) {
  asm volatile("{\n.reg .pred p;\n.reg .u32 c, x;\n.reg .b128 t;\n.reg .b64 lo, hi;\nmov.u32 c, 0;\n"
    "FL:\nxor.b32 x, %3, %5;\nand.b32 x, x, %6;\nsetp.eq.u32 p, x, 0;\n@p bra FD;\n"
    "ld.relaxed.gpu.global.b128 t, [%4];\nmov.b128 {lo, hi}, t;\nmov.b64 {%0, %1}, lo;\nmov.b64 {%2, %3}, hi;\n"
    "add.u32 c, c, 1;\nsetp.lt.u32 p, c, 100000;\n@p bra FL;\nFD:\n}"
    : "+r"(v[0]), "+r"(v[1]), "+r"(v[2]), "+r"(v[3]) : "l"(p), "r"(tag), "r"(mask) : "memory");
}
__device__ __forceinline__ void fence_acq() { asm volatile("fence.acq_rel.gpu;" ::: "memory"); }
__device__ __forceinline__ bool elect_one() {
  uint32_t p; asm volatile("{\n.reg .pred P;\nelect.sync _|P, 0xffffffff;\nselp.u32 %0, 1, 0, P;\n}" : "=r"(p)); return p;
}
__device__ __forceinline__ void bar_sync(int id, int n) { asm volatile("bar.sync %0, %1;" :: "r"(id), "r"(n) : "memory"); }
__device__ __forceinline__ void fence_async() { asm volatile("fence.proxy.async.shared::cta;" ::: "memory"); }
__device__ __forceinline__ void fence_async_g() { asm volatile("fence.proxy.async.global;" ::: "memory"); }
__device__ __forceinline__ void tma2d(uint32_t dst, const CUtensorMap* m, uint32_t bar, int c0, int c1) {
  asm volatile("cp.async.bulk.tensor.2d.shared::cluster.global.mbarrier::complete_tx::bytes [%0], [%1, {%3, %4}], [%2];"
    :: "r"(dst), "l"(m), "r"(bar), "r"(c0), "r"(c1) : "memory");
}
__device__ __forceinline__ void tma3d(uint32_t dst, const CUtensorMap* m, uint32_t bar, int c0, int c1, int c2) {
  asm volatile("cp.async.bulk.tensor.3d.shared::cluster.global.mbarrier::complete_tx::bytes [%0], [%1, {%3, %4, %5}], [%2];"
    :: "r"(dst), "l"(m), "r"(bar), "r"(c0), "r"(c1), "r"(c2) : "memory");
}
__device__ __forceinline__ void tma4d(uint32_t dst, const CUtensorMap* m, uint32_t bar, int c0, int c1, int c2, int c3) {
  asm volatile("cp.async.bulk.tensor.4d.shared::cluster.global.mbarrier::complete_tx::bytes [%0], [%1, {%3, %4, %5, %6}], [%2];"
    :: "r"(dst), "l"(m), "r"(bar), "r"(c0), "r"(c1), "r"(c2), "r"(c3) : "memory");
}
__device__ __forceinline__ void tma2d_st(const CUtensorMap* m, uint32_t src, int c0, int c1) {
  asm volatile("cp.async.bulk.tensor.2d.global.shared::cta.bulk_group [%0, {%2, %3}], [%1];"
    :: "l"(m), "r"(src), "r"(c0), "r"(c1) : "memory");
}
__device__ __forceinline__ void bulk_ld(uint32_t dst, const void* src, uint32_t bytes, uint32_t bar) {
  asm volatile("cp.async.bulk.shared::cluster.global.mbarrier::complete_tx::bytes [%0], [%1], %2, [%3];"
    :: "r"(dst), "l"(src), "r"(bytes), "r"(bar) : "memory");
}
__device__ __forceinline__ void bulk_st(void* dst, uint32_t src, uint32_t bytes) {
  asm volatile("cp.async.bulk.global.shared::cta.bulk_group [%0], [%1], %2;" :: "l"(dst), "r"(src), "r"(bytes) : "memory");
}
__device__ __forceinline__ void bulk_commit() { asm volatile("cp.async.bulk.commit_group;" ::: "memory"); }
__device__ __forceinline__ void bulk_wait0() { asm volatile("cp.async.bulk.wait_group 0;" ::: "memory"); }
__device__ __forceinline__ void bulk_wait0_read() { asm volatile("cp.async.bulk.wait_group.read 0;" ::: "memory"); }
__device__ __forceinline__ unsigned ld_rlx(const unsigned* p) { unsigned v; asm volatile("ld.relaxed.gpu.global.u32 %0, [%1];" : "=r"(v) : "l"(p) : "memory"); return v; }
__device__ __forceinline__ unsigned ld_acq(const unsigned* p) { unsigned v; asm volatile("ld.acquire.gpu.global.u32 %0, [%1];" : "=r"(v) : "l"(p) : "memory"); return v; }
__device__ __forceinline__ void st_rlx(unsigned* p, unsigned v) { asm volatile("st.relaxed.gpu.global.u32 [%0], %1;" :: "l"(p), "r"(v) : "memory"); }
__device__ __forceinline__ void st_rel(unsigned* p, unsigned v) { asm volatile("st.release.gpu.global.u32 [%0], %1;" :: "l"(p), "r"(v) : "memory"); }
__device__ __forceinline__ void ld128_rlx(uint32_t* v, const void* p) {
  asm volatile("{\n.reg .b128 t;\n.reg .b64 lo, hi;\nld.relaxed.gpu.global.b128 t, [%4];\nmov.b128 {lo, hi}, t;\n"
    "mov.b64 {%0, %1}, lo;\nmov.b64 {%2, %3}, hi;\n}" : "=r"(v[0]), "=r"(v[1]), "=r"(v[2]), "=r"(v[3]) : "l"(p) : "memory");
}
__device__ __forceinline__ void st128_rlx(void* p, const uint32_t* v) {
  asm volatile("{\n.reg .b128 t;\n.reg .b64 lo, hi;\nmov.b64 lo, {%1, %2};\nmov.b64 hi, {%3, %4};\nmov.b128 t, {lo, hi};\n"
    "st.relaxed.gpu.global.b128 [%0], t;\n}" :: "l"(p), "r"(v[0]), "r"(v[1]), "r"(v[2]), "r"(v[3]) : "memory");
}
__device__ __forceinline__ uint32_t lds32(uint32_t a) { uint32_t v; asm volatile("ld.shared.u32 %0, [%1];" : "=r"(v) : "r"(a) : "memory"); return v; }
__device__ __forceinline__ uint32_t lds32v(uint32_t a) { uint32_t v; asm volatile("ld.volatile.shared.u32 %0, [%1];" : "=r"(v) : "r"(a) : "memory"); return v; }
__device__ __forceinline__ uint32_t cpa(uint32_t a, uint32_t one) { uint32_t v; asm volatile("mul.lo.u32 %0, %1, %2;" : "=r"(v) : "r"(a), "r"(one)); return v; }
__device__ __forceinline__ uint32_t cpb(uint32_t a, uint32_t zero) { uint32_t v; asm volatile("or.b32 %0, %1, %2;" : "=r"(v) : "r"(a), "r"(zero)); return v; }
__device__ __forceinline__ uint32_t lds16(uint32_t a) { uint16_t v; asm volatile("ld.shared.u16 %0, [%1];" : "=h"(v) : "r"(a) : "memory"); return v; }
__device__ __forceinline__ float ldsf(uint32_t a) { float v; asm volatile("ld.shared.f32 %0, [%1];" : "=f"(v) : "r"(a) : "memory"); return v; }
__device__ __forceinline__ void lds128(uint32_t* v, uint32_t a) { asm volatile("ld.shared.v4.u32 {%0,%1,%2,%3}, [%4];" : "=r"(v[0]), "=r"(v[1]), "=r"(v[2]), "=r"(v[3]) : "r"(a) : "memory"); }
__device__ __forceinline__ void sts32(uint32_t a, uint32_t v) { asm volatile("st.shared.u32 [%0], %1;" :: "r"(a), "r"(v) : "memory"); }
__device__ __forceinline__ void sts16(uint32_t a, uint32_t v) { asm volatile("st.shared.u16 [%0], %1;" :: "r"(a), "h"((uint16_t)v) : "memory"); }
__device__ __forceinline__ void sts64f(uint32_t a, float x, float y) { asm volatile("st.shared.v2.f32 [%0], {%1,%2};" :: "r"(a), "f"(x), "f"(y) : "memory"); }
__device__ __forceinline__ void sts128(uint32_t a, uint32_t x, uint32_t y, uint32_t z, uint32_t w) { asm volatile("st.shared.v4.u32 [%0], {%1,%2,%3,%4};" :: "r"(a), "r"(x), "r"(y), "r"(z), "r"(w) : "memory"); }
__device__ __forceinline__ void stsm4(uint32_t a, uint32_t r0, uint32_t r1, uint32_t r2, uint32_t r3) {
  asm volatile("stmatrix.sync.aligned.m8n8.x4.shared.b16 [%0], {%1,%2,%3,%4};" :: "r"(a), "r"(r0), "r"(r1), "r"(r2), "r"(r3) : "memory");
}
__device__ __forceinline__ void stsm4t(uint32_t a, uint32_t r0, uint32_t r1, uint32_t r2, uint32_t r3) {
  asm volatile("stmatrix.sync.aligned.m8n8.x4.trans.shared.b16 [%0], {%1,%2,%3,%4};" :: "r"(a), "r"(r0), "r"(r1), "r"(r2), "r"(r3) : "memory");
}
__device__ __forceinline__ void ldsm4t(uint32_t* r, uint32_t a) {
  asm volatile("ldmatrix.sync.aligned.m8n8.x4.trans.shared.b16 {%0,%1,%2,%3}, [%4];" : "=r"(r[0]), "=r"(r[1]), "=r"(r[2]), "=r"(r[3]) : "r"(a) : "memory");
}
__device__ __forceinline__ void ldsm4(uint32_t* r, uint32_t a) {
  asm volatile("ldmatrix.sync.aligned.m8n8.x4.shared.b16 {%0,%1,%2,%3}, [%4];" : "=r"(r[0]), "=r"(r[1]), "=r"(r[2]), "=r"(r[3]) : "r"(a) : "memory");
}
__device__ __forceinline__ void mma16816(float* d, const uint32_t* a, const uint32_t* b) {
  asm volatile("mma.sync.aligned.m16n8k16.row.col.f32.bf16.bf16.f32 {%0,%1,%2,%3}, {%4,%5,%6,%7}, {%8,%9}, {%0,%1,%2,%3};"
    : "+f"(d[0]), "+f"(d[1]), "+f"(d[2]), "+f"(d[3]) : "r"(a[0]), "r"(a[1]), "r"(a[2]), "r"(a[3]), "r"(b[0]), "r"(b[1]));
}
__device__ __forceinline__ uint32_t pack2(float lo, float hi) { uint32_t r; asm("cvt.rn.bf16x2.f32 %0, %1, %2;" : "=r"(r) : "f"(hi), "f"(lo)); return r; }
__device__ __forceinline__ uint32_t packh(float lo, float hi) { uint32_t r; asm("cvt.rn.f16x2.f32 %0, %1, %2;" : "=r"(r) : "f"(hi), "f"(lo)); return r; }
__device__ __forceinline__ uint32_t hcmul(uint32_t x, uint32_t zp, uint32_t zq) {
  const __half2 xx = *reinterpret_cast<__half2*>(&x);
  const __half2 r = __hfma2(__high2half2(xx), *reinterpret_cast<__half2*>(&zq), __hmul2(__low2half2(xx), *reinterpret_cast<__half2*>(&zp)));
  return *reinterpret_cast<const uint32_t*>(&r);
}
__device__ __forceinline__ void hcm2(uint32_t xr, uint32_t xi, uint32_t z, uint32_t& pr, uint32_t& pi) {
  const __half2 a = *reinterpret_cast<__half2*>(&xr), b = *reinterpret_cast<__half2*>(&xi), zz = *reinterpret_cast<__half2*>(&z);
  const __half2 re = __hfma2(__hneg2(b), __high2half2(zz), __hmul2(a, __low2half2(zz)));
  const __half2 im = __hfma2(a, __high2half2(zz), __hmul2(b, __low2half2(zz)));
  pr = *reinterpret_cast<const uint32_t*>(&re); pi = *reinterpret_cast<const uint32_t*>(&im);
}
__device__ __forceinline__ void sts64(uint32_t a, uint32_t x, uint32_t y) { asm volatile("st.shared.v2.u32 [%0], {%1,%2};" :: "r"(a), "r"(x), "r"(y) : "memory"); }
__device__ __forceinline__ void lds64(uint32_t* v, uint32_t a) { asm volatile("ld.shared.v2.u32 {%0,%1}, [%2];" : "=r"(v[0]), "=r"(v[1]) : "r"(a) : "memory"); }
__device__ __forceinline__ float bf_lo(uint32_t v) { return __uint_as_float(v << 16); }
__device__ __forceinline__ float bf_hi(uint32_t v) { return __uint_as_float(v & 0xffff0000u); }
__device__ __forceinline__ float bf_round(float x) { return bf_lo(pack2(x, 0.f)); }
__device__ __forceinline__ float ex2(float x) { float r; asm("ex2.approx.ftz.f32 %0, %1;" : "=f"(r) : "f"(x)); return r; }
__device__ __forceinline__ float phi(float t, float l2e = 1.44269504089f) { float e = ex2(t * l2e); return (t > 0.f ? t + 1.f : e) + 1e-6f; }
__device__ __forceinline__ void wg_fence() { asm volatile("wgmma.fence.sync.aligned;" ::: "memory"); }
__device__ __forceinline__ void wg_commit() { asm volatile("wgmma.commit_group.sync.aligned;" ::: "memory"); }
template <int N> __device__ __forceinline__ void wg_wait() { asm volatile("wgmma.wait_group.sync.aligned %0;" :: "n"(N) : "memory"); }
template <int N> __device__ __forceinline__ void pin(float* a) {
  #pragma unroll
  for (int i = 0; i < N; i++) asm volatile("" : "+f"(a[i]) :: "memory");
}
__device__ __forceinline__ int opaque(int v) { asm volatile("" : "+r"(v)); return v; }
template <int N> __device__ __forceinline__ void zero(float* a) {
  #pragma unroll
  for (int i = 0; i < N; i++) asm volatile("mov.b32 %0, 0;" : "=f"(a[i]));
}
template <int N> __device__ __forceinline__ void pinu(uint32_t* a) {
  #pragma unroll
  for (int i = 0; i < N; i++) asm volatile("" : "+r"(a[i]) :: "memory");
}
__device__ __forceinline__ void cexp_t(float lg2mag, float turns, float& re, float& im) {
  float m = ex2(lg2mag);
  float fr = (turns - __fadd_rn(__fadd_rn(turns, 12582912.f), -12582912.f)) * 6.283185307f;
  re = m * __cosf(fr); im = m * __sinf(fr);
}
__device__ __forceinline__ void cmul(float ar, float ai, float br, float bi, float& cr, float& ci) {
  cr = fmaf(ar, br, -ai * bi); ci = fmaf(ar, bi, ai * br);
}

__device__ __forceinline__ void wg_ss192_tb(float* d, uint64_t da, uint64_t db, int scale_d) {
  asm volatile("{\n.reg .pred p;\nsetp.ne.b32 p, %98, 0;\n"
    "wgmma.mma_async.sync.aligned.m64n192k16.f32.bf16.bf16 "
    "{%0, %1, %2, %3, %4, %5, %6, %7, %8, %9, %10, %11, %12, %13, %14, %15, %16, %17, %18, %19, %20, %21, %22, %23, %24, %25, %26, %27, %28, %29, %30, %31, %32, %33, %34, %35, %36, %37, %38, %39, %40, %41, %42, %43, %44, %45, %46, %47, %48, %49, %50, %51, %52, %53, %54, %55, %56, %57, %58, %59, %60, %61, %62, %63, %64, %65, %66, %67, %68, %69, %70, %71, %72, %73, %74, %75, %76, %77, %78, %79, %80, %81, %82, %83, %84, %85, %86, %87, %88, %89, %90, %91, %92, %93, %94, %95}, %96, %97, p, 1, 1, 0, 1;\n}\n"
    : "+f"(d[0]), "+f"(d[1]), "+f"(d[2]), "+f"(d[3]), "+f"(d[4]), "+f"(d[5]), "+f"(d[6]), "+f"(d[7]), "+f"(d[8]), "+f"(d[9]), "+f"(d[10]), "+f"(d[11]), "+f"(d[12]), "+f"(d[13]), "+f"(d[14]), "+f"(d[15]), "+f"(d[16]), "+f"(d[17]), "+f"(d[18]), "+f"(d[19]), "+f"(d[20]), "+f"(d[21]), "+f"(d[22]), "+f"(d[23]), "+f"(d[24]), "+f"(d[25]), "+f"(d[26]), "+f"(d[27]), "+f"(d[28]), "+f"(d[29]), "+f"(d[30]), "+f"(d[31]), "+f"(d[32]), "+f"(d[33]), "+f"(d[34]), "+f"(d[35]), "+f"(d[36]), "+f"(d[37]), "+f"(d[38]), "+f"(d[39]), "+f"(d[40]), "+f"(d[41]), "+f"(d[42]), "+f"(d[43]), "+f"(d[44]), "+f"(d[45]), "+f"(d[46]), "+f"(d[47]), "+f"(d[48]), "+f"(d[49]), "+f"(d[50]), "+f"(d[51]), "+f"(d[52]), "+f"(d[53]), "+f"(d[54]), "+f"(d[55]), "+f"(d[56]), "+f"(d[57]), "+f"(d[58]), "+f"(d[59]), "+f"(d[60]), "+f"(d[61]), "+f"(d[62]), "+f"(d[63]), "+f"(d[64]), "+f"(d[65]), "+f"(d[66]), "+f"(d[67]), "+f"(d[68]), "+f"(d[69]), "+f"(d[70]), "+f"(d[71]), "+f"(d[72]), "+f"(d[73]), "+f"(d[74]), "+f"(d[75]), "+f"(d[76]), "+f"(d[77]), "+f"(d[78]), "+f"(d[79]), "+f"(d[80]), "+f"(d[81]), "+f"(d[82]), "+f"(d[83]), "+f"(d[84]), "+f"(d[85]), "+f"(d[86]), "+f"(d[87]), "+f"(d[88]), "+f"(d[89]), "+f"(d[90]), "+f"(d[91]), "+f"(d[92]), "+f"(d[93]), "+f"(d[94]), "+f"(d[95])
    : "l"(da), "l"(db), "r"(scale_d));
}
__device__ __forceinline__ void wg_ss48_tb(float* d, uint64_t da, uint64_t db, int scale_d) {
  asm volatile("{\n.reg .pred p;\nsetp.ne.b32 p, %26, 0;\n"
    "wgmma.mma_async.sync.aligned.m64n48k16.f32.bf16.bf16 "
    "{%0, %1, %2, %3, %4, %5, %6, %7, %8, %9, %10, %11, %12, %13, %14, %15, %16, %17, %18, %19, %20, %21, %22, %23}, %24, %25, p, 1, 1, 0, 1;\n}\n"
    : "+f"(d[0]), "+f"(d[1]), "+f"(d[2]), "+f"(d[3]), "+f"(d[4]), "+f"(d[5]), "+f"(d[6]), "+f"(d[7]), "+f"(d[8]), "+f"(d[9]), "+f"(d[10]), "+f"(d[11]), "+f"(d[12]), "+f"(d[13]), "+f"(d[14]), "+f"(d[15]), "+f"(d[16]), "+f"(d[17]), "+f"(d[18]), "+f"(d[19]), "+f"(d[20]), "+f"(d[21]), "+f"(d[22]), "+f"(d[23])
    : "l"(da), "l"(db), "r"(scale_d));
}
__device__ __forceinline__ void wg_ss48_tt(float* d, uint64_t da, uint64_t db, int scale_d) {
  asm volatile("{\n.reg .pred p;\nsetp.ne.b32 p, %26, 0;\n"
    "wgmma.mma_async.sync.aligned.m64n48k16.f32.bf16.bf16 "
    "{%0, %1, %2, %3, %4, %5, %6, %7, %8, %9, %10, %11, %12, %13, %14, %15, %16, %17, %18, %19, %20, %21, %22, %23}, %24, %25, p, 1, 1, 1, 1;\n}\n"
    : "+f"(d[0]), "+f"(d[1]), "+f"(d[2]), "+f"(d[3]), "+f"(d[4]), "+f"(d[5]), "+f"(d[6]), "+f"(d[7]), "+f"(d[8]), "+f"(d[9]), "+f"(d[10]), "+f"(d[11]), "+f"(d[12]), "+f"(d[13]), "+f"(d[14]), "+f"(d[15]), "+f"(d[16]), "+f"(d[17]), "+f"(d[18]), "+f"(d[19]), "+f"(d[20]), "+f"(d[21]), "+f"(d[22]), "+f"(d[23])
    : "l"(da), "l"(db), "r"(scale_d));
}
__device__ __forceinline__ void wg_rs88_tb(float* d, const uint32_t* a, uint64_t db, int scale_d) {
  asm volatile("{\n.reg .pred p;\nsetp.ne.b32 p, %49, 0;\n"
    "wgmma.mma_async.sync.aligned.m64n88k16.f32.bf16.bf16 "
    "{%0, %1, %2, %3, %4, %5, %6, %7, %8, %9, %10, %11, %12, %13, %14, %15, %16, %17, %18, %19, %20, %21, %22, %23, %24, %25, %26, %27, %28, %29, %30, %31, %32, %33, %34, %35, %36, %37, %38, %39, %40, %41, %42, %43}, {%44, %45, %46, %47}, %48, p, 1, 1, 1;\n}\n"
    : "+f"(d[0]), "+f"(d[1]), "+f"(d[2]), "+f"(d[3]), "+f"(d[4]), "+f"(d[5]), "+f"(d[6]), "+f"(d[7]), "+f"(d[8]), "+f"(d[9]), "+f"(d[10]), "+f"(d[11]), "+f"(d[12]), "+f"(d[13]), "+f"(d[14]), "+f"(d[15]), "+f"(d[16]), "+f"(d[17]), "+f"(d[18]), "+f"(d[19]), "+f"(d[20]), "+f"(d[21]), "+f"(d[22]), "+f"(d[23]), "+f"(d[24]), "+f"(d[25]), "+f"(d[26]), "+f"(d[27]), "+f"(d[28]), "+f"(d[29]), "+f"(d[30]), "+f"(d[31]), "+f"(d[32]), "+f"(d[33]), "+f"(d[34]), "+f"(d[35]), "+f"(d[36]), "+f"(d[37]), "+f"(d[38]), "+f"(d[39]), "+f"(d[40]), "+f"(d[41]), "+f"(d[42]), "+f"(d[43])
    : "r"(a[0]), "r"(a[1]), "r"(a[2]), "r"(a[3]), "l"(db), "r"(scale_d));
}
__device__ __forceinline__ void wg_ss80_tb(float* d, uint64_t da, uint64_t db, int scale_d) {
  asm volatile("{\n.reg .pred p;\nsetp.ne.b32 p, %42, 0;\n"
    "wgmma.mma_async.sync.aligned.m64n80k16.f32.bf16.bf16 "
    "{%0, %1, %2, %3, %4, %5, %6, %7, %8, %9, %10, %11, %12, %13, %14, %15, %16, %17, %18, %19, %20, %21, %22, %23, %24, %25, %26, %27, %28, %29, %30, %31, %32, %33, %34, %35, %36, %37, %38, %39}, %40, %41, p, 1, 1, 0, 1;\n}\n"
    : "+f"(d[0]), "+f"(d[1]), "+f"(d[2]), "+f"(d[3]), "+f"(d[4]), "+f"(d[5]), "+f"(d[6]), "+f"(d[7]), "+f"(d[8]), "+f"(d[9]), "+f"(d[10]), "+f"(d[11]), "+f"(d[12]), "+f"(d[13]), "+f"(d[14]), "+f"(d[15]), "+f"(d[16]), "+f"(d[17]), "+f"(d[18]), "+f"(d[19]), "+f"(d[20]), "+f"(d[21]), "+f"(d[22]), "+f"(d[23]), "+f"(d[24]), "+f"(d[25]), "+f"(d[26]), "+f"(d[27]), "+f"(d[28]), "+f"(d[29]), "+f"(d[30]), "+f"(d[31]), "+f"(d[32]), "+f"(d[33]), "+f"(d[34]), "+f"(d[35]), "+f"(d[36]), "+f"(d[37]), "+f"(d[38]), "+f"(d[39])
    : "l"(da), "l"(db), "r"(scale_d));
}
__device__ __forceinline__ void wg_ss48_tt_h(float* d, uint64_t da, uint64_t db, int scale_d) {
  asm volatile("{\n.reg .pred p;\nsetp.ne.b32 p, %26, 0;\n"
    "wgmma.mma_async.sync.aligned.m64n48k16.f32.f16.f16 "
    "{%0, %1, %2, %3, %4, %5, %6, %7, %8, %9, %10, %11, %12, %13, %14, %15, %16, %17, %18, %19, %20, %21, %22, %23}, %24, %25, p, 1, 1, 1, 1;\n}\n"
    : "+f"(d[0]), "+f"(d[1]), "+f"(d[2]), "+f"(d[3]), "+f"(d[4]), "+f"(d[5]), "+f"(d[6]), "+f"(d[7]), "+f"(d[8]), "+f"(d[9]), "+f"(d[10]), "+f"(d[11]), "+f"(d[12]), "+f"(d[13]), "+f"(d[14]), "+f"(d[15]), "+f"(d[16]), "+f"(d[17]), "+f"(d[18]), "+f"(d[19]), "+f"(d[20]), "+f"(d[21]), "+f"(d[22]), "+f"(d[23])
    : "l"(da), "l"(db), "r"(scale_d));
}

struct Params {
  CUtensorMap m[M_COUNT];
  const __nv_bfloat16 *u, *par[4], *logdt, *dskip, *wo;
};

#define CHUNK(i) ((i) == 0 ? c : ((i) == 7 ? (c ^ 1) : (((c & 6) + 1 + (i)) & 7)))
#define FLAG(kind, rr, cc) (&g_flag[((kind) * 128 + (rr) * 8 + (cc)) * 32])
#define SLOT(i) ((i) == 0 || (i) == 5 ? OFF_EXTRA : OFF_BLK + ((i) == 7 ? 0 : (i) == 6 ? 4 : (i) - 1) * BLK)
__device__ __forceinline__ void load_quad(uint32_t* A, uint32_t addr) {
  A[0] = lds32v(addr); A[1] = lds32v(addr + 32); A[2] = lds32v(addr - 32); A[3] = lds32v(addr);
}

__global__ void __launch_bounds__(512, 1) fused_kernel(const __grid_constant__ Params prm) {
  extern __shared__ unsigned char smem_raw[];
  const uint32_t sb = __shfl_sync(0xffffffff, smem_u32(smem_raw), 0);
  const int tid = threadIdx.x, lane = tid & 31;
  const int warp = __shfl_sync(0xffffffff, tid >> 5, 0), wg = warp >> 2, w4 = warp & 3;
  const int cta = blockIdx.x, r = cta >> 3, c = cta & 7;
  if ((sb & 0xffffffu) != SB0) return;
#define BAR(i) (sb + OFF_BAR + 8 * (i))
  const bool sw64 = ((c + 1) & 2) != 0;

  if (wg == 3) {
    if (warp == 13 && elect_one()) {
      #pragma unroll
      for (int i = M_W128; i <= M_WR; i++) asm volatile("prefetch.tensormap [%0];" :: "l"(&prm.m[i]) : "memory");
    }
    asm volatile("setmaxnreg.dec.sync.aligned.u32 56;");
    if (warp == 12) {
      if (elect_one()) {
        #pragma unroll
        for (int i = 0; i < 5; i++) mbar_init(BAR(BR_FULL + i), 1);
        asm volatile("fence.mbarrier_init.release.cluster;" ::: "memory");
      }
      {
        const CUtensorMap* mwp = &prm.m[sw64 ? M_W64 : M_W128];
        const int mcol = (c * 80 + (c & 1) * 16) >> (sw64 ? 5 : 6), rcol = c * 80 + ((c & 1) ? 0 : 64);
        uint32_t s = 0, ph = 1, xs = 0;
        #pragma unroll 1
        for (int kb = 0; kb < 20; kb++) {
          if (kb == 2) bar_sync(0, 512);
          if (kb >= 5) mbar_wait(BAR(BR_EMPTY) + 8 * s, ph);
          if (EN_ATT && elect_one()) {
            const uint32_t st = sb + s * W_SLOT, fb = BAR(BR_FULL) + 8 * s;
            mbar_expect_tx(fb, (kb & 1) ? W_SLOT : W_SLOT + 16384);
            if (!(kb & 1)) tma2d(sb + OFF_X + xs, &prm.m[M_X], fb, kb * 32, r * 128);
            tma4d(st, mwp, fb, 0, kb * 32, mcol, 0);
            tma3d(st + 12288, &prm.m[M_WR], fb, rcol, kb * 32, 0);
          }
          if (kb == 12 && elect_one()) asm volatile("cp.async.bulk.prefetch.L2.global [%0], 6400;" :: "l"(prm.wo + cta * 3200) : "memory");
          if (!EN_ATT && kb == 2) break;
          if (++s == 5) { s = 0; ph ^= 1; }
          if (kb & 1) { xs += 16384; if (xs == 49152) xs = 0; }
        }
      }
      if (EN_ATT) {
      mbar_wait(BAR(BR_EPOCH), 0);
      const unsigned epoch = lds32(sb + OFF_EPOCH);
      const unsigned* fo = FLAG(3, r, lane & 7);
      unsigned seen = __ballot_sync(0xffffffff, ld_rlx(lane < 16 ? fo : FLAG(0, lane & 15, c)) == epoch) & 0xffu;
      mbar_wait(BAR(BR_GEMM), 0);
      if (elect_one()) {
        mbar_expect_tx(BAR(BR_WO), 10240);
        tma2d(sb, &prm.m[M_WO], BAR(BR_WO), c * 64, c * 80);
        mbar_expect_tx(BAR(BR_KVP), 61440);
        mbar_expect_tx(BAR(BR_WO + 1), 7 * 10240);
      }
      {
        uint32_t ds = sb + OFF_WOR + (lane >> 3) * 128 + (((lane & 7) ^ (lane >> 3)) << 4);
        #pragma unroll 1
        for (int h = 0; h < 2; h++) {
          const int i = (lane & 6) + h;
          const char* gs = reinterpret_cast<const char*>(prm.wo) + (size_t)((lane >> 3) + CHUNK(i) * 80) * 1280 + 1024 + c * 32 + (lane & 1) * 16;
          #pragma unroll 2
          for (int q = 0; q < 20; q++) {
            asm volatile("cp.async.cg.shared.global [%0], [%1], 16;" :: "r"(ds), "l"(gs) : "memory");
            ds = (ds + 512) ^ 64; gs += 5120;
          }
        }
      }
      mbar_wait(BAR(BR_PUB), 0);
      poll_all(FLAG(0, lane & 15, c), epoch);
      if (elect_one()) { TS(23); bulk_ld(sb + OFF_KVP, &g_kvp[c * 16 * 240], 61440, BAR(BR_KVP)); }
      asm volatile("cp.async.wait_all;" ::: "memory");
      fence_async();
      mbar_arrive(BAR(BR_WO));
      mbar_wait(BAR(BR_SUM), 0);
      if (elect_one()) {
        #pragma unroll 1
        for (int i = 1; i < 8; i++) tma2d(sb + i * 10240, &prm.m[M_WO], BAR(BR_WO + 1), c * 64, CHUNK(i) * 80);
      }
      mbar_wait(BAR(BR_OSTG), 0);
      if (elect_one()) {
        bulk_st(&g_o[cta * 1280], sb + OFF_EXTRA, 20480);
        bulk_commit();
        bulk_wait0();
        st_rlx(FLAG(3, r, c), epoch);
        TS(20);
      }
      __syncwarp();
      #pragma unroll 1
      for (int i = 1; i < 8; i++) {
        const int src = CHUNK(i);
        if (!((seen >> src) & 1)) seen = poll_bit(fo, epoch, 1u << src);
        if (i == 5 || i == 7) mbar_wait(BAR(BR_OEMPTY) + 4 * (i - 5), 0);
        if (EN_SSM && (i == 1 || i == 4)) mbar_wait(BAR(BR_FREE) + 2 * (i & 4), 0);
        if (elect_one()) {
          mbar_expect_tx(BAR(BR_OFULL) + 8 * i, 20480);
          bulk_ld(sb + SLOT(i), &g_o[(r * 8 + src) * 1280], 20480, BAR(BR_OFULL) + 8 * i);
          if (i == 1) TS(21);
          if (i == 7) TS(22);
        }
        __syncwarp();
      }
      if (lane == 0) { DUMP(20, 30); }
      }
    } else {
      const int hw = warp - 13, ht = tid - 416;
      unsigned epoch = 0;
      if (hw == 2 && elect_one()) {
        #pragma unroll
        for (int i = 5; i < BR_COUNT; i++) mbar_init(BAR(i), i == BR_WO ? 33 : i < BR_EMPTY ? 1 : i < BR_OEMPTY ? 2 : i < BR_Y ? 8 : i < BR_OSTG ? 128 : 256);
        asm volatile("fence.mbarrier_init.release.cluster;" ::: "memory");
      }
      bar_sync(0, 512);
      if (hw == 1 && elect_one()) {
        #pragma unroll
        for (int i = M_WO; i < M_COUNT; i++) asm volatile("prefetch.tensormap [%0];" :: "l"(&prm.m[i]) : "memory");
      }
      if (hw == 0) {
        if (lane == 0) {
          epoch = ld_rlx(&g_epoch[cta]) + 1;
          st_rlx(&g_epoch[cta], epoch);
          sts32(sb + OFF_EPOCH, epoch);
          mbar_arrive(BAR(BR_EPOCH));
        }
        epoch = __shfl_sync(0xffffffff, epoch, 0);
      }
      if (EN_SSM) {
      const int mi = lane >> 3, rw = lane & 7, ch0 = c * 80 + r * 5;
      if (EN_ATT) mbar_wait(BAR(BR_FULL + U_AFTER), 0);
      #pragma unroll 1
      for (int i = hw; i < 5; i += 3) {
        const int cg = c * 80 + i * 16 + (lane >> 4) * 8, t0 = r * 128 + (lane & 15) * 8;
        const uint4* gs = reinterpret_cast<const uint4*>(prm.u + (size_t)t0 * 640 + cg);
        uint4* gd = reinterpret_cast<uint4*>(g_uy + (size_t)cg * 2048 + t0);
        uint4 v[8];
        #pragma unroll
        for (int q = 0; q < 8; q++) v[q] = __ldg(gs + q * 80);
#define TR(f, sel) make_uint4(__byte_perm(v[0].f, v[1].f, sel), __byte_perm(v[2].f, v[3].f, sel), __byte_perm(v[4].f, v[5].f, sel), __byte_perm(v[6].f, v[7].f, sel))
        gd[0] = TR(x, 0x5410); gd[256] = TR(x, 0x7632); gd[512] = TR(y, 0x5410); gd[768] = TR(y, 0x7632);
        gd[1024] = TR(z, 0x5410); gd[1280] = TR(z, 0x7632); gd[1536] = TR(w, 0x5410); gd[1792] = TR(w, 0x7632);
      }
      bar_sync(5, 96);
      if (ht == 0) TS(36);
      if (hw == 0) {
        if (lane == 0) { st_rel(FLAG(1, r, c), epoch); TS(30); }
        __syncwarp();
        poll_all_acq(FLAG(1, lane & 15, c), epoch);
        if (elect_one()) {
          fence_async_g();
          mbar_expect_tx(BAR(BR_U), 20480);
          #pragma unroll 1
          for (int q = 0; q < 5; q++) tma2d(sb + OFF_BLK + q * BLK, &prm.m[M_SB], BAR(BR_U), 0, (ch0 + q) * 32);
          TS(31);
        }
        __syncwarp();
      }
      if (hw == 0) {
        #pragma unroll 1
        for (int p = 0; p < 2; p++) {
          mbar_wait(BAR(BR_Y) + 8 * p, 0);
          if (elect_one()) {
            #pragma unroll 1
            for (int k = 4 * p; k < 4 + p; k++) tma2d_st(&prm.m[M_SB], sb + OFF_BLK + k * BLK, 0, (640 + ch0 + k) * 32);
            bulk_commit(); bulk_wait0_read();
            mbar_arrive(BAR(BR_FREE) + 8 * p);
          }
          __syncwarp();
        }
        if (elect_one()) {
          mbar_expect_tx(BAR(BR_YIN), 20480);
          bulk_wait0();
          st_rel(FLAG(2, r, c), epoch);
          TS(33);
        }
        __syncwarp();
        poll_all_acq(FLAG(2, lane & 15, c), epoch);
        if (EN_ATT) mbar_wait(BAR(BR_OEMPTY + 3), 0);
        if (elect_one()) {
          fence_async_g();
          tma2d(sb + OFF_BLK + BLK, &prm.m[M_SA], BAR(BR_YIN), r * 128, 640 + c * 80);
          tma2d(sb + OFF_BLK + BLK + 10240, &prm.m[M_SA], BAR(BR_YIN), r * 128 + 64, 640 + c * 80);
          TS(34);
        }
      }
      {
        uint32_t sa = sb + OFF_BLK + BLK + (hw * 8 + rw) * 128 + ((mi ^ rw) << 4);
        uint32_t da = sb + OFF_BLK + 2 * BLK + (8 * mi + rw) * 160 + hw * 16;
        mbar_wait(BAR(BR_YIN), 0);
        #pragma unroll 1
        for (int i = hw; i < 10; i += 3) {
          uint32_t v[4][4];
          #pragma unroll
          for (int q = 0; q < 4; q++) ldsm4t(v[q], (sa ^ ((q & 1) * 64)) + (q >> 1) * 10240);
          #pragma unroll
          for (int q = 0; q < 4; q++) stsm4(da + q * 5120, v[q][0], v[q][1], v[q][2], v[q][3]);
          sa += 3072; da += 48;
        }
      }
      fence_async();
      bar_sync(5, 96);
      if (hw == 0 && elect_one()) {
        tma2d_st(&prm.m[M_OUT], sb + OFF_BLK + 2 * BLK, c * 80, r * 128);
        bulk_commit(); bulk_wait0_read();
        TS(35); DUMP(30, 40); DUMP(0, 1);
      }
      }
    }
  } else if (wg < 2) {
    asm volatile("setmaxnreg.inc.sync.aligned.u32 152;");
    bar_sync(0, 512);
    if (!EN_ATT) {
    if (EN_SSM) {
      mbar_wait(BAR(BR_U), 0);
      mbar_wait(BAR(BR_KGEN), 0);
      #pragma unroll 1
      for (int q6 = warp; q6 < 30; q6 += 8) {
        {
          const int k = q6 / 6, kap = (q6 - 6 * k) * 32 + lane;
          const uint32_t blk = sb + OFF_BLK + k * BLK;
          float P[33];
          P[0] = 0.f;
          #pragma unroll
          for (int q = 0; q < 4; q++) {
            const int ch = kap - 3 + q;
            uint32_t v[4];
            lds128(v, blk + (uint32_t)((ch * 16) ^ ((ch * 2) & 0x70)));
            #pragma unroll
            for (int e = 0; e < 4; e++) {
              P[q * 8 + 2 * e + 1] = (q == 0 && e < 2) ? 0.f : P[q * 8 + 2 * e] + bf_lo(v[e]);
              P[q * 8 + 2 * e + 2] = (q == 0 && e < 2) ? 0.f : P[q * 8 + 2 * e + 1] + bf_hi(v[e]);
            }
          }
#define WIN(lo, hi, e) (P[25 + (e) - (lo)] - P[24 + (e) - (hi)])
#define WIN8(lo, hi) pack2(WIN(lo, hi, 0), WIN(lo, hi, 1)), pack2(WIN(lo, hi, 2), WIN(lo, hi, 3)), pack2(WIN(lo, hi, 4), WIN(lo, hi, 5)), pack2(WIN(lo, hi, 6), WIN(lo, hi, 7))
          const uint32_t o2 = blk + B_D + (kap & 1) * 1552 + (kap >> 1) * 16;
          sts128(o2, WIN8(3, 5));
          sts128(o2 + B_D5, WIN8(6, 10));
          if (kap < 128) {
            const uint32_t o = blk + B_D + (kap & 1) * 1024 + (kap >> 1) * 16;
            sts128(o + B_D7, WIN8(5, 11));
            sts128(o + B_D9, WIN8(12, 20));
          }
        }
      }
      if (tid < 10) sts128(sb + OFF_BLK + (tid >> 1) * BLK + B_D + (tid & 1) * B_D5 + 1536, 0, 0, 0, 0);
      mbar_arrive(BAR(BR_DRDY));
      if (tid == 0) TS(12);
    }
    }
    if (EN_ATT) {
    const int tq = lane & 3, t7 = tid & 127;
    float am[96], ar[24];
    {
      constexpr uint64_t da0 = mkdesc(SB0 + OFF_X, 16, 1024, 1), dr0 = mkdesc(SB0 + 12288, 1024, 256, 3);
      const uint64_t db0 = sw64 ? mkdesc(SB0, 2048, 512, 2) : mkdesc(SB0, 4096, 1024, 1);
      const uint32_t kst = sw64 ? 64 : 128, bh = db0 >> 32;
      uint32_t s = 0, ph = 0, xo = 0;
      #pragma unroll 1
      for (int kb = 0; kb < 20; kb++) {
        const uint32_t wo_ = s * (W_SLOT >> 4), al = (uint32_t)da0 + wg * 512 + xo, bl = (uint32_t)db0 + wo_, rl = (uint32_t)dr0 + wo_;
        mbar_wait(BAR(BR_FULL) + 8 * s, ph);
        if (kb == 0 && tid == 0) TS(1);
        wg_fence();
        wg_ss192_tb(am, desc2(al, da0 >> 32), desc2(bl, bh), kb != 0);
        wg_ss48_tb(ar, desc2(al, da0 >> 32), desc2(rl, dr0 >> 32), kb != 0);
        wg_ss192_tb(am, desc2(al + 2, da0 >> 32), desc2(bl + kst, bh), 1);
        wg_ss48_tb(ar, desc2(al + 2, da0 >> 32), desc2(rl + 32, dr0 >> 32), 1);
        wg_commit();
        wg_wait<1>();
        if (t7 == 0 && kb > 0 && kb < 16) mbar_arrive(BAR(BR_EMPTY) + 8 * (s == 0 ? 4 : s - 1));
        if (++s == 5) { s = 0; ph ^= 1; }
        xo += (kb & 1) ? 1020 : 4;
        if (xo == 3072) xo = 0;
      }
      wg_wait<0>();
      pin<96>(am); pin<24>(ar);
    }
    if (tid == 0) TS(2);
#define QV(j, e) ((j) < 8 ? am[4 * (j) + (e)] : ar[4 * ((j) - 8) + (e)])
#define KV_(j, e) ((j) < 8 ? am[32 + 4 * (j) + (e)] : ar[8 + 4 * ((j) - 8) + (e)])
#define VV(j, e) ((j) < 8 ? am[64 + 4 * (j) + (e)] : ar[16 + 4 * ((j) - 8) + (e)])
    {
      bar_sync(1, 256);
      if (tid == 0) mbar_arrive(BAR(BR_GEMM));
      const uint32_t ro = sb + (uint32_t)((warp * 16 + (lane & 15)) * 16);
      const int l0 = 2 * (c & 1) + (lane >> 4);
      const uint32_t ones = (tq == 0) ? 0x00003f80u : 0u;
#define PV(j) pack2(VV(j, 0), VV(j, 1)), pack2(VV(j, 2), VV(j, 3))
#define PK(j) pack2(phi(KV_(j, 0)), phi(KV_(j, 1))), pack2(phi(KV_(j, 2)), phi(KV_(j, 3)))
      stsm4(ro + OFF_V + (5 + 6 * (lane >> 4)) * 2048, ones, ones, ones, ones);
      #pragma unroll
      for (int j = 0; j < 10; j += 2) {
        const int l = (j == 8 && (c & 1)) ? l0 - 2 : l0 + j;
        stsm4(ro + OFF_V + (l + (l >= 5)) * 2048, PV(j), PV(j + 1));
        stsm4(ro + OFF_PK + l * 2048, PK(j), PK(j + 1));
      }
    }
    fence_async();
    bar_sync(1, 256);
    if (tid == 0) TS(3);
    mbar_wait(BAR(BR_EPOCH), 0);
    const unsigned epoch = lds32(sb + OFF_EPOCH);
    {
      float kv[24]; zero<24>(kv);
      constexpr uint64_t da = mkdesc(SB0 + OFF_PK, 128, 2048, 0), db = mkdesc(SB0 + OFF_V, 128, 2048, 0);
      wg_fence();
      #pragma unroll
      for (int s = 0; s < 8; s++) wg_ss48_tt(kv, desc2((uint32_t)da + wg * 640 + s * 16, da >> 32), desc2((uint32_t)db + wg * 768 + s * 16, db >> 32), s != 0);
      wg_commit();
      wg_wait<0>();
      pin<24>(kv);
      if (tid == 0) TS(15);
      if (w4 < 3) {
        const uint32_t wb = sb + OFF_KVS + (wg * 3 + w4) * 1536 + (lane & 15) * 96;
        #pragma unroll
        for (int j = 0; j < 6; j += 2)
          stsm4(wb + (j + (lane >> 4)) * 16, pack2(kv[4 * j], kv[4 * j + 1]), pack2(kv[4 * j + 2], kv[4 * j + 3]),
                pack2(kv[4 * j + 4], kv[4 * j + 5]), pack2(kv[4 * j + 6], kv[4 * j + 7]));
        __syncwarp();
        const int dl = w4 * 16 + (lane & 15), hl = dl >= 20;
        if (dl < 40) {
          uint4* dst = &g_kvp[(c * 16 + r) * 240 + wg * 40 + dl];
          uint32_t v[4], z[4];
          lds128(v, wb + (3 * hl + (lane >> 4)) * 16);
          lds64(z, wb + 32 + 8 * hl); z[2] = lds32(wb + 80); z[3] = epoch & 1u;
          v[3] = (v[3] & ~1u) | z[3];
          st128_rlx(dst + (lane >> 4) * 80, v);
          if (lane < 16) st128_rlx(dst + 160, z);
        }
      }
    }
    fence_async();
    bar_sync(1, 256);
    if (tid == 0) { st_rlx(FLAG(0, r, c), epoch); mbar_arrive(BAR(BR_PUB)); TS(4); }
    const int kvi = (tid >= 80) + (tid >= 160) + (tid >= 240), kd = tid - 80 * kvi;
    const int khd = kd / 20, kt0 = 5 * (khd >> 1) + 2 * (khd & 1);
    const uint32_t rb = sb + OFF_KVB + kd * 16;
    if (kvi < 3) {
      #pragma unroll 1
      for (int m = kvi; m < 7; m += 3) { const int q = kt0 + 3 + m; sts128(rb + (q >= 10 ? q - 10 : q) * 1280, 0, 0, 0, 0); }
    }
    uint32_t qa[20];
    {
      const float sc = 1.44269504089f + __uint_as_float(lds32(sb + OFF_EPOCH) ^ epoch);
      #pragma unroll
      for (int j = 0; j < 10; j++) { qa[2 * j] = pack2(phi(QV(j, 0), sc), phi(QV(j, 1), sc)); qa[2 * j + 1] = pack2(phi(QV(j, 2), sc), phi(QV(j, 3), sc)); }
    }
    if (tid == 0) TS(5);
    if (EN_SSM) {
      mbar_wait(BAR(BR_U), 0);
      mbar_wait(BAR(BR_KGEN), 0);
      #pragma unroll 1
      for (int q6 = warp; q6 < 30; q6 += 8) {
        {
          const int k = q6 / 6, kap = (q6 - 6 * k) * 32 + lane;
          const uint32_t blk = sb + OFF_BLK + k * BLK;
          float P[33];
          P[0] = 0.f;
          #pragma unroll
          for (int q = 0; q < 4; q++) {
            const int ch = kap - 3 + q;
            uint32_t v[4];
            lds128(v, blk + (uint32_t)((ch * 16) ^ ((ch * 2) & 0x70)));
            #pragma unroll
            for (int e = 0; e < 4; e++) {
              P[q * 8 + 2 * e + 1] = (q == 0 && e < 2) ? 0.f : P[q * 8 + 2 * e] + bf_lo(v[e]);
              P[q * 8 + 2 * e + 2] = (q == 0 && e < 2) ? 0.f : P[q * 8 + 2 * e + 1] + bf_hi(v[e]);
            }
          }
#define WIN(lo, hi, e) (P[25 + (e) - (lo)] - P[24 + (e) - (hi)])
#define WIN8(lo, hi) pack2(WIN(lo, hi, 0), WIN(lo, hi, 1)), pack2(WIN(lo, hi, 2), WIN(lo, hi, 3)), pack2(WIN(lo, hi, 4), WIN(lo, hi, 5)), pack2(WIN(lo, hi, 6), WIN(lo, hi, 7))
          const uint32_t o2 = blk + B_D + (kap & 1) * 1552 + (kap >> 1) * 16;
          sts128(o2, WIN8(3, 5));
          sts128(o2 + B_D5, WIN8(6, 10));
          if (kap < 128) {
            const uint32_t o = blk + B_D + (kap & 1) * 1024 + (kap >> 1) * 16;
            sts128(o + B_D7, WIN8(5, 11));
            sts128(o + B_D9, WIN8(12, 20));
          }
        }
      }
      if (tid < 10) sts128(sb + OFF_BLK + (tid >> 1) * BLK + B_D + (tid & 1) * B_D5 + 1536, 0, 0, 0, 0);
      mbar_arrive(BAR(BR_DRDY));
      if (tid == 0) TS(12);
    }
    mbar_wait(BAR(BR_KVP), 0);
    if (tid == 0) TS(6);
    if (kvi < 3) {
      float s[8];
      zero<8>(s);
      uint32_t bad = 0;
      #pragma unroll 4
      for (int i = 0; i < 16; i++) {
        uint32_t w[4];
        lds128(w, sb + OFF_KVP + tid * 16 + i * 3840);
        bad |= w[3] ^ epoch;
        #pragma unroll
        for (int e = 0; e < 4; e++) { s[2 * e] += bf_lo(w[e]); s[2 * e + 1] += bf_hi(w[e]); }
      }
      if (__builtin_expect(bad & 1u, 0)) {
        zero<8>(s);
        #pragma unroll 1
        for (int i = 0; i < 16; i++) {
          uint32_t w[4] = {0, 0, 0, ~epoch};
          fix128_w3(w, &g_kvp[(c * 16 + i) * 240 + tid], epoch, 1u);
          #pragma unroll
          for (int e = 0; e < 4; e++) { s[2 * e] += bf_lo(w[e]); s[2 * e + 1] += bf_hi(w[e]); }
        }
        FIXCNT
      }
      const uint32_t p0 = pack2(s[0], s[1]), p1 = pack2(s[2], s[3]), p2 = pack2(s[4], s[5]), p3 = pack2(s[6], s[7]);
      if (kvi < 2) sts128(rb + (kt0 + (khd & 1) + kvi) * 1280, p0, p1, p2, p3);
      else {
        const bool od = khd & 1;
        sts128(rb + (5 * (khd >> 1) + 2) * 1280, od ? 0u : p0, od ? 0u : p1, od ? p0 : 0u, od ? p1 : 0u);
        const uint32_t zz = (p2 & 0xffffu) << (16 * (khd & 1));
        sts128(rb + 10 * 1280, khd < 2 ? zz : 0u, khd < 2 ? 0u : zz, 0u, 0u);
      }
    }
    fence_async();
    bar_sync(1, 256);
    if (tid == 0) { mbar_arrive(BAR(BR_SUM)); TS(7); }
    {
      float oa[44]; zero<44>(oa);
      constexpr uint64_t db = mkdesc(SB0 + OFF_KVB, 128, 1280, 0);
      wg_fence();
      #pragma unroll
      for (int s = 0; s < 5; s++) wg_rs88_tb(oa, &qa[4 * s], desc2((uint32_t)db + ((s == 4 && (c & 1)) ? 0 : (s + (c & 1)) * 16), db >> 32), s != 0);
      wg_commit();
      wg_wait<0>();
      pin<44>(oa);
      if (tid == 0) TS(13);
      float rc[4], rd[2][4];
      #pragma unroll
      for (int e = 0; e < 4; e++) asm("rcp.approx.ftz.f32 %0, %1;" : "=f"(rc[e]) : "f"(oa[40 + e] + 1e-6f));
      #pragma unroll
      for (int h = 0; h < 4; h++) {
        rd[0][h] = __shfl_sync(0xffffffff, rc[h & 1], (lane & 28) | (h >> 1));
        rd[1][h] = __shfl_sync(0xffffffff, rc[2 + (h & 1)], (lane & 28) | (h >> 1));
      }
      #pragma unroll
      for (int j = 0; j < 10; j++) {
        #pragma unroll
        for (int h = 0; h < 2; h++) {
          float f;
          if (j == 2) f = tq < 2 ? rd[h][0] : rd[h][1];
          else if (j == 7) f = tq < 2 ? rd[h][2] : rd[h][3];
          else f = rd[h][(8 * j) / 20];
          qa[2 * j + h] = pack2(oa[4 * j + 2 * h] * f, oa[4 * j + 2 * h + 1] * f);
        }
      }
      const uint32_t m0 = (lane & 7) == ((2 * w4) & 7), m1 = (lane & 7) == 2 * w4 + 1;
      const uint32_t oa_ = sb + OFF_EXTRA + (lane >> 4) * 2048 + (warp * 16 + (lane & 15)) * 16;
      bar_sync(1, 256);
#define TAG(v, m) (((v) & ~(m)) | (epoch & (m)))
      #pragma unroll
      for (int s = 0; s < 5; s++) stsm4(oa_ + s * 4096, TAG(qa[4 * s], m0), TAG(qa[4 * s + 1], m1), TAG(qa[4 * s + 2], m0), TAG(qa[4 * s + 3], m1));
    }
    fence_async();
    mbar_arrive(BAR(BR_OSTG));
    if (tid == 0) TS(8);
    float oc[40]; zero<40>(oc);
    {
      constexpr uint64_t dw0 = mkdesc(SB0, OFF_WOR, 1024, 1), da0 = mkdesc(SB0, 2048, 128, 0);
      const uint32_t ck = sb + tid * 32 + ((lane >> 2) << 2), ck2 = ck + (wg ? 0 : 16384);
      uint32_t bad = 0;
      auto tile = [&](int i, uint32_t so) {
        const uint32_t al = (uint32_t)da0 + wg * 64 + (so >> 4), wl = (uint32_t)dw0 + i * 640 - (i >> 1) * (1278 << 16);
        wg_fence();
        #pragma unroll
        for (int s = 0; s < 5; s++) wg_ss80_tb(oc, desc2(al + s * 256, da0 >> 32), desc2(wl + s * 128, dw0 >> 32), (i | s) != 0);
        wg_commit();
        bad |= (lds32(ck + so) ^ epoch) | (lds32(ck + so + 8192) ^ epoch) | (lds32(ck2 + so) ^ epoch);
      };
      mbar_wait(BAR(BR_WO), 0);
      mbar_wait(BAR(BR_OSTG), 0);
      tile(0, SLOT(0));
      mbar_wait(BAR(BR_WO + 1), 0);
      #pragma unroll 1
      for (int i = 1; i < 8; i++) {
        if (i == 1) { wg_wait<0>(); if (lane == 0) mbar_arrive(BAR(BR_OEMPTY)); }
        mbar_wait(BAR(BR_OFULL) + 8 * i, 0);
        if (i == 1 && tid == 0) TS(9);
        tile(i, SLOT(i));
        wg_wait<1>();
        if (lane == 0 && i > 1) mbar_arrive(BAR(BR_OEMPTY - 1) + 8 * i);
      }
      #pragma unroll 1
      for (int n = 0; n < 56; n++) {
        const int i = n & 7;
        if (i == 0) {
          uint32_t any;
          asm volatile("{\n.reg .pred p;\nsetp.ne.u32 p, %1, 0;\nbarrier.red.or.pred p, 1, 256, p;\nselp.u32 %0, 1, 0, p;\n}" : "=r"(any) : "r"(bad & 1u) : "memory");
          if (!any) break;
          bad = 0;
          FIXCNT
        }
        wg_wait<0>();
        bar_sync(1, 256);
        if (tid == 0) { mbar_expect_tx(BAR(BR_RETRY), 20480); bulk_ld(sb + SLOT(0), &g_o[(r * 8 + CHUNK(i)) * 1280], 20480, BAR(BR_RETRY)); }
        mbar_wait(BAR(BR_RETRY), n & 1);
        tile(i, SLOT(0));
      }
      wg_wait<0>();
      pin<40>(oc);
    }
    if (tid == 0) TS(10);
    {
      const int row = w4 * 16 + (lane & 15);
      const uint32_t ob = sb + SLOT(4) + wg * 10240;
      #pragma unroll
      for (int j = 0; j < 8; j += 2)
        stsm4(ob + row * 128 + (((j + (lane >> 4)) ^ (row & 7)) << 4), pack2(oc[4 * j], oc[4 * j + 1]), pack2(oc[4 * j + 2], oc[4 * j + 3]),
              pack2(oc[4 * j + 4], oc[4 * j + 5]), pack2(oc[4 * j + 6], oc[4 * j + 7]));
      stsm4(ob + 8192 + row * 32 + (lane >> 4) * 16, pack2(oc[32], oc[33]), pack2(oc[34], oc[35]), pack2(oc[36], oc[37]), pack2(oc[38], oc[39]));
      fence_async();
      bar_sync(2 + wg, 128);
      if (w4 == 0 && elect_one()) {
        tma2d_st(&prm.m[M_O64], ob, 640 + c * 64, r * 128 + wg * 64);
        tma2d_st(&prm.m[M_O16], ob + 8192, 1152 + c * 16, r * 128 + wg * 64);
        bulk_commit(); bulk_wait0_read();
        if (wg == 0) { TS(11); DUMP(0, 20); }
      }
    }
    }
  } else {
    uint4 pv[3];
    const uint4* pp = reinterpret_cast<const uint4*>(prm.par[w4] + (c * 80 + r * 5) * 128);
    pv[0] = __ldg(pp + lane); pv[1] = __ldg(pp + 32 + lane); pv[2] = __ldg(pp + 64 + (lane & 15));
    const int kq = c * 80 + r * 5 + min(lane, 4);
    const unsigned short ldt = __ldg(reinterpret_cast<const unsigned short*>(prm.logdt) + kq), dsk0 = __ldg(reinterpret_cast<const unsigned short*>(prm.dskip) + kq);
    asm volatile("setmaxnreg.inc.sync.aligned.u32 152;");
    bar_sync(0, 512);
    if (EN_SSM) {
    const int g = lane >> 2, tq = lane & 3, t7 = tid & 127;
    {
      #pragma unroll 1
      for (int k = 0; k < 5; k++) {
        const uint32_t tz = sb + OFF_BLK + k * BLK + B_TBL + t7 * 16;
        if (t7 < 32 || t7 >= 96) sts128(tz, 0, 0, 0, 0);
        if (t7 < 124) sts128(tz + 2048, 0, 0, 0, 0);
        if (t7 < 16) sts128(sb + OFF_BLK + k * BLK - 256 + t7 * 16, 0, 0, 0, 0);
      }
      if (t7 < 5) sts64(sb + OFF_BLK + t7 * BLK + B_SP + 8, __float_as_uint(bf_round(expf(bf_lo(ldt)))), (uint32_t)dsk0 << 16);
      const uint32_t st = sb + OFF_BLK + (lane >> 4) * BLK + B_TBL + 512 + w4 * 256 + (lane & 15) * 16;
      #pragma unroll
      for (int i = 0; i < 3; i++) {
        if (i < 2 || lane < 16) sts128(st + 2 * i * BLK, pv[i].x, pv[i].y, pv[i].z, pv[i].w);
        if (w4 >= 2) {
          const uint32_t m2 = __vmaxu2(__vmaxu2(pv[i].x & 0x7fff7fffu, pv[i].y & 0x7fff7fffu), __vmaxu2(pv[i].z & 0x7fff7fffu, pv[i].w & 0x7fff7fffu));
          const uint32_t m = __reduce_max_sync(lane < 16 ? 0x0000ffffu : 0xffff0000u, max(m2 & 0xffffu, m2 >> 16));
          if ((lane & 15) == 0 && (i < 2 || lane == 0)) sts32(sb + OFF_BLK + (2 * i + (lane >> 4)) * BLK + B_SP + 8 + w4 * 4, m);
        }
      }
    }
    bar_sync(4, 128);
    if (t7 == 0) TS(40);
    {
      const uint32_t fa = sb + OFF_BLK + B_D + ((t7 >> 4) & 3) * BLK + ((lane >> 3) & 1) * 256 + (lane & 7) * 16;
      const uint32_t ea = fa + (w4 >> 1) * 2048, ga = fa + 4096 + (w4 >> 1) * 1536;
      constexpr uint64_t dE = mkdesc(SB0 + OFF_BLK + B_D, 128, 512, 0), dG = mkdesc(SB0 + OFF_BLK + B_D + 4096, 128, 512, 0);
      const uint32_t xa = sb + OFF_BLK + 4 * BLK + B_D + t7 * 8;
      float ka[24]; zero<24>(ka);
      float fac = 0.f, dsk = 0.f, kk[6];
      zero<6>(kk);
      wg_fence();
      wg_ss48_tt_h(ka, dE, dG, 0);
      wg_commit();
      #pragma unroll 1
      for (int k = 0; k < 7; k++) {
        if (k >= 2) {
          const uint32_t blk = sb + OFF_BLK + (k - 2) * BLK;
        {
          const int j = (w4 & 1) * 16 + (w4 >> 1) * 8 + g;
          const uint32_t tb = blk + B_TBL;
          const uint32_t pa_ = tb + (16 + 8 * j + 2 * tq) * 4;
          const uint32_t v = pack2(kk[1], kk[0]);
          sts32(pa_ + 4, v); sts16(pa_, v >> 16); sts16(pa_ + 10, v);
          const uint32_t u = pack2(kk[2], kk[3]), w = pack2(kk[4], kk[5]);
          if (tq < 2) {
            const uint32_t pb = tb + (16 + 256 + 8 * j + 4 * tq) * 4;
            sts16(pb, u); sts32(pb + 4, __byte_perm(u, 0, 0x1010)); sts32(pb + 8, __byte_perm(u, 0, 0x1032)); sts16(pb + 14, u >> 16);
            if (j | tq) { sts16(pb - 4, u); sts16(pb + 2, u); }
            const int i = 64 * tq + j;
            const uint32_t e0 = tb + (T_F3 + (((i - 1) & 1) ? 80 : 0) + ((i - 1) >> 1)) * 4, e1 = i ? e0 : tb + (T_F2 + 144 + 31) * 4;
            sts16(e1, w); sts16(e1 + 6, w); sts16(e0 + 64, w >> 16); sts16(e0 + 70, w >> 16);
            if (i == 0) { sts16(tb + (T_S + 3) * 4, w); sts32(tb + (T_S + 4) * 4, __byte_perm(w, 0, 0x1010)); sts16(tb + (T_S + 5) * 4 + 2, w); }
          } else {
            const int i = 32 * (tq - 2) + j;
            const uint32_t e1 = tb + (i ? T_F2 + ((2 * i - 1) & 3) * 48 + ((2 * i - 1) >> 2) : 16 + 511) * 4;
            const uint32_t e2 = tb + (T_F2 + (i & 1) * 96 + (i >> 1)) * 4;
            sts16(e1, u); sts16(e1 + 6, u); sts16(e2, u >> 16); sts16(e2 + 6, u >> 16);
            if (i == 0) {
              const uint32_t uu = __byte_perm(u, 0, 0x1010);
              sts32(tb + 528 * 4, uu); sts32(tb + 529 * 4, uu); sts32(tb + 530 * 4, uu); sts16(tb + 531 * 4 + 2, u);
              sts16(tb + (T_F3 + 80 + 63) * 4, w);
            }
          }
        }
        }
        if (k == 6) break;
        uint32_t F[56];
        float facn, dskn;
#define PUT4(i, a, b, c_, d) { F[4 * (i)] = a; F[4 * (i) + 1] = b; F[4 * (i) + 2] = c_; F[4 * (i) + 3] = d; }
        {
          const uint32_t nb = sb + OFF_BLK + min(k, 4) * BLK;
          const uint32_t st = nb + B_TBL + 512 + t7 * 2;
          uint32_t q[2], mm[2];
          const uint32_t p0 = lds16(st), p1 = lds16(st + 256), p2 = lds16(st + 512), p3 = lds16(st + 768);
          lds64(q, nb + B_SP + 8); lds64(mm, nb + B_SP + 16);
          const float dt = __uint_as_float(q[0]); dskn = __uint_as_float(q[1]);
          const uint32_t ex = min(max(max(mm[0], mm[1]) >> 7, 1u), 253u);
          const float sc = __uint_as_float((254u - ex) << 23);
          facn = 2.f * dt * __uint_as_float(ex << 23);
          const float lr = -bf_round(expf(bf_lo(p0))) * dt * 1.44269504089f;
          const float tn = bf_lo(p1) * dt * 0.15915494309f;
          float z1r, z1i, z2r, z2i, z4r, z4i, xr[8], xi[8], gr[8], gi[8], wr[9], wi[9];
          cexp_t(lr, -tn, z1r, z1i);
          cexp_t(lr * 8.f, tn * 8.f, xr[1], xi[1]);
          cexp_t(lr * 64.f, tn * 64.f, wr[0], wi[0]);
          xr[0] = 1.f; xi[0] = 0.f;
          cmul(xr[1], xi[1], xr[1], xi[1], xr[2], xi[2]); cmul(xr[2], xi[2], xr[1], xi[1], xr[3], xi[3]);
          cmul(xr[2], xi[2], xr[2], xi[2], xr[4], xi[4]);
          #pragma unroll
          for (int b = 1; b < 4; b++) cmul(xr[4], xi[4], xr[b], xi[b], xr[4 + b], xi[4 + b]);
          cmul(wr[0], wi[0], wr[0], wi[0], wr[1], wi[1]); cmul(wr[1], wi[1], wr[0], wi[0], wr[2], wi[2]);
          cmul(wr[1], wi[1], wr[1], wi[1], wr[3], wi[3]); cmul(wr[3], wi[3], wr[3], wi[3], wr[4], wi[4]);
          cmul(wr[4], wi[4], wr[3], wi[3], wr[5], wi[5]); cmul(wr[4], wi[4], wr[4], wi[4], wr[6], wi[6]);
          cmul(wr[6], wi[6], wr[4], wi[4], wr[7], wi[7]); cmul(wr[6], wi[6], wr[6], wi[6], wr[8], wi[8]);
          uint32_t R[4], I[4], PR[4], PI[4];
          #pragma unroll
          for (int b = 0; b < 4; b++) { R[b] = packh(xr[2 * b], xr[2 * b + 1]); I[b] = packh(xi[2 * b], xi[2 * b + 1]); }
          PUT4(0, R[0], R[1], R[2], R[3]); PUT4(1, I[0], I[1], I[2], I[3]);
          #pragma unroll
          for (int i = 0; i < 3; i++) {
            const uint32_t z = packh(wr[i], wi[i]);
            #pragma unroll
            for (int b = 0; b < 4; b++) hcm2(R[b], I[b], z, PR[b], PI[b]);
            PUT4(2 * i + 2, PR[0], PR[1], PR[2], PR[3]); PUT4(2 * i + 3, PI[0], PI[1], PI[2], PI[3]);
          }
          gr[0] = bf_lo(p2) * sc; gi[0] = -bf_lo(p3) * sc;
          cmul(z1r, z1i, z1r, z1i, z2r, z2i); cmul(z2r, z2i, z2r, z2i, z4r, z4i);
          cmul(gr[0], gi[0], z1r, z1i, gr[1], gi[1]);
          cmul(gr[0], gi[0], z2r, z2i, gr[2], gi[2]); cmul(gr[1], gi[1], z2r, z2i, gr[3], gi[3]);
          #pragma unroll
          for (int b = 0; b < 4; b++) cmul(gr[b], gi[b], z4r, z4i, gr[4 + b], gi[4 + b]);
          PUT4(8, packh(gr[0], gr[1]), packh(gr[2], gr[3]), packh(gr[4], gr[5]), packh(gr[6], gr[7]));
          PUT4(9, packh(gi[0], gi[1]), packh(gi[2], gi[3]), packh(gi[4], gi[5]), packh(gi[6], gi[7]));
          {
            const uint32_t z = packh(wr[3], -wi[3]), a4r = packh(gr[0], gr[4]), a4i = packh(gi[0], gi[4]);
            hcm2(packh(gr[0], gr[2]), packh(gi[0], gi[2]), z, PR[0], PI[0]);
            hcm2(packh(gr[4], gr[6]), packh(gi[4], gi[6]), z, PR[1], PI[1]);
            hcm2(a4r, a4i, packh(wr[4], -wi[4]), PR[2], PI[2]);
            hcm2(a4r, a4i, packh(wr[5], -wi[5]), PR[3], PI[3]);
            PUT4(10, PR[0], PR[1], PR[2], PR[3]); PUT4(11, PI[0], PI[1], PI[2], PI[3]);
            float hr, hi_;
            cmul(gr[0], gi[0], wr[3], -wi[3], hr, hi_);
            const uint32_t cr = packh(gr[0], hr), ci = packh(gi[0], hi_);
            #pragma unroll
            for (int i = 0; i < 3; i++) hcm2(cr, ci, packh(wr[6 + i], -wi[6 + i]), PR[i], PI[i]);
            PUT4(12, PR[0], PR[1], PR[2], 0u); PUT4(13, PI[0], PI[1], PI[2], 0u);
          }
        }
        if (t7 == 0 && k == 2) TS(50);
        wg_wait<0>();
        pin<24>(ka);
        if (t7 == 0 && k == 2) TS(51);
        const bool up = w4 >= 2;
        #pragma unroll
        for (int n = 0; n < 3; n++) {
          sts64f(xa + n * 1024, up ? ka[12 + 4 * n] : ka[4 * n + 2], up ? ka[13 + 4 * n] : ka[4 * n + 3]);
          kk[2 * n] = up ? ka[14 + 4 * n] : ka[4 * n]; kk[2 * n + 1] = up ? ka[15 + 4 * n] : ka[4 * n + 1];
        }
        bar_sync(4, 128);
        uint32_t o[6];
        #pragma unroll
        for (int n = 0; n < 3; n++) lds64(&o[2 * n], (xa ^ 512) + n * 1024);
        if (k < 5) {
          #pragma unroll
          for (int i = 0; i < 14; i++) sts128((i < 8 ? ea + (i >> 1) * 512 : ga + ((i - 8) >> 1) * 512) + (i & 1) * 128, F[4 * i], F[4 * i + 1], F[4 * i + 2], F[4 * i + 3]);
        }
        #pragma unroll
        for (int n = 0; n < 6; n++) kk[n] = (kk[n] + __uint_as_float(o[n])) * fac;
        if (t7 == 0) kk[0] += dsk;
        fac = facn; dsk = dskn;
        fence_async();
        bar_sync(4, 128);
        if (t7 == 0 && k == 2) TS(52);
        wg_fence();
        #pragma unroll
        for (int s = 0; s < 8; s++) if (s == 0 || k < 5) wg_ss48_tt_h(ka, dE + (s >> 1) * (BLK >> 4) + (s & 1) * 16, dG + (s >> 1) * (BLK >> 4) + (s & 1) * 16, s != 0);
        wg_commit();
        if (t7 == 0 && k == 2) TS(53);
      }
      wg_wait<0>();
      bar_sync(4, 128);
      if (t7 == 0) { mbar_arrive(BAR(BR_KGEN)); TS(41); }
    }
    mbar_wait(BAR(BR_U), 0);
    if (EN_ATT) mbar_wait(BAR(BR_GEMM), 0);
    if (t7 == 0) TS(42);
    #pragma unroll 1
    for (int pass = 1; pass >= 0; pass--) {
      const int k = pass ? w4 : 4;
      const uint32_t blk = sb + OFF_BLK + k * BLK, tb = blk + B_TBL + (uint32_t)((g - 2 * tq) * 4);
      float acc[16][4];
      zero<64>(&acc[0][0]);
      const int kl = 16 * (lane >> 4) + 2 * (lane & 7) + ((lane >> 3) & 1);
      {
        auto ubase = [&](int sh) { const int q = kl - 2 * sh; return blk + (uint32_t)((q * 16) ^ ((q * 2) & 0x70)); };
#define LDQ(A, sh) _Pragma("unroll") for (int m = 0; m < 4; m++) load_quad(A[m], tb + (16 + 16 * (sh) + 128 * m) * 4);
#define LDB(B, ub, h) _Pragma("unroll") for (int p = 0; p < 4; p++) ldsm4(B[p], ((ub) ^ ((p & 1) * 64)) + (4 * (h) + p) * 512);
#define MLO(A, B) _Pragma("unroll") for (int m = 0; m < 4; m++) _Pragma("unroll") for (int cc = 0; cc < 8; cc++) mma16816(acc[cc + m], A[m], &B[cc >> 1][(cc & 1) * 2]);
#define MHI(A, B) _Pragma("unroll") for (int m = 0; m < 4; m++) _Pragma("unroll") for (int cc = 0; cc < 8 - m; cc++) mma16816(acc[8 + cc + m], A[m], &B[cc >> 1][(cc & 1) * 2]);
        int p_ = pass ? 0 : w4;
        const int pe = pass ? 4 : w4 + 1;
        uint32_t A[4][4], A2[4][4], Bl[4][4], Bh[4][4];
        uint32_t ub = ubase(p_ + 4);
        LDQ(A, p_ + 4) LDB(Bl, ub, 0)
        #pragma unroll 1
        for (; p_ < pe; p_++) {
          LDB(Bh, ub, 1)
          MLO(A, Bl)
          ub = ubase(p_);
          LDQ(A2, p_) LDB(Bl, ub, 0)
          MHI(A, Bh)
          LDB(Bh, ub, 1)
          load_quad(A[0], tb + (16 + 512 + 16 * (p_ & 1)) * 4); load_quad(A[1], tb + (T_S + 16 * (p_ & 1)) * 4);
          MLO(A2, Bl)
          if (p_ < 2) {
            #pragma unroll
            for (int cc = 0; cc < 8; cc++) mma16816(acc[cc + 4], A[0], &Bl[cc >> 1][(cc & 1) * 2]);
            #pragma unroll
            for (int cc = 0; cc < 4; cc++) mma16816(acc[cc + 12], A[0], &Bh[cc >> 1][(cc & 1) * 2]);
            #pragma unroll
            for (int cc = 0; cc < 8; cc++) mma16816(acc[cc + 8], A[1], &Bl[cc >> 1][(cc & 1) * 2]);
          }
          const int pn = ((p_ + 1) & 3) + 4;
          ub = ubase(pn);
          LDQ(A, pn) LDB(Bl, ub, 0)
          MHI(A2, Bh)
        }
      }
      if (t7 == 0) TS(57 + 3 * pass);
      mbar_wait(BAR(BR_DRDY), 0);
      {
        const int ih = (lane >> 3) & 1;
        const uint32_t dl = blk + B_D + (uint32_t)(((lane >> 4) * 8 + (lane & 7)) * 16);
        const uint32_t d0_ = dl + ih * 1552, d8_ = dl + (ih ? 0 : 1536), d3_ = dl + B_D7 + ih * 1024;
        auto cls2 = [&](uint32_t da, uint32_t ta) {
          uint32_t B[6][2], A[6][4];
          #pragma unroll
          for (int e = 0; e < 6; e++) { B[e][0] = lds32v(ta + (e + 4) * 32); B[e][1] = lds32v(ta + (e + 3) * 32); }
          #pragma unroll
          for (int kk = 0; kk < 6; kk++) ldsm4t(A[kk], da + kk * 256);
          #pragma unroll
          for (int e = 0; e < 6; e++)
            #pragma unroll
            for (int kk = 0; kk < 6; kk++) if (2 * kk + e + 4 < 16) mma16816(acc[2 * kk + e + 4], A[kk], B[e]);
        };
        auto cls3 = [&](uint32_t da, uint32_t ta) {
          uint32_t B[8][2], A[4][4];
          #pragma unroll
          for (int e = 0; e < 8; e++) { B[e][0] = lds32v(ta + (e + 8) * 32); B[e][1] = lds32v(ta + (e + 7) * 32); }
          #pragma unroll
          for (int kk = 0; kk < 4; kk++) ldsm4t(A[kk], da + kk * 256);
          #pragma unroll
          for (int kk = 0; kk < 4; kk++)
            #pragma unroll
            for (int e = 0; e < 8; e++) if (2 * kk + e + 8 < 16) mma16816(acc[2 * kk + e + 8], A[kk], B[e]);
        };
        #pragma unroll 1
        for (int a = pass ? 0 : w4; a < (pass ? 4 : w4 + 1); a++) cls2(((a & 2) ? d8_ : d0_) + (a & 1) * B_D5, tb + (T_F2 + 48 * a - 32) * 4);
        #pragma unroll 1
        for (int b = pass ? 0 : (w4 & 1); b < (pass ? 2 : w4 - 1); b++) cls3(d3_ + b * 2048, tb + (T_F3 + 80 * b - 64) * 4);
      }
      if (t7 == 0) TS(58 + 3 * pass);
      const uint32_t ya = blk + (uint32_t)((kl * 16) ^ ((kl * 2) & 0x70));
#define STY(p) stsm4t((ya ^ (((p) & 1) * 64)) + (p) * 512, pack2(acc[2 * (p)][0], acc[2 * (p)][1]), pack2(acc[2 * (p)][2], acc[2 * (p)][3]), \
                      pack2(acc[2 * (p) + 1][0], acc[2 * (p) + 1][1]), pack2(acc[2 * (p) + 1][2], acc[2 * (p) + 1][3]))
      if (pass == 0) {
        const uint32_t xw = blk + 4096 + w4 * 4096 + lane * 16, xr = blk + 4096 + w4 * 1024 + lane * 16;
        #pragma unroll
        for (int h = 0; h < 2; h++) {
          bar_sync(4, 128);
          #pragma unroll
          for (int i = 0; i < 8; i++)
            sts128(xw + i * 512, __float_as_uint(acc[8 * h + i][0]), __float_as_uint(acc[8 * h + i][1]), __float_as_uint(acc[8 * h + i][2]), __float_as_uint(acc[8 * h + i][3]));
          bar_sync(4, 128);
          float y[8];
          #pragma unroll
          for (int i = 0; i < 8; i++) {
            uint32_t o[4]; lds128(o, xr + (i >> 1) * 4096 + (i & 1) * 512);
            #pragma unroll
            for (int e = 0; e < 4; e++) y[4 * (i & 1) + e] = i < 2 ? __uint_as_float(o[e]) : y[4 * (i & 1) + e] + __uint_as_float(o[e]);
          }
          stsm4t((ya ^ ((w4 & 1) * 64)) + (4 * h + w4) * 512, pack2(y[0], y[1]), pack2(y[2], y[3]), pack2(y[4], y[5]), pack2(y[6], y[7]));
        }
      } else {
        __syncwarp();
        #pragma unroll
        for (int p = 0; p < 8; p++) STY(p);
      }
      if (t7 == 0 && !pass) TS(55);
      fence_async();
      mbar_arrive(BAR(BR_Y + 1) - 8 * pass);
      if (t7 == 0) TS(59 + 3 * pass);
    }
    if (t7 == 0) DUMP(40, 64);
    }
  }
}

typedef CUresult (*EncFn)(CUtensorMap*, CUtensorMapDataType, cuuint32_t, void*, const cuuint64_t*, const cuuint64_t*, const cuuint32_t*,
                          const cuuint32_t*, CUtensorMapInterleave, CUtensorMapSwizzle, CUtensorMapL2promotion, CUtensorMapFloatOOBfill);
static void mkmap(EncFn enc, CUtensorMap* m, const void* base, int rank, const cuuint64_t* dims, const cuuint64_t* strides, const cuuint32_t* box, CUtensorMapSwizzle swz) {
  cuuint32_t es[5] = {1, 1, 1, 1, 1};
  enc(m, CU_TENSOR_MAP_DATA_TYPE_BFLOAT16, rank, const_cast<void*>(base), dims, strides, box, es, CU_TENSOR_MAP_INTERLEAVE_NONE, swz,
      CU_TENSOR_MAP_L2_PROMOTION_L2_128B, CU_TENSOR_MAP_FLOAT_OOB_FILL_NONE);
}

extern "C" void kernel_launch(void* const* d_in, const int* in_sizes, int n_in, void* d_out, int out_size) {
  void* fn = nullptr; cudaDriverEntryPointQueryResult qr;
  cudaGetDriverEntryPoint("cuTensorMapEncodeTiled", &fn, cudaEnableDefault, &qr);
  EncFn enc = (EncFn)fn;
  void* uy = nullptr; cudaGetSymbolAddress(&uy, g_uy);
  const cuuint64_t dx[2] = {640, 2048}, sx[1] = {1280};
  const cuuint32_t bx[2] = {64, 128}, bu[2] = {80, 128};
  const cuuint64_t dw[3] = {640, 640, 3}, sw[2] = {3840, 1280};
  const cuuint32_t br[3] = {16, 32, 3};
  const cuuint64_t dwa[4] = {64, 640, 10, 3}, swa[3] = {3840, 128, 1280}, dwb[4] = {32, 640, 20, 3}, swb[3] = {3840, 64, 1280};
  const cuuint32_t bwa[4] = {64, 32, 1, 3}, bwb[4] = {32, 32, 2, 3};
  const cuuint64_t dwo[2] = {640, 640};
  const cuuint32_t bwo[2] = {64, 80}, bo64[2] = {64, 64}, bo16[2] = {16, 64};
  const cuuint64_t dsa[2] = {2048, 1280}, ssa[1] = {4096};
  const cuuint32_t bsa[2] = {64, 80};
  const cuuint64_t dsb[2] = {64, 40960}, ssb[1] = {128};
  const cuuint32_t bsb[2] = {64, 32};
  const cuuint64_t dout[2] = {1280, 2048}, sout[1] = {2560};
  Params prm;
  mkmap(enc, &prm.m[M_X], d_in[7], 2, dx, sx, bx, CU_TENSOR_MAP_SWIZZLE_128B);
  mkmap(enc, &prm.m[M_W128], d_in[8], 4, dwa, swa, bwa, CU_TENSOR_MAP_SWIZZLE_128B);
  mkmap(enc, &prm.m[M_W64], d_in[8], 4, dwb, swb, bwb, CU_TENSOR_MAP_SWIZZLE_64B);
  mkmap(enc, &prm.m[M_WR], d_in[8], 3, dw, sw, br, CU_TENSOR_MAP_SWIZZLE_32B);
  mkmap(enc, &prm.m[M_WO], d_in[9], 2, dwo, sx, bwo, CU_TENSOR_MAP_SWIZZLE_128B);
  mkmap(enc, &prm.m[M_O64], d_out, 2, dout, sout, bo64, CU_TENSOR_MAP_SWIZZLE_128B);
  mkmap(enc, &prm.m[M_O16], d_out, 2, dout, sout, bo16, CU_TENSOR_MAP_SWIZZLE_NONE);
  mkmap(enc, &prm.m[M_SA], uy, 2, dsa, ssa, bsa, CU_TENSOR_MAP_SWIZZLE_128B);
  mkmap(enc, &prm.m[M_SB], uy, 2, dsb, ssb, bsb, CU_TENSOR_MAP_SWIZZLE_128B);
  mkmap(enc, &prm.m[M_OUT], d_out, 2, dout, sout, bu, CU_TENSOR_MAP_SWIZZLE_NONE);
  prm.u = (const __nv_bfloat16*)d_in[0]; prm.wo = (const __nv_bfloat16*)d_in[9];
  for (int i = 0; i < 4; i++) prm.par[i] = (const __nv_bfloat16*)d_in[1 + i];
  prm.logdt = (const __nv_bfloat16*)d_in[5]; prm.dskip = (const __nv_bfloat16*)d_in[6];
  cudaFuncSetAttribute(fused_kernel, cudaFuncAttributeMaxDynamicSharedMemorySize, SMEM_BYTES);
  cudaLaunchConfig_t cfg = {};
  cfg.gridDim = dim3(128); cfg.blockDim = dim3(512); cfg.dynamicSmemBytes = SMEM_BYTES; cfg.stream = cudaStreamPerThread;
  cudaLaunchAttribute at[1];
  at[0].id = cudaLaunchAttributeClusterDimension; at[0].val.clusterDim.x = 2; at[0].val.clusterDim.y = 1; at[0].val.clusterDim.z = 1;
  cfg.attrs = at; cfg.numAttrs = 1;
  cudaLaunchKernelEx(&cfg, fused_kernel, prm);
}
```

```cpp
#include <cuda_runtime.h>
#include <cuda_bf16.h>
#include <cuda_fp16.h>
#include <cuda.h>
#include <stdint.h>

#define U_AFTER 9
#define U_NPF 5
#define EN_ATT 1
#define EN_SSM 1

__device__ __align__(1024) __nv_bfloat16 g_uy[2 * 640 * 2048];
__device__ __align__(128) uint4 g_kvp[8 * 16 * 240];
__device__ __align__(128) uint4 g_o[128 * 1280];
__device__ __align__(128) unsigned g_flag[4 * 128 * 32];
__device__ unsigned g_epoch[128];
#define TS(i) do {} while (0)
#define DUMP(lo, hi) do {} while (0)
#define FIXCNT

constexpr uint32_t SB0 = 1024;
constexpr uint32_t W_SLOT = 15360, OFF_X = 76800;
constexpr uint32_t OFF_WOR = 81920, OFF_KVP = 10240, OFF_KVS = 71680, OFF_PK = 10240, OFF_V = 30720, OFF_EXTRA = 102400, OFF_KVB = OFF_EXTRA;
constexpr uint32_t OFF_BAR = 125952, OFF_BLK = 128000, BLK = 20480;
constexpr uint32_t B_D = 4096, B_D5 = 3088, B_D7 = 6176, B_D9 = 8224, B_TBL = 14400, B_SP = 18432;
constexpr int T_S = 576, T_F2 = 624, T_F3 = 816;
constexpr uint32_t SMEM_BYTES = OFF_BLK + 5 * BLK;
enum { BR_FULL = 0, BR_WO = 5, BR_PUB = 7, BR_KVP = 8, BR_U = 9, BR_SUM = 10, BR_GEMM = 11, BR_YIN = 13, BR_EPOCH = 14,
       BR_FREE = 15, BR_RETRY = 17, BR_OFULL = 18, BR_EMPTY = 26, BR_KG1 = 31, BR_OEMPTY = 32, BR_Y = 39, BR_OSTG = 41, BR_KGEN = 42, BR_COUNT = 44 };
constexpr uint32_t OFF_EPOCH = OFF_BAR + 8 * BR_COUNT;
enum { M_X, M_W128, M_W64, M_WR, M_WO, M_O64, M_O16, M_SA, M_SB, M_OUT, M_COUNT };

__device__ __forceinline__ long long clk64() { long long t; asm volatile("mov.u64 %0, %%clock64;" : "=l"(t) :: "memory"); return t; }
__device__ __forceinline__ uint32_t smem_u32(const void* p) { return (uint32_t)__cvta_generic_to_shared(p); }
__host__ __device__ constexpr uint64_t mkdesc(uint32_t addr, uint32_t lbo, uint32_t sbo, uint32_t swz) {
  return (uint64_t)((addr & 0x3FFFF) >> 4) | ((uint64_t)(lbo >> 4) << 16) | ((uint64_t)(sbo >> 4) << 32) | ((uint64_t)swz << 62);
}
__device__ __forceinline__ uint64_t desc2(uint32_t lo, uint32_t hi) { uint64_t d; asm("mov.b64 %0, {%1, %2};" : "=l"(d) : "r"(lo), "r"(hi)); return d; }
__device__ __forceinline__ void mbar_init(uint32_t bar, uint32_t cnt) { asm volatile("mbarrier.init.shared::cta.b64 [%0], %1;" :: "r"(bar), "r"(cnt) : "memory"); }
__device__ __forceinline__ void mbar_expect_tx(uint32_t bar, uint32_t bytes) { asm volatile("mbarrier.arrive.expect_tx.shared::cta.b64 _, [%0], %1;" :: "r"(bar), "r"(bytes) : "memory"); }
__device__ __forceinline__ void mbar_arrive(uint32_t bar) { asm volatile("mbarrier.arrive.shared::cta.b64 _, [%0];" :: "r"(bar) : "memory"); }
__device__ __forceinline__ void mbar_wait(uint32_t bar, uint32_t parity) {
  asm volatile("{\n.reg .pred p;\n.reg .u32 c;\nmov.u32 c, 0;\n"
    "WL:\nmbarrier.try_wait.parity.shared::cta.b64 p, [%0], %1;\n@p bra WD;\n"
    "add.u32 c, c, 1;\nsetp.lt.u32 p, c, 200000;\n@p bra WL;\nWD:\n}" :: "r"(bar), "r"(parity) : "memory");
}
__device__ __forceinline__ void poll_all(const unsigned* p, unsigned val) {
  asm volatile("{\n.reg .pred p;\n.reg .u32 c, v;\nmov.u32 c, 0;\n"
    "PL:\nld.relaxed.gpu.global.u32 v, [%0];\nsetp.eq.u32 p, v, %1;\nvote.sync.all.pred p, p, 0xffffffff;\n@p bra PD;\n"
    "add.u32 c, c, 1;\nsetp.lt.u32 p, c, 100000;\n@p bra PL;\nPD:\n}" :: "l"(p), "r"(val) : "memory");
}
__device__ __forceinline__ void poll_all_acq(const unsigned* p, unsigned val) {
  asm volatile("{\n.reg .pred p;\n.reg .u32 c, v;\nmov.u32 c, 0;\n"
    "PL:\nld.acquire.gpu.global.u32 v, [%0];\nsetp.eq.u32 p, v, %1;\nvote.sync.all.pred p, p, 0xffffffff;\n@p bra PD;\n"
    "add.u32 c, c, 1;\nsetp.lt.u32 p, c, 100000;\n@p bra PL;\nPD:\n}" :: "l"(p), "r"(val) : "memory");
}
__device__ __forceinline__ unsigned poll_bit(const unsigned* p, unsigned val, unsigned mask) {
  unsigned bal;
  asm volatile("{\n.reg .pred p;\n.reg .u32 c, v;\nmov.u32 c, 0;\n"
    "PL:\nld.relaxed.gpu.global.u32 v, [%1];\nsetp.eq.u32 p, v, %2;\nvote.sync.ballot.b32 %0, p, 0xffffffff;\n"
    "and.b32 v, %0, %3;\nsetp.ne.u32 p, v, 0;\n@p bra PD;\n"
    "add.u32 c, c, 1;\nsetp.lt.u32 p, c, 100000;\n@p bra PL;\nPD:\n}" : "=&r"(bal) : "l"(p), "r"(val), "r"(mask) : "memory");
  return bal;
}
__device__ __forceinline__ void fix128_w0(uint32_t* v, const void* p, uint32_t tag, uint32_t mask) {
  asm volatile("{\n.reg .pred p;\n.reg .u32 c, x;\n.reg .b128 t;\n.reg .b64 lo, hi;\nmov.u32 c, 0;\n"
    "FL:\nxor.b32 x, %0, %5;\nand.b32 x, x, %6;\nsetp.eq.u32 p, x, 0;\n@p bra FD;\n"
    "ld.relaxed.gpu.global.b128 t, [%4];\nmov.b128 {lo, hi}, t;\nmov.b64 {%0, %1}, lo;\nmov.b64 {%2, %3}, hi;\n"
    "add.u32 c, c, 1;\nsetp.lt.u32 p, c, 100000;\n@p bra FL;\nFD:\n}"
    : "+r"(v[0]), "+r"(v[1]), "+r"(v[2]), "+r"(v[3]) : "l"(p), "r"(tag), "r"(mask) : "memory");
}
__device__ __forceinline__ void fix128_w3(uint32_t* v, const void* p, uint32_t tag, uint32_t mask) {
  asm volatile("{\n.reg .pred p;\n.reg .u32 c, x;\n.reg .b128 t;\n.reg .b64 lo, hi;\nmov.u32 c, 0;\n"
    "FL:\nxor.b32 x, %3, %5;\nand.b32 x, x, %6;\nsetp.eq.u32 p, x, 0;\n@p bra FD;\n"
    "ld.relaxed.gpu.global.b128 t, [%4];\nmov.b128 {lo, hi}, t;\nmov.b64 {%0, %1}, lo;\nmov.b64 {%2, %3}, hi;\n"
    "add.u32 c, c, 1;\nsetp.lt.u32 p, c, 100000;\n@p bra FL;\nFD:\n}"
    : "+r"(v[0]), "+r"(v[1]), "+r"(v[2]), "+r"(v[3]) : "l"(p), "r"(tag), "r"(mask) : "memory");
}
__device__ __forceinline__ void fence_acq() { asm volatile("fence.acq_rel.gpu;" ::: "memory"); }
__device__ __forceinline__ bool elect_one() {
  uint32_t p; asm volatile("{\n.reg .pred P;\nelect.sync _|P, 0xffffffff;\nselp.u32 %0, 1, 0, P;\n}" : "=r"(p)); return p;
}
__device__ __forceinline__ void bar_sync(int id, int n) { asm volatile("bar.sync %0, %1;" :: "r"(id), "r"(n) : "memory"); }
__device__ __forceinline__ void fence_async() { asm volatile("fence.proxy.async.shared::cta;" ::: "memory"); }
__device__ __forceinline__ void fence_async_g() { asm volatile("fence.proxy.async.global;" ::: "memory"); }
__device__ __forceinline__ void tma2d(uint32_t dst, const CUtensorMap* m, uint32_t bar, int c0, int c1) {
  asm volatile("cp.async.bulk.tensor.2d.shared::cluster.global.mbarrier::complete_tx::bytes [%0], [%1, {%3, %4}], [%2];"
    :: "r"(dst), "l"(m), "r"(bar), "r"(c0), "r"(c1) : "memory");
}
__device__ __forceinline__ void tma3d(uint32_t dst, const CUtensorMap* m, uint32_t bar, int c0, int c1, int c2) {
  asm volatile("cp.async.bulk.tensor.3d.shared::cluster.global.mbarrier::complete_tx::bytes [%0], [%1, {%3, %4, %5}], [%2];"
    :: "r"(dst), "l"(m), "r"(bar), "r"(c0), "r"(c1), "r"(c2) : "memory");
}
__device__ __forceinline__ void tma4d(uint32_t dst, const CUtensorMap* m, uint32_t bar, int c0, int c1, int c2, int c3) {
  asm volatile("cp.async.bulk.tensor.4d.shared::cluster.global.mbarrier::complete_tx::bytes [%0], [%1, {%3, %4, %5, %6}], [%2];"
    :: "r"(dst), "l"(m), "r"(bar), "r"(c0), "r"(c1), "r"(c2), "r"(c3) : "memory");
}
__device__ __forceinline__ void tma2d_st(const CUtensorMap* m, uint32_t src, int c0, int c1) {
  asm volatile("cp.async.bulk.tensor.2d.global.shared::cta.bulk_group [%0, {%2, %3}], [%1];"
    :: "l"(m), "r"(src), "r"(c0), "r"(c1) : "memory");
}
__device__ __forceinline__ void bulk_ld(uint32_t dst, const void* src, uint32_t bytes, uint32_t bar) {
  asm volatile("cp.async.bulk.shared::cluster.global.mbarrier::complete_tx::bytes [%0], [%1], %2, [%3];"
    :: "r"(dst), "l"(src), "r"(bytes), "r"(bar) : "memory");
}
__device__ __forceinline__ void bulk_st(void* dst, uint32_t src, uint32_t bytes) {
  asm volatile("cp.async.bulk.global.shared::cta.bulk_group [%0], [%1], %2;" :: "l"(dst), "r"(src), "r"(bytes) : "memory");
}
__device__ __forceinline__ void bulk_commit() { asm volatile("cp.async.bulk.commit_group;" ::: "memory"); }
__device__ __forceinline__ void bulk_wait0() { asm volatile("cp.async.bulk.wait_group 0;" ::: "memory"); }
__device__ __forceinline__ void bulk_wait0_read() { asm volatile("cp.async.bulk.wait_group.read 0;" ::: "memory"); }
__device__ __forceinline__ unsigned ld_rlx(const unsigned* p) { unsigned v; asm volatile("ld.relaxed.gpu.global.u32 %0, [%1];" : "=r"(v) : "l"(p) : "memory"); return v; }
__device__ __forceinline__ unsigned ld_acq(const unsigned* p) { unsigned v; asm volatile("ld.acquire.gpu.global.u32 %0, [%1];" : "=r"(v) : "l"(p) : "memory"); return v; }
__device__ __forceinline__ void st_rlx(unsigned* p, unsigned v) { asm volatile("st.relaxed.gpu.global.u32 [%0], %1;" :: "l"(p), "r"(v) : "memory"); }
__device__ __forceinline__ void st_rel(unsigned* p, unsigned v) { asm volatile("st.release.gpu.global.u32 [%0], %1;" :: "l"(p), "r"(v) : "memory"); }
__device__ __forceinline__ void ld128_rlx(uint32_t* v, const void* p) {
  asm volatile("{\n.reg .b128 t;\n.reg .b64 lo, hi;\nld.relaxed.gpu.global.b128 t, [%4];\nmov.b128 {lo, hi}, t;\n"
    "mov.b64 {%0, %1}, lo;\nmov.b64 {%2, %3}, hi;\n}" : "=r"(v[0]), "=r"(v[1]), "=r"(v[2]), "=r"(v[3]) : "l"(p) : "memory");
}
__device__ __forceinline__ void st128_rlx(void* p, const uint32_t* v) {
  asm volatile("{\n.reg .b128 t;\n.reg .b64 lo, hi;\nmov.b64 lo, {%1, %2};\nmov.b64 hi, {%3, %4};\nmov.b128 t, {lo, hi};\n"
    "st.relaxed.gpu.global.b128 [%0], t;\n}" :: "l"(p), "r"(v[0]), "r"(v[1]), "r"(v[2]), "r"(v[3]) : "memory");
}
__device__ __forceinline__ uint32_t lds32(uint32_t a) { uint32_t v; asm volatile("ld.shared.u32 %0, [%1];" : "=r"(v) : "r"(a) : "memory"); return v; }
__device__ __forceinline__ uint32_t lds32v(uint32_t a) { uint32_t v; asm volatile("ld.volatile.shared.u32 %0, [%1];" : "=r"(v) : "r"(a) : "memory"); return v; }
__device__ __forceinline__ uint32_t cpa(uint32_t a, uint32_t one) { uint32_t v; asm volatile("mul.lo.u32 %0, %1, %2;" : "=r"(v) : "r"(a), "r"(one)); return v; }
__device__ __forceinline__ uint32_t cpb(uint32_t a, uint32_t zero) { uint32_t v; asm volatile("or.b32 %0, %1, %2;" : "=r"(v) : "r"(a), "r"(zero)); return v; }
__device__ __forceinline__ uint32_t lds16(uint32_t a) { uint16_t v; asm volatile("ld.shared.u16 %0, [%1];" : "=h"(v) : "r"(a) : "memory"); return v; }
__device__ __forceinline__ float ldsf(uint32_t a) { float v; asm volatile("ld.shared.f32 %0, [%1];" : "=f"(v) : "r"(a) : "memory"); return v; }
__device__ __forceinline__ void lds128(uint32_t* v, uint32_t a) { asm volatile("ld.shared.v4.u32 {%0,%1,%2,%3}, [%4];" : "=r"(v[0]), "=r"(v[1]), "=r"(v[2]), "=r"(v[3]) : "r"(a) : "memory"); }
__device__ __forceinline__ void sts32(uint32_t a, uint32_t v) { asm volatile("st.shared.u32 [%0], %1;" :: "r"(a), "r"(v) : "memory"); }
__device__ __forceinline__ void sts16(uint32_t a, uint32_t v) { asm volatile("st.shared.u16 [%0], %1;" :: "r"(a), "h"((uint16_t)v) : "memory"); }
__device__ __forceinline__ void sts64f(uint32_t a, float x, float y) { asm volatile("st.shared.v2.f32 [%0], {%1,%2};" :: "r"(a), "f"(x), "f"(y) : "memory"); }
__device__ __forceinline__ void sts128(uint32_t a, uint32_t x, uint32_t y, uint32_t z, uint32_t w) { asm volatile("st.shared.v4.u32 [%0], {%1,%2,%3,%4};" :: "r"(a), "r"(x), "r"(y), "r"(z), "r"(w) : "memory"); }
__device__ __forceinline__ void stsm4(uint32_t a, uint32_t r0, uint32_t r1, uint32_t r2, uint32_t r3) {
  asm volatile("stmatrix.sync.aligned.m8n8.x4.shared.b16 [%0], {%1,%2,%3,%4};" :: "r"(a), "r"(r0), "r"(r1), "r"(r2), "r"(r3) : "memory");
}
__device__ __forceinline__ void stsm4t(uint32_t a, uint32_t r0, uint32_t r1, uint32_t r2, uint32_t r3) {
  asm volatile("stmatrix.sync.aligned.m8n8.x4.trans.shared.b16 [%0], {%1,%2,%3,%4};" :: "r"(a), "r"(r0), "r"(r1), "r"(r2), "r"(r3) : "memory");
}
__device__ __forceinline__ void ldsm4t(uint32_t* r, uint32_t a) {
  asm volatile("ldmatrix.sync.aligned.m8n8.x4.trans.shared.b16 {%0,%1,%2,%3}, [%4];" : "=r"(r[0]), "=r"(r[1]), "=r"(r[2]), "=r"(r[3]) : "r"(a) : "memory");
}
__device__ __forceinline__ void ldsm4(uint32_t* r, uint32_t a) {
  asm volatile("ldmatrix.sync.aligned.m8n8.x4.shared.b16 {%0,%1,%2,%3}, [%4];" : "=r"(r[0]), "=r"(r[1]), "=r"(r[2]), "=r"(r[3]) : "r"(a) : "memory");
}
__device__ __forceinline__ void mma16816(float* d, const uint32_t* a, const uint32_t* b) {
  asm volatile("mma.sync.aligned.m16n8k16.row.col.f32.bf16.bf16.f32 {%0,%1,%2,%3}, {%4,%5,%6,%7}, {%8,%9}, {%0,%1,%2,%3};"
    : "+f"(d[0]), "+f"(d[1]), "+f"(d[2]), "+f"(d[3]) : "r"(a[0]), "r"(a[1]), "r"(a[2]), "r"(a[3]), "r"(b[0]), "r"(b[1]));
}
__device__ __forceinline__ uint32_t pack2(float lo, float hi) { uint32_t r; asm("cvt.rn.bf16x2.f32 %0, %1, %2;" : "=r"(r) : "f"(hi), "f"(lo)); return r; }
__device__ __forceinline__ uint32_t packh(float lo, float hi) { uint32_t r; asm("cvt.rn.f16x2.f32 %0, %1, %2;" : "=r"(r) : "f"(hi), "f"(lo)); return r; }
__device__ __forceinline__ uint32_t hcmul(uint32_t x, uint32_t zp, uint32_t zq) {
  const __half2 xx = *reinterpret_cast<__half2*>(&x);
  const __half2 r = __hfma2(__high2half2(xx), *reinterpret_cast<__half2*>(&zq), __hmul2(__low2half2(xx), *reinterpret_cast<__half2*>(&zp)));
  return *reinterpret_cast<const uint32_t*>(&r);
}
__device__ __forceinline__ void hcm2(uint32_t xr, uint32_t xi, uint32_t z, uint32_t& pr, uint32_t& pi) {
  const __half2 a = *reinterpret_cast<__half2*>(&xr), b = *reinterpret_cast<__half2*>(&xi), zz = *reinterpret_cast<__half2*>(&z);
  const __half2 re = __hfma2(__hneg2(b), __high2half2(zz), __hmul2(a, __low2half2(zz)));
  const __half2 im = __hfma2(a, __high2half2(zz), __hmul2(b, __low2half2(zz)));
  pr = *reinterpret_cast<const uint32_t*>(&re); pi = *reinterpret_cast<const uint32_t*>(&im);
}
__device__ __forceinline__ void sts64(uint32_t a, uint32_t x, uint32_t y) { asm volatile("st.shared.v2.u32 [%0], {%1,%2};" :: "r"(a), "r"(x), "r"(y) : "memory"); }
__device__ __forceinline__ void lds64(uint32_t* v, uint32_t a) { asm volatile("ld.shared.v2.u32 {%0,%1}, [%2];" : "=r"(v[0]), "=r"(v[1]) : "r"(a) : "memory"); }
__device__ __forceinline__ float bf_lo(uint32_t v) { return __uint_as_float(v << 16); }
__device__ __forceinline__ float bf_hi(uint32_t v) { return __uint_as_float(v & 0xffff0000u); }
__device__ __forceinline__ float bf_round(float x) { return bf_lo(pack2(x, 0.f)); }
__device__ __forceinline__ float ex2(float x) { float r; asm("ex2.approx.ftz.f32 %0, %1;" : "=f"(r) : "f"(x)); return r; }
__device__ __forceinline__ float phi(float t, float l2e = 1.44269504089f) { float e = ex2(t * l2e); return (t > 0.f ? t + 1.f : e) + 1e-6f; }
__device__ __forceinline__ void wg_fence() { asm volatile("wgmma.fence.sync.aligned;" ::: "memory"); }
__device__ __forceinline__ void wg_commit() { asm volatile("wgmma.commit_group.sync.aligned;" ::: "memory"); }
template <int N> __device__ __forceinline__ void wg_wait() { asm volatile("wgmma.wait_group.sync.aligned %0;" :: "n"(N) : "memory"); }
template <int N> __device__ __forceinline__ void pin(float* a) {
  #pragma unroll
  for (int i = 0; i < N; i++) asm volatile("" : "+f"(a[i]) :: "memory");
}
__device__ __forceinline__ int opaque(int v) { asm volatile("" : "+r"(v)); return v; }
template <int N> __device__ __forceinline__ void zero(float* a) {
  #pragma unroll
  for (int i = 0; i < N; i++) asm volatile("mov.b32 %0, 0;" : "=f"(a[i]));
}
template <int N> __device__ __forceinline__ void pinu(uint32_t* a) {
  #pragma unroll
  for (int i = 0; i < N; i++) asm volatile("" : "+r"(a[i]) :: "memory");
}
__device__ __forceinline__ void cexp_t(float lg2mag, float turns, float& re, float& im) {
  float m = ex2(lg2mag);
  float fr = (turns - __fadd_rn(__fadd_rn(turns, 12582912.f), -12582912.f)) * 6.283185307f;
  re = m * __cosf(fr); im = m * __sinf(fr);
}
__device__ __forceinline__ void cmul(float ar, float ai, float br, float bi, float& cr, float& ci) {
  cr = fmaf(ar, br, -ai * bi); ci = fmaf(ar, bi, ai * br);
}

__device__ __forceinline__ void wg_ss192_tb(float* d, uint64_t da, uint64_t db, int scale_d) {
  asm volatile("{\n.reg .pred p;\nsetp.ne.b32 p, %98, 0;\n"
    "wgmma.mma_async.sync.aligned.m64n192k16.f32.bf16.bf16 "
    "{%0, %1, %2, %3, %4, %5, %6, %7, %8, %9, %10, %11, %12, %13, %14, %15, %16, %17, %18, %19, %20, %21, %22, %23, %24, %25, %26, %27, %28, %29, %30, %31, %32, %33, %34, %35, %36, %37, %38, %39, %40, %41, %42, %43, %44, %45, %46, %47, %48, %49, %50, %51, %52, %53, %54, %55, %56, %57, %58, %59, %60, %61, %62, %63, %64, %65, %66, %67, %68, %69, %70, %71, %72, %73, %74, %75, %76, %77, %78, %79, %80, %81, %82, %83, %84, %85, %86, %87, %88, %89, %90, %91, %92, %93, %94, %95}, %96, %97, p, 1, 1, 0, 1;\n}\n"
    : "+f"(d[0]), "+f"(d[1]), "+f"(d[2]), "+f"(d[3]), "+f"(d[4]), "+f"(d[5]), "+f"(d[6]), "+f"(d[7]), "+f"(d[8]), "+f"(d[9]), "+f"(d[10]), "+f"(d[11]), "+f"(d[12]), "+f"(d[13]), "+f"(d[14]), "+f"(d[15]), "+f"(d[16]), "+f"(d[17]), "+f"(d[18]), "+f"(d[19]), "+f"(d[20]), "+f"(d[21]), "+f"(d[22]), "+f"(d[23]), "+f"(d[24]), "+f"(d[25]), "+f"(d[26]), "+f"(d[27]), "+f"(d[28]), "+f"(d[29]), "+f"(d[30]), "+f"(d[31]), "+f"(d[32]), "+f"(d[33]), "+f"(d[34]), "+f"(d[35]), "+f"(d[36]), "+f"(d[37]), "+f"(d[38]), "+f"(d[39]), "+f"(d[40]), "+f"(d[41]), "+f"(d[42]), "+f"(d[43]), "+f"(d[44]), "+f"(d[45]), "+f"(d[46]), "+f"(d[47]), "+f"(d[48]), "+f"(d[49]), "+f"(d[50]), "+f"(d[51]), "+f"(d[52]), "+f"(d[53]), "+f"(d[54]), "+f"(d[55]), "+f"(d[56]), "+f"(d[57]), "+f"(d[58]), "+f"(d[59]), "+f"(d[60]), "+f"(d[61]), "+f"(d[62]), "+f"(d[63]), "+f"(d[64]), "+f"(d[65]), "+f"(d[66]), "+f"(d[67]), "+f"(d[68]), "+f"(d[69]), "+f"(d[70]), "+f"(d[71]), "+f"(d[72]), "+f"(d[73]), "+f"(d[74]), "+f"(d[75]), "+f"(d[76]), "+f"(d[77]), "+f"(d[78]), "+f"(d[79]), "+f"(d[80]), "+f"(d[81]), "+f"(d[82]), "+f"(d[83]), "+f"(d[84]), "+f"(d[85]), "+f"(d[86]), "+f"(d[87]), "+f"(d[88]), "+f"(d[89]), "+f"(d[90]), "+f"(d[91]), "+f"(d[92]), "+f"(d[93]), "+f"(d[94]), "+f"(d[95])
    : "l"(da), "l"(db), "r"(scale_d));
}
__device__ __forceinline__ void wg_ss48_tb(float* d, uint64_t da, uint64_t db, int scale_d) {
  asm volatile("{\n.reg .pred p;\nsetp.ne.b32 p, %26, 0;\n"
    "wgmma.mma_async.sync.aligned.m64n48k16.f32.bf16.bf16 "
    "{%0, %1, %2, %3, %4, %5, %6, %7, %8, %9, %10, %11, %12, %13, %14, %15, %16, %17, %18, %19, %20, %21, %22, %23}, %24, %25, p, 1, 1, 0, 1;\n}\n"
    : "+f"(d[0]), "+f"(d[1]), "+f"(d[2]), "+f"(d[3]), "+f"(d[4]), "+f"(d[5]), "+f"(d[6]), "+f"(d[7]), "+f"(d[8]), "+f"(d[9]), "+f"(d[10]), "+f"(d[11]), "+f"(d[12]), "+f"(d[13]), "+f"(d[14]), "+f"(d[15]), "+f"(d[16]), "+f"(d[17]), "+f"(d[18]), "+f"(d[19]), "+f"(d[20]), "+f"(d[21]), "+f"(d[22]), "+f"(d[23])
    : "l"(da), "l"(db), "r"(scale_d));
}
__device__ __forceinline__ void wg_ss48_tt(float* d, uint64_t da, uint64_t db, int scale_d) {
  asm volatile("{\n.reg .pred p;\nsetp.ne.b32 p, %26, 0;\n"
    "wgmma.mma_async.sync.aligned.m64n48k16.f32.bf16.bf16 "
    "{%0, %1, %2, %3, %4, %5, %6, %7, %8, %9, %10, %11, %12, %13, %14, %15, %16, %17, %18, %19, %20, %21, %22, %23}, %24, %25, p, 1, 1, 1, 1;\n}\n"
    : "+f"(d[0]), "+f"(d[1]), "+f"(d[2]), "+f"(d[3]), "+f"(d[4]), "+f"(d[5]), "+f"(d[6]), "+f"(d[7]), "+f"(d[8]), "+f"(d[9]), "+f"(d[10]), "+f"(d[11]), "+f"(d[12]), "+f"(d[13]), "+f"(d[14]), "+f"(d[15]), "+f"(d[16]), "+f"(d[17]), "+f"(d[18]), "+f"(d[19]), "+f"(d[20]), "+f"(d[21]), "+f"(d[22]), "+f"(d[23])
    : "l"(da), "l"(db), "r"(scale_d));
}
__device__ __forceinline__ void wg_rs88_tb(float* d, const uint32_t* a, uint64_t db, int scale_d) {
  asm volatile("{\n.reg .pred p;\nsetp.ne.b32 p, %49, 0;\n"
    "wgmma.mma_async.sync.aligned.m64n88k16.f32.bf16.bf16 "
    "{%0, %1, %2, %3, %4, %5, %6, %7, %8, %9, %10, %11, %12, %13, %14, %15, %16, %17, %18, %19, %20, %21, %22, %23, %24, %25, %26, %27, %28, %29, %30, %31, %32, %33, %34, %35, %36, %37, %38, %39, %40, %41, %42, %43}, {%44, %45, %46, %47}, %48, p, 1, 1, 1;\n}\n"
    : "+f"(d[0]), "+f"(d[1]), "+f"(d[2]), "+f"(d[3]), "+f"(d[4]), "+f"(d[5]), "+f"(d[6]), "+f"(d[7]), "+f"(d[8]), "+f"(d[9]), "+f"(d[10]), "+f"(d[11]), "+f"(d[12]), "+f"(d[13]), "+f"(d[14]), "+f"(d[15]), "+f"(d[16]), "+f"(d[17]), "+f"(d[18]), "+f"(d[19]), "+f"(d[20]), "+f"(d[21]), "+f"(d[22]), "+f"(d[23]), "+f"(d[24]), "+f"(d[25]), "+f"(d[26]), "+f"(d[27]), "+f"(d[28]), "+f"(d[29]), "+f"(d[30]), "+f"(d[31]), "+f"(d[32]), "+f"(d[33]), "+f"(d[34]), "+f"(d[35]), "+f"(d[36]), "+f"(d[37]), "+f"(d[38]), "+f"(d[39]), "+f"(d[40]), "+f"(d[41]), "+f"(d[42]), "+f"(d[43])
    : "r"(a[0]), "r"(a[1]), "r"(a[2]), "r"(a[3]), "l"(db), "r"(scale_d));
}
__device__ __forceinline__ void wg_ss80_tb(float* d, uint64_t da, uint64_t db, int scale_d) {
  asm volatile("{\n.reg .pred p;\nsetp.ne.b32 p, %42, 0;\n"
    "wgmma.mma_async.sync.aligned.m64n80k16.f32.bf16.bf16 "
    "{%0, %1, %2, %3, %4, %5, %6, %7, %8, %9, %10, %11, %12, %13, %14, %15, %16, %17, %18, %19, %20, %21, %22, %23, %24, %25, %26, %27, %28, %29, %30, %31, %32, %33, %34, %35, %36, %37, %38, %39}, %40, %41, p, 1, 1, 0, 1;\n}\n"
    : "+f"(d[0]), "+f"(d[1]), "+f"(d[2]), "+f"(d[3]), "+f"(d[4]), "+f"(d[5]), "+f"(d[6]), "+f"(d[7]), "+f"(d[8]), "+f"(d[9]), "+f"(d[10]), "+f"(d[11]), "+f"(d[12]), "+f"(d[13]), "+f"(d[14]), "+f"(d[15]), "+f"(d[16]), "+f"(d[17]), "+f"(d[18]), "+f"(d[19]), "+f"(d[20]), "+f"(d[21]), "+f"(d[22]), "+f"(d[23]), "+f"(d[24]), "+f"(d[25]), "+f"(d[26]), "+f"(d[27]), "+f"(d[28]), "+f"(d[29]), "+f"(d[30]), "+f"(d[31]), "+f"(d[32]), "+f"(d[33]), "+f"(d[34]), "+f"(d[35]), "+f"(d[36]), "+f"(d[37]), "+f"(d[38]), "+f"(d[39])
    : "l"(da), "l"(db), "r"(scale_d));
}
__device__ __forceinline__ void wg_ss48_tt_h(float* d, uint64_t da, uint64_t db, int scale_d) {
  asm volatile("{\n.reg .pred p;\nsetp.ne.b32 p, %26, 0;\n"
    "wgmma.mma_async.sync.aligned.m64n48k16.f32.f16.f16 "
    "{%0, %1, %2, %3, %4, %5, %6, %7, %8, %9, %10, %11, %12, %13, %14, %15, %16, %17, %18, %19, %20, %21, %22, %23}, %24, %25, p, 1, 1, 1, 1;\n}\n"
    : "+f"(d[0]), "+f"(d[1]), "+f"(d[2]), "+f"(d[3]), "+f"(d[4]), "+f"(d[5]), "+f"(d[6]), "+f"(d[7]), "+f"(d[8]), "+f"(d[9]), "+f"(d[10]), "+f"(d[11]), "+f"(d[12]), "+f"(d[13]), "+f"(d[14]), "+f"(d[15]), "+f"(d[16]), "+f"(d[17]), "+f"(d[18]), "+f"(d[19]), "+f"(d[20]), "+f"(d[21]), "+f"(d[22]), "+f"(d[23])
    : "l"(da), "l"(db), "r"(scale_d));
}

struct Params {
  CUtensorMap m[M_COUNT];
  const __nv_bfloat16 *u, *par[4], *logdt, *dskip, *wo;
};

#define CHUNK(i) ((i) == 0 ? c : ((i) == 7 ? (c ^ 1) : (((c & 6) + 1 + (i)) & 7)))
#define FLAG(kind, rr, cc) (&g_flag[((kind) * 128 + (rr) * 8 + (cc)) * 32])
#define SLOT(i) ((i) == 0 || (i) == 5 ? OFF_EXTRA : OFF_BLK + ((i) == 7 ? 0 : (i) == 6 ? 4 : (i) - 1) * BLK)
__device__ __forceinline__ void load_quad(uint32_t* A, uint32_t addr) {
  A[0] = lds32v(addr); A[1] = lds32v(addr + 32); A[2] = lds32v(addr - 32); A[3] = lds32v(addr);
}

__global__ void __launch_bounds__(512, 1) fused_kernel(const __grid_constant__ Params prm) {
  extern __shared__ unsigned char smem_raw[];
  const uint32_t sb = __shfl_sync(0xffffffff, smem_u32(smem_raw), 0);
  const int tid = threadIdx.x, lane = tid & 31;
  const int warp = __shfl_sync(0xffffffff, tid >> 5, 0), wg = warp >> 2, w4 = warp & 3;
  const int cta = blockIdx.x, r = cta >> 3, c = cta & 7;
  if ((sb & 0xffffffu) != SB0) return;
#define BAR(i) (sb + OFF_BAR + 8 * (i))
  const bool sw64 = ((c + 1) & 2) != 0;

  if (wg == 3) {
    if (warp == 13 && elect_one()) {
      #pragma unroll
      for (int i = M_W128; i <= M_WR; i++) asm volatile("prefetch.tensormap [%0];" :: "l"(&prm.m[i]) : "memory");
    }
    asm volatile("setmaxnreg.dec.sync.aligned.u32 56;");
    if (warp == 12) {
      if (elect_one()) {
        #pragma unroll
        for (int i = 0; i < 5; i++) mbar_init(BAR(BR_FULL + i), 1);
        asm volatile("fence.mbarrier_init.release.cluster;" ::: "memory");
      }
      {
        const CUtensorMap* mwp = &prm.m[sw64 ? M_W64 : M_W128];
        const int mcol = (c * 80 + (c & 1) * 16) >> (sw64 ? 5 : 6), rcol = c * 80 + ((c & 1) ? 0 : 64);
        uint32_t s = 0, ph = 1, xs = 0;
        #pragma unroll 1
        for (int kb = 0; kb < 20; kb++) {
          if (kb == 4) bar_sync(0, 512);
          if (EN_SSM && kb == 4) mbar_wait(BAR(BR_KG1), 0);
          if (kb >= 5) mbar_wait(BAR(BR_EMPTY) + 8 * s, ph);
          if (EN_ATT && elect_one()) {
            const uint32_t st = sb + s * W_SLOT, fb = BAR(BR_FULL) + 8 * s;
            mbar_expect_tx(fb, (kb & 1) ? W_SLOT : W_SLOT + 16384);
            if (!(kb & 1)) tma2d(sb + OFF_X + xs, &prm.m[M_X], fb, kb * 32, r * 128);
            tma4d(st, mwp, fb, 0, kb * 32, mcol, 0);
            tma3d(st + 12288, &prm.m[M_WR], fb, rcol, kb * 32, 0);
          }
          if (kb >= 3 && kb < 3 + U_NPF && elect_one())
            asm volatile("cp.async.bulk.prefetch.L2.global [%0], %1;" :: "l"(prm.u + cta * 10240 + (kb - 3) * (10240 / U_NPF)), "n"(20480 / U_NPF) : "memory");
          if (kb == 14 && elect_one()) asm volatile("cp.async.bulk.prefetch.L2.global [%0], 6400;" :: "l"(prm.wo + cta * 3200) : "memory");
          if (!EN_ATT && kb == 4) break;
          if (++s == 5) { s = 0; ph ^= 1; }
          if (kb & 1) { xs += 16384; if (xs == 49152) xs = 0; }
        }
      }
      if (EN_ATT) {
      mbar_wait(BAR(BR_EPOCH), 0);
      const unsigned epoch = lds32(sb + OFF_EPOCH);
      const unsigned* fo = FLAG(3, r, lane & 7);
      unsigned seen = __ballot_sync(0xffffffff, ld_rlx(lane < 16 ? fo : FLAG(0, lane & 15, c)) == epoch) & 0xffu;
      mbar_wait(BAR(BR_GEMM), 0);
      if (elect_one()) {
        mbar_expect_tx(BAR(BR_WO), 10240);
        tma2d(sb, &prm.m[M_WO], BAR(BR_WO), c * 64, c * 80);
        mbar_expect_tx(BAR(BR_KVP), 61440);
        mbar_expect_tx(BAR(BR_WO + 1), 7 * 10240);
      }
      {
        uint32_t ds = sb + OFF_WOR + (lane >> 3) * 128 + (((lane & 7) ^ (lane >> 3)) << 4);
        #pragma unroll 1
        for (int h = 0; h < 2; h++) {
          const int i = (lane & 6) + h;
          const char* gs = reinterpret_cast<const char*>(prm.wo) + (size_t)((lane >> 3) + CHUNK(i) * 80) * 1280 + 1024 + c * 32 + (lane & 1) * 16;
          #pragma unroll 2
          for (int q = 0; q < 20; q++) {
            asm volatile("cp.async.cg.shared.global [%0], [%1], 16;" :: "r"(ds), "l"(gs) : "memory");
            ds = (ds + 512) ^ 64; gs += 5120;
          }
        }
      }
      mbar_wait(BAR(BR_PUB), 0);
      poll_all(FLAG(0, lane & 15, c), epoch);
      if (elect_one()) { TS(23); bulk_ld(sb + OFF_KVP, &g_kvp[c * 16 * 240], 61440, BAR(BR_KVP)); }
      asm volatile("cp.async.wait_all;" ::: "memory");
      fence_async();
      mbar_arrive(BAR(BR_WO));
      mbar_wait(BAR(BR_SUM), 0);
      if (elect_one()) {
        #pragma unroll 1
        for (int i = 1; i < 8; i++) tma2d(sb + i * 10240, &prm.m[M_WO], BAR(BR_WO + 1), c * 64, CHUNK(i) * 80);
      }
      mbar_wait(BAR(BR_OSTG), 0);
      if (elect_one()) {
        bulk_st(&g_o[cta * 1280], sb + OFF_EXTRA, 20480);
        bulk_commit();
        bulk_wait0();
        st_rlx(FLAG(3, r, c), epoch);
        TS(20);
      }
      __syncwarp();
      #pragma unroll 1
      for (int i = 1; i < 8; i++) {
        const int src = CHUNK(i);
        if (!((seen >> src) & 1)) seen = poll_bit(fo, epoch, 1u << src);
        if (i == 5 || i == 7) mbar_wait(BAR(BR_OEMPTY) + 4 * (i - 5), 0);
        if (EN_SSM && (i == 1 || i == 4)) mbar_wait(BAR(BR_FREE) + 2 * (i & 4), 0);
        if (elect_one()) {
          mbar_expect_tx(BAR(BR_OFULL) + 8 * i, 20480);
          bulk_ld(sb + SLOT(i), &g_o[(r * 8 + src) * 1280], 20480, BAR(BR_OFULL) + 8 * i);
          if (i == 1) TS(21);
          if (i == 7) TS(22);
        }
        __syncwarp();
      }
      if (lane == 0) { DUMP(20, 30); }
      }
    } else {
      const int hw = warp - 13, ht = tid - 416;
      unsigned epoch = 0;
      if (hw == 2 && elect_one()) {
        #pragma unroll
        for (int i = 5; i < BR_COUNT; i++) mbar_init(BAR(i), i == BR_WO ? 33 : i < BR_EMPTY ? 1 : i < BR_OEMPTY ? 2 : i < BR_Y ? 8 : i < BR_OSTG ? 128 : 256);
        asm volatile("fence.mbarrier_init.release.cluster;" ::: "memory");
      }
      bar_sync(0, 512);
      if (hw == 1 && elect_one()) {
        #pragma unroll
        for (int i = M_WO; i < M_COUNT; i++) asm volatile("prefetch.tensormap [%0];" :: "l"(&prm.m[i]) : "memory");
      }
      if (hw == 0) {
        if (lane == 0) {
          epoch = ld_rlx(&g_epoch[cta]) + 1;
          st_rlx(&g_epoch[cta], epoch);
          sts32(sb + OFF_EPOCH, epoch);
          mbar_arrive(BAR(BR_EPOCH));
        }
        epoch = __shfl_sync(0xffffffff, epoch, 0);
      }
      if (EN_SSM) {
      const int mi = lane >> 3, rw = lane & 7, ch0 = c * 80 + r * 5;
      mbar_wait(BAR(BR_KG1), 0);
      if (EN_ATT) { mbar_wait(BAR(BR_FULL + U_AFTER % 5), 0); if (U_AFTER >= 5) mbar_wait(BAR(BR_FULL + U_AFTER % 5), 1); }
      #pragma unroll 1
      for (int i = hw; i < 5; i += 3) {
        const int cg = c * 80 + i * 16 + (lane >> 4) * 8, t0 = r * 128 + (lane & 15) * 8;
        const uint4* gs = reinterpret_cast<const uint4*>(prm.u + (size_t)t0 * 640 + cg);
        uint4* gd = reinterpret_cast<uint4*>(g_uy + (size_t)cg * 2048 + t0);
        uint4 v[8];
        #pragma unroll
        for (int q = 0; q < 8; q++) v[q] = __ldg(gs + q * 80);
#define TR(f, sel) make_uint4(__byte_perm(v[0].f, v[1].f, sel), __byte_perm(v[2].f, v[3].f, sel), __byte_perm(v[4].f, v[5].f, sel), __byte_perm(v[6].f, v[7].f, sel))
        gd[0] = TR(x, 0x5410); gd[256] = TR(x, 0x7632); gd[512] = TR(y, 0x5410); gd[768] = TR(y, 0x7632);
        gd[1024] = TR(z, 0x5410); gd[1280] = TR(z, 0x7632); gd[1536] = TR(w, 0x5410); gd[1792] = TR(w, 0x7632);
      }
      bar_sync(5, 96);
      if (ht == 0) TS(36);
      if (hw == 0) {
        if (lane == 0) { st_rel(FLAG(1, r, c), epoch); TS(30); }
        __syncwarp();
        poll_all_acq(FLAG(1, lane & 15, c), epoch);
        if (elect_one()) {
          fence_async_g();
          mbar_expect_tx(BAR(BR_U), 20480);
          #pragma unroll 1
          for (int q = 0; q < 5; q++) tma2d(sb + OFF_BLK + q * BLK, &prm.m[M_SB], BAR(BR_U), 0, (ch0 + q) * 32);
          TS(31);
        }
        __syncwarp();
      }
      if (hw == 0) {
        #pragma unroll 1
        for (int p = 0; p < 2; p++) {
          mbar_wait(BAR(BR_Y) + 8 * p, 0);
          if (elect_one()) {
            #pragma unroll 1
            for (int k = 4 * p; k < 4 + p; k++) tma2d_st(&prm.m[M_SB], sb + OFF_BLK + k * BLK, 0, (640 + ch0 + k) * 32);
            bulk_commit(); bulk_wait0_read();
            mbar_arrive(BAR(BR_FREE) + 8 * p);
          }
          __syncwarp();
        }
        if (elect_one()) {
          mbar_expect_tx(BAR(BR_YIN), 20480);
          bulk_wait0();
          st_rel(FLAG(2, r, c), epoch);
          TS(33);
        }
        __syncwarp();
        poll_all_acq(FLAG(2, lane & 15, c), epoch);
        if (EN_ATT) mbar_wait(BAR(BR_OEMPTY + 3), 0);
        if (elect_one()) {
          fence_async_g();
          tma2d(sb + OFF_BLK + BLK, &prm.m[M_SA], BAR(BR_YIN), r * 128, 640 + c * 80);
          tma2d(sb + OFF_BLK + BLK + 10240, &prm.m[M_SA], BAR(BR_YIN), r * 128 + 64, 640 + c * 80);
          TS(34);
        }
      }
      {
        uint32_t sa = sb + OFF_BLK + BLK + (hw * 8 + rw) * 128 + ((mi ^ rw) << 4);
        uint32_t da = sb + OFF_BLK + 2 * BLK + (8 * mi + rw) * 160 + hw * 16;
        mbar_wait(BAR(BR_YIN), 0);
        #pragma unroll 1
        for (int i = hw; i < 10; i += 3) {
          uint32_t v[4][4];
          #pragma unroll
          for (int q = 0; q < 4; q++) ldsm4t(v[q], (sa ^ ((q & 1) * 64)) + (q >> 1) * 10240);
          #pragma unroll
          for (int q = 0; q < 4; q++) stsm4(da + q * 5120, v[q][0], v[q][1], v[q][2], v[q][3]);
          sa += 3072; da += 48;
        }
      }
      fence_async();
      bar_sync(5, 96);
      if (hw == 0 && elect_one()) {
        tma2d_st(&prm.m[M_OUT], sb + OFF_BLK + 2 * BLK, c * 80, r * 128);
        bulk_commit(); bulk_wait0_read();
        TS(35); DUMP(30, 40); DUMP(0, 1);
      }
      }
    }
  } else {
    const int g = lane >> 2, tq = lane & 3, t7 = tid & 127;
    uint32_t pr[3][3];
    #pragma unroll
    for (int q = 0; q < 3; q++) {
      const int ch = c * 80 + r * 5 + (wg == 2 ? 2 + q : wg);
      #pragma unroll
      for (int e = 0; e < 2; e++)
        pr[q][e] = __ldg(reinterpret_cast<const unsigned short*>(prm.par[2 * e]) + ch * 128 + t7) | ((uint32_t)__ldg(reinterpret_cast<const unsigned short*>(prm.par[2 * e + 1]) + ch * 128 + t7) << 16);
      pr[q][2] = __ldg(reinterpret_cast<const unsigned short*>(prm.logdt) + ch) | ((uint32_t)__ldg(reinterpret_cast<const unsigned short*>(prm.dskip) + ch) << 16);
    }
    asm volatile("setmaxnreg.inc.sync.aligned.u32 152;");
    if (EN_SSM) {
      #pragma unroll 1
      for (int i = tid; i < 5 * 272; i += 384) {
        const int k = i / 272, q = i - k * 272;
        sts128(sb + OFF_BLK + k * BLK + (q < 256 ? B_TBL + q * 16 : q * 16 - 4352), 0, 0, 0, 0);
      }
      #pragma unroll
      for (int q = 0; q < 3; q++) {
        const uint32_t m = __reduce_max_sync(0xffffffff, max(pr[q][1] & 0x7fffu, (pr[q][1] >> 16) & 0x7fffu));
        if (lane == 0) sts32(sb + OFF_EPOCH + 16 + (wg * 3 + q) * 16 + w4 * 4, m);
      }
    }
    bar_sync(0, 512);
    if (tid == 256) TS(40);
    if (EN_SSM) {
      const uint32_t p0 = wg == 1 ? 4 * W_SLOT : OFF_BLK + wg * 3584, p1 = wg == 1 ? 7168 : BLK, p2 = wg == 1 ? OFF_X + 32768 - 4 * W_SLOT : 2 * BLK;
      const uint32_t fa = sb + p0 + (lane >> 4) * p1 + (w4 & 1) * p2 + ((lane >> 3) & 1) * 256 + (lane & 7) * 16;
      const uint32_t ea = fa + (w4 >> 1) * 2048, ga = fa + 4096 + (w4 >> 1) * 1536;
      constexpr uint64_t dE = mkdesc(SB0, 128, 512, 0);
      const uint32_t xa = sb + OFF_BLK + 4 * BLK + B_D + wg * 3072 + t7 * 8;
      #pragma unroll 1
      for (int k = wg; k < (wg == 2 ? 5 : wg + 1); k++) {
        const uint32_t blk = sb + OFF_BLK + k * BLK;
        const uint32_t pa0 = pr[0][0], pc0 = pr[0][1];
        const float dt = bf_round(expf(bf_lo(pr[0][2]))), dsk = bf_hi(pr[0][2]);
        #pragma unroll
        for (int e = 0; e < 3; e++) { pr[0][e] = pr[1][e]; pr[1][e] = pr[2][e]; }
        float fac;
        {
          uint32_t mm[4];
          lds128(mm, sb + OFF_EPOCH + 16 + (wg * 2 + k) * 16);
          const uint32_t ex = min(max(max(max(mm[0], mm[1]), max(mm[2], mm[3])) >> 7, 1u), 253u);
          const float sc = __uint_as_float((254u - ex) << 23);
          fac = 2.f * dt * __uint_as_float(ex << 23);
          const float lr = -bf_round(expf(bf_lo(pa0))) * dt * 1.44269504089f;
          const float tn = bf_hi(pa0) * dt * 0.15915494309f;
          float z1r, z1i, z2r, z2i, z4r, z4i, xr[8], xi[8], gr[8], gi[8], wr[9], wi[9];
          cexp_t(lr, -tn, z1r, z1i);
          cexp_t(lr * 8.f, tn * 8.f, xr[1], xi[1]);
          cexp_t(lr * 64.f, tn * 64.f, wr[0], wi[0]);
          xr[0] = 1.f; xi[0] = 0.f;
          cmul(xr[1], xi[1], xr[1], xi[1], xr[2], xi[2]); cmul(xr[2], xi[2], xr[1], xi[1], xr[3], xi[3]);
          cmul(xr[2], xi[2], xr[2], xi[2], xr[4], xi[4]);
          #pragma unroll
          for (int b = 1; b < 4; b++) cmul(xr[4], xi[4], xr[b], xi[b], xr[4 + b], xi[4 + b]);
          cmul(wr[0], wi[0], wr[0], wi[0], wr[1], wi[1]); cmul(wr[1], wi[1], wr[0], wi[0], wr[2], wi[2]);
          cmul(wr[1], wi[1], wr[1], wi[1], wr[3], wi[3]); cmul(wr[3], wi[3], wr[3], wi[3], wr[4], wi[4]);
          cmul(wr[4], wi[4], wr[3], wi[3], wr[5], wi[5]); cmul(wr[4], wi[4], wr[4], wi[4], wr[6], wi[6]);
          cmul(wr[6], wi[6], wr[4], wi[4], wr[7], wi[7]); cmul(wr[6], wi[6], wr[6], wi[6], wr[8], wi[8]);
          uint32_t R[4], I[4], PR[4], PI[4];
          #pragma unroll
          for (int b = 0; b < 4; b++) { R[b] = packh(xr[2 * b], xr[2 * b + 1]); I[b] = packh(xi[2 * b], xi[2 * b + 1]); }
          sts128(ea, R[0], R[1], R[2], R[3]); sts128(ea + 128, I[0], I[1], I[2], I[3]);
          #pragma unroll
          for (int i = 0; i < 3; i++) {
            const uint32_t z = packh(wr[i], wi[i]);
            #pragma unroll
            for (int b = 0; b < 4; b++) hcm2(R[b], I[b], z, PR[b], PI[b]);
            sts128(ea + (i + 1) * 512, PR[0], PR[1], PR[2], PR[3]); sts128(ea + (i + 1) * 512 + 128, PI[0], PI[1], PI[2], PI[3]);
          }
          gr[0] = bf_lo(pc0) * sc; gi[0] = -bf_hi(pc0) * sc;
          cmul(z1r, z1i, z1r, z1i, z2r, z2i); cmul(z2r, z2i, z2r, z2i, z4r, z4i);
          cmul(gr[0], gi[0], z1r, z1i, gr[1], gi[1]);
          cmul(gr[0], gi[0], z2r, z2i, gr[2], gi[2]); cmul(gr[1], gi[1], z2r, z2i, gr[3], gi[3]);
          #pragma unroll
          for (int b = 0; b < 4; b++) cmul(gr[b], gi[b], z4r, z4i, gr[4 + b], gi[4 + b]);
          sts128(ga, packh(gr[0], gr[1]), packh(gr[2], gr[3]), packh(gr[4], gr[5]), packh(gr[6], gr[7]));
          sts128(ga + 128, packh(gi[0], gi[1]), packh(gi[2], gi[3]), packh(gi[4], gi[5]), packh(gi[6], gi[7]));
          {
            const uint32_t z = packh(wr[3], -wi[3]), a4r = packh(gr[0], gr[4]), a4i = packh(gi[0], gi[4]);
            hcm2(packh(gr[0], gr[2]), packh(gi[0], gi[2]), z, PR[0], PI[0]);
            hcm2(packh(gr[4], gr[6]), packh(gi[4], gi[6]), z, PR[1], PI[1]);
            hcm2(a4r, a4i, packh(wr[4], -wi[4]), PR[2], PI[2]);
            hcm2(a4r, a4i, packh(wr[5], -wi[5]), PR[3], PI[3]);
            sts128(ga + 512, PR[0], PR[1], PR[2], PR[3]); sts128(ga + 512 + 128, PI[0], PI[1], PI[2], PI[3]);
            float hr, hi_;
            cmul(gr[0], gi[0], wr[3], -wi[3], hr, hi_);
            const uint32_t cr = packh(gr[0], hr), ci = packh(gi[0], hi_);
            #pragma unroll
            for (int i = 0; i < 3; i++) hcm2(cr, ci, packh(wr[6 + i], -wi[6 + i]), PR[i], PI[i]);
            sts128(ga + 1024, PR[0], PR[1], PR[2], 0u); sts128(ga + 1024 + 128, PI[0], PI[1], PI[2], 0u);
          }
        }
        fence_async();
        bar_sync(2 + wg, 128);
        if (t7 == 0 && k == 3) TS(50);
        float ka[24]; zero<24>(ka);
        wg_fence();
        #pragma unroll
        for (int s = 0; s < 8; s++) {
          const uint32_t lo = (uint32_t)dE + ((p0 + ((s >> 1) & 1) * p1 + (s >> 2) * p2) >> 4) + (s & 1) * 16;
          wg_ss48_tt_h(ka, desc2(lo, dE >> 32), desc2(lo + 256, dE >> 32), s != 0);
        }
        wg_commit();
        wg_wait<0>();
        pin<24>(ka);
        if (t7 == 0 && k == 3) TS(51);
        float kk[6];
        {
          const bool up = w4 >= 2;
          #pragma unroll
          for (int n = 0; n < 3; n++) {
            sts64f(xa + n * 1024, up ? ka[12 + 4 * n] : ka[4 * n + 2], up ? ka[13 + 4 * n] : ka[4 * n + 3]);
            kk[2 * n] = up ? ka[14 + 4 * n] : ka[4 * n]; kk[2 * n + 1] = up ? ka[15 + 4 * n] : ka[4 * n + 1];
          }
          bar_sync(2 + wg, 128);
          if (t7 == 0 && wg < 2) mbar_arrive(BAR(BR_KG1));
          #pragma unroll
          for (int n = 0; n < 3; n++) {
            uint32_t o[2]; lds64(o, (xa ^ 512) + n * 1024);
            kk[2 * n] = (kk[2 * n] + __uint_as_float(o[0])) * fac; kk[2 * n + 1] = (kk[2 * n + 1] + __uint_as_float(o[1])) * fac;
          }
        }
        if (t7 == 0 && k == 3) TS(52);
        {
          const int j = (w4 & 1) * 16 + (w4 >> 1) * 8 + g;
          const uint32_t tb = blk + B_TBL;
          if (t7 == 0) kk[0] += dsk;
          const uint32_t pa_ = tb + (16 + 8 * j + 2 * tq) * 4;
          const uint32_t v = pack2(kk[1], kk[0]);
          sts32(pa_ + 4, v); sts16(pa_, v >> 16); sts16(pa_ + 10, v);
          const uint32_t u = pack2(kk[2], kk[3]), w = pack2(kk[4], kk[5]);
          if (tq < 2) {
            const uint32_t pb = tb + (16 + 256 + 8 * j + 4 * tq) * 4;
            sts16(pb, u); sts32(pb + 4, __byte_perm(u, 0, 0x1010)); sts32(pb + 8, __byte_perm(u, 0, 0x1032)); sts16(pb + 14, u >> 16);
            if (j | tq) { sts16(pb - 4, u); sts16(pb + 2, u); }
            const int i = 64 * tq + j;
            const uint32_t e0 = tb + (T_F3 + (((i - 1) & 1) ? 80 : 0) + ((i - 1) >> 1)) * 4, e1 = i ? e0 : tb + (T_F2 + 144 + 31) * 4;
            sts16(e1, w); sts16(e1 + 6, w); sts16(e0 + 64, w >> 16); sts16(e0 + 70, w >> 16);
            if (i == 0) { sts16(tb + (T_S + 3) * 4, w); sts32(tb + (T_S + 4) * 4, __byte_perm(w, 0, 0x1010)); sts16(tb + (T_S + 5) * 4 + 2, w); }
          } else {
            const int i = 32 * (tq - 2) + j;
            const uint32_t e1 = tb + (i ? T_F2 + ((2 * i - 1) & 3) * 48 + ((2 * i - 1) >> 2) : 16 + 511) * 4;
            const uint32_t e2 = tb + (T_F2 + (i & 1) * 96 + (i >> 1)) * 4;
            sts16(e1, u); sts16(e1 + 6, u); sts16(e2, u >> 16); sts16(e2 + 6, u >> 16);
            if (i == 0) {
              const uint32_t uu = __byte_perm(u, 0, 0x1010);
              sts32(tb + 528 * 4, uu); sts32(tb + 529 * 4, uu); sts32(tb + 530 * 4, uu); sts16(tb + 531 * 4 + 2, u);
              sts16(tb + (T_F3 + 80 + 63) * 4, w);
            }
          }
        }
        if (t7 == 0 && k == 3) TS(53);
      }
      if (wg < 2) mbar_arrive(BAR(BR_KGEN));
    }
    if (tid == 0) TS(14);
  if (wg < 2) {
    if (EN_ATT) {
    float am[96], ar[24];
    {
      constexpr uint64_t da0 = mkdesc(SB0 + OFF_X, 16, 1024, 1), dr0 = mkdesc(SB0 + 12288, 1024, 256, 3);
      const uint64_t db0 = sw64 ? mkdesc(SB0, 2048, 512, 2) : mkdesc(SB0, 4096, 1024, 1);
      const uint32_t kst = sw64 ? 64 : 128, bh = db0 >> 32;
      uint32_t s = 0, ph = 0, xo = 0;
      #pragma unroll 1
      for (int kb = 0; kb < 20; kb++) {
        const uint32_t wo_ = s * (W_SLOT >> 4), al = (uint32_t)da0 + wg * 512 + xo, bl = (uint32_t)db0 + wo_, rl = (uint32_t)dr0 + wo_;
        mbar_wait(BAR(BR_FULL) + 8 * s, ph);
        if (kb == 0 && tid == 0) TS(1);
        wg_fence();
        wg_ss192_tb(am, desc2(al, da0 >> 32), desc2(bl, bh), kb != 0);
        wg_ss48_tb(ar, desc2(al, da0 >> 32), desc2(rl, dr0 >> 32), kb != 0);
        wg_ss192_tb(am, desc2(al + 2, da0 >> 32), desc2(bl + kst, bh), 1);
        wg_ss48_tb(ar, desc2(al + 2, da0 >> 32), desc2(rl + 32, dr0 >> 32), 1);
        wg_commit();
        wg_wait<1>();
        if (t7 == 0 && kb > 0 && kb < 16) mbar_arrive(BAR(BR_EMPTY) + 8 * (s == 0 ? 4 : s - 1));
        if (++s == 5) { s = 0; ph ^= 1; }
        xo += (kb & 1) ? 1020 : 4;
        if (xo == 3072) xo = 0;
      }
      wg_wait<0>();
      pin<96>(am); pin<24>(ar);
    }
    if (tid == 0) TS(2);
#define QV(j, e) ((j) < 8 ? am[4 * (j) + (e)] : ar[4 * ((j) - 8) + (e)])
#define KV_(j, e) ((j) < 8 ? am[32 + 4 * (j) + (e)] : ar[8 + 4 * ((j) - 8) + (e)])
#define VV(j, e) ((j) < 8 ? am[64 + 4 * (j) + (e)] : ar[16 + 4 * ((j) - 8) + (e)])
    {
      bar_sync(1, 256);
      if (tid == 0) mbar_arrive(BAR(BR_GEMM));
      const uint32_t ro = sb + (uint32_t)((warp * 16 + (lane & 15)) * 16);
      const int l0 = 2 * (c & 1) + (lane >> 4);
      const uint32_t ones = (tq == 0) ? 0x00003f80u : 0u;
#define PV(j) pack2(VV(j, 0), VV(j, 1)), pack2(VV(j, 2), VV(j, 3))
#define PK(j) pack2(phi(KV_(j, 0)), phi(KV_(j, 1))), pack2(phi(KV_(j, 2)), phi(KV_(j, 3)))
      stsm4(ro + OFF_V + (5 + 6 * (lane >> 4)) * 2048, ones, ones, ones, ones);
      #pragma unroll
      for (int j = 0; j < 10; j += 2) {
        const int l = (j == 8 && (c & 1)) ? l0 - 2 : l0 + j;
        stsm4(ro + OFF_V + (l + (l >= 5)) * 2048, PV(j), PV(j + 1));
        stsm4(ro + OFF_PK + l * 2048, PK(j), PK(j + 1));
      }
    }
    fence_async();
    bar_sync(1, 256);
    if (tid == 0) TS(3);
    mbar_wait(BAR(BR_EPOCH), 0);
    const unsigned epoch = lds32(sb + OFF_EPOCH);
    {
      float kv[24]; zero<24>(kv);
      constexpr uint64_t da = mkdesc(SB0 + OFF_PK, 128, 2048, 0), db = mkdesc(SB0 + OFF_V, 128, 2048, 0);
      wg_fence();
      #pragma unroll
      for (int s = 0; s < 8; s++) wg_ss48_tt(kv, desc2((uint32_t)da + wg * 640 + s * 16, da >> 32), desc2((uint32_t)db + wg * 768 + s * 16, db >> 32), s != 0);
      wg_commit();
      wg_wait<0>();
      pin<24>(kv);
      if (tid == 0) TS(15);
      if (w4 < 3) {
        const uint32_t wb = sb + OFF_KVS + (wg * 3 + w4) * 1536 + (lane & 15) * 96;
        #pragma unroll
        for (int j = 0; j < 6; j += 2)
          stsm4(wb + (j + (lane >> 4)) * 16, pack2(kv[4 * j], kv[4 * j + 1]), pack2(kv[4 * j + 2], kv[4 * j + 3]),
                pack2(kv[4 * j + 4], kv[4 * j + 5]), pack2(kv[4 * j + 6], kv[4 * j + 7]));
        __syncwarp();
        const int dl = w4 * 16 + (lane & 15), hl = dl >= 20;
        if (dl < 40) {
          uint4* dst = &g_kvp[(c * 16 + r) * 240 + wg * 40 + dl];
          uint32_t v[4], z[4];
          lds128(v, wb + (3 * hl + (lane >> 4)) * 16);
          lds64(z, wb + 32 + 8 * hl); z[2] = lds32(wb + 80); z[3] = epoch & 1u;
          v[3] = (v[3] & ~1u) | z[3];
          st128_rlx(dst + (lane >> 4) * 80, v);
          if (lane < 16) st128_rlx(dst + 160, z);
        }
      }
    }
    fence_async();
    bar_sync(1, 256);
    if (tid == 0) { st_rlx(FLAG(0, r, c), epoch); mbar_arrive(BAR(BR_PUB)); TS(4); }
    const int kvi = (tid >= 80) + (tid >= 160) + (tid >= 240), kd = tid - 80 * kvi;
    const int khd = kd / 20, kt0 = 5 * (khd >> 1) + 2 * (khd & 1);
    const uint32_t rb = sb + OFF_KVB + kd * 16;
    if (kvi < 3) {
      #pragma unroll 1
      for (int m = kvi; m < 7; m += 3) { const int q = kt0 + 3 + m; sts128(rb + (q >= 10 ? q - 10 : q) * 1280, 0, 0, 0, 0); }
    }
    uint32_t qa[20];
    {
      const float sc = 1.44269504089f + __uint_as_float(lds32(sb + OFF_EPOCH) ^ epoch);
      #pragma unroll
      for (int j = 0; j < 10; j++) { qa[2 * j] = pack2(phi(QV(j, 0), sc), phi(QV(j, 1), sc)); qa[2 * j + 1] = pack2(phi(QV(j, 2), sc), phi(QV(j, 3), sc)); }
    }
    if (tid == 0) TS(5);
    mbar_wait(BAR(BR_KVP), 0);
    if (tid == 0) TS(6);
    if (kvi < 3) {
      float s[8];
      zero<8>(s);
      uint32_t bad = 0;
      #pragma unroll 4
      for (int i = 0; i < 16; i++) {
        uint32_t w[4];
        lds128(w, sb + OFF_KVP + tid * 16 + i * 3840);
        bad |= w[3] ^ epoch;
        #pragma unroll
        for (int e = 0; e < 4; e++) { s[2 * e] += bf_lo(w[e]); s[2 * e + 1] += bf_hi(w[e]); }
      }
      if (__builtin_expect(bad & 1u, 0)) {
        zero<8>(s);
        #pragma unroll 1
        for (int i = 0; i < 16; i++) {
          uint32_t w[4] = {0, 0, 0, ~epoch};
          fix128_w3(w, &g_kvp[(c * 16 + i) * 240 + tid], epoch, 1u);
          #pragma unroll
          for (int e = 0; e < 4; e++) { s[2 * e] += bf_lo(w[e]); s[2 * e + 1] += bf_hi(w[e]); }
        }
        FIXCNT
      }
      const uint32_t p0 = pack2(s[0], s[1]), p1 = pack2(s[2], s[3]), p2 = pack2(s[4], s[5]), p3 = pack2(s[6], s[7]);
      if (kvi < 2) sts128(rb + (kt0 + (khd & 1) + kvi) * 1280, p0, p1, p2, p3);
      else {
        const bool od = khd & 1;
        sts128(rb + (5 * (khd >> 1) + 2) * 1280, od ? 0u : p0, od ? 0u : p1, od ? p0 : 0u, od ? p1 : 0u);
        const uint32_t zz = (p2 & 0xffffu) << (16 * (khd & 1));
        sts128(rb + 10 * 1280, khd < 2 ? zz : 0u, khd < 2 ? 0u : zz, 0u, 0u);
      }
    }
    fence_async();
    bar_sync(1, 256);
    if (tid == 0) { mbar_arrive(BAR(BR_SUM)); TS(7); }
    {
      float oa[44]; zero<44>(oa);
      constexpr uint64_t db = mkdesc(SB0 + OFF_KVB, 128, 1280, 0);
      wg_fence();
      #pragma unroll
      for (int s = 0; s < 5; s++) wg_rs88_tb(oa, &qa[4 * s], desc2((uint32_t)db + ((s == 4 && (c & 1)) ? 0 : (s + (c & 1)) * 16), db >> 32), s != 0);
      wg_commit();
      wg_wait<0>();
      pin<44>(oa);
      if (tid == 0) TS(13);
      float rc[4], rd[2][4];
      #pragma unroll
      for (int e = 0; e < 4; e++) asm("rcp.approx.ftz.f32 %0, %1;" : "=f"(rc[e]) : "f"(oa[40 + e] + 1e-6f));
      #pragma unroll
      for (int h = 0; h < 4; h++) {
        rd[0][h] = __shfl_sync(0xffffffff, rc[h & 1], (lane & 28) | (h >> 1));
        rd[1][h] = __shfl_sync(0xffffffff, rc[2 + (h & 1)], (lane & 28) | (h >> 1));
      }
      #pragma unroll
      for (int j = 0; j < 10; j++) {
        #pragma unroll
        for (int h = 0; h < 2; h++) {
          float f;
          if (j == 2) f = tq < 2 ? rd[h][0] : rd[h][1];
          else if (j == 7) f = tq < 2 ? rd[h][2] : rd[h][3];
          else f = rd[h][(8 * j) / 20];
          qa[2 * j + h] = pack2(oa[4 * j + 2 * h] * f, oa[4 * j + 2 * h + 1] * f);
        }
      }
      const uint32_t m0 = (lane & 7) == ((2 * w4) & 7), m1 = (lane & 7) == 2 * w4 + 1;
      const uint32_t oa_ = sb + OFF_EXTRA + (lane >> 4) * 2048 + (warp * 16 + (lane & 15)) * 16;
      bar_sync(1, 256);
#define TAG(v, m) (((v) & ~(m)) | (epoch & (m)))
      #pragma unroll
      for (int s = 0; s < 5; s++) stsm4(oa_ + s * 4096, TAG(qa[4 * s], m0), TAG(qa[4 * s + 1], m1), TAG(qa[4 * s + 2], m0), TAG(qa[4 * s + 3], m1));
    }
    fence_async();
    mbar_arrive(BAR(BR_OSTG));
    if (tid == 0) TS(8);
    float oc[40]; zero<40>(oc);
    {
      constexpr uint64_t dw0 = mkdesc(SB0, OFF_WOR, 1024, 1), da0 = mkdesc(SB0, 2048, 128, 0);
      const uint32_t ck = sb + tid * 32 + ((lane >> 2) << 2), ck2 = ck + (wg ? 0 : 16384);
      uint32_t bad = 0;
      auto tile = [&](int i, uint32_t so) {
        const uint32_t al = (uint32_t)da0 + wg * 64 + (so >> 4), wl = (uint32_t)dw0 + i * 640 - (i >> 1) * (1278 << 16);
        wg_fence();
        #pragma unroll
        for (int s = 0; s < 5; s++) wg_ss80_tb(oc, desc2(al + s * 256, da0 >> 32), desc2(wl + s * 128, dw0 >> 32), (i | s) != 0);
        wg_commit();
        bad |= (lds32(ck + so) ^ epoch) | (lds32(ck + so + 8192) ^ epoch) | (lds32(ck2 + so) ^ epoch);
      };
      mbar_wait(BAR(BR_WO), 0);
      mbar_wait(BAR(BR_OSTG), 0);
      tile(0, SLOT(0));
      mbar_wait(BAR(BR_WO + 1), 0);
      #pragma unroll 1
      for (int i = 1; i < 8; i++) {
        if (i == 1) { wg_wait<0>(); if (lane == 0) mbar_arrive(BAR(BR_OEMPTY)); }
        mbar_wait(BAR(BR_OFULL) + 8 * i, 0);
        if (i == 1 && tid == 0) TS(9);
        tile(i, SLOT(i));
        wg_wait<1>();
        if (lane == 0 && i > 1) mbar_arrive(BAR(BR_OEMPTY - 1) + 8 * i);
      }
      #pragma unroll 1
      for (int n = 0; n < 56; n++) {
        const int i = n & 7;
        if (i == 0) {
          uint32_t any;
          asm volatile("{\n.reg .pred p;\nsetp.ne.u32 p, %1, 0;\nbarrier.red.or.pred p, 1, 256, p;\nselp.u32 %0, 1, 0, p;\n}" : "=r"(any) : "r"(bad & 1u) : "memory");
          if (!any) break;
          bad = 0;
          FIXCNT
        }
        wg_wait<0>();
        bar_sync(1, 256);
        if (tid == 0) { mbar_expect_tx(BAR(BR_RETRY), 20480); bulk_ld(sb + SLOT(0), &g_o[(r * 8 + CHUNK(i)) * 1280], 20480, BAR(BR_RETRY)); }
        mbar_wait(BAR(BR_RETRY), n & 1);
        tile(i, SLOT(0));
      }
      wg_wait<0>();
      pin<40>(oc);
    }
    if (tid == 0) TS(10);
    {
      const int row = w4 * 16 + (lane & 15);
      const uint32_t ob = sb + SLOT(4) + wg * 10240;
      #pragma unroll
      for (int j = 0; j < 8; j += 2)
        stsm4(ob + row * 128 + (((j + (lane >> 4)) ^ (row & 7)) << 4), pack2(oc[4 * j], oc[4 * j + 1]), pack2(oc[4 * j + 2], oc[4 * j + 3]),
              pack2(oc[4 * j + 4], oc[4 * j + 5]), pack2(oc[4 * j + 6], oc[4 * j + 7]));
      stsm4(ob + 8192 + row * 32 + (lane >> 4) * 16, pack2(oc[32], oc[33]), pack2(oc[34], oc[35]), pack2(oc[36], oc[37]), pack2(oc[38], oc[39]));
      fence_async();
      bar_sync(2 + wg, 128);
      if (w4 == 0 && elect_one()) {
        tma2d_st(&prm.m[M_O64], ob, 640 + c * 64, r * 128 + wg * 64);
        tma2d_st(&prm.m[M_O16], ob + 8192, 1152 + c * 16, r * 128 + wg * 64);
        bulk_commit(); bulk_wait0_read();
        if (wg == 0) { TS(11); DUMP(0, 20); }
      }
    }
    }
  } else {
    if (EN_SSM) {
    if (t7 == 0) TS(41);
    mbar_wait(BAR(BR_U), 0);
    mbar_wait(BAR(BR_KGEN), 0);
    bar_sync(4, 128);
    if (t7 == 0) TS(43);
    {
      #pragma unroll 1
      for (int q6 = w4; q6 < 30; q6 += 4) {
        {
          const int k = q6 / 6, kap = (q6 - 6 * k) * 32 + lane;
          const uint32_t blk = sb + OFF_BLK + k * BLK;
          float P[33];
          P[0] = 0.f;
          #pragma unroll
          for (int q = 0; q < 4; q++) {
            const int ch = kap - 3 + q;
            uint32_t v[4];
            lds128(v, blk + (uint32_t)((ch * 16) ^ ((ch * 2) & 0x70)));
            #pragma unroll
            for (int e = 0; e < 4; e++) {
              P[q * 8 + 2 * e + 1] = (q == 0 && e < 2) ? 0.f : P[q * 8 + 2 * e] + bf_lo(v[e]);
              P[q * 8 + 2 * e + 2] = (q == 0 && e < 2) ? 0.f : P[q * 8 + 2 * e + 1] + bf_hi(v[e]);
            }
          }
#define WIN(lo, hi, e) (P[25 + (e) - (lo)] - P[24 + (e) - (hi)])
#define WIN8(lo, hi) pack2(WIN(lo, hi, 0), WIN(lo, hi, 1)), pack2(WIN(lo, hi, 2), WIN(lo, hi, 3)), pack2(WIN(lo, hi, 4), WIN(lo, hi, 5)), pack2(WIN(lo, hi, 6), WIN(lo, hi, 7))
          const uint32_t o2 = blk + B_D + (kap & 1) * 1552 + (kap >> 1) * 16;
          sts128(o2, WIN8(3, 5));
          sts128(o2 + B_D5, WIN8(6, 10));
          if (kap < 128) {
            const uint32_t o = blk + B_D + (kap & 1) * 1024 + (kap >> 1) * 16;
            sts128(o + B_D7, WIN8(5, 11));
            sts128(o + B_D9, WIN8(12, 20));
          }
        }
      }
      if (t7 < 10) sts128(sb + OFF_BLK + (t7 >> 1) * BLK + B_D + (t7 & 1) * B_D5 + 1536, 0, 0, 0, 0);
    }
    bar_sync(4, 128);
    if (t7 == 0) TS(44);
    if (EN_ATT) mbar_wait(BAR(BR_GEMM), 0);
    if (t7 == 0) TS(42);
    #pragma unroll 1
    for (int pass = 1; pass >= 0; pass--) {
      const int k = pass ? w4 : 4;
      const uint32_t blk = sb + OFF_BLK + k * BLK, tb = blk + B_TBL + (uint32_t)((g - 2 * tq) * 4);
      float acc[16][4];
      zero<64>(&acc[0][0]);
      const int kl = 16 * (lane >> 4) + 2 * (lane & 7) + ((lane >> 3) & 1);
      {
        auto ubase = [&](int sh) { const int q = kl - 2 * sh; return blk + (uint32_t)((q * 16) ^ ((q * 2) & 0x70)); };
#define LDQ(A, sh) _Pragma("unroll") for (int m = 0; m < 4; m++) load_quad(A[m], tb + (16 + 16 * (sh) + 128 * m) * 4);
#define LDB(B, ub, h) _Pragma("unroll") for (int p = 0; p < 4; p++) ldsm4(B[p], ((ub) ^ ((p & 1) * 64)) + (4 * (h) + p) * 512);
#define MLO(A, B) _Pragma("unroll") for (int m = 0; m < 4; m++) _Pragma("unroll") for (int cc = 0; cc < 8; cc++) mma16816(acc[cc + m], A[m], &B[cc >> 1][(cc & 1) * 2]);
#define MHI(A, B) _Pragma("unroll") for (int m = 0; m < 4; m++) _Pragma("unroll") for (int cc = 0; cc < 8 - m; cc++) mma16816(acc[8 + cc + m], A[m], &B[cc >> 1][(cc & 1) * 2]);
        int p_ = pass ? 0 : w4;
        const int pe = pass ? 4 : w4 + 1;
        uint32_t A[4][4], A2[4][4], Bl[4][4], Bh[4][4];
        uint32_t ub = ubase(p_ + 4);
        LDQ(A, p_ + 4) LDB(Bl, ub, 0)
        #pragma unroll 1
        for (; p_ < pe; p_++) {
          LDB(Bh, ub, 1)
          MLO(A, Bl)
          ub = ubase(p_);
          LDQ(A2, p_) LDB(Bl, ub, 0)
          MHI(A, Bh)
          LDB(Bh, ub, 1)
          load_quad(A[0], tb + (16 + 512 + 16 * (p_ & 1)) * 4); load_quad(A[1], tb + (T_S + 16 * (p_ & 1)) * 4);
          MLO(A2, Bl)
          if (p_ < 2) {
            #pragma unroll
            for (int cc = 0; cc < 8; cc++) mma16816(acc[cc + 4], A[0], &Bl[cc >> 1][(cc & 1) * 2]);
            #pragma unroll
            for (int cc = 0; cc < 4; cc++) mma16816(acc[cc + 12], A[0], &Bh[cc >> 1][(cc & 1) * 2]);
            #pragma unroll
            for (int cc = 0; cc < 8; cc++) mma16816(acc[cc + 8], A[1], &Bl[cc >> 1][(cc & 1) * 2]);
          }
          const int pn = ((p_ + 1) & 3) + 4;
          ub = ubase(pn);
          LDQ(A, pn) LDB(Bl, ub, 0)
          MHI(A2, Bh)
        }
      }
      if (t7 == 0) TS(57 + 3 * pass);
      {
        const int ih = (lane >> 3) & 1;
        const uint32_t dl = blk + B_D + (uint32_t)(((lane >> 4) * 8 + (lane & 7)) * 16);
        const uint32_t d0_ = dl + ih * 1552, d8_ = dl + (ih ? 0 : 1536), d3_ = dl + B_D7 + ih * 1024;
        auto cls2 = [&](uint32_t da, uint32_t ta) {
          uint32_t B[6][2], A[6][4];
          #pragma unroll
          for (int e = 0; e < 6; e++) { B[e][0] = lds32v(ta + (e + 4) * 32); B[e][1] = lds32v(ta + (e + 3) * 32); }
          #pragma unroll
          for (int kk = 0; kk < 6; kk++) ldsm4t(A[kk], da + kk * 256);
          #pragma unroll
          for (int e = 0; e < 6; e++)
            #pragma unroll
            for (int kk = 0; kk < 6; kk++) if (2 * kk + e + 4 < 16) mma16816(acc[2 * kk + e + 4], A[kk], B[e]);
        };
        auto cls3 = [&](uint32_t da, uint32_t ta) {
          uint32_t B[8][2], A[4][4];
          #pragma unroll
          for (int e = 0; e < 8; e++) { B[e][0] = lds32v(ta + (e + 8) * 32); B[e][1] = lds32v(ta + (e + 7) * 32); }
          #pragma unroll
          for (int kk = 0; kk < 4; kk++) ldsm4t(A[kk], da + kk * 256);
          #pragma unroll
          for (int kk = 0; kk < 4; kk++)
            #pragma unroll
            for (int e = 0; e < 8; e++) if (2 * kk + e + 8 < 16) mma16816(acc[2 * kk + e + 8], A[kk], B[e]);
        };
        #pragma unroll 1
        for (int a = pass ? 0 : w4; a < (pass ? 4 : w4 + 1); a++) cls2(((a & 2) ? d8_ : d0_) + (a & 1) * B_D5, tb + (T_F2 + 48 * a - 32) * 4);
        #pragma unroll 1
        for (int b = pass ? 0 : (w4 & 1); b < (pass ? 2 : w4 - 1); b++) cls3(d3_ + b * 2048, tb + (T_F3 + 80 * b - 64) * 4);
      }
      if (t7 == 0) TS(58 + 3 * pass);
      const uint32_t ya = blk + (uint32_t)((kl * 16) ^ ((kl * 2) & 0x70));
#define STY(p) stsm4t((ya ^ (((p) & 1) * 64)) + (p) * 512, pack2(acc[2 * (p)][0], acc[2 * (p)][1]), pack2(acc[2 * (p)][2], acc[2 * (p)][3]), \
                      pack2(acc[2 * (p) + 1][0], acc[2 * (p) + 1][1]), pack2(acc[2 * (p) + 1][2], acc[2 * (p) + 1][3]))
      if (pass == 0) {
        const uint32_t xw = blk + 4096 + w4 * 4096 + lane * 16, xr = blk + 4096 + w4 * 1024 + lane * 16;
        #pragma unroll
        for (int h = 0; h < 2; h++) {
          bar_sync(4, 128);
          #pragma unroll
          for (int i = 0; i < 8; i++)
            sts128(xw + i * 512, __float_as_uint(acc[8 * h + i][0]), __float_as_uint(acc[8 * h + i][1]), __float_as_uint(acc[8 * h + i][2]), __float_as_uint(acc[8 * h + i][3]));
          bar_sync(4, 128);
          float y[8];
          #pragma unroll
          for (int i = 0; i < 8; i++) {
            uint32_t o[4]; lds128(o, xr + (i >> 1) * 4096 + (i & 1) * 512);
            #pragma unroll
            for (int e = 0; e < 4; e++) y[4 * (i & 1) + e] = i < 2 ? __uint_as_float(o[e]) : y[4 * (i & 1) + e] + __uint_as_float(o[e]);
          }
          stsm4t((ya ^ ((w4 & 1) * 64)) + (4 * h + w4) * 512, pack2(y[0], y[1]), pack2(y[2], y[3]), pack2(y[4], y[5]), pack2(y[6], y[7]));
        }
      } else {
        __syncwarp();
        #pragma unroll
        for (int p = 0; p < 8; p++) STY(p);
      }
      if (t7 == 0 && !pass) TS(55);
      fence_async();
      mbar_arrive(BAR(BR_Y + 1) - 8 * pass);
      if (t7 == 0) TS(59 + 3 * pass);
    }
    if (t7 == 0) DUMP(40, 64);
    }
  }
  }
}

typedef CUresult (*EncFn)(CUtensorMap*, CUtensorMapDataType, cuuint32_t, void*, const cuuint64_t*, const cuuint64_t*, const cuuint32_t*,
                          const cuuint32_t*, CUtensorMapInterleave, CUtensorMapSwizzle, CUtensorMapL2promotion, CUtensorMapFloatOOBfill);
static void mkmap(EncFn enc, CUtensorMap* m, const void* base, int rank, const cuuint64_t* dims, const cuuint64_t* strides, const cuuint32_t* box, CUtensorMapSwizzle swz) {
  cuuint32_t es[5] = {1, 1, 1, 1, 1};
  enc(m, CU_TENSOR_MAP_DATA_TYPE_BFLOAT16, rank, const_cast<void*>(base), dims, strides, box, es, CU_TENSOR_MAP_INTERLEAVE_NONE, swz,
      CU_TENSOR_MAP_L2_PROMOTION_L2_128B, CU_TENSOR_MAP_FLOAT_OOB_FILL_NONE);
}

extern "C" void kernel_launch(void* const* d_in, const int* in_sizes, int n_in, void* d_out, int out_size) {
  void* fn = nullptr; cudaDriverEntryPointQueryResult qr;
  cudaGetDriverEntryPoint("cuTensorMapEncodeTiled", &fn, cudaEnableDefault, &qr);
  EncFn enc = (EncFn)fn;
  void* uy = nullptr; cudaGetSymbolAddress(&uy, g_uy);
  const cuuint64_t dx[2] = {640, 2048}, sx[1] = {1280};
  const cuuint32_t bx[2] = {64, 128}, bu[2] = {80, 128};
  const cuuint64_t dw[3] = {640, 640, 3}, sw[2] = {3840, 1280};
  const cuuint32_t br[3] = {16, 32, 3};
  const cuuint64_t dwa[4] = {64, 640, 10, 3}, swa[3] = {3840, 128, 1280}, dwb[4] = {32, 640, 20, 3}, swb[3] = {3840, 64, 1280};
  const cuuint32_t bwa[4] = {64, 32, 1, 3}, bwb[4] = {32, 32, 2, 3};
  const cuuint64_t dwo[2] = {640, 640};
  const cuuint32_t bwo[2] = {64, 80}, bo64[2] = {64, 64}, bo16[2] = {16, 64};
  const cuuint64_t dsa[2] = {2048, 1280}, ssa[1] = {4096};
  const cuuint32_t bsa[2] = {64, 80};
  const cuuint64_t dsb[2] = {64, 40960}, ssb[1] = {128};
  const cuuint32_t bsb[2] = {64, 32};
  const cuuint64_t dout[2] = {1280, 2048}, sout[1] = {2560};
  Params prm;
  mkmap(enc, &prm.m[M_X], d_in[7], 2, dx, sx, bx, CU_TENSOR_MAP_SWIZZLE_128B);
  mkmap(enc, &prm.m[M_W128], d_in[8], 4, dwa, swa, bwa, CU_TENSOR_MAP_SWIZZLE_128B);
  mkmap(enc, &prm.m[M_W64], d_in[8], 4, dwb, swb, bwb, CU_TENSOR_MAP_SWIZZLE_64B);
  mkmap(enc, &prm.m[M_WR], d_in[8], 3, dw, sw, br, CU_TENSOR_MAP_SWIZZLE_32B);
  mkmap(enc, &prm.m[M_WO], d_in[9], 2, dwo, sx, bwo, CU_TENSOR_MAP_SWIZZLE_128B);
  mkmap(enc, &prm.m[M_O64], d_out, 2, dout, sout, bo64, CU_TENSOR_MAP_SWIZZLE_128B);
  mkmap(enc, &prm.m[M_O16], d_out, 2, dout, sout, bo16, CU_TENSOR_MAP_SWIZZLE_NONE);
  mkmap(enc, &prm.m[M_SA], uy, 2, dsa, ssa, bsa, CU_TENSOR_MAP_SWIZZLE_128B);
  mkmap(enc, &prm.m[M_SB], uy, 2, dsb, ssb, bsb, CU_TENSOR_MAP_SWIZZLE_128B);
  mkmap(enc, &prm.m[M_OUT], d_out, 2, dout, sout, bu, CU_TENSOR_MAP_SWIZZLE_NONE);
  prm.u = (const __nv_bfloat16*)d_in[0]; prm.wo = (const __nv_bfloat16*)d_in[9];
  for (int i = 0; i < 4; i++) prm.par[i] = (const __nv_bfloat16*)d_in[1 + i];
  prm.logdt = (const __nv_bfloat16*)d_in[5]; prm.dskip = (const __nv_bfloat16*)d_in[6];
  cudaFuncSetAttribute(fused_kernel, cudaFuncAttributeMaxDynamicSharedMemorySize, SMEM_BYTES);
  cudaLaunchConfig_t cfg = {};
  cfg.gridDim = dim3(128); cfg.blockDim = dim3(512); cfg.dynamicSmemBytes = SMEM_BYTES; cfg.stream = cudaStreamPerThread;
  cudaLaunchAttribute at[1];
  at[0].id = cudaLaunchAttributeClusterDimension; at[0].val.clusterDim.x = 2; at[0].val.clusterDim.y = 1; at[0].val.clusterDim.z = 1;
  cfg.attrs = at; cfg.numAttrs = 1;
  cudaLaunchKernelEx(&cfg, fused_kernel, prm);
}
```

```cpp
#include <cuda_runtime.h>
#include <cuda_bf16.h>
#include <cuda_fp16.h>
#include <cuda.h>
#include <stdint.h>

#define U_AFTER 9
#define U_NPF 5
#define EN_ATT 1
#define EN_SSM 1

__device__ __align__(1024) __nv_bfloat16 g_uy[2 * 640 * 2048];
__device__ __align__(128) uint4 g_kvp[8 * 16 * 240];
__device__ __align__(128) uint4 g_o[128 * 1280];
__device__ __align__(128) unsigned g_flag[4 * 128 * 32];
__device__ unsigned g_epoch[128];
#define TS(i) do {} while (0)
#define DUMP(lo, hi) do {} while (0)
#define FIXCNT

constexpr uint32_t SB0 = 1024;
constexpr uint32_t W_SLOT = 15360, OFF_X = 76800;
constexpr uint32_t OFF_WOR = 81920, OFF_KVP = 10240, OFF_KVS = 71680, OFF_PK = 10240, OFF_V = 30720, OFF_EXTRA = 102400, OFF_KVB = OFF_EXTRA;
constexpr uint32_t OFF_BAR = 125952, OFF_BLK = 128000, BLK = 20480;
constexpr uint32_t B_D = 4096, B_D5 = 3088, B_D7 = 6176, B_D9 = 8224, B_TBL = 14400;
constexpr int T_S = 576, T_F2 = 624, T_F3 = 816;
constexpr uint32_t SMEM_BYTES = OFF_BLK + 5 * BLK;
enum { BR_FULL = 0, BR_WO = 5, BR_PUB = 7, BR_KVP = 8, BR_U = 9, BR_SUM = 10, BR_GEMM = 11, BR_YIN = 13, BR_EPOCH = 14,
       BR_FREE = 15, BR_RETRY = 17, BR_OFULL = 18, BR_EMPTY = 26, BR_KG1 = 31, BR_OEMPTY = 32, BR_Y = 39, BR_OSTG = 41, BR_KGEN = 42, BR_COUNT = 44 };
constexpr uint32_t OFF_EPOCH = OFF_BAR + 8 * BR_COUNT;
enum { M_X, M_W128, M_W64, M_WR, M_WO, M_O64, M_O16, M_SA, M_SB, M_OUT, M_COUNT };

__device__ __forceinline__ long long clk64() { long long t; asm volatile("mov.u64 %0, %%clock64;" : "=l"(t) :: "memory"); return t; }
__device__ __forceinline__ uint32_t smem_u32(const void* p) { return (uint32_t)__cvta_generic_to_shared(p); }
__host__ __device__ constexpr uint64_t mkdesc(uint32_t addr, uint32_t lbo, uint32_t sbo, uint32_t swz) {
  return (uint64_t)((addr & 0x3FFFF) >> 4) | ((uint64_t)(lbo >> 4) << 16) | ((uint64_t)(sbo >> 4) << 32) | ((uint64_t)swz << 62);
}
__device__ __forceinline__ uint64_t desc2(uint32_t lo, uint32_t hi) { uint64_t d; asm("mov.b64 %0, {%1, %2};" : "=l"(d) : "r"(lo), "r"(hi)); return d; }
__device__ __forceinline__ void mbar_init(uint32_t bar, uint32_t cnt) { asm volatile("mbarrier.init.shared::cta.b64 [%0], %1;" :: "r"(bar), "r"(cnt) : "memory"); }
__device__ __forceinline__ void mbar_expect_tx(uint32_t bar, uint32_t bytes) { asm volatile("mbarrier.arrive.expect_tx.shared::cta.b64 _, [%0], %1;" :: "r"(bar), "r"(bytes) : "memory"); }
__device__ __forceinline__ void mbar_arrive(uint32_t bar) { asm volatile("mbarrier.arrive.shared::cta.b64 _, [%0];" :: "r"(bar) : "memory"); }
__device__ __forceinline__ void mbar_wait(uint32_t bar, uint32_t parity) {
  asm volatile("{\n.reg .pred p;\n.reg .u32 c;\nmov.u32 c, 0;\n"
    "WL:\nmbarrier.try_wait.parity.shared::cta.b64 p, [%0], %1;\n@p bra WD;\n"
    "add.u32 c, c, 1;\nsetp.lt.u32 p, c, 200000;\n@p bra WL;\nWD:\n}" :: "r"(bar), "r"(parity) : "memory");
}
__device__ __forceinline__ void poll_all(const unsigned* p, unsigned val) {
  asm volatile("{\n.reg .pred p;\n.reg .u32 c, v;\nmov.u32 c, 0;\n"
    "PL:\nld.relaxed.gpu.global.u32 v, [%0];\nsetp.eq.u32 p, v, %1;\nvote.sync.all.pred p, p, 0xffffffff;\n@p bra PD;\n"
    "add.u32 c, c, 1;\nsetp.lt.u32 p, c, 100000;\n@p bra PL;\nPD:\n}" :: "l"(p), "r"(val) : "memory");
}
__device__ __forceinline__ void poll_all_acq(const unsigned* p, unsigned val) {
  asm volatile("{\n.reg .pred p;\n.reg .u32 c, v;\nmov.u32 c, 0;\n"
    "PL:\nld.acquire.gpu.global.u32 v, [%0];\nsetp.eq.u32 p, v, %1;\nvote.sync.all.pred p, p, 0xffffffff;\n@p bra PD;\n"
    "add.u32 c, c, 1;\nsetp.lt.u32 p, c, 100000;\n@p bra PL;\nPD:\n}" :: "l"(p), "r"(val) : "memory");
}
__device__ __forceinline__ unsigned poll_bit(const unsigned* p, unsigned val, unsigned mask) {
  unsigned bal;
  asm volatile("{\n.reg .pred p;\n.reg .u32 c, v;\nmov.u32 c, 0;\n"
    "PL:\nld.relaxed.gpu.global.u32 v, [%1];\nsetp.eq.u32 p, v, %2;\nvote.sync.ballot.b32 %0, p, 0xffffffff;\n"
    "and.b32 v, %0, %3;\nsetp.ne.u32 p, v, 0;\n@p bra PD;\n"
    "add.u32 c, c, 1;\nsetp.lt.u32 p, c, 100000;\n@p bra PL;\nPD:\n}" : "=&r"(bal) : "l"(p), "r"(val), "r"(mask) : "memory");
  return bal;
}
__device__ __forceinline__ void fix128_w0(uint32_t* v, const void* p, uint32_t tag, uint32_t mask) {
  asm volatile("{\n.reg .pred p;\n.reg .u32 c, x;\n.reg .b128 t;\n.reg .b64 lo, hi;\nmov.u32 c, 0;\n"
    "FL:\nxor.b32 x, %0, %5;\nand.b32 x, x, %6;\nsetp.eq.u32 p, x, 0;\n@p bra FD;\n"
    "ld.relaxed.gpu.global.b128 t, [%4];\nmov.b128 {lo, hi}, t;\nmov.b64 {%0, %1}, lo;\nmov.b64 {%2, %3}, hi;\n"
    "add.u32 c, c, 1;\nsetp.lt.u32 p, c, 100000;\n@p bra FL;\nFD:\n}"
    : "+r"(v[0]), "+r"(v[1]), "+r"(v[2]), "+r"(v[3]) : "l"(p), "r"(tag), "r"(mask) : "memory");
}
__device__ __forceinline__ void fix128_w3(uint32_t* v, const void* p, uint32_t tag, uint32_t mask) {
  asm volatile("{\n.reg .pred p;\n.reg .u32 c, x;\n.reg .b128 t;\n.reg .b64 lo, hi;\nmov.u32 c, 0;\n"
    "FL:\nxor.b32 x, %3, %5;\nand.b32 x, x, %6;\nsetp.eq.u32 p, x, 0;\n@p bra FD;\n"
    "ld.relaxed.gpu.global.b128 t, [%4];\nmov.b128 {lo, hi}, t;\nmov.b64 {%0, %1}, lo;\nmov.b64 {%2, %3}, hi;\n"
    "add.u32 c, c, 1;\nsetp.lt.u32 p, c, 100000;\n@p bra FL;\nFD:\n}"
    : "+r"(v[0]), "+r"(v[1]), "+r"(v[2]), "+r"(v[3]) : "l"(p), "r"(tag), "r"(mask) : "memory");
}
__device__ __forceinline__ void fence_acq() { asm volatile("fence.acq_rel.gpu;" ::: "memory"); }
__device__ __forceinline__ bool elect_one() {
  uint32_t p; asm volatile("{\n.reg .pred P;\nelect.sync _|P, 0xffffffff;\nselp.u32 %0, 1, 0, P;\n}" : "=r"(p)); return p;
}
__device__ __forceinline__ void bar_sync(int id, int n) { asm volatile("bar.sync %0, %1;" :: "r"(id), "r"(n) : "memory"); }
__device__ __forceinline__ void fence_async() { asm volatile("fence.proxy.async.shared::cta;" ::: "memory"); }
__device__ __forceinline__ void fence_async_g() { asm volatile("fence.proxy.async.global;" ::: "memory"); }
__device__ __forceinline__ void tma2d(uint32_t dst, const CUtensorMap* m, uint32_t bar, int c0, int c1) {
  asm volatile("cp.async.bulk.tensor.2d.shared::cluster.global.mbarrier::complete_tx::bytes [%0], [%1, {%3, %4}], [%2];"
    :: "r"(dst), "l"(m), "r"(bar), "r"(c0), "r"(c1) : "memory");
}
__device__ __forceinline__ void tma3d(uint32_t dst, const CUtensorMap* m, uint32_t bar, int c0, int c1, int c2) {
  asm volatile("cp.async.bulk.tensor.3d.shared::cluster.global.mbarrier::complete_tx::bytes [%0], [%1, {%3, %4, %5}], [%2];"
    :: "r"(dst), "l"(m), "r"(bar), "r"(c0), "r"(c1), "r"(c2) : "memory");
}
__device__ __forceinline__ void tma4d(uint32_t dst, const CUtensorMap* m, uint32_t bar, int c0, int c1, int c2, int c3) {
  asm volatile("cp.async.bulk.tensor.4d.shared::cluster.global.mbarrier::complete_tx::bytes [%0], [%1, {%3, %4, %5, %6}], [%2];"
    :: "r"(dst), "l"(m), "r"(bar), "r"(c0), "r"(c1), "r"(c2), "r"(c3) : "memory");
}
__device__ __forceinline__ void tma2d_st(const CUtensorMap* m, uint32_t src, int c0, int c1) {
  asm volatile("cp.async.bulk.tensor.2d.global.shared::cta.bulk_group [%0, {%2, %3}], [%1];"
    :: "l"(m), "r"(src), "r"(c0), "r"(c1) : "memory");
}
__device__ __forceinline__ void bulk_ld(uint32_t dst, const void* src, uint32_t bytes, uint32_t bar) {
  asm volatile("cp.async.bulk.shared::cluster.global.mbarrier::complete_tx::bytes [%0], [%1], %2, [%3];"
    :: "r"(dst), "l"(src), "r"(bytes), "r"(bar) : "memory");
}
__device__ __forceinline__ void bulk_st(void* dst, uint32_t src, uint32_t bytes) {
  asm volatile("cp.async.bulk.global.shared::cta.bulk_group [%0], [%1], %2;" :: "l"(dst), "r"(src), "r"(bytes) : "memory");
}
__device__ __forceinline__ void bulk_commit() { asm volatile("cp.async.bulk.commit_group;" ::: "memory"); }
__device__ __forceinline__ void bulk_wait0() { asm volatile("cp.async.bulk.wait_group 0;" ::: "memory"); }
__device__ __forceinline__ void bulk_wait0_read() { asm volatile("cp.async.bulk.wait_group.read 0;" ::: "memory"); }
__device__ __forceinline__ unsigned ld_rlx(const unsigned* p) { unsigned v; asm volatile("ld.relaxed.gpu.global.u32 %0, [%1];" : "=r"(v) : "l"(p) : "memory"); return v; }
__device__ __forceinline__ unsigned ld_acq(const unsigned* p) { unsigned v; asm volatile("ld.acquire.gpu.global.u32 %0, [%1];" : "=r"(v) : "l"(p) : "memory"); return v; }
__device__ __forceinline__ void st_rlx(unsigned* p, unsigned v) { asm volatile("st.relaxed.gpu.global.u32 [%0], %1;" :: "l"(p), "r"(v) : "memory"); }
__device__ __forceinline__ void st_rel(unsigned* p, unsigned v) { asm volatile("st.release.gpu.global.u32 [%0], %1;" :: "l"(p), "r"(v) : "memory"); }
__device__ __forceinline__ void ld128_rlx(uint32_t* v, const void* p) {
  asm volatile("{\n.reg .b128 t;\n.reg .b64 lo, hi;\nld.relaxed.gpu.global.b128 t, [%4];\nmov.b128 {lo, hi}, t;\n"
    "mov.b64 {%0, %1}, lo;\nmov.b64 {%2, %3}, hi;\n}" : "=r"(v[0]), "=r"(v[1]), "=r"(v[2]), "=r"(v[3]) : "l"(p) : "memory");
}
__device__ __forceinline__ void st128_rlx(void* p, const uint32_t* v) {
  asm volatile("{\n.reg .b128 t;\n.reg .b64 lo, hi;\nmov.b64 lo, {%1, %2};\nmov.b64 hi, {%3, %4};\nmov.b128 t, {lo, hi};\n"
    "st.relaxed.gpu.global.b128 [%0], t;\n}" :: "l"(p), "r"(v[0]), "r"(v[1]), "r"(v[2]), "r"(v[3]) : "memory");
}
__device__ __forceinline__ uint32_t lds32(uint32_t a) { uint32_t v; asm volatile("ld.shared.u32 %0, [%1];" : "=r"(v) : "r"(a) : "memory"); return v; }
__device__ __forceinline__ uint32_t lds32v(uint32_t a) { uint32_t v; asm volatile("ld.volatile.shared.u32 %0, [%1];" : "=r"(v) : "r"(a) : "memory"); return v; }
__device__ __forceinline__ uint32_t cpa(uint32_t a, uint32_t one) { uint32_t v; asm volatile("mul.lo.u32 %0, %1, %2;" : "=r"(v) : "r"(a), "r"(one)); return v; }
__device__ __forceinline__ uint32_t cpb(uint32_t a, uint32_t zero) { uint32_t v; asm volatile("or.b32 %0, %1, %2;" : "=r"(v) : "r"(a), "r"(zero)); return v; }
__device__ __forceinline__ uint32_t lds16(uint32_t a) { uint16_t v; asm volatile("ld.shared.u16 %0, [%1];" : "=h"(v) : "r"(a) : "memory"); return v; }
__device__ __forceinline__ float ldsf(uint32_t a) { float v; asm volatile("ld.shared.f32 %0, [%1];" : "=f"(v) : "r"(a) : "memory"); return v; }
__device__ __forceinline__ void lds128(uint32_t* v, uint32_t a) { asm volatile("ld.shared.v4.u32 {%0,%1,%2,%3}, [%4];" : "=r"(v[0]), "=r"(v[1]), "=r"(v[2]), "=r"(v[3]) : "r"(a) : "memory"); }
__device__ __forceinline__ void sts32(uint32_t a, uint32_t v) { asm volatile("st.shared.u32 [%0], %1;" :: "r"(a), "r"(v) : "memory"); }
__device__ __forceinline__ void sts16(uint32_t a, uint32_t v) { asm volatile("st.shared.u16 [%0], %1;" :: "r"(a), "h"((uint16_t)v) : "memory"); }
__device__ __forceinline__ void sts64f(uint32_t a, float x, float y) { asm volatile("st.shared.v2.f32 [%0], {%1,%2};" :: "r"(a), "f"(x), "f"(y) : "memory"); }
__device__ __forceinline__ void sts128(uint32_t a, uint32_t x, uint32_t y, uint32_t z, uint32_t w) { asm volatile("st.shared.v4.u32 [%0], {%1,%2,%3,%4};" :: "r"(a), "r"(x), "r"(y), "r"(z), "r"(w) : "memory"); }
__device__ __forceinline__ void stsm4(uint32_t a, uint32_t r0, uint32_t r1, uint32_t r2, uint32_t r3) {
  asm volatile("stmatrix.sync.aligned.m8n8.x4.shared.b16 [%0], {%1,%2,%3,%4};" :: "r"(a), "r"(r0), "r"(r1), "r"(r2), "r"(r3) : "memory");
}
__device__ __forceinline__ void stsm4t(uint32_t a, uint32_t r0, uint32_t r1, uint32_t r2, uint32_t r3) {
  asm volatile("stmatrix.sync.aligned.m8n8.x4.trans.shared.b16 [%0], {%1,%2,%3,%4};" :: "r"(a), "r"(r0), "r"(r1), "r"(r2), "r"(r3) : "memory");
}
__device__ __forceinline__ void ldsm4t(uint32_t* r, uint32_t a) {
  asm volatile("ldmatrix.sync.aligned.m8n8.x4.trans.shared.b16 {%0,%1,%2,%3}, [%4];" : "=r"(r[0]), "=r"(r[1]), "=r"(r[2]), "=r"(r[3]) : "r"(a) : "memory");
}
__device__ __forceinline__ void ldsm4(uint32_t* r, uint32_t a) {
  asm volatile("ldmatrix.sync.aligned.m8n8.x4.shared.b16 {%0,%1,%2,%3}, [%4];" : "=r"(r[0]), "=r"(r[1]), "=r"(r[2]), "=r"(r[3]) : "r"(a) : "memory");
}
__device__ __forceinline__ void mma16816(float* d, const uint32_t* a, const uint32_t* b) {
  asm volatile("mma.sync.aligned.m16n8k16.row.col.f32.bf16.bf16.f32 {%0,%1,%2,%3}, {%4,%5,%6,%7}, {%8,%9}, {%0,%1,%2,%3};"
    : "+f"(d[0]), "+f"(d[1]), "+f"(d[2]), "+f"(d[3]) : "r"(a[0]), "r"(a[1]), "r"(a[2]), "r"(a[3]), "r"(b[0]), "r"(b[1]));
}
__device__ __forceinline__ uint32_t pack2(float lo, float hi) { uint32_t r; asm("cvt.rn.bf16x2.f32 %0, %1, %2;" : "=r"(r) : "f"(hi), "f"(lo)); return r; }
__device__ __forceinline__ uint32_t packh(float lo, float hi) { uint32_t r; asm("cvt.rn.f16x2.f32 %0, %1, %2;" : "=r"(r) : "f"(hi), "f"(lo)); return r; }
__device__ __forceinline__ uint32_t hcmul(uint32_t x, uint32_t zp, uint32_t zq) {
  const __half2 xx = *reinterpret_cast<__half2*>(&x);
  const __half2 r = __hfma2(__high2half2(xx), *reinterpret_cast<__half2*>(&zq), __hmul2(__low2half2(xx), *reinterpret_cast<__half2*>(&zp)));
  return *reinterpret_cast<const uint32_t*>(&r);
}
__device__ __forceinline__ void hcm2(uint32_t xr, uint32_t xi, uint32_t z, uint32_t& pr, uint32_t& pi) {
  const __half2 a = *reinterpret_cast<__half2*>(&xr), b = *reinterpret_cast<__half2*>(&xi), zz = *reinterpret_cast<__half2*>(&z);
  const __half2 re = __hfma2(__hneg2(b), __high2half2(zz), __hmul2(a, __low2half2(zz)));
  const __half2 im = __hfma2(a, __high2half2(zz), __hmul2(b, __low2half2(zz)));
  pr = *reinterpret_cast<const uint32_t*>(&re); pi = *reinterpret_cast<const uint32_t*>(&im);
}
__device__ __forceinline__ void sts64(uint32_t a, uint32_t x, uint32_t y) { asm volatile("st.shared.v2.u32 [%0], {%1,%2};" :: "r"(a), "r"(x), "r"(y) : "memory"); }
__device__ __forceinline__ void lds64(uint32_t* v, uint32_t a) { asm volatile("ld.shared.v2.u32 {%0,%1}, [%2];" : "=r"(v[0]), "=r"(v[1]) : "r"(a) : "memory"); }
__device__ __forceinline__ float bf_lo(uint32_t v) { return __uint_as_float(v << 16); }
__device__ __forceinline__ float bf_hi(uint32_t v) { return __uint_as_float(v & 0xffff0000u); }
__device__ __forceinline__ float bf_round(float x) { return bf_lo(pack2(x, 0.f)); }
__device__ __forceinline__ float ex2(float x) { float r; asm("ex2.approx.ftz.f32 %0, %1;" : "=f"(r) : "f"(x)); return r; }
__device__ __forceinline__ float phi(float t, float l2e = 1.44269504089f) {
  float e = ex2(t * l2e) + 1e-6f;
  asm("{\n.reg .pred p;\nsetp.gt.f32 p, %1, 0f00000000;\n@p add.f32 %0, %1, 0f3F800008;\n}" : "+f"(e) : "f"(t));
  return e;
}
__device__ __forceinline__ void wg_fence() { asm volatile("wgmma.fence.sync.aligned;" ::: "memory"); }
__device__ __forceinline__ void wg_commit() { asm volatile("wgmma.commit_group.sync.aligned;" ::: "memory"); }
template <int N> __device__ __forceinline__ void wg_wait() { asm volatile("wgmma.wait_group.sync.aligned %0;" :: "n"(N) : "memory"); }
template <int N> __device__ __forceinline__ void pin(float* a) {
  #pragma unroll
  for (int i = 0; i < N; i++) asm volatile("" : "+f"(a[i]) :: "memory");
}
__device__ __forceinline__ int rtid() { int t; asm volatile("mov.u32 %0, %%tid.x;" : "=r"(t)); return t; }
__device__ __forceinline__ int opaque(int v) { asm volatile("" : "+r"(v)); return v; }
template <int N> __device__ __forceinline__ void zero(float* a) {
  #pragma unroll
  for (int i = 0; i < N; i++) asm volatile("mov.b32 %0, 0;" : "=f"(a[i]));
}
template <int N> __device__ __forceinline__ void pinu(uint32_t* a) {
  #pragma unroll
  for (int i = 0; i < N; i++) asm volatile("" : "+r"(a[i]) :: "memory");
}
__device__ __forceinline__ void cexp_t(float lg2mag, float turns, float& re, float& im) {
  float m = ex2(lg2mag);
  float fr = (turns - __fadd_rn(__fadd_rn(turns, 12582912.f), -12582912.f)) * 6.283185307f;
  re = m * __cosf(fr); im = m * __sinf(fr);
}
__device__ __forceinline__ void cmul(float ar, float ai, float br, float bi, float& cr, float& ci) {
  cr = fmaf(ar, br, -ai * bi); ci = fmaf(ar, bi, ai * br);
}

__device__ __forceinline__ void wg_ss192_tb(float* d, uint64_t da, uint64_t db, int scale_d) {
  asm volatile("{\n.reg .pred p;\nsetp.ne.b32 p, %98, 0;\n"
    "wgmma.mma_async.sync.aligned.m64n192k16.f32.bf16.bf16 "
    "{%0, %1, %2, %3, %4, %5, %6, %7, %8, %9, %10, %11, %12, %13, %14, %15, %16, %17, %18, %19, %20, %21, %22, %23, %24, %25, %26, %27, %28, %29, %30, %31, %32, %33, %34, %35, %36, %37, %38, %39, %40, %41, %42, %43, %44, %45, %46, %47, %48, %49, %50, %51, %52, %53, %54, %55, %56, %57, %58, %59, %60, %61, %62, %63, %64, %65, %66, %67, %68, %69, %70, %71, %72, %73, %74, %75, %76, %77, %78, %79, %80, %81, %82, %83, %84, %85, %86, %87, %88, %89, %90, %91, %92, %93, %94, %95}, %96, %97, p, 1, 1, 0, 1;\n}\n"
    : "+f"(d[0]), "+f"(d[1]), "+f"(d[2]), "+f"(d[3]), "+f"(d[4]), "+f"(d[5]), "+f"(d[6]), "+f"(d[7]), "+f"(d[8]), "+f"(d[9]), "+f"(d[10]), "+f"(d[11]), "+f"(d[12]), "+f"(d[13]), "+f"(d[14]), "+f"(d[15]), "+f"(d[16]), "+f"(d[17]), "+f"(d[18]), "+f"(d[19]), "+f"(d[20]), "+f"(d[21]), "+f"(d[22]), "+f"(d[23]), "+f"(d[24]), "+f"(d[25]), "+f"(d[26]), "+f"(d[27]), "+f"(d[28]), "+f"(d[29]), "+f"(d[30]), "+f"(d[31]), "+f"(d[32]), "+f"(d[33]), "+f"(d[34]), "+f"(d[35]), "+f"(d[36]), "+f"(d[37]), "+f"(d[38]), "+f"(d[39]), "+f"(d[40]), "+f"(d[41]), "+f"(d[42]), "+f"(d[43]), "+f"(d[44]), "+f"(d[45]), "+f"(d[46]), "+f"(d[47]), "+f"(d[48]), "+f"(d[49]), "+f"(d[50]), "+f"(d[51]), "+f"(d[52]), "+f"(d[53]), "+f"(d[54]), "+f"(d[55]), "+f"(d[56]), "+f"(d[57]), "+f"(d[58]), "+f"(d[59]), "+f"(d[60]), "+f"(d[61]), "+f"(d[62]), "+f"(d[63]), "+f"(d[64]), "+f"(d[65]), "+f"(d[66]), "+f"(d[67]), "+f"(d[68]), "+f"(d[69]), "+f"(d[70]), "+f"(d[71]), "+f"(d[72]), "+f"(d[73]), "+f"(d[74]), "+f"(d[75]), "+f"(d[76]), "+f"(d[77]), "+f"(d[78]), "+f"(d[79]), "+f"(d[80]), "+f"(d[81]), "+f"(d[82]), "+f"(d[83]), "+f"(d[84]), "+f"(d[85]), "+f"(d[86]), "+f"(d[87]), "+f"(d[88]), "+f"(d[89]), "+f"(d[90]), "+f"(d[91]), "+f"(d[92]), "+f"(d[93]), "+f"(d[94]), "+f"(d[95])
    : "l"(da), "l"(db), "r"(scale_d));
}
__device__ __forceinline__ void wg_ss48_tb(float* d, uint64_t da, uint64_t db, int scale_d) {
  asm volatile("{\n.reg .pred p;\nsetp.ne.b32 p, %26, 0;\n"
    "wgmma.mma_async.sync.aligned.m64n48k16.f32.bf16.bf16 "
    "{%0, %1, %2, %3, %4, %5, %6, %7, %8, %9, %10, %11, %12, %13, %14, %15, %16, %17, %18, %19, %20, %21, %22, %23}, %24, %25, p, 1, 1, 0, 1;\n}\n"
    : "+f"(d[0]), "+f"(d[1]), "+f"(d[2]), "+f"(d[3]), "+f"(d[4]), "+f"(d[5]), "+f"(d[6]), "+f"(d[7]), "+f"(d[8]), "+f"(d[9]), "+f"(d[10]), "+f"(d[11]), "+f"(d[12]), "+f"(d[13]), "+f"(d[14]), "+f"(d[15]), "+f"(d[16]), "+f"(d[17]), "+f"(d[18]), "+f"(d[19]), "+f"(d[20]), "+f"(d[21]), "+f"(d[22]), "+f"(d[23])
    : "l"(da), "l"(db), "r"(scale_d));
}
__device__ __forceinline__ void wg_ss48_tt(float* d, uint64_t da, uint64_t db, int scale_d) {
  asm volatile("{\n.reg .pred p;\nsetp.ne.b32 p, %26, 0;\n"
    "wgmma.mma_async.sync.aligned.m64n48k16.f32.bf16.bf16 "
    "{%0, %1, %2, %3, %4, %5, %6, %7, %8, %9, %10, %11, %12, %13, %14, %15, %16, %17, %18, %19, %20, %21, %22, %23}, %24, %25, p, 1, 1, 1, 1;\n}\n"
    : "+f"(d[0]), "+f"(d[1]), "+f"(d[2]), "+f"(d[3]), "+f"(d[4]), "+f"(d[5]), "+f"(d[6]), "+f"(d[7]), "+f"(d[8]), "+f"(d[9]), "+f"(d[10]), "+f"(d[11]), "+f"(d[12]), "+f"(d[13]), "+f"(d[14]), "+f"(d[15]), "+f"(d[16]), "+f"(d[17]), "+f"(d[18]), "+f"(d[19]), "+f"(d[20]), "+f"(d[21]), "+f"(d[22]), "+f"(d[23])
    : "l"(da), "l"(db), "r"(scale_d));
}
__device__ __forceinline__ void wg_rs88_tb(float* d, const uint32_t* a, uint64_t db, int scale_d) {
  asm volatile("{\n.reg .pred p;\nsetp.ne.b32 p, %49, 0;\n"
    "wgmma.mma_async.sync.aligned.m64n88k16.f32.bf16.bf16 "
    "{%0, %1, %2, %3, %4, %5, %6, %7, %8, %9, %10, %11, %12, %13, %14, %15, %16, %17, %18, %19, %20, %21, %22, %23, %24, %25, %26, %27, %28, %29, %30, %31, %32, %33, %34, %35, %36, %37, %38, %39, %40, %41, %42, %43}, {%44, %45, %46, %47}, %48, p, 1, 1, 1;\n}\n"
    : "+f"(d[0]), "+f"(d[1]), "+f"(d[2]), "+f"(d[3]), "+f"(d[4]), "+f"(d[5]), "+f"(d[6]), "+f"(d[7]), "+f"(d[8]), "+f"(d[9]), "+f"(d[10]), "+f"(d[11]), "+f"(d[12]), "+f"(d[13]), "+f"(d[14]), "+f"(d[15]), "+f"(d[16]), "+f"(d[17]), "+f"(d[18]), "+f"(d[19]), "+f"(d[20]), "+f"(d[21]), "+f"(d[22]), "+f"(d[23]), "+f"(d[24]), "+f"(d[25]), "+f"(d[26]), "+f"(d[27]), "+f"(d[28]), "+f"(d[29]), "+f"(d[30]), "+f"(d[31]), "+f"(d[32]), "+f"(d[33]), "+f"(d[34]), "+f"(d[35]), "+f"(d[36]), "+f"(d[37]), "+f"(d[38]), "+f"(d[39]), "+f"(d[40]), "+f"(d[41]), "+f"(d[42]), "+f"(d[43])
    : "r"(a[0]), "r"(a[1]), "r"(a[2]), "r"(a[3]), "l"(db), "r"(scale_d));
}
__device__ __forceinline__ void wg_ss80_tb(float* d, uint64_t da, uint64_t db, int scale_d) {
  asm volatile("{\n.reg .pred p;\nsetp.ne.b32 p, %42, 0;\n"
    "wgmma.mma_async.sync.aligned.m64n80k16.f32.bf16.bf16 "
    "{%0, %1, %2, %3, %4, %5, %6, %7, %8, %9, %10, %11, %12, %13, %14, %15, %16, %17, %18, %19, %20, %21, %22, %23, %24, %25, %26, %27, %28, %29, %30, %31, %32, %33, %34, %35, %36, %37, %38, %39}, %40, %41, p, 1, 1, 0, 1;\n}\n"
    : "+f"(d[0]), "+f"(d[1]), "+f"(d[2]), "+f"(d[3]), "+f"(d[4]), "+f"(d[5]), "+f"(d[6]), "+f"(d[7]), "+f"(d[8]), "+f"(d[9]), "+f"(d[10]), "+f"(d[11]), "+f"(d[12]), "+f"(d[13]), "+f"(d[14]), "+f"(d[15]), "+f"(d[16]), "+f"(d[17]), "+f"(d[18]), "+f"(d[19]), "+f"(d[20]), "+f"(d[21]), "+f"(d[22]), "+f"(d[23]), "+f"(d[24]), "+f"(d[25]), "+f"(d[26]), "+f"(d[27]), "+f"(d[28]), "+f"(d[29]), "+f"(d[30]), "+f"(d[31]), "+f"(d[32]), "+f"(d[33]), "+f"(d[34]), "+f"(d[35]), "+f"(d[36]), "+f"(d[37]), "+f"(d[38]), "+f"(d[39])
    : "l"(da), "l"(db), "r"(scale_d));
}
__device__ __forceinline__ void wg_ss48_tt_h(float* d, uint64_t da, uint64_t db, int scale_d) {
  asm volatile("{\n.reg .pred p;\nsetp.ne.b32 p, %26, 0;\n"
    "wgmma.mma_async.sync.aligned.m64n48k16.f32.f16.f16 "
    "{%0, %1, %2, %3, %4, %5, %6, %7, %8, %9, %10, %11, %12, %13, %14, %15, %16, %17, %18, %19, %20, %21, %22, %23}, %24, %25, p, 1, 1, 1, 1;\n}\n"
    : "+f"(d[0]), "+f"(d[1]), "+f"(d[2]), "+f"(d[3]), "+f"(d[4]), "+f"(d[5]), "+f"(d[6]), "+f"(d[7]), "+f"(d[8]), "+f"(d[9]), "+f"(d[10]), "+f"(d[11]), "+f"(d[12]), "+f"(d[13]), "+f"(d[14]), "+f"(d[15]), "+f"(d[16]), "+f"(d[17]), "+f"(d[18]), "+f"(d[19]), "+f"(d[20]), "+f"(d[21]), "+f"(d[22]), "+f"(d[23])
    : "l"(da), "l"(db), "r"(scale_d));
}

struct Params {
  const __nv_bfloat16 *par[4], *logdt, *dskip, *u, *wo;
  CUtensorMap m[M_COUNT];
};

#define CHUNK(i) ((i) == 0 ? c : ((i) == 7 ? (c ^ 1) : (((c & 6) + 1 + (i)) & 7)))
#define FLAG(kind, rr, cc) (&g_flag[((kind) * 128 + (rr) * 8 + (cc)) * 32])
#define SLOT(i) ((i) == 0 || (i) == 5 ? OFF_EXTRA : OFF_BLK + ((i) == 7 ? 0 : (i) == 6 ? 4 : (i) - 1) * BLK)
__device__ __forceinline__ void load_quad(uint32_t* A, uint32_t addr) {
  A[0] = lds32v(addr); A[1] = lds32v(addr + 32); A[2] = lds32v(addr - 32); A[3] = lds32v(addr);
}

__global__ void __launch_bounds__(512, 1) fused_kernel(const __grid_constant__ Params prm) {
  extern __shared__ unsigned char smem_raw[];
  const uint32_t sb = __shfl_sync(0xffffffff, smem_u32(smem_raw), 0);
  const int tid = threadIdx.x, lane = tid & 31;
  const int warp = __shfl_sync(0xffffffff, tid >> 5, 0), wg = warp >> 2, w4 = warp & 3;
  const int cta = blockIdx.x, r = cta >> 3, c = cta & 7;
  if ((sb & 0xffffffu) != SB0) return;
#define BAR(i) (sb + OFF_BAR + 8 * (i))
  const bool sw64 = ((c + 1) & 2) != 0;

  if (wg == 3) {
    if (warp == 13 && elect_one()) {
      #pragma unroll
      for (int i = M_W128; i <= M_WR; i++) asm volatile("prefetch.tensormap [%0];" :: "l"(&prm.m[i]) : "memory");
    }
    asm volatile("setmaxnreg.dec.sync.aligned.u32 56;");
    const int tid = rtid(), lane = tid & 31;
    if (warp == 12) {
      if (elect_one()) {
        #pragma unroll
        for (int i = 0; i < 5; i++) mbar_init(BAR(BR_FULL + i), 1);
        asm volatile("fence.mbarrier_init.release.cluster;" ::: "memory");
      }
      {
        const CUtensorMap* mwp = &prm.m[sw64 ? M_W64 : M_W128];
        const int mcol = (c * 80 + (c & 1) * 16) >> (sw64 ? 5 : 6), rcol = c * 80 + ((c & 1) ? 0 : 64);
        uint32_t s = 0, ph = 1, xs = 0;
        #pragma unroll 1
        for (int kb = 0; kb < 20; kb++) {
          if (kb == 4) bar_sync(0, 512);
          if (EN_SSM && kb == 4) mbar_wait(BAR(BR_KG1), 0);
          if (kb >= 5) mbar_wait(BAR(BR_EMPTY) + 8 * s, ph);
          if (EN_ATT && elect_one()) {
            const uint32_t st = sb + s * W_SLOT, fb = BAR(BR_FULL) + 8 * s;
            mbar_expect_tx(fb, (kb & 1) ? W_SLOT : W_SLOT + 16384);
            if (!(kb & 1)) tma2d(sb + OFF_X + xs, &prm.m[M_X], fb, kb * 32, r * 128);
            tma4d(st, mwp, fb, 0, kb * 32, mcol, 0);
            tma3d(st + 12288, &prm.m[M_WR], fb, rcol, kb * 32, 0);
          }
          if (kb == 14 && elect_one()) asm volatile("cp.async.bulk.prefetch.L2.global [%0], 6400;" :: "l"(prm.wo + cta * 3200) : "memory");
          if (!EN_ATT && kb == 4) break;
          if (++s == 5) { s = 0; ph ^= 1; }
          if (kb & 1) { xs += 16384; if (xs == 49152) xs = 0; }
        }
      }
      if (EN_ATT) {
      mbar_wait(BAR(BR_EPOCH), 0);
      const unsigned epoch = lds32(sb + OFF_EPOCH);
      const unsigned* fo = FLAG(3, r, lane & 7);
      unsigned seen = __ballot_sync(0xffffffff, ld_rlx(lane < 16 ? fo : FLAG(0, lane & 15, c)) == epoch) & 0xffu;
      mbar_wait(BAR(BR_GEMM), 0);
      if (elect_one()) {
        mbar_expect_tx(BAR(BR_WO), 10240);
        tma2d(sb, &prm.m[M_WO], BAR(BR_WO), c * 64, c * 80);
        mbar_expect_tx(BAR(BR_KVP), 61440);
        mbar_expect_tx(BAR(BR_WO + 1), 7 * 10240);
      }
      {
        uint32_t ds = sb + OFF_WOR + (lane >> 3) * 128 + (((lane & 7) ^ (lane >> 3)) << 4);
        #pragma unroll 1
        for (int h = 0; h < 2; h++) {
          const int i = (lane & 6) + h;
          const char* gs = reinterpret_cast<const char*>(prm.wo) + (size_t)((lane >> 3) + CHUNK(i) * 80) * 1280 + 1024 + c * 32 + (lane & 1) * 16;
          #pragma unroll 2
          for (int q = 0; q < 20; q++) {
            asm volatile("cp.async.cg.shared.global [%0], [%1], 16;" :: "r"(ds), "l"(gs) : "memory");
            ds = (ds + 512) ^ 64; gs += 5120;
          }
        }
      }
      mbar_wait(BAR(BR_PUB), 0);
      poll_all(FLAG(0, lane & 15, c), epoch);
      if (elect_one()) { TS(23); bulk_ld(sb + OFF_KVP, &g_kvp[c * 16 * 240], 61440, BAR(BR_KVP)); }
      asm volatile("cp.async.wait_all;" ::: "memory");
      fence_async();
      mbar_arrive(BAR(BR_WO));
      mbar_wait(BAR(BR_SUM), 0);
      if (elect_one()) {
        #pragma unroll 1
        for (int i = 1; i < 8; i++) tma2d(sb + i * 10240, &prm.m[M_WO], BAR(BR_WO + 1), c * 64, CHUNK(i) * 80);
      }
      mbar_wait(BAR(BR_OSTG), 0);
      if (elect_one()) {
        bulk_st(&g_o[cta * 1280], sb + OFF_EXTRA, 20480);
        bulk_commit();
        bulk_wait0();
        st_rlx(FLAG(3, r, c), epoch);
        TS(20);
      }
      __syncwarp();
      #pragma unroll 1
      for (int i = 1; i < 8; i++) {
        const int src = CHUNK(i);
        if (!((seen >> src) & 1)) seen = poll_bit(fo, epoch, 1u << src);
        if (i == 5 || i == 7) mbar_wait(BAR(BR_OEMPTY) + 4 * (i - 5), 0);
        if (EN_SSM && (i == 1 || i == 4)) mbar_wait(BAR(BR_FREE) + 2 * (i & 4), 0);
        if (elect_one()) {
          mbar_expect_tx(BAR(BR_OFULL) + 8 * i, 20480);
          bulk_ld(sb + SLOT(i), &g_o[(r * 8 + src) * 1280], 20480, BAR(BR_OFULL) + 8 * i);
          if (i == 1) TS(21);
          if (i == 7) TS(22);
        }
        __syncwarp();
      }
      if (lane == 0) { DUMP(20, 30); }
      }
    } else {
      const int hw = warp - 13, ht = tid - 416;
      const unsigned epoch = ld_rlx(&g_epoch[cta]) + 1;
      if (hw == 2 && elect_one()) {
        #pragma unroll
        for (int i = 5; i < BR_COUNT; i++) mbar_init(BAR(i), i == BR_WO ? 33 : i < BR_EMPTY ? 1 : i < BR_OEMPTY ? 2 : i < BR_Y ? 8 : i < BR_OSTG ? 128 : 256);
        asm volatile("fence.mbarrier_init.release.cluster;" ::: "memory");
      }
      bar_sync(0, 512);
      if (EN_SSM) {
      #pragma unroll 1
      for (int i = hw; i < 5; i += 3) {
        const uint32_t ln = rtid(), cg = c * 10 + i * 2 + ((ln >> 4) & 1), t0 = r * 16 + (ln & 15);
        const uint4* gs = reinterpret_cast<const uint4*>(prm.u) + (t0 * 640 + cg);
        uint4* gd = reinterpret_cast<uint4*>(g_uy) + (cg * 2048 + t0);
        uint4 v[8];
        #pragma unroll
        for (int q = 0; q < 8; q++) v[q] = __ldg(gs + q * 80);
#define TR(o, f, sel) asm volatile("st.global.v4.u32 [%0], {%1,%2,%3,%4};" :: "l"(gd + (o)), "r"(__byte_perm(v[0].f, v[1].f, sel)), \
          "r"(__byte_perm(v[2].f, v[3].f, sel)), "r"(__byte_perm(v[4].f, v[5].f, sel)), "r"(__byte_perm(v[6].f, v[7].f, sel)) : "memory")
        TR(0, x, 0x5410); TR(256, x, 0x7632); TR(512, y, 0x5410); TR(768, y, 0x7632);
        TR(1024, z, 0x5410); TR(1280, z, 0x7632); TR(1536, w, 0x5410); TR(1792, w, 0x7632);
      }
      }
      if (hw == 1 && elect_one()) {
        #pragma unroll
        for (int i = M_WO; i < M_COUNT; i++) asm volatile("prefetch.tensormap [%0];" :: "l"(&prm.m[i]) : "memory");
      }
      bar_sync(5, 96);
      if (ht == 0) {
        st_rlx(&g_epoch[cta], epoch);
        sts32(sb + OFF_EPOCH, epoch);
        mbar_arrive(BAR(BR_EPOCH));
      }
      if (EN_SSM) {
      const int mi = lane >> 3, rw = lane & 7, ch0 = c * 80 + r * 5;
      if (ht == 0) TS(36);
      if (hw == 0) {
        if (lane == 0) { st_rel(FLAG(1, r, c), epoch); TS(30); }
        __syncwarp();
        poll_all_acq(FLAG(1, lane & 15, c), epoch);
        mbar_wait(BAR(BR_KG1), 0);
        if (elect_one()) {
          fence_async_g();
          mbar_expect_tx(BAR(BR_U), 20480);
          #pragma unroll 1
          for (int q = 0; q < 5; q++) tma2d(sb + OFF_BLK + q * BLK, &prm.m[M_SB], BAR(BR_U), 0, (ch0 + q) * 32);
          TS(31);
        }
        __syncwarp();
      }
      if (hw == 0) {
        #pragma unroll 1
        for (int p = 0; p < 2; p++) {
          mbar_wait(BAR(BR_Y) + 8 * p, 0);
          if (elect_one()) {
            #pragma unroll 1
            for (int k = 4 * p; k < 4 + p; k++) tma2d_st(&prm.m[M_SB], sb + OFF_BLK + k * BLK, 0, (640 + ch0 + k) * 32);
            bulk_commit(); bulk_wait0_read();
            mbar_arrive(BAR(BR_FREE) + 8 * p);
          }
          __syncwarp();
        }
        if (elect_one()) {
          mbar_expect_tx(BAR(BR_YIN), 20480);
          bulk_wait0();
          st_rel(FLAG(2, r, c), epoch);
          TS(33);
        }
        __syncwarp();
        poll_all_acq(FLAG(2, lane & 15, c), epoch);
        if (EN_ATT) mbar_wait(BAR(BR_OEMPTY + 3), 0);
        if (elect_one()) {
          fence_async_g();
          tma2d(sb + OFF_BLK + BLK, &prm.m[M_SA], BAR(BR_YIN), r * 128, 640 + c * 80);
          tma2d(sb + OFF_BLK + BLK + 10240, &prm.m[M_SA], BAR(BR_YIN), r * 128 + 64, 640 + c * 80);
          TS(34);
        }
      }
      {
        uint32_t sa = sb + OFF_BLK + BLK + (hw * 8 + rw) * 128 + ((mi ^ rw) << 4);
        uint32_t da = sb + OFF_BLK + 2 * BLK + (8 * mi + rw) * 160 + hw * 16;
        mbar_wait(BAR(BR_YIN), 0);
        #pragma unroll 1
        for (int i = hw; i < 10; i += 3) {
          uint32_t v[4][4];
          #pragma unroll
          for (int q = 0; q < 4; q++) ldsm4t(v[q], (sa ^ ((q & 1) * 64)) + (q >> 1) * 10240);
          #pragma unroll
          for (int q = 0; q < 4; q++) stsm4(da + q * 5120, v[q][0], v[q][1], v[q][2], v[q][3]);
          sa += 3072; da += 48;
        }
      }
      fence_async();
      bar_sync(5, 96);
      if (hw == 0 && elect_one()) {
        tma2d_st(&prm.m[M_OUT], sb + OFF_BLK + 2 * BLK, c * 80, r * 128);
        bulk_commit(); bulk_wait0_read();
        TS(35); DUMP(30, 40); DUMP(0, 1);
      }
      }
    }
  } else {
    const int g = lane >> 2, tq = lane & 3, t7 = tid & 127;
    uint32_t pr[3][3];
    {
      const int ch = c * 80 + r * 5 + wg;
      uint32_t raw[3][6];
      #pragma unroll
      for (int e = 0; e < 6; e++) {
        const __nv_bfloat16* pp = e < 4 ? prm.par[e] + ch * 128 + t7 : (e == 4 ? prm.logdt : prm.dskip) + ch;
        #pragma unroll
        for (int q = 0; q < 3; q++) asm volatile("ld.global.nc.u16 %0, [%1];" : "=r"(raw[q][e]) : "l"(pp + q * (e < 4 ? 128 : 1)));
      }
      asm volatile("setmaxnreg.inc.sync.aligned.u32 152;");
      if (EN_SSM) {
        #pragma unroll 1
        for (int k = wg; k < (wg == 2 ? 5 : wg + 1); k++) {
          const uint32_t z = sb + OFF_BLK + k * BLK + t7 * 16;
          sts128(z + B_TBL, 0, 0, 0, 0); sts128(z + B_TBL + 2048, 0, 0, 0, 0);
          if (t7 < 16) sts128(z - 256, 0, 0, 0, 0);
        }
      }
      bar_sync(0, 512);
      #pragma unroll
      for (int q = 0; q < 3; q++) {
        #pragma unroll
        for (int e = 0; e < 3; e++) pr[q][e] = raw[q][2 * e] | (raw[q][2 * e + 1] << 16);
        const uint32_t m = __reduce_max_sync(0xffffffff, max(raw[q][2] & 0x7fffu, raw[q][3] & 0x7fffu));
        if (lane == 0) sts32(sb + OFF_EPOCH + 16 + (wg * 3 + q) * 16 + w4 * 4, m);
      }
      bar_sync(2 + wg, 128);
    }
    if (tid == 256) TS(40);
    if (EN_SSM) {
      const uint32_t p0 = wg == 1 ? 4 * W_SLOT : OFF_BLK + wg * 3584, p1 = wg == 1 ? 7168 : BLK, p2 = wg == 1 ? OFF_X + 32768 - 4 * W_SLOT : 2 * BLK;
      const uint32_t fa = sb + p0 + (lane >> 4) * p1 + (w4 & 1) * p2 + ((lane >> 3) & 1) * 256 + (lane & 7) * 16;
      const uint32_t ea = fa + (w4 >> 1) * 2048, ga = fa + 4096 + (w4 >> 1) * 1536;
      constexpr uint64_t dE = mkdesc(SB0, 128, 512, 0);
      const uint32_t xa = sb + OFF_BLK + 4 * BLK + B_D + wg * 3072 + t7 * 8;
      #pragma unroll 1
      for (int k = wg; k < (wg == 2 ? 5 : wg + 1); k++) {
        const uint32_t blk = sb + OFF_BLK + k * BLK;
        const uint32_t pa0 = pr[0][0], pc0 = pr[0][1];
        const float dt = bf_round(expf(bf_lo(pr[0][2]))), dsk = bf_hi(pr[0][2]);
        #pragma unroll
        for (int e = 0; e < 3; e++) { pr[0][e] = pr[1][e]; pr[1][e] = pr[2][e]; }
        float fac;
        {
          uint32_t mm[4];
          lds128(mm, sb + OFF_EPOCH + 16 + (wg * 2 + k) * 16);
          const uint32_t ex = min(max(max(max(mm[0], mm[1]), max(mm[2], mm[3])) >> 7, 1u), 253u);
          const float sc = __uint_as_float((254u - ex) << 23);
          fac = 2.f * dt * __uint_as_float(ex << 23);
          const float lr = -bf_round(expf(bf_lo(pa0))) * dt * 1.44269504089f;
          const float tn = bf_hi(pa0) * dt * 0.15915494309f;
          float z1r, z1i, z2r, z2i, z4r, z4i, xr[8], xi[8], gr[8], gi[8], wr[9], wi[9];
          cexp_t(lr, -tn, z1r, z1i);
          cexp_t(lr * 8.f, tn * 8.f, xr[1], xi[1]);
          cexp_t(lr * 64.f, tn * 64.f, wr[0], wi[0]);
          xr[0] = 1.f; xi[0] = 0.f;
          cmul(xr[1], xi[1], xr[1], xi[1], xr[2], xi[2]); cmul(xr[2], xi[2], xr[1], xi[1], xr[3], xi[3]);
          cmul(xr[2], xi[2], xr[2], xi[2], xr[4], xi[4]);
          #pragma unroll
          for (int b = 1; b < 4; b++) cmul(xr[4], xi[4], xr[b], xi[b], xr[4 + b], xi[4 + b]);
          cmul(wr[0], wi[0], wr[0], wi[0], wr[1], wi[1]); cmul(wr[1], wi[1], wr[0], wi[0], wr[2], wi[2]);
          cmul(wr[1], wi[1], wr[1], wi[1], wr[3], wi[3]); cmul(wr[3], wi[3], wr[3], wi[3], wr[4], wi[4]);
          cmul(wr[4], wi[4], wr[3], wi[3], wr[5], wi[5]); cmul(wr[4], wi[4], wr[4], wi[4], wr[6], wi[6]);
          cmul(wr[6], wi[6], wr[4], wi[4], wr[7], wi[7]); cmul(wr[6], wi[6], wr[6], wi[6], wr[8], wi[8]);
          uint32_t R[4], I[4], PR[4], PI[4];
          #pragma unroll
          for (int b = 0; b < 4; b++) { R[b] = packh(xr[2 * b], xr[2 * b + 1]); I[b] = packh(xi[2 * b], xi[2 * b + 1]); }
          sts128(ea, R[0], R[1], R[2], R[3]); sts128(ea + 128, I[0], I[1], I[2], I[3]);
          #pragma unroll
          for (int i = 0; i < 3; i++) {
            const uint32_t z = packh(wr[i], wi[i]);
            #pragma unroll
            for (int b = 0; b < 4; b++) hcm2(R[b], I[b], z, PR[b], PI[b]);
            sts128(ea + (i + 1) * 512, PR[0], PR[1], PR[2], PR[3]); sts128(ea + (i + 1) * 512 + 128, PI[0], PI[1], PI[2], PI[3]);
          }
          gr[0] = bf_lo(pc0) * sc; gi[0] = -bf_hi(pc0) * sc;
          cmul(z1r, z1i, z1r, z1i, z2r, z2i); cmul(z2r, z2i, z2r, z2i, z4r, z4i);
          cmul(gr[0], gi[0], z1r, z1i, gr[1], gi[1]);
          cmul(gr[0], gi[0], z2r, z2i, gr[2], gi[2]); cmul(gr[1], gi[1], z2r, z2i, gr[3], gi[3]);
          #pragma unroll
          for (int b = 0; b < 4; b++) cmul(gr[b], gi[b], z4r, z4i, gr[4 + b], gi[4 + b]);
          sts128(ga, packh(gr[0], gr[1]), packh(gr[2], gr[3]), packh(gr[4], gr[5]), packh(gr[6], gr[7]));
          sts128(ga + 128, packh(gi[0], gi[1]), packh(gi[2], gi[3]), packh(gi[4], gi[5]), packh(gi[6], gi[7]));
          {
            const uint32_t z = packh(wr[3], -wi[3]), a4r = packh(gr[0], gr[4]), a4i = packh(gi[0], gi[4]);
            hcm2(packh(gr[0], gr[2]), packh(gi[0], gi[2]), z, PR[0], PI[0]);
            hcm2(packh(gr[4], gr[6]), packh(gi[4], gi[6]), z, PR[1], PI[1]);
            hcm2(a4r, a4i, packh(wr[4], -wi[4]), PR[2], PI[2]);
            hcm2(a4r, a4i, packh(wr[5], -wi[5]), PR[3], PI[3]);
            sts128(ga + 512, PR[0], PR[1], PR[2], PR[3]); sts128(ga + 512 + 128, PI[0], PI[1], PI[2], PI[3]);
            float hr, hi_;
            cmul(gr[0], gi[0], wr[3], -wi[3], hr, hi_);
            const uint32_t cr = packh(gr[0], hr), ci = packh(gi[0], hi_);
            #pragma unroll
            for (int i = 0; i < 3; i++) hcm2(cr, ci, packh(wr[6 + i], -wi[6 + i]), PR[i], PI[i]);
            sts128(ga + 1024, PR[0], PR[1], PR[2], 0u); sts128(ga + 1024 + 128, PI[0], PI[1], PI[2], 0u);
          }
        }
        fence_async();
        bar_sync(2 + wg, 128);
        if (t7 == 0 && k == 3) TS(50);
        float ka[24]; zero<24>(ka);
        wg_fence();
        #pragma unroll
        for (int s = 0; s < 8; s++) {
          const uint32_t lo = (uint32_t)dE + ((p0 + ((s >> 1) & 1) * p1 + (s >> 2) * p2) >> 4) + (s & 1) * 16;
          wg_ss48_tt_h(ka, desc2(lo, dE >> 32), desc2(lo + 256, dE >> 32), s != 0);
        }
        wg_commit();
        wg_wait<0>();
        pin<24>(ka);
        if (t7 == 0 && k == 3) TS(51);
        float kk[6];
        {
          const bool up = w4 >= 2;
          #pragma unroll
          for (int n = 0; n < 3; n++) {
            sts64f(xa + n * 1024, up ? ka[12 + 4 * n] : ka[4 * n + 2], up ? ka[13 + 4 * n] : ka[4 * n + 3]);
            kk[2 * n] = up ? ka[14 + 4 * n] : ka[4 * n]; kk[2 * n + 1] = up ? ka[15 + 4 * n] : ka[4 * n + 1];
          }
          bar_sync(2 + wg, 128);
          if (t7 == 0 && wg < 2) mbar_arrive(BAR(BR_KG1));
          #pragma unroll
          for (int n = 0; n < 3; n++) {
            uint32_t o[2]; lds64(o, (xa ^ 512) + n * 1024);
            kk[2 * n] = (kk[2 * n] + __uint_as_float(o[0])) * fac; kk[2 * n + 1] = (kk[2 * n + 1] + __uint_as_float(o[1])) * fac;
          }
        }
        if (t7 == 0 && k == 3) TS(52);
        {
          const int j = (w4 & 1) * 16 + (w4 >> 1) * 8 + g;
          const uint32_t tb = blk + B_TBL;
          if (t7 == 0) kk[0] += dsk;
          const uint32_t pa_ = tb + (16 + 8 * j + 2 * tq) * 4;
          const uint32_t v = pack2(kk[1], kk[0]);
          sts32(pa_ + 4, v); sts16(pa_, v >> 16); sts16(pa_ + 10, v);
          const uint32_t u = pack2(kk[2], kk[3]), w = pack2(kk[4], kk[5]);
          if (tq < 2) {
            const uint32_t pb = tb + (16 + 256 + 8 * j + 4 * tq) * 4;
            sts16(pb, u); sts32(pb + 4, __byte_perm(u, 0, 0x1010)); sts32(pb + 8, __byte_perm(u, 0, 0x1032)); sts16(pb + 14, u >> 16);
            if (j | tq) { sts16(pb - 4, u); sts16(pb + 2, u); }
            const int i = 64 * tq + j;
            const uint32_t e0 = tb + (T_F3 + (((i - 1) & 1) ? 80 : 0) + ((i - 1) >> 1)) * 4, e1 = i ? e0 : tb + (T_F2 + 144 + 31) * 4;
            sts16(e1, w); sts16(e1 + 6, w); sts16(e0 + 64, w >> 16); sts16(e0 + 70, w >> 16);
            if (i == 0) { sts16(tb + (T_S + 3) * 4, w); sts32(tb + (T_S + 4) * 4, __byte_perm(w, 0, 0x1010)); sts16(tb + (T_S + 5) * 4 + 2, w); }
          } else {
            const int i = 32 * (tq - 2) + j;
            const uint32_t e1 = tb + (i ? T_F2 + ((2 * i - 1) & 3) * 48 + ((2 * i - 1) >> 2) : 16 + 511) * 4;
            const uint32_t e2 = tb + (T_F2 + (i & 1) * 96 + (i >> 1)) * 4;
            sts16(e1, u); sts16(e1 + 6, u); sts16(e2, u >> 16); sts16(e2 + 6, u >> 16);
            if (i == 0) {
              const uint32_t uu = __byte_perm(u, 0, 0x1010);
              sts32(tb + 528 * 4, uu); sts32(tb + 529 * 4, uu); sts32(tb + 530 * 4, uu); sts16(tb + 531 * 4 + 2, u);
              sts16(tb + (T_F3 + 80 + 63) * 4, w);
            }
          }
        }
        if (t7 == 0 && k == 3) TS(53);
      }
      if (wg < 2) mbar_arrive(BAR(BR_KGEN));
    }
    if (tid == 0) TS(14);
  if (wg < 2) {
    if (EN_ATT) {
    float am[96], ar[24];
    {
      const bool lead = (rtid() & 127) == 0;
      constexpr uint64_t da0 = mkdesc(SB0 + OFF_X, 16, 1024, 1), dr0 = mkdesc(SB0 + 12288, 1024, 256, 3);
      const uint64_t db0 = sw64 ? mkdesc(SB0, 2048, 512, 2) : mkdesc(SB0, 4096, 1024, 1);
      const uint32_t kst = sw64 ? 64 : 128, bh = db0 >> 32;
      uint32_t s = 0, ph = 0, xo = 0;
      #pragma unroll 1
      for (int kb = 0; kb < 20; kb++) {
        const uint32_t wo_ = s * (W_SLOT >> 4), al = (uint32_t)da0 + wg * 512 + xo, bl = (uint32_t)db0 + wo_, rl = (uint32_t)dr0 + wo_;
        mbar_wait(BAR(BR_FULL) + 8 * s, ph);
        if (kb == 0 && lead && wg == 0) TS(1);
        wg_fence();
        wg_ss192_tb(am, desc2(al, da0 >> 32), desc2(bl, bh), kb != 0);
        wg_ss48_tb(ar, desc2(al, da0 >> 32), desc2(rl, dr0 >> 32), kb != 0);
        wg_ss192_tb(am, desc2(al + 2, da0 >> 32), desc2(bl + kst, bh), 1);
        wg_ss48_tb(ar, desc2(al + 2, da0 >> 32), desc2(rl + 32, dr0 >> 32), 1);
        wg_commit();
        wg_wait<1>();
        if (lead && kb > 0 && kb < 16) mbar_arrive(BAR(BR_EMPTY) + 8 * (s == 0 ? 4 : s - 1));
        if (++s == 5) { s = 0; ph ^= 1; }
        xo += (kb & 1) ? 1020 : 4;
        if (xo == 3072) xo = 0;
      }
      wg_wait<0>();
      pin<96>(am); pin<24>(ar);
    }
    const int tid = rtid(), lane = tid & 31, tq = lane & 3;
    if (tid == 0) TS(2);
#define QV(j, e) ((j) < 8 ? am[4 * (j) + (e)] : ar[4 * ((j) - 8) + (e)])
#define KV_(j, e) ((j) < 8 ? am[32 + 4 * (j) + (e)] : ar[8 + 4 * ((j) - 8) + (e)])
#define VV(j, e) ((j) < 8 ? am[64 + 4 * (j) + (e)] : ar[16 + 4 * ((j) - 8) + (e)])
    {
      bar_sync(1, 256);
      if (tid == 0) mbar_arrive(BAR(BR_GEMM));
      const uint32_t ro = sb + (uint32_t)((warp * 16 + (lane & 15)) * 16);
      const int l0 = 2 * (c & 1) + (lane >> 4);
      const uint32_t ones = (tq == 0) ? 0x00003f80u : 0u;
#define PV(j) pack2(VV(j, 0), VV(j, 1)), pack2(VV(j, 2), VV(j, 3))
#define PK(j) pack2(phi(KV_(j, 0)), phi(KV_(j, 1))), pack2(phi(KV_(j, 2)), phi(KV_(j, 3)))
      stsm4(ro + OFF_V + (5 + 6 * (lane >> 4)) * 2048, ones, ones, ones, ones);
      #pragma unroll
      for (int j = 0; j < 10; j += 2) {
        const int l = (j == 8 && (c & 1)) ? l0 - 2 : l0 + j;
        stsm4(ro + OFF_V + (l + (l >= 5)) * 2048, PV(j), PV(j + 1));
        stsm4(ro + OFF_PK + l * 2048, PK(j), PK(j + 1));
      }
    }
    fence_async();
    bar_sync(1, 256);
    if (tid == 0) TS(3);
    mbar_wait(BAR(BR_EPOCH), 0);
    const unsigned epoch = lds32(sb + OFF_EPOCH);
    {
      float kv[24]; zero<24>(kv);
      constexpr uint64_t da = mkdesc(SB0 + OFF_PK, 128, 2048, 0), db = mkdesc(SB0 + OFF_V, 128, 2048, 0);
      wg_fence();
      #pragma unroll
      for (int s = 0; s < 8; s++) wg_ss48_tt(kv, desc2((uint32_t)da + wg * 640 + s * 16, da >> 32), desc2((uint32_t)db + wg * 768 + s * 16, db >> 32), s != 0);
      wg_commit();
      wg_wait<0>();
      pin<24>(kv);
      if (tid == 0) TS(15);
      if (w4 < 3) {
        const uint32_t wb = sb + OFF_KVS + (wg * 3 + w4) * 1536 + (lane & 15) * 96;
        #pragma unroll
        for (int j = 0; j < 6; j += 2)
          stsm4(wb + (j + (lane >> 4)) * 16, pack2(kv[4 * j], kv[4 * j + 1]), pack2(kv[4 * j + 2], kv[4 * j + 3]),
                pack2(kv[4 * j + 4], kv[4 * j + 5]), pack2(kv[4 * j + 6], kv[4 * j + 7]));
        __syncwarp();
        const int dl = w4 * 16 + (lane & 15), hl = dl >= 20;
        if (dl < 40) {
          uint4* dst = &g_kvp[(c * 16 + r) * 240 + wg * 40 + dl];
          uint32_t v[4], z[4];
          lds128(v, wb + (3 * hl + (lane >> 4)) * 16);
          lds64(z, wb + 32 + 8 * hl); z[2] = lds32(wb + 80); z[3] = epoch & 1u;
          v[3] = (v[3] & ~1u) | z[3];
          st128_rlx(dst + (lane >> 4) * 80, v);
          if (lane < 16) st128_rlx(dst + 160, z);
        }
      }
    }
    fence_async();
    bar_sync(1, 256);
    if (tid == 0) { st_rlx(FLAG(0, r, c), epoch); mbar_arrive(BAR(BR_PUB)); TS(4); }
    const int kvi = (tid >= 80) + (tid >= 160) + (tid >= 240), kd = tid - 80 * kvi;
    const int khd = kd / 20, kt0 = 5 * (khd >> 1) + 2 * (khd & 1);
    const uint32_t rb = sb + OFF_KVB + kd * 16;
    if (kvi < 3) {
      #pragma unroll 1
      for (int m = kvi; m < 7; m += 3) { const int q = kt0 + 3 + m; sts128(rb + (q >= 10 ? q - 10 : q) * 1280, 0, 0, 0, 0); }
    }
    uint32_t qa[20];
    {
      const float sc = 1.44269504089f + __uint_as_float(lds32(sb + OFF_EPOCH) ^ epoch);
      #pragma unroll
      for (int j = 0; j < 10; j++) { qa[2 * j] = pack2(phi(QV(j, 0), sc), phi(QV(j, 1), sc)); qa[2 * j + 1] = pack2(phi(QV(j, 2), sc), phi(QV(j, 3), sc)); }
    }
    if (tid == 0) TS(5);
    mbar_wait(BAR(BR_KVP), 0);
    if (tid == 0) TS(6);
    if (kvi < 3) {
      float s[8];
      zero<8>(s);
      uint32_t bad = 0;
      #pragma unroll 4
      for (int i = 0; i < 16; i++) {
        uint32_t w[4];
        lds128(w, sb + OFF_KVP + tid * 16 + i * 3840);
        bad |= w[3] ^ epoch;
        #pragma unroll
        for (int e = 0; e < 4; e++) { s[2 * e] += bf_lo(w[e]); s[2 * e + 1] += bf_hi(w[e]); }
      }
      if (__builtin_expect(bad & 1u, 0)) {
        zero<8>(s);
        #pragma unroll 1
        for (int i = 0; i < 16; i++) {
          uint32_t w[4] = {0, 0, 0, ~epoch};
          fix128_w3(w, &g_kvp[(c * 16 + i) * 240 + tid], epoch, 1u);
          #pragma unroll
          for (int e = 0; e < 4; e++) { s[2 * e] += bf_lo(w[e]); s[2 * e + 1] += bf_hi(w[e]); }
        }
        FIXCNT
      }
      const uint32_t p0 = pack2(s[0], s[1]), p1 = pack2(s[2], s[3]), p2 = pack2(s[4], s[5]), p3 = pack2(s[6], s[7]);
      if (kvi < 2) sts128(rb + (kt0 + (khd & 1) + kvi) * 1280, p0, p1, p2, p3);
      else {
        const bool od = khd & 1;
        sts128(rb + (5 * (khd >> 1) + 2) * 1280, od ? 0u : p0, od ? 0u : p1, od ? p0 : 0u, od ? p1 : 0u);
        const uint32_t zz = (p2 & 0xffffu) << (16 * (khd & 1));
        sts128(rb + 10 * 1280, khd < 2 ? zz : 0u, khd < 2 ? 0u : zz, 0u, 0u);
      }
    }
    fence_async();
    bar_sync(1, 256);
    if (tid == 0) { mbar_arrive(BAR(BR_SUM)); TS(7); }
    {
      float oa[44]; zero<44>(oa);
      constexpr uint64_t db = mkdesc(SB0 + OFF_KVB, 128, 1280, 0);
      wg_fence();
      #pragma unroll
      for (int s = 0; s < 5; s++) wg_rs88_tb(oa, &qa[4 * s], desc2((uint32_t)db + ((s == 4 && (c & 1)) ? 0 : (s + (c & 1)) * 16), db >> 32), s != 0);
      wg_commit();
      wg_wait<0>();
      pin<44>(oa);
      if (tid == 0) TS(13);
      float rc[4], rd[2][4];
      #pragma unroll
      for (int e = 0; e < 4; e++) asm("rcp.approx.ftz.f32 %0, %1;" : "=f"(rc[e]) : "f"(oa[40 + e] + 1e-6f));
      #pragma unroll
      for (int h = 0; h < 4; h++) {
        rd[0][h] = __shfl_sync(0xffffffff, rc[h & 1], (lane & 28) | (h >> 1));
        rd[1][h] = __shfl_sync(0xffffffff, rc[2 + (h & 1)], (lane & 28) | (h >> 1));
      }
      #pragma unroll
      for (int j = 0; j < 10; j++) {
        #pragma unroll
        for (int h = 0; h < 2; h++) {
          float f;
          if (j == 2) f = tq < 2 ? rd[h][0] : rd[h][1];
          else if (j == 7) f = tq < 2 ? rd[h][2] : rd[h][3];
          else f = rd[h][(8 * j) / 20];
          qa[2 * j + h] = pack2(oa[4 * j + 2 * h] * f, oa[4 * j + 2 * h + 1] * f);
        }
      }
      const uint32_t m0 = (lane & 7) == ((2 * w4) & 7), m1 = (lane & 7) == 2 * w4 + 1;
      const uint32_t oa_ = sb + OFF_EXTRA + (lane >> 4) * 2048 + (warp * 16 + (lane & 15)) * 16;
      bar_sync(1, 256);
#define TAG(v, m) (((v) & ~(m)) | (epoch & (m)))
      #pragma unroll
      for (int s = 0; s < 5; s++) stsm4(oa_ + s * 4096, TAG(qa[4 * s], m0), TAG(qa[4 * s + 1], m1), TAG(qa[4 * s + 2], m0), TAG(qa[4 * s + 3], m1));
    }
    fence_async();
    mbar_arrive(BAR(BR_OSTG));
    if (tid == 0) TS(8);
    float oc[40]; zero<40>(oc);
    {
      constexpr uint64_t dw0 = mkdesc(SB0, OFF_WOR, 1024, 1), da0 = mkdesc(SB0, 2048, 128, 0);
      const uint32_t ck = sb + tid * 32 + ((lane >> 2) << 2), ck2 = ck + (wg ? 0 : 16384);
      uint32_t bad = 0;
      auto tile = [&](int i, uint32_t so) {
        const uint32_t al = (uint32_t)da0 + wg * 64 + (so >> 4), wl = (uint32_t)dw0 + i * 640 - (i >> 1) * (1278 << 16);
        wg_fence();
        #pragma unroll
        for (int s = 0; s < 5; s++) wg_ss80_tb(oc, desc2(al + s * 256, da0 >> 32), desc2(wl + s * 128, dw0 >> 32), (i | s) != 0);
        wg_commit();
        bad |= (lds32(ck + so) ^ epoch) | (lds32(ck + so + 8192) ^ epoch) | (lds32(ck2 + so) ^ epoch);
      };
      mbar_wait(BAR(BR_WO), 0);
      mbar_wait(BAR(BR_OSTG), 0);
      tile(0, SLOT(0));
      mbar_wait(BAR(BR_WO + 1), 0);
      #pragma unroll 1
      for (int i = 1; i < 8; i++) {
        if (i == 1) { wg_wait<0>(); if (lane == 0) mbar_arrive(BAR(BR_OEMPTY)); }
        mbar_wait(BAR(BR_OFULL) + 8 * i, 0);
        if (i == 1 && tid == 0) TS(9);
        tile(i, SLOT(i));
        wg_wait<1>();
        if (lane == 0 && i > 1) mbar_arrive(BAR(BR_OEMPTY - 1) + 8 * i);
      }
      #pragma unroll 1
      for (int n = 0; n < 56; n++) {
        const int i = n & 7;
        if (i == 0) {
          uint32_t any;
          asm volatile("{\n.reg .pred p;\nsetp.ne.u32 p, %1, 0;\nbarrier.red.or.pred p, 1, 256, p;\nselp.u32 %0, 1, 0, p;\n}" : "=r"(any) : "r"(bad & 1u) : "memory");
          if (!any) break;
          bad = 0;
          FIXCNT
        }
        wg_wait<0>();
        bar_sync(1, 256);
        if (tid == 0) { mbar_expect_tx(BAR(BR_RETRY), 20480); bulk_ld(sb + SLOT(0), &g_o[(r * 8 + CHUNK(i)) * 1280], 20480, BAR(BR_RETRY)); }
        mbar_wait(BAR(BR_RETRY), n & 1);
        tile(i, SLOT(0));
      }
      wg_wait<0>();
      pin<40>(oc);
    }
    if (tid == 0) TS(10);
    {
      const int row = w4 * 16 + (lane & 15);
      const uint32_t ob = sb + SLOT(4) + wg * 10240;
      #pragma unroll
      for (int j = 0; j < 8; j += 2)
        stsm4(ob + row * 128 + (((j + (lane >> 4)) ^ (row & 7)) << 4), pack2(oc[4 * j], oc[4 * j + 1]), pack2(oc[4 * j + 2], oc[4 * j + 3]),
              pack2(oc[4 * j + 4], oc[4 * j + 5]), pack2(oc[4 * j + 6], oc[4 * j + 7]));
      stsm4(ob + 8192 + row * 32 + (lane >> 4) * 16, pack2(oc[32], oc[33]), pack2(oc[34], oc[35]), pack2(oc[36], oc[37]), pack2(oc[38], oc[39]));
      fence_async();
      bar_sync(2 + wg, 128);
      if (w4 == 0 && elect_one()) {
        tma2d_st(&prm.m[M_O64], ob, 640 + c * 64, r * 128 + wg * 64);
        tma2d_st(&prm.m[M_O16], ob + 8192, 1152 + c * 16, r * 128 + wg * 64);
        bulk_commit(); bulk_wait0_read();
        if (wg == 0) { TS(11); DUMP(0, 20); }
      }
    }
    }
  } else {
    if (EN_SSM) {
    const int tid = rtid(), lane = tid & 31, g = lane >> 2, tq = lane & 3, t7 = tid & 127;
    if (t7 == 0) TS(41);
    mbar_wait(BAR(BR_U), 0);
    mbar_wait(BAR(BR_KGEN), 0);
    bar_sync(4, 128);
    if (t7 == 0) TS(43);
    {
      #pragma unroll 1
      for (int q6 = w4; q6 < 30; q6 += 4) {
        {
          const int k = q6 / 6, kap = (q6 - 6 * k) * 32 + lane;
          const uint32_t blk = sb + OFF_BLK + k * BLK;
          float P[33];
          P[0] = 0.f;
          #pragma unroll
          for (int q = 0; q < 4; q++) {
            const int ch = kap - 3 + q;
            uint32_t v[4];
            lds128(v, blk + (uint32_t)((ch * 16) ^ ((ch * 2) & 0x70)));
            #pragma unroll
            for (int e = 0; e < 4; e++) {
              P[q * 8 + 2 * e + 1] = (q == 0 && e < 2) ? 0.f : P[q * 8 + 2 * e] + bf_lo(v[e]);
              P[q * 8 + 2 * e + 2] = (q == 0 && e < 2) ? 0.f : P[q * 8 + 2 * e + 1] + bf_hi(v[e]);
            }
          }
#define WIN(lo, hi, e) (P[25 + (e) - (lo)] - P[24 + (e) - (hi)])
#define WIN8(lo, hi) pack2(WIN(lo, hi, 0), WIN(lo, hi, 1)), pack2(WIN(lo, hi, 2), WIN(lo, hi, 3)), pack2(WIN(lo, hi, 4), WIN(lo, hi, 5)), pack2(WIN(lo, hi, 6), WIN(lo, hi, 7))
          const uint32_t o2 = blk + B_D + (kap & 1) * 1552 + (kap >> 1) * 16;
          sts128(o2, WIN8(3, 5));
          sts128(o2 + B_D5, WIN8(6, 10));
          if (kap < 128) {
            const uint32_t o = blk + B_D + (kap & 1) * 1024 + (kap >> 1) * 16;
            sts128(o + B_D7, WIN8(5, 11));
            sts128(o + B_D9, WIN8(12, 20));
          }
        }
      }
      if (t7 < 10) sts128(sb + OFF_BLK + (t7 >> 1) * BLK + B_D + (t7 & 1) * B_D5 + 1536, 0, 0, 0, 0);
    }
    bar_sync(4, 128);
    if (t7 == 0) TS(44);
    if (EN_ATT) mbar_wait(BAR(BR_GEMM), 0);
    if (t7 == 0) TS(42);
    #pragma unroll 1
    for (int pass = 1; pass >= 0; pass--) {
      const int k = pass ? w4 : 4;
      const uint32_t blk = sb + OFF_BLK + k * BLK, tb = blk + B_TBL + (uint32_t)((g - 2 * tq) * 4);
      float acc[16][4];
      zero<64>(&acc[0][0]);
      const int kl = 16 * (lane >> 4) + 2 * (lane & 7) + ((lane >> 3) & 1);
      {
        auto ubase = [&](int sh) { const int q = kl - 2 * sh; return blk + (uint32_t)((q * 16) ^ ((q * 2) & 0x70)); };
#define LDQ(A, sh) _Pragma("unroll") for (int m = 0; m < 4; m++) load_quad(A[m], tb + (16 + 16 * (sh) + 128 * m) * 4);
#define LDB(B, ub, h) _Pragma("unroll") for (int p = 0; p < 4; p++) ldsm4(B[p], ((ub) ^ ((p & 1) * 64)) + (4 * (h) + p) * 512);
#define MLO(A, B) _Pragma("unroll") for (int m = 0; m < 4; m++) _Pragma("unroll") for (int cc = 0; cc < 8; cc++) mma16816(acc[cc + m], A[m], &B[cc >> 1][(cc & 1) * 2]);
#define MHI(A, B) _Pragma("unroll") for (int m = 0; m < 4; m++) _Pragma("unroll") for (int cc = 0; cc < 8 - m; cc++) mma16816(acc[8 + cc + m], A[m], &B[cc >> 1][(cc & 1) * 2]);
        int p_ = pass ? 0 : w4;
        const int pe = pass ? 4 : w4 + 1;
        uint32_t A[4][4], A2[4][4], Bl[4][4], Bh[4][4];
        uint32_t ub = ubase(p_ + 4);
        LDQ(A, p_ + 4) LDB(Bl, ub, 0)
        #pragma unroll 1
        for (; p_ < pe; p_++) {
          LDB(Bh, ub, 1)
          MLO(A, Bl)
          ub = ubase(p_);
          LDQ(A2, p_) LDB(Bl, ub, 0)
          MHI(A, Bh)
          LDB(Bh, ub, 1)
          load_quad(A[0], tb + (16 + 512 + 16 * (p_ & 1)) * 4); load_quad(A[1], tb + (T_S + 16 * (p_ & 1)) * 4);
          MLO(A2, Bl)
          if (p_ < 2) {
            #pragma unroll
            for (int cc = 0; cc < 8; cc++) mma16816(acc[cc + 4], A[0], &Bl[cc >> 1][(cc & 1) * 2]);
            #pragma unroll
            for (int cc = 0; cc < 4; cc++) mma16816(acc[cc + 12], A[0], &Bh[cc >> 1][(cc & 1) * 2]);
            #pragma unroll
            for (int cc = 0; cc < 8; cc++) mma16816(acc[cc + 8], A[1], &Bl[cc >> 1][(cc & 1) * 2]);
          }
          const int pn = ((p_ + 1) & 3) + 4;
          ub = ubase(pn);
          LDQ(A, pn) LDB(Bl, ub, 0)
          MHI(A2, Bh)
        }
      }
      if (t7 == 0) TS(57 + 3 * pass);
      {
        const int ih = (lane >> 3) & 1;
        const uint32_t dl = blk + B_D + (uint32_t)(((lane >> 4) * 8 + (lane & 7)) * 16);
        const uint32_t d0_ = dl + ih * 1552, d8_ = dl + (ih ? 0 : 1536), d3_ = dl + B_D7 + ih * 1024;
        auto cls2 = [&](uint32_t da, uint32_t ta) {
          uint32_t B[6][2], A[6][4];
          #pragma unroll
          for (int e = 0; e < 6; e++) { B[e][0] = lds32v(ta + (e + 4) * 32); B[e][1] = lds32v(ta + (e + 3) * 32); }
          #pragma unroll
          for (int kk = 0; kk < 6; kk++) ldsm4t(A[kk], da + kk * 256);
          #pragma unroll
          for (int e = 0; e < 6; e++)
            #pragma unroll
            for (int kk = 0; kk < 6; kk++) if (2 * kk + e + 4 < 16) mma16816(acc[2 * kk + e + 4], A[kk], B[e]);
        };
        auto cls3 = [&](uint32_t da, uint32_t ta) {
          uint32_t B[8][2], A[4][4];
          #pragma unroll
          for (int e = 0; e < 8; e++) { B[e][0] = lds32v(ta + (e + 8) * 32); B[e][1] = lds32v(ta + (e + 7) * 32); }
          #pragma unroll
          for (int kk = 0; kk < 4; kk++) ldsm4t(A[kk], da + kk * 256);
          #pragma unroll
          for (int kk = 0; kk < 4; kk++)
            #pragma unroll
            for (int e = 0; e < 8; e++) if (2 * kk + e + 8 < 16) mma16816(acc[2 * kk + e + 8], A[kk], B[e]);
        };
        #pragma unroll 1
        for (int a = pass ? 0 : w4; a < (pass ? 4 : w4 + 1); a++) cls2(((a & 2) ? d8_ : d0_) + (a & 1) * B_D5, tb + (T_F2 + 48 * a - 32) * 4);
        #pragma unroll 1
        for (int b = pass ? 0 : (w4 & 1); b < (pass ? 2 : w4 - 1); b++) cls3(d3_ + b * 2048, tb + (T_F3 + 80 * b - 64) * 4);
      }
      if (t7 == 0) TS(58 + 3 * pass);
      const uint32_t ya = blk + (uint32_t)((kl * 16) ^ ((kl * 2) & 0x70));
#define STY(p) stsm4t((ya ^ (((p) & 1) * 64)) + (p) * 512, pack2(acc[2 * (p)][0], acc[2 * (p)][1]), pack2(acc[2 * (p)][2], acc[2 * (p)][3]), \
                      pack2(acc[2 * (p) + 1][0], acc[2 * (p) + 1][1]), pack2(acc[2 * (p) + 1][2], acc[2 * (p) + 1][3]))
      if (pass == 0) {
        const uint32_t xw = blk + 4096 + w4 * 4096 + lane * 16, xr = blk + 4096 + w4 * 1024 + lane * 16;
        #pragma unroll
        for (int h = 0; h < 2; h++) {
          bar_sync(4, 128);
          #pragma unroll
          for (int i = 0; i < 8; i++)
            sts128(xw + i * 512, __float_as_uint(acc[8 * h + i][0]), __float_as_uint(acc[8 * h + i][1]), __float_as_uint(acc[8 * h + i][2]), __float_as_uint(acc[8 * h + i][3]));
          bar_sync(4, 128);
          float y[8];
          #pragma unroll
          for (int i = 0; i < 8; i++) {
            uint32_t o[4]; lds128(o, xr + (i >> 1) * 4096 + (i & 1) * 512);
            #pragma unroll
            for (int e = 0; e < 4; e++) y[4 * (i & 1) + e] = i < 2 ? __uint_as_float(o[e]) : y[4 * (i & 1) + e] + __uint_as_float(o[e]);
          }
          stsm4t((ya ^ ((w4 & 1) * 64)) + (4 * h + w4) * 512, pack2(y[0], y[1]), pack2(y[2], y[3]), pack2(y[4], y[5]), pack2(y[6], y[7]));
        }
      } else {
        __syncwarp();
        #pragma unroll
        for (int p = 0; p < 8; p++) STY(p);
      }
      if (t7 == 0 && !pass) TS(55);
      fence_async();
      mbar_arrive(BAR(BR_Y + 1) - 8 * pass);
      if (t7 == 0) TS(59 + 3 * pass);
    }
    if (t7 == 0) DUMP(40, 64);
    }
  }
  }
}

typedef CUresult (*EncFn)(CUtensorMap*, CUtensorMapDataType, cuuint32_t, void*, const cuuint64_t*, const cuuint64_t*, const cuuint32_t*,
                          const cuuint32_t*, CUtensorMapInterleave, CUtensorMapSwizzle, CUtensorMapL2promotion, CUtensorMapFloatOOBfill);
static void mkmap(EncFn enc, CUtensorMap* m, const void* base, int rank, const cuuint64_t* dims, const cuuint64_t* strides, const cuuint32_t* box, CUtensorMapSwizzle swz) {
  cuuint32_t es[5] = {1, 1, 1, 1, 1};
  enc(m, CU_TENSOR_MAP_DATA_TYPE_BFLOAT16, rank, const_cast<void*>(base), dims, strides, box, es, CU_TENSOR_MAP_INTERLEAVE_NONE, swz,
      CU_TENSOR_MAP_L2_PROMOTION_L2_128B, CU_TENSOR_MAP_FLOAT_OOB_FILL_NONE);
}

extern "C" void kernel_launch(void* const* d_in, const int* in_sizes, int n_in, void* d_out, int out_size) {
  void* fn = nullptr; cudaDriverEntryPointQueryResult qr;
  cudaGetDriverEntryPoint("cuTensorMapEncodeTiled", &fn, cudaEnableDefault, &qr);
  EncFn enc = (EncFn)fn;
  void* uy = nullptr; cudaGetSymbolAddress(&uy, g_uy);
  const cuuint64_t dx[2] = {640, 2048}, sx[1] = {1280};
  const cuuint32_t bx[2] = {64, 128}, bu[2] = {80, 128};
  const cuuint64_t dw[3] = {640, 640, 3}, sw[2] = {3840, 1280};
  const cuuint32_t br[3] = {16, 32, 3};
  const cuuint64_t dwa[4] = {64, 640, 10, 3}, swa[3] = {3840, 128, 1280}, dwb[4] = {32, 640, 20, 3}, swb[3] = {3840, 64, 1280};
  const cuuint32_t bwa[4] = {64, 32, 1, 3}, bwb[4] = {32, 32, 2, 3};
  const cuuint64_t dwo[2] = {640, 640};
  const cuuint32_t bwo[2] = {64, 80}, bo64[2] = {64, 64}, bo16[2] = {16, 64};
  const cuuint64_t dsa[2] = {2048, 1280}, ssa[1] = {4096};
  const cuuint32_t bsa[2] = {64, 80};
  const cuuint64_t dsb[2] = {64, 40960}, ssb[1] = {128};
  const cuuint32_t bsb[2] = {64, 32};
  const cuuint64_t dout[2] = {1280, 2048}, sout[1] = {2560};
  Params prm;
  mkmap(enc, &prm.m[M_X], d_in[7], 2, dx, sx, bx, CU_TENSOR_MAP_SWIZZLE_128B);
  mkmap(enc, &prm.m[M_W128], d_in[8], 4, dwa, swa, bwa, CU_TENSOR_MAP_SWIZZLE_128B);
  mkmap(enc, &prm.m[M_W64], d_in[8], 4, dwb, swb, bwb, CU_TENSOR_MAP_SWIZZLE_64B);
  mkmap(enc, &prm.m[M_WR], d_in[8], 3, dw, sw, br, CU_TENSOR_MAP_SWIZZLE_32B);
  mkmap(enc, &prm.m[M_WO], d_in[9], 2, dwo, sx, bwo, CU_TENSOR_MAP_SWIZZLE_128B);
  mkmap(enc, &prm.m[M_O64], d_out, 2, dout, sout, bo64, CU_TENSOR_MAP_SWIZZLE_128B);
  mkmap(enc, &prm.m[M_O16], d_out, 2, dout, sout, bo16, CU_TENSOR_MAP_SWIZZLE_NONE);
  mkmap(enc, &prm.m[M_SA], uy, 2, dsa, ssa, bsa, CU_TENSOR_MAP_SWIZZLE_128B);
  mkmap(enc, &prm.m[M_SB], uy, 2, dsb, ssb, bsb, CU_TENSOR_MAP_SWIZZLE_128B);
  mkmap(enc, &prm.m[M_OUT], d_out, 2, dout, sout, bu, CU_TENSOR_MAP_SWIZZLE_NONE);
  prm.u = (const __nv_bfloat16*)d_in[0]; prm.wo = (const __nv_bfloat16*)d_in[9];
  for (int i = 0; i < 4; i++) prm.par[i] = (const __nv_bfloat16*)d_in[1 + i];
  prm.logdt = (const __nv_bfloat16*)d_in[5]; prm.dskip = (const __nv_bfloat16*)d_in[6];
  cudaFuncSetAttribute(fused_kernel, cudaFuncAttributeMaxDynamicSharedMemorySize, SMEM_BYTES);
  cudaLaunchConfig_t cfg = {};
  cfg.gridDim = dim3(128); cfg.blockDim = dim3(512); cfg.dynamicSmemBytes = SMEM_BYTES; cfg.stream = cudaStreamPerThread;
  cudaLaunchAttribute at[1];
  at[0].id = cudaLaunchAttributeClusterDimension; at[0].val.clusterDim.x = 2; at[0].val.clusterDim.y = 1; at[0].val.clusterDim.z = 1;
  cfg.attrs = at; cfg.numAttrs = 1;
  cudaLaunchKernelEx(&cfg, fused_kernel, prm);
}
```

```cpp
#include <cuda_runtime.h>
#include <cuda_bf16.h>
#include <cuda_fp16.h>
#include <cuda.h>
#include <stdint.h>

#define U_AFTER 9
#define U_NPF 5
#define EN_ATT 1
#define EN_SSM 1

__device__ __align__(1024) __nv_bfloat16 g_uy[2 * 640 * 2048];
__device__ __align__(128) uint4 g_kvp[8 * 16 * 240];
__device__ __align__(128) uint4 g_o[128 * 1280];
__device__ __align__(128) unsigned g_flag[4 * 128 * 32];
__device__ unsigned g_epoch[128];
#define TS(i) do {} while (0)
#define DUMP(lo, hi) do {} while (0)
#define FIXCNT

constexpr uint32_t SB0 = 1024;
constexpr uint32_t W_SLOT = 15360, OFF_X = 76800;
constexpr uint32_t OFF_WOR = 81920, OFF_KVP = 10240, OFF_KVS = 71680, OFF_PK = 10240, OFF_V = 30720, OFF_EXTRA = 102400, OFF_KVB = OFF_EXTRA;
constexpr uint32_t OFF_UT = 3 * W_SLOT;
constexpr uint32_t OFF_BAR = 125952, OFF_BLK = 128000, BLK = 20480;
constexpr uint32_t B_D = 4096, B_D5 = 3088, B_D7 = 6176, B_D9 = 8224, B_TBL = 14400;
constexpr int T_S = 576, T_F2 = 624, T_F3 = 816;
constexpr uint32_t SMEM_BYTES = OFF_BLK + 5 * BLK;
enum { BR_FULL = 0, BR_WO = 5, BR_PUB = 7, BR_KVP = 8, BR_U = 9, BR_SUM = 10, BR_GEMM = 11, BR_UIN = 12, BR_YIN = 13, BR_EPOCH = 14,
       BR_FREE = 15, BR_RETRY = 17, BR_OFULL = 18, BR_UOUT = 26, BR_EMPTY = 27, BR_OEMPTY = 32, BR_Y = 39, BR_OSTG = 41, BR_KGEN = 42, BR_COUNT = 44 };
constexpr uint32_t OFF_EPOCH = OFF_BAR + 8 * BR_COUNT;
enum { M_X, M_W128, M_W64, M_WR, M_U, M_WO, M_O64, M_O16, M_SA, M_SB, M_OUT, M_COUNT };

__device__ __forceinline__ long long clk64() { long long t; asm volatile("mov.u64 %0, %%clock64;" : "=l"(t) :: "memory"); return t; }
__device__ __forceinline__ uint32_t smem_u32(const void* p) { return (uint32_t)__cvta_generic_to_shared(p); }
__host__ __device__ constexpr uint64_t mkdesc(uint32_t addr, uint32_t lbo, uint32_t sbo, uint32_t swz) {
  return (uint64_t)((addr & 0x3FFFF) >> 4) | ((uint64_t)(lbo >> 4) << 16) | ((uint64_t)(sbo >> 4) << 32) | ((uint64_t)swz << 62);
}
__device__ __forceinline__ uint64_t desc2(uint32_t lo, uint32_t hi) { uint64_t d; asm("mov.b64 %0, {%1, %2};" : "=l"(d) : "r"(lo), "r"(hi)); return d; }
__device__ __forceinline__ void mbar_init(uint32_t bar, uint32_t cnt) { asm volatile("mbarrier.init.shared::cta.b64 [%0], %1;" :: "r"(bar), "r"(cnt) : "memory"); }
__device__ __forceinline__ void mbar_expect_tx(uint32_t bar, uint32_t bytes) { asm volatile("mbarrier.arrive.expect_tx.shared::cta.b64 _, [%0], %1;" :: "r"(bar), "r"(bytes) : "memory"); }
__device__ __forceinline__ void mbar_arrive(uint32_t bar) { asm volatile("mbarrier.arrive.shared::cta.b64 _, [%0];" :: "r"(bar) : "memory"); }
__device__ __forceinline__ void mbar_wait(uint32_t bar, uint32_t parity) {
  asm volatile("{\n.reg .pred p;\n.reg .u32 c;\nmov.u32 c, 0;\n"
    "WL:\nmbarrier.try_wait.parity.shared::cta.b64 p, [%0], %1;\n@p bra WD;\n"
    "add.u32 c, c, 1;\nsetp.lt.u32 p, c, 200000;\n@p bra WL;\nWD:\n}" :: "r"(bar), "r"(parity) : "memory");
}
__device__ __forceinline__ void poll_all(const unsigned* p, unsigned val) {
  asm volatile("{\n.reg .pred p;\n.reg .u32 c, v;\nmov.u32 c, 0;\n"
    "PL:\nld.relaxed.gpu.global.u32 v, [%0];\nsetp.eq.u32 p, v, %1;\nvote.sync.all.pred p, p, 0xffffffff;\n@p bra PD;\n"
    "add.u32 c, c, 1;\nsetp.lt.u32 p, c, 100000;\n@p bra PL;\nPD:\n}" :: "l"(p), "r"(val) : "memory");
}
__device__ __forceinline__ void poll_all_acq(const unsigned* p, unsigned val) {
  asm volatile("{\n.reg .pred p;\n.reg .u32 c, v;\nmov.u32 c, 0;\n"
    "PL:\nld.acquire.gpu.global.u32 v, [%0];\nsetp.eq.u32 p, v, %1;\nvote.sync.all.pred p, p, 0xffffffff;\n@p bra PD;\n"
    "add.u32 c, c, 1;\nsetp.lt.u32 p, c, 100000;\n@p bra PL;\nPD:\n}" :: "l"(p), "r"(val) : "memory");
}
__device__ __forceinline__ unsigned poll_bit(const unsigned* p, unsigned val, unsigned mask) {
  unsigned bal;
  asm volatile("{\n.reg .pred p;\n.reg .u32 c, v;\nmov.u32 c, 0;\n"
    "PL:\nld.relaxed.gpu.global.u32 v, [%1];\nsetp.eq.u32 p, v, %2;\nvote.sync.ballot.b32 %0, p, 0xffffffff;\n"
    "and.b32 v, %0, %3;\nsetp.ne.u32 p, v, 0;\n@p bra PD;\n"
    "add.u32 c, c, 1;\nsetp.lt.u32 p, c, 100000;\n@p bra PL;\nPD:\n}" : "=&r"(bal) : "l"(p), "r"(val), "r"(mask) : "memory");
  return bal;
}
__device__ __forceinline__ void fix128_w0(uint32_t* v, const void* p, uint32_t tag, uint32_t mask) {
  asm volatile("{\n.reg .pred p;\n.reg .u32 c, x;\n.reg .b128 t;\n.reg .b64 lo, hi;\nmov.u32 c, 0;\n"
    "FL:\nxor.b32 x, %0, %5;\nand.b32 x, x, %6;\nsetp.eq.u32 p, x, 0;\n@p bra FD;\n"
    "ld.relaxed.gpu.global.b128 t, [%4];\nmov.b128 {lo, hi}, t;\nmov.b64 {%0, %1}, lo;\nmov.b64 {%2, %3}, hi;\n"
    "add.u32 c, c, 1;\nsetp.lt.u32 p, c, 100000;\n@p bra FL;\nFD:\n}"
    : "+r"(v[0]), "+r"(v[1]), "+r"(v[2]), "+r"(v[3]) : "l"(p), "r"(tag), "r"(mask) : "memory");
}
__device__ __forceinline__ void fix128_w3(uint32_t* v, const void* p, uint32_t tag, uint32_t mask) {
  asm volatile("{\n.reg .pred p;\n.reg .u32 c, x;\n.reg .b128 t;\n.reg .b64 lo, hi;\nmov.u32 c, 0;\n"
    "FL:\nxor.b32 x, %3, %5;\nand.b32 x, x, %6;\nsetp.eq.u32 p, x, 0;\n@p bra FD;\n"
    "ld.relaxed.gpu.global.b128 t, [%4];\nmov.b128 {lo, hi}, t;\nmov.b64 {%0, %1}, lo;\nmov.b64 {%2, %3}, hi;\n"
    "add.u32 c, c, 1;\nsetp.lt.u32 p, c, 100000;\n@p bra FL;\nFD:\n}"
    : "+r"(v[0]), "+r"(v[1]), "+r"(v[2]), "+r"(v[3]) : "l"(p), "r"(tag), "r"(mask) : "memory");
}
__device__ __forceinline__ void fence_acq() { asm volatile("fence.acq_rel.gpu;" ::: "memory"); }
__device__ __forceinline__ bool elect_one() {
  uint32_t p; asm volatile("{\n.reg .pred P;\nelect.sync _|P, 0xffffffff;\nselp.u32 %0, 1, 0, P;\n}" : "=r"(p)); return p;
}
__device__ __forceinline__ void bar_sync(int id, int n) { asm volatile("bar.sync %0, %1;" :: "r"(id), "r"(n) : "memory"); }
__device__ __forceinline__ void fence_async() { asm volatile("fence.proxy.async.shared::cta;" ::: "memory"); }
__device__ __forceinline__ void fence_async_g() { asm volatile("fence.proxy.async.global;" ::: "memory"); }
__device__ __forceinline__ void tma2d(uint32_t dst, const CUtensorMap* m, uint32_t bar, int c0, int c1) {
  asm volatile("cp.async.bulk.tensor.2d.shared::cluster.global.mbarrier::complete_tx::bytes [%0], [%1, {%3, %4}], [%2];"
    :: "r"(dst), "l"(m), "r"(bar), "r"(c0), "r"(c1) : "memory");
}
__device__ __forceinline__ void tma3d(uint32_t dst, const CUtensorMap* m, uint32_t bar, int c0, int c1, int c2) {
  asm volatile("cp.async.bulk.tensor.3d.shared::cluster.global.mbarrier::complete_tx::bytes [%0], [%1, {%3, %4, %5}], [%2];"
    :: "r"(dst), "l"(m), "r"(bar), "r"(c0), "r"(c1), "r"(c2) : "memory");
}
__device__ __forceinline__ void tma4d(uint32_t dst, const CUtensorMap* m, uint32_t bar, int c0, int c1, int c2, int c3) {
  asm volatile("cp.async.bulk.tensor.4d.shared::cluster.global.mbarrier::complete_tx::bytes [%0], [%1, {%3, %4, %5, %6}], [%2];"
    :: "r"(dst), "l"(m), "r"(bar), "r"(c0), "r"(c1), "r"(c2), "r"(c3) : "memory");
}
__device__ __forceinline__ void tma2d_st(const CUtensorMap* m, uint32_t src, int c0, int c1) {
  asm volatile("cp.async.bulk.tensor.2d.global.shared::cta.bulk_group [%0, {%2, %3}], [%1];"
    :: "l"(m), "r"(src), "r"(c0), "r"(c1) : "memory");
}
__device__ __forceinline__ void bulk_ld(uint32_t dst, const void* src, uint32_t bytes, uint32_t bar) {
  asm volatile("cp.async.bulk.shared::cluster.global.mbarrier::complete_tx::bytes [%0], [%1], %2, [%3];"
    :: "r"(dst), "l"(src), "r"(bytes), "r"(bar) : "memory");
}
__device__ __forceinline__ void bulk_st(void* dst, uint32_t src, uint32_t bytes) {
  asm volatile("cp.async.bulk.global.shared::cta.bulk_group [%0], [%1], %2;" :: "l"(dst), "r"(src), "r"(bytes) : "memory");
}
__device__ __forceinline__ void bulk_commit() { asm volatile("cp.async.bulk.commit_group;" ::: "memory"); }
__device__ __forceinline__ void bulk_wait0() { asm volatile("cp.async.bulk.wait_group 0;" ::: "memory"); }
__device__ __forceinline__ void bulk_wait0_read() { asm volatile("cp.async.bulk.wait_group.read 0;" ::: "memory"); }
__device__ __forceinline__ unsigned ld_rlx(const unsigned* p) { unsigned v; asm volatile("ld.relaxed.gpu.global.u32 %0, [%1];" : "=r"(v) : "l"(p) : "memory"); return v; }
__device__ __forceinline__ unsigned ld_acq(const unsigned* p) { unsigned v; asm volatile("ld.acquire.gpu.global.u32 %0, [%1];" : "=r"(v) : "l"(p) : "memory"); return v; }
__device__ __forceinline__ void st_rlx(unsigned* p, unsigned v) { asm volatile("st.relaxed.gpu.global.u32 [%0], %1;" :: "l"(p), "r"(v) : "memory"); }
__device__ __forceinline__ void st_rel(unsigned* p, unsigned v) { asm volatile("st.release.gpu.global.u32 [%0], %1;" :: "l"(p), "r"(v) : "memory"); }
__device__ __forceinline__ void ld128_rlx(uint32_t* v, const void* p) {
  asm volatile("{\n.reg .b128 t;\n.reg .b64 lo, hi;\nld.relaxed.gpu.global.b128 t, [%4];\nmov.b128 {lo, hi}, t;\n"
    "mov.b64 {%0, %1}, lo;\nmov.b64 {%2, %3}, hi;\n}" : "=r"(v[0]), "=r"(v[1]), "=r"(v[2]), "=r"(v[3]) : "l"(p) : "memory");
}
__device__ __forceinline__ void st128_rlx(void* p, const uint32_t* v) {
  asm volatile("{\n.reg .b128 t;\n.reg .b64 lo, hi;\nmov.b64 lo, {%1, %2};\nmov.b64 hi, {%3, %4};\nmov.b128 t, {lo, hi};\n"
    "st.relaxed.gpu.global.b128 [%0], t;\n}" :: "l"(p), "r"(v[0]), "r"(v[1]), "r"(v[2]), "r"(v[3]) : "memory");
}
__device__ __forceinline__ uint32_t lds32(uint32_t a) { uint32_t v; asm volatile("ld.shared.u32 %0, [%1];" : "=r"(v) : "r"(a) : "memory"); return v; }
__device__ __forceinline__ uint32_t lds32v(uint32_t a) { uint32_t v; asm volatile("ld.volatile.shared.u32 %0, [%1];" : "=r"(v) : "r"(a) : "memory"); return v; }
__device__ __forceinline__ uint32_t cpa(uint32_t a, uint32_t one) { uint32_t v; asm volatile("mul.lo.u32 %0, %1, %2;" : "=r"(v) : "r"(a), "r"(one)); return v; }
__device__ __forceinline__ uint32_t cpb(uint32_t a, uint32_t zero) { uint32_t v; asm volatile("or.b32 %0, %1, %2;" : "=r"(v) : "r"(a), "r"(zero)); return v; }
__device__ __forceinline__ uint32_t lds16(uint32_t a) { uint16_t v; asm volatile("ld.shared.u16 %0, [%1];" : "=h"(v) : "r"(a) : "memory"); return v; }
__device__ __forceinline__ float ldsf(uint32_t a) { float v; asm volatile("ld.shared.f32 %0, [%1];" : "=f"(v) : "r"(a) : "memory"); return v; }
__device__ __forceinline__ void lds128(uint32_t* v, uint32_t a) { asm volatile("ld.shared.v4.u32 {%0,%1,%2,%3}, [%4];" : "=r"(v[0]), "=r"(v[1]), "=r"(v[2]), "=r"(v[3]) : "r"(a) : "memory"); }
__device__ __forceinline__ void sts32(uint32_t a, uint32_t v) { asm volatile("st.shared.u32 [%0], %1;" :: "r"(a), "r"(v) : "memory"); }
__device__ __forceinline__ void sts16(uint32_t a, uint32_t v) { asm volatile("st.shared.u16 [%0], %1;" :: "r"(a), "h"((uint16_t)v) : "memory"); }
__device__ __forceinline__ void sts64f(uint32_t a, float x, float y) { asm volatile("st.shared.v2.f32 [%0], {%1,%2};" :: "r"(a), "f"(x), "f"(y) : "memory"); }
__device__ __forceinline__ void sts128(uint32_t a, uint32_t x, uint32_t y, uint32_t z, uint32_t w) { asm volatile("st.shared.v4.u32 [%0], {%1,%2,%3,%4};" :: "r"(a), "r"(x), "r"(y), "r"(z), "r"(w) : "memory"); }
__device__ __forceinline__ void stsm4(uint32_t a, uint32_t r0, uint32_t r1, uint32_t r2, uint32_t r3) {
  asm volatile("stmatrix.sync.aligned.m8n8.x4.shared.b16 [%0], {%1,%2,%3,%4};" :: "r"(a), "r"(r0), "r"(r1), "r"(r2), "r"(r3) : "memory");
}
__device__ __forceinline__ void stsm4t(uint32_t a, uint32_t r0, uint32_t r1, uint32_t r2, uint32_t r3) {
  asm volatile("stmatrix.sync.aligned.m8n8.x4.trans.shared.b16 [%0], {%1,%2,%3,%4};" :: "r"(a), "r"(r0), "r"(r1), "r"(r2), "r"(r3) : "memory");
}
__device__ __forceinline__ void ldsm4t(uint32_t* r, uint32_t a) {
  asm volatile("ldmatrix.sync.aligned.m8n8.x4.trans.shared.b16 {%0,%1,%2,%3}, [%4];" : "=r"(r[0]), "=r"(r[1]), "=r"(r[2]), "=r"(r[3]) : "r"(a) : "memory");
}
__device__ __forceinline__ void ldsm4(uint32_t* r, uint32_t a) {
  asm volatile("ldmatrix.sync.aligned.m8n8.x4.shared.b16 {%0,%1,%2,%3}, [%4];" : "=r"(r[0]), "=r"(r[1]), "=r"(r[2]), "=r"(r[3]) : "r"(a) : "memory");
}
__device__ __forceinline__ void mma16816(float* d, const uint32_t* a, const uint32_t* b) {
  asm volatile("mma.sync.aligned.m16n8k16.row.col.f32.bf16.bf16.f32 {%0,%1,%2,%3}, {%4,%5,%6,%7}, {%8,%9}, {%0,%1,%2,%3};"
    : "+f"(d[0]), "+f"(d[1]), "+f"(d[2]), "+f"(d[3]) : "r"(a[0]), "r"(a[1]), "r"(a[2]), "r"(a[3]), "r"(b[0]), "r"(b[1]));
}
__device__ __forceinline__ uint32_t pack2(float lo, float hi) { uint32_t r; asm("cvt.rn.bf16x2.f32 %0, %1, %2;" : "=r"(r) : "f"(hi), "f"(lo)); return r; }
__device__ __forceinline__ uint32_t packh(float lo, float hi) { uint32_t r; asm("cvt.rn.f16x2.f32 %0, %1, %2;" : "=r"(r) : "f"(hi), "f"(lo)); return r; }
__device__ __forceinline__ uint32_t hcmul(uint32_t x, uint32_t zp, uint32_t zq) {
  const __half2 xx = *reinterpret_cast<__half2*>(&x);
  const __half2 r = __hfma2(__high2half2(xx), *reinterpret_cast<__half2*>(&zq), __hmul2(__low2half2(xx), *reinterpret_cast<__half2*>(&zp)));
  return *reinterpret_cast<const uint32_t*>(&r);
}
__device__ __forceinline__ void hcm2(uint32_t xr, uint32_t xi, uint32_t z, uint32_t& pr, uint32_t& pi) {
  const __half2 a = *reinterpret_cast<__half2*>(&xr), b = *reinterpret_cast<__half2*>(&xi), zz = *reinterpret_cast<__half2*>(&z);
  const __half2 re = __hfma2(__hneg2(b), __high2half2(zz), __hmul2(a, __low2half2(zz)));
  const __half2 im = __hfma2(a, __high2half2(zz), __hmul2(b, __low2half2(zz)));
  pr = *reinterpret_cast<const uint32_t*>(&re); pi = *reinterpret_cast<const uint32_t*>(&im);
}
__device__ __forceinline__ void sts64(uint32_t a, uint32_t x, uint32_t y) { asm volatile("st.shared.v2.u32 [%0], {%1,%2};" :: "r"(a), "r"(x), "r"(y) : "memory"); }
__device__ __forceinline__ void lds64(uint32_t* v, uint32_t a) { asm volatile("ld.shared.v2.u32 {%0,%1}, [%2];" : "=r"(v[0]), "=r"(v[1]) : "r"(a) : "memory"); }
__device__ __forceinline__ float bf_lo(uint32_t v) { return __uint_as_float(v << 16); }
__device__ __forceinline__ float bf_hi(uint32_t v) { return __uint_as_float(v & 0xffff0000u); }
__device__ __forceinline__ float bf_round(float x) { return bf_lo(pack2(x, 0.f)); }
__device__ __forceinline__ float ex2(float x) { float r; asm("ex2.approx.ftz.f32 %0, %1;" : "=f"(r) : "f"(x)); return r; }
__device__ __forceinline__ float phi(float t, float l2e = 1.44269504089f) {
  float e = ex2(t * l2e) + 1e-6f;
  asm("{\n.reg .pred p;\nsetp.gt.f32 p, %1, 0f00000000;\n@p add.f32 %0, %1, 0f3F800008;\n}" : "+f"(e) : "f"(t));
  return e;
}
__device__ __forceinline__ void wg_fence() { asm volatile("wgmma.fence.sync.aligned;" ::: "memory"); }
__device__ __forceinline__ void wg_commit() { asm volatile("wgmma.commit_group.sync.aligned;" ::: "memory"); }
template <int N> __device__ __forceinline__ void wg_wait() { asm volatile("wgmma.wait_group.sync.aligned %0;" :: "n"(N) : "memory"); }
template <int N> __device__ __forceinline__ void pin(float* a) {
  #pragma unroll
  for (int i = 0; i < N; i++) asm volatile("" : "+f"(a[i]) :: "memory");
}
__device__ __forceinline__ int rtid() { int t; asm volatile("mov.u32 %0, %%tid.x;" : "=r"(t)); return t; }
__device__ __forceinline__ int opaque(int v) { asm volatile("" : "+r"(v)); return v; }
template <int N> __device__ __forceinline__ void zero(float* a) {
  #pragma unroll
  for (int i = 0; i < N; i++) asm volatile("mov.b32 %0, 0;" : "=f"(a[i]));
}
template <int N> __device__ __forceinline__ void pinu(uint32_t* a) {
  #pragma unroll
  for (int i = 0; i < N; i++) asm volatile("" : "+r"(a[i]) :: "memory");
}
__device__ __forceinline__ void cexp_t(float lg2mag, float turns, float& re, float& im) {
  float m = ex2(lg2mag);
  float fr = (turns - __fadd_rn(__fadd_rn(turns, 12582912.f), -12582912.f)) * 6.283185307f;
  re = m * __cosf(fr); im = m * __sinf(fr);
}
__device__ __forceinline__ void cmul(float ar, float ai, float br, float bi, float& cr, float& ci) {
  cr = fmaf(ar, br, -ai * bi); ci = fmaf(ar, bi, ai * br);
}

__device__ __forceinline__ void wg_ss192_tb(float* d, uint64_t da, uint64_t db, int scale_d) {
  asm volatile("{\n.reg .pred p;\nsetp.ne.b32 p, %98, 0;\n"
    "wgmma.mma_async.sync.aligned.m64n192k16.f32.bf16.bf16 "
    "{%0, %1, %2, %3, %4, %5, %6, %7, %8, %9, %10, %11, %12, %13, %14, %15, %16, %17, %18, %19, %20, %21, %22, %23, %24, %25, %26, %27, %28, %29, %30, %31, %32, %33, %34, %35, %36, %37, %38, %39, %40, %41, %42, %43, %44, %45, %46, %47, %48, %49, %50, %51, %52, %53, %54, %55, %56, %57, %58, %59, %60, %61, %62, %63, %64, %65, %66, %67, %68, %69, %70, %71, %72, %73, %74, %75, %76, %77, %78, %79, %80, %81, %82, %83, %84, %85, %86, %87, %88, %89, %90, %91, %92, %93, %94, %95}, %96, %97, p, 1, 1, 0, 1;\n}\n"
    : "+f"(d[0]), "+f"(d[1]), "+f"(d[2]), "+f"(d[3]), "+f"(d[4]), "+f"(d[5]), "+f"(d[6]), "+f"(d[7]), "+f"(d[8]), "+f"(d[9]), "+f"(d[10]), "+f"(d[11]), "+f"(d[12]), "+f"(d[13]), "+f"(d[14]), "+f"(d[15]), "+f"(d[16]), "+f"(d[17]), "+f"(d[18]), "+f"(d[19]), "+f"(d[20]), "+f"(d[21]), "+f"(d[22]), "+f"(d[23]), "+f"(d[24]), "+f"(d[25]), "+f"(d[26]), "+f"(d[27]), "+f"(d[28]), "+f"(d[29]), "+f"(d[30]), "+f"(d[31]), "+f"(d[32]), "+f"(d[33]), "+f"(d[34]), "+f"(d[35]), "+f"(d[36]), "+f"(d[37]), "+f"(d[38]), "+f"(d[39]), "+f"(d[40]), "+f"(d[41]), "+f"(d[42]), "+f"(d[43]), "+f"(d[44]), "+f"(d[45]), "+f"(d[46]), "+f"(d[47]), "+f"(d[48]), "+f"(d[49]), "+f"(d[50]), "+f"(d[51]), "+f"(d[52]), "+f"(d[53]), "+f"(d[54]), "+f"(d[55]), "+f"(d[56]), "+f"(d[57]), "+f"(d[58]), "+f"(d[59]), "+f"(d[60]), "+f"(d[61]), "+f"(d[62]), "+f"(d[63]), "+f"(d[64]), "+f"(d[65]), "+f"(d[66]), "+f"(d[67]), "+f"(d[68]), "+f"(d[69]), "+f"(d[70]), "+f"(d[71]), "+f"(d[72]), "+f"(d[73]), "+f"(d[74]), "+f"(d[75]), "+f"(d[76]), "+f"(d[77]), "+f"(d[78]), "+f"(d[79]), "+f"(d[80]), "+f"(d[81]), "+f"(d[82]), "+f"(d[83]), "+f"(d[84]), "+f"(d[85]), "+f"(d[86]), "+f"(d[87]), "+f"(d[88]), "+f"(d[89]), "+f"(d[90]), "+f"(d[91]), "+f"(d[92]), "+f"(d[93]), "+f"(d[94]), "+f"(d[95])
    : "l"(da), "l"(db), "r"(scale_d));
}
__device__ __forceinline__ void wg_ss48_tb(float* d, uint64_t da, uint64_t db, int scale_d) {
  asm volatile("{\n.reg .pred p;\nsetp.ne.b32 p, %26, 0;\n"
    "wgmma.mma_async.sync.aligned.m64n48k16.f32.bf16.bf16 "
    "{%0, %1, %2, %3, %4, %5, %6, %7, %8, %9, %10, %11, %12, %13, %14, %15, %16, %17, %18, %19, %20, %21, %22, %23}, %24, %25, p, 1, 1, 0, 1;\n}\n"
    : "+f"(d[0]), "+f"(d[1]), "+f"(d[2]), "+f"(d[3]), "+f"(d[4]), "+f"(d[5]), "+f"(d[6]), "+f"(d[7]), "+f"(d[8]), "+f"(d[9]), "+f"(d[10]), "+f"(d[11]), "+f"(d[12]), "+f"(d[13]), "+f"(d[14]), "+f"(d[15]), "+f"(d[16]), "+f"(d[17]), "+f"(d[18]), "+f"(d[19]), "+f"(d[20]), "+f"(d[21]), "+f"(d[22]), "+f"(d[23])
    : "l"(da), "l"(db), "r"(scale_d));
}
__device__ __forceinline__ void wg_ss48_tt(float* d, uint64_t da, uint64_t db, int scale_d) {
  asm volatile("{\n.reg .pred p;\nsetp.ne.b32 p, %26, 0;\n"
    "wgmma.mma_async.sync.aligned.m64n48k16.f32.bf16.bf16 "
    "{%0, %1, %2, %3, %4, %5, %6, %7, %8, %9, %10, %11, %12, %13, %14, %15, %16, %17, %18, %19, %20, %21, %22, %23}, %24, %25, p, 1, 1, 1, 1;\n}\n"
    : "+f"(d[0]), "+f"(d[1]), "+f"(d[2]), "+f"(d[3]), "+f"(d[4]), "+f"(d[5]), "+f"(d[6]), "+f"(d[7]), "+f"(d[8]), "+f"(d[9]), "+f"(d[10]), "+f"(d[11]), "+f"(d[12]), "+f"(d[13]), "+f"(d[14]), "+f"(d[15]), "+f"(d[16]), "+f"(d[17]), "+f"(d[18]), "+f"(d[19]), "+f"(d[20]), "+f"(d[21]), "+f"(d[22]), "+f"(d[23])
    : "l"(da), "l"(db), "r"(scale_d));
}
__device__ __forceinline__ void wg_rs88_tb(float* d, const uint32_t* a, uint64_t db, int scale_d) {
  asm volatile("{\n.reg .pred p;\nsetp.ne.b32 p, %49, 0;\n"
    "wgmma.mma_async.sync.aligned.m64n88k16.f32.bf16.bf16 "
    "{%0, %1, %2, %3, %4, %5, %6, %7, %8, %9, %10, %11, %12, %13, %14, %15, %16, %17, %18, %19, %20, %21, %22, %23, %24, %25, %26, %27, %28, %29, %30, %31, %32, %33, %34, %35, %36, %37, %38, %39, %40, %41, %42, %43}, {%44, %45, %46, %47}, %48, p, 1, 1, 1;\n}\n"
    : "+f"(d[0]), "+f"(d[1]), "+f"(d[2]), "+f"(d[3]), "+f"(d[4]), "+f"(d[5]), "+f"(d[6]), "+f"(d[7]), "+f"(d[8]), "+f"(d[9]), "+f"(d[10]), "+f"(d[11]), "+f"(d[12]), "+f"(d[13]), "+f"(d[14]), "+f"(d[15]), "+f"(d[16]), "+f"(d[17]), "+f"(d[18]), "+f"(d[19]), "+f"(d[20]), "+f"(d[21]), "+f"(d[22]), "+f"(d[23]), "+f"(d[24]), "+f"(d[25]), "+f"(d[26]), "+f"(d[27]), "+f"(d[28]), "+f"(d[29]), "+f"(d[30]), "+f"(d[31]), "+f"(d[32]), "+f"(d[33]), "+f"(d[34]), "+f"(d[35]), "+f"(d[36]), "+f"(d[37]), "+f"(d[38]), "+f"(d[39]), "+f"(d[40]), "+f"(d[41]), "+f"(d[42]), "+f"(d[43])
    : "r"(a[0]), "r"(a[1]), "r"(a[2]), "r"(a[3]), "l"(db), "r"(scale_d));
}
__device__ __forceinline__ void wg_ss80_tb(float* d, uint64_t da, uint64_t db, int scale_d) {
  asm volatile("{\n.reg .pred p;\nsetp.ne.b32 p, %42, 0;\n"
    "wgmma.mma_async.sync.aligned.m64n80k16.f32.bf16.bf16 "
    "{%0, %1, %2, %3, %4, %5, %6, %7, %8, %9, %10, %11, %12, %13, %14, %15, %16, %17, %18, %19, %20, %21, %22, %23, %24, %25, %26, %27, %28, %29, %30, %31, %32, %33, %34, %35, %36, %37, %38, %39}, %40, %41, p, 1, 1, 0, 1;\n}\n"
    : "+f"(d[0]), "+f"(d[1]), "+f"(d[2]), "+f"(d[3]), "+f"(d[4]), "+f"(d[5]), "+f"(d[6]), "+f"(d[7]), "+f"(d[8]), "+f"(d[9]), "+f"(d[10]), "+f"(d[11]), "+f"(d[12]), "+f"(d[13]), "+f"(d[14]), "+f"(d[15]), "+f"(d[16]), "+f"(d[17]), "+f"(d[18]), "+f"(d[19]), "+f"(d[20]), "+f"(d[21]), "+f"(d[22]), "+f"(d[23]), "+f"(d[24]), "+f"(d[25]), "+f"(d[26]), "+f"(d[27]), "+f"(d[28]), "+f"(d[29]), "+f"(d[30]), "+f"(d[31]), "+f"(d[32]), "+f"(d[33]), "+f"(d[34]), "+f"(d[35]), "+f"(d[36]), "+f"(d[37]), "+f"(d[38]), "+f"(d[39])
    : "l"(da), "l"(db), "r"(scale_d));
}
__device__ __forceinline__ void wg_ss48_tt_h(float* d, uint64_t da, uint64_t db, int scale_d) {
  asm volatile("{\n.reg .pred p;\nsetp.ne.b32 p, %26, 0;\n"
    "wgmma.mma_async.sync.aligned.m64n48k16.f32.f16.f16 "
    "{%0, %1, %2, %3, %4, %5, %6, %7, %8, %9, %10, %11, %12, %13, %14, %15, %16, %17, %18, %19, %20, %21, %22, %23}, %24, %25, p, 1, 1, 1, 1;\n}\n"
    : "+f"(d[0]), "+f"(d[1]), "+f"(d[2]), "+f"(d[3]), "+f"(d[4]), "+f"(d[5]), "+f"(d[6]), "+f"(d[7]), "+f"(d[8]), "+f"(d[9]), "+f"(d[10]), "+f"(d[11]), "+f"(d[12]), "+f"(d[13]), "+f"(d[14]), "+f"(d[15]), "+f"(d[16]), "+f"(d[17]), "+f"(d[18]), "+f"(d[19]), "+f"(d[20]), "+f"(d[21]), "+f"(d[22]), "+f"(d[23])
    : "l"(da), "l"(db), "r"(scale_d));
}

struct Params {
  const __nv_bfloat16 *par[4], *logdt, *dskip, *u, *wo;
  CUtensorMap m[M_COUNT];
};

#define CHUNK(i) ((i) == 0 ? c : ((i) == 7 ? (c ^ 1) : (((c & 6) + 1 + (i)) & 7)))
#define FLAG(kind, rr, cc) (&g_flag[((kind) * 128 + (rr) * 8 + (cc)) * 32])
#define SLOT(i) ((i) == 0 || (i) == 5 ? OFF_EXTRA : OFF_BLK + ((i) == 7 ? 0 : (i) == 6 ? 4 : (i) - 1) * BLK)
__device__ __forceinline__ void load_quad(uint32_t* A, uint32_t addr) {
  A[0] = lds32v(addr); A[1] = lds32v(addr + 32); A[2] = lds32v(addr - 32); A[3] = lds32v(addr);
}

__global__ void __launch_bounds__(512, 1) fused_kernel(const __grid_constant__ Params prm) {
  extern __shared__ unsigned char smem_raw[];
  const uint32_t sb = __shfl_sync(0xffffffff, smem_u32(smem_raw), 0);
  const int tid = threadIdx.x, lane = tid & 31;
  const int warp = __shfl_sync(0xffffffff, tid >> 5, 0), wg = warp >> 2, w4 = warp & 3;
  const int cta = blockIdx.x, r = cta >> 3, c = cta & 7;
  if ((sb & 0xffffffu) != SB0) return;
#define BAR(i) (sb + OFF_BAR + 8 * (i))
  const bool sw64 = ((c + 1) & 2) != 0;

  if (wg == 3) {
    if (warp == 13 && elect_one()) {
      #pragma unroll
      for (int i = M_W128; i <= M_U; i++) asm volatile("prefetch.tensormap [%0];" :: "l"(&prm.m[i]) : "memory");
    }
    asm volatile("setmaxnreg.dec.sync.aligned.u32 56;");
    const int tid = rtid(), lane = tid & 31;
    if (warp == 12) {
      if (elect_one()) {
        #pragma unroll
        for (int i = 0; i < 5; i++) mbar_init(BAR(BR_FULL + i), 1);
        asm volatile("fence.mbarrier_init.release.cluster;" ::: "memory");
      }
      {
        const CUtensorMap* mwp = &prm.m[sw64 ? M_W64 : M_W128];
        const int mcol = (c * 80 + (c & 1) * 16) >> (sw64 ? 5 : 6), rcol = c * 80 + ((c & 1) ? 0 : 64);
        uint32_t s = 0, ph = 1, xs = 0;
        #pragma unroll 1
        for (int kb = 0; kb < 20; kb++) {
          if (kb == 3) bar_sync(0, 512);
          if (EN_SSM && kb == 3) { mbar_wait(BAR(BR_UOUT), 0); mbar_wait(BAR(BR_KGEN), 0); }
          if (kb >= 5) mbar_wait(BAR(BR_EMPTY) + 8 * s, ph);
          if (EN_ATT && elect_one()) {
            const uint32_t st = sb + s * W_SLOT, fb = BAR(BR_FULL) + 8 * s;
            mbar_expect_tx(fb, (kb & 1) ? W_SLOT : W_SLOT + 16384);
            if (!(kb & 1)) tma2d(sb + OFF_X + xs, &prm.m[M_X], fb, kb * 32, r * 128);
            tma4d(st, mwp, fb, 0, kb * 32, mcol, 0);
            tma3d(st + 12288, &prm.m[M_WR], fb, rcol, kb * 32, 0);
          }
          if (kb == 14 && elect_one()) asm volatile("cp.async.bulk.prefetch.L2.global [%0], 6400;" :: "l"(prm.wo + cta * 3200) : "memory");
          if (!EN_ATT && kb == 3) break;
          if (++s == 5) { s = 0; ph ^= 1; }
          if (kb & 1) { xs += 16384; if (xs == 49152) xs = 0; }
        }
      }
      if (EN_ATT) {
      mbar_wait(BAR(BR_EPOCH), 0);
      const unsigned epoch = lds32(sb + OFF_EPOCH);
      const unsigned* fo = FLAG(3, r, lane & 7);
      unsigned seen = __ballot_sync(0xffffffff, ld_rlx(lane < 16 ? fo : FLAG(0, lane & 15, c)) == epoch) & 0xffu;
      mbar_wait(BAR(BR_GEMM), 0);
      if (elect_one()) {
        mbar_expect_tx(BAR(BR_WO), 10240);
        tma2d(sb, &prm.m[M_WO], BAR(BR_WO), c * 64, c * 80);
        mbar_expect_tx(BAR(BR_KVP), 61440);
        mbar_expect_tx(BAR(BR_WO + 1), 7 * 10240);
      }
      {
        uint32_t ds = sb + OFF_WOR + (lane >> 3) * 128 + (((lane & 7) ^ (lane >> 3)) << 4);
        #pragma unroll 1
        for (int h = 0; h < 2; h++) {
          const int i = (lane & 6) + h;
          const char* gs = reinterpret_cast<const char*>(prm.wo) + (size_t)((lane >> 3) + CHUNK(i) * 80) * 1280 + 1024 + c * 32 + (lane & 1) * 16;
          #pragma unroll 2
          for (int q = 0; q < 20; q++) {
            asm volatile("cp.async.cg.shared.global [%0], [%1], 16;" :: "r"(ds), "l"(gs) : "memory");
            ds = (ds + 512) ^ 64; gs += 5120;
          }
        }
      }
      mbar_wait(BAR(BR_PUB), 0);
      poll_all(FLAG(0, lane & 15, c), epoch);
      if (elect_one()) { TS(23); bulk_ld(sb + OFF_KVP, &g_kvp[c * 16 * 240], 61440, BAR(BR_KVP)); }
      asm volatile("cp.async.wait_all;" ::: "memory");
      fence_async();
      mbar_arrive(BAR(BR_WO));
      mbar_wait(BAR(BR_SUM), 0);
      if (elect_one()) {
        #pragma unroll 1
        for (int i = 1; i < 8; i++) tma2d(sb + i * 10240, &prm.m[M_WO], BAR(BR_WO + 1), c * 64, CHUNK(i) * 80);
      }
      mbar_wait(BAR(BR_OSTG), 0);
      if (elect_one()) {
        bulk_st(&g_o[cta * 1280], sb + OFF_EXTRA, 20480);
        bulk_commit();
        bulk_wait0();
        st_rlx(FLAG(3, r, c), epoch);
        TS(20);
      }
      __syncwarp();
      #pragma unroll 1
      for (int i = 1; i < 8; i++) {
        const int src = CHUNK(i);
        if (!((seen >> src) & 1)) seen = poll_bit(fo, epoch, 1u << src);
        if (i == 5 || i == 7) mbar_wait(BAR(BR_OEMPTY) + 4 * (i - 5), 0);
        if (EN_SSM && (i == 1 || i == 4)) mbar_wait(BAR(BR_FREE) + 2 * (i & 4), 0);
        if (elect_one()) {
          mbar_expect_tx(BAR(BR_OFULL) + 8 * i, 20480);
          bulk_ld(sb + SLOT(i), &g_o[(r * 8 + src) * 1280], 20480, BAR(BR_OFULL) + 8 * i);
          if (i == 1) TS(21);
          if (i == 7) TS(22);
        }
        __syncwarp();
      }
      if (lane == 0) { DUMP(20, 30); }
      }
    } else {
      const int hw = warp - 13, ht = tid - 416;
      const unsigned epoch = hw == 0 ? ld_rlx(&g_epoch[cta]) + 1 : 0;
      if (hw == 2 && elect_one()) {
        #pragma unroll
        for (int i = 5; i < BR_COUNT; i++) mbar_init(BAR(i), i == BR_WO ? 33 : i < BR_EMPTY ? 1 : i < BR_OEMPTY ? 2 : i < BR_Y ? 8 : i < BR_OSTG ? 128 : 256);
        asm volatile("fence.mbarrier_init.release.cluster;" ::: "memory");
      }
      bar_sync(0, 512);
      if (EN_SSM && hw == 0 && elect_one()) { mbar_expect_tx(BAR(BR_UIN), 20480); tma2d(sb + OFF_UT, &prm.m[M_U], BAR(BR_UIN), c * 80, r * 128); }
      if (hw == 1 && elect_one()) {
        #pragma unroll
        for (int i = M_WO; i < M_COUNT; i++) asm volatile("prefetch.tensormap [%0];" :: "l"(&prm.m[i]) : "memory");
      }
      if (ht == 0) {
        st_rlx(&g_epoch[cta], epoch);
        sts32(sb + OFF_EPOCH, epoch);
        mbar_arrive(BAR(BR_EPOCH));
      }
      if (EN_SSM) {
      const int mi = lane >> 3, rw = lane & 7, ch0 = c * 80 + r * 5;
      mbar_wait(BAR(BR_UIN), 0);
      if (ht == 0) TS(36);
      #pragma unroll 1
      for (int h = 0; h < 2; h++) {
        const uint32_t sa = sb + OFF_UT + h * 10240 + (8 * mi + rw) * 160 + hw * 16, da = sb + OFF_UT + h * 10240 + (hw * 8 + rw) * 128 + ((mi ^ rw) << 4);
        uint32_t v[8][4];
        #pragma unroll
        for (int q = 0; q < 8; q++) if (q < 6 || hw == 0) ldsm4t(v[q], sa + (q & 1) * 5120 + (q >> 1) * 48);
        bar_sync(5, 96);
        #pragma unroll
        for (int q = 0; q < 8; q++) if (q < 6 || hw == 0) stsm4((da ^ ((q & 1) * 64)) + (q >> 1) * 3072, v[q][0], v[q][1], v[q][2], v[q][3]);
      }
      fence_async();
      bar_sync(5, 96);
      if (hw == 0) {
        if (elect_one()) {
          tma2d_st(&prm.m[M_SA], sb + OFF_UT, r * 128, c * 80);
          tma2d_st(&prm.m[M_SA], sb + OFF_UT + 10240, r * 128 + 64, c * 80);
          bulk_commit(); bulk_wait0_read();
          mbar_arrive(BAR(BR_UOUT));
          TS(37);
          bulk_wait0();
          st_rel(FLAG(1, r, c), epoch);
          TS(30);
        }
        __syncwarp();
        poll_all_acq(FLAG(1, lane & 15, c), epoch);
        mbar_wait(BAR(BR_KGEN), 0);
        if (elect_one()) {
          fence_async_g();
          mbar_expect_tx(BAR(BR_U), 20480);
          #pragma unroll 1
          for (int q = 0; q < 5; q++) tma2d(sb + OFF_BLK + q * BLK, &prm.m[M_SB], BAR(BR_U), 0, (ch0 + q) * 32);
          TS(31);
        }
        __syncwarp();
      }
      if (hw == 0) {
        #pragma unroll 1
        for (int p = 0; p < 2; p++) {
          mbar_wait(BAR(BR_Y) + 8 * p, 0);
          if (elect_one()) {
            #pragma unroll 1
            for (int k = 4 * p; k < 4 + p; k++) tma2d_st(&prm.m[M_SB], sb + OFF_BLK + k * BLK, 0, (640 + ch0 + k) * 32);
            bulk_commit(); bulk_wait0_read();
            mbar_arrive(BAR(BR_FREE) + 8 * p);
          }
          __syncwarp();
        }
        if (elect_one()) {
          mbar_expect_tx(BAR(BR_YIN), 20480);
          bulk_wait0();
          st_rel(FLAG(2, r, c), epoch);
          TS(33);
        }
        __syncwarp();
        poll_all_acq(FLAG(2, lane & 15, c), epoch);
        if (EN_ATT) mbar_wait(BAR(BR_OEMPTY + 3), 0);
        if (elect_one()) {
          fence_async_g();
          tma2d(sb + OFF_BLK + BLK, &prm.m[M_SA], BAR(BR_YIN), r * 128, 640 + c * 80);
          tma2d(sb + OFF_BLK + BLK + 10240, &prm.m[M_SA], BAR(BR_YIN), r * 128 + 64, 640 + c * 80);
          TS(34);
        }
      }
      {
        uint32_t sa = sb + OFF_BLK + BLK + (hw * 8 + rw) * 128 + ((mi ^ rw) << 4);
        uint32_t da = sb + OFF_BLK + 2 * BLK + (8 * mi + rw) * 160 + hw * 16;
        mbar_wait(BAR(BR_YIN), 0);
        #pragma unroll 1
        for (int i = hw; i < 10; i += 3) {
          uint32_t v[4][4];
          #pragma unroll
          for (int q = 0; q < 4; q++) ldsm4t(v[q], (sa ^ ((q & 1) * 64)) + (q >> 1) * 10240);
          #pragma unroll
          for (int q = 0; q < 4; q++) stsm4(da + q * 5120, v[q][0], v[q][1], v[q][2], v[q][3]);
          sa += 3072; da += 48;
        }
      }
      fence_async();
      bar_sync(5, 96);
      if (hw == 0 && elect_one()) {
        tma2d_st(&prm.m[M_OUT], sb + OFF_BLK + 2 * BLK, c * 80, r * 128);
        bulk_commit(); bulk_wait0_read();
        TS(35); DUMP(30, 40); DUMP(0, 1);
      }
      }
    }
  } else {
    const int g = lane >> 2, tq = lane & 3, t7 = tid & 127;
    uint32_t pr[3][3];
    {
      const int ch = c * 80 + r * 5 + wg;
      uint32_t raw[3][6];
      #pragma unroll
      for (int e = 0; e < 6; e++) {
        const __nv_bfloat16* pp = e < 4 ? prm.par[e] + ch * 128 + t7 : (e == 4 ? prm.logdt : prm.dskip) + ch;
        #pragma unroll
        for (int q = 0; q < 3; q++) asm volatile("ld.global.nc.u16 %0, [%1];" : "=r"(raw[q][e]) : "l"(pp + q * (e < 4 ? 128 : 1)));
      }
      asm volatile("setmaxnreg.inc.sync.aligned.u32 152;");
      if (EN_SSM) {
        #pragma unroll 1
        for (int k = wg; k < (wg == 2 ? 5 : wg + 1); k++) {
          const uint32_t z = sb + OFF_BLK + k * BLK + t7 * 16;
          sts128(z + B_TBL, 0, 0, 0, 0); sts128(z + B_TBL + 2048, 0, 0, 0, 0);
          if (t7 < 16) sts128(z - 256, 0, 0, 0, 0);
        }
      }
      bar_sync(0, 512);
      #pragma unroll
      for (int q = 0; q < 3; q++) {
        #pragma unroll
        for (int e = 0; e < 3; e++) pr[q][e] = raw[q][2 * e] | (raw[q][2 * e + 1] << 16);
        const uint32_t m = __reduce_max_sync(0xffffffff, max(raw[q][2] & 0x7fffu, raw[q][3] & 0x7fffu));
        if (lane == 0) sts32(sb + OFF_EPOCH + 16 + (wg * 3 + q) * 16 + w4 * 4, m);
      }
      bar_sync(2 + wg, 128);
    }
    if (tid == 256) TS(40);
    if (EN_SSM) {
      const uint32_t p0 = wg == 1 ? OFF_X + 32768 : OFF_BLK + wg * 3584, p1 = wg == 1 ? 7168 : BLK, p2 = wg == 1 ? OFF_BLK + 4 * BLK - OFF_X - 32768 : 2 * BLK;
      const uint32_t fa = sb + p0 + (lane >> 4) * p1 + (w4 & 1) * p2 + ((lane >> 3) & 1) * 256 + (lane & 7) * 16;
      const uint32_t ea = fa + (w4 >> 1) * 2048, ga = fa + 4096 + (w4 >> 1) * 1536;
      constexpr uint64_t dE = mkdesc(SB0, 128, 512, 0);
      const uint32_t xs = wg == 2 ? BLK : 1024, xb = sb + (wg == 2 ? OFF_BLK + 18560 : OFF_UT + 20480 + wg * 3072), xa = xb + t7 * 8, xr_ = xb + (t7 ^ 64) * 8;
      #pragma unroll 1
      for (int k = wg; k < (wg == 2 ? 5 : wg + 1); k++) {
        const uint32_t blk = sb + OFF_BLK + k * BLK;
        const uint32_t pa0 = pr[0][0], pc0 = pr[0][1];
        const float dt = bf_round(expf(bf_lo(pr[0][2]))), dsk = bf_hi(pr[0][2]);
        #pragma unroll
        for (int e = 0; e < 3; e++) { pr[0][e] = pr[1][e]; pr[1][e] = pr[2][e]; }
        float fac;
        {
          uint32_t mm[4];
          lds128(mm, sb + OFF_EPOCH + 16 + (wg * 2 + k) * 16);
          const uint32_t ex = min(max(max(max(mm[0], mm[1]), max(mm[2], mm[3])) >> 7, 1u), 253u);
          const float sc = __uint_as_float((254u - ex) << 23);
          fac = 2.f * dt * __uint_as_float(ex << 23);
          const float lr = -bf_round(expf(bf_lo(pa0))) * dt * 1.44269504089f;
          const float tn = bf_hi(pa0) * dt * 0.15915494309f;
          float z1r, z1i, z2r, z2i, z4r, z4i, xr[8], xi[8], gr[8], gi[8], wr[9], wi[9];
          cexp_t(lr, -tn, z1r, z1i);
          cexp_t(lr * 8.f, tn * 8.f, xr[1], xi[1]);
          cexp_t(lr * 64.f, tn * 64.f, wr[0], wi[0]);
          xr[0] = 1.f; xi[0] = 0.f;
          cmul(xr[1], xi[1], xr[1], xi[1], xr[2], xi[2]); cmul(xr[2], xi[2], xr[1], xi[1], xr[3], xi[3]);
          cmul(xr[2], xi[2], xr[2], xi[2], xr[4], xi[4]);
          #pragma unroll
          for (int b = 1; b < 4; b++) cmul(xr[4], xi[4], xr[b], xi[b], xr[4 + b], xi[4 + b]);
          cmul(wr[0], wi[0], wr[0], wi[0], wr[1], wi[1]); cmul(wr[1], wi[1], wr[0], wi[0], wr[2], wi[2]);
          cmul(wr[1], wi[1], wr[1], wi[1], wr[3], wi[3]); cmul(wr[3], wi[3], wr[3], wi[3], wr[4], wi[4]);
          cmul(wr[4], wi[4], wr[3], wi[3], wr[5], wi[5]); cmul(wr[4], wi[4], wr[4], wi[4], wr[6], wi[6]);
          cmul(wr[6], wi[6], wr[4], wi[4], wr[7], wi[7]); cmul(wr[6], wi[6], wr[6], wi[6], wr[8], wi[8]);
          uint32_t R[4], I[4], PR[4], PI[4];
          #pragma unroll
          for (int b = 0; b < 4; b++) { R[b] = packh(xr[2 * b], xr[2 * b + 1]); I[b] = packh(xi[2 * b], xi[2 * b + 1]); }
          sts128(ea, R[0], R[1], R[2], R[3]); sts128(ea + 128, I[0], I[1], I[2], I[3]);
          #pragma unroll
          for (int i = 0; i < 3; i++) {
            const uint32_t z = packh(wr[i], wi[i]);
            #pragma unroll
            for (int b = 0; b < 4; b++) hcm2(R[b], I[b], z, PR[b], PI[b]);
            sts128(ea + (i + 1) * 512, PR[0], PR[1], PR[2], PR[3]); sts128(ea + (i + 1) * 512 + 128, PI[0], PI[1], PI[2], PI[3]);
          }
          gr[0] = bf_lo(pc0) * sc; gi[0] = -bf_hi(pc0) * sc;
          cmul(z1r, z1i, z1r, z1i, z2r, z2i); cmul(z2r, z2i, z2r, z2i, z4r, z4i);
          cmul(gr[0], gi[0], z1r, z1i, gr[1], gi[1]);
          cmul(gr[0], gi[0], z2r, z2i, gr[2], gi[2]); cmul(gr[1], gi[1], z2r, z2i, gr[3], gi[3]);
          #pragma unroll
          for (int b = 0; b < 4; b++) cmul(gr[b], gi[b], z4r, z4i, gr[4 + b], gi[4 + b]);
          sts128(ga, packh(gr[0], gr[1]), packh(gr[2], gr[3]), packh(gr[4], gr[5]), packh(gr[6], gr[7]));
          sts128(ga + 128, packh(gi[0], gi[1]), packh(gi[2], gi[3]), packh(gi[4], gi[5]), packh(gi[6], gi[7]));
          {
            const uint32_t z = packh(wr[3], -wi[3]), a4r = packh(gr[0], gr[4]), a4i = packh(gi[0], gi[4]);
            hcm2(packh(gr[0], gr[2]), packh(gi[0], gi[2]), z, PR[0], PI[0]);
            hcm2(packh(gr[4], gr[6]), packh(gi[4], gi[6]), z, PR[1], PI[1]);
            hcm2(a4r, a4i, packh(wr[4], -wi[4]), PR[2], PI[2]);
            hcm2(a4r, a4i, packh(wr[5], -wi[5]), PR[3], PI[3]);
            sts128(ga + 512, PR[0], PR[1], PR[2], PR[3]); sts128(ga + 512 + 128, PI[0], PI[1], PI[2], PI[3]);
            float hr, hi_;
            cmul(gr[0], gi[0], wr[3], -wi[3], hr, hi_);
            const uint32_t cr = packh(gr[0], hr), ci = packh(gi[0], hi_);
            #pragma unroll
            for (int i = 0; i < 3; i++) hcm2(cr, ci, packh(wr[6 + i], -wi[6 + i]), PR[i], PI[i]);
            sts128(ga + 1024, PR[0], PR[1], PR[2], 0u); sts128(ga + 1024 + 128, PI[0], PI[1], PI[2], 0u);
          }
        }
        fence_async();
        bar_sync(2 + wg, 128);
        if (t7 == 0 && k == 3) TS(50);
        float ka[24]; zero<24>(ka);
        wg_fence();
        #pragma unroll
        for (int s = 0; s < 8; s++) {
          const uint32_t lo = (uint32_t)dE + ((p0 + ((s >> 1) & 1) * p1 + (s >> 2) * p2) >> 4) + (s & 1) * 16;
          wg_ss48_tt_h(ka, desc2(lo, dE >> 32), desc2(lo + 256, dE >> 32), s != 0);
        }
        wg_commit();
        wg_wait<0>();
        pin<24>(ka);
        if (t7 == 0 && k == 3) TS(51);
        float kk[6];
        {
          const bool up = w4 >= 2;
          #pragma unroll
          for (int n = 0; n < 3; n++) {
            sts64f(xa + n * xs, up ? ka[12 + 4 * n] : ka[4 * n + 2], up ? ka[13 + 4 * n] : ka[4 * n + 3]);
            kk[2 * n] = up ? ka[14 + 4 * n] : ka[4 * n]; kk[2 * n + 1] = up ? ka[15 + 4 * n] : ka[4 * n + 1];
          }
          bar_sync(2 + wg, 128);
          #pragma unroll
          for (int n = 0; n < 3; n++) {
            uint32_t o[2]; lds64(o, xr_ + n * xs);
            kk[2 * n] = (kk[2 * n] + __uint_as_float(o[0])) * fac; kk[2 * n + 1] = (kk[2 * n + 1] + __uint_as_float(o[1])) * fac;
          }
        }
        if (t7 == 0 && k == 3) TS(52);
        {
          const int j = (w4 & 1) * 16 + (w4 >> 1) * 8 + g;
          const uint32_t tb = blk + B_TBL;
          if (t7 == 0) kk[0] += dsk;
          const uint32_t pa_ = tb + (16 + 8 * j + 2 * tq) * 4;
          const uint32_t v = pack2(kk[1], kk[0]);
          sts32(pa_ + 4, v); sts16(pa_, v >> 16); sts16(pa_ + 10, v);
          const uint32_t u = pack2(kk[2], kk[3]), w = pack2(kk[4], kk[5]);
          if (tq < 2) {
            const uint32_t pb = tb + (16 + 256 + 8 * j + 4 * tq) * 4;
            sts16(pb, u); sts32(pb + 4, __byte_perm(u, 0, 0x1010)); sts32(pb + 8, __byte_perm(u, 0, 0x1032)); sts16(pb + 14, u >> 16);
            if (j | tq) { sts16(pb - 4, u); sts16(pb + 2, u); }
            const int i = 64 * tq + j;
            const uint32_t e0 = tb + (T_F3 + (((i - 1) & 1) ? 80 : 0) + ((i - 1) >> 1)) * 4, e1 = i ? e0 : tb + (T_F2 + 144 + 31) * 4;
            sts16(e1, w); sts16(e1 + 6, w); sts16(e0 + 64, w >> 16); sts16(e0 + 70, w >> 16);
            if (i == 0) { sts16(tb + (T_S + 3) * 4, w); sts32(tb + (T_S + 4) * 4, __byte_perm(w, 0, 0x1010)); sts16(tb + (T_S + 5) * 4 + 2, w); }
          } else {
            const int i = 32 * (tq - 2) + j;
            const uint32_t e1 = tb + (i ? T_F2 + ((2 * i - 1) & 3) * 48 + ((2 * i - 1) >> 2) : 16 + 511) * 4;
            const uint32_t e2 = tb + (T_F2 + (i & 1) * 96 + (i >> 1)) * 4;
            sts16(e1, u); sts16(e1 + 6, u); sts16(e2, u >> 16); sts16(e2 + 6, u >> 16);
            if (i == 0) {
              const uint32_t uu = __byte_perm(u, 0, 0x1010);
              sts32(tb + 528 * 4, uu); sts32(tb + 529 * 4, uu); sts32(tb + 530 * 4, uu); sts16(tb + 531 * 4 + 2, u);
              sts16(tb + (T_F3 + 80 + 63) * 4, w);
            }
          }
        }
        if (t7 == 0 && k == 3) TS(53);
      }
      if (wg < 2) { fence_async(); mbar_arrive(BAR(BR_KGEN)); }
    }
    if (tid == 0) TS(14);
  if (wg < 2) {
    if (EN_ATT) {
    float am[96], ar[24];
    {
      const bool lead = (rtid() & 127) == 0;
      constexpr uint64_t da0 = mkdesc(SB0 + OFF_X, 16, 1024, 1), dr0 = mkdesc(SB0 + 12288, 1024, 256, 3);
      const uint64_t db0 = sw64 ? mkdesc(SB0, 2048, 512, 2) : mkdesc(SB0, 4096, 1024, 1);
      const uint32_t kst = sw64 ? 64 : 128, bh = db0 >> 32;
      uint32_t s = 0, ph = 0, xo = 0;
      #pragma unroll 1
      for (int kb = 0; kb < 20; kb++) {
        const uint32_t wo_ = s * (W_SLOT >> 4), al = (uint32_t)da0 + wg * 512 + xo, bl = (uint32_t)db0 + wo_, rl = (uint32_t)dr0 + wo_;
        mbar_wait(BAR(BR_FULL) + 8 * s, ph);
        if (kb == 0 && lead && wg == 0) TS(1);
        wg_fence();
        wg_ss192_tb(am, desc2(al, da0 >> 32), desc2(bl, bh), kb != 0);
        wg_ss48_tb(ar, desc2(al, da0 >> 32), desc2(rl, dr0 >> 32), kb != 0);
        wg_ss192_tb(am, desc2(al + 2, da0 >> 32), desc2(bl + kst, bh), 1);
        wg_ss48_tb(ar, desc2(al + 2, da0 >> 32), desc2(rl + 32, dr0 >> 32), 1);
        wg_commit();
        wg_wait<1>();
        if (lead && kb > 0 && kb < 16) mbar_arrive(BAR(BR_EMPTY) + 8 * (s == 0 ? 4 : s - 1));
        if (++s == 5) { s = 0; ph ^= 1; }
        xo += (kb & 1) ? 1020 : 4;
        if (xo == 3072) xo = 0;
      }
      wg_wait<0>();
      pin<96>(am); pin<24>(ar);
    }
    const int tid = rtid(), lane = tid & 31, tq = lane & 3;
    if (tid == 0) TS(2);
#define QV(j, e) ((j) < 8 ? am[4 * (j) + (e)] : ar[4 * ((j) - 8) + (e)])
#define KV_(j, e) ((j) < 8 ? am[32 + 4 * (j) + (e)] : ar[8 + 4 * ((j) - 8) + (e)])
#define VV(j, e) ((j) < 8 ? am[64 + 4 * (j) + (e)] : ar[16 + 4 * ((j) - 8) + (e)])
    {
      bar_sync(1, 256);
      if (tid == 0) mbar_arrive(BAR(BR_GEMM));
      const uint32_t ro = sb + (uint32_t)((warp * 16 + (lane & 15)) * 16);
      const int l0 = 2 * (c & 1) + (lane >> 4);
      const uint32_t ones = (tq == 0) ? 0x00003f80u : 0u;
#define PV(j) pack2(VV(j, 0), VV(j, 1)), pack2(VV(j, 2), VV(j, 3))
#define PK(j) pack2(phi(KV_(j, 0)), phi(KV_(j, 1))), pack2(phi(KV_(j, 2)), phi(KV_(j, 3)))
      stsm4(ro + OFF_V + (5 + 6 * (lane >> 4)) * 2048, ones, ones, ones, ones);
      #pragma unroll
      for (int j = 0; j < 10; j += 2) {
        const int l = (j == 8 && (c & 1)) ? l0 - 2 : l0 + j;
        stsm4(ro + OFF_V + (l + (l >= 5)) * 2048, PV(j), PV(j + 1));
        stsm4(ro + OFF_PK + l * 2048, PK(j), PK(j + 1));
      }
    }
    fence_async();
    bar_sync(1, 256);
    if (tid == 0) TS(3);
    mbar_wait(BAR(BR_EPOCH), 0);
    const unsigned epoch = lds32(sb + OFF_EPOCH);
    {
      float kv[24]; zero<24>(kv);
      constexpr uint64_t da = mkdesc(SB0 + OFF_PK, 128, 2048, 0), db = mkdesc(SB0 + OFF_V, 128, 2048, 0);
      wg_fence();
      #pragma unroll
      for (int s = 0; s < 8; s++) wg_ss48_tt(kv, desc2((uint32_t)da + wg * 640 + s * 16, da >> 32), desc2((uint32_t)db + wg * 768 + s * 16, db >> 32), s != 0);
      wg_commit();
      wg_wait<0>();
      pin<24>(kv);
      if (tid == 0) TS(15);
      if (w4 < 3) {
        const uint32_t wb = sb + OFF_KVS + (wg * 3 + w4) * 1536 + (lane & 15) * 96;
        #pragma unroll
        for (int j = 0; j < 6; j += 2)
          stsm4(wb + (j + (lane >> 4)) * 16, pack2(kv[4 * j], kv[4 * j + 1]), pack2(kv[4 * j + 2], kv[4 * j + 3]),
                pack2(kv[4 * j + 4], kv[4 * j + 5]), pack2(kv[4 * j + 6], kv[4 * j + 7]));
        __syncwarp();
        const int dl = w4 * 16 + (lane & 15), hl = dl >= 20;
        if (dl < 40) {
          uint4* dst = &g_kvp[(c * 16 + r) * 240 + wg * 40 + dl];
          uint32_t v[4], z[4];
          lds128(v, wb + (3 * hl + (lane >> 4)) * 16);
          lds64(z, wb + 32 + 8 * hl); z[2] = lds32(wb + 80); z[3] = epoch & 1u;
          v[3] = (v[3] & ~1u) | z[3];
          st128_rlx(dst + (lane >> 4) * 80, v);
          if (lane < 16) st128_rlx(dst + 160, z);
        }
      }
    }
    fence_async();
    bar_sync(1, 256);
    if (tid == 0) { st_rlx(FLAG(0, r, c), epoch); mbar_arrive(BAR(BR_PUB)); TS(4); }
    const int kvi = (tid >= 80) + (tid >= 160) + (tid >= 240), kd = tid - 80 * kvi;
    const int khd = kd / 20, kt0 = 5 * (khd >> 1) + 2 * (khd & 1);
    const uint32_t rb = sb + OFF_KVB + kd * 16;
    if (kvi < 3) {
      #pragma unroll 1
      for (int m = kvi; m < 7; m += 3) { const int q = kt0 + 3 + m; sts128(rb + (q >= 10 ? q - 10 : q) * 1280, 0, 0, 0, 0); }
    }
    uint32_t qa[20];
    {
      const float sc = 1.44269504089f + __uint_as_float(lds32(sb + OFF_EPOCH) ^ epoch);
      #pragma unroll
      for (int j = 0; j < 10; j++) { qa[2 * j] = pack2(phi(QV(j, 0), sc), phi(QV(j, 1), sc)); qa[2 * j + 1] = pack2(phi(QV(j, 2), sc), phi(QV(j, 3), sc)); }
    }
    if (tid == 0) TS(5);
    mbar_wait(BAR(BR_KVP), 0);
    if (tid == 0) TS(6);
    if (kvi < 3) {
      float s[8];
      zero<8>(s);
      uint32_t bad = 0;
      #pragma unroll 4
      for (int i = 0; i < 16; i++) {
        uint32_t w[4];
        lds128(w, sb + OFF_KVP + tid * 16 + i * 3840);
        bad |= w[3] ^ epoch;
        #pragma unroll
        for (int e = 0; e < 4; e++) { s[2 * e] += bf_lo(w[e]); s[2 * e + 1] += bf_hi(w[e]); }
      }
      if (__builtin_expect(bad & 1u, 0)) {
        zero<8>(s);
        #pragma unroll 1
        for (int i = 0; i < 16; i++) {
          uint32_t w[4] = {0, 0, 0, ~epoch};
          fix128_w3(w, &g_kvp[(c * 16 + i) * 240 + tid], epoch, 1u);
          #pragma unroll
          for (int e = 0; e < 4; e++) { s[2 * e] += bf_lo(w[e]); s[2 * e + 1] += bf_hi(w[e]); }
        }
        FIXCNT
      }
      const uint32_t p0 = pack2(s[0], s[1]), p1 = pack2(s[2], s[3]), p2 = pack2(s[4], s[5]), p3 = pack2(s[6], s[7]);
      if (kvi < 2) sts128(rb + (kt0 + (khd & 1) + kvi) * 1280, p0, p1, p2, p3);
      else {
        const bool od = khd & 1;
        sts128(rb + (5 * (khd >> 1) + 2) * 1280, od ? 0u : p0, od ? 0u : p1, od ? p0 : 0u, od ? p1 : 0u);
        const uint32_t zz = (p2 & 0xffffu) << (16 * (khd & 1));
        sts128(rb + 10 * 1280, khd < 2 ? zz : 0u, khd < 2 ? 0u : zz, 0u, 0u);
      }
    }
    fence_async();
    bar_sync(1, 256);
    if (tid == 0) { mbar_arrive(BAR(BR_SUM)); TS(7); }
    {
      float oa[44]; zero<44>(oa);
      constexpr uint64_t db = mkdesc(SB0 + OFF_KVB, 128, 1280, 0);
      wg_fence();
      #pragma unroll
      for (int s = 0; s < 5; s++) wg_rs88_tb(oa, &qa[4 * s], desc2((uint32_t)db + ((s == 4 && (c & 1)) ? 0 : (s + (c & 1)) * 16), db >> 32), s != 0);
      wg_commit();
      wg_wait<0>();
      pin<44>(oa);
      if (tid == 0) TS(13);
      float rc[4], rd[2][4];
      #pragma unroll
      for (int e = 0; e < 4; e++) asm("rcp.approx.ftz.f32 %0, %1;" : "=f"(rc[e]) : "f"(oa[40 + e] + 1e-6f));
      #pragma unroll
      for (int h = 0; h < 4; h++) {
        rd[0][h] = __shfl_sync(0xffffffff, rc[h & 1], (lane & 28) | (h >> 1));
        rd[1][h] = __shfl_sync(0xffffffff, rc[2 + (h & 1)], (lane & 28) | (h >> 1));
      }
      #pragma unroll
      for (int j = 0; j < 10; j++) {
        #pragma unroll
        for (int h = 0; h < 2; h++) {
          float f;
          if (j == 2) f = tq < 2 ? rd[h][0] : rd[h][1];
          else if (j == 7) f = tq < 2 ? rd[h][2] : rd[h][3];
          else f = rd[h][(8 * j) / 20];
          qa[2 * j + h] = pack2(oa[4 * j + 2 * h] * f, oa[4 * j + 2 * h + 1] * f);
        }
      }
      const uint32_t m0 = (lane & 7) == ((2 * w4) & 7), m1 = (lane & 7) == 2 * w4 + 1;
      const uint32_t oa_ = sb + OFF_EXTRA + (lane >> 4) * 2048 + (warp * 16 + (lane & 15)) * 16;
      bar_sync(1, 256);
#define TAG(v, m) (((v) & ~(m)) | (epoch & (m)))
      #pragma unroll
      for (int s = 0; s < 5; s++) stsm4(oa_ + s * 4096, TAG(qa[4 * s], m0), TAG(qa[4 * s + 1], m1), TAG(qa[4 * s + 2], m0), TAG(qa[4 * s + 3], m1));
    }
    fence_async();
    mbar_arrive(BAR(BR_OSTG));
    if (tid == 0) TS(8);
    float oc[40]; zero<40>(oc);
    {
      constexpr uint64_t dw0 = mkdesc(SB0, OFF_WOR, 1024, 1), da0 = mkdesc(SB0, 2048, 128, 0);
      const uint32_t ck = sb + tid * 32 + ((lane >> 2) << 2), ck2 = ck + (wg ? 0 : 16384);
      uint32_t bad = 0;
      auto tile = [&](int i, uint32_t so) {
        const uint32_t al = (uint32_t)da0 + wg * 64 + (so >> 4), wl = (uint32_t)dw0 + i * 640 - (i >> 1) * (1278 << 16);
        wg_fence();
        #pragma unroll
        for (int s = 0; s < 5; s++) wg_ss80_tb(oc, desc2(al + s * 256, da0 >> 32), desc2(wl + s * 128, dw0 >> 32), (i | s) != 0);
        wg_commit();
        bad |= (lds32(ck + so) ^ epoch) | (lds32(ck + so + 8192) ^ epoch) | (lds32(ck2 + so) ^ epoch);
      };
      mbar_wait(BAR(BR_WO), 0);
      mbar_wait(BAR(BR_OSTG), 0);
      tile(0, SLOT(0));
      mbar_wait(BAR(BR_WO + 1), 0);
      #pragma unroll 1
      for (int i = 1; i < 8; i++) {
        if (i == 1) { wg_wait<0>(); if (lane == 0) mbar_arrive(BAR(BR_OEMPTY)); }
        mbar_wait(BAR(BR_OFULL) + 8 * i, 0);
        if (i == 1 && tid == 0) TS(9);
        tile(i, SLOT(i));
        wg_wait<1>();
        if (lane == 0 && i > 1) mbar_arrive(BAR(BR_OEMPTY - 1) + 8 * i);
      }
      #pragma unroll 1
      for (int n = 0; n < 56; n++) {
        const int i = n & 7;
        if (i == 0) {
          uint32_t any;
          asm volatile("{\n.reg .pred p;\nsetp.ne.u32 p, %1, 0;\nbarrier.red.or.pred p, 1, 256, p;\nselp.u32 %0, 1, 0, p;\n}" : "=r"(any) : "r"(bad & 1u) : "memory");
          if (!any) break;
          bad = 0;
          FIXCNT
        }
        wg_wait<0>();
        bar_sync(1, 256);
        if (tid == 0) { mbar_expect_tx(BAR(BR_RETRY), 20480); bulk_ld(sb + SLOT(0), &g_o[(r * 8 + CHUNK(i)) * 1280], 20480, BAR(BR_RETRY)); }
        mbar_wait(BAR(BR_RETRY), n & 1);
        tile(i, SLOT(0));
      }
      wg_wait<0>();
      pin<40>(oc);
    }
    if (tid == 0) TS(10);
    {
      const int row = w4 * 16 + (lane & 15);
      const uint32_t ob = sb + SLOT(4) + wg * 10240;
      #pragma unroll
      for (int j = 0; j < 8; j += 2)
        stsm4(ob + row * 128 + (((j + (lane >> 4)) ^ (row & 7)) << 4), pack2(oc[4 * j], oc[4 * j + 1]), pack2(oc[4 * j + 2], oc[4 * j + 3]),
              pack2(oc[4 * j + 4], oc[4 * j + 5]), pack2(oc[4 * j + 6], oc[4 * j + 7]));
      stsm4(ob + 8192 + row * 32 + (lane >> 4) * 16, pack2(oc[32], oc[33]), pack2(oc[34], oc[35]), pack2(oc[36], oc[37]), pack2(oc[38], oc[39]));
      fence_async();
      bar_sync(2 + wg, 128);
      if (w4 == 0 && elect_one()) {
        tma2d_st(&prm.m[M_O64], ob, 640 + c * 64, r * 128 + wg * 64);
        tma2d_st(&prm.m[M_O16], ob + 8192, 1152 + c * 16, r * 128 + wg * 64);
        bulk_commit(); bulk_wait0_read();
        if (wg == 0) { TS(11); DUMP(0, 20); }
      }
    }
    }
  } else {
    if (EN_SSM) {
    const int tid = rtid(), lane = tid & 31, g = lane >> 2, tq = lane & 3, t7 = tid & 127;
    if (t7 == 0) TS(41);
    mbar_wait(BAR(BR_U), 0);
    mbar_wait(BAR(BR_KGEN), 0);
    bar_sync(4, 128);
    if (t7 == 0) TS(43);
    {
      #pragma unroll 1
      for (int q6 = w4; q6 < 30; q6 += 4) {
        {
          const int k = q6 / 6, kap = (q6 - 6 * k) * 32 + lane;
          const uint32_t blk = sb + OFF_BLK + k * BLK;
          float P[33];
          P[0] = 0.f;
          #pragma unroll
          for (int q = 0; q < 4; q++) {
            const int ch = kap - 3 + q;
            uint32_t v[4];
            lds128(v, blk + (uint32_t)((ch * 16) ^ ((ch * 2) & 0x70)));
            #pragma unroll
            for (int e = 0; e < 4; e++) {
              P[q * 8 + 2 * e + 1] = (q == 0 && e < 2) ? 0.f : P[q * 8 + 2 * e] + bf_lo(v[e]);
              P[q * 8 + 2 * e + 2] = (q == 0 && e < 2) ? 0.f : P[q * 8 + 2 * e + 1] + bf_hi(v[e]);
            }
          }
#define WIN(lo, hi, e) (P[25 + (e) - (lo)] - P[24 + (e) - (hi)])
#define WIN8(lo, hi) pack2(WIN(lo, hi, 0), WIN(lo, hi, 1)), pack2(WIN(lo, hi, 2), WIN(lo, hi, 3)), pack2(WIN(lo, hi, 4), WIN(lo, hi, 5)), pack2(WIN(lo, hi, 6), WIN(lo, hi, 7))
          const uint32_t o2 = blk + B_D + (kap & 1) * 1552 + (kap >> 1) * 16;
          sts128(o2, WIN8(3, 5));
          sts128(o2 + B_D5, WIN8(6, 10));
          if (kap < 128) {
            const uint32_t o = blk + B_D + (kap & 1) * 1024 + (kap >> 1) * 16;
            sts128(o + B_D7, WIN8(5, 11));
            sts128(o + B_D9, WIN8(12, 20));
          }
        }
      }
      if (t7 < 10) sts128(sb + OFF_BLK + (t7 >> 1) * BLK + B_D + (t7 & 1) * B_D5 + 1536, 0, 0, 0, 0);
    }
    bar_sync(4, 128);
    if (t7 == 0) TS(44);
    if (EN_ATT) mbar_wait(BAR(BR_GEMM), 0);
    if (t7 == 0) TS(42);
    #pragma unroll 1
    for (int pass = 1; pass >= 0; pass--) {
      const int k = pass ? w4 : 4;
      const uint32_t blk = sb + OFF_BLK + k * BLK, tb = blk + B_TBL + (uint32_t)((g - 2 * tq) * 4);
      float acc[16][4];
      zero<64>(&acc[0][0]);
      const int kl = 16 * (lane >> 4) + 2 * (lane & 7) + ((lane >> 3) & 1);
      {
        auto ubase = [&](int sh) { const int q = kl - 2 * sh; return blk + (uint32_t)((q * 16) ^ ((q * 2) & 0x70)); };
#define LDQ(A, sh) _Pragma("unroll") for (int m = 0; m < 4; m++) load_quad(A[m], tb + (16 + 16 * (sh) + 128 * m) * 4);
#define LDB(B, ub, h) _Pragma("unroll") for (int p = 0; p < 4; p++) ldsm4(B[p], ((ub) ^ ((p & 1) * 64)) + (4 * (h) + p) * 512);
#define MLO(A, B) _Pragma("unroll") for (int m = 0; m < 4; m++) _Pragma("unroll") for (int cc = 0; cc < 8; cc++) mma16816(acc[cc + m], A[m], &B[cc >> 1][(cc & 1) * 2]);
#define MHI(A, B) _Pragma("unroll") for (int m = 0; m < 4; m++) _Pragma("unroll") for (int cc = 0; cc < 8 - m; cc++) mma16816(acc[8 + cc + m], A[m], &B[cc >> 1][(cc & 1) * 2]);
        int p_ = pass ? 0 : w4;
        const int pe = pass ? 4 : w4 + 1;
        uint32_t A[4][4], A2[4][4], Bl[4][4], Bh[4][4];
        uint32_t ub = ubase(p_ + 4);
        LDQ(A, p_ + 4) LDB(Bl, ub, 0)
        #pragma unroll 1
        for (; p_ < pe; p_++) {
          LDB(Bh, ub, 1)
          MLO(A, Bl)
          ub = ubase(p_);
          LDQ(A2, p_) LDB(Bl, ub, 0)
          MHI(A, Bh)
          LDB(Bh, ub, 1)
          load_quad(A[0], tb + (16 + 512 + 16 * (p_ & 1)) * 4); load_quad(A[1], tb + (T_S + 16 * (p_ & 1)) * 4);
          MLO(A2, Bl)
          if (p_ < 2) {
            #pragma unroll
            for (int cc = 0; cc < 8; cc++) mma16816(acc[cc + 4], A[0], &Bl[cc >> 1][(cc & 1) * 2]);
            #pragma unroll
            for (int cc = 0; cc < 4; cc++) mma16816(acc[cc + 12], A[0], &Bh[cc >> 1][(cc & 1) * 2]);
            #pragma unroll
            for (int cc = 0; cc < 8; cc++) mma16816(acc[cc + 8], A[1], &Bl[cc >> 1][(cc & 1) * 2]);
          }
          const int pn = ((p_ + 1) & 3) + 4;
          ub = ubase(pn);
          LDQ(A, pn) LDB(Bl, ub, 0)
          MHI(A2, Bh)
        }
      }
      if (t7 == 0) TS(57 + 3 * pass);
      {
        const int ih = (lane >> 3) & 1;
        const uint32_t dl = blk + B_D + (uint32_t)(((lane >> 4) * 8 + (lane & 7)) * 16);
        const uint32_t d0_ = dl + ih * 1552, d8_ = dl + (ih ? 0 : 1536), d3_ = dl + B_D7 + ih * 1024;
        auto cls2 = [&](uint32_t da, uint32_t ta) {
          uint32_t B[6][2], A[6][4];
          #pragma unroll
          for (int e = 0; e < 6; e++) { B[e][0] = lds32v(ta + (e + 4) * 32); B[e][1] = lds32v(ta + (e + 3) * 32); }
          #pragma unroll
          for (int kk = 0; kk < 6; kk++) ldsm4t(A[kk], da + kk * 256);
          #pragma unroll
          for (int e = 0; e < 6; e++)
            #pragma unroll
            for (int kk = 0; kk < 6; kk++) if (2 * kk + e + 4 < 16) mma16816(acc[2 * kk + e + 4], A[kk], B[e]);
        };
        auto cls3 = [&](uint32_t da, uint32_t ta) {
          uint32_t B[8][2], A[4][4];
          #pragma unroll
          for (int e = 0; e < 8; e++) { B[e][0] = lds32v(ta + (e + 8) * 32); B[e][1] = lds32v(ta + (e + 7) * 32); }
          #pragma unroll
          for (int kk = 0; kk < 4; kk++) ldsm4t(A[kk], da + kk * 256);
          #pragma unroll
          for (int kk = 0; kk < 4; kk++)
            #pragma unroll
            for (int e = 0; e < 8; e++) if (2 * kk + e + 8 < 16) mma16816(acc[2 * kk + e + 8], A[kk], B[e]);
        };
        #pragma unroll 1
        for (int a = pass ? 0 : w4; a < (pass ? 4 : w4 + 1); a++) cls2(((a & 2) ? d8_ : d0_) + (a & 1) * B_D5, tb + (T_F2 + 48 * a - 32) * 4);
        #pragma unroll 1
        for (int b = pass ? 0 : (w4 & 1); b < (pass ? 2 : w4 - 1); b++) cls3(d3_ + b * 2048, tb + (T_F3 + 80 * b - 64) * 4);
      }
      if (t7 == 0) TS(58 + 3 * pass);
      const uint32_t ya = blk + (uint32_t)((kl * 16) ^ ((kl * 2) & 0x70));
#define STY(p) stsm4t((ya ^ (((p) & 1) * 64)) + (p) * 512, pack2(acc[2 * (p)][0], acc[2 * (p)][1]), pack2(acc[2 * (p)][2], acc[2 * (p)][3]), \
                      pack2(acc[2 * (p) + 1][0], acc[2 * (p) + 1][1]), pack2(acc[2 * (p) + 1][2], acc[2 * (p) + 1][3]))
      if (pass == 0) {
        const uint32_t xw = blk + 4096 + w4 * 4096 + lane * 16, xr = blk + 4096 + w4 * 1024 + lane * 16;
        #pragma unroll
        for (int h = 0; h < 2; h++) {
          bar_sync(4, 128);
          #pragma unroll
          for (int i = 0; i < 8; i++)
            sts128(xw + i * 512, __float_as_uint(acc[8 * h + i][0]), __float_as_uint(acc[8 * h + i][1]), __float_as_uint(acc[8 * h + i][2]), __float_as_uint(acc[8 * h + i][3]));
          bar_sync(4, 128);
          float y[8];
          #pragma unroll
          for (int i = 0; i < 8; i++) {
            uint32_t o[4]; lds128(o, xr + (i >> 1) * 4096 + (i & 1) * 512);
            #pragma unroll
            for (int e = 0; e < 4; e++) y[4 * (i & 1) + e] = i < 2 ? __uint_as_float(o[e]) : y[4 * (i & 1) + e] + __uint_as_float(o[e]);
          }
          stsm4t((ya ^ ((w4 & 1) * 64)) + (4 * h + w4) * 512, pack2(y[0], y[1]), pack2(y[2], y[3]), pack2(y[4], y[5]), pack2(y[6], y[7]));
        }
      } else {
        __syncwarp();
        #pragma unroll
        for (int p = 0; p < 8; p++) STY(p);
      }
      if (t7 == 0 && !pass) TS(55);
      fence_async();
      mbar_arrive(BAR(BR_Y + 1) - 8 * pass);
      if (t7 == 0) TS(59 + 3 * pass);
    }
    if (t7 == 0) DUMP(40, 64);
    }
  }
  }
}

typedef CUresult (*EncFn)(CUtensorMap*, CUtensorMapDataType, cuuint32_t, void*, const cuuint64_t*, const cuuint64_t*, const cuuint32_t*,
                          const cuuint32_t*, CUtensorMapInterleave, CUtensorMapSwizzle, CUtensorMapL2promotion, CUtensorMapFloatOOBfill);
static void mkmap(EncFn enc, CUtensorMap* m, const void* base, int rank, const cuuint64_t* dims, const cuuint64_t* strides, const cuuint32_t* box, CUtensorMapSwizzle swz) {
  cuuint32_t es[5] = {1, 1, 1, 1, 1};
  enc(m, CU_TENSOR_MAP_DATA_TYPE_BFLOAT16, rank, const_cast<void*>(base), dims, strides, box, es, CU_TENSOR_MAP_INTERLEAVE_NONE, swz,
      CU_TENSOR_MAP_L2_PROMOTION_L2_128B, CU_TENSOR_MAP_FLOAT_OOB_FILL_NONE);
}

extern "C" void kernel_launch(void* const* d_in, const int* in_sizes, int n_in, void* d_out, int out_size) {
  void* fn = nullptr; cudaDriverEntryPointQueryResult qr;
  cudaGetDriverEntryPoint("cuTensorMapEncodeTiled", &fn, cudaEnableDefault, &qr);
  EncFn enc = (EncFn)fn;
  void* uy = nullptr; cudaGetSymbolAddress(&uy, g_uy);
  const cuuint64_t dx[2] = {640, 2048}, sx[1] = {1280};
  const cuuint32_t bx[2] = {64, 128}, bu[2] = {80, 128};
  const cuuint64_t dw[3] = {640, 640, 3}, sw[2] = {3840, 1280};
  const cuuint32_t br[3] = {16, 32, 3};
  const cuuint64_t dwa[4] = {64, 640, 10, 3}, swa[3] = {3840, 128, 1280}, dwb[4] = {32, 640, 20, 3}, swb[3] = {3840, 64, 1280};
  const cuuint32_t bwa[4] = {64, 32, 1, 3}, bwb[4] = {32, 32, 2, 3};
  const cuuint64_t dwo[2] = {640, 640};
  const cuuint32_t bwo[2] = {64, 80}, bo64[2] = {64, 64}, bo16[2] = {16, 64};
  const cuuint64_t dsa[2] = {2048, 1280}, ssa[1] = {4096};
  const cuuint32_t bsa[2] = {64, 80};
  const cuuint64_t dsb[2] = {64, 40960}, ssb[1] = {128};
  const cuuint32_t bsb[2] = {64, 32};
  const cuuint64_t dout[2] = {1280, 2048}, sout[1] = {2560};
  Params prm;
  mkmap(enc, &prm.m[M_X], d_in[7], 2, dx, sx, bx, CU_TENSOR_MAP_SWIZZLE_128B);
  mkmap(enc, &prm.m[M_W128], d_in[8], 4, dwa, swa, bwa, CU_TENSOR_MAP_SWIZZLE_128B);
  mkmap(enc, &prm.m[M_W64], d_in[8], 4, dwb, swb, bwb, CU_TENSOR_MAP_SWIZZLE_64B);
  mkmap(enc, &prm.m[M_WR], d_in[8], 3, dw, sw, br, CU_TENSOR_MAP_SWIZZLE_32B);
  mkmap(enc, &prm.m[M_U], d_in[0], 2, dx, sx, bu, CU_TENSOR_MAP_SWIZZLE_NONE);
  mkmap(enc, &prm.m[M_WO], d_in[9], 2, dwo, sx, bwo, CU_TENSOR_MAP_SWIZZLE_128B);
  mkmap(enc, &prm.m[M_O64], d_out, 2, dout, sout, bo64, CU_TENSOR_MAP_SWIZZLE_128B);
  mkmap(enc, &prm.m[M_O16], d_out, 2, dout, sout, bo16, CU_TENSOR_MAP_SWIZZLE_NONE);
  mkmap(enc, &prm.m[M_SA], uy, 2, dsa, ssa, bsa, CU_TENSOR_MAP_SWIZZLE_128B);
  mkmap(enc, &prm.m[M_SB], uy, 2, dsb, ssb, bsb, CU_TENSOR_MAP_SWIZZLE_128B);
  mkmap(enc, &prm.m[M_OUT], d_out, 2, dout, sout, bu, CU_TENSOR_MAP_SWIZZLE_NONE);
  prm.u = (const __nv_bfloat16*)d_in[0]; prm.wo = (const __nv_bfloat16*)d_in[9];
  for (int i = 0; i < 4; i++) prm.par[i] = (const __nv_bfloat16*)d_in[1 + i];
  prm.logdt = (const __nv_bfloat16*)d_in[5]; prm.dskip = (const __nv_bfloat16*)d_in[6];
  cudaFuncSetAttribute(fused_kernel, cudaFuncAttributeMaxDynamicSharedMemorySize, SMEM_BYTES);
  cudaLaunchConfig_t cfg = {};
  cfg.gridDim = dim3(128); cfg.blockDim = dim3(512); cfg.dynamicSmemBytes = SMEM_BYTES; cfg.stream = cudaStreamPerThread;
  cudaLaunchAttribute at[1];
  at[0].id = cudaLaunchAttributeClusterDimension; at[0].val.clusterDim.x = 2; at[0].val.clusterDim.y = 1; at[0].val.clusterDim.z = 1;
  cfg.attrs = at; cfg.numAttrs = 1;
  cudaLaunchKernelEx(&cfg, fused_kernel, prm);
}
```

```cpp
#include <cuda_runtime.h>
#include <cuda_bf16.h>
#include <cuda_fp16.h>
#include <cuda.h>
#include <stdint.h>

#define U_AFTER 1
#define KST 2
#define EN_ATT 1
#define EN_SSM 1

__device__ __align__(1024) __nv_bfloat16 g_uy[2 * 640 * 2048];
__device__ __align__(128) uint4 g_kvp[8 * 16 * 240];
__device__ __align__(128) uint4 g_o[128 * 1280];
__device__ __align__(128) unsigned g_flag[4 * 128 * 32];
__device__ unsigned g_epoch[128];
#define TS(i) do {} while (0)
#define DUMP(lo, hi) do {} while (0)
#define FIXCNT

constexpr uint32_t SB0 = 1024;
constexpr uint32_t W_SLOT = 15360, OFF_X = 76800;
constexpr uint32_t OFF_WOR = 81920, OFF_KVP = 10240, OFF_KVS = 71680, OFF_PK = 10240, OFF_V = 30720, OFF_EXTRA = 102400, OFF_KVB = OFF_EXTRA;
constexpr uint32_t OFF_BAR = 125952, OFF_BLK = 128000, BLK = 20480;
constexpr uint32_t B_D = 4096, B_D5 = 3088, B_D7 = 6176, B_D9 = 8224, B_TBL = 14400;
constexpr int T_S = 576, T_F2 = 624, T_F3 = 816;
constexpr uint32_t SMEM_BYTES = OFF_BLK + 5 * BLK;
enum { BR_FULL = 0, BR_WO = 5, BR_PUB = 7, BR_KVP = 8, BR_U = 9, BR_SUM = 10, BR_GEMM = 11, BR_UIN = 12, BR_YIN = 13, BR_EPOCH = 14,
       BR_FREE = 15, BR_RETRY = 17, BR_OFULL = 18, BR_KS = 26, BR_EMPTY = 31, BR_OEMPTY = 36, BR_Y = 43, BR_OSTG = 45, BR_KF = 46,
       BR_DRDY = 47, BR_COUNT = 48 };
constexpr uint32_t OFF_EPOCH = OFF_BAR + 8 * BR_COUNT;
enum { M_X, M_W128, M_W64, M_WR, M_U, M_WO, M_O64, M_O16, M_SA, M_SB, M_OUT, M_COUNT };

__device__ __forceinline__ long long clk64() { long long t; asm volatile("mov.u64 %0, %%clock64;" : "=l"(t) :: "memory"); return t; }
__device__ __forceinline__ uint32_t smem_u32(const void* p) { return (uint32_t)__cvta_generic_to_shared(p); }
__host__ __device__ constexpr uint64_t mkdesc(uint32_t addr, uint32_t lbo, uint32_t sbo, uint32_t swz) {
  return (uint64_t)((addr & 0x3FFFF) >> 4) | ((uint64_t)(lbo >> 4) << 16) | ((uint64_t)(sbo >> 4) << 32) | ((uint64_t)swz << 62);
}
__device__ __forceinline__ uint64_t desc2(uint32_t lo, uint32_t hi) { uint64_t d; asm("mov.b64 %0, {%1, %2};" : "=l"(d) : "r"(lo), "r"(hi)); return d; }
__device__ __forceinline__ void mbar_init(uint32_t bar, uint32_t cnt) { asm volatile("mbarrier.init.shared::cta.b64 [%0], %1;" :: "r"(bar), "r"(cnt) : "memory"); }
__device__ __forceinline__ void mbar_expect_tx(uint32_t bar, uint32_t bytes) { asm volatile("mbarrier.arrive.expect_tx.shared::cta.b64 _, [%0], %1;" :: "r"(bar), "r"(bytes) : "memory"); }
__device__ __forceinline__ void mbar_arrive(uint32_t bar) { asm volatile("mbarrier.arrive.shared::cta.b64 _, [%0];" :: "r"(bar) : "memory"); }
__device__ __forceinline__ void mbar_wait(uint32_t bar, uint32_t parity) {
  asm volatile("{\n.reg .pred p;\n.reg .u32 c;\nmov.u32 c, 0;\n"
    "WL:\nmbarrier.try_wait.parity.shared::cta.b64 p, [%0], %1;\n@p bra WD;\n"
    "add.u32 c, c, 1;\nsetp.lt.u32 p, c, 200000;\n@p bra WL;\nWD:\n}" :: "r"(bar), "r"(parity) : "memory");
}
__device__ __forceinline__ void poll_all(const unsigned* p, unsigned val) {
  asm volatile("{\n.reg .pred p;\n.reg .u32 c, v;\nmov.u32 c, 0;\n"
    "PL:\nld.relaxed.gpu.global.u32 v, [%0];\nsetp.eq.u32 p, v, %1;\nvote.sync.all.pred p, p, 0xffffffff;\n@p bra PD;\n"
    "add.u32 c, c, 1;\nsetp.lt.u32 p, c, 100000;\n@p bra PL;\nPD:\n}" :: "l"(p), "r"(val) : "memory");
}
__device__ __forceinline__ void poll_all_acq(const unsigned* p, unsigned val) {
  asm volatile("{\n.reg .pred p;\n.reg .u32 c, v;\nmov.u32 c, 0;\n"
    "PL:\nld.acquire.gpu.global.u32 v, [%0];\nsetp.eq.u32 p, v, %1;\nvote.sync.all.pred p, p, 0xffffffff;\n@p bra PD;\n"
    "add.u32 c, c, 1;\nsetp.lt.u32 p, c, 100000;\n@p bra PL;\nPD:\n}" :: "l"(p), "r"(val) : "memory");
}
__device__ __forceinline__ unsigned poll_bit(const unsigned* p, unsigned val, unsigned mask) {
  unsigned bal;
  asm volatile("{\n.reg .pred p;\n.reg .u32 c, v;\nmov.u32 c, 0;\n"
    "PL:\nld.relaxed.gpu.global.u32 v, [%1];\nsetp.eq.u32 p, v, %2;\nvote.sync.ballot.b32 %0, p, 0xffffffff;\n"
    "and.b32 v, %0, %3;\nsetp.ne.u32 p, v, 0;\n@p bra PD;\n"
    "add.u32 c, c, 1;\nsetp.lt.u32 p, c, 100000;\n@p bra PL;\nPD:\n}" : "=&r"(bal) : "l"(p), "r"(val), "r"(mask) : "memory");
  return bal;
}
__device__ __forceinline__ void fix128_w0(uint32_t* v, const void* p, uint32_t tag, uint32_t mask) {
  asm volatile("{\n.reg .pred p;\n.reg .u32 c, x;\n.reg .b128 t;\n.reg .b64 lo, hi;\nmov.u32 c, 0;\n"
    "FL:\nxor.b32 x, %0, %5;\nand.b32 x, x, %6;\nsetp.eq.u32 p, x, 0;\n@p bra FD;\n"
    "ld.relaxed.gpu.global.b128 t, [%4];\nmov.b128 {lo, hi}, t;\nmov.b64 {%0, %1}, lo;\nmov.b64 {%2, %3}, hi;\n"
    "add.u32 c, c, 1;\nsetp.lt.u32 p, c, 100000;\n@p bra FL;\nFD:\n}"
    : "+r"(v[0]), "+r"(v[1]), "+r"(v[2]), "+r"(v[3]) : "l"(p), "r"(tag), "r"(mask) : "memory");
}
__device__ __forceinline__ void fix128_w3(uint32_t* v, const void* p, uint32_t tag, uint32_t mask) {
  asm volatile("{\n.reg .pred p;\n.reg .u32 c, x;\n.reg .b128 t;\n.reg .b64 lo, hi;\nmov.u32 c, 0;\n"
    "FL:\nxor.b32 x, %3, %5;\nand.b32 x, x, %6;\nsetp.eq.u32 p, x, 0;\n@p bra FD;\n"
    "ld.relaxed.gpu.global.b128 t, [%4];\nmov.b128 {lo, hi}, t;\nmov.b64 {%0, %1}, lo;\nmov.b64 {%2, %3}, hi;\n"
    "add.u32 c, c, 1;\nsetp.lt.u32 p, c, 100000;\n@p bra FL;\nFD:\n}"
    : "+r"(v[0]), "+r"(v[1]), "+r"(v[2]), "+r"(v[3]) : "l"(p), "r"(tag), "r"(mask) : "memory");
}
__device__ __forceinline__ void fence_acq() { asm volatile("fence.acq_rel.gpu;" ::: "memory"); }
__device__ __forceinline__ bool elect_one() {
  uint32_t p; asm volatile("{\n.reg .pred P;\nelect.sync _|P, 0xffffffff;\nselp.u32 %0, 1, 0, P;\n}" : "=r"(p)); return p;
}
__device__ __forceinline__ void bar_sync(int id, int n) { asm volatile("bar.sync %0, %1;" :: "r"(id), "r"(n) : "memory"); }
__device__ __forceinline__ void fence_async() { asm volatile("fence.proxy.async.shared::cta;" ::: "memory"); }
__device__ __forceinline__ void fence_async_g() { asm volatile("fence.proxy.async.global;" ::: "memory"); }
__device__ __forceinline__ void tma2d(uint32_t dst, const CUtensorMap* m, uint32_t bar, int c0, int c1) {
  asm volatile("cp.async.bulk.tensor.2d.shared::cluster.global.mbarrier::complete_tx::bytes [%0], [%1, {%3, %4}], [%2];"
    :: "r"(dst), "l"(m), "r"(bar), "r"(c0), "r"(c1) : "memory");
}
__device__ __forceinline__ void tma3d(uint32_t dst, const CUtensorMap* m, uint32_t bar, int c0, int c1, int c2) {
  asm volatile("cp.async.bulk.tensor.3d.shared::cluster.global.mbarrier::complete_tx::bytes [%0], [%1, {%3, %4, %5}], [%2];"
    :: "r"(dst), "l"(m), "r"(bar), "r"(c0), "r"(c1), "r"(c2) : "memory");
}
__device__ __forceinline__ void tma4d(uint32_t dst, const CUtensorMap* m, uint32_t bar, int c0, int c1, int c2, int c3) {
  asm volatile("cp.async.bulk.tensor.4d.shared::cluster.global.mbarrier::complete_tx::bytes [%0], [%1, {%3, %4, %5, %6}], [%2];"
    :: "r"(dst), "l"(m), "r"(bar), "r"(c0), "r"(c1), "r"(c2), "r"(c3) : "memory");
}
__device__ __forceinline__ void tma2d_st(const CUtensorMap* m, uint32_t src, int c0, int c1) {
  asm volatile("cp.async.bulk.tensor.2d.global.shared::cta.bulk_group [%0, {%2, %3}], [%1];"
    :: "l"(m), "r"(src), "r"(c0), "r"(c1) : "memory");
}
__device__ __forceinline__ void bulk_ld(uint32_t dst, const void* src, uint32_t bytes, uint32_t bar) {
  asm volatile("cp.async.bulk.shared::cluster.global.mbarrier::complete_tx::bytes [%0], [%1], %2, [%3];"
    :: "r"(dst), "l"(src), "r"(bytes), "r"(bar) : "memory");
}
__device__ __forceinline__ void bulk_st(void* dst, uint32_t src, uint32_t bytes) {
  asm volatile("cp.async.bulk.global.shared::cta.bulk_group [%0], [%1], %2;" :: "l"(dst), "r"(src), "r"(bytes) : "memory");
}
__device__ __forceinline__ void bulk_commit() { asm volatile("cp.async.bulk.commit_group;" ::: "memory"); }
__device__ __forceinline__ void bulk_wait0() { asm volatile("cp.async.bulk.wait_group 0;" ::: "memory"); }
__device__ __forceinline__ void bulk_wait0_read() { asm volatile("cp.async.bulk.wait_group.read 0;" ::: "memory"); }
__device__ __forceinline__ unsigned ld_rlx(const unsigned* p) { unsigned v; asm volatile("ld.relaxed.gpu.global.u32 %0, [%1];" : "=r"(v) : "l"(p) : "memory"); return v; }
__device__ __forceinline__ unsigned ld_acq(const unsigned* p) { unsigned v; asm volatile("ld.acquire.gpu.global.u32 %0, [%1];" : "=r"(v) : "l"(p) : "memory"); return v; }
__device__ __forceinline__ void st_rlx(unsigned* p, unsigned v) { asm volatile("st.relaxed.gpu.global.u32 [%0], %1;" :: "l"(p), "r"(v) : "memory"); }
__device__ __forceinline__ void st_rel(unsigned* p, unsigned v) { asm volatile("st.release.gpu.global.u32 [%0], %1;" :: "l"(p), "r"(v) : "memory"); }
__device__ __forceinline__ void ld128_rlx(uint32_t* v, const void* p) {
  asm volatile("{\n.reg .b128 t;\n.reg .b64 lo, hi;\nld.relaxed.gpu.global.b128 t, [%4];\nmov.b128 {lo, hi}, t;\n"
    "mov.b64 {%0, %1}, lo;\nmov.b64 {%2, %3}, hi;\n}" : "=r"(v[0]), "=r"(v[1]), "=r"(v[2]), "=r"(v[3]) : "l"(p) : "memory");
}
__device__ __forceinline__ void st128_rlx(void* p, const uint32_t* v) {
  asm volatile("{\n.reg .b128 t;\n.reg .b64 lo, hi;\nmov.b64 lo, {%1, %2};\nmov.b64 hi, {%3, %4};\nmov.b128 t, {lo, hi};\n"
    "st.relaxed.gpu.global.b128 [%0], t;\n}" :: "l"(p), "r"(v[0]), "r"(v[1]), "r"(v[2]), "r"(v[3]) : "memory");
}
__device__ __forceinline__ uint32_t lds32(uint32_t a) { uint32_t v; asm volatile("ld.shared.u32 %0, [%1];" : "=r"(v) : "r"(a) : "memory"); return v; }
__device__ __forceinline__ uint32_t lds32v(uint32_t a) { uint32_t v; asm volatile("ld.volatile.shared.u32 %0, [%1];" : "=r"(v) : "r"(a) : "memory"); return v; }
__device__ __forceinline__ uint32_t cpa(uint32_t a, uint32_t one) { uint32_t v; asm volatile("mul.lo.u32 %0, %1, %2;" : "=r"(v) : "r"(a), "r"(one)); return v; }
__device__ __forceinline__ uint32_t cpb(uint32_t a, uint32_t zero) { uint32_t v; asm volatile("or.b32 %0, %1, %2;" : "=r"(v) : "r"(a), "r"(zero)); return v; }
__device__ __forceinline__ uint32_t lds16(uint32_t a) { uint16_t v; asm volatile("ld.shared.u16 %0, [%1];" : "=h"(v) : "r"(a) : "memory"); return v; }
__device__ __forceinline__ float ldsf(uint32_t a) { float v; asm volatile("ld.shared.f32 %0, [%1];" : "=f"(v) : "r"(a) : "memory"); return v; }
__device__ __forceinline__ void lds128(uint32_t* v, uint32_t a) { asm volatile("ld.shared.v4.u32 {%0,%1,%2,%3}, [%4];" : "=r"(v[0]), "=r"(v[1]), "=r"(v[2]), "=r"(v[3]) : "r"(a) : "memory"); }
__device__ __forceinline__ void sts32(uint32_t a, uint32_t v) { asm volatile("st.shared.u32 [%0], %1;" :: "r"(a), "r"(v) : "memory"); }
__device__ __forceinline__ void sts16(uint32_t a, uint32_t v) { asm volatile("st.shared.u16 [%0], %1;" :: "r"(a), "h"((uint16_t)v) : "memory"); }
__device__ __forceinline__ void sts64f(uint32_t a, float x, float y) { asm volatile("st.shared.v2.f32 [%0], {%1,%2};" :: "r"(a), "f"(x), "f"(y) : "memory"); }
__device__ __forceinline__ void sts128(uint32_t a, uint32_t x, uint32_t y, uint32_t z, uint32_t w) { asm volatile("st.shared.v4.u32 [%0], {%1,%2,%3,%4};" :: "r"(a), "r"(x), "r"(y), "r"(z), "r"(w) : "memory"); }
__device__ __forceinline__ void stsm4(uint32_t a, uint32_t r0, uint32_t r1, uint32_t r2, uint32_t r3) {
  asm volatile("stmatrix.sync.aligned.m8n8.x4.shared.b16 [%0], {%1,%2,%3,%4};" :: "r"(a), "r"(r0), "r"(r1), "r"(r2), "r"(r3) : "memory");
}
__device__ __forceinline__ void stsm4t(uint32_t a, uint32_t r0, uint32_t r1, uint32_t r2, uint32_t r3) {
  asm volatile("stmatrix.sync.aligned.m8n8.x4.trans.shared.b16 [%0], {%1,%2,%3,%4};" :: "r"(a), "r"(r0), "r"(r1), "r"(r2), "r"(r3) : "memory");
}
__device__ __forceinline__ void ldsm4t(uint32_t* r, uint32_t a) {
  asm volatile("ldmatrix.sync.aligned.m8n8.x4.trans.shared.b16 {%0,%1,%2,%3}, [%4];" : "=r"(r[0]), "=r"(r[1]), "=r"(r[2]), "=r"(r[3]) : "r"(a) : "memory");
}
__device__ __forceinline__ void ldsm4(uint32_t* r, uint32_t a) {
  asm volatile("ldmatrix.sync.aligned.m8n8.x4.shared.b16 {%0,%1,%2,%3}, [%4];" : "=r"(r[0]), "=r"(r[1]), "=r"(r[2]), "=r"(r[3]) : "r"(a) : "memory");
}
__device__ __forceinline__ void mma16816(float* d, const uint32_t* a, const uint32_t* b) {
  asm volatile("mma.sync.aligned.m16n8k16.row.col.f32.bf16.bf16.f32 {%0,%1,%2,%3}, {%4,%5,%6,%7}, {%8,%9}, {%0,%1,%2,%3};"
    : "+f"(d[0]), "+f"(d[1]), "+f"(d[2]), "+f"(d[3]) : "r"(a[0]), "r"(a[1]), "r"(a[2]), "r"(a[3]), "r"(b[0]), "r"(b[1]));
}
__device__ __forceinline__ uint32_t pack2(float lo, float hi) { uint32_t r; asm("cvt.rn.bf16x2.f32 %0, %1, %2;" : "=r"(r) : "f"(hi), "f"(lo)); return r; }
__device__ __forceinline__ uint32_t packh(float lo, float hi) { uint32_t r; asm("cvt.rn.f16x2.f32 %0, %1, %2;" : "=r"(r) : "f"(hi), "f"(lo)); return r; }
__device__ __forceinline__ uint32_t hcmul(uint32_t x, uint32_t zp, uint32_t zq) {
  const __half2 xx = *reinterpret_cast<__half2*>(&x);
  const __half2 r = __hfma2(__high2half2(xx), *reinterpret_cast<__half2*>(&zq), __hmul2(__low2half2(xx), *reinterpret_cast<__half2*>(&zp)));
  return *reinterpret_cast<const uint32_t*>(&r);
}
__device__ __forceinline__ void hcm2(uint32_t xr, uint32_t xi, uint32_t z, uint32_t& pr, uint32_t& pi) {
  const __half2 a = *reinterpret_cast<__half2*>(&xr), b = *reinterpret_cast<__half2*>(&xi), zz = *reinterpret_cast<__half2*>(&z);
  const __half2 re = __hfma2(__hneg2(b), __high2half2(zz), __hmul2(a, __low2half2(zz)));
  const __half2 im = __hfma2(a, __high2half2(zz), __hmul2(b, __low2half2(zz)));
  pr = *reinterpret_cast<const uint32_t*>(&re); pi = *reinterpret_cast<const uint32_t*>(&im);
}
__device__ __forceinline__ void sts64(uint32_t a, uint32_t x, uint32_t y) { asm volatile("st.shared.v2.u32 [%0], {%1,%2};" :: "r"(a), "r"(x), "r"(y) : "memory"); }
__device__ __forceinline__ void lds64(uint32_t* v, uint32_t a) { asm volatile("ld.shared.v2.u32 {%0,%1}, [%2];" : "=r"(v[0]), "=r"(v[1]) : "r"(a) : "memory"); }
__device__ __forceinline__ float bf_lo(uint32_t v) { return __uint_as_float(v << 16); }
__device__ __forceinline__ float bf_hi(uint32_t v) { return __uint_as_float(v & 0xffff0000u); }
__device__ __forceinline__ float bf_round(float x) { return bf_lo(pack2(x, 0.f)); }
__device__ __forceinline__ float ex2(float x) { float r; asm("ex2.approx.ftz.f32 %0, %1;" : "=f"(r) : "f"(x)); return r; }
__device__ __forceinline__ float phi(float t, float l2e = 1.44269504089f) {
  float e = ex2(t * l2e) + 1e-6f;
  asm("{\n.reg .pred p;\nsetp.gt.f32 p, %1, 0f00000000;\n@p add.f32 %0, %1, 0f3F800008;\n}" : "+f"(e) : "f"(t));
  return e;
}
__device__ __forceinline__ void wg_fence() { asm volatile("wgmma.fence.sync.aligned;" ::: "memory"); }
__device__ __forceinline__ void wg_commit() { asm volatile("wgmma.commit_group.sync.aligned;" ::: "memory"); }
template <int N> __device__ __forceinline__ void wg_wait() { asm volatile("wgmma.wait_group.sync.aligned %0;" :: "n"(N) : "memory"); }
template <int N> __device__ __forceinline__ void pin(float* a) {
  #pragma unroll
  for (int i = 0; i < N; i++) asm volatile("" : "+f"(a[i]) :: "memory");
}
__device__ __forceinline__ int rtid() { int t; asm volatile("mov.u32 %0, %%tid.x;" : "=r"(t)); return t; }
__device__ __forceinline__ int opaque(int v) { asm volatile("" : "+r"(v)); return v; }
template <int N> __device__ __forceinline__ void zero(float* a) {
  #pragma unroll
  for (int i = 0; i < N; i++) asm volatile("mov.b32 %0, 0;" : "=f"(a[i]));
}
template <int N> __device__ __forceinline__ void pinu(uint32_t* a) {
  #pragma unroll
  for (int i = 0; i < N; i++) asm volatile("" : "+r"(a[i]) :: "memory");
}
__device__ __forceinline__ void cexp_t(float lg2mag, float turns, float& re, float& im) {
  float m = ex2(lg2mag);
  float fr = (turns - __fadd_rn(__fadd_rn(turns, 12582912.f), -12582912.f)) * 6.283185307f;
  re = m * __cosf(fr); im = m * __sinf(fr);
}
__device__ __forceinline__ void cmul(float ar, float ai, float br, float bi, float& cr, float& ci) {
  cr = fmaf(ar, br, -ai * bi); ci = fmaf(ar, bi, ai * br);
}

__device__ __forceinline__ void wg_ss192_tb(float* d, uint64_t da, uint64_t db, int scale_d) {
  asm volatile("{\n.reg .pred p;\nsetp.ne.b32 p, %98, 0;\n"
    "wgmma.mma_async.sync.aligned.m64n192k16.f32.bf16.bf16 "
    "{%0, %1, %2, %3, %4, %5, %6, %7, %8, %9, %10, %11, %12, %13, %14, %15, %16, %17, %18, %19, %20, %21, %22, %23, %24, %25, %26, %27, %28, %29, %30, %31, %32, %33, %34, %35, %36, %37, %38, %39, %40, %41, %42, %43, %44, %45, %46, %47, %48, %49, %50, %51, %52, %53, %54, %55, %56, %57, %58, %59, %60, %61, %62, %63, %64, %65, %66, %67, %68, %69, %70, %71, %72, %73, %74, %75, %76, %77, %78, %79, %80, %81, %82, %83, %84, %85, %86, %87, %88, %89, %90, %91, %92, %93, %94, %95}, %96, %97, p, 1, 1, 0, 1;\n}\n"
    : "+f"(d[0]), "+f"(d[1]), "+f"(d[2]), "+f"(d[3]), "+f"(d[4]), "+f"(d[5]), "+f"(d[6]), "+f"(d[7]), "+f"(d[8]), "+f"(d[9]), "+f"(d[10]), "+f"(d[11]), "+f"(d[12]), "+f"(d[13]), "+f"(d[14]), "+f"(d[15]), "+f"(d[16]), "+f"(d[17]), "+f"(d[18]), "+f"(d[19]), "+f"(d[20]), "+f"(d[21]), "+f"(d[22]), "+f"(d[23]), "+f"(d[24]), "+f"(d[25]), "+f"(d[26]), "+f"(d[27]), "+f"(d[28]), "+f"(d[29]), "+f"(d[30]), "+f"(d[31]), "+f"(d[32]), "+f"(d[33]), "+f"(d[34]), "+f"(d[35]), "+f"(d[36]), "+f"(d[37]), "+f"(d[38]), "+f"(d[39]), "+f"(d[40]), "+f"(d[41]), "+f"(d[42]), "+f"(d[43]), "+f"(d[44]), "+f"(d[45]), "+f"(d[46]), "+f"(d[47]), "+f"(d[48]), "+f"(d[49]), "+f"(d[50]), "+f"(d[51]), "+f"(d[52]), "+f"(d[53]), "+f"(d[54]), "+f"(d[55]), "+f"(d[56]), "+f"(d[57]), "+f"(d[58]), "+f"(d[59]), "+f"(d[60]), "+f"(d[61]), "+f"(d[62]), "+f"(d[63]), "+f"(d[64]), "+f"(d[65]), "+f"(d[66]), "+f"(d[67]), "+f"(d[68]), "+f"(d[69]), "+f"(d[70]), "+f"(d[71]), "+f"(d[72]), "+f"(d[73]), "+f"(d[74]), "+f"(d[75]), "+f"(d[76]), "+f"(d[77]), "+f"(d[78]), "+f"(d[79]), "+f"(d[80]), "+f"(d[81]), "+f"(d[82]), "+f"(d[83]), "+f"(d[84]), "+f"(d[85]), "+f"(d[86]), "+f"(d[87]), "+f"(d[88]), "+f"(d[89]), "+f"(d[90]), "+f"(d[91]), "+f"(d[92]), "+f"(d[93]), "+f"(d[94]), "+f"(d[95])
    : "l"(da), "l"(db), "r"(scale_d));
}
__device__ __forceinline__ void wg_ss48_tb(float* d, uint64_t da, uint64_t db, int scale_d) {
  asm volatile("{\n.reg .pred p;\nsetp.ne.b32 p, %26, 0;\n"
    "wgmma.mma_async.sync.aligned.m64n48k16.f32.bf16.bf16 "
    "{%0, %1, %2, %3, %4, %5, %6, %7, %8, %9, %10, %11, %12, %13, %14, %15, %16, %17, %18, %19, %20, %21, %22, %23}, %24, %25, p, 1, 1, 0, 1;\n}\n"
    : "+f"(d[0]), "+f"(d[1]), "+f"(d[2]), "+f"(d[3]), "+f"(d[4]), "+f"(d[5]), "+f"(d[6]), "+f"(d[7]), "+f"(d[8]), "+f"(d[9]), "+f"(d[10]), "+f"(d[11]), "+f"(d[12]), "+f"(d[13]), "+f"(d[14]), "+f"(d[15]), "+f"(d[16]), "+f"(d[17]), "+f"(d[18]), "+f"(d[19]), "+f"(d[20]), "+f"(d[21]), "+f"(d[22]), "+f"(d[23])
    : "l"(da), "l"(db), "r"(scale_d));
}
__device__ __forceinline__ void wg_ss48_tt(float* d, uint64_t da, uint64_t db, int scale_d) {
  asm volatile("{\n.reg .pred p;\nsetp.ne.b32 p, %26, 0;\n"
    "wgmma.mma_async.sync.aligned.m64n48k16.f32.bf16.bf16 "
    "{%0, %1, %2, %3, %4, %5, %6, %7, %8, %9, %10, %11, %12, %13, %14, %15, %16, %17, %18, %19, %20, %21, %22, %23}, %24, %25, p, 1, 1, 1, 1;\n}\n"
    : "+f"(d[0]), "+f"(d[1]), "+f"(d[2]), "+f"(d[3]), "+f"(d[4]), "+f"(d[5]), "+f"(d[6]), "+f"(d[7]), "+f"(d[8]), "+f"(d[9]), "+f"(d[10]), "+f"(d[11]), "+f"(d[12]), "+f"(d[13]), "+f"(d[14]), "+f"(d[15]), "+f"(d[16]), "+f"(d[17]), "+f"(d[18]), "+f"(d[19]), "+f"(d[20]), "+f"(d[21]), "+f"(d[22]), "+f"(d[23])
    : "l"(da), "l"(db), "r"(scale_d));
}
__device__ __forceinline__ void wg_rs88_tb(float* d, const uint32_t* a, uint64_t db, int scale_d) {
  asm volatile("{\n.reg .pred p;\nsetp.ne.b32 p, %49, 0;\n"
    "wgmma.mma_async.sync.aligned.m64n88k16.f32.bf16.bf16 "
    "{%0, %1, %2, %3, %4, %5, %6, %7, %8, %9, %10, %11, %12, %13, %14, %15, %16, %17, %18, %19, %20, %21, %22, %23, %24, %25, %26, %27, %28, %29, %30, %31, %32, %33, %34, %35, %36, %37, %38, %39, %40, %41, %42, %43}, {%44, %45, %46, %47}, %48, p, 1, 1, 1;\n}\n"
    : "+f"(d[0]), "+f"(d[1]), "+f"(d[2]), "+f"(d[3]), "+f"(d[4]), "+f"(d[5]), "+f"(d[6]), "+f"(d[7]), "+f"(d[8]), "+f"(d[9]), "+f"(d[10]), "+f"(d[11]), "+f"(d[12]), "+f"(d[13]), "+f"(d[14]), "+f"(d[15]), "+f"(d[16]), "+f"(d[17]), "+f"(d[18]), "+f"(d[19]), "+f"(d[20]), "+f"(d[21]), "+f"(d[22]), "+f"(d[23]), "+f"(d[24]), "+f"(d[25]), "+f"(d[26]), "+f"(d[27]), "+f"(d[28]), "+f"(d[29]), "+f"(d[30]), "+f"(d[31]), "+f"(d[32]), "+f"(d[33]), "+f"(d[34]), "+f"(d[35]), "+f"(d[36]), "+f"(d[37]), "+f"(d[38]), "+f"(d[39]), "+f"(d[40]), "+f"(d[41]), "+f"(d[42]), "+f"(d[43])
    : "r"(a[0]), "r"(a[1]), "r"(a[2]), "r"(a[3]), "l"(db), "r"(scale_d));
}
__device__ __forceinline__ void wg_ss80_tb(float* d, uint64_t da, uint64_t db, int scale_d) {
  asm volatile("{\n.reg .pred p;\nsetp.ne.b32 p, %42, 0;\n"
    "wgmma.mma_async.sync.aligned.m64n80k16.f32.bf16.bf16 "
    "{%0, %1, %2, %3, %4, %5, %6, %7, %8, %9, %10, %11, %12, %13, %14, %15, %16, %17, %18, %19, %20, %21, %22, %23, %24, %25, %26, %27, %28, %29, %30, %31, %32, %33, %34, %35, %36, %37, %38, %39}, %40, %41, p, 1, 1, 0, 1;\n}\n"
    : "+f"(d[0]), "+f"(d[1]), "+f"(d[2]), "+f"(d[3]), "+f"(d[4]), "+f"(d[5]), "+f"(d[6]), "+f"(d[7]), "+f"(d[8]), "+f"(d[9]), "+f"(d[10]), "+f"(d[11]), "+f"(d[12]), "+f"(d[13]), "+f"(d[14]), "+f"(d[15]), "+f"(d[16]), "+f"(d[17]), "+f"(d[18]), "+f"(d[19]), "+f"(d[20]), "+f"(d[21]), "+f"(d[22]), "+f"(d[23]), "+f"(d[24]), "+f"(d[25]), "+f"(d[26]), "+f"(d[27]), "+f"(d[28]), "+f"(d[29]), "+f"(d[30]), "+f"(d[31]), "+f"(d[32]), "+f"(d[33]), "+f"(d[34]), "+f"(d[35]), "+f"(d[36]), "+f"(d[37]), "+f"(d[38]), "+f"(d[39])
    : "l"(da), "l"(db), "r"(scale_d));
}
__device__ __forceinline__ void wg_ss48_tt_h(float* d, uint64_t da, uint64_t db, int scale_d) {
  asm volatile("{\n.reg .pred p;\nsetp.ne.b32 p, %26, 0;\n"
    "wgmma.mma_async.sync.aligned.m64n48k16.f32.f16.f16 "
    "{%0, %1, %2, %3, %4, %5, %6, %7, %8, %9, %10, %11, %12, %13, %14, %15, %16, %17, %18, %19, %20, %21, %22, %23}, %24, %25, p, 1, 1, 1, 1;\n}\n"
    : "+f"(d[0]), "+f"(d[1]), "+f"(d[2]), "+f"(d[3]), "+f"(d[4]), "+f"(d[5]), "+f"(d[6]), "+f"(d[7]), "+f"(d[8]), "+f"(d[9]), "+f"(d[10]), "+f"(d[11]), "+f"(d[12]), "+f"(d[13]), "+f"(d[14]), "+f"(d[15]), "+f"(d[16]), "+f"(d[17]), "+f"(d[18]), "+f"(d[19]), "+f"(d[20]), "+f"(d[21]), "+f"(d[22]), "+f"(d[23])
    : "l"(da), "l"(db), "r"(scale_d));
}

struct Params {
  const __nv_bfloat16 *par[4], *logdt, *dskip, *u, *wo;
  CUtensorMap m[M_COUNT];
};

#define CHUNK(i) ((i) == 0 ? c : ((i) == 7 ? (c ^ 1) : (((c & 6) + 1 + (i)) & 7)))
#define FLAG(kind, rr, cc) (&g_flag[((kind) * 128 + (rr) * 8 + (cc)) * 32])
#define SLOT(i) ((i) == 0 || (i) == 5 ? OFF_EXTRA : OFF_BLK + ((i) == 7 ? 0 : (i) == 6 ? 4 : (i) - 1) * BLK)
__device__ __forceinline__ void load_quad(uint32_t* A, uint32_t addr) {
  A[0] = lds32v(addr); A[1] = lds32v(addr + 32); A[2] = lds32v(addr - 32); A[3] = lds32v(addr);
}

__global__ void __launch_bounds__(512, 1) fused_kernel(const __grid_constant__ Params prm) {
  extern __shared__ unsigned char smem_raw[];
  const uint32_t sb = __shfl_sync(0xffffffff, smem_u32(smem_raw), 0);
  const int tid = threadIdx.x, lane = tid & 31;
  const int warp = __shfl_sync(0xffffffff, tid >> 5, 0), wg = warp >> 2, w4 = warp & 3;
  const int cta = blockIdx.x, r = cta >> 3, c = cta & 7;
  if ((sb & 0xffffffu) != SB0) return;
#define BAR(i) (sb + OFF_BAR + 8 * (i))
  const bool sw64 = ((c + 1) & 2) != 0;

  if (wg == 3) {
    if (warp == 13 && elect_one()) {
      #pragma unroll
      for (int i = M_W128; i <= M_WR; i++) asm volatile("prefetch.tensormap [%0];" :: "l"(&prm.m[i]) : "memory");
    }
    asm volatile("setmaxnreg.dec.sync.aligned.u32 56;");
    const int tid = rtid(), lane = tid & 31;
    if (warp == 12) {
      if (elect_one()) {
        #pragma unroll
        for (int i = 0; i < 5; i++) mbar_init(BAR(BR_FULL + i), 1);
        asm volatile("fence.mbarrier_init.release.cluster;" ::: "memory");
      }
      {
        const CUtensorMap* mwp = &prm.m[sw64 ? M_W64 : M_W128];
        const int mcol = (c * 80 + (c & 1) * 16) >> (sw64 ? 5 : 6), rcol = c * 80 + ((c & 1) ? 0 : 64);
        uint32_t s = 0, ph = 1, xs = 0;
        #pragma unroll 1
        for (int kb = 0; kb < 20; kb++) {
          if (kb == 1) bar_sync(0, 512);
          if (EN_SSM && kb == 4) mbar_wait(BAR(BR_KS), 0);
          if (kb >= 5) mbar_wait(BAR(BR_EMPTY) + 8 * s, ph);
          if (EN_ATT && elect_one()) {
            const uint32_t st = sb + s * W_SLOT, fb = BAR(BR_FULL) + 8 * s;
            mbar_expect_tx(fb, (kb & 1) ? W_SLOT : W_SLOT + 16384);
            if (!(kb & 1)) tma2d(sb + OFF_X + xs, &prm.m[M_X], fb, kb * 32, r * 128);
            tma4d(st, mwp, fb, 0, kb * 32, mcol, 0);
            tma3d(st + 12288, &prm.m[M_WR], fb, rcol, kb * 32, 0);
          }
          if (kb < 4 && lane == 0) TS(24 + kb);
          if (kb >= 4 && kb < 8 && elect_one())
            asm volatile("cp.async.bulk.prefetch.L2.global [%0], 5120;" :: "l"(prm.u + cta * 10240 + (kb - 4) * 2560) : "memory");
          if (kb == 14 && elect_one()) asm volatile("cp.async.bulk.prefetch.L2.global [%0], 6400;" :: "l"(prm.wo + cta * 3200) : "memory");
          if (!EN_ATT && kb == 1) break;
          if (++s == 5) { s = 0; ph ^= 1; }
          if (kb & 1) { xs += 16384; if (xs == 49152) xs = 0; }
        }
      }
      if (EN_ATT) {
      mbar_wait(BAR(BR_EPOCH), 0);
      const unsigned epoch = lds32(sb + OFF_EPOCH);
      const unsigned* fo = FLAG(3, r, lane & 7);
      unsigned seen = __ballot_sync(0xffffffff, ld_rlx(lane < 16 ? fo : FLAG(0, lane & 15, c)) == epoch) & 0xffu;
      mbar_wait(BAR(BR_GEMM), 0);
      if (elect_one()) {
        mbar_expect_tx(BAR(BR_WO), 10240);
        tma2d(sb, &prm.m[M_WO], BAR(BR_WO), c * 64, c * 80);
        mbar_expect_tx(BAR(BR_KVP), 61440);
        mbar_expect_tx(BAR(BR_WO + 1), 7 * 10240);
      }
      {
        uint32_t ds = sb + OFF_WOR + (lane >> 3) * 128 + (((lane & 7) ^ (lane >> 3)) << 4);
        #pragma unroll 1
        for (int h = 0; h < 2; h++) {
          const int i = (lane & 6) + h;
          const char* gs = reinterpret_cast<const char*>(prm.wo) + (size_t)((lane >> 3) + CHUNK(i) * 80) * 1280 + 1024 + c * 32 + (lane & 1) * 16;
          #pragma unroll 2
          for (int q = 0; q < 20; q++) {
            asm volatile("cp.async.cg.shared.global [%0], [%1], 16;" :: "r"(ds), "l"(gs) : "memory");
            ds = (ds + 512) ^ 64; gs += 5120;
          }
        }
      }
      mbar_wait(BAR(BR_PUB), 0);
      poll_all(FLAG(0, lane & 15, c), epoch);
      if (elect_one()) { TS(23); bulk_ld(sb + OFF_KVP, &g_kvp[c * 16 * 240], 61440, BAR(BR_KVP)); }
      asm volatile("cp.async.wait_all;" ::: "memory");
      fence_async();
      mbar_arrive(BAR(BR_WO));
      mbar_wait(BAR(BR_SUM), 0);
      if (elect_one()) {
        #pragma unroll 1
        for (int i = 1; i < 8; i++) tma2d(sb + i * 10240, &prm.m[M_WO], BAR(BR_WO + 1), c * 64, CHUNK(i) * 80);
      }
      mbar_wait(BAR(BR_OSTG), 0);
      if (elect_one()) {
        bulk_st(&g_o[cta * 1280], sb + OFF_EXTRA, 20480);
        bulk_commit();
        bulk_wait0();
        st_rlx(FLAG(3, r, c), epoch);
        TS(20);
      }
      __syncwarp();
      #pragma unroll 1
      for (int i = 1; i < 8; i++) {
        const int src = CHUNK(i);
        if (!((seen >> src) & 1)) seen = poll_bit(fo, epoch, 1u << src);
        if (i == 5 || i == 7) mbar_wait(BAR(BR_OEMPTY) + 4 * (i - 5), 0);
        if (EN_SSM && (i == 1 || i == 4)) mbar_wait(BAR(BR_FREE) + 2 * (i & 4), 0);
        if (elect_one()) {
          mbar_expect_tx(BAR(BR_OFULL) + 8 * i, 20480);
          bulk_ld(sb + SLOT(i), &g_o[(r * 8 + src) * 1280], 20480, BAR(BR_OFULL) + 8 * i);
          if (i == 1) TS(21);
          if (i == 7) TS(22);
        }
        __syncwarp();
      }
      if (lane == 0) { DUMP(20, 30); }
      }
    } else {
      const int hw = warp - 13, ht = tid - 416;
      const unsigned epoch = hw == 0 ? ld_rlx(&g_epoch[cta]) + 1 : 0;
      if (hw == 2 && elect_one()) {
        #pragma unroll
        for (int i = 5; i < BR_COUNT; i++) mbar_init(BAR(i), i == BR_WO ? 33 : i < BR_EMPTY ? 1 : i < BR_OEMPTY ? 2 : i < BR_Y ? 8 : i < BR_OSTG ? 128 : i < BR_DRDY ? 256 : 96);
        asm volatile("fence.mbarrier_init.release.cluster;" ::: "memory");
      }
      bar_sync(0, 512);
      if (hw == 1 && elect_one()) {
        #pragma unroll
        for (int i = M_U; i < M_COUNT; i++) asm volatile("prefetch.tensormap [%0];" :: "l"(&prm.m[i]) : "memory");
      }
      if (ht == 0) {
        st_rlx(&g_epoch[cta], epoch);
        sts32(sb + OFF_EPOCH, epoch);
        mbar_arrive(BAR(BR_EPOCH));
      }
      if (EN_SSM) {
      const int mi = lane >> 3, rw = lane & 7, ch0 = c * 80 + r * 5;
      mbar_wait(BAR(BR_KS + U_AFTER), 0);
      #pragma unroll 1
      for (int h = 0; h < 2; h++) {
        const uint32_t ut = sb + OFF_BLK + 4 * BLK;
        if (hw == 0 && elect_one()) { mbar_expect_tx(BAR(BR_UIN), 10240); tma2d(ut, &prm.m[M_U], BAR(BR_UIN), c * 80, r * 128 + h * 64); }
        const uint32_t sa = ut + (8 * mi + rw) * 160 + hw * 16, da = ut + (hw * 8 + rw) * 128 + ((mi ^ rw) << 4);
        uint32_t v[8][4];
        mbar_wait(BAR(BR_UIN), h);
        if (ht == 0) TS(36 + h);
        #pragma unroll
        for (int q = 0; q < 8; q++) if (q < 6 || hw == 0) ldsm4t(v[q], sa + (q & 1) * 5120 + (q >> 1) * 48);
        bar_sync(5, 96);
        #pragma unroll
        for (int q = 0; q < 8; q++) if (q < 6 || hw == 0) stsm4((da ^ ((q & 1) * 64)) + (q >> 1) * 3072, v[q][0], v[q][1], v[q][2], v[q][3]);
        fence_async();
        bar_sync(5, 96);
        if (hw == 0 && elect_one()) { tma2d_st(&prm.m[M_SA], ut, r * 128 + h * 64, c * 80); bulk_commit(); bulk_wait0_read(); }
      }
      if (hw == 0) {
        if (elect_one()) { bulk_wait0(); st_rel(FLAG(1, r, c), epoch); TS(30); }
        __syncwarp();
        poll_all_acq(FLAG(1, lane & 15, c), epoch);
        mbar_wait(BAR(BR_KS + 1), 0);
        if (elect_one()) {
          fence_async_g();
          mbar_expect_tx(BAR(BR_U), 20480);
          #pragma unroll 1
          for (int q = 0; q < 5; q++) tma2d(sb + OFF_BLK + q * BLK, &prm.m[M_SB], BAR(BR_U), 0, (ch0 + q) * 32);
          TS(31);
        }
        __syncwarp();
      }
      mbar_wait(BAR(BR_U), 0);
      mbar_wait(BAR(BR_KS + 4), 0);
      if (ht == 0) TS(38);
      #pragma unroll 1
      for (int q6 = hw; q6 < 30; q6 += 3) {
        {
          const int k = q6 / 6, kap = (q6 - 6 * k) * 32 + lane;
          const uint32_t blk = sb + OFF_BLK + k * BLK;
          float P[33];
          P[0] = 0.f;
          #pragma unroll
          for (int q = 0; q < 4; q++) {
            const int ch = kap - 3 + q;
            uint32_t v[4];
            lds128(v, blk + (uint32_t)((ch * 16) ^ ((ch * 2) & 0x70)));
            #pragma unroll
            for (int e = 0; e < 4; e++) {
              P[q * 8 + 2 * e + 1] = (q == 0 && e < 2) ? 0.f : P[q * 8 + 2 * e] + bf_lo(v[e]);
              P[q * 8 + 2 * e + 2] = (q == 0 && e < 2) ? 0.f : P[q * 8 + 2 * e + 1] + bf_hi(v[e]);
            }
          }
#define WIN(lo, hi, e) (P[25 + (e) - (lo)] - P[24 + (e) - (hi)])
#define WIN8(lo, hi) pack2(WIN(lo, hi, 0), WIN(lo, hi, 1)), pack2(WIN(lo, hi, 2), WIN(lo, hi, 3)), pack2(WIN(lo, hi, 4), WIN(lo, hi, 5)), pack2(WIN(lo, hi, 6), WIN(lo, hi, 7))
          const uint32_t o2 = blk + B_D + (kap & 1) * 1552 + (kap >> 1) * 16;
          sts128(o2, WIN8(3, 5));
          sts128(o2 + B_D5, WIN8(6, 10));
          if (kap < 128) {
            const uint32_t o = blk + B_D + (kap & 1) * 1024 + (kap >> 1) * 16;
            sts128(o + B_D7, WIN8(5, 11));
            sts128(o + B_D9, WIN8(12, 20));
          }
        }
      }
      if (ht < 10) sts128(sb + OFF_BLK + (ht >> 1) * BLK + B_D + (ht & 1) * B_D5 + 1536, 0, 0, 0, 0);
      mbar_arrive(BAR(BR_DRDY));
      if (ht == 0) TS(32);
      if (hw == 0) {
        #pragma unroll 1
        for (int p = 0; p < 2; p++) {
          mbar_wait(BAR(BR_Y) + 8 * p, 0);
          if (elect_one()) {
            #pragma unroll 1
            for (int k = 4 * p; k < 4 + p; k++) tma2d_st(&prm.m[M_SB], sb + OFF_BLK + k * BLK, 0, (640 + ch0 + k) * 32);
            bulk_commit(); bulk_wait0_read();
            mbar_arrive(BAR(BR_FREE) + 8 * p);
          }
          __syncwarp();
        }
        if (elect_one()) {
          mbar_expect_tx(BAR(BR_YIN), 20480);
          bulk_wait0();
          st_rel(FLAG(2, r, c), epoch);
          TS(33);
        }
        __syncwarp();
        poll_all_acq(FLAG(2, lane & 15, c), epoch);
        if (EN_ATT) mbar_wait(BAR(BR_OEMPTY + 3), 0);
        if (elect_one()) {
          fence_async_g();
          tma2d(sb + OFF_BLK + BLK, &prm.m[M_SA], BAR(BR_YIN), r * 128, 640 + c * 80);
          tma2d(sb + OFF_BLK + BLK + 10240, &prm.m[M_SA], BAR(BR_YIN), r * 128 + 64, 640 + c * 80);
          TS(34);
        }
      }
      {
        uint32_t sa = sb + OFF_BLK + BLK + (hw * 8 + rw) * 128 + ((mi ^ rw) << 4);
        uint32_t da = sb + OFF_BLK + 2 * BLK + (8 * mi + rw) * 160 + hw * 16;
        mbar_wait(BAR(BR_YIN), 0);
        #pragma unroll 1
        for (int i = hw; i < 10; i += 3) {
          uint32_t v[4][4];
          #pragma unroll
          for (int q = 0; q < 4; q++) ldsm4t(v[q], (sa ^ ((q & 1) * 64)) + (q >> 1) * 10240);
          #pragma unroll
          for (int q = 0; q < 4; q++) stsm4(da + q * 5120, v[q][0], v[q][1], v[q][2], v[q][3]);
          sa += 3072; da += 48;
        }
      }
      fence_async();
      bar_sync(5, 96);
      if (hw == 0 && elect_one()) {
        tma2d_st(&prm.m[M_OUT], sb + OFF_BLK + 2 * BLK, c * 80, r * 128);
        bulk_commit(); bulk_wait0_read();
        TS(35); DUMP(30, 40); DUMP(0, 1);
      }
      }
    }
  } else {
    const int g = lane >> 2, tq = lane & 3, t7 = tid & 127;
    uint32_t pr[3][2], pd;
    {
      const int ch = c * 80 + r * 5 + wg;
      uint32_t raw[3][4];
      #pragma unroll
      for (int e = 0; e < 4; e++) {
        const __nv_bfloat16* pp = prm.par[e] + ch * 128 + t7;
        #pragma unroll
        for (int q = 0; q < 3; q++) {
          raw[q][e] = 0;
          if (q == 0 || wg == 2) asm volatile("ld.global.nc.u16 %0, [%1];" : "=r"(raw[q][e]) : "l"(pp + q * 128));
        }
      }
      asm volatile("ld.global.nc.u16 %0, [%1];" : "=r"(pd) : "l"(((lane & 4) ? prm.dskip : prm.logdt) + ch + min(lane & 3, 2)));
      asm volatile("setmaxnreg.inc.sync.aligned.u32 152;");
      bar_sync(0, 512);
      if (EN_SSM && wg == 2) {
        #pragma unroll 1
        for (int k = 0; k < 5; k++) {
          const uint32_t z = sb + OFF_BLK + k * BLK + t7 * 16;
          sts128(z + B_TBL, 0, 0, 0, 0); sts128(z + B_TBL + 2048, 0, 0, 0, 0);
          if (t7 < 16) sts128(z - 256, 0, 0, 0, 0);
        }
      }
      const uint32_t zz = lds32(sb + OFF_EPOCH + 8) & 0u | opaque(0);
      #pragma unroll
      for (int q = 0; q < 3; q++) {
        #pragma unroll
        for (int e = 0; e < 2; e++) pr[q][e] = raw[q][2 * e] | (raw[q][2 * e + 1] << 16);
        const uint32_t m = __reduce_max_sync(0xffffffff, max(raw[q][2] & 0x7fffu, raw[q][3] & 0x7fffu) + zz);
        if (lane == 0) sts32(sb + OFF_EPOCH + 64 + (wg * 3 + q) * 16 + w4 * 4, m);
      }
      bar_sync(2 + wg, 128);
    }
    if (tid == 256) TS(40);
    if (EN_SSM) {
#define P0(w) ((w) == 1 ? OFF_X + 32768 : OFF_BLK + (w) * 3584)
#define P1(w) ((w) == 1 ? 7168 : BLK)
#define P2(w) ((w) == 1 ? OFF_BLK + 4 * BLK - OFF_X - 32768 : 2 * BLK)
      const uint32_t fa = sb + P0(wg) + (lane >> 4) * P1(wg) + (w4 & 1) * P2(wg) + ((lane >> 3) & 1) * 256 + (lane & 7) * 16;
      const uint32_t ea = fa + (w4 >> 1) * 2048, ga = fa + 4096 + (w4 >> 1) * 1536;
      constexpr uint64_t dE = mkdesc(SB0, 128, 512, 0);
      const uint32_t xa = sb + OFF_BLK + 18560 + t7 * 8, xr_ = sb + OFF_BLK + 18560 + (t7 ^ 64) * 8;
      #pragma unroll 1
      for (int it = 0; it < 5; it++) {
        const int k = it < 2 ? 1 - it : it, fs = min(k, 2);
        const uint32_t blk = sb + OFF_BLK + k * BLK;
        if (it == 0 || it >= 3) {
          const int q = it ? it - 2 : 0;
          const uint32_t pa0 = pr[0][0], pc0 = pr[0][1];
          const float dt = bf_round(expf(bf_lo(__shfl_sync(0xffffffff, pd, q))));
          #pragma unroll
          for (int e = 0; e < 2; e++) { pr[0][e] = pr[1][e]; pr[1][e] = pr[2][e]; }
          uint32_t mm[4];
          lds128(mm, sb + OFF_EPOCH + 64 + (wg * 3 + q) * 16);
          const uint32_t ex = min(max(max(max(mm[0], mm[1]), max(mm[2], mm[3])) >> 7, 1u), 253u);
          const float sc = __uint_as_float((254u - ex) << 23);
          if (t7 == 4 + q) sts64(sb + OFF_EPOCH + 16 + (wg + q) * 8, __float_as_uint(2.f * dt * __uint_as_float(ex << 23)), pd << 16);
          const float lr = -bf_round(expf(bf_lo(pa0))) * dt * 1.44269504089f;
          const float tn = bf_hi(pa0) * dt * 0.15915494309f;
          float z1r, z1i, z2r, z2i, z4r, z4i, xr[8], xi[8], gr[8], gi[8], wr[9], wi[9];
          cexp_t(lr, -tn, z1r, z1i);
          cexp_t(lr * 8.f, tn * 8.f, xr[1], xi[1]);
          cexp_t(lr * 64.f, tn * 64.f, wr[0], wi[0]);
          xr[0] = 1.f; xi[0] = 0.f;
          cmul(xr[1], xi[1], xr[1], xi[1], xr[2], xi[2]); cmul(xr[2], xi[2], xr[1], xi[1], xr[3], xi[3]);
          cmul(xr[2], xi[2], xr[2], xi[2], xr[4], xi[4]);
          #pragma unroll
          for (int b = 1; b < 4; b++) cmul(xr[4], xi[4], xr[b], xi[b], xr[4 + b], xi[4 + b]);
          cmul(wr[0], wi[0], wr[0], wi[0], wr[1], wi[1]); cmul(wr[1], wi[1], wr[0], wi[0], wr[2], wi[2]);
          cmul(wr[1], wi[1], wr[1], wi[1], wr[3], wi[3]); cmul(wr[3], wi[3], wr[3], wi[3], wr[4], wi[4]);
          cmul(wr[4], wi[4], wr[3], wi[3], wr[5], wi[5]); cmul(wr[4], wi[4], wr[4], wi[4], wr[6], wi[6]);
          cmul(wr[6], wi[6], wr[4], wi[4], wr[7], wi[7]); cmul(wr[6], wi[6], wr[6], wi[6], wr[8], wi[8]);
          uint32_t R[4], I[4], PR[4], PI[4];
          #pragma unroll
          for (int b = 0; b < 4; b++) { R[b] = packh(xr[2 * b], xr[2 * b + 1]); I[b] = packh(xi[2 * b], xi[2 * b + 1]); }
          sts128(ea, R[0], R[1], R[2], R[3]); sts128(ea + 128, I[0], I[1], I[2], I[3]);
          #pragma unroll
          for (int i = 0; i < 3; i++) {
            const uint32_t z = packh(wr[i], wi[i]);
            #pragma unroll
            for (int b = 0; b < 4; b++) hcm2(R[b], I[b], z, PR[b], PI[b]);
            sts128(ea + (i + 1) * 512, PR[0], PR[1], PR[2], PR[3]); sts128(ea + (i + 1) * 512 + 128, PI[0], PI[1], PI[2], PI[3]);
          }
          gr[0] = bf_lo(pc0) * sc; gi[0] = -bf_hi(pc0) * sc;
          cmul(z1r, z1i, z1r, z1i, z2r, z2i); cmul(z2r, z2i, z2r, z2i, z4r, z4i);
          cmul(gr[0], gi[0], z1r, z1i, gr[1], gi[1]);
          cmul(gr[0], gi[0], z2r, z2i, gr[2], gi[2]); cmul(gr[1], gi[1], z2r, z2i, gr[3], gi[3]);
          #pragma unroll
          for (int b = 0; b < 4; b++) cmul(gr[b], gi[b], z4r, z4i, gr[4 + b], gi[4 + b]);
          sts128(ga, packh(gr[0], gr[1]), packh(gr[2], gr[3]), packh(gr[4], gr[5]), packh(gr[6], gr[7]));
          sts128(ga + 128, packh(gi[0], gi[1]), packh(gi[2], gi[3]), packh(gi[4], gi[5]), packh(gi[6], gi[7]));
          {
            const uint32_t z = packh(wr[3], -wi[3]), a4r = packh(gr[0], gr[4]), a4i = packh(gi[0], gi[4]);
            hcm2(packh(gr[0], gr[2]), packh(gi[0], gi[2]), z, PR[0], PI[0]);
            hcm2(packh(gr[4], gr[6]), packh(gi[4], gi[6]), z, PR[1], PI[1]);
            hcm2(a4r, a4i, packh(wr[4], -wi[4]), PR[2], PI[2]);
            hcm2(a4r, a4i, packh(wr[5], -wi[5]), PR[3], PI[3]);
            sts128(ga + 512, PR[0], PR[1], PR[2], PR[3]); sts128(ga + 512 + 128, PI[0], PI[1], PI[2], PI[3]);
            float hr, hi_;
            cmul(gr[0], gi[0], wr[3], -wi[3], hr, hi_);
            const uint32_t cr = packh(gr[0], hr), ci = packh(gi[0], hi_);
            #pragma unroll
            for (int i = 0; i < 3; i++) hcm2(cr, ci, packh(wr[6 + i], -wi[6 + i]), PR[i], PI[i]);
            sts128(ga + 1024, PR[0], PR[1], PR[2], 0u); sts128(ga + 1024 + 128, PI[0], PI[1], PI[2], 0u);
          }
          if (t7 == 0 && k == KST) TS(48);
          fence_async();
          if (wg < 2) { mbar_arrive(BAR(BR_KF)); break; }
          bar_sync(4, 128);
          if (it == 0) mbar_wait(BAR(BR_KF), 0);
        }
        if (t7 == 0 && k == KST) TS(50);
        uint32_t fd[2];
        lds64(fd, sb + OFF_EPOCH + 16 + k * 8);
        const float fac = __uint_as_float(fd[0]), dsk = __uint_as_float(fd[1]);
        float ka[24]; zero<24>(ka);
        wg_fence();
        #pragma unroll
        for (int s = 0; s < 8; s++) {
          const uint32_t lo = (uint32_t)dE + ((P0(fs) + ((s >> 1) & 1) * P1(fs) + (s >> 2) * P2(fs)) >> 4) + (s & 1) * 16;
          wg_ss48_tt_h(ka, desc2(lo, dE >> 32), desc2(lo + 256, dE >> 32), s != 0);
        }
        wg_commit();
        wg_wait<0>();
        pin<24>(ka);
        if (t7 == 0 && k == KST) TS(51);
        float kk[6];
        {
          const bool up = w4 >= 2;
          #pragma unroll
          for (int n = 0; n < 3; n++) {
            sts64f(xa + n * BLK, up ? ka[12 + 4 * n] : ka[4 * n + 2], up ? ka[13 + 4 * n] : ka[4 * n + 3]);
            kk[2 * n] = up ? ka[14 + 4 * n] : ka[4 * n]; kk[2 * n + 1] = up ? ka[15 + 4 * n] : ka[4 * n + 1];
          }
          bar_sync(4, 128);
          if (t7 == 0) mbar_arrive(BAR(BR_KS) + 8 * it);
          #pragma unroll
          for (int n = 0; n < 3; n++) {
            uint32_t o[2]; lds64(o, xr_ + n * BLK);
            kk[2 * n] = (kk[2 * n] + __uint_as_float(o[0])) * fac; kk[2 * n + 1] = (kk[2 * n + 1] + __uint_as_float(o[1])) * fac;
          }
        }
        if (t7 == 0 && k == KST) TS(52);
        {
          const int j = (w4 & 1) * 16 + (w4 >> 1) * 8 + g;
          const uint32_t tb = blk + B_TBL;
          if (t7 == 0) kk[0] += dsk;
          const uint32_t pa_ = tb + (16 + 8 * j + 2 * tq) * 4;
          const uint32_t v = pack2(kk[1], kk[0]);
          sts32(pa_ + 4, v); sts16(pa_, v >> 16); sts16(pa_ + 10, v);
          const uint32_t u = pack2(kk[2], kk[3]), w = pack2(kk[4], kk[5]);
          if (tq < 2) {
            const uint32_t pb = tb + (16 + 256 + 8 * j + 4 * tq) * 4;
            sts16(pb, u); sts32(pb + 4, __byte_perm(u, 0, 0x1010)); sts32(pb + 8, __byte_perm(u, 0, 0x1032)); sts16(pb + 14, u >> 16);
            if (j | tq) { sts16(pb - 4, u); sts16(pb + 2, u); }
            const int i = 64 * tq + j;
            const uint32_t e0 = tb + (T_F3 + (((i - 1) & 1) ? 80 : 0) + ((i - 1) >> 1)) * 4, e1 = i ? e0 : tb + (T_F2 + 144 + 31) * 4;
            sts16(e1, w); sts16(e1 + 6, w); sts16(e0 + 64, w >> 16); sts16(e0 + 70, w >> 16);
            if (i == 0) { sts16(tb + (T_S + 3) * 4, w); sts32(tb + (T_S + 4) * 4, __byte_perm(w, 0, 0x1010)); sts16(tb + (T_S + 5) * 4 + 2, w); }
          } else {
            const int i = 32 * (tq - 2) + j;
            const uint32_t e1 = tb + (i ? T_F2 + ((2 * i - 1) & 3) * 48 + ((2 * i - 1) >> 2) : 16 + 511) * 4;
            const uint32_t e2 = tb + (T_F2 + (i & 1) * 96 + (i >> 1)) * 4;
            sts16(e1, u); sts16(e1 + 6, u); sts16(e2, u >> 16); sts16(e2 + 6, u >> 16);
            if (i == 0) {
              const uint32_t uu = __byte_perm(u, 0, 0x1010);
              sts32(tb + 528 * 4, uu); sts32(tb + 529 * 4, uu); sts32(tb + 530 * 4, uu); sts16(tb + 531 * 4 + 2, u);
              sts16(tb + (T_F3 + 80 + 63) * 4, w);
            }
          }
        }
        if (it < 2) bar_sync(4, 128);
        if (t7 == 0 && k == KST) TS(53);
      }
    }
    if (tid == 0) TS(14);
  if (wg < 2) {
    if (EN_ATT) {
    float am[96], ar[24];
    {
      const bool lead = (rtid() & 127) == 0;
      constexpr uint64_t da0 = mkdesc(SB0 + OFF_X, 16, 1024, 1), dr0 = mkdesc(SB0 + 12288, 1024, 256, 3);
      const uint64_t db0 = sw64 ? mkdesc(SB0, 2048, 512, 2) : mkdesc(SB0, 4096, 1024, 1);
      const uint32_t kst = sw64 ? 64 : 128, bh = db0 >> 32;
      uint32_t s = 0, ph = 0, xo = 0;
      #pragma unroll 1
      for (int kb = 0; kb < 20; kb++) {
        const uint32_t wo_ = s * (W_SLOT >> 4), al = (uint32_t)da0 + wg * 512 + xo, bl = (uint32_t)db0 + wo_, rl = (uint32_t)dr0 + wo_;
        mbar_wait(BAR(BR_FULL) + 8 * s, ph);
        if (kb == 0 && lead && wg == 0) TS(1);
        wg_fence();
        wg_ss192_tb(am, desc2(al, da0 >> 32), desc2(bl, bh), kb != 0);
        wg_ss48_tb(ar, desc2(al, da0 >> 32), desc2(rl, dr0 >> 32), kb != 0);
        wg_ss192_tb(am, desc2(al + 2, da0 >> 32), desc2(bl + kst, bh), 1);
        wg_ss48_tb(ar, desc2(al + 2, da0 >> 32), desc2(rl + 32, dr0 >> 32), 1);
        wg_commit();
        wg_wait<1>();
        if (lead && kb > 0 && kb < 16) mbar_arrive(BAR(BR_EMPTY) + 8 * (s == 0 ? 4 : s - 1));
        if (++s == 5) { s = 0; ph ^= 1; }
        xo += (kb & 1) ? 1020 : 4;
        if (xo == 3072) xo = 0;
      }
      wg_wait<0>();
      pin<96>(am); pin<24>(ar);
    }
    const int tid = rtid(), lane = tid & 31, tq = lane & 3;
    if (tid == 0) TS(2);
#define QV(j, e) ((j) < 8 ? am[4 * (j) + (e)] : ar[4 * ((j) - 8) + (e)])
#define KV_(j, e) ((j) < 8 ? am[32 + 4 * (j) + (e)] : ar[8 + 4 * ((j) - 8) + (e)])
#define VV(j, e) ((j) < 8 ? am[64 + 4 * (j) + (e)] : ar[16 + 4 * ((j) - 8) + (e)])
    {
      bar_sync(1, 256);
      if (tid == 0) mbar_arrive(BAR(BR_GEMM));
      const uint32_t ro = sb + (uint32_t)((warp * 16 + (lane & 15)) * 16);
      const int l0 = 2 * (c & 1) + (lane >> 4);
      const uint32_t ones = (tq == 0) ? 0x00003f80u : 0u;
#define PV(j) pack2(VV(j, 0), VV(j, 1)), pack2(VV(j, 2), VV(j, 3))
#define PK(j) pack2(phi(KV_(j, 0)), phi(KV_(j, 1))), pack2(phi(KV_(j, 2)), phi(KV_(j, 3)))
      stsm4(ro + OFF_V + (5 + 6 * (lane >> 4)) * 2048, ones, ones, ones, ones);
      #pragma unroll
      for (int j = 0; j < 10; j += 2) {
        const int l = (j == 8 && (c & 1)) ? l0 - 2 : l0 + j;
        stsm4(ro + OFF_V + (l + (l >= 5)) * 2048, PV(j), PV(j + 1));
        stsm4(ro + OFF_PK + l * 2048, PK(j), PK(j + 1));
      }
    }
    fence_async();
    bar_sync(1, 256);
    if (tid == 0) TS(3);
    mbar_wait(BAR(BR_EPOCH), 0);
    const unsigned epoch = lds32(sb + OFF_EPOCH);
    {
      float kv[24]; zero<24>(kv);
      constexpr uint64_t da = mkdesc(SB0 + OFF_PK, 128, 2048, 0), db = mkdesc(SB0 + OFF_V, 128, 2048, 0);
      wg_fence();
      #pragma unroll
      for (int s = 0; s < 8; s++) wg_ss48_tt(kv, desc2((uint32_t)da + wg * 640 + s * 16, da >> 32), desc2((uint32_t)db + wg * 768 + s * 16, db >> 32), s != 0);
      wg_commit();
      wg_wait<0>();
      pin<24>(kv);
      if (tid == 0) TS(15);
      if (w4 < 3) {
        const uint32_t wb = sb + OFF_KVS + (wg * 3 + w4) * 1536 + (lane & 15) * 96;
        #pragma unroll
        for (int j = 0; j < 6; j += 2)
          stsm4(wb + (j + (lane >> 4)) * 16, pack2(kv[4 * j], kv[4 * j + 1]), pack2(kv[4 * j + 2], kv[4 * j + 3]),
                pack2(kv[4 * j + 4], kv[4 * j + 5]), pack2(kv[4 * j + 6], kv[4 * j + 7]));
        __syncwarp();
        const int dl = w4 * 16 + (lane & 15), hl = dl >= 20;
        if (dl < 40) {
          uint4* dst = &g_kvp[(c * 16 + r) * 240 + wg * 40 + dl];
          uint32_t v[4], z[4];
          lds128(v, wb + (3 * hl + (lane >> 4)) * 16);
          lds64(z, wb + 32 + 8 * hl); z[2] = lds32(wb + 80); z[3] = epoch & 1u;
          v[3] = (v[3] & ~1u) | z[3];
          st128_rlx(dst + (lane >> 4) * 80, v);
          if (lane < 16) st128_rlx(dst + 160, z);
        }
      }
    }
    fence_async();
    bar_sync(1, 256);
    if (tid == 0) { st_rlx(FLAG(0, r, c), epoch); mbar_arrive(BAR(BR_PUB)); TS(4); }
    const int kvi = (tid >= 80) + (tid >= 160) + (tid >= 240), kd = tid - 80 * kvi;
    const int khd = kd / 20, kt0 = 5 * (khd >> 1) + 2 * (khd & 1);
    const uint32_t rb = sb + OFF_KVB + kd * 16;
    if (kvi < 3) {
      #pragma unroll 1
      for (int m = kvi; m < 7; m += 3) { const int q = kt0 + 3 + m; sts128(rb + (q >= 10 ? q - 10 : q) * 1280, 0, 0, 0, 0); }
    }
    uint32_t qa[20];
    {
      const float sc = 1.44269504089f + __uint_as_float(lds32(sb + OFF_EPOCH) ^ epoch);
      #pragma unroll
      for (int j = 0; j < 10; j++) { qa[2 * j] = pack2(phi(QV(j, 0), sc), phi(QV(j, 1), sc)); qa[2 * j + 1] = pack2(phi(QV(j, 2), sc), phi(QV(j, 3), sc)); }
    }
    if (tid == 0) TS(5);
    mbar_wait(BAR(BR_KVP), 0);
    if (tid == 0) TS(6);
    if (kvi < 3) {
      float s[8];
      zero<8>(s);
      uint32_t bad = 0;
      #pragma unroll 4
      for (int i = 0; i < 16; i++) {
        uint32_t w[4];
        lds128(w, sb + OFF_KVP + tid * 16 + i * 3840);
        bad |= w[3] ^ epoch;
        #pragma unroll
        for (int e = 0; e < 4; e++) { s[2 * e] += bf_lo(w[e]); s[2 * e + 1] += bf_hi(w[e]); }
      }
      if (__builtin_expect(bad & 1u, 0)) {
        zero<8>(s);
        #pragma unroll 1
        for (int i = 0; i < 16; i++) {
          uint32_t w[4] = {0, 0, 0, ~epoch};
          fix128_w3(w, &g_kvp[(c * 16 + i) * 240 + tid], epoch, 1u);
          #pragma unroll
          for (int e = 0; e < 4; e++) { s[2 * e] += bf_lo(w[e]); s[2 * e + 1] += bf_hi(w[e]); }
        }
        FIXCNT
      }
      const uint32_t p0 = pack2(s[0], s[1]), p1 = pack2(s[2], s[3]), p2 = pack2(s[4], s[5]), p3 = pack2(s[6], s[7]);
      if (kvi < 2) sts128(rb + (kt0 + (khd & 1) + kvi) * 1280, p0, p1, p2, p3);
      else {
        const bool od = khd & 1;
        sts128(rb + (5 * (khd >> 1) + 2) * 1280, od ? 0u : p0, od ? 0u : p1, od ? p0 : 0u, od ? p1 : 0u);
        const uint32_t zz = (p2 & 0xffffu) << (16 * (khd & 1));
        sts128(rb + 10 * 1280, khd < 2 ? zz : 0u, khd < 2 ? 0u : zz, 0u, 0u);
      }
    }
    fence_async();
    bar_sync(1, 256);
    if (tid == 0) { mbar_arrive(BAR(BR_SUM)); TS(7); }
    {
      float oa[44]; zero<44>(oa);
      constexpr uint64_t db = mkdesc(SB0 + OFF_KVB, 128, 1280, 0);
      wg_fence();
      #pragma unroll
      for (int s = 0; s < 5; s++) wg_rs88_tb(oa, &qa[4 * s], desc2((uint32_t)db + ((s == 4 && (c & 1)) ? 0 : (s + (c & 1)) * 16), db >> 32), s != 0);
      wg_commit();
      wg_wait<0>();
      pin<44>(oa);
      if (tid == 0) TS(13);
      float rc[4], rd[2][4];
      #pragma unroll
      for (int e = 0; e < 4; e++) asm("rcp.approx.ftz.f32 %0, %1;" : "=f"(rc[e]) : "f"(oa[40 + e] + 1e-6f));
      #pragma unroll
      for (int h = 0; h < 4; h++) {
        rd[0][h] = __shfl_sync(0xffffffff, rc[h & 1], (lane & 28) | (h >> 1));
        rd[1][h] = __shfl_sync(0xffffffff, rc[2 + (h & 1)], (lane & 28) | (h >> 1));
      }
      #pragma unroll
      for (int j = 0; j < 10; j++) {
        #pragma unroll
        for (int h = 0; h < 2; h++) {
          float f;
          if (j == 2) f = tq < 2 ? rd[h][0] : rd[h][1];
          else if (j == 7) f = tq < 2 ? rd[h][2] : rd[h][3];
          else f = rd[h][(8 * j) / 20];
          qa[2 * j + h] = pack2(oa[4 * j + 2 * h] * f, oa[4 * j + 2 * h + 1] * f);
        }
      }
      const uint32_t m0 = (lane & 7) == ((2 * w4) & 7), m1 = (lane & 7) == 2 * w4 + 1;
      const uint32_t oa_ = sb + OFF_EXTRA + (lane >> 4) * 2048 + (warp * 16 + (lane & 15)) * 16;
      bar_sync(1, 256);
#define TAG(v, m) (((v) & ~(m)) | (epoch & (m)))
      #pragma unroll
      for (int s = 0; s < 5; s++) stsm4(oa_ + s * 4096, TAG(qa[4 * s], m0), TAG(qa[4 * s + 1], m1), TAG(qa[4 * s + 2], m0), TAG(qa[4 * s + 3], m1));
    }
    fence_async();
    mbar_arrive(BAR(BR_OSTG));
    if (tid == 0) TS(8);
    float oc[40]; zero<40>(oc);
    {
      constexpr uint64_t dw0 = mkdesc(SB0, OFF_WOR, 1024, 1), da0 = mkdesc(SB0, 2048, 128, 0);
      const uint32_t ck = sb + tid * 32 + ((lane >> 2) << 2), ck2 = ck + (wg ? 0 : 16384);
      uint32_t bad = 0;
      auto tile = [&](int i, uint32_t so) {
        const uint32_t al = (uint32_t)da0 + wg * 64 + (so >> 4), wl = (uint32_t)dw0 + i * 640 - (i >> 1) * (1278 << 16);
        wg_fence();
        #pragma unroll
        for (int s = 0; s < 5; s++) wg_ss80_tb(oc, desc2(al + s * 256, da0 >> 32), desc2(wl + s * 128, dw0 >> 32), (i | s) != 0);
        wg_commit();
        bad |= (lds32(ck + so) ^ epoch) | (lds32(ck + so + 8192) ^ epoch) | (lds32(ck2 + so) ^ epoch);
      };
      mbar_wait(BAR(BR_WO), 0);
      mbar_wait(BAR(BR_OSTG), 0);
      tile(0, SLOT(0));
      mbar_wait(BAR(BR_WO + 1), 0);
      #pragma unroll 1
      for (int i = 1; i < 8; i++) {
        if (i == 1) { wg_wait<0>(); if (lane == 0) mbar_arrive(BAR(BR_OEMPTY)); }
        mbar_wait(BAR(BR_OFULL) + 8 * i, 0);
        if (i == 1 && tid == 0) TS(9);
        tile(i, SLOT(i));
        wg_wait<1>();
        if (lane == 0 && i > 1) mbar_arrive(BAR(BR_OEMPTY - 1) + 8 * i);
      }
      #pragma unroll 1
      for (int n = 0; n < 56; n++) {
        const int i = n & 7;
        if (i == 0) {
          uint32_t any;
          asm volatile("{\n.reg .pred p;\nsetp.ne.u32 p, %1, 0;\nbarrier.red.or.pred p, 1, 256, p;\nselp.u32 %0, 1, 0, p;\n}" : "=r"(any) : "r"(bad & 1u) : "memory");
          if (!any) break;
          bad = 0;
          FIXCNT
        }
        wg_wait<0>();
        bar_sync(1, 256);
        if (tid == 0) { mbar_expect_tx(BAR(BR_RETRY), 20480); bulk_ld(sb + SLOT(0), &g_o[(r * 8 + CHUNK(i)) * 1280], 20480, BAR(BR_RETRY)); }
        mbar_wait(BAR(BR_RETRY), n & 1);
        tile(i, SLOT(0));
      }
      wg_wait<0>();
      pin<40>(oc);
    }
    if (tid == 0) TS(10);
    {
      const int row = w4 * 16 + (lane & 15);
      const uint32_t ob = sb + SLOT(4) + wg * 10240;
      #pragma unroll
      for (int j = 0; j < 8; j += 2)
        stsm4(ob + row * 128 + (((j + (lane >> 4)) ^ (row & 7)) << 4), pack2(oc[4 * j], oc[4 * j + 1]), pack2(oc[4 * j + 2], oc[4 * j + 3]),
              pack2(oc[4 * j + 4], oc[4 * j + 5]), pack2(oc[4 * j + 6], oc[4 * j + 7]));
      stsm4(ob + 8192 + row * 32 + (lane >> 4) * 16, pack2(oc[32], oc[33]), pack2(oc[34], oc[35]), pack2(oc[36], oc[37]), pack2(oc[38], oc[39]));
      fence_async();
      bar_sync(2 + wg, 128);
      if (w4 == 0 && elect_one()) {
        tma2d_st(&prm.m[M_O64], ob, 640 + c * 64, r * 128 + wg * 64);
        tma2d_st(&prm.m[M_O16], ob + 8192, 1152 + c * 16, r * 128 + wg * 64);
        bulk_commit(); bulk_wait0_read();
        if (wg == 0) { TS(11); DUMP(0, 20); }
      }
    }
    }
  } else {
    if (EN_SSM) {
    const int tid = rtid(), lane = tid & 31, g = lane >> 2, tq = lane & 3, t7 = tid & 127;
    if (t7 == 0) TS(41);
    mbar_wait(BAR(BR_U), 0);
    bar_sync(4, 128);
    if (EN_ATT) mbar_wait(BAR(BR_GEMM), 0);
    if (t7 == 0) TS(42);
    #pragma unroll 1
    for (int pass = 1; pass >= 0; pass--) {
      const int k = pass ? w4 : 4;
      const uint32_t blk = sb + OFF_BLK + k * BLK, tb = blk + B_TBL + (uint32_t)((g - 2 * tq) * 4);
      float acc[16][4];
      zero<64>(&acc[0][0]);
      const int kl = 16 * (lane >> 4) + 2 * (lane & 7) + ((lane >> 3) & 1);
      {
        auto ubase = [&](int sh) { const int q = kl - 2 * sh; return blk + (uint32_t)((q * 16) ^ ((q * 2) & 0x70)); };
#define LDQ(A, sh) _Pragma("unroll") for (int m = 0; m < 4; m++) load_quad(A[m], tb + (16 + 16 * (sh) + 128 * m) * 4);
#define LDB(B, ub, h) _Pragma("unroll") for (int p = 0; p < 4; p++) ldsm4(B[p], ((ub) ^ ((p & 1) * 64)) + (4 * (h) + p) * 512);
#define MLO(A, B) _Pragma("unroll") for (int m = 0; m < 4; m++) _Pragma("unroll") for (int cc = 0; cc < 8; cc++) mma16816(acc[cc + m], A[m], &B[cc >> 1][(cc & 1) * 2]);
#define MHI(A, B) _Pragma("unroll") for (int m = 0; m < 4; m++) _Pragma("unroll") for (int cc = 0; cc < 8 - m; cc++) mma16816(acc[8 + cc + m], A[m], &B[cc >> 1][(cc & 1) * 2]);
        int p_ = pass ? 0 : w4;
        const int pe = pass ? 4 : w4 + 1;
        uint32_t A[4][4], A2[4][4], Bl[4][4], Bh[4][4];
        uint32_t ub = ubase(p_ + 4);
        LDQ(A, p_ + 4) LDB(Bl, ub, 0)
        #pragma unroll 1
        for (; p_ < pe; p_++) {
          LDB(Bh, ub, 1)
          MLO(A, Bl)
          ub = ubase(p_);
          LDQ(A2, p_) LDB(Bl, ub, 0)
          MHI(A, Bh)
          LDB(Bh, ub, 1)
          load_quad(A[0], tb + (16 + 512 + 16 * (p_ & 1)) * 4); load_quad(A[1], tb + (T_S + 16 * (p_ & 1)) * 4);
          MLO(A2, Bl)
          if (p_ < 2) {
            #pragma unroll
            for (int cc = 0; cc < 8; cc++) mma16816(acc[cc + 4], A[0], &Bl[cc >> 1][(cc & 1) * 2]);
            #pragma unroll
            for (int cc = 0; cc < 4; cc++) mma16816(acc[cc + 12], A[0], &Bh[cc >> 1][(cc & 1) * 2]);
            #pragma unroll
            for (int cc = 0; cc < 8; cc++) mma16816(acc[cc + 8], A[1], &Bl[cc >> 1][(cc & 1) * 2]);
          }
          const int pn = ((p_ + 1) & 3) + 4;
          ub = ubase(pn);
          LDQ(A, pn) LDB(Bl, ub, 0)
          MHI(A2, Bh)
        }
      }
      if (t7 == 0) TS(57 + 3 * pass);
      mbar_wait(BAR(BR_DRDY), 0);
      {
        const int ih = (lane >> 3) & 1;
        const uint32_t dl = blk + B_D + (uint32_t)(((lane >> 4) * 8 + (lane & 7)) * 16);
        const uint32_t d0_ = dl + ih * 1552, d8_ = dl + (ih ? 0 : 1536), d3_ = dl + B_D7 + ih * 1024;
        auto cls2 = [&](uint32_t da, uint32_t ta) {
          uint32_t B[6][2], A[6][4];
          #pragma unroll
          for (int e = 0; e < 6; e++) { B[e][0] = lds32v(ta + (e + 4) * 32); B[e][1] = lds32v(ta + (e + 3) * 32); }
          #pragma unroll
          for (int kk = 0; kk < 6; kk++) ldsm4t(A[kk], da + kk * 256);
          #pragma unroll
          for (int e = 0; e < 6; e++)
            #pragma unroll
            for (int kk = 0; kk < 6; kk++) if (2 * kk + e + 4 < 16) mma16816(acc[2 * kk + e + 4], A[kk], B[e]);
        };
        auto cls3 = [&](uint32_t da, uint32_t ta) {
          uint32_t B[8][2], A[4][4];
          #pragma unroll
          for (int e = 0; e < 8; e++) { B[e][0] = lds32v(ta + (e + 8) * 32); B[e][1] = lds32v(ta + (e + 7) * 32); }
          #pragma unroll
          for (int kk = 0; kk < 4; kk++) ldsm4t(A[kk], da + kk * 256);
          #pragma unroll
          for (int kk = 0; kk < 4; kk++)
            #pragma unroll
            for (int e = 0; e < 8; e++) if (2 * kk + e + 8 < 16) mma16816(acc[2 * kk + e + 8], A[kk], B[e]);
        };
        #pragma unroll 1
        for (int a = pass ? 0 : w4; a < (pass ? 4 : w4 + 1); a++) cls2(((a & 2) ? d8_ : d0_) + (a & 1) * B_D5, tb + (T_F2 + 48 * a - 32) * 4);
        #pragma unroll 1
        for (int b = pass ? 0 : (w4 & 1); b < (pass ? 2 : w4 - 1); b++) cls3(d3_ + b * 2048, tb + (T_F3 + 80 * b - 64) * 4);
      }
      if (t7 == 0) TS(58 + 3 * pass);
      const uint32_t ya = blk + (uint32_t)((kl * 16) ^ ((kl * 2) & 0x70));
#define STY(p) stsm4t((ya ^ (((p) & 1) * 64)) + (p) * 512, pack2(acc[2 * (p)][0], acc[2 * (p)][1]), pack2(acc[2 * (p)][2], acc[2 * (p)][3]), \
                      pack2(acc[2 * (p) + 1][0], acc[2 * (p) + 1][1]), pack2(acc[2 * (p) + 1][2], acc[2 * (p) + 1][3]))
      if (pass == 0) {
        const uint32_t xw = blk + 4096 + w4 * 4096 + lane * 16, xr = blk + 4096 + w4 * 1024 + lane * 16;
        #pragma unroll
        for (int h = 0; h < 2; h++) {
          bar_sync(4, 128);
          #pragma unroll
          for (int i = 0; i < 8; i++)
            sts128(xw + i * 512, __float_as_uint(acc[8 * h + i][0]), __float_as_uint(acc[8 * h + i][1]), __float_as_uint(acc[8 * h + i][2]), __float_as_uint(acc[8 * h + i][3]));
          bar_sync(4, 128);
          float y[8];
          #pragma unroll
          for (int i = 0; i < 8; i++) {
            uint32_t o[4]; lds128(o, xr + (i >> 1) * 4096 + (i & 1) * 512);
            #pragma unroll
            for (int e = 0; e < 4; e++) y[4 * (i & 1) + e] = i < 2 ? __uint_as_float(o[e]) : y[4 * (i & 1) + e] + __uint_as_float(o[e]);
          }
          stsm4t((ya ^ ((w4 & 1) * 64)) + (4 * h + w4) * 512, pack2(y[0], y[1]), pack2(y[2], y[3]), pack2(y[4], y[5]), pack2(y[6], y[7]));
        }
      } else {
        __syncwarp();
        #pragma unroll
        for (int p = 0; p < 8; p++) STY(p);
      }
      if (t7 == 0 && !pass) TS(55);
      fence_async();
      mbar_arrive(BAR(BR_Y + 1) - 8 * pass);
      if (t7 == 0) TS(59 + 3 * pass);
    }
    if (t7 == 0) DUMP(40, 64);
    }
  }
  }
}

typedef CUresult (*EncFn)(CUtensorMap*, CUtensorMapDataType, cuuint32_t, void*, const cuuint64_t*, const cuuint64_t*, const cuuint32_t*,
                          const cuuint32_t*, CUtensorMapInterleave, CUtensorMapSwizzle, CUtensorMapL2promotion, CUtensorMapFloatOOBfill);
static void mkmap(EncFn enc, CUtensorMap* m, const void* base, int rank, const cuuint64_t* dims, const cuuint64_t* strides, const cuuint32_t* box, CUtensorMapSwizzle swz) {
  cuuint32_t es[5] = {1, 1, 1, 1, 1};
  enc(m, CU_TENSOR_MAP_DATA_TYPE_BFLOAT16, rank, const_cast<void*>(base), dims, strides, box, es, CU_TENSOR_MAP_INTERLEAVE_NONE, swz,
      CU_TENSOR_MAP_L2_PROMOTION_L2_128B, CU_TENSOR_MAP_FLOAT_OOB_FILL_NONE);
}

extern "C" void kernel_launch(void* const* d_in, const int* in_sizes, int n_in, void* d_out, int out_size) {
  void* fn = nullptr; cudaDriverEntryPointQueryResult qr;
  cudaGetDriverEntryPoint("cuTensorMapEncodeTiled", &fn, cudaEnableDefault, &qr);
  EncFn enc = (EncFn)fn;
  void* uy = nullptr; cudaGetSymbolAddress(&uy, g_uy);
  const cuuint64_t dx[2] = {640, 2048}, sx[1] = {1280};
  const cuuint32_t bx[2] = {64, 128}, bu[2] = {80, 128}, bu2[2] = {80, 64};
  const cuuint64_t dw[3] = {640, 640, 3}, sw[2] = {3840, 1280};
  const cuuint32_t br[3] = {16, 32, 3};
  const cuuint64_t dwa[4] = {64, 640, 10, 3}, swa[3] = {3840, 128, 1280}, dwb[4] = {32, 640, 20, 3}, swb[3] = {3840, 64, 1280};
  const cuuint32_t bwa[4] = {64, 32, 1, 3}, bwb[4] = {32, 32, 2, 3};
  const cuuint64_t dwo[2] = {640, 640};
  const cuuint32_t bwo[2] = {64, 80}, bo64[2] = {64, 64}, bo16[2] = {16, 64};
  const cuuint64_t dsa[2] = {2048, 1280}, ssa[1] = {4096};
  const cuuint32_t bsa[2] = {64, 80};
  const cuuint64_t dsb[2] = {64, 40960}, ssb[1] = {128};
  const cuuint32_t bsb[2] = {64, 32};
  const cuuint64_t dout[2] = {1280, 2048}, sout[1] = {2560};
  Params prm;
  mkmap(enc, &prm.m[M_X], d_in[7], 2, dx, sx, bx, CU_TENSOR_MAP_SWIZZLE_128B);
  mkmap(enc, &prm.m[M_W128], d_in[8], 4, dwa, swa, bwa, CU_TENSOR_MAP_SWIZZLE_128B);
  mkmap(enc, &prm.m[M_W64], d_in[8], 4, dwb, swb, bwb, CU_TENSOR_MAP_SWIZZLE_64B);
  mkmap(enc, &prm.m[M_WR], d_in[8], 3, dw, sw, br, CU_TENSOR_MAP_SWIZZLE_32B);
  mkmap(enc, &prm.m[M_U], d_in[0], 2, dx, sx, bu2, CU_TENSOR_MAP_SWIZZLE_NONE);
  mkmap(enc, &prm.m[M_WO], d_in[9], 2, dwo, sx, bwo, CU_TENSOR_MAP_SWIZZLE_128B);
  mkmap(enc, &prm.m[M_O64], d_out, 2, dout, sout, bo64, CU_TENSOR_MAP_SWIZZLE_128B);
  mkmap(enc, &prm.m[M_O16], d_out, 2, dout, sout, bo16, CU_TENSOR_MAP_SWIZZLE_NONE);
  mkmap(enc, &prm.m[M_SA], uy, 2, dsa, ssa, bsa, CU_TENSOR_MAP_SWIZZLE_128B);
  mkmap(enc, &prm.m[M_SB], uy, 2, dsb, ssb, bsb, CU_TENSOR_MAP_SWIZZLE_128B);
  mkmap(enc, &prm.m[M_OUT], d_out, 2, dout, sout, bu, CU_TENSOR_MAP_SWIZZLE_NONE);
  prm.u = (const __nv_bfloat16*)d_in[0]; prm.wo = (const __nv_bfloat16*)d_in[9];
  for (int i = 0; i < 4; i++) prm.par[i] = (const __nv_bfloat16*)d_in[1 + i];
  prm.logdt = (const __nv_bfloat16*)d_in[5]; prm.dskip = (const __nv_bfloat16*)d_in[6];
  cudaFuncSetAttribute(fused_kernel, cudaFuncAttributeMaxDynamicSharedMemorySize, SMEM_BYTES);
  cudaLaunchConfig_t cfg = {};
  cfg.gridDim = dim3(128); cfg.blockDim = dim3(512); cfg.dynamicSmemBytes = SMEM_BYTES; cfg.stream = cudaStreamPerThread;
  cudaLaunchAttribute at[1];
  at[0].id = cudaLaunchAttributeClusterDimension; at[0].val.clusterDim.x = 2; at[0].val.clusterDim.y = 1; at[0].val.clusterDim.z = 1;
  cfg.attrs = at; cfg.numAttrs = 1;
  cudaLaunchKernelEx(&cfg, fused_kernel, prm);
}
```

```cpp
#include <cuda_runtime.h>
#include <cuda_bf16.h>
#include <cuda_fp16.h>
#include <cuda.h>
#include <stdint.h>

#define KST 2
#define EN_ATT 1
#define EN_SSM 1

__device__ __align__(1024) __nv_bfloat16 g_uy[2 * 640 * 2048];
__device__ __align__(128) uint4 g_kvp[8 * 16 * 240];
__device__ __align__(128) uint4 g_o[128 * 1280];
__device__ __align__(128) unsigned g_flag[4 * 128 * 32];
__device__ unsigned g_epoch[128];
#define TS(i) do {} while (0)
#define DUMP(lo, hi) do {} while (0)
#define FIXCNT

constexpr uint32_t SB0 = 1024;
constexpr uint32_t W_SLOT = 15360, OFF_X = 76800;
constexpr uint32_t OFF_WOR = 81920, OFF_KVP = 10240, OFF_KVS = 71680, OFF_PK = 10240, OFF_V = 30720, OFF_EXTRA = 102400, OFF_KVB = OFF_EXTRA;
constexpr uint32_t OFF_UT = 3 * W_SLOT;
constexpr uint32_t OFF_BAR = 125952, OFF_BLK = 128000, BLK = 20480;
constexpr uint32_t B_D = 4096, B_D5 = 3088, B_D7 = 6176, B_D9 = 8224, B_TBL = 14400;
constexpr int T_S = 576, T_F2 = 624, T_F3 = 816;
constexpr uint32_t SMEM_BYTES = OFF_BLK + 5 * BLK;
enum { BR_FULL = 0, BR_WO = 5, BR_PUB = 7, BR_KVP = 8, BR_U = 9, BR_SUM = 10, BR_GEMM = 11, BR_UIN = 12, BR_YIN = 13, BR_EPOCH = 14,
       BR_FREE = 15, BR_RETRY = 17, BR_UOUT = 18, BR_OFULL = 18, BR_KS = 26, BR_EMPTY = 31, BR_OEMPTY = 36, BR_Y = 43, BR_OSTG = 45, BR_DRDY = 46,
       BR_COUNT = 48 };
constexpr uint32_t OFF_EPOCH = OFF_BAR + 8 * BR_COUNT;
enum { M_X, M_W128, M_W64, M_WR, M_U, M_WO, M_O64, M_O16, M_SA, M_SB, M_OUT, M_COUNT };

__device__ __forceinline__ long long clk64() { long long t; asm volatile("mov.u64 %0, %%clock64;" : "=l"(t) :: "memory"); return t; }
__device__ __forceinline__ uint32_t smem_u32(const void* p) { return (uint32_t)__cvta_generic_to_shared(p); }
__host__ __device__ constexpr uint64_t mkdesc(uint32_t addr, uint32_t lbo, uint32_t sbo, uint32_t swz) {
  return (uint64_t)((addr & 0x3FFFF) >> 4) | ((uint64_t)(lbo >> 4) << 16) | ((uint64_t)(sbo >> 4) << 32) | ((uint64_t)swz << 62);
}
__device__ __forceinline__ uint64_t desc2(uint32_t lo, uint32_t hi) { uint64_t d; asm("mov.b64 %0, {%1, %2};" : "=l"(d) : "r"(lo), "r"(hi)); return d; }
__device__ __forceinline__ void mbar_init(uint32_t bar, uint32_t cnt) { asm volatile("mbarrier.init.shared::cta.b64 [%0], %1;" :: "r"(bar), "r"(cnt) : "memory"); }
__device__ __forceinline__ void mbar_expect_tx(uint32_t bar, uint32_t bytes) { asm volatile("mbarrier.arrive.expect_tx.shared::cta.b64 _, [%0], %1;" :: "r"(bar), "r"(bytes) : "memory"); }
__device__ __forceinline__ void mbar_arrive(uint32_t bar) { asm volatile("mbarrier.arrive.shared::cta.b64 _, [%0];" :: "r"(bar) : "memory"); }
__device__ __forceinline__ void mbar_wait(uint32_t bar, uint32_t parity) {
  asm volatile("{\n.reg .pred p;\n.reg .u32 c;\nmov.u32 c, 0;\n"
    "WL:\nmbarrier.try_wait.parity.shared::cta.b64 p, [%0], %1;\n@p bra WD;\n"
    "add.u32 c, c, 1;\nsetp.lt.u32 p, c, 200000;\n@p bra WL;\nWD:\n}" :: "r"(bar), "r"(parity) : "memory");
}
__device__ __forceinline__ void poll_all(const unsigned* p, unsigned val) {
  asm volatile("{\n.reg .pred p;\n.reg .u32 c, v;\nmov.u32 c, 0;\n"
    "PL:\nld.relaxed.gpu.global.u32 v, [%0];\nsetp.eq.u32 p, v, %1;\nvote.sync.all.pred p, p, 0xffffffff;\n@p bra PD;\n"
    "add.u32 c, c, 1;\nsetp.lt.u32 p, c, 100000;\n@p bra PL;\nPD:\n}" :: "l"(p), "r"(val) : "memory");
}
__device__ __forceinline__ void poll_all_acq(const unsigned* p, unsigned val) {
  asm volatile("{\n.reg .pred p;\n.reg .u32 c, v;\nmov.u32 c, 0;\n"
    "PL:\nld.acquire.gpu.global.u32 v, [%0];\nsetp.eq.u32 p, v, %1;\nvote.sync.all.pred p, p, 0xffffffff;\n@p bra PD;\n"
    "add.u32 c, c, 1;\nsetp.lt.u32 p, c, 100000;\n@p bra PL;\nPD:\n}" :: "l"(p), "r"(val) : "memory");
}
__device__ __forceinline__ unsigned poll_bit(const unsigned* p, unsigned val, unsigned mask) {
  unsigned bal;
  asm volatile("{\n.reg .pred p;\n.reg .u32 c, v;\nmov.u32 c, 0;\n"
    "PL:\nld.relaxed.gpu.global.u32 v, [%1];\nsetp.eq.u32 p, v, %2;\nvote.sync.ballot.b32 %0, p, 0xffffffff;\n"
    "and.b32 v, %0, %3;\nsetp.ne.u32 p, v, 0;\n@p bra PD;\n"
    "add.u32 c, c, 1;\nsetp.lt.u32 p, c, 100000;\n@p bra PL;\nPD:\n}" : "=&r"(bal) : "l"(p), "r"(val), "r"(mask) : "memory");
  return bal;
}
__device__ __forceinline__ void fix128_w0(uint32_t* v, const void* p, uint32_t tag, uint32_t mask) {
  asm volatile("{\n.reg .pred p;\n.reg .u32 c, x;\n.reg .b128 t;\n.reg .b64 lo, hi;\nmov.u32 c, 0;\n"
    "FL:\nxor.b32 x, %0, %5;\nand.b32 x, x, %6;\nsetp.eq.u32 p, x, 0;\n@p bra FD;\n"
    "ld.relaxed.gpu.global.b128 t, [%4];\nmov.b128 {lo, hi}, t;\nmov.b64 {%0, %1}, lo;\nmov.b64 {%2, %3}, hi;\n"
    "add.u32 c, c, 1;\nsetp.lt.u32 p, c, 100000;\n@p bra FL;\nFD:\n}"
    : "+r"(v[0]), "+r"(v[1]), "+r"(v[2]), "+r"(v[3]) : "l"(p), "r"(tag), "r"(mask) : "memory");
}
__device__ __forceinline__ void fix128_w3(uint32_t* v, const void* p, uint32_t tag, uint32_t mask) {
  asm volatile("{\n.reg .pred p;\n.reg .u32 c, x;\n.reg .b128 t;\n.reg .b64 lo, hi;\nmov.u32 c, 0;\n"
    "FL:\nxor.b32 x, %3, %5;\nand.b32 x, x, %6;\nsetp.eq.u32 p, x, 0;\n@p bra FD;\n"
    "ld.relaxed.gpu.global.b128 t, [%4];\nmov.b128 {lo, hi}, t;\nmov.b64 {%0, %1}, lo;\nmov.b64 {%2, %3}, hi;\n"
    "add.u32 c, c, 1;\nsetp.lt.u32 p, c, 100000;\n@p bra FL;\nFD:\n}"
    : "+r"(v[0]), "+r"(v[1]), "+r"(v[2]), "+r"(v[3]) : "l"(p), "r"(tag), "r"(mask) : "memory");
}
__device__ __forceinline__ void fence_acq() { asm volatile("fence.acq_rel.gpu;" ::: "memory"); }
__device__ __forceinline__ bool elect_one() {
  uint32_t p; asm volatile("{\n.reg .pred P;\nelect.sync _|P, 0xffffffff;\nselp.u32 %0, 1, 0, P;\n}" : "=r"(p)); return p;
}
__device__ __forceinline__ void bar_sync(int id, int n) { asm volatile("bar.sync %0, %1;" :: "r"(id), "r"(n) : "memory"); }
__device__ __forceinline__ void fence_async() { asm volatile("fence.proxy.async.shared::cta;" ::: "memory"); }
__device__ __forceinline__ void fence_async_g() { asm volatile("fence.proxy.async.global;" ::: "memory"); }
__device__ __forceinline__ void tma2d(uint32_t dst, const CUtensorMap* m, uint32_t bar, int c0, int c1) {
  asm volatile("cp.async.bulk.tensor.2d.shared::cluster.global.mbarrier::complete_tx::bytes [%0], [%1, {%3, %4}], [%2];"
    :: "r"(dst), "l"(m), "r"(bar), "r"(c0), "r"(c1) : "memory");
}
__device__ __forceinline__ void tma3d(uint32_t dst, const CUtensorMap* m, uint32_t bar, int c0, int c1, int c2) {
  asm volatile("cp.async.bulk.tensor.3d.shared::cluster.global.mbarrier::complete_tx::bytes [%0], [%1, {%3, %4, %5}], [%2];"
    :: "r"(dst), "l"(m), "r"(bar), "r"(c0), "r"(c1), "r"(c2) : "memory");
}
__device__ __forceinline__ void tma4d(uint32_t dst, const CUtensorMap* m, uint32_t bar, int c0, int c1, int c2, int c3) {
  asm volatile("cp.async.bulk.tensor.4d.shared::cluster.global.mbarrier::complete_tx::bytes [%0], [%1, {%3, %4, %5, %6}], [%2];"
    :: "r"(dst), "l"(m), "r"(bar), "r"(c0), "r"(c1), "r"(c2), "r"(c3) : "memory");
}
__device__ __forceinline__ void tma2d_st(const CUtensorMap* m, uint32_t src, int c0, int c1) {
  asm volatile("cp.async.bulk.tensor.2d.global.shared::cta.bulk_group [%0, {%2, %3}], [%1];"
    :: "l"(m), "r"(src), "r"(c0), "r"(c1) : "memory");
}
__device__ __forceinline__ void bulk_ld(uint32_t dst, const void* src, uint32_t bytes, uint32_t bar) {
  asm volatile("cp.async.bulk.shared::cluster.global.mbarrier::complete_tx::bytes [%0], [%1], %2, [%3];"
    :: "r"(dst), "l"(src), "r"(bytes), "r"(bar) : "memory");
}
__device__ __forceinline__ void bulk_st(void* dst, uint32_t src, uint32_t bytes) {
  asm volatile("cp.async.bulk.global.shared::cta.bulk_group [%0], [%1], %2;" :: "l"(dst), "r"(src), "r"(bytes) : "memory");
}
__device__ __forceinline__ void bulk_commit() { asm volatile("cp.async.bulk.commit_group;" ::: "memory"); }
__device__ __forceinline__ void bulk_wait0() { asm volatile("cp.async.bulk.wait_group 0;" ::: "memory"); }
__device__ __forceinline__ void bulk_wait0_read() { asm volatile("cp.async.bulk.wait_group.read 0;" ::: "memory"); }
__device__ __forceinline__ unsigned ld_rlx(const unsigned* p) { unsigned v; asm volatile("ld.relaxed.gpu.global.u32 %0, [%1];" : "=r"(v) : "l"(p) : "memory"); return v; }
__device__ __forceinline__ unsigned ld_acq(const unsigned* p) { unsigned v; asm volatile("ld.acquire.gpu.global.u32 %0, [%1];" : "=r"(v) : "l"(p) : "memory"); return v; }
__device__ __forceinline__ void st_rlx(unsigned* p, unsigned v) { asm volatile("st.relaxed.gpu.global.u32 [%0], %1;" :: "l"(p), "r"(v) : "memory"); }
__device__ __forceinline__ void st_rel(unsigned* p, unsigned v) { asm volatile("st.release.gpu.global.u32 [%0], %1;" :: "l"(p), "r"(v) : "memory"); }
__device__ __forceinline__ void ld128_rlx(uint32_t* v, const void* p) {
  asm volatile("{\n.reg .b128 t;\n.reg .b64 lo, hi;\nld.relaxed.gpu.global.b128 t, [%4];\nmov.b128 {lo, hi}, t;\n"
    "mov.b64 {%0, %1}, lo;\nmov.b64 {%2, %3}, hi;\n}" : "=r"(v[0]), "=r"(v[1]), "=r"(v[2]), "=r"(v[3]) : "l"(p) : "memory");
}
__device__ __forceinline__ void st128_rlx(void* p, const uint32_t* v) {
  asm volatile("{\n.reg .b128 t;\n.reg .b64 lo, hi;\nmov.b64 lo, {%1, %2};\nmov.b64 hi, {%3, %4};\nmov.b128 t, {lo, hi};\n"
    "st.relaxed.gpu.global.b128 [%0], t;\n}" :: "l"(p), "r"(v[0]), "r"(v[1]), "r"(v[2]), "r"(v[3]) : "memory");
}
__device__ __forceinline__ uint32_t lds32(uint32_t a) { uint32_t v; asm volatile("ld.shared.u32 %0, [%1];" : "=r"(v) : "r"(a) : "memory"); return v; }
__device__ __forceinline__ uint32_t lds32v(uint32_t a) { uint32_t v; asm volatile("ld.volatile.shared.u32 %0, [%1];" : "=r"(v) : "r"(a) : "memory"); return v; }
__device__ __forceinline__ uint32_t cpa(uint32_t a, uint32_t one) { uint32_t v; asm volatile("mul.lo.u32 %0, %1, %2;" : "=r"(v) : "r"(a), "r"(one)); return v; }
__device__ __forceinline__ uint32_t cpb(uint32_t a, uint32_t zero) { uint32_t v; asm volatile("or.b32 %0, %1, %2;" : "=r"(v) : "r"(a), "r"(zero)); return v; }
__device__ __forceinline__ uint32_t lds16(uint32_t a) { uint16_t v; asm volatile("ld.shared.u16 %0, [%1];" : "=h"(v) : "r"(a) : "memory"); return v; }
__device__ __forceinline__ float ldsf(uint32_t a) { float v; asm volatile("ld.shared.f32 %0, [%1];" : "=f"(v) : "r"(a) : "memory"); return v; }
__device__ __forceinline__ void lds128(uint32_t* v, uint32_t a) { asm volatile("ld.shared.v4.u32 {%0,%1,%2,%3}, [%4];" : "=r"(v[0]), "=r"(v[1]), "=r"(v[2]), "=r"(v[3]) : "r"(a) : "memory"); }
__device__ __forceinline__ void sts32(uint32_t a, uint32_t v) { asm volatile("st.shared.u32 [%0], %1;" :: "r"(a), "r"(v) : "memory"); }
__device__ __forceinline__ void sts16(uint32_t a, uint32_t v) { asm volatile("st.shared.u16 [%0], %1;" :: "r"(a), "h"((uint16_t)v) : "memory"); }
__device__ __forceinline__ void sts64f(uint32_t a, float x, float y) { asm volatile("st.shared.v2.f32 [%0], {%1,%2};" :: "r"(a), "f"(x), "f"(y) : "memory"); }
__device__ __forceinline__ void sts128(uint32_t a, uint32_t x, uint32_t y, uint32_t z, uint32_t w) { asm volatile("st.shared.v4.u32 [%0], {%1,%2,%3,%4};" :: "r"(a), "r"(x), "r"(y), "r"(z), "r"(w) : "memory"); }
__device__ __forceinline__ void stsm4(uint32_t a, uint32_t r0, uint32_t r1, uint32_t r2, uint32_t r3) {
  asm volatile("stmatrix.sync.aligned.m8n8.x4.shared.b16 [%0], {%1,%2,%3,%4};" :: "r"(a), "r"(r0), "r"(r1), "r"(r2), "r"(r3) : "memory");
}
__device__ __forceinline__ void stsm4t(uint32_t a, uint32_t r0, uint32_t r1, uint32_t r2, uint32_t r3) {
  asm volatile("stmatrix.sync.aligned.m8n8.x4.trans.shared.b16 [%0], {%1,%2,%3,%4};" :: "r"(a), "r"(r0), "r"(r1), "r"(r2), "r"(r3) : "memory");
}
__device__ __forceinline__ void ldsm4t(uint32_t* r, uint32_t a) {
  asm volatile("ldmatrix.sync.aligned.m8n8.x4.trans.shared.b16 {%0,%1,%2,%3}, [%4];" : "=r"(r[0]), "=r"(r[1]), "=r"(r[2]), "=r"(r[3]) : "r"(a) : "memory");
}
__device__ __forceinline__ void ldsm4(uint32_t* r, uint32_t a) {
  asm volatile("ldmatrix.sync.aligned.m8n8.x4.shared.b16 {%0,%1,%2,%3}, [%4];" : "=r"(r[0]), "=r"(r[1]), "=r"(r[2]), "=r"(r[3]) : "r"(a) : "memory");
}
__device__ __forceinline__ void mma16816(float* d, const uint32_t* a, const uint32_t* b) {
  asm volatile("mma.sync.aligned.m16n8k16.row.col.f32.bf16.bf16.f32 {%0,%1,%2,%3}, {%4,%5,%6,%7}, {%8,%9}, {%0,%1,%2,%3};"
    : "+f"(d[0]), "+f"(d[1]), "+f"(d[2]), "+f"(d[3]) : "r"(a[0]), "r"(a[1]), "r"(a[2]), "r"(a[3]), "r"(b[0]), "r"(b[1]));
}
__device__ __forceinline__ uint32_t pack2(float lo, float hi) { uint32_t r; asm("cvt.rn.bf16x2.f32 %0, %1, %2;" : "=r"(r) : "f"(hi), "f"(lo)); return r; }
__device__ __forceinline__ uint32_t packh(float lo, float hi) { uint32_t r; asm("cvt.rn.f16x2.f32 %0, %1, %2;" : "=r"(r) : "f"(hi), "f"(lo)); return r; }
__device__ __forceinline__ uint32_t hcmul(uint32_t x, uint32_t zp, uint32_t zq) {
  const __half2 xx = *reinterpret_cast<__half2*>(&x);
  const __half2 r = __hfma2(__high2half2(xx), *reinterpret_cast<__half2*>(&zq), __hmul2(__low2half2(xx), *reinterpret_cast<__half2*>(&zp)));
  return *reinterpret_cast<const uint32_t*>(&r);
}
__device__ __forceinline__ void hcm2(uint32_t xr, uint32_t xi, uint32_t z, uint32_t& pr, uint32_t& pi) {
  const __half2 a = *reinterpret_cast<__half2*>(&xr), b = *reinterpret_cast<__half2*>(&xi), zz = *reinterpret_cast<__half2*>(&z);
  const __half2 re = __hfma2(__hneg2(b), __high2half2(zz), __hmul2(a, __low2half2(zz)));
  const __half2 im = __hfma2(a, __high2half2(zz), __hmul2(b, __low2half2(zz)));
  pr = *reinterpret_cast<const uint32_t*>(&re); pi = *reinterpret_cast<const uint32_t*>(&im);
}
__device__ __forceinline__ void sts64(uint32_t a, uint32_t x, uint32_t y) { asm volatile("st.shared.v2.u32 [%0], {%1,%2};" :: "r"(a), "r"(x), "r"(y) : "memory"); }
__device__ __forceinline__ void lds64(uint32_t* v, uint32_t a) { asm volatile("ld.shared.v2.u32 {%0,%1}, [%2];" : "=r"(v[0]), "=r"(v[1]) : "r"(a) : "memory"); }
__device__ __forceinline__ float bf_lo(uint32_t v) { return __uint_as_float(v << 16); }
__device__ __forceinline__ float bf_hi(uint32_t v) { return __uint_as_float(v & 0xffff0000u); }
__device__ __forceinline__ float bf_round(float x) { return bf_lo(pack2(x, 0.f)); }
__device__ __forceinline__ float ex2(float x) { float r; asm("ex2.approx.ftz.f32 %0, %1;" : "=f"(r) : "f"(x)); return r; }
__device__ __forceinline__ float phi(float t, float l2e = 1.44269504089f) {
  float e = ex2(t * l2e) + 1e-6f;
  asm("{\n.reg .pred p;\nsetp.gt.f32 p, %1, 0f00000000;\n@p add.f32 %0, %1, 0f3F800008;\n}" : "+f"(e) : "f"(t));
  return e;
}
__device__ __forceinline__ void wg_fence() { asm volatile("wgmma.fence.sync.aligned;" ::: "memory"); }
__device__ __forceinline__ void wg_commit() { asm volatile("wgmma.commit_group.sync.aligned;" ::: "memory"); }
template <int N> __device__ __forceinline__ void wg_wait() { asm volatile("wgmma.wait_group.sync.aligned %0;" :: "n"(N) : "memory"); }
template <int N> __device__ __forceinline__ void pin(float* a) {
  #pragma unroll
  for (int i = 0; i < N; i++) asm volatile("" : "+f"(a[i]) :: "memory");
}
__device__ __forceinline__ int rtid() { int t; asm volatile("mov.u32 %0, %%tid.x;" : "=r"(t)); return t; }
__device__ __forceinline__ int opaque(int v) { asm volatile("" : "+r"(v)); return v; }
template <int N> __device__ __forceinline__ void zero(float* a) {
  #pragma unroll
  for (int i = 0; i < N; i++) asm volatile("mov.b32 %0, 0;" : "=f"(a[i]));
}
template <int N> __device__ __forceinline__ void pinu(uint32_t* a) {
  #pragma unroll
  for (int i = 0; i < N; i++) asm volatile("" : "+r"(a[i]) :: "memory");
}
__device__ __forceinline__ void cexp_t(float lg2mag, float turns, float& re, float& im) {
  float m = ex2(lg2mag);
  float fr = (turns - __fadd_rn(__fadd_rn(turns, 12582912.f), -12582912.f)) * 6.283185307f;
  re = m * __cosf(fr); im = m * __sinf(fr);
}
__device__ __forceinline__ void cmul(float ar, float ai, float br, float bi, float& cr, float& ci) {
  cr = fmaf(ar, br, -ai * bi); ci = fmaf(ar, bi, ai * br);
}

__device__ __forceinline__ void wg_ss192_tb(float* d, uint64_t da, uint64_t db, int scale_d) {
  asm volatile("{\n.reg .pred p;\nsetp.ne.b32 p, %98, 0;\n"
    "wgmma.mma_async.sync.aligned.m64n192k16.f32.bf16.bf16 "
    "{%0, %1, %2, %3, %4, %5, %6, %7, %8, %9, %10, %11, %12, %13, %14, %15, %16, %17, %18, %19, %20, %21, %22, %23, %24, %25, %26, %27, %28, %29, %30, %31, %32, %33, %34, %35, %36, %37, %38, %39, %40, %41, %42, %43, %44, %45, %46, %47, %48, %49, %50, %51, %52, %53, %54, %55, %56, %57, %58, %59, %60, %61, %62, %63, %64, %65, %66, %67, %68, %69, %70, %71, %72, %73, %74, %75, %76, %77, %78, %79, %80, %81, %82, %83, %84, %85, %86, %87, %88, %89, %90, %91, %92, %93, %94, %95}, %96, %97, p, 1, 1, 0, 1;\n}\n"
    : "+f"(d[0]), "+f"(d[1]), "+f"(d[2]), "+f"(d[3]), "+f"(d[4]), "+f"(d[5]), "+f"(d[6]), "+f"(d[7]), "+f"(d[8]), "+f"(d[9]), "+f"(d[10]), "+f"(d[11]), "+f"(d[12]), "+f"(d[13]), "+f"(d[14]), "+f"(d[15]), "+f"(d[16]), "+f"(d[17]), "+f"(d[18]), "+f"(d[19]), "+f"(d[20]), "+f"(d[21]), "+f"(d[22]), "+f"(d[23]), "+f"(d[24]), "+f"(d[25]), "+f"(d[26]), "+f"(d[27]), "+f"(d[28]), "+f"(d[29]), "+f"(d[30]), "+f"(d[31]), "+f"(d[32]), "+f"(d[33]), "+f"(d[34]), "+f"(d[35]), "+f"(d[36]), "+f"(d[37]), "+f"(d[38]), "+f"(d[39]), "+f"(d[40]), "+f"(d[41]), "+f"(d[42]), "+f"(d[43]), "+f"(d[44]), "+f"(d[45]), "+f"(d[46]), "+f"(d[47]), "+f"(d[48]), "+f"(d[49]), "+f"(d[50]), "+f"(d[51]), "+f"(d[52]), "+f"(d[53]), "+f"(d[54]), "+f"(d[55]), "+f"(d[56]), "+f"(d[57]), "+f"(d[58]), "+f"(d[59]), "+f"(d[60]), "+f"(d[61]), "+f"(d[62]), "+f"(d[63]), "+f"(d[64]), "+f"(d[65]), "+f"(d[66]), "+f"(d[67]), "+f"(d[68]), "+f"(d[69]), "+f"(d[70]), "+f"(d[71]), "+f"(d[72]), "+f"(d[73]), "+f"(d[74]), "+f"(d[75]), "+f"(d[76]), "+f"(d[77]), "+f"(d[78]), "+f"(d[79]), "+f"(d[80]), "+f"(d[81]), "+f"(d[82]), "+f"(d[83]), "+f"(d[84]), "+f"(d[85]), "+f"(d[86]), "+f"(d[87]), "+f"(d[88]), "+f"(d[89]), "+f"(d[90]), "+f"(d[91]), "+f"(d[92]), "+f"(d[93]), "+f"(d[94]), "+f"(d[95])
    : "l"(da), "l"(db), "r"(scale_d));
}
__device__ __forceinline__ void wg_ss48_tb(float* d, uint64_t da, uint64_t db, int scale_d) {
  asm volatile("{\n.reg .pred p;\nsetp.ne.b32 p, %26, 0;\n"
    "wgmma.mma_async.sync.aligned.m64n48k16.f32.bf16.bf16 "
    "{%0, %1, %2, %3, %4, %5, %6, %7, %8, %9, %10, %11, %12, %13, %14, %15, %16, %17, %18, %19, %20, %21, %22, %23}, %24, %25, p, 1, 1, 0, 1;\n}\n"
    : "+f"(d[0]), "+f"(d[1]), "+f"(d[2]), "+f"(d[3]), "+f"(d[4]), "+f"(d[5]), "+f"(d[6]), "+f"(d[7]), "+f"(d[8]), "+f"(d[9]), "+f"(d[10]), "+f"(d[11]), "+f"(d[12]), "+f"(d[13]), "+f"(d[14]), "+f"(d[15]), "+f"(d[16]), "+f"(d[17]), "+f"(d[18]), "+f"(d[19]), "+f"(d[20]), "+f"(d[21]), "+f"(d[22]), "+f"(d[23])
    : "l"(da), "l"(db), "r"(scale_d));
}
__device__ __forceinline__ void wg_ss48_tt(float* d, uint64_t da, uint64_t db, int scale_d) {
  asm volatile("{\n.reg .pred p;\nsetp.ne.b32 p, %26, 0;\n"
    "wgmma.mma_async.sync.aligned.m64n48k16.f32.bf16.bf16 "
    "{%0, %1, %2, %3, %4, %5, %6, %7, %8, %9, %10, %11, %12, %13, %14, %15, %16, %17, %18, %19, %20, %21, %22, %23}, %24, %25, p, 1, 1, 1, 1;\n}\n"
    : "+f"(d[0]), "+f"(d[1]), "+f"(d[2]), "+f"(d[3]), "+f"(d[4]), "+f"(d[5]), "+f"(d[6]), "+f"(d[7]), "+f"(d[8]), "+f"(d[9]), "+f"(d[10]), "+f"(d[11]), "+f"(d[12]), "+f"(d[13]), "+f"(d[14]), "+f"(d[15]), "+f"(d[16]), "+f"(d[17]), "+f"(d[18]), "+f"(d[19]), "+f"(d[20]), "+f"(d[21]), "+f"(d[22]), "+f"(d[23])
    : "l"(da), "l"(db), "r"(scale_d));
}
__device__ __forceinline__ void wg_rs88_tb(float* d, const uint32_t* a, uint64_t db, int scale_d) {
  asm volatile("{\n.reg .pred p;\nsetp.ne.b32 p, %49, 0;\n"
    "wgmma.mma_async.sync.aligned.m64n88k16.f32.bf16.bf16 "
    "{%0, %1, %2, %3, %4, %5, %6, %7, %8, %9, %10, %11, %12, %13, %14, %15, %16, %17, %18, %19, %20, %21, %22, %23, %24, %25, %26, %27, %28, %29, %30, %31, %32, %33, %34, %35, %36, %37, %38, %39, %40, %41, %42, %43}, {%44, %45, %46, %47}, %48, p, 1, 1, 1;\n}\n"
    : "+f"(d[0]), "+f"(d[1]), "+f"(d[2]), "+f"(d[3]), "+f"(d[4]), "+f"(d[5]), "+f"(d[6]), "+f"(d[7]), "+f"(d[8]), "+f"(d[9]), "+f"(d[10]), "+f"(d[11]), "+f"(d[12]), "+f"(d[13]), "+f"(d[14]), "+f"(d[15]), "+f"(d[16]), "+f"(d[17]), "+f"(d[18]), "+f"(d[19]), "+f"(d[20]), "+f"(d[21]), "+f"(d[22]), "+f"(d[23]), "+f"(d[24]), "+f"(d[25]), "+f"(d[26]), "+f"(d[27]), "+f"(d[28]), "+f"(d[29]), "+f"(d[30]), "+f"(d[31]), "+f"(d[32]), "+f"(d[33]), "+f"(d[34]), "+f"(d[35]), "+f"(d[36]), "+f"(d[37]), "+f"(d[38]), "+f"(d[39]), "+f"(d[40]), "+f"(d[41]), "+f"(d[42]), "+f"(d[43])
    : "r"(a[0]), "r"(a[1]), "r"(a[2]), "r"(a[3]), "l"(db), "r"(scale_d));
}
__device__ __forceinline__ void wg_ss80_tb(float* d, uint64_t da, uint64_t db, int scale_d) {
  asm volatile("{\n.reg .pred p;\nsetp.ne.b32 p, %42, 0;\n"
    "wgmma.mma_async.sync.aligned.m64n80k16.f32.bf16.bf16 "
    "{%0, %1, %2, %3, %4, %5, %6, %7, %8, %9, %10, %11, %12, %13, %14, %15, %16, %17, %18, %19, %20, %21, %22, %23, %24, %25, %26, %27, %28, %29, %30, %31, %32, %33, %34, %35, %36, %37, %38, %39}, %40, %41, p, 1, 1, 0, 1;\n}\n"
    : "+f"(d[0]), "+f"(d[1]), "+f"(d[2]), "+f"(d[3]), "+f"(d[4]), "+f"(d[5]), "+f"(d[6]), "+f"(d[7]), "+f"(d[8]), "+f"(d[9]), "+f"(d[10]), "+f"(d[11]), "+f"(d[12]), "+f"(d[13]), "+f"(d[14]), "+f"(d[15]), "+f"(d[16]), "+f"(d[17]), "+f"(d[18]), "+f"(d[19]), "+f"(d[20]), "+f"(d[21]), "+f"(d[22]), "+f"(d[23]), "+f"(d[24]), "+f"(d[25]), "+f"(d[26]), "+f"(d[27]), "+f"(d[28]), "+f"(d[29]), "+f"(d[30]), "+f"(d[31]), "+f"(d[32]), "+f"(d[33]), "+f"(d[34]), "+f"(d[35]), "+f"(d[36]), "+f"(d[37]), "+f"(d[38]), "+f"(d[39])
    : "l"(da), "l"(db), "r"(scale_d));
}
__device__ __forceinline__ void wg_ss48_tt_h(float* d, uint64_t da, uint64_t db, int scale_d) {
  asm volatile("{\n.reg .pred p;\nsetp.ne.b32 p, %26, 0;\n"
    "wgmma.mma_async.sync.aligned.m64n48k16.f32.f16.f16 "
    "{%0, %1, %2, %3, %4, %5, %6, %7, %8, %9, %10, %11, %12, %13, %14, %15, %16, %17, %18, %19, %20, %21, %22, %23}, %24, %25, p, 1, 1, 1, 1;\n}\n"
    : "+f"(d[0]), "+f"(d[1]), "+f"(d[2]), "+f"(d[3]), "+f"(d[4]), "+f"(d[5]), "+f"(d[6]), "+f"(d[7]), "+f"(d[8]), "+f"(d[9]), "+f"(d[10]), "+f"(d[11]), "+f"(d[12]), "+f"(d[13]), "+f"(d[14]), "+f"(d[15]), "+f"(d[16]), "+f"(d[17]), "+f"(d[18]), "+f"(d[19]), "+f"(d[20]), "+f"(d[21]), "+f"(d[22]), "+f"(d[23])
    : "l"(da), "l"(db), "r"(scale_d));
}

struct Params {
  const __nv_bfloat16 *par[4], *logdt, *dskip, *u, *wo;
  CUtensorMap m[M_COUNT];
};

#define CHUNK(i) ((i) == 0 ? c : ((i) == 7 ? (c ^ 1) : (((c & 6) + 1 + (i)) & 7)))
#define FLAG(kind, rr, cc) (&g_flag[((kind) * 128 + (rr) * 8 + (cc)) * 32])
#define SLOT(i) ((i) == 0 || (i) == 5 ? OFF_EXTRA : OFF_BLK + ((i) == 7 ? 0 : (i) == 6 ? 4 : (i) - 1) * BLK)
__device__ __forceinline__ void load_quad(uint32_t* A, uint32_t addr) {
  A[0] = lds32v(addr); A[1] = lds32v(addr + 32); A[2] = lds32v(addr - 32); A[3] = lds32v(addr);
}

__global__ void __launch_bounds__(512, 1) fused_kernel(const __grid_constant__ Params prm) {
  extern __shared__ unsigned char smem_raw[];
  const uint32_t sb = __shfl_sync(0xffffffff, smem_u32(smem_raw), 0);
  const int tid = threadIdx.x, lane = tid & 31;
  const int warp = __shfl_sync(0xffffffff, tid >> 5, 0), wg = warp >> 2, w4 = warp & 3;
  const int cta = blockIdx.x, r = cta >> 3, c = cta & 7;
  if ((sb & 0xffffffu) != SB0) return;
#define BAR(i) (sb + OFF_BAR + 8 * (i))
  const bool sw64 = ((c + 1) & 2) != 0;

  if (wg == 3) {
    if (warp == 13 && elect_one()) {
      #pragma unroll
      for (int i = M_W128; i <= M_U; i++) asm volatile("prefetch.tensormap [%0];" :: "l"(&prm.m[i]) : "memory");
    }
    asm volatile("setmaxnreg.dec.sync.aligned.u32 56;");
    const int tid = rtid(), lane = tid & 31;
    if (warp == 12) {
      if (elect_one()) {
        #pragma unroll
        for (int i = 0; i < 5; i++) mbar_init(BAR(BR_FULL + i), 1);
        asm volatile("fence.mbarrier_init.release.cluster;" ::: "memory");
      }
      {
        const CUtensorMap* mwp = &prm.m[sw64 ? M_W64 : M_W128];
        const int mcol = (c * 80 + (c & 1) * 16) >> (sw64 ? 5 : 6), rcol = c * 80 + ((c & 1) ? 0 : 64);
        uint32_t s = 0, ph = 1, xs = 0;
        #pragma unroll 1
        for (int kb = 0; kb < 20; kb++) {
          if (kb == 1) asm volatile("bar.arrive 0, 512;" ::: "memory");
          if (kb == 3) { bar_sync(6, 128); if (EN_SSM) mbar_wait(BAR(BR_UOUT), 0); }
          if (EN_SSM && kb == 4) mbar_wait(BAR(BR_KS), 0);
          if (kb >= 5) mbar_wait(BAR(BR_EMPTY) + 8 * s, ph);
          if (EN_ATT && elect_one()) {
            const uint32_t st = sb + s * W_SLOT, fb = BAR(BR_FULL) + 8 * s;
            mbar_expect_tx(fb, (kb & 1) ? W_SLOT : W_SLOT + 16384);
            if (!(kb & 1)) tma2d(sb + OFF_X + xs, &prm.m[M_X], fb, kb * 32, r * 128);
            tma4d(st, mwp, fb, 0, kb * 32, mcol, 0);
            tma3d(st + 12288, &prm.m[M_WR], fb, rcol, kb * 32, 0);
          }
          if (kb < 4 && lane == 0) TS(24 + kb);
          if (kb == 14 && elect_one()) asm volatile("cp.async.bulk.prefetch.L2.global [%0], 6400;" :: "l"(prm.wo + cta * 3200) : "memory");
          if (!EN_ATT && kb == 3) break;
          if (++s == 5) { s = 0; ph ^= 1; }
          if (kb & 1) { xs += 16384; if (xs == 49152) xs = 0; }
        }
      }
      if (EN_ATT) {
      mbar_wait(BAR(BR_EPOCH), 0);
      const unsigned epoch = lds32(sb + OFF_EPOCH);
      const unsigned* fo = FLAG(3, r, lane & 7);
      unsigned seen = __ballot_sync(0xffffffff, ld_rlx(lane < 16 ? fo : FLAG(0, lane & 15, c)) == epoch) & 0xffu;
      mbar_wait(BAR(BR_GEMM), 0);
      if (elect_one()) {
        mbar_expect_tx(BAR(BR_WO), 10240);
        tma2d(sb, &prm.m[M_WO], BAR(BR_WO), c * 64, c * 80);
        mbar_expect_tx(BAR(BR_KVP), 61440);
        mbar_expect_tx(BAR(BR_WO + 1), 7 * 10240);
      }
      {
        uint32_t ds = sb + OFF_WOR + (lane >> 3) * 128 + (((lane & 7) ^ (lane >> 3)) << 4);
        #pragma unroll 1
        for (int h = 0; h < 2; h++) {
          const int i = (lane & 6) + h;
          const char* gs = reinterpret_cast<const char*>(prm.wo) + (size_t)((lane >> 3) + CHUNK(i) * 80) * 1280 + 1024 + c * 32 + (lane & 1) * 16;
          #pragma unroll 2
          for (int q = 0; q < 20; q++) {
            asm volatile("cp.async.cg.shared.global [%0], [%1], 16;" :: "r"(ds), "l"(gs) : "memory");
            ds = (ds + 512) ^ 64; gs += 5120;
          }
        }
      }
      mbar_wait(BAR(BR_PUB), 0);
      poll_all(FLAG(0, lane & 15, c), epoch);
      if (elect_one()) { TS(23); bulk_ld(sb + OFF_KVP, &g_kvp[c * 16 * 240], 61440, BAR(BR_KVP)); }
      asm volatile("cp.async.wait_all;" ::: "memory");
      fence_async();
      mbar_arrive(BAR(BR_WO));
      mbar_wait(BAR(BR_SUM), 0);
      if (elect_one()) {
        #pragma unroll 1
        for (int i = 1; i < 8; i++) tma2d(sb + i * 10240, &prm.m[M_WO], BAR(BR_WO + 1), c * 64, CHUNK(i) * 80);
      }
      mbar_wait(BAR(BR_OSTG), 0);
      if (elect_one()) {
        bulk_st(&g_o[cta * 1280], sb + OFF_EXTRA, 20480);
        bulk_commit();
        bulk_wait0();
        st_rlx(FLAG(3, r, c), epoch);
        TS(20);
      }
      __syncwarp();
      #pragma unroll 1
      for (int i = 1; i < 8; i++) {
        const int src = CHUNK(i);
        if (!((seen >> src) & 1)) seen = poll_bit(fo, epoch, 1u << src);
        if (i == 5 || i == 7) mbar_wait(BAR(BR_OEMPTY) + 4 * (i - 5), 0);
        if (EN_SSM && (i == 1 || i == 4)) mbar_wait(BAR(BR_FREE) + 2 * (i & 4), 0);
        if (elect_one()) {
          mbar_expect_tx(BAR(BR_OFULL) + 8 * i, 20480);
          bulk_ld(sb + SLOT(i), &g_o[(r * 8 + src) * 1280], 20480, BAR(BR_OFULL) + 8 * i);
          if (i == 1) TS(21);
          if (i == 7) TS(22);
        }
        __syncwarp();
      }
      if (lane == 0) { DUMP(20, 30); }
      }
    } else {
      const int hw = warp - 13, ht = tid - 416;
      if (hw == 2 && elect_one()) {
        #pragma unroll
        for (int i = 5; i < BR_COUNT; i++) mbar_init(BAR(i), i == BR_WO ? 33 : i < BR_EMPTY ? 1 : i < BR_OEMPTY ? 2 : i < BR_Y ? 8 : i < BR_OSTG ? 128 : 256);
        asm volatile("fence.mbarrier_init.release.cluster;" ::: "memory");
        if (EN_SSM) { mbar_expect_tx(BAR(BR_UIN), 20480); tma2d(sb + OFF_UT, &prm.m[M_U], BAR(BR_UIN), c * 80, r * 128); }
      }
      __syncwarp();
      asm volatile("bar.arrive 0, 512;" ::: "memory");
      const unsigned epoch = hw == 0 ? ld_rlx(&g_epoch[cta]) + 1 : 0;
      bar_sync(6, 128);
      if (hw == 1 && elect_one()) {
        #pragma unroll
        for (int i = M_WO; i < M_COUNT; i++) asm volatile("prefetch.tensormap [%0];" :: "l"(&prm.m[i]) : "memory");
      }
      if (ht == 0) {
        st_rlx(&g_epoch[cta], epoch);
        sts32(sb + OFF_EPOCH, epoch);
        mbar_arrive(BAR(BR_EPOCH));
      }
      if (EN_SSM) {
      const int mi = lane >> 3, rw = lane & 7, ch0 = c * 80 + r * 5;
      mbar_wait(BAR(BR_UIN), 0);
      if (ht == 0) TS(36);
      #pragma unroll 1
      for (int h = 0; h < 2; h++) {
        const uint32_t sa = sb + OFF_UT + h * 10240 + (8 * mi + rw) * 160 + hw * 16, da = sb + OFF_UT + h * 10240 + (hw * 8 + rw) * 128 + ((mi ^ rw) << 4);
        uint32_t v[8][4];
        #pragma unroll
        for (int q = 0; q < 8; q++) if (q < 6 || hw == 0) ldsm4t(v[q], sa + (q & 1) * 5120 + (q >> 1) * 48);
        bar_sync(5, 96);
        #pragma unroll
        for (int q = 0; q < 8; q++) if (q < 6 || hw == 0) stsm4((da ^ ((q & 1) * 64)) + (q >> 1) * 3072, v[q][0], v[q][1], v[q][2], v[q][3]);
      }
      fence_async();
      bar_sync(5, 96);
      if (hw == 0) {
        if (elect_one()) {
          tma2d_st(&prm.m[M_SA], sb + OFF_UT, r * 128, c * 80);
          tma2d_st(&prm.m[M_SA], sb + OFF_UT + 10240, r * 128 + 64, c * 80);
          bulk_commit(); bulk_wait0_read();
          mbar_arrive(BAR(BR_UOUT));
          TS(37);
          bulk_wait0();
          st_rel(FLAG(1, r, c), epoch);
          TS(30);
        }
        __syncwarp();
        poll_all_acq(FLAG(1, lane & 15, c), epoch);
        mbar_wait(BAR(BR_KS + 1), 0);
        if (elect_one()) {
          fence_async_g();
          mbar_expect_tx(BAR(BR_U), 20480);
          #pragma unroll 1
          for (int q = 0; q < 5; q++) tma2d(sb + OFF_BLK + q * BLK, &prm.m[M_SB], BAR(BR_U), 0, (ch0 + q) * 32);
          TS(31);
        }
        __syncwarp();
      }
      if (hw == 0) {
        #pragma unroll 1
        for (int p = 0; p < 2; p++) {
          mbar_wait(BAR(BR_Y) + 8 * p, 0);
          if (elect_one()) {
            #pragma unroll 1
            for (int k = 4 * p; k < 4 + p; k++) tma2d_st(&prm.m[M_SB], sb + OFF_BLK + k * BLK, 0, (640 + ch0 + k) * 32);
            bulk_commit(); bulk_wait0_read();
            mbar_arrive(BAR(BR_FREE) + 8 * p);
          }
          __syncwarp();
        }
        if (elect_one()) {
          mbar_expect_tx(BAR(BR_YIN), 20480);
          bulk_wait0();
          st_rel(FLAG(2, r, c), epoch);
          TS(33);
        }
        __syncwarp();
        poll_all_acq(FLAG(2, lane & 15, c), epoch);
        if (EN_ATT) mbar_wait(BAR(BR_OEMPTY + 3), 0);
        if (elect_one()) {
          fence_async_g();
          tma2d(sb + OFF_BLK + BLK, &prm.m[M_SA], BAR(BR_YIN), r * 128, 640 + c * 80);
          tma2d(sb + OFF_BLK + BLK + 10240, &prm.m[M_SA], BAR(BR_YIN), r * 128 + 64, 640 + c * 80);
          TS(34);
        }
      }
      {
        uint32_t sa = sb + OFF_BLK + BLK + (hw * 8 + rw) * 128 + ((mi ^ rw) << 4);
        uint32_t da = sb + OFF_BLK + 2 * BLK + (8 * mi + rw) * 160 + hw * 16;
        mbar_wait(BAR(BR_YIN), 0);
        #pragma unroll 1
        for (int i = hw; i < 10; i += 3) {
          uint32_t v[4][4];
          #pragma unroll
          for (int q = 0; q < 4; q++) ldsm4t(v[q], (sa ^ ((q & 1) * 64)) + (q >> 1) * 10240);
          #pragma unroll
          for (int q = 0; q < 4; q++) stsm4(da + q * 5120, v[q][0], v[q][1], v[q][2], v[q][3]);
          sa += 3072; da += 48;
        }
      }
      fence_async();
      bar_sync(5, 96);
      if (hw == 0 && elect_one()) {
        tma2d_st(&prm.m[M_OUT], sb + OFF_BLK + 2 * BLK, c * 80, r * 128);
        bulk_commit(); bulk_wait0_read();
        TS(35); DUMP(30, 40); DUMP(0, 1);
      }
      }
    }
  } else {
    const int g = lane >> 2, tq = lane & 3, t7 = tid & 127;
    uint32_t pr[3][2], pd;
    {
      const int ch = c * 80 + r * 5 + wg;
      uint32_t raw[3][4];
      #pragma unroll
      for (int e = 0; e < 4; e++) {
        const __nv_bfloat16* pp = prm.par[e] + ch * 128 + t7;
        #pragma unroll
        for (int q = 0; q < 3; q++) {
          raw[q][e] = 0;
          if (q == 0 || wg == 2) asm volatile("ld.global.nc.u16 %0, [%1];" : "=r"(raw[q][e]) : "l"(pp + q * 128));
        }
      }
      asm volatile("ld.global.nc.u16 %0, [%1];" : "=r"(pd) : "l"(((lane & 4) ? prm.dskip : prm.logdt) + ch + min(lane & 3, 2)));
      asm volatile("setmaxnreg.inc.sync.aligned.u32 152;");
      if (tid == 256) TS(45);
      if (EN_SSM && wg == 2) {
        #pragma unroll 1
        for (int k = 0; k < 5; k++) {
          const uint32_t z = sb + OFF_BLK + k * BLK + t7 * 16;
          sts128(z + B_TBL, 0, 0, 0, 0); sts128(z + B_TBL + 2048, 0, 0, 0, 0);
          if (t7 < 16) sts128(z - 256, 0, 0, 0, 0);
        }
      }
      #pragma unroll
      for (int q = 0; q < 3; q++) {
        #pragma unroll
        for (int e = 0; e < 2; e++) pr[q][e] = raw[q][2 * e] | (raw[q][2 * e + 1] << 16);
        const uint32_t m = __reduce_max_sync(0xffffffff, max(raw[q][2] & 0x7fffu, raw[q][3] & 0x7fffu));
        if (lane == 0) sts32(sb + OFF_EPOCH + 64 + (wg * 3 + q) * 16 + w4 * 4, m);
      }
      bar_sync(2 + wg, 128);
    }
    if (tid == 256) TS(40);
    if (EN_SSM) {
#define P0(w) ((w) == 1 ? OFF_X + 32768 : OFF_BLK + (w) * 3584)
#define P1(w) ((w) == 1 ? 7168 : BLK)
#define P2(w) ((w) == 1 ? OFF_BLK + 4 * BLK - OFF_X - 32768 : 2 * BLK)
      const uint32_t fa = sb + P0(wg) + (lane >> 4) * P1(wg) + (w4 & 1) * P2(wg) + ((lane >> 3) & 1) * 256 + (lane & 7) * 16;
      const uint32_t ea = fa + (w4 >> 1) * 2048, ga = fa + 4096 + (w4 >> 1) * 1536;
      constexpr uint64_t dE = mkdesc(SB0, 128, 512, 0);
      const uint32_t xa = sb + OFF_BLK + 18560 + t7 * 8, xr_ = sb + OFF_BLK + 18560 + (t7 ^ 64) * 8;
      #pragma unroll 1
      for (int it = 0; it < 5; it++) {
        const int k = it < 2 ? 1 - it : it, fs = min(k, 2);
        const uint32_t blk = sb + OFF_BLK + k * BLK;
        if (it == 0 || it >= 3) {
          const int q = it ? it - 2 : 0;
          const uint32_t pa0 = pr[0][0], pc0 = pr[0][1];
          const float dt = bf_round(expf(bf_lo(__shfl_sync(0xffffffff, pd, q))));
          #pragma unroll
          for (int e = 0; e < 2; e++) { pr[0][e] = pr[1][e]; pr[1][e] = pr[2][e]; }
          uint32_t mm[4];
          lds128(mm, sb + OFF_EPOCH + 64 + (wg * 3 + q) * 16);
          const uint32_t ex = min(max(max(max(mm[0], mm[1]), max(mm[2], mm[3])) >> 7, 1u), 253u);
          const float sc = __uint_as_float((254u - ex) << 23);
          if (t7 == 4 + q) sts64(sb + OFF_EPOCH + 16 + (wg + q) * 8, __float_as_uint(2.f * dt * __uint_as_float(ex << 23)), pd << 16);
          const float lr = -bf_round(expf(bf_lo(pa0))) * dt * 1.44269504089f;
          const float tn = bf_hi(pa0) * dt * 0.15915494309f;
          float z1r, z1i, z2r, z2i, z4r, z4i, xr[8], xi[8], gr[8], gi[8], wr[9], wi[9];
          cexp_t(lr, -tn, z1r, z1i);
          cexp_t(lr * 8.f, tn * 8.f, xr[1], xi[1]);
          cexp_t(lr * 64.f, tn * 64.f, wr[0], wi[0]);
          xr[0] = 1.f; xi[0] = 0.f;
          cmul(xr[1], xi[1], xr[1], xi[1], xr[2], xi[2]); cmul(xr[2], xi[2], xr[1], xi[1], xr[3], xi[3]);
          cmul(xr[2], xi[2], xr[2], xi[2], xr[4], xi[4]);
          #pragma unroll
          for (int b = 1; b < 4; b++) cmul(xr[4], xi[4], xr[b], xi[b], xr[4 + b], xi[4 + b]);
          cmul(wr[0], wi[0], wr[0], wi[0], wr[1], wi[1]); cmul(wr[1], wi[1], wr[0], wi[0], wr[2], wi[2]);
          cmul(wr[1], wi[1], wr[1], wi[1], wr[3], wi[3]); cmul(wr[3], wi[3], wr[3], wi[3], wr[4], wi[4]);
          cmul(wr[4], wi[4], wr[3], wi[3], wr[5], wi[5]); cmul(wr[4], wi[4], wr[4], wi[4], wr[6], wi[6]);
          cmul(wr[6], wi[6], wr[4], wi[4], wr[7], wi[7]); cmul(wr[6], wi[6], wr[6], wi[6], wr[8], wi[8]);
          uint32_t R[4], I[4], PR[4], PI[4];
          #pragma unroll
          for (int b = 0; b < 4; b++) { R[b] = packh(xr[2 * b], xr[2 * b + 1]); I[b] = packh(xi[2 * b], xi[2 * b + 1]); }
          sts128(ea, R[0], R[1], R[2], R[3]); sts128(ea + 128, I[0], I[1], I[2], I[3]);
          #pragma unroll
          for (int i = 0; i < 3; i++) {
            const uint32_t z = packh(wr[i], wi[i]);
            #pragma unroll
            for (int b = 0; b < 4; b++) hcm2(R[b], I[b], z, PR[b], PI[b]);
            sts128(ea + (i + 1) * 512, PR[0], PR[1], PR[2], PR[3]); sts128(ea + (i + 1) * 512 + 128, PI[0], PI[1], PI[2], PI[3]);
          }
          gr[0] = bf_lo(pc0) * sc; gi[0] = -bf_hi(pc0) * sc;
          cmul(z1r, z1i, z1r, z1i, z2r, z2i); cmul(z2r, z2i, z2r, z2i, z4r, z4i);
          cmul(gr[0], gi[0], z1r, z1i, gr[1], gi[1]);
          cmul(gr[0], gi[0], z2r, z2i, gr[2], gi[2]); cmul(gr[1], gi[1], z2r, z2i, gr[3], gi[3]);
          #pragma unroll
          for (int b = 0; b < 4; b++) cmul(gr[b], gi[b], z4r, z4i, gr[4 + b], gi[4 + b]);
          sts128(ga, packh(gr[0], gr[1]), packh(gr[2], gr[3]), packh(gr[4], gr[5]), packh(gr[6], gr[7]));
          sts128(ga + 128, packh(gi[0], gi[1]), packh(gi[2], gi[3]), packh(gi[4], gi[5]), packh(gi[6], gi[7]));
          {
            const uint32_t z = packh(wr[3], -wi[3]), a4r = packh(gr[0], gr[4]), a4i = packh(gi[0], gi[4]);
            hcm2(packh(gr[0], gr[2]), packh(gi[0], gi[2]), z, PR[0], PI[0]);
            hcm2(packh(gr[4], gr[6]), packh(gi[4], gi[6]), z, PR[1], PI[1]);
            hcm2(a4r, a4i, packh(wr[4], -wi[4]), PR[2], PI[2]);
            hcm2(a4r, a4i, packh(wr[5], -wi[5]), PR[3], PI[3]);
            sts128(ga + 512, PR[0], PR[1], PR[2], PR[3]); sts128(ga + 512 + 128, PI[0], PI[1], PI[2], PI[3]);
            float hr, hi_;
            cmul(gr[0], gi[0], wr[3], -wi[3], hr, hi_);
            const uint32_t cr = packh(gr[0], hr), ci = packh(gi[0], hi_);
            #pragma unroll
            for (int i = 0; i < 3; i++) hcm2(cr, ci, packh(wr[6 + i], -wi[6 + i]), PR[i], PI[i]);
            sts128(ga + 1024, PR[0], PR[1], PR[2], 0u); sts128(ga + 1024 + 128, PI[0], PI[1], PI[2], 0u);
          }
          if (t7 == 0 && k == KST) TS(48);
          fence_async();
          bar_sync(it ? 4 : 0, it ? 128 : 512);
          if (wg < 2) break;
        }
        if (t7 == 0 && k == KST) TS(50);
        uint32_t fd[2];
        lds64(fd, sb + OFF_EPOCH + 16 + k * 8);
        const float fac = __uint_as_float(fd[0]), dsk = __uint_as_float(fd[1]);
        float ka[24]; zero<24>(ka);
        wg_fence();
        #pragma unroll
        for (int s = 0; s < 8; s++) {
          const uint32_t lo = (uint32_t)dE + ((P0(fs) + ((s >> 1) & 1) * P1(fs) + (s >> 2) * P2(fs)) >> 4) + (s & 1) * 16;
          wg_ss48_tt_h(ka, desc2(lo, dE >> 32), desc2(lo + 256, dE >> 32), s != 0);
        }
        wg_commit();
        wg_wait<0>();
        pin<24>(ka);
        if (t7 == 0 && k == KST) TS(51);
        float kk[6];
        {
          const bool up = w4 >= 2;
          #pragma unroll
          for (int n = 0; n < 3; n++) {
            sts64f(xa + n * BLK, up ? ka[12 + 4 * n] : ka[4 * n + 2], up ? ka[13 + 4 * n] : ka[4 * n + 3]);
            kk[2 * n] = up ? ka[14 + 4 * n] : ka[4 * n]; kk[2 * n + 1] = up ? ka[15 + 4 * n] : ka[4 * n + 1];
          }
          bar_sync(4, 128);
          if (t7 == 0) mbar_arrive(BAR(BR_KS) + 8 * it);
          #pragma unroll
          for (int n = 0; n < 3; n++) {
            uint32_t o[2]; lds64(o, xr_ + n * BLK);
            kk[2 * n] = (kk[2 * n] + __uint_as_float(o[0])) * fac; kk[2 * n + 1] = (kk[2 * n + 1] + __uint_as_float(o[1])) * fac;
          }
        }
        if (t7 == 0 && k == KST) TS(52);
        {
          const int j = (w4 & 1) * 16 + (w4 >> 1) * 8 + g;
          const uint32_t tb = blk + B_TBL;
          if (t7 == 0) kk[0] += dsk;
          const uint32_t pa_ = tb + (16 + 8 * j + 2 * tq) * 4;
          const uint32_t v = pack2(kk[1], kk[0]);
          sts32(pa_ + 4, v); sts16(pa_, v >> 16); sts16(pa_ + 10, v);
          const uint32_t u = pack2(kk[2], kk[3]), w = pack2(kk[4], kk[5]);
          if (tq < 2) {
            const uint32_t pb = tb + (16 + 256 + 8 * j + 4 * tq) * 4;
            sts16(pb, u); sts32(pb + 4, __byte_perm(u, 0, 0x1010)); sts32(pb + 8, __byte_perm(u, 0, 0x1032)); sts16(pb + 14, u >> 16);
            if (j | tq) { sts16(pb - 4, u); sts16(pb + 2, u); }
            const int i = 64 * tq + j;
            const uint32_t e0 = tb + (T_F3 + (((i - 1) & 1) ? 80 : 0) + ((i - 1) >> 1)) * 4, e1 = i ? e0 : tb + (T_F2 + 144 + 31) * 4;
            sts16(e1, w); sts16(e1 + 6, w); sts16(e0 + 64, w >> 16); sts16(e0 + 70, w >> 16);
            if (i == 0) { sts16(tb + (T_S + 3) * 4, w); sts32(tb + (T_S + 4) * 4, __byte_perm(w, 0, 0x1010)); sts16(tb + (T_S + 5) * 4 + 2, w); }
          } else {
            const int i = 32 * (tq - 2) + j;
            const uint32_t e1 = tb + (i ? T_F2 + ((2 * i - 1) & 3) * 48 + ((2 * i - 1) >> 2) : 16 + 511) * 4;
            const uint32_t e2 = tb + (T_F2 + (i & 1) * 96 + (i >> 1)) * 4;
            sts16(e1, u); sts16(e1 + 6, u); sts16(e2, u >> 16); sts16(e2 + 6, u >> 16);
            if (i == 0) {
              const uint32_t uu = __byte_perm(u, 0, 0x1010);
              sts32(tb + 528 * 4, uu); sts32(tb + 529 * 4, uu); sts32(tb + 530 * 4, uu); sts16(tb + 531 * 4 + 2, u);
              sts16(tb + (T_F3 + 80 + 63) * 4, w);
            }
          }
        }
        if (it < 2) bar_sync(4, 128);
        if (t7 == 0 && k == KST) TS(53);
      }
    }
    if (!EN_SSM) bar_sync(0, 512);
    if (tid == 0) TS(14);
  if (wg < 2) {
    if (!EN_ATT) {
    if (EN_SSM) {
      mbar_wait(BAR(BR_U), 0);
      mbar_wait(BAR(BR_KS + 4), 0);
      if (tid == 0) TS(16);
      #pragma unroll 1
      for (int q6 = warp; q6 < 30; q6 += 8) {
        {
          const int k = q6 / 6, kap = (q6 - 6 * k) * 32 + lane;
          const uint32_t blk = sb + OFF_BLK + k * BLK;
          float P[33];
          P[0] = 0.f;
          #pragma unroll
          for (int q = 0; q < 4; q++) {
            const int ch = kap - 3 + q;
            uint32_t v[4];
            lds128(v, blk + (uint32_t)((ch * 16) ^ ((ch * 2) & 0x70)));
            #pragma unroll
            for (int e = 0; e < 4; e++) {
              P[q * 8 + 2 * e + 1] = (q == 0 && e < 2) ? 0.f : P[q * 8 + 2 * e] + bf_lo(v[e]);
              P[q * 8 + 2 * e + 2] = (q == 0 && e < 2) ? 0.f : P[q * 8 + 2 * e + 1] + bf_hi(v[e]);
            }
          }
#define WIN(lo, hi, e) (P[25 + (e) - (lo)] - P[24 + (e) - (hi)])
#define WIN8(lo, hi) pack2(WIN(lo, hi, 0), WIN(lo, hi, 1)), pack2(WIN(lo, hi, 2), WIN(lo, hi, 3)), pack2(WIN(lo, hi, 4), WIN(lo, hi, 5)), pack2(WIN(lo, hi, 6), WIN(lo, hi, 7))
          const uint32_t o2 = blk + B_D + (kap & 1) * 1552 + (kap >> 1) * 16;
          sts128(o2, WIN8(3, 5));
          sts128(o2 + B_D5, WIN8(6, 10));
          if (kap < 128) {
            const uint32_t o = blk + B_D + (kap & 1) * 1024 + (kap >> 1) * 16;
            sts128(o + B_D7, WIN8(5, 11));
            sts128(o + B_D9, WIN8(12, 20));
          }
        }
      }
      if (tid < 10) sts128(sb + OFF_BLK + (tid >> 1) * BLK + B_D + (tid & 1) * B_D5 + 1536, 0, 0, 0, 0);
      mbar_arrive(BAR(BR_DRDY));
      if (tid == 0) TS(12);
    }
    }
    if (EN_ATT) {
    float am[96], ar[24];
    {
      const bool lead = (rtid() & 127) == 0;
      constexpr uint64_t da0 = mkdesc(SB0 + OFF_X, 16, 1024, 1), dr0 = mkdesc(SB0 + 12288, 1024, 256, 3);
      const uint64_t db0 = sw64 ? mkdesc(SB0, 2048, 512, 2) : mkdesc(SB0, 4096, 1024, 1);
      const uint32_t kst = sw64 ? 64 : 128, bh = db0 >> 32;
      uint32_t s = 0, ph = 0, xo = 0;
      #pragma unroll 1
      for (int kb = 0; kb < 20; kb++) {
        const uint32_t wo_ = s * (W_SLOT >> 4), al = (uint32_t)da0 + wg * 512 + xo, bl = (uint32_t)db0 + wo_, rl = (uint32_t)dr0 + wo_;
        mbar_wait(BAR(BR_FULL) + 8 * s, ph);
        if (kb == 0 && lead && wg == 0) TS(1);
        wg_fence();
        wg_ss192_tb(am, desc2(al, da0 >> 32), desc2(bl, bh), kb != 0);
        wg_ss48_tb(ar, desc2(al, da0 >> 32), desc2(rl, dr0 >> 32), kb != 0);
        wg_ss192_tb(am, desc2(al + 2, da0 >> 32), desc2(bl + kst, bh), 1);
        wg_ss48_tb(ar, desc2(al + 2, da0 >> 32), desc2(rl + 32, dr0 >> 32), 1);
        wg_commit();
        wg_wait<1>();
        if (lead && kb > 0 && kb < 16) mbar_arrive(BAR(BR_EMPTY) + 8 * (s == 0 ? 4 : s - 1));
        if (++s == 5) { s = 0; ph ^= 1; }
        xo += (kb & 1) ? 1020 : 4;
        if (xo == 3072) xo = 0;
      }
      wg_wait<0>();
      pin<96>(am); pin<24>(ar);
    }
    const int tid = rtid(), lane = tid & 31, tq = lane & 3;
    if (tid == 0) TS(2);
#define QV(j, e) ((j) < 8 ? am[4 * (j) + (e)] : ar[4 * ((j) - 8) + (e)])
#define KV_(j, e) ((j) < 8 ? am[32 + 4 * (j) + (e)] : ar[8 + 4 * ((j) - 8) + (e)])
#define VV(j, e) ((j) < 8 ? am[64 + 4 * (j) + (e)] : ar[16 + 4 * ((j) - 8) + (e)])
    {
      bar_sync(1, 256);
      if (tid == 0) mbar_arrive(BAR(BR_GEMM));
      const uint32_t ro = sb + (uint32_t)((warp * 16 + (lane & 15)) * 16);
      const int l0 = 2 * (c & 1) + (lane >> 4);
      const uint32_t ones = (tq == 0) ? 0x00003f80u : 0u;
#define PV(j) pack2(VV(j, 0), VV(j, 1)), pack2(VV(j, 2), VV(j, 3))
#define PK(j) pack2(phi(KV_(j, 0)), phi(KV_(j, 1))), pack2(phi(KV_(j, 2)), phi(KV_(j, 3)))
      stsm4(ro + OFF_V + (5 + 6 * (lane >> 4)) * 2048, ones, ones, ones, ones);
      #pragma unroll
      for (int j = 0; j < 10; j += 2) {
        const int l = (j == 8 && (c & 1)) ? l0 - 2 : l0 + j;
        stsm4(ro + OFF_V + (l + (l >= 5)) * 2048, PV(j), PV(j + 1));
        stsm4(ro + OFF_PK + l * 2048, PK(j), PK(j + 1));
      }
    }
    fence_async();
    bar_sync(1, 256);
    if (tid == 0) TS(3);
    mbar_wait(BAR(BR_EPOCH), 0);
    const unsigned epoch = lds32(sb + OFF_EPOCH);
    {
      float kv[24]; zero<24>(kv);
      constexpr uint64_t da = mkdesc(SB0 + OFF_PK, 128, 2048, 0), db = mkdesc(SB0 + OFF_V, 128, 2048, 0);
      wg_fence();
      #pragma unroll
      for (int s = 0; s < 8; s++) wg_ss48_tt(kv, desc2((uint32_t)da + wg * 640 + s * 16, da >> 32), desc2((uint32_t)db + wg * 768 + s * 16, db >> 32), s != 0);
      wg_commit();
      wg_wait<0>();
      pin<24>(kv);
      if (tid == 0) TS(15);
      if (w4 < 3) {
        const uint32_t wb = sb + OFF_KVS + (wg * 3 + w4) * 1536 + (lane & 15) * 96;
        #pragma unroll
        for (int j = 0; j < 6; j += 2)
          stsm4(wb + (j + (lane >> 4)) * 16, pack2(kv[4 * j], kv[4 * j + 1]), pack2(kv[4 * j + 2], kv[4 * j + 3]),
                pack2(kv[4 * j + 4], kv[4 * j + 5]), pack2(kv[4 * j + 6], kv[4 * j + 7]));
        __syncwarp();
        const int dl = w4 * 16 + (lane & 15), hl = dl >= 20;
        if (dl < 40) {
          uint4* dst = &g_kvp[(c * 16 + r) * 240 + wg * 40 + dl];
          uint32_t v[4], z[4];
          lds128(v, wb + (3 * hl + (lane >> 4)) * 16);
          lds64(z, wb + 32 + 8 * hl); z[2] = lds32(wb + 80); z[3] = epoch & 1u;
          v[3] = (v[3] & ~1u) | z[3];
          st128_rlx(dst + (lane >> 4) * 80, v);
          if (lane < 16) st128_rlx(dst + 160, z);
        }
      }
    }
    fence_async();
    bar_sync(1, 256);
    if (tid == 0) { st_rlx(FLAG(0, r, c), epoch); mbar_arrive(BAR(BR_PUB)); TS(4); }
    const int kvi = (tid >= 80) + (tid >= 160) + (tid >= 240), kd = tid - 80 * kvi;
    const int khd = kd / 20, kt0 = 5 * (khd >> 1) + 2 * (khd & 1);
    const uint32_t rb = sb + OFF_KVB + kd * 16;
    if (kvi < 3) {
      #pragma unroll 1
      for (int m = kvi; m < 7; m += 3) { const int q = kt0 + 3 + m; sts128(rb + (q >= 10 ? q - 10 : q) * 1280, 0, 0, 0, 0); }
    }
    uint32_t qa[20];
    {
      const float sc = 1.44269504089f + __uint_as_float(lds32(sb + OFF_EPOCH) ^ epoch);
      #pragma unroll
      for (int j = 0; j < 10; j++) { qa[2 * j] = pack2(phi(QV(j, 0), sc), phi(QV(j, 1), sc)); qa[2 * j + 1] = pack2(phi(QV(j, 2), sc), phi(QV(j, 3), sc)); }
    }
    if (tid == 0) TS(5);
    if (EN_SSM) {
      mbar_wait(BAR(BR_U), 0);
      mbar_wait(BAR(BR_KS + 4), 0);
      if (tid == 0) TS(16);
      #pragma unroll 1
      for (int q6 = warp; q6 < 30; q6 += 8) {
        {
          const int k = q6 / 6, kap = (q6 - 6 * k) * 32 + lane;
          const uint32_t blk = sb + OFF_BLK + k * BLK;
          float P[33];
          P[0] = 0.f;
          #pragma unroll
          for (int q = 0; q < 4; q++) {
            const int ch = kap - 3 + q;
            uint32_t v[4];
            lds128(v, blk + (uint32_t)((ch * 16) ^ ((ch * 2) & 0x70)));
            #pragma unroll
            for (int e = 0; e < 4; e++) {
              P[q * 8 + 2 * e + 1] = (q == 0 && e < 2) ? 0.f : P[q * 8 + 2 * e] + bf_lo(v[e]);
              P[q * 8 + 2 * e + 2] = (q == 0 && e < 2) ? 0.f : P[q * 8 + 2 * e + 1] + bf_hi(v[e]);
            }
          }
#define WIN(lo, hi, e) (P[25 + (e) - (lo)] - P[24 + (e) - (hi)])
#define WIN8(lo, hi) pack2(WIN(lo, hi, 0), WIN(lo, hi, 1)), pack2(WIN(lo, hi, 2), WIN(lo, hi, 3)), pack2(WIN(lo, hi, 4), WIN(lo, hi, 5)), pack2(WIN(lo, hi, 6), WIN(lo, hi, 7))
          const uint32_t o2 = blk + B_D + (kap & 1) * 1552 + (kap >> 1) * 16;
          sts128(o2, WIN8(3, 5));
          sts128(o2 + B_D5, WIN8(6, 10));
          if (kap < 128) {
            const uint32_t o = blk + B_D + (kap & 1) * 1024 + (kap >> 1) * 16;
            sts128(o + B_D7, WIN8(5, 11));
            sts128(o + B_D9, WIN8(12, 20));
          }
        }
      }
      if (tid < 10) sts128(sb + OFF_BLK + (tid >> 1) * BLK + B_D + (tid & 1) * B_D5 + 1536, 0, 0, 0, 0);
      mbar_arrive(BAR(BR_DRDY));
      if (tid == 0) TS(12);
    }
    mbar_wait(BAR(BR_KVP), 0);
    if (tid == 0) TS(6);
    if (kvi < 3) {
      float s[8];
      zero<8>(s);
      uint32_t bad = 0;
      #pragma unroll 4
      for (int i = 0; i < 16; i++) {
        uint32_t w[4];
        lds128(w, sb + OFF_KVP + tid * 16 + i * 3840);
        bad |= w[3] ^ epoch;
        #pragma unroll
        for (int e = 0; e < 4; e++) { s[2 * e] += bf_lo(w[e]); s[2 * e + 1] += bf_hi(w[e]); }
      }
      if (__builtin_expect(bad & 1u, 0)) {
        zero<8>(s);
        #pragma unroll 1
        for (int i = 0; i < 16; i++) {
          uint32_t w[4] = {0, 0, 0, ~epoch};
          fix128_w3(w, &g_kvp[(c * 16 + i) * 240 + tid], epoch, 1u);
          #pragma unroll
          for (int e = 0; e < 4; e++) { s[2 * e] += bf_lo(w[e]); s[2 * e + 1] += bf_hi(w[e]); }
        }
        FIXCNT
      }
      const uint32_t p0 = pack2(s[0], s[1]), p1 = pack2(s[2], s[3]), p2 = pack2(s[4], s[5]), p3 = pack2(s[6], s[7]);
      if (kvi < 2) sts128(rb + (kt0 + (khd & 1) + kvi) * 1280, p0, p1, p2, p3);
      else {
        const bool od = khd & 1;
        sts128(rb + (5 * (khd >> 1) + 2) * 1280, od ? 0u : p0, od ? 0u : p1, od ? p0 : 0u, od ? p1 : 0u);
        const uint32_t zz = (p2 & 0xffffu) << (16 * (khd & 1));
        sts128(rb + 10 * 1280, khd < 2 ? zz : 0u, khd < 2 ? 0u : zz, 0u, 0u);
      }
    }
    fence_async();
    bar_sync(1, 256);
    if (tid == 0) { mbar_arrive(BAR(BR_SUM)); TS(7); }
    {
      float oa[44]; zero<44>(oa);
      constexpr uint64_t db = mkdesc(SB0 + OFF_KVB, 128, 1280, 0);
      wg_fence();
      #pragma unroll
      for (int s = 0; s < 5; s++) wg_rs88_tb(oa, &qa[4 * s], desc2((uint32_t)db + ((s == 4 && (c & 1)) ? 0 : (s + (c & 1)) * 16), db >> 32), s != 0);
      wg_commit();
      wg_wait<0>();
      pin<44>(oa);
      if (tid == 0) TS(13);
      float rc[4], rd[2][4];
      #pragma unroll
      for (int e = 0; e < 4; e++) asm("rcp.approx.ftz.f32 %0, %1;" : "=f"(rc[e]) : "f"(oa[40 + e] + 1e-6f));
      #pragma unroll
      for (int h = 0; h < 4; h++) {
        rd[0][h] = __shfl_sync(0xffffffff, rc[h & 1], (lane & 28) | (h >> 1));
        rd[1][h] = __shfl_sync(0xffffffff, rc[2 + (h & 1)], (lane & 28) | (h >> 1));
      }
      #pragma unroll
      for (int j = 0; j < 10; j++) {
        #pragma unroll
        for (int h = 0; h < 2; h++) {
          float f;
          if (j == 2) f = tq < 2 ? rd[h][0] : rd[h][1];
          else if (j == 7) f = tq < 2 ? rd[h][2] : rd[h][3];
          else f = rd[h][(8 * j) / 20];
          qa[2 * j + h] = pack2(oa[4 * j + 2 * h] * f, oa[4 * j + 2 * h + 1] * f);
        }
      }
      const uint32_t m0 = (lane & 7) == ((2 * w4) & 7), m1 = (lane & 7) == 2 * w4 + 1;
      const uint32_t oa_ = sb + OFF_EXTRA + (lane >> 4) * 2048 + (warp * 16 + (lane & 15)) * 16;
      bar_sync(1, 256);
#define TAG(v, m) (((v) & ~(m)) | (epoch & (m)))
      #pragma unroll
      for (int s = 0; s < 5; s++) stsm4(oa_ + s * 4096, TAG(qa[4 * s], m0), TAG(qa[4 * s + 1], m1), TAG(qa[4 * s + 2], m0), TAG(qa[4 * s + 3], m1));
    }
    fence_async();
    mbar_arrive(BAR(BR_OSTG));
    if (tid == 0) TS(8);
    float oc[40]; zero<40>(oc);
    {
      constexpr uint64_t dw0 = mkdesc(SB0, OFF_WOR, 1024, 1), da0 = mkdesc(SB0, 2048, 128, 0);
      const uint32_t ck = sb + tid * 32 + ((lane >> 2) << 2), ck2 = ck + (wg ? 0 : 16384);
      uint32_t bad = 0;
      auto tile = [&](int i, uint32_t so) {
        const uint32_t al = (uint32_t)da0 + wg * 64 + (so >> 4), wl = (uint32_t)dw0 + i * 640 - (i >> 1) * (1278 << 16);
        wg_fence();
        #pragma unroll
        for (int s = 0; s < 5; s++) wg_ss80_tb(oc, desc2(al + s * 256, da0 >> 32), desc2(wl + s * 128, dw0 >> 32), (i | s) != 0);
        wg_commit();
        bad |= (lds32(ck + so) ^ epoch) | (lds32(ck + so + 8192) ^ epoch) | (lds32(ck2 + so) ^ epoch);
      };
      mbar_wait(BAR(BR_WO), 0);
      mbar_wait(BAR(BR_OSTG), 0);
      tile(0, SLOT(0));
      mbar_wait(BAR(BR_WO + 1), 0);
      #pragma unroll 1
      for (int i = 1; i < 8; i++) {
        if (i == 1) { wg_wait<0>(); if (lane == 0) mbar_arrive(BAR(BR_OEMPTY)); }
        mbar_wait(BAR(BR_OFULL) + 8 * i, 0);
        if (i == 1 && tid == 0) TS(9);
        tile(i, SLOT(i));
        wg_wait<1>();
        if (lane == 0 && i > 1) mbar_arrive(BAR(BR_OEMPTY - 1) + 8 * i);
      }
      #pragma unroll 1
      for (int n = 0; n < 56; n++) {
        const int i = n & 7;
        if (i == 0) {
          uint32_t any;
          asm volatile("{\n.reg .pred p;\nsetp.ne.u32 p, %1, 0;\nbarrier.red.or.pred p, 1, 256, p;\nselp.u32 %0, 1, 0, p;\n}" : "=r"(any) : "r"(bad & 1u) : "memory");
          if (!any) break;
          bad = 0;
          FIXCNT
        }
        wg_wait<0>();
        bar_sync(1, 256);
        if (tid == 0) { mbar_expect_tx(BAR(BR_RETRY), 20480); bulk_ld(sb + SLOT(0), &g_o[(r * 8 + CHUNK(i)) * 1280], 20480, BAR(BR_RETRY)); }
        mbar_wait(BAR(BR_RETRY), n & 1);
        tile(i, SLOT(0));
      }
      wg_wait<0>();
      pin<40>(oc);
    }
    if (tid == 0) TS(10);
    {
      const int row = w4 * 16 + (lane & 15);
      const uint32_t ob = sb + SLOT(4) + wg * 10240;
      #pragma unroll
      for (int j = 0; j < 8; j += 2)
        stsm4(ob + row * 128 + (((j + (lane >> 4)) ^ (row & 7)) << 4), pack2(oc[4 * j], oc[4 * j + 1]), pack2(oc[4 * j + 2], oc[4 * j + 3]),
              pack2(oc[4 * j + 4], oc[4 * j + 5]), pack2(oc[4 * j + 6], oc[4 * j + 7]));
      stsm4(ob + 8192 + row * 32 + (lane >> 4) * 16, pack2(oc[32], oc[33]), pack2(oc[34], oc[35]), pack2(oc[36], oc[37]), pack2(oc[38], oc[39]));
      fence_async();
      bar_sync(2 + wg, 128);
      if (w4 == 0 && elect_one()) {
        tma2d_st(&prm.m[M_O64], ob, 640 + c * 64, r * 128 + wg * 64);
        tma2d_st(&prm.m[M_O16], ob + 8192, 1152 + c * 16, r * 128 + wg * 64);
        bulk_commit(); bulk_wait0_read();
        if (wg == 0) { TS(11); DUMP(0, 20); }
      }
    }
    }
  } else {
    if (EN_SSM) {
    const int tid = rtid(), lane = tid & 31, g = lane >> 2, tq = lane & 3, t7 = tid & 127;
    if (t7 == 0) TS(41);
    mbar_wait(BAR(BR_U), 0);
    bar_sync(4, 128);
    if (EN_ATT) mbar_wait(BAR(BR_GEMM), 0);
    if (t7 == 0) TS(42);
    #pragma unroll 1
    for (int pass = 1; pass >= 0; pass--) {
      const int k = pass ? w4 : 4;
      const uint32_t blk = sb + OFF_BLK + k * BLK, tb = blk + B_TBL + (uint32_t)((g - 2 * tq) * 4);
      float acc[16][4];
      zero<64>(&acc[0][0]);
      const int kl = 16 * (lane >> 4) + 2 * (lane & 7) + ((lane >> 3) & 1);
      {
        auto ubase = [&](int sh) { const int q = kl - 2 * sh; return blk + (uint32_t)((q * 16) ^ ((q * 2) & 0x70)); };
#define LDQ(A, sh) _Pragma("unroll") for (int m = 0; m < 4; m++) load_quad(A[m], tb + (16 + 16 * (sh) + 128 * m) * 4);
#define LDB(B, ub, h) _Pragma("unroll") for (int p = 0; p < 4; p++) ldsm4(B[p], ((ub) ^ ((p & 1) * 64)) + (4 * (h) + p) * 512);
#define MLO(A, B) _Pragma("unroll") for (int m = 0; m < 4; m++) _Pragma("unroll") for (int cc = 0; cc < 8; cc++) mma16816(acc[cc + m], A[m], &B[cc >> 1][(cc & 1) * 2]);
#define MHI(A, B) _Pragma("unroll") for (int m = 0; m < 4; m++) _Pragma("unroll") for (int cc = 0; cc < 8 - m; cc++) mma16816(acc[8 + cc + m], A[m], &B[cc >> 1][(cc & 1) * 2]);
        int p_ = pass ? 0 : w4;
        const int pe = pass ? 4 : w4 + 1;
        uint32_t A[4][4], A2[4][4], Bl[4][4], Bh[4][4];
        uint32_t ub = ubase(p_ + 4);
        LDQ(A, p_ + 4) LDB(Bl, ub, 0)
        #pragma unroll 1
        for (; p_ < pe; p_++) {
          LDB(Bh, ub, 1)
          MLO(A, Bl)
          ub = ubase(p_);
          LDQ(A2, p_) LDB(Bl, ub, 0)
          MHI(A, Bh)
          LDB(Bh, ub, 1)
          load_quad(A[0], tb + (16 + 512 + 16 * (p_ & 1)) * 4); load_quad(A[1], tb + (T_S + 16 * (p_ & 1)) * 4);
          MLO(A2, Bl)
          if (p_ < 2) {
            #pragma unroll
            for (int cc = 0; cc < 8; cc++) mma16816(acc[cc + 4], A[0], &Bl[cc >> 1][(cc & 1) * 2]);
            #pragma unroll
            for (int cc = 0; cc < 4; cc++) mma16816(acc[cc + 12], A[0], &Bh[cc >> 1][(cc & 1) * 2]);
            #pragma unroll
            for (int cc = 0; cc < 8; cc++) mma16816(acc[cc + 8], A[1], &Bl[cc >> 1][(cc & 1) * 2]);
          }
          const int pn = ((p_ + 1) & 3) + 4;
          ub = ubase(pn);
          LDQ(A, pn) LDB(Bl, ub, 0)
          MHI(A2, Bh)
        }
      }
      if (t7 == 0) TS(57 + 3 * pass);
      mbar_wait(BAR(BR_DRDY), 0);
      {
        const int ih = (lane >> 3) & 1;
        const uint32_t dl = blk + B_D + (uint32_t)(((lane >> 4) * 8 + (lane & 7)) * 16);
        const uint32_t d0_ = dl + ih * 1552, d8_ = dl + (ih ? 0 : 1536), d3_ = dl + B_D7 + ih * 1024;
        auto cls2 = [&](uint32_t da, uint32_t ta) {
          uint32_t B[6][2], A[6][4];
          #pragma unroll
          for (int e = 0; e < 6; e++) { B[e][0] = lds32v(ta + (e + 4) * 32); B[e][1] = lds32v(ta + (e + 3) * 32); }
          #pragma unroll
          for (int kk = 0; kk < 6; kk++) ldsm4t(A[kk], da + kk * 256);
          #pragma unroll
          for (int e = 0; e < 6; e++)
            #pragma unroll
            for (int kk = 0; kk < 6; kk++) if (2 * kk + e + 4 < 16) mma16816(acc[2 * kk + e + 4], A[kk], B[e]);
        };
        auto cls3 = [&](uint32_t da, uint32_t ta) {
          uint32_t B[8][2], A[4][4];
          #pragma unroll
          for (int e = 0; e < 8; e++) { B[e][0] = lds32v(ta + (e + 8) * 32); B[e][1] = lds32v(ta + (e + 7) * 32); }
          #pragma unroll
          for (int kk = 0; kk < 4; kk++) ldsm4t(A[kk], da + kk * 256);
          #pragma unroll
          for (int kk = 0; kk < 4; kk++)
            #pragma unroll
            for (int e = 0; e < 8; e++) if (2 * kk + e + 8 < 16) mma16816(acc[2 * kk + e + 8], A[kk], B[e]);
        };
        #pragma unroll 1
        for (int a = pass ? 0 : w4; a < (pass ? 4 : w4 + 1); a++) cls2(((a & 2) ? d8_ : d0_) + (a & 1) * B_D5, tb + (T_F2 + 48 * a - 32) * 4);
        #pragma unroll 1
        for (int b = pass ? 0 : (w4 & 1); b < (pass ? 2 : w4 - 1); b++) cls3(d3_ + b * 2048, tb + (T_F3 + 80 * b - 64) * 4);
      }
      if (t7 == 0) TS(58 + 3 * pass);
      const uint32_t ya = blk + (uint32_t)((kl * 16) ^ ((kl * 2) & 0x70));
#define STY(p) stsm4t((ya ^ (((p) & 1) * 64)) + (p) * 512, pack2(acc[2 * (p)][0], acc[2 * (p)][1]), pack2(acc[2 * (p)][2], acc[2 * (p)][3]), \
                      pack2(acc[2 * (p) + 1][0], acc[2 * (p) + 1][1]), pack2(acc[2 * (p) + 1][2], acc[2 * (p) + 1][3]))
      if (pass == 0) {
        const uint32_t xw = blk + 4096 + w4 * 4096 + lane * 16, xr = blk + 4096 + w4 * 1024 + lane * 16;
        #pragma unroll
        for (int h = 0; h < 2; h++) {
          bar_sync(4, 128);
          #pragma unroll
          for (int i = 0; i < 8; i++)
            sts128(xw + i * 512, __float_as_uint(acc[8 * h + i][0]), __float_as_uint(acc[8 * h + i][1]), __float_as_uint(acc[8 * h + i][2]), __float_as_uint(acc[8 * h + i][3]));
          bar_sync(4, 128);
          float y[8];
          #pragma unroll
          for (int i = 0; i < 8; i++) {
            uint32_t o[4]; lds128(o, xr + (i >> 1) * 4096 + (i & 1) * 512);
            #pragma unroll
            for (int e = 0; e < 4; e++) y[4 * (i & 1) + e] = i < 2 ? __uint_as_float(o[e]) : y[4 * (i & 1) + e] + __uint_as_float(o[e]);
          }
          stsm4t((ya ^ ((w4 & 1) * 64)) + (4 * h + w4) * 512, pack2(y[0], y[1]), pack2(y[2], y[3]), pack2(y[4], y[5]), pack2(y[6], y[7]));
        }
      } else {
        __syncwarp();
        #pragma unroll
        for (int p = 0; p < 8; p++) STY(p);
      }
      if (t7 == 0 && !pass) TS(55);
      fence_async();
      mbar_arrive(BAR(BR_Y + 1) - 8 * pass);
      if (t7 == 0) TS(59 + 3 * pass);
    }
    if (t7 == 0) DUMP(40, 64);
    }
  }
  }
}

typedef CUresult (*EncFn)(CUtensorMap*, CUtensorMapDataType, cuuint32_t, void*, const cuuint64_t*, const cuuint64_t*, const cuuint32_t*,
                          const cuuint32_t*, CUtensorMapInterleave, CUtensorMapSwizzle, CUtensorMapL2promotion, CUtensorMapFloatOOBfill);
static void mkmap(EncFn enc, CUtensorMap* m, const void* base, int rank, const cuuint64_t* dims, const cuuint64_t* strides, const cuuint32_t* box, CUtensorMapSwizzle swz) {
  cuuint32_t es[5] = {1, 1, 1, 1, 1};
  enc(m, CU_TENSOR_MAP_DATA_TYPE_BFLOAT16, rank, const_cast<void*>(base), dims, strides, box, es, CU_TENSOR_MAP_INTERLEAVE_NONE, swz,
      CU_TENSOR_MAP_L2_PROMOTION_L2_128B, CU_TENSOR_MAP_FLOAT_OOB_FILL_NONE);
}

extern "C" void kernel_launch(void* const* d_in, const int* in_sizes, int n_in, void* d_out, int out_size) {
  void* fn = nullptr; cudaDriverEntryPointQueryResult qr;
  cudaGetDriverEntryPoint("cuTensorMapEncodeTiled", &fn, cudaEnableDefault, &qr);
  EncFn enc = (EncFn)fn;
  void* uy = nullptr; cudaGetSymbolAddress(&uy, g_uy);
  const cuuint64_t dx[2] = {640, 2048}, sx[1] = {1280};
  const cuuint32_t bx[2] = {64, 128}, bu[2] = {80, 128};
  const cuuint64_t dw[3] = {640, 640, 3}, sw[2] = {3840, 1280};
  const cuuint32_t br[3] = {16, 32, 3};
  const cuuint64_t dwa[4] = {64, 640, 10, 3}, swa[3] = {3840, 128, 1280}, dwb[4] = {32, 640, 20, 3}, swb[3] = {3840, 64, 1280};
  const cuuint32_t bwa[4] = {64, 32, 1, 3}, bwb[4] = {32, 32, 2, 3};
  const cuuint64_t dwo[2] = {640, 640};
  const cuuint32_t bwo[2] = {64, 80}, bo64[2] = {64, 64}, bo16[2] = {16, 64};
  const cuuint64_t dsa[2] = {2048, 1280}, ssa[1] = {4096};
  const cuuint32_t bsa[2] = {64, 80};
  const cuuint64_t dsb[2] = {64, 40960}, ssb[1] = {128};
  const cuuint32_t bsb[2] = {64, 32};
  const cuuint64_t dout[2] = {1280, 2048}, sout[1] = {2560};
  Params prm;
  mkmap(enc, &prm.m[M_X], d_in[7], 2, dx, sx, bx, CU_TENSOR_MAP_SWIZZLE_128B);
  mkmap(enc, &prm.m[M_W128], d_in[8], 4, dwa, swa, bwa, CU_TENSOR_MAP_SWIZZLE_128B);
  mkmap(enc, &prm.m[M_W64], d_in[8], 4, dwb, swb, bwb, CU_TENSOR_MAP_SWIZZLE_64B);
  mkmap(enc, &prm.m[M_WR], d_in[8], 3, dw, sw, br, CU_TENSOR_MAP_SWIZZLE_32B);
  mkmap(enc, &prm.m[M_U], d_in[0], 2, dx, sx, bu, CU_TENSOR_MAP_SWIZZLE_NONE);
  mkmap(enc, &prm.m[M_WO], d_in[9], 2, dwo, sx, bwo, CU_TENSOR_MAP_SWIZZLE_128B);
  mkmap(enc, &prm.m[M_O64], d_out, 2, dout, sout, bo64, CU_TENSOR_MAP_SWIZZLE_128B);
  mkmap(enc, &prm.m[M_O16], d_out, 2, dout, sout, bo16, CU_TENSOR_MAP_SWIZZLE_NONE);
  mkmap(enc, &prm.m[M_SA], uy, 2, dsa, ssa, bsa, CU_TENSOR_MAP_SWIZZLE_128B);
  mkmap(enc, &prm.m[M_SB], uy, 2, dsb, ssb, bsb, CU_TENSOR_MAP_SWIZZLE_128B);
  mkmap(enc, &prm.m[M_OUT], d_out, 2, dout, sout, bu, CU_TENSOR_MAP_SWIZZLE_NONE);
  prm.u = (const __nv_bfloat16*)d_in[0]; prm.wo = (const __nv_bfloat16*)d_in[9];
  for (int i = 0; i < 4; i++) prm.par[i] = (const __nv_bfloat16*)d_in[1 + i];
  prm.logdt = (const __nv_bfloat16*)d_in[5]; prm.dskip = (const __nv_bfloat16*)d_in[6];
  cudaFuncSetAttribute(fused_kernel, cudaFuncAttributeMaxDynamicSharedMemorySize, SMEM_BYTES);
  cudaLaunchConfig_t cfg = {};
  cfg.gridDim = dim3(128); cfg.blockDim = dim3(512); cfg.dynamicSmemBytes = SMEM_BYTES; cfg.stream = cudaStreamPerThread;
  cudaLaunchAttribute at[1];
  at[0].id = cudaLaunchAttributeClusterDimension; at[0].val.clusterDim.x = 2; at[0].val.clusterDim.y = 1; at[0].val.clusterDim.z = 1;
  cfg.attrs = at; cfg.numAttrs = 1;
  cudaLaunchKernelEx(&cfg, fused_kernel, prm);
}
```

```cpp
#include <cuda_runtime.h>
#include <cuda_bf16.h>
#include <cuda_fp16.h>
#include <cuda.h>
#include <stdint.h>

#define KST 2
#define EN_ATT 1
#define EN_SSM 1

__device__ __align__(1024) __nv_bfloat16 g_uy[2 * 640 * 2048];
__device__ __align__(128) uint4 g_kvp[8 * 16 * 240];
__device__ __align__(128) uint4 g_o[128 * 1280];
__device__ __align__(128) unsigned g_flag[4 * 128 * 32];
__device__ unsigned g_epoch[128];
#define TS(i) do {} while (0)
#define DUMP(lo, hi) do {} while (0)
#define FIXCNT

constexpr uint32_t SB0 = 1024;
constexpr uint32_t W_SLOT = 15360, OFF_X = 76800;
constexpr uint32_t OFF_WOR = 81920, OFF_KVP = 10240, OFF_KVS = 71680, OFF_PK = 10240, OFF_V = 30720, OFF_EXTRA = 102400, OFF_KVB = OFF_EXTRA;
constexpr uint32_t OFF_UT = 3 * W_SLOT;
constexpr uint32_t OFF_BAR = 125952, OFF_BLK = 128000, BLK = 20480;
constexpr uint32_t B_D = 4096, B_D5 = 3088, B_D7 = 6176, B_D9 = 8224, B_TBL = 14400;
constexpr int T_S = 576, T_F2 = 624, T_F3 = 816;
constexpr uint32_t SMEM_BYTES = OFF_BLK + 5 * BLK;
enum { BR_FULL = 0, BR_WO = 5, BR_PUB = 7, BR_KVP = 8, BR_U = 9, BR_SUM = 10, BR_GEMM = 11, BR_UIN = 12, BR_YIN = 13, BR_EPOCH = 14,
       BR_FREE = 15, BR_RETRY = 17, BR_UOUT = 18, BR_OFULL = 18, BR_KS = 26, BR_EMPTY = 31, BR_OEMPTY = 36, BR_Y = 43, BR_OSTG = 45, BR_KF = 46,
       BR_COUNT = 48 };
constexpr uint32_t OFF_EPOCH = OFF_BAR + 8 * BR_COUNT;
enum { M_X, M_W128, M_W64, M_WR, M_U, M_WO, M_O64, M_O16, M_SA, M_SB, M_OUT, M_COUNT };

__device__ __forceinline__ long long clk64() { long long t; asm volatile("mov.u64 %0, %%clock64;" : "=l"(t) :: "memory"); return t; }
__device__ __forceinline__ uint32_t smem_u32(const void* p) { return (uint32_t)__cvta_generic_to_shared(p); }
__host__ __device__ constexpr uint64_t mkdesc(uint32_t addr, uint32_t lbo, uint32_t sbo, uint32_t swz) {
  return (uint64_t)((addr & 0x3FFFF) >> 4) | ((uint64_t)(lbo >> 4) << 16) | ((uint64_t)(sbo >> 4) << 32) | ((uint64_t)swz << 62);
}
__device__ __forceinline__ uint64_t desc2(uint32_t lo, uint32_t hi) { uint64_t d; asm("mov.b64 %0, {%1, %2};" : "=l"(d) : "r"(lo), "r"(hi)); return d; }
__device__ __forceinline__ void mbar_init(uint32_t bar, uint32_t cnt) { asm volatile("mbarrier.init.shared::cta.b64 [%0], %1;" :: "r"(bar), "r"(cnt) : "memory"); }
__device__ __forceinline__ void mbar_expect_tx(uint32_t bar, uint32_t bytes) { asm volatile("mbarrier.arrive.expect_tx.shared::cta.b64 _, [%0], %1;" :: "r"(bar), "r"(bytes) : "memory"); }
__device__ __forceinline__ void mbar_arrive(uint32_t bar) { asm volatile("mbarrier.arrive.shared::cta.b64 _, [%0];" :: "r"(bar) : "memory"); }
__device__ __forceinline__ void mbar_wait(uint32_t bar, uint32_t parity) {
  asm volatile("{\n.reg .pred p;\n.reg .u32 c;\nmov.u32 c, 0;\n"
    "WL:\nmbarrier.try_wait.parity.shared::cta.b64 p, [%0], %1;\n@p bra WD;\n"
    "add.u32 c, c, 1;\nsetp.lt.u32 p, c, 200000;\n@p bra WL;\nWD:\n}" :: "r"(bar), "r"(parity) : "memory");
}
__device__ __forceinline__ void poll_all(const unsigned* p, unsigned val) {
  asm volatile("{\n.reg .pred p;\n.reg .u32 c, v;\nmov.u32 c, 0;\n"
    "PL:\nld.relaxed.gpu.global.u32 v, [%0];\nsetp.eq.u32 p, v, %1;\nvote.sync.all.pred p, p, 0xffffffff;\n@p bra PD;\n"
    "add.u32 c, c, 1;\nsetp.lt.u32 p, c, 100000;\n@p bra PL;\nPD:\n}" :: "l"(p), "r"(val) : "memory");
}
__device__ __forceinline__ void poll_all_acq(const unsigned* p, unsigned val) {
  asm volatile("{\n.reg .pred p;\n.reg .u32 c, v;\nmov.u32 c, 0;\n"
    "PL:\nld.acquire.gpu.global.u32 v, [%0];\nsetp.eq.u32 p, v, %1;\nvote.sync.all.pred p, p, 0xffffffff;\n@p bra PD;\n"
    "add.u32 c, c, 1;\nsetp.lt.u32 p, c, 100000;\n@p bra PL;\nPD:\n}" :: "l"(p), "r"(val) : "memory");
}
__device__ __forceinline__ unsigned poll_bit(const unsigned* p, unsigned val, unsigned mask) {
  unsigned bal;
  asm volatile("{\n.reg .pred p;\n.reg .u32 c, v;\nmov.u32 c, 0;\n"
    "PL:\nld.relaxed.gpu.global.u32 v, [%1];\nsetp.eq.u32 p, v, %2;\nvote.sync.ballot.b32 %0, p, 0xffffffff;\n"
    "and.b32 v, %0, %3;\nsetp.ne.u32 p, v, 0;\n@p bra PD;\n"
    "add.u32 c, c, 1;\nsetp.lt.u32 p, c, 100000;\n@p bra PL;\nPD:\n}" : "=&r"(bal) : "l"(p), "r"(val), "r"(mask) : "memory");
  return bal;
}
__device__ __forceinline__ void fix128_w0(uint32_t* v, const void* p, uint32_t tag, uint32_t mask) {
  asm volatile("{\n.reg .pred p;\n.reg .u32 c, x;\n.reg .b128 t;\n.reg .b64 lo, hi;\nmov.u32 c, 0;\n"
    "FL:\nxor.b32 x, %0, %5;\nand.b32 x, x, %6;\nsetp.eq.u32 p, x, 0;\n@p bra FD;\n"
    "ld.relaxed.gpu.global.b128 t, [%4];\nmov.b128 {lo, hi}, t;\nmov.b64 {%0, %1}, lo;\nmov.b64 {%2, %3}, hi;\n"
    "add.u32 c, c, 1;\nsetp.lt.u32 p, c, 100000;\n@p bra FL;\nFD:\n}"
    : "+r"(v[0]), "+r"(v[1]), "+r"(v[2]), "+r"(v[3]) : "l"(p), "r"(tag), "r"(mask) : "memory");
}
__device__ __forceinline__ void fix128_w3(uint32_t* v, const void* p, uint32_t tag, uint32_t mask) {
  asm volatile("{\n.reg .pred p;\n.reg .u32 c, x;\n.reg .b128 t;\n.reg .b64 lo, hi;\nmov.u32 c, 0;\n"
    "FL:\nxor.b32 x, %3, %5;\nand.b32 x, x, %6;\nsetp.eq.u32 p, x, 0;\n@p bra FD;\n"
    "ld.relaxed.gpu.global.b128 t, [%4];\nmov.b128 {lo, hi}, t;\nmov.b64 {%0, %1}, lo;\nmov.b64 {%2, %3}, hi;\n"
    "add.u32 c, c, 1;\nsetp.lt.u32 p, c, 100000;\n@p bra FL;\nFD:\n}"
    : "+r"(v[0]), "+r"(v[1]), "+r"(v[2]), "+r"(v[3]) : "l"(p), "r"(tag), "r"(mask) : "memory");
}
__device__ __forceinline__ void fence_acq() { asm volatile("fence.acq_rel.gpu;" ::: "memory"); }
__device__ __forceinline__ bool elect_one() {
  uint32_t p; asm volatile("{\n.reg .pred P;\nelect.sync _|P, 0xffffffff;\nselp.u32 %0, 1, 0, P;\n}" : "=r"(p)); return p;
}
__device__ __forceinline__ void bar_sync(int id, int n) { asm volatile("bar.sync %0, %1;" :: "r"(id), "r"(n) : "memory"); }
__device__ __forceinline__ void fence_async() { asm volatile("fence.proxy.async.shared::cta;" ::: "memory"); }
__device__ __forceinline__ void fence_async_g() { asm volatile("fence.proxy.async.global;" ::: "memory"); }
__device__ __forceinline__ void tma2d(uint32_t dst, const CUtensorMap* m, uint32_t bar, int c0, int c1) {
  asm volatile("cp.async.bulk.tensor.2d.shared::cluster.global.mbarrier::complete_tx::bytes [%0], [%1, {%3, %4}], [%2];"
    :: "r"(dst), "l"(m), "r"(bar), "r"(c0), "r"(c1) : "memory");
}
__device__ __forceinline__ void tma3d(uint32_t dst, const CUtensorMap* m, uint32_t bar, int c0, int c1, int c2) {
  asm volatile("cp.async.bulk.tensor.3d.shared::cluster.global.mbarrier::complete_tx::bytes [%0], [%1, {%3, %4, %5}], [%2];"
    :: "r"(dst), "l"(m), "r"(bar), "r"(c0), "r"(c1), "r"(c2) : "memory");
}
__device__ __forceinline__ void tma4d(uint32_t dst, const CUtensorMap* m, uint32_t bar, int c0, int c1, int c2, int c3) {
  asm volatile("cp.async.bulk.tensor.4d.shared::cluster.global.mbarrier::complete_tx::bytes [%0], [%1, {%3, %4, %5, %6}], [%2];"
    :: "r"(dst), "l"(m), "r"(bar), "r"(c0), "r"(c1), "r"(c2), "r"(c3) : "memory");
}
__device__ __forceinline__ void tma2d_st(const CUtensorMap* m, uint32_t src, int c0, int c1) {
  asm volatile("cp.async.bulk.tensor.2d.global.shared::cta.bulk_group [%0, {%2, %3}], [%1];"
    :: "l"(m), "r"(src), "r"(c0), "r"(c1) : "memory");
}
__device__ __forceinline__ void bulk_ld(uint32_t dst, const void* src, uint32_t bytes, uint32_t bar) {
  asm volatile("cp.async.bulk.shared::cluster.global.mbarrier::complete_tx::bytes [%0], [%1], %2, [%3];"
    :: "r"(dst), "l"(src), "r"(bytes), "r"(bar) : "memory");
}
__device__ __forceinline__ void bulk_st(void* dst, uint32_t src, uint32_t bytes) {
  asm volatile("cp.async.bulk.global.shared::cta.bulk_group [%0], [%1], %2;" :: "l"(dst), "r"(src), "r"(bytes) : "memory");
}
__device__ __forceinline__ void bulk_commit() { asm volatile("cp.async.bulk.commit_group;" ::: "memory"); }
__device__ __forceinline__ void bulk_wait0() { asm volatile("cp.async.bulk.wait_group 0;" ::: "memory"); }
__device__ __forceinline__ void bulk_wait0_read() { asm volatile("cp.async.bulk.wait_group.read 0;" ::: "memory"); }
__device__ __forceinline__ unsigned ld_rlx(const unsigned* p) { unsigned v; asm volatile("ld.relaxed.gpu.global.u32 %0, [%1];" : "=r"(v) : "l"(p) : "memory"); return v; }
__device__ __forceinline__ unsigned ld_acq(const unsigned* p) { unsigned v; asm volatile("ld.acquire.gpu.global.u32 %0, [%1];" : "=r"(v) : "l"(p) : "memory"); return v; }
__device__ __forceinline__ void st_rlx(unsigned* p, unsigned v) { asm volatile("st.relaxed.gpu.global.u32 [%0], %1;" :: "l"(p), "r"(v) : "memory"); }
__device__ __forceinline__ void st_rel(unsigned* p, unsigned v) { asm volatile("st.release.gpu.global.u32 [%0], %1;" :: "l"(p), "r"(v) : "memory"); }
__device__ __forceinline__ void ld128_rlx(uint32_t* v, const void* p) {
  asm volatile("{\n.reg .b128 t;\n.reg .b64 lo, hi;\nld.relaxed.gpu.global.b128 t, [%4];\nmov.b128 {lo, hi}, t;\n"
    "mov.b64 {%0, %1}, lo;\nmov.b64 {%2, %3}, hi;\n}" : "=r"(v[0]), "=r"(v[1]), "=r"(v[2]), "=r"(v[3]) : "l"(p) : "memory");
}
__device__ __forceinline__ void st128_rlx(void* p, const uint32_t* v) {
  asm volatile("{\n.reg .b128 t;\n.reg .b64 lo, hi;\nmov.b64 lo, {%1, %2};\nmov.b64 hi, {%3, %4};\nmov.b128 t, {lo, hi};\n"
    "st.relaxed.gpu.global.b128 [%0], t;\n}" :: "l"(p), "r"(v[0]), "r"(v[1]), "r"(v[2]), "r"(v[3]) : "memory");
}
__device__ __forceinline__ uint32_t lds32(uint32_t a) { uint32_t v; asm volatile("ld.shared.u32 %0, [%1];" : "=r"(v) : "r"(a) : "memory"); return v; }
__device__ __forceinline__ uint32_t lds32v(uint32_t a) { uint32_t v; asm volatile("ld.volatile.shared.u32 %0, [%1];" : "=r"(v) : "r"(a) : "memory"); return v; }
__device__ __forceinline__ uint32_t cpa(uint32_t a, uint32_t one) { uint32_t v; asm volatile("mul.lo.u32 %0, %1, %2;" : "=r"(v) : "r"(a), "r"(one)); return v; }
__device__ __forceinline__ uint32_t cpb(uint32_t a, uint32_t zero) { uint32_t v; asm volatile("or.b32 %0, %1, %2;" : "=r"(v) : "r"(a), "r"(zero)); return v; }
__device__ __forceinline__ uint32_t lds16(uint32_t a) { uint16_t v; asm volatile("ld.shared.u16 %0, [%1];" : "=h"(v) : "r"(a) : "memory"); return v; }
__device__ __forceinline__ float ldsf(uint32_t a) { float v; asm volatile("ld.shared.f32 %0, [%1];" : "=f"(v) : "r"(a) : "memory"); return v; }
__device__ __forceinline__ void lds128(uint32_t* v, uint32_t a) { asm volatile("ld.shared.v4.u32 {%0,%1,%2,%3}, [%4];" : "=r"(v[0]), "=r"(v[1]), "=r"(v[2]), "=r"(v[3]) : "r"(a) : "memory"); }
__device__ __forceinline__ void sts32(uint32_t a, uint32_t v) { asm volatile("st.shared.u32 [%0], %1;" :: "r"(a), "r"(v) : "memory"); }
__device__ __forceinline__ void sts16(uint32_t a, uint32_t v) { asm volatile("st.shared.u16 [%0], %1;" :: "r"(a), "h"((uint16_t)v) : "memory"); }
__device__ __forceinline__ void sts64f(uint32_t a, float x, float y) { asm volatile("st.shared.v2.f32 [%0], {%1,%2};" :: "r"(a), "f"(x), "f"(y) : "memory"); }
__device__ __forceinline__ void sts128(uint32_t a, uint32_t x, uint32_t y, uint32_t z, uint32_t w) { asm volatile("st.shared.v4.u32 [%0], {%1,%2,%3,%4};" :: "r"(a), "r"(x), "r"(y), "r"(z), "r"(w) : "memory"); }
__device__ __forceinline__ void stsm4(uint32_t a, uint32_t r0, uint32_t r1, uint32_t r2, uint32_t r3) {
  asm volatile("stmatrix.sync.aligned.m8n8.x4.shared.b16 [%0], {%1,%2,%3,%4};" :: "r"(a), "r"(r0), "r"(r1), "r"(r2), "r"(r3) : "memory");
}
__device__ __forceinline__ void stsm4t(uint32_t a, uint32_t r0, uint32_t r1, uint32_t r2, uint32_t r3) {
  asm volatile("stmatrix.sync.aligned.m8n8.x4.trans.shared.b16 [%0], {%1,%2,%3,%4};" :: "r"(a), "r"(r0), "r"(r1), "r"(r2), "r"(r3) : "memory");
}
__device__ __forceinline__ void ldsm4t(uint32_t* r, uint32_t a) {
  asm volatile("ldmatrix.sync.aligned.m8n8.x4.trans.shared.b16 {%0,%1,%2,%3}, [%4];" : "=r"(r[0]), "=r"(r[1]), "=r"(r[2]), "=r"(r[3]) : "r"(a) : "memory");
}
__device__ __forceinline__ void ldsm4(uint32_t* r, uint32_t a) {
  asm volatile("ldmatrix.sync.aligned.m8n8.x4.shared.b16 {%0,%1,%2,%3}, [%4];" : "=r"(r[0]), "=r"(r[1]), "=r"(r[2]), "=r"(r[3]) : "r"(a) : "memory");
}
__device__ __forceinline__ void mma16816(float* d, const uint32_t* a, const uint32_t* b) {
  asm volatile("mma.sync.aligned.m16n8k16.row.col.f32.bf16.bf16.f32 {%0,%1,%2,%3}, {%4,%5,%6,%7}, {%8,%9}, {%0,%1,%2,%3};"
    : "+f"(d[0]), "+f"(d[1]), "+f"(d[2]), "+f"(d[3]) : "r"(a[0]), "r"(a[1]), "r"(a[2]), "r"(a[3]), "r"(b[0]), "r"(b[1]));
}
__device__ __forceinline__ uint32_t pack2(float lo, float hi) { uint32_t r; asm("cvt.rn.bf16x2.f32 %0, %1, %2;" : "=r"(r) : "f"(hi), "f"(lo)); return r; }
__device__ __forceinline__ uint32_t packh(float lo, float hi) { uint32_t r; asm("cvt.rn.f16x2.f32 %0, %1, %2;" : "=r"(r) : "f"(hi), "f"(lo)); return r; }
__device__ __forceinline__ uint32_t hcmul(uint32_t x, uint32_t zp, uint32_t zq) {
  const __half2 xx = *reinterpret_cast<__half2*>(&x);
  const __half2 r = __hfma2(__high2half2(xx), *reinterpret_cast<__half2*>(&zq), __hmul2(__low2half2(xx), *reinterpret_cast<__half2*>(&zp)));
  return *reinterpret_cast<const uint32_t*>(&r);
}
__device__ __forceinline__ void hcm2(uint32_t xr, uint32_t xi, uint32_t z, uint32_t& pr, uint32_t& pi) {
  const __half2 a = *reinterpret_cast<__half2*>(&xr), b = *reinterpret_cast<__half2*>(&xi), zz = *reinterpret_cast<__half2*>(&z);
  const __half2 re = __hfma2(__hneg2(b), __high2half2(zz), __hmul2(a, __low2half2(zz)));
  const __half2 im = __hfma2(a, __high2half2(zz), __hmul2(b, __low2half2(zz)));
  pr = *reinterpret_cast<const uint32_t*>(&re); pi = *reinterpret_cast<const uint32_t*>(&im);
}
__device__ __forceinline__ void sts64(uint32_t a, uint32_t x, uint32_t y) { asm volatile("st.shared.v2.u32 [%0], {%1,%2};" :: "r"(a), "r"(x), "r"(y) : "memory"); }
__device__ __forceinline__ void lds64(uint32_t* v, uint32_t a) { asm volatile("ld.shared.v2.u32 {%0,%1}, [%2];" : "=r"(v[0]), "=r"(v[1]) : "r"(a) : "memory"); }
__device__ __forceinline__ float bf_lo(uint32_t v) { return __uint_as_float(v << 16); }
__device__ __forceinline__ float bf_hi(uint32_t v) { return __uint_as_float(v & 0xffff0000u); }
__device__ __forceinline__ float bf_round(float x) { return bf_lo(pack2(x, 0.f)); }
__device__ __forceinline__ float ex2(float x) { float r; asm("ex2.approx.ftz.f32 %0, %1;" : "=f"(r) : "f"(x)); return r; }
__device__ __forceinline__ float phi(float t, float l2e = 1.44269504089f) {
  float e = ex2(t * l2e) + 1e-6f;
  asm("{\n.reg .pred p;\nsetp.gt.f32 p, %1, 0f00000000;\n@p add.f32 %0, %1, 0f3F800008;\n}" : "+f"(e) : "f"(t));
  return e;
}
__device__ __forceinline__ void wg_fence() { asm volatile("wgmma.fence.sync.aligned;" ::: "memory"); }
__device__ __forceinline__ void wg_commit() { asm volatile("wgmma.commit_group.sync.aligned;" ::: "memory"); }
template <int N> __device__ __forceinline__ void wg_wait() { asm volatile("wgmma.wait_group.sync.aligned %0;" :: "n"(N) : "memory"); }
template <int N> __device__ __forceinline__ void pin(float* a) {
  #pragma unroll
  for (int i = 0; i < N; i++) asm volatile("" : "+f"(a[i]) :: "memory");
}
__device__ __forceinline__ int rtid() { int t; asm volatile("mov.u32 %0, %%tid.x;" : "=r"(t)); return t; }
__device__ __forceinline__ int opaque(int v) { asm volatile("" : "+r"(v)); return v; }
template <int N> __device__ __forceinline__ void zero(float* a) {
  #pragma unroll
  for (int i = 0; i < N; i++) asm volatile("mov.b32 %0, 0;" : "=f"(a[i]));
}
template <int N> __device__ __forceinline__ void pinu(uint32_t* a) {
  #pragma unroll
  for (int i = 0; i < N; i++) asm volatile("" : "+r"(a[i]) :: "memory");
}
__device__ __forceinline__ void cexp_t(float lg2mag, float turns, float& re, float& im) {
  float m = ex2(lg2mag);
  float fr = (turns - __fadd_rn(__fadd_rn(turns, 12582912.f), -12582912.f)) * 6.283185307f;
  re = m * __cosf(fr); im = m * __sinf(fr);
}
__device__ __forceinline__ void cmul(float ar, float ai, float br, float bi, float& cr, float& ci) {
  cr = fmaf(ar, br, -ai * bi); ci = fmaf(ar, bi, ai * br);
}

__device__ __forceinline__ void wg_ss192_tb(float* d, uint64_t da, uint64_t db, int scale_d) {
  asm volatile("{\n.reg .pred p;\nsetp.ne.b32 p, %98, 0;\n"
    "wgmma.mma_async.sync.aligned.m64n192k16.f32.bf16.bf16 "
    "{%0, %1, %2, %3, %4, %5, %6, %7, %8, %9, %10, %11, %12, %13, %14, %15, %16, %17, %18, %19, %20, %21, %22, %23, %24, %25, %26, %27, %28, %29, %30, %31, %32, %33, %34, %35, %36, %37, %38, %39, %40, %41, %42, %43, %44, %45, %46, %47, %48, %49, %50, %51, %52, %53, %54, %55, %56, %57, %58, %59, %60, %61, %62, %63, %64, %65, %66, %67, %68, %69, %70, %71, %72, %73, %74, %75, %76, %77, %78, %79, %80, %81, %82, %83, %84, %85, %86, %87, %88, %89, %90, %91, %92, %93, %94, %95}, %96, %97, p, 1, 1, 0, 1;\n}\n"
    : "+f"(d[0]), "+f"(d[1]), "+f"(d[2]), "+f"(d[3]), "+f"(d[4]), "+f"(d[5]), "+f"(d[6]), "+f"(d[7]), "+f"(d[8]), "+f"(d[9]), "+f"(d[10]), "+f"(d[11]), "+f"(d[12]), "+f"(d[13]), "+f"(d[14]), "+f"(d[15]), "+f"(d[16]), "+f"(d[17]), "+f"(d[18]), "+f"(d[19]), "+f"(d[20]), "+f"(d[21]), "+f"(d[22]), "+f"(d[23]), "+f"(d[24]), "+f"(d[25]), "+f"(d[26]), "+f"(d[27]), "+f"(d[28]), "+f"(d[29]), "+f"(d[30]), "+f"(d[31]), "+f"(d[32]), "+f"(d[33]), "+f"(d[34]), "+f"(d[35]), "+f"(d[36]), "+f"(d[37]), "+f"(d[38]), "+f"(d[39]), "+f"(d[40]), "+f"(d[41]), "+f"(d[42]), "+f"(d[43]), "+f"(d[44]), "+f"(d[45]), "+f"(d[46]), "+f"(d[47]), "+f"(d[48]), "+f"(d[49]), "+f"(d[50]), "+f"(d[51]), "+f"(d[52]), "+f"(d[53]), "+f"(d[54]), "+f"(d[55]), "+f"(d[56]), "+f"(d[57]), "+f"(d[58]), "+f"(d[59]), "+f"(d[60]), "+f"(d[61]), "+f"(d[62]), "+f"(d[63]), "+f"(d[64]), "+f"(d[65]), "+f"(d[66]), "+f"(d[67]), "+f"(d[68]), "+f"(d[69]), "+f"(d[70]), "+f"(d[71]), "+f"(d[72]), "+f"(d[73]), "+f"(d[74]), "+f"(d[75]), "+f"(d[76]), "+f"(d[77]), "+f"(d[78]), "+f"(d[79]), "+f"(d[80]), "+f"(d[81]), "+f"(d[82]), "+f"(d[83]), "+f"(d[84]), "+f"(d[85]), "+f"(d[86]), "+f"(d[87]), "+f"(d[88]), "+f"(d[89]), "+f"(d[90]), "+f"(d[91]), "+f"(d[92]), "+f"(d[93]), "+f"(d[94]), "+f"(d[95])
    : "l"(da), "l"(db), "r"(scale_d));
}
__device__ __forceinline__ void wg_ss48_tb(float* d, uint64_t da, uint64_t db, int scale_d) {
  asm volatile("{\n.reg .pred p;\nsetp.ne.b32 p, %26, 0;\n"
    "wgmma.mma_async.sync.aligned.m64n48k16.f32.bf16.bf16 "
    "{%0, %1, %2, %3, %4, %5, %6, %7, %8, %9, %10, %11, %12, %13, %14, %15, %16, %17, %18, %19, %20, %21, %22, %23}, %24, %25, p, 1, 1, 0, 1;\n}\n"
    : "+f"(d[0]), "+f"(d[1]), "+f"(d[2]), "+f"(d[3]), "+f"(d[4]), "+f"(d[5]), "+f"(d[6]), "+f"(d[7]), "+f"(d[8]), "+f"(d[9]), "+f"(d[10]), "+f"(d[11]), "+f"(d[12]), "+f"(d[13]), "+f"(d[14]), "+f"(d[15]), "+f"(d[16]), "+f"(d[17]), "+f"(d[18]), "+f"(d[19]), "+f"(d[20]), "+f"(d[21]), "+f"(d[22]), "+f"(d[23])
    : "l"(da), "l"(db), "r"(scale_d));
}
__device__ __forceinline__ void wg_ss48_tt(float* d, uint64_t da, uint64_t db, int scale_d) {
  asm volatile("{\n.reg .pred p;\nsetp.ne.b32 p, %26, 0;\n"
    "wgmma.mma_async.sync.aligned.m64n48k16.f32.bf16.bf16 "
    "{%0, %1, %2, %3, %4, %5, %6, %7, %8, %9, %10, %11, %12, %13, %14, %15, %16, %17, %18, %19, %20, %21, %22, %23}, %24, %25, p, 1, 1, 1, 1;\n}\n"
    : "+f"(d[0]), "+f"(d[1]), "+f"(d[2]), "+f"(d[3]), "+f"(d[4]), "+f"(d[5]), "+f"(d[6]), "+f"(d[7]), "+f"(d[8]), "+f"(d[9]), "+f"(d[10]), "+f"(d[11]), "+f"(d[12]), "+f"(d[13]), "+f"(d[14]), "+f"(d[15]), "+f"(d[16]), "+f"(d[17]), "+f"(d[18]), "+f"(d[19]), "+f"(d[20]), "+f"(d[21]), "+f"(d[22]), "+f"(d[23])
    : "l"(da), "l"(db), "r"(scale_d));
}
__device__ __forceinline__ void wg_rs88_tb(float* d, const uint32_t* a, uint64_t db, int scale_d) {
  asm volatile("{\n.reg .pred p;\nsetp.ne.b32 p, %49, 0;\n"
    "wgmma.mma_async.sync.aligned.m64n88k16.f32.bf16.bf16 "
    "{%0, %1, %2, %3, %4, %5, %6, %7, %8, %9, %10, %11, %12, %13, %14, %15, %16, %17, %18, %19, %20, %21, %22, %23, %24, %25, %26, %27, %28, %29, %30, %31, %32, %33, %34, %35, %36, %37, %38, %39, %40, %41, %42, %43}, {%44, %45, %46, %47}, %48, p, 1, 1, 1;\n}\n"
    : "+f"(d[0]), "+f"(d[1]), "+f"(d[2]), "+f"(d[3]), "+f"(d[4]), "+f"(d[5]), "+f"(d[6]), "+f"(d[7]), "+f"(d[8]), "+f"(d[9]), "+f"(d[10]), "+f"(d[11]), "+f"(d[12]), "+f"(d[13]), "+f"(d[14]), "+f"(d[15]), "+f"(d[16]), "+f"(d[17]), "+f"(d[18]), "+f"(d[19]), "+f"(d[20]), "+f"(d[21]), "+f"(d[22]), "+f"(d[23]), "+f"(d[24]), "+f"(d[25]), "+f"(d[26]), "+f"(d[27]), "+f"(d[28]), "+f"(d[29]), "+f"(d[30]), "+f"(d[31]), "+f"(d[32]), "+f"(d[33]), "+f"(d[34]), "+f"(d[35]), "+f"(d[36]), "+f"(d[37]), "+f"(d[38]), "+f"(d[39]), "+f"(d[40]), "+f"(d[41]), "+f"(d[42]), "+f"(d[43])
    : "r"(a[0]), "r"(a[1]), "r"(a[2]), "r"(a[3]), "l"(db), "r"(scale_d));
}
__device__ __forceinline__ void wg_ss80_tb(float* d, uint64_t da, uint64_t db, int scale_d) {
  asm volatile("{\n.reg .pred p;\nsetp.ne.b32 p, %42, 0;\n"
    "wgmma.mma_async.sync.aligned.m64n80k16.f32.bf16.bf16 "
    "{%0, %1, %2, %3, %4, %5, %6, %7, %8, %9, %10, %11, %12, %13, %14, %15, %16, %17, %18, %19, %20, %21, %22, %23, %24, %25, %26, %27, %28, %29, %30, %31, %32, %33, %34, %35, %36, %37, %38, %39}, %40, %41, p, 1, 1, 0, 1;\n}\n"
    : "+f"(d[0]), "+f"(d[1]), "+f"(d[2]), "+f"(d[3]), "+f"(d[4]), "+f"(d[5]), "+f"(d[6]), "+f"(d[7]), "+f"(d[8]), "+f"(d[9]), "+f"(d[10]), "+f"(d[11]), "+f"(d[12]), "+f"(d[13]), "+f"(d[14]), "+f"(d[15]), "+f"(d[16]), "+f"(d[17]), "+f"(d[18]), "+f"(d[19]), "+f"(d[20]), "+f"(d[21]), "+f"(d[22]), "+f"(d[23]), "+f"(d[24]), "+f"(d[25]), "+f"(d[26]), "+f"(d[27]), "+f"(d[28]), "+f"(d[29]), "+f"(d[30]), "+f"(d[31]), "+f"(d[32]), "+f"(d[33]), "+f"(d[34]), "+f"(d[35]), "+f"(d[36]), "+f"(d[37]), "+f"(d[38]), "+f"(d[39])
    : "l"(da), "l"(db), "r"(scale_d));
}
__device__ __forceinline__ void wg_ss48_tt_h(float* d, uint64_t da, uint64_t db, int scale_d) {
  asm volatile("{\n.reg .pred p;\nsetp.ne.b32 p, %26, 0;\n"
    "wgmma.mma_async.sync.aligned.m64n48k16.f32.f16.f16 "
    "{%0, %1, %2, %3, %4, %5, %6, %7, %8, %9, %10, %11, %12, %13, %14, %15, %16, %17, %18, %19, %20, %21, %22, %23}, %24, %25, p, 1, 1, 1, 1;\n}\n"
    : "+f"(d[0]), "+f"(d[1]), "+f"(d[2]), "+f"(d[3]), "+f"(d[4]), "+f"(d[5]), "+f"(d[6]), "+f"(d[7]), "+f"(d[8]), "+f"(d[9]), "+f"(d[10]), "+f"(d[11]), "+f"(d[12]), "+f"(d[13]), "+f"(d[14]), "+f"(d[15]), "+f"(d[16]), "+f"(d[17]), "+f"(d[18]), "+f"(d[19]), "+f"(d[20]), "+f"(d[21]), "+f"(d[22]), "+f"(d[23])
    : "l"(da), "l"(db), "r"(scale_d));
}

struct Params {
  const __nv_bfloat16 *par[4], *logdt, *dskip, *u, *wo;
  CUtensorMap m[M_COUNT];
};

#define CHUNK(i) ((i) == 0 ? c : ((i) == 7 ? (c ^ 1) : (((c & 6) + 1 + (i)) & 7)))
#define FLAG(kind, rr, cc) (&g_flag[((kind) * 128 + (rr) * 8 + (cc)) * 32])
#define SLOT(i) ((i) == 0 || (i) == 5 ? OFF_EXTRA : OFF_BLK + ((i) == 7 ? 0 : (i) == 6 ? 4 : (i) - 1) * BLK)
__device__ __forceinline__ void load_quad(uint32_t* A, uint32_t addr) {
  A[0] = lds32v(addr); A[1] = lds32v(addr + 32); A[2] = lds32v(addr - 32); A[3] = lds32v(addr);
}

__global__ void __launch_bounds__(512, 1) fused_kernel(const __grid_constant__ Params prm) {
  extern __shared__ unsigned char smem_raw[];
  const uint32_t sb = __shfl_sync(0xffffffff, smem_u32(smem_raw), 0);
  const int tid = threadIdx.x, lane = tid & 31;
  const int warp = __shfl_sync(0xffffffff, tid >> 5, 0), wg = warp >> 2, w4 = warp & 3;
  const int cta = blockIdx.x, r = cta >> 3, c = cta & 7;
  if ((sb & 0xffffffu) != SB0) return;
#define BAR(i) (sb + OFF_BAR + 8 * (i))
  const bool sw64 = ((c + 1) & 2) != 0;

  if (wg == 3) {
    if (warp == 13 && elect_one()) {
      #pragma unroll
      for (int i = M_W128; i <= M_U; i++) asm volatile("prefetch.tensormap [%0];" :: "l"(&prm.m[i]) : "memory");
    }
    asm volatile("setmaxnreg.dec.sync.aligned.u32 56;");
    const int tid = rtid(), lane = tid & 31;
    if (warp == 12) {
      if (elect_one()) {
        #pragma unroll
        for (int i = 0; i < 5; i++) mbar_init(BAR(BR_FULL + i), 1);
        asm volatile("fence.mbarrier_init.release.cluster;" ::: "memory");
      }
      {
        const CUtensorMap* mwp = &prm.m[sw64 ? M_W64 : M_W128];
        const int mcol = (c * 80 + (c & 1) * 16) >> (sw64 ? 5 : 6), rcol = c * 80 + ((c & 1) ? 0 : 64);
        uint32_t s = 0, ph = 1, xs = 0;
        #pragma unroll 1
        for (int kb = 0; kb < 20; kb++) {
          if (kb == 1) asm volatile("bar.arrive 0, 512;" ::: "memory");
          if (kb == 3) { bar_sync(6, 128); if (EN_SSM) mbar_wait(BAR(BR_UOUT), 0); }
          if (EN_SSM && kb == 4) mbar_wait(BAR(BR_KS + 3), 0);
          if (kb >= 5) mbar_wait(BAR(BR_EMPTY) + 8 * s, ph);
          if (EN_ATT && elect_one()) {
            const uint32_t st = sb + s * W_SLOT, fb = BAR(BR_FULL) + 8 * s;
            mbar_expect_tx(fb, (kb & 1) ? W_SLOT : W_SLOT + 16384);
            if (!(kb & 1)) tma2d(sb + OFF_X + xs, &prm.m[M_X], fb, kb * 32, r * 128);
            tma4d(st, mwp, fb, 0, kb * 32, mcol, 0);
            tma3d(st + 12288, &prm.m[M_WR], fb, rcol, kb * 32, 0);
          }
          if (kb < 4 && lane == 0) TS(24 + kb);
          if (kb == 14 && elect_one()) asm volatile("cp.async.bulk.prefetch.L2.global [%0], 6400;" :: "l"(prm.wo + cta * 3200) : "memory");
          if (!EN_ATT && kb == 3) break;
          if (++s == 5) { s = 0; ph ^= 1; }
          if (kb & 1) { xs += 16384; if (xs == 49152) xs = 0; }
        }
      }
      if (EN_ATT) {
      mbar_wait(BAR(BR_EPOCH), 0);
      const unsigned epoch = lds32(sb + OFF_EPOCH);
      const unsigned* fo = FLAG(3, r, lane & 7);
      unsigned seen = __ballot_sync(0xffffffff, ld_rlx(lane < 16 ? fo : FLAG(0, lane & 15, c)) == epoch) & 0xffu;
      mbar_wait(BAR(BR_GEMM), 0);
      if (elect_one()) {
        mbar_expect_tx(BAR(BR_WO), 10240);
        tma2d(sb, &prm.m[M_WO], BAR(BR_WO), c * 64, c * 80);
        mbar_expect_tx(BAR(BR_KVP), 61440);
        mbar_expect_tx(BAR(BR_WO + 1), 7 * 10240);
      }
      {
        uint32_t ds = sb + OFF_WOR + (lane >> 3) * 128 + (((lane & 7) ^ (lane >> 3)) << 4);
        #pragma unroll 1
        for (int h = 0; h < 2; h++) {
          const int i = (lane & 6) + h;
          const char* gs = reinterpret_cast<const char*>(prm.wo) + (size_t)((lane >> 3) + CHUNK(i) * 80) * 1280 + 1024 + c * 32 + (lane & 1) * 16;
          #pragma unroll 2
          for (int q = 0; q < 20; q++) {
            asm volatile("cp.async.cg.shared.global [%0], [%1], 16;" :: "r"(ds), "l"(gs) : "memory");
            ds = (ds + 512) ^ 64; gs += 5120;
          }
        }
      }
      mbar_wait(BAR(BR_PUB), 0);
      poll_all(FLAG(0, lane & 15, c), epoch);
      if (elect_one()) { TS(23); bulk_ld(sb + OFF_KVP, &g_kvp[c * 16 * 240], 61440, BAR(BR_KVP)); }
      asm volatile("cp.async.wait_all;" ::: "memory");
      fence_async();
      mbar_arrive(BAR(BR_WO));
      mbar_wait(BAR(BR_SUM), 0);
      if (elect_one()) {
        #pragma unroll 1
        for (int i = 1; i < 8; i++) tma2d(sb + i * 10240, &prm.m[M_WO], BAR(BR_WO + 1), c * 64, CHUNK(i) * 80);
      }
      mbar_wait(BAR(BR_OSTG), 0);
      if (elect_one()) {
        bulk_st(&g_o[cta * 1280], sb + OFF_EXTRA, 20480);
        bulk_commit();
        bulk_wait0();
        st_rlx(FLAG(3, r, c), epoch);
        TS(20);
      }
      __syncwarp();
      #pragma unroll 1
      for (int i = 1; i < 8; i++) {
        const int src = CHUNK(i);
        if (!((seen >> src) & 1)) seen = poll_bit(fo, epoch, 1u << src);
        if (i == 5 || i == 7) mbar_wait(BAR(BR_OEMPTY) + 4 * (i - 5), 0);
        if (EN_SSM && (i == 1 || i == 4)) mbar_wait(BAR(BR_FREE) + 2 * (i & 4), 0);
        if (elect_one()) {
          mbar_expect_tx(BAR(BR_OFULL) + 8 * i, 20480);
          bulk_ld(sb + SLOT(i), &g_o[(r * 8 + src) * 1280], 20480, BAR(BR_OFULL) + 8 * i);
          if (i == 1) TS(21);
          if (i == 7) TS(22);
        }
        __syncwarp();
      }
      if (lane == 0) { DUMP(20, 30); }
      }
    } else {
      const int hw = warp - 13, ht = tid - 416;
      if (hw == 2 && elect_one()) {
        #pragma unroll
        for (int i = 5; i < BR_COUNT; i++) mbar_init(BAR(i), i == BR_WO ? 33 : i < BR_EMPTY ? 1 : i < BR_OEMPTY ? 2 : i < BR_Y ? 8 : i < BR_OSTG ? 128 : 256);
        asm volatile("fence.mbarrier_init.release.cluster;" ::: "memory");
        if (EN_SSM) { mbar_expect_tx(BAR(BR_UIN), 20480); tma2d(sb + OFF_UT, &prm.m[M_U], BAR(BR_UIN), c * 80, r * 128); }
      }
      __syncwarp();
      asm volatile("bar.arrive 0, 512;" ::: "memory");
      const unsigned epoch = hw == 0 ? ld_rlx(&g_epoch[cta]) + 1 : 0;
      bar_sync(6, 128);
      if (hw == 1 && elect_one()) {
        #pragma unroll
        for (int i = M_WO; i < M_COUNT; i++) asm volatile("prefetch.tensormap [%0];" :: "l"(&prm.m[i]) : "memory");
      }
      if (ht == 0) {
        st_rlx(&g_epoch[cta], epoch);
        sts32(sb + OFF_EPOCH, epoch);
        mbar_arrive(BAR(BR_EPOCH));
      }
      if (EN_SSM) {
      const int mi = lane >> 3, rw = lane & 7, ch0 = c * 80 + r * 5;
      mbar_wait(BAR(BR_UIN), 0);
      if (ht == 0) TS(36);
      #pragma unroll 1
      for (int h = 0; h < 2; h++) {
        const uint32_t sa = sb + OFF_UT + h * 10240 + (8 * mi + rw) * 160 + hw * 16, da = sb + OFF_UT + h * 10240 + (hw * 8 + rw) * 128 + ((mi ^ rw) << 4);
        uint32_t v[8][4];
        #pragma unroll
        for (int q = 0; q < 8; q++) if (q < 6 || hw == 0) ldsm4t(v[q], sa + (q & 1) * 5120 + (q >> 1) * 48);
        bar_sync(5, 96);
        #pragma unroll
        for (int q = 0; q < 8; q++) if (q < 6 || hw == 0) stsm4((da ^ ((q & 1) * 64)) + (q >> 1) * 3072, v[q][0], v[q][1], v[q][2], v[q][3]);
      }
      fence_async();
      bar_sync(5, 96);
      if (hw == 0) {
        if (elect_one()) {
          tma2d_st(&prm.m[M_SA], sb + OFF_UT, r * 128, c * 80);
          tma2d_st(&prm.m[M_SA], sb + OFF_UT + 10240, r * 128 + 64, c * 80);
          bulk_commit(); bulk_wait0_read();
          mbar_arrive(BAR(BR_UOUT));
          TS(37);
          bulk_wait0();
          st_rel(FLAG(1, r, c), epoch);
          TS(30);
        }
        __syncwarp();
        poll_all_acq(FLAG(1, lane & 15, c), epoch);
        mbar_wait(BAR(BR_KS + 4), 0);
        if (elect_one()) {
          fence_async_g();
          mbar_expect_tx(BAR(BR_U), 20480);
          #pragma unroll 1
          for (int q = 0; q < 5; q++) tma2d(sb + OFF_BLK + q * BLK, &prm.m[M_SB], BAR(BR_U), 0, (ch0 + q) * 32);
          TS(31);
        }
        __syncwarp();
      }
      if (hw == 0) {
        #pragma unroll 1
        for (int p = 0; p < 2; p++) {
          mbar_wait(BAR(BR_Y) + 8 * p, 0);
          if (elect_one()) {
            #pragma unroll 1
            for (int k = 4 * p; k < 4 + p; k++) tma2d_st(&prm.m[M_SB], sb + OFF_BLK + k * BLK, 0, (640 + ch0 + k) * 32);
            bulk_commit(); bulk_wait0_read();
            mbar_arrive(BAR(BR_FREE) + 8 * p);
          }
          __syncwarp();
        }
        if (elect_one()) {
          mbar_expect_tx(BAR(BR_YIN), 20480);
          bulk_wait0();
          st_rel(FLAG(2, r, c), epoch);
          TS(33);
        }
        __syncwarp();
        poll_all_acq(FLAG(2, lane & 15, c), epoch);
        if (EN_ATT) mbar_wait(BAR(BR_OEMPTY + 3), 0);
        if (elect_one()) {
          fence_async_g();
          tma2d(sb + OFF_BLK + BLK, &prm.m[M_SA], BAR(BR_YIN), r * 128, 640 + c * 80);
          tma2d(sb + OFF_BLK + BLK + 10240, &prm.m[M_SA], BAR(BR_YIN), r * 128 + 64, 640 + c * 80);
          TS(34);
        }
      }
      {
        uint32_t sa = sb + OFF_BLK + BLK + (hw * 8 + rw) * 128 + ((mi ^ rw) << 4);
        uint32_t da = sb + OFF_BLK + 2 * BLK + (8 * mi + rw) * 160 + hw * 16;
        mbar_wait(BAR(BR_YIN), 0);
        #pragma unroll 1
        for (int i = hw; i < 10; i += 3) {
          uint32_t v[4][4];
          #pragma unroll
          for (int q = 0; q < 4; q++) ldsm4t(v[q], (sa ^ ((q & 1) * 64)) + (q >> 1) * 10240);
          #pragma unroll
          for (int q = 0; q < 4; q++) stsm4(da + q * 5120, v[q][0], v[q][1], v[q][2], v[q][3]);
          sa += 3072; da += 48;
        }
      }
      fence_async();
      bar_sync(5, 96);
      if (hw == 0 && elect_one()) {
        tma2d_st(&prm.m[M_OUT], sb + OFF_BLK + 2 * BLK, c * 80, r * 128);
        bulk_commit(); bulk_wait0_read();
        TS(35); DUMP(30, 40); DUMP(0, 1);
      }
      }
    }
  } else {
    const int g = lane >> 2, tq = lane & 3, t7 = tid & 127;
    uint32_t pr[2][2], pd;
    {
      const int ch = c * 80 + r * 5 + wg;
      uint32_t raw[2][4];
      #pragma unroll
      for (int e = 0; e < 4; e++) {
        const __nv_bfloat16* pp = prm.par[e] + ch * 128 + t7;
        asm volatile("ld.global.nc.u16 %0, [%1];" : "=r"(raw[0][e]) : "l"(pp));
        asm volatile("ld.global.nc.u16 %0, [%1];" : "=r"(raw[1][e]) : "l"(pp + (wg < 2 ? 384 : 0)));
      }
      asm volatile("ld.global.nc.u16 %0, [%1];" : "=r"(pd) : "l"(((lane & 2) ? prm.dskip : prm.logdt) + ch + ((lane & 1) && wg < 2 ? 3 : 0)));
      asm volatile("setmaxnreg.inc.sync.aligned.u32 152;");
      if (EN_SSM && wg == 2) {
        #pragma unroll 1
        for (int k = 0; k < 5; k++) {
          const uint32_t z = sb + OFF_BLK + k * BLK + t7 * 16;
          sts128(z + B_TBL, 0, 0, 0, 0); sts128(z + B_TBL + 2048, 0, 0, 0, 0);
          if (t7 < 16) sts128(z - 256, 0, 0, 0, 0);
        }
      }
      #pragma unroll
      for (int q = 0; q < 2; q++) {
        #pragma unroll
        for (int e = 0; e < 2; e++) pr[q][e] = raw[q][2 * e] | (raw[q][2 * e + 1] << 16);
        const uint32_t m = __reduce_max_sync(0xffffffff, max(raw[q][2] & 0x7fffu, raw[q][3] & 0x7fffu));
        if (lane == 0) sts32(sb + OFF_EPOCH + 64 + (wg * 2 + q) * 16 + w4 * 4, m);
      }
      bar_sync(2 + wg, 128);
    }
    if (tid == 256) TS(40);
#define P0(w) ((w) == 1 ? OFF_X + 32768 : OFF_BLK + (w) * 3584)
#define P1(w) ((w) == 1 ? 7168 : BLK)
#define P2(w) ((w) == 1 ? OFF_BLK + 4 * BLK - OFF_X - 32768 : 2 * BLK)
    if (EN_SSM) {
      const uint32_t fa = sb + P0(wg) + (lane >> 4) * P1(wg) + (w4 & 1) * P2(wg) + ((lane >> 3) & 1) * 256 + (lane & 7) * 16;
      const uint32_t ea = fa + (w4 >> 1) * 2048, ga = fa + 4096 + (w4 >> 1) * 1536;
      #pragma unroll 1
      for (int q = 0; q < (wg < 2 ? 2 : 1); q++) {
        uint32_t F[56];
#define PUT4(i, a, b, c_, d) { F[4 * (i)] = a; F[4 * (i) + 1] = b; F[4 * (i) + 2] = c_; F[4 * (i) + 3] = d; }
        {
          const uint32_t pa0 = pr[0][0], pc0 = pr[0][1];
          const float dt = bf_round(expf(bf_lo(__shfl_sync(0xffffffff, pd, q))));
          pr[0][0] = pr[1][0]; pr[0][1] = pr[1][1];
          uint32_t mm[4];
          lds128(mm, sb + OFF_EPOCH + 64 + (wg * 2 + q) * 16);
          const uint32_t ex = min(max(max(max(mm[0], mm[1]), max(mm[2], mm[3])) >> 7, 1u), 253u);
          const float sc = __uint_as_float((254u - ex) << 23);
          if (t7 == 2 + q) sts64(sb + OFF_EPOCH + 16 + (wg + 3 * q) * 8, __float_as_uint(2.f * dt * __uint_as_float(ex << 23)), pd << 16);
          const float lr = -bf_round(expf(bf_lo(pa0))) * dt * 1.44269504089f;
          const float tn = bf_hi(pa0) * dt * 0.15915494309f;
          float z1r, z1i, z2r, z2i, z4r, z4i, xr[8], xi[8], gr[8], gi[8], wr[9], wi[9];
          cexp_t(lr, -tn, z1r, z1i);
          cexp_t(lr * 8.f, tn * 8.f, xr[1], xi[1]);
          cexp_t(lr * 64.f, tn * 64.f, wr[0], wi[0]);
          xr[0] = 1.f; xi[0] = 0.f;
          cmul(xr[1], xi[1], xr[1], xi[1], xr[2], xi[2]); cmul(xr[2], xi[2], xr[1], xi[1], xr[3], xi[3]);
          cmul(xr[2], xi[2], xr[2], xi[2], xr[4], xi[4]);
          #pragma unroll
          for (int b = 1; b < 4; b++) cmul(xr[4], xi[4], xr[b], xi[b], xr[4 + b], xi[4 + b]);
          cmul(wr[0], wi[0], wr[0], wi[0], wr[1], wi[1]); cmul(wr[1], wi[1], wr[0], wi[0], wr[2], wi[2]);
          cmul(wr[1], wi[1], wr[1], wi[1], wr[3], wi[3]); cmul(wr[3], wi[3], wr[3], wi[3], wr[4], wi[4]);
          cmul(wr[4], wi[4], wr[3], wi[3], wr[5], wi[5]); cmul(wr[4], wi[4], wr[4], wi[4], wr[6], wi[6]);
          cmul(wr[6], wi[6], wr[4], wi[4], wr[7], wi[7]); cmul(wr[6], wi[6], wr[6], wi[6], wr[8], wi[8]);
          uint32_t R[4], I[4], PR[4], PI[4];
          #pragma unroll
          for (int b = 0; b < 4; b++) { R[b] = packh(xr[2 * b], xr[2 * b + 1]); I[b] = packh(xi[2 * b], xi[2 * b + 1]); }
          PUT4(0, R[0], R[1], R[2], R[3]); PUT4(1, I[0], I[1], I[2], I[3]);
          #pragma unroll
          for (int i = 0; i < 3; i++) {
            const uint32_t z = packh(wr[i], wi[i]);
            #pragma unroll
            for (int b = 0; b < 4; b++) hcm2(R[b], I[b], z, PR[b], PI[b]);
            PUT4(2 * i + 2, PR[0], PR[1], PR[2], PR[3]); PUT4(2 * i + 3, PI[0], PI[1], PI[2], PI[3]);
          }
          gr[0] = bf_lo(pc0) * sc; gi[0] = -bf_hi(pc0) * sc;
          cmul(z1r, z1i, z1r, z1i, z2r, z2i); cmul(z2r, z2i, z2r, z2i, z4r, z4i);
          cmul(gr[0], gi[0], z1r, z1i, gr[1], gi[1]);
          cmul(gr[0], gi[0], z2r, z2i, gr[2], gi[2]); cmul(gr[1], gi[1], z2r, z2i, gr[3], gi[3]);
          #pragma unroll
          for (int b = 0; b < 4; b++) cmul(gr[b], gi[b], z4r, z4i, gr[4 + b], gi[4 + b]);
          PUT4(8, packh(gr[0], gr[1]), packh(gr[2], gr[3]), packh(gr[4], gr[5]), packh(gr[6], gr[7]));
          PUT4(9, packh(gi[0], gi[1]), packh(gi[2], gi[3]), packh(gi[4], gi[5]), packh(gi[6], gi[7]));
          {
            const uint32_t z = packh(wr[3], -wi[3]), a4r = packh(gr[0], gr[4]), a4i = packh(gi[0], gi[4]);
            hcm2(packh(gr[0], gr[2]), packh(gi[0], gi[2]), z, PR[0], PI[0]);
            hcm2(packh(gr[4], gr[6]), packh(gi[4], gi[6]), z, PR[1], PI[1]);
            hcm2(a4r, a4i, packh(wr[4], -wi[4]), PR[2], PI[2]);
            hcm2(a4r, a4i, packh(wr[5], -wi[5]), PR[3], PI[3]);
            PUT4(10, PR[0], PR[1], PR[2], PR[3]); PUT4(11, PI[0], PI[1], PI[2], PI[3]);
            float hr, hi_;
            cmul(gr[0], gi[0], wr[3], -wi[3], hr, hi_);
            const uint32_t cr = packh(gr[0], hr), ci = packh(gi[0], hi_);
            #pragma unroll
            for (int i = 0; i < 3; i++) hcm2(cr, ci, packh(wr[6 + i], -wi[6 + i]), PR[i], PI[i]);
            PUT4(12, PR[0], PR[1], PR[2], 0u); PUT4(13, PI[0], PI[1], PI[2], 0u);
          }
        }
        if (q) mbar_wait(BAR(BR_KS + 1) - 8 * wg, 0);
        #pragma unroll
        for (int i = 0; i < 14; i++) sts128((i < 8 ? ea + (i >> 1) * 512 : ga + ((i - 8) >> 1) * 512) + (i & 1) * 128, F[4 * i], F[4 * i + 1], F[4 * i + 2], F[4 * i + 3]);
        fence_async();
        if (q) mbar_arrive(BAR(BR_KF)); else bar_sync(0, 512);
        if (tid == 0) TS(17 + q);
      }
    }
    if (!EN_SSM) bar_sync(0, 512);
    if (tid == 0) TS(14);
  if (wg < 2) {
    if (EN_ATT) {
    float am[96], ar[24];
    {
      const bool lead = (rtid() & 127) == 0;
      constexpr uint64_t da0 = mkdesc(SB0 + OFF_X, 16, 1024, 1), dr0 = mkdesc(SB0 + 12288, 1024, 256, 3);
      const uint64_t db0 = sw64 ? mkdesc(SB0, 2048, 512, 2) : mkdesc(SB0, 4096, 1024, 1);
      const uint32_t kst = sw64 ? 64 : 128, bh = db0 >> 32;
      uint32_t s = 0, ph = 0, xo = 0;
      #pragma unroll 1
      for (int kb = 0; kb < 20; kb++) {
        const uint32_t wo_ = s * (W_SLOT >> 4), al = (uint32_t)da0 + wg * 512 + xo, bl = (uint32_t)db0 + wo_, rl = (uint32_t)dr0 + wo_;
        mbar_wait(BAR(BR_FULL) + 8 * s, ph);
        if (kb == 0 && lead && wg == 0) TS(1);
        wg_fence();
        wg_ss192_tb(am, desc2(al, da0 >> 32), desc2(bl, bh), kb != 0);
        wg_ss48_tb(ar, desc2(al, da0 >> 32), desc2(rl, dr0 >> 32), kb != 0);
        wg_ss192_tb(am, desc2(al + 2, da0 >> 32), desc2(bl + kst, bh), 1);
        wg_ss48_tb(ar, desc2(al + 2, da0 >> 32), desc2(rl + 32, dr0 >> 32), 1);
        wg_commit();
        wg_wait<1>();
        if (lead && kb > 0 && kb < 16) mbar_arrive(BAR(BR_EMPTY) + 8 * (s == 0 ? 4 : s - 1));
        if (++s == 5) { s = 0; ph ^= 1; }
        xo += (kb & 1) ? 1020 : 4;
        if (xo == 3072) xo = 0;
      }
      wg_wait<0>();
      pin<96>(am); pin<24>(ar);
    }
    const int tid = rtid(), lane = tid & 31, tq = lane & 3;
    if (tid == 0) TS(2);
#define QV(j, e) ((j) < 8 ? am[4 * (j) + (e)] : ar[4 * ((j) - 8) + (e)])
#define KV_(j, e) ((j) < 8 ? am[32 + 4 * (j) + (e)] : ar[8 + 4 * ((j) - 8) + (e)])
#define VV(j, e) ((j) < 8 ? am[64 + 4 * (j) + (e)] : ar[16 + 4 * ((j) - 8) + (e)])
    {
      bar_sync(1, 256);
      if (tid == 0) mbar_arrive(BAR(BR_GEMM));
      const uint32_t ro = sb + (uint32_t)((warp * 16 + (lane & 15)) * 16);
      const int l0 = 2 * (c & 1) + (lane >> 4);
      const uint32_t ones = (tq == 0) ? 0x00003f80u : 0u;
#define PV(j) pack2(VV(j, 0), VV(j, 1)), pack2(VV(j, 2), VV(j, 3))
#define PK(j) pack2(phi(KV_(j, 0)), phi(KV_(j, 1))), pack2(phi(KV_(j, 2)), phi(KV_(j, 3)))
      stsm4(ro + OFF_V + (5 + 6 * (lane >> 4)) * 2048, ones, ones, ones, ones);
      #pragma unroll
      for (int j = 0; j < 10; j += 2) {
        const int l = (j == 8 && (c & 1)) ? l0 - 2 : l0 + j;
        stsm4(ro + OFF_V + (l + (l >= 5)) * 2048, PV(j), PV(j + 1));
        stsm4(ro + OFF_PK + l * 2048, PK(j), PK(j + 1));
      }
    }
    fence_async();
    bar_sync(1, 256);
    if (tid == 0) TS(3);
    mbar_wait(BAR(BR_EPOCH), 0);
    const unsigned epoch = lds32(sb + OFF_EPOCH);
    {
      float kv[24]; zero<24>(kv);
      constexpr uint64_t da = mkdesc(SB0 + OFF_PK, 128, 2048, 0), db = mkdesc(SB0 + OFF_V, 128, 2048, 0);
      wg_fence();
      #pragma unroll
      for (int s = 0; s < 8; s++) wg_ss48_tt(kv, desc2((uint32_t)da + wg * 640 + s * 16, da >> 32), desc2((uint32_t)db + wg * 768 + s * 16, db >> 32), s != 0);
      wg_commit();
      wg_wait<0>();
      pin<24>(kv);
      if (tid == 0) TS(15);
      if (w4 < 3) {
        const uint32_t wb = sb + OFF_KVS + (wg * 3 + w4) * 1536 + (lane & 15) * 96;
        #pragma unroll
        for (int j = 0; j < 6; j += 2)
          stsm4(wb + (j + (lane >> 4)) * 16, pack2(kv[4 * j], kv[4 * j + 1]), pack2(kv[4 * j + 2], kv[4 * j + 3]),
                pack2(kv[4 * j + 4], kv[4 * j + 5]), pack2(kv[4 * j + 6], kv[4 * j + 7]));
        __syncwarp();
        const int dl = w4 * 16 + (lane & 15), hl = dl >= 20;
        if (dl < 40) {
          uint4* dst = &g_kvp[(c * 16 + r) * 240 + wg * 40 + dl];
          uint32_t v[4], z[4];
          lds128(v, wb + (3 * hl + (lane >> 4)) * 16);
          lds64(z, wb + 32 + 8 * hl); z[2] = lds32(wb + 80); z[3] = epoch & 1u;
          v[3] = (v[3] & ~1u) | z[3];
          st128_rlx(dst + (lane >> 4) * 80, v);
          if (lane < 16) st128_rlx(dst + 160, z);
        }
      }
    }
    fence_async();
    bar_sync(1, 256);
    if (tid == 0) { st_rlx(FLAG(0, r, c), epoch); mbar_arrive(BAR(BR_PUB)); TS(4); }
    const int kvi = (tid >= 80) + (tid >= 160) + (tid >= 240), kd = tid - 80 * kvi;
    const int khd = kd / 20, kt0 = 5 * (khd >> 1) + 2 * (khd & 1);
    const uint32_t rb = sb + OFF_KVB + kd * 16;
    if (kvi < 3) {
      #pragma unroll 1
      for (int m = kvi; m < 7; m += 3) { const int q = kt0 + 3 + m; sts128(rb + (q >= 10 ? q - 10 : q) * 1280, 0, 0, 0, 0); }
    }
    uint32_t qa[20];
    {
      const float sc = 1.44269504089f + __uint_as_float(lds32(sb + OFF_EPOCH) ^ epoch);
      #pragma unroll
      for (int j = 0; j < 10; j++) { qa[2 * j] = pack2(phi(QV(j, 0), sc), phi(QV(j, 1), sc)); qa[2 * j + 1] = pack2(phi(QV(j, 2), sc), phi(QV(j, 3), sc)); }
    }
    if (tid == 0) TS(5);
    mbar_wait(BAR(BR_KVP), 0);
    if (tid == 0) TS(6);
    if (kvi < 3) {
      float s[8];
      zero<8>(s);
      uint32_t bad = 0;
      #pragma unroll 4
      for (int i = 0; i < 16; i++) {
        uint32_t w[4];
        lds128(w, sb + OFF_KVP + tid * 16 + i * 3840);
        bad |= w[3] ^ epoch;
        #pragma unroll
        for (int e = 0; e < 4; e++) { s[2 * e] += bf_lo(w[e]); s[2 * e + 1] += bf_hi(w[e]); }
      }
      if (__builtin_expect(bad & 1u, 0)) {
        zero<8>(s);
        #pragma unroll 1
        for (int i = 0; i < 16; i++) {
          uint32_t w[4] = {0, 0, 0, ~epoch};
          fix128_w3(w, &g_kvp[(c * 16 + i) * 240 + tid], epoch, 1u);
          #pragma unroll
          for (int e = 0; e < 4; e++) { s[2 * e] += bf_lo(w[e]); s[2 * e + 1] += bf_hi(w[e]); }
        }
        FIXCNT
      }
      const uint32_t p0 = pack2(s[0], s[1]), p1 = pack2(s[2], s[3]), p2 = pack2(s[4], s[5]), p3 = pack2(s[6], s[7]);
      if (kvi < 2) sts128(rb + (kt0 + (khd & 1) + kvi) * 1280, p0, p1, p2, p3);
      else {
        const bool od = khd & 1;
        sts128(rb + (5 * (khd >> 1) + 2) * 1280, od ? 0u : p0, od ? 0u : p1, od ? p0 : 0u, od ? p1 : 0u);
        const uint32_t zz = (p2 & 0xffffu) << (16 * (khd & 1));
        sts128(rb + 10 * 1280, khd < 2 ? zz : 0u, khd < 2 ? 0u : zz, 0u, 0u);
      }
    }
    fence_async();
    bar_sync(1, 256);
    if (tid == 0) { mbar_arrive(BAR(BR_SUM)); TS(7); }
    {
      float oa[44]; zero<44>(oa);
      constexpr uint64_t db = mkdesc(SB0 + OFF_KVB, 128, 1280, 0);
      wg_fence();
      #pragma unroll
      for (int s = 0; s < 5; s++) wg_rs88_tb(oa, &qa[4 * s], desc2((uint32_t)db + ((s == 4 && (c & 1)) ? 0 : (s + (c & 1)) * 16), db >> 32), s != 0);
      wg_commit();
      wg_wait<0>();
      pin<44>(oa);
      if (tid == 0) TS(13);
      float rc[4], rd[2][4];
      #pragma unroll
      for (int e = 0; e < 4; e++) asm("rcp.approx.ftz.f32 %0, %1;" : "=f"(rc[e]) : "f"(oa[40 + e] + 1e-6f));
      #pragma unroll
      for (int h = 0; h < 4; h++) {
        rd[0][h] = __shfl_sync(0xffffffff, rc[h & 1], (lane & 28) | (h >> 1));
        rd[1][h] = __shfl_sync(0xffffffff, rc[2 + (h & 1)], (lane & 28) | (h >> 1));
      }
      #pragma unroll
      for (int j = 0; j < 10; j++) {
        #pragma unroll
        for (int h = 0; h < 2; h++) {
          float f;
          if (j == 2) f = tq < 2 ? rd[h][0] : rd[h][1];
          else if (j == 7) f = tq < 2 ? rd[h][2] : rd[h][3];
          else f = rd[h][(8 * j) / 20];
          qa[2 * j + h] = pack2(oa[4 * j + 2 * h] * f, oa[4 * j + 2 * h + 1] * f);
        }
      }
      const uint32_t m0 = (lane & 7) == ((2 * w4) & 7), m1 = (lane & 7) == 2 * w4 + 1;
      const uint32_t oa_ = sb + OFF_EXTRA + (lane >> 4) * 2048 + (warp * 16 + (lane & 15)) * 16;
      bar_sync(1, 256);
#define TAG(v, m) (((v) & ~(m)) | (epoch & (m)))
      #pragma unroll
      for (int s = 0; s < 5; s++) stsm4(oa_ + s * 4096, TAG(qa[4 * s], m0), TAG(qa[4 * s + 1], m1), TAG(qa[4 * s + 2], m0), TAG(qa[4 * s + 3], m1));
    }
    fence_async();
    mbar_arrive(BAR(BR_OSTG));
    if (tid == 0) TS(8);
    float oc[40]; zero<40>(oc);
    {
      constexpr uint64_t dw0 = mkdesc(SB0, OFF_WOR, 1024, 1), da0 = mkdesc(SB0, 2048, 128, 0);
      const uint32_t ck = sb + tid * 32 + ((lane >> 2) << 2), ck2 = ck + (wg ? 0 : 16384);
      uint32_t bad = 0;
      auto tile = [&](int i, uint32_t so) {
        const uint32_t al = (uint32_t)da0 + wg * 64 + (so >> 4), wl = (uint32_t)dw0 + i * 640 - (i >> 1) * (1278 << 16);
        wg_fence();
        #pragma unroll
        for (int s = 0; s < 5; s++) wg_ss80_tb(oc, desc2(al + s * 256, da0 >> 32), desc2(wl + s * 128, dw0 >> 32), (i | s) != 0);
        wg_commit();
        bad |= (lds32(ck + so) ^ epoch) | (lds32(ck + so + 8192) ^ epoch) | (lds32(ck2 + so) ^ epoch);
      };
      mbar_wait(BAR(BR_WO), 0);
      mbar_wait(BAR(BR_OSTG), 0);
      tile(0, SLOT(0));
      mbar_wait(BAR(BR_WO + 1), 0);
      #pragma unroll 1
      for (int i = 1; i < 8; i++) {
        if (i == 1) { wg_wait<0>(); if (lane == 0) mbar_arrive(BAR(BR_OEMPTY)); }
        mbar_wait(BAR(BR_OFULL) + 8 * i, 0);
        if (i == 1 && tid == 0) TS(9);
        tile(i, SLOT(i));
        wg_wait<1>();
        if (lane == 0 && i > 1) mbar_arrive(BAR(BR_OEMPTY - 1) + 8 * i);
      }
      #pragma unroll 1
      for (int n = 0; n < 56; n++) {
        const int i = n & 7;
        if (i == 0) {
          uint32_t any;
          asm volatile("{\n.reg .pred p;\nsetp.ne.u32 p, %1, 0;\nbarrier.red.or.pred p, 1, 256, p;\nselp.u32 %0, 1, 0, p;\n}" : "=r"(any) : "r"(bad & 1u) : "memory");
          if (!any) break;
          bad = 0;
          FIXCNT
        }
        wg_wait<0>();
        bar_sync(1, 256);
        if (tid == 0) { mbar_expect_tx(BAR(BR_RETRY), 20480); bulk_ld(sb + SLOT(0), &g_o[(r * 8 + CHUNK(i)) * 1280], 20480, BAR(BR_RETRY)); }
        mbar_wait(BAR(BR_RETRY), n & 1);
        tile(i, SLOT(0));
      }
      wg_wait<0>();
      pin<40>(oc);
    }
    if (tid == 0) TS(10);
    {
      const int row = w4 * 16 + (lane & 15);
      const uint32_t ob = sb + SLOT(4) + wg * 10240;
      #pragma unroll
      for (int j = 0; j < 8; j += 2)
        stsm4(ob + row * 128 + (((j + (lane >> 4)) ^ (row & 7)) << 4), pack2(oc[4 * j], oc[4 * j + 1]), pack2(oc[4 * j + 2], oc[4 * j + 3]),
              pack2(oc[4 * j + 4], oc[4 * j + 5]), pack2(oc[4 * j + 6], oc[4 * j + 7]));
      stsm4(ob + 8192 + row * 32 + (lane >> 4) * 16, pack2(oc[32], oc[33]), pack2(oc[34], oc[35]), pack2(oc[36], oc[37]), pack2(oc[38], oc[39]));
      fence_async();
      bar_sync(2 + wg, 128);
      if (w4 == 0 && elect_one()) {
        tma2d_st(&prm.m[M_O64], ob, 640 + c * 64, r * 128 + wg * 64);
        tma2d_st(&prm.m[M_O16], ob + 8192, 1152 + c * 16, r * 128 + wg * 64);
        bulk_commit(); bulk_wait0_read();
        if (wg == 0) { TS(11); DUMP(0, 20); }
      }
    }
    }
  } else {
    if (EN_SSM) {
    const int tid = rtid(), lane = tid & 31, g = lane >> 2, tq = lane & 3, t7 = tid & 127;
    {
      constexpr uint64_t dE = mkdesc(SB0, 128, 512, 0);
      const uint32_t xa = sb + OFF_BLK + 18560 + t7 * 8, xr_ = sb + OFF_BLK + 18560 + (t7 ^ 64) * 8;
      float ka[24]; zero<24>(ka);
      auto product = [&](int fs) {
        wg_fence();
        #pragma unroll
        for (int s = 0; s < 8; s++) {
          const uint32_t lo = (uint32_t)dE + ((P0(fs) + ((s >> 1) & 1) * P1(fs) + (s >> 2) * P2(fs)) >> 4) + (s & 1) * 16;
          wg_ss48_tt_h(ka, desc2(lo, dE >> 32), desc2(lo + 256, dE >> 32), s != 0);
        }
        wg_commit();
      };
      product(1);
      #pragma unroll 1
      for (int it = 0; it < 5; it++) {
        const int k = (0x34201 >> (4 * it)) & 7;
        const uint32_t blk = sb + OFF_BLK + k * BLK;
        uint32_t fd[2];
        lds64(fd, sb + OFF_EPOCH + 16 + k * 8);
        const float fac = __uint_as_float(fd[0]), dsk = __uint_as_float(fd[1]);
        wg_wait<0>();
        pin<24>(ka);
        float kk[6];
        const bool up = w4 >= 2;
        if (it) bar_sync(4, 128);
        #pragma unroll
        for (int n = 0; n < 3; n++) {
          sts64f(xa + n * BLK, up ? ka[12 + 4 * n] : ka[4 * n + 2], up ? ka[13 + 4 * n] : ka[4 * n + 3]);
          kk[2 * n] = up ? ka[14 + 4 * n] : ka[4 * n]; kk[2 * n + 1] = up ? ka[15 + 4 * n] : ka[4 * n + 1];
        }
        pin<6>(kk);
        bar_sync(4, 128);
        if (t7 == 0) mbar_arrive(BAR(BR_KS) + 8 * it);
        if (it == 2) mbar_wait(BAR(BR_KF), 0);
        product((0x20120 >> (4 * it)) & 3);
        #pragma unroll
        for (int n = 0; n < 3; n++) {
          uint32_t o[2]; lds64(o, xr_ + n * BLK);
          kk[2 * n] = (kk[2 * n] + __uint_as_float(o[0])) * fac; kk[2 * n + 1] = (kk[2 * n + 1] + __uint_as_float(o[1])) * fac;
        }
        {
          const int j = (w4 & 1) * 16 + (w4 >> 1) * 8 + g;
          const uint32_t tb = blk + B_TBL;
          if (t7 == 0) kk[0] += dsk;
          const uint32_t pa_ = tb + (16 + 8 * j + 2 * tq) * 4;
          const uint32_t v = pack2(kk[1], kk[0]);
          sts32(pa_ + 4, v); sts16(pa_, v >> 16); sts16(pa_ + 10, v);
          const uint32_t u = pack2(kk[2], kk[3]), w = pack2(kk[4], kk[5]);
          if (tq < 2) {
            const uint32_t pb = tb + (16 + 256 + 8 * j + 4 * tq) * 4;
            sts16(pb, u); sts32(pb + 4, __byte_perm(u, 0, 0x1010)); sts32(pb + 8, __byte_perm(u, 0, 0x1032)); sts16(pb + 14, u >> 16);
            if (j | tq) { sts16(pb - 4, u); sts16(pb + 2, u); }
            const int i = 64 * tq + j;
            const uint32_t e0 = tb + (T_F3 + (((i - 1) & 1) ? 80 : 0) + ((i - 1) >> 1)) * 4, e1 = i ? e0 : tb + (T_F2 + 144 + 31) * 4;
            sts16(e1, w); sts16(e1 + 6, w); sts16(e0 + 64, w >> 16); sts16(e0 + 70, w >> 16);
            if (i == 0) { sts16(tb + (T_S + 3) * 4, w); sts32(tb + (T_S + 4) * 4, __byte_perm(w, 0, 0x1010)); sts16(tb + (T_S + 5) * 4 + 2, w); }
          } else {
            const int i = 32 * (tq - 2) + j;
            const uint32_t e1 = tb + (i ? T_F2 + ((2 * i - 1) & 3) * 48 + ((2 * i - 1) >> 2) : 16 + 511) * 4;
            const uint32_t e2 = tb + (T_F2 + (i & 1) * 96 + (i >> 1)) * 4;
            sts16(e1, u); sts16(e1 + 6, u); sts16(e2, u >> 16); sts16(e2 + 6, u >> 16);
            if (i == 0) {
              const uint32_t uu = __byte_perm(u, 0, 0x1010);
              sts32(tb + 528 * 4, uu); sts32(tb + 529 * 4, uu); sts32(tb + 530 * 4, uu); sts16(tb + 531 * 4 + 2, u);
              sts16(tb + (T_F3 + 80 + 63) * 4, w);
            }
          }
        }
        if (t7 == 0) TS(48 + it);
      }
      wg_wait<0>();
    }
    if (t7 == 0) TS(41);
    if (EN_SSM) {
      mbar_wait(BAR(BR_U), 0);
      bar_sync(4, 128);
      if (t7 == 0) TS(43);
      #pragma unroll 1
      for (int q6 = w4; q6 < 30; q6 += 4) {
        {
          const int k = q6 / 6, kap = (q6 - 6 * k) * 32 + lane;
          const uint32_t blk = sb + OFF_BLK + k * BLK;
          float P[33];
          P[0] = 0.f;
          #pragma unroll
          for (int q = 0; q < 4; q++) {
            const int ch = kap - 3 + q;
            uint32_t v[4];
            lds128(v, blk + (uint32_t)((ch * 16) ^ ((ch * 2) & 0x70)));
            #pragma unroll
            for (int e = 0; e < 4; e++) {
              P[q * 8 + 2 * e + 1] = (q == 0 && e < 2) ? 0.f : P[q * 8 + 2 * e] + bf_lo(v[e]);
              P[q * 8 + 2 * e + 2] = (q == 0 && e < 2) ? 0.f : P[q * 8 + 2 * e + 1] + bf_hi(v[e]);
            }
          }
#define WIN(lo, hi, e) (P[25 + (e) - (lo)] - P[24 + (e) - (hi)])
#define WIN8(lo, hi) pack2(WIN(lo, hi, 0), WIN(lo, hi, 1)), pack2(WIN(lo, hi, 2), WIN(lo, hi, 3)), pack2(WIN(lo, hi, 4), WIN(lo, hi, 5)), pack2(WIN(lo, hi, 6), WIN(lo, hi, 7))
          const uint32_t o2 = blk + B_D + (kap & 1) * 1552 + (kap >> 1) * 16;
          sts128(o2, WIN8(3, 5));
          sts128(o2 + B_D5, WIN8(6, 10));
          if (kap < 128) {
            const uint32_t o = blk + B_D + (kap & 1) * 1024 + (kap >> 1) * 16;
            sts128(o + B_D7, WIN8(5, 11));
            sts128(o + B_D9, WIN8(12, 20));
          }
        }
      }
      if (t7 < 10) sts128(sb + OFF_BLK + (t7 >> 1) * BLK + B_D + (t7 & 1) * B_D5 + 1536, 0, 0, 0, 0);
      bar_sync(4, 128);
      if (t7 == 0) TS(44);
    }
    if (EN_ATT) mbar_wait(BAR(BR_GEMM), 0);
    if (t7 == 0) TS(42);
    #pragma unroll 1
    for (int pass = 1; pass >= 0; pass--) {
      const int k = pass ? w4 : 4;
      const uint32_t blk = sb + OFF_BLK + k * BLK, tb = blk + B_TBL + (uint32_t)((g - 2 * tq) * 4);
      float acc[16][4];
      zero<64>(&acc[0][0]);
      const int kl = 16 * (lane >> 4) + 2 * (lane & 7) + ((lane >> 3) & 1);
      {
        auto ubase = [&](int sh) { const int q = kl - 2 * sh; return blk + (uint32_t)((q * 16) ^ ((q * 2) & 0x70)); };
#define LDQ(A, sh) _Pragma("unroll") for (int m = 0; m < 4; m++) load_quad(A[m], tb + (16 + 16 * (sh) + 128 * m) * 4);
#define LDB(B, ub, h) _Pragma("unroll") for (int p = 0; p < 4; p++) ldsm4(B[p], ((ub) ^ ((p & 1) * 64)) + (4 * (h) + p) * 512);
#define MLO(A, B) _Pragma("unroll") for (int m = 0; m < 4; m++) _Pragma("unroll") for (int cc = 0; cc < 8; cc++) mma16816(acc[cc + m], A[m], &B[cc >> 1][(cc & 1) * 2]);
#define MHI(A, B) _Pragma("unroll") for (int m = 0; m < 4; m++) _Pragma("unroll") for (int cc = 0; cc < 8 - m; cc++) mma16816(acc[8 + cc + m], A[m], &B[cc >> 1][(cc & 1) * 2]);
        int p_ = pass ? 0 : w4;
        const int pe = pass ? 4 : w4 + 1;
        uint32_t A[4][4], A2[4][4], Bl[4][4], Bh[4][4];
        uint32_t ub = ubase(p_ + 4);
        LDQ(A, p_ + 4) LDB(Bl, ub, 0)
        #pragma unroll 1
        for (; p_ < pe; p_++) {
          LDB(Bh, ub, 1)
          MLO(A, Bl)
          ub = ubase(p_);
          LDQ(A2, p_) LDB(Bl, ub, 0)
          MHI(A, Bh)
          LDB(Bh, ub, 1)
          load_quad(A[0], tb + (16 + 512 + 16 * (p_ & 1)) * 4); load_quad(A[1], tb + (T_S + 16 * (p_ & 1)) * 4);
          MLO(A2, Bl)
          if (p_ < 2) {
            #pragma unroll
            for (int cc = 0; cc < 8; cc++) mma16816(acc[cc + 4], A[0], &Bl[cc >> 1][(cc & 1) * 2]);
            #pragma unroll
            for (int cc = 0; cc < 4; cc++) mma16816(acc[cc + 12], A[0], &Bh[cc >> 1][(cc & 1) * 2]);
            #pragma unroll
            for (int cc = 0; cc < 8; cc++) mma16816(acc[cc + 8], A[1], &Bl[cc >> 1][(cc & 1) * 2]);
          }
          const int pn = ((p_ + 1) & 3) + 4;
          ub = ubase(pn);
          LDQ(A, pn) LDB(Bl, ub, 0)
          MHI(A2, Bh)
        }
      }
      if (t7 == 0) TS(57 + 3 * pass);
      {
        const int ih = (lane >> 3) & 1;
        const uint32_t dl = blk + B_D + (uint32_t)(((lane >> 4) * 8 + (lane & 7)) * 16);
        const uint32_t d0_ = dl + ih * 1552, d8_ = dl + (ih ? 0 : 1536), d3_ = dl + B_D7 + ih * 1024;
        auto cls2 = [&](uint32_t da, uint32_t ta) {
          uint32_t B[6][2], A[6][4];
          #pragma unroll
          for (int e = 0; e < 6; e++) { B[e][0] = lds32v(ta + (e + 4) * 32); B[e][1] = lds32v(ta + (e + 3) * 32); }
          #pragma unroll
          for (int kk = 0; kk < 6; kk++) ldsm4t(A[kk], da + kk * 256);
          #pragma unroll
          for (int e = 0; e < 6; e++)
            #pragma unroll
            for (int kk = 0; kk < 6; kk++) if (2 * kk + e + 4 < 16) mma16816(acc[2 * kk + e + 4], A[kk], B[e]);
        };
        auto cls3 = [&](uint32_t da, uint32_t ta) {
          uint32_t B[8][2], A[4][4];
          #pragma unroll
          for (int e = 0; e < 8; e++) { B[e][0] = lds32v(ta + (e + 8) * 32); B[e][1] = lds32v(ta + (e + 7) * 32); }
          #pragma unroll
          for (int kk = 0; kk < 4; kk++) ldsm4t(A[kk], da + kk * 256);
          #pragma unroll
          for (int kk = 0; kk < 4; kk++)
            #pragma unroll
            for (int e = 0; e < 8; e++) if (2 * kk + e + 8 < 16) mma16816(acc[2 * kk + e + 8], A[kk], B[e]);
        };
        #pragma unroll 1
        for (int a = pass ? 0 : w4; a < (pass ? 4 : w4 + 1); a++) cls2(((a & 2) ? d8_ : d0_) + (a & 1) * B_D5, tb + (T_F2 + 48 * a - 32) * 4);
        #pragma unroll 1
        for (int b = pass ? 0 : (w4 & 1); b < (pass ? 2 : w4 - 1); b++) cls3(d3_ + b * 2048, tb + (T_F3 + 80 * b - 64) * 4);
      }
      if (t7 == 0) TS(58 + 3 * pass);
      const uint32_t ya = blk + (uint32_t)((kl * 16) ^ ((kl * 2) & 0x70));
#define STY(p) stsm4t((ya ^ (((p) & 1) * 64)) + (p) * 512, pack2(acc[2 * (p)][0], acc[2 * (p)][1]), pack2(acc[2 * (p)][2], acc[2 * (p)][3]), \
                      pack2(acc[2 * (p) + 1][0], acc[2 * (p) + 1][1]), pack2(acc[2 * (p) + 1][2], acc[2 * (p) + 1][3]))
      if (pass == 0) {
        const uint32_t xw = blk + 4096 + w4 * 4096 + lane * 16, xr = blk + 4096 + w4 * 1024 + lane * 16;
        #pragma unroll
        for (int h = 0; h < 2; h++) {
          bar_sync(4, 128);
          #pragma unroll
          for (int i = 0; i < 8; i++)
            sts128(xw + i * 512, __float_as_uint(acc[8 * h + i][0]), __float_as_uint(acc[8 * h + i][1]), __float_as_uint(acc[8 * h + i][2]), __float_as_uint(acc[8 * h + i][3]));
          bar_sync(4, 128);
          float y[8];
          #pragma unroll
          for (int i = 0; i < 8; i++) {
            uint32_t o[4]; lds128(o, xr + (i >> 1) * 4096 + (i & 1) * 512);
            #pragma unroll
            for (int e = 0; e < 4; e++) y[4 * (i & 1) + e] = i < 2 ? __uint_as_float(o[e]) : y[4 * (i & 1) + e] + __uint_as_float(o[e]);
          }
          stsm4t((ya ^ ((w4 & 1) * 64)) + (4 * h + w4) * 512, pack2(y[0], y[1]), pack2(y[2], y[3]), pack2(y[4], y[5]), pack2(y[6], y[7]));
        }
      } else {
        __syncwarp();
        #pragma unroll
        for (int p = 0; p < 8; p++) STY(p);
      }
      if (t7 == 0 && !pass) TS(55);
      fence_async();
      mbar_arrive(BAR(BR_Y + 1) - 8 * pass);
      if (t7 == 0) TS(59 + 3 * pass);
    }
    if (t7 == 0) DUMP(40, 64);
    }
  }
  }
}

typedef CUresult (*EncFn)(CUtensorMap*, CUtensorMapDataType, cuuint32_t, void*, const cuuint64_t*, const cuuint64_t*, const cuuint32_t*,
                          const cuuint32_t*, CUtensorMapInterleave, CUtensorMapSwizzle, CUtensorMapL2promotion, CUtensorMapFloatOOBfill);
static void mkmap(EncFn enc, CUtensorMap* m, const void* base, int rank, const cuuint64_t* dims, const cuuint64_t* strides, const cuuint32_t* box, CUtensorMapSwizzle swz) {
  cuuint32_t es[5] = {1, 1, 1, 1, 1};
  enc(m, CU_TENSOR_MAP_DATA_TYPE_BFLOAT16, rank, const_cast<void*>(base), dims, strides, box, es, CU_TENSOR_MAP_INTERLEAVE_NONE, swz,
      CU_TENSOR_MAP_L2_PROMOTION_L2_128B, CU_TENSOR_MAP_FLOAT_OOB_FILL_NONE);
}

extern "C" void kernel_launch(void* const* d_in, const int* in_sizes, int n_in, void* d_out, int out_size) {
  void* fn = nullptr; cudaDriverEntryPointQueryResult qr;
  cudaGetDriverEntryPoint("cuTensorMapEncodeTiled", &fn, cudaEnableDefault, &qr);
  EncFn enc = (EncFn)fn;
  void* uy = nullptr; cudaGetSymbolAddress(&uy, g_uy);
  const cuuint64_t dx[2] = {640, 2048}, sx[1] = {1280};
  const cuuint32_t bx[2] = {64, 128}, bu[2] = {80, 128};
  const cuuint64_t dw[3] = {640, 640, 3}, sw[2] = {3840, 1280};
  const cuuint32_t br[3] = {16, 32, 3};
  const cuuint64_t dwa[4] = {64, 640, 10, 3}, swa[3] = {3840, 128, 1280}, dwb[4] = {32, 640, 20, 3}, swb[3] = {3840, 64, 1280};
  const cuuint32_t bwa[4] = {64, 32, 1, 3}, bwb[4] = {32, 32, 2, 3};
  const cuuint64_t dwo[2] = {640, 640};
  const cuuint32_t bwo[2] = {64, 80}, bo64[2] = {64, 64}, bo16[2] = {16, 64};
  const cuuint64_t dsa[2] = {2048, 1280}, ssa[1] = {4096};
  const cuuint32_t bsa[2] = {64, 80};
  const cuuint64_t dsb[2] = {64, 40960}, ssb[1] = {128};
  const cuuint32_t bsb[2] = {64, 32};
  const cuuint64_t dout[2] = {1280, 2048}, sout[1] = {2560};
  Params prm;
  mkmap(enc, &prm.m[M_X], d_in[7], 2, dx, sx, bx, CU_TENSOR_MAP_SWIZZLE_128B);
  mkmap(enc, &prm.m[M_W128], d_in[8], 4, dwa, swa, bwa, CU_TENSOR_MAP_SWIZZLE_128B);
  mkmap(enc, &prm.m[M_W64], d_in[8], 4, dwb, swb, bwb, CU_TENSOR_MAP_SWIZZLE_64B);
  mkmap(enc, &prm.m[M_WR], d_in[8], 3, dw, sw, br, CU_TENSOR_MAP_SWIZZLE_32B);
  mkmap(enc, &prm.m[M_U], d_in[0], 2, dx, sx, bu, CU_TENSOR_MAP_SWIZZLE_NONE);
  mkmap(enc, &prm.m[M_WO], d_in[9], 2, dwo, sx, bwo, CU_TENSOR_MAP_SWIZZLE_128B);
  mkmap(enc, &prm.m[M_O64], d_out, 2, dout, sout, bo64, CU_TENSOR_MAP_SWIZZLE_128B);
  mkmap(enc, &prm.m[M_O16], d_out, 2, dout, sout, bo16, CU_TENSOR_MAP_SWIZZLE_NONE);
  mkmap(enc, &prm.m[M_SA], uy, 2, dsa, ssa, bsa, CU_TENSOR_MAP_SWIZZLE_128B);
  mkmap(enc, &prm.m[M_SB], uy, 2, dsb, ssb, bsb, CU_TENSOR_MAP_SWIZZLE_128B);
  mkmap(enc, &prm.m[M_OUT], d_out, 2, dout, sout, bu, CU_TENSOR_MAP_SWIZZLE_NONE);
  prm.u = (const __nv_bfloat16*)d_in[0]; prm.wo = (const __nv_bfloat16*)d_in[9];
  for (int i = 0; i < 4; i++) prm.par[i] = (const __nv_bfloat16*)d_in[1 + i];
  prm.logdt = (const __nv_bfloat16*)d_in[5]; prm.dskip = (const __nv_bfloat16*)d_in[6];
  cudaFuncSetAttribute(fused_kernel, cudaFuncAttributeMaxDynamicSharedMemorySize, SMEM_BYTES);
  cudaLaunchConfig_t cfg = {};
  cfg.gridDim = dim3(128); cfg.blockDim = dim3(512); cfg.dynamicSmemBytes = SMEM_BYTES; cfg.stream = cudaStreamPerThread;
  cudaLaunchAttribute at[1];
  at[0].id = cudaLaunchAttributeClusterDimension; at[0].val.clusterDim.x = 2; at[0].val.clusterDim.y = 1; at[0].val.clusterDim.z = 1;
  cfg.attrs = at; cfg.numAttrs = 1;
  cudaLaunchKernelEx(&cfg, fused_kernel, prm);
}
```

```cpp
#include <cuda_runtime.h>
#include <cuda_bf16.h>
#include <cuda_fp16.h>
#include <cuda.h>
#include <stdint.h>

#define KST 2
#define EN_ATT 1
#define EN_SSM 1

__device__ __align__(1024) __nv_bfloat16 g_uy[2 * 640 * 2048];
__device__ __align__(128) uint4 g_kvp[8 * 16 * 240];
__device__ __align__(128) uint4 g_o[128 * 1280];
__device__ __align__(128) unsigned g_flag[4 * 128 * 32];
__device__ unsigned g_epoch[128];
#define TS(i) do {} while (0)
#define DUMP(lo, hi) do {} while (0)
#define FIXCNT

constexpr uint32_t SB0 = 1024;
constexpr uint32_t W_SLOT = 15360, OFF_X = 76800;
constexpr uint32_t OFF_WOR = 81920, OFF_KVP = 10240, OFF_KVS = 71680, OFF_PK = 10240, OFF_V = 30720, OFF_EXTRA = 102400, OFF_KVB = OFF_EXTRA;
constexpr uint32_t OFF_UT = 3 * W_SLOT;
constexpr uint32_t OFF_BAR = 125952, OFF_BLK = 128000, BLK = 20480;
constexpr uint32_t B_D = 4096, B_D5 = 3088, B_D7 = 6176, B_D9 = 8224, B_TBL = 14400;
constexpr int T_S = 576, T_F2 = 624, T_F3 = 816;
constexpr uint32_t SMEM_BYTES = OFF_BLK + 5 * BLK;
enum { BR_FULL = 0, BR_WO = 5, BR_PUB = 7, BR_KVP = 8, BR_U = 9, BR_SUM = 10, BR_GEMM = 11, BR_UIN = 12, BR_YIN = 13, BR_EPOCH = 14,
       BR_FREE = 15, BR_RETRY = 17, BR_UOUT = 18, BR_OFULL = 18, BR_KS = 26, BR_EMPTY = 31, BR_OEMPTY = 36, BR_Y = 43, BR_OSTG = 45, BR_KF = 46, BR_CONV = 16,
       BR_COUNT = 48 };
constexpr uint32_t OFF_EPOCH = OFF_BAR + 8 * BR_COUNT;
enum { M_X, M_W128, M_W64, M_WR, M_U, M_WO, M_O64, M_O16, M_SA, M_SB, M_OUT, M_COUNT };

__device__ __forceinline__ long long clk64() { long long t; asm volatile("mov.u64 %0, %%clock64;" : "=l"(t) :: "memory"); return t; }
__device__ __forceinline__ uint32_t smem_u32(const void* p) { return (uint32_t)__cvta_generic_to_shared(p); }
__host__ __device__ constexpr uint64_t mkdesc(uint32_t addr, uint32_t lbo, uint32_t sbo, uint32_t swz) {
  return (uint64_t)((addr & 0x3FFFF) >> 4) | ((uint64_t)(lbo >> 4) << 16) | ((uint64_t)(sbo >> 4) << 32) | ((uint64_t)swz << 62);
}
__device__ __forceinline__ uint64_t desc2(uint32_t lo, uint32_t hi) { uint64_t d; asm("mov.b64 %0, {%1, %2};" : "=l"(d) : "r"(lo), "r"(hi)); return d; }
__device__ __forceinline__ void mbar_init(uint32_t bar, uint32_t cnt) { asm volatile("mbarrier.init.shared::cta.b64 [%0], %1;" :: "r"(bar), "r"(cnt) : "memory"); }
__device__ __forceinline__ void mbar_expect_tx(uint32_t bar, uint32_t bytes) { asm volatile("mbarrier.arrive.expect_tx.shared::cta.b64 _, [%0], %1;" :: "r"(bar), "r"(bytes) : "memory"); }
__device__ __forceinline__ void mbar_arrive(uint32_t bar) { asm volatile("mbarrier.arrive.shared::cta.b64 _, [%0];" :: "r"(bar) : "memory"); }
__device__ __forceinline__ void mbar_wait(uint32_t bar, uint32_t parity) {
  asm volatile("{\n.reg .pred p;\n.reg .u32 c;\nmov.u32 c, 0;\n"
    "WL:\nmbarrier.try_wait.parity.shared::cta.b64 p, [%0], %1;\n@p bra WD;\n"
    "add.u32 c, c, 1;\nsetp.lt.u32 p, c, 200000;\n@p bra WL;\nWD:\n}" :: "r"(bar), "r"(parity) : "memory");
}
__device__ __forceinline__ void poll_all(const unsigned* p, unsigned val) {
  asm volatile("{\n.reg .pred p;\n.reg .u32 c, v;\nmov.u32 c, 0;\n"
    "PL:\nld.relaxed.gpu.global.u32 v, [%0];\nsetp.eq.u32 p, v, %1;\nvote.sync.all.pred p, p, 0xffffffff;\n@p bra PD;\n"
    "add.u32 c, c, 1;\nsetp.lt.u32 p, c, 100000;\n@p bra PL;\nPD:\n}" :: "l"(p), "r"(val) : "memory");
}
__device__ __forceinline__ void poll_all_acq(const unsigned* p, unsigned val) {
  asm volatile("{\n.reg .pred p;\n.reg .u32 c, v;\nmov.u32 c, 0;\n"
    "PL:\nld.acquire.gpu.global.u32 v, [%0];\nsetp.eq.u32 p, v, %1;\nvote.sync.all.pred p, p, 0xffffffff;\n@p bra PD;\n"
    "add.u32 c, c, 1;\nsetp.lt.u32 p, c, 100000;\n@p bra PL;\nPD:\n}" :: "l"(p), "r"(val) : "memory");
}
__device__ __forceinline__ unsigned poll_bit(const unsigned* p, unsigned val, unsigned mask) {
  unsigned bal;
  asm volatile("{\n.reg .pred p;\n.reg .u32 c, v;\nmov.u32 c, 0;\n"
    "PL:\nld.relaxed.gpu.global.u32 v, [%1];\nsetp.eq.u32 p, v, %2;\nvote.sync.ballot.b32 %0, p, 0xffffffff;\n"
    "and.b32 v, %0, %3;\nsetp.ne.u32 p, v, 0;\n@p bra PD;\n"
    "add.u32 c, c, 1;\nsetp.lt.u32 p, c, 100000;\n@p bra PL;\nPD:\n}" : "=&r"(bal) : "l"(p), "r"(val), "r"(mask) : "memory");
  return bal;
}
__device__ __forceinline__ void fix128_w0(uint32_t* v, const void* p, uint32_t tag, uint32_t mask) {
  asm volatile("{\n.reg .pred p;\n.reg .u32 c, x;\n.reg .b128 t;\n.reg .b64 lo, hi;\nmov.u32 c, 0;\n"
    "FL:\nxor.b32 x, %0, %5;\nand.b32 x, x, %6;\nsetp.eq.u32 p, x, 0;\n@p bra FD;\n"
    "ld.relaxed.gpu.global.b128 t, [%4];\nmov.b128 {lo, hi}, t;\nmov.b64 {%0, %1}, lo;\nmov.b64 {%2, %3}, hi;\n"
    "add.u32 c, c, 1;\nsetp.lt.u32 p, c, 100000;\n@p bra FL;\nFD:\n}"
    : "+r"(v[0]), "+r"(v[1]), "+r"(v[2]), "+r"(v[3]) : "l"(p), "r"(tag), "r"(mask) : "memory");
}
__device__ __forceinline__ void fix128_w3(uint32_t* v, const void* p, uint32_t tag, uint32_t mask) {
  asm volatile("{\n.reg .pred p;\n.reg .u32 c, x;\n.reg .b128 t;\n.reg .b64 lo, hi;\nmov.u32 c, 0;\n"
    "FL:\nxor.b32 x, %3, %5;\nand.b32 x, x, %6;\nsetp.eq.u32 p, x, 0;\n@p bra FD;\n"
    "ld.relaxed.gpu.global.b128 t, [%4];\nmov.b128 {lo, hi}, t;\nmov.b64 {%0, %1}, lo;\nmov.b64 {%2, %3}, hi;\n"
    "add.u32 c, c, 1;\nsetp.lt.u32 p, c, 100000;\n@p bra FL;\nFD:\n}"
    : "+r"(v[0]), "+r"(v[1]), "+r"(v[2]), "+r"(v[3]) : "l"(p), "r"(tag), "r"(mask) : "memory");
}
__device__ __forceinline__ void fence_acq() { asm volatile("fence.acq_rel.gpu;" ::: "memory"); }
__device__ __forceinline__ bool elect_one() {
  uint32_t p; asm volatile("{\n.reg .pred P;\nelect.sync _|P, 0xffffffff;\nselp.u32 %0, 1, 0, P;\n}" : "=r"(p)); return p;
}
__device__ __forceinline__ void bar_sync(int id, int n) { asm volatile("bar.sync %0, %1;" :: "r"(id), "r"(n) : "memory"); }
__device__ __forceinline__ void fence_async() { asm volatile("fence.proxy.async.shared::cta;" ::: "memory"); }
__device__ __forceinline__ void fence_async_g() { asm volatile("fence.proxy.async.global;" ::: "memory"); }
__device__ __forceinline__ void tma2d(uint32_t dst, const CUtensorMap* m, uint32_t bar, int c0, int c1) {
  asm volatile("cp.async.bulk.tensor.2d.shared::cluster.global.mbarrier::complete_tx::bytes [%0], [%1, {%3, %4}], [%2];"
    :: "r"(dst), "l"(m), "r"(bar), "r"(c0), "r"(c1) : "memory");
}
__device__ __forceinline__ void tma3d(uint32_t dst, const CUtensorMap* m, uint32_t bar, int c0, int c1, int c2) {
  asm volatile("cp.async.bulk.tensor.3d.shared::cluster.global.mbarrier::complete_tx::bytes [%0], [%1, {%3, %4, %5}], [%2];"
    :: "r"(dst), "l"(m), "r"(bar), "r"(c0), "r"(c1), "r"(c2) : "memory");
}
__device__ __forceinline__ void tma4d(uint32_t dst, const CUtensorMap* m, uint32_t bar, int c0, int c1, int c2, int c3) {
  asm volatile("cp.async.bulk.tensor.4d.shared::cluster.global.mbarrier::complete_tx::bytes [%0], [%1, {%3, %4, %5, %6}], [%2];"
    :: "r"(dst), "l"(m), "r"(bar), "r"(c0), "r"(c1), "r"(c2), "r"(c3) : "memory");
}
__device__ __forceinline__ void tma2d_st(const CUtensorMap* m, uint32_t src, int c0, int c1) {
  asm volatile("cp.async.bulk.tensor.2d.global.shared::cta.bulk_group [%0, {%2, %3}], [%1];"
    :: "l"(m), "r"(src), "r"(c0), "r"(c1) : "memory");
}
__device__ __forceinline__ void bulk_ld(uint32_t dst, const void* src, uint32_t bytes, uint32_t bar) {
  asm volatile("cp.async.bulk.shared::cluster.global.mbarrier::complete_tx::bytes [%0], [%1], %2, [%3];"
    :: "r"(dst), "l"(src), "r"(bytes), "r"(bar) : "memory");
}
__device__ __forceinline__ void bulk_st(void* dst, uint32_t src, uint32_t bytes) {
  asm volatile("cp.async.bulk.global.shared::cta.bulk_group [%0], [%1], %2;" :: "l"(dst), "r"(src), "r"(bytes) : "memory");
}
__device__ __forceinline__ void bulk_commit() { asm volatile("cp.async.bulk.commit_group;" ::: "memory"); }
__device__ __forceinline__ void bulk_wait0() { asm volatile("cp.async.bulk.wait_group 0;" ::: "memory"); }
__device__ __forceinline__ void bulk_wait0_read() { asm volatile("cp.async.bulk.wait_group.read 0;" ::: "memory"); }
__device__ __forceinline__ unsigned ld_rlx(const unsigned* p) { unsigned v; asm volatile("ld.relaxed.gpu.global.u32 %0, [%1];" : "=r"(v) : "l"(p) : "memory"); return v; }
__device__ __forceinline__ unsigned ld_acq(const unsigned* p) { unsigned v; asm volatile("ld.acquire.gpu.global.u32 %0, [%1];" : "=r"(v) : "l"(p) : "memory"); return v; }
__device__ __forceinline__ void st_rlx(unsigned* p, unsigned v) { asm volatile("st.relaxed.gpu.global.u32 [%0], %1;" :: "l"(p), "r"(v) : "memory"); }
__device__ __forceinline__ void st_rel(unsigned* p, unsigned v) { asm volatile("st.release.gpu.global.u32 [%0], %1;" :: "l"(p), "r"(v) : "memory"); }
__device__ __forceinline__ void ld128_rlx(uint32_t* v, const void* p) {
  asm volatile("{\n.reg .b128 t;\n.reg .b64 lo, hi;\nld.relaxed.gpu.global.b128 t, [%4];\nmov.b128 {lo, hi}, t;\n"
    "mov.b64 {%0, %1}, lo;\nmov.b64 {%2, %3}, hi;\n}" : "=r"(v[0]), "=r"(v[1]), "=r"(v[2]), "=r"(v[3]) : "l"(p) : "memory");
}
__device__ __forceinline__ void st128_rlx(void* p, const uint32_t* v) {
  asm volatile("{\n.reg .b128 t;\n.reg .b64 lo, hi;\nmov.b64 lo, {%1, %2};\nmov.b64 hi, {%3, %4};\nmov.b128 t, {lo, hi};\n"
    "st.relaxed.gpu.global.b128 [%0], t;\n}" :: "l"(p), "r"(v[0]), "r"(v[1]), "r"(v[2]), "r"(v[3]) : "memory");
}
__device__ __forceinline__ uint32_t lds32(uint32_t a) { uint32_t v; asm volatile("ld.shared.u32 %0, [%1];" : "=r"(v) : "r"(a) : "memory"); return v; }
__device__ __forceinline__ uint32_t lds32v(uint32_t a) { uint32_t v; asm volatile("ld.volatile.shared.u32 %0, [%1];" : "=r"(v) : "r"(a) : "memory"); return v; }
__device__ __forceinline__ uint32_t cpa(uint32_t a, uint32_t one) { uint32_t v; asm volatile("mul.lo.u32 %0, %1, %2;" : "=r"(v) : "r"(a), "r"(one)); return v; }
__device__ __forceinline__ uint32_t cpb(uint32_t a, uint32_t zero) { uint32_t v; asm volatile("or.b32 %0, %1, %2;" : "=r"(v) : "r"(a), "r"(zero)); return v; }
__device__ __forceinline__ uint32_t lds16(uint32_t a) { uint16_t v; asm volatile("ld.shared.u16 %0, [%1];" : "=h"(v) : "r"(a) : "memory"); return v; }
__device__ __forceinline__ float ldsf(uint32_t a) { float v; asm volatile("ld.shared.f32 %0, [%1];" : "=f"(v) : "r"(a) : "memory"); return v; }
__device__ __forceinline__ void lds128(uint32_t* v, uint32_t a) { asm volatile("ld.shared.v4.u32 {%0,%1,%2,%3}, [%4];" : "=r"(v[0]), "=r"(v[1]), "=r"(v[2]), "=r"(v[3]) : "r"(a) : "memory"); }
__device__ __forceinline__ void sts32(uint32_t a, uint32_t v) { asm volatile("st.shared.u32 [%0], %1;" :: "r"(a), "r"(v) : "memory"); }
__device__ __forceinline__ void sts16(uint32_t a, uint32_t v) { asm volatile("st.shared.u16 [%0], %1;" :: "r"(a), "h"((uint16_t)v) : "memory"); }
__device__ __forceinline__ void sts64f(uint32_t a, float x, float y) { asm volatile("st.shared.v2.f32 [%0], {%1,%2};" :: "r"(a), "f"(x), "f"(y) : "memory"); }
__device__ __forceinline__ void sts128(uint32_t a, uint32_t x, uint32_t y, uint32_t z, uint32_t w) { asm volatile("st.shared.v4.u32 [%0], {%1,%2,%3,%4};" :: "r"(a), "r"(x), "r"(y), "r"(z), "r"(w) : "memory"); }
__device__ __forceinline__ void stsm4(uint32_t a, uint32_t r0, uint32_t r1, uint32_t r2, uint32_t r3) {
  asm volatile("stmatrix.sync.aligned.m8n8.x4.shared.b16 [%0], {%1,%2,%3,%4};" :: "r"(a), "r"(r0), "r"(r1), "r"(r2), "r"(r3) : "memory");
}
__device__ __forceinline__ void stsm4t(uint32_t a, uint32_t r0, uint32_t r1, uint32_t r2, uint32_t r3) {
  asm volatile("stmatrix.sync.aligned.m8n8.x4.trans.shared.b16 [%0], {%1,%2,%3,%4};" :: "r"(a), "r"(r0), "r"(r1), "r"(r2), "r"(r3) : "memory");
}
__device__ __forceinline__ void ldsm4t(uint32_t* r, uint32_t a) {
  asm volatile("ldmatrix.sync.aligned.m8n8.x4.trans.shared.b16 {%0,%1,%2,%3}, [%4];" : "=r"(r[0]), "=r"(r[1]), "=r"(r[2]), "=r"(r[3]) : "r"(a) : "memory");
}
__device__ __forceinline__ void ldsm4(uint32_t* r, uint32_t a) {
  asm volatile("ldmatrix.sync.aligned.m8n8.x4.shared.b16 {%0,%1,%2,%3}, [%4];" : "=r"(r[0]), "=r"(r[1]), "=r"(r[2]), "=r"(r[3]) : "r"(a) : "memory");
}
__device__ __forceinline__ void mma16816(float* d, const uint32_t* a, const uint32_t* b) {
  asm volatile("mma.sync.aligned.m16n8k16.row.col.f32.bf16.bf16.f32 {%0,%1,%2,%3}, {%4,%5,%6,%7}, {%8,%9}, {%0,%1,%2,%3};"
    : "+f"(d[0]), "+f"(d[1]), "+f"(d[2]), "+f"(d[3]) : "r"(a[0]), "r"(a[1]), "r"(a[2]), "r"(a[3]), "r"(b[0]), "r"(b[1]));
}
__device__ __forceinline__ uint32_t pack2(float lo, float hi) { uint32_t r; asm("cvt.rn.bf16x2.f32 %0, %1, %2;" : "=r"(r) : "f"(hi), "f"(lo)); return r; }
__device__ __forceinline__ uint32_t packh(float lo, float hi) { uint32_t r; asm("cvt.rn.f16x2.f32 %0, %1, %2;" : "=r"(r) : "f"(hi), "f"(lo)); return r; }
__device__ __forceinline__ uint32_t hcmul(uint32_t x, uint32_t zp, uint32_t zq) {
  const __half2 xx = *reinterpret_cast<__half2*>(&x);
  const __half2 r = __hfma2(__high2half2(xx), *reinterpret_cast<__half2*>(&zq), __hmul2(__low2half2(xx), *reinterpret_cast<__half2*>(&zp)));
  return *reinterpret_cast<const uint32_t*>(&r);
}
__device__ __forceinline__ void hcm2(uint32_t xr, uint32_t xi, uint32_t z, uint32_t& pr, uint32_t& pi) {
  const __half2 a = *reinterpret_cast<__half2*>(&xr), b = *reinterpret_cast<__half2*>(&xi), zz = *reinterpret_cast<__half2*>(&z);
  const __half2 re = __hfma2(__hneg2(b), __high2half2(zz), __hmul2(a, __low2half2(zz)));
  const __half2 im = __hfma2(a, __high2half2(zz), __hmul2(b, __low2half2(zz)));
  pr = *reinterpret_cast<const uint32_t*>(&re); pi = *reinterpret_cast<const uint32_t*>(&im);
}
__device__ __forceinline__ void sts64(uint32_t a, uint32_t x, uint32_t y) { asm volatile("st.shared.v2.u32 [%0], {%1,%2};" :: "r"(a), "r"(x), "r"(y) : "memory"); }
__device__ __forceinline__ void lds64(uint32_t* v, uint32_t a) { asm volatile("ld.shared.v2.u32 {%0,%1}, [%2];" : "=r"(v[0]), "=r"(v[1]) : "r"(a) : "memory"); }
__device__ __forceinline__ float bf_lo(uint32_t v) { return __uint_as_float(v << 16); }
__device__ __forceinline__ float bf_hi(uint32_t v) { return __uint_as_float(v & 0xffff0000u); }
__device__ __forceinline__ float bf_round(float x) { return bf_lo(pack2(x, 0.f)); }
__device__ __forceinline__ float ex2(float x) { float r; asm("ex2.approx.ftz.f32 %0, %1;" : "=f"(r) : "f"(x)); return r; }
__device__ __forceinline__ float phi(float t, float l2e = 1.44269504089f) {
  float e = ex2(t * l2e) + 1e-6f;
  asm("{\n.reg .pred p;\nsetp.gt.f32 p, %1, 0f00000000;\n@p add.f32 %0, %1, 0f3F800008;\n}" : "+f"(e) : "f"(t));
  return e;
}
__device__ __forceinline__ void wg_fence() { asm volatile("wgmma.fence.sync.aligned;" ::: "memory"); }
__device__ __forceinline__ void wg_commit() { asm volatile("wgmma.commit_group.sync.aligned;" ::: "memory"); }
template <int N> __device__ __forceinline__ void wg_wait() { asm volatile("wgmma.wait_group.sync.aligned %0;" :: "n"(N) : "memory"); }
template <int N> __device__ __forceinline__ void pin(float* a) {
  #pragma unroll
  for (int i = 0; i < N; i++) asm volatile("" : "+f"(a[i]) :: "memory");
}
__device__ __forceinline__ int rtid() { int t; asm volatile("mov.u32 %0, %%tid.x;" : "=r"(t)); return t; }
__device__ __forceinline__ int opaque(int v) { asm volatile("" : "+r"(v)); return v; }
template <int N> __device__ __forceinline__ void zero(float* a) {
  #pragma unroll
  for (int i = 0; i < N; i++) asm volatile("mov.b32 %0, 0;" : "=f"(a[i]));
}
template <int N> __device__ __forceinline__ void pinu(uint32_t* a) {
  #pragma unroll
  for (int i = 0; i < N; i++) asm volatile("" : "+r"(a[i]) :: "memory");
}
__device__ __forceinline__ void cexp_t(float lg2mag, float turns, float& re, float& im) {
  float m = ex2(lg2mag);
  float fr = (turns - __fadd_rn(__fadd_rn(turns, 12582912.f), -12582912.f)) * 6.283185307f;
  re = m * __cosf(fr); im = m * __sinf(fr);
}
__device__ __forceinline__ void cmul(float ar, float ai, float br, float bi, float& cr, float& ci) {
  cr = fmaf(ar, br, -ai * bi); ci = fmaf(ar, bi, ai * br);
}

__device__ __forceinline__ void wg_ss192_tb(float* d, uint64_t da, uint64_t db, int scale_d) {
  asm volatile("{\n.reg .pred p;\nsetp.ne.b32 p, %98, 0;\n"
    "wgmma.mma_async.sync.aligned.m64n192k16.f32.bf16.bf16 "
    "{%0, %1, %2, %3, %4, %5, %6, %7, %8, %9, %10, %11, %12, %13, %14, %15, %16, %17, %18, %19, %20, %21, %22, %23, %24, %25, %26, %27, %28, %29, %30, %31, %32, %33, %34, %35, %36, %37, %38, %39, %40, %41, %42, %43, %44, %45, %46, %47, %48, %49, %50, %51, %52, %53, %54, %55, %56, %57, %58, %59, %60, %61, %62, %63, %64, %65, %66, %67, %68, %69, %70, %71, %72, %73, %74, %75, %76, %77, %78, %79, %80, %81, %82, %83, %84, %85, %86, %87, %88, %89, %90, %91, %92, %93, %94, %95}, %96, %97, p, 1, 1, 0, 1;\n}\n"
    : "+f"(d[0]), "+f"(d[1]), "+f"(d[2]), "+f"(d[3]), "+f"(d[4]), "+f"(d[5]), "+f"(d[6]), "+f"(d[7]), "+f"(d[8]), "+f"(d[9]), "+f"(d[10]), "+f"(d[11]), "+f"(d[12]), "+f"(d[13]), "+f"(d[14]), "+f"(d[15]), "+f"(d[16]), "+f"(d[17]), "+f"(d[18]), "+f"(d[19]), "+f"(d[20]), "+f"(d[21]), "+f"(d[22]), "+f"(d[23]), "+f"(d[24]), "+f"(d[25]), "+f"(d[26]), "+f"(d[27]), "+f"(d[28]), "+f"(d[29]), "+f"(d[30]), "+f"(d[31]), "+f"(d[32]), "+f"(d[33]), "+f"(d[34]), "+f"(d[35]), "+f"(d[36]), "+f"(d[37]), "+f"(d[38]), "+f"(d[39]), "+f"(d[40]), "+f"(d[41]), "+f"(d[42]), "+f"(d[43]), "+f"(d[44]), "+f"(d[45]), "+f"(d[46]), "+f"(d[47]), "+f"(d[48]), "+f"(d[49]), "+f"(d[50]), "+f"(d[51]), "+f"(d[52]), "+f"(d[53]), "+f"(d[54]), "+f"(d[55]), "+f"(d[56]), "+f"(d[57]), "+f"(d[58]), "+f"(d[59]), "+f"(d[60]), "+f"(d[61]), "+f"(d[62]), "+f"(d[63]), "+f"(d[64]), "+f"(d[65]), "+f"(d[66]), "+f"(d[67]), "+f"(d[68]), "+f"(d[69]), "+f"(d[70]), "+f"(d[71]), "+f"(d[72]), "+f"(d[73]), "+f"(d[74]), "+f"(d[75]), "+f"(d[76]), "+f"(d[77]), "+f"(d[78]), "+f"(d[79]), "+f"(d[80]), "+f"(d[81]), "+f"(d[82]), "+f"(d[83]), "+f"(d[84]), "+f"(d[85]), "+f"(d[86]), "+f"(d[87]), "+f"(d[88]), "+f"(d[89]), "+f"(d[90]), "+f"(d[91]), "+f"(d[92]), "+f"(d[93]), "+f"(d[94]), "+f"(d[95])
    : "l"(da), "l"(db), "r"(scale_d));
}
__device__ __forceinline__ void wg_ss48_tb(float* d, uint64_t da, uint64_t db, int scale_d) {
  asm volatile("{\n.reg .pred p;\nsetp.ne.b32 p, %26, 0;\n"
    "wgmma.mma_async.sync.aligned.m64n48k16.f32.bf16.bf16 "
    "{%0, %1, %2, %3, %4, %5, %6, %7, %8, %9, %10, %11, %12, %13, %14, %15, %16, %17, %18, %19, %20, %21, %22, %23}, %24, %25, p, 1, 1, 0, 1;\n}\n"
    : "+f"(d[0]), "+f"(d[1]), "+f"(d[2]), "+f"(d[3]), "+f"(d[4]), "+f"(d[5]), "+f"(d[6]), "+f"(d[7]), "+f"(d[8]), "+f"(d[9]), "+f"(d[10]), "+f"(d[11]), "+f"(d[12]), "+f"(d[13]), "+f"(d[14]), "+f"(d[15]), "+f"(d[16]), "+f"(d[17]), "+f"(d[18]), "+f"(d[19]), "+f"(d[20]), "+f"(d[21]), "+f"(d[22]), "+f"(d[23])
    : "l"(da), "l"(db), "r"(scale_d));
}
__device__ __forceinline__ void wg_ss48_tt(float* d, uint64_t da, uint64_t db, int scale_d) {
  asm volatile("{\n.reg .pred p;\nsetp.ne.b32 p, %26, 0;\n"
    "wgmma.mma_async.sync.aligned.m64n48k16.f32.bf16.bf16 "
    "{%0, %1, %2, %3, %4, %5, %6, %7, %8, %9, %10, %11, %12, %13, %14, %15, %16, %17, %18, %19, %20, %21, %22, %23}, %24, %25, p, 1, 1, 1, 1;\n}\n"
    : "+f"(d[0]), "+f"(d[1]), "+f"(d[2]), "+f"(d[3]), "+f"(d[4]), "+f"(d[5]), "+f"(d[6]), "+f"(d[7]), "+f"(d[8]), "+f"(d[9]), "+f"(d[10]), "+f"(d[11]), "+f"(d[12]), "+f"(d[13]), "+f"(d[14]), "+f"(d[15]), "+f"(d[16]), "+f"(d[17]), "+f"(d[18]), "+f"(d[19]), "+f"(d[20]), "+f"(d[21]), "+f"(d[22]), "+f"(d[23])
    : "l"(da), "l"(db), "r"(scale_d));
}
__device__ __forceinline__ void wg_rs88_tb(float* d, const uint32_t* a, uint64_t db, int scale_d) {
  asm volatile("{\n.reg .pred p;\nsetp.ne.b32 p, %49, 0;\n"
    "wgmma.mma_async.sync.aligned.m64n88k16.f32.bf16.bf16 "
    "{%0, %1, %2, %3, %4, %5, %6, %7, %8, %9, %10, %11, %12, %13, %14, %15, %16, %17, %18, %19, %20, %21, %22, %23, %24, %25, %26, %27, %28, %29, %30, %31, %32, %33, %34, %35, %36, %37, %38, %39, %40, %41, %42, %43}, {%44, %45, %46, %47}, %48, p, 1, 1, 1;\n}\n"
    : "+f"(d[0]), "+f"(d[1]), "+f"(d[2]), "+f"(d[3]), "+f"(d[4]), "+f"(d[5]), "+f"(d[6]), "+f"(d[7]), "+f"(d[8]), "+f"(d[9]), "+f"(d[10]), "+f"(d[11]), "+f"(d[12]), "+f"(d[13]), "+f"(d[14]), "+f"(d[15]), "+f"(d[16]), "+f"(d[17]), "+f"(d[18]), "+f"(d[19]), "+f"(d[20]), "+f"(d[21]), "+f"(d[22]), "+f"(d[23]), "+f"(d[24]), "+f"(d[25]), "+f"(d[26]), "+f"(d[27]), "+f"(d[28]), "+f"(d[29]), "+f"(d[30]), "+f"(d[31]), "+f"(d[32]), "+f"(d[33]), "+f"(d[34]), "+f"(d[35]), "+f"(d[36]), "+f"(d[37]), "+f"(d[38]), "+f"(d[39]), "+f"(d[40]), "+f"(d[41]), "+f"(d[42]), "+f"(d[43])
    : "r"(a[0]), "r"(a[1]), "r"(a[2]), "r"(a[3]), "l"(db), "r"(scale_d));
}
__device__ __forceinline__ void wg_ss80_tb(float* d, uint64_t da, uint64_t db, int scale_d) {
  asm volatile("{\n.reg .pred p;\nsetp.ne.b32 p, %42, 0;\n"
    "wgmma.mma_async.sync.aligned.m64n80k16.f32.bf16.bf16 "
    "{%0, %1, %2, %3, %4, %5, %6, %7, %8, %9, %10, %11, %12, %13, %14, %15, %16, %17, %18, %19, %20, %21, %22, %23, %24, %25, %26, %27, %28, %29, %30, %31, %32, %33, %34, %35, %36, %37, %38, %39}, %40, %41, p, 1, 1, 0, 1;\n}\n"
    : "+f"(d[0]), "+f"(d[1]), "+f"(d[2]), "+f"(d[3]), "+f"(d[4]), "+f"(d[5]), "+f"(d[6]), "+f"(d[7]), "+f"(d[8]), "+f"(d[9]), "+f"(d[10]), "+f"(d[11]), "+f"(d[12]), "+f"(d[13]), "+f"(d[14]), "+f"(d[15]), "+f"(d[16]), "+f"(d[17]), "+f"(d[18]), "+f"(d[19]), "+f"(d[20]), "+f"(d[21]), "+f"(d[22]), "+f"(d[23]), "+f"(d[24]), "+f"(d[25]), "+f"(d[26]), "+f"(d[27]), "+f"(d[28]), "+f"(d[29]), "+f"(d[30]), "+f"(d[31]), "+f"(d[32]), "+f"(d[33]), "+f"(d[34]), "+f"(d[35]), "+f"(d[36]), "+f"(d[37]), "+f"(d[38]), "+f"(d[39])
    : "l"(da), "l"(db), "r"(scale_d));
}
__device__ __forceinline__ void wg_ss48_tt_h(float* d, uint64_t da, uint64_t db, int scale_d) {
  asm volatile("{\n.reg .pred p;\nsetp.ne.b32 p, %26, 0;\n"
    "wgmma.mma_async.sync.aligned.m64n48k16.f32.f16.f16 "
    "{%0, %1, %2, %3, %4, %5, %6, %7, %8, %9, %10, %11, %12, %13, %14, %15, %16, %17, %18, %19, %20, %21, %22, %23}, %24, %25, p, 1, 1, 1, 1;\n}\n"
    : "+f"(d[0]), "+f"(d[1]), "+f"(d[2]), "+f"(d[3]), "+f"(d[4]), "+f"(d[5]), "+f"(d[6]), "+f"(d[7]), "+f"(d[8]), "+f"(d[9]), "+f"(d[10]), "+f"(d[11]), "+f"(d[12]), "+f"(d[13]), "+f"(d[14]), "+f"(d[15]), "+f"(d[16]), "+f"(d[17]), "+f"(d[18]), "+f"(d[19]), "+f"(d[20]), "+f"(d[21]), "+f"(d[22]), "+f"(d[23])
    : "l"(da), "l"(db), "r"(scale_d));
}

struct Params {
  const __nv_bfloat16 *par[4], *logdt, *dskip, *u, *wo;
  CUtensorMap m[M_COUNT];
};

#define CHUNK(i) ((i) == 0 ? c : ((i) == 7 ? (c ^ 1) : (((c & 6) + 1 + (i)) & 7)))
#define FLAG(kind, rr, cc) (&g_flag[((kind) * 128 + (rr) * 8 + (cc)) * 32])
#define SLOT(i) ((i) == 0 || (i) == 5 ? OFF_EXTRA : OFF_BLK - 256 + ((i) > 5 ? (i) - 6 : (i) - 1) * BLK)
__device__ __forceinline__ void load_quad(uint32_t* A, uint32_t addr) {
  A[0] = lds32v(addr); A[1] = lds32v(addr + 32); A[2] = lds32v(addr - 32); A[3] = lds32v(addr);
}

__global__ void __launch_bounds__(512, 1) fused_kernel(const __grid_constant__ Params prm) {
  extern __shared__ unsigned char smem_raw[];
  const uint32_t sb = __shfl_sync(0xffffffff, smem_u32(smem_raw), 0);
  const int tid = threadIdx.x, lane = tid & 31;
  const int warp = __shfl_sync(0xffffffff, tid >> 5, 0), wg = warp >> 2, w4 = warp & 3;
  const int cta = blockIdx.x, r = cta >> 3, c = cta & 7;
  if ((sb & 0xffffffu) != SB0) return;
#define BAR(i) (sb + OFF_BAR + 8 * (i))
  const bool sw64 = ((c + 1) & 2) != 0;

  if (wg == 3) {
    if (warp == 13 && elect_one()) {
      #pragma unroll
      for (int i = M_W128; i <= M_U; i++) asm volatile("prefetch.tensormap [%0];" :: "l"(&prm.m[i]) : "memory");
    }
    asm volatile("setmaxnreg.dec.sync.aligned.u32 56;");
    const int tid = rtid(), lane = tid & 31;
    if (warp == 12) {
      if (elect_one()) {
        #pragma unroll
        for (int i = 0; i < 5; i++) mbar_init(BAR(BR_FULL + i), 1);
        asm volatile("fence.mbarrier_init.release.cluster;" ::: "memory");
      }
      {
        const CUtensorMap* mwp = &prm.m[sw64 ? M_W64 : M_W128];
        const int mcol = (c * 80 + (c & 1) * 16) >> (sw64 ? 5 : 6), rcol = c * 80 + ((c & 1) ? 0 : 64);
        uint32_t s = 0, ph = 1, xs = 0;
        #pragma unroll 1
        for (int kb = 0; kb < 20; kb++) {
          if (kb == 1) asm volatile("bar.arrive 0, 512;" ::: "memory");
          if (kb == 3) { bar_sync(6, 128); if (EN_SSM) mbar_wait(BAR(BR_UOUT), 0); }
          if (EN_SSM && kb == 4) mbar_wait(BAR(BR_KS + 3), 0);
          if (kb >= 5) mbar_wait(BAR(BR_EMPTY) + 8 * s, ph);
          if (EN_ATT && elect_one()) {
            const uint32_t st = sb + s * W_SLOT, fb = BAR(BR_FULL) + 8 * s;
            mbar_expect_tx(fb, (kb & 1) ? W_SLOT : W_SLOT + 16384);
            if (!(kb & 1)) tma2d(sb + OFF_X + xs, &prm.m[M_X], fb, kb * 32, r * 128);
            tma4d(st, mwp, fb, 0, kb * 32, mcol, 0);
            tma3d(st + 12288, &prm.m[M_WR], fb, rcol, kb * 32, 0);
          }
          if (kb < 4 && lane == 0) TS(24 + kb);
          if (kb == 14 && elect_one()) asm volatile("cp.async.bulk.prefetch.L2.global [%0], 6400;" :: "l"(prm.wo + cta * 3200) : "memory");
          if (!EN_ATT && kb == 3) break;
          if (++s == 5) { s = 0; ph ^= 1; }
          if (kb & 1) { xs += 16384; if (xs == 49152) xs = 0; }
        }
      }
      if (EN_ATT) {
      mbar_wait(BAR(BR_EPOCH), 0);
      const unsigned epoch = lds32(sb + OFF_EPOCH);
      const unsigned* fo = FLAG(3, r, lane & 7);
      unsigned seen = __ballot_sync(0xffffffff, ld_rlx(lane < 16 ? fo : FLAG(0, lane & 15, c)) == epoch) & 0xffu;
      mbar_wait(BAR(BR_GEMM), 0);
      if (elect_one()) {
        mbar_expect_tx(BAR(BR_WO), 10240);
        tma2d(sb, &prm.m[M_WO], BAR(BR_WO), c * 64, c * 80);
        mbar_expect_tx(BAR(BR_KVP), 61440);
        mbar_expect_tx(BAR(BR_WO + 1), 7 * 10240);
      }
      {
        uint32_t ds = sb + OFF_WOR + (lane >> 3) * 128 + (((lane & 7) ^ (lane >> 3)) << 4);
        #pragma unroll 1
        for (int h = 0; h < 2; h++) {
          const int i = (lane & 6) + h;
          const char* gs = reinterpret_cast<const char*>(prm.wo) + (size_t)((lane >> 3) + CHUNK(i) * 80) * 1280 + 1024 + c * 32 + (lane & 1) * 16;
          #pragma unroll 2
          for (int q = 0; q < 20; q++) {
            asm volatile("cp.async.cg.shared.global [%0], [%1], 16;" :: "r"(ds), "l"(gs) : "memory");
            ds = (ds + 512) ^ 64; gs += 5120;
          }
        }
      }
      mbar_wait(BAR(BR_PUB), 0);
      poll_all(FLAG(0, lane & 15, c), epoch);
      if (elect_one()) { TS(23); bulk_ld(sb + OFF_KVP, &g_kvp[c * 16 * 240], 61440, BAR(BR_KVP)); }
      asm volatile("cp.async.wait_all;" ::: "memory");
      fence_async();
      mbar_arrive(BAR(BR_WO));
      mbar_wait(BAR(BR_SUM), 0);
      if (elect_one()) {
        #pragma unroll 1
        for (int i = 1; i < 8; i++) tma2d(sb + i * 10240, &prm.m[M_WO], BAR(BR_WO + 1), c * 64, CHUNK(i) * 80);
      }
      mbar_wait(BAR(BR_OSTG), 0);
      if (elect_one()) {
        bulk_st(&g_o[cta * 1280], sb + OFF_EXTRA, 20480);
        bulk_commit();
        bulk_wait0();
        st_rlx(FLAG(3, r, c), epoch);
        TS(20);
      }
      __syncwarp();
      #pragma unroll 1
      for (int i = 1; i < 8; i++) {
        const int src = CHUNK(i);
        if (!((seen >> src) & 1)) seen = poll_bit(fo, epoch, 1u << src);
        if (i >= 5) mbar_wait(BAR(BR_OEMPTY - 5) + 8 * i, 0);
        if (EN_SSM && i == 1) mbar_wait(BAR(BR_FREE), 0);
        if (elect_one()) {
          mbar_expect_tx(BAR(BR_OFULL) + 8 * i, 20480);
          bulk_ld(sb + SLOT(i), &g_o[(r * 8 + src) * 1280], 20480, BAR(BR_OFULL) + 8 * i);
          if (i == 1) TS(21);
          if (i == 7) TS(22);
        }
        __syncwarp();
      }
      if (lane == 0) { DUMP(20, 30); }
      }
    } else {
      const int hw = warp - 13, ht = tid - 416;
      if (hw == 2 && elect_one()) {
        #pragma unroll
        for (int i = 5; i < BR_COUNT; i++) mbar_init(BAR(i), i == BR_WO ? 33 : i < BR_EMPTY ? 1 : i < BR_OEMPTY ? 2 : i < BR_Y ? 8 : i < BR_OSTG ? 128 : 256);
        asm volatile("fence.mbarrier_init.release.cluster;" ::: "memory");
        if (EN_SSM) { mbar_expect_tx(BAR(BR_UIN), 20480); tma2d(sb + OFF_UT, &prm.m[M_U], BAR(BR_UIN), c * 80, r * 128); }
      }
      __syncwarp();
      asm volatile("bar.arrive 0, 512;" ::: "memory");
      const unsigned epoch = hw == 0 ? ld_rlx(&g_epoch[cta]) + 1 : 0;
      bar_sync(6, 128);
      if (hw == 1 && elect_one()) {
        #pragma unroll
        for (int i = M_WO; i < M_COUNT; i++) asm volatile("prefetch.tensormap [%0];" :: "l"(&prm.m[i]) : "memory");
      }
      if (ht == 0) {
        st_rlx(&g_epoch[cta], epoch);
        sts32(sb + OFF_EPOCH, epoch);
        mbar_arrive(BAR(BR_EPOCH));
      }
      if (EN_SSM) {
      const int mi = lane >> 3, rw = lane & 7, ch0 = c * 80 + r * 5;
      mbar_wait(BAR(BR_UIN), 0);
      if (ht == 0) TS(36);
      #pragma unroll 1
      for (int h = 0; h < 2; h++) {
        const uint32_t sa = sb + OFF_UT + h * 10240 + (8 * mi + rw) * 160 + hw * 16, da = sb + OFF_UT + h * 10240 + (hw * 8 + rw) * 128 + ((mi ^ rw) << 4);
        uint32_t v[8][4];
        #pragma unroll
        for (int q = 0; q < 8; q++) if (q < 6 || hw == 0) ldsm4t(v[q], sa + (q & 1) * 5120 + (q >> 1) * 48);
        bar_sync(5, 96);
        #pragma unroll
        for (int q = 0; q < 8; q++) if (q < 6 || hw == 0) stsm4((da ^ ((q & 1) * 64)) + (q >> 1) * 3072, v[q][0], v[q][1], v[q][2], v[q][3]);
      }
      fence_async();
      bar_sync(5, 96);
      if (hw == 0) {
        if (elect_one()) {
          tma2d_st(&prm.m[M_SA], sb + OFF_UT, r * 128, c * 80);
          tma2d_st(&prm.m[M_SA], sb + OFF_UT + 10240, r * 128 + 64, c * 80);
          bulk_commit(); bulk_wait0_read();
          mbar_arrive(BAR(BR_UOUT));
          TS(37);
          bulk_wait0();
          st_rel(FLAG(1, r, c), epoch);
          TS(30);
        }
        __syncwarp();
        poll_all_acq(FLAG(1, lane & 15, c), epoch);
        mbar_wait(BAR(BR_KS + 4), 0);
        if (elect_one()) {
          fence_async_g();
          mbar_expect_tx(BAR(BR_U), 20480);
          #pragma unroll 1
          for (int q = 0; q < 5; q++) tma2d(sb + OFF_BLK + q * BLK, &prm.m[M_SB], BAR(BR_U), 0, (ch0 + q) * 32);
          TS(31);
        }
        __syncwarp();
      }
      if (hw == 0) {
        #pragma unroll 1
        for (int p = 0; p < 2; p++) {
          mbar_wait(BAR(BR_Y) + 8 * p, 0);
          if (elect_one()) {
            #pragma unroll 1
            for (int k = 4 * p; k < 4 + p; k++) tma2d_st(&prm.m[M_SB], sb + OFF_BLK + k * BLK, 0, (640 + ch0 + k) * 32);
            bulk_commit(); bulk_wait0_read();
            if (p == 0) mbar_arrive(BAR(BR_FREE));
          }
          __syncwarp();
        }
        if (elect_one()) {
          mbar_expect_tx(BAR(BR_YIN), 20480);
          bulk_wait0();
          st_rel(FLAG(2, r, c), epoch);
          TS(33);
        }
        __syncwarp();
        poll_all_acq(FLAG(2, lane & 15, c), epoch);
        if (elect_one()) {
          fence_async_g();
          tma2d(sb + OFF_BLK + 4 * BLK, &prm.m[M_SA], BAR(BR_YIN), r * 128, 640 + c * 80);
          tma2d(sb + OFF_BLK + 4 * BLK + 10240, &prm.m[M_SA], BAR(BR_YIN), r * 128 + 64, 640 + c * 80);
          TS(34);
        }
      }
      {
        uint32_t sa = sb + OFF_BLK + 4 * BLK + (hw * 8 + rw) * 128 + ((mi ^ rw) << 4);
        uint32_t da = sb + SLOT(3) + (8 * mi + rw) * 160 + hw * 16;
        if (EN_ATT) mbar_wait(BAR(BR_OEMPTY + 3), 0);
        mbar_wait(BAR(BR_YIN), 0);
        #pragma unroll 1
        for (int i = hw; i < 10; i += 3) {
          uint32_t v[4][4];
          #pragma unroll
          for (int q = 0; q < 4; q++) ldsm4t(v[q], (sa ^ ((q & 1) * 64)) + (q >> 1) * 10240);
          #pragma unroll
          for (int q = 0; q < 4; q++) stsm4(da + q * 5120, v[q][0], v[q][1], v[q][2], v[q][3]);
          sa += 3072; da += 48;
        }
      }
      fence_async();
      bar_sync(5, 96);
      if (hw == 0 && elect_one()) {
        tma2d_st(&prm.m[M_OUT], sb + SLOT(3), c * 80, r * 128);
        bulk_commit(); bulk_wait0_read();
        TS(35); DUMP(30, 40); DUMP(0, 1);
      }
      }
    }
  } else {
    const int g = lane >> 2, tq = lane & 3, t7 = tid & 127;
    uint32_t pr[2][2], pd;
    {
      const int ch = c * 80 + r * 5 + wg;
      uint32_t raw[2][4];
      #pragma unroll
      for (int e = 0; e < 4; e++) {
        const __nv_bfloat16* pp = prm.par[e] + ch * 128 + t7;
        asm volatile("ld.global.nc.u16 %0, [%1];" : "=r"(raw[0][e]) : "l"(pp));
        asm volatile("ld.global.nc.u16 %0, [%1];" : "=r"(raw[1][e]) : "l"(pp + (wg < 2 ? 384 : 0)));
      }
      asm volatile("ld.global.nc.u16 %0, [%1];" : "=r"(pd) : "l"(((lane & 2) ? prm.dskip : prm.logdt) + ch + ((lane & 1) && wg < 2 ? 3 : 0)));
      asm volatile("setmaxnreg.inc.sync.aligned.u32 152;");
      if (EN_SSM && wg == 2) {
        #pragma unroll 1
        for (int k = 0; k < 5; k++) {
          const uint32_t z = sb + OFF_BLK + k * BLK + t7 * 16;
          sts128(z + B_TBL, 0, 0, 0, 0); sts128(z + B_TBL + 2048, 0, 0, 0, 0);
          if (t7 < 16) sts128(z - 256, 0, 0, 0, 0);
        }
      }
      #pragma unroll
      for (int q = 0; q < 2; q++) {
        #pragma unroll
        for (int e = 0; e < 2; e++) pr[q][e] = raw[q][2 * e] | (raw[q][2 * e + 1] << 16);
        const uint32_t m = __reduce_max_sync(0xffffffff, max(raw[q][2] & 0x7fffu, raw[q][3] & 0x7fffu));
        if (lane == 0) sts32(sb + OFF_EPOCH + 64 + (wg * 2 + q) * 16 + w4 * 4, m);
      }
      bar_sync(2 + wg, 128);
    }
    if (tid == 256) TS(40);
#define P0(w) ((w) == 1 ? OFF_X + 32768 : OFF_BLK + (w) * 3584)
#define P1(w) ((w) == 1 ? 7168 : BLK)
#define P2(w) ((w) == 1 ? OFF_BLK + 4 * BLK - OFF_X - 32768 : 2 * BLK)
    if (EN_SSM) {
      const uint32_t fa = sb + P0(wg) + (lane >> 4) * P1(wg) + (w4 & 1) * P2(wg) + ((lane >> 3) & 1) * 256 + (lane & 7) * 16;
      const uint32_t ea = fa + (w4 >> 1) * 2048, ga = fa + 4096 + (w4 >> 1) * 1536;
      #pragma unroll 1
      for (int q = 0; q < (wg < 2 ? 2 : 1); q++) {
        uint32_t F[56];
#define PUT4(i, a, b, c_, d) { F[4 * (i)] = a; F[4 * (i) + 1] = b; F[4 * (i) + 2] = c_; F[4 * (i) + 3] = d; }
        {
          const uint32_t pa0 = pr[0][0], pc0 = pr[0][1];
          const float dt = bf_round(expf(bf_lo(__shfl_sync(0xffffffff, pd, q))));
          pr[0][0] = pr[1][0]; pr[0][1] = pr[1][1];
          uint32_t mm[4];
          lds128(mm, sb + OFF_EPOCH + 64 + (wg * 2 + q) * 16);
          const uint32_t ex = min(max(max(max(mm[0], mm[1]), max(mm[2], mm[3])) >> 7, 1u), 253u);
          const float sc = __uint_as_float((254u - ex) << 23);
          if (t7 == 2 + q) sts64(sb + OFF_EPOCH + 16 + (wg + 3 * q) * 8, __float_as_uint(2.f * dt * __uint_as_float(ex << 23)), pd << 16);
          const float lr = -bf_round(expf(bf_lo(pa0))) * dt * 1.44269504089f;
          const float tn = bf_hi(pa0) * dt * 0.15915494309f;
          float z1r, z1i, z2r, z2i, z4r, z4i, xr[8], xi[8], gr[8], gi[8], wr[9], wi[9];
          cexp_t(lr, -tn, z1r, z1i);
          cexp_t(lr * 8.f, tn * 8.f, xr[1], xi[1]);
          cexp_t(lr * 64.f, tn * 64.f, wr[0], wi[0]);
          xr[0] = 1.f; xi[0] = 0.f;
          cmul(xr[1], xi[1], xr[1], xi[1], xr[2], xi[2]); cmul(xr[2], xi[2], xr[1], xi[1], xr[3], xi[3]);
          cmul(xr[2], xi[2], xr[2], xi[2], xr[4], xi[4]);
          #pragma unroll
          for (int b = 1; b < 4; b++) cmul(xr[4], xi[4], xr[b], xi[b], xr[4 + b], xi[4 + b]);
          cmul(wr[0], wi[0], wr[0], wi[0], wr[1], wi[1]); cmul(wr[1], wi[1], wr[0], wi[0], wr[2], wi[2]);
          cmul(wr[1], wi[1], wr[1], wi[1], wr[3], wi[3]); cmul(wr[3], wi[3], wr[3], wi[3], wr[4], wi[4]);
          cmul(wr[4], wi[4], wr[3], wi[3], wr[5], wi[5]); cmul(wr[4], wi[4], wr[4], wi[4], wr[6], wi[6]);
          cmul(wr[6], wi[6], wr[4], wi[4], wr[7], wi[7]); cmul(wr[6], wi[6], wr[6], wi[6], wr[8], wi[8]);
          uint32_t R[4], I[4], PR[4], PI[4];
          #pragma unroll
          for (int b = 0; b < 4; b++) { R[b] = packh(xr[2 * b], xr[2 * b + 1]); I[b] = packh(xi[2 * b], xi[2 * b + 1]); }
          PUT4(0, R[0], R[1], R[2], R[3]); PUT4(1, I[0], I[1], I[2], I[3]);
          #pragma unroll
          for (int i = 0; i < 3; i++) {
            const uint32_t z = packh(wr[i], wi[i]);
            #pragma unroll
            for (int b = 0; b < 4; b++) hcm2(R[b], I[b], z, PR[b], PI[b]);
            PUT4(2 * i + 2, PR[0], PR[1], PR[2], PR[3]); PUT4(2 * i + 3, PI[0], PI[1], PI[2], PI[3]);
          }
          gr[0] = bf_lo(pc0) * sc; gi[0] = -bf_hi(pc0) * sc;
          cmul(z1r, z1i, z1r, z1i, z2r, z2i); cmul(z2r, z2i, z2r, z2i, z4r, z4i);
          cmul(gr[0], gi[0], z1r, z1i, gr[1], gi[1]);
          cmul(gr[0], gi[0], z2r, z2i, gr[2], gi[2]); cmul(gr[1], gi[1], z2r, z2i, gr[3], gi[3]);
          #pragma unroll
          for (int b = 0; b < 4; b++) cmul(gr[b], gi[b], z4r, z4i, gr[4 + b], gi[4 + b]);
          PUT4(8, packh(gr[0], gr[1]), packh(gr[2], gr[3]), packh(gr[4], gr[5]), packh(gr[6], gr[7]));
          PUT4(9, packh(gi[0], gi[1]), packh(gi[2], gi[3]), packh(gi[4], gi[5]), packh(gi[6], gi[7]));
          {
            const uint32_t z = packh(wr[3], -wi[3]), a4r = packh(gr[0], gr[4]), a4i = packh(gi[0], gi[4]);
            hcm2(packh(gr[0], gr[2]), packh(gi[0], gi[2]), z, PR[0], PI[0]);
            hcm2(packh(gr[4], gr[6]), packh(gi[4], gi[6]), z, PR[1], PI[1]);
            hcm2(a4r, a4i, packh(wr[4], -wi[4]), PR[2], PI[2]);
            hcm2(a4r, a4i, packh(wr[5], -wi[5]), PR[3], PI[3]);
            PUT4(10, PR[0], PR[1], PR[2], PR[3]); PUT4(11, PI[0], PI[1], PI[2], PI[3]);
            float hr, hi_;
            cmul(gr[0], gi[0], wr[3], -wi[3], hr, hi_);
            const uint32_t cr = packh(gr[0], hr), ci = packh(gi[0], hi_);
            #pragma unroll
            for (int i = 0; i < 3; i++) hcm2(cr, ci, packh(wr[6 + i], -wi[6 + i]), PR[i], PI[i]);
            PUT4(12, PR[0], PR[1], PR[2], 0u); PUT4(13, PI[0], PI[1], PI[2], 0u);
          }
        }
        if (q) mbar_wait(BAR(BR_KS + 1) - 8 * wg, 0);
        #pragma unroll
        for (int i = 0; i < 14; i++) sts128((i < 8 ? ea + (i >> 1) * 512 : ga + ((i - 8) >> 1) * 512) + (i & 1) * 128, F[4 * i], F[4 * i + 1], F[4 * i + 2], F[4 * i + 3]);
        fence_async();
        if (q) mbar_arrive(BAR(BR_KF)); else bar_sync(0, 512);
        if (tid == 0) TS(17 + q);
      }
    }
    if (!EN_SSM) bar_sync(0, 512);
    if (tid == 0) TS(14);
  if (wg < 2) {
    if (EN_ATT) {
    float am[96], ar[24];
    {
      const bool lead = (rtid() & 127) == 0;
      constexpr uint64_t da0 = mkdesc(SB0 + OFF_X, 16, 1024, 1), dr0 = mkdesc(SB0 + 12288, 1024, 256, 3);
      const uint64_t db0 = sw64 ? mkdesc(SB0, 2048, 512, 2) : mkdesc(SB0, 4096, 1024, 1);
      const uint32_t kst = sw64 ? 64 : 128, bh = db0 >> 32;
      uint32_t s = 0, ph = 0, xo = 0;
      #pragma unroll 1
      for (int kb = 0; kb < 20; kb++) {
        const uint32_t wo_ = s * (W_SLOT >> 4), al = (uint32_t)da0 + wg * 512 + xo, bl = (uint32_t)db0 + wo_, rl = (uint32_t)dr0 + wo_;
        mbar_wait(BAR(BR_FULL) + 8 * s, ph);
        if (kb == 0 && lead && wg == 0) TS(1);
        wg_fence();
        wg_ss192_tb(am, desc2(al, da0 >> 32), desc2(bl, bh), kb != 0);
        wg_ss48_tb(ar, desc2(al, da0 >> 32), desc2(rl, dr0 >> 32), kb != 0);
        wg_ss192_tb(am, desc2(al + 2, da0 >> 32), desc2(bl + kst, bh), 1);
        wg_ss48_tb(ar, desc2(al + 2, da0 >> 32), desc2(rl + 32, dr0 >> 32), 1);
        wg_commit();
        wg_wait<1>();
        if (lead && kb > 0 && kb < 16) mbar_arrive(BAR(BR_EMPTY) + 8 * (s == 0 ? 4 : s - 1));
        if (++s == 5) { s = 0; ph ^= 1; }
        xo += (kb & 1) ? 1020 : 4;
        if (xo == 3072) xo = 0;
      }
      wg_wait<0>();
      pin<96>(am); pin<24>(ar);
    }
    const int tid = rtid(), lane = tid & 31, tq = lane & 3;
    if (tid == 0) TS(2);
#define QV(j, e) ((j) < 8 ? am[4 * (j) + (e)] : ar[4 * ((j) - 8) + (e)])
#define KV_(j, e) ((j) < 8 ? am[32 + 4 * (j) + (e)] : ar[8 + 4 * ((j) - 8) + (e)])
#define VV(j, e) ((j) < 8 ? am[64 + 4 * (j) + (e)] : ar[16 + 4 * ((j) - 8) + (e)])
    {
      bar_sync(1, 256);
      if (tid == 0) mbar_arrive(BAR(BR_GEMM));
      const uint32_t ro = sb + (uint32_t)((warp * 16 + (lane & 15)) * 16);
      const int l0 = 2 * (c & 1) + (lane >> 4);
      const uint32_t ones = (tq == 0) ? 0x00003f80u : 0u;
#define PV(j) pack2(VV(j, 0), VV(j, 1)), pack2(VV(j, 2), VV(j, 3))
#define PK(j) pack2(phi(KV_(j, 0)), phi(KV_(j, 1))), pack2(phi(KV_(j, 2)), phi(KV_(j, 3)))
      stsm4(ro + OFF_V + (5 + 6 * (lane >> 4)) * 2048, ones, ones, ones, ones);
      #pragma unroll
      for (int j = 0; j < 10; j += 2) {
        const int l = (j == 8 && (c & 1)) ? l0 - 2 : l0 + j;
        stsm4(ro + OFF_V + (l + (l >= 5)) * 2048, PV(j), PV(j + 1));
        stsm4(ro + OFF_PK + l * 2048, PK(j), PK(j + 1));
      }
    }
    fence_async();
    bar_sync(1, 256);
    if (tid == 0) TS(3);
    mbar_wait(BAR(BR_EPOCH), 0);
    const unsigned epoch = lds32(sb + OFF_EPOCH);
    {
      float kv[24]; zero<24>(kv);
      constexpr uint64_t da = mkdesc(SB0 + OFF_PK, 128, 2048, 0), db = mkdesc(SB0 + OFF_V, 128, 2048, 0);
      wg_fence();
      #pragma unroll
      for (int s = 0; s < 8; s++) wg_ss48_tt(kv, desc2((uint32_t)da + wg * 640 + s * 16, da >> 32), desc2((uint32_t)db + wg * 768 + s * 16, db >> 32), s != 0);
      wg_commit();
      wg_wait<0>();
      pin<24>(kv);
      if (tid == 0) TS(15);
      if (w4 < 3) {
        const uint32_t wb = sb + OFF_KVS + (wg * 3 + w4) * 1536 + (lane & 15) * 96;
        #pragma unroll
        for (int j = 0; j < 6; j += 2)
          stsm4(wb + (j + (lane >> 4)) * 16, pack2(kv[4 * j], kv[4 * j + 1]), pack2(kv[4 * j + 2], kv[4 * j + 3]),
                pack2(kv[4 * j + 4], kv[4 * j + 5]), pack2(kv[4 * j + 6], kv[4 * j + 7]));
        __syncwarp();
        const int dl = w4 * 16 + (lane & 15), hl = dl >= 20;
        if (dl < 40) {
          uint4* dst = &g_kvp[(c * 16 + r) * 240 + wg * 40 + dl];
          uint32_t v[4], z[4];
          lds128(v, wb + (3 * hl + (lane >> 4)) * 16);
          lds64(z, wb + 32 + 8 * hl); z[2] = lds32(wb + 80); z[3] = epoch & 1u;
          v[3] = (v[3] & ~1u) | z[3];
          st128_rlx(dst + (lane >> 4) * 80, v);
          if (lane < 16) st128_rlx(dst + 160, z);
        }
      }
    }
    fence_async();
    bar_sync(1, 256);
    if (tid == 0) { st_rlx(FLAG(0, r, c), epoch); mbar_arrive(BAR(BR_PUB)); TS(4); }
    const int kvi = (tid >= 80) + (tid >= 160) + (tid >= 240), kd = tid - 80 * kvi;
    const int khd = kd / 20, kt0 = 5 * (khd >> 1) + 2 * (khd & 1);
    const uint32_t rb = sb + OFF_KVB + kd * 16;
    if (kvi < 3) {
      #pragma unroll 1
      for (int m = kvi; m < 7; m += 3) { const int q = kt0 + 3 + m; sts128(rb + (q >= 10 ? q - 10 : q) * 1280, 0, 0, 0, 0); }
    }
    uint32_t qa[20];
    {
      const float sc = 1.44269504089f + __uint_as_float(lds32(sb + OFF_EPOCH) ^ epoch);
      #pragma unroll
      for (int j = 0; j < 10; j++) { qa[2 * j] = pack2(phi(QV(j, 0), sc), phi(QV(j, 1), sc)); qa[2 * j + 1] = pack2(phi(QV(j, 2), sc), phi(QV(j, 3), sc)); }
    }
    if (tid == 0) TS(5);
    mbar_wait(BAR(BR_KVP), 0);
    if (tid == 0) TS(6);
    if (kvi < 3) {
      float s[8];
      zero<8>(s);
      uint32_t bad = 0;
      #pragma unroll 4
      for (int i = 0; i < 16; i++) {
        uint32_t w[4];
        lds128(w, sb + OFF_KVP + tid * 16 + i * 3840);
        bad |= w[3] ^ epoch;
        #pragma unroll
        for (int e = 0; e < 4; e++) { s[2 * e] += bf_lo(w[e]); s[2 * e + 1] += bf_hi(w[e]); }
      }
      if (__builtin_expect(bad & 1u, 0)) {
        zero<8>(s);
        #pragma unroll 1
        for (int i = 0; i < 16; i++) {
          uint32_t w[4] = {0, 0, 0, ~epoch};
          fix128_w3(w, &g_kvp[(c * 16 + i) * 240 + tid], epoch, 1u);
          #pragma unroll
          for (int e = 0; e < 4; e++) { s[2 * e] += bf_lo(w[e]); s[2 * e + 1] += bf_hi(w[e]); }
        }
        FIXCNT
      }
      const uint32_t p0 = pack2(s[0], s[1]), p1 = pack2(s[2], s[3]), p2 = pack2(s[4], s[5]), p3 = pack2(s[6], s[7]);
      if (kvi < 2) sts128(rb + (kt0 + (khd & 1) + kvi) * 1280, p0, p1, p2, p3);
      else {
        const bool od = khd & 1;
        sts128(rb + (5 * (khd >> 1) + 2) * 1280, od ? 0u : p0, od ? 0u : p1, od ? p0 : 0u, od ? p1 : 0u);
        const uint32_t zz = (p2 & 0xffffu) << (16 * (khd & 1));
        sts128(rb + 10 * 1280, khd < 2 ? zz : 0u, khd < 2 ? 0u : zz, 0u, 0u);
      }
    }
    fence_async();
    bar_sync(1, 256);
    if (tid == 0) { mbar_arrive(BAR(BR_SUM)); TS(7); }
    {
      float oa[44]; zero<44>(oa);
      constexpr uint64_t db = mkdesc(SB0 + OFF_KVB, 128, 1280, 0);
      wg_fence();
      #pragma unroll
      for (int s = 0; s < 5; s++) wg_rs88_tb(oa, &qa[4 * s], desc2((uint32_t)db + ((s == 4 && (c & 1)) ? 0 : (s + (c & 1)) * 16), db >> 32), s != 0);
      wg_commit();
      wg_wait<0>();
      pin<44>(oa);
      if (tid == 0) TS(13);
      float rc[4], rd[2][4];
      #pragma unroll
      for (int e = 0; e < 4; e++) asm("rcp.approx.ftz.f32 %0, %1;" : "=f"(rc[e]) : "f"(oa[40 + e] + 1e-6f));
      #pragma unroll
      for (int h = 0; h < 4; h++) {
        rd[0][h] = __shfl_sync(0xffffffff, rc[h & 1], (lane & 28) | (h >> 1));
        rd[1][h] = __shfl_sync(0xffffffff, rc[2 + (h & 1)], (lane & 28) | (h >> 1));
      }
      #pragma unroll
      for (int j = 0; j < 10; j++) {
        #pragma unroll
        for (int h = 0; h < 2; h++) {
          float f;
          if (j == 2) f = tq < 2 ? rd[h][0] : rd[h][1];
          else if (j == 7) f = tq < 2 ? rd[h][2] : rd[h][3];
          else f = rd[h][(8 * j) / 20];
          qa[2 * j + h] = pack2(oa[4 * j + 2 * h] * f, oa[4 * j + 2 * h + 1] * f);
        }
      }
      const uint32_t m0 = (lane & 7) == ((2 * w4) & 7), m1 = (lane & 7) == 2 * w4 + 1;
      const uint32_t oa_ = sb + OFF_EXTRA + (lane >> 4) * 2048 + (warp * 16 + (lane & 15)) * 16;
      bar_sync(1, 256);
#define TAG(v, m) (((v) & ~(m)) | (epoch & (m)))
      #pragma unroll
      for (int s = 0; s < 5; s++) stsm4(oa_ + s * 4096, TAG(qa[4 * s], m0), TAG(qa[4 * s + 1], m1), TAG(qa[4 * s + 2], m0), TAG(qa[4 * s + 3], m1));
    }
    fence_async();
    mbar_arrive(BAR(BR_OSTG));
    if (tid == 0) TS(8);
    float oc[40]; zero<40>(oc);
    {
      constexpr uint64_t dw0 = mkdesc(SB0, OFF_WOR, 1024, 1), da0 = mkdesc(SB0, 2048, 128, 0);
      const uint32_t ck = sb + tid * 32 + ((lane >> 2) << 2), ck2 = ck + (wg ? 0 : 16384);
      uint32_t bad = 0;
      auto tile = [&](int i, uint32_t so) {
        const uint32_t al = (uint32_t)da0 + wg * 64 + (so >> 4), wl = (uint32_t)dw0 + i * 640 - (i >> 1) * (1278 << 16);
        wg_fence();
        #pragma unroll
        for (int s = 0; s < 5; s++) wg_ss80_tb(oc, desc2(al + s * 256, da0 >> 32), desc2(wl + s * 128, dw0 >> 32), (i | s) != 0);
        wg_commit();
        bad |= (lds32(ck + so) ^ epoch) | (lds32(ck + so + 8192) ^ epoch) | (lds32(ck2 + so) ^ epoch);
      };
      mbar_wait(BAR(BR_WO), 0);
      mbar_wait(BAR(BR_OSTG), 0);
      tile(0, SLOT(0));
      mbar_wait(BAR(BR_WO + 1), 0);
      #pragma unroll 1
      for (int i = 1; i < 8; i++) {
        if (i == 1) {
          wg_wait<0>();
          if (lane == 0) mbar_arrive(BAR(BR_OEMPTY));
          if (EN_SSM) mbar_wait(BAR(BR_CONV), 0);
        }
        mbar_wait(BAR(BR_OFULL) + 8 * i, 0);
        if (i == 1 && tid == 0) TS(9);
        tile(i, SLOT(i));
        wg_wait<1>();
        if (lane == 0 && i > 1) mbar_arrive(BAR(BR_OEMPTY - 1) + 8 * i);
      }
      #pragma unroll 1
      for (int n = 0; n < 56; n++) {
        const int i = n & 7;
        if (i == 0) {
          uint32_t any;
          asm volatile("{\n.reg .pred p;\nsetp.ne.u32 p, %1, 0;\nbarrier.red.or.pred p, 1, 256, p;\nselp.u32 %0, 1, 0, p;\n}" : "=r"(any) : "r"(bad & 1u) : "memory");
          if (!any) break;
          bad = 0;
          FIXCNT
        }
        wg_wait<0>();
        bar_sync(1, 256);
        if (tid == 0) { mbar_expect_tx(BAR(BR_RETRY), 20480); bulk_ld(sb + SLOT(0), &g_o[(r * 8 + CHUNK(i)) * 1280], 20480, BAR(BR_RETRY)); }
        mbar_wait(BAR(BR_RETRY), n & 1);
        tile(i, SLOT(0));
      }
      wg_wait<0>();
      pin<40>(oc);
    }
    if (tid == 0) TS(10);
    {
      const int row = w4 * 16 + (lane & 15);
      const uint32_t ob = sb + OFF_BLK + 3 * BLK + wg * 10240;
      #pragma unroll
      for (int j = 0; j < 8; j += 2)
        stsm4(ob + row * 128 + (((j + (lane >> 4)) ^ (row & 7)) << 4), pack2(oc[4 * j], oc[4 * j + 1]), pack2(oc[4 * j + 2], oc[4 * j + 3]),
              pack2(oc[4 * j + 4], oc[4 * j + 5]), pack2(oc[4 * j + 6], oc[4 * j + 7]));
      stsm4(ob + 8192 + row * 32 + (lane >> 4) * 16, pack2(oc[32], oc[33]), pack2(oc[34], oc[35]), pack2(oc[36], oc[37]), pack2(oc[38], oc[39]));
      fence_async();
      bar_sync(2 + wg, 128);
      if (w4 == 0 && elect_one()) {
        tma2d_st(&prm.m[M_O64], ob, 640 + c * 64, r * 128 + wg * 64);
        tma2d_st(&prm.m[M_O16], ob + 8192, 1152 + c * 16, r * 128 + wg * 64);
        bulk_commit(); bulk_wait0_read();
        if (wg == 0) { TS(11); DUMP(0, 20); }
      }
    }
    }
  } else {
    if (EN_SSM) {
    const int tid = rtid(), lane = tid & 31, g = lane >> 2, tq = lane & 3, t7 = tid & 127;
    {
      constexpr uint64_t dE = mkdesc(SB0, 128, 512, 0);
      const uint32_t xa = sb + OFF_BLK + 18560 + t7 * 8, xr_ = sb + OFF_BLK + 18560 + (t7 ^ 64) * 8;
      float ka[24]; zero<24>(ka);
      auto product = [&](int fs) {
        wg_fence();
        #pragma unroll
        for (int s = 0; s < 8; s++) {
          const uint32_t lo = (uint32_t)dE + ((P0(fs) + ((s >> 1) & 1) * P1(fs) + (s >> 2) * P2(fs)) >> 4) + (s & 1) * 16;
          wg_ss48_tt_h(ka, desc2(lo, dE >> 32), desc2(lo + 256, dE >> 32), s != 0);
        }
        wg_commit();
      };
      product(1);
      #pragma unroll 1
      for (int it = 0; it < 5; it++) {
        const int k = (0x34201 >> (4 * it)) & 7;
        const uint32_t blk = sb + OFF_BLK + k * BLK;
        uint32_t fd[2];
        lds64(fd, sb + OFF_EPOCH + 16 + k * 8);
        const float fac = __uint_as_float(fd[0]), dsk = __uint_as_float(fd[1]);
        wg_wait<0>();
        pin<24>(ka);
        float kk[6];
        const bool up = w4 >= 2;
        if (it) bar_sync(4, 128);
        #pragma unroll
        for (int n = 0; n < 3; n++) {
          sts64f(xa + n * BLK, up ? ka[12 + 4 * n] : ka[4 * n + 2], up ? ka[13 + 4 * n] : ka[4 * n + 3]);
          kk[2 * n] = up ? ka[14 + 4 * n] : ka[4 * n]; kk[2 * n + 1] = up ? ka[15 + 4 * n] : ka[4 * n + 1];
        }
        pin<6>(kk);
        bar_sync(4, 128);
        if (t7 == 0) mbar_arrive(BAR(BR_KS) + 8 * it);
        if (it == 2) mbar_wait(BAR(BR_KF), 0);
        product((0x20120 >> (4 * it)) & 3);
        #pragma unroll
        for (int n = 0; n < 3; n++) {
          uint32_t o[2]; lds64(o, xr_ + n * BLK);
          kk[2 * n] = (kk[2 * n] + __uint_as_float(o[0])) * fac; kk[2 * n + 1] = (kk[2 * n + 1] + __uint_as_float(o[1])) * fac;
        }
        {
          const int j = (w4 & 1) * 16 + (w4 >> 1) * 8 + g;
          const uint32_t tb = blk + B_TBL;
          if (t7 == 0) kk[0] += dsk;
          const uint32_t pa_ = tb + (16 + 8 * j + 2 * tq) * 4;
          const uint32_t v = pack2(kk[1], kk[0]);
          sts32(pa_ + 4, v); sts16(pa_, v >> 16); sts16(pa_ + 10, v);
          const uint32_t u = pack2(kk[2], kk[3]), w = pack2(kk[4], kk[5]);
          if (tq < 2) {
            const uint32_t pb = tb + (16 + 256 + 8 * j + 4 * tq) * 4;
            sts16(pb, u); sts32(pb + 4, __byte_perm(u, 0, 0x1010)); sts32(pb + 8, __byte_perm(u, 0, 0x1032)); sts16(pb + 14, u >> 16);
            if (j | tq) { sts16(pb - 4, u); sts16(pb + 2, u); }
            const int i = 64 * tq + j;
            const uint32_t e0 = tb + (T_F3 + (((i - 1) & 1) ? 80 : 0) + ((i - 1) >> 1)) * 4, e1 = i ? e0 : tb + (T_F2 + 144 + 31) * 4;
            sts16(e1, w); sts16(e1 + 6, w); sts16(e0 + 64, w >> 16); sts16(e0 + 70, w >> 16);
            if (i == 0) { sts16(tb + (T_S + 3) * 4, w); sts32(tb + (T_S + 4) * 4, __byte_perm(w, 0, 0x1010)); sts16(tb + (T_S + 5) * 4 + 2, w); }
          } else {
            const int i = 32 * (tq - 2) + j;
            const uint32_t e1 = tb + (i ? T_F2 + ((2 * i - 1) & 3) * 48 + ((2 * i - 1) >> 2) : 16 + 511) * 4;
            const uint32_t e2 = tb + (T_F2 + (i & 1) * 96 + (i >> 1)) * 4;
            sts16(e1, u); sts16(e1 + 6, u); sts16(e2, u >> 16); sts16(e2 + 6, u >> 16);
            if (i == 0) {
              const uint32_t uu = __byte_perm(u, 0, 0x1010);
              sts32(tb + 528 * 4, uu); sts32(tb + 529 * 4, uu); sts32(tb + 530 * 4, uu); sts16(tb + 531 * 4 + 2, u);
              sts16(tb + (T_F3 + 80 + 63) * 4, w);
            }
          }
        }
        if (t7 == 0) TS(48 + it);
      }
      wg_wait<0>();
    }
    if (t7 == 0) TS(41);
    if (EN_SSM) {
      mbar_wait(BAR(BR_U), 0);
      bar_sync(4, 128);
      if (t7 == 0) TS(43);
      #pragma unroll 1
      for (int q6 = w4; q6 < 30; q6 += 4) {
        {
          const int k = q6 / 6, kap = (q6 - 6 * k) * 32 + lane;
          const uint32_t blk = sb + OFF_BLK + k * BLK;
          float P[33];
          P[0] = 0.f;
          #pragma unroll
          for (int q = 0; q < 4; q++) {
            const int ch = kap - 3 + q;
            uint32_t v[4];
            lds128(v, blk + (uint32_t)((ch * 16) ^ ((ch * 2) & 0x70)));
            #pragma unroll
            for (int e = 0; e < 4; e++) {
              P[q * 8 + 2 * e + 1] = (q == 0 && e < 2) ? 0.f : P[q * 8 + 2 * e] + bf_lo(v[e]);
              P[q * 8 + 2 * e + 2] = (q == 0 && e < 2) ? 0.f : P[q * 8 + 2 * e + 1] + bf_hi(v[e]);
            }
          }
#define WIN(lo, hi, e) (P[25 + (e) - (lo)] - P[24 + (e) - (hi)])
#define WIN8(lo, hi) pack2(WIN(lo, hi, 0), WIN(lo, hi, 1)), pack2(WIN(lo, hi, 2), WIN(lo, hi, 3)), pack2(WIN(lo, hi, 4), WIN(lo, hi, 5)), pack2(WIN(lo, hi, 6), WIN(lo, hi, 7))
          const uint32_t o2 = blk + B_D + (kap & 1) * 1552 + (kap >> 1) * 16;
          sts128(o2, WIN8(3, 5));
          sts128(o2 + B_D5, WIN8(6, 10));
          if (kap < 128) {
            const uint32_t o = blk + B_D + (kap & 1) * 1024 + (kap >> 1) * 16;
            sts128(o + B_D7, WIN8(5, 11));
            sts128(o + B_D9, WIN8(12, 20));
          }
        }
      }
      if (t7 < 10) sts128(sb + OFF_BLK + (t7 >> 1) * BLK + B_D + (t7 & 1) * B_D5 + 1536, 0, 0, 0, 0);
      bar_sync(4, 128);
      if (t7 == 0) TS(44);
    }
    if (EN_ATT) mbar_wait(BAR(BR_GEMM), 0);
    if (t7 == 0) TS(42);
    #pragma unroll 1
    for (int pass = 1; pass >= 0; pass--) {
      const int k = pass ? w4 : 4;
      const uint32_t blk = sb + OFF_BLK + k * BLK, tb = blk + B_TBL + (uint32_t)((g - 2 * tq) * 4);
      float acc[16][4];
      zero<64>(&acc[0][0]);
      const int kl = 16 * (lane >> 4) + 2 * (lane & 7) + ((lane >> 3) & 1);
      {
        auto ubase = [&](int sh) { const int q = kl - 2 * sh; return blk + (uint32_t)((q * 16) ^ ((q * 2) & 0x70)); };
#define LDQ(A, sh) _Pragma("unroll") for (int m = 0; m < 4; m++) load_quad(A[m], tb + (16 + 16 * (sh) + 128 * m) * 4);
#define LDB(B, ub, h) _Pragma("unroll") for (int p = 0; p < 4; p++) ldsm4(B[p], ((ub) ^ ((p & 1) * 64)) + (4 * (h) + p) * 512);
#define MLO(A, B) _Pragma("unroll") for (int m = 0; m < 4; m++) _Pragma("unroll") for (int cc = 0; cc < 8; cc++) mma16816(acc[cc + m], A[m], &B[cc >> 1][(cc & 1) * 2]);
#define MHI(A, B) _Pragma("unroll") for (int m = 0; m < 4; m++) _Pragma("unroll") for (int cc = 0; cc < 8 - m; cc++) mma16816(acc[8 + cc + m], A[m], &B[cc >> 1][(cc & 1) * 2]);
        int p_ = pass ? 0 : w4;
        const int pe = pass ? 4 : w4 + 1;
        uint32_t A[4][4], A2[4][4], Bl[4][4], Bh[4][4];
        uint32_t ub = ubase(p_ + 4);
        LDQ(A, p_ + 4) LDB(Bl, ub, 0)
        #pragma unroll 1
        for (; p_ < pe; p_++) {
          LDB(Bh, ub, 1)
          MLO(A, Bl)
          ub = ubase(p_);
          LDQ(A2, p_) LDB(Bl, ub, 0)
          MHI(A, Bh)
          LDB(Bh, ub, 1)
          load_quad(A[0], tb + (16 + 512 + 16 * (p_ & 1)) * 4); load_quad(A[1], tb + (T_S + 16 * (p_ & 1)) * 4);
          MLO(A2, Bl)
          if (p_ < 2) {
            #pragma unroll
            for (int cc = 0; cc < 8; cc++) mma16816(acc[cc + 4], A[0], &Bl[cc >> 1][(cc & 1) * 2]);
            #pragma unroll
            for (int cc = 0; cc < 4; cc++) mma16816(acc[cc + 12], A[0], &Bh[cc >> 1][(cc & 1) * 2]);
            #pragma unroll
            for (int cc = 0; cc < 8; cc++) mma16816(acc[cc + 8], A[1], &Bl[cc >> 1][(cc & 1) * 2]);
          }
          const int pn = ((p_ + 1) & 3) + 4;
          ub = ubase(pn);
          LDQ(A, pn) LDB(Bl, ub, 0)
          MHI(A2, Bh)
        }
      }
      if (t7 == 0) TS(57 + 3 * pass);
      {
        const int ih = (lane >> 3) & 1;
        const uint32_t dl = blk + B_D + (uint32_t)(((lane >> 4) * 8 + (lane & 7)) * 16);
        const uint32_t d0_ = dl + ih * 1552, d8_ = dl + (ih ? 0 : 1536), d3_ = dl + B_D7 + ih * 1024;
        auto cls2 = [&](uint32_t da, uint32_t ta) {
          uint32_t B[6][2], A[6][4];
          #pragma unroll
          for (int e = 0; e < 6; e++) { B[e][0] = lds32v(ta + (e + 4) * 32); B[e][1] = lds32v(ta + (e + 3) * 32); }
          #pragma unroll
          for (int kk = 0; kk < 6; kk++) ldsm4t(A[kk], da + kk * 256);
          #pragma unroll
          for (int e = 0; e < 6; e++)
            #pragma unroll
            for (int kk = 0; kk < 6; kk++) if (2 * kk + e + 4 < 16) mma16816(acc[2 * kk + e + 4], A[kk], B[e]);
        };
        auto cls3 = [&](uint32_t da, uint32_t ta) {
          uint32_t B[8][2], A[4][4];
          #pragma unroll
          for (int e = 0; e < 8; e++) { B[e][0] = lds32v(ta + (e + 8) * 32); B[e][1] = lds32v(ta + (e + 7) * 32); }
          #pragma unroll
          for (int kk = 0; kk < 4; kk++) ldsm4t(A[kk], da + kk * 256);
          #pragma unroll
          for (int kk = 0; kk < 4; kk++)
            #pragma unroll
            for (int e = 0; e < 8; e++) if (2 * kk + e + 8 < 16) mma16816(acc[2 * kk + e + 8], A[kk], B[e]);
        };
        #pragma unroll 1
        for (int a = pass ? 0 : w4; a < (pass ? 4 : w4 + 1); a++) cls2(((a & 2) ? d8_ : d0_) + (a & 1) * B_D5, tb + (T_F2 + 48 * a - 32) * 4);
        #pragma unroll 1
        for (int b = pass ? 0 : (w4 & 1); b < (pass ? 2 : w4 - 1); b++) cls3(d3_ + b * 2048, tb + (T_F3 + 80 * b - 64) * 4);
      }
      if (t7 == 0) TS(58 + 3 * pass);
      const uint32_t ya = blk + (uint32_t)((kl * 16) ^ ((kl * 2) & 0x70));
#define STY(p) stsm4t((ya ^ (((p) & 1) * 64)) + (p) * 512, pack2(acc[2 * (p)][0], acc[2 * (p)][1]), pack2(acc[2 * (p)][2], acc[2 * (p)][3]), \
                      pack2(acc[2 * (p) + 1][0], acc[2 * (p) + 1][1]), pack2(acc[2 * (p) + 1][2], acc[2 * (p) + 1][3]))
      if (pass == 0) {
        const uint32_t xw = blk + 4096 + w4 * 4096 + lane * 16, xr = blk + 4096 + w4 * 1024 + lane * 16;
        #pragma unroll
        for (int h = 0; h < 2; h++) {
          bar_sync(4, 128);
          if (h == 1 && t7 == 0) mbar_arrive(BAR(BR_CONV));
          #pragma unroll
          for (int i = 0; i < 8; i++)
            sts128(xw + i * 512, __float_as_uint(acc[8 * h + i][0]), __float_as_uint(acc[8 * h + i][1]), __float_as_uint(acc[8 * h + i][2]), __float_as_uint(acc[8 * h + i][3]));
          bar_sync(4, 128);
          float y[8];
          #pragma unroll
          for (int i = 0; i < 8; i++) {
            uint32_t o[4]; lds128(o, xr + (i >> 1) * 4096 + (i & 1) * 512);
            #pragma unroll
            for (int e = 0; e < 4; e++) y[4 * (i & 1) + e] = i < 2 ? __uint_as_float(o[e]) : y[4 * (i & 1) + e] + __uint_as_float(o[e]);
          }
          stsm4t((ya ^ ((w4 & 1) * 64)) + (4 * h + w4) * 512, pack2(y[0], y[1]), pack2(y[2], y[3]), pack2(y[4], y[5]), pack2(y[6], y[7]));
        }
      } else {
        __syncwarp();
        #pragma unroll
        for (int p = 0; p < 8; p++) STY(p);
      }
      if (t7 == 0 && !pass) TS(55);
      fence_async();
      mbar_arrive(BAR(BR_Y + 1) - 8 * pass);
      if (t7 == 0) TS(59 + 3 * pass);
    }
    if (t7 == 0) DUMP(40, 64);
    }
  }
  }
}

typedef CUresult (*EncFn)(CUtensorMap*, CUtensorMapDataType, cuuint32_t, void*, const cuuint64_t*, const cuuint64_t*, const cuuint32_t*,
                          const cuuint32_t*, CUtensorMapInterleave, CUtensorMapSwizzle, CUtensorMapL2promotion, CUtensorMapFloatOOBfill);
static void mkmap(EncFn enc, CUtensorMap* m, const void* base, int rank, const cuuint64_t* dims, const cuuint64_t* strides, const cuuint32_t* box, CUtensorMapSwizzle swz) {
  cuuint32_t es[5] = {1, 1, 1, 1, 1};
  enc(m, CU_TENSOR_MAP_DATA_TYPE_BFLOAT16, rank, const_cast<void*>(base), dims, strides, box, es, CU_TENSOR_MAP_INTERLEAVE_NONE, swz,
      CU_TENSOR_MAP_L2_PROMOTION_L2_128B, CU_TENSOR_MAP_FLOAT_OOB_FILL_NONE);
}

extern "C" void kernel_launch(void* const* d_in, const int* in_sizes, int n_in, void* d_out, int out_size) {
  void* fn = nullptr; cudaDriverEntryPointQueryResult qr;
  cudaGetDriverEntryPoint("cuTensorMapEncodeTiled", &fn, cudaEnableDefault, &qr);
  EncFn enc = (EncFn)fn;
  void* uy = nullptr; cudaGetSymbolAddress(&uy, g_uy);
  const cuuint64_t dx[2] = {640, 2048}, sx[1] = {1280};
  const cuuint32_t bx[2] = {64, 128}, bu[2] = {80, 128};
  const cuuint64_t dw[3] = {640, 640, 3}, sw[2] = {3840, 1280};
  const cuuint32_t br[3] = {16, 32, 3};
  const cuuint64_t dwa[4] = {64, 640, 10, 3}, swa[3] = {3840, 128, 1280}, dwb[4] = {32, 640, 20, 3}, swb[3] = {3840, 64, 1280};
  const cuuint32_t bwa[4] = {64, 32, 1, 3}, bwb[4] = {32, 32, 2, 3};
  const cuuint64_t dwo[2] = {640, 640};
  const cuuint32_t bwo[2] = {64, 80}, bo64[2] = {64, 64}, bo16[2] = {16, 64};
  const cuuint64_t dsa[2] = {2048, 1280}, ssa[1] = {4096};
  const cuuint32_t bsa[2] = {64, 80};
  const cuuint64_t dsb[2] = {64, 40960}, ssb[1] = {128};
  const cuuint32_t bsb[2] = {64, 32};
  const cuuint64_t dout[2] = {1280, 2048}, sout[1] = {2560};
  Params prm;
  mkmap(enc, &prm.m[M_X], d_in[7], 2, dx, sx, bx, CU_TENSOR_MAP_SWIZZLE_128B);
  mkmap(enc, &prm.m[M_W128], d_in[8], 4, dwa, swa, bwa, CU_TENSOR_MAP_SWIZZLE_128B);
  mkmap(enc, &prm.m[M_W64], d_in[8], 4, dwb, swb, bwb, CU_TENSOR_MAP_SWIZZLE_64B);
  mkmap(enc, &prm.m[M_WR], d_in[8], 3, dw, sw, br, CU_TENSOR_MAP_SWIZZLE_32B);
  mkmap(enc, &prm.m[M_U], d_in[0], 2, dx, sx, bu, CU_TENSOR_MAP_SWIZZLE_NONE);
  mkmap(enc, &prm.m[M_WO], d_in[9], 2, dwo, sx, bwo, CU_TENSOR_MAP_SWIZZLE_128B);
  mkmap(enc, &prm.m[M_O64], d_out, 2, dout, sout, bo64, CU_TENSOR_MAP_SWIZZLE_128B);
  mkmap(enc, &prm.m[M_O16], d_out, 2, dout, sout, bo16, CU_TENSOR_MAP_SWIZZLE_NONE);
  mkmap(enc, &prm.m[M_SA], uy, 2, dsa, ssa, bsa, CU_TENSOR_MAP_SWIZZLE_128B);
  mkmap(enc, &prm.m[M_SB], uy, 2, dsb, ssb, bsb, CU_TENSOR_MAP_SWIZZLE_128B);
  mkmap(enc, &prm.m[M_OUT], d_out, 2, dout, sout, bu, CU_TENSOR_MAP_SWIZZLE_NONE);
  prm.u = (const __nv_bfloat16*)d_in[0]; prm.wo = (const __nv_bfloat16*)d_in[9];
  for (int i = 0; i < 4; i++) prm.par[i] = (const __nv_bfloat16*)d_in[1 + i];
  prm.logdt = (const __nv_bfloat16*)d_in[5]; prm.dskip = (const __nv_bfloat16*)d_in[6];
  cudaFuncSetAttribute(fused_kernel, cudaFuncAttributeMaxDynamicSharedMemorySize, SMEM_BYTES);
  cudaLaunchConfig_t cfg = {};
  cfg.gridDim = dim3(128); cfg.blockDim = dim3(512); cfg.dynamicSmemBytes = SMEM_BYTES; cfg.stream = cudaStreamPerThread;
  cudaLaunchAttribute at[1];
  at[0].id = cudaLaunchAttributeClusterDimension; at[0].val.clusterDim.x = 2; at[0].val.clusterDim.y = 1; at[0].val.clusterDim.z = 1;
  cfg.attrs = at; cfg.numAttrs = 1;
  cudaLaunchKernelEx(&cfg, fused_kernel, prm);
}
```

```cpp
#include <cuda_runtime.h>
#include <cuda_bf16.h>
#include <cuda_fp16.h>
#include <cuda.h>
#include <stdint.h>

#define KST 2
#define EN_ATT 1
#define EN_SSM 1

__device__ __align__(1024) __nv_bfloat16 g_uy[2 * 640 * 2048];
__device__ __align__(128) uint4 g_kvp[8 * 16 * 240];
__device__ __align__(128) uint4 g_o[128 * 1280];
__device__ __align__(128) unsigned g_flag[4 * 128 * 32];
__device__ unsigned g_epoch[128];
#define TS(i) do {} while (0)
#define DUMP(lo, hi) do {} while (0)
#define FIXCNT

constexpr uint32_t SB0 = 1024;
constexpr uint32_t W_SLOT = 15360, OFF_X = 76800;
constexpr uint32_t OFF_WOR = 81920, OFF_KVP = 10240, OFF_KVS = 71680, OFF_PK = 10240, OFF_V = 30720, OFF_EXTRA = 102400, OFF_KVB = OFF_EXTRA;
constexpr uint32_t OFF_BAR = 125952, OFF_BLK = 128000, BLK = 20480;
constexpr uint32_t B_D = 4096, B_D5 = 3088, B_D7 = 6176, B_D9 = 8224, B_TBL = 14400;
constexpr int T_S = 576, T_F2 = 624, T_F3 = 816;
constexpr uint32_t OFF_UT = OFF_BLK + 4 * BLK;
constexpr uint32_t SMEM_BYTES = OFF_BLK + 5 * BLK;
enum { BR_FULL = 0, BR_WO = 5, BR_PUB = 7, BR_KVP = 8, BR_U = 9, BR_SUM = 10, BR_GEMM = 11, BR_UIN = 12, BR_YIN = 13, BR_EPOCH = 14,
       BR_FREE = 15, BR_RETRY = 17, BR_UOUT = 18, BR_OFULL = 18, BR_KS = 26, BR_EMPTY = 31, BR_OEMPTY = 36, BR_Y = 43, BR_OSTG = 45, BR_CONV = 16,
       BR_DRDY = 46, BR_U2 = 47, BR_COUNT = 48 };
constexpr uint32_t OFF_EPOCH = OFF_BAR + 8 * BR_COUNT;
enum { M_X, M_W128, M_W64, M_WR, M_U, M_WO, M_O64, M_O16, M_SA, M_OUT, M_COUNT };

__device__ __forceinline__ long long clk64() { long long t; asm volatile("mov.u64 %0, %%clock64;" : "=l"(t) :: "memory"); return t; }
__device__ __forceinline__ uint32_t smem_u32(const void* p) { return (uint32_t)__cvta_generic_to_shared(p); }
__host__ __device__ constexpr uint64_t mkdesc(uint32_t addr, uint32_t lbo, uint32_t sbo, uint32_t swz) {
  return (uint64_t)((addr & 0x3FFFF) >> 4) | ((uint64_t)(lbo >> 4) << 16) | ((uint64_t)(sbo >> 4) << 32) | ((uint64_t)swz << 62);
}
__device__ __forceinline__ uint64_t desc2(uint32_t lo, uint32_t hi) { uint64_t d; asm("mov.b64 %0, {%1, %2};" : "=l"(d) : "r"(lo), "r"(hi)); return d; }
__device__ __forceinline__ void mbar_init(uint32_t bar, uint32_t cnt) { asm volatile("mbarrier.init.shared::cta.b64 [%0], %1;" :: "r"(bar), "r"(cnt) : "memory"); }
__device__ __forceinline__ void mbar_expect_tx(uint32_t bar, uint32_t bytes) { asm volatile("mbarrier.arrive.expect_tx.shared::cta.b64 _, [%0], %1;" :: "r"(bar), "r"(bytes) : "memory"); }
__device__ __forceinline__ void mbar_arrive(uint32_t bar) { asm volatile("mbarrier.arrive.shared::cta.b64 _, [%0];" :: "r"(bar) : "memory"); }
__device__ __forceinline__ void mbar_wait(uint32_t bar, uint32_t parity) {
  asm volatile("{\n.reg .pred p;\n.reg .u32 c;\nmov.u32 c, 0;\n"
    "WL:\nmbarrier.try_wait.parity.shared::cta.b64 p, [%0], %1;\n@p bra WD;\n"
    "add.u32 c, c, 1;\nsetp.lt.u32 p, c, 200000;\n@p bra WL;\nWD:\n}" :: "r"(bar), "r"(parity) : "memory");
}
__device__ __forceinline__ void poll_all(const unsigned* p, unsigned val) {
  asm volatile("{\n.reg .pred p;\n.reg .u32 c, v;\nmov.u32 c, 0;\n"
    "PL:\nld.relaxed.gpu.global.u32 v, [%0];\nsetp.eq.u32 p, v, %1;\nvote.sync.all.pred p, p, 0xffffffff;\n@p bra PD;\n"
    "add.u32 c, c, 1;\nsetp.lt.u32 p, c, 100000;\n@p bra PL;\nPD:\n}" :: "l"(p), "r"(val) : "memory");
}
__device__ __forceinline__ void poll_all_acq(const unsigned* p, unsigned val) {
  asm volatile("{\n.reg .pred p;\n.reg .u32 c, v;\nmov.u32 c, 0;\n"
    "PL:\nld.acquire.gpu.global.u32 v, [%0];\nsetp.eq.u32 p, v, %1;\nvote.sync.all.pred p, p, 0xffffffff;\n@p bra PD;\n"
    "add.u32 c, c, 1;\nsetp.lt.u32 p, c, 100000;\n@p bra PL;\nPD:\n}" :: "l"(p), "r"(val) : "memory");
}
__device__ __forceinline__ unsigned poll_bit(const unsigned* p, unsigned val, unsigned mask) {
  unsigned bal;
  asm volatile("{\n.reg .pred p;\n.reg .u32 c, v;\nmov.u32 c, 0;\n"
    "PL:\nld.relaxed.gpu.global.u32 v, [%1];\nsetp.eq.u32 p, v, %2;\nvote.sync.ballot.b32 %0, p, 0xffffffff;\n"
    "and.b32 v, %0, %3;\nsetp.ne.u32 p, v, 0;\n@p bra PD;\n"
    "add.u32 c, c, 1;\nsetp.lt.u32 p, c, 100000;\n@p bra PL;\nPD:\n}" : "=&r"(bal) : "l"(p), "r"(val), "r"(mask) : "memory");
  return bal;
}
__device__ __forceinline__ void fix128_w0(uint32_t* v, const void* p, uint32_t tag, uint32_t mask) {
  asm volatile("{\n.reg .pred p;\n.reg .u32 c, x;\n.reg .b128 t;\n.reg .b64 lo, hi;\nmov.u32 c, 0;\n"
    "FL:\nxor.b32 x, %0, %5;\nand.b32 x, x, %6;\nsetp.eq.u32 p, x, 0;\n@p bra FD;\n"
    "ld.relaxed.gpu.global.b128 t, [%4];\nmov.b128 {lo, hi}, t;\nmov.b64 {%0, %1}, lo;\nmov.b64 {%2, %3}, hi;\n"
    "add.u32 c, c, 1;\nsetp.lt.u32 p, c, 100000;\n@p bra FL;\nFD:\n}"
    : "+r"(v[0]), "+r"(v[1]), "+r"(v[2]), "+r"(v[3]) : "l"(p), "r"(tag), "r"(mask) : "memory");
}
__device__ __forceinline__ void fix128_w3(uint32_t* v, const void* p, uint32_t tag, uint32_t mask) {
  asm volatile("{\n.reg .pred p;\n.reg .u32 c, x;\n.reg .b128 t;\n.reg .b64 lo, hi;\nmov.u32 c, 0;\n"
    "FL:\nxor.b32 x, %3, %5;\nand.b32 x, x, %6;\nsetp.eq.u32 p, x, 0;\n@p bra FD;\n"
    "ld.relaxed.gpu.global.b128 t, [%4];\nmov.b128 {lo, hi}, t;\nmov.b64 {%0, %1}, lo;\nmov.b64 {%2, %3}, hi;\n"
    "add.u32 c, c, 1;\nsetp.lt.u32 p, c, 100000;\n@p bra FL;\nFD:\n}"
    : "+r"(v[0]), "+r"(v[1]), "+r"(v[2]), "+r"(v[3]) : "l"(p), "r"(tag), "r"(mask) : "memory");
}
__device__ __forceinline__ void fence_acq() { asm volatile("fence.acq_rel.gpu;" ::: "memory"); }
__device__ __forceinline__ bool elect_one() {
  uint32_t p; asm volatile("{\n.reg .pred P;\nelect.sync _|P, 0xffffffff;\nselp.u32 %0, 1, 0, P;\n}" : "=r"(p)); return p;
}
__device__ __forceinline__ void bar_sync(int id, int n) { asm volatile("bar.sync %0, %1;" :: "r"(id), "r"(n) : "memory"); }
__device__ __forceinline__ void fence_async() { asm volatile("fence.proxy.async.shared::cta;" ::: "memory"); }
__device__ __forceinline__ void fence_async_g() { asm volatile("fence.proxy.async.global;" ::: "memory"); }
__device__ __forceinline__ void tma2d(uint32_t dst, const CUtensorMap* m, uint32_t bar, int c0, int c1) {
  asm volatile("cp.async.bulk.tensor.2d.shared::cluster.global.mbarrier::complete_tx::bytes [%0], [%1, {%3, %4}], [%2];"
    :: "r"(dst), "l"(m), "r"(bar), "r"(c0), "r"(c1) : "memory");
}
__device__ __forceinline__ void tma3d(uint32_t dst, const CUtensorMap* m, uint32_t bar, int c0, int c1, int c2) {
  asm volatile("cp.async.bulk.tensor.3d.shared::cluster.global.mbarrier::complete_tx::bytes [%0], [%1, {%3, %4, %5}], [%2];"
    :: "r"(dst), "l"(m), "r"(bar), "r"(c0), "r"(c1), "r"(c2) : "memory");
}
__device__ __forceinline__ void tma4d(uint32_t dst, const CUtensorMap* m, uint32_t bar, int c0, int c1, int c2, int c3) {
  asm volatile("cp.async.bulk.tensor.4d.shared::cluster.global.mbarrier::complete_tx::bytes [%0], [%1, {%3, %4, %5, %6}], [%2];"
    :: "r"(dst), "l"(m), "r"(bar), "r"(c0), "r"(c1), "r"(c2), "r"(c3) : "memory");
}
__device__ __forceinline__ void tma2d_st(const CUtensorMap* m, uint32_t src, int c0, int c1) {
  asm volatile("cp.async.bulk.tensor.2d.global.shared::cta.bulk_group [%0, {%2, %3}], [%1];"
    :: "l"(m), "r"(src), "r"(c0), "r"(c1) : "memory");
}
__device__ __forceinline__ void bulk_ld(uint32_t dst, const void* src, uint32_t bytes, uint32_t bar) {
  asm volatile("cp.async.bulk.shared::cluster.global.mbarrier::complete_tx::bytes [%0], [%1], %2, [%3];"
    :: "r"(dst), "l"(src), "r"(bytes), "r"(bar) : "memory");
}
__device__ __forceinline__ void bulk_st(void* dst, uint32_t src, uint32_t bytes) {
  asm volatile("cp.async.bulk.global.shared::cta.bulk_group [%0], [%1], %2;" :: "l"(dst), "r"(src), "r"(bytes) : "memory");
}
__device__ __forceinline__ void bulk_commit() { asm volatile("cp.async.bulk.commit_group;" ::: "memory"); }
__device__ __forceinline__ void bulk_wait0() { asm volatile("cp.async.bulk.wait_group 0;" ::: "memory"); }
__device__ __forceinline__ void bulk_wait0_read() { asm volatile("cp.async.bulk.wait_group.read 0;" ::: "memory"); }
__device__ __forceinline__ unsigned ld_rlx(const unsigned* p) { unsigned v; asm volatile("ld.relaxed.gpu.global.u32 %0, [%1];" : "=r"(v) : "l"(p) : "memory"); return v; }
__device__ __forceinline__ unsigned ld_acq(const unsigned* p) { unsigned v; asm volatile("ld.acquire.gpu.global.u32 %0, [%1];" : "=r"(v) : "l"(p) : "memory"); return v; }
__device__ __forceinline__ void st_rlx(unsigned* p, unsigned v) { asm volatile("st.relaxed.gpu.global.u32 [%0], %1;" :: "l"(p), "r"(v) : "memory"); }
__device__ __forceinline__ void st_rel(unsigned* p, unsigned v) { asm volatile("st.release.gpu.global.u32 [%0], %1;" :: "l"(p), "r"(v) : "memory"); }
__device__ __forceinline__ void ld128_rlx(uint32_t* v, const void* p) {
  asm volatile("{\n.reg .b128 t;\n.reg .b64 lo, hi;\nld.relaxed.gpu.global.b128 t, [%4];\nmov.b128 {lo, hi}, t;\n"
    "mov.b64 {%0, %1}, lo;\nmov.b64 {%2, %3}, hi;\n}" : "=r"(v[0]), "=r"(v[1]), "=r"(v[2]), "=r"(v[3]) : "l"(p) : "memory");
}
__device__ __forceinline__ void st128_rlx(void* p, const uint32_t* v) {
  asm volatile("{\n.reg .b128 t;\n.reg .b64 lo, hi;\nmov.b64 lo, {%1, %2};\nmov.b64 hi, {%3, %4};\nmov.b128 t, {lo, hi};\n"
    "st.relaxed.gpu.global.b128 [%0], t;\n}" :: "l"(p), "r"(v[0]), "r"(v[1]), "r"(v[2]), "r"(v[3]) : "memory");
}
__device__ __forceinline__ uint32_t lds32(uint32_t a) { uint32_t v; asm volatile("ld.shared.u32 %0, [%1];" : "=r"(v) : "r"(a) : "memory"); return v; }
__device__ __forceinline__ uint32_t lds32v(uint32_t a) { uint32_t v; asm volatile("ld.volatile.shared.u32 %0, [%1];" : "=r"(v) : "r"(a) : "memory"); return v; }
__device__ __forceinline__ uint32_t cpa(uint32_t a, uint32_t one) { uint32_t v; asm volatile("mul.lo.u32 %0, %1, %2;" : "=r"(v) : "r"(a), "r"(one)); return v; }
__device__ __forceinline__ uint32_t cpb(uint32_t a, uint32_t zero) { uint32_t v; asm volatile("or.b32 %0, %1, %2;" : "=r"(v) : "r"(a), "r"(zero)); return v; }
__device__ __forceinline__ uint32_t lds16(uint32_t a) { uint16_t v; asm volatile("ld.shared.u16 %0, [%1];" : "=h"(v) : "r"(a) : "memory"); return v; }
__device__ __forceinline__ float ldsf(uint32_t a) { float v; asm volatile("ld.shared.f32 %0, [%1];" : "=f"(v) : "r"(a) : "memory"); return v; }
__device__ __forceinline__ void lds128(uint32_t* v, uint32_t a) { asm volatile("ld.shared.v4.u32 {%0,%1,%2,%3}, [%4];" : "=r"(v[0]), "=r"(v[1]), "=r"(v[2]), "=r"(v[3]) : "r"(a) : "memory"); }
__device__ __forceinline__ void sts32(uint32_t a, uint32_t v) { asm volatile("st.shared.u32 [%0], %1;" :: "r"(a), "r"(v) : "memory"); }
__device__ __forceinline__ void sts16(uint32_t a, uint32_t v) { asm volatile("st.shared.u16 [%0], %1;" :: "r"(a), "h"((uint16_t)v) : "memory"); }
__device__ __forceinline__ void sts64f(uint32_t a, float x, float y) { asm volatile("st.shared.v2.f32 [%0], {%1,%2};" :: "r"(a), "f"(x), "f"(y) : "memory"); }
__device__ __forceinline__ void sts128(uint32_t a, uint32_t x, uint32_t y, uint32_t z, uint32_t w) { asm volatile("st.shared.v4.u32 [%0], {%1,%2,%3,%4};" :: "r"(a), "r"(x), "r"(y), "r"(z), "r"(w) : "memory"); }
__device__ __forceinline__ void stsm4(uint32_t a, uint32_t r0, uint32_t r1, uint32_t r2, uint32_t r3) {
  asm volatile("stmatrix.sync.aligned.m8n8.x4.shared.b16 [%0], {%1,%2,%3,%4};" :: "r"(a), "r"(r0), "r"(r1), "r"(r2), "r"(r3) : "memory");
}
__device__ __forceinline__ void stsm4t(uint32_t a, uint32_t r0, uint32_t r1, uint32_t r2, uint32_t r3) {
  asm volatile("stmatrix.sync.aligned.m8n8.x4.trans.shared.b16 [%0], {%1,%2,%3,%4};" :: "r"(a), "r"(r0), "r"(r1), "r"(r2), "r"(r3) : "memory");
}
__device__ __forceinline__ void ldsm4t(uint32_t* r, uint32_t a) {
  asm volatile("ldmatrix.sync.aligned.m8n8.x4.trans.shared.b16 {%0,%1,%2,%3}, [%4];" : "=r"(r[0]), "=r"(r[1]), "=r"(r[2]), "=r"(r[3]) : "r"(a) : "memory");
}
__device__ __forceinline__ void ldsm4(uint32_t* r, uint32_t a) {
  asm volatile("ldmatrix.sync.aligned.m8n8.x4.shared.b16 {%0,%1,%2,%3}, [%4];" : "=r"(r[0]), "=r"(r[1]), "=r"(r[2]), "=r"(r[3]) : "r"(a) : "memory");
}
__device__ __forceinline__ void mma16816(float* d, const uint32_t* a, const uint32_t* b) {
  asm volatile("mma.sync.aligned.m16n8k16.row.col.f32.bf16.bf16.f32 {%0,%1,%2,%3}, {%4,%5,%6,%7}, {%8,%9}, {%0,%1,%2,%3};"
    : "+f"(d[0]), "+f"(d[1]), "+f"(d[2]), "+f"(d[3]) : "r"(a[0]), "r"(a[1]), "r"(a[2]), "r"(a[3]), "r"(b[0]), "r"(b[1]));
}
__device__ __forceinline__ uint32_t pack2(float lo, float hi) { uint32_t r; asm("cvt.rn.bf16x2.f32 %0, %1, %2;" : "=r"(r) : "f"(hi), "f"(lo)); return r; }
__device__ __forceinline__ uint32_t packh(float lo, float hi) { uint32_t r; asm("cvt.rn.f16x2.f32 %0, %1, %2;" : "=r"(r) : "f"(hi), "f"(lo)); return r; }
__device__ __forceinline__ uint32_t hcmul(uint32_t x, uint32_t zp, uint32_t zq) {
  const __half2 xx = *reinterpret_cast<__half2*>(&x);
  const __half2 r = __hfma2(__high2half2(xx), *reinterpret_cast<__half2*>(&zq), __hmul2(__low2half2(xx), *reinterpret_cast<__half2*>(&zp)));
  return *reinterpret_cast<const uint32_t*>(&r);
}
__device__ __forceinline__ void hcm2(uint32_t xr, uint32_t xi, uint32_t z, uint32_t& pr, uint32_t& pi) {
  const __half2 a = *reinterpret_cast<__half2*>(&xr), b = *reinterpret_cast<__half2*>(&xi), zz = *reinterpret_cast<__half2*>(&z);
  const __half2 re = __hfma2(__hneg2(b), __high2half2(zz), __hmul2(a, __low2half2(zz)));
  const __half2 im = __hfma2(a, __high2half2(zz), __hmul2(b, __low2half2(zz)));
  pr = *reinterpret_cast<const uint32_t*>(&re); pi = *reinterpret_cast<const uint32_t*>(&im);
}
__device__ __forceinline__ void sts64(uint32_t a, uint32_t x, uint32_t y) { asm volatile("st.shared.v2.u32 [%0], {%1,%2};" :: "r"(a), "r"(x), "r"(y) : "memory"); }
__device__ __forceinline__ void lds64(uint32_t* v, uint32_t a) { asm volatile("ld.shared.v2.u32 {%0,%1}, [%2];" : "=r"(v[0]), "=r"(v[1]) : "r"(a) : "memory"); }
__device__ __forceinline__ float bf_lo(uint32_t v) { return __uint_as_float(v << 16); }
__device__ __forceinline__ float bf_hi(uint32_t v) { return __uint_as_float(v & 0xffff0000u); }
__device__ __forceinline__ float bf_round(float x) { return bf_lo(pack2(x, 0.f)); }
__device__ __forceinline__ float ex2(float x) { float r; asm("ex2.approx.ftz.f32 %0, %1;" : "=f"(r) : "f"(x)); return r; }
__device__ __forceinline__ float phi(float t, float l2e = 1.44269504089f) {
  float e = ex2(t * l2e) + 1e-6f;
  asm("{\n.reg .pred p;\nsetp.gt.f32 p, %1, 0f00000000;\n@p add.f32 %0, %1, 0f3F800008;\n}" : "+f"(e) : "f"(t));
  return e;
}
__device__ __forceinline__ void wg_fence() { asm volatile("wgmma.fence.sync.aligned;" ::: "memory"); }
__device__ __forceinline__ void wg_commit() { asm volatile("wgmma.commit_group.sync.aligned;" ::: "memory"); }
template <int N> __device__ __forceinline__ void wg_wait() { asm volatile("wgmma.wait_group.sync.aligned %0;" :: "n"(N) : "memory"); }
template <int N> __device__ __forceinline__ void pin(float* a) {
  #pragma unroll
  for (int i = 0; i < N; i++) asm volatile("" : "+f"(a[i]) :: "memory");
}
__device__ __forceinline__ int rtid() { int t; asm volatile("mov.u32 %0, %%tid.x;" : "=r"(t)); return t; }
__device__ __forceinline__ int opaque(int v) { asm volatile("" : "+r"(v)); return v; }
template <int N> __device__ __forceinline__ void zero(float* a) {
  #pragma unroll
  for (int i = 0; i < N; i++) asm volatile("mov.b32 %0, 0;" : "=f"(a[i]));
}
template <int N> __device__ __forceinline__ void pinu(uint32_t* a) {
  #pragma unroll
  for (int i = 0; i < N; i++) asm volatile("" : "+r"(a[i]) :: "memory");
}
__device__ __forceinline__ void cexp_t(float lg2mag, float turns, float& re, float& im) {
  float m = ex2(lg2mag);
  float fr = (turns - __fadd_rn(__fadd_rn(turns, 12582912.f), -12582912.f)) * 6.283185307f;
  re = m * __cosf(fr); im = m * __sinf(fr);
}
__device__ __forceinline__ void cmul(float ar, float ai, float br, float bi, float& cr, float& ci) {
  cr = fmaf(ar, br, -ai * bi); ci = fmaf(ar, bi, ai * br);
}

__device__ __forceinline__ void wg_ss192_tb(float* d, uint64_t da, uint64_t db, int scale_d) {
  asm volatile("{\n.reg .pred p;\nsetp.ne.b32 p, %98, 0;\n"
    "wgmma.mma_async.sync.aligned.m64n192k16.f32.bf16.bf16 "
    "{%0, %1, %2, %3, %4, %5, %6, %7, %8, %9, %10, %11, %12, %13, %14, %15, %16, %17, %18, %19, %20, %21, %22, %23, %24, %25, %26, %27, %28, %29, %30, %31, %32, %33, %34, %35, %36, %37, %38, %39, %40, %41, %42, %43, %44, %45, %46, %47, %48, %49, %50, %51, %52, %53, %54, %55, %56, %57, %58, %59, %60, %61, %62, %63, %64, %65, %66, %67, %68, %69, %70, %71, %72, %73, %74, %75, %76, %77, %78, %79, %80, %81, %82, %83, %84, %85, %86, %87, %88, %89, %90, %91, %92, %93, %94, %95}, %96, %97, p, 1, 1, 0, 1;\n}\n"
    : "+f"(d[0]), "+f"(d[1]), "+f"(d[2]), "+f"(d[3]), "+f"(d[4]), "+f"(d[5]), "+f"(d[6]), "+f"(d[7]), "+f"(d[8]), "+f"(d[9]), "+f"(d[10]), "+f"(d[11]), "+f"(d[12]), "+f"(d[13]), "+f"(d[14]), "+f"(d[15]), "+f"(d[16]), "+f"(d[17]), "+f"(d[18]), "+f"(d[19]), "+f"(d[20]), "+f"(d[21]), "+f"(d[22]), "+f"(d[23]), "+f"(d[24]), "+f"(d[25]), "+f"(d[26]), "+f"(d[27]), "+f"(d[28]), "+f"(d[29]), "+f"(d[30]), "+f"(d[31]), "+f"(d[32]), "+f"(d[33]), "+f"(d[34]), "+f"(d[35]), "+f"(d[36]), "+f"(d[37]), "+f"(d[38]), "+f"(d[39]), "+f"(d[40]), "+f"(d[41]), "+f"(d[42]), "+f"(d[43]), "+f"(d[44]), "+f"(d[45]), "+f"(d[46]), "+f"(d[47]), "+f"(d[48]), "+f"(d[49]), "+f"(d[50]), "+f"(d[51]), "+f"(d[52]), "+f"(d[53]), "+f"(d[54]), "+f"(d[55]), "+f"(d[56]), "+f"(d[57]), "+f"(d[58]), "+f"(d[59]), "+f"(d[60]), "+f"(d[61]), "+f"(d[62]), "+f"(d[63]), "+f"(d[64]), "+f"(d[65]), "+f"(d[66]), "+f"(d[67]), "+f"(d[68]), "+f"(d[69]), "+f"(d[70]), "+f"(d[71]), "+f"(d[72]), "+f"(d[73]), "+f"(d[74]), "+f"(d[75]), "+f"(d[76]), "+f"(d[77]), "+f"(d[78]), "+f"(d[79]), "+f"(d[80]), "+f"(d[81]), "+f"(d[82]), "+f"(d[83]), "+f"(d[84]), "+f"(d[85]), "+f"(d[86]), "+f"(d[87]), "+f"(d[88]), "+f"(d[89]), "+f"(d[90]), "+f"(d[91]), "+f"(d[92]), "+f"(d[93]), "+f"(d[94]), "+f"(d[95])
    : "l"(da), "l"(db), "r"(scale_d));
}
__device__ __forceinline__ void wg_ss48_tb(float* d, uint64_t da, uint64_t db, int scale_d) {
  asm volatile("{\n.reg .pred p;\nsetp.ne.b32 p, %26, 0;\n"
    "wgmma.mma_async.sync.aligned.m64n48k16.f32.bf16.bf16 "
    "{%0, %1, %2, %3, %4, %5, %6, %7, %8, %9, %10, %11, %12, %13, %14, %15, %16, %17, %18, %19, %20, %21, %22, %23}, %24, %25, p, 1, 1, 0, 1;\n}\n"
    : "+f"(d[0]), "+f"(d[1]), "+f"(d[2]), "+f"(d[3]), "+f"(d[4]), "+f"(d[5]), "+f"(d[6]), "+f"(d[7]), "+f"(d[8]), "+f"(d[9]), "+f"(d[10]), "+f"(d[11]), "+f"(d[12]), "+f"(d[13]), "+f"(d[14]), "+f"(d[15]), "+f"(d[16]), "+f"(d[17]), "+f"(d[18]), "+f"(d[19]), "+f"(d[20]), "+f"(d[21]), "+f"(d[22]), "+f"(d[23])
    : "l"(da), "l"(db), "r"(scale_d));
}
__device__ __forceinline__ void wg_ss48_tt(float* d, uint64_t da, uint64_t db, int scale_d) {
  asm volatile("{\n.reg .pred p;\nsetp.ne.b32 p, %26, 0;\n"
    "wgmma.mma_async.sync.aligned.m64n48k16.f32.bf16.bf16 "
    "{%0, %1, %2, %3, %4, %5, %6, %7, %8, %9, %10, %11, %12, %13, %14, %15, %16, %17, %18, %19, %20, %21, %22, %23}, %24, %25, p, 1, 1, 1, 1;\n}\n"
    : "+f"(d[0]), "+f"(d[1]), "+f"(d[2]), "+f"(d[3]), "+f"(d[4]), "+f"(d[5]), "+f"(d[6]), "+f"(d[7]), "+f"(d[8]), "+f"(d[9]), "+f"(d[10]), "+f"(d[11]), "+f"(d[12]), "+f"(d[13]), "+f"(d[14]), "+f"(d[15]), "+f"(d[16]), "+f"(d[17]), "+f"(d[18]), "+f"(d[19]), "+f"(d[20]), "+f"(d[21]), "+f"(d[22]), "+f"(d[23])
    : "l"(da), "l"(db), "r"(scale_d));
}
__device__ __forceinline__ void wg_rs88_tb(float* d, const uint32_t* a, uint64_t db, int scale_d) {
  asm volatile("{\n.reg .pred p;\nsetp.ne.b32 p, %49, 0;\n"
    "wgmma.mma_async.sync.aligned.m64n88k16.f32.bf16.bf16 "
    "{%0, %1, %2, %3, %4, %5, %6, %7, %8, %9, %10, %11, %12, %13, %14, %15, %16, %17, %18, %19, %20, %21, %22, %23, %24, %25, %26, %27, %28, %29, %30, %31, %32, %33, %34, %35, %36, %37, %38, %39, %40, %41, %42, %43}, {%44, %45, %46, %47}, %48, p, 1, 1, 1;\n}\n"
    : "+f"(d[0]), "+f"(d[1]), "+f"(d[2]), "+f"(d[3]), "+f"(d[4]), "+f"(d[5]), "+f"(d[6]), "+f"(d[7]), "+f"(d[8]), "+f"(d[9]), "+f"(d[10]), "+f"(d[11]), "+f"(d[12]), "+f"(d[13]), "+f"(d[14]), "+f"(d[15]), "+f"(d[16]), "+f"(d[17]), "+f"(d[18]), "+f"(d[19]), "+f"(d[20]), "+f"(d[21]), "+f"(d[22]), "+f"(d[23]), "+f"(d[24]), "+f"(d[25]), "+f"(d[26]), "+f"(d[27]), "+f"(d[28]), "+f"(d[29]), "+f"(d[30]), "+f"(d[31]), "+f"(d[32]), "+f"(d[33]), "+f"(d[34]), "+f"(d[35]), "+f"(d[36]), "+f"(d[37]), "+f"(d[38]), "+f"(d[39]), "+f"(d[40]), "+f"(d[41]), "+f"(d[42]), "+f"(d[43])
    : "r"(a[0]), "r"(a[1]), "r"(a[2]), "r"(a[3]), "l"(db), "r"(scale_d));
}
__device__ __forceinline__ void wg_ss80_tb(float* d, uint64_t da, uint64_t db, int scale_d) {
  asm volatile("{\n.reg .pred p;\nsetp.ne.b32 p, %42, 0;\n"
    "wgmma.mma_async.sync.aligned.m64n80k16.f32.bf16.bf16 "
    "{%0, %1, %2, %3, %4, %5, %6, %7, %8, %9, %10, %11, %12, %13, %14, %15, %16, %17, %18, %19, %20, %21, %22, %23, %24, %25, %26, %27, %28, %29, %30, %31, %32, %33, %34, %35, %36, %37, %38, %39}, %40, %41, p, 1, 1, 0, 1;\n}\n"
    : "+f"(d[0]), "+f"(d[1]), "+f"(d[2]), "+f"(d[3]), "+f"(d[4]), "+f"(d[5]), "+f"(d[6]), "+f"(d[7]), "+f"(d[8]), "+f"(d[9]), "+f"(d[10]), "+f"(d[11]), "+f"(d[12]), "+f"(d[13]), "+f"(d[14]), "+f"(d[15]), "+f"(d[16]), "+f"(d[17]), "+f"(d[18]), "+f"(d[19]), "+f"(d[20]), "+f"(d[21]), "+f"(d[22]), "+f"(d[23]), "+f"(d[24]), "+f"(d[25]), "+f"(d[26]), "+f"(d[27]), "+f"(d[28]), "+f"(d[29]), "+f"(d[30]), "+f"(d[31]), "+f"(d[32]), "+f"(d[33]), "+f"(d[34]), "+f"(d[35]), "+f"(d[36]), "+f"(d[37]), "+f"(d[38]), "+f"(d[39])
    : "l"(da), "l"(db), "r"(scale_d));
}
__device__ __forceinline__ void wg_ss48_tt_h(float* d, uint64_t da, uint64_t db, int scale_d) {
  asm volatile("{\n.reg .pred p;\nsetp.ne.b32 p, %26, 0;\n"
    "wgmma.mma_async.sync.aligned.m64n48k16.f32.f16.f16 "
    "{%0, %1, %2, %3, %4, %5, %6, %7, %8, %9, %10, %11, %12, %13, %14, %15, %16, %17, %18, %19, %20, %21, %22, %23}, %24, %25, p, 1, 1, 1, 1;\n}\n"
    : "+f"(d[0]), "+f"(d[1]), "+f"(d[2]), "+f"(d[3]), "+f"(d[4]), "+f"(d[5]), "+f"(d[6]), "+f"(d[7]), "+f"(d[8]), "+f"(d[9]), "+f"(d[10]), "+f"(d[11]), "+f"(d[12]), "+f"(d[13]), "+f"(d[14]), "+f"(d[15]), "+f"(d[16]), "+f"(d[17]), "+f"(d[18]), "+f"(d[19]), "+f"(d[20]), "+f"(d[21]), "+f"(d[22]), "+f"(d[23])
    : "l"(da), "l"(db), "r"(scale_d));
}

struct Params {
  const __nv_bfloat16 *par[4], *logdt, *dskip, *u, *wo;
  CUtensorMap m[M_COUNT];
};

#define CHUNK(i) ((i) == 0 ? c : ((i) == 7 ? (c ^ 1) : (((c & 6) + 1 + (i)) & 7)))
#define FLAG(kind, rr, cc) (&g_flag[((kind) * 128 + (rr) * 8 + (cc)) * 32])
#define SLOT(i) ((i) == 0 || (i) == 5 ? OFF_EXTRA : OFF_BLK - 256 + ((i) > 5 ? (i) - 6 : (i) - 1) * BLK)
__device__ __forceinline__ void load_quad(uint32_t* A, uint32_t addr) {
  A[0] = lds32v(addr); A[1] = lds32v(addr + 32); A[2] = lds32v(addr - 32); A[3] = lds32v(addr);
}

__global__ void __launch_bounds__(512, 1) fused_kernel(const __grid_constant__ Params prm) {
  extern __shared__ unsigned char smem_raw[];
  const uint32_t sb = __shfl_sync(0xffffffff, smem_u32(smem_raw), 0);
  const int tid = threadIdx.x, lane = tid & 31;
  const int warp = __shfl_sync(0xffffffff, tid >> 5, 0), wg = warp >> 2, w4 = warp & 3;
  const int cta = blockIdx.x, r = cta >> 3, c = cta & 7;
  if ((sb & 0xffffffu) != SB0) return;
#define BAR(i) (sb + OFF_BAR + 8 * (i))
  const bool sw64 = ((c + 1) & 2) != 0;

  if (wg == 3) {
    if (warp == 13 && elect_one()) {
      #pragma unroll
      for (int i = M_W128; i <= M_U; i++) asm volatile("prefetch.tensormap [%0];" :: "l"(&prm.m[i]) : "memory");
    }
    asm volatile("setmaxnreg.dec.sync.aligned.u32 56;");
    const int tid = rtid(), lane = tid & 31;
    if (warp == 12) {
      if (elect_one()) {
        #pragma unroll
        for (int i = 0; i < 5; i++) mbar_init(BAR(BR_FULL + i), 1);
        asm volatile("fence.mbarrier_init.release.cluster;" ::: "memory");
      }
      {
        const CUtensorMap* mwp = &prm.m[sw64 ? M_W64 : M_W128];
        const int mcol = (c * 80 + (c & 1) * 16) >> (sw64 ? 5 : 6), rcol = c * 80 + ((c & 1) ? 0 : 64);
        uint32_t s = 0, ph = 1, xs = 0;
        #pragma unroll 1
        for (int kb = 0; kb < 20; kb++) {
          if (kb == 1) asm volatile("bar.arrive 0, 512;" ::: "memory");
          if (kb == 4) { bar_sync(6, 128); if (EN_SSM) mbar_wait(BAR(BR_KS), 0); }
          if (kb >= 5) mbar_wait(BAR(BR_EMPTY) + 8 * s, ph);
          if (EN_ATT && elect_one()) {
            const uint32_t st = sb + s * W_SLOT, fb = BAR(BR_FULL) + 8 * s;
            mbar_expect_tx(fb, (kb & 1) ? W_SLOT : W_SLOT + 16384);
            if (!(kb & 1)) tma2d(sb + OFF_X + xs, &prm.m[M_X], fb, kb * 32, r * 128);
            tma4d(st, mwp, fb, 0, kb * 32, mcol, 0);
            tma3d(st + 12288, &prm.m[M_WR], fb, rcol, kb * 32, 0);
          }
          if (kb < 4 && lane == 0) TS(24 + kb);
          if (kb == 14 && elect_one()) asm volatile("cp.async.bulk.prefetch.L2.global [%0], 6400;" :: "l"(prm.wo + cta * 3200) : "memory");
          if (!EN_ATT && kb == 4) break;
          if (++s == 5) { s = 0; ph ^= 1; }
          if (kb & 1) { xs += 16384; if (xs == 49152) xs = 0; }
        }
      }
      if (EN_ATT) {
      mbar_wait(BAR(BR_EPOCH), 0);
      const unsigned epoch = lds32(sb + OFF_EPOCH);
      const unsigned* fo = FLAG(3, r, lane & 7);
      unsigned seen = __ballot_sync(0xffffffff, ld_rlx(lane < 16 ? fo : FLAG(0, lane & 15, c)) == epoch) & 0xffu;
      mbar_wait(BAR(BR_GEMM), 0);
      if (elect_one()) {
        mbar_expect_tx(BAR(BR_WO), 10240);
        tma2d(sb, &prm.m[M_WO], BAR(BR_WO), c * 64, c * 80);
        mbar_expect_tx(BAR(BR_KVP), 61440);
        mbar_expect_tx(BAR(BR_WO + 1), 7 * 10240);
      }
      {
        uint32_t ds = sb + OFF_WOR + (lane >> 3) * 128 + (((lane & 7) ^ (lane >> 3)) << 4);
        #pragma unroll 1
        for (int h = 0; h < 2; h++) {
          const int i = (lane & 6) + h;
          const char* gs = reinterpret_cast<const char*>(prm.wo) + (size_t)((lane >> 3) + CHUNK(i) * 80) * 1280 + 1024 + c * 32 + (lane & 1) * 16;
          #pragma unroll 2
          for (int q = 0; q < 20; q++) {
            asm volatile("cp.async.cg.shared.global [%0], [%1], 16;" :: "r"(ds), "l"(gs) : "memory");
            ds = (ds + 512) ^ 64; gs += 5120;
          }
        }
      }
      mbar_wait(BAR(BR_PUB), 0);
      poll_all(FLAG(0, lane & 15, c), epoch);
      if (elect_one()) { TS(23); bulk_ld(sb + OFF_KVP, &g_kvp[c * 16 * 240], 61440, BAR(BR_KVP)); }
      asm volatile("cp.async.wait_all;" ::: "memory");
      fence_async();
      mbar_arrive(BAR(BR_WO));
      mbar_wait(BAR(BR_SUM), 0);
      if (elect_one()) {
        #pragma unroll 1
        for (int i = 1; i < 8; i++) tma2d(sb + i * 10240, &prm.m[M_WO], BAR(BR_WO + 1), c * 64, CHUNK(i) * 80);
      }
      mbar_wait(BAR(BR_OSTG), 0);
      if (elect_one()) {
        bulk_st(&g_o[cta * 1280], sb + OFF_EXTRA, 20480);
        bulk_commit();
        bulk_wait0();
        st_rlx(FLAG(3, r, c), epoch);
        TS(20);
      }
      __syncwarp();
      #pragma unroll 1
      for (int i = 1; i < 8; i++) {
        const int src = CHUNK(i);
        if (!((seen >> src) & 1)) seen = poll_bit(fo, epoch, 1u << src);
        if (i >= 5) mbar_wait(BAR(BR_OEMPTY - 5) + 8 * i, 0);
        if (EN_SSM && i == 1) mbar_wait(BAR(BR_FREE), 0);
        if (elect_one()) {
          mbar_expect_tx(BAR(BR_OFULL) + 8 * i, 20480);
          bulk_ld(sb + SLOT(i), &g_o[(r * 8 + src) * 1280], 20480, BAR(BR_OFULL) + 8 * i);
          if (i == 1) TS(21);
          if (i == 7) TS(22);
        }
        __syncwarp();
      }
      if (lane == 0) { DUMP(20, 30); }
      }
    } else {
      const int hw = warp - 13, ht = tid - 416;
      if (hw == 2 && elect_one()) {
        #pragma unroll
        for (int i = 5; i < BR_COUNT; i++) mbar_init(BAR(i), i == BR_WO ? 33 : i < BR_EMPTY ? 1 : i < BR_OEMPTY ? 2 : i < BR_Y ? 8 : i < BR_OSTG ? 4 : i == BR_OSTG ? 8 : i == BR_DRDY ? 3 : 1);
        asm volatile("fence.mbarrier_init.release.cluster;" ::: "memory");
        if (EN_SSM) { mbar_expect_tx(BAR(BR_UIN), 20480); tma2d(sb + OFF_UT, &prm.m[M_U], BAR(BR_UIN), c * 80, r * 128); }
      }
      __syncwarp();
      asm volatile("bar.arrive 0, 512;" ::: "memory");
      const unsigned epoch = hw == 0 ? ld_rlx(&g_epoch[cta]) + 1 : 0;
      bar_sync(5, 96);
      asm volatile("bar.arrive 6, 128;" ::: "memory");
      if (hw == 1 && elect_one()) {
        #pragma unroll
        for (int i = M_WO; i < M_COUNT; i++) asm volatile("prefetch.tensormap [%0];" :: "l"(&prm.m[i]) : "memory");
      }
      if (ht == 0) {
        st_rlx(&g_epoch[cta], epoch);
        sts32(sb + OFF_EPOCH, epoch);
        mbar_arrive(BAR(BR_EPOCH));
      }
      if (EN_SSM) {
      const int mi = lane >> 3, rw = lane & 7, ch0 = c * 80 + r * 5;
      mbar_wait(BAR(BR_UIN), 0);
      if (ht == 0) TS(36);
      #pragma unroll 1
      for (int h = 0; h < 2; h++) {
        const uint32_t sa = sb + OFF_UT + h * 10240 + (8 * mi + rw) * 160 + hw * 16, da = sb + OFF_UT + h * 10240 + (hw * 8 + rw) * 128 + ((mi ^ rw ^ h) << 4);
        uint32_t v[8][4];
        #pragma unroll
        for (int q = 0; q < 8; q++) if (q < 6 || hw == 0) ldsm4t(v[q], sa + (q & 1) * 5120 + (q >> 1) * 48);
        bar_sync(5, 96);
        #pragma unroll
        for (int q = 0; q < 8; q++) if (q < 6 || hw == 0) stsm4((da ^ ((q & 1) * 64)) + (q >> 1) * 3072, v[q][0], v[q][1], v[q][2], v[q][3]);
      }
      fence_async();
      bar_sync(5, 96);
      if (hw == 0) {
        if (elect_one()) {
          tma2d_st(&prm.m[M_SA], sb + OFF_UT, r * 128, c * 80);
          tma2d_st(&prm.m[M_SA], sb + OFF_UT + 10240, r * 128 + 64, c * 80);
          bulk_commit(); bulk_wait0_read();
          mbar_arrive(BAR(BR_UOUT));
          TS(37);
          bulk_wait0();
          st_rel(FLAG(1, r, c), epoch);
          TS(30);
        }
        __syncwarp();
        poll_all_acq(FLAG(1, lane & 15, c), epoch);
      }
      #pragma unroll 1
      for (int q6 = hw; q6 < 30; q6 += 3) {
        if (q6 < 3 || (q6 >= 18 && q6 < 21)) {
          const int p = q6 >= 18;
          if (hw == 0) {
            mbar_wait(BAR(BR_KS + 2) + 16 * p, 0);
            if (elect_one()) {
              fence_async_g();
              mbar_expect_tx(BAR(p ? BR_U2 : BR_U), p ? 8192 : 12288);
              #pragma unroll 1
              for (int q = 3 * p; q < 3 + 2 * p; q++) bulk_ld(sb + OFF_BLK + q * BLK, g_uy + (ch0 + q) * 2048, 4096, BAR(p ? BR_U2 : BR_U));
              TS(31);
            }
            __syncwarp();
            mbar_wait(BAR(p ? BR_U2 : BR_U), 0);
          }
          bar_sync(5, 96);
          if (ht == 0) TS(38 + p);
        }
        {
          const int k = q6 / 6, kap = (q6 - 6 * k) * 32 + lane;
          const uint32_t blk = sb + OFF_BLK + k * BLK;
          float P[33];
          P[0] = 0.f;
          #pragma unroll
          for (int q = 0; q < 4; q++) {
            const int ch = kap - 3 + q;
            uint32_t v[4];
            lds128(v, blk + (uint32_t)((ch * 16) ^ ((ch * 2) & 0x10)));
            #pragma unroll
            for (int e = 0; e < 4; e++) {
              P[q * 8 + 2 * e + 1] = (q == 0 && e < 2) ? 0.f : P[q * 8 + 2 * e] + bf_lo(v[e]);
              P[q * 8 + 2 * e + 2] = (q == 0 && e < 2) ? 0.f : P[q * 8 + 2 * e + 1] + bf_hi(v[e]);
            }
          }
#define WIN(lo, hi, e) (P[25 + (e) - (lo)] - P[24 + (e) - (hi)])
#define WIN8(lo, hi) pack2(WIN(lo, hi, 0), WIN(lo, hi, 1)), pack2(WIN(lo, hi, 2), WIN(lo, hi, 3)), pack2(WIN(lo, hi, 4), WIN(lo, hi, 5)), pack2(WIN(lo, hi, 6), WIN(lo, hi, 7))
          const uint32_t o2 = blk + B_D + (kap & 1) * 1552 + (kap >> 1) * 16;
          sts128(o2, WIN8(3, 5));
          sts128(o2 + B_D5, WIN8(6, 10));
          if (kap < 128) {
            const uint32_t o = blk + B_D + (kap & 1) * 1024 + (kap >> 1) * 16;
            sts128(o + B_D7, WIN8(5, 11));
            sts128(o + B_D9, WIN8(12, 20));
          }
        }
      }
      if (ht < 10) sts128(sb + OFF_BLK + (ht >> 1) * BLK + B_D + (ht & 1) * B_D5 + 1536, 0, 0, 0, 0);
      __syncwarp();
      if (lane == 0) mbar_arrive(BAR(BR_DRDY));
      if (ht == 0) TS(32);
      if (hw == 0) {
        #pragma unroll 1
        for (int p = 0; p < 2; p++) {
          mbar_wait(BAR(BR_Y) + 8 * p, 0);
          if (elect_one()) {
            #pragma unroll 1
            for (int k = 4 * p; k < 4 + p; k++) bulk_st(g_uy + (640 + ch0 + k) * 2048, sb + OFF_BLK + k * BLK, 4096);
            bulk_commit(); bulk_wait0_read();
            if (p == 0) mbar_arrive(BAR(BR_FREE));
          }
          __syncwarp();
        }
        if (elect_one()) {
          mbar_expect_tx(BAR(BR_YIN), 20480);
          bulk_wait0();
          st_rel(FLAG(2, r, c), epoch);
          TS(33);
        }
        __syncwarp();
        poll_all_acq(FLAG(2, lane & 15, c), epoch);
        if (elect_one()) {
          fence_async_g();
          tma2d(sb + OFF_BLK + 4 * BLK, &prm.m[M_SA], BAR(BR_YIN), r * 128, 640 + c * 80);
          tma2d(sb + OFF_BLK + 4 * BLK + 10240, &prm.m[M_SA], BAR(BR_YIN), r * 128 + 64, 640 + c * 80);
          TS(34);
        }
      }
      {
        uint32_t sa = sb + OFF_BLK + 4 * BLK + (hw * 8 + rw) * 128 + ((mi ^ rw) << 4);
        uint32_t da = sb + SLOT(3) + (8 * mi + rw) * 160 + hw * 16;
        if (hw == 0) {
          if (EN_ATT) mbar_wait(BAR(BR_OEMPTY + 3), 0);
          mbar_wait(BAR(BR_YIN), 0);
        }
        bar_sync(5, 96);
        #pragma unroll 1
        for (int i = hw; i < 10; i += 3) {
          uint32_t v[4][4];
          #pragma unroll
          for (int q = 0; q < 4; q++) ldsm4t(v[q], (sa ^ ((q & 1) * 64 + (q >> 1) * 16)) + (q >> 1) * 10240);
          #pragma unroll
          for (int q = 0; q < 4; q++) stsm4(da + q * 5120, v[q][0], v[q][1], v[q][2], v[q][3]);
          sa += 3072; da += 48;
        }
      }
      fence_async();
      bar_sync(5, 96);
      if (hw == 0 && elect_one()) {
        tma2d_st(&prm.m[M_OUT], sb + SLOT(3), c * 80, r * 128);
        bulk_commit(); bulk_wait0_read();
        TS(35); DUMP(30, 40); DUMP(0, 1);
      }
      }
    }
  } else {
    const int g = lane >> 2, tq = lane & 3, t7 = tid & 127;
    uint32_t pr[3][2], pd;
    {
      const int ch = c * 80 + r * 5 + wg;
      uint32_t raw[3][4];
      #pragma unroll
      for (int e = 0; e < 4; e++) {
        const __nv_bfloat16* pp = prm.par[e] + ch * 128 + t7;
        #pragma unroll
        for (int q = 0; q < 3; q++) {
          raw[q][e] = 0;
          if (q == 0 || wg == 2) asm volatile("ld.global.nc.u16 %0, [%1];" : "=r"(raw[q][e]) : "l"(pp + q * 128));
        }
      }
      asm volatile("ld.global.nc.u16 %0, [%1];" : "=r"(pd) : "l"(((lane & 4) ? prm.dskip : prm.logdt) + ch + min(lane & 3, 2)));
      asm volatile("setmaxnreg.inc.sync.aligned.u32 152;");
      if (EN_SSM && wg < 2) {
        #pragma unroll
        for (int k = 0; k < 2; k++) {
          const uint32_t z = sb + OFF_BLK + (2 * wg + k) * BLK + t7 * 16;
          sts128(z + B_TBL, 0, 0, 0, 0); sts128(z + B_TBL + 2048, 0, 0, 0, 0);
        }
        if (tid < 80) sts128(sb + OFF_BLK + (tid >> 4) * BLK - 256 + (tid & 15) * 16, 0, 0, 0, 0);
      }
      #pragma unroll
      for (int q = 0; q < 3; q++) {
        #pragma unroll
        for (int e = 0; e < 2; e++) pr[q][e] = raw[q][2 * e] | (raw[q][2 * e + 1] << 16);
        const uint32_t m = __reduce_max_sync(0xffffffff, max(raw[q][2] & 0x7fffu, raw[q][3] & 0x7fffu));
        if (lane == 0) sts32(sb + OFF_EPOCH + 64 + (wg * 3 + q) * 16 + w4 * 4, m);
      }
      bar_sync(2 + wg, 128);
    }
    if (tid == 256) TS(40);
    if (EN_SSM) {
#define P0(w) ((w) == 1 ? 4 * W_SLOT : OFF_BLK + (w) * BLK)
#define P2(w) ((w) == 1 ? OFF_X + 32768 - 4 * W_SLOT : BLK)
      uint32_t ea = sb + P0(wg) + (lane >> 4) * 7168 + (w4 & 1) * P2(wg) + ((lane >> 3) & 1) * 256 + (lane & 7) * 16 + (w4 >> 1) * 2048;
      constexpr uint64_t dE = mkdesc(SB0, 128, 512, 0);
      const uint32_t xa = sb + OFF_BLK + 18560 + t7 * 8, xr_ = sb + OFF_BLK + 18560 + (t7 ^ 64) * 8;
      float ka[24]; zero<24>(ka);
      wg_fence();
      wg_ss48_tt_h(ka, dE + (OFF_BLK >> 4), dE + (OFF_BLK >> 4), 0);
      wg_commit();
      #pragma unroll 1
      for (int it = -1; it < 5; it++) {
        const int k = it < 2 ? 1 - it : it;
        const bool nf = it < 0 || it == 2 || it == 3;
        const uint32_t blk = sb + OFF_BLK + k * BLK;
        uint32_t F[56];
#define PUT4(i, a, b, c_, d) { F[4 * (i)] = a; F[4 * (i) + 1] = b; F[4 * (i) + 2] = c_; F[4 * (i) + 3] = d; }
        if (nf) {
          const int q = it < 0 ? 0 : it - 1;
          const uint32_t pa0 = pr[0][0], pc0 = pr[0][1];
          const float dt = bf_round(expf(bf_lo(__shfl_sync(0xffffffff, pd, q))));
          #pragma unroll
          for (int e = 0; e < 2; e++) { pr[0][e] = pr[1][e]; pr[1][e] = pr[2][e]; }
          uint32_t mm[4];
          lds128(mm, sb + OFF_EPOCH + 64 + (wg * 3 + q) * 16);
          const uint32_t ex = min(max(max(max(mm[0], mm[1]), max(mm[2], mm[3])) >> 7, 1u), 253u);
          const float sc = __uint_as_float((254u - ex) << 23);
          if (t7 == 4 + q) sts64(sb + OFF_EPOCH + 16 + (wg + q) * 8, __float_as_uint(2.f * dt * __uint_as_float(ex << 23)), pd << 16);
          const float lr = -bf_round(expf(bf_lo(pa0))) * dt * 1.44269504089f;
          const float tn = bf_hi(pa0) * dt * 0.15915494309f;
          float z1r, z1i, z2r, z2i, z4r, z4i, xr[8], xi[8], gr[8], gi[8], wr[9], wi[9];
          cexp_t(lr, -tn, z1r, z1i);
          cexp_t(lr * 8.f, tn * 8.f, xr[1], xi[1]);
          cexp_t(lr * 64.f, tn * 64.f, wr[0], wi[0]);
          xr[0] = 1.f; xi[0] = 0.f;
          cmul(xr[1], xi[1], xr[1], xi[1], xr[2], xi[2]); cmul(xr[2], xi[2], xr[1], xi[1], xr[3], xi[3]);
          cmul(xr[2], xi[2], xr[2], xi[2], xr[4], xi[4]);
          #pragma unroll
          for (int b = 1; b < 4; b++) cmul(xr[4], xi[4], xr[b], xi[b], xr[4 + b], xi[4 + b]);
          cmul(wr[0], wi[0], wr[0], wi[0], wr[1], wi[1]); cmul(wr[1], wi[1], wr[0], wi[0], wr[2], wi[2]);
          cmul(wr[1], wi[1], wr[1], wi[1], wr[3], wi[3]); cmul(wr[3], wi[3], wr[3], wi[3], wr[4], wi[4]);
          cmul(wr[4], wi[4], wr[3], wi[3], wr[5], wi[5]); cmul(wr[4], wi[4], wr[4], wi[4], wr[6], wi[6]);
          cmul(wr[6], wi[6], wr[4], wi[4], wr[7], wi[7]); cmul(wr[6], wi[6], wr[6], wi[6], wr[8], wi[8]);
          uint32_t R[4], I[4], PR[4], PI[4];
          #pragma unroll
          for (int b = 0; b < 4; b++) { R[b] = packh(xr[2 * b], xr[2 * b + 1]); I[b] = packh(xi[2 * b], xi[2 * b + 1]); }
          PUT4(0, R[0], R[1], R[2], R[3]); PUT4(1, I[0], I[1], I[2], I[3]);
          #pragma unroll
          for (int i = 0; i < 3; i++) {
            const uint32_t z = packh(wr[i], wi[i]);
            #pragma unroll
            for (int b = 0; b < 4; b++) hcm2(R[b], I[b], z, PR[b], PI[b]);
            PUT4(2 * i + 2, PR[0], PR[1], PR[2], PR[3]); PUT4(2 * i + 3, PI[0], PI[1], PI[2], PI[3]);
          }
          gr[0] = bf_lo(pc0) * sc; gi[0] = -bf_hi(pc0) * sc;
          cmul(z1r, z1i, z1r, z1i, z2r, z2i); cmul(z2r, z2i, z2r, z2i, z4r, z4i);
          cmul(gr[0], gi[0], z1r, z1i, gr[1], gi[1]);
          cmul(gr[0], gi[0], z2r, z2i, gr[2], gi[2]); cmul(gr[1], gi[1], z2r, z2i, gr[3], gi[3]);
          #pragma unroll
          for (int b = 0; b < 4; b++) cmul(gr[b], gi[b], z4r, z4i, gr[4 + b], gi[4 + b]);
          PUT4(8, packh(gr[0], gr[1]), packh(gr[2], gr[3]), packh(gr[4], gr[5]), packh(gr[6], gr[7]));
          PUT4(9, packh(gi[0], gi[1]), packh(gi[2], gi[3]), packh(gi[4], gi[5]), packh(gi[6], gi[7]));
          {
            const uint32_t z = packh(wr[3], -wi[3]), a4r = packh(gr[0], gr[4]), a4i = packh(gi[0], gi[4]);
            hcm2(packh(gr[0], gr[2]), packh(gi[0], gi[2]), z, PR[0], PI[0]);
            hcm2(packh(gr[4], gr[6]), packh(gi[4], gi[6]), z, PR[1], PI[1]);
            hcm2(a4r, a4i, packh(wr[4], -wi[4]), PR[2], PI[2]);
            hcm2(a4r, a4i, packh(wr[5], -wi[5]), PR[3], PI[3]);
            PUT4(10, PR[0], PR[1], PR[2], PR[3]); PUT4(11, PI[0], PI[1], PI[2], PI[3]);
            float hr, hi_;
            cmul(gr[0], gi[0], wr[3], -wi[3], hr, hi_);
            const uint32_t cr = packh(gr[0], hr), ci = packh(gi[0], hi_);
            #pragma unroll
            for (int i = 0; i < 3; i++) hcm2(cr, ci, packh(wr[6 + i], -wi[6 + i]), PR[i], PI[i]);
            PUT4(12, PR[0], PR[1], PR[2], 0u); PUT4(13, PI[0], PI[1], PI[2], 0u);
          }
        }
        else {
          #pragma unroll
          for (int i = 0; i < 56; i++) asm volatile("" : "=r"(F[i]));
        }
        uint32_t fd[2];
        lds64(fd, sb + OFF_EPOCH + 16 + k * 8);
        const float fac = __uint_as_float(fd[0]), dsk = __uint_as_float(fd[1]);
        wg_wait<0>();
        pin<24>(ka);
        float kk[6];
        const bool up = w4 >= 2;
        if (it == 1 || it == 2) bar_sync(4, 128);
        #pragma unroll
        for (int n = 0; n < 3; n++) {
          if (it >= 0) sts64f(xa + n * BLK, up ? ka[12 + 4 * n] : ka[4 * n + 2], up ? ka[13 + 4 * n] : ka[4 * n + 3]);
          kk[2 * n] = up ? ka[14 + 4 * n] : ka[4 * n]; kk[2 * n + 1] = up ? ka[15 + 4 * n] : ka[4 * n + 1];
        }
        pin<6>(kk);
        if (it >= 0) {
          bar_sync(4, 128);
          if (t7 == 0) mbar_arrive(BAR(BR_KS) + 8 * it);
          #pragma unroll
          for (int n = 0; n < 3; n++) {
            uint32_t o[2]; lds64(o, xr_ + n * BLK);
            kk[2 * n] = (kk[2 * n] + __uint_as_float(o[0])) * fac; kk[2 * n + 1] = (kk[2 * n + 1] + __uint_as_float(o[1])) * fac;
          }
        }
        if (nf) {
          if (it == 2) {
            mbar_wait(BAR(BR_UOUT), 0);
            ea += BLK;
            sts128(sb + OFF_UT + B_TBL + t7 * 16, 0, 0, 0, 0); sts128(sb + OFF_UT + B_TBL + 2048 + t7 * 16, 0, 0, 0, 0);
          }
          const uint32_t ga = ea + 4096 - (w4 >> 1) * 512;
          #pragma unroll
          for (int i = 0; i < 14; i++) sts128((i < 8 ? ea + (i >> 1) * 512 : ga + ((i - 8) >> 1) * 512) + (i & 1) * 128, F[4 * i], F[4 * i + 1], F[4 * i + 2], F[4 * i + 3]);
          fence_async();
          bar_sync(it < 0 ? 0 : 4, it < 0 ? 512 : 128);
          if (wg < 2) break;
        }
        if (it < 4) {
          const int fs = (0x33201 >> (4 * it + 4)) & 3;
          wg_fence();
          #pragma unroll
          for (int s = 0; s < 8; s++) {
            const uint32_t lo = (uint32_t)dE + ((P0(fs) + (s >> 2) * P2(fs)) >> 4) + ((s >> 1) & 1) * 448 + (s & 1) * 16;
            wg_ss48_tt_h(ka, desc2(lo, dE >> 32), desc2(lo + 256, dE >> 32), s != 0);
          }
          wg_commit();
        }
        if (it >= 0)
        {
          const int j = (w4 & 1) * 16 + (w4 >> 1) * 8 + g;
          const uint32_t tb = blk + B_TBL;
          if (t7 == 0) kk[0] += dsk;
          const uint32_t pa_ = tb + (16 + 8 * j + 2 * tq) * 4;
          const uint32_t v = pack2(kk[1], kk[0]);
          sts32(pa_ + 4, v); sts16(pa_, v >> 16); sts16(pa_ + 10, v);
          const uint32_t u = pack2(kk[2], kk[3]), w = pack2(kk[4], kk[5]);
          if (tq < 2) {
            const uint32_t pb = tb + (16 + 256 + 8 * j + 4 * tq) * 4;
            sts16(pb, u); sts32(pb + 4, __byte_perm(u, 0, 0x1010)); sts32(pb + 8, __byte_perm(u, 0, 0x1032)); sts16(pb + 14, u >> 16);
            if (j | tq) { sts16(pb - 4, u); sts16(pb + 2, u); }
            const int i = 64 * tq + j;
            const uint32_t e0 = tb + (T_F3 + (((i - 1) & 1) ? 80 : 0) + ((i - 1) >> 1)) * 4, e1 = i ? e0 : tb + (T_F2 + 144 + 31) * 4;
            sts16(e1, w); sts16(e1 + 6, w); sts16(e0 + 64, w >> 16); sts16(e0 + 70, w >> 16);
            if (i == 0) { sts16(tb + (T_S + 3) * 4, w); sts32(tb + (T_S + 4) * 4, __byte_perm(w, 0, 0x1010)); sts16(tb + (T_S + 5) * 4 + 2, w); }
          } else {
            const int i = 32 * (tq - 2) + j;
            const uint32_t e1 = tb + (i ? T_F2 + ((2 * i - 1) & 3) * 48 + ((2 * i - 1) >> 2) : 16 + 511) * 4;
            const uint32_t e2 = tb + (T_F2 + (i & 1) * 96 + (i >> 1)) * 4;
            sts16(e1, u); sts16(e1 + 6, u); sts16(e2, u >> 16); sts16(e2 + 6, u >> 16);
            if (i == 0) {
              const uint32_t uu = __byte_perm(u, 0, 0x1010);
              sts32(tb + 528 * 4, uu); sts32(tb + 529 * 4, uu); sts32(tb + 530 * 4, uu); sts16(tb + 531 * 4 + 2, u);
              sts16(tb + (T_F3 + 80 + 63) * 4, w);
            }
          }
        }
        if (t7 == 0) TS(49 + it);
      }
      wg_wait<0>();
      pin<24>(ka);
    }
    if (!EN_SSM) bar_sync(0, 512);
    if (tid == 0) TS(14);
  if (wg < 2) {
    if (EN_ATT) {
    float am[96], ar[24];
    {
      const bool lead = (rtid() & 127) == 0;
      constexpr uint64_t da0 = mkdesc(SB0 + OFF_X, 16, 1024, 1), dr0 = mkdesc(SB0 + 12288, 1024, 256, 3);
      const uint64_t db0 = sw64 ? mkdesc(SB0, 2048, 512, 2) : mkdesc(SB0, 4096, 1024, 1);
      const uint32_t kst = sw64 ? 64 : 128, bh = db0 >> 32;
      uint32_t s = 0, ph = 0, xo = 0;
      #pragma unroll 1
      for (int kb = 0; kb < 20; kb++) {
        const uint32_t wo_ = s * (W_SLOT >> 4), al = (uint32_t)da0 + wg * 512 + xo, bl = (uint32_t)db0 + wo_, rl = (uint32_t)dr0 + wo_;
        mbar_wait(BAR(BR_FULL) + 8 * s, ph);
        if (kb == 0 && lead && wg == 0) TS(1);
        wg_fence();
        wg_ss192_tb(am, desc2(al, da0 >> 32), desc2(bl, bh), kb != 0);
        wg_ss48_tb(ar, desc2(al, da0 >> 32), desc2(rl, dr0 >> 32), kb != 0);
        wg_ss192_tb(am, desc2(al + 2, da0 >> 32), desc2(bl + kst, bh), 1);
        wg_ss48_tb(ar, desc2(al + 2, da0 >> 32), desc2(rl + 32, dr0 >> 32), 1);
        wg_commit();
        wg_wait<1>();
        if (lead && kb > 0 && kb < 16) mbar_arrive(BAR(BR_EMPTY) + 8 * (s == 0 ? 4 : s - 1));
        if (++s == 5) { s = 0; ph ^= 1; }
        xo += (kb & 1) ? 1020 : 4;
        if (xo == 3072) xo = 0;
      }
      wg_wait<0>();
      pin<96>(am); pin<24>(ar);
    }
    const int tid = rtid(), lane = tid & 31, tq = lane & 3;
    if (tid == 0) TS(2);
#define QV(j, e) ((j) < 8 ? am[4 * (j) + (e)] : ar[4 * ((j) - 8) + (e)])
#define KV_(j, e) ((j) < 8 ? am[32 + 4 * (j) + (e)] : ar[8 + 4 * ((j) - 8) + (e)])
#define VV(j, e) ((j) < 8 ? am[64 + 4 * (j) + (e)] : ar[16 + 4 * ((j) - 8) + (e)])
    {
      bar_sync(1, 256);
      if (tid == 0) mbar_arrive(BAR(BR_GEMM));
      const uint32_t ro = sb + (uint32_t)((warp * 16 + (lane & 15)) * 16);
      const int l0 = 2 * (c & 1) + (lane >> 4);
      const uint32_t ones = (tq == 0) ? 0x00003f80u : 0u;
#define PV(j) pack2(VV(j, 0), VV(j, 1)), pack2(VV(j, 2), VV(j, 3))
#define PK(j) pack2(phi(KV_(j, 0)), phi(KV_(j, 1))), pack2(phi(KV_(j, 2)), phi(KV_(j, 3)))
      stsm4(ro + OFF_V + (5 + 6 * (lane >> 4)) * 2048, ones, ones, ones, ones);
      #pragma unroll
      for (int j = 0; j < 10; j += 2) {
        const int l = (j == 8 && (c & 1)) ? l0 - 2 : l0 + j;
        stsm4(ro + OFF_V + (l + (l >= 5)) * 2048, PV(j), PV(j + 1));
        stsm4(ro + OFF_PK + l * 2048, PK(j), PK(j + 1));
      }
    }
    fence_async();
    bar_sync(1, 256);
    if (tid == 0) TS(3);
    mbar_wait(BAR(BR_EPOCH), 0);
    const unsigned epoch = lds32(sb + OFF_EPOCH);
    {
      float kv[24]; zero<24>(kv);
      constexpr uint64_t da = mkdesc(SB0 + OFF_PK, 128, 2048, 0), db = mkdesc(SB0 + OFF_V, 128, 2048, 0);
      wg_fence();
      #pragma unroll
      for (int s = 0; s < 8; s++) wg_ss48_tt(kv, desc2((uint32_t)da + wg * 640 + s * 16, da >> 32), desc2((uint32_t)db + wg * 768 + s * 16, db >> 32), s != 0);
      wg_commit();
      wg_wait<0>();
      pin<24>(kv);
      if (tid == 0) TS(15);
      if (w4 < 3) {
        const uint32_t wb = sb + OFF_KVS + (wg * 3 + w4) * 1536 + (lane & 15) * 96;
        #pragma unroll
        for (int j = 0; j < 6; j += 2)
          stsm4(wb + (j + (lane >> 4)) * 16, pack2(kv[4 * j], kv[4 * j + 1]), pack2(kv[4 * j + 2], kv[4 * j + 3]),
                pack2(kv[4 * j + 4], kv[4 * j + 5]), pack2(kv[4 * j + 6], kv[4 * j + 7]));
        __syncwarp();
        const int dl = w4 * 16 + (lane & 15), hl = dl >= 20;
        if (dl < 40) {
          uint4* dst = &g_kvp[(c * 16 + r) * 240 + wg * 40 + dl];
          uint32_t v[4], z[4];
          lds128(v, wb + (3 * hl + (lane >> 4)) * 16);
          lds64(z, wb + 32 + 8 * hl); z[2] = lds32(wb + 80); z[3] = epoch & 1u;
          v[3] = (v[3] & ~1u) | z[3];
          st128_rlx(dst + (lane >> 4) * 80, v);
          if (lane < 16) st128_rlx(dst + 160, z);
        }
      }
    }
    fence_async();
    bar_sync(1, 256);
    if (tid == 0) { st_rlx(FLAG(0, r, c), epoch); mbar_arrive(BAR(BR_PUB)); TS(4); }
    const int kvi = (tid >= 80) + (tid >= 160) + (tid >= 240), kd = tid - 80 * kvi;
    const int khd = kd / 20, kt0 = 5 * (khd >> 1) + 2 * (khd & 1);
    const uint32_t rb = sb + OFF_KVB + kd * 16;
    if (kvi < 3) {
      #pragma unroll 1
      for (int m = kvi; m < 7; m += 3) { const int q = kt0 + 3 + m; sts128(rb + (q >= 10 ? q - 10 : q) * 1280, 0, 0, 0, 0); }
    }
    uint32_t qa[20];
    {
      const float sc = 1.44269504089f + __uint_as_float(lds32(sb + OFF_EPOCH) ^ epoch);
      #pragma unroll
      for (int j = 0; j < 10; j++) { qa[2 * j] = pack2(phi(QV(j, 0), sc), phi(QV(j, 1), sc)); qa[2 * j + 1] = pack2(phi(QV(j, 2), sc), phi(QV(j, 3), sc)); }
    }
    if (tid == 0) TS(5);
    if (warp == 7) mbar_wait(BAR(BR_KVP), 0);
    bar_sync(1, 256);
    if (tid == 0) TS(6);
    if (kvi < 3) {
      float s[8];
      zero<8>(s);
      uint32_t bad = 0;
      #pragma unroll 4
      for (int i = 0; i < 16; i++) {
        uint32_t w[4];
        lds128(w, sb + OFF_KVP + tid * 16 + i * 3840);
        bad |= w[3] ^ epoch;
        #pragma unroll
        for (int e = 0; e < 4; e++) { s[2 * e] += bf_lo(w[e]); s[2 * e + 1] += bf_hi(w[e]); }
      }
      if (__builtin_expect(bad & 1u, 0)) {
        zero<8>(s);
        #pragma unroll 1
        for (int i = 0; i < 16; i++) {
          uint32_t w[4] = {0, 0, 0, ~epoch};
          fix128_w3(w, &g_kvp[(c * 16 + i) * 240 + tid], epoch, 1u);
          #pragma unroll
          for (int e = 0; e < 4; e++) { s[2 * e] += bf_lo(w[e]); s[2 * e + 1] += bf_hi(w[e]); }
        }
        FIXCNT
      }
      const uint32_t p0 = pack2(s[0], s[1]), p1 = pack2(s[2], s[3]), p2 = pack2(s[4], s[5]), p3 = pack2(s[6], s[7]);
      if (kvi < 2) sts128(rb + (kt0 + (khd & 1) + kvi) * 1280, p0, p1, p2, p3);
      else {
        const bool od = khd & 1;
        sts128(rb + (5 * (khd >> 1) + 2) * 1280, od ? 0u : p0, od ? 0u : p1, od ? p0 : 0u, od ? p1 : 0u);
        const uint32_t zz = (p2 & 0xffffu) << (16 * (khd & 1));
        sts128(rb + 10 * 1280, khd < 2 ? zz : 0u, khd < 2 ? 0u : zz, 0u, 0u);
      }
    }
    fence_async();
    bar_sync(1, 256);
    if (tid == 0) { mbar_arrive(BAR(BR_SUM)); TS(7); }
    {
      float oa[44]; zero<44>(oa);
      constexpr uint64_t db = mkdesc(SB0 + OFF_KVB, 128, 1280, 0);
      wg_fence();
      #pragma unroll
      for (int s = 0; s < 5; s++) wg_rs88_tb(oa, &qa[4 * s], desc2((uint32_t)db + ((s == 4 && (c & 1)) ? 0 : (s + (c & 1)) * 16), db >> 32), s != 0);
      wg_commit();
      wg_wait<0>();
      pin<44>(oa);
      if (tid == 0) TS(13);
      float rc[4], rd[2][4];
      #pragma unroll
      for (int e = 0; e < 4; e++) asm("rcp.approx.ftz.f32 %0, %1;" : "=f"(rc[e]) : "f"(oa[40 + e] + 1e-6f));
      #pragma unroll
      for (int h = 0; h < 4; h++) {
        rd[0][h] = __shfl_sync(0xffffffff, rc[h & 1], (lane & 28) | (h >> 1));
        rd[1][h] = __shfl_sync(0xffffffff, rc[2 + (h & 1)], (lane & 28) | (h >> 1));
      }
      #pragma unroll
      for (int j = 0; j < 10; j++) {
        #pragma unroll
        for (int h = 0; h < 2; h++) {
          float f;
          if (j == 2) f = tq < 2 ? rd[h][0] : rd[h][1];
          else if (j == 7) f = tq < 2 ? rd[h][2] : rd[h][3];
          else f = rd[h][(8 * j) / 20];
          qa[2 * j + h] = pack2(oa[4 * j + 2 * h] * f, oa[4 * j + 2 * h + 1] * f);
        }
      }
      const uint32_t m0 = (lane & 7) == ((2 * w4) & 7), m1 = (lane & 7) == 2 * w4 + 1;
      const uint32_t oa_ = sb + OFF_EXTRA + (lane >> 4) * 2048 + (warp * 16 + (lane & 15)) * 16;
      bar_sync(1, 256);
#define TAG(v, m) (((v) & ~(m)) | (epoch & (m)))
      #pragma unroll
      for (int s = 0; s < 5; s++) stsm4(oa_ + s * 4096, TAG(qa[4 * s], m0), TAG(qa[4 * s + 1], m1), TAG(qa[4 * s + 2], m0), TAG(qa[4 * s + 3], m1));
    }
    fence_async();
    __syncwarp();
    if (lane == 0) mbar_arrive(BAR(BR_OSTG));
    if (tid == 0) TS(8);
    float oc[40]; zero<40>(oc);
    {
      constexpr uint64_t dw0 = mkdesc(SB0, OFF_WOR, 1024, 1), da0 = mkdesc(SB0, 2048, 128, 0);
      const uint32_t ck = sb + tid * 32 + ((lane >> 2) << 2), ck2 = ck + (wg ? 0 : 16384);
      uint32_t bad = 0;
      auto tile = [&](int i, uint32_t so) {
        const uint32_t al = (uint32_t)da0 + wg * 64 + (so >> 4), wl = (uint32_t)dw0 + i * 640 - (i >> 1) * (1278 << 16);
        wg_fence();
        #pragma unroll
        for (int s = 0; s < 5; s++) wg_ss80_tb(oc, desc2(al + s * 256, da0 >> 32), desc2(wl + s * 128, dw0 >> 32), (i | s) != 0);
        wg_commit();
        bad |= (lds32(ck + so) ^ epoch) | (lds32(ck + so + 8192) ^ epoch) | (lds32(ck2 + so) ^ epoch);
      };
      mbar_wait(BAR(BR_WO), 0);
      mbar_wait(BAR(BR_OSTG), 0);
      tile(0, SLOT(0));
      mbar_wait(BAR(BR_WO + 1), 0);
      #pragma unroll 1
      for (int i = 1; i < 8; i++) {
        if (i == 1) {
          wg_wait<0>();
          if (lane == 0) mbar_arrive(BAR(BR_OEMPTY));
          if (EN_SSM && w4 == 0) mbar_wait(BAR(BR_CONV), 0);
          if (w4 == 0) mbar_wait(BAR(BR_OFULL + 1), 0);
          bar_sync(2 + wg, 128);
        }
        mbar_wait(BAR(BR_OFULL) + 8 * i, 0);
        if (i == 1 && tid == 0) TS(9);
        tile(i, SLOT(i));
        wg_wait<1>();
        if (lane == 0 && i > 1) mbar_arrive(BAR(BR_OEMPTY - 1) + 8 * i);
      }
      #pragma unroll 1
      for (int n = 0; n < 56; n++) {
        const int i = n & 7;
        if (i == 0) {
          uint32_t any;
          asm volatile("{\n.reg .pred p;\nsetp.ne.u32 p, %1, 0;\nbarrier.red.or.pred p, 1, 256, p;\nselp.u32 %0, 1, 0, p;\n}" : "=r"(any) : "r"(bad & 1u) : "memory");
          if (!any) break;
          bad = 0;
          FIXCNT
        }
        wg_wait<0>();
        bar_sync(1, 256);
        if (tid == 0) { mbar_expect_tx(BAR(BR_RETRY), 20480); bulk_ld(sb + SLOT(0), &g_o[(r * 8 + CHUNK(i)) * 1280], 20480, BAR(BR_RETRY)); }
        mbar_wait(BAR(BR_RETRY), n & 1);
        tile(i, SLOT(0));
      }
      wg_wait<0>();
      pin<40>(oc);
    }
    if (tid == 0) TS(10);
    {
      const int row = w4 * 16 + (lane & 15);
      const uint32_t ob = sb + OFF_BLK + 3 * BLK + wg * 10240;
      #pragma unroll
      for (int j = 0; j < 8; j += 2)
        stsm4(ob + row * 128 + (((j + (lane >> 4)) ^ (row & 7)) << 4), pack2(oc[4 * j], oc[4 * j + 1]), pack2(oc[4 * j + 2], oc[4 * j + 3]),
              pack2(oc[4 * j + 4], oc[4 * j + 5]), pack2(oc[4 * j + 6], oc[4 * j + 7]));
      stsm4(ob + 8192 + row * 32 + (lane >> 4) * 16, pack2(oc[32], oc[33]), pack2(oc[34], oc[35]), pack2(oc[36], oc[37]), pack2(oc[38], oc[39]));
      fence_async();
      bar_sync(2 + wg, 128);
      if (w4 == 0 && elect_one()) {
        tma2d_st(&prm.m[M_O64], ob, 640 + c * 64, r * 128 + wg * 64);
        tma2d_st(&prm.m[M_O16], ob + 8192, 1152 + c * 16, r * 128 + wg * 64);
        bulk_commit(); bulk_wait0_read();
        if (wg == 0) { TS(11); DUMP(0, 20); }
      }
    }
    }
  } else {
    if (EN_SSM) {
    const int tid = rtid(), lane = tid & 31, g = lane >> 2, tq = lane & 3, t7 = tid & 127;
    if (t7 == 0) TS(41);
    mbar_wait(BAR(BR_U), 0);
    mbar_wait(BAR(BR_U2), 0);
    bar_sync(4, 128);
    if (EN_ATT) mbar_wait(BAR(BR_GEMM), 0);
    if (t7 == 0) TS(42);
    #pragma unroll 1
    for (int pass = 1; pass >= 0; pass--) {
      const int k = pass ? w4 : 4;
      const uint32_t blk = sb + OFF_BLK + k * BLK, tb = blk + B_TBL + (uint32_t)((g - 2 * tq) * 4);
      float acc[16][4];
      zero<64>(&acc[0][0]);
      const int kl = 16 * (lane >> 4) + 2 * (lane & 7) + ((lane >> 3) & 1);
      {
        auto ubase = [&](int sh) { const int q = kl - 2 * sh; return blk + (uint32_t)((q * 16) ^ ((q * 2) & 0x10)); };
#define LDQ(A, sh) _Pragma("unroll") for (int m = 0; m < 4; m++) load_quad(A[m], tb + (16 + 16 * (sh) + 128 * m) * 4);
#define LDB(B, ub, h) _Pragma("unroll") for (int p = 0; p < 4; p++) ldsm4(B[p], (ub) + (4 * (h) + p) * 512);
#define MLO(A, B) _Pragma("unroll") for (int m = 0; m < 4; m++) _Pragma("unroll") for (int cc = 0; cc < 8; cc++) mma16816(acc[cc + m], A[m], &B[cc >> 1][(cc & 1) * 2]);
#define MHI(A, B) _Pragma("unroll") for (int m = 0; m < 4; m++) _Pragma("unroll") for (int cc = 0; cc < 8 - m; cc++) mma16816(acc[8 + cc + m], A[m], &B[cc >> 1][(cc & 1) * 2]);
        int p_ = pass ? 0 : w4;
        const int pe = pass ? 4 : w4 + 1;
        uint32_t A[4][4], A2[4][4], Bl[4][4], Bh[4][4];
        uint32_t ub = ubase(p_ + 4);
        LDQ(A, p_ + 4) LDB(Bl, ub, 0)
        #pragma unroll 1
        for (; p_ < pe; p_++) {
          LDB(Bh, ub, 1)
          MLO(A, Bl)
          ub = ubase(p_);
          LDQ(A2, p_) LDB(Bl, ub, 0)
          MHI(A, Bh)
          LDB(Bh, ub, 1)
          load_quad(A[0], tb + (16 + 512 + 16 * (p_ & 1)) * 4); load_quad(A[1], tb + (T_S + 16 * (p_ & 1)) * 4);
          MLO(A2, Bl)
          if (p_ < 2) {
            #pragma unroll
            for (int cc = 0; cc < 8; cc++) mma16816(acc[cc + 4], A[0], &Bl[cc >> 1][(cc & 1) * 2]);
            #pragma unroll
            for (int cc = 0; cc < 4; cc++) mma16816(acc[cc + 12], A[0], &Bh[cc >> 1][(cc & 1) * 2]);
            #pragma unroll
            for (int cc = 0; cc < 8; cc++) mma16816(acc[cc + 8], A[1], &Bl[cc >> 1][(cc & 1) * 2]);
          }
          const int pn = ((p_ + 1) & 3) + 4;
          ub = ubase(pn);
          LDQ(A, pn) LDB(Bl, ub, 0)
          MHI(A2, Bh)
        }
      }
      if (t7 == 0) TS(57 + 3 * pass);
      mbar_wait(BAR(BR_DRDY), 0);
      {
        const int ih = (lane >> 3) & 1;
        const uint32_t dl = blk + B_D + (uint32_t)(((lane >> 4) * 8 + (lane & 7)) * 16);
        const uint32_t d0_ = dl + ih * 1552, d8_ = dl + (ih ? 0 : 1536), d3_ = dl + B_D7 + ih * 1024;
        auto cls2 = [&](uint32_t da, uint32_t ta) {
          uint32_t B[6][2], A[6][4];
          #pragma unroll
          for (int e = 0; e < 6; e++) { B[e][0] = lds32v(ta + (e + 4) * 32); B[e][1] = lds32v(ta + (e + 3) * 32); }
          #pragma unroll
          for (int kk = 0; kk < 6; kk++) ldsm4t(A[kk], da + kk * 256);
          #pragma unroll
          for (int e = 0; e < 6; e++)
            #pragma unroll
            for (int kk = 0; kk < 6; kk++) if (2 * kk + e + 4 < 16) mma16816(acc[2 * kk + e + 4], A[kk], B[e]);
        };
        auto cls3 = [&](uint32_t da, uint32_t ta) {
          uint32_t B[8][2], A[4][4];
          #pragma unroll
          for (int e = 0; e < 8; e++) { B[e][0] = lds32v(ta + (e + 8) * 32); B[e][1] = lds32v(ta + (e + 7) * 32); }
          #pragma unroll
          for (int kk = 0; kk < 4; kk++) ldsm4t(A[kk], da + kk * 256);
          #pragma unroll
          for (int kk = 0; kk < 4; kk++)
            #pragma unroll
            for (int e = 0; e < 8; e++) if (2 * kk + e + 8 < 16) mma16816(acc[2 * kk + e + 8], A[kk], B[e]);
        };
        #pragma unroll 1
        for (int a = pass ? 0 : w4; a < (pass ? 4 : w4 + 1); a++) cls2(((a & 2) ? d8_ : d0_) + (a & 1) * B_D5, tb + (T_F2 + 48 * a - 32) * 4);
        #pragma unroll 1
        for (int b = pass ? 0 : (w4 & 1); b < (pass ? 2 : w4 - 1); b++) cls3(d3_ + b * 2048, tb + (T_F3 + 80 * b - 64) * 4);
      }
      if (t7 == 0) TS(58 + 3 * pass);
      const uint32_t ya = blk + (uint32_t)((kl * 16) ^ ((kl * 2) & 0x10));
#define STY(p) stsm4t(ya + (p) * 512, pack2(acc[2 * (p)][0], acc[2 * (p)][1]), pack2(acc[2 * (p)][2], acc[2 * (p)][3]), \
                      pack2(acc[2 * (p) + 1][0], acc[2 * (p) + 1][1]), pack2(acc[2 * (p) + 1][2], acc[2 * (p) + 1][3]))
      if (pass == 0) {
        const uint32_t xw = blk + 4096 + w4 * 4096 + lane * 16, xr = blk + 4096 + w4 * 1024 + lane * 16;
        #pragma unroll
        for (int h = 0; h < 2; h++) {
          bar_sync(4, 128);
          if (h == 1 && t7 == 0) mbar_arrive(BAR(BR_CONV));
          #pragma unroll
          for (int i = 0; i < 8; i++)
            sts128(xw + i * 512, __float_as_uint(acc[8 * h + i][0]), __float_as_uint(acc[8 * h + i][1]), __float_as_uint(acc[8 * h + i][2]), __float_as_uint(acc[8 * h + i][3]));
          bar_sync(4, 128);
          float y[8];
          #pragma unroll
          for (int i = 0; i < 8; i++) {
            uint32_t o[4]; lds128(o, xr + (i >> 1) * 4096 + (i & 1) * 512);
            #pragma unroll
            for (int e = 0; e < 4; e++) y[4 * (i & 1) + e] = i < 2 ? __uint_as_float(o[e]) : y[4 * (i & 1) + e] + __uint_as_float(o[e]);
          }
          stsm4t(ya + (4 * h + w4) * 512, pack2(y[0], y[1]), pack2(y[2], y[3]), pack2(y[4], y[5]), pack2(y[6], y[7]));
        }
      } else {
        __syncwarp();
        #pragma unroll
        for (int p = 0; p < 8; p++) STY(p);
      }
      if (t7 == 0 && !pass) TS(55);
      fence_async();
      __syncwarp();
      if (lane == 0) mbar_arrive(BAR(BR_Y + 1) - 8 * pass);
      if (t7 == 0) TS(59 + 3 * pass);
    }
    if (t7 == 0) DUMP(40, 64);
    }
  }
  }
}

typedef CUresult (*EncFn)(CUtensorMap*, CUtensorMapDataType, cuuint32_t, void*, const cuuint64_t*, const cuuint64_t*, const cuuint32_t*,
                          const cuuint32_t*, CUtensorMapInterleave, CUtensorMapSwizzle, CUtensorMapL2promotion, CUtensorMapFloatOOBfill);
static void mkmap(EncFn enc, CUtensorMap* m, const void* base, int rank, const cuuint64_t* dims, const cuuint64_t* strides, const cuuint32_t* box, CUtensorMapSwizzle swz) {
  cuuint32_t es[5] = {1, 1, 1, 1, 1};
  enc(m, CU_TENSOR_MAP_DATA_TYPE_BFLOAT16, rank, const_cast<void*>(base), dims, strides, box, es, CU_TENSOR_MAP_INTERLEAVE_NONE, swz,
      CU_TENSOR_MAP_L2_PROMOTION_L2_128B, CU_TENSOR_MAP_FLOAT_OOB_FILL_NONE);
}

extern "C" void kernel_launch(void* const* d_in, const int* in_sizes, int n_in, void* d_out, int out_size) {
  void* fn = nullptr; cudaDriverEntryPointQueryResult qr;
  cudaGetDriverEntryPoint("cuTensorMapEncodeTiled", &fn, cudaEnableDefault, &qr);
  EncFn enc = (EncFn)fn;
  void* uy = nullptr; cudaGetSymbolAddress(&uy, g_uy);
  const cuuint64_t dx[2] = {640, 2048}, sx[1] = {1280};
  const cuuint32_t bx[2] = {64, 128}, bu[2] = {80, 128};
  const cuuint64_t dw[3] = {640, 640, 3}, sw[2] = {3840, 1280};
  const cuuint32_t br[3] = {16, 32, 3};
  const cuuint64_t dwa[4] = {64, 640, 10, 3}, swa[3] = {3840, 128, 1280}, dwb[4] = {32, 640, 20, 3}, swb[3] = {3840, 64, 1280};
  const cuuint32_t bwa[4] = {64, 32, 1, 3}, bwb[4] = {32, 32, 2, 3};
  const cuuint64_t dwo[2] = {640, 640};
  const cuuint32_t bwo[2] = {64, 80}, bo64[2] = {64, 64}, bo16[2] = {16, 64};
  const cuuint64_t dsa[2] = {2048, 1280}, ssa[1] = {4096};
  const cuuint32_t bsa[2] = {64, 80};
  const cuuint64_t dout[2] = {1280, 2048}, sout[1] = {2560};
  Params prm;
  mkmap(enc, &prm.m[M_X], d_in[7], 2, dx, sx, bx, CU_TENSOR_MAP_SWIZZLE_128B);
  mkmap(enc, &prm.m[M_W128], d_in[8], 4, dwa, swa, bwa, CU_TENSOR_MAP_SWIZZLE_128B);
  mkmap(enc, &prm.m[M_W64], d_in[8], 4, dwb, swb, bwb, CU_TENSOR_MAP_SWIZZLE_64B);
  mkmap(enc, &prm.m[M_WR], d_in[8], 3, dw, sw, br, CU_TENSOR_MAP_SWIZZLE_32B);
  mkmap(enc, &prm.m[M_U], d_in[0], 2, dx, sx, bu, CU_TENSOR_MAP_SWIZZLE_NONE);
  mkmap(enc, &prm.m[M_WO], d_in[9], 2, dwo, sx, bwo, CU_TENSOR_MAP_SWIZZLE_128B);
  mkmap(enc, &prm.m[M_O64], d_out, 2, dout, sout, bo64, CU_TENSOR_MAP_SWIZZLE_128B);
  mkmap(enc, &prm.m[M_O16], d_out, 2, dout, sout, bo16, CU_TENSOR_MAP_SWIZZLE_NONE);
  mkmap(enc, &prm.m[M_SA], uy, 2, dsa, ssa, bsa, CU_TENSOR_MAP_SWIZZLE_128B);
  mkmap(enc, &prm.m[M_OUT], d_out, 2, dout, sout, bu, CU_TENSOR_MAP_SWIZZLE_NONE);
  prm.u = (const __nv_bfloat16*)d_in[0]; prm.wo = (const __nv_bfloat16*)d_in[9];
  for (int i = 0; i < 4; i++) prm.par[i] = (const __nv_bfloat16*)d_in[1 + i];
  prm.logdt = (const __nv_bfloat16*)d_in[5]; prm.dskip = (const __nv_bfloat16*)d_in[6];
  cudaFuncSetAttribute(fused_kernel, cudaFuncAttributeMaxDynamicSharedMemorySize, SMEM_BYTES);
  cudaLaunchConfig_t cfg = {};
  cfg.gridDim = dim3(128); cfg.blockDim = dim3(512); cfg.dynamicSmemBytes = SMEM_BYTES; cfg.stream = cudaStreamPerThread;
  cudaLaunchAttribute at[1];
  at[0].id = cudaLaunchAttributeClusterDimension; at[0].val.clusterDim.x = 2; at[0].val.clusterDim.y = 1; at[0].val.clusterDim.z = 1;
  cfg.attrs = at; cfg.numAttrs = 1;
  cudaLaunchKernelEx(&cfg, fused_kernel, prm);
}
```

```cpp
#include <cuda_runtime.h>
#include <cuda_bf16.h>
#include <cuda_fp16.h>
#include <cuda.h>
#include <stdint.h>

#define KST 2
#define EN_ATT 1
#define EN_SSM 1

__device__ __align__(1024) __nv_bfloat16 g_uy[2 * 640 * 2048];
__device__ __align__(128) uint4 g_kvp[8 * 16 * 240];
__device__ __align__(128) uint4 g_o[128 * 1280];
__device__ __align__(128) unsigned g_flag[4 * 128 * 32];
__device__ unsigned g_epoch[128];
#define TS(i) do {} while (0)
#define DUMP(lo, hi) do {} while (0)
#define FIXCNT

constexpr uint32_t SB0 = 1024;
constexpr uint32_t W_SLOT = 15360, OFF_X = 76800;
constexpr uint32_t OFF_WOR = 81920, OFF_KVP = 10240, OFF_KVS = 71680, OFF_PK = 10240, OFF_V = 30720, OFF_EXTRA = 102400, OFF_KVB = OFF_EXTRA;
constexpr uint32_t OFF_BAR = 125952, OFF_BLK = 128000, BLK = 20480;
constexpr uint32_t B_D = 4096, B_D5 = 3088, B_D7 = 6176, B_D9 = 8224, B_TBL = 14400;
constexpr int T_S = 576, T_F2 = 624, T_F3 = 816;
constexpr uint32_t OFF_UT = OFF_BLK + 4 * BLK;
constexpr uint32_t SMEM_BYTES = OFF_BLK + 5 * BLK;
enum { BR_FULL = 0, BR_WO = 5, BR_PUB = 7, BR_KVP = 8, BR_U = 9, BR_SUM = 10, BR_GEMM = 11, BR_UIN = 12, BR_YIN = 13, BR_EPOCH = 14,
       BR_FREE = 15, BR_RETRY = 17, BR_UOUT = 18, BR_OFULL = 18, BR_KS = 26, BR_EMPTY = 31, BR_OEMPTY = 36, BR_Y = 43, BR_OSTG = 45,
       BR_DRDY = 46, BR_U2 = 48, BR_COUNT = 50 };
constexpr uint32_t OFF_EPOCH = OFF_BAR + 8 * BR_COUNT;
enum { M_X, M_W128, M_W64, M_WR, M_U, M_WO, M_O64, M_O16, M_SA, M_OUT, M_COUNT };

__device__ __forceinline__ long long clk64() { long long t; asm volatile("mov.u64 %0, %%clock64;" : "=l"(t) :: "memory"); return t; }
__device__ __forceinline__ uint32_t smem_u32(const void* p) { return (uint32_t)__cvta_generic_to_shared(p); }
__host__ __device__ constexpr uint64_t mkdesc(uint32_t addr, uint32_t lbo, uint32_t sbo, uint32_t swz) {
  return (uint64_t)((addr & 0x3FFFF) >> 4) | ((uint64_t)(lbo >> 4) << 16) | ((uint64_t)(sbo >> 4) << 32) | ((uint64_t)swz << 62);
}
__device__ __forceinline__ uint64_t desc2(uint32_t lo, uint32_t hi) { uint64_t d; asm("mov.b64 %0, {%1, %2};" : "=l"(d) : "r"(lo), "r"(hi)); return d; }
__device__ __forceinline__ void mbar_init(uint32_t bar, uint32_t cnt) { asm volatile("mbarrier.init.shared::cta.b64 [%0], %1;" :: "r"(bar), "r"(cnt) : "memory"); }
__device__ __forceinline__ void mbar_expect_tx(uint32_t bar, uint32_t bytes) { asm volatile("mbarrier.arrive.expect_tx.shared::cta.b64 _, [%0], %1;" :: "r"(bar), "r"(bytes) : "memory"); }
__device__ __forceinline__ void mbar_arrive(uint32_t bar) { asm volatile("mbarrier.arrive.shared::cta.b64 _, [%0];" :: "r"(bar) : "memory"); }
__device__ __forceinline__ void mbar_wait(uint32_t bar, uint32_t parity) {
  asm volatile("{\n.reg .pred p;\n.reg .u32 c;\nmov.u32 c, 0;\n"
    "WL:\nmbarrier.try_wait.parity.shared::cta.b64 p, [%0], %1;\n@p bra WD;\n"
    "add.u32 c, c, 1;\nsetp.lt.u32 p, c, 200000;\n@p bra WL;\nWD:\n}" :: "r"(bar), "r"(parity) : "memory");
}
__device__ __forceinline__ void poll_all(const unsigned* p, unsigned val) {
  asm volatile("{\n.reg .pred p;\n.reg .u32 c, v;\nmov.u32 c, 0;\n"
    "PL:\nld.relaxed.gpu.global.u32 v, [%0];\nsetp.eq.u32 p, v, %1;\nvote.sync.all.pred p, p, 0xffffffff;\n@p bra PD;\n"
    "add.u32 c, c, 1;\nsetp.lt.u32 p, c, 100000;\n@p bra PL;\nPD:\n}" :: "l"(p), "r"(val) : "memory");
}
__device__ __forceinline__ void poll_all_acq(const unsigned* p, unsigned val) {
  asm volatile("{\n.reg .pred p;\n.reg .u32 c, v;\nmov.u32 c, 0;\n"
    "PL:\nld.acquire.gpu.global.u32 v, [%0];\nsetp.eq.u32 p, v, %1;\nvote.sync.all.pred p, p, 0xffffffff;\n@p bra PD;\n"
    "add.u32 c, c, 1;\nsetp.lt.u32 p, c, 100000;\n@p bra PL;\nPD:\n}" :: "l"(p), "r"(val) : "memory");
}
__device__ __forceinline__ unsigned poll_bit(const unsigned* p, unsigned val, unsigned mask) {
  unsigned bal;
  asm volatile("{\n.reg .pred p;\n.reg .u32 c, v;\nmov.u32 c, 0;\n"
    "PL:\nld.relaxed.gpu.global.u32 v, [%1];\nsetp.eq.u32 p, v, %2;\nvote.sync.ballot.b32 %0, p, 0xffffffff;\n"
    "and.b32 v, %0, %3;\nsetp.ne.u32 p, v, 0;\n@p bra PD;\n"
    "add.u32 c, c, 1;\nsetp.lt.u32 p, c, 100000;\n@p bra PL;\nPD:\n}" : "=&r"(bal) : "l"(p), "r"(val), "r"(mask) : "memory");
  return bal;
}
__device__ __forceinline__ void fix128_w0(uint32_t* v, const void* p, uint32_t tag, uint32_t mask) {
  asm volatile("{\n.reg .pred p;\n.reg .u32 c, x;\n.reg .b128 t;\n.reg .b64 lo, hi;\nmov.u32 c, 0;\n"
    "FL:\nxor.b32 x, %0, %5;\nand.b32 x, x, %6;\nsetp.eq.u32 p, x, 0;\n@p bra FD;\n"
    "ld.relaxed.gpu.global.b128 t, [%4];\nmov.b128 {lo, hi}, t;\nmov.b64 {%0, %1}, lo;\nmov.b64 {%2, %3}, hi;\n"
    "add.u32 c, c, 1;\nsetp.lt.u32 p, c, 100000;\n@p bra FL;\nFD:\n}"
    : "+r"(v[0]), "+r"(v[1]), "+r"(v[2]), "+r"(v[3]) : "l"(p), "r"(tag), "r"(mask) : "memory");
}
__device__ __forceinline__ void fix128_w3(uint32_t* v, const void* p, uint32_t tag, uint32_t mask) {
  asm volatile("{\n.reg .pred p;\n.reg .u32 c, x;\n.reg .b128 t;\n.reg .b64 lo, hi;\nmov.u32 c, 0;\n"
    "FL:\nxor.b32 x, %3, %5;\nand.b32 x, x, %6;\nsetp.eq.u32 p, x, 0;\n@p bra FD;\n"
    "ld.relaxed.gpu.global.b128 t, [%4];\nmov.b128 {lo, hi}, t;\nmov.b64 {%0, %1}, lo;\nmov.b64 {%2, %3}, hi;\n"
    "add.u32 c, c, 1;\nsetp.lt.u32 p, c, 100000;\n@p bra FL;\nFD:\n}"
    : "+r"(v[0]), "+r"(v[1]), "+r"(v[2]), "+r"(v[3]) : "l"(p), "r"(tag), "r"(mask) : "memory");
}
__device__ __forceinline__ void fence_acq() { asm volatile("fence.acq_rel.gpu;" ::: "memory"); }
__device__ __forceinline__ bool elect_one() {
  uint32_t p; asm volatile("{\n.reg .pred P;\nelect.sync _|P, 0xffffffff;\nselp.u32 %0, 1, 0, P;\n}" : "=r"(p)); return p;
}
__device__ __forceinline__ void bar_sync(int id, int n) { asm volatile("bar.sync %0, %1;" :: "r"(id), "r"(n) : "memory"); }
__device__ __forceinline__ void fence_async() { asm volatile("fence.proxy.async.shared::cta;" ::: "memory"); }
__device__ __forceinline__ void fence_async_g() { asm volatile("fence.proxy.async.global;" ::: "memory"); }
__device__ __forceinline__ void tma2d(uint32_t dst, const CUtensorMap* m, uint32_t bar, int c0, int c1) {
  asm volatile("cp.async.bulk.tensor.2d.shared::cluster.global.mbarrier::complete_tx::bytes [%0], [%1, {%3, %4}], [%2];"
    :: "r"(dst), "l"(m), "r"(bar), "r"(c0), "r"(c1) : "memory");
}
__device__ __forceinline__ void tma3d(uint32_t dst, const CUtensorMap* m, uint32_t bar, int c0, int c1, int c2) {
  asm volatile("cp.async.bulk.tensor.3d.shared::cluster.global.mbarrier::complete_tx::bytes [%0], [%1, {%3, %4, %5}], [%2];"
    :: "r"(dst), "l"(m), "r"(bar), "r"(c0), "r"(c1), "r"(c2) : "memory");
}
__device__ __forceinline__ void tma4d(uint32_t dst, const CUtensorMap* m, uint32_t bar, int c0, int c1, int c2, int c3) {
  asm volatile("cp.async.bulk.tensor.4d.shared::cluster.global.mbarrier::complete_tx::bytes [%0], [%1, {%3, %4, %5, %6}], [%2];"
    :: "r"(dst), "l"(m), "r"(bar), "r"(c0), "r"(c1), "r"(c2), "r"(c3) : "memory");
}
__device__ __forceinline__ void tma2d_st(const CUtensorMap* m, uint32_t src, int c0, int c1) {
  asm volatile("cp.async.bulk.tensor.2d.global.shared::cta.bulk_group [%0, {%2, %3}], [%1];"
    :: "l"(m), "r"(src), "r"(c0), "r"(c1) : "memory");
}
__device__ __forceinline__ void bulk_ld(uint32_t dst, const void* src, uint32_t bytes, uint32_t bar) {
  asm volatile("cp.async.bulk.shared::cluster.global.mbarrier::complete_tx::bytes [%0], [%1], %2, [%3];"
    :: "r"(dst), "l"(src), "r"(bytes), "r"(bar) : "memory");
}
__device__ __forceinline__ void bulk_st(void* dst, uint32_t src, uint32_t bytes) {
  asm volatile("cp.async.bulk.global.shared::cta.bulk_group [%0], [%1], %2;" :: "l"(dst), "r"(src), "r"(bytes) : "memory");
}
__device__ __forceinline__ void bulk_commit() { asm volatile("cp.async.bulk.commit_group;" ::: "memory"); }
__device__ __forceinline__ void bulk_wait0() { asm volatile("cp.async.bulk.wait_group 0;" ::: "memory"); }
__device__ __forceinline__ void bulk_wait0_read() { asm volatile("cp.async.bulk.wait_group.read 0;" ::: "memory"); }
__device__ __forceinline__ unsigned ld_rlx(const unsigned* p) { unsigned v; asm volatile("ld.relaxed.gpu.global.u32 %0, [%1];" : "=r"(v) : "l"(p) : "memory"); return v; }
__device__ __forceinline__ unsigned ld_acq(const unsigned* p) { unsigned v; asm volatile("ld.acquire.gpu.global.u32 %0, [%1];" : "=r"(v) : "l"(p) : "memory"); return v; }
__device__ __forceinline__ void st_rlx(unsigned* p, unsigned v) { asm volatile("st.relaxed.gpu.global.u32 [%0], %1;" :: "l"(p), "r"(v) : "memory"); }
__device__ __forceinline__ void st_rel(unsigned* p, unsigned v) { asm volatile("st.release.gpu.global.u32 [%0], %1;" :: "l"(p), "r"(v) : "memory"); }
__device__ __forceinline__ void ld128_rlx(uint32_t* v, const void* p) {
  asm volatile("{\n.reg .b128 t;\n.reg .b64 lo, hi;\nld.relaxed.gpu.global.b128 t, [%4];\nmov.b128 {lo, hi}, t;\n"
    "mov.b64 {%0, %1}, lo;\nmov.b64 {%2, %3}, hi;\n}" : "=r"(v[0]), "=r"(v[1]), "=r"(v[2]), "=r"(v[3]) : "l"(p) : "memory");
}
__device__ __forceinline__ void st128_rlx(void* p, const uint32_t* v) {
  asm volatile("{\n.reg .b128 t;\n.reg .b64 lo, hi;\nmov.b64 lo, {%1, %2};\nmov.b64 hi, {%3, %4};\nmov.b128 t, {lo, hi};\n"
    "st.relaxed.gpu.global.b128 [%0], t;\n}" :: "l"(p), "r"(v[0]), "r"(v[1]), "r"(v[2]), "r"(v[3]) : "memory");
}
__device__ __forceinline__ uint32_t lds32(uint32_t a) { uint32_t v; asm volatile("ld.shared.u32 %0, [%1];" : "=r"(v) : "r"(a) : "memory"); return v; }
__device__ __forceinline__ uint32_t lds32v(uint32_t a) { uint32_t v; asm volatile("ld.volatile.shared.u32 %0, [%1];" : "=r"(v) : "r"(a) : "memory"); return v; }
__device__ __forceinline__ uint32_t cpa(uint32_t a, uint32_t one) { uint32_t v; asm volatile("mul.lo.u32 %0, %1, %2;" : "=r"(v) : "r"(a), "r"(one)); return v; }
__device__ __forceinline__ uint32_t cpb(uint32_t a, uint32_t zero) { uint32_t v; asm volatile("or.b32 %0, %1, %2;" : "=r"(v) : "r"(a), "r"(zero)); return v; }
__device__ __forceinline__ uint32_t lds16(uint32_t a) { uint16_t v; asm volatile("ld.shared.u16 %0, [%1];" : "=h"(v) : "r"(a) : "memory"); return v; }
__device__ __forceinline__ float ldsf(uint32_t a) { float v; asm volatile("ld.shared.f32 %0, [%1];" : "=f"(v) : "r"(a) : "memory"); return v; }
__device__ __forceinline__ void lds128(uint32_t* v, uint32_t a) { asm volatile("ld.shared.v4.u32 {%0,%1,%2,%3}, [%4];" : "=r"(v[0]), "=r"(v[1]), "=r"(v[2]), "=r"(v[3]) : "r"(a) : "memory"); }
__device__ __forceinline__ void sts32(uint32_t a, uint32_t v) { asm volatile("st.shared.u32 [%0], %1;" :: "r"(a), "r"(v) : "memory"); }
__device__ __forceinline__ void sts16(uint32_t a, uint32_t v) { asm volatile("st.shared.u16 [%0], %1;" :: "r"(a), "h"((uint16_t)v) : "memory"); }
__device__ __forceinline__ void sts64f(uint32_t a, float x, float y) { asm volatile("st.shared.v2.f32 [%0], {%1,%2};" :: "r"(a), "f"(x), "f"(y) : "memory"); }
__device__ __forceinline__ void sts128(uint32_t a, uint32_t x, uint32_t y, uint32_t z, uint32_t w) { asm volatile("st.shared.v4.u32 [%0], {%1,%2,%3,%4};" :: "r"(a), "r"(x), "r"(y), "r"(z), "r"(w) : "memory"); }
__device__ __forceinline__ void stsm4(uint32_t a, uint32_t r0, uint32_t r1, uint32_t r2, uint32_t r3) {
  asm volatile("stmatrix.sync.aligned.m8n8.x4.shared.b16 [%0], {%1,%2,%3,%4};" :: "r"(a), "r"(r0), "r"(r1), "r"(r2), "r"(r3) : "memory");
}
__device__ __forceinline__ void stsm4t(uint32_t a, uint32_t r0, uint32_t r1, uint32_t r2, uint32_t r3) {
  asm volatile("stmatrix.sync.aligned.m8n8.x4.trans.shared.b16 [%0], {%1,%2,%3,%4};" :: "r"(a), "r"(r0), "r"(r1), "r"(r2), "r"(r3) : "memory");
}
__device__ __forceinline__ void ldsm4t(uint32_t* r, uint32_t a) {
  asm volatile("ldmatrix.sync.aligned.m8n8.x4.trans.shared.b16 {%0,%1,%2,%3}, [%4];" : "=r"(r[0]), "=r"(r[1]), "=r"(r[2]), "=r"(r[3]) : "r"(a) : "memory");
}
__device__ __forceinline__ void ldsm4(uint32_t* r, uint32_t a) {
  asm volatile("ldmatrix.sync.aligned.m8n8.x4.shared.b16 {%0,%1,%2,%3}, [%4];" : "=r"(r[0]), "=r"(r[1]), "=r"(r[2]), "=r"(r[3]) : "r"(a) : "memory");
}
__device__ __forceinline__ void mma16816(float* d, const uint32_t* a, const uint32_t* b) {
  asm volatile("mma.sync.aligned.m16n8k16.row.col.f32.bf16.bf16.f32 {%0,%1,%2,%3}, {%4,%5,%6,%7}, {%8,%9}, {%0,%1,%2,%3};"
    : "+f"(d[0]), "+f"(d[1]), "+f"(d[2]), "+f"(d[3]) : "r"(a[0]), "r"(a[1]), "r"(a[2]), "r"(a[3]), "r"(b[0]), "r"(b[1]));
}
__device__ __forceinline__ uint32_t pack2(float lo, float hi) { uint32_t r; asm("cvt.rn.bf16x2.f32 %0, %1, %2;" : "=r"(r) : "f"(hi), "f"(lo)); return r; }
__device__ __forceinline__ uint32_t packh(float lo, float hi) { uint32_t r; asm("cvt.rn.f16x2.f32 %0, %1, %2;" : "=r"(r) : "f"(hi), "f"(lo)); return r; }
__device__ __forceinline__ uint32_t hcmul(uint32_t x, uint32_t zp, uint32_t zq) {
  const __half2 xx = *reinterpret_cast<__half2*>(&x);
  const __half2 r = __hfma2(__high2half2(xx), *reinterpret_cast<__half2*>(&zq), __hmul2(__low2half2(xx), *reinterpret_cast<__half2*>(&zp)));
  return *reinterpret_cast<const uint32_t*>(&r);
}
__device__ __forceinline__ void hcm2(uint32_t xr, uint32_t xi, uint32_t z, uint32_t& pr, uint32_t& pi) {
  const __half2 a = *reinterpret_cast<__half2*>(&xr), b = *reinterpret_cast<__half2*>(&xi), zz = *reinterpret_cast<__half2*>(&z);
  const __half2 re = __hfma2(__hneg2(b), __high2half2(zz), __hmul2(a, __low2half2(zz)));
  const __half2 im = __hfma2(a, __high2half2(zz), __hmul2(b, __low2half2(zz)));
  pr = *reinterpret_cast<const uint32_t*>(&re); pi = *reinterpret_cast<const uint32_t*>(&im);
}
__device__ __forceinline__ void sts64(uint32_t a, uint32_t x, uint32_t y) { asm volatile("st.shared.v2.u32 [%0], {%1,%2};" :: "r"(a), "r"(x), "r"(y) : "memory"); }
__device__ __forceinline__ void lds64(uint32_t* v, uint32_t a) { asm volatile("ld.shared.v2.u32 {%0,%1}, [%2];" : "=r"(v[0]), "=r"(v[1]) : "r"(a) : "memory"); }
__device__ __forceinline__ float bf_lo(uint32_t v) { return __uint_as_float(v << 16); }
__device__ __forceinline__ float bf_hi(uint32_t v) { return __uint_as_float(v & 0xffff0000u); }
__device__ __forceinline__ float bf_round(float x) { return bf_lo(pack2(x, 0.f)); }
__device__ __forceinline__ float ex2(float x) { float r; asm("ex2.approx.ftz.f32 %0, %1;" : "=f"(r) : "f"(x)); return r; }
__device__ __forceinline__ float phi(float t, float l2e = 1.44269504089f) {
  float e = ex2(t * l2e) + 1e-6f;
  asm("{\n.reg .pred p;\nsetp.gt.f32 p, %1, 0f00000000;\n@p add.f32 %0, %1, 0f3F800008;\n}" : "+f"(e) : "f"(t));
  return e;
}
__device__ __forceinline__ void wg_fence() { asm volatile("wgmma.fence.sync.aligned;" ::: "memory"); }
__device__ __forceinline__ void wg_commit() { asm volatile("wgmma.commit_group.sync.aligned;" ::: "memory"); }
template <int N> __device__ __forceinline__ void wg_wait() { asm volatile("wgmma.wait_group.sync.aligned %0;" :: "n"(N) : "memory"); }
template <int N> __device__ __forceinline__ void pin(float* a) {
  #pragma unroll
  for (int i = 0; i < N; i++) asm volatile("" : "+f"(a[i]) :: "memory");
}
__device__ __forceinline__ int rtid() { int t; asm volatile("mov.u32 %0, %%tid.x;" : "=r"(t)); return t; }
__device__ __forceinline__ int opaque(int v) { asm volatile("" : "+r"(v)); return v; }
template <int N> __device__ __forceinline__ void zero(float* a) {
  #pragma unroll
  for (int i = 0; i < N; i++) asm volatile("mov.b32 %0, 0;" : "=f"(a[i]));
}
template <int N> __device__ __forceinline__ void pinu(uint32_t* a) {
  #pragma unroll
  for (int i = 0; i < N; i++) asm volatile("" : "+r"(a[i]) :: "memory");
}
__device__ __forceinline__ void cexp_t(float lg2mag, float turns, float& re, float& im) {
  float m = ex2(lg2mag);
  float fr = (turns - __fadd_rn(__fadd_rn(turns, 12582912.f), -12582912.f)) * 6.283185307f;
  re = m * __cosf(fr); im = m * __sinf(fr);
}
__device__ __forceinline__ void cmul(float ar, float ai, float br, float bi, float& cr, float& ci) {
  cr = fmaf(ar, br, -ai * bi); ci = fmaf(ar, bi, ai * br);
}

__device__ __forceinline__ void wg_ss192_tb(float* d, uint64_t da, uint64_t db, int scale_d) {
  asm volatile("{\n.reg .pred p;\nsetp.ne.b32 p, %98, 0;\n"
    "wgmma.mma_async.sync.aligned.m64n192k16.f32.bf16.bf16 "
    "{%0, %1, %2, %3, %4, %5, %6, %7, %8, %9, %10, %11, %12, %13, %14, %15, %16, %17, %18, %19, %20, %21, %22, %23, %24, %25, %26, %27, %28, %29, %30, %31, %32, %33, %34, %35, %36, %37, %38, %39, %40, %41, %42, %43, %44, %45, %46, %47, %48, %49, %50, %51, %52, %53, %54, %55, %56, %57, %58, %59, %60, %61, %62, %63, %64, %65, %66, %67, %68, %69, %70, %71, %72, %73, %74, %75, %76, %77, %78, %79, %80, %81, %82, %83, %84, %85, %86, %87, %88, %89, %90, %91, %92, %93, %94, %95}, %96, %97, p, 1, 1, 0, 1;\n}\n"
    : "+f"(d[0]), "+f"(d[1]), "+f"(d[2]), "+f"(d[3]), "+f"(d[4]), "+f"(d[5]), "+f"(d[6]), "+f"(d[7]), "+f"(d[8]), "+f"(d[9]), "+f"(d[10]), "+f"(d[11]), "+f"(d[12]), "+f"(d[13]), "+f"(d[14]), "+f"(d[15]), "+f"(d[16]), "+f"(d[17]), "+f"(d[18]), "+f"(d[19]), "+f"(d[20]), "+f"(d[21]), "+f"(d[22]), "+f"(d[23]), "+f"(d[24]), "+f"(d[25]), "+f"(d[26]), "+f"(d[27]), "+f"(d[28]), "+f"(d[29]), "+f"(d[30]), "+f"(d[31]), "+f"(d[32]), "+f"(d[33]), "+f"(d[34]), "+f"(d[35]), "+f"(d[36]), "+f"(d[37]), "+f"(d[38]), "+f"(d[39]), "+f"(d[40]), "+f"(d[41]), "+f"(d[42]), "+f"(d[43]), "+f"(d[44]), "+f"(d[45]), "+f"(d[46]), "+f"(d[47]), "+f"(d[48]), "+f"(d[49]), "+f"(d[50]), "+f"(d[51]), "+f"(d[52]), "+f"(d[53]), "+f"(d[54]), "+f"(d[55]), "+f"(d[56]), "+f"(d[57]), "+f"(d[58]), "+f"(d[59]), "+f"(d[60]), "+f"(d[61]), "+f"(d[62]), "+f"(d[63]), "+f"(d[64]), "+f"(d[65]), "+f"(d[66]), "+f"(d[67]), "+f"(d[68]), "+f"(d[69]), "+f"(d[70]), "+f"(d[71]), "+f"(d[72]), "+f"(d[73]), "+f"(d[74]), "+f"(d[75]), "+f"(d[76]), "+f"(d[77]), "+f"(d[78]), "+f"(d[79]), "+f"(d[80]), "+f"(d[81]), "+f"(d[82]), "+f"(d[83]), "+f"(d[84]), "+f"(d[85]), "+f"(d[86]), "+f"(d[87]), "+f"(d[88]), "+f"(d[89]), "+f"(d[90]), "+f"(d[91]), "+f"(d[92]), "+f"(d[93]), "+f"(d[94]), "+f"(d[95])
    : "l"(da), "l"(db), "r"(scale_d));
}
__device__ __forceinline__ void wg_ss48_tb(float* d, uint64_t da, uint64_t db, int scale_d) {
  asm volatile("{\n.reg .pred p;\nsetp.ne.b32 p, %26, 0;\n"
    "wgmma.mma_async.sync.aligned.m64n48k16.f32.bf16.bf16 "
    "{%0, %1, %2, %3, %4, %5, %6, %7, %8, %9, %10, %11, %12, %13, %14, %15, %16, %17, %18, %19, %20, %21, %22, %23}, %24, %25, p, 1, 1, 0, 1;\n}\n"
    : "+f"(d[0]), "+f"(d[1]), "+f"(d[2]), "+f"(d[3]), "+f"(d[4]), "+f"(d[5]), "+f"(d[6]), "+f"(d[7]), "+f"(d[8]), "+f"(d[9]), "+f"(d[10]), "+f"(d[11]), "+f"(d[12]), "+f"(d[13]), "+f"(d[14]), "+f"(d[15]), "+f"(d[16]), "+f"(d[17]), "+f"(d[18]), "+f"(d[19]), "+f"(d[20]), "+f"(d[21]), "+f"(d[22]), "+f"(d[23])
    : "l"(da), "l"(db), "r"(scale_d));
}
__device__ __forceinline__ void wg_ss48_tt(float* d, uint64_t da, uint64_t db, int scale_d) {
  asm volatile("{\n.reg .pred p;\nsetp.ne.b32 p, %26, 0;\n"
    "wgmma.mma_async.sync.aligned.m64n48k16.f32.bf16.bf16 "
    "{%0, %1, %2, %3, %4, %5, %6, %7, %8, %9, %10, %11, %12, %13, %14, %15, %16, %17, %18, %19, %20, %21, %22, %23}, %24, %25, p, 1, 1, 1, 1;\n}\n"
    : "+f"(d[0]), "+f"(d[1]), "+f"(d[2]), "+f"(d[3]), "+f"(d[4]), "+f"(d[5]), "+f"(d[6]), "+f"(d[7]), "+f"(d[8]), "+f"(d[9]), "+f"(d[10]), "+f"(d[11]), "+f"(d[12]), "+f"(d[13]), "+f"(d[14]), "+f"(d[15]), "+f"(d[16]), "+f"(d[17]), "+f"(d[18]), "+f"(d[19]), "+f"(d[20]), "+f"(d[21]), "+f"(d[22]), "+f"(d[23])
    : "l"(da), "l"(db), "r"(scale_d));
}
__device__ __forceinline__ void wg_rs88_tb(float* d, const uint32_t* a, uint64_t db, int scale_d) {
  asm volatile("{\n.reg .pred p;\nsetp.ne.b32 p, %49, 0;\n"
    "wgmma.mma_async.sync.aligned.m64n88k16.f32.bf16.bf16 "
    "{%0, %1, %2, %3, %4, %5, %6, %7, %8, %9, %10, %11, %12, %13, %14, %15, %16, %17, %18, %19, %20, %21, %22, %23, %24, %25, %26, %27, %28, %29, %30, %31, %32, %33, %34, %35, %36, %37, %38, %39, %40, %41, %42, %43}, {%44, %45, %46, %47}, %48, p, 1, 1, 1;\n}\n"
    : "+f"(d[0]), "+f"(d[1]), "+f"(d[2]), "+f"(d[3]), "+f"(d[4]), "+f"(d[5]), "+f"(d[6]), "+f"(d[7]), "+f"(d[8]), "+f"(d[9]), "+f"(d[10]), "+f"(d[11]), "+f"(d[12]), "+f"(d[13]), "+f"(d[14]), "+f"(d[15]), "+f"(d[16]), "+f"(d[17]), "+f"(d[18]), "+f"(d[19]), "+f"(d[20]), "+f"(d[21]), "+f"(d[22]), "+f"(d[23]), "+f"(d[24]), "+f"(d[25]), "+f"(d[26]), "+f"(d[27]), "+f"(d[28]), "+f"(d[29]), "+f"(d[30]), "+f"(d[31]), "+f"(d[32]), "+f"(d[33]), "+f"(d[34]), "+f"(d[35]), "+f"(d[36]), "+f"(d[37]), "+f"(d[38]), "+f"(d[39]), "+f"(d[40]), "+f"(d[41]), "+f"(d[42]), "+f"(d[43])
    : "r"(a[0]), "r"(a[1]), "r"(a[2]), "r"(a[3]), "l"(db), "r"(scale_d));
}
__device__ __forceinline__ void wg_ss80_tb(float* d, uint64_t da, uint64_t db, int scale_d) {
  asm volatile("{\n.reg .pred p;\nsetp.ne.b32 p, %42, 0;\n"
    "wgmma.mma_async.sync.aligned.m64n80k16.f32.bf16.bf16 "
    "{%0, %1, %2, %3, %4, %5, %6, %7, %8, %9, %10, %11, %12, %13, %14, %15, %16, %17, %18, %19, %20, %21, %22, %23, %24, %25, %26, %27, %28, %29, %30, %31, %32, %33, %34, %35, %36, %37, %38, %39}, %40, %41, p, 1, 1, 0, 1;\n}\n"
    : "+f"(d[0]), "+f"(d[1]), "+f"(d[2]), "+f"(d[3]), "+f"(d[4]), "+f"(d[5]), "+f"(d[6]), "+f"(d[7]), "+f"(d[8]), "+f"(d[9]), "+f"(d[10]), "+f"(d[11]), "+f"(d[12]), "+f"(d[13]), "+f"(d[14]), "+f"(d[15]), "+f"(d[16]), "+f"(d[17]), "+f"(d[18]), "+f"(d[19]), "+f"(d[20]), "+f"(d[21]), "+f"(d[22]), "+f"(d[23]), "+f"(d[24]), "+f"(d[25]), "+f"(d[26]), "+f"(d[27]), "+f"(d[28]), "+f"(d[29]), "+f"(d[30]), "+f"(d[31]), "+f"(d[32]), "+f"(d[33]), "+f"(d[34]), "+f"(d[35]), "+f"(d[36]), "+f"(d[37]), "+f"(d[38]), "+f"(d[39])
    : "l"(da), "l"(db), "r"(scale_d));
}
__device__ __forceinline__ void wg_ss48_tt_h(float* d, uint64_t da, uint64_t db, int scale_d) {
  asm volatile("{\n.reg .pred p;\nsetp.ne.b32 p, %26, 0;\n"
    "wgmma.mma_async.sync.aligned.m64n48k16.f32.f16.f16 "
    "{%0, %1, %2, %3, %4, %5, %6, %7, %8, %9, %10, %11, %12, %13, %14, %15, %16, %17, %18, %19, %20, %21, %22, %23}, %24, %25, p, 1, 1, 1, 1;\n}\n"
    : "+f"(d[0]), "+f"(d[1]), "+f"(d[2]), "+f"(d[3]), "+f"(d[4]), "+f"(d[5]), "+f"(d[6]), "+f"(d[7]), "+f"(d[8]), "+f"(d[9]), "+f"(d[10]), "+f"(d[11]), "+f"(d[12]), "+f"(d[13]), "+f"(d[14]), "+f"(d[15]), "+f"(d[16]), "+f"(d[17]), "+f"(d[18]), "+f"(d[19]), "+f"(d[20]), "+f"(d[21]), "+f"(d[22]), "+f"(d[23])
    : "l"(da), "l"(db), "r"(scale_d));
}

struct Params {
  const __nv_bfloat16 *par[4], *logdt, *dskip, *u, *wo;
  CUtensorMap m[M_COUNT];
};

#define CHUNK(i) ((i) == 0 ? c : ((i) == 7 ? (c ^ 1) : (((c & 6) + 1 + (i)) & 7)))
#define FLAG(kind, rr, cc) (&g_flag[((kind) * 128 + (rr) * 8 + (cc)) * 32])
#define SLOT(i) ((i) == 0 || (i) == 2 ? OFF_EXTRA : OFF_BLK - 256 + ((i) == 1 || (i) == 7 ? 0 : (i) - 2) * BLK)
__device__ __forceinline__ void load_quad(uint32_t* A, uint32_t addr) {
  A[0] = lds32v(addr); A[1] = lds32v(addr + 32); A[2] = lds32v(addr - 32); A[3] = lds32v(addr);
}

__device__ __forceinline__ void y_transpose(uint32_t sb, int w5, int lane) {
  const int mi = lane >> 3, rw = lane & 7;
  const uint32_t sa = sb + OFF_EXTRA + (w5 * 16 + rw) * 128 + ((mi ^ rw) << 4), da = sb + SLOT(3) + (8 * mi + rw) * 160 + w5 * 32;
  bar_sync(7, 160);
  uint32_t v[8][4];
  #pragma unroll
  for (int q = 0; q < 8; q++) ldsm4t(v[q], (sa ^ ((q & 1) * 64 + ((q >> 1) & 1) * 16)) + ((q >> 1) & 1) * 10240 + (q >> 2) * 1024);
  #pragma unroll
  for (int q = 0; q < 8; q++) stsm4(da + (q & 3) * 5120 + (q >> 2) * 16, v[q][0], v[q][1], v[q][2], v[q][3]);
  fence_async();
  bar_sync(7, 160);
}

__global__ void __launch_bounds__(512, 1) fused_kernel(const __grid_constant__ Params prm) {
  extern __shared__ unsigned char smem_raw[];
  const uint32_t sb = __shfl_sync(0xffffffff, smem_u32(smem_raw), 0);
  const int tid = threadIdx.x, lane = tid & 31;
  const int warp = __shfl_sync(0xffffffff, tid >> 5, 0), wg = warp >> 2, w4 = warp & 3;
  const int cta = blockIdx.x, r = cta >> 3, c = cta & 7;
  if ((sb & 0xffffffu) != SB0) return;
#define BAR(i) (sb + OFF_BAR + 8 * (i))
  const bool sw64 = ((c + 1) & 2) != 0;

  if (wg == 3) {
    if (warp == 13 && elect_one()) {
      #pragma unroll
      for (int i = M_W128; i <= M_U; i++) asm volatile("prefetch.tensormap [%0];" :: "l"(&prm.m[i]) : "memory");
    }
    asm volatile("setmaxnreg.dec.sync.aligned.u32 56;");
    const int tid = rtid(), lane = tid & 31;
    if (warp == 12) {
      if (elect_one()) {
        #pragma unroll
        for (int i = 0; i < 5; i++) mbar_init(BAR(BR_FULL + i), 1);
        asm volatile("fence.mbarrier_init.release.cluster;" ::: "memory");
      }
      {
        const CUtensorMap* mwp = &prm.m[sw64 ? M_W64 : M_W128];
        const int mcol = (c * 80 + (c & 1) * 16) >> (sw64 ? 5 : 6), rcol = c * 80 + ((c & 1) ? 0 : 64);
        uint32_t s = 0, ph = 1, xs = 0;
        #pragma unroll 1
        for (int kb = 0; kb < 20; kb++) {
          if (kb == 1) asm volatile("bar.arrive 0, 512;" ::: "memory");
          if (kb == 4) { bar_sync(6, 128); if (EN_SSM) mbar_wait(BAR(BR_KS), 0); }
          if (kb >= 5) mbar_wait(BAR(BR_EMPTY) + 8 * s, ph);
          if (EN_ATT && elect_one()) {
            const uint32_t st = sb + s * W_SLOT, fb = BAR(BR_FULL) + 8 * s;
            mbar_expect_tx(fb, (kb & 1) ? W_SLOT : W_SLOT + 16384);
            if (!(kb & 1)) tma2d(sb + OFF_X + xs, &prm.m[M_X], fb, kb * 32, r * 128);
            tma4d(st, mwp, fb, 0, kb * 32, mcol, 0);
            tma3d(st + 12288, &prm.m[M_WR], fb, rcol, kb * 32, 0);
          }
          if (kb < 4 && lane == 0) TS(24 + kb);
          if (kb == 14 && elect_one()) asm volatile("cp.async.bulk.prefetch.L2.global [%0], 6400;" :: "l"(prm.wo + cta * 3200) : "memory");
          if (!EN_ATT && kb == 4) break;
          if (++s == 5) { s = 0; ph ^= 1; }
          if (kb & 1) { xs += 16384; if (xs == 49152) xs = 0; }
        }
      }
      if (EN_ATT) {
      mbar_wait(BAR(BR_EPOCH), 0);
      const unsigned epoch = lds32(sb + OFF_EPOCH);
      const unsigned* fo = FLAG(3, r, lane & 7);
      unsigned seen = __ballot_sync(0xffffffff, ld_rlx(lane < 16 ? fo : FLAG(0, lane & 15, c)) == epoch) & 0xffu;
      mbar_wait(BAR(BR_GEMM), 0);
      if (elect_one()) {
        mbar_expect_tx(BAR(BR_WO), 10240);
        tma2d(sb, &prm.m[M_WO], BAR(BR_WO), c * 64, c * 80);
        mbar_expect_tx(BAR(BR_KVP), 61440);
        mbar_expect_tx(BAR(BR_WO + 1), 7 * 10240);
      }
      {
        uint32_t ds = sb + OFF_WOR + (lane >> 3) * 128 + (((lane & 7) ^ (lane >> 3)) << 4);
        #pragma unroll 1
        for (int h = 0; h < 2; h++) {
          const int i = (lane & 6) + h;
          const char* gs = reinterpret_cast<const char*>(prm.wo) + (size_t)((lane >> 3) + CHUNK(i) * 80) * 1280 + 1024 + c * 32 + (lane & 1) * 16;
          #pragma unroll 2
          for (int q = 0; q < 20; q++) {
            asm volatile("cp.async.cg.shared.global [%0], [%1], 16;" :: "r"(ds), "l"(gs) : "memory");
            ds = (ds + 512) ^ 64; gs += 5120;
          }
        }
      }
      mbar_wait(BAR(BR_PUB), 0);
      poll_all(FLAG(0, lane & 15, c), epoch);
      if (elect_one()) { TS(23); bulk_ld(sb + OFF_KVP, &g_kvp[c * 16 * 240], 61440, BAR(BR_KVP)); }
      asm volatile("cp.async.wait_all;" ::: "memory");
      fence_async();
      mbar_arrive(BAR(BR_WO));
      mbar_wait(BAR(BR_SUM), 0);
      if (elect_one()) {
        #pragma unroll 1
        for (int i = 1; i < 8; i++) tma2d(sb + i * 10240, &prm.m[M_WO], BAR(BR_WO + 1), c * 64, CHUNK(i) * 80);
      }
      mbar_wait(BAR(BR_OSTG), 0);
      if (elect_one()) {
        bulk_st(&g_o[cta * 1280], sb + OFF_EXTRA, 20480);
        bulk_commit();
        bulk_wait0();
        st_rlx(FLAG(3, r, c), epoch);
        TS(20);
      }
      __syncwarp();
      #pragma unroll 1
      for (int i = 1; i < 8; i++) {
        const int src = CHUNK(i);
        if (!((seen >> src) & 1)) seen = poll_bit(fo, epoch, 1u << src);
        if (i == 2 || i == 7) mbar_wait(BAR(BR_OEMPTY) + 8 * (i & 1), 0);
        if (EN_SSM && (i == 1 || i == 3)) mbar_wait(BAR(BR_FREE) + 4 * (i - 1), 0);
        if (elect_one()) {
          mbar_expect_tx(BAR(BR_OFULL) + 8 * i, 20480);
          bulk_ld(sb + SLOT(i), &g_o[(r * 8 + src) * 1280], 20480, BAR(BR_OFULL) + 8 * i);
          if (i == 1) TS(21);
          if (i == 7) TS(22);
        }
        __syncwarp();
      }
      if (lane == 0) { DUMP(20, 30); }
      }
    } else {
      const int hw = warp - 13, ht = tid - 416;
      if (hw == 2 && elect_one()) {
        #pragma unroll
        for (int i = 5; i < BR_COUNT; i++) mbar_init(BAR(i), i == BR_WO ? 33 : i < BR_EMPTY ? 1 : i < BR_OEMPTY ? 2 : i < BR_Y ? 8 : i < BR_OSTG ? 4 : i == BR_OSTG ? 8 : i < BR_U2 ? 3 : 1);
        asm volatile("fence.mbarrier_init.release.cluster;" ::: "memory");
        if (EN_SSM) { mbar_expect_tx(BAR(BR_UIN), 20480); tma2d(sb + OFF_UT, &prm.m[M_U], BAR(BR_UIN), c * 80, r * 128); }
      }
      __syncwarp();
      asm volatile("bar.arrive 0, 512;" ::: "memory");
      const unsigned epoch = hw == 0 ? ld_rlx(&g_epoch[cta]) + 1 : 0;
      bar_sync(5, 96);
      asm volatile("bar.arrive 6, 128;" ::: "memory");
      if (hw == 1 && elect_one()) {
        #pragma unroll
        for (int i = M_WO; i < M_COUNT; i++) asm volatile("prefetch.tensormap [%0];" :: "l"(&prm.m[i]) : "memory");
      }
      if (ht == 0) {
        st_rlx(&g_epoch[cta], epoch);
        sts32(sb + OFF_EPOCH, epoch);
        mbar_arrive(BAR(BR_EPOCH));
      }
      if (EN_SSM) {
      const int mi = lane >> 3, rw = lane & 7, ch0 = c * 80 + r * 5;
      mbar_wait(BAR(BR_UIN), 0);
      if (ht == 0) TS(36);
      #pragma unroll 1
      for (int h = 0; h < 2; h++) {
        const uint32_t sa = sb + OFF_UT + h * 10240 + (8 * mi + rw) * 160 + hw * 16, da = sb + OFF_UT + h * 10240 + (hw * 8 + rw) * 128 + ((mi ^ rw ^ h) << 4);
        uint32_t v[8][4];
        #pragma unroll
        for (int q = 0; q < 8; q++) if (q < 6 || hw == 0) ldsm4t(v[q], sa + (q & 1) * 5120 + (q >> 1) * 48);
        bar_sync(5, 96);
        #pragma unroll
        for (int q = 0; q < 8; q++) if (q < 6 || hw == 0) stsm4((da ^ ((q & 1) * 64)) + (q >> 1) * 3072, v[q][0], v[q][1], v[q][2], v[q][3]);
      }
      fence_async();
      bar_sync(5, 96);
      if (hw == 0) {
        if (elect_one()) {
          tma2d_st(&prm.m[M_SA], sb + OFF_UT, r * 128, c * 80);
          tma2d_st(&prm.m[M_SA], sb + OFF_UT + 10240, r * 128 + 64, c * 80);
          bulk_commit(); bulk_wait0_read();
          mbar_arrive(BAR(BR_UOUT));
          TS(37);
          bulk_wait0();
          st_rel(FLAG(1, r, c), epoch);
          TS(30);
        }
        __syncwarp();
        poll_all_acq(FLAG(1, lane & 15, c), epoch);
      }
      #pragma unroll 1
      for (int q6 = hw; q6 < 30; q6 += 3) {
        if (q6 >= 6 && q6 < 9) { __syncwarp(); if (lane == 0) mbar_arrive(BAR(BR_DRDY)); }
        if (q6 < 3 || (q6 >= 18 && q6 < 21)) {
          const int p = q6 >= 18;
          if (hw == 0) {
            mbar_wait(BAR(BR_KS + 2) + 16 * p, 0);
            if (elect_one()) {
              fence_async_g();
              mbar_expect_tx(BAR(p ? BR_U2 : BR_U), p ? 8192 : 12288);
              #pragma unroll 1
              for (int q = 3 * p; q < 3 + 2 * p; q++) bulk_ld(sb + OFF_BLK + q * BLK, g_uy + (ch0 + q) * 2048, 4096, BAR(p ? BR_U2 : BR_U));
              TS(31);
            }
            __syncwarp();
            mbar_wait(BAR(p ? BR_U2 : BR_U), 0);
          }
          bar_sync(5, 96);
          if (ht == 0) TS(38 + p);
        }
        {
          const int k = q6 / 6, kap = (q6 - 6 * k) * 32 + lane;
          const uint32_t blk = sb + OFF_BLK + k * BLK;
          float P[33];
          P[0] = 0.f;
          #pragma unroll
          for (int q = 0; q < 4; q++) {
            const int ch = kap - 3 + q;
            uint32_t v[4];
            lds128(v, blk + (uint32_t)((ch * 16) ^ ((ch * 2) & 0x10)));
            #pragma unroll
            for (int e = 0; e < 4; e++) {
              P[q * 8 + 2 * e + 1] = (q == 0 && e < 2) ? 0.f : P[q * 8 + 2 * e] + bf_lo(v[e]);
              P[q * 8 + 2 * e + 2] = (q == 0 && e < 2) ? 0.f : P[q * 8 + 2 * e + 1] + bf_hi(v[e]);
            }
          }
#define WIN(lo, hi, e) (P[25 + (e) - (lo)] - P[24 + (e) - (hi)])
#define WIN8(lo, hi) pack2(WIN(lo, hi, 0), WIN(lo, hi, 1)), pack2(WIN(lo, hi, 2), WIN(lo, hi, 3)), pack2(WIN(lo, hi, 4), WIN(lo, hi, 5)), pack2(WIN(lo, hi, 6), WIN(lo, hi, 7))
          const uint32_t o2 = blk + B_D + (kap & 1) * 1552 + (kap >> 1) * 16;
          sts128(o2, WIN8(3, 5));
          sts128(o2 + B_D5, WIN8(6, 10));
          if (kap < 2) sts128(blk + B_D + kap * B_D5 + 1536, 0, 0, 0, 0);
          if (kap < 128) {
            const uint32_t o = blk + B_D + (kap & 1) * 1024 + (kap >> 1) * 16;
            sts128(o + B_D7, WIN8(5, 11));
            sts128(o + B_D9, WIN8(12, 20));
          }
        }
      }
      __syncwarp();
      if (lane == 0) mbar_arrive(BAR(BR_DRDY + 1));
      if (ht == 0) TS(32);
      if (hw == 0) {
        #pragma unroll 1
        for (int p = 0; p < 2; p++) {
          mbar_wait(BAR(BR_Y) + 8 * p, 0);
          if (elect_one()) {
            #pragma unroll 1
            for (int k = p; k < 1 + 4 * p; k++) bulk_st(g_uy + (640 + ch0 + k) * 2048, sb + OFF_BLK + k * BLK, 4096);
            bulk_commit(); bulk_wait0_read();
            mbar_arrive(BAR(BR_FREE) + 8 * p);
          }
          __syncwarp();
        }
        if (elect_one()) {
          mbar_expect_tx(BAR(BR_YIN), 20480);
          bulk_wait0();
          st_rel(FLAG(2, r, c), epoch);
          TS(33);
        }
        __syncwarp();
        poll_all_acq(FLAG(2, lane & 15, c), epoch);
        if (EN_ATT) mbar_wait(BAR(BR_OEMPTY + 2), 0);
        if (elect_one()) {
          fence_async_g();
          tma2d(sb + OFF_EXTRA, &prm.m[M_SA], BAR(BR_YIN), r * 128, 640 + c * 80);
          tma2d(sb + OFF_EXTRA + 10240, &prm.m[M_SA], BAR(BR_YIN), r * 128 + 64, 640 + c * 80);
          TS(34);
        }
        __syncwarp();
        if (EN_ATT) mbar_wait(BAR(BR_OEMPTY + 3), 0);
        mbar_wait(BAR(BR_YIN), 0);
        y_transpose(sb, 4, lane);
      if (elect_one()) {
        tma2d_st(&prm.m[M_OUT], sb + SLOT(3), c * 80, r * 128);
        bulk_commit(); bulk_wait0_read();
        TS(35); DUMP(30, 40); DUMP(0, 1);
      }
      }
      }
    }
  } else {
    const int g = lane >> 2, tq = lane & 3, t7 = tid & 127;
    uint32_t pr[3][2], pd;
    {
      const int ch = c * 80 + r * 5 + wg;
      uint32_t raw[3][4];
      #pragma unroll
      for (int e = 0; e < 4; e++) {
        const __nv_bfloat16* pp = prm.par[e] + ch * 128 + t7;
        #pragma unroll
        for (int q = 0; q < 3; q++) {
          raw[q][e] = 0;
          if (q == 0 || wg == 2) asm volatile("ld.global.nc.u16 %0, [%1];" : "=r"(raw[q][e]) : "l"(pp + q * 128));
        }
      }
      asm volatile("ld.global.nc.u16 %0, [%1];" : "=r"(pd) : "l"(((lane & 4) ? prm.dskip : prm.logdt) + ch + min(lane & 3, 2)));
      asm volatile("setmaxnreg.inc.sync.aligned.u32 152;");
      if (EN_SSM && wg < 2) {
        #pragma unroll
        for (int k = 0; k < 2; k++) {
          const uint32_t z = sb + OFF_BLK + (2 * wg + k) * BLK + t7 * 16;
          sts128(z + B_TBL, 0, 0, 0, 0); sts128(z + B_TBL + 2048, 0, 0, 0, 0);
        }
        if (tid < 80) sts128(sb + OFF_BLK + (tid >> 4) * BLK - 256 + (tid & 15) * 16, 0, 0, 0, 0);
      }
      #pragma unroll
      for (int q = 0; q < 3; q++) {
        #pragma unroll
        for (int e = 0; e < 2; e++) pr[q][e] = raw[q][2 * e] | (raw[q][2 * e + 1] << 16);
        const uint32_t m = __reduce_max_sync(0xffffffff, max(raw[q][2] & 0x7fffu, raw[q][3] & 0x7fffu));
        if (lane == 0) sts32(sb + OFF_EPOCH + 64 + (wg * 3 + q) * 16 + w4 * 4, m);
      }
      bar_sync(2 + wg, 128);
    }
    if (tid == 256) TS(40);
    if (EN_SSM) {
#define P0(w) ((w) == 1 ? 4 * W_SLOT : OFF_BLK + (w) * BLK)
#define P2(w) ((w) == 1 ? OFF_X + 32768 - 4 * W_SLOT : BLK)
      uint32_t ea = sb + P0(wg) + (lane >> 4) * 7168 + (w4 & 1) * P2(wg) + ((lane >> 3) & 1) * 256 + (lane & 7) * 16 + (w4 >> 1) * 2048;
      constexpr uint64_t dE = mkdesc(SB0, 128, 512, 0);
      const uint32_t xa = sb + OFF_BLK + 18560 + t7 * 8, xr_ = sb + OFF_BLK + 18560 + (t7 ^ 64) * 8;
      float ka[24]; zero<24>(ka);
      wg_fence();
      wg_ss48_tt_h(ka, dE + (OFF_BLK >> 4), dE + (OFF_BLK >> 4), 0);
      wg_commit();
      #pragma unroll 1
      for (int it = -1; it < 5; it++) {
        const int k = it < 2 ? 1 - it : it;
        const bool nf = it < 0 || it == 2 || it == 3;
        const uint32_t blk = sb + OFF_BLK + k * BLK;
        uint32_t F[56];
#define PUT4(i, a, b, c_, d) { F[4 * (i)] = a; F[4 * (i) + 1] = b; F[4 * (i) + 2] = c_; F[4 * (i) + 3] = d; }
        if (nf) {
          const int q = it < 0 ? 0 : it - 1;
          const uint32_t pa0 = pr[0][0], pc0 = pr[0][1];
          const float dt = bf_round(expf(bf_lo(__shfl_sync(0xffffffff, pd, q))));
          #pragma unroll
          for (int e = 0; e < 2; e++) { pr[0][e] = pr[1][e]; pr[1][e] = pr[2][e]; }
          uint32_t mm[4];
          lds128(mm, sb + OFF_EPOCH + 64 + (wg * 3 + q) * 16);
          const uint32_t ex = min(max(max(max(mm[0], mm[1]), max(mm[2], mm[3])) >> 7, 1u), 253u);
          const float sc = __uint_as_float((254u - ex) << 23);
          if (t7 == 4 + q) sts64(sb + OFF_EPOCH + 16 + (wg + q) * 8, __float_as_uint(2.f * dt * __uint_as_float(ex << 23)), pd << 16);
          const float lr = -bf_round(expf(bf_lo(pa0))) * dt * 1.44269504089f;
          const float tn = bf_hi(pa0) * dt * 0.15915494309f;
          float z1r, z1i, z2r, z2i, z4r, z4i, xr[8], xi[8], gr[8], gi[8], wr[9], wi[9];
          cexp_t(lr, -tn, z1r, z1i);
          cexp_t(lr * 8.f, tn * 8.f, xr[1], xi[1]);
          cexp_t(lr * 64.f, tn * 64.f, wr[0], wi[0]);
          xr[0] = 1.f; xi[0] = 0.f;
          cmul(xr[1], xi[1], xr[1], xi[1], xr[2], xi[2]); cmul(xr[2], xi[2], xr[1], xi[1], xr[3], xi[3]);
          cmul(xr[2], xi[2], xr[2], xi[2], xr[4], xi[4]);
          #pragma unroll
          for (int b = 1; b < 4; b++) cmul(xr[4], xi[4], xr[b], xi[b], xr[4 + b], xi[4 + b]);
          cmul(wr[0], wi[0], wr[0], wi[0], wr[1], wi[1]); cmul(wr[1], wi[1], wr[0], wi[0], wr[2], wi[2]);
          cmul(wr[1], wi[1], wr[1], wi[1], wr[3], wi[3]); cmul(wr[3], wi[3], wr[3], wi[3], wr[4], wi[4]);
          cmul(wr[4], wi[4], wr[3], wi[3], wr[5], wi[5]); cmul(wr[4], wi[4], wr[4], wi[4], wr[6], wi[6]);
          cmul(wr[6], wi[6], wr[4], wi[4], wr[7], wi[7]); cmul(wr[6], wi[6], wr[6], wi[6], wr[8], wi[8]);
          uint32_t R[4], I[4], PR[4], PI[4];
          #pragma unroll
          for (int b = 0; b < 4; b++) { R[b] = packh(xr[2 * b], xr[2 * b + 1]); I[b] = packh(xi[2 * b], xi[2 * b + 1]); }
          PUT4(0, R[0], R[1], R[2], R[3]); PUT4(1, I[0], I[1], I[2], I[3]);
          #pragma unroll
          for (int i = 0; i < 3; i++) {
            const uint32_t z = packh(wr[i], wi[i]);
            #pragma unroll
            for (int b = 0; b < 4; b++) hcm2(R[b], I[b], z, PR[b], PI[b]);
            PUT4(2 * i + 2, PR[0], PR[1], PR[2], PR[3]); PUT4(2 * i + 3, PI[0], PI[1], PI[2], PI[3]);
          }
          gr[0] = bf_lo(pc0) * sc; gi[0] = -bf_hi(pc0) * sc;
          cmul(z1r, z1i, z1r, z1i, z2r, z2i); cmul(z2r, z2i, z2r, z2i, z4r, z4i);
          cmul(gr[0], gi[0], z1r, z1i, gr[1], gi[1]);
          cmul(gr[0], gi[0], z2r, z2i, gr[2], gi[2]); cmul(gr[1], gi[1], z2r, z2i, gr[3], gi[3]);
          #pragma unroll
          for (int b = 0; b < 4; b++) cmul(gr[b], gi[b], z4r, z4i, gr[4 + b], gi[4 + b]);
          PUT4(8, packh(gr[0], gr[1]), packh(gr[2], gr[3]), packh(gr[4], gr[5]), packh(gr[6], gr[7]));
          PUT4(9, packh(gi[0], gi[1]), packh(gi[2], gi[3]), packh(gi[4], gi[5]), packh(gi[6], gi[7]));
          {
            const uint32_t z = packh(wr[3], -wi[3]), a4r = packh(gr[0], gr[4]), a4i = packh(gi[0], gi[4]);
            hcm2(packh(gr[0], gr[2]), packh(gi[0], gi[2]), z, PR[0], PI[0]);
            hcm2(packh(gr[4], gr[6]), packh(gi[4], gi[6]), z, PR[1], PI[1]);
            hcm2(a4r, a4i, packh(wr[4], -wi[4]), PR[2], PI[2]);
            hcm2(a4r, a4i, packh(wr[5], -wi[5]), PR[3], PI[3]);
            PUT4(10, PR[0], PR[1], PR[2], PR[3]); PUT4(11, PI[0], PI[1], PI[2], PI[3]);
            float hr, hi_;
            cmul(gr[0], gi[0], wr[3], -wi[3], hr, hi_);
            const uint32_t cr = packh(gr[0], hr), ci = packh(gi[0], hi_);
            #pragma unroll
            for (int i = 0; i < 3; i++) hcm2(cr, ci, packh(wr[6 + i], -wi[6 + i]), PR[i], PI[i]);
            PUT4(12, PR[0], PR[1], PR[2], 0u); PUT4(13, PI[0], PI[1], PI[2], 0u);
          }
        }
        else {
          #pragma unroll
          for (int i = 0; i < 56; i++) asm volatile("" : "=r"(F[i]));
        }
        uint32_t fd[2];
        lds64(fd, sb + OFF_EPOCH + 16 + k * 8);
        const float fac = __uint_as_float(fd[0]), dsk = __uint_as_float(fd[1]);
        wg_wait<0>();
        pin<24>(ka);
        float kk[6];
        const bool up = w4 >= 2;
        if (it == 1 || it == 2) bar_sync(4, 128);
        #pragma unroll
        for (int n = 0; n < 3; n++) {
          if (it >= 0) sts64f(xa + n * BLK, up ? ka[12 + 4 * n] : ka[4 * n + 2], up ? ka[13 + 4 * n] : ka[4 * n + 3]);
          kk[2 * n] = up ? ka[14 + 4 * n] : ka[4 * n]; kk[2 * n + 1] = up ? ka[15 + 4 * n] : ka[4 * n + 1];
        }
        pin<6>(kk);
        if (it >= 0) {
          bar_sync(4, 128);
          if (t7 == 0) mbar_arrive(BAR(BR_KS) + 8 * it);
          #pragma unroll
          for (int n = 0; n < 3; n++) {
            uint32_t o[2]; lds64(o, xr_ + n * BLK);
            kk[2 * n] = (kk[2 * n] + __uint_as_float(o[0])) * fac; kk[2 * n + 1] = (kk[2 * n + 1] + __uint_as_float(o[1])) * fac;
          }
        }
        if (nf) {
          if (it == 2) {
            mbar_wait(BAR(BR_UOUT), 0);
            ea += BLK;
            sts128(sb + OFF_UT + B_TBL + t7 * 16, 0, 0, 0, 0); sts128(sb + OFF_UT + B_TBL + 2048 + t7 * 16, 0, 0, 0, 0);
          }
          const uint32_t ga = ea + 4096 - (w4 >> 1) * 512;
          #pragma unroll
          for (int i = 0; i < 14; i++) sts128((i < 8 ? ea + (i >> 1) * 512 : ga + ((i - 8) >> 1) * 512) + (i & 1) * 128, F[4 * i], F[4 * i + 1], F[4 * i + 2], F[4 * i + 3]);
          fence_async();
          bar_sync(it < 0 ? 0 : 4, it < 0 ? 512 : 128);
          if (wg < 2) break;
        }
        if (it < 4) {
          const int fs = (0x33201 >> (4 * it + 4)) & 3;
          wg_fence();
          #pragma unroll
          for (int s = 0; s < 8; s++) {
            const uint32_t lo = (uint32_t)dE + ((P0(fs) + (s >> 2) * P2(fs)) >> 4) + ((s >> 1) & 1) * 448 + (s & 1) * 16;
            wg_ss48_tt_h(ka, desc2(lo, dE >> 32), desc2(lo + 256, dE >> 32), s != 0);
          }
          wg_commit();
        }
        if (it >= 0)
        {
          const int j = (w4 & 1) * 16 + (w4 >> 1) * 8 + g;
          const uint32_t tb = blk + B_TBL;
          if (t7 == 0) kk[0] += dsk;
          const uint32_t pa_ = tb + (16 + 8 * j + 2 * tq) * 4;
          const uint32_t v = pack2(kk[1], kk[0]);
          sts32(pa_ + 4, v); sts16(pa_, v >> 16); sts16(pa_ + 10, v);
          const uint32_t u = pack2(kk[2], kk[3]), w = pack2(kk[4], kk[5]);
          if (tq < 2) {
            const uint32_t pb = tb + (16 + 256 + 8 * j + 4 * tq) * 4;
            sts16(pb, u); sts32(pb + 4, __byte_perm(u, 0, 0x1010)); sts32(pb + 8, __byte_perm(u, 0, 0x1032)); sts16(pb + 14, u >> 16);
            if (j | tq) { sts16(pb - 4, u); sts16(pb + 2, u); }
            const int i = 64 * tq + j;
            const uint32_t e0 = tb + (T_F3 + (((i - 1) & 1) ? 80 : 0) + ((i - 1) >> 1)) * 4, e1 = i ? e0 : tb + (T_F2 + 144 + 31) * 4;
            sts16(e1, w); sts16(e1 + 6, w); sts16(e0 + 64, w >> 16); sts16(e0 + 70, w >> 16);
            if (i == 0) { sts16(tb + (T_S + 3) * 4, w); sts32(tb + (T_S + 4) * 4, __byte_perm(w, 0, 0x1010)); sts16(tb + (T_S + 5) * 4 + 2, w); }
          } else {
            const int i = 32 * (tq - 2) + j;
            const uint32_t e1 = tb + (i ? T_F2 + ((2 * i - 1) & 3) * 48 + ((2 * i - 1) >> 2) : 16 + 511) * 4;
            const uint32_t e2 = tb + (T_F2 + (i & 1) * 96 + (i >> 1)) * 4;
            sts16(e1, u); sts16(e1 + 6, u); sts16(e2, u >> 16); sts16(e2 + 6, u >> 16);
            if (i == 0) {
              const uint32_t uu = __byte_perm(u, 0, 0x1010);
              sts32(tb + 528 * 4, uu); sts32(tb + 529 * 4, uu); sts32(tb + 530 * 4, uu); sts16(tb + 531 * 4 + 2, u);
              sts16(tb + (T_F3 + 80 + 63) * 4, w);
            }
          }
        }
        if (t7 == 0) TS(49 + it);
      }
      wg_wait<0>();
      pin<24>(ka);
    }
    if (!EN_SSM) bar_sync(0, 512);
    if (tid == 0) TS(14);
  if (wg < 2) {
    if (EN_ATT) {
    float am[96], ar[24];
    {
      const bool lead = (rtid() & 127) == 0;
      constexpr uint64_t da0 = mkdesc(SB0 + OFF_X, 16, 1024, 1), dr0 = mkdesc(SB0 + 12288, 1024, 256, 3);
      const uint64_t db0 = sw64 ? mkdesc(SB0, 2048, 512, 2) : mkdesc(SB0, 4096, 1024, 1);
      const uint32_t kst = sw64 ? 64 : 128, bh = db0 >> 32;
      uint32_t s = 0, ph = 0, xo = 0;
      #pragma unroll 1
      for (int kb = 0; kb < 20; kb++) {
        const uint32_t wo_ = s * (W_SLOT >> 4), al = (uint32_t)da0 + wg * 512 + xo, bl = (uint32_t)db0 + wo_, rl = (uint32_t)dr0 + wo_;
        mbar_wait(BAR(BR_FULL) + 8 * s, ph);
        if (kb == 0 && lead && wg == 0) TS(1);
        wg_fence();
        wg_ss192_tb(am, desc2(al, da0 >> 32), desc2(bl, bh), kb != 0);
        wg_ss48_tb(ar, desc2(al, da0 >> 32), desc2(rl, dr0 >> 32), kb != 0);
        wg_ss192_tb(am, desc2(al + 2, da0 >> 32), desc2(bl + kst, bh), 1);
        wg_ss48_tb(ar, desc2(al + 2, da0 >> 32), desc2(rl + 32, dr0 >> 32), 1);
        wg_commit();
        wg_wait<1>();
        if (lead && kb > 0 && kb < 16) mbar_arrive(BAR(BR_EMPTY) + 8 * (s == 0 ? 4 : s - 1));
        if (++s == 5) { s = 0; ph ^= 1; }
        xo += (kb & 1) ? 1020 : 4;
        if (xo == 3072) xo = 0;
      }
      wg_wait<0>();
      pin<96>(am); pin<24>(ar);
    }
    const int tid = rtid(), lane = tid & 31, tq = lane & 3;
    if (tid == 0) TS(2);
#define QV(j, e) ((j) < 8 ? am[4 * (j) + (e)] : ar[4 * ((j) - 8) + (e)])
#define KV_(j, e) ((j) < 8 ? am[32 + 4 * (j) + (e)] : ar[8 + 4 * ((j) - 8) + (e)])
#define VV(j, e) ((j) < 8 ? am[64 + 4 * (j) + (e)] : ar[16 + 4 * ((j) - 8) + (e)])
    {
      bar_sync(1, 256);
      if (tid == 0) mbar_arrive(BAR(BR_GEMM));
      const uint32_t ro = sb + (uint32_t)((warp * 16 + (lane & 15)) * 16);
      const int l0 = 2 * (c & 1) + (lane >> 4);
      const uint32_t ones = (tq == 0) ? 0x00003f80u : 0u;
#define PV(j) pack2(VV(j, 0), VV(j, 1)), pack2(VV(j, 2), VV(j, 3))
#define PK(j) pack2(phi(KV_(j, 0)), phi(KV_(j, 1))), pack2(phi(KV_(j, 2)), phi(KV_(j, 3)))
      stsm4(ro + OFF_V + (5 + 6 * (lane >> 4)) * 2048, ones, ones, ones, ones);
      #pragma unroll
      for (int j = 0; j < 10; j += 2) {
        const int l = (j == 8 && (c & 1)) ? l0 - 2 : l0 + j;
        stsm4(ro + OFF_V + (l + (l >= 5)) * 2048, PV(j), PV(j + 1));
        stsm4(ro + OFF_PK + l * 2048, PK(j), PK(j + 1));
      }
    }
    fence_async();
    bar_sync(1, 256);
    if (tid == 0) TS(3);
    mbar_wait(BAR(BR_EPOCH), 0);
    const unsigned epoch = lds32(sb + OFF_EPOCH);
    {
      float kv[24]; zero<24>(kv);
      constexpr uint64_t da = mkdesc(SB0 + OFF_PK, 128, 2048, 0), db = mkdesc(SB0 + OFF_V, 128, 2048, 0);
      wg_fence();
      #pragma unroll
      for (int s = 0; s < 8; s++) wg_ss48_tt(kv, desc2((uint32_t)da + wg * 640 + s * 16, da >> 32), desc2((uint32_t)db + wg * 768 + s * 16, db >> 32), s != 0);
      wg_commit();
      wg_wait<0>();
      pin<24>(kv);
      if (tid == 0) TS(15);
      if (w4 < 3) {
        const uint32_t wb = sb + OFF_KVS + (wg * 3 + w4) * 1536 + (lane & 15) * 96;
        #pragma unroll
        for (int j = 0; j < 6; j += 2)
          stsm4(wb + (j + (lane >> 4)) * 16, pack2(kv[4 * j], kv[4 * j + 1]), pack2(kv[4 * j + 2], kv[4 * j + 3]),
                pack2(kv[4 * j + 4], kv[4 * j + 5]), pack2(kv[4 * j + 6], kv[4 * j + 7]));
        __syncwarp();
        const int dl = w4 * 16 + (lane & 15), hl = dl >= 20;
        if (dl < 40) {
          uint4* dst = &g_kvp[(c * 16 + r) * 240 + wg * 40 + dl];
          uint32_t v[4], z[4];
          lds128(v, wb + (3 * hl + (lane >> 4)) * 16);
          lds64(z, wb + 32 + 8 * hl); z[2] = lds32(wb + 80); z[3] = epoch & 1u;
          v[3] = (v[3] & ~1u) | z[3];
          st128_rlx(dst + (lane >> 4) * 80, v);
          if (lane < 16) st128_rlx(dst + 160, z);
        }
      }
    }
    fence_async();
    bar_sync(1, 256);
    if (tid == 0) { st_rlx(FLAG(0, r, c), epoch); mbar_arrive(BAR(BR_PUB)); TS(4); }
    const int kvi = (tid >= 80) + (tid >= 160) + (tid >= 240), kd = tid - 80 * kvi;
    const int khd = kd / 20, kt0 = 5 * (khd >> 1) + 2 * (khd & 1);
    const uint32_t rb = sb + OFF_KVB + kd * 16;
    if (kvi < 3) {
      #pragma unroll 1
      for (int m = kvi; m < 7; m += 3) { const int q = kt0 + 3 + m; sts128(rb + (q >= 10 ? q - 10 : q) * 1280, 0, 0, 0, 0); }
    }
    uint32_t qa[20];
    {
      const float sc = 1.44269504089f + __uint_as_float(lds32(sb + OFF_EPOCH) ^ epoch);
      #pragma unroll
      for (int j = 0; j < 10; j++) { qa[2 * j] = pack2(phi(QV(j, 0), sc), phi(QV(j, 1), sc)); qa[2 * j + 1] = pack2(phi(QV(j, 2), sc), phi(QV(j, 3), sc)); }
    }
    if (tid == 0) TS(5);
    if (warp == 7) mbar_wait(BAR(BR_KVP), 0);
    bar_sync(1, 256);
    if (tid == 0) TS(6);
    if (kvi < 3) {
      float s[8];
      zero<8>(s);
      uint32_t bad = 0;
      #pragma unroll 4
      for (int i = 0; i < 16; i++) {
        uint32_t w[4];
        lds128(w, sb + OFF_KVP + tid * 16 + i * 3840);
        bad |= w[3] ^ epoch;
        #pragma unroll
        for (int e = 0; e < 4; e++) { s[2 * e] += bf_lo(w[e]); s[2 * e + 1] += bf_hi(w[e]); }
      }
      if (__builtin_expect(bad & 1u, 0)) {
        zero<8>(s);
        #pragma unroll 1
        for (int i = 0; i < 16; i++) {
          uint32_t w[4] = {0, 0, 0, ~epoch};
          fix128_w3(w, &g_kvp[(c * 16 + i) * 240 + tid], epoch, 1u);
          #pragma unroll
          for (int e = 0; e < 4; e++) { s[2 * e] += bf_lo(w[e]); s[2 * e + 1] += bf_hi(w[e]); }
        }
        FIXCNT
      }
      const uint32_t p0 = pack2(s[0], s[1]), p1 = pack2(s[2], s[3]), p2 = pack2(s[4], s[5]), p3 = pack2(s[6], s[7]);
      if (kvi < 2) sts128(rb + (kt0 + (khd & 1) + kvi) * 1280, p0, p1, p2, p3);
      else {
        const bool od = khd & 1;
        sts128(rb + (5 * (khd >> 1) + 2) * 1280, od ? 0u : p0, od ? 0u : p1, od ? p0 : 0u, od ? p1 : 0u);
        const uint32_t zz = (p2 & 0xffffu) << (16 * (khd & 1));
        sts128(rb + 10 * 1280, khd < 2 ? zz : 0u, khd < 2 ? 0u : zz, 0u, 0u);
      }
    }
    fence_async();
    bar_sync(1, 256);
    if (tid == 0) { mbar_arrive(BAR(BR_SUM)); TS(7); }
    {
      float oa[44]; zero<44>(oa);
      constexpr uint64_t db = mkdesc(SB0 + OFF_KVB, 128, 1280, 0);
      wg_fence();
      #pragma unroll
      for (int s = 0; s < 5; s++) wg_rs88_tb(oa, &qa[4 * s], desc2((uint32_t)db + ((s == 4 && (c & 1)) ? 0 : (s + (c & 1)) * 16), db >> 32), s != 0);
      wg_commit();
      wg_wait<0>();
      pin<44>(oa);
      if (tid == 0) TS(13);
      float rc[4], rd[2][4];
      #pragma unroll
      for (int e = 0; e < 4; e++) asm("rcp.approx.ftz.f32 %0, %1;" : "=f"(rc[e]) : "f"(oa[40 + e] + 1e-6f));
      #pragma unroll
      for (int h = 0; h < 4; h++) {
        rd[0][h] = __shfl_sync(0xffffffff, rc[h & 1], (lane & 28) | (h >> 1));
        rd[1][h] = __shfl_sync(0xffffffff, rc[2 + (h & 1)], (lane & 28) | (h >> 1));
      }
      #pragma unroll
      for (int j = 0; j < 10; j++) {
        #pragma unroll
        for (int h = 0; h < 2; h++) {
          float f;
          if (j == 2) f = tq < 2 ? rd[h][0] : rd[h][1];
          else if (j == 7) f = tq < 2 ? rd[h][2] : rd[h][3];
          else f = rd[h][(8 * j) / 20];
          qa[2 * j + h] = pack2(oa[4 * j + 2 * h] * f, oa[4 * j + 2 * h + 1] * f);
        }
      }
      const uint32_t m0 = (lane & 7) == ((2 * w4) & 7), m1 = (lane & 7) == 2 * w4 + 1;
      const uint32_t oa_ = sb + OFF_EXTRA + (lane >> 4) * 2048 + (warp * 16 + (lane & 15)) * 16;
      bar_sync(1, 256);
#define TAG(v, m) (((v) & ~(m)) | (epoch & (m)))
      #pragma unroll
      for (int s = 0; s < 5; s++) stsm4(oa_ + s * 4096, TAG(qa[4 * s], m0), TAG(qa[4 * s + 1], m1), TAG(qa[4 * s + 2], m0), TAG(qa[4 * s + 3], m1));
    }
    fence_async();
    __syncwarp();
    if (lane == 0) mbar_arrive(BAR(BR_OSTG));
    if (tid == 0) TS(8);
    float oc[40]; zero<40>(oc);
    {
      constexpr uint64_t dw0 = mkdesc(SB0, OFF_WOR, 1024, 1), da0 = mkdesc(SB0, 2048, 128, 0);
      const uint32_t ck = sb + tid * 32 + ((lane >> 2) << 2), ck2 = ck + (wg ? 0 : 16384);
      uint32_t bad = 0;
      auto tile = [&](int i, uint32_t so) {
        const uint32_t al = (uint32_t)da0 + wg * 64 + (so >> 4), wl = (uint32_t)dw0 + i * 640 - (i >> 1) * (1278 << 16);
        wg_fence();
        #pragma unroll
        for (int s = 0; s < 5; s++) wg_ss80_tb(oc, desc2(al + s * 256, da0 >> 32), desc2(wl + s * 128, dw0 >> 32), (i | s) != 0);
        wg_commit();
        bad |= (lds32(ck + so) ^ epoch) | (lds32(ck + so + 8192) ^ epoch) | (lds32(ck2 + so) ^ epoch);
      };
      mbar_wait(BAR(BR_WO), 0);
      mbar_wait(BAR(BR_OSTG), 0);
      tile(0, SLOT(0));
      mbar_wait(BAR(BR_WO + 1), 0);
      #pragma unroll 1
      for (int i = 1; i < 8; i++) {
        if (i == 1) {
          wg_wait<0>();
          if (lane == 0) mbar_arrive(BAR(BR_OEMPTY));
          if (EN_SSM && w4 == 0) mbar_wait(BAR(BR_Y + 1), 0);
          if (w4 == 0) mbar_wait(BAR(BR_OFULL + 1), 0);
          bar_sync(2 + wg, 128);
        }
        mbar_wait(BAR(BR_OFULL) + 8 * i, 0);
        if (i == 1 && tid == 0) TS(9);
        tile(i, SLOT(i));
        wg_wait<1>();
        if (lane == 0 && i > 1) mbar_arrive(BAR(BR_OEMPTY - 1) + 8 * i);
      }
      #pragma unroll 1
      for (int n = 0; n < 56; n++) {
        const int i = n & 7;
        if (i == 0) {
          uint32_t any;
          asm volatile("{\n.reg .pred p;\nsetp.ne.u32 p, %1, 0;\nbarrier.red.or.pred p, 1, 256, p;\nselp.u32 %0, 1, 0, p;\n}" : "=r"(any) : "r"(bad & 1u) : "memory");
          if (!any) break;
          bad = 0;
          FIXCNT
        }
        wg_wait<0>();
        bar_sync(1, 256);
        if (tid == 0) { mbar_expect_tx(BAR(BR_RETRY), 20480); bulk_ld(sb + SLOT(6), &g_o[(r * 8 + CHUNK(i)) * 1280], 20480, BAR(BR_RETRY)); }
        mbar_wait(BAR(BR_RETRY), n & 1);
        tile(i, SLOT(6));
      }
      wg_wait<0>();
      pin<40>(oc);
    }
    if (tid == 0) TS(10);
    {
      const int row = w4 * 16 + (lane & 15);
      const uint32_t ob = sb + OFF_BLK + 2 * BLK + wg * 10240;
      #pragma unroll
      for (int j = 0; j < 8; j += 2)
        stsm4(ob + row * 128 + (((j + (lane >> 4)) ^ (row & 7)) << 4), pack2(oc[4 * j], oc[4 * j + 1]), pack2(oc[4 * j + 2], oc[4 * j + 3]),
              pack2(oc[4 * j + 4], oc[4 * j + 5]), pack2(oc[4 * j + 6], oc[4 * j + 7]));
      stsm4(ob + 8192 + row * 32 + (lane >> 4) * 16, pack2(oc[32], oc[33]), pack2(oc[34], oc[35]), pack2(oc[36], oc[37]), pack2(oc[38], oc[39]));
      fence_async();
      bar_sync(2 + wg, 128);
      if (w4 == 0 && elect_one()) {
        tma2d_st(&prm.m[M_O64], ob, 640 + c * 64, r * 128 + wg * 64);
        tma2d_st(&prm.m[M_O16], ob + 8192, 1152 + c * 16, r * 128 + wg * 64);
        bulk_commit(); bulk_wait0_read();
        if (wg == 0) { TS(11); DUMP(0, 20); }
      }
    }
    }
  } else {
    if (EN_SSM) {
    const int tid = rtid(), lane = tid & 31, g = lane >> 2, tq = lane & 3, t7 = tid & 127;
    if (t7 == 0) TS(41);
    mbar_wait(BAR(BR_U), 0);
    bar_sync(4, 128);
    if (EN_ATT) mbar_wait(BAR(BR_GEMM), 0);
    if (t7 == 0) TS(42);
    #pragma unroll 1
    for (int pass = 0; pass < 2; pass++) {
      const int k = pass ? w4 + 1 : 0;
      if (pass) mbar_wait(BAR(BR_U2), 0);
      const uint32_t blk = sb + OFF_BLK + k * BLK, tb = blk + B_TBL + (uint32_t)((g - 2 * tq) * 4);
      float acc[16][4];
      zero<64>(&acc[0][0]);
      const int kl = 16 * (lane >> 4) + 2 * (lane & 7) + ((lane >> 3) & 1);
      {
        auto ubase = [&](int sh) { const int q = kl - 2 * sh; return blk + (uint32_t)((q * 16) ^ ((q * 2) & 0x10)); };
#define LDQ(A, sh) _Pragma("unroll") for (int m = 0; m < 4; m++) load_quad(A[m], tb + (16 + 16 * (sh) + 128 * m) * 4);
#define LDB(B, ub, h) _Pragma("unroll") for (int p = 0; p < 4; p++) ldsm4(B[p], (ub) + (4 * (h) + p) * 512);
#define MLO(A, B) _Pragma("unroll") for (int m = 0; m < 4; m++) _Pragma("unroll") for (int cc = 0; cc < 8; cc++) mma16816(acc[cc + m], A[m], &B[cc >> 1][(cc & 1) * 2]);
#define MHI(A, B) _Pragma("unroll") for (int m = 0; m < 4; m++) _Pragma("unroll") for (int cc = 0; cc < 8 - m; cc++) mma16816(acc[8 + cc + m], A[m], &B[cc >> 1][(cc & 1) * 2]);
        int p_ = pass ? 0 : w4;
        const int pe = pass ? 4 : w4 + 1;
        uint32_t A[4][4], A2[4][4], Bl[4][4], Bh[4][4];
        uint32_t ub = ubase(p_ + 4);
        LDQ(A, p_ + 4) LDB(Bl, ub, 0)
        #pragma unroll 1
        for (; p_ < pe; p_++) {
          LDB(Bh, ub, 1)
          MLO(A, Bl)
          ub = ubase(p_);
          LDQ(A2, p_) LDB(Bl, ub, 0)
          MHI(A, Bh)
          LDB(Bh, ub, 1)
          load_quad(A[0], tb + (16 + 512 + 16 * (p_ & 1)) * 4); load_quad(A[1], tb + (T_S + 16 * (p_ & 1)) * 4);
          MLO(A2, Bl)
          if (p_ < 2) {
            #pragma unroll
            for (int cc = 0; cc < 8; cc++) mma16816(acc[cc + 4], A[0], &Bl[cc >> 1][(cc & 1) * 2]);
            #pragma unroll
            for (int cc = 0; cc < 4; cc++) mma16816(acc[cc + 12], A[0], &Bh[cc >> 1][(cc & 1) * 2]);
            #pragma unroll
            for (int cc = 0; cc < 8; cc++) mma16816(acc[cc + 8], A[1], &Bl[cc >> 1][(cc & 1) * 2]);
          }
          const int pn = ((p_ + 1) & 3) + 4;
          ub = ubase(pn);
          LDQ(A, pn) LDB(Bl, ub, 0)
          MHI(A2, Bh)
        }
      }
      if (t7 == 0) TS(57 + 3 * pass);
      mbar_wait(BAR(BR_DRDY) + 8 * pass, 0);
      {
        const int ih = (lane >> 3) & 1;
        const uint32_t dl = blk + B_D + (uint32_t)(((lane >> 4) * 8 + (lane & 7)) * 16);
        const uint32_t d0_ = dl + ih * 1552, d8_ = dl + (ih ? 0 : 1536), d3_ = dl + B_D7 + ih * 1024;
        auto cls2 = [&](uint32_t da, uint32_t ta) {
          uint32_t B[6][2], A[6][4];
          #pragma unroll
          for (int e = 0; e < 6; e++) { B[e][0] = lds32v(ta + (e + 4) * 32); B[e][1] = lds32v(ta + (e + 3) * 32); }
          #pragma unroll
          for (int kk = 0; kk < 6; kk++) ldsm4t(A[kk], da + kk * 256);
          #pragma unroll
          for (int e = 0; e < 6; e++)
            #pragma unroll
            for (int kk = 0; kk < 6; kk++) if (2 * kk + e + 4 < 16) mma16816(acc[2 * kk + e + 4], A[kk], B[e]);
        };
        auto cls3 = [&](uint32_t da, uint32_t ta) {
          uint32_t B[8][2], A[4][4];
          #pragma unroll
          for (int e = 0; e < 8; e++) { B[e][0] = lds32v(ta + (e + 8) * 32); B[e][1] = lds32v(ta + (e + 7) * 32); }
          #pragma unroll
          for (int kk = 0; kk < 4; kk++) ldsm4t(A[kk], da + kk * 256);
          #pragma unroll
          for (int kk = 0; kk < 4; kk++)
            #pragma unroll
            for (int e = 0; e < 8; e++) if (2 * kk + e + 8 < 16) mma16816(acc[2 * kk + e + 8], A[kk], B[e]);
        };
        if (pass) {
          #pragma unroll 1
          for (int a = 0; a < 2; a++) {
            cls2(d0_ + a * B_D5, tb + (T_F2 + 48 * a - 32) * 4);
            cls2(d8_ + a * B_D5, tb + (T_F2 + 48 * a + 64) * 4);
            cls3(d3_ + a * 2048, tb + (T_F3 + 80 * a - 64) * 4);
          }
        } else {
          cls2(((w4 & 2) ? d8_ : d0_) + (w4 & 1) * B_D5, tb + (T_F2 + 48 * w4 - 32) * 4);
          if (w4 >= 2) cls3(d3_ + (w4 - 2) * 2048, tb + (T_F3 + 80 * (w4 - 2) - 64) * 4);
        }
      }
      if (t7 == 0) TS(58 + 3 * pass);
      const uint32_t ya = blk + (uint32_t)((kl * 16) ^ ((kl * 2) & 0x10));
#define STY(p) stsm4t(ya + (p) * 512, pack2(acc[2 * (p)][0], acc[2 * (p)][1]), pack2(acc[2 * (p)][2], acc[2 * (p)][3]), \
                      pack2(acc[2 * (p) + 1][0], acc[2 * (p) + 1][1]), pack2(acc[2 * (p) + 1][2], acc[2 * (p) + 1][3]))
      if (pass == 0) {
        const uint32_t xw = blk + 3840 + w4 * 4096 + lane * 16, xr = blk + 3840 + w4 * 1024 + lane * 16;
        #pragma unroll
        for (int h = 0; h < 2; h++) {
          bar_sync(4, 128);
          #pragma unroll
          for (int i = 0; i < 8; i++)
            sts128(xw + i * 512, __float_as_uint(acc[8 * h + i][0]), __float_as_uint(acc[8 * h + i][1]), __float_as_uint(acc[8 * h + i][2]), __float_as_uint(acc[8 * h + i][3]));
          bar_sync(4, 128);
          float y[8];
          #pragma unroll
          for (int i = 0; i < 8; i++) {
            uint32_t o[4]; lds128(o, xr + (i >> 1) * 4096 + (i & 1) * 512);
            #pragma unroll
            for (int e = 0; e < 4; e++) y[4 * (i & 1) + e] = i < 2 ? __uint_as_float(o[e]) : y[4 * (i & 1) + e] + __uint_as_float(o[e]);
          }
          if (h) bar_sync(4, 128);
          stsm4t(ya + (4 * h + w4) * 512, pack2(y[0], y[1]), pack2(y[2], y[3]), pack2(y[4], y[5]), pack2(y[6], y[7]));
        }
      } else {
        __syncwarp();
        #pragma unroll
        for (int p = 0; p < 8; p++) STY(p);
      }
      if (t7 == 0 && !pass) TS(55);
      fence_async();
      __syncwarp();
      if (lane == 0) mbar_arrive(BAR(BR_Y) + 8 * pass);
      if (t7 == 0) TS(59 + 3 * pass);
    }
    if (t7 == 0) DUMP(40, 64);
    y_transpose(sb, w4, lane);
    }
  }
  }
}

typedef CUresult (*EncFn)(CUtensorMap*, CUtensorMapDataType, cuuint32_t, void*, const cuuint64_t*, const cuuint64_t*, const cuuint32_t*,
                          const cuuint32_t*, CUtensorMapInterleave, CUtensorMapSwizzle, CUtensorMapL2promotion, CUtensorMapFloatOOBfill);
static void mkmap(EncFn enc, CUtensorMap* m, const void* base, int rank, const cuuint64_t* dims, const cuuint64_t* strides, const cuuint32_t* box, CUtensorMapSwizzle swz) {
  cuuint32_t es[5] = {1, 1, 1, 1, 1};
  enc(m, CU_TENSOR_MAP_DATA_TYPE_BFLOAT16, rank, const_cast<void*>(base), dims, strides, box, es, CU_TENSOR_MAP_INTERLEAVE_NONE, swz,
      CU_TENSOR_MAP_L2_PROMOTION_L2_128B, CU_TENSOR_MAP_FLOAT_OOB_FILL_NONE);
}

extern "C" void kernel_launch(void* const* d_in, const int* in_sizes, int n_in, void* d_out, int out_size) {
  void* fn = nullptr; cudaDriverEntryPointQueryResult qr;
  cudaGetDriverEntryPoint("cuTensorMapEncodeTiled", &fn, cudaEnableDefault, &qr);
  EncFn enc = (EncFn)fn;
  void* uy = nullptr; cudaGetSymbolAddress(&uy, g_uy);
  const cuuint64_t dx[2] = {640, 2048}, sx[1] = {1280};
  const cuuint32_t bx[2] = {64, 128}, bu[2] = {80, 128};
  const cuuint64_t dw[3] = {640, 640, 3}, sw[2] = {3840, 1280};
  const cuuint32_t br[3] = {16, 32, 3};
  const cuuint64_t dwa[4] = {64, 640, 10, 3}, swa[3] = {3840, 128, 1280}, dwb[4] = {32, 640, 20, 3}, swb[3] = {3840, 64, 1280};
  const cuuint32_t bwa[4] = {64, 32, 1, 3}, bwb[4] = {32, 32, 2, 3};
  const cuuint64_t dwo[2] = {640, 640};
  const cuuint32_t bwo[2] = {64, 80}, bo64[2] = {64, 64}, bo16[2] = {16, 64};
  const cuuint64_t dsa[2] = {2048, 1280}, ssa[1] = {4096};
  const cuuint32_t bsa[2] = {64, 80};
  const cuuint64_t dout[2] = {1280, 2048}, sout[1] = {2560};
  Params prm;
  mkmap(enc, &prm.m[M_X], d_in[7], 2, dx, sx, bx, CU_TENSOR_MAP_SWIZZLE_128B);
  mkmap(enc, &prm.m[M_W128], d_in[8], 4, dwa, swa, bwa, CU_TENSOR_MAP_SWIZZLE_128B);
  mkmap(enc, &prm.m[M_W64], d_in[8], 4, dwb, swb, bwb, CU_TENSOR_MAP_SWIZZLE_64B);
  mkmap(enc, &prm.m[M_WR], d_in[8], 3, dw, sw, br, CU_TENSOR_MAP_SWIZZLE_32B);
  mkmap(enc, &prm.m[M_U], d_in[0], 2, dx, sx, bu, CU_TENSOR_MAP_SWIZZLE_NONE);
  mkmap(enc, &prm.m[M_WO], d_in[9], 2, dwo, sx, bwo, CU_TENSOR_MAP_SWIZZLE_128B);
  mkmap(enc, &prm.m[M_O64], d_out, 2, dout, sout, bo64, CU_TENSOR_MAP_SWIZZLE_128B);
  mkmap(enc, &prm.m[M_O16], d_out, 2, dout, sout, bo16, CU_TENSOR_MAP_SWIZZLE_NONE);
  mkmap(enc, &prm.m[M_SA], uy, 2, dsa, ssa, bsa, CU_TENSOR_MAP_SWIZZLE_128B);
  mkmap(enc, &prm.m[M_OUT], d_out, 2, dout, sout, bu, CU_TENSOR_MAP_SWIZZLE_NONE);
  prm.u = (const __nv_bfloat16*)d_in[0]; prm.wo = (const __nv_bfloat16*)d_in[9];
  for (int i = 0; i < 4; i++) prm.par[i] = (const __nv_bfloat16*)d_in[1 + i];
  prm.logdt = (const __nv_bfloat16*)d_in[5]; prm.dskip = (const __nv_bfloat16*)d_in[6];
  cudaFuncSetAttribute(fused_kernel, cudaFuncAttributeMaxDynamicSharedMemorySize, SMEM_BYTES);
  cudaLaunchConfig_t cfg = {};
  cfg.gridDim = dim3(128); cfg.blockDim = dim3(512); cfg.dynamicSmemBytes = SMEM_BYTES; cfg.stream = cudaStreamPerThread;
  cudaLaunchAttribute at[1];
  at[0].id = cudaLaunchAttributeClusterDimension; at[0].val.clusterDim.x = 2; at[0].val.clusterDim.y = 1; at[0].val.clusterDim.z = 1;
  cfg.attrs = at; cfg.numAttrs = 1;
  cudaLaunchKernelEx(&cfg, fused_kernel, prm);
}
```

```cpp
#include <cuda_runtime.h>
#include <cuda_bf16.h>
#include <cuda_fp16.h>
#include <cuda.h>
#include <stdint.h>

#define KST 2
#define EN_ATT 1
#define EN_SSM 1

__device__ __align__(1024) __nv_bfloat16 g_uy[2 * 640 * 2048];
__device__ __align__(128) uint4 g_kvp[8 * 16 * 240];
__device__ __align__(128) uint4 g_o[128 * 1280];
__device__ __align__(128) unsigned g_flag[4 * 128 * 32];
__device__ unsigned g_epoch[128];
#define TS(i) do {} while (0)
#define DUMP(lo, hi) do {} while (0)
#define FIXCNT

constexpr uint32_t SB0 = 1024;
constexpr uint32_t W_SLOT = 15360, OFF_X = 76800;
constexpr uint32_t OFF_WOR = 81920, OFF_KVP = 10240, OFF_KVS = 71680, OFF_PK = 10240, OFF_V = 30720, OFF_EXTRA = 102400, OFF_KVB = OFF_EXTRA;
constexpr uint32_t OFF_BAR = 125952, OFF_BLK = 128000, BLK = 20480;
constexpr uint32_t B_D = 4096, B_D5 = 3088, B_D7 = 6176, B_D9 = 8224, B_TBL = 14400;
constexpr int T_S = 576, T_F2 = 624, T_F3 = 816;
constexpr uint32_t OFF_UT = OFF_BLK + 4 * BLK;
constexpr uint32_t SMEM_BYTES = OFF_BLK + 5 * BLK;
enum { BR_FULL = 0, BR_WO = 5, BR_PUB = 7, BR_KVP = 8, BR_U = 9, BR_SUM = 10, BR_GEMM = 11, BR_UIN = 12, BR_YIN = 13, BR_EPOCH = 14,
       BR_FREE = 15, BR_RETRY = 17, BR_UOUT = 18, BR_OFULL = 18, BR_KS = 26, BR_EMPTY = 31, BR_OEMPTY = 36, BR_Y = 43, BR_OSTG = 45,
       BR_DRDY = 46, BR_U2 = 48, BR_COUNT = 50 };
constexpr uint32_t OFF_EPOCH = OFF_BAR + 8 * BR_COUNT;
enum { M_X, M_W128, M_W64, M_WR, M_U, M_WO, M_O64, M_O16, M_SA, M_OUT, M_COUNT };

__device__ __forceinline__ long long clk64() { long long t; asm volatile("mov.u64 %0, %%clock64;" : "=l"(t) :: "memory"); return t; }
__device__ __forceinline__ uint32_t smem_u32(const void* p) { return (uint32_t)__cvta_generic_to_shared(p); }
__host__ __device__ constexpr uint64_t mkdesc(uint32_t addr, uint32_t lbo, uint32_t sbo, uint32_t swz) {
  return (uint64_t)((addr & 0x3FFFF) >> 4) | ((uint64_t)(lbo >> 4) << 16) | ((uint64_t)(sbo >> 4) << 32) | ((uint64_t)swz << 62);
}
__device__ __forceinline__ uint64_t desc2(uint32_t lo, uint32_t hi) { uint64_t d; asm("mov.b64 %0, {%1, %2};" : "=l"(d) : "r"(lo), "r"(hi)); return d; }
__device__ __forceinline__ void mbar_init(uint32_t bar, uint32_t cnt) { asm volatile("mbarrier.init.shared::cta.b64 [%0], %1;" :: "r"(bar), "r"(cnt) : "memory"); }
__device__ __forceinline__ void mbar_expect_tx(uint32_t bar, uint32_t bytes) { asm volatile("mbarrier.arrive.expect_tx.shared::cta.b64 _, [%0], %1;" :: "r"(bar), "r"(bytes) : "memory"); }
__device__ __forceinline__ void mbar_arrive(uint32_t bar) { asm volatile("mbarrier.arrive.shared::cta.b64 _, [%0];" :: "r"(bar) : "memory"); }
__device__ __forceinline__ void mbar_wait(uint32_t bar, uint32_t parity) {
  asm volatile("{\n.reg .pred p;\n.reg .u32 c;\nmov.u32 c, 0;\n"
    "WL:\nmbarrier.try_wait.parity.shared::cta.b64 p, [%0], %1;\n@p bra WD;\n"
    "add.u32 c, c, 1;\nsetp.lt.u32 p, c, 200000;\n@p bra WL;\nWD:\n}" :: "r"(bar), "r"(parity) : "memory");
}
__device__ __forceinline__ void poll_all(const unsigned* p, unsigned val) {
  asm volatile("{\n.reg .pred p;\n.reg .u32 c, v;\nmov.u32 c, 0;\n"
    "PL:\nld.relaxed.gpu.global.u32 v, [%0];\nsetp.eq.u32 p, v, %1;\nvote.sync.all.pred p, p, 0xffffffff;\n@p bra PD;\n"
    "add.u32 c, c, 1;\nsetp.lt.u32 p, c, 100000;\n@p bra PL;\nPD:\n}" :: "l"(p), "r"(val) : "memory");
}
__device__ __forceinline__ void poll_all_acq(const unsigned* p, unsigned val) {
  asm volatile("{\n.reg .pred p;\n.reg .u32 c, v;\nmov.u32 c, 0;\n"
    "PL:\nld.acquire.gpu.global.u32 v, [%0];\nsetp.eq.u32 p, v, %1;\nvote.sync.all.pred p, p, 0xffffffff;\n@p bra PD;\n"
    "add.u32 c, c, 1;\nsetp.lt.u32 p, c, 100000;\n@p bra PL;\nPD:\n}" :: "l"(p), "r"(val) : "memory");
}
__device__ __forceinline__ unsigned poll_bit(const unsigned* p, unsigned val, unsigned mask) {
  unsigned bal;
  asm volatile("{\n.reg .pred p;\n.reg .u32 c, v;\nmov.u32 c, 0;\n"
    "PL:\nld.relaxed.gpu.global.u32 v, [%1];\nsetp.eq.u32 p, v, %2;\nvote.sync.ballot.b32 %0, p, 0xffffffff;\n"
    "and.b32 v, %0, %3;\nsetp.ne.u32 p, v, 0;\n@p bra PD;\n"
    "add.u32 c, c, 1;\nsetp.lt.u32 p, c, 100000;\n@p bra PL;\nPD:\n}" : "=&r"(bal) : "l"(p), "r"(val), "r"(mask) : "memory");
  return bal;
}
__device__ __forceinline__ void fix128_w0(uint32_t* v, const void* p, uint32_t tag, uint32_t mask) {
  asm volatile("{\n.reg .pred p;\n.reg .u32 c, x;\n.reg .b128 t;\n.reg .b64 lo, hi;\nmov.u32 c, 0;\n"
    "FL:\nxor.b32 x, %0, %5;\nand.b32 x, x, %6;\nsetp.eq.u32 p, x, 0;\n@p bra FD;\n"
    "ld.relaxed.gpu.global.b128 t, [%4];\nmov.b128 {lo, hi}, t;\nmov.b64 {%0, %1}, lo;\nmov.b64 {%2, %3}, hi;\n"
    "add.u32 c, c, 1;\nsetp.lt.u32 p, c, 100000;\n@p bra FL;\nFD:\n}"
    : "+r"(v[0]), "+r"(v[1]), "+r"(v[2]), "+r"(v[3]) : "l"(p), "r"(tag), "r"(mask) : "memory");
}
__device__ __forceinline__ void fix128_w3(uint32_t* v, const void* p, uint32_t tag, uint32_t mask) {
  asm volatile("{\n.reg .pred p;\n.reg .u32 c, x;\n.reg .b128 t;\n.reg .b64 lo, hi;\nmov.u32 c, 0;\n"
    "FL:\nxor.b32 x, %3, %5;\nand.b32 x, x, %6;\nsetp.eq.u32 p, x, 0;\n@p bra FD;\n"
    "ld.relaxed.gpu.global.b128 t, [%4];\nmov.b128 {lo, hi}, t;\nmov.b64 {%0, %1}, lo;\nmov.b64 {%2, %3}, hi;\n"
    "add.u32 c, c, 1;\nsetp.lt.u32 p, c, 100000;\n@p bra FL;\nFD:\n}"
    : "+r"(v[0]), "+r"(v[1]), "+r"(v[2]), "+r"(v[3]) : "l"(p), "r"(tag), "r"(mask) : "memory");
}
__device__ __forceinline__ void fence_acq() { asm volatile("fence.acq_rel.gpu;" ::: "memory"); }
__device__ __forceinline__ bool elect_one() {
  uint32_t p; asm volatile("{\n.reg .pred P;\nelect.sync _|P, 0xffffffff;\nselp.u32 %0, 1, 0, P;\n}" : "=r"(p)); return p;
}
__device__ __forceinline__ void bar_sync(int id, int n) { asm volatile("bar.sync %0, %1;" :: "r"(id), "r"(n) : "memory"); }
__device__ __forceinline__ void fence_async() { asm volatile("fence.proxy.async.shared::cta;" ::: "memory"); }
__device__ __forceinline__ void fence_async_g() { asm volatile("fence.proxy.async.global;" ::: "memory"); }
__device__ __forceinline__ void tma2d(uint32_t dst, const CUtensorMap* m, uint32_t bar, int c0, int c1) {
  asm volatile("cp.async.bulk.tensor.2d.shared::cluster.global.mbarrier::complete_tx::bytes [%0], [%1, {%3, %4}], [%2];"
    :: "r"(dst), "l"(m), "r"(bar), "r"(c0), "r"(c1) : "memory");
}
__device__ __forceinline__ void tma3d(uint32_t dst, const CUtensorMap* m, uint32_t bar, int c0, int c1, int c2) {
  asm volatile("cp.async.bulk.tensor.3d.shared::cluster.global.mbarrier::complete_tx::bytes [%0], [%1, {%3, %4, %5}], [%2];"
    :: "r"(dst), "l"(m), "r"(bar), "r"(c0), "r"(c1), "r"(c2) : "memory");
}
__device__ __forceinline__ void tma4d(uint32_t dst, const CUtensorMap* m, uint32_t bar, int c0, int c1, int c2, int c3) {
  asm volatile("cp.async.bulk.tensor.4d.shared::cluster.global.mbarrier::complete_tx::bytes [%0], [%1, {%3, %4, %5, %6}], [%2];"
    :: "r"(dst), "l"(m), "r"(bar), "r"(c0), "r"(c1), "r"(c2), "r"(c3) : "memory");
}
__device__ __forceinline__ void tma2d_st(const CUtensorMap* m, uint32_t src, int c0, int c1) {
  asm volatile("cp.async.bulk.tensor.2d.global.shared::cta.bulk_group [%0, {%2, %3}], [%1];"
    :: "l"(m), "r"(src), "r"(c0), "r"(c1) : "memory");
}
__device__ __forceinline__ void bulk_ld(uint32_t dst, const void* src, uint32_t bytes, uint32_t bar) {
  asm volatile("cp.async.bulk.shared::cluster.global.mbarrier::complete_tx::bytes [%0], [%1], %2, [%3];"
    :: "r"(dst), "l"(src), "r"(bytes), "r"(bar) : "memory");
}
__device__ __forceinline__ void bulk_st(void* dst, uint32_t src, uint32_t bytes) {
  asm volatile("cp.async.bulk.global.shared::cta.bulk_group [%0], [%1], %2;" :: "l"(dst), "r"(src), "r"(bytes) : "memory");
}
__device__ __forceinline__ void bulk_commit() { asm volatile("cp.async.bulk.commit_group;" ::: "memory"); }
__device__ __forceinline__ void bulk_wait0() { asm volatile("cp.async.bulk.wait_group 0;" ::: "memory"); }
__device__ __forceinline__ void bulk_wait0_read() { asm volatile("cp.async.bulk.wait_group.read 0;" ::: "memory"); }
__device__ __forceinline__ unsigned ld_rlx(const unsigned* p) { unsigned v; asm volatile("ld.relaxed.gpu.global.u32 %0, [%1];" : "=r"(v) : "l"(p) : "memory"); return v; }
__device__ __forceinline__ unsigned ld_acq(const unsigned* p) { unsigned v; asm volatile("ld.acquire.gpu.global.u32 %0, [%1];" : "=r"(v) : "l"(p) : "memory"); return v; }
__device__ __forceinline__ void st_rlx(unsigned* p, unsigned v) { asm volatile("st.relaxed.gpu.global.u32 [%0], %1;" :: "l"(p), "r"(v) : "memory"); }
__device__ __forceinline__ void st_rel(unsigned* p, unsigned v) { asm volatile("st.release.gpu.global.u32 [%0], %1;" :: "l"(p), "r"(v) : "memory"); }
__device__ __forceinline__ void ld128_rlx(uint32_t* v, const void* p) {
  asm volatile("{\n.reg .b128 t;\n.reg .b64 lo, hi;\nld.relaxed.gpu.global.b128 t, [%4];\nmov.b128 {lo, hi}, t;\n"
    "mov.b64 {%0, %1}, lo;\nmov.b64 {%2, %3}, hi;\n}" : "=r"(v[0]), "=r"(v[1]), "=r"(v[2]), "=r"(v[3]) : "l"(p) : "memory");
}
__device__ __forceinline__ void st128_rlx(void* p, const uint32_t* v) {
  asm volatile("{\n.reg .b128 t;\n.reg .b64 lo, hi;\nmov.b64 lo, {%1, %2};\nmov.b64 hi, {%3, %4};\nmov.b128 t, {lo, hi};\n"
    "st.relaxed.gpu.global.b128 [%0], t;\n}" :: "l"(p), "r"(v[0]), "r"(v[1]), "r"(v[2]), "r"(v[3]) : "memory");
}
__device__ __forceinline__ uint32_t lds32(uint32_t a) { uint32_t v; asm volatile("ld.shared.u32 %0, [%1];" : "=r"(v) : "r"(a) : "memory"); return v; }
__device__ __forceinline__ uint32_t lds32v(uint32_t a) { uint32_t v; asm volatile("ld.volatile.shared.u32 %0, [%1];" : "=r"(v) : "r"(a) : "memory"); return v; }
__device__ __forceinline__ uint32_t cpa(uint32_t a, uint32_t one) { uint32_t v; asm volatile("mul.lo.u32 %0, %1, %2;" : "=r"(v) : "r"(a), "r"(one)); return v; }
__device__ __forceinline__ uint32_t cpb(uint32_t a, uint32_t zero) { uint32_t v; asm volatile("or.b32 %0, %1, %2;" : "=r"(v) : "r"(a), "r"(zero)); return v; }
__device__ __forceinline__ uint32_t lds16(uint32_t a) { uint16_t v; asm volatile("ld.shared.u16 %0, [%1];" : "=h"(v) : "r"(a) : "memory"); return v; }
__device__ __forceinline__ float ldsf(uint32_t a) { float v; asm volatile("ld.shared.f32 %0, [%1];" : "=f"(v) : "r"(a) : "memory"); return v; }
__device__ __forceinline__ void lds128(uint32_t* v, uint32_t a) { asm volatile("ld.shared.v4.u32 {%0,%1,%2,%3}, [%4];" : "=r"(v[0]), "=r"(v[1]), "=r"(v[2]), "=r"(v[3]) : "r"(a) : "memory"); }
__device__ __forceinline__ void sts32(uint32_t a, uint32_t v) { asm volatile("st.shared.u32 [%0], %1;" :: "r"(a), "r"(v) : "memory"); }
__device__ __forceinline__ void sts16(uint32_t a, uint32_t v) { asm volatile("st.shared.u16 [%0], %1;" :: "r"(a), "h"((uint16_t)v) : "memory"); }
__device__ __forceinline__ void sts64f(uint32_t a, float x, float y) { asm volatile("st.shared.v2.f32 [%0], {%1,%2};" :: "r"(a), "f"(x), "f"(y) : "memory"); }
__device__ __forceinline__ void sts128(uint32_t a, uint32_t x, uint32_t y, uint32_t z, uint32_t w) { asm volatile("st.shared.v4.u32 [%0], {%1,%2,%3,%4};" :: "r"(a), "r"(x), "r"(y), "r"(z), "r"(w) : "memory"); }
__device__ __forceinline__ void stsm4(uint32_t a, uint32_t r0, uint32_t r1, uint32_t r2, uint32_t r3) {
  asm volatile("stmatrix.sync.aligned.m8n8.x4.shared.b16 [%0], {%1,%2,%3,%4};" :: "r"(a), "r"(r0), "r"(r1), "r"(r2), "r"(r3) : "memory");
}
__device__ __forceinline__ void stsm4t(uint32_t a, uint32_t r0, uint32_t r1, uint32_t r2, uint32_t r3) {
  asm volatile("stmatrix.sync.aligned.m8n8.x4.trans.shared.b16 [%0], {%1,%2,%3,%4};" :: "r"(a), "r"(r0), "r"(r1), "r"(r2), "r"(r3) : "memory");
}
__device__ __forceinline__ void ldsm4t(uint32_t* r, uint32_t a) {
  asm volatile("ldmatrix.sync.aligned.m8n8.x4.trans.shared.b16 {%0,%1,%2,%3}, [%4];" : "=r"(r[0]), "=r"(r[1]), "=r"(r[2]), "=r"(r[3]) : "r"(a) : "memory");
}
__device__ __forceinline__ void ldsm4(uint32_t* r, uint32_t a) {
  asm volatile("ldmatrix.sync.aligned.m8n8.x4.shared.b16 {%0,%1,%2,%3}, [%4];" : "=r"(r[0]), "=r"(r[1]), "=r"(r[2]), "=r"(r[3]) : "r"(a) : "memory");
}
__device__ __forceinline__ void mma16816(float* d, const uint32_t* a, const uint32_t* b) {
  asm volatile("mma.sync.aligned.m16n8k16.row.col.f32.bf16.bf16.f32 {%0,%1,%2,%3}, {%4,%5,%6,%7}, {%8,%9}, {%0,%1,%2,%3};"
    : "+f"(d[0]), "+f"(d[1]), "+f"(d[2]), "+f"(d[3]) : "r"(a[0]), "r"(a[1]), "r"(a[2]), "r"(a[3]), "r"(b[0]), "r"(b[1]));
}
__device__ __forceinline__ uint32_t pack2(float lo, float hi) { uint32_t r; asm("cvt.rn.bf16x2.f32 %0, %1, %2;" : "=r"(r) : "f"(hi), "f"(lo)); return r; }
__device__ __forceinline__ uint32_t packh(float lo, float hi) { uint32_t r; asm("cvt.rn.f16x2.f32 %0, %1, %2;" : "=r"(r) : "f"(hi), "f"(lo)); return r; }
__device__ __forceinline__ uint32_t hcmul(uint32_t x, uint32_t zp, uint32_t zq) {
  const __half2 xx = *reinterpret_cast<__half2*>(&x);
  const __half2 r = __hfma2(__high2half2(xx), *reinterpret_cast<__half2*>(&zq), __hmul2(__low2half2(xx), *reinterpret_cast<__half2*>(&zp)));
  return *reinterpret_cast<const uint32_t*>(&r);
}
__device__ __forceinline__ void hcm2(uint32_t xr, uint32_t xi, uint32_t z, uint32_t& pr, uint32_t& pi) {
  const __half2 a = *reinterpret_cast<__half2*>(&xr), b = *reinterpret_cast<__half2*>(&xi), zz = *reinterpret_cast<__half2*>(&z);
  const __half2 re = __hfma2(__hneg2(b), __high2half2(zz), __hmul2(a, __low2half2(zz)));
  const __half2 im = __hfma2(a, __high2half2(zz), __hmul2(b, __low2half2(zz)));
  pr = *reinterpret_cast<const uint32_t*>(&re); pi = *reinterpret_cast<const uint32_t*>(&im);
}
__device__ __forceinline__ void sts64(uint32_t a, uint32_t x, uint32_t y) { asm volatile("st.shared.v2.u32 [%0], {%1,%2};" :: "r"(a), "r"(x), "r"(y) : "memory"); }
__device__ __forceinline__ void lds64(uint32_t* v, uint32_t a) { asm volatile("ld.shared.v2.u32 {%0,%1}, [%2];" : "=r"(v[0]), "=r"(v[1]) : "r"(a) : "memory"); }
__device__ __forceinline__ float bf_lo(uint32_t v) { return __uint_as_float(v << 16); }
__device__ __forceinline__ float bf_hi(uint32_t v) { return __uint_as_float(v & 0xffff0000u); }
__device__ __forceinline__ float bf_round(float x) { return bf_lo(pack2(x, 0.f)); }
__device__ __forceinline__ float ex2(float x) { float r; asm("ex2.approx.ftz.f32 %0, %1;" : "=f"(r) : "f"(x)); return r; }
__device__ __forceinline__ float phi(float t, float l2e = 1.44269504089f) {
  float e = ex2(t * l2e) + 1e-6f;
  asm("{\n.reg .pred p;\nsetp.gt.f32 p, %1, 0f00000000;\n@p add.f32 %0, %1, 0f3F800008;\n}" : "+f"(e) : "f"(t));
  return e;
}
__device__ __forceinline__ void wg_fence() { asm volatile("wgmma.fence.sync.aligned;" ::: "memory"); }
__device__ __forceinline__ void wg_commit() { asm volatile("wgmma.commit_group.sync.aligned;" ::: "memory"); }
template <int N> __device__ __forceinline__ void wg_wait() { asm volatile("wgmma.wait_group.sync.aligned %0;" :: "n"(N) : "memory"); }
template <int N> __device__ __forceinline__ void pin(float* a) {
  #pragma unroll
  for (int i = 0; i < N; i++) asm volatile("" : "+f"(a[i]) :: "memory");
}
__device__ __forceinline__ int rtid() { int t; asm volatile("mov.u32 %0, %%tid.x;" : "=r"(t)); return t; }
__device__ __forceinline__ int opaque(int v) { asm volatile("" : "+r"(v)); return v; }
template <int N> __device__ __forceinline__ void zero(float* a) {
  #pragma unroll
  for (int i = 0; i < N; i++) asm volatile("mov.b32 %0, 0;" : "=f"(a[i]));
}
template <int N> __device__ __forceinline__ void pinu(uint32_t* a) {
  #pragma unroll
  for (int i = 0; i < N; i++) asm volatile("" : "+r"(a[i]) :: "memory");
}
__device__ __forceinline__ void cexp_t(float lg2mag, float turns, float& re, float& im) {
  float m = ex2(lg2mag);
  float fr = (turns - __fadd_rn(__fadd_rn(turns, 12582912.f), -12582912.f)) * 6.283185307f;
  re = m * __cosf(fr); im = m * __sinf(fr);
}
__device__ __forceinline__ void cmul(float ar, float ai, float br, float bi, float& cr, float& ci) {
  cr = fmaf(ar, br, -ai * bi); ci = fmaf(ar, bi, ai * br);
}

__device__ __forceinline__ void wg_ss192_tb(float* d, uint64_t da, uint64_t db, int scale_d) {
  asm volatile("{\n.reg .pred p;\nsetp.ne.b32 p, %98, 0;\n"
    "wgmma.mma_async.sync.aligned.m64n192k16.f32.bf16.bf16 "
    "{%0, %1, %2, %3, %4, %5, %6, %7, %8, %9, %10, %11, %12, %13, %14, %15, %16, %17, %18, %19, %20, %21, %22, %23, %24, %25, %26, %27, %28, %29, %30, %31, %32, %33, %34, %35, %36, %37, %38, %39, %40, %41, %42, %43, %44, %45, %46, %47, %48, %49, %50, %51, %52, %53, %54, %55, %56, %57, %58, %59, %60, %61, %62, %63, %64, %65, %66, %67, %68, %69, %70, %71, %72, %73, %74, %75, %76, %77, %78, %79, %80, %81, %82, %83, %84, %85, %86, %87, %88, %89, %90, %91, %92, %93, %94, %95}, %96, %97, p, 1, 1, 0, 1;\n}\n"
    : "+f"(d[0]), "+f"(d[1]), "+f"(d[2]), "+f"(d[3]), "+f"(d[4]), "+f"(d[5]), "+f"(d[6]), "+f"(d[7]), "+f"(d[8]), "+f"(d[9]), "+f"(d[10]), "+f"(d[11]), "+f"(d[12]), "+f"(d[13]), "+f"(d[14]), "+f"(d[15]), "+f"(d[16]), "+f"(d[17]), "+f"(d[18]), "+f"(d[19]), "+f"(d[20]), "+f"(d[21]), "+f"(d[22]), "+f"(d[23]), "+f"(d[24]), "+f"(d[25]), "+f"(d[26]), "+f"(d[27]), "+f"(d[28]), "+f"(d[29]), "+f"(d[30]), "+f"(d[31]), "+f"(d[32]), "+f"(d[33]), "+f"(d[34]), "+f"(d[35]), "+f"(d[36]), "+f"(d[37]), "+f"(d[38]), "+f"(d[39]), "+f"(d[40]), "+f"(d[41]), "+f"(d[42]), "+f"(d[43]), "+f"(d[44]), "+f"(d[45]), "+f"(d[46]), "+f"(d[47]), "+f"(d[48]), "+f"(d[49]), "+f"(d[50]), "+f"(d[51]), "+f"(d[52]), "+f"(d[53]), "+f"(d[54]), "+f"(d[55]), "+f"(d[56]), "+f"(d[57]), "+f"(d[58]), "+f"(d[59]), "+f"(d[60]), "+f"(d[61]), "+f"(d[62]), "+f"(d[63]), "+f"(d[64]), "+f"(d[65]), "+f"(d[66]), "+f"(d[67]), "+f"(d[68]), "+f"(d[69]), "+f"(d[70]), "+f"(d[71]), "+f"(d[72]), "+f"(d[73]), "+f"(d[74]), "+f"(d[75]), "+f"(d[76]), "+f"(d[77]), "+f"(d[78]), "+f"(d[79]), "+f"(d[80]), "+f"(d[81]), "+f"(d[82]), "+f"(d[83]), "+f"(d[84]), "+f"(d[85]), "+f"(d[86]), "+f"(d[87]), "+f"(d[88]), "+f"(d[89]), "+f"(d[90]), "+f"(d[91]), "+f"(d[92]), "+f"(d[93]), "+f"(d[94]), "+f"(d[95])
    : "l"(da), "l"(db), "r"(scale_d));
}
__device__ __forceinline__ void wg_ss48_tb(float* d, uint64_t da, uint64_t db, int scale_d) {
  asm volatile("{\n.reg .pred p;\nsetp.ne.b32 p, %26, 0;\n"
    "wgmma.mma_async.sync.aligned.m64n48k16.f32.bf16.bf16 "
    "{%0, %1, %2, %3, %4, %5, %6, %7, %8, %9, %10, %11, %12, %13, %14, %15, %16, %17, %18, %19, %20, %21, %22, %23}, %24, %25, p, 1, 1, 0, 1;\n}\n"
    : "+f"(d[0]), "+f"(d[1]), "+f"(d[2]), "+f"(d[3]), "+f"(d[4]), "+f"(d[5]), "+f"(d[6]), "+f"(d[7]), "+f"(d[8]), "+f"(d[9]), "+f"(d[10]), "+f"(d[11]), "+f"(d[12]), "+f"(d[13]), "+f"(d[14]), "+f"(d[15]), "+f"(d[16]), "+f"(d[17]), "+f"(d[18]), "+f"(d[19]), "+f"(d[20]), "+f"(d[21]), "+f"(d[22]), "+f"(d[23])
    : "l"(da), "l"(db), "r"(scale_d));
}
__device__ __forceinline__ void wg_ss48_tt(float* d, uint64_t da, uint64_t db, int scale_d) {
  asm volatile("{\n.reg .pred p;\nsetp.ne.b32 p, %26, 0;\n"
    "wgmma.mma_async.sync.aligned.m64n48k16.f32.bf16.bf16 "
    "{%0, %1, %2, %3, %4, %5, %6, %7, %8, %9, %10, %11, %12, %13, %14, %15, %16, %17, %18, %19, %20, %21, %22, %23}, %24, %25, p, 1, 1, 1, 1;\n}\n"
    : "+f"(d[0]), "+f"(d[1]), "+f"(d[2]), "+f"(d[3]), "+f"(d[4]), "+f"(d[5]), "+f"(d[6]), "+f"(d[7]), "+f"(d[8]), "+f"(d[9]), "+f"(d[10]), "+f"(d[11]), "+f"(d[12]), "+f"(d[13]), "+f"(d[14]), "+f"(d[15]), "+f"(d[16]), "+f"(d[17]), "+f"(d[18]), "+f"(d[19]), "+f"(d[20]), "+f"(d[21]), "+f"(d[22]), "+f"(d[23])
    : "l"(da), "l"(db), "r"(scale_d));
}
__device__ __forceinline__ void wg_rs88_tb(float* d, const uint32_t* a, uint64_t db, int scale_d) {
  asm volatile("{\n.reg .pred p;\nsetp.ne.b32 p, %49, 0;\n"
    "wgmma.mma_async.sync.aligned.m64n88k16.f32.bf16.bf16 "
    "{%0, %1, %2, %3, %4, %5, %6, %7, %8, %9, %10, %11, %12, %13, %14, %15, %16, %17, %18, %19, %20, %21, %22, %23, %24, %25, %26, %27, %28, %29, %30, %31, %32, %33, %34, %35, %36, %37, %38, %39, %40, %41, %42, %43}, {%44, %45, %46, %47}, %48, p, 1, 1, 1;\n}\n"
    : "+f"(d[0]), "+f"(d[1]), "+f"(d[2]), "+f"(d[3]), "+f"(d[4]), "+f"(d[5]), "+f"(d[6]), "+f"(d[7]), "+f"(d[8]), "+f"(d[9]), "+f"(d[10]), "+f"(d[11]), "+f"(d[12]), "+f"(d[13]), "+f"(d[14]), "+f"(d[15]), "+f"(d[16]), "+f"(d[17]), "+f"(d[18]), "+f"(d[19]), "+f"(d[20]), "+f"(d[21]), "+f"(d[22]), "+f"(d[23]), "+f"(d[24]), "+f"(d[25]), "+f"(d[26]), "+f"(d[27]), "+f"(d[28]), "+f"(d[29]), "+f"(d[30]), "+f"(d[31]), "+f"(d[32]), "+f"(d[33]), "+f"(d[34]), "+f"(d[35]), "+f"(d[36]), "+f"(d[37]), "+f"(d[38]), "+f"(d[39]), "+f"(d[40]), "+f"(d[41]), "+f"(d[42]), "+f"(d[43])
    : "r"(a[0]), "r"(a[1]), "r"(a[2]), "r"(a[3]), "l"(db), "r"(scale_d));
}
__device__ __forceinline__ void wg_ss80_tb(float* d, uint64_t da, uint64_t db, int scale_d) {
  asm volatile("{\n.reg .pred p;\nsetp.ne.b32 p, %42, 0;\n"
    "wgmma.mma_async.sync.aligned.m64n80k16.f32.bf16.bf16 "
    "{%0, %1, %2, %3, %4, %5, %6, %7, %8, %9, %10, %11, %12, %13, %14, %15, %16, %17, %18, %19, %20, %21, %22, %23, %24, %25, %26, %27, %28, %29, %30, %31, %32, %33, %34, %35, %36, %37, %38, %39}, %40, %41, p, 1, 1, 0, 1;\n}\n"
    : "+f"(d[0]), "+f"(d[1]), "+f"(d[2]), "+f"(d[3]), "+f"(d[4]), "+f"(d[5]), "+f"(d[6]), "+f"(d[7]), "+f"(d[8]), "+f"(d[9]), "+f"(d[10]), "+f"(d[11]), "+f"(d[12]), "+f"(d[13]), "+f"(d[14]), "+f"(d[15]), "+f"(d[16]), "+f"(d[17]), "+f"(d[18]), "+f"(d[19]), "+f"(d[20]), "+f"(d[21]), "+f"(d[22]), "+f"(d[23]), "+f"(d[24]), "+f"(d[25]), "+f"(d[26]), "+f"(d[27]), "+f"(d[28]), "+f"(d[29]), "+f"(d[30]), "+f"(d[31]), "+f"(d[32]), "+f"(d[33]), "+f"(d[34]), "+f"(d[35]), "+f"(d[36]), "+f"(d[37]), "+f"(d[38]), "+f"(d[39])
    : "l"(da), "l"(db), "r"(scale_d));
}
__device__ __forceinline__ void wg_ss48_tt_h(float* d, uint64_t da, uint64_t db, int scale_d) {
  asm volatile("{\n.reg .pred p;\nsetp.ne.b32 p, %26, 0;\n"
    "wgmma.mma_async.sync.aligned.m64n48k16.f32.f16.f16 "
    "{%0, %1, %2, %3, %4, %5, %6, %7, %8, %9, %10, %11, %12, %13, %14, %15, %16, %17, %18, %19, %20, %21, %22, %23}, %24, %25, p, 1, 1, 1, 1;\n}\n"
    : "+f"(d[0]), "+f"(d[1]), "+f"(d[2]), "+f"(d[3]), "+f"(d[4]), "+f"(d[5]), "+f"(d[6]), "+f"(d[7]), "+f"(d[8]), "+f"(d[9]), "+f"(d[10]), "+f"(d[11]), "+f"(d[12]), "+f"(d[13]), "+f"(d[14]), "+f"(d[15]), "+f"(d[16]), "+f"(d[17]), "+f"(d[18]), "+f"(d[19]), "+f"(d[20]), "+f"(d[21]), "+f"(d[22]), "+f"(d[23])
    : "l"(da), "l"(db), "r"(scale_d));
}

struct Params {
  const __nv_bfloat16 *par[4], *logdt, *dskip, *u, *wo;
  CUtensorMap m[M_COUNT];
};

#define CHUNK(i) ((i) == 0 ? c : ((i) == 7 ? (c ^ 1) : (((c & 6) + 1 + (i)) & 7)))
#define FLAG(kind, rr, cc) (&g_flag[((kind) * 128 + (rr) * 8 + (cc)) * 32])
#define SLOT(i) ((i) == 0 || (i) == 2 ? OFF_EXTRA : OFF_BLK - 256 + ((i) == 1 || (i) == 7 ? 0 : (i) - 2) * BLK)
__device__ __forceinline__ void load_quad(uint32_t* A, uint32_t addr) {
  A[0] = lds32v(addr); A[1] = lds32v(addr + 32); A[2] = lds32v(addr - 32); A[3] = lds32v(addr);
}

__device__ __forceinline__ bool y_transpose(uint32_t sb, int w5, int lane, uint32_t ytag) {
  const int mi = lane >> 3, rw = lane & 7;
  const uint32_t sa = sb + OFF_EXTRA + (w5 * 16 + rw) * 128 + ((mi ^ rw) << 4), da = sb + SLOT(3) + (8 * mi + rw) * 160 + w5 * 32;
  const uint32_t ym = lane < 4 ? 0x10001u : 0u;
  bar_sync(7, 160);
  uint32_t v[8][4], bad = 0;
  #pragma unroll
  for (int q = 0; q < 8; q++) ldsm4t(v[q], (sa ^ ((q & 1) * 64 + ((q >> 1) & 1) * 16)) + ((q >> 1) & 1) * 10240 + (q >> 2) * 1024);
  #pragma unroll
  for (int q = 0; q < 8; q++) {
    bad |= (v[q][0] ^ ytag) | (v[q][2] ^ ytag);
    stsm4(da + (q & 3) * 5120 + (q >> 2) * 16, v[q][0] & ~ym, v[q][1], v[q][2] & ~ym, v[q][3]);
  }
  fence_async();
  uint32_t any;
  asm volatile("{\n.reg .pred p;\nsetp.ne.u32 p, %1, 0;\nbarrier.red.or.pred p, 7, 160, p;\nselp.u32 %0, 1, 0, p;\n}" : "=r"(any) : "r"(bad & ym) : "memory");
  return any;
}

__global__ void __launch_bounds__(512, 1) fused_kernel(const __grid_constant__ Params prm) {
  extern __shared__ unsigned char smem_raw[];
  const uint32_t sb = __shfl_sync(0xffffffff, smem_u32(smem_raw), 0);
  const int tid = threadIdx.x, lane = tid & 31;
  const int warp = __shfl_sync(0xffffffff, tid >> 5, 0), wg = warp >> 2, w4 = warp & 3;
  const int cta = blockIdx.x, r = cta >> 3, c = cta & 7;
  if ((sb & 0xffffffu) != SB0) return;
#define BAR(i) (sb + OFF_BAR + 8 * (i))
  const bool sw64 = ((c + 1) & 2) != 0;

  if (wg == 3) {
    if (warp == 13 && elect_one()) {
      #pragma unroll
      for (int i = M_W128; i <= M_U; i++) asm volatile("prefetch.tensormap [%0];" :: "l"(&prm.m[i]) : "memory");
    }
    asm volatile("setmaxnreg.dec.sync.aligned.u32 56;");
    const int tid = rtid(), lane = tid & 31;
    if (warp == 12) {
      if (elect_one()) {
        #pragma unroll
        for (int i = 0; i < 5; i++) mbar_init(BAR(BR_FULL + i), 1);
        asm volatile("fence.mbarrier_init.release.cluster;" ::: "memory");
      }
      {
        const CUtensorMap* mwp = &prm.m[sw64 ? M_W64 : M_W128];
        const int mcol = (c * 80 + (c & 1) * 16) >> (sw64 ? 5 : 6), rcol = c * 80 + ((c & 1) ? 0 : 64);
        uint32_t s = 0, ph = 1, xs = 0;
        #pragma unroll 1
        for (int kb = 0; kb < 20; kb++) {
          if (kb == 1) asm volatile("bar.arrive 0, 512;" ::: "memory");
          if (kb == 4) { bar_sync(6, 128); if (EN_SSM) mbar_wait(BAR(BR_KS), 0); }
          if (kb >= 5) mbar_wait(BAR(BR_EMPTY) + 8 * s, ph);
          if (EN_ATT && elect_one()) {
            const uint32_t st = sb + s * W_SLOT, fb = BAR(BR_FULL) + 8 * s;
            mbar_expect_tx(fb, (kb & 1) ? W_SLOT : W_SLOT + 16384);
            if (!(kb & 1)) tma2d(sb + OFF_X + xs, &prm.m[M_X], fb, kb * 32, r * 128);
            tma4d(st, mwp, fb, 0, kb * 32, mcol, 0);
            tma3d(st + 12288, &prm.m[M_WR], fb, rcol, kb * 32, 0);
          }
          if (kb < 4 && lane == 0) TS(24 + kb);
          if (kb == 14 && elect_one()) asm volatile("cp.async.bulk.prefetch.L2.global [%0], 6400;" :: "l"(prm.wo + cta * 3200) : "memory");
          if (!EN_ATT && kb == 4) break;
          if (++s == 5) { s = 0; ph ^= 1; }
          if (kb & 1) { xs += 16384; if (xs == 49152) xs = 0; }
        }
      }
      if (EN_ATT) {
      mbar_wait(BAR(BR_EPOCH), 0);
      const unsigned epoch = lds32(sb + OFF_EPOCH);
      const unsigned* fo = FLAG(3, r, lane & 7);
      unsigned seen = __ballot_sync(0xffffffff, ld_rlx(lane < 16 ? fo : FLAG(0, lane & 15, c)) == epoch) & 0xffu;
      mbar_wait(BAR(BR_GEMM), 0);
      if (elect_one()) {
        mbar_expect_tx(BAR(BR_WO), 10240);
        tma2d(sb, &prm.m[M_WO], BAR(BR_WO), c * 64, c * 80);
        mbar_expect_tx(BAR(BR_KVP), 61440);
        mbar_expect_tx(BAR(BR_WO + 1), 7 * 10240);
      }
      {
        uint32_t ds = sb + OFF_WOR + (lane >> 3) * 128 + (((lane & 7) ^ (lane >> 3)) << 4);
        #pragma unroll 1
        for (int h = 0; h < 2; h++) {
          const int i = (lane & 6) + h;
          const char* gs = reinterpret_cast<const char*>(prm.wo) + (size_t)((lane >> 3) + CHUNK(i) * 80) * 1280 + 1024 + c * 32 + (lane & 1) * 16;
          #pragma unroll 2
          for (int q = 0; q < 20; q++) {
            asm volatile("cp.async.cg.shared.global [%0], [%1], 16;" :: "r"(ds), "l"(gs) : "memory");
            ds = (ds + 512) ^ 64; gs += 5120;
          }
        }
      }
      mbar_wait(BAR(BR_PUB), 0);
      poll_all(FLAG(0, lane & 15, c), epoch);
      if (elect_one()) { TS(23); bulk_ld(sb + OFF_KVP, &g_kvp[c * 16 * 240], 61440, BAR(BR_KVP)); }
      asm volatile("cp.async.wait_all;" ::: "memory");
      fence_async();
      mbar_arrive(BAR(BR_WO));
      mbar_wait(BAR(BR_SUM), 0);
      if (elect_one()) {
        #pragma unroll 1
        for (int i = 1; i < 8; i++) tma2d(sb + i * 10240, &prm.m[M_WO], BAR(BR_WO + 1), c * 64, CHUNK(i) * 80);
      }
      mbar_wait(BAR(BR_OSTG), 0);
      if (elect_one()) {
        bulk_st(&g_o[cta * 1280], sb + OFF_EXTRA, 20480);
        bulk_commit();
        bulk_wait0();
        st_rlx(FLAG(3, r, c), epoch);
        TS(20);
      }
      __syncwarp();
      #pragma unroll 1
      for (int i = 1; i < 8; i++) {
        const int src = CHUNK(i);
        if (!((seen >> src) & 1)) seen = poll_bit(fo, epoch, 1u << src);
        if (i == 2 || i == 7) mbar_wait(BAR(BR_OEMPTY) + 8 * (i & 1), 0);
        if (EN_SSM && (i == 1 || i == 3)) mbar_wait(BAR(BR_FREE) + 4 * (i - 1), 0);
        if (elect_one()) {
          mbar_expect_tx(BAR(BR_OFULL) + 8 * i, 20480);
          bulk_ld(sb + SLOT(i), &g_o[(r * 8 + src) * 1280], 20480, BAR(BR_OFULL) + 8 * i);
          if (i == 1) TS(21);
          if (i == 7) TS(22);
        }
        __syncwarp();
      }
      if (lane == 0) { DUMP(20, 30); }
      }
    } else {
      const int hw = warp - 13, ht = tid - 416;
      if (hw == 2 && elect_one()) {
        #pragma unroll
        for (int i = 5; i < BR_COUNT; i++) mbar_init(BAR(i), i == BR_WO ? 33 : i < BR_EMPTY ? 1 : i < BR_OEMPTY ? 2 : i < BR_Y ? 8 : i < BR_OSTG ? 4 : i == BR_OSTG ? 8 : i < BR_U2 ? 3 : 1);
        asm volatile("fence.mbarrier_init.release.cluster;" ::: "memory");
        if (EN_SSM) { mbar_expect_tx(BAR(BR_UIN), 20480); tma2d(sb + OFF_UT, &prm.m[M_U], BAR(BR_UIN), c * 80, r * 128); }
      }
      __syncwarp();
      asm volatile("bar.arrive 0, 512;" ::: "memory");
      const unsigned epoch = hw == 0 ? ld_rlx(&g_epoch[cta]) + 1 : 0;
      bar_sync(5, 96);
      asm volatile("bar.arrive 6, 128;" ::: "memory");
      if (hw == 1 && elect_one()) {
        #pragma unroll
        for (int i = M_WO; i < M_COUNT; i++) asm volatile("prefetch.tensormap [%0];" :: "l"(&prm.m[i]) : "memory");
      }
      if (ht == 0) {
        st_rlx(&g_epoch[cta], epoch);
        sts32(sb + OFF_EPOCH, epoch);
        mbar_arrive(BAR(BR_EPOCH));
      }
      if (EN_SSM) {
      const int mi = lane >> 3, rw = lane & 7, ch0 = c * 80 + r * 5;
      mbar_wait(BAR(BR_UIN), 0);
      if (ht == 0) TS(36);
      #pragma unroll 1
      for (int h = 0; h < 2; h++) {
        const uint32_t sa = sb + OFF_UT + h * 10240 + (8 * mi + rw) * 160 + hw * 16, da = sb + OFF_UT + h * 10240 + (hw * 8 + rw) * 128 + ((mi ^ rw ^ h) << 4);
        uint32_t v[8][4];
        #pragma unroll
        for (int q = 0; q < 8; q++) if (q < 6 || hw == 0) ldsm4t(v[q], sa + (q & 1) * 5120 + (q >> 1) * 48);
        bar_sync(5, 96);
        #pragma unroll
        for (int q = 0; q < 8; q++) if (q < 6 || hw == 0) stsm4((da ^ ((q & 1) * 64)) + (q >> 1) * 3072, v[q][0], v[q][1], v[q][2], v[q][3]);
      }
      fence_async();
      bar_sync(5, 96);
      if (hw == 0) {
        if (elect_one()) {
          tma2d_st(&prm.m[M_SA], sb + OFF_UT, r * 128, c * 80);
          tma2d_st(&prm.m[M_SA], sb + OFF_UT + 10240, r * 128 + 64, c * 80);
          bulk_commit(); bulk_wait0_read();
          mbar_arrive(BAR(BR_UOUT));
          TS(37);
          bulk_wait0();
          st_rel(FLAG(1, r, c), epoch);
          TS(30);
        }
        __syncwarp();
        poll_all_acq(FLAG(1, lane & 15, c), epoch);
      }
      #pragma unroll 1
      for (int q6 = hw; q6 < 30; q6 += 3) {
        if (q6 >= 6 && q6 < 9) { __syncwarp(); if (lane == 0) mbar_arrive(BAR(BR_DRDY)); }
        if (q6 < 3 || (q6 >= 18 && q6 < 21)) {
          const int p = q6 >= 18;
          if (hw == 0) {
            mbar_wait(BAR(BR_KS + 2) + 16 * p, 0);
            if (elect_one()) {
              fence_async_g();
              mbar_expect_tx(BAR(p ? BR_U2 : BR_U), p ? 8192 : 12288);
              #pragma unroll 1
              for (int q = 3 * p; q < 3 + 2 * p; q++) bulk_ld(sb + OFF_BLK + q * BLK, g_uy + (ch0 + q) * 2048, 4096, BAR(p ? BR_U2 : BR_U));
              TS(31);
            }
            __syncwarp();
            mbar_wait(BAR(p ? BR_U2 : BR_U), 0);
          }
          bar_sync(5, 96);
          if (ht == 0) TS(38 + p);
        }
        {
          const int k = q6 / 6, kap = (q6 - 6 * k) * 32 + lane;
          const uint32_t blk = sb + OFF_BLK + k * BLK;
          float P[33];
          P[0] = 0.f;
          #pragma unroll
          for (int q = 0; q < 4; q++) {
            const int ch = kap - 3 + q;
            uint32_t v[4];
            lds128(v, blk + (uint32_t)((ch * 16) ^ ((ch * 2) & 0x10)));
            #pragma unroll
            for (int e = 0; e < 4; e++) {
              P[q * 8 + 2 * e + 1] = (q == 0 && e < 2) ? 0.f : P[q * 8 + 2 * e] + bf_lo(v[e]);
              P[q * 8 + 2 * e + 2] = (q == 0 && e < 2) ? 0.f : P[q * 8 + 2 * e + 1] + bf_hi(v[e]);
            }
          }
#define WIN(lo, hi, e) (P[25 + (e) - (lo)] - P[24 + (e) - (hi)])
#define WIN8(lo, hi) pack2(WIN(lo, hi, 0), WIN(lo, hi, 1)), pack2(WIN(lo, hi, 2), WIN(lo, hi, 3)), pack2(WIN(lo, hi, 4), WIN(lo, hi, 5)), pack2(WIN(lo, hi, 6), WIN(lo, hi, 7))
          const uint32_t o2 = blk + B_D + (kap & 1) * 1552 + (kap >> 1) * 16;
          sts128(o2, WIN8(3, 5));
          sts128(o2 + B_D5, WIN8(6, 10));
          if (kap < 2) sts128(blk + B_D + kap * B_D5 + 1536, 0, 0, 0, 0);
          if (kap < 128) {
            const uint32_t o = blk + B_D + (kap & 1) * 1024 + (kap >> 1) * 16;
            sts128(o + B_D7, WIN8(5, 11));
            sts128(o + B_D9, WIN8(12, 20));
          }
        }
      }
      __syncwarp();
      if (lane == 0) mbar_arrive(BAR(BR_DRDY + 1));
      if (ht == 0) TS(32);
      if (hw == 0) {
        #pragma unroll 1
        for (int p = 0; p < 2; p++) {
          mbar_wait(BAR(BR_Y) + 8 * p, 0);
          if (elect_one()) {
            #pragma unroll 1
            for (int k = p; k < 1 + 4 * p; k++) bulk_st(g_uy + (640 + ch0 + k) * 2048, sb + OFF_BLK + k * BLK, 4096);
            bulk_commit(); bulk_wait0_read();
            mbar_arrive(BAR(BR_FREE) + 8 * p);
          }
          __syncwarp();
        }
        if (elect_one()) { bulk_wait0(); st_rlx(FLAG(2, r, c), epoch); TS(33); }
        __syncwarp();
        poll_all(FLAG(2, lane & 15, c), epoch);
        if (EN_ATT) mbar_wait(BAR(BR_OEMPTY + 2), 0);
        #pragma unroll 1
        for (int n = 0; n < 64; n++) {
          if (elect_one()) {
            mbar_expect_tx(BAR(BR_YIN), 20480);
            tma2d(sb + OFF_EXTRA, &prm.m[M_SA], BAR(BR_YIN), r * 128, 640 + c * 80);
            tma2d(sb + OFF_EXTRA + 10240, &prm.m[M_SA], BAR(BR_YIN), r * 128 + 64, 640 + c * 80);
            TS(34);
          }
          __syncwarp();
          if (EN_ATT) mbar_wait(BAR(BR_OEMPTY + 3), 0);
          mbar_wait(BAR(BR_YIN), n & 1);
          if (!y_transpose(sb, 4, lane, (epoch & 1u) * 0x10001u)) break;
          FIXCNT
        }
      if (elect_one()) {
        tma2d_st(&prm.m[M_OUT], sb + SLOT(3), c * 80, r * 128);
        bulk_commit(); bulk_wait0_read();
        TS(35); DUMP(30, 40); DUMP(0, 1);
      }
      }
      }
    }
  } else {
    const int g = lane >> 2, tq = lane & 3, t7 = tid & 127;
    uint32_t pr[3][2], pd;
    {
      const int ch = c * 80 + r * 5 + wg;
      uint32_t raw[3][4];
      #pragma unroll
      for (int e = 0; e < 4; e++) {
        const __nv_bfloat16* pp = prm.par[e] + ch * 128 + t7;
        #pragma unroll
        for (int q = 0; q < 3; q++) {
          raw[q][e] = 0;
          if (q == 0 || wg == 2) asm volatile("ld.global.nc.u16 %0, [%1];" : "=r"(raw[q][e]) : "l"(pp + q * 128));
        }
      }
      asm volatile("ld.global.nc.u16 %0, [%1];" : "=r"(pd) : "l"(((lane & 4) ? prm.dskip : prm.logdt) + ch + min(lane & 3, 2)));
      asm volatile("setmaxnreg.inc.sync.aligned.u32 152;");
      if (EN_SSM && wg < 2) {
        #pragma unroll
        for (int k = 0; k < 2; k++) {
          const uint32_t z = sb + OFF_BLK + (2 * wg + k) * BLK + t7 * 16;
          sts128(z + B_TBL, 0, 0, 0, 0); sts128(z + B_TBL + 2048, 0, 0, 0, 0);
        }
        if (tid < 80) sts128(sb + OFF_BLK + (tid >> 4) * BLK - 256 + (tid & 15) * 16, 0, 0, 0, 0);
      }
      #pragma unroll
      for (int q = 0; q < 3; q++) {
        #pragma unroll
        for (int e = 0; e < 2; e++) pr[q][e] = raw[q][2 * e] | (raw[q][2 * e + 1] << 16);
        const uint32_t m = __reduce_max_sync(0xffffffff, max(raw[q][2] & 0x7fffu, raw[q][3] & 0x7fffu));
        if (lane == 0) sts32(sb + OFF_EPOCH + 64 + (wg * 3 + q) * 16 + w4 * 4, m);
      }
      bar_sync(2 + wg, 128);
    }
    if (tid == 256) TS(40);
    if (EN_SSM) {
#define P0(w) ((w) == 1 ? 4 * W_SLOT : OFF_BLK + (w) * BLK)
#define P2(w) ((w) == 1 ? OFF_X + 32768 - 4 * W_SLOT : BLK)
      uint32_t ea = sb + P0(wg) + (lane >> 4) * 7168 + (w4 & 1) * P2(wg) + ((lane >> 3) & 1) * 256 + (lane & 7) * 16 + (w4 >> 1) * 2048;
      constexpr uint64_t dE = mkdesc(SB0, 128, 512, 0);
      const uint32_t xa = sb + OFF_BLK + 18560 + t7 * 8, xr_ = sb + OFF_BLK + 18560 + (t7 ^ 64) * 8;
      float ka[24]; zero<24>(ka);
      wg_fence();
      wg_ss48_tt_h(ka, dE + (OFF_BLK >> 4), dE + (OFF_BLK >> 4), 0);
      wg_commit();
      #pragma unroll 1
      for (int it = -1; it < 5; it++) {
        const int k = it < 2 ? 1 - it : it;
        const bool nf = it < 0 || it == 2 || it == 3;
        const uint32_t blk = sb + OFF_BLK + k * BLK;
        uint32_t F[56];
#define PUT4(i, a, b, c_, d) { F[4 * (i)] = a; F[4 * (i) + 1] = b; F[4 * (i) + 2] = c_; F[4 * (i) + 3] = d; }
        if (nf) {
          const int q = it < 0 ? 0 : it - 1;
          const uint32_t pa0 = pr[0][0], pc0 = pr[0][1];
          const float dt = bf_round(expf(bf_lo(__shfl_sync(0xffffffff, pd, q))));
          #pragma unroll
          for (int e = 0; e < 2; e++) { pr[0][e] = pr[1][e]; pr[1][e] = pr[2][e]; }
          uint32_t mm[4];
          lds128(mm, sb + OFF_EPOCH + 64 + (wg * 3 + q) * 16);
          const uint32_t ex = min(max(max(max(mm[0], mm[1]), max(mm[2], mm[3])) >> 7, 1u), 253u);
          const float sc = __uint_as_float((254u - ex) << 23);
          if (t7 == 4 + q) sts64(sb + OFF_EPOCH + 16 + (wg + q) * 8, __float_as_uint(2.f * dt * __uint_as_float(ex << 23)), pd << 16);
          const float lr = -bf_round(expf(bf_lo(pa0))) * dt * 1.44269504089f;
          const float tn = bf_hi(pa0) * dt * 0.15915494309f;
          float z1r, z1i, z2r, z2i, z4r, z4i, xr[8], xi[8], gr[8], gi[8], wr[9], wi[9];
          cexp_t(lr, -tn, z1r, z1i);
          cexp_t(lr * 8.f, tn * 8.f, xr[1], xi[1]);
          cexp_t(lr * 64.f, tn * 64.f, wr[0], wi[0]);
          xr[0] = 1.f; xi[0] = 0.f;
          cmul(xr[1], xi[1], xr[1], xi[1], xr[2], xi[2]); cmul(xr[2], xi[2], xr[1], xi[1], xr[3], xi[3]);
          cmul(xr[2], xi[2], xr[2], xi[2], xr[4], xi[4]);
          #pragma unroll
          for (int b = 1; b < 4; b++) cmul(xr[4], xi[4], xr[b], xi[b], xr[4 + b], xi[4 + b]);
          cmul(wr[0], wi[0], wr[0], wi[0], wr[1], wi[1]); cmul(wr[1], wi[1], wr[0], wi[0], wr[2], wi[2]);
          cmul(wr[1], wi[1], wr[1], wi[1], wr[3], wi[3]); cmul(wr[3], wi[3], wr[3], wi[3], wr[4], wi[4]);
          cmul(wr[4], wi[4], wr[3], wi[3], wr[5], wi[5]); cmul(wr[4], wi[4], wr[4], wi[4], wr[6], wi[6]);
          cmul(wr[6], wi[6], wr[4], wi[4], wr[7], wi[7]); cmul(wr[6], wi[6], wr[6], wi[6], wr[8], wi[8]);
          uint32_t R[4], I[4], PR[4], PI[4];
          #pragma unroll
          for (int b = 0; b < 4; b++) { R[b] = packh(xr[2 * b], xr[2 * b + 1]); I[b] = packh(xi[2 * b], xi[2 * b + 1]); }
          PUT4(0, R[0], R[1], R[2], R[3]); PUT4(1, I[0], I[1], I[2], I[3]);
          #pragma unroll
          for (int i = 0; i < 3; i++) {
            const uint32_t z = packh(wr[i], wi[i]);
            #pragma unroll
            for (int b = 0; b < 4; b++) hcm2(R[b], I[b], z, PR[b], PI[b]);
            PUT4(2 * i + 2, PR[0], PR[1], PR[2], PR[3]); PUT4(2 * i + 3, PI[0], PI[1], PI[2], PI[3]);
          }
          gr[0] = bf_lo(pc0) * sc; gi[0] = -bf_hi(pc0) * sc;
          cmul(z1r, z1i, z1r, z1i, z2r, z2i); cmul(z2r, z2i, z2r, z2i, z4r, z4i);
          cmul(gr[0], gi[0], z1r, z1i, gr[1], gi[1]);
          cmul(gr[0], gi[0], z2r, z2i, gr[2], gi[2]); cmul(gr[1], gi[1], z2r, z2i, gr[3], gi[3]);
          #pragma unroll
          for (int b = 0; b < 4; b++) cmul(gr[b], gi[b], z4r, z4i, gr[4 + b], gi[4 + b]);
          PUT4(8, packh(gr[0], gr[1]), packh(gr[2], gr[3]), packh(gr[4], gr[5]), packh(gr[6], gr[7]));
          PUT4(9, packh(gi[0], gi[1]), packh(gi[2], gi[3]), packh(gi[4], gi[5]), packh(gi[6], gi[7]));
          {
            const uint32_t z = packh(wr[3], -wi[3]), a4r = packh(gr[0], gr[4]), a4i = packh(gi[0], gi[4]);
            hcm2(packh(gr[0], gr[2]), packh(gi[0], gi[2]), z, PR[0], PI[0]);
            hcm2(packh(gr[4], gr[6]), packh(gi[4], gi[6]), z, PR[1], PI[1]);
            hcm2(a4r, a4i, packh(wr[4], -wi[4]), PR[2], PI[2]);
            hcm2(a4r, a4i, packh(wr[5], -wi[5]), PR[3], PI[3]);
            PUT4(10, PR[0], PR[1], PR[2], PR[3]); PUT4(11, PI[0], PI[1], PI[2], PI[3]);
            float hr, hi_;
            cmul(gr[0], gi[0], wr[3], -wi[3], hr, hi_);
            const uint32_t cr = packh(gr[0], hr), ci = packh(gi[0], hi_);
            #pragma unroll
            for (int i = 0; i < 3; i++) hcm2(cr, ci, packh(wr[6 + i], -wi[6 + i]), PR[i], PI[i]);
            PUT4(12, PR[0], PR[1], PR[2], 0u); PUT4(13, PI[0], PI[1], PI[2], 0u);
          }
        }
        else {
          #pragma unroll
          for (int i = 0; i < 56; i++) asm volatile("" : "=r"(F[i]));
        }
        uint32_t fd[2];
        lds64(fd, sb + OFF_EPOCH + 16 + k * 8);
        const float fac = __uint_as_float(fd[0]), dsk = __uint_as_float(fd[1]);
        wg_wait<0>();
        pin<24>(ka);
        float kk[6];
        const bool up = w4 >= 2;
        if (it == 1 || it == 2) bar_sync(4, 128);
        #pragma unroll
        for (int n = 0; n < 3; n++) {
          if (it >= 0) sts64f(xa + n * BLK, up ? ka[12 + 4 * n] : ka[4 * n + 2], up ? ka[13 + 4 * n] : ka[4 * n + 3]);
          kk[2 * n] = up ? ka[14 + 4 * n] : ka[4 * n]; kk[2 * n + 1] = up ? ka[15 + 4 * n] : ka[4 * n + 1];
        }
        pin<6>(kk);
        if (it >= 0) {
          bar_sync(4, 128);
          if (t7 == 0) mbar_arrive(BAR(BR_KS) + 8 * it);
          #pragma unroll
          for (int n = 0; n < 3; n++) {
            uint32_t o[2]; lds64(o, xr_ + n * BLK);
            kk[2 * n] = (kk[2 * n] + __uint_as_float(o[0])) * fac; kk[2 * n + 1] = (kk[2 * n + 1] + __uint_as_float(o[1])) * fac;
          }
        }
        if (nf) {
          if (it == 2) {
            mbar_wait(BAR(BR_UOUT), 0);
            ea += BLK;
            sts128(sb + OFF_UT + B_TBL + t7 * 16, 0, 0, 0, 0); sts128(sb + OFF_UT + B_TBL + 2048 + t7 * 16, 0, 0, 0, 0);
          }
          const uint32_t ga = ea + 4096 - (w4 >> 1) * 512;
          #pragma unroll
          for (int i = 0; i < 14; i++) sts128((i < 8 ? ea + (i >> 1) * 512 : ga + ((i - 8) >> 1) * 512) + (i & 1) * 128, F[4 * i], F[4 * i + 1], F[4 * i + 2], F[4 * i + 3]);
          fence_async();
          bar_sync(it < 0 ? 0 : 4, it < 0 ? 512 : 128);
          if (wg < 2) break;
        }
        if (it < 4) {
          const int fs = (0x33201 >> (4 * it + 4)) & 3;
          wg_fence();
          #pragma unroll
          for (int s = 0; s < 8; s++) {
            const uint32_t lo = (uint32_t)dE + ((P0(fs) + (s >> 2) * P2(fs)) >> 4) + ((s >> 1) & 1) * 448 + (s & 1) * 16;
            wg_ss48_tt_h(ka, desc2(lo, dE >> 32), desc2(lo + 256, dE >> 32), s != 0);
          }
          wg_commit();
        }
        if (it >= 0)
        {
          const int j = (w4 & 1) * 16 + (w4 >> 1) * 8 + g;
          const uint32_t tb = blk + B_TBL;
          if (t7 == 0) kk[0] += dsk;
          const uint32_t pa_ = tb + (16 + 8 * j + 2 * tq) * 4;
          const uint32_t v = pack2(kk[1], kk[0]);
          sts32(pa_ + 4, v); sts16(pa_, v >> 16); sts16(pa_ + 10, v);
          const uint32_t u = pack2(kk[2], kk[3]), w = pack2(kk[4], kk[5]);
          if (tq < 2) {
            const uint32_t pb = tb + (16 + 256 + 8 * j + 4 * tq) * 4;
            sts16(pb, u); sts32(pb + 4, __byte_perm(u, 0, 0x1010)); sts32(pb + 8, __byte_perm(u, 0, 0x1032)); sts16(pb + 14, u >> 16);
            if (j | tq) { sts16(pb - 4, u); sts16(pb + 2, u); }
            const int i = 64 * tq + j;
            const uint32_t e0 = tb + (T_F3 + (((i - 1) & 1) ? 80 : 0) + ((i - 1) >> 1)) * 4, e1 = i ? e0 : tb + (T_F2 + 144 + 31) * 4;
            sts16(e1, w); sts16(e1 + 6, w); sts16(e0 + 64, w >> 16); sts16(e0 + 70, w >> 16);
            if (i == 0) { sts16(tb + (T_S + 3) * 4, w); sts32(tb + (T_S + 4) * 4, __byte_perm(w, 0, 0x1010)); sts16(tb + (T_S + 5) * 4 + 2, w); }
          } else {
            const int i = 32 * (tq - 2) + j;
            const uint32_t e1 = tb + (i ? T_F2 + ((2 * i - 1) & 3) * 48 + ((2 * i - 1) >> 2) : 16 + 511) * 4;
            const uint32_t e2 = tb + (T_F2 + (i & 1) * 96 + (i >> 1)) * 4;
            sts16(e1, u); sts16(e1 + 6, u); sts16(e2, u >> 16); sts16(e2 + 6, u >> 16);
            if (i == 0) {
              const uint32_t uu = __byte_perm(u, 0, 0x1010);
              sts32(tb + 528 * 4, uu); sts32(tb + 529 * 4, uu); sts32(tb + 530 * 4, uu); sts16(tb + 531 * 4 + 2, u);
              sts16(tb + (T_F3 + 80 + 63) * 4, w);
            }
          }
        }
        if (t7 == 0) TS(49 + it);
      }
      wg_wait<0>();
      pin<24>(ka);
    }
    if (!EN_SSM) bar_sync(0, 512);
    if (tid == 0) TS(14);
  if (wg < 2) {
    if (EN_ATT) {
    float am[96], ar[24];
    {
      const bool lead = (rtid() & 127) == 0;
      constexpr uint64_t da0 = mkdesc(SB0 + OFF_X, 16, 1024, 1), dr0 = mkdesc(SB0 + 12288, 1024, 256, 3);
      const uint64_t db0 = sw64 ? mkdesc(SB0, 2048, 512, 2) : mkdesc(SB0, 4096, 1024, 1);
      const uint32_t kst = sw64 ? 64 : 128, bh = db0 >> 32;
      uint32_t s = 0, ph = 0, xo = 0;
      #pragma unroll 1
      for (int kb = 0; kb < 20; kb++) {
        const uint32_t wo_ = s * (W_SLOT >> 4), al = (uint32_t)da0 + wg * 512 + xo, bl = (uint32_t)db0 + wo_, rl = (uint32_t)dr0 + wo_;
        mbar_wait(BAR(BR_FULL) + 8 * s, ph);
        if (kb == 0 && lead && wg == 0) TS(1);
        wg_fence();
        wg_ss192_tb(am, desc2(al, da0 >> 32), desc2(bl, bh), kb != 0);
        wg_ss48_tb(ar, desc2(al, da0 >> 32), desc2(rl, dr0 >> 32), kb != 0);
        wg_ss192_tb(am, desc2(al + 2, da0 >> 32), desc2(bl + kst, bh), 1);
        wg_ss48_tb(ar, desc2(al + 2, da0 >> 32), desc2(rl + 32, dr0 >> 32), 1);
        wg_commit();
        wg_wait<1>();
        if (lead && kb > 0 && kb < 16) mbar_arrive(BAR(BR_EMPTY) + 8 * (s == 0 ? 4 : s - 1));
        if (++s == 5) { s = 0; ph ^= 1; }
        xo += (kb & 1) ? 1020 : 4;
        if (xo == 3072) xo = 0;
      }
      wg_wait<0>();
      pin<96>(am); pin<24>(ar);
    }
    const int tid = rtid(), lane = tid & 31, tq = lane & 3;
    if (tid == 0) TS(2);
#define QV(j, e) ((j) < 8 ? am[4 * (j) + (e)] : ar[4 * ((j) - 8) + (e)])
#define KV_(j, e) ((j) < 8 ? am[32 + 4 * (j) + (e)] : ar[8 + 4 * ((j) - 8) + (e)])
#define VV(j, e) ((j) < 8 ? am[64 + 4 * (j) + (e)] : ar[16 + 4 * ((j) - 8) + (e)])
    {
      bar_sync(1, 256);
      if (tid == 0) mbar_arrive(BAR(BR_GEMM));
      const uint32_t ro = sb + (uint32_t)((warp * 16 + (lane & 15)) * 16);
      const int l0 = 2 * (c & 1) + (lane >> 4);
      const uint32_t ones = (tq == 0) ? 0x00003f80u : 0u;
#define PV(j) pack2(VV(j, 0), VV(j, 1)), pack2(VV(j, 2), VV(j, 3))
#define PK(j) pack2(phi(KV_(j, 0)), phi(KV_(j, 1))), pack2(phi(KV_(j, 2)), phi(KV_(j, 3)))
      stsm4(ro + OFF_V + (5 + 6 * (lane >> 4)) * 2048, ones, ones, ones, ones);
      #pragma unroll
      for (int j = 0; j < 10; j += 2) {
        const int l = (j == 8 && (c & 1)) ? l0 - 2 : l0 + j;
        stsm4(ro + OFF_V + (l + (l >= 5)) * 2048, PV(j), PV(j + 1));
        stsm4(ro + OFF_PK + l * 2048, PK(j), PK(j + 1));
      }
    }
    fence_async();
    bar_sync(1, 256);
    if (tid == 0) TS(3);
    mbar_wait(BAR(BR_EPOCH), 0);
    const unsigned epoch = lds32(sb + OFF_EPOCH);
    {
      float kv[24]; zero<24>(kv);
      constexpr uint64_t da = mkdesc(SB0 + OFF_PK, 128, 2048, 0), db = mkdesc(SB0 + OFF_V, 128, 2048, 0);
      wg_fence();
      #pragma unroll
      for (int s = 0; s < 8; s++) wg_ss48_tt(kv, desc2((uint32_t)da + wg * 640 + s * 16, da >> 32), desc2((uint32_t)db + wg * 768 + s * 16, db >> 32), s != 0);
      wg_commit();
      wg_wait<0>();
      pin<24>(kv);
      if (tid == 0) TS(15);
      if (w4 < 3) {
        const uint32_t wb = sb + OFF_KVS + (wg * 3 + w4) * 1536 + (lane & 15) * 96;
        #pragma unroll
        for (int j = 0; j < 6; j += 2)
          stsm4(wb + (j + (lane >> 4)) * 16, pack2(kv[4 * j], kv[4 * j + 1]), pack2(kv[4 * j + 2], kv[4 * j + 3]),
                pack2(kv[4 * j + 4], kv[4 * j + 5]), pack2(kv[4 * j + 6], kv[4 * j + 7]));
        __syncwarp();
        const int dl = w4 * 16 + (lane & 15), hl = dl >= 20;
        if (dl < 40) {
          uint4* dst = &g_kvp[(c * 16 + r) * 240 + wg * 40 + dl];
          uint32_t v[4], z[4];
          lds128(v, wb + (3 * hl + (lane >> 4)) * 16);
          lds64(z, wb + 32 + 8 * hl); z[2] = lds32(wb + 80); z[3] = epoch & 1u;
          v[3] = (v[3] & ~1u) | z[3];
          st128_rlx(dst + (lane >> 4) * 80, v);
          if (lane < 16) st128_rlx(dst + 160, z);
        }
      }
    }
    fence_async();
    bar_sync(1, 256);
    if (tid == 0) { st_rlx(FLAG(0, r, c), epoch); mbar_arrive(BAR(BR_PUB)); TS(4); }
    const int kvi = (tid >= 80) + (tid >= 160) + (tid >= 240), kd = tid - 80 * kvi;
    const int khd = kd / 20, kt0 = 5 * (khd >> 1) + 2 * (khd & 1);
    const uint32_t rb = sb + OFF_KVB + kd * 16;
    if (kvi < 3) {
      #pragma unroll 1
      for (int m = kvi; m < 7; m += 3) { const int q = kt0 + 3 + m; sts128(rb + (q >= 10 ? q - 10 : q) * 1280, 0, 0, 0, 0); }
    }
    uint32_t qa[20];
    {
      const float sc = 1.44269504089f + __uint_as_float(lds32(sb + OFF_EPOCH) ^ epoch);
      #pragma unroll
      for (int j = 0; j < 10; j++) { qa[2 * j] = pack2(phi(QV(j, 0), sc), phi(QV(j, 1), sc)); qa[2 * j + 1] = pack2(phi(QV(j, 2), sc), phi(QV(j, 3), sc)); }
    }
    if (tid == 0) TS(5);
    if (warp == 7) mbar_wait(BAR(BR_KVP), 0);
    bar_sync(1, 256);
    if (tid == 0) TS(6);
    if (kvi < 3) {
      float s[8];
      zero<8>(s);
      uint32_t bad = 0;
      #pragma unroll 4
      for (int i = 0; i < 16; i++) {
        uint32_t w[4];
        lds128(w, sb + OFF_KVP + tid * 16 + i * 3840);
        bad |= w[3] ^ epoch;
        #pragma unroll
        for (int e = 0; e < 4; e++) { s[2 * e] += bf_lo(w[e]); s[2 * e + 1] += bf_hi(w[e]); }
      }
      if (__builtin_expect(bad & 1u, 0)) {
        zero<8>(s);
        #pragma unroll 1
        for (int i = 0; i < 16; i++) {
          uint32_t w[4] = {0, 0, 0, ~epoch};
          fix128_w3(w, &g_kvp[(c * 16 + i) * 240 + tid], epoch, 1u);
          #pragma unroll
          for (int e = 0; e < 4; e++) { s[2 * e] += bf_lo(w[e]); s[2 * e + 1] += bf_hi(w[e]); }
        }
        FIXCNT
      }
      const uint32_t p0 = pack2(s[0], s[1]), p1 = pack2(s[2], s[3]), p2 = pack2(s[4], s[5]), p3 = pack2(s[6], s[7]);
      if (kvi < 2) sts128(rb + (kt0 + (khd & 1) + kvi) * 1280, p0, p1, p2, p3);
      else {
        const bool od = khd & 1;
        sts128(rb + (5 * (khd >> 1) + 2) * 1280, od ? 0u : p0, od ? 0u : p1, od ? p0 : 0u, od ? p1 : 0u);
        const uint32_t zz = (p2 & 0xffffu) << (16 * (khd & 1));
        sts128(rb + 10 * 1280, khd < 2 ? zz : 0u, khd < 2 ? 0u : zz, 0u, 0u);
      }
    }
    fence_async();
    bar_sync(1, 256);
    if (tid == 0) { mbar_arrive(BAR(BR_SUM)); TS(7); }
    {
      float oa[44]; zero<44>(oa);
      constexpr uint64_t db = mkdesc(SB0 + OFF_KVB, 128, 1280, 0);
      wg_fence();
      #pragma unroll
      for (int s = 0; s < 5; s++) wg_rs88_tb(oa, &qa[4 * s], desc2((uint32_t)db + ((s == 4 && (c & 1)) ? 0 : (s + (c & 1)) * 16), db >> 32), s != 0);
      wg_commit();
      wg_wait<0>();
      pin<44>(oa);
      if (tid == 0) TS(13);
      float rc[4], rd[2][4];
      #pragma unroll
      for (int e = 0; e < 4; e++) asm("rcp.approx.ftz.f32 %0, %1;" : "=f"(rc[e]) : "f"(oa[40 + e] + 1e-6f));
      #pragma unroll
      for (int h = 0; h < 4; h++) {
        rd[0][h] = __shfl_sync(0xffffffff, rc[h & 1], (lane & 28) | (h >> 1));
        rd[1][h] = __shfl_sync(0xffffffff, rc[2 + (h & 1)], (lane & 28) | (h >> 1));
      }
      #pragma unroll
      for (int j = 0; j < 10; j++) {
        #pragma unroll
        for (int h = 0; h < 2; h++) {
          float f;
          if (j == 2) f = tq < 2 ? rd[h][0] : rd[h][1];
          else if (j == 7) f = tq < 2 ? rd[h][2] : rd[h][3];
          else f = rd[h][(8 * j) / 20];
          qa[2 * j + h] = pack2(oa[4 * j + 2 * h] * f, oa[4 * j + 2 * h + 1] * f);
        }
      }
      const uint32_t m0 = (lane & 7) == ((2 * w4) & 7), m1 = (lane & 7) == 2 * w4 + 1;
      const uint32_t oa_ = sb + OFF_EXTRA + (lane >> 4) * 2048 + (warp * 16 + (lane & 15)) * 16;
      bar_sync(1, 256);
#define TAG(v, m) (((v) & ~(m)) | (epoch & (m)))
      #pragma unroll
      for (int s = 0; s < 5; s++) stsm4(oa_ + s * 4096, TAG(qa[4 * s], m0), TAG(qa[4 * s + 1], m1), TAG(qa[4 * s + 2], m0), TAG(qa[4 * s + 3], m1));
    }
    fence_async();
    __syncwarp();
    if (lane == 0) mbar_arrive(BAR(BR_OSTG));
    if (tid == 0) TS(8);
    float oc[40]; zero<40>(oc);
    {
      constexpr uint64_t dw0 = mkdesc(SB0, OFF_WOR, 1024, 1), da0 = mkdesc(SB0, 2048, 128, 0);
      const uint32_t ck = sb + tid * 32 + ((lane >> 2) << 2), ck2 = ck + (wg ? 0 : 16384);
      uint32_t bad = 0;
      auto tile = [&](int i, uint32_t so) {
        const uint32_t al = (uint32_t)da0 + wg * 64 + (so >> 4), wl = (uint32_t)dw0 + i * 640 - (i >> 1) * (1278 << 16);
        wg_fence();
        #pragma unroll
        for (int s = 0; s < 5; s++) wg_ss80_tb(oc, desc2(al + s * 256, da0 >> 32), desc2(wl + s * 128, dw0 >> 32), (i | s) != 0);
        wg_commit();
        bad |= (lds32(ck + so) ^ epoch) | (lds32(ck + so + 8192) ^ epoch) | (lds32(ck2 + so) ^ epoch);
      };
      mbar_wait(BAR(BR_WO), 0);
      mbar_wait(BAR(BR_OSTG), 0);
      tile(0, SLOT(0));
      mbar_wait(BAR(BR_WO + 1), 0);
      #pragma unroll 1
      for (int i = 1; i < 8; i++) {
        if (i == 1) {
          wg_wait<0>();
          if (lane == 0) mbar_arrive(BAR(BR_OEMPTY));
          if (EN_SSM && w4 == 0) mbar_wait(BAR(BR_Y + 1), 0);
          if (w4 == 0) mbar_wait(BAR(BR_OFULL + 1), 0);
          bar_sync(2 + wg, 128);
        }
        mbar_wait(BAR(BR_OFULL) + 8 * i, 0);
        if (i == 1 && tid == 0) TS(9);
        tile(i, SLOT(i));
        wg_wait<1>();
        if (lane == 0 && i > 1) mbar_arrive(BAR(BR_OEMPTY - 1) + 8 * i);
      }
      #pragma unroll 1
      for (int n = 0; n < 56; n++) {
        const int i = n & 7;
        if (i == 0) {
          uint32_t any;
          asm volatile("{\n.reg .pred p;\nsetp.ne.u32 p, %1, 0;\nbarrier.red.or.pred p, 1, 256, p;\nselp.u32 %0, 1, 0, p;\n}" : "=r"(any) : "r"(bad & 1u) : "memory");
          if (!any) break;
          bad = 0;
          FIXCNT
        }
        wg_wait<0>();
        bar_sync(1, 256);
        if (tid == 0) { mbar_expect_tx(BAR(BR_RETRY), 20480); bulk_ld(sb + SLOT(6), &g_o[(r * 8 + CHUNK(i)) * 1280], 20480, BAR(BR_RETRY)); }
        mbar_wait(BAR(BR_RETRY), n & 1);
        tile(i, SLOT(6));
      }
      wg_wait<0>();
      pin<40>(oc);
    }
    if (tid == 0) TS(10);
    {
      const int row = w4 * 16 + (lane & 15);
      const uint32_t ob = sb + OFF_BLK + 2 * BLK + wg * 10240;
      #pragma unroll
      for (int j = 0; j < 8; j += 2)
        stsm4(ob + row * 128 + (((j + (lane >> 4)) ^ (row & 7)) << 4), pack2(oc[4 * j], oc[4 * j + 1]), pack2(oc[4 * j + 2], oc[4 * j + 3]),
              pack2(oc[4 * j + 4], oc[4 * j + 5]), pack2(oc[4 * j + 6], oc[4 * j + 7]));
      stsm4(ob + 8192 + row * 32 + (lane >> 4) * 16, pack2(oc[32], oc[33]), pack2(oc[34], oc[35]), pack2(oc[36], oc[37]), pack2(oc[38], oc[39]));
      fence_async();
      bar_sync(2 + wg, 128);
      if (w4 == 0 && elect_one()) {
        tma2d_st(&prm.m[M_O64], ob, 640 + c * 64, r * 128 + wg * 64);
        tma2d_st(&prm.m[M_O16], ob + 8192, 1152 + c * 16, r * 128 + wg * 64);
        bulk_commit(); bulk_wait0_read();
        if (wg == 0) { TS(11); DUMP(0, 20); }
      }
    }
    }
  } else {
    if (EN_SSM) {
    const int tid = rtid(), lane = tid & 31, g = lane >> 2, tq = lane & 3, t7 = tid & 127;
    if (t7 == 0) TS(41);
    mbar_wait(BAR(BR_U), 0);
    bar_sync(4, 128);
    if (EN_ATT) mbar_wait(BAR(BR_GEMM), 0);
    if (t7 == 0) TS(42);
    mbar_wait(BAR(BR_EPOCH), 0);
    const uint32_t ytag = (lds32(sb + OFF_EPOCH) & 1u) * 0x10001u, ym = lane < 4 ? 0x10001u : 0u;
    #pragma unroll 1
    for (int pass = 0; pass < 2; pass++) {
      const int k = pass ? w4 + 1 : 0;
      if (pass) mbar_wait(BAR(BR_U2), 0);
      const uint32_t blk = sb + OFF_BLK + k * BLK, tb = blk + B_TBL + (uint32_t)((g - 2 * tq) * 4);
      float acc[16][4];
      zero<64>(&acc[0][0]);
      const int kl = 16 * (lane >> 4) + 2 * (lane & 7) + ((lane >> 3) & 1);
      {
        auto ubase = [&](int sh) { const int q = kl - 2 * sh; return blk + (uint32_t)((q * 16) ^ ((q * 2) & 0x10)); };
#define LDQ(A, sh) _Pragma("unroll") for (int m = 0; m < 4; m++) load_quad(A[m], tb + (16 + 16 * (sh) + 128 * m) * 4);
#define LDB(B, ub, h) _Pragma("unroll") for (int p = 0; p < 4; p++) ldsm4(B[p], (ub) + (4 * (h) + p) * 512);
#define MLO(A, B) _Pragma("unroll") for (int m = 0; m < 4; m++) _Pragma("unroll") for (int cc = 0; cc < 8; cc++) mma16816(acc[cc + m], A[m], &B[cc >> 1][(cc & 1) * 2]);
#define MHI(A, B) _Pragma("unroll") for (int m = 0; m < 4; m++) _Pragma("unroll") for (int cc = 0; cc < 8 - m; cc++) mma16816(acc[8 + cc + m], A[m], &B[cc >> 1][(cc & 1) * 2]);
        int p_ = pass ? 0 : w4;
        const int pe = pass ? 4 : w4 + 1;
        uint32_t A[4][4], A2[4][4], Bl[4][4], Bh[4][4];
        uint32_t ub = ubase(p_ + 4);
        LDQ(A, p_ + 4) LDB(Bl, ub, 0)
        #pragma unroll 1
        for (; p_ < pe; p_++) {
          LDB(Bh, ub, 1)
          MLO(A, Bl)
          ub = ubase(p_);
          LDQ(A2, p_) LDB(Bl, ub, 0)
          MHI(A, Bh)
          LDB(Bh, ub, 1)
          load_quad(A[0], tb + (16 + 512 + 16 * (p_ & 1)) * 4); load_quad(A[1], tb + (T_S + 16 * (p_ & 1)) * 4);
          MLO(A2, Bl)
          if (p_ < 2) {
            #pragma unroll
            for (int cc = 0; cc < 8; cc++) mma16816(acc[cc + 4], A[0], &Bl[cc >> 1][(cc & 1) * 2]);
            #pragma unroll
            for (int cc = 0; cc < 4; cc++) mma16816(acc[cc + 12], A[0], &Bh[cc >> 1][(cc & 1) * 2]);
            #pragma unroll
            for (int cc = 0; cc < 8; cc++) mma16816(acc[cc + 8], A[1], &Bl[cc >> 1][(cc & 1) * 2]);
          }
          const int pn = ((p_ + 1) & 3) + 4;
          ub = ubase(pn);
          LDQ(A, pn) LDB(Bl, ub, 0)
          MHI(A2, Bh)
        }
      }
      if (t7 == 0) TS(57 + 3 * pass);
      mbar_wait(BAR(BR_DRDY) + 8 * pass, 0);
      {
        const int ih = (lane >> 3) & 1;
        const uint32_t dl = blk + B_D + (uint32_t)(((lane >> 4) * 8 + (lane & 7)) * 16);
        const uint32_t d0_ = dl + ih * 1552, d8_ = dl + (ih ? 0 : 1536), d3_ = dl + B_D7 + ih * 1024;
        auto cls2 = [&](uint32_t da, uint32_t ta) {
          uint32_t B[6][2], A[6][4];
          #pragma unroll
          for (int e = 0; e < 6; e++) { B[e][0] = lds32v(ta + (e + 4) * 32); B[e][1] = lds32v(ta + (e + 3) * 32); }
          #pragma unroll
          for (int kk = 0; kk < 6; kk++) ldsm4t(A[kk], da + kk * 256);
          #pragma unroll
          for (int e = 0; e < 6; e++)
            #pragma unroll
            for (int kk = 0; kk < 6; kk++) if (2 * kk + e + 4 < 16) mma16816(acc[2 * kk + e + 4], A[kk], B[e]);
        };
        auto cls3 = [&](uint32_t da, uint32_t ta) {
          uint32_t B[8][2], A[4][4];
          #pragma unroll
          for (int e = 0; e < 8; e++) { B[e][0] = lds32v(ta + (e + 8) * 32); B[e][1] = lds32v(ta + (e + 7) * 32); }
          #pragma unroll
          for (int kk = 0; kk < 4; kk++) ldsm4t(A[kk], da + kk * 256);
          #pragma unroll
          for (int kk = 0; kk < 4; kk++)
            #pragma unroll
            for (int e = 0; e < 8; e++) if (2 * kk + e + 8 < 16) mma16816(acc[2 * kk + e + 8], A[kk], B[e]);
        };
        if (pass) {
          #pragma unroll 1
          for (int a = 0; a < 2; a++) {
            cls2(d0_ + a * B_D5, tb + (T_F2 + 48 * a - 32) * 4);
            cls2(d8_ + a * B_D5, tb + (T_F2 + 48 * a + 64) * 4);
            cls3(d3_ + a * 2048, tb + (T_F3 + 80 * a - 64) * 4);
          }
        } else {
          cls2(((w4 & 2) ? d8_ : d0_) + (w4 & 1) * B_D5, tb + (T_F2 + 48 * w4 - 32) * 4);
          if (w4 >= 2) cls3(d3_ + (w4 - 2) * 2048, tb + (T_F3 + 80 * (w4 - 2) - 64) * 4);
        }
      }
      if (t7 == 0) TS(58 + 3 * pass);
      const uint32_t ya = blk + (uint32_t)((kl * 16) ^ ((kl * 2) & 0x10));
#define YTAG(v) (((v) & ~ym) | (ytag & ym))
#define STY(p) stsm4t(ya + (p) * 512, YTAG(pack2(acc[2 * (p)][0], acc[2 * (p)][1])), pack2(acc[2 * (p)][2], acc[2 * (p)][3]), \
                      YTAG(pack2(acc[2 * (p) + 1][0], acc[2 * (p) + 1][1])), pack2(acc[2 * (p) + 1][2], acc[2 * (p) + 1][3]))
      if (pass == 0) {
        const uint32_t xw = blk + 3840 + w4 * 4096 + lane * 16, xr = blk + 3840 + w4 * 1024 + lane * 16;
        #pragma unroll
        for (int h = 0; h < 2; h++) {
          bar_sync(4, 128);
          #pragma unroll
          for (int i = 0; i < 8; i++)
            sts128(xw + i * 512, __float_as_uint(acc[8 * h + i][0]), __float_as_uint(acc[8 * h + i][1]), __float_as_uint(acc[8 * h + i][2]), __float_as_uint(acc[8 * h + i][3]));
          bar_sync(4, 128);
          float y[8];
          #pragma unroll
          for (int i = 0; i < 8; i++) {
            uint32_t o[4]; lds128(o, xr + (i >> 1) * 4096 + (i & 1) * 512);
            #pragma unroll
            for (int e = 0; e < 4; e++) y[4 * (i & 1) + e] = i < 2 ? __uint_as_float(o[e]) : y[4 * (i & 1) + e] + __uint_as_float(o[e]);
          }
          if (h) bar_sync(4, 128);
          stsm4t(ya + (4 * h + w4) * 512, YTAG(pack2(y[0], y[1])), pack2(y[2], y[3]), YTAG(pack2(y[4], y[5])), pack2(y[6], y[7]));
        }
      } else {
        __syncwarp();
        #pragma unroll
        for (int p = 0; p < 8; p++) STY(p);
      }
      if (t7 == 0 && !pass) TS(55);
      fence_async();
      __syncwarp();
      if (lane == 0) mbar_arrive(BAR(BR_Y) + 8 * pass);
      if (t7 == 0) TS(59 + 3 * pass);
    }
    if (t7 == 0) DUMP(40, 64);
    #pragma unroll 1
    for (int n = 0; n < 64; n++) if (!y_transpose(sb, w4, lane, ytag)) break;
    }
  }
  }
}

typedef CUresult (*EncFn)(CUtensorMap*, CUtensorMapDataType, cuuint32_t, void*, const cuuint64_t*, const cuuint64_t*, const cuuint32_t*,
                          const cuuint32_t*, CUtensorMapInterleave, CUtensorMapSwizzle, CUtensorMapL2promotion, CUtensorMapFloatOOBfill);
static void mkmap(EncFn enc, CUtensorMap* m, const void* base, int rank, const cuuint64_t* dims, const cuuint64_t* strides, const cuuint32_t* box, CUtensorMapSwizzle swz) {
  cuuint32_t es[5] = {1, 1, 1, 1, 1};
  enc(m, CU_TENSOR_MAP_DATA_TYPE_BFLOAT16, rank, const_cast<void*>(base), dims, strides, box, es, CU_TENSOR_MAP_INTERLEAVE_NONE, swz,
      CU_TENSOR_MAP_L2_PROMOTION_L2_128B, CU_TENSOR_MAP_FLOAT_OOB_FILL_NONE);
}

extern "C" void kernel_launch(void* const* d_in, const int* in_sizes, int n_in, void* d_out, int out_size) {
  void* fn = nullptr; cudaDriverEntryPointQueryResult qr;
  cudaGetDriverEntryPoint("cuTensorMapEncodeTiled", &fn, cudaEnableDefault, &qr);
  EncFn enc = (EncFn)fn;
  void* uy = nullptr; cudaGetSymbolAddress(&uy, g_uy);
  const cuuint64_t dx[2] = {640, 2048}, sx[1] = {1280};
  const cuuint32_t bx[2] = {64, 128}, bu[2] = {80, 128};
  const cuuint64_t dw[3] = {640, 640, 3}, sw[2] = {3840, 1280};
  const cuuint32_t br[3] = {16, 32, 3};
  const cuuint64_t dwa[4] = {64, 640, 10, 3}, swa[3] = {3840, 128, 1280}, dwb[4] = {32, 640, 20, 3}, swb[3] = {3840, 64, 1280};
  const cuuint32_t bwa[4] = {64, 32, 1, 3}, bwb[4] = {32, 32, 2, 3};
  const cuuint64_t dwo[2] = {640, 640};
  const cuuint32_t bwo[2] = {64, 80}, bo64[2] = {64, 64}, bo16[2] = {16, 64};
  const cuuint64_t dsa[2] = {2048, 1280}, ssa[1] = {4096};
  const cuuint32_t bsa[2] = {64, 80};
  const cuuint64_t dout[2] = {1280, 2048}, sout[1] = {2560};
  Params prm;
  mkmap(enc, &prm.m[M_X], d_in[7], 2, dx, sx, bx, CU_TENSOR_MAP_SWIZZLE_128B);
  mkmap(enc, &prm.m[M_W128], d_in[8], 4, dwa, swa, bwa, CU_TENSOR_MAP_SWIZZLE_128B);
  mkmap(enc, &prm.m[M_W64], d_in[8], 4, dwb, swb, bwb, CU_TENSOR_MAP_SWIZZLE_64B);
  mkmap(enc, &prm.m[M_WR], d_in[8], 3, dw, sw, br, CU_TENSOR_MAP_SWIZZLE_32B);
  mkmap(enc, &prm.m[M_U], d_in[0], 2, dx, sx, bu, CU_TENSOR_MAP_SWIZZLE_NONE);
  mkmap(enc, &prm.m[M_WO], d_in[9], 2, dwo, sx, bwo, CU_TENSOR_MAP_SWIZZLE_128B);
  mkmap(enc, &prm.m[M_O64], d_out, 2, dout, sout, bo64, CU_TENSOR_MAP_SWIZZLE_128B);
  mkmap(enc, &prm.m[M_O16], d_out, 2, dout, sout, bo16, CU_TENSOR_MAP_SWIZZLE_NONE);
  mkmap(enc, &prm.m[M_SA], uy, 2, dsa, ssa, bsa, CU_TENSOR_MAP_SWIZZLE_128B);
  mkmap(enc, &prm.m[M_OUT], d_out, 2, dout, sout, bu, CU_TENSOR_MAP_SWIZZLE_NONE);
  prm.u = (const __nv_bfloat16*)d_in[0]; prm.wo = (const __nv_bfloat16*)d_in[9];
  for (int i = 0; i < 4; i++) prm.par[i] = (const __nv_bfloat16*)d_in[1 + i];
  prm.logdt = (const __nv_bfloat16*)d_in[5]; prm.dskip = (const __nv_bfloat16*)d_in[6];
  cudaFuncSetAttribute(fused_kernel, cudaFuncAttributeMaxDynamicSharedMemorySize, SMEM_BYTES);
  cudaLaunchConfig_t cfg = {};
  cfg.gridDim = dim3(128); cfg.blockDim = dim3(512); cfg.dynamicSmemBytes = SMEM_BYTES; cfg.stream = cudaStreamPerThread;
  cudaLaunchAttribute at[1];
  at[0].id = cudaLaunchAttributeClusterDimension; at[0].val.clusterDim.x = 2; at[0].val.clusterDim.y = 1; at[0].val.clusterDim.z = 1;
  cfg.attrs = at; cfg.numAttrs = 1;
  cudaLaunchKernelEx(&cfg, fused_kernel, prm);
}
```

```cpp
#include <cuda_runtime.h>
#include <cuda_bf16.h>
#include <cuda_fp16.h>
#include <cuda.h>
#include <stdint.h>

#define KST 2
#define EN_ATT 1
#define EN_SSM 1

__device__ __align__(1024) __nv_bfloat16 g_uy[2 * 640 * 2048];
__device__ __align__(128) uint4 g_kvp[8 * 16 * 240];
__device__ __align__(128) uint4 g_o[128 * 1280];
__device__ __align__(128) unsigned g_flag[4 * 128 * 32];
__device__ unsigned g_epoch[128];
#define TS(i) do {} while (0)
#define DUMP(lo, hi) do {} while (0)
#define FIXCNT

constexpr uint32_t SB0 = 1024;
constexpr uint32_t W_SLOT = 15360, OFF_X = 76800;
constexpr uint32_t OFF_WOR = 81920, OFF_KVP = 10240, OFF_KVS = 71680, OFF_PK = 10240, OFF_V = 30720, OFF_EXTRA = 102400, OFF_KVB = OFF_EXTRA;
constexpr uint32_t OFF_BAR = 125952, OFF_BLK = 128000, BLK = 20480;
constexpr uint32_t B_D = 4096, B_D5 = 3088, B_D7 = 6176, B_D9 = 8224, B_TBL = 14400;
constexpr int T_S = 576, T_F2 = 624, T_F3 = 816;
constexpr uint32_t OFF_UT = OFF_BLK + 4 * BLK;
constexpr uint32_t SMEM_BYTES = OFF_BLK + 5 * BLK;
enum { BR_FULL = 0, BR_WO = 5, BR_PUB = 7, BR_KVP = 8, BR_U = 9, BR_SUM = 10, BR_GEMM = 11, BR_UIN = 12, BR_YIN = 13, BR_EPOCH = 14,
       BR_FREE = 15, BR_RETRY = 17, BR_UOUT = 18, BR_OFULL = 18, BR_KS = 26, BR_EMPTY = 31, BR_OEMPTY = 36, BR_Y = 43, BR_OSTG = 45,
       BR_DRDY = 46, BR_U2 = 48, BR_COUNT = 50 };
constexpr uint32_t OFF_EPOCH = OFF_BAR + 8 * BR_COUNT;
enum { M_X, M_W128, M_W64, M_WR, M_U, M_WO, M_O64, M_O16, M_SA, M_OUT, M_COUNT };

__device__ __forceinline__ long long clk64() { long long t; asm volatile("mov.u64 %0, %%clock64;" : "=l"(t) :: "memory"); return t; }
__device__ __forceinline__ uint32_t smem_u32(const void* p) { return (uint32_t)__cvta_generic_to_shared(p); }
__host__ __device__ constexpr uint64_t mkdesc(uint32_t addr, uint32_t lbo, uint32_t sbo, uint32_t swz) {
  return (uint64_t)((addr & 0x3FFFF) >> 4) | ((uint64_t)(lbo >> 4) << 16) | ((uint64_t)(sbo >> 4) << 32) | ((uint64_t)swz << 62);
}
__device__ __forceinline__ uint64_t desc2(uint32_t lo, uint32_t hi) { uint64_t d; asm("mov.b64 %0, {%1, %2};" : "=l"(d) : "r"(lo), "r"(hi)); return d; }
__device__ __forceinline__ void mbar_init(uint32_t bar, uint32_t cnt) { asm volatile("mbarrier.init.shared::cta.b64 [%0], %1;" :: "r"(bar), "r"(cnt) : "memory"); }
__device__ __forceinline__ void mbar_expect_tx(uint32_t bar, uint32_t bytes) { asm volatile("mbarrier.arrive.expect_tx.shared::cta.b64 _, [%0], %1;" :: "r"(bar), "r"(bytes) : "memory"); }
__device__ __forceinline__ void mbar_arrive(uint32_t bar) { asm volatile("mbarrier.arrive.shared::cta.b64 _, [%0];" :: "r"(bar) : "memory"); }
__device__ __forceinline__ void mbar_wait(uint32_t bar, uint32_t parity) {
  asm volatile("{\n.reg .pred p;\n.reg .u32 c;\nmov.u32 c, 0;\n"
    "WL:\nmbarrier.try_wait.parity.shared::cta.b64 p, [%0], %1;\n@p bra WD;\n"
    "add.u32 c, c, 1;\nsetp.lt.u32 p, c, 200000;\n@p bra WL;\nWD:\n}" :: "r"(bar), "r"(parity) : "memory");
}
__device__ __forceinline__ void poll_all(const unsigned* p, unsigned val) {
  asm volatile("{\n.reg .pred p;\n.reg .u32 c, v;\nmov.u32 c, 0;\n"
    "PL:\nld.relaxed.gpu.global.u32 v, [%0];\nsetp.eq.u32 p, v, %1;\nvote.sync.all.pred p, p, 0xffffffff;\n@p bra PD;\n"
    "add.u32 c, c, 1;\nsetp.lt.u32 p, c, 100000;\n@p bra PL;\nPD:\n}" :: "l"(p), "r"(val) : "memory");
}
__device__ __forceinline__ void poll_all_acq(const unsigned* p, unsigned val) {
  asm volatile("{\n.reg .pred p;\n.reg .u32 c, v;\nmov.u32 c, 0;\n"
    "PL:\nld.acquire.gpu.global.u32 v, [%0];\nsetp.eq.u32 p, v, %1;\nvote.sync.all.pred p, p, 0xffffffff;\n@p bra PD;\n"
    "add.u32 c, c, 1;\nsetp.lt.u32 p, c, 100000;\n@p bra PL;\nPD:\n}" :: "l"(p), "r"(val) : "memory");
}
__device__ __forceinline__ unsigned poll_bit(const unsigned* p, unsigned val, unsigned mask) {
  unsigned bal;
  asm volatile("{\n.reg .pred p;\n.reg .u32 c, v;\nmov.u32 c, 0;\n"
    "PL:\nld.relaxed.gpu.global.u32 v, [%1];\nsetp.eq.u32 p, v, %2;\nvote.sync.ballot.b32 %0, p, 0xffffffff;\n"
    "and.b32 v, %0, %3;\nsetp.ne.u32 p, v, 0;\n@p bra PD;\n"
    "add.u32 c, c, 1;\nsetp.lt.u32 p, c, 100000;\n@p bra PL;\nPD:\n}" : "=&r"(bal) : "l"(p), "r"(val), "r"(mask) : "memory");
  return bal;
}
__device__ __forceinline__ void fix128_w0(uint32_t* v, const void* p, uint32_t tag, uint32_t mask) {
  asm volatile("{\n.reg .pred p;\n.reg .u32 c, x;\n.reg .b128 t;\n.reg .b64 lo, hi;\nmov.u32 c, 0;\n"
    "FL:\nxor.b32 x, %0, %5;\nand.b32 x, x, %6;\nsetp.eq.u32 p, x, 0;\n@p bra FD;\n"
    "ld.relaxed.gpu.global.b128 t, [%4];\nmov.b128 {lo, hi}, t;\nmov.b64 {%0, %1}, lo;\nmov.b64 {%2, %3}, hi;\n"
    "add.u32 c, c, 1;\nsetp.lt.u32 p, c, 100000;\n@p bra FL;\nFD:\n}"
    : "+r"(v[0]), "+r"(v[1]), "+r"(v[2]), "+r"(v[3]) : "l"(p), "r"(tag), "r"(mask) : "memory");
}
__device__ __forceinline__ void fix128_w3(uint32_t* v, const void* p, uint32_t tag, uint32_t mask) {
  asm volatile("{\n.reg .pred p;\n.reg .u32 c, x;\n.reg .b128 t;\n.reg .b64 lo, hi;\nmov.u32 c, 0;\n"
    "FL:\nxor.b32 x, %3, %5;\nand.b32 x, x, %6;\nsetp.eq.u32 p, x, 0;\n@p bra FD;\n"
    "ld.relaxed.gpu.global.b128 t, [%4];\nmov.b128 {lo, hi}, t;\nmov.b64 {%0, %1}, lo;\nmov.b64 {%2, %3}, hi;\n"
    "add.u32 c, c, 1;\nsetp.lt.u32 p, c, 100000;\n@p bra FL;\nFD:\n}"
    : "+r"(v[0]), "+r"(v[1]), "+r"(v[2]), "+r"(v[3]) : "l"(p), "r"(tag), "r"(mask) : "memory");
}
__device__ __forceinline__ void fence_acq() { asm volatile("fence.acq_rel.gpu;" ::: "memory"); }
__device__ __forceinline__ bool elect_one() {
  uint32_t p; asm volatile("{\n.reg .pred P;\nelect.sync _|P, 0xffffffff;\nselp.u32 %0, 1, 0, P;\n}" : "=r"(p)); return p;
}
__device__ __forceinline__ void bar_sync(int id, int n) { asm volatile("bar.sync %0, %1;" :: "r"(id), "r"(n) : "memory"); }
__device__ __forceinline__ void fence_async() { asm volatile("fence.proxy.async.shared::cta;" ::: "memory"); }
__device__ __forceinline__ void fence_async_g() { asm volatile("fence.proxy.async.global;" ::: "memory"); }
__device__ __forceinline__ void tma2d(uint32_t dst, const CUtensorMap* m, uint32_t bar, int c0, int c1) {
  asm volatile("cp.async.bulk.tensor.2d.shared::cluster.global.mbarrier::complete_tx::bytes [%0], [%1, {%3, %4}], [%2];"
    :: "r"(dst), "l"(m), "r"(bar), "r"(c0), "r"(c1) : "memory");
}
__device__ __forceinline__ void tma3d(uint32_t dst, const CUtensorMap* m, uint32_t bar, int c0, int c1, int c2) {
  asm volatile("cp.async.bulk.tensor.3d.shared::cluster.global.mbarrier::complete_tx::bytes [%0], [%1, {%3, %4, %5}], [%2];"
    :: "r"(dst), "l"(m), "r"(bar), "r"(c0), "r"(c1), "r"(c2) : "memory");
}
__device__ __forceinline__ void tma4d(uint32_t dst, const CUtensorMap* m, uint32_t bar, int c0, int c1, int c2, int c3) {
  asm volatile("cp.async.bulk.tensor.4d.shared::cluster.global.mbarrier::complete_tx::bytes [%0], [%1, {%3, %4, %5, %6}], [%2];"
    :: "r"(dst), "l"(m), "r"(bar), "r"(c0), "r"(c1), "r"(c2), "r"(c3) : "memory");
}
__device__ __forceinline__ void tma2d_st(const CUtensorMap* m, uint32_t src, int c0, int c1) {
  asm volatile("cp.async.bulk.tensor.2d.global.shared::cta.bulk_group [%0, {%2, %3}], [%1];"
    :: "l"(m), "r"(src), "r"(c0), "r"(c1) : "memory");
}
__device__ __forceinline__ void bulk_ld(uint32_t dst, const void* src, uint32_t bytes, uint32_t bar) {
  asm volatile("cp.async.bulk.shared::cluster.global.mbarrier::complete_tx::bytes [%0], [%1], %2, [%3];"
    :: "r"(dst), "l"(src), "r"(bytes), "r"(bar) : "memory");
}
__device__ __forceinline__ void bulk_st(void* dst, uint32_t src, uint32_t bytes) {
  asm volatile("cp.async.bulk.global.shared::cta.bulk_group [%0], [%1], %2;" :: "l"(dst), "r"(src), "r"(bytes) : "memory");
}
__device__ __forceinline__ void bulk_commit() { asm volatile("cp.async.bulk.commit_group;" ::: "memory"); }
__device__ __forceinline__ void bulk_wait0() { asm volatile("cp.async.bulk.wait_group 0;" ::: "memory"); }
__device__ __forceinline__ void bulk_wait0_read() { asm volatile("cp.async.bulk.wait_group.read 0;" ::: "memory"); }
__device__ __forceinline__ unsigned ld_rlx(const unsigned* p) { unsigned v; asm volatile("ld.relaxed.gpu.global.u32 %0, [%1];" : "=r"(v) : "l"(p) : "memory"); return v; }
__device__ __forceinline__ unsigned ld_acq(const unsigned* p) { unsigned v; asm volatile("ld.acquire.gpu.global.u32 %0, [%1];" : "=r"(v) : "l"(p) : "memory"); return v; }
__device__ __forceinline__ void st_rlx(unsigned* p, unsigned v) { asm volatile("st.relaxed.gpu.global.u32 [%0], %1;" :: "l"(p), "r"(v) : "memory"); }
__device__ __forceinline__ void st_rel(unsigned* p, unsigned v) { asm volatile("st.release.gpu.global.u32 [%0], %1;" :: "l"(p), "r"(v) : "memory"); }
__device__ __forceinline__ void ld128_rlx(uint32_t* v, const void* p) {
  asm volatile("{\n.reg .b128 t;\n.reg .b64 lo, hi;\nld.relaxed.gpu.global.b128 t, [%4];\nmov.b128 {lo, hi}, t;\n"
    "mov.b64 {%0, %1}, lo;\nmov.b64 {%2, %3}, hi;\n}" : "=r"(v[0]), "=r"(v[1]), "=r"(v[2]), "=r"(v[3]) : "l"(p) : "memory");
}
__device__ __forceinline__ void st128_rlx(void* p, const uint32_t* v) {
  asm volatile("{\n.reg .b128 t;\n.reg .b64 lo, hi;\nmov.b64 lo, {%1, %2};\nmov.b64 hi, {%3, %4};\nmov.b128 t, {lo, hi};\n"
    "st.relaxed.gpu.global.b128 [%0], t;\n}" :: "l"(p), "r"(v[0]), "r"(v[1]), "r"(v[2]), "r"(v[3]) : "memory");
}
__device__ __forceinline__ uint32_t lds32(uint32_t a) { uint32_t v; asm volatile("ld.shared.u32 %0, [%1];" : "=r"(v) : "r"(a) : "memory"); return v; }
__device__ __forceinline__ uint32_t lds32v(uint32_t a) { uint32_t v; asm volatile("ld.volatile.shared.u32 %0, [%1];" : "=r"(v) : "r"(a) : "memory"); return v; }
__device__ __forceinline__ uint32_t cpa(uint32_t a, uint32_t one) { uint32_t v; asm volatile("mul.lo.u32 %0, %1, %2;" : "=r"(v) : "r"(a), "r"(one)); return v; }
__device__ __forceinline__ uint32_t cpb(uint32_t a, uint32_t zero) { uint32_t v; asm volatile("or.b32 %0, %1, %2;" : "=r"(v) : "r"(a), "r"(zero)); return v; }
__device__ __forceinline__ uint32_t lds16(uint32_t a) { uint16_t v; asm volatile("ld.shared.u16 %0, [%1];" : "=h"(v) : "r"(a) : "memory"); return v; }
__device__ __forceinline__ float ldsf(uint32_t a) { float v; asm volatile("ld.shared.f32 %0, [%1];" : "=f"(v) : "r"(a) : "memory"); return v; }
__device__ __forceinline__ void lds128(uint32_t* v, uint32_t a) { asm volatile("ld.shared.v4.u32 {%0,%1,%2,%3}, [%4];" : "=r"(v[0]), "=r"(v[1]), "=r"(v[2]), "=r"(v[3]) : "r"(a) : "memory"); }
__device__ __forceinline__ void sts32(uint32_t a, uint32_t v) { asm volatile("st.shared.u32 [%0], %1;" :: "r"(a), "r"(v) : "memory"); }
__device__ __forceinline__ void sts16(uint32_t a, uint32_t v) { asm volatile("st.shared.u16 [%0], %1;" :: "r"(a), "h"((uint16_t)v) : "memory"); }
__device__ __forceinline__ void sts64f(uint32_t a, float x, float y) { asm volatile("st.shared.v2.f32 [%0], {%1,%2};" :: "r"(a), "f"(x), "f"(y) : "memory"); }
__device__ __forceinline__ void sts128(uint32_t a, uint32_t x, uint32_t y, uint32_t z, uint32_t w) { asm volatile("st.shared.v4.u32 [%0], {%1,%2,%3,%4};" :: "r"(a), "r"(x), "r"(y), "r"(z), "r"(w) : "memory"); }
__device__ __forceinline__ void stsm4(uint32_t a, uint32_t r0, uint32_t r1, uint32_t r2, uint32_t r3) {
  asm volatile("stmatrix.sync.aligned.m8n8.x4.shared.b16 [%0], {%1,%2,%3,%4};" :: "r"(a), "r"(r0), "r"(r1), "r"(r2), "r"(r3) : "memory");
}
__device__ __forceinline__ void stsm4t(uint32_t a, uint32_t r0, uint32_t r1, uint32_t r2, uint32_t r3) {
  asm volatile("stmatrix.sync.aligned.m8n8.x4.trans.shared.b16 [%0], {%1,%2,%3,%4};" :: "r"(a), "r"(r0), "r"(r1), "r"(r2), "r"(r3) : "memory");
}
__device__ __forceinline__ void ldsm4t(uint32_t* r, uint32_t a) {
  asm volatile("ldmatrix.sync.aligned.m8n8.x4.trans.shared.b16 {%0,%1,%2,%3}, [%4];" : "=r"(r[0]), "=r"(r[1]), "=r"(r[2]), "=r"(r[3]) : "r"(a) : "memory");
}
__device__ __forceinline__ void ldsm4(uint32_t* r, uint32_t a) {
  asm volatile("ldmatrix.sync.aligned.m8n8.x4.shared.b16 {%0,%1,%2,%3}, [%4];" : "=r"(r[0]), "=r"(r[1]), "=r"(r[2]), "=r"(r[3]) : "r"(a) : "memory");
}
__device__ __forceinline__ void mma16816(float* d, const uint32_t* a, const uint32_t* b) {
  asm volatile("mma.sync.aligned.m16n8k16.row.col.f32.bf16.bf16.f32 {%0,%1,%2,%3}, {%4,%5,%6,%7}, {%8,%9}, {%0,%1,%2,%3};"
    : "+f"(d[0]), "+f"(d[1]), "+f"(d[2]), "+f"(d[3]) : "r"(a[0]), "r"(a[1]), "r"(a[2]), "r"(a[3]), "r"(b[0]), "r"(b[1]));
}
__device__ __forceinline__ uint32_t pack2(float lo, float hi) { uint32_t r; asm("cvt.rn.bf16x2.f32 %0, %1, %2;" : "=r"(r) : "f"(hi), "f"(lo)); return r; }
__device__ __forceinline__ uint32_t packh(float lo, float hi) { uint32_t r; asm("cvt.rn.f16x2.f32 %0, %1, %2;" : "=r"(r) : "f"(hi), "f"(lo)); return r; }
__device__ __forceinline__ uint32_t hcmul(uint32_t x, uint32_t zp, uint32_t zq) {
  const __half2 xx = *reinterpret_cast<__half2*>(&x);
  const __half2 r = __hfma2(__high2half2(xx), *reinterpret_cast<__half2*>(&zq), __hmul2(__low2half2(xx), *reinterpret_cast<__half2*>(&zp)));
  return *reinterpret_cast<const uint32_t*>(&r);
}
__device__ __forceinline__ void hcm2(uint32_t xr, uint32_t xi, uint32_t z, uint32_t& pr, uint32_t& pi) {
  const __half2 a = *reinterpret_cast<__half2*>(&xr), b = *reinterpret_cast<__half2*>(&xi), zz = *reinterpret_cast<__half2*>(&z);
  const __half2 re = __hfma2(__hneg2(b), __high2half2(zz), __hmul2(a, __low2half2(zz)));
  const __half2 im = __hfma2(a, __high2half2(zz), __hmul2(b, __low2half2(zz)));
  pr = *reinterpret_cast<const uint32_t*>(&re); pi = *reinterpret_cast<const uint32_t*>(&im);
}
__device__ __forceinline__ void sts64(uint32_t a, uint32_t x, uint32_t y) { asm volatile("st.shared.v2.u32 [%0], {%1,%2};" :: "r"(a), "r"(x), "r"(y) : "memory"); }
__device__ __forceinline__ void lds64(uint32_t* v, uint32_t a) { asm volatile("ld.shared.v2.u32 {%0,%1}, [%2];" : "=r"(v[0]), "=r"(v[1]) : "r"(a) : "memory"); }
__device__ __forceinline__ float bf_lo(uint32_t v) { return __uint_as_float(v << 16); }
__device__ __forceinline__ float bf_hi(uint32_t v) { return __uint_as_float(v & 0xffff0000u); }
__device__ __forceinline__ float bf_round(float x) { return bf_lo(pack2(x, 0.f)); }
__device__ __forceinline__ float ex2(float x) { float r; asm("ex2.approx.ftz.f32 %0, %1;" : "=f"(r) : "f"(x)); return r; }
__device__ __forceinline__ float phi(float t, float l2e = 1.44269504089f) {
  float e = ex2(t * l2e) + 1e-6f;
  asm("{\n.reg .pred p;\nsetp.gt.f32 p, %1, 0f00000000;\n@p add.f32 %0, %1, 0f3F800008;\n}" : "+f"(e) : "f"(t));
  return e;
}
__device__ __forceinline__ void wg_fence() { asm volatile("wgmma.fence.sync.aligned;" ::: "memory"); }
__device__ __forceinline__ void wg_commit() { asm volatile("wgmma.commit_group.sync.aligned;" ::: "memory"); }
template <int N> __device__ __forceinline__ void wg_wait() { asm volatile("wgmma.wait_group.sync.aligned %0;" :: "n"(N) : "memory"); }
template <int N> __device__ __forceinline__ void pin(float* a) {
  #pragma unroll
  for (int i = 0; i < N; i++) asm volatile("" : "+f"(a[i]) :: "memory");
}
__device__ __forceinline__ int rtid() { int t; asm volatile("mov.u32 %0, %%tid.x;" : "=r"(t)); return t; }
__device__ __forceinline__ int opaque(int v) { asm volatile("" : "+r"(v)); return v; }
template <int N> __device__ __forceinline__ void zero(float* a) {
  #pragma unroll
  for (int i = 0; i < N; i++) asm volatile("mov.b32 %0, 0;" : "=f"(a[i]));
}
template <int N> __device__ __forceinline__ void pinu(uint32_t* a) {
  #pragma unroll
  for (int i = 0; i < N; i++) asm volatile("" : "+r"(a[i]) :: "memory");
}
__device__ __forceinline__ void cexp_t(float lg2mag, float turns, float& re, float& im) {
  float m = ex2(lg2mag);
  float fr = (turns - __fadd_rn(__fadd_rn(turns, 12582912.f), -12582912.f)) * 6.283185307f;
  re = m * __cosf(fr); im = m * __sinf(fr);
}
__device__ __forceinline__ void cmul(float ar, float ai, float br, float bi, float& cr, float& ci) {
  cr = fmaf(ar, br, -ai * bi); ci = fmaf(ar, bi, ai * br);
}

__device__ __forceinline__ void wg_ss192_tb(float* d, uint64_t da, uint64_t db, int scale_d) {
  asm volatile("{\n.reg .pred p;\nsetp.ne.b32 p, %98, 0;\n"
    "wgmma.mma_async.sync.aligned.m64n192k16.f32.bf16.bf16 "
    "{%0, %1, %2, %3, %4, %5, %6, %7, %8, %9, %10, %11, %12, %13, %14, %15, %16, %17, %18, %19, %20, %21, %22, %23, %24, %25, %26, %27, %28, %29, %30, %31, %32, %33, %34, %35, %36, %37, %38, %39, %40, %41, %42, %43, %44, %45, %46, %47, %48, %49, %50, %51, %52, %53, %54, %55, %56, %57, %58, %59, %60, %61, %62, %63, %64, %65, %66, %67, %68, %69, %70, %71, %72, %73, %74, %75, %76, %77, %78, %79, %80, %81, %82, %83, %84, %85, %86, %87, %88, %89, %90, %91, %92, %93, %94, %95}, %96, %97, p, 1, 1, 0, 1;\n}\n"
    : "+f"(d[0]), "+f"(d[1]), "+f"(d[2]), "+f"(d[3]), "+f"(d[4]), "+f"(d[5]), "+f"(d[6]), "+f"(d[7]), "+f"(d[8]), "+f"(d[9]), "+f"(d[10]), "+f"(d[11]), "+f"(d[12]), "+f"(d[13]), "+f"(d[14]), "+f"(d[15]), "+f"(d[16]), "+f"(d[17]), "+f"(d[18]), "+f"(d[19]), "+f"(d[20]), "+f"(d[21]), "+f"(d[22]), "+f"(d[23]), "+f"(d[24]), "+f"(d[25]), "+f"(d[26]), "+f"(d[27]), "+f"(d[28]), "+f"(d[29]), "+f"(d[30]), "+f"(d[31]), "+f"(d[32]), "+f"(d[33]), "+f"(d[34]), "+f"(d[35]), "+f"(d[36]), "+f"(d[37]), "+f"(d[38]), "+f"(d[39]), "+f"(d[40]), "+f"(d[41]), "+f"(d[42]), "+f"(d[43]), "+f"(d[44]), "+f"(d[45]), "+f"(d[46]), "+f"(d[47]), "+f"(d[48]), "+f"(d[49]), "+f"(d[50]), "+f"(d[51]), "+f"(d[52]), "+f"(d[53]), "+f"(d[54]), "+f"(d[55]), "+f"(d[56]), "+f"(d[57]), "+f"(d[58]), "+f"(d[59]), "+f"(d[60]), "+f"(d[61]), "+f"(d[62]), "+f"(d[63]), "+f"(d[64]), "+f"(d[65]), "+f"(d[66]), "+f"(d[67]), "+f"(d[68]), "+f"(d[69]), "+f"(d[70]), "+f"(d[71]), "+f"(d[72]), "+f"(d[73]), "+f"(d[74]), "+f"(d[75]), "+f"(d[76]), "+f"(d[77]), "+f"(d[78]), "+f"(d[79]), "+f"(d[80]), "+f"(d[81]), "+f"(d[82]), "+f"(d[83]), "+f"(d[84]), "+f"(d[85]), "+f"(d[86]), "+f"(d[87]), "+f"(d[88]), "+f"(d[89]), "+f"(d[90]), "+f"(d[91]), "+f"(d[92]), "+f"(d[93]), "+f"(d[94]), "+f"(d[95])
    : "l"(da), "l"(db), "r"(scale_d));
}
__device__ __forceinline__ void wg_ss48_tb(float* d, uint64_t da, uint64_t db, int scale_d) {
  asm volatile("{\n.reg .pred p;\nsetp.ne.b32 p, %26, 0;\n"
    "wgmma.mma_async.sync.aligned.m64n48k16.f32.bf16.bf16 "
    "{%0, %1, %2, %3, %4, %5, %6, %7, %8, %9, %10, %11, %12, %13, %14, %15, %16, %17, %18, %19, %20, %21, %22, %23}, %24, %25, p, 1, 1, 0, 1;\n}\n"
    : "+f"(d[0]), "+f"(d[1]), "+f"(d[2]), "+f"(d[3]), "+f"(d[4]), "+f"(d[5]), "+f"(d[6]), "+f"(d[7]), "+f"(d[8]), "+f"(d[9]), "+f"(d[10]), "+f"(d[11]), "+f"(d[12]), "+f"(d[13]), "+f"(d[14]), "+f"(d[15]), "+f"(d[16]), "+f"(d[17]), "+f"(d[18]), "+f"(d[19]), "+f"(d[20]), "+f"(d[21]), "+f"(d[22]), "+f"(d[23])
    : "l"(da), "l"(db), "r"(scale_d));
}
__device__ __forceinline__ void wg_ss48_tt(float* d, uint64_t da, uint64_t db, int scale_d) {
  asm volatile("{\n.reg .pred p;\nsetp.ne.b32 p, %26, 0;\n"
    "wgmma.mma_async.sync.aligned.m64n48k16.f32.bf16.bf16 "
    "{%0, %1, %2, %3, %4, %5, %6, %7, %8, %9, %10, %11, %12, %13, %14, %15, %16, %17, %18, %19, %20, %21, %22, %23}, %24, %25, p, 1, 1, 1, 1;\n}\n"
    : "+f"(d[0]), "+f"(d[1]), "+f"(d[2]), "+f"(d[3]), "+f"(d[4]), "+f"(d[5]), "+f"(d[6]), "+f"(d[7]), "+f"(d[8]), "+f"(d[9]), "+f"(d[10]), "+f"(d[11]), "+f"(d[12]), "+f"(d[13]), "+f"(d[14]), "+f"(d[15]), "+f"(d[16]), "+f"(d[17]), "+f"(d[18]), "+f"(d[19]), "+f"(d[20]), "+f"(d[21]), "+f"(d[22]), "+f"(d[23])
    : "l"(da), "l"(db), "r"(scale_d));
}
__device__ __forceinline__ void wg_rs88_tb(float* d, const uint32_t* a, uint64_t db, int scale_d) {
  asm volatile("{\n.reg .pred p;\nsetp.ne.b32 p, %49, 0;\n"
    "wgmma.mma_async.sync.aligned.m64n88k16.f32.bf16.bf16 "
    "{%0, %1, %2, %3, %4, %5, %6, %7, %8, %9, %10, %11, %12, %13, %14, %15, %16, %17, %18, %19, %20, %21, %22, %23, %24, %25, %26, %27, %28, %29, %30, %31, %32, %33, %34, %35, %36, %37, %38, %39, %40, %41, %42, %43}, {%44, %45, %46, %47}, %48, p, 1, 1, 1;\n}\n"
    : "+f"(d[0]), "+f"(d[1]), "+f"(d[2]), "+f"(d[3]), "+f"(d[4]), "+f"(d[5]), "+f"(d[6]), "+f"(d[7]), "+f"(d[8]), "+f"(d[9]), "+f"(d[10]), "+f"(d[11]), "+f"(d[12]), "+f"(d[13]), "+f"(d[14]), "+f"(d[15]), "+f"(d[16]), "+f"(d[17]), "+f"(d[18]), "+f"(d[19]), "+f"(d[20]), "+f"(d[21]), "+f"(d[22]), "+f"(d[23]), "+f"(d[24]), "+f"(d[25]), "+f"(d[26]), "+f"(d[27]), "+f"(d[28]), "+f"(d[29]), "+f"(d[30]), "+f"(d[31]), "+f"(d[32]), "+f"(d[33]), "+f"(d[34]), "+f"(d[35]), "+f"(d[36]), "+f"(d[37]), "+f"(d[38]), "+f"(d[39]), "+f"(d[40]), "+f"(d[41]), "+f"(d[42]), "+f"(d[43])
    : "r"(a[0]), "r"(a[1]), "r"(a[2]), "r"(a[3]), "l"(db), "r"(scale_d));
}
__device__ __forceinline__ void wg_ss80_tb(float* d, uint64_t da, uint64_t db, int scale_d) {
  asm volatile("{\n.reg .pred p;\nsetp.ne.b32 p, %42, 0;\n"
    "wgmma.mma_async.sync.aligned.m64n80k16.f32.bf16.bf16 "
    "{%0, %1, %2, %3, %4, %5, %6, %7, %8, %9, %10, %11, %12, %13, %14, %15, %16, %17, %18, %19, %20, %21, %22, %23, %24, %25, %26, %27, %28, %29, %30, %31, %32, %33, %34, %35, %36, %37, %38, %39}, %40, %41, p, 1, 1, 0, 1;\n}\n"
    : "+f"(d[0]), "+f"(d[1]), "+f"(d[2]), "+f"(d[3]), "+f"(d[4]), "+f"(d[5]), "+f"(d[6]), "+f"(d[7]), "+f"(d[8]), "+f"(d[9]), "+f"(d[10]), "+f"(d[11]), "+f"(d[12]), "+f"(d[13]), "+f"(d[14]), "+f"(d[15]), "+f"(d[16]), "+f"(d[17]), "+f"(d[18]), "+f"(d[19]), "+f"(d[20]), "+f"(d[21]), "+f"(d[22]), "+f"(d[23]), "+f"(d[24]), "+f"(d[25]), "+f"(d[26]), "+f"(d[27]), "+f"(d[28]), "+f"(d[29]), "+f"(d[30]), "+f"(d[31]), "+f"(d[32]), "+f"(d[33]), "+f"(d[34]), "+f"(d[35]), "+f"(d[36]), "+f"(d[37]), "+f"(d[38]), "+f"(d[39])
    : "l"(da), "l"(db), "r"(scale_d));
}
__device__ __forceinline__ void wg_ss48_tt_h(float* d, uint64_t da, uint64_t db, int scale_d) {
  asm volatile("{\n.reg .pred p;\nsetp.ne.b32 p, %26, 0;\n"
    "wgmma.mma_async.sync.aligned.m64n48k16.f32.f16.f16 "
    "{%0, %1, %2, %3, %4, %5, %6, %7, %8, %9, %10, %11, %12, %13, %14, %15, %16, %17, %18, %19, %20, %21, %22, %23}, %24, %25, p, 1, 1, 1, 1;\n}\n"
    : "+f"(d[0]), "+f"(d[1]), "+f"(d[2]), "+f"(d[3]), "+f"(d[4]), "+f"(d[5]), "+f"(d[6]), "+f"(d[7]), "+f"(d[8]), "+f"(d[9]), "+f"(d[10]), "+f"(d[11]), "+f"(d[12]), "+f"(d[13]), "+f"(d[14]), "+f"(d[15]), "+f"(d[16]), "+f"(d[17]), "+f"(d[18]), "+f"(d[19]), "+f"(d[20]), "+f"(d[21]), "+f"(d[22]), "+f"(d[23])
    : "l"(da), "l"(db), "r"(scale_d));
}

struct Params {
  const __nv_bfloat16 *par[4], *logdt, *dskip, *u, *wo;
  CUtensorMap m[M_COUNT];
};

#define CHUNK(i) ((i) == 0 ? c : ((i) == 7 ? (c ^ 1) : (((c & 6) + 1 + (i)) & 7)))
#define FLAG(kind, rr, cc) (&g_flag[((kind) * 128 + (rr) * 8 + (cc)) * 32])
#define SLOT(i) ((i) == 0 || (i) == 1 ? OFF_EXTRA : OFF_BLK - 256 + ((i) == 7 ? 0 : (i) - 2) * BLK)
__device__ __forceinline__ void load_quad(uint32_t* A, uint32_t addr) {
  A[0] = lds32v(addr); A[1] = lds32v(addr + 32); A[2] = lds32v(addr - 32); A[3] = lds32v(addr);
}

__device__ __forceinline__ bool y_transpose(uint32_t sb, int w5, int lane, uint32_t ytag) {
  const int mi = lane >> 3, rw = lane & 7;
  const uint32_t sa = sb + OFF_EXTRA + (w5 * 16 + rw) * 128 + ((mi ^ rw) << 4), da = sb + SLOT(3) + (8 * mi + rw) * 160 + w5 * 32;
  const uint32_t ym = lane < 4 ? 0x10001u : 0u;
  bar_sync(7, 160);
  uint32_t v[8][4], bad = 0;
  #pragma unroll
  for (int q = 0; q < 8; q++) ldsm4t(v[q], (sa ^ ((q & 1) * 64 + ((q >> 1) & 1) * 16)) + ((q >> 1) & 1) * 10240 + (q >> 2) * 1024);
  #pragma unroll
  for (int q = 0; q < 8; q++) {
    bad |= (v[q][0] ^ ytag) | (v[q][2] ^ ytag);
    stsm4(da + (q & 3) * 5120 + (q >> 2) * 16, v[q][0] & ~ym, v[q][1], v[q][2] & ~ym, v[q][3]);
  }
  fence_async();
  uint32_t any;
  asm volatile("{\n.reg .pred p;\nsetp.ne.u32 p, %1, 0;\nbarrier.red.or.pred p, 7, 160, p;\nselp.u32 %0, 1, 0, p;\n}" : "=r"(any) : "r"(bad & ym) : "memory");
  return any;
}

__global__ void __launch_bounds__(512, 1) fused_kernel(const __grid_constant__ Params prm) {
  extern __shared__ unsigned char smem_raw[];
  const uint32_t sb = __shfl_sync(0xffffffff, smem_u32(smem_raw), 0);
  const int tid = threadIdx.x, lane = tid & 31;
  const int warp = __shfl_sync(0xffffffff, tid >> 5, 0), wg = warp >> 2, w4 = warp & 3;
  const int cta = blockIdx.x, r = cta >> 3, c = cta & 7;
  if ((sb & 0xffffffu) != SB0) return;
#define BAR(i) (sb + OFF_BAR + 8 * (i))
  const bool sw64 = ((c + 1) & 2) != 0;

  if (wg == 3) {
    if (warp == 13 && elect_one()) {
      #pragma unroll
      for (int i = M_W128; i <= M_U; i++) asm volatile("prefetch.tensormap [%0];" :: "l"(&prm.m[i]) : "memory");
    }
    asm volatile("setmaxnreg.dec.sync.aligned.u32 56;");
    const int tid = rtid(), lane = tid & 31;
    if (warp == 12) {
      if (elect_one()) {
        #pragma unroll
        for (int i = 0; i < 5; i++) mbar_init(BAR(BR_FULL + i), 1);
        asm volatile("fence.mbarrier_init.release.cluster;" ::: "memory");
      }
      {
        const CUtensorMap* mwp = &prm.m[sw64 ? M_W64 : M_W128];
        const int mcol = (c * 80 + (c & 1) * 16) >> (sw64 ? 5 : 6), rcol = c * 80 + ((c & 1) ? 0 : 64);
        uint32_t s = 0, ph = 1, xs = 0;
        #pragma unroll 1
        for (int kb = 0; kb < 20; kb++) {
          if (kb == 1) asm volatile("bar.arrive 0, 512;" ::: "memory");
          if (kb == 4) { bar_sync(6, 128); if (EN_SSM) mbar_wait(BAR(BR_KS), 0); }
          if (kb >= 5) mbar_wait(BAR(BR_EMPTY) + 8 * s, ph);
          if (EN_ATT && elect_one()) {
            const uint32_t st = sb + s * W_SLOT, fb = BAR(BR_FULL) + 8 * s;
            mbar_expect_tx(fb, (kb & 1) ? W_SLOT : W_SLOT + 16384);
            if (!(kb & 1)) tma2d(sb + OFF_X + xs, &prm.m[M_X], fb, kb * 32, r * 128);
            tma4d(st, mwp, fb, 0, kb * 32, mcol, 0);
            tma3d(st + 12288, &prm.m[M_WR], fb, rcol, kb * 32, 0);
          }
          if (kb < 4 && lane == 0) TS(24 + kb);
          if (kb == 14 && elect_one()) asm volatile("cp.async.bulk.prefetch.L2.global [%0], 6400;" :: "l"(prm.wo + cta * 3200) : "memory");
          if (!EN_ATT && kb == 4) break;
          if (++s == 5) { s = 0; ph ^= 1; }
          if (kb & 1) { xs += 16384; if (xs == 49152) xs = 0; }
        }
      }
      if (EN_ATT) {
      mbar_wait(BAR(BR_EPOCH), 0);
      const unsigned epoch = lds32(sb + OFF_EPOCH);
      const unsigned* fo = FLAG(3, r, lane & 7);
      unsigned seen = __ballot_sync(0xffffffff, ld_rlx(lane < 16 ? fo : FLAG(0, lane & 15, c)) == epoch) & 0xffu;
      mbar_wait(BAR(BR_GEMM), 0);
      if (elect_one()) {
        mbar_expect_tx(BAR(BR_WO), 10240);
        tma2d(sb, &prm.m[M_WO], BAR(BR_WO), c * 64, c * 80);
        mbar_expect_tx(BAR(BR_KVP), 61440);
        mbar_expect_tx(BAR(BR_WO + 1), 7 * 10240);
      }
      {
        uint32_t ds = sb + OFF_WOR + (lane >> 3) * 128 + (((lane & 7) ^ (lane >> 3)) << 4);
        #pragma unroll 1
        for (int h = 0; h < 2; h++) {
          const int i = (lane & 6) + h;
          const char* gs = reinterpret_cast<const char*>(prm.wo) + (size_t)((lane >> 3) + CHUNK(i) * 80) * 1280 + 1024 + c * 32 + (lane & 1) * 16;
          #pragma unroll 2
          for (int q = 0; q < 20; q++) {
            asm volatile("cp.async.cg.shared.global [%0], [%1], 16;" :: "r"(ds), "l"(gs) : "memory");
            ds = (ds + 512) ^ 64; gs += 5120;
          }
        }
      }
      mbar_wait(BAR(BR_PUB), 0);
      poll_all(FLAG(0, lane & 15, c), epoch);
      if (elect_one()) { TS(23); bulk_ld(sb + OFF_KVP, &g_kvp[c * 16 * 240], 61440, BAR(BR_KVP)); }
      asm volatile("cp.async.wait_all;" ::: "memory");
      fence_async();
      mbar_arrive(BAR(BR_WO));
      mbar_wait(BAR(BR_SUM), 0);
      if (elect_one()) {
        #pragma unroll 1
        for (int i = 1; i < 8; i++) tma2d(sb + i * 10240, &prm.m[M_WO], BAR(BR_WO + 1), c * 64, CHUNK(i) * 80);
      }
      mbar_wait(BAR(BR_OSTG), 0);
      if (elect_one()) {
        bulk_st(&g_o[cta * 1280], sb + OFF_EXTRA, 20480);
        bulk_commit();
        bulk_wait0();
        st_rlx(FLAG(3, r, c), epoch);
        TS(20);
      }
      __syncwarp();
      #pragma unroll 1
      for (int i = 1; i < 8; i++) {
        const int src = CHUNK(i);
        if (!((seen >> src) & 1)) seen = poll_bit(fo, epoch, 1u << src);
        if (i == 1 || i == 7) mbar_wait(BAR(BR_OEMPTY) + 8 * (i & 2), 0);
        if (EN_SSM && (i == 2 || i == 6)) mbar_wait(BAR(BR_FREE) + 2 * (i & 4), 0);
        if (elect_one()) {
          mbar_expect_tx(BAR(BR_OFULL) + 8 * i, 20480);
          bulk_ld(sb + SLOT(i), &g_o[(r * 8 + src) * 1280], 20480, BAR(BR_OFULL) + 8 * i);
          if (i == 1) TS(21);
          if (i == 7) TS(22);
        }
        __syncwarp();
      }
      if (lane == 0) { DUMP(20, 30); }
      }
    } else {
      const int hw = warp - 13, ht = tid - 416;
      if (hw == 2 && elect_one()) {
        #pragma unroll
        for (int i = 5; i < BR_COUNT; i++) mbar_init(BAR(i), i == BR_WO ? 33 : i < BR_EMPTY ? 1 : i < BR_OEMPTY ? 2 : i < BR_Y ? 8 : i < BR_OSTG ? 4 : i == BR_OSTG ? 8 : i < BR_U2 ? 3 : 1);
        asm volatile("fence.mbarrier_init.release.cluster;" ::: "memory");
        if (EN_SSM) { mbar_expect_tx(BAR(BR_UIN), 20480); tma2d(sb + OFF_UT, &prm.m[M_U], BAR(BR_UIN), c * 80, r * 128); }
      }
      __syncwarp();
      asm volatile("bar.arrive 0, 512;" ::: "memory");
      const unsigned epoch = hw == 0 ? ld_rlx(&g_epoch[cta]) + 1 : 0;
      bar_sync(5, 96);
      asm volatile("bar.arrive 6, 128;" ::: "memory");
      if (hw == 1 && elect_one()) {
        #pragma unroll
        for (int i = M_WO; i < M_COUNT; i++) asm volatile("prefetch.tensormap [%0];" :: "l"(&prm.m[i]) : "memory");
      }
      if (ht == 0) {
        st_rlx(&g_epoch[cta], epoch);
        sts32(sb + OFF_EPOCH, epoch);
        mbar_arrive(BAR(BR_EPOCH));
      }
      if (EN_SSM) {
      const int mi = lane >> 3, rw = lane & 7, ch0 = c * 80 + r * 5;
      mbar_wait(BAR(BR_UIN), 0);
      if (ht == 0) TS(36);
      #pragma unroll 1
      for (int h = 0; h < 2; h++) {
        const uint32_t sa = sb + OFF_UT + h * 10240 + (8 * mi + rw) * 160 + hw * 16, da = sb + OFF_UT + h * 10240 + (hw * 8 + rw) * 128 + ((mi ^ rw ^ h) << 4);
        uint32_t v[8][4];
        #pragma unroll
        for (int q = 0; q < 8; q++) if (q < 6 || hw == 0) ldsm4t(v[q], sa + (q & 1) * 5120 + (q >> 1) * 48);
        bar_sync(5, 96);
        #pragma unroll
        for (int q = 0; q < 8; q++) if (q < 6 || hw == 0) stsm4((da ^ ((q & 1) * 64)) + (q >> 1) * 3072, v[q][0], v[q][1], v[q][2], v[q][3]);
      }
      fence_async();
      bar_sync(5, 96);
      if (hw == 0) {
        if (elect_one()) {
          tma2d_st(&prm.m[M_SA], sb + OFF_UT, r * 128, c * 80);
          tma2d_st(&prm.m[M_SA], sb + OFF_UT + 10240, r * 128 + 64, c * 80);
          bulk_commit(); bulk_wait0_read();
          mbar_arrive(BAR(BR_UOUT));
          TS(37);
          bulk_wait0();
          st_rel(FLAG(1, r, c), epoch);
          TS(30);
        }
        __syncwarp();
        poll_all_acq(FLAG(1, lane & 15, c), epoch);
      }
      #pragma unroll 1
      for (int q6 = hw; q6 < 30; q6 += 3) {
        if (q6 >= 24 && q6 < 27) { __syncwarp(); if (lane == 0) mbar_arrive(BAR(BR_DRDY)); }
        if (q6 < 3 || (q6 >= 18 && q6 < 21)) {
          const int p = q6 >= 18;
          if (hw == 0) {
            if (!p) {
              mbar_wait(BAR(BR_KS + 2), 0);
              if (elect_one()) {
                fence_async_g();
                mbar_expect_tx(BAR(BR_U), 12288);
                #pragma unroll 1
                for (int q = 0; q < 3; q++) bulk_ld(sb + OFF_BLK + q * BLK, g_uy + (ch0 + q) * 2048, 4096, BAR(BR_U));
                TS(31);
              }
              __syncwarp();
            }
            mbar_wait(BAR(p ? BR_U2 : BR_U), 0);
          }
          bar_sync(5, 96);
          if (ht == 0) TS(38 + p);
        }
        {
          const int k = q6 / 6, kap = (q6 - 6 * k) * 32 + lane;
          const uint32_t blk = sb + OFF_BLK + k * BLK;
          float P[33];
          P[0] = 0.f;
          #pragma unroll
          for (int q = 0; q < 4; q++) {
            const int ch = kap - 3 + q;
            uint32_t v[4];
            lds128(v, blk + (uint32_t)((ch * 16) ^ ((ch * 2) & 0x10)));
            #pragma unroll
            for (int e = 0; e < 4; e++) {
              P[q * 8 + 2 * e + 1] = (q == 0 && e < 2) ? 0.f : P[q * 8 + 2 * e] + bf_lo(v[e]);
              P[q * 8 + 2 * e + 2] = (q == 0 && e < 2) ? 0.f : P[q * 8 + 2 * e + 1] + bf_hi(v[e]);
            }
          }
#define WIN(lo, hi, e) (P[25 + (e) - (lo)] - P[24 + (e) - (hi)])
#define WIN8(lo, hi) pack2(WIN(lo, hi, 0), WIN(lo, hi, 1)), pack2(WIN(lo, hi, 2), WIN(lo, hi, 3)), pack2(WIN(lo, hi, 4), WIN(lo, hi, 5)), pack2(WIN(lo, hi, 6), WIN(lo, hi, 7))
          const uint32_t o2 = blk + B_D + (kap & 1) * 1552 + (kap >> 1) * 16;
          sts128(o2, WIN8(3, 5));
          sts128(o2 + B_D5, WIN8(6, 10));
          if (kap < 2) sts128(blk + B_D + kap * B_D5 + 1536, 0, 0, 0, 0);
          if (kap < 128) {
            const uint32_t o = blk + B_D + (kap & 1) * 1024 + (kap >> 1) * 16;
            sts128(o + B_D7, WIN8(5, 11));
            sts128(o + B_D9, WIN8(12, 20));
          }
        }
      }
      __syncwarp();
      if (lane == 0) mbar_arrive(BAR(BR_DRDY + 1));
      if (ht == 0) TS(32);
      if (hw == 0) {
        #pragma unroll 1
        for (int p = 0; p < 2; p++) {
          mbar_wait(BAR(BR_Y) + 8 * p, 0);
          if (elect_one()) {
            #pragma unroll 1
            for (int k = 4 * p; k < 4 + p; k++) bulk_st(g_uy + (640 + ch0 + k) * 2048, sb + OFF_BLK + k * BLK, 4096);
            bulk_commit(); bulk_wait0_read();
            mbar_arrive(BAR(BR_FREE) + 8 * p);
          }
          __syncwarp();
        }
        if (elect_one()) { bulk_wait0(); st_rlx(FLAG(2, r, c), epoch); TS(33); }
        __syncwarp();
        poll_all(FLAG(2, lane & 15, c), epoch);
        if (EN_ATT) mbar_wait(BAR(BR_OEMPTY + 1), 0);
        #pragma unroll 1
        for (int n = 0; n < 64; n++) {
          if (elect_one()) {
            mbar_expect_tx(BAR(BR_YIN), 20480);
            tma2d(sb + OFF_EXTRA, &prm.m[M_SA], BAR(BR_YIN), r * 128, 640 + c * 80);
            tma2d(sb + OFF_EXTRA + 10240, &prm.m[M_SA], BAR(BR_YIN), r * 128 + 64, 640 + c * 80);
            TS(34);
          }
          __syncwarp();
          if (EN_ATT) mbar_wait(BAR(BR_OEMPTY + 3), 0);
          mbar_wait(BAR(BR_YIN), n & 1);
          if (!y_transpose(sb, 4, lane, (epoch & 1u) * 0x10001u)) break;
          FIXCNT
        }
      if (elect_one()) {
        tma2d_st(&prm.m[M_OUT], sb + SLOT(3), c * 80, r * 128);
        bulk_commit(); bulk_wait0_read();
        TS(35); DUMP(30, 40); DUMP(0, 1);
      }
      }
      }
    }
  } else {
    const int g = lane >> 2, tq = lane & 3, t7 = tid & 127;
    uint32_t pr[3][2], pd;
    {
      const int ch = c * 80 + r * 5 + wg;
      uint32_t raw[3][4];
      #pragma unroll
      for (int e = 0; e < 4; e++) {
        const __nv_bfloat16* pp = prm.par[e] + ch * 128 + t7;
        #pragma unroll
        for (int q = 0; q < 3; q++) {
          raw[q][e] = 0;
          if (q == 0 || wg == 2) asm volatile("ld.global.nc.u16 %0, [%1];" : "=r"(raw[q][e]) : "l"(pp + q * 128));
        }
      }
      asm volatile("ld.global.nc.u16 %0, [%1];" : "=r"(pd) : "l"(((lane & 4) ? prm.dskip : prm.logdt) + ch + min(lane & 3, 2)));
      asm volatile("setmaxnreg.inc.sync.aligned.u32 152;");
      if (EN_SSM && wg < 2) {
        #pragma unroll
        for (int k = 0; k < 2; k++) {
          const uint32_t z = sb + OFF_BLK + (2 * wg + k) * BLK + t7 * 16;
          sts128(z + B_TBL, 0, 0, 0, 0); sts128(z + B_TBL + 2048, 0, 0, 0, 0);
        }
        if (tid < 80) sts128(sb + OFF_BLK + (tid >> 4) * BLK - 256 + (tid & 15) * 16, 0, 0, 0, 0);
      }
      #pragma unroll
      for (int q = 0; q < 3; q++) {
        #pragma unroll
        for (int e = 0; e < 2; e++) pr[q][e] = raw[q][2 * e] | (raw[q][2 * e + 1] << 16);
        const uint32_t m = __reduce_max_sync(0xffffffff, max(raw[q][2] & 0x7fffu, raw[q][3] & 0x7fffu));
        if (lane == 0) sts32(sb + OFF_EPOCH + 64 + (wg * 3 + q) * 16 + w4 * 4, m);
      }
      bar_sync(2 + wg, 128);
    }
    if (tid == 256) TS(40);
    if (EN_SSM) {
#define P0(w) ((w) == 1 ? 4 * W_SLOT : OFF_BLK + (w) * BLK)
#define P2(w) ((w) == 1 ? OFF_X + 32768 - 4 * W_SLOT : BLK)
      uint32_t ea = sb + P0(wg) + (lane >> 4) * 7168 + (w4 & 1) * P2(wg) + ((lane >> 3) & 1) * 256 + (lane & 7) * 16 + (w4 >> 1) * 2048;
      constexpr uint64_t dE = mkdesc(SB0, 128, 512, 0);
      const uint32_t xa = sb + OFF_BLK + 18560 + t7 * 8, xr_ = sb + OFF_BLK + 18560 + (t7 ^ 64) * 8;
      float ka[24]; zero<24>(ka);
      wg_fence();
      wg_ss48_tt_h(ka, dE + (OFF_BLK >> 4), dE + (OFF_BLK >> 4), 0);
      wg_commit();
      #pragma unroll 1
      for (int it = -1; it < 5; it++) {
        const int k = it < 2 ? 1 - it : it;
        const bool nf = it < 0 || it == 2 || it == 3;
        const uint32_t blk = sb + OFF_BLK + k * BLK;
        uint32_t F[56];
#define PUT4(i, a, b, c_, d) { F[4 * (i)] = a; F[4 * (i) + 1] = b; F[4 * (i) + 2] = c_; F[4 * (i) + 3] = d; }
        if (nf) {
          const int q = it < 0 ? 0 : it - 1;
          const uint32_t pa0 = pr[0][0], pc0 = pr[0][1];
          const float dt = bf_round(expf(bf_lo(__shfl_sync(0xffffffff, pd, q))));
          #pragma unroll
          for (int e = 0; e < 2; e++) { pr[0][e] = pr[1][e]; pr[1][e] = pr[2][e]; }
          uint32_t mm[4];
          lds128(mm, sb + OFF_EPOCH + 64 + (wg * 3 + q) * 16);
          const uint32_t ex = min(max(max(max(mm[0], mm[1]), max(mm[2], mm[3])) >> 7, 1u), 253u);
          const float sc = __uint_as_float((254u - ex) << 23);
          if (t7 == 4 + q) sts64(sb + OFF_EPOCH + 16 + (wg + q) * 8, __float_as_uint(2.f * dt * __uint_as_float(ex << 23)), pd << 16);
          const float lr = -bf_round(expf(bf_lo(pa0))) * dt * 1.44269504089f;
          const float tn = bf_hi(pa0) * dt * 0.15915494309f;
          float z1r, z1i, z2r, z2i, z4r, z4i, xr[8], xi[8], gr[8], gi[8], wr[9], wi[9];
          cexp_t(lr, -tn, z1r, z1i);
          cexp_t(lr * 8.f, tn * 8.f, xr[1], xi[1]);
          cexp_t(lr * 64.f, tn * 64.f, wr[0], wi[0]);
          xr[0] = 1.f; xi[0] = 0.f;
          cmul(xr[1], xi[1], xr[1], xi[1], xr[2], xi[2]); cmul(xr[2], xi[2], xr[1], xi[1], xr[3], xi[3]);
          cmul(xr[2], xi[2], xr[2], xi[2], xr[4], xi[4]);
          #pragma unroll
          for (int b = 1; b < 4; b++) cmul(xr[4], xi[4], xr[b], xi[b], xr[4 + b], xi[4 + b]);
          cmul(wr[0], wi[0], wr[0], wi[0], wr[1], wi[1]); cmul(wr[1], wi[1], wr[0], wi[0], wr[2], wi[2]);
          cmul(wr[1], wi[1], wr[1], wi[1], wr[3], wi[3]); cmul(wr[3], wi[3], wr[3], wi[3], wr[4], wi[4]);
          cmul(wr[4], wi[4], wr[3], wi[3], wr[5], wi[5]); cmul(wr[4], wi[4], wr[4], wi[4], wr[6], wi[6]);
          cmul(wr[6], wi[6], wr[4], wi[4], wr[7], wi[7]); cmul(wr[6], wi[6], wr[6], wi[6], wr[8], wi[8]);
          uint32_t R[4], I[4], PR[4], PI[4];
          #pragma unroll
          for (int b = 0; b < 4; b++) { R[b] = packh(xr[2 * b], xr[2 * b + 1]); I[b] = packh(xi[2 * b], xi[2 * b + 1]); }
          PUT4(0, R[0], R[1], R[2], R[3]); PUT4(1, I[0], I[1], I[2], I[3]);
          #pragma unroll
          for (int i = 0; i < 3; i++) {
            const uint32_t z = packh(wr[i], wi[i]);
            #pragma unroll
            for (int b = 0; b < 4; b++) hcm2(R[b], I[b], z, PR[b], PI[b]);
            PUT4(2 * i + 2, PR[0], PR[1], PR[2], PR[3]); PUT4(2 * i + 3, PI[0], PI[1], PI[2], PI[3]);
          }
          gr[0] = bf_lo(pc0) * sc; gi[0] = -bf_hi(pc0) * sc;
          cmul(z1r, z1i, z1r, z1i, z2r, z2i); cmul(z2r, z2i, z2r, z2i, z4r, z4i);
          cmul(gr[0], gi[0], z1r, z1i, gr[1], gi[1]);
          cmul(gr[0], gi[0], z2r, z2i, gr[2], gi[2]); cmul(gr[1], gi[1], z2r, z2i, gr[3], gi[3]);
          #pragma unroll
          for (int b = 0; b < 4; b++) cmul(gr[b], gi[b], z4r, z4i, gr[4 + b], gi[4 + b]);
          PUT4(8, packh(gr[0], gr[1]), packh(gr[2], gr[3]), packh(gr[4], gr[5]), packh(gr[6], gr[7]));
          PUT4(9, packh(gi[0], gi[1]), packh(gi[2], gi[3]), packh(gi[4], gi[5]), packh(gi[6], gi[7]));
          {
            const uint32_t z = packh(wr[3], -wi[3]), a4r = packh(gr[0], gr[4]), a4i = packh(gi[0], gi[4]);
            hcm2(packh(gr[0], gr[2]), packh(gi[0], gi[2]), z, PR[0], PI[0]);
            hcm2(packh(gr[4], gr[6]), packh(gi[4], gi[6]), z, PR[1], PI[1]);
            hcm2(a4r, a4i, packh(wr[4], -wi[4]), PR[2], PI[2]);
            hcm2(a4r, a4i, packh(wr[5], -wi[5]), PR[3], PI[3]);
            PUT4(10, PR[0], PR[1], PR[2], PR[3]); PUT4(11, PI[0], PI[1], PI[2], PI[3]);
            float hr, hi_;
            cmul(gr[0], gi[0], wr[3], -wi[3], hr, hi_);
            const uint32_t cr = packh(gr[0], hr), ci = packh(gi[0], hi_);
            #pragma unroll
            for (int i = 0; i < 3; i++) hcm2(cr, ci, packh(wr[6 + i], -wi[6 + i]), PR[i], PI[i]);
            PUT4(12, PR[0], PR[1], PR[2], 0u); PUT4(13, PI[0], PI[1], PI[2], 0u);
          }
        }
        else {
          #pragma unroll
          for (int i = 0; i < 56; i++) asm volatile("" : "=r"(F[i]));
        }
        uint32_t fd[2];
        lds64(fd, sb + OFF_EPOCH + 16 + k * 8);
        const float fac = __uint_as_float(fd[0]), dsk = __uint_as_float(fd[1]);
        wg_wait<0>();
        pin<24>(ka);
        float kk[6];
        const bool up = w4 >= 2;
        if (it == 1 || it == 2) bar_sync(4, 128);
        #pragma unroll
        for (int n = 0; n < 3; n++) {
          if (it >= 0) sts64f(xa + n * BLK, up ? ka[12 + 4 * n] : ka[4 * n + 2], up ? ka[13 + 4 * n] : ka[4 * n + 3]);
          kk[2 * n] = up ? ka[14 + 4 * n] : ka[4 * n]; kk[2 * n + 1] = up ? ka[15 + 4 * n] : ka[4 * n + 1];
        }
        pin<6>(kk);
        if (it >= 0) {
          bar_sync(4, 128);
          if (t7 == 0) mbar_arrive(BAR(BR_KS) + 8 * it);
          if (it == 4 && w4 == 0) {
            mbar_wait(BAR(BR_U), 0);
            if (elect_one()) {
              mbar_expect_tx(BAR(BR_U2), 8192);
              bulk_ld(blk - BLK, g_uy + (c * 80 + r * 5 + 3) * 2048, 4096, BAR(BR_U2)); bulk_ld(blk, g_uy + (c * 80 + r * 5 + 4) * 2048, 4096, BAR(BR_U2));
            }
            __syncwarp();
          }
          #pragma unroll
          for (int n = 0; n < 3; n++) {
            uint32_t o[2]; lds64(o, xr_ + n * BLK);
            kk[2 * n] = (kk[2 * n] + __uint_as_float(o[0])) * fac; kk[2 * n + 1] = (kk[2 * n + 1] + __uint_as_float(o[1])) * fac;
          }
        }
        if (nf) {
          if (it == 2) {
            mbar_wait(BAR(BR_UOUT), 0);
            ea += BLK;
            sts128(sb + OFF_UT + B_TBL + t7 * 16, 0, 0, 0, 0); sts128(sb + OFF_UT + B_TBL + 2048 + t7 * 16, 0, 0, 0, 0);
          }
          const uint32_t ga = ea + 4096 - (w4 >> 1) * 512;
          #pragma unroll
          for (int i = 0; i < 14; i++) sts128((i < 8 ? ea + (i >> 1) * 512 : ga + ((i - 8) >> 1) * 512) + (i & 1) * 128, F[4 * i], F[4 * i + 1], F[4 * i + 2], F[4 * i + 3]);
          fence_async();
          bar_sync(it < 0 ? 0 : 4, it < 0 ? 512 : 128);
          if (wg < 2) break;
        }
        if (it < 4) {
          const int fs = (0x33201 >> (4 * it + 4)) & 3;
          wg_fence();
          #pragma unroll
          for (int s = 0; s < 8; s++) {
            const uint32_t lo = (uint32_t)dE + ((P0(fs) + (s >> 2) * P2(fs)) >> 4) + ((s >> 1) & 1) * 448 + (s & 1) * 16;
            wg_ss48_tt_h(ka, desc2(lo, dE >> 32), desc2(lo + 256, dE >> 32), s != 0);
          }
          wg_commit();
        }
        if (it >= 0)
        {
          const int j = (w4 & 1) * 16 + (w4 >> 1) * 8 + g;
          const uint32_t tb = blk + B_TBL;
          if (t7 == 0) kk[0] += dsk;
          const uint32_t pa_ = tb + (16 + 8 * j + 2 * tq) * 4;
          const uint32_t v = pack2(kk[1], kk[0]);
          sts32(pa_ + 4, v); sts16(pa_, v >> 16); sts16(pa_ + 10, v);
          const uint32_t u = pack2(kk[2], kk[3]), w = pack2(kk[4], kk[5]);
          if (tq < 2) {
            const uint32_t pb = tb + (16 + 256 + 8 * j + 4 * tq) * 4;
            sts16(pb, u); sts32(pb + 4, __byte_perm(u, 0, 0x1010)); sts32(pb + 8, __byte_perm(u, 0, 0x1032)); sts16(pb + 14, u >> 16);
            if (j | tq) { sts16(pb - 4, u); sts16(pb + 2, u); }
            const int i = 64 * tq + j;
            const uint32_t e0 = tb + (T_F3 + (((i - 1) & 1) ? 80 : 0) + ((i - 1) >> 1)) * 4, e1 = i ? e0 : tb + (T_F2 + 144 + 31) * 4;
            sts16(e1, w); sts16(e1 + 6, w); sts16(e0 + 64, w >> 16); sts16(e0 + 70, w >> 16);
            if (i == 0) { sts16(tb + (T_S + 3) * 4, w); sts32(tb + (T_S + 4) * 4, __byte_perm(w, 0, 0x1010)); sts16(tb + (T_S + 5) * 4 + 2, w); }
          } else {
            const int i = 32 * (tq - 2) + j;
            const uint32_t e1 = tb + (i ? T_F2 + ((2 * i - 1) & 3) * 48 + ((2 * i - 1) >> 2) : 16 + 511) * 4;
            const uint32_t e2 = tb + (T_F2 + (i & 1) * 96 + (i >> 1)) * 4;
            sts16(e1, u); sts16(e1 + 6, u); sts16(e2, u >> 16); sts16(e2 + 6, u >> 16);
            if (i == 0) {
              const uint32_t uu = __byte_perm(u, 0, 0x1010);
              sts32(tb + 528 * 4, uu); sts32(tb + 529 * 4, uu); sts32(tb + 530 * 4, uu); sts16(tb + 531 * 4 + 2, u);
              sts16(tb + (T_F3 + 80 + 63) * 4, w);
            }
          }
        }
        if (t7 == 0) TS(49 + it);
      }
      wg_wait<0>();
      pin<24>(ka);
    }
    if (!EN_SSM) bar_sync(0, 512);
    if (tid == 0) TS(14);
  if (wg < 2) {
    if (EN_ATT) {
    float am[96], ar[24];
    {
      const bool lead = (rtid() & 127) == 0;
      constexpr uint64_t da0 = mkdesc(SB0 + OFF_X, 16, 1024, 1), dr0 = mkdesc(SB0 + 12288, 1024, 256, 3);
      const uint64_t db0 = sw64 ? mkdesc(SB0, 2048, 512, 2) : mkdesc(SB0, 4096, 1024, 1);
      const uint32_t kst = sw64 ? 64 : 128, bh = db0 >> 32;
      uint32_t s = 0, ph = 0, xo = 0;
      #pragma unroll 1
      for (int kb = 0; kb < 20; kb++) {
        const uint32_t wo_ = s * (W_SLOT >> 4), al = (uint32_t)da0 + wg * 512 + xo, bl = (uint32_t)db0 + wo_, rl = (uint32_t)dr0 + wo_;
        mbar_wait(BAR(BR_FULL) + 8 * s, ph);
        if (kb == 0 && lead && wg == 0) TS(1);
        wg_fence();
        wg_ss192_tb(am, desc2(al, da0 >> 32), desc2(bl, bh), kb != 0);
        wg_ss48_tb(ar, desc2(al, da0 >> 32), desc2(rl, dr0 >> 32), kb != 0);
        wg_ss192_tb(am, desc2(al + 2, da0 >> 32), desc2(bl + kst, bh), 1);
        wg_ss48_tb(ar, desc2(al + 2, da0 >> 32), desc2(rl + 32, dr0 >> 32), 1);
        wg_commit();
        wg_wait<1>();
        if (lead && kb > 0 && kb < 16) mbar_arrive(BAR(BR_EMPTY) + 8 * (s == 0 ? 4 : s - 1));
        if (++s == 5) { s = 0; ph ^= 1; }
        xo += (kb & 1) ? 1020 : 4;
        if (xo == 3072) xo = 0;
      }
      wg_wait<0>();
      pin<96>(am); pin<24>(ar);
    }
    const int tid = rtid(), lane = tid & 31, tq = lane & 3;
    if (tid == 0) TS(2);
#define QV(j, e) ((j) < 8 ? am[4 * (j) + (e)] : ar[4 * ((j) - 8) + (e)])
#define KV_(j, e) ((j) < 8 ? am[32 + 4 * (j) + (e)] : ar[8 + 4 * ((j) - 8) + (e)])
#define VV(j, e) ((j) < 8 ? am[64 + 4 * (j) + (e)] : ar[16 + 4 * ((j) - 8) + (e)])
    {
      bar_sync(1, 256);
      if (tid == 0) mbar_arrive(BAR(BR_GEMM));
      const uint32_t ro = sb + (uint32_t)((warp * 16 + (lane & 15)) * 16);
      const int l0 = 2 * (c & 1) + (lane >> 4);
      const uint32_t ones = (tq == 0) ? 0x00003f80u : 0u;
#define PV(j) pack2(VV(j, 0), VV(j, 1)), pack2(VV(j, 2), VV(j, 3))
#define PK(j) pack2(phi(KV_(j, 0)), phi(KV_(j, 1))), pack2(phi(KV_(j, 2)), phi(KV_(j, 3)))
      stsm4(ro + OFF_V + (5 + 6 * (lane >> 4)) * 2048, ones, ones, ones, ones);
      #pragma unroll
      for (int j = 0; j < 10; j += 2) {
        const int l = (j == 8 && (c & 1)) ? l0 - 2 : l0 + j;
        stsm4(ro + OFF_V + (l + (l >= 5)) * 2048, PV(j), PV(j + 1));
        stsm4(ro + OFF_PK + l * 2048, PK(j), PK(j + 1));
      }
    }
    fence_async();
    bar_sync(1, 256);
    if (tid == 0) TS(3);
    mbar_wait(BAR(BR_EPOCH), 0);
    const unsigned epoch = lds32(sb + OFF_EPOCH);
    {
      float kv[24]; zero<24>(kv);
      constexpr uint64_t da = mkdesc(SB0 + OFF_PK, 128, 2048, 0), db = mkdesc(SB0 + OFF_V, 128, 2048, 0);
      wg_fence();
      #pragma unroll
      for (int s = 0; s < 8; s++) wg_ss48_tt(kv, desc2((uint32_t)da + wg * 640 + s * 16, da >> 32), desc2((uint32_t)db + wg * 768 + s * 16, db >> 32), s != 0);
      wg_commit();
      wg_wait<0>();
      pin<24>(kv);
      if (tid == 0) TS(15);
      if (w4 < 3) {
        const uint32_t wb = sb + OFF_KVS + (wg * 3 + w4) * 1536 + (lane & 15) * 96;
        #pragma unroll
        for (int j = 0; j < 6; j += 2)
          stsm4(wb + (j + (lane >> 4)) * 16, pack2(kv[4 * j], kv[4 * j + 1]), pack2(kv[4 * j + 2], kv[4 * j + 3]),
                pack2(kv[4 * j + 4], kv[4 * j + 5]), pack2(kv[4 * j + 6], kv[4 * j + 7]));
        __syncwarp();
        const int dl = w4 * 16 + (lane & 15), hl = dl >= 20;
        if (dl < 40) {
          uint4* dst = &g_kvp[(c * 16 + r) * 240 + wg * 40 + dl];
          uint32_t v[4], z[4];
          lds128(v, wb + (3 * hl + (lane >> 4)) * 16);
          lds64(z, wb + 32 + 8 * hl); z[2] = lds32(wb + 80); z[3] = epoch & 1u;
          v[3] = (v[3] & ~1u) | z[3];
          st128_rlx(dst + (lane >> 4) * 80, v);
          if (lane < 16) st128_rlx(dst + 160, z);
        }
      }
    }
    fence_async();
    bar_sync(1, 256);
    if (tid == 0) { st_rlx(FLAG(0, r, c), epoch); mbar_arrive(BAR(BR_PUB)); TS(4); }
    const int kvi = (tid >= 80) + (tid >= 160) + (tid >= 240), kd = tid - 80 * kvi;
    const int khd = kd / 20, kt0 = 5 * (khd >> 1) + 2 * (khd & 1);
    const uint32_t rb = sb + OFF_KVB + kd * 16;
    if (kvi < 3) {
      #pragma unroll 1
      for (int m = kvi; m < 7; m += 3) { const int q = kt0 + 3 + m; sts128(rb + (q >= 10 ? q - 10 : q) * 1280, 0, 0, 0, 0); }
    }
    uint32_t qa[20];
    {
      const float sc = 1.44269504089f + __uint_as_float(lds32(sb + OFF_EPOCH) ^ epoch);
      #pragma unroll
      for (int j = 0; j < 10; j++) { qa[2 * j] = pack2(phi(QV(j, 0), sc), phi(QV(j, 1), sc)); qa[2 * j + 1] = pack2(phi(QV(j, 2), sc), phi(QV(j, 3), sc)); }
    }
    if (tid == 0) TS(5);
    if (warp == 7) mbar_wait(BAR(BR_KVP), 0);
    bar_sync(1, 256);
    if (tid == 0) TS(6);
    if (kvi < 3) {
      float s[8];
      zero<8>(s);
      uint32_t bad = 0;
      #pragma unroll 4
      for (int i = 0; i < 16; i++) {
        uint32_t w[4];
        lds128(w, sb + OFF_KVP + tid * 16 + i * 3840);
        bad |= w[3] ^ epoch;
        #pragma unroll
        for (int e = 0; e < 4; e++) { s[2 * e] += bf_lo(w[e]); s[2 * e + 1] += bf_hi(w[e]); }
      }
      if (__builtin_expect(bad & 1u, 0)) {
        zero<8>(s);
        #pragma unroll 1
        for (int i = 0; i < 16; i++) {
          uint32_t w[4] = {0, 0, 0, ~epoch};
          fix128_w3(w, &g_kvp[(c * 16 + i) * 240 + tid], epoch, 1u);
          #pragma unroll
          for (int e = 0; e < 4; e++) { s[2 * e] += bf_lo(w[e]); s[2 * e + 1] += bf_hi(w[e]); }
        }
        FIXCNT
      }
      const uint32_t p0 = pack2(s[0], s[1]), p1 = pack2(s[2], s[3]), p2 = pack2(s[4], s[5]), p3 = pack2(s[6], s[7]);
      if (kvi < 2) sts128(rb + (kt0 + (khd & 1) + kvi) * 1280, p0, p1, p2, p3);
      else {
        const bool od = khd & 1;
        sts128(rb + (5 * (khd >> 1) + 2) * 1280, od ? 0u : p0, od ? 0u : p1, od ? p0 : 0u, od ? p1 : 0u);
        const uint32_t zz = (p2 & 0xffffu) << (16 * (khd & 1));
        sts128(rb + 10 * 1280, khd < 2 ? zz : 0u, khd < 2 ? 0u : zz, 0u, 0u);
      }
    }
    fence_async();
    bar_sync(1, 256);
    if (tid == 0) { mbar_arrive(BAR(BR_SUM)); TS(7); }
    {
      float oa[44]; zero<44>(oa);
      constexpr uint64_t db = mkdesc(SB0 + OFF_KVB, 128, 1280, 0);
      wg_fence();
      #pragma unroll
      for (int s = 0; s < 5; s++) wg_rs88_tb(oa, &qa[4 * s], desc2((uint32_t)db + ((s == 4 && (c & 1)) ? 0 : (s + (c & 1)) * 16), db >> 32), s != 0);
      wg_commit();
      wg_wait<0>();
      pin<44>(oa);
      if (tid == 0) TS(13);
      float rc[4], rd[2][4];
      #pragma unroll
      for (int e = 0; e < 4; e++) asm("rcp.approx.ftz.f32 %0, %1;" : "=f"(rc[e]) : "f"(oa[40 + e] + 1e-6f));
      #pragma unroll
      for (int h = 0; h < 4; h++) {
        rd[0][h] = __shfl_sync(0xffffffff, rc[h & 1], (lane & 28) | (h >> 1));
        rd[1][h] = __shfl_sync(0xffffffff, rc[2 + (h & 1)], (lane & 28) | (h >> 1));
      }
      #pragma unroll
      for (int j = 0; j < 10; j++) {
        #pragma unroll
        for (int h = 0; h < 2; h++) {
          float f;
          if (j == 2) f = tq < 2 ? rd[h][0] : rd[h][1];
          else if (j == 7) f = tq < 2 ? rd[h][2] : rd[h][3];
          else f = rd[h][(8 * j) / 20];
          qa[2 * j + h] = pack2(oa[4 * j + 2 * h] * f, oa[4 * j + 2 * h + 1] * f);
        }
      }
      const uint32_t m0 = (lane & 7) == ((2 * w4) & 7), m1 = (lane & 7) == 2 * w4 + 1;
      const uint32_t oa_ = sb + OFF_EXTRA + (lane >> 4) * 2048 + (warp * 16 + (lane & 15)) * 16;
      bar_sync(1, 256);
#define TAG(v, m) (((v) & ~(m)) | (epoch & (m)))
      #pragma unroll
      for (int s = 0; s < 5; s++) stsm4(oa_ + s * 4096, TAG(qa[4 * s], m0), TAG(qa[4 * s + 1], m1), TAG(qa[4 * s + 2], m0), TAG(qa[4 * s + 3], m1));
    }
    fence_async();
    __syncwarp();
    if (lane == 0) mbar_arrive(BAR(BR_OSTG));
    if (tid == 0) TS(8);
    float oc[40]; zero<40>(oc);
    {
      constexpr uint64_t dw0 = mkdesc(SB0, OFF_WOR, 1024, 1), da0 = mkdesc(SB0, 2048, 128, 0);
      const uint32_t ck = sb + tid * 32 + ((lane >> 2) << 2), ck2 = ck + (wg ? 0 : 16384);
      uint32_t bad = 0;
      auto tile = [&](int i, uint32_t so) {
        const uint32_t al = (uint32_t)da0 + wg * 64 + (so >> 4), wl = (uint32_t)dw0 + i * 640 - (i >> 1) * (1278 << 16);
        wg_fence();
        #pragma unroll
        for (int s = 0; s < 5; s++) wg_ss80_tb(oc, desc2(al + s * 256, da0 >> 32), desc2(wl + s * 128, dw0 >> 32), (i | s) != 0);
        wg_commit();
        bad |= (lds32(ck + so) ^ epoch) | (lds32(ck + so + 8192) ^ epoch) | (lds32(ck2 + so) ^ epoch);
      };
      mbar_wait(BAR(BR_WO), 0);
      mbar_wait(BAR(BR_OSTG), 0);
      tile(0, SLOT(0));
      mbar_wait(BAR(BR_WO + 1), 0);
      #pragma unroll 1
      for (int i = 1; i < 8; i++) {
        if (i == 1) {
          wg_wait<0>();
          if (lane == 0) mbar_arrive(BAR(BR_OEMPTY));
          if (EN_SSM && w4 == 0) mbar_wait(BAR(BR_Y + 1), 0);
          if (w4 == 0) mbar_wait(BAR(BR_OFULL + 1), 0);
          bar_sync(2 + wg, 128);
        }
        mbar_wait(BAR(BR_OFULL) + 8 * i, 0);
        if (i == 1 && tid == 0) TS(9);
        tile(i, SLOT(i));
        wg_wait<1>();
        if (lane == 0 && i > 1) mbar_arrive(BAR(BR_OEMPTY - 1) + 8 * i);
      }
      #pragma unroll 1
      for (int n = 0; n < 56; n++) {
        const int i = n & 7;
        if (i == 0) {
          uint32_t any;
          asm volatile("{\n.reg .pred p;\nsetp.ne.u32 p, %1, 0;\nbarrier.red.or.pred p, 1, 256, p;\nselp.u32 %0, 1, 0, p;\n}" : "=r"(any) : "r"(bad & 1u) : "memory");
          if (!any) break;
          bad = 0;
          FIXCNT
        }
        wg_wait<0>();
        bar_sync(1, 256);
        if (tid == 0) { mbar_expect_tx(BAR(BR_RETRY), 20480); bulk_ld(sb + SLOT(6), &g_o[(r * 8 + CHUNK(i)) * 1280], 20480, BAR(BR_RETRY)); }
        mbar_wait(BAR(BR_RETRY), n & 1);
        tile(i, SLOT(6));
      }
      wg_wait<0>();
      pin<40>(oc);
    }
    if (tid == 0) TS(10);
    {
      const int row = w4 * 16 + (lane & 15);
      const uint32_t ob = sb + OFF_BLK + 2 * BLK + wg * 10240;
      #pragma unroll
      for (int j = 0; j < 8; j += 2)
        stsm4(ob + row * 128 + (((j + (lane >> 4)) ^ (row & 7)) << 4), pack2(oc[4 * j], oc[4 * j + 1]), pack2(oc[4 * j + 2], oc[4 * j + 3]),
              pack2(oc[4 * j + 4], oc[4 * j + 5]), pack2(oc[4 * j + 6], oc[4 * j + 7]));
      stsm4(ob + 8192 + row * 32 + (lane >> 4) * 16, pack2(oc[32], oc[33]), pack2(oc[34], oc[35]), pack2(oc[36], oc[37]), pack2(oc[38], oc[39]));
      fence_async();
      bar_sync(2 + wg, 128);
      if (w4 == 0 && elect_one()) {
        tma2d_st(&prm.m[M_O64], ob, 640 + c * 64, r * 128 + wg * 64);
        tma2d_st(&prm.m[M_O16], ob + 8192, 1152 + c * 16, r * 128 + wg * 64);
        bulk_commit(); bulk_wait0_read();
        if (wg == 0) { TS(11); DUMP(0, 20); }
      }
    }
    }
  } else {
    if (EN_SSM) {
    const int tid = rtid(), lane = tid & 31, g = lane >> 2, tq = lane & 3, t7 = tid & 127;
    if (t7 == 0) TS(41);
    mbar_wait(BAR(BR_U), 0);
    bar_sync(4, 128);
    if (EN_ATT) mbar_wait(BAR(BR_GEMM), 0);
    if (t7 == 0) TS(42);
    mbar_wait(BAR(BR_EPOCH), 0);
    const uint32_t ytag = (lds32(sb + OFF_EPOCH) & 1u) * 0x10001u, ym = lane < 4 ? 0x10001u : 0u;
    #pragma unroll 1
    for (int pass = 1; pass >= 0; pass--) {
      const int k = pass ? w4 : 4;
      if (k >= 3) mbar_wait(BAR(BR_U2), 0);
      const uint32_t blk = sb + OFF_BLK + k * BLK, tb = blk + B_TBL + (uint32_t)((g - 2 * tq) * 4);
      float acc[16][4];
      zero<64>(&acc[0][0]);
      const int kl = 16 * (lane >> 4) + 2 * (lane & 7) + ((lane >> 3) & 1);
      {
        auto ubase = [&](int sh) { const int q = kl - 2 * sh; return blk + (uint32_t)((q * 16) ^ ((q * 2) & 0x10)); };
#define LDQ(A, sh) _Pragma("unroll") for (int m = 0; m < 4; m++) load_quad(A[m], tb + (16 + 16 * (sh) + 128 * m) * 4);
#define LDB(B, ub, h) _Pragma("unroll") for (int p = 0; p < 4; p++) ldsm4(B[p], (ub) + (4 * (h) + p) * 512);
#define MLO(A, B) _Pragma("unroll") for (int m = 0; m < 4; m++) _Pragma("unroll") for (int cc = 0; cc < 8; cc++) mma16816(acc[cc + m], A[m], &B[cc >> 1][(cc & 1) * 2]);
#define MHI(A, B) _Pragma("unroll") for (int m = 0; m < 4; m++) _Pragma("unroll") for (int cc = 0; cc < 8 - m; cc++) mma16816(acc[8 + cc + m], A[m], &B[cc >> 1][(cc & 1) * 2]);
        int p_ = pass ? 0 : w4;
        const int pe = pass ? 4 : w4 + 1;
        uint32_t A[4][4], A2[4][4], Bl[4][4], Bh[4][4];
        uint32_t ub = ubase(p_ + 4);
        LDQ(A, p_ + 4) LDB(Bl, ub, 0)
        #pragma unroll 1
        for (; p_ < pe; p_++) {
          LDB(Bh, ub, 1)
          MLO(A, Bl)
          ub = ubase(p_);
          LDQ(A2, p_) LDB(Bl, ub, 0)
          MHI(A, Bh)
          LDB(Bh, ub, 1)
          load_quad(A[0], tb + (16 + 512 + 16 * (p_ & 1)) * 4); load_quad(A[1], tb + (T_S + 16 * (p_ & 1)) * 4);
          MLO(A2, Bl)
          if (p_ < 2) {
            #pragma unroll
            for (int cc = 0; cc < 8; cc++) mma16816(acc[cc + 4], A[0], &Bl[cc >> 1][(cc & 1) * 2]);
            #pragma unroll
            for (int cc = 0; cc < 4; cc++) mma16816(acc[cc + 12], A[0], &Bh[cc >> 1][(cc & 1) * 2]);
            #pragma unroll
            for (int cc = 0; cc < 8; cc++) mma16816(acc[cc + 8], A[1], &Bl[cc >> 1][(cc & 1) * 2]);
          }
          const int pn = ((p_ + 1) & 3) + 4;
          ub = ubase(pn);
          LDQ(A, pn) LDB(Bl, ub, 0)
          MHI(A2, Bh)
        }
      }
      if (t7 == 0) TS(57 + 3 * pass);
      mbar_wait(BAR(BR_DRDY + 1) - 8 * pass, 0);
      {
        const int ih = (lane >> 3) & 1;
        const uint32_t dl = blk + B_D + (uint32_t)(((lane >> 4) * 8 + (lane & 7)) * 16);
        const uint32_t d0_ = dl + ih * 1552, d8_ = dl + (ih ? 0 : 1536), d3_ = dl + B_D7 + ih * 1024;
        auto cls2 = [&](uint32_t da, uint32_t ta) {
          uint32_t B[6][2], A[6][4];
          #pragma unroll
          for (int e = 0; e < 6; e++) { B[e][0] = lds32v(ta + (e + 4) * 32); B[e][1] = lds32v(ta + (e + 3) * 32); }
          #pragma unroll
          for (int kk = 0; kk < 6; kk++) ldsm4t(A[kk], da + kk * 256);
          #pragma unroll
          for (int e = 0; e < 6; e++)
            #pragma unroll
            for (int kk = 0; kk < 6; kk++) if (2 * kk + e + 4 < 16) mma16816(acc[2 * kk + e + 4], A[kk], B[e]);
        };
        auto cls3 = [&](uint32_t da, uint32_t ta) {
          uint32_t B[8][2], A[4][4];
          #pragma unroll
          for (int e = 0; e < 8; e++) { B[e][0] = lds32v(ta + (e + 8) * 32); B[e][1] = lds32v(ta + (e + 7) * 32); }
          #pragma unroll
          for (int kk = 0; kk < 4; kk++) ldsm4t(A[kk], da + kk * 256);
          #pragma unroll
          for (int kk = 0; kk < 4; kk++)
            #pragma unroll
            for (int e = 0; e < 8; e++) if (2 * kk + e + 8 < 16) mma16816(acc[2 * kk + e + 8], A[kk], B[e]);
        };
        if (pass) {
          #pragma unroll 1
          for (int a = 0; a < 2; a++) {
            cls2(d0_ + a * B_D5, tb + (T_F2 + 48 * a - 32) * 4);
            cls2(d8_ + a * B_D5, tb + (T_F2 + 48 * a + 64) * 4);
            cls3(d3_ + a * 2048, tb + (T_F3 + 80 * a - 64) * 4);
          }
        } else {
          cls2(((w4 & 2) ? d8_ : d0_) + (w4 & 1) * B_D5, tb + (T_F2 + 48 * w4 - 32) * 4);
          if (w4 >= 2) cls3(d3_ + (w4 - 2) * 2048, tb + (T_F3 + 80 * (w4 - 2) - 64) * 4);
        }
      }
      if (t7 == 0) TS(58 + 3 * pass);
      const uint32_t ya = blk + (uint32_t)((kl * 16) ^ ((kl * 2) & 0x10));
#define YTAG(v) (((v) & ~ym) | (ytag & ym))
#define STY(p) stsm4t(ya + (p) * 512, YTAG(pack2(acc[2 * (p)][0], acc[2 * (p)][1])), pack2(acc[2 * (p)][2], acc[2 * (p)][3]), \
                      YTAG(pack2(acc[2 * (p) + 1][0], acc[2 * (p) + 1][1])), pack2(acc[2 * (p) + 1][2], acc[2 * (p) + 1][3]))
      if (pass == 0) {
        const uint32_t xw = blk + 4096 + w4 * 4096 + lane * 16, xr = blk + 4096 + w4 * 1024 + lane * 16;
        #pragma unroll
        for (int h = 0; h < 2; h++) {
          bar_sync(4, 128);
          #pragma unroll
          for (int i = 0; i < 8; i++)
            sts128(xw + i * 512, __float_as_uint(acc[8 * h + i][0]), __float_as_uint(acc[8 * h + i][1]), __float_as_uint(acc[8 * h + i][2]), __float_as_uint(acc[8 * h + i][3]));
          bar_sync(4, 128);
          float y[8];
          #pragma unroll
          for (int i = 0; i < 8; i++) {
            uint32_t o[4]; lds128(o, xr + (i >> 1) * 4096 + (i & 1) * 512);
            #pragma unroll
            for (int e = 0; e < 4; e++) y[4 * (i & 1) + e] = i < 2 ? __uint_as_float(o[e]) : y[4 * (i & 1) + e] + __uint_as_float(o[e]);
          }
          stsm4t(ya + (4 * h + w4) * 512, YTAG(pack2(y[0], y[1])), pack2(y[2], y[3]), YTAG(pack2(y[4], y[5])), pack2(y[6], y[7]));
        }
      } else {
        __syncwarp();
        #pragma unroll
        for (int p = 0; p < 8; p++) STY(p);
      }
      if (t7 == 0 && !pass) TS(55);
      fence_async();
      __syncwarp();
      if (lane == 0) mbar_arrive(BAR(BR_Y + 1) - 8 * pass);
      if (t7 == 0) TS(59 + 3 * pass);
    }
    if (t7 == 0) DUMP(40, 64);
    #pragma unroll 1
    for (int n = 0; n < 64; n++) if (!y_transpose(sb, w4, lane, ytag)) break;
    }
  }
  }
}

typedef CUresult (*EncFn)(CUtensorMap*, CUtensorMapDataType, cuuint32_t, void*, const cuuint64_t*, const cuuint64_t*, const cuuint32_t*,
                          const cuuint32_t*, CUtensorMapInterleave, CUtensorMapSwizzle, CUtensorMapL2promotion, CUtensorMapFloatOOBfill);
static void mkmap(EncFn enc, CUtensorMap* m, const void* base, int rank, const cuuint64_t* dims, const cuuint64_t* strides, const cuuint32_t* box, CUtensorMapSwizzle swz) {
  cuuint32_t es[5] = {1, 1, 1, 1, 1};
  enc(m, CU_TENSOR_MAP_DATA_TYPE_BFLOAT16, rank, const_cast<void*>(base), dims, strides, box, es, CU_TENSOR_MAP_INTERLEAVE_NONE, swz,
      CU_TENSOR_MAP_L2_PROMOTION_L2_128B, CU_TENSOR_MAP_FLOAT_OOB_FILL_NONE);
}

extern "C" void kernel_launch(void* const* d_in, const int* in_sizes, int n_in, void* d_out, int out_size) {
  void* fn = nullptr; cudaDriverEntryPointQueryResult qr;
  cudaGetDriverEntryPoint("cuTensorMapEncodeTiled", &fn, cudaEnableDefault, &qr);
  EncFn enc = (EncFn)fn;
  void* uy = nullptr; cudaGetSymbolAddress(&uy, g_uy);
  const cuuint64_t dx[2] = {640, 2048}, sx[1] = {1280};
  const cuuint32_t bx[2] = {64, 128}, bu[2] = {80, 128};
  const cuuint64_t dw[3] = {640, 640, 3}, sw[2] = {3840, 1280};
  const cuuint32_t br[3] = {16, 32, 3};
  const cuuint64_t dwa[4] = {64, 640, 10, 3}, swa[3] = {3840, 128, 1280}, dwb[4] = {32, 640, 20, 3}, swb[3] = {3840, 64, 1280};
  const cuuint32_t bwa[4] = {64, 32, 1, 3}, bwb[4] = {32, 32, 2, 3};
  const cuuint64_t dwo[2] = {640, 640};
  const cuuint32_t bwo[2] = {64, 80}, bo64[2] = {64, 64}, bo16[2] = {16, 64};
  const cuuint64_t dsa[2] = {2048, 1280}, ssa[1] = {4096};
  const cuuint32_t bsa[2] = {64, 80};
  const cuuint64_t dout[2] = {1280, 2048}, sout[1] = {2560};
  Params prm;
  mkmap(enc, &prm.m[M_X], d_in[7], 2, dx, sx, bx, CU_TENSOR_MAP_SWIZZLE_128B);
  mkmap(enc, &prm.m[M_W128], d_in[8], 4, dwa, swa, bwa, CU_TENSOR_MAP_SWIZZLE_128B);
  mkmap(enc, &prm.m[M_W64], d_in[8], 4, dwb, swb, bwb, CU_TENSOR_MAP_SWIZZLE_64B);
  mkmap(enc, &prm.m[M_WR], d_in[8], 3, dw, sw, br, CU_TENSOR_MAP_SWIZZLE_32B);
  mkmap(enc, &prm.m[M_U], d_in[0], 2, dx, sx, bu, CU_TENSOR_MAP_SWIZZLE_NONE);
  mkmap(enc, &prm.m[M_WO], d_in[9], 2, dwo, sx, bwo, CU_TENSOR_MAP_SWIZZLE_128B);
  mkmap(enc, &prm.m[M_O64], d_out, 2, dout, sout, bo64, CU_TENSOR_MAP_SWIZZLE_128B);
  mkmap(enc, &prm.m[M_O16], d_out, 2, dout, sout, bo16, CU_TENSOR_MAP_SWIZZLE_NONE);
  mkmap(enc, &prm.m[M_SA], uy, 2, dsa, ssa, bsa, CU_TENSOR_MAP_SWIZZLE_128B);
  mkmap(enc, &prm.m[M_OUT], d_out, 2, dout, sout, bu, CU_TENSOR_MAP_SWIZZLE_NONE);
  prm.u = (const __nv_bfloat16*)d_in[0]; prm.wo = (const __nv_bfloat16*)d_in[9];
  for (int i = 0; i < 4; i++) prm.par[i] = (const __nv_bfloat16*)d_in[1 + i];
  prm.logdt = (const __nv_bfloat16*)d_in[5]; prm.dskip = (const __nv_bfloat16*)d_in[6];
  cudaFuncSetAttribute(fused_kernel, cudaFuncAttributeMaxDynamicSharedMemorySize, SMEM_BYTES);
  cudaLaunchConfig_t cfg = {};
  cfg.gridDim = dim3(128); cfg.blockDim = dim3(512); cfg.dynamicSmemBytes = SMEM_BYTES; cfg.stream = cudaStreamPerThread;
  cudaLaunchAttribute at[1];
  at[0].id = cudaLaunchAttributeClusterDimension; at[0].val.clusterDim.x = 2; at[0].val.clusterDim.y = 1; at[0].val.clusterDim.z = 1;
  cfg.attrs = at; cfg.numAttrs = 1;
  cudaLaunchKernelEx(&cfg, fused_kernel, prm);
}
```

```cpp
#include <cuda_runtime.h>
#include <cuda_bf16.h>
#include <cuda_fp16.h>
#include <cuda.h>
#include <stdint.h>

#define KST 2
#define EN_ATT 1
#define EN_SSM 1

__device__ __align__(1024) __nv_bfloat16 g_uy[2 * 640 * 2048];
__device__ __align__(128) uint4 g_kvp[8 * 16 * 240];
__device__ __align__(128) uint4 g_o[128 * 1280];
__device__ __align__(128) unsigned g_flag[4 * 128 * 32];
__device__ unsigned g_epoch[128];
#define TS(i) do {} while (0)
#define DUMP(lo, hi) do {} while (0)
#define FIXCNT

constexpr uint32_t SB0 = 1024;
constexpr uint32_t W_SLOT = 15360, OFF_X = 76800;
constexpr uint32_t OFF_WOR = 81920, OFF_KVP = 10240, OFF_KVS = 71680, OFF_PK = 10240, OFF_V = 30720, OFF_EXTRA = 102400, OFF_KVB = OFF_EXTRA;
constexpr uint32_t OFF_BAR = 125952, OFF_BLK = 128000, BLK = 20480;
constexpr uint32_t B_D = 4096, B_D5 = 3088, B_D7 = 6176, B_D9 = 8224, B_TBL = 14400;
constexpr int T_S = 576, T_F2 = 624, T_F3 = 816;
constexpr uint32_t OFF_UT = OFF_BLK + 4 * BLK;
constexpr uint32_t SMEM_BYTES = OFF_BLK + 5 * BLK;
enum { BR_FULL = 0, BR_WO = 5, BR_PUB = 7, BR_KVP = 8, BR_U = 9, BR_SUM = 10, BR_GEMM = 11, BR_UIN = 12, BR_YIN = 13, BR_EPOCH = 14,
       BR_FREE = 15, BR_RETRY = 17, BR_UOUT = 18, BR_OFULL = 18, BR_KS = 26, BR_EMPTY = 31, BR_OEMPTY = 36, BR_Y = 43, BR_OSTG = 45,
       BR_DRDY = 46, BR_U2 = 48, BR_COUNT = 50 };
constexpr uint32_t OFF_EPOCH = OFF_BAR + 8 * BR_COUNT;
enum { M_X, M_W128, M_W64, M_WR, M_U, M_WO, M_O64, M_O16, M_SA, M_OUT, M_COUNT };

__device__ __forceinline__ long long clk64() { long long t; asm volatile("mov.u64 %0, %%clock64;" : "=l"(t) :: "memory"); return t; }
__device__ __forceinline__ uint32_t smem_u32(const void* p) { return (uint32_t)__cvta_generic_to_shared(p); }
__host__ __device__ constexpr uint64_t mkdesc(uint32_t addr, uint32_t lbo, uint32_t sbo, uint32_t swz) {
  return (uint64_t)((addr & 0x3FFFF) >> 4) | ((uint64_t)(lbo >> 4) << 16) | ((uint64_t)(sbo >> 4) << 32) | ((uint64_t)swz << 62);
}
__device__ __forceinline__ uint64_t desc2(uint32_t lo, uint32_t hi) { uint64_t d; asm("mov.b64 %0, {%1, %2};" : "=l"(d) : "r"(lo), "r"(hi)); return d; }
__device__ __forceinline__ void mbar_init(uint32_t bar, uint32_t cnt) { asm volatile("mbarrier.init.shared::cta.b64 [%0], %1;" :: "r"(bar), "r"(cnt) : "memory"); }
__device__ __forceinline__ void mbar_expect_tx(uint32_t bar, uint32_t bytes) { asm volatile("mbarrier.arrive.expect_tx.shared::cta.b64 _, [%0], %1;" :: "r"(bar), "r"(bytes) : "memory"); }
__device__ __forceinline__ void mbar_arrive(uint32_t bar) { asm volatile("mbarrier.arrive.shared::cta.b64 _, [%0];" :: "r"(bar) : "memory"); }
__device__ __forceinline__ void mbar_wait(uint32_t bar, uint32_t parity) {
  asm volatile("{\n.reg .pred p;\n.reg .u32 c;\nmov.u32 c, 0;\n"
    "WL:\nmbarrier.try_wait.parity.shared::cta.b64 p, [%0], %1;\n@p bra WD;\n"
    "add.u32 c, c, 1;\nsetp.lt.u32 p, c, 200000;\n@p bra WL;\nWD:\n}" :: "r"(bar), "r"(parity) : "memory");
}
__device__ __forceinline__ void poll_all(const unsigned* p, unsigned val) {
  asm volatile("{\n.reg .pred p;\n.reg .u32 c, v;\nmov.u32 c, 0;\n"
    "PL:\nld.relaxed.gpu.global.u32 v, [%0];\nsetp.eq.u32 p, v, %1;\nvote.sync.all.pred p, p, 0xffffffff;\n@p bra PD;\n"
    "add.u32 c, c, 1;\nsetp.lt.u32 p, c, 100000;\n@p bra PL;\nPD:\n}" :: "l"(p), "r"(val) : "memory");
}
__device__ __forceinline__ void poll_all_acq(const unsigned* p, unsigned val) {
  asm volatile("{\n.reg .pred p;\n.reg .u32 c, v;\nmov.u32 c, 0;\n"
    "PL:\nld.acquire.gpu.global.u32 v, [%0];\nsetp.eq.u32 p, v, %1;\nvote.sync.all.pred p, p, 0xffffffff;\n@p bra PD;\n"
    "add.u32 c, c, 1;\nsetp.lt.u32 p, c, 100000;\n@p bra PL;\nPD:\n}" :: "l"(p), "r"(val) : "memory");
}
__device__ __forceinline__ unsigned poll_bit(const unsigned* p, unsigned val, unsigned mask) {
  unsigned bal;
  asm volatile("{\n.reg .pred p;\n.reg .u32 c, v;\nmov.u32 c, 0;\n"
    "PL:\nld.relaxed.gpu.global.u32 v, [%1];\nsetp.eq.u32 p, v, %2;\nvote.sync.ballot.b32 %0, p, 0xffffffff;\n"
    "and.b32 v, %0, %3;\nsetp.ne.u32 p, v, 0;\n@p bra PD;\n"
    "add.u32 c, c, 1;\nsetp.lt.u32 p, c, 100000;\n@p bra PL;\nPD:\n}" : "=&r"(bal) : "l"(p), "r"(val), "r"(mask) : "memory");
  return bal;
}
__device__ __forceinline__ void fix128_w0(uint32_t* v, const void* p, uint32_t tag, uint32_t mask) {
  asm volatile("{\n.reg .pred p;\n.reg .u32 c, x;\n.reg .b128 t;\n.reg .b64 lo, hi;\nmov.u32 c, 0;\n"
    "FL:\nxor.b32 x, %0, %5;\nand.b32 x, x, %6;\nsetp.eq.u32 p, x, 0;\n@p bra FD;\n"
    "ld.relaxed.gpu.global.b128 t, [%4];\nmov.b128 {lo, hi}, t;\nmov.b64 {%0, %1}, lo;\nmov.b64 {%2, %3}, hi;\n"
    "add.u32 c, c, 1;\nsetp.lt.u32 p, c, 100000;\n@p bra FL;\nFD:\n}"
    : "+r"(v[0]), "+r"(v[1]), "+r"(v[2]), "+r"(v[3]) : "l"(p), "r"(tag), "r"(mask) : "memory");
}
__device__ __forceinline__ void fix128_w3(uint32_t* v, const void* p, uint32_t tag, uint32_t mask) {
  asm volatile("{\n.reg .pred p;\n.reg .u32 c, x;\n.reg .b128 t;\n.reg .b64 lo, hi;\nmov.u32 c, 0;\n"
    "FL:\nxor.b32 x, %3, %5;\nand.b32 x, x, %6;\nsetp.eq.u32 p, x, 0;\n@p bra FD;\n"
    "ld.relaxed.gpu.global.b128 t, [%4];\nmov.b128 {lo, hi}, t;\nmov.b64 {%0, %1}, lo;\nmov.b64 {%2, %3}, hi;\n"
    "add.u32 c, c, 1;\nsetp.lt.u32 p, c, 100000;\n@p bra FL;\nFD:\n}"
    : "+r"(v[0]), "+r"(v[1]), "+r"(v[2]), "+r"(v[3]) : "l"(p), "r"(tag), "r"(mask) : "memory");
}
__device__ __forceinline__ void fence_acq() { asm volatile("fence.acq_rel.gpu;" ::: "memory"); }
__device__ __forceinline__ bool elect_one() {
  uint32_t p; asm volatile("{\n.reg .pred P;\nelect.sync _|P, 0xffffffff;\nselp.u32 %0, 1, 0, P;\n}" : "=r"(p)); return p;
}
__device__ __forceinline__ void bar_sync(int id, int n) { asm volatile("bar.sync %0, %1;" :: "r"(id), "r"(n) : "memory"); }
__device__ __forceinline__ void fence_async() { asm volatile("fence.proxy.async.shared::cta;" ::: "memory"); }
__device__ __forceinline__ void fence_async_g() { asm volatile("fence.proxy.async.global;" ::: "memory"); }
__device__ __forceinline__ void tma2d(uint32_t dst, const CUtensorMap* m, uint32_t bar, int c0, int c1) {
  asm volatile("cp.async.bulk.tensor.2d.shared::cluster.global.mbarrier::complete_tx::bytes [%0], [%1, {%3, %4}], [%2];"
    :: "r"(dst), "l"(m), "r"(bar), "r"(c0), "r"(c1) : "memory");
}
__device__ __forceinline__ void tma3d(uint32_t dst, const CUtensorMap* m, uint32_t bar, int c0, int c1, int c2) {
  asm volatile("cp.async.bulk.tensor.3d.shared::cluster.global.mbarrier::complete_tx::bytes [%0], [%1, {%3, %4, %5}], [%2];"
    :: "r"(dst), "l"(m), "r"(bar), "r"(c0), "r"(c1), "r"(c2) : "memory");
}
__device__ __forceinline__ void tma4d(uint32_t dst, const CUtensorMap* m, uint32_t bar, int c0, int c1, int c2, int c3) {
  asm volatile("cp.async.bulk.tensor.4d.shared::cluster.global.mbarrier::complete_tx::bytes [%0], [%1, {%3, %4, %5, %6}], [%2];"
    :: "r"(dst), "l"(m), "r"(bar), "r"(c0), "r"(c1), "r"(c2), "r"(c3) : "memory");
}
__device__ __forceinline__ void tma2d_st(const CUtensorMap* m, uint32_t src, int c0, int c1) {
  asm volatile("cp.async.bulk.tensor.2d.global.shared::cta.bulk_group [%0, {%2, %3}], [%1];"
    :: "l"(m), "r"(src), "r"(c0), "r"(c1) : "memory");
}
__device__ __forceinline__ void bulk_ld(uint32_t dst, const void* src, uint32_t bytes, uint32_t bar) {
  asm volatile("cp.async.bulk.shared::cluster.global.mbarrier::complete_tx::bytes [%0], [%1], %2, [%3];"
    :: "r"(dst), "l"(src), "r"(bytes), "r"(bar) : "memory");
}
__device__ __forceinline__ void bulk_st(void* dst, uint32_t src, uint32_t bytes) {
  asm volatile("cp.async.bulk.global.shared::cta.bulk_group [%0], [%1], %2;" :: "l"(dst), "r"(src), "r"(bytes) : "memory");
}
__device__ __forceinline__ void bulk_commit() { asm volatile("cp.async.bulk.commit_group;" ::: "memory"); }
__device__ __forceinline__ void bulk_wait0() { asm volatile("cp.async.bulk.wait_group 0;" ::: "memory"); }
__device__ __forceinline__ void bulk_wait0_read() { asm volatile("cp.async.bulk.wait_group.read 0;" ::: "memory"); }
__device__ __forceinline__ unsigned ld_rlx(const unsigned* p) { unsigned v; asm volatile("ld.relaxed.gpu.global.u32 %0, [%1];" : "=r"(v) : "l"(p) : "memory"); return v; }
__device__ __forceinline__ unsigned ld_acq(const unsigned* p) { unsigned v; asm volatile("ld.acquire.gpu.global.u32 %0, [%1];" : "=r"(v) : "l"(p) : "memory"); return v; }
__device__ __forceinline__ void st_rlx(unsigned* p, unsigned v) { asm volatile("st.relaxed.gpu.global.u32 [%0], %1;" :: "l"(p), "r"(v) : "memory"); }
__device__ __forceinline__ void st_rel(unsigned* p, unsigned v) { asm volatile("st.release.gpu.global.u32 [%0], %1;" :: "l"(p), "r"(v) : "memory"); }
__device__ __forceinline__ void ld128_rlx(uint32_t* v, const void* p) {
  asm volatile("{\n.reg .b128 t;\n.reg .b64 lo, hi;\nld.relaxed.gpu.global.b128 t, [%4];\nmov.b128 {lo, hi}, t;\n"
    "mov.b64 {%0, %1}, lo;\nmov.b64 {%2, %3}, hi;\n}" : "=r"(v[0]), "=r"(v[1]), "=r"(v[2]), "=r"(v[3]) : "l"(p) : "memory");
}
__device__ __forceinline__ void st128_rlx(void* p, const uint32_t* v) {
  asm volatile("{\n.reg .b128 t;\n.reg .b64 lo, hi;\nmov.b64 lo, {%1, %2};\nmov.b64 hi, {%3, %4};\nmov.b128 t, {lo, hi};\n"
    "st.relaxed.gpu.global.b128 [%0], t;\n}" :: "l"(p), "r"(v[0]), "r"(v[1]), "r"(v[2]), "r"(v[3]) : "memory");
}
__device__ __forceinline__ uint32_t lds32(uint32_t a) { uint32_t v; asm volatile("ld.shared.u32 %0, [%1];" : "=r"(v) : "r"(a) : "memory"); return v; }
__device__ __forceinline__ uint32_t lds32v(uint32_t a) { uint32_t v; asm volatile("ld.volatile.shared.u32 %0, [%1];" : "=r"(v) : "r"(a) : "memory"); return v; }
__device__ __forceinline__ uint32_t cpa(uint32_t a, uint32_t one) { uint32_t v; asm volatile("mul.lo.u32 %0, %1, %2;" : "=r"(v) : "r"(a), "r"(one)); return v; }
__device__ __forceinline__ uint32_t cpb(uint32_t a, uint32_t zero) { uint32_t v; asm volatile("or.b32 %0, %1, %2;" : "=r"(v) : "r"(a), "r"(zero)); return v; }
__device__ __forceinline__ uint32_t lds16(uint32_t a) { uint16_t v; asm volatile("ld.shared.u16 %0, [%1];" : "=h"(v) : "r"(a) : "memory"); return v; }
__device__ __forceinline__ float ldsf(uint32_t a) { float v; asm volatile("ld.shared.f32 %0, [%1];" : "=f"(v) : "r"(a) : "memory"); return v; }
__device__ __forceinline__ void lds128(uint32_t* v, uint32_t a) { asm volatile("ld.shared.v4.u32 {%0,%1,%2,%3}, [%4];" : "=r"(v[0]), "=r"(v[1]), "=r"(v[2]), "=r"(v[3]) : "r"(a) : "memory"); }
__device__ __forceinline__ void sts32(uint32_t a, uint32_t v) { asm volatile("st.shared.u32 [%0], %1;" :: "r"(a), "r"(v) : "memory"); }
__device__ __forceinline__ void sts16(uint32_t a, uint32_t v) { asm volatile("st.shared.u16 [%0], %1;" :: "r"(a), "h"((uint16_t)v) : "memory"); }
__device__ __forceinline__ void sts64f(uint32_t a, float x, float y) { asm volatile("st.shared.v2.f32 [%0], {%1,%2};" :: "r"(a), "f"(x), "f"(y) : "memory"); }
__device__ __forceinline__ void sts128(uint32_t a, uint32_t x, uint32_t y, uint32_t z, uint32_t w) { asm volatile("st.shared.v4.u32 [%0], {%1,%2,%3,%4};" :: "r"(a), "r"(x), "r"(y), "r"(z), "r"(w) : "memory"); }
__device__ __forceinline__ void stsm4(uint32_t a, uint32_t r0, uint32_t r1, uint32_t r2, uint32_t r3) {
  asm volatile("stmatrix.sync.aligned.m8n8.x4.shared.b16 [%0], {%1,%2,%3,%4};" :: "r"(a), "r"(r0), "r"(r1), "r"(r2), "r"(r3) : "memory");
}
__device__ __forceinline__ void stsm4t(uint32_t a, uint32_t r0, uint32_t r1, uint32_t r2, uint32_t r3) {
  asm volatile("stmatrix.sync.aligned.m8n8.x4.trans.shared.b16 [%0], {%1,%2,%3,%4};" :: "r"(a), "r"(r0), "r"(r1), "r"(r2), "r"(r3) : "memory");
}
__device__ __forceinline__ void ldsm4t(uint32_t* r, uint32_t a) {
  asm volatile("ldmatrix.sync.aligned.m8n8.x4.trans.shared.b16 {%0,%1,%2,%3}, [%4];" : "=r"(r[0]), "=r"(r[1]), "=r"(r[2]), "=r"(r[3]) : "r"(a) : "memory");
}
__device__ __forceinline__ void ldsm4(uint32_t* r, uint32_t a) {
  asm volatile("ldmatrix.sync.aligned.m8n8.x4.shared.b16 {%0,%1,%2,%3}, [%4];" : "=r"(r[0]), "=r"(r[1]), "=r"(r[2]), "=r"(r[3]) : "r"(a) : "memory");
}
__device__ __forceinline__ void mma16816(float* d, const uint32_t* a, const uint32_t* b) {
  asm volatile("mma.sync.aligned.m16n8k16.row.col.f32.bf16.bf16.f32 {%0,%1,%2,%3}, {%4,%5,%6,%7}, {%8,%9}, {%0,%1,%2,%3};"
    : "+f"(d[0]), "+f"(d[1]), "+f"(d[2]), "+f"(d[3]) : "r"(a[0]), "r"(a[1]), "r"(a[2]), "r"(a[3]), "r"(b[0]), "r"(b[1]));
}
__device__ __forceinline__ uint32_t pack2(float lo, float hi) { uint32_t r; asm("cvt.rn.bf16x2.f32 %0, %1, %2;" : "=r"(r) : "f"(hi), "f"(lo)); return r; }
__device__ __forceinline__ uint32_t packh(float lo, float hi) { uint32_t r; asm("cvt.rn.f16x2.f32 %0, %1, %2;" : "=r"(r) : "f"(hi), "f"(lo)); return r; }
__device__ __forceinline__ uint32_t hcmul(uint32_t x, uint32_t zp, uint32_t zq) {
  const __half2 xx = *reinterpret_cast<__half2*>(&x);
  const __half2 r = __hfma2(__high2half2(xx), *reinterpret_cast<__half2*>(&zq), __hmul2(__low2half2(xx), *reinterpret_cast<__half2*>(&zp)));
  return *reinterpret_cast<const uint32_t*>(&r);
}
__device__ __forceinline__ void hcm2(uint32_t xr, uint32_t xi, uint32_t z, uint32_t& pr, uint32_t& pi) {
  const __half2 a = *reinterpret_cast<__half2*>(&xr), b = *reinterpret_cast<__half2*>(&xi), zz = *reinterpret_cast<__half2*>(&z);
  const __half2 re = __hfma2(__hneg2(b), __high2half2(zz), __hmul2(a, __low2half2(zz)));
  const __half2 im = __hfma2(a, __high2half2(zz), __hmul2(b, __low2half2(zz)));
  pr = *reinterpret_cast<const uint32_t*>(&re); pi = *reinterpret_cast<const uint32_t*>(&im);
}
__device__ __forceinline__ void sts64(uint32_t a, uint32_t x, uint32_t y) { asm volatile("st.shared.v2.u32 [%0], {%1,%2};" :: "r"(a), "r"(x), "r"(y) : "memory"); }
__device__ __forceinline__ void lds64(uint32_t* v, uint32_t a) { asm volatile("ld.shared.v2.u32 {%0,%1}, [%2];" : "=r"(v[0]), "=r"(v[1]) : "r"(a) : "memory"); }
__device__ __forceinline__ float bf_lo(uint32_t v) { return __uint_as_float(v << 16); }
__device__ __forceinline__ float bf_hi(uint32_t v) { return __uint_as_float(v & 0xffff0000u); }
__device__ __forceinline__ float bf_round(float x) { return bf_lo(pack2(x, 0.f)); }
__device__ __forceinline__ float ex2(float x) { float r; asm("ex2.approx.ftz.f32 %0, %1;" : "=f"(r) : "f"(x)); return r; }
__device__ __forceinline__ float phi(float t, float l2e = 1.44269504089f) {
  float e = ex2(t * l2e) + 1e-6f;
  asm("{\n.reg .pred p;\nsetp.gt.f32 p, %1, 0f00000000;\n@p add.f32 %0, %1, 0f3F800008;\n}" : "+f"(e) : "f"(t));
  return e;
}
__device__ __forceinline__ void wg_fence() { asm volatile("wgmma.fence.sync.aligned;" ::: "memory"); }
__device__ __forceinline__ void wg_commit() { asm volatile("wgmma.commit_group.sync.aligned;" ::: "memory"); }
template <int N> __device__ __forceinline__ void wg_wait() { asm volatile("wgmma.wait_group.sync.aligned %0;" :: "n"(N) : "memory"); }
template <int N> __device__ __forceinline__ void pin(float* a) {
  #pragma unroll
  for (int i = 0; i < N; i++) asm volatile("" : "+f"(a[i]) :: "memory");
}
__device__ __forceinline__ int rtid() { int t; asm volatile("mov.u32 %0, %%tid.x;" : "=r"(t)); return t; }
__device__ __forceinline__ int opaque(int v) { asm volatile("" : "+r"(v)); return v; }
template <int N> __device__ __forceinline__ void zero(float* a) {
  #pragma unroll
  for (int i = 0; i < N; i++) asm volatile("mov.b32 %0, 0;" : "=f"(a[i]));
}
template <int N> __device__ __forceinline__ void pinu(uint32_t* a) {
  #pragma unroll
  for (int i = 0; i < N; i++) asm volatile("" : "+r"(a[i]) :: "memory");
}
__device__ __forceinline__ void cexp_t(float lg2mag, float turns, float& re, float& im) {
  float m = ex2(lg2mag);
  float fr = (turns - __fadd_rn(__fadd_rn(turns, 12582912.f), -12582912.f)) * 6.283185307f;
  re = m * __cosf(fr); im = m * __sinf(fr);
}
__device__ __forceinline__ void cmul(float ar, float ai, float br, float bi, float& cr, float& ci) {
  cr = fmaf(ar, br, -ai * bi); ci = fmaf(ar, bi, ai * br);
}

__device__ __forceinline__ void wg_ss192_tb(float* d, uint64_t da, uint64_t db, int scale_d) {
  asm volatile("{\n.reg .pred p;\nsetp.ne.b32 p, %98, 0;\n"
    "wgmma.mma_async.sync.aligned.m64n192k16.f32.bf16.bf16 "
    "{%0, %1, %2, %3, %4, %5, %6, %7, %8, %9, %10, %11, %12, %13, %14, %15, %16, %17, %18, %19, %20, %21, %22, %23, %24, %25, %26, %27, %28, %29, %30, %31, %32, %33, %34, %35, %36, %37, %38, %39, %40, %41, %42, %43, %44, %45, %46, %47, %48, %49, %50, %51, %52, %53, %54, %55, %56, %57, %58, %59, %60, %61, %62, %63, %64, %65, %66, %67, %68, %69, %70, %71, %72, %73, %74, %75, %76, %77, %78, %79, %80, %81, %82, %83, %84, %85, %86, %87, %88, %89, %90, %91, %92, %93, %94, %95}, %96, %97, p, 1, 1, 0, 1;\n}\n"
    : "+f"(d[0]), "+f"(d[1]), "+f"(d[2]), "+f"(d[3]), "+f"(d[4]), "+f"(d[5]), "+f"(d[6]), "+f"(d[7]), "+f"(d[8]), "+f"(d[9]), "+f"(d[10]), "+f"(d[11]), "+f"(d[12]), "+f"(d[13]), "+f"(d[14]), "+f"(d[15]), "+f"(d[16]), "+f"(d[17]), "+f"(d[18]), "+f"(d[19]), "+f"(d[20]), "+f"(d[21]), "+f"(d[22]), "+f"(d[23]), "+f"(d[24]), "+f"(d[25]), "+f"(d[26]), "+f"(d[27]), "+f"(d[28]), "+f"(d[29]), "+f"(d[30]), "+f"(d[31]), "+f"(d[32]), "+f"(d[33]), "+f"(d[34]), "+f"(d[35]), "+f"(d[36]), "+f"(d[37]), "+f"(d[38]), "+f"(d[39]), "+f"(d[40]), "+f"(d[41]), "+f"(d[42]), "+f"(d[43]), "+f"(d[44]), "+f"(d[45]), "+f"(d[46]), "+f"(d[47]), "+f"(d[48]), "+f"(d[49]), "+f"(d[50]), "+f"(d[51]), "+f"(d[52]), "+f"(d[53]), "+f"(d[54]), "+f"(d[55]), "+f"(d[56]), "+f"(d[57]), "+f"(d[58]), "+f"(d[59]), "+f"(d[60]), "+f"(d[61]), "+f"(d[62]), "+f"(d[63]), "+f"(d[64]), "+f"(d[65]), "+f"(d[66]), "+f"(d[67]), "+f"(d[68]), "+f"(d[69]), "+f"(d[70]), "+f"(d[71]), "+f"(d[72]), "+f"(d[73]), "+f"(d[74]), "+f"(d[75]), "+f"(d[76]), "+f"(d[77]), "+f"(d[78]), "+f"(d[79]), "+f"(d[80]), "+f"(d[81]), "+f"(d[82]), "+f"(d[83]), "+f"(d[84]), "+f"(d[85]), "+f"(d[86]), "+f"(d[87]), "+f"(d[88]), "+f"(d[89]), "+f"(d[90]), "+f"(d[91]), "+f"(d[92]), "+f"(d[93]), "+f"(d[94]), "+f"(d[95])
    : "l"(da), "l"(db), "r"(scale_d));
}
__device__ __forceinline__ void wg_ss48_tb(float* d, uint64_t da, uint64_t db, int scale_d) {
  asm volatile("{\n.reg .pred p;\nsetp.ne.b32 p, %26, 0;\n"
    "wgmma.mma_async.sync.aligned.m64n48k16.f32.bf16.bf16 "
    "{%0, %1, %2, %3, %4, %5, %6, %7, %8, %9, %10, %11, %12, %13, %14, %15, %16, %17, %18, %19, %20, %21, %22, %23}, %24, %25, p, 1, 1, 0, 1;\n}\n"
    : "+f"(d[0]), "+f"(d[1]), "+f"(d[2]), "+f"(d[3]), "+f"(d[4]), "+f"(d[5]), "+f"(d[6]), "+f"(d[7]), "+f"(d[8]), "+f"(d[9]), "+f"(d[10]), "+f"(d[11]), "+f"(d[12]), "+f"(d[13]), "+f"(d[14]), "+f"(d[15]), "+f"(d[16]), "+f"(d[17]), "+f"(d[18]), "+f"(d[19]), "+f"(d[20]), "+f"(d[21]), "+f"(d[22]), "+f"(d[23])
    : "l"(da), "l"(db), "r"(scale_d));
}
__device__ __forceinline__ void wg_ss48_tt(float* d, uint64_t da, uint64_t db, int scale_d) {
  asm volatile("{\n.reg .pred p;\nsetp.ne.b32 p, %26, 0;\n"
    "wgmma.mma_async.sync.aligned.m64n48k16.f32.bf16.bf16 "
    "{%0, %1, %2, %3, %4, %5, %6, %7, %8, %9, %10, %11, %12, %13, %14, %15, %16, %17, %18, %19, %20, %21, %22, %23}, %24, %25, p, 1, 1, 1, 1;\n}\n"
    : "+f"(d[0]), "+f"(d[1]), "+f"(d[2]), "+f"(d[3]), "+f"(d[4]), "+f"(d[5]), "+f"(d[6]), "+f"(d[7]), "+f"(d[8]), "+f"(d[9]), "+f"(d[10]), "+f"(d[11]), "+f"(d[12]), "+f"(d[13]), "+f"(d[14]), "+f"(d[15]), "+f"(d[16]), "+f"(d[17]), "+f"(d[18]), "+f"(d[19]), "+f"(d[20]), "+f"(d[21]), "+f"(d[22]), "+f"(d[23])
    : "l"(da), "l"(db), "r"(scale_d));
}
__device__ __forceinline__ void wg_rs88_tb(float* d, const uint32_t* a, uint64_t db, int scale_d) {
  asm volatile("{\n.reg .pred p;\nsetp.ne.b32 p, %49, 0;\n"
    "wgmma.mma_async.sync.aligned.m64n88k16.f32.bf16.bf16 "
    "{%0, %1, %2, %3, %4, %5, %6, %7, %8, %9, %10, %11, %12, %13, %14, %15, %16, %17, %18, %19, %20, %21, %22, %23, %24, %25, %26, %27, %28, %29, %30, %31, %32, %33, %34, %35, %36, %37, %38, %39, %40, %41, %42, %43}, {%44, %45, %46, %47}, %48, p, 1, 1, 1;\n}\n"
    : "+f"(d[0]), "+f"(d[1]), "+f"(d[2]), "+f"(d[3]), "+f"(d[4]), "+f"(d[5]), "+f"(d[6]), "+f"(d[7]), "+f"(d[8]), "+f"(d[9]), "+f"(d[10]), "+f"(d[11]), "+f"(d[12]), "+f"(d[13]), "+f"(d[14]), "+f"(d[15]), "+f"(d[16]), "+f"(d[17]), "+f"(d[18]), "+f"(d[19]), "+f"(d[20]), "+f"(d[21]), "+f"(d[22]), "+f"(d[23]), "+f"(d[24]), "+f"(d[25]), "+f"(d[26]), "+f"(d[27]), "+f"(d[28]), "+f"(d[29]), "+f"(d[30]), "+f"(d[31]), "+f"(d[32]), "+f"(d[33]), "+f"(d[34]), "+f"(d[35]), "+f"(d[36]), "+f"(d[37]), "+f"(d[38]), "+f"(d[39]), "+f"(d[40]), "+f"(d[41]), "+f"(d[42]), "+f"(d[43])
    : "r"(a[0]), "r"(a[1]), "r"(a[2]), "r"(a[3]), "l"(db), "r"(scale_d));
}
__device__ __forceinline__ void wg_ss80_tb(float* d, uint64_t da, uint64_t db, int scale_d) {
  asm volatile("{\n.reg .pred p;\nsetp.ne.b32 p, %42, 0;\n"
    "wgmma.mma_async.sync.aligned.m64n80k16.f32.bf16.bf16 "
    "{%0, %1, %2, %3, %4, %5, %6, %7, %8, %9, %10, %11, %12, %13, %14, %15, %16, %17, %18, %19, %20, %21, %22, %23, %24, %25, %26, %27, %28, %29, %30, %31, %32, %33, %34, %35, %36, %37, %38, %39}, %40, %41, p, 1, 1, 0, 1;\n}\n"
    : "+f"(d[0]), "+f"(d[1]), "+f"(d[2]), "+f"(d[3]), "+f"(d[4]), "+f"(d[5]), "+f"(d[6]), "+f"(d[7]), "+f"(d[8]), "+f"(d[9]), "+f"(d[10]), "+f"(d[11]), "+f"(d[12]), "+f"(d[13]), "+f"(d[14]), "+f"(d[15]), "+f"(d[16]), "+f"(d[17]), "+f"(d[18]), "+f"(d[19]), "+f"(d[20]), "+f"(d[21]), "+f"(d[22]), "+f"(d[23]), "+f"(d[24]), "+f"(d[25]), "+f"(d[26]), "+f"(d[27]), "+f"(d[28]), "+f"(d[29]), "+f"(d[30]), "+f"(d[31]), "+f"(d[32]), "+f"(d[33]), "+f"(d[34]), "+f"(d[35]), "+f"(d[36]), "+f"(d[37]), "+f"(d[38]), "+f"(d[39])
    : "l"(da), "l"(db), "r"(scale_d));
}
__device__ __forceinline__ void wg_ss48_tt_h(float* d, uint64_t da, uint64_t db, int scale_d) {
  asm volatile("{\n.reg .pred p;\nsetp.ne.b32 p, %26, 0;\n"
    "wgmma.mma_async.sync.aligned.m64n48k16.f32.f16.f16 "
    "{%0, %1, %2, %3, %4, %5, %6, %7, %8, %9, %10, %11, %12, %13, %14, %15, %16, %17, %18, %19, %20, %21, %22, %23}, %24, %25, p, 1, 1, 1, 1;\n}\n"
    : "+f"(d[0]), "+f"(d[1]), "+f"(d[2]), "+f"(d[3]), "+f"(d[4]), "+f"(d[5]), "+f"(d[6]), "+f"(d[7]), "+f"(d[8]), "+f"(d[9]), "+f"(d[10]), "+f"(d[11]), "+f"(d[12]), "+f"(d[13]), "+f"(d[14]), "+f"(d[15]), "+f"(d[16]), "+f"(d[17]), "+f"(d[18]), "+f"(d[19]), "+f"(d[20]), "+f"(d[21]), "+f"(d[22]), "+f"(d[23])
    : "l"(da), "l"(db), "r"(scale_d));
}

struct Params {
  const __nv_bfloat16 *par[4], *logdt, *dskip, *u, *wo;
  CUtensorMap m[M_COUNT];
};

#define CHUNK(i) ((i) == 0 ? c : ((i) == 7 ? (c ^ 1) : (((c & 6) + 1 + (i)) & 7)))
#define FLAG(kind, rr, cc) (&g_flag[((kind) * 128 + (rr) * 8 + (cc)) * 32])
#define SLOT(i) ((i) == 0 || (i) == 1 ? OFF_EXTRA : OFF_BLK - 256 + ((i) == 7 ? 0 : (i) - 2) * BLK)
__device__ __forceinline__ void load_quad(uint32_t* A, uint32_t addr) {
  A[0] = lds32v(addr); A[1] = lds32v(addr + 32); A[2] = lds32v(addr - 32); A[3] = lds32v(addr);
}

__device__ __forceinline__ bool y_transpose(uint32_t sb, int w5, int lane, uint32_t ytag) {
  const int mi = lane >> 3, rw = lane & 7;
  const uint32_t sa = sb + OFF_EXTRA + (w5 * 16 + rw) * 128 + ((mi ^ rw) << 4), da = sb + SLOT(3) + (8 * mi + rw) * 160 + w5 * 32;
  const uint32_t ym = lane < 4 ? 0x10001u : 0u;
  bar_sync(7, 160);
  uint32_t v[8][4], bad = 0;
  #pragma unroll
  for (int q = 0; q < 8; q++) ldsm4t(v[q], (sa ^ ((q & 1) * 64 + ((q >> 1) & 1) * 16)) + ((q >> 1) & 1) * 10240 + (q >> 2) * 1024);
  #pragma unroll
  for (int q = 0; q < 8; q++) {
    bad |= (v[q][0] ^ ytag) | (v[q][2] ^ ytag);
    stsm4(da + (q & 3) * 5120 + (q >> 2) * 16, v[q][0] & ~ym, v[q][1], v[q][2] & ~ym, v[q][3]);
  }
  fence_async();
  uint32_t any;
  asm volatile("{\n.reg .pred p;\nsetp.ne.u32 p, %1, 0;\nbarrier.red.or.pred p, 7, 160, p;\nselp.u32 %0, 1, 0, p;\n}" : "=r"(any) : "r"(bad & ym) : "memory");
  return any;
}

__global__ void __launch_bounds__(512, 1) fused_kernel(const __grid_constant__ Params prm) {
  extern __shared__ unsigned char smem_raw[];
  const uint32_t sb = __shfl_sync(0xffffffff, smem_u32(smem_raw), 0);
  const int tid = threadIdx.x, lane = tid & 31;
  const int warp = __shfl_sync(0xffffffff, tid >> 5, 0), wg = warp >> 2, w4 = warp & 3;
  const int cta = blockIdx.x, r = cta >> 3, c = cta & 7;
  if ((sb & 0xffffffu) != SB0) return;
#define BAR(i) (sb + OFF_BAR + 8 * (i))
  const bool sw64 = ((c + 1) & 2) != 0;

  if (wg == 3) {
    if (warp == 13 && elect_one()) {
      #pragma unroll
      for (int i = M_W128; i <= M_U; i++) asm volatile("prefetch.tensormap [%0];" :: "l"(&prm.m[i]) : "memory");
    }
    asm volatile("setmaxnreg.dec.sync.aligned.u32 56;");
    const int tid = rtid(), lane = tid & 31;
    if (warp == 12) {
      if (elect_one()) {
        #pragma unroll
        for (int i = 0; i < 5; i++) mbar_init(BAR(BR_FULL + i), 1);
        asm volatile("fence.mbarrier_init.release.cluster;" ::: "memory");
      }
      {
        const CUtensorMap* mwp = &prm.m[sw64 ? M_W64 : M_W128];
        const int mcol = (c * 80 + (c & 1) * 16) >> (sw64 ? 5 : 6), rcol = c * 80 + ((c & 1) ? 0 : 64);
        uint32_t s = 0, ph = 1, xs = 0;
        #pragma unroll 1
        for (int kb = 0; kb < 20; kb++) {
          if (kb == 1) asm volatile("bar.arrive 0, 512;" ::: "memory");
          if (kb == 4) { bar_sync(6, 128); if (EN_SSM) mbar_wait(BAR(BR_KS), 0); }
          if (kb >= 5) mbar_wait(BAR(BR_EMPTY) + 8 * s, ph);
          if (EN_ATT && elect_one()) {
            const uint32_t st = sb + s * W_SLOT, fb = BAR(BR_FULL) + 8 * s;
            mbar_expect_tx(fb, (kb & 1) ? W_SLOT : W_SLOT + 16384);
            if (!(kb & 1)) tma2d(sb + OFF_X + xs, &prm.m[M_X], fb, kb * 32, r * 128);
            tma4d(st, mwp, fb, 0, kb * 32, mcol, 0);
            tma3d(st + 12288, &prm.m[M_WR], fb, rcol, kb * 32, 0);
          }
          if (kb < 4 && lane == 0) TS(24 + kb);
          if (kb == 14 && elect_one()) asm volatile("cp.async.bulk.prefetch.L2.global [%0], 6400;" :: "l"(prm.wo + cta * 3200) : "memory");
          if (!EN_ATT && kb == 4) break;
          if (++s == 5) { s = 0; ph ^= 1; }
          if (kb & 1) { xs += 16384; if (xs == 49152) xs = 0; }
        }
      }
      if (EN_ATT) {
      mbar_wait(BAR(BR_EPOCH), 0);
      const unsigned epoch = lds32(sb + OFF_EPOCH);
      const unsigned* fo = FLAG(3, r, lane & 7);
      unsigned seen = __ballot_sync(0xffffffff, ld_rlx(lane < 16 ? fo : FLAG(0, lane & 15, c)) == epoch) & 0xffu;
      mbar_wait(BAR(BR_GEMM), 0);
      if (elect_one()) {
        mbar_expect_tx(BAR(BR_WO), 10240);
        tma2d(sb, &prm.m[M_WO], BAR(BR_WO), c * 64, c * 80);
        mbar_expect_tx(BAR(BR_KVP), 61440);
        mbar_expect_tx(BAR(BR_WO + 1), 7 * 10240);
      }
      {
        uint32_t ds = sb + OFF_WOR + (lane >> 3) * 128 + (((lane & 7) ^ (lane >> 3)) << 4);
        #pragma unroll 1
        for (int h = 0; h < 2; h++) {
          const int i = (lane & 6) + h;
          const char* gs = reinterpret_cast<const char*>(prm.wo) + (size_t)((lane >> 3) + CHUNK(i) * 80) * 1280 + 1024 + c * 32 + (lane & 1) * 16;
          #pragma unroll 2
          for (int q = 0; q < 20; q++) {
            asm volatile("cp.async.cg.shared.global [%0], [%1], 16;" :: "r"(ds), "l"(gs) : "memory");
            ds = (ds + 512) ^ 64; gs += 5120;
          }
        }
      }
      mbar_wait(BAR(BR_PUB), 0);
      poll_all(FLAG(0, lane & 15, c), epoch);
      if (elect_one()) { TS(23); bulk_ld(sb + OFF_KVP, &g_kvp[c * 16 * 240], 61440, BAR(BR_KVP)); }
      asm volatile("cp.async.wait_all;" ::: "memory");
      fence_async();
      mbar_arrive(BAR(BR_WO));
      mbar_wait(BAR(BR_SUM), 0);
      if (elect_one()) {
        #pragma unroll 1
        for (int i = 1; i < 8; i++) tma2d(sb + i * 10240, &prm.m[M_WO], BAR(BR_WO + 1), c * 64, CHUNK(i) * 80);
      }
      mbar_wait(BAR(BR_OSTG), 0);
      if (elect_one()) {
        bulk_st(&g_o[cta * 1280], sb + OFF_EXTRA, 20480);
        bulk_commit();
        bulk_wait0();
        st_rlx(FLAG(3, r, c), epoch);
        TS(20);
      }
      __syncwarp();
      #pragma unroll 1
      for (int i = 1; i < 8; i++) {
        const int src = CHUNK(i);
        if (!((seen >> src) & 1)) seen = poll_bit(fo, epoch, 1u << src);
        if (i == 1 || i == 7) mbar_wait(BAR(BR_OEMPTY) + 8 * (i & 2), 0);
        if (EN_SSM && (i == 2 || i == 6)) mbar_wait(BAR(BR_FREE) + 2 * (i & 4), 0);
        if (elect_one()) {
          mbar_expect_tx(BAR(BR_OFULL) + 8 * i, 20480);
          bulk_ld(sb + SLOT(i), &g_o[(r * 8 + src) * 1280], 20480, BAR(BR_OFULL) + 8 * i);
          if (i == 1) TS(21);
          if (i == 7) TS(22);
        }
        __syncwarp();
      }
      if (lane == 0) { DUMP(20, 30); }
      }
    } else {
      const int hw = warp - 13, ht = tid - 416;
      if (hw == 2 && elect_one()) {
        #pragma unroll
        for (int i = 5; i < BR_COUNT; i++) mbar_init(BAR(i), i == BR_WO ? 33 : i < BR_EMPTY ? 1 : i < BR_OEMPTY ? 2 : i < BR_Y ? 8 : i < BR_OSTG ? 4 : i == BR_OSTG ? 8 : i < BR_U2 ? 3 : 1);
        asm volatile("fence.mbarrier_init.release.cluster;" ::: "memory");
        if (EN_SSM) { mbar_expect_tx(BAR(BR_UIN), 20480); tma2d(sb + OFF_UT, &prm.m[M_U], BAR(BR_UIN), c * 80, r * 128); }
      }
      __syncwarp();
      asm volatile("bar.arrive 0, 512;" ::: "memory");
      const unsigned epoch = hw == 0 ? ld_rlx(&g_epoch[cta]) + 1 : 0;
      bar_sync(5, 96);
      asm volatile("bar.arrive 6, 128;" ::: "memory");
      if (hw == 1 && elect_one()) {
        #pragma unroll
        for (int i = M_WO; i < M_COUNT; i++) asm volatile("prefetch.tensormap [%0];" :: "l"(&prm.m[i]) : "memory");
      }
      if (ht == 0) {
        st_rlx(&g_epoch[cta], epoch);
        sts32(sb + OFF_EPOCH, epoch);
        mbar_arrive(BAR(BR_EPOCH));
      }
      if (EN_SSM) {
      const int mi = lane >> 3, rw = lane & 7, ch0 = c * 80 + r * 5;
      mbar_wait(BAR(BR_UIN), 0);
      if (ht == 0) TS(36);
      #pragma unroll 1
      for (int h = 0; h < 2; h++) {
        const uint32_t sa = sb + OFF_UT + h * 10240 + (8 * mi + rw) * 160 + hw * 16, da = sb + OFF_UT + h * 10240 + (hw * 8 + rw) * 128 + ((mi ^ rw ^ h) << 4);
        uint32_t v[8][4];
        #pragma unroll
        for (int q = 0; q < 8; q++) if (q < 6 || hw == 0) ldsm4t(v[q], sa + (q & 1) * 5120 + (q >> 1) * 48);
        bar_sync(5, 96);
        #pragma unroll
        for (int q = 0; q < 8; q++) if (q < 6 || hw == 0) stsm4((da ^ ((q & 1) * 64)) + (q >> 1) * 3072, v[q][0], v[q][1], v[q][2], v[q][3]);
      }
      fence_async();
      bar_sync(5, 96);
      if (hw == 0) {
        if (elect_one()) {
          tma2d_st(&prm.m[M_SA], sb + OFF_UT, r * 128, c * 80);
          tma2d_st(&prm.m[M_SA], sb + OFF_UT + 10240, r * 128 + 64, c * 80);
          bulk_commit(); bulk_wait0_read();
          mbar_arrive(BAR(BR_UOUT));
          TS(37);
          bulk_wait0();
          st_rel(FLAG(1, r, c), epoch);
          TS(30);
        }
        __syncwarp();
        poll_all_acq(FLAG(1, lane & 15, c), epoch);
      }
      #pragma unroll 1
      for (int q6 = hw; q6 < 30; q6 += 3) {
        if (q6 >= 24 && q6 < 27) { __syncwarp(); if (lane == 0) mbar_arrive(BAR(BR_DRDY)); }
        if (q6 < 3 || (q6 >= 18 && q6 < 21)) {
          const int p = q6 >= 18;
          if (hw == 0) {
            if (!p) {
              mbar_wait(BAR(BR_KS + 2), 0);
              if (elect_one()) {
                fence_async_g();
                mbar_expect_tx(BAR(BR_U), 12288);
                #pragma unroll 1
                for (int q = 0; q < 3; q++) bulk_ld(sb + OFF_BLK + q * BLK, g_uy + (ch0 + q) * 2048, 4096, BAR(BR_U));
                TS(31);
              }
              __syncwarp();
            }
            mbar_wait(BAR(p ? BR_U2 : BR_U), 0);
          }
          bar_sync(5, 96);
          if (ht == 0) TS(38 + p);
        }
        {
          const int k = q6 / 6, kap = (q6 - 6 * k) * 32 + lane;
          const uint32_t blk = sb + OFF_BLK + k * BLK;
          float P[33];
          P[0] = 0.f;
          #pragma unroll
          for (int q = 0; q < 4; q++) {
            const int ch = kap - 3 + q;
            uint32_t v[4];
            lds128(v, blk + (uint32_t)((ch * 16) ^ ((ch * 2) & 0x10)));
            #pragma unroll
            for (int e = 0; e < 4; e++) {
              P[q * 8 + 2 * e + 1] = (q == 0 && e < 2) ? 0.f : P[q * 8 + 2 * e] + bf_lo(v[e]);
              P[q * 8 + 2 * e + 2] = (q == 0 && e < 2) ? 0.f : P[q * 8 + 2 * e + 1] + bf_hi(v[e]);
            }
          }
#define WIN(lo, hi, e) (P[25 + (e) - (lo)] - P[24 + (e) - (hi)])
#define WIN8(lo, hi) pack2(WIN(lo, hi, 0), WIN(lo, hi, 1)), pack2(WIN(lo, hi, 2), WIN(lo, hi, 3)), pack2(WIN(lo, hi, 4), WIN(lo, hi, 5)), pack2(WIN(lo, hi, 6), WIN(lo, hi, 7))
          const uint32_t o2 = blk + B_D + (kap & 1) * 1552 + (kap >> 1) * 16;
          sts128(o2, WIN8(3, 5));
          sts128(o2 + B_D5, WIN8(6, 10));
          if (kap < 2) sts128(blk + B_D + kap * B_D5 + 1536, 0, 0, 0, 0);
          if (kap < 128) {
            const uint32_t o = blk + B_D + (kap & 1) * 1024 + (kap >> 1) * 16;
            sts128(o + B_D7, WIN8(5, 11));
            sts128(o + B_D9, WIN8(12, 20));
          }
        }
      }
      __syncwarp();
      if (lane == 0) mbar_arrive(BAR(BR_DRDY + 1));
      if (ht == 0) TS(32);
      if (hw == 0) {
        #pragma unroll 1
        for (int p = 0; p < 2; p++) {
          mbar_wait(BAR(BR_Y) + 8 * p, 0);
          if (elect_one()) {
            #pragma unroll 1
            for (int k = 4 * p; k < 4 + p; k++) bulk_st(g_uy + (640 + ch0 + k) * 2048, sb + OFF_BLK + k * BLK, 4096);
            bulk_commit(); bulk_wait0_read();
            mbar_arrive(BAR(BR_FREE) + 8 * p);
          }
          __syncwarp();
        }
        if (elect_one()) { bulk_wait0(); st_rlx(FLAG(2, r, c), epoch); TS(33); }
        __syncwarp();
        poll_all(FLAG(2, lane & 15, c), epoch);
        if (EN_ATT) mbar_wait(BAR(BR_OEMPTY + 1), 0);
        #pragma unroll 1
        for (int n = 0; n < 64; n++) {
          if (elect_one()) {
            mbar_expect_tx(BAR(BR_YIN), 20480);
            tma2d(sb + OFF_EXTRA, &prm.m[M_SA], BAR(BR_YIN), r * 128, 640 + c * 80);
            tma2d(sb + OFF_EXTRA + 10240, &prm.m[M_SA], BAR(BR_YIN), r * 128 + 64, 640 + c * 80);
            TS(34);
          }
          __syncwarp();
          if (EN_ATT) mbar_wait(BAR(BR_OEMPTY + 3), 0);
          mbar_wait(BAR(BR_YIN), n & 1);
          if (!y_transpose(sb, 4, lane, (epoch & 1u) * 0x10001u)) break;
          FIXCNT
        }
      if (elect_one()) {
        tma2d_st(&prm.m[M_OUT], sb + SLOT(3), c * 80, r * 128);
        bulk_commit(); bulk_wait0_read();
        TS(35); DUMP(30, 40); DUMP(0, 1);
      }
      }
      }
    }
  } else {
    const int g = lane >> 2, tq = lane & 3, t7 = tid & 127;
    uint32_t pr[3][2], pd;
    {
      const int ch = c * 80 + r * 5 + wg;
      uint32_t raw[3][4];
      #pragma unroll
      for (int e = 0; e < 4; e++) {
        const __nv_bfloat16* pp = prm.par[e] + ch * 128 + t7;
        #pragma unroll
        for (int q = 0; q < 3; q++) {
          raw[q][e] = 0;
          if (q == 0 || wg == 2) asm volatile("ld.global.nc.u16 %0, [%1];" : "=r"(raw[q][e]) : "l"(pp + q * 128));
        }
      }
      asm volatile("ld.global.nc.u16 %0, [%1];" : "=r"(pd) : "l"(((lane & 4) ? prm.dskip : prm.logdt) + ch + min(lane & 3, 2)));
      asm volatile("setmaxnreg.inc.sync.aligned.u32 152;");
      if (EN_SSM && wg < 2) {
        #pragma unroll
        for (int k = 0; k < 2; k++) {
          const uint32_t z = sb + OFF_BLK + (2 * wg + k) * BLK + t7 * 16;
          sts128(z + B_TBL, 0, 0, 0, 0); sts128(z + B_TBL + 2048, 0, 0, 0, 0);
        }
        if (tid < 80) sts128(sb + OFF_BLK + (tid >> 4) * BLK - 256 + (tid & 15) * 16, 0, 0, 0, 0);
      }
      #pragma unroll
      for (int q = 0; q < 3; q++) {
        #pragma unroll
        for (int e = 0; e < 2; e++) pr[q][e] = raw[q][2 * e] | (raw[q][2 * e + 1] << 16);
        const uint32_t m = __reduce_max_sync(0xffffffff, max(raw[q][2] & 0x7fffu, raw[q][3] & 0x7fffu));
        if (lane == 0) sts32(sb + OFF_EPOCH + 64 + (wg * 3 + q) * 16 + w4 * 4, m);
      }
      bar_sync(2 + wg, 128);
    }
    if (tid == 256) TS(40);
    if (EN_SSM) {
#define P0(w) ((w) == 1 ? 4 * W_SLOT : OFF_BLK + (w) * BLK)
#define P2(w) ((w) == 1 ? OFF_X + 32768 - 4 * W_SLOT : BLK)
      uint32_t ea = sb + P0(wg) + (lane >> 4) * 7168 + (w4 & 1) * P2(wg) + ((lane >> 3) & 1) * 256 + (lane & 7) * 16 + (w4 >> 1) * 2048;
      constexpr uint64_t dE = mkdesc(SB0, 128, 512, 0);
      const uint32_t xa = sb + OFF_BLK + 18560 + t7 * 8, xr_ = sb + OFF_BLK + 18560 + (t7 ^ 64) * 8;
      const int j = (w4 & 1) * 16 + (w4 >> 1) * 8 + g, i2 = tq < 2 ? 64 * tq + j : 32 * (tq - 2) + j;
      const uint32_t e2 = B_TBL + 4 * (tq < 2 ? T_F3 + (((i2 - 1) & 1) ? 80 : 0) + ((i2 - 1) >> 1) + 16 : T_F2 + (i2 & 1) * 96 + (i2 >> 1));
      const uint32_t e1 = tq < 2 ? (i2 ? e2 - 64 : B_TBL + 4 * (T_F2 + 175)) : B_TBL + 4 * (i2 ? T_F2 + ((2 * i2 - 1) & 3) * 48 + ((2 * i2 - 1) >> 2) : 16 + 511);
      const uint32_t e0 = B_TBL + (16 + 8 * j + 2 * tq) * 4;
      #pragma unroll 1
      for (int it = 0; it < 5; it++) {
        const int k = it < 2 ? 1 - it : it;
        const uint32_t blk = sb + OFF_BLK + k * BLK;
        if (it == 0 || it >= 3) {
          const int q = it ? it - 2 : 0;
          if (it == 3) {
            mbar_wait(BAR(BR_UOUT), 0);
            ea += BLK;
            sts128(sb + OFF_UT + B_TBL + t7 * 16, 0, 0, 0, 0); sts128(sb + OFF_UT + B_TBL + 2048 + t7 * 16, 0, 0, 0, 0);
          }
          const uint32_t ga = ea + 4096 - (w4 >> 1) * 512;
#define PUT4(i, a, b, c_, d) sts128(((i) < 8 ? ea + ((i) >> 1) * 512 : ga + (((i) - 8) >> 1) * 512) + ((i) & 1) * 128, a, b, c_, d)
          const uint32_t pa0 = pr[0][0], pc0 = pr[0][1];
          const float dt = bf_round(expf(bf_lo(__shfl_sync(0xffffffff, pd, q))));
          #pragma unroll
          for (int e = 0; e < 2; e++) { pr[0][e] = pr[1][e]; pr[1][e] = pr[2][e]; }
          uint32_t mm[4];
          lds128(mm, sb + OFF_EPOCH + 64 + (wg * 3 + q) * 16);
          const uint32_t ex = min(max(max(max(mm[0], mm[1]), max(mm[2], mm[3])) >> 7, 1u), 253u);
          const float sc = __uint_as_float((254u - ex) << 23);
          if (t7 == 4 + q) sts64(sb + OFF_EPOCH + 16 + (wg + q) * 8, __float_as_uint(2.f * dt * __uint_as_float(ex << 23)), pd << 16);
          const float lr = -bf_round(expf(bf_lo(pa0))) * dt * 1.44269504089f;
          const float tn = bf_hi(pa0) * dt * 0.15915494309f;
          float z1r, z1i, z2r, z2i, z4r, z4i, xr[8], xi[8], gr[8], gi[8], wr[9], wi[9];
          cexp_t(lr, -tn, z1r, z1i);
          cexp_t(lr * 8.f, tn * 8.f, xr[1], xi[1]);
          cexp_t(lr * 64.f, tn * 64.f, wr[0], wi[0]);
          xr[0] = 1.f; xi[0] = 0.f;
          cmul(xr[1], xi[1], xr[1], xi[1], xr[2], xi[2]); cmul(xr[2], xi[2], xr[1], xi[1], xr[3], xi[3]);
          cmul(xr[2], xi[2], xr[2], xi[2], xr[4], xi[4]);
          #pragma unroll
          for (int b = 1; b < 4; b++) cmul(xr[4], xi[4], xr[b], xi[b], xr[4 + b], xi[4 + b]);
          cmul(wr[0], wi[0], wr[0], wi[0], wr[1], wi[1]); cmul(wr[1], wi[1], wr[0], wi[0], wr[2], wi[2]);
          cmul(wr[1], wi[1], wr[1], wi[1], wr[3], wi[3]); cmul(wr[3], wi[3], wr[3], wi[3], wr[4], wi[4]);
          cmul(wr[4], wi[4], wr[3], wi[3], wr[5], wi[5]); cmul(wr[4], wi[4], wr[4], wi[4], wr[6], wi[6]);
          cmul(wr[6], wi[6], wr[4], wi[4], wr[7], wi[7]); cmul(wr[6], wi[6], wr[6], wi[6], wr[8], wi[8]);
          uint32_t R[4], I[4], PR[4], PI[4];
          #pragma unroll
          for (int b = 0; b < 4; b++) { R[b] = packh(xr[2 * b], xr[2 * b + 1]); I[b] = packh(xi[2 * b], xi[2 * b + 1]); }
          PUT4(0, R[0], R[1], R[2], R[3]); PUT4(1, I[0], I[1], I[2], I[3]);
          #pragma unroll
          for (int i = 0; i < 3; i++) {
            const uint32_t z = packh(wr[i], wi[i]);
            #pragma unroll
            for (int b = 0; b < 4; b++) hcm2(R[b], I[b], z, PR[b], PI[b]);
            PUT4(2 * i + 2, PR[0], PR[1], PR[2], PR[3]); PUT4(2 * i + 3, PI[0], PI[1], PI[2], PI[3]);
          }
          gr[0] = bf_lo(pc0) * sc; gi[0] = -bf_hi(pc0) * sc;
          cmul(z1r, z1i, z1r, z1i, z2r, z2i); cmul(z2r, z2i, z2r, z2i, z4r, z4i);
          cmul(gr[0], gi[0], z1r, z1i, gr[1], gi[1]);
          cmul(gr[0], gi[0], z2r, z2i, gr[2], gi[2]); cmul(gr[1], gi[1], z2r, z2i, gr[3], gi[3]);
          #pragma unroll
          for (int b = 0; b < 4; b++) cmul(gr[b], gi[b], z4r, z4i, gr[4 + b], gi[4 + b]);
          PUT4(8, packh(gr[0], gr[1]), packh(gr[2], gr[3]), packh(gr[4], gr[5]), packh(gr[6], gr[7]));
          PUT4(9, packh(gi[0], gi[1]), packh(gi[2], gi[3]), packh(gi[4], gi[5]), packh(gi[6], gi[7]));
          {
            const uint32_t z = packh(wr[3], -wi[3]), a4r = packh(gr[0], gr[4]), a4i = packh(gi[0], gi[4]);
            hcm2(packh(gr[0], gr[2]), packh(gi[0], gi[2]), z, PR[0], PI[0]);
            hcm2(packh(gr[4], gr[6]), packh(gi[4], gi[6]), z, PR[1], PI[1]);
            hcm2(a4r, a4i, packh(wr[4], -wi[4]), PR[2], PI[2]);
            hcm2(a4r, a4i, packh(wr[5], -wi[5]), PR[3], PI[3]);
            PUT4(10, PR[0], PR[1], PR[2], PR[3]); PUT4(11, PI[0], PI[1], PI[2], PI[3]);
            float hr, hi_;
            cmul(gr[0], gi[0], wr[3], -wi[3], hr, hi_);
            const uint32_t cr = packh(gr[0], hr), ci = packh(gi[0], hi_);
            #pragma unroll
            for (int i = 0; i < 3; i++) hcm2(cr, ci, packh(wr[6 + i], -wi[6 + i]), PR[i], PI[i]);
            PUT4(12, PR[0], PR[1], PR[2], 0u); PUT4(13, PI[0], PI[1], PI[2], 0u);
          }
          fence_async();
          bar_sync(it ? 4 : 0, it ? 128 : 512);
          if (wg < 2) break;
        }
        float ka[24]; zero<24>(ka);
        const int fs = min(k, 3);
        wg_fence();
        #pragma unroll
        for (int s = 0; s < 8; s++) {
          const uint32_t lo = (uint32_t)dE + ((P0(fs) + (s >> 2) * P2(fs)) >> 4) + ((s >> 1) & 1) * 448 + (s & 1) * 16;
          wg_ss48_tt_h(ka, desc2(lo, dE >> 32), desc2(lo + 256, dE >> 32), s != 0);
        }
        wg_commit();
        uint32_t fd[2];
        lds64(fd, sb + OFF_EPOCH + 16 + k * 8);
        if (it == 1 || it == 2) bar_sync(4, 128);
        wg_wait<0>();
        pin<24>(ka);
        float kk[6];
        const bool up = w4 >= 2;
        #pragma unroll
        for (int n = 0; n < 3; n++) {
          sts64f(xa + n * BLK, up ? ka[12 + 4 * n] : ka[4 * n + 2], up ? ka[13 + 4 * n] : ka[4 * n + 3]);
          kk[2 * n] = up ? ka[14 + 4 * n] : ka[4 * n]; kk[2 * n + 1] = up ? ka[15 + 4 * n] : ka[4 * n + 1];
        }
        bar_sync(4, 128);
        if (t7 == 0) mbar_arrive(BAR(BR_KS) + 8 * it);
          if (it == 4 && w4 == 0) {
            mbar_wait(BAR(BR_U), 0);
            if (elect_one()) {
              mbar_expect_tx(BAR(BR_U2), 8192);
              bulk_ld(blk - BLK, g_uy + (c * 80 + r * 5 + 3) * 2048, 4096, BAR(BR_U2)); bulk_ld(blk, g_uy + (c * 80 + r * 5 + 4) * 2048, 4096, BAR(BR_U2));
            }
            __syncwarp();
          }
        #pragma unroll
        for (int n = 0; n < 3; n++) {
          uint32_t o[2]; lds64(o, xr_ + n * BLK);
          kk[2 * n] = (kk[2 * n] + __uint_as_float(o[0])) * __uint_as_float(fd[0]); kk[2 * n + 1] = (kk[2 * n + 1] + __uint_as_float(o[1])) * __uint_as_float(fd[0]);
        }
        if (t7 == 0) kk[0] += __uint_as_float(fd[1]);
        {
          const uint32_t v = pack2(kk[1], kk[0]), vh = v >> 16;
          const uint32_t u = pack2(kk[2], kk[3]), w = pack2(kk[4], kk[5]), uu = pack2(kk[2], kk[2]), us = pack2(kk[3], kk[2]);
          const uint32_t x = tq < 2 ? w : u, xh = x >> 16;
          sts32(blk + e0 + 4, v); sts16(blk + e0, vh); sts16(blk + e0 + 10, v);
          sts16(blk + e1, x); sts16(blk + e1 + 6, x); sts16(blk + e2, xh); sts16(blk + e2 + 6, xh);
          if (tq < 2) {
            const uint32_t pb = blk + e0 + 1024 + 8 * tq;
            sts32(pb + 4, uu); sts32(pb + 8, us); sts16(pb + 14, us);
            if (i2) { sts16(pb - 4, u); sts32(pb, uu); }
          }
          if (i2 == 0) {
            const uint32_t tb = blk + B_TBL;
            if (tq == 0) { sts16(tb + (16 + 256) * 4, u); sts16(tb + (T_S + 3) * 4, w); sts32(tb + (T_S + 4) * 4, pack2(kk[4], kk[4])); sts16(tb + (T_S + 5) * 4 + 2, w); }
            else { sts32(tb + 528 * 4, uu); sts32(tb + 529 * 4, uu); sts32(tb + 530 * 4, uu); sts16(tb + 531 * 4 + 2, u); sts16(tb + (T_F3 + 80 + 63) * 4, w); }
          }
        }
        if (t7 == 0) TS(49 + it);
      }
    }
    if (!EN_SSM) bar_sync(0, 512);
    if (tid == 0) TS(14);
  if (wg < 2) {
    if (EN_ATT) {
    float am[96], ar[24];
    {
      const bool lead = (rtid() & 127) == 0;
      constexpr uint64_t da0 = mkdesc(SB0 + OFF_X, 16, 1024, 1), dr0 = mkdesc(SB0 + 12288, 1024, 256, 3);
      const uint64_t db0 = sw64 ? mkdesc(SB0, 2048, 512, 2) : mkdesc(SB0, 4096, 1024, 1);
      const uint32_t kst = sw64 ? 64 : 128, bh = db0 >> 32;
      uint32_t s = 0, ph = 0, xo = 0;
      #pragma unroll 1
      for (int kb = 0; kb < 20; kb++) {
        const uint32_t wo_ = s * (W_SLOT >> 4), al = (uint32_t)da0 + wg * 512 + xo, bl = (uint32_t)db0 + wo_, rl = (uint32_t)dr0 + wo_;
        mbar_wait(BAR(BR_FULL) + 8 * s, ph);
        if (kb == 0 && lead && wg == 0) TS(1);
        wg_fence();
        wg_ss192_tb(am, desc2(al, da0 >> 32), desc2(bl, bh), kb != 0);
        wg_ss48_tb(ar, desc2(al, da0 >> 32), desc2(rl, dr0 >> 32), kb != 0);
        wg_ss192_tb(am, desc2(al + 2, da0 >> 32), desc2(bl + kst, bh), 1);
        wg_ss48_tb(ar, desc2(al + 2, da0 >> 32), desc2(rl + 32, dr0 >> 32), 1);
        wg_commit();
        wg_wait<1>();
        if (lead && kb > 0 && kb < 16) mbar_arrive(BAR(BR_EMPTY) + 8 * (s == 0 ? 4 : s - 1));
        if (++s == 5) { s = 0; ph ^= 1; }
        xo += (kb & 1) ? 1020 : 4;
        if (xo == 3072) xo = 0;
      }
      wg_wait<0>();
      pin<96>(am); pin<24>(ar);
    }
    const int tid = rtid(), lane = tid & 31, tq = lane & 3;
    if (tid == 0) TS(2);
#define QV(j, e) ((j) < 8 ? am[4 * (j) + (e)] : ar[4 * ((j) - 8) + (e)])
#define KV_(j, e) ((j) < 8 ? am[32 + 4 * (j) + (e)] : ar[8 + 4 * ((j) - 8) + (e)])
#define VV(j, e) ((j) < 8 ? am[64 + 4 * (j) + (e)] : ar[16 + 4 * ((j) - 8) + (e)])
    {
      bar_sync(1, 256);
      if (tid == 0) mbar_arrive(BAR(BR_GEMM));
      const uint32_t ro = sb + (uint32_t)((warp * 16 + (lane & 15)) * 16);
      const int l0 = 2 * (c & 1) + (lane >> 4);
      const uint32_t ones = (tq == 0) ? 0x00003f80u : 0u;
#define PV(j) pack2(VV(j, 0), VV(j, 1)), pack2(VV(j, 2), VV(j, 3))
#define PK(j) pack2(phi(KV_(j, 0)), phi(KV_(j, 1))), pack2(phi(KV_(j, 2)), phi(KV_(j, 3)))
      stsm4(ro + OFF_V + (5 + 6 * (lane >> 4)) * 2048, ones, ones, ones, ones);
      #pragma unroll
      for (int j = 0; j < 10; j += 2) {
        const int l = (j == 8 && (c & 1)) ? l0 - 2 : l0 + j;
        stsm4(ro + OFF_V + (l + (l >= 5)) * 2048, PV(j), PV(j + 1));
        stsm4(ro + OFF_PK + l * 2048, PK(j), PK(j + 1));
      }
    }
    fence_async();
    bar_sync(1, 256);
    if (tid == 0) TS(3);
    mbar_wait(BAR(BR_EPOCH), 0);
    const unsigned epoch = lds32(sb + OFF_EPOCH);
    {
      float kv[24]; zero<24>(kv);
      constexpr uint64_t da = mkdesc(SB0 + OFF_PK, 128, 2048, 0), db = mkdesc(SB0 + OFF_V, 128, 2048, 0);
      wg_fence();
      #pragma unroll
      for (int s = 0; s < 8; s++) wg_ss48_tt(kv, desc2((uint32_t)da + wg * 640 + s * 16, da >> 32), desc2((uint32_t)db + wg * 768 + s * 16, db >> 32), s != 0);
      wg_commit();
      wg_wait<0>();
      pin<24>(kv);
      if (tid == 0) TS(15);
      if (w4 < 3) {
        const uint32_t wb = sb + OFF_KVS + (wg * 3 + w4) * 1536 + (lane & 15) * 96;
        #pragma unroll
        for (int j = 0; j < 6; j += 2)
          stsm4(wb + (j + (lane >> 4)) * 16, pack2(kv[4 * j], kv[4 * j + 1]), pack2(kv[4 * j + 2], kv[4 * j + 3]),
                pack2(kv[4 * j + 4], kv[4 * j + 5]), pack2(kv[4 * j + 6], kv[4 * j + 7]));
        __syncwarp();
        const int dl = w4 * 16 + (lane & 15), hl = dl >= 20;
        if (dl < 40) {
          uint4* dst = &g_kvp[(c * 16 + r) * 240 + wg * 40 + dl];
          uint32_t v[4], z[4];
          lds128(v, wb + (3 * hl + (lane >> 4)) * 16);
          lds64(z, wb + 32 + 8 * hl); z[2] = lds32(wb + 80); z[3] = epoch & 1u;
          v[3] = (v[3] & ~1u) | z[3];
          st128_rlx(dst + (lane >> 4) * 80, v);
          if (lane < 16) st128_rlx(dst + 160, z);
        }
      }
    }
    fence_async();
    bar_sync(1, 256);
    if (tid == 0) { st_rlx(FLAG(0, r, c), epoch); mbar_arrive(BAR(BR_PUB)); TS(4); }
    const int kvi = (tid >= 80) + (tid >= 160) + (tid >= 240), kd = tid - 80 * kvi;
    const int khd = kd / 20, kt0 = 5 * (khd >> 1) + 2 * (khd & 1);
    const uint32_t rb = sb + OFF_KVB + kd * 16;
    if (kvi < 3) {
      #pragma unroll 1
      for (int m = kvi; m < 7; m += 3) { const int q = kt0 + 3 + m; sts128(rb + (q >= 10 ? q - 10 : q) * 1280, 0, 0, 0, 0); }
    }
    uint32_t qa[20];
    {
      const float sc = 1.44269504089f + __uint_as_float(lds32(sb + OFF_EPOCH) ^ epoch);
      #pragma unroll
      for (int j = 0; j < 10; j++) { qa[2 * j] = pack2(phi(QV(j, 0), sc), phi(QV(j, 1), sc)); qa[2 * j + 1] = pack2(phi(QV(j, 2), sc), phi(QV(j, 3), sc)); }
    }
    if (tid == 0) TS(5);
    if (warp == 7) mbar_wait(BAR(BR_KVP), 0);
    bar_sync(1, 256);
    if (tid == 0) TS(6);
    if (kvi < 3) {
      float s[8];
      zero<8>(s);
      uint32_t bad = 0;
      #pragma unroll 4
      for (int i = 0; i < 16; i++) {
        uint32_t w[4];
        lds128(w, sb + OFF_KVP + tid * 16 + i * 3840);
        bad |= w[3] ^ epoch;
        #pragma unroll
        for (int e = 0; e < 4; e++) { s[2 * e] += bf_lo(w[e]); s[2 * e + 1] += bf_hi(w[e]); }
      }
      if (__builtin_expect(bad & 1u, 0)) {
        zero<8>(s);
        #pragma unroll 1
        for (int i = 0; i < 16; i++) {
          uint32_t w[4] = {0, 0, 0, ~epoch};
          fix128_w3(w, &g_kvp[(c * 16 + i) * 240 + tid], epoch, 1u);
          #pragma unroll
          for (int e = 0; e < 4; e++) { s[2 * e] += bf_lo(w[e]); s[2 * e + 1] += bf_hi(w[e]); }
        }
        FIXCNT
      }
      const uint32_t p0 = pack2(s[0], s[1]), p1 = pack2(s[2], s[3]), p2 = pack2(s[4], s[5]), p3 = pack2(s[6], s[7]);
      if (kvi < 2) sts128(rb + (kt0 + (khd & 1) + kvi) * 1280, p0, p1, p2, p3);
      else {
        const bool od = khd & 1;
        sts128(rb + (5 * (khd >> 1) + 2) * 1280, od ? 0u : p0, od ? 0u : p1, od ? p0 : 0u, od ? p1 : 0u);
        const uint32_t zz = (p2 & 0xffffu) << (16 * (khd & 1));
        sts128(rb + 10 * 1280, khd < 2 ? zz : 0u, khd < 2 ? 0u : zz, 0u, 0u);
      }
    }
    fence_async();
    bar_sync(1, 256);
    if (tid == 0) { mbar_arrive(BAR(BR_SUM)); TS(7); }
    {
      float oa[44]; zero<44>(oa);
      constexpr uint64_t db = mkdesc(SB0 + OFF_KVB, 128, 1280, 0);
      wg_fence();
      #pragma unroll
      for (int s = 0; s < 5; s++) wg_rs88_tb(oa, &qa[4 * s], desc2((uint32_t)db + ((s == 4 && (c & 1)) ? 0 : (s + (c & 1)) * 16), db >> 32), s != 0);
      wg_commit();
      wg_wait<0>();
      pin<44>(oa);
      if (tid == 0) TS(13);
      float rc[4], rd[2][4];
      #pragma unroll
      for (int e = 0; e < 4; e++) asm("rcp.approx.ftz.f32 %0, %1;" : "=f"(rc[e]) : "f"(oa[40 + e] + 1e-6f));
      #pragma unroll
      for (int h = 0; h < 4; h++) {
        rd[0][h] = __shfl_sync(0xffffffff, rc[h & 1], (lane & 28) | (h >> 1));
        rd[1][h] = __shfl_sync(0xffffffff, rc[2 + (h & 1)], (lane & 28) | (h >> 1));
      }
      #pragma unroll
      for (int j = 0; j < 10; j++) {
        #pragma unroll
        for (int h = 0; h < 2; h++) {
          float f;
          if (j == 2) f = tq < 2 ? rd[h][0] : rd[h][1];
          else if (j == 7) f = tq < 2 ? rd[h][2] : rd[h][3];
          else f = rd[h][(8 * j) / 20];
          qa[2 * j + h] = pack2(oa[4 * j + 2 * h] * f, oa[4 * j + 2 * h + 1] * f);
        }
      }
      const uint32_t m0 = (lane & 7) == ((2 * w4) & 7), m1 = (lane & 7) == 2 * w4 + 1;
      const uint32_t oa_ = sb + OFF_EXTRA + (lane >> 4) * 2048 + (warp * 16 + (lane & 15)) * 16;
      bar_sync(1, 256);
#define TAG(v, m) (((v) & ~(m)) | (epoch & (m)))
      #pragma unroll
      for (int s = 0; s < 5; s++) stsm4(oa_ + s * 4096, TAG(qa[4 * s], m0), TAG(qa[4 * s + 1], m1), TAG(qa[4 * s + 2], m0), TAG(qa[4 * s + 3], m1));
    }
    fence_async();
    __syncwarp();
    if (lane == 0) mbar_arrive(BAR(BR_OSTG));
    if (tid == 0) TS(8);
    float oc[40]; zero<40>(oc);
    {
      constexpr uint64_t dw0 = mkdesc(SB0, OFF_WOR, 1024, 1), da0 = mkdesc(SB0, 2048, 128, 0);
      const uint32_t ck = sb + tid * 32 + ((lane >> 2) << 2), ck2 = ck + (wg ? 0 : 16384);
      uint32_t bad = 0;
      auto tile = [&](int i, uint32_t so) {
        const uint32_t al = (uint32_t)da0 + wg * 64 + (so >> 4), wl = (uint32_t)dw0 + i * 640 - (i >> 1) * (1278 << 16);
        wg_fence();
        #pragma unroll
        for (int s = 0; s < 5; s++) wg_ss80_tb(oc, desc2(al + s * 256, da0 >> 32), desc2(wl + s * 128, dw0 >> 32), (i | s) != 0);
        wg_commit();
        bad |= (lds32(ck + so) ^ epoch) | (lds32(ck + so + 8192) ^ epoch) | (lds32(ck2 + so) ^ epoch);
      };
      mbar_wait(BAR(BR_WO), 0);
      mbar_wait(BAR(BR_OSTG), 0);
      tile(0, SLOT(0));
      mbar_wait(BAR(BR_WO + 1), 0);
      #pragma unroll 1
      for (int i = 1; i < 8; i++) {
        if (i == 1) {
          wg_wait<0>();
          if (lane == 0) mbar_arrive(BAR(BR_OEMPTY));
          if (EN_SSM && w4 == 0) mbar_wait(BAR(BR_Y + 1), 0);
          if (w4 == 0) mbar_wait(BAR(BR_OFULL + 1), 0);
          bar_sync(2 + wg, 128);
        }
        mbar_wait(BAR(BR_OFULL) + 8 * i, 0);
        if (i == 1 && tid == 0) TS(9);
        tile(i, SLOT(i));
        wg_wait<1>();
        if (lane == 0 && i > 1) mbar_arrive(BAR(BR_OEMPTY - 1) + 8 * i);
      }
      #pragma unroll 1
      for (int n = 0; n < 56; n++) {
        const int i = n & 7;
        if (i == 0) {
          uint32_t any;
          asm volatile("{\n.reg .pred p;\nsetp.ne.u32 p, %1, 0;\nbarrier.red.or.pred p, 1, 256, p;\nselp.u32 %0, 1, 0, p;\n}" : "=r"(any) : "r"(bad & 1u) : "memory");
          if (!any) break;
          bad = 0;
          FIXCNT
        }
        wg_wait<0>();
        bar_sync(1, 256);
        if (tid == 0) { mbar_expect_tx(BAR(BR_RETRY), 20480); bulk_ld(sb + SLOT(6), &g_o[(r * 8 + CHUNK(i)) * 1280], 20480, BAR(BR_RETRY)); }
        mbar_wait(BAR(BR_RETRY), n & 1);
        tile(i, SLOT(6));
      }
      wg_wait<0>();
      pin<40>(oc);
    }
    if (tid == 0) TS(10);
    {
      const int row = w4 * 16 + (lane & 15);
      const uint32_t ob = sb + OFF_BLK + 2 * BLK + wg * 10240;
      #pragma unroll
      for (int j = 0; j < 8; j += 2)
        stsm4(ob + row * 128 + (((j + (lane >> 4)) ^ (row & 7)) << 4), pack2(oc[4 * j], oc[4 * j + 1]), pack2(oc[4 * j + 2], oc[4 * j + 3]),
              pack2(oc[4 * j + 4], oc[4 * j + 5]), pack2(oc[4 * j + 6], oc[4 * j + 7]));
      stsm4(ob + 8192 + row * 32 + (lane >> 4) * 16, pack2(oc[32], oc[33]), pack2(oc[34], oc[35]), pack2(oc[36], oc[37]), pack2(oc[38], oc[39]));
      fence_async();
      bar_sync(2 + wg, 128);
      if (w4 == 0 && elect_one()) {
        tma2d_st(&prm.m[M_O64], ob, 640 + c * 64, r * 128 + wg * 64);
        tma2d_st(&prm.m[M_O16], ob + 8192, 1152 + c * 16, r * 128 + wg * 64);
        bulk_commit(); bulk_wait0_read();
        if (wg == 0) { TS(11); DUMP(0, 20); }
      }
    }
    }
  } else {
    if (EN_SSM) {
    const int tid = rtid(), lane = tid & 31, g = lane >> 2, tq = lane & 3, t7 = tid & 127;
    if (t7 == 0) TS(41);
    mbar_wait(BAR(BR_U), 0);
    bar_sync(4, 128);
    if (EN_ATT) mbar_wait(BAR(BR_GEMM), 0);
    if (t7 == 0) TS(42);
    mbar_wait(BAR(BR_EPOCH), 0);
    const uint32_t ytag = (lds32(sb + OFF_EPOCH) & 1u) * 0x10001u, ym = lane < 4 ? 0x10001u : 0u;
    #pragma unroll 1
    for (int pass = 1; pass >= 0; pass--) {
      const int k = pass ? w4 : 4;
      if (k >= 3) mbar_wait(BAR(BR_U2), 0);
      const uint32_t blk = sb + OFF_BLK + k * BLK, tb = blk + B_TBL + (uint32_t)((g - 2 * tq) * 4);
      float acc[16][4];
      zero<64>(&acc[0][0]);
      const int kl = 16 * (lane >> 4) + 2 * (lane & 7) + ((lane >> 3) & 1);
      {
        auto ubase = [&](int sh) { const int q = kl - 2 * sh; return blk + (uint32_t)((q * 16) ^ ((q * 2) & 0x10)); };
#define LDQ(A, sh) _Pragma("unroll") for (int m = 0; m < 4; m++) load_quad(A[m], tb + (16 + 16 * (sh) + 128 * m) * 4);
#define LDB(B, ub, h) _Pragma("unroll") for (int p = 0; p < 4; p++) ldsm4(B[p], (ub) + (4 * (h) + p) * 512);
#define MLO(A, B) _Pragma("unroll") for (int m = 0; m < 4; m++) _Pragma("unroll") for (int cc = 0; cc < 8; cc++) mma16816(acc[cc + m], A[m], &B[cc >> 1][(cc & 1) * 2]);
#define MHI(A, B) _Pragma("unroll") for (int m = 0; m < 4; m++) _Pragma("unroll") for (int cc = 0; cc < 8 - m; cc++) mma16816(acc[8 + cc + m], A[m], &B[cc >> 1][(cc & 1) * 2]);
        int p_ = pass ? 0 : w4;
        const int pe = pass ? 4 : w4 + 1;
        uint32_t A[4][4], A2[4][4], Bl[4][4], Bh[4][4];
        uint32_t ub = ubase(p_ + 4);
        LDQ(A, p_ + 4) LDB(Bl, ub, 0)
        #pragma unroll 1
        for (; p_ < pe; p_++) {
          LDB(Bh, ub, 1)
          MLO(A, Bl)
          ub = ubase(p_);
          LDQ(A2, p_) LDB(Bl, ub, 0)
          MHI(A, Bh)
          LDB(Bh, ub, 1)
          load_quad(A[0], tb + (16 + 512 + 16 * (p_ & 1)) * 4); load_quad(A[1], tb + (T_S + 16 * (p_ & 1)) * 4);
          MLO(A2, Bl)
          if (p_ < 2) {
            #pragma unroll
            for (int cc = 0; cc < 8; cc++) mma16816(acc[cc + 4], A[0], &Bl[cc >> 1][(cc & 1) * 2]);
            #pragma unroll
            for (int cc = 0; cc < 4; cc++) mma16816(acc[cc + 12], A[0], &Bh[cc >> 1][(cc & 1) * 2]);
            #pragma unroll
            for (int cc = 0; cc < 8; cc++) mma16816(acc[cc + 8], A[1], &Bl[cc >> 1][(cc & 1) * 2]);
          }
          const int pn = ((p_ + 1) & 3) + 4;
          ub = ubase(pn);
          LDQ(A, pn) LDB(Bl, ub, 0)
          MHI(A2, Bh)
        }
      }
      if (t7 == 0) TS(57 + 3 * pass);
      mbar_wait(BAR(BR_DRDY + 1) - 8 * pass, 0);
      {
        const int ih = (lane >> 3) & 1;
        const uint32_t dl = blk + B_D + (uint32_t)(((lane >> 4) * 8 + (lane & 7)) * 16);
        const uint32_t d0_ = dl + ih * 1552, d8_ = dl + (ih ? 0 : 1536), d3_ = dl + B_D7 + ih * 1024;
        auto cls2 = [&](uint32_t da, uint32_t ta) {
          uint32_t B[6][2], A[6][4];
          #pragma unroll
          for (int e = 0; e < 6; e++) { B[e][0] = lds32v(ta + (e + 4) * 32); B[e][1] = lds32v(ta + (e + 3) * 32); }
          #pragma unroll
          for (int kk = 0; kk < 6; kk++) ldsm4t(A[kk], da + kk * 256);
          #pragma unroll
          for (int e = 0; e < 6; e++)
            #pragma unroll
            for (int kk = 0; kk < 6; kk++) if (2 * kk + e + 4 < 16) mma16816(acc[2 * kk + e + 4], A[kk], B[e]);
        };
        auto cls3 = [&](uint32_t da, uint32_t ta) {
          uint32_t B[8][2], A[4][4];
          #pragma unroll
          for (int e = 0; e < 8; e++) { B[e][0] = lds32v(ta + (e + 8) * 32); B[e][1] = lds32v(ta + (e + 7) * 32); }
          #pragma unroll
          for (int kk = 0; kk < 4; kk++) ldsm4t(A[kk], da + kk * 256);
          #pragma unroll
          for (int kk = 0; kk < 4; kk++)
            #pragma unroll
            for (int e = 0; e < 8; e++) if (2 * kk + e + 8 < 16) mma16816(acc[2 * kk + e + 8], A[kk], B[e]);
        };
        if (pass) {
          #pragma unroll 1
          for (int a = 0; a < 2; a++) {
            cls2(d0_ + a * B_D5, tb + (T_F2 + 48 * a - 32) * 4);
            cls2(d8_ + a * B_D5, tb + (T_F2 + 48 * a + 64) * 4);
            cls3(d3_ + a * 2048, tb + (T_F3 + 80 * a - 64) * 4);
          }
        } else {
          cls2(((w4 & 2) ? d8_ : d0_) + (w4 & 1) * B_D5, tb + (T_F2 + 48 * w4 - 32) * 4);
          if (w4 >= 2) cls3(d3_ + (w4 - 2) * 2048, tb + (T_F3 + 80 * (w4 - 2) - 64) * 4);
        }
      }
      if (t7 == 0) TS(58 + 3 * pass);
      const uint32_t ya = blk + (uint32_t)((kl * 16) ^ ((kl * 2) & 0x10));
#define YTAG(v) (((v) & ~ym) | (ytag & ym))
#define STY(p) stsm4t(ya + (p) * 512, YTAG(pack2(acc[2 * (p)][0], acc[2 * (p)][1])), pack2(acc[2 * (p)][2], acc[2 * (p)][3]), \
                      YTAG(pack2(acc[2 * (p) + 1][0], acc[2 * (p) + 1][1])), pack2(acc[2 * (p) + 1][2], acc[2 * (p) + 1][3]))
      if (pass == 0) {
        const uint32_t xw = blk + 4096 + w4 * 4096 + lane * 16, xr = blk + 4096 + w4 * 1024 + lane * 16;
        #pragma unroll
        for (int h = 0; h < 2; h++) {
          bar_sync(4, 128);
          #pragma unroll
          for (int i = 0; i < 8; i++)
            sts128(xw + i * 512, __float_as_uint(acc[8 * h + i][0]), __float_as_uint(acc[8 * h + i][1]), __float_as_uint(acc[8 * h + i][2]), __float_as_uint(acc[8 * h + i][3]));
          bar_sync(4, 128);
          float y[8];
          #pragma unroll
          for (int i = 0; i < 8; i++) {
            uint32_t o[4]; lds128(o, xr + (i >> 1) * 4096 + (i & 1) * 512);
            #pragma unroll
            for (int e = 0; e < 4; e++) y[4 * (i & 1) + e] = i < 2 ? __uint_as_float(o[e]) : y[4 * (i & 1) + e] + __uint_as_float(o[e]);
          }
          stsm4t(ya + (4 * h + w4) * 512, YTAG(pack2(y[0], y[1])), pack2(y[2], y[3]), YTAG(pack2(y[4], y[5])), pack2(y[6], y[7]));
        }
      } else {
        __syncwarp();
        #pragma unroll
        for (int p = 0; p < 8; p++) STY(p);
      }
      if (t7 == 0 && !pass) TS(55);
      fence_async();
      __syncwarp();
      if (lane == 0) mbar_arrive(BAR(BR_Y + 1) - 8 * pass);
      if (t7 == 0) TS(59 + 3 * pass);
    }
    if (t7 == 0) DUMP(40, 64);
    #pragma unroll 1
    for (int n = 0; n < 64; n++) if (!y_transpose(sb, w4, lane, ytag)) break;
    }
  }
  }
}

typedef CUresult (*EncFn)(CUtensorMap*, CUtensorMapDataType, cuuint32_t, void*, const cuuint64_t*, const cuuint64_t*, const cuuint32_t*,
                          const cuuint32_t*, CUtensorMapInterleave, CUtensorMapSwizzle, CUtensorMapL2promotion, CUtensorMapFloatOOBfill);
static void mkmap(EncFn enc, CUtensorMap* m, const void* base, int rank, const cuuint64_t* dims, const cuuint64_t* strides, const cuuint32_t* box, CUtensorMapSwizzle swz) {
  cuuint32_t es[5] = {1, 1, 1, 1, 1};
  enc(m, CU_TENSOR_MAP_DATA_TYPE_BFLOAT16, rank, const_cast<void*>(base), dims, strides, box, es, CU_TENSOR_MAP_INTERLEAVE_NONE, swz,
      CU_TENSOR_MAP_L2_PROMOTION_L2_128B, CU_TENSOR_MAP_FLOAT_OOB_FILL_NONE);
}

extern "C" void kernel_launch(void* const* d_in, const int* in_sizes, int n_in, void* d_out, int out_size) {
  void* fn = nullptr; cudaDriverEntryPointQueryResult qr;
  cudaGetDriverEntryPoint("cuTensorMapEncodeTiled", &fn, cudaEnableDefault, &qr);
  EncFn enc = (EncFn)fn;
  void* uy = nullptr; cudaGetSymbolAddress(&uy, g_uy);
  const cuuint64_t dx[2] = {640, 2048}, sx[1] = {1280};
  const cuuint32_t bx[2] = {64, 128}, bu[2] = {80, 128};
  const cuuint64_t dw[3] = {640, 640, 3}, sw[2] = {3840, 1280};
  const cuuint32_t br[3] = {16, 32, 3};
  const cuuint64_t dwa[4] = {64, 640, 10, 3}, swa[3] = {3840, 128, 1280}, dwb[4] = {32, 640, 20, 3}, swb[3] = {3840, 64, 1280};
  const cuuint32_t bwa[4] = {64, 32, 1, 3}, bwb[4] = {32, 32, 2, 3};
  const cuuint64_t dwo[2] = {640, 640};
  const cuuint32_t bwo[2] = {64, 80}, bo64[2] = {64, 64}, bo16[2] = {16, 64};
  const cuuint64_t dsa[2] = {2048, 1280}, ssa[1] = {4096};
  const cuuint32_t bsa[2] = {64, 80};
  const cuuint64_t dout[2] = {1280, 2048}, sout[1] = {2560};
  Params prm;
  mkmap(enc, &prm.m[M_X], d_in[7], 2, dx, sx, bx, CU_TENSOR_MAP_SWIZZLE_128B);
  mkmap(enc, &prm.m[M_W128], d_in[8], 4, dwa, swa, bwa, CU_TENSOR_MAP_SWIZZLE_128B);
  mkmap(enc, &prm.m[M_W64], d_in[8], 4, dwb, swb, bwb, CU_TENSOR_MAP_SWIZZLE_64B);
  mkmap(enc, &prm.m[M_WR], d_in[8], 3, dw, sw, br, CU_TENSOR_MAP_SWIZZLE_32B);
  mkmap(enc, &prm.m[M_U], d_in[0], 2, dx, sx, bu, CU_TENSOR_MAP_SWIZZLE_NONE);
  mkmap(enc, &prm.m[M_WO], d_in[9], 2, dwo, sx, bwo, CU_TENSOR_MAP_SWIZZLE_128B);
  mkmap(enc, &prm.m[M_O64], d_out, 2, dout, sout, bo64, CU_TENSOR_MAP_SWIZZLE_128B);
  mkmap(enc, &prm.m[M_O16], d_out, 2, dout, sout, bo16, CU_TENSOR_MAP_SWIZZLE_NONE);
  mkmap(enc, &prm.m[M_SA], uy, 2, dsa, ssa, bsa, CU_TENSOR_MAP_SWIZZLE_128B);
  mkmap(enc, &prm.m[M_OUT], d_out, 2, dout, sout, bu, CU_TENSOR_MAP_SWIZZLE_NONE);
  prm.u = (const __nv_bfloat16*)d_in[0]; prm.wo = (const __nv_bfloat16*)d_in[9];
  for (int i = 0; i < 4; i++) prm.par[i] = (const __nv_bfloat16*)d_in[1 + i];
  prm.logdt = (const __nv_bfloat16*)d_in[5]; prm.dskip = (const __nv_bfloat16*)d_in[6];
  cudaFuncSetAttribute(fused_kernel, cudaFuncAttributeMaxDynamicSharedMemorySize, SMEM_BYTES);
  cudaLaunchConfig_t cfg = {};
  cfg.gridDim = dim3(128); cfg.blockDim = dim3(512); cfg.dynamicSmemBytes = SMEM_BYTES; cfg.stream = cudaStreamPerThread;
  cudaLaunchAttribute at[1];
  at[0].id = cudaLaunchAttributeClusterDimension; at[0].val.clusterDim.x = 2; at[0].val.clusterDim.y = 1; at[0].val.clusterDim.z = 1;
  cfg.attrs = at; cfg.numAttrs = 1;
  cudaLaunchKernelEx(&cfg, fused_kernel, prm);
}
```

```cpp
#include <cuda_runtime.h>
#include <cuda_bf16.h>
#include <cuda_fp16.h>
#include <cuda.h>
#include <stdint.h>

#define KST 2
#define EN_ATT 1
#define EN_SSM 1

__device__ __align__(1024) __nv_bfloat16 g_uy[2 * 640 * 2048];
__device__ __align__(128) uint4 g_kvp[8 * 16 * 240];
__device__ __align__(128) uint4 g_o[128 * 1280];
__device__ __align__(128) unsigned g_flag[4 * 128 * 32];
__device__ unsigned g_epoch[128];
#define TS(i) do {} while (0)
#define DUMP(lo, hi) do {} while (0)
#define FIXCNT

constexpr uint32_t SB0 = 1024;
constexpr uint32_t W_SLOT = 15360, OFF_X = 76800;
constexpr uint32_t OFF_WOR = 81920, OFF_KVP = 10240, OFF_KVS = 71680, OFF_PK = 10240, OFF_V = 30720, OFF_EXTRA = 102400, OFF_KVB = OFF_EXTRA;
constexpr uint32_t OFF_BAR = 125952, OFF_BLK = 128000, BLK = 20480;
constexpr uint32_t B_D = 4096, B_D5 = 3088, B_D7 = 6176, B_D9 = 8224, B_TBL = 14400;
constexpr int T_S = 576, T_F2 = 624, T_F3 = 816;
constexpr uint32_t OFF_UT = OFF_BLK + 4 * BLK;
constexpr uint32_t SMEM_BYTES = OFF_BLK + 5 * BLK;
enum { BR_FULL = 0, BR_WO = 5, BR_PUB = 7, BR_KVP = 8, BR_U = 9, BR_SUM = 10, BR_GEMM = 11, BR_UIN = 12, BR_YIN = 13, BR_EPOCH = 14,
       BR_FREE = 15, BR_RETRY = 17, BR_UOUT = 18, BR_OFULL = 18, BR_KS = 26, BR_EMPTY = 31, BR_OEMPTY = 36, BR_Y = 43, BR_OSTG = 45,
       BR_DRDY = 46, BR_U2 = 48, BR_COUNT = 50 };
constexpr uint32_t OFF_EPOCH = OFF_BAR + 8 * BR_COUNT;
enum { M_X, M_W128, M_W64, M_WR, M_U, M_WO, M_O64, M_O16, M_SA, M_OUT, M_COUNT };

__device__ __forceinline__ long long clk64() { long long t; asm volatile("mov.u64 %0, %%clock64;" : "=l"(t) :: "memory"); return t; }
__device__ __forceinline__ uint32_t smem_u32(const void* p) { return (uint32_t)__cvta_generic_to_shared(p); }
__host__ __device__ constexpr uint64_t mkdesc(uint32_t addr, uint32_t lbo, uint32_t sbo, uint32_t swz) {
  return (uint64_t)((addr & 0x3FFFF) >> 4) | ((uint64_t)(lbo >> 4) << 16) | ((uint64_t)(sbo >> 4) << 32) | ((uint64_t)swz << 62);
}
__device__ __forceinline__ uint64_t desc2(uint32_t lo, uint32_t hi) { uint64_t d; asm("mov.b64 %0, {%1, %2};" : "=l"(d) : "r"(lo), "r"(hi)); return d; }
__device__ __forceinline__ void mbar_init(uint32_t bar, uint32_t cnt) { asm volatile("mbarrier.init.shared::cta.b64 [%0], %1;" :: "r"(bar), "r"(cnt) : "memory"); }
__device__ __forceinline__ void mbar_expect_tx(uint32_t bar, uint32_t bytes) { asm volatile("mbarrier.arrive.expect_tx.shared::cta.b64 _, [%0], %1;" :: "r"(bar), "r"(bytes) : "memory"); }
__device__ __forceinline__ void mbar_arrive(uint32_t bar) { asm volatile("mbarrier.arrive.shared::cta.b64 _, [%0];" :: "r"(bar) : "memory"); }
__device__ __forceinline__ void mbar_wait(uint32_t bar, uint32_t parity) {
  asm volatile("{\n.reg .pred p;\n.reg .u32 c;\nmov.u32 c, 0;\n"
    "WL:\nmbarrier.try_wait.parity.shared::cta.b64 p, [%0], %1;\n@p bra WD;\n"
    "add.u32 c, c, 1;\nsetp.lt.u32 p, c, 200000;\n@p bra WL;\nWD:\n}" :: "r"(bar), "r"(parity) : "memory");
}
__device__ __forceinline__ void poll_all(const unsigned* p, unsigned val) {
  asm volatile("{\n.reg .pred p;\n.reg .u32 c, v;\nmov.u32 c, 0;\n"
    "PL:\nld.relaxed.gpu.global.u32 v, [%0];\nsetp.eq.u32 p, v, %1;\nvote.sync.all.pred p, p, 0xffffffff;\n@p bra PD;\n"
    "add.u32 c, c, 1;\nsetp.lt.u32 p, c, 100000;\n@p bra PL;\nPD:\n}" :: "l"(p), "r"(val) : "memory");
}
__device__ __forceinline__ void poll_all_acq(const unsigned* p, unsigned val) {
  asm volatile("{\n.reg .pred p;\n.reg .u32 c, v;\nmov.u32 c, 0;\n"
    "PL:\nld.acquire.gpu.global.u32 v, [%0];\nsetp.eq.u32 p, v, %1;\nvote.sync.all.pred p, p, 0xffffffff;\n@p bra PD;\n"
    "add.u32 c, c, 1;\nsetp.lt.u32 p, c, 100000;\n@p bra PL;\nPD:\n}" :: "l"(p), "r"(val) : "memory");
}
__device__ __forceinline__ unsigned poll_bit(const unsigned* p, unsigned val, unsigned mask) {
  unsigned bal;
  asm volatile("{\n.reg .pred p;\n.reg .u32 c, v;\nmov.u32 c, 0;\n"
    "PL:\nld.relaxed.gpu.global.u32 v, [%1];\nsetp.eq.u32 p, v, %2;\nvote.sync.ballot.b32 %0, p, 0xffffffff;\n"
    "and.b32 v, %0, %3;\nsetp.ne.u32 p, v, 0;\n@p bra PD;\n"
    "add.u32 c, c, 1;\nsetp.lt.u32 p, c, 100000;\n@p bra PL;\nPD:\n}" : "=&r"(bal) : "l"(p), "r"(val), "r"(mask) : "memory");
  return bal;
}
__device__ __forceinline__ void fix128_w0(uint32_t* v, const void* p, uint32_t tag, uint32_t mask) {
  asm volatile("{\n.reg .pred p;\n.reg .u32 c, x;\n.reg .b128 t;\n.reg .b64 lo, hi;\nmov.u32 c, 0;\n"
    "FL:\nxor.b32 x, %0, %5;\nand.b32 x, x, %6;\nsetp.eq.u32 p, x, 0;\n@p bra FD;\n"
    "ld.relaxed.gpu.global.b128 t, [%4];\nmov.b128 {lo, hi}, t;\nmov.b64 {%0, %1}, lo;\nmov.b64 {%2, %3}, hi;\n"
    "add.u32 c, c, 1;\nsetp.lt.u32 p, c, 100000;\n@p bra FL;\nFD:\n}"
    : "+r"(v[0]), "+r"(v[1]), "+r"(v[2]), "+r"(v[3]) : "l"(p), "r"(tag), "r"(mask) : "memory");
}
__device__ __forceinline__ void fix128_w3(uint32_t* v, const void* p, uint32_t tag, uint32_t mask) {
  asm volatile("{\n.reg .pred p;\n.reg .u32 c, x;\n.reg .b128 t;\n.reg .b64 lo, hi;\nmov.u32 c, 0;\n"
    "FL:\nxor.b32 x, %3, %5;\nand.b32 x, x, %6;\nsetp.eq.u32 p, x, 0;\n@p bra FD;\n"
    "ld.relaxed.gpu.global.b128 t, [%4];\nmov.b128 {lo, hi}, t;\nmov.b64 {%0, %1}, lo;\nmov.b64 {%2, %3}, hi;\n"
    "add.u32 c, c, 1;\nsetp.lt.u32 p, c, 100000;\n@p bra FL;\nFD:\n}"
    : "+r"(v[0]), "+r"(v[1]), "+r"(v[2]), "+r"(v[3]) : "l"(p), "r"(tag), "r"(mask) : "memory");
}
__device__ __forceinline__ void fence_acq() { asm volatile("fence.acq_rel.gpu;" ::: "memory"); }
__device__ __forceinline__ bool elect_one() {
  uint32_t p; asm volatile("{\n.reg .pred P;\nelect.sync _|P, 0xffffffff;\nselp.u32 %0, 1, 0, P;\n}" : "=r"(p)); return p;
}
__device__ __forceinline__ void bar_sync(int id, int n) { asm volatile("bar.sync %0, %1;" :: "r"(id), "r"(n) : "memory"); }
__device__ __forceinline__ void fence_async() { asm volatile("fence.proxy.async.shared::cta;" ::: "memory"); }
__device__ __forceinline__ void fence_async_g() { asm volatile("fence.proxy.async.global;" ::: "memory"); }
__device__ __forceinline__ void tma2d(uint32_t dst, const CUtensorMap* m, uint32_t bar, int c0, int c1) {
  asm volatile("cp.async.bulk.tensor.2d.shared::cluster.global.mbarrier::complete_tx::bytes [%0], [%1, {%3, %4}], [%2];"
    :: "r"(dst), "l"(m), "r"(bar), "r"(c0), "r"(c1) : "memory");
}
__device__ __forceinline__ void tma3d(uint32_t dst, const CUtensorMap* m, uint32_t bar, int c0, int c1, int c2) {
  asm volatile("cp.async.bulk.tensor.3d.shared::cluster.global.mbarrier::complete_tx::bytes [%0], [%1, {%3, %4, %5}], [%2];"
    :: "r"(dst), "l"(m), "r"(bar), "r"(c0), "r"(c1), "r"(c2) : "memory");
}
__device__ __forceinline__ void tma4d(uint32_t dst, const CUtensorMap* m, uint32_t bar, int c0, int c1, int c2, int c3) {
  asm volatile("cp.async.bulk.tensor.4d.shared::cluster.global.mbarrier::complete_tx::bytes [%0], [%1, {%3, %4, %5, %6}], [%2];"
    :: "r"(dst), "l"(m), "r"(bar), "r"(c0), "r"(c1), "r"(c2), "r"(c3) : "memory");
}
__device__ __forceinline__ void tma2d_st(const CUtensorMap* m, uint32_t src, int c0, int c1) {
  asm volatile("cp.async.bulk.tensor.2d.global.shared::cta.bulk_group [%0, {%2, %3}], [%1];"
    :: "l"(m), "r"(src), "r"(c0), "r"(c1) : "memory");
}
__device__ __forceinline__ void bulk_ld(uint32_t dst, const void* src, uint32_t bytes, uint32_t bar) {
  asm volatile("cp.async.bulk.shared::cluster.global.mbarrier::complete_tx::bytes [%0], [%1], %2, [%3];"
    :: "r"(dst), "l"(src), "r"(bytes), "r"(bar) : "memory");
}
__device__ __forceinline__ void bulk_st(void* dst, uint32_t src, uint32_t bytes) {
  asm volatile("cp.async.bulk.global.shared::cta.bulk_group [%0], [%1], %2;" :: "l"(dst), "r"(src), "r"(bytes) : "memory");
}
__device__ __forceinline__ void bulk_commit() { asm volatile("cp.async.bulk.commit_group;" ::: "memory"); }
__device__ __forceinline__ void bulk_wait0() { asm volatile("cp.async.bulk.wait_group 0;" ::: "memory"); }
__device__ __forceinline__ void bulk_wait0_read() { asm volatile("cp.async.bulk.wait_group.read 0;" ::: "memory"); }
__device__ __forceinline__ unsigned ld_rlx(const unsigned* p) { unsigned v; asm volatile("ld.relaxed.gpu.global.u32 %0, [%1];" : "=r"(v) : "l"(p) : "memory"); return v; }
__device__ __forceinline__ unsigned ld_acq(const unsigned* p) { unsigned v; asm volatile("ld.acquire.gpu.global.u32 %0, [%1];" : "=r"(v) : "l"(p) : "memory"); return v; }
__device__ __forceinline__ void st_rlx(unsigned* p, unsigned v) { asm volatile("st.relaxed.gpu.global.u32 [%0], %1;" :: "l"(p), "r"(v) : "memory"); }
__device__ __forceinline__ void st_rel(unsigned* p, unsigned v) { asm volatile("st.release.gpu.global.u32 [%0], %1;" :: "l"(p), "r"(v) : "memory"); }
__device__ __forceinline__ void ld128_rlx(uint32_t* v, const void* p) {
  asm volatile("{\n.reg .b128 t;\n.reg .b64 lo, hi;\nld.relaxed.gpu.global.b128 t, [%4];\nmov.b128 {lo, hi}, t;\n"
    "mov.b64 {%0, %1}, lo;\nmov.b64 {%2, %3}, hi;\n}" : "=r"(v[0]), "=r"(v[1]), "=r"(v[2]), "=r"(v[3]) : "l"(p) : "memory");
}
__device__ __forceinline__ void st128_rlx(void* p, const uint32_t* v) {
  asm volatile("{\n.reg .b128 t;\n.reg .b64 lo, hi;\nmov.b64 lo, {%1, %2};\nmov.b64 hi, {%3, %4};\nmov.b128 t, {lo, hi};\n"
    "st.relaxed.gpu.global.b128 [%0], t;\n}" :: "l"(p), "r"(v[0]), "r"(v[1]), "r"(v[2]), "r"(v[3]) : "memory");
}
__device__ __forceinline__ uint32_t lds32(uint32_t a) { uint32_t v; asm volatile("ld.shared.u32 %0, [%1];" : "=r"(v) : "r"(a) : "memory"); return v; }
__device__ __forceinline__ uint32_t lds32v(uint32_t a) { uint32_t v; asm volatile("ld.volatile.shared.u32 %0, [%1];" : "=r"(v) : "r"(a) : "memory"); return v; }
__device__ __forceinline__ uint32_t cpa(uint32_t a, uint32_t one) { uint32_t v; asm volatile("mul.lo.u32 %0, %1, %2;" : "=r"(v) : "r"(a), "r"(one)); return v; }
__device__ __forceinline__ uint32_t cpb(uint32_t a, uint32_t zero) { uint32_t v; asm volatile("or.b32 %0, %1, %2;" : "=r"(v) : "r"(a), "r"(zero)); return v; }
__device__ __forceinline__ uint32_t lds16(uint32_t a) { uint16_t v; asm volatile("ld.shared.u16 %0, [%1];" : "=h"(v) : "r"(a) : "memory"); return v; }
__device__ __forceinline__ float ldsf(uint32_t a) { float v; asm volatile("ld.shared.f32 %0, [%1];" : "=f"(v) : "r"(a) : "memory"); return v; }
__device__ __forceinline__ void lds128(uint32_t* v, uint32_t a) { asm volatile("ld.shared.v4.u32 {%0,%1,%2,%3}, [%4];" : "=r"(v[0]), "=r"(v[1]), "=r"(v[2]), "=r"(v[3]) : "r"(a) : "memory"); }
__device__ __forceinline__ void sts32(uint32_t a, uint32_t v) { asm volatile("st.shared.u32 [%0], %1;" :: "r"(a), "r"(v) : "memory"); }
__device__ __forceinline__ void sts16(uint32_t a, uint32_t v) { asm volatile("st.shared.u16 [%0], %1;" :: "r"(a), "h"((uint16_t)v) : "memory"); }
__device__ __forceinline__ void sts64f(uint32_t a, float x, float y) { asm volatile("st.shared.v2.f32 [%0], {%1,%2};" :: "r"(a), "f"(x), "f"(y) : "memory"); }
__device__ __forceinline__ void sts128(uint32_t a, uint32_t x, uint32_t y, uint32_t z, uint32_t w) { asm volatile("st.shared.v4.u32 [%0], {%1,%2,%3,%4};" :: "r"(a), "r"(x), "r"(y), "r"(z), "r"(w) : "memory"); }
__device__ __forceinline__ void stsm4(uint32_t a, uint32_t r0, uint32_t r1, uint32_t r2, uint32_t r3) {
  asm volatile("stmatrix.sync.aligned.m8n8.x4.shared.b16 [%0], {%1,%2,%3,%4};" :: "r"(a), "r"(r0), "r"(r1), "r"(r2), "r"(r3) : "memory");
}
__device__ __forceinline__ void stsm4t(uint32_t a, uint32_t r0, uint32_t r1, uint32_t r2, uint32_t r3) {
  asm volatile("stmatrix.sync.aligned.m8n8.x4.trans.shared.b16 [%0], {%1,%2,%3,%4};" :: "r"(a), "r"(r0), "r"(r1), "r"(r2), "r"(r3) : "memory");
}
__device__ __forceinline__ void ldsm4t(uint32_t* r, uint32_t a) {
  asm volatile("ldmatrix.sync.aligned.m8n8.x4.trans.shared.b16 {%0,%1,%2,%3}, [%4];" : "=r"(r[0]), "=r"(r[1]), "=r"(r[2]), "=r"(r[3]) : "r"(a) : "memory");
}
__device__ __forceinline__ void ldsm4(uint32_t* r, uint32_t a) {
  asm volatile("ldmatrix.sync.aligned.m8n8.x4.shared.b16 {%0,%1,%2,%3}, [%4];" : "=r"(r[0]), "=r"(r[1]), "=r"(r[2]), "=r"(r[3]) : "r"(a) : "memory");
}
__device__ __forceinline__ void mma16816(float* d, const uint32_t* a, const uint32_t* b) {
  asm volatile("mma.sync.aligned.m16n8k16.row.col.f32.bf16.bf16.f32 {%0,%1,%2,%3}, {%4,%5,%6,%7}, {%8,%9}, {%0,%1,%2,%3};"
    : "+f"(d[0]), "+f"(d[1]), "+f"(d[2]), "+f"(d[3]) : "r"(a[0]), "r"(a[1]), "r"(a[2]), "r"(a[3]), "r"(b[0]), "r"(b[1]));
}
__device__ __forceinline__ uint32_t pack2(float lo, float hi) { uint32_t r; asm("cvt.rn.bf16x2.f32 %0, %1, %2;" : "=r"(r) : "f"(hi), "f"(lo)); return r; }
__device__ __forceinline__ uint32_t packh(float lo, float hi) { uint32_t r; asm("cvt.rn.f16x2.f32 %0, %1, %2;" : "=r"(r) : "f"(hi), "f"(lo)); return r; }
__device__ __forceinline__ uint32_t hcmul(uint32_t x, uint32_t zp, uint32_t zq) {
  const __half2 xx = *reinterpret_cast<__half2*>(&x);
  const __half2 r = __hfma2(__high2half2(xx), *reinterpret_cast<__half2*>(&zq), __hmul2(__low2half2(xx), *reinterpret_cast<__half2*>(&zp)));
  return *reinterpret_cast<const uint32_t*>(&r);
}
__device__ __forceinline__ void hcm2(uint32_t xr, uint32_t xi, uint32_t z, uint32_t& pr, uint32_t& pi) {
  const __half2 a = *reinterpret_cast<__half2*>(&xr), b = *reinterpret_cast<__half2*>(&xi), zz = *reinterpret_cast<__half2*>(&z);
  const __half2 re = __hfma2(__hneg2(b), __high2half2(zz), __hmul2(a, __low2half2(zz)));
  const __half2 im = __hfma2(a, __high2half2(zz), __hmul2(b, __low2half2(zz)));
  pr = *reinterpret_cast<const uint32_t*>(&re); pi = *reinterpret_cast<const uint32_t*>(&im);
}
__device__ __forceinline__ void sts64(uint32_t a, uint32_t x, uint32_t y) { asm volatile("st.shared.v2.u32 [%0], {%1,%2};" :: "r"(a), "r"(x), "r"(y) : "memory"); }
__device__ __forceinline__ void lds64(uint32_t* v, uint32_t a) { asm volatile("ld.shared.v2.u32 {%0,%1}, [%2];" : "=r"(v[0]), "=r"(v[1]) : "r"(a) : "memory"); }
__device__ __forceinline__ float bf_lo(uint32_t v) { return __uint_as_float(v << 16); }
__device__ __forceinline__ float bf_hi(uint32_t v) { return __uint_as_float(v & 0xffff0000u); }
__device__ __forceinline__ float bf_round(float x) { return bf_lo(pack2(x, 0.f)); }
__device__ __forceinline__ float ex2(float x) { float r; asm("ex2.approx.ftz.f32 %0, %1;" : "=f"(r) : "f"(x)); return r; }
__device__ __forceinline__ float phi(float t, float l2e = 1.44269504089f) {
  float e = ex2(t * l2e) + 1e-6f;
  asm("{\n.reg .pred p;\nsetp.gt.f32 p, %1, 0f00000000;\n@p add.f32 %0, %1, 0f3F800008;\n}" : "+f"(e) : "f"(t));
  return e;
}
__device__ __forceinline__ void wg_fence() { asm volatile("wgmma.fence.sync.aligned;" ::: "memory"); }
__device__ __forceinline__ void wg_commit() { asm volatile("wgmma.commit_group.sync.aligned;" ::: "memory"); }
template <int N> __device__ __forceinline__ void wg_wait() { asm volatile("wgmma.wait_group.sync.aligned %0;" :: "n"(N) : "memory"); }
template <int N> __device__ __forceinline__ void pin(float* a) {
  #pragma unroll
  for (int i = 0; i < N; i++) asm volatile("" : "+f"(a[i]) :: "memory");
}
__device__ __forceinline__ int rtid() { int t; asm volatile("mov.u32 %0, %%tid.x;" : "=r"(t)); return t; }
__device__ __forceinline__ int opaque(int v) { asm volatile("" : "+r"(v)); return v; }
template <int N> __device__ __forceinline__ void zero(float* a) {
  #pragma unroll
  for (int i = 0; i < N; i++) asm volatile("mov.b32 %0, 0;" : "=f"(a[i]));
}
template <int N> __device__ __forceinline__ void pinu(uint32_t* a) {
  #pragma unroll
  for (int i = 0; i < N; i++) asm volatile("" : "+r"(a[i]) :: "memory");
}
__device__ __forceinline__ void cexp_t(float lg2mag, float turns, float& re, float& im) {
  float m = ex2(lg2mag);
  float fr = (turns - __fadd_rn(__fadd_rn(turns, 12582912.f), -12582912.f)) * 6.283185307f;
  re = m * __cosf(fr); im = m * __sinf(fr);
}
__device__ __forceinline__ void cmul(float ar, float ai, float br, float bi, float& cr, float& ci) {
  cr = fmaf(ar, br, -ai * bi); ci = fmaf(ar, bi, ai * br);
}

__device__ __forceinline__ void wg_ss48_tt(float* d, uint64_t da, uint64_t db, int scale_d) {
  asm volatile("{\n.reg .pred p;\nsetp.ne.b32 p, %26, 0;\n"
    "wgmma.mma_async.sync.aligned.m64n48k16.f32.bf16.bf16 "
    "{%0, %1, %2, %3, %4, %5, %6, %7, %8, %9, %10, %11, %12, %13, %14, %15, %16, %17, %18, %19, %20, %21, %22, %23}, %24, %25, p, 1, 1, 1, 1;\n}\n"
    : "+f"(d[0]), "+f"(d[1]), "+f"(d[2]), "+f"(d[3]), "+f"(d[4]), "+f"(d[5]), "+f"(d[6]), "+f"(d[7]), "+f"(d[8]), "+f"(d[9]), "+f"(d[10]), "+f"(d[11]), "+f"(d[12]), "+f"(d[13]), "+f"(d[14]), "+f"(d[15]), "+f"(d[16]), "+f"(d[17]), "+f"(d[18]), "+f"(d[19]), "+f"(d[20]), "+f"(d[21]), "+f"(d[22]), "+f"(d[23])
    : "l"(da), "l"(db), "r"(scale_d));
}
__device__ __forceinline__ void wg_rs88_tb(float* d, const uint32_t* a, uint64_t db, int scale_d) {
  asm volatile("{\n.reg .pred p;\nsetp.ne.b32 p, %49, 0;\n"
    "wgmma.mma_async.sync.aligned.m64n88k16.f32.bf16.bf16 "
    "{%0, %1, %2, %3, %4, %5, %6, %7, %8, %9, %10, %11, %12, %13, %14, %15, %16, %17, %18, %19, %20, %21, %22, %23, %24, %25, %26, %27, %28, %29, %30, %31, %32, %33, %34, %35, %36, %37, %38, %39, %40, %41, %42, %43}, {%44, %45, %46, %47}, %48, p, 1, 1, 1;\n}\n"
    : "+f"(d[0]), "+f"(d[1]), "+f"(d[2]), "+f"(d[3]), "+f"(d[4]), "+f"(d[5]), "+f"(d[6]), "+f"(d[7]), "+f"(d[8]), "+f"(d[9]), "+f"(d[10]), "+f"(d[11]), "+f"(d[12]), "+f"(d[13]), "+f"(d[14]), "+f"(d[15]), "+f"(d[16]), "+f"(d[17]), "+f"(d[18]), "+f"(d[19]), "+f"(d[20]), "+f"(d[21]), "+f"(d[22]), "+f"(d[23]), "+f"(d[24]), "+f"(d[25]), "+f"(d[26]), "+f"(d[27]), "+f"(d[28]), "+f"(d[29]), "+f"(d[30]), "+f"(d[31]), "+f"(d[32]), "+f"(d[33]), "+f"(d[34]), "+f"(d[35]), "+f"(d[36]), "+f"(d[37]), "+f"(d[38]), "+f"(d[39]), "+f"(d[40]), "+f"(d[41]), "+f"(d[42]), "+f"(d[43])
    : "r"(a[0]), "r"(a[1]), "r"(a[2]), "r"(a[3]), "l"(db), "r"(scale_d));
}
__device__ __forceinline__ void wg_ss80_tb(float* d, uint64_t da, uint64_t db, int scale_d) {
  asm volatile("{\n.reg .pred p;\nsetp.ne.b32 p, %42, 0;\n"
    "wgmma.mma_async.sync.aligned.m64n80k16.f32.bf16.bf16 "
    "{%0, %1, %2, %3, %4, %5, %6, %7, %8, %9, %10, %11, %12, %13, %14, %15, %16, %17, %18, %19, %20, %21, %22, %23, %24, %25, %26, %27, %28, %29, %30, %31, %32, %33, %34, %35, %36, %37, %38, %39}, %40, %41, p, 1, 1, 0, 1;\n}\n"
    : "+f"(d[0]), "+f"(d[1]), "+f"(d[2]), "+f"(d[3]), "+f"(d[4]), "+f"(d[5]), "+f"(d[6]), "+f"(d[7]), "+f"(d[8]), "+f"(d[9]), "+f"(d[10]), "+f"(d[11]), "+f"(d[12]), "+f"(d[13]), "+f"(d[14]), "+f"(d[15]), "+f"(d[16]), "+f"(d[17]), "+f"(d[18]), "+f"(d[19]), "+f"(d[20]), "+f"(d[21]), "+f"(d[22]), "+f"(d[23]), "+f"(d[24]), "+f"(d[25]), "+f"(d[26]), "+f"(d[27]), "+f"(d[28]), "+f"(d[29]), "+f"(d[30]), "+f"(d[31]), "+f"(d[32]), "+f"(d[33]), "+f"(d[34]), "+f"(d[35]), "+f"(d[36]), "+f"(d[37]), "+f"(d[38]), "+f"(d[39])
    : "l"(da), "l"(db), "r"(scale_d));
}
__device__ __forceinline__ void wg_ss48_tt_h(float* d, uint64_t da, uint64_t db, int scale_d) {
  asm volatile("{\n.reg .pred p;\nsetp.ne.b32 p, %26, 0;\n"
    "wgmma.mma_async.sync.aligned.m64n48k16.f32.f16.f16 "
    "{%0, %1, %2, %3, %4, %5, %6, %7, %8, %9, %10, %11, %12, %13, %14, %15, %16, %17, %18, %19, %20, %21, %22, %23}, %24, %25, p, 1, 1, 1, 1;\n}\n"
    : "+f"(d[0]), "+f"(d[1]), "+f"(d[2]), "+f"(d[3]), "+f"(d[4]), "+f"(d[5]), "+f"(d[6]), "+f"(d[7]), "+f"(d[8]), "+f"(d[9]), "+f"(d[10]), "+f"(d[11]), "+f"(d[12]), "+f"(d[13]), "+f"(d[14]), "+f"(d[15]), "+f"(d[16]), "+f"(d[17]), "+f"(d[18]), "+f"(d[19]), "+f"(d[20]), "+f"(d[21]), "+f"(d[22]), "+f"(d[23])
    : "l"(da), "l"(db), "r"(scale_d));
}
__device__ __forceinline__ void wg_rs192_tb(float* d, const uint32_t* a, uint64_t db, int scale_d) {
  asm volatile("{\n.reg .pred p;\nsetp.ne.b32 p, %101, 0;\n"
    "wgmma.mma_async.sync.aligned.m64n192k16.f32.bf16.bf16 "
    "{%0, %1, %2, %3, %4, %5, %6, %7, %8, %9, %10, %11, %12, %13, %14, %15, %16, %17, %18, %19, %20, %21, %22, %23, %24, %25, %26, %27, %28, %29, %30, %31, %32, %33, %34, %35, %36, %37, %38, %39, %40, %41, %42, %43, %44, %45, %46, %47, %48, %49, %50, %51, %52, %53, %54, %55, %56, %57, %58, %59, %60, %61, %62, %63, %64, %65, %66, %67, %68, %69, %70, %71, %72, %73, %74, %75, %76, %77, %78, %79, %80, %81, %82, %83, %84, %85, %86, %87, %88, %89, %90, %91, %92, %93, %94, %95}, {%96, %97, %98, %99}, %100, p, 1, 1, 1;\n}\n"
    : "+f"(d[0]), "+f"(d[1]), "+f"(d[2]), "+f"(d[3]), "+f"(d[4]), "+f"(d[5]), "+f"(d[6]), "+f"(d[7]), "+f"(d[8]), "+f"(d[9]), "+f"(d[10]), "+f"(d[11]), "+f"(d[12]), "+f"(d[13]), "+f"(d[14]), "+f"(d[15]), "+f"(d[16]), "+f"(d[17]), "+f"(d[18]), "+f"(d[19]), "+f"(d[20]), "+f"(d[21]), "+f"(d[22]), "+f"(d[23]), "+f"(d[24]), "+f"(d[25]), "+f"(d[26]), "+f"(d[27]), "+f"(d[28]), "+f"(d[29]), "+f"(d[30]), "+f"(d[31]), "+f"(d[32]), "+f"(d[33]), "+f"(d[34]), "+f"(d[35]), "+f"(d[36]), "+f"(d[37]), "+f"(d[38]), "+f"(d[39]), "+f"(d[40]), "+f"(d[41]), "+f"(d[42]), "+f"(d[43]), "+f"(d[44]), "+f"(d[45]), "+f"(d[46]), "+f"(d[47]), "+f"(d[48]), "+f"(d[49]), "+f"(d[50]), "+f"(d[51]), "+f"(d[52]), "+f"(d[53]), "+f"(d[54]), "+f"(d[55]), "+f"(d[56]), "+f"(d[57]), "+f"(d[58]), "+f"(d[59]), "+f"(d[60]), "+f"(d[61]), "+f"(d[62]), "+f"(d[63]), "+f"(d[64]), "+f"(d[65]), "+f"(d[66]), "+f"(d[67]), "+f"(d[68]), "+f"(d[69]), "+f"(d[70]), "+f"(d[71]), "+f"(d[72]), "+f"(d[73]), "+f"(d[74]), "+f"(d[75]), "+f"(d[76]), "+f"(d[77]), "+f"(d[78]), "+f"(d[79]), "+f"(d[80]), "+f"(d[81]), "+f"(d[82]), "+f"(d[83]), "+f"(d[84]), "+f"(d[85]), "+f"(d[86]), "+f"(d[87]), "+f"(d[88]), "+f"(d[89]), "+f"(d[90]), "+f"(d[91]), "+f"(d[92]), "+f"(d[93]), "+f"(d[94]), "+f"(d[95])
    : "r"(a[0]), "r"(a[1]), "r"(a[2]), "r"(a[3]), "l"(db), "r"(scale_d));
}
__device__ __forceinline__ void wg_rs48_tb(float* d, const uint32_t* a, uint64_t db, int scale_d) {
  asm volatile("{\n.reg .pred p;\nsetp.ne.b32 p, %29, 0;\n"
    "wgmma.mma_async.sync.aligned.m64n48k16.f32.bf16.bf16 "
    "{%0, %1, %2, %3, %4, %5, %6, %7, %8, %9, %10, %11, %12, %13, %14, %15, %16, %17, %18, %19, %20, %21, %22, %23}, {%24, %25, %26, %27}, %28, p, 1, 1, 1;\n}\n"
    : "+f"(d[0]), "+f"(d[1]), "+f"(d[2]), "+f"(d[3]), "+f"(d[4]), "+f"(d[5]), "+f"(d[6]), "+f"(d[7]), "+f"(d[8]), "+f"(d[9]), "+f"(d[10]), "+f"(d[11]), "+f"(d[12]), "+f"(d[13]), "+f"(d[14]), "+f"(d[15]), "+f"(d[16]), "+f"(d[17]), "+f"(d[18]), "+f"(d[19]), "+f"(d[20]), "+f"(d[21]), "+f"(d[22]), "+f"(d[23])
    : "r"(a[0]), "r"(a[1]), "r"(a[2]), "r"(a[3]), "l"(db), "r"(scale_d));
}

struct Params {
  const __nv_bfloat16 *par[4], *logdt, *dskip, *u, *wo;
  CUtensorMap m[M_COUNT];
};

#define CHUNK(i) ((i) == 0 ? c : ((i) == 7 ? (c ^ 1) : (((c & 6) + 1 + (i)) & 7)))
#define FLAG(kind, rr, cc) (&g_flag[((kind) * 128 + (rr) * 8 + (cc)) * 32])
#define SLOT(i) ((i) == 0 || (i) == 1 ? OFF_EXTRA : OFF_BLK - 256 + ((i) == 7 ? 0 : (i) - 2) * BLK)
__device__ __forceinline__ void load_quad(uint32_t* A, uint32_t addr) {
  A[0] = lds32v(addr); A[1] = lds32v(addr + 32); A[2] = lds32v(addr - 32); A[3] = lds32v(addr);
}

__device__ __forceinline__ bool y_transpose(uint32_t sb, int w5, int lane, uint32_t ytag) {
  const int mi = lane >> 3, rw = lane & 7;
  const uint32_t sa = sb + OFF_EXTRA + (w5 * 16 + rw) * 128 + ((mi ^ rw) << 4), da = sb + SLOT(3) + (8 * mi + rw) * 160 + w5 * 32;
  const uint32_t ym = lane < 4 ? 0x10001u : 0u;
  bar_sync(7, 160);
  uint32_t v[8][4], bad = 0;
  #pragma unroll
  for (int q = 0; q < 8; q++) ldsm4t(v[q], (sa ^ ((q & 1) * 64 + ((q >> 1) & 1) * 16)) + ((q >> 1) & 1) * 10240 + (q >> 2) * 1024);
  #pragma unroll
  for (int q = 0; q < 8; q++) {
    bad |= (v[q][0] ^ ytag) | (v[q][2] ^ ytag);
    stsm4(da + (q & 3) * 5120 + (q >> 2) * 16, v[q][0] & ~ym, v[q][1], v[q][2] & ~ym, v[q][3]);
  }
  fence_async();
  uint32_t any;
  asm volatile("{\n.reg .pred p;\nsetp.ne.u32 p, %1, 0;\nbarrier.red.or.pred p, 7, 160, p;\nselp.u32 %0, 1, 0, p;\n}" : "=r"(any) : "r"(bad & ym) : "memory");
  return any;
}

__global__ void __launch_bounds__(512, 1) fused_kernel(const __grid_constant__ Params prm) {
  extern __shared__ unsigned char smem_raw[];
  const uint32_t sb = __shfl_sync(0xffffffff, smem_u32(smem_raw), 0);
  const int tid = threadIdx.x, lane = tid & 31;
  const int warp = __shfl_sync(0xffffffff, tid >> 5, 0), wg = warp >> 2, w4 = warp & 3;
  const int cta = blockIdx.x, r = cta >> 3, c = cta & 7;
  if ((sb & 0xffffffu) != SB0) return;
#define BAR(i) (sb + OFF_BAR + 8 * (i))
  const bool sw64 = ((c + 1) & 2) != 0;

  if (wg == 3) {
    if (warp == 13 && elect_one()) {
      #pragma unroll
      for (int i = M_W128; i <= M_U; i++) asm volatile("prefetch.tensormap [%0];" :: "l"(&prm.m[i]) : "memory");
    }
    asm volatile("setmaxnreg.dec.sync.aligned.u32 56;");
    const int tid = rtid(), lane = tid & 31;
    if (warp == 12) {
      if (elect_one()) {
        #pragma unroll
        for (int i = 0; i < 5; i++) mbar_init(BAR(BR_FULL + i), 1);
        asm volatile("fence.mbarrier_init.release.cluster;" ::: "memory");
      }
      {
        const CUtensorMap* mwp = &prm.m[sw64 ? M_W64 : M_W128];
        const int mcol = (c * 80 + (c & 1) * 16) >> (sw64 ? 5 : 6), rcol = c * 80 + ((c & 1) ? 0 : 64);
        uint32_t s = 0, ph = 1, xs = 0;
        #pragma unroll 1
        for (int kb = 0; kb < 20; kb++) {
          if (kb == 1) asm volatile("bar.arrive 0, 512;" ::: "memory");
          if (kb == 4) bar_sync(6, 128);
          if (kb >= 5) mbar_wait(BAR(BR_EMPTY) + 8 * s, ph);
          if (EN_ATT && elect_one()) {
            const uint32_t st = sb + s * W_SLOT, fb = BAR(BR_FULL) + 8 * s;
            mbar_expect_tx(fb, (kb & 1) ? W_SLOT : W_SLOT + 16384);
            if (!(kb & 1)) tma2d(sb + OFF_X + xs, &prm.m[M_X], fb, kb * 32, r * 128);
            tma4d(st, mwp, fb, 0, kb * 32, mcol, 0);
            tma3d(st + 12288, &prm.m[M_WR], fb, rcol, kb * 32, 0);
          }
          if (kb < 4 && lane == 0) TS(24 + kb);
          if (kb == 14 && elect_one()) asm volatile("cp.async.bulk.prefetch.L2.global [%0], 6400;" :: "l"(prm.wo + cta * 3200) : "memory");
          if (!EN_ATT && kb == 4) break;
          if (++s == 5) { s = 0; ph ^= 1; }
          if (kb & 1) { xs += 16384; if (xs == 49152) xs = 0; }
        }
      }
      if (EN_ATT) {
      mbar_wait(BAR(BR_EPOCH), 0);
      const unsigned epoch = lds32(sb + OFF_EPOCH);
      const unsigned* fo = FLAG(3, r, lane & 7);
      unsigned seen = __ballot_sync(0xffffffff, ld_rlx(lane < 16 ? fo : FLAG(0, lane & 15, c)) == epoch) & 0xffu;
      mbar_wait(BAR(BR_GEMM), 0);
      if (elect_one()) {
        mbar_expect_tx(BAR(BR_WO), 10240);
        tma2d(sb, &prm.m[M_WO], BAR(BR_WO), c * 64, c * 80);
        mbar_expect_tx(BAR(BR_KVP), 61440);
        mbar_expect_tx(BAR(BR_WO + 1), 7 * 10240);
      }
      {
        uint32_t ds = sb + OFF_WOR + (lane >> 3) * 128 + (((lane & 7) ^ (lane >> 3)) << 4);
        #pragma unroll 1
        for (int h = 0; h < 2; h++) {
          const int i = (lane & 6) + h;
          const char* gs = reinterpret_cast<const char*>(prm.wo) + (size_t)((lane >> 3) + CHUNK(i) * 80) * 1280 + 1024 + c * 32 + (lane & 1) * 16;
          #pragma unroll 2
          for (int q = 0; q < 20; q++) {
            asm volatile("cp.async.cg.shared.global [%0], [%1], 16;" :: "r"(ds), "l"(gs) : "memory");
            ds = (ds + 512) ^ 64; gs += 5120;
          }
        }
      }
      mbar_wait(BAR(BR_PUB), 0);
      poll_all(FLAG(0, lane & 15, c), epoch);
      if (elect_one()) { TS(23); bulk_ld(sb + OFF_KVP, &g_kvp[c * 16 * 240], 61440, BAR(BR_KVP)); }
      asm volatile("cp.async.wait_all;" ::: "memory");
      fence_async();
      mbar_arrive(BAR(BR_WO));
      mbar_wait(BAR(BR_SUM), 0);
      if (elect_one()) {
        #pragma unroll 1
        for (int i = 1; i < 8; i++) tma2d(sb + i * 10240, &prm.m[M_WO], BAR(BR_WO + 1), c * 64, CHUNK(i) * 80);
      }
      mbar_wait(BAR(BR_OSTG), 0);
      if (elect_one()) {
        bulk_st(&g_o[cta * 1280], sb + OFF_EXTRA, 20480);
        bulk_commit();
        bulk_wait0();
        st_rlx(FLAG(3, r, c), epoch);
        TS(20);
      }
      __syncwarp();
      #pragma unroll 1
      for (int i = 1; i < 8; i++) {
        const int src = CHUNK(i);
        if (!((seen >> src) & 1)) seen = poll_bit(fo, epoch, 1u << src);
        if (i == 1 || i == 7) mbar_wait(BAR(BR_OEMPTY) + 8 * (i & 2), 0);
        if (EN_SSM && (i == 2 || i == 6)) mbar_wait(BAR(BR_FREE) + 2 * (i & 4), 0);
        if (elect_one()) {
          mbar_expect_tx(BAR(BR_OFULL) + 8 * i, 20480);
          bulk_ld(sb + SLOT(i), &g_o[(r * 8 + src) * 1280], 20480, BAR(BR_OFULL) + 8 * i);
          if (i == 1) TS(21);
          if (i == 7) TS(22);
        }
        __syncwarp();
      }
      if (lane == 0) { DUMP(20, 30); }
      }
    } else {
      const int hw = warp - 13, ht = tid - 416;
      if (hw == 2 && elect_one()) {
        #pragma unroll
        for (int i = 5; i < BR_COUNT; i++) mbar_init(BAR(i), i == BR_WO ? 33 : i < BR_EMPTY ? 1 : i < BR_OEMPTY ? 2 : i < BR_Y ? 8 : i < BR_OSTG ? 4 : i == BR_OSTG ? 8 : i < BR_U2 ? 3 : 1);
        asm volatile("fence.mbarrier_init.release.cluster;" ::: "memory");
        if (EN_SSM) { mbar_expect_tx(BAR(BR_UIN), 20480); tma2d(sb + OFF_UT, &prm.m[M_U], BAR(BR_UIN), c * 80, r * 128); }
      }
      __syncwarp();
      asm volatile("bar.arrive 0, 512;" ::: "memory");
      if (EN_SSM && hw == 2) asm volatile("bar.arrive 8, 160;" ::: "memory");
      const unsigned epoch = hw == 0 ? ld_rlx(&g_epoch[cta]) + 1 : 0;
      bar_sync(5, 96);
      asm volatile("bar.arrive 6, 128;" ::: "memory");
      if (hw == 1 && elect_one()) {
        #pragma unroll
        for (int i = M_WO; i < M_COUNT; i++) asm volatile("prefetch.tensormap [%0];" :: "l"(&prm.m[i]) : "memory");
      }
      if (ht == 0) {
        st_rlx(&g_epoch[cta], epoch);
        sts32(sb + OFF_EPOCH, epoch);
        mbar_arrive(BAR(BR_EPOCH));
      }
      if (EN_SSM) {
      const int mi = lane >> 3, rw = lane & 7, ch0 = c * 80 + r * 5;
      mbar_wait(BAR(BR_UIN), 0);
      if (ht == 0) TS(36);
      #pragma unroll 1
      for (int h = 0; h < 2; h++) {
        const uint32_t sa = sb + OFF_UT + h * 10240 + (8 * mi + rw) * 160 + hw * 16, da = sb + OFF_UT + h * 10240 + (hw * 8 + rw) * 128 + ((mi ^ rw ^ h) << 4);
        uint32_t v[8][4];
        #pragma unroll
        for (int q = 0; q < 8; q++) if (q < 6 || hw == 0) ldsm4t(v[q], sa + (q & 1) * 5120 + (q >> 1) * 48);
        bar_sync(5, 96);
        #pragma unroll
        for (int q = 0; q < 8; q++) if (q < 6 || hw == 0) stsm4((da ^ ((q & 1) * 64)) + (q >> 1) * 3072, v[q][0], v[q][1], v[q][2], v[q][3]);
      }
      fence_async();
      bar_sync(5, 96);
      if (hw == 0) {
        if (elect_one()) {
          tma2d_st(&prm.m[M_SA], sb + OFF_UT, r * 128, c * 80);
          tma2d_st(&prm.m[M_SA], sb + OFF_UT + 10240, r * 128 + 64, c * 80);
          bulk_commit(); bulk_wait0_read();
          mbar_arrive(BAR(BR_UOUT));
          TS(37);
          bulk_wait0();
          st_rel(FLAG(1, r, c), epoch);
          TS(30);
        }
        __syncwarp();
        poll_all_acq(FLAG(1, lane & 15, c), epoch);
      }
      #pragma unroll 1
      for (int q6 = hw; q6 < 30; q6 += 3) {
        if (q6 < 3 || (q6 >= 18 && q6 < 21)) {
          const int p = q6 >= 18;
          if (hw == 0) {
            if (!p) {
              if (elect_one()) {
                fence_async_g();
                mbar_expect_tx(BAR(BR_U), 12288);
                #pragma unroll 1
                for (int q = 0; q < 3; q++) bulk_ld(sb + OFF_BLK + q * q * BLK, g_uy + (ch0 + q * q) * 2048, 4096, BAR(BR_U));
                TS(31);
              }
              __syncwarp();
            }
            mbar_wait(BAR(p ? BR_U2 : BR_U), 0);
          }
          bar_sync(5, 96);
          if (ht == 0) TS(38 + p);
        }
        {
          const int k = q6 / 6, kap = (q6 - 6 * k) * 32 + lane;
          const uint32_t blk = sb + OFF_BLK + ((0x32410 >> (4 * k)) & 7) * BLK;
          float P[33];
          P[0] = 0.f;
          #pragma unroll
          for (int q = 0; q < 4; q++) {
            const int ch = kap - 3 + q;
            uint32_t v[4];
            lds128(v, blk + (uint32_t)((ch * 16) ^ ((ch * 2) & 0x10)));
            #pragma unroll
            for (int e = 0; e < 4; e++) {
              P[q * 8 + 2 * e + 1] = (q == 0 && e < 2) ? 0.f : P[q * 8 + 2 * e] + bf_lo(v[e]);
              P[q * 8 + 2 * e + 2] = (q == 0 && e < 2) ? 0.f : P[q * 8 + 2 * e + 1] + bf_hi(v[e]);
            }
          }
#define WIN(lo, hi, e) (P[25 + (e) - (lo)] - P[24 + (e) - (hi)])
#define WIN8(lo, hi) pack2(WIN(lo, hi, 0), WIN(lo, hi, 1)), pack2(WIN(lo, hi, 2), WIN(lo, hi, 3)), pack2(WIN(lo, hi, 4), WIN(lo, hi, 5)), pack2(WIN(lo, hi, 6), WIN(lo, hi, 7))
          const uint32_t o2 = blk + B_D + (kap & 1) * 1552 + (kap >> 1) * 16;
          sts128(o2, WIN8(3, 5));
          sts128(o2 + B_D5, WIN8(6, 10));
          if (kap < 2) sts128(blk + B_D + kap * B_D5 + 1536, 0, 0, 0, 0);
          if (kap < 128) {
            const uint32_t o = blk + B_D + (kap & 1) * 1024 + (kap >> 1) * 16;
            sts128(o + B_D7, WIN8(5, 11));
            sts128(o + B_D9, WIN8(12, 20));
          }
        }
      }
      __syncwarp();
      if (lane == 0) mbar_arrive(BAR(BR_DRDY + 1));
      if (ht == 0) TS(32);
      if (hw == 0) {
        #pragma unroll 1
        for (int p = 0; p < 2; p++) {
          mbar_wait(BAR(BR_Y) + 8 * p, 0);
          if (elect_one()) {
            #pragma unroll 1
            for (int k = 4 * p; k < 4 + p; k++) bulk_st(g_uy + (640 + ch0 + k) * 2048, sb + OFF_BLK + k * BLK, 4096);
            bulk_commit(); bulk_wait0_read();
            mbar_arrive(BAR(BR_FREE) + 8 * p);
          }
          __syncwarp();
        }
        if (elect_one()) { bulk_wait0(); st_rlx(FLAG(2, r, c), epoch); TS(33); }
        __syncwarp();
        poll_all(FLAG(2, lane & 15, c), epoch);
        if (EN_ATT) mbar_wait(BAR(BR_OEMPTY + 1), 0);
        #pragma unroll 1
        for (int n = 0; n < 64; n++) {
          if (elect_one()) {
            mbar_expect_tx(BAR(BR_YIN), 20480);
            tma2d(sb + OFF_EXTRA, &prm.m[M_SA], BAR(BR_YIN), r * 128, 640 + c * 80);
            tma2d(sb + OFF_EXTRA + 10240, &prm.m[M_SA], BAR(BR_YIN), r * 128 + 64, 640 + c * 80);
            TS(34);
          }
          __syncwarp();
          if (EN_ATT) mbar_wait(BAR(BR_OEMPTY + 3), 0);
          mbar_wait(BAR(BR_YIN), n & 1);
          if (!y_transpose(sb, 4, lane, (epoch & 1u) * 0x10001u)) break;
          FIXCNT
        }
      if (elect_one()) {
        tma2d_st(&prm.m[M_OUT], sb + SLOT(3), c * 80, r * 128);
        bulk_commit(); bulk_wait0_read();
        TS(35); DUMP(30, 40); DUMP(0, 1);
      }
      }
      }
    }
  } else if (wg < 2) {
    asm volatile("setmaxnreg.inc.sync.aligned.u32 160;");
    bar_sync(0, 512);
    if (EN_ATT) {
    float am[96], ar[24];
    {
      const bool lead = (rtid() & 127) == 0;
      constexpr uint64_t dr0 = mkdesc(SB0 + 12288, 1024, 256, 3);
      const uint64_t db0 = sw64 ? mkdesc(SB0, 2048, 512, 2) : mkdesc(SB0, 4096, 1024, 1);
      const uint32_t kst = sw64 ? 64 : 128, bh = db0 >> 32;
      uint32_t s = 0, ph = 0, xo = 0;
      const int ln = rtid() & 31;
      const uint32_t xa = sb + OFF_X + (warp * 16 + (ln & 15)) * 128 + (((ln >> 4) ^ (ln & 7)) << 4);
      uint32_t A[8];
      mbar_wait(BAR(BR_FULL), 0);
      if (lead && wg == 0) TS(1);
      ldsm4(A, xa); ldsm4(A + 4, xa);
      wg_fence();
      wg_rs48_tb(ar, A + 4, dr0, 0); wg_rs192_tb(am, A + 4, db0, 0);
      wg_commit();
      uint32_t xk = xa, eb = 0;
      #pragma unroll 1
      for (int kb = 0; kb < 20; kb++) {
        const uint32_t wo_ = s * (W_SLOT >> 4), bl = (uint32_t)db0 + wo_, rl = (uint32_t)dr0 + wo_;
        wg_fence();
        wg_rs48_tb(ar, A, desc2(rl, dr0 >> 32), kb != 0);
        wg_rs192_tb(am, A, desc2(bl, bh), kb != 0);
        wg_commit();
        wg_wait<1>();
        ldsm4(A + 4, xk ^ 32);
        if (lead && kb > 0 && kb < 16) mbar_arrive(eb);
        eb = BAR(BR_EMPTY) + 8 * s;
        wg_fence();
        wg_rs48_tb(ar, A + 4, desc2(rl + 32, dr0 >> 32), 1);
        wg_rs192_tb(am, A + 4, desc2(bl + kst, bh), 1);
        wg_commit();
        if (++s == 5) { s = 0; ph ^= 1; }
        if (kb & 1) { xo += 16384; if (xo == 49152) xo = 0; }
        if (kb < 19) mbar_wait(BAR(BR_FULL) + 8 * s, ph);
        xk = (xa + xo) ^ ((~kb & 1) * 64);
        wg_wait<1>();
        ldsm4(A, xk);
      }
      wg_wait<0>();
      pin<96>(am); pin<24>(ar);
    }
    const int tid = rtid(), lane = tid & 31, tq = lane & 3;
    if (tid == 0) TS(2);
#define QV(j, e) ((j) < 8 ? am[4 * (j) + (e)] : ar[4 * ((j) - 8) + (e)])
#define KV_(j, e) ((j) < 8 ? am[32 + 4 * (j) + (e)] : ar[8 + 4 * ((j) - 8) + (e)])
#define VV(j, e) ((j) < 8 ? am[64 + 4 * (j) + (e)] : ar[16 + 4 * ((j) - 8) + (e)])
    {
      bar_sync(1, 256);
      if (tid == 0) mbar_arrive(BAR(BR_GEMM));
      const uint32_t ro = sb + (uint32_t)((warp * 16 + (lane & 15)) * 16);
      const int l0 = 2 * (c & 1) + (lane >> 4);
      const uint32_t ones = (tq == 0) ? 0x00003f80u : 0u;
#define PV(j) pack2(VV(j, 0), VV(j, 1)), pack2(VV(j, 2), VV(j, 3))
#define PK(j) pack2(phi(KV_(j, 0)), phi(KV_(j, 1))), pack2(phi(KV_(j, 2)), phi(KV_(j, 3)))
      stsm4(ro + OFF_V + (5 + 6 * (lane >> 4)) * 2048, ones, ones, ones, ones);
      #pragma unroll
      for (int j = 0; j < 10; j += 2) {
        const int l = (j == 8 && (c & 1)) ? l0 - 2 : l0 + j;
        stsm4(ro + OFF_V + (l + (l >= 5)) * 2048, PV(j), PV(j + 1));
        stsm4(ro + OFF_PK + l * 2048, PK(j), PK(j + 1));
      }
    }
    fence_async();
    bar_sync(1, 256);
    if (tid == 0) TS(3);
    mbar_wait(BAR(BR_EPOCH), 0);
    const unsigned epoch = lds32(sb + OFF_EPOCH);
    {
      float kv[24]; zero<24>(kv);
      constexpr uint64_t da = mkdesc(SB0 + OFF_PK, 128, 2048, 0), db = mkdesc(SB0 + OFF_V, 128, 2048, 0);
      wg_fence();
      #pragma unroll
      for (int s = 0; s < 8; s++) wg_ss48_tt(kv, desc2((uint32_t)da + wg * 640 + s * 16, da >> 32), desc2((uint32_t)db + wg * 768 + s * 16, db >> 32), s != 0);
      wg_commit();
      wg_wait<0>();
      pin<24>(kv);
      if (tid == 0) TS(15);
      if (w4 < 3) {
        const uint32_t wb = sb + OFF_KVS + (wg * 3 + w4) * 1536 + (lane & 15) * 96;
        #pragma unroll
        for (int j = 0; j < 6; j += 2)
          stsm4(wb + (j + (lane >> 4)) * 16, pack2(kv[4 * j], kv[4 * j + 1]), pack2(kv[4 * j + 2], kv[4 * j + 3]),
                pack2(kv[4 * j + 4], kv[4 * j + 5]), pack2(kv[4 * j + 6], kv[4 * j + 7]));
        __syncwarp();
        const int dl = w4 * 16 + (lane & 15), hl = dl >= 20;
        if (dl < 40) {
          uint4* dst = &g_kvp[(c * 16 + r) * 240 + wg * 40 + dl];
          uint32_t v[4], z[4];
          lds128(v, wb + (3 * hl + (lane >> 4)) * 16);
          lds64(z, wb + 32 + 8 * hl); z[2] = lds32(wb + 80); z[3] = epoch & 1u;
          v[3] = (v[3] & ~1u) | z[3];
          st128_rlx(dst + (lane >> 4) * 80, v);
          if (lane < 16) st128_rlx(dst + 160, z);
        }
      }
    }
    fence_async();
    bar_sync(1, 256);
    if (tid == 0) { st_rlx(FLAG(0, r, c), epoch); mbar_arrive(BAR(BR_PUB)); TS(4); }
    const int kvi = (tid >= 80) + (tid >= 160) + (tid >= 240), kd = tid - 80 * kvi;
    const int khd = kd / 20, kt0 = 5 * (khd >> 1) + 2 * (khd & 1);
    const uint32_t rb = sb + OFF_KVB + kd * 16;
    if (kvi < 3) {
      #pragma unroll 1
      for (int m = kvi; m < 7; m += 3) { const int q = kt0 + 3 + m; sts128(rb + (q >= 10 ? q - 10 : q) * 1280, 0, 0, 0, 0); }
    }
    uint32_t qa[20];
    {
      const float sc = 1.44269504089f + __uint_as_float(lds32(sb + OFF_EPOCH) ^ epoch);
      #pragma unroll
      for (int j = 0; j < 10; j++) { qa[2 * j] = pack2(phi(QV(j, 0), sc), phi(QV(j, 1), sc)); qa[2 * j + 1] = pack2(phi(QV(j, 2), sc), phi(QV(j, 3), sc)); }
    }
    if (tid == 0) TS(5);
    if (warp == 7) mbar_wait(BAR(BR_KVP), 0);
    bar_sync(1, 256);
    if (tid == 0) TS(6);
    if (kvi < 3) {
      float s[8];
      zero<8>(s);
      uint32_t bad = 0;
      #pragma unroll 4
      for (int i = 0; i < 16; i++) {
        uint32_t w[4];
        lds128(w, sb + OFF_KVP + tid * 16 + i * 3840);
        bad |= w[3] ^ epoch;
        #pragma unroll
        for (int e = 0; e < 4; e++) { s[2 * e] += bf_lo(w[e]); s[2 * e + 1] += bf_hi(w[e]); }
      }
      if (__builtin_expect(bad & 1u, 0)) {
        zero<8>(s);
        #pragma unroll 1
        for (int i = 0; i < 16; i++) {
          uint32_t w[4] = {0, 0, 0, ~epoch};
          fix128_w3(w, &g_kvp[(c * 16 + i) * 240 + tid], epoch, 1u);
          #pragma unroll
          for (int e = 0; e < 4; e++) { s[2 * e] += bf_lo(w[e]); s[2 * e + 1] += bf_hi(w[e]); }
        }
        FIXCNT
      }
      const uint32_t p0 = pack2(s[0], s[1]), p1 = pack2(s[2], s[3]), p2 = pack2(s[4], s[5]), p3 = pack2(s[6], s[7]);
      if (kvi < 2) sts128(rb + (kt0 + (khd & 1) + kvi) * 1280, p0, p1, p2, p3);
      else {
        const bool od = khd & 1;
        sts128(rb + (5 * (khd >> 1) + 2) * 1280, od ? 0u : p0, od ? 0u : p1, od ? p0 : 0u, od ? p1 : 0u);
        const uint32_t zz = (p2 & 0xffffu) << (16 * (khd & 1));
        sts128(rb + 10 * 1280, khd < 2 ? zz : 0u, khd < 2 ? 0u : zz, 0u, 0u);
      }
    }
    fence_async();
    bar_sync(1, 256);
    if (tid == 0) { mbar_arrive(BAR(BR_SUM)); TS(7); }
    {
      float oa[44]; zero<44>(oa);
      constexpr uint64_t db = mkdesc(SB0 + OFF_KVB, 128, 1280, 0);
      wg_fence();
      #pragma unroll
      for (int s = 0; s < 5; s++) wg_rs88_tb(oa, &qa[4 * s], desc2((uint32_t)db + ((s == 4 && (c & 1)) ? 0 : (s + (c & 1)) * 16), db >> 32), s != 0);
      wg_commit();
      wg_wait<0>();
      pin<44>(oa);
      if (tid == 0) TS(13);
      float rc[4], rd[2][4];
      #pragma unroll
      for (int e = 0; e < 4; e++) asm("rcp.approx.ftz.f32 %0, %1;" : "=f"(rc[e]) : "f"(oa[40 + e] + 1e-6f));
      #pragma unroll
      for (int h = 0; h < 4; h++) {
        rd[0][h] = __shfl_sync(0xffffffff, rc[h & 1], (lane & 28) | (h >> 1));
        rd[1][h] = __shfl_sync(0xffffffff, rc[2 + (h & 1)], (lane & 28) | (h >> 1));
      }
      #pragma unroll
      for (int j = 0; j < 10; j++) {
        #pragma unroll
        for (int h = 0; h < 2; h++) {
          float f;
          if (j == 2) f = tq < 2 ? rd[h][0] : rd[h][1];
          else if (j == 7) f = tq < 2 ? rd[h][2] : rd[h][3];
          else f = rd[h][(8 * j) / 20];
          qa[2 * j + h] = pack2(oa[4 * j + 2 * h] * f, oa[4 * j + 2 * h + 1] * f);
        }
      }
      const uint32_t m0 = (lane & 7) == ((2 * w4) & 7), m1 = (lane & 7) == 2 * w4 + 1;
      const uint32_t oa_ = sb + OFF_EXTRA + (lane >> 4) * 2048 + (warp * 16 + (lane & 15)) * 16;
      bar_sync(1, 256);
#define TAG(v, m) (((v) & ~(m)) | (epoch & (m)))
      #pragma unroll
      for (int s = 0; s < 5; s++) stsm4(oa_ + s * 4096, TAG(qa[4 * s], m0), TAG(qa[4 * s + 1], m1), TAG(qa[4 * s + 2], m0), TAG(qa[4 * s + 3], m1));
    }
    fence_async();
    __syncwarp();
    if (lane == 0) mbar_arrive(BAR(BR_OSTG));
    if (tid == 0) TS(8);
    float oc[40]; zero<40>(oc);
    {
      constexpr uint64_t dw0 = mkdesc(SB0, OFF_WOR, 1024, 1), da0 = mkdesc(SB0, 2048, 128, 0);
      const uint32_t ck = sb + tid * 32 + ((lane >> 2) << 2), ck2 = ck + (wg ? 0 : 16384);
      uint32_t bad = 0;
      auto tile = [&](int i, uint32_t so) {
        const uint32_t al = (uint32_t)da0 + wg * 64 + (so >> 4), wl = (uint32_t)dw0 + i * 640 - (i >> 1) * (1278 << 16);
        wg_fence();
        #pragma unroll
        for (int s = 0; s < 5; s++) wg_ss80_tb(oc, desc2(al + s * 256, da0 >> 32), desc2(wl + s * 128, dw0 >> 32), (i | s) != 0);
        wg_commit();
        bad |= (lds32(ck + so) ^ epoch) | (lds32(ck + so + 8192) ^ epoch) | (lds32(ck2 + so) ^ epoch);
      };
      mbar_wait(BAR(BR_WO), 0);
      mbar_wait(BAR(BR_OSTG), 0);
      tile(0, SLOT(0));
      mbar_wait(BAR(BR_WO + 1), 0);
      #pragma unroll 1
      for (int i = 1; i < 8; i++) {
        if (i == 1) {
          wg_wait<0>();
          if (lane == 0) mbar_arrive(BAR(BR_OEMPTY));
          if (EN_SSM && w4 == 0) mbar_wait(BAR(BR_Y + 1), 0);
          if (w4 == 0) mbar_wait(BAR(BR_OFULL + 1), 0);
          bar_sync(2 + wg, 128);
        }
        mbar_wait(BAR(BR_OFULL) + 8 * i, 0);
        if (i == 1 && tid == 0) TS(9);
        tile(i, SLOT(i));
        wg_wait<1>();
        if (lane == 0 && i > 1) mbar_arrive(BAR(BR_OEMPTY - 1) + 8 * i);
      }
      #pragma unroll 1
      for (int n = 0; n < 56; n++) {
        const int i = n & 7;
        if (i == 0) {
          uint32_t any;
          asm volatile("{\n.reg .pred p;\nsetp.ne.u32 p, %1, 0;\nbarrier.red.or.pred p, 1, 256, p;\nselp.u32 %0, 1, 0, p;\n}" : "=r"(any) : "r"(bad & 1u) : "memory");
          if (!any) break;
          bad = 0;
          FIXCNT
        }
        wg_wait<0>();
        bar_sync(1, 256);
        if (tid == 0) { mbar_expect_tx(BAR(BR_RETRY), 20480); bulk_ld(sb + SLOT(6), &g_o[(r * 8 + CHUNK(i)) * 1280], 20480, BAR(BR_RETRY)); }
        mbar_wait(BAR(BR_RETRY), n & 1);
        tile(i, SLOT(6));
      }
      wg_wait<0>();
      pin<40>(oc);
    }
    if (tid == 0) TS(10);
    {
      const int row = w4 * 16 + (lane & 15);
      const uint32_t ob = sb + OFF_BLK + 2 * BLK + wg * 10240;
      #pragma unroll
      for (int j = 0; j < 8; j += 2)
        stsm4(ob + row * 128 + (((j + (lane >> 4)) ^ (row & 7)) << 4), pack2(oc[4 * j], oc[4 * j + 1]), pack2(oc[4 * j + 2], oc[4 * j + 3]),
              pack2(oc[4 * j + 4], oc[4 * j + 5]), pack2(oc[4 * j + 6], oc[4 * j + 7]));
      stsm4(ob + 8192 + row * 32 + (lane >> 4) * 16, pack2(oc[32], oc[33]), pack2(oc[34], oc[35]), pack2(oc[36], oc[37]), pack2(oc[38], oc[39]));
      fence_async();
      bar_sync(2 + wg, 128);
      if (w4 == 0 && elect_one()) {
        tma2d_st(&prm.m[M_O64], ob, 640 + c * 64, r * 128 + wg * 64);
        tma2d_st(&prm.m[M_O16], ob + 8192, 1152 + c * 16, r * 128 + wg * 64);
        bulk_commit(); bulk_wait0_read();
        if (wg == 0) { TS(11); DUMP(0, 20); }
      }
    }
    }
  } else {
    const int g = lane >> 2, tq = lane & 3, t7 = tid & 127;
    uint32_t raw[5][4], pd;
    {
      const int ch = c * 80 + r * 5;
      #pragma unroll
      for (int e = 0; e < 4; e++) {
        const __nv_bfloat16* pp = prm.par[e] + ch * 128 + t7;
        #pragma unroll
        for (int q = 0; q < 5; q++) asm volatile("ld.global.nc.u16 %0, [%1];" : "=r"(raw[q][e]) : "l"(pp + q * 128));
      }
      asm volatile("ld.global.nc.u16 %0, [%1];" : "=r"(pd) : "l"(((lane & 8) ? prm.dskip : prm.logdt) + ch + min(lane & 7, 4)));
    }
    asm volatile("setmaxnreg.inc.sync.aligned.u32 136;");
    asm volatile("bar.arrive 0, 512;" ::: "memory");
    if (EN_SSM) {
    {
      #pragma unroll 1
      for (int k = 0; k < 4; k++) {
        const uint32_t z = sb + OFF_BLK + k * BLK + t7 * 16;
        sts128(z + B_TBL, 0, 0, 0, 0); sts128(z + B_TBL + 2048, 0, 0, 0, 0);
      }
      if (t7 < 80) sts128(sb + OFF_BLK + (t7 >> 4) * BLK - 256 + (t7 & 15) * 16, 0, 0, 0, 0);
      const uint32_t ea = sb + OFF_BLK + (2 + (w4 & 1)) * BLK + (lane >> 4) * 7168 + ((lane >> 3) & 1) * 256 + (lane & 7) * 16 + (w4 >> 1) * 2048;
      constexpr uint64_t dE = mkdesc(SB0 + OFF_BLK + 2 * BLK, 128, 512, 0);
      const uint32_t xa = sb + OFF_BLK + 18560 + t7 * 8, xr_ = sb + OFF_BLK + 18560 + (t7 ^ 64) * 8;
      uint32_t pr[5][2];
      #pragma unroll
      for (int q = 0; q < 5; q++) {
        #pragma unroll
        for (int e = 0; e < 2; e++) pr[q][e] = raw[q][2 * e] | (raw[q][2 * e + 1] << 16);
        const uint32_t m = __reduce_max_sync(0xffffffff, max(raw[q][2] & 0x7fffu, raw[q][3] & 0x7fffu));
        if (lane == 0) sts32(sb + OFF_EPOCH + 64 + q * 16 + w4 * 4, m);
      }
      bar_sync(8, 160);
      if (t7 == 0) TS(40);
      const int j = (w4 & 1) * 16 + (w4 >> 1) * 8 + g, i2 = tq < 2 ? 64 * tq + j : 32 * (tq - 2) + j;
      const uint32_t e2 = B_TBL + 4 * (tq < 2 ? T_F3 + (((i2 - 1) & 1) ? 80 : 0) + ((i2 - 1) >> 1) + 16 : T_F2 + (i2 & 1) * 96 + (i2 >> 1));
      const uint32_t e1 = tq < 2 ? (i2 ? e2 - 64 : B_TBL + 4 * (T_F2 + 175)) : B_TBL + 4 * (i2 ? T_F2 + ((2 * i2 - 1) & 3) * 48 + ((2 * i2 - 1) >> 2) : 16 + 511);
      const uint32_t e0 = B_TBL + (16 + 8 * j + 2 * tq) * 4;
      #pragma unroll 1
      for (int it = 0; it < 5; it++) {
        const int k = it;
        const uint32_t blk = sb + OFF_BLK + k * BLK;
        float fac;
        {
          const int q = it;
          if (it == 4) {
            mbar_wait(BAR(BR_UOUT), 0);
            sts128(sb + OFF_UT + B_TBL + t7 * 16, 0, 0, 0, 0); sts128(sb + OFF_UT + B_TBL + 2048 + t7 * 16, 0, 0, 0, 0);
          }
          const uint32_t ga = ea + 4096 - (w4 >> 1) * 512;
#define PUT4(i, a, b, c_, d) sts128(((i) < 8 ? ea + ((i) >> 1) * 512 : ga + (((i) - 8) >> 1) * 512) + ((i) & 1) * 128, a, b, c_, d)
          const uint32_t pa0 = pr[0][0], pc0 = pr[0][1];
          const float dt = bf_round(expf(bf_lo(__shfl_sync(0xffffffff, pd, q))));
          #pragma unroll
          for (int e = 0; e < 2; e++) { pr[0][e] = pr[1][e]; pr[1][e] = pr[2][e]; pr[2][e] = pr[3][e]; pr[3][e] = pr[4][e]; }
          uint32_t mm[4];
          lds128(mm, sb + OFF_EPOCH + 64 + q * 16);
          const uint32_t ex = min(max(max(max(mm[0], mm[1]), max(mm[2], mm[3])) >> 7, 1u), 253u);
          const float sc = __uint_as_float((254u - ex) << 23);
          fac = 2.f * dt * __uint_as_float(ex << 23);
          const float lr = -bf_round(expf(bf_lo(pa0))) * dt * 1.44269504089f;
          const float tn = bf_hi(pa0) * dt * 0.15915494309f;
          float z1r, z1i, z2r, z2i, z4r, z4i, xr[8], xi[8], gr[8], gi[8], wr[9], wi[9];
          cexp_t(lr, -tn, z1r, z1i);
          cexp_t(lr * 8.f, tn * 8.f, xr[1], xi[1]);
          cexp_t(lr * 64.f, tn * 64.f, wr[0], wi[0]);
          xr[0] = 1.f; xi[0] = 0.f;
          cmul(xr[1], xi[1], xr[1], xi[1], xr[2], xi[2]); cmul(xr[2], xi[2], xr[1], xi[1], xr[3], xi[3]);
          cmul(xr[2], xi[2], xr[2], xi[2], xr[4], xi[4]);
          #pragma unroll
          for (int b = 1; b < 4; b++) cmul(xr[4], xi[4], xr[b], xi[b], xr[4 + b], xi[4 + b]);
          cmul(wr[0], wi[0], wr[0], wi[0], wr[1], wi[1]); cmul(wr[1], wi[1], wr[0], wi[0], wr[2], wi[2]);
          cmul(wr[1], wi[1], wr[1], wi[1], wr[3], wi[3]); cmul(wr[3], wi[3], wr[3], wi[3], wr[4], wi[4]);
          cmul(wr[4], wi[4], wr[3], wi[3], wr[5], wi[5]); cmul(wr[4], wi[4], wr[4], wi[4], wr[6], wi[6]);
          cmul(wr[6], wi[6], wr[4], wi[4], wr[7], wi[7]); cmul(wr[6], wi[6], wr[6], wi[6], wr[8], wi[8]);
          uint32_t R[4], I[4], PR[4], PI[4];
          #pragma unroll
          for (int b = 0; b < 4; b++) { R[b] = packh(xr[2 * b], xr[2 * b + 1]); I[b] = packh(xi[2 * b], xi[2 * b + 1]); }
          PUT4(0, R[0], R[1], R[2], R[3]); PUT4(1, I[0], I[1], I[2], I[3]);
          #pragma unroll
          for (int i = 0; i < 3; i++) {
            const uint32_t z = packh(wr[i], wi[i]);
            #pragma unroll
            for (int b = 0; b < 4; b++) hcm2(R[b], I[b], z, PR[b], PI[b]);
            PUT4(2 * i + 2, PR[0], PR[1], PR[2], PR[3]); PUT4(2 * i + 3, PI[0], PI[1], PI[2], PI[3]);
          }
          gr[0] = bf_lo(pc0) * sc; gi[0] = -bf_hi(pc0) * sc;
          cmul(z1r, z1i, z1r, z1i, z2r, z2i); cmul(z2r, z2i, z2r, z2i, z4r, z4i);
          cmul(gr[0], gi[0], z1r, z1i, gr[1], gi[1]);
          cmul(gr[0], gi[0], z2r, z2i, gr[2], gi[2]); cmul(gr[1], gi[1], z2r, z2i, gr[3], gi[3]);
          #pragma unroll
          for (int b = 0; b < 4; b++) cmul(gr[b], gi[b], z4r, z4i, gr[4 + b], gi[4 + b]);
          PUT4(8, packh(gr[0], gr[1]), packh(gr[2], gr[3]), packh(gr[4], gr[5]), packh(gr[6], gr[7]));
          PUT4(9, packh(gi[0], gi[1]), packh(gi[2], gi[3]), packh(gi[4], gi[5]), packh(gi[6], gi[7]));
          {
            const uint32_t z = packh(wr[3], -wi[3]), a4r = packh(gr[0], gr[4]), a4i = packh(gi[0], gi[4]);
            hcm2(packh(gr[0], gr[2]), packh(gi[0], gi[2]), z, PR[0], PI[0]);
            hcm2(packh(gr[4], gr[6]), packh(gi[4], gi[6]), z, PR[1], PI[1]);
            hcm2(a4r, a4i, packh(wr[4], -wi[4]), PR[2], PI[2]);
            hcm2(a4r, a4i, packh(wr[5], -wi[5]), PR[3], PI[3]);
            PUT4(10, PR[0], PR[1], PR[2], PR[3]); PUT4(11, PI[0], PI[1], PI[2], PI[3]);
            float hr, hi_;
            cmul(gr[0], gi[0], wr[3], -wi[3], hr, hi_);
            const uint32_t cr = packh(gr[0], hr), ci = packh(gi[0], hi_);
            #pragma unroll
            for (int i = 0; i < 3; i++) hcm2(cr, ci, packh(wr[6 + i], -wi[6 + i]), PR[i], PI[i]);
            PUT4(12, PR[0], PR[1], PR[2], 0u); PUT4(13, PI[0], PI[1], PI[2], 0u);
          }
          fence_async();
          bar_sync(4, 128);
        }
        float ka[24]; zero<24>(ka);
        wg_fence();
        #pragma unroll
        for (int s = 0; s < 8; s++) {
          const uint64_t d = dE + (s >> 2) * (BLK >> 4) + ((s >> 1) & 1) * 448 + (s & 1) * 16;
          wg_ss48_tt_h(ka, d, d + 256, s != 0);
        }
        wg_commit();
        const float dsk = bf_lo(__shfl_sync(0xffffffff, pd, 8 + it));
        wg_wait<0>();
        pin<24>(ka);
        float kk[6];
        const bool up = w4 >= 2;
        #pragma unroll
        for (int n = 0; n < 3; n++) {
          sts64f(xa + n * BLK, up ? ka[12 + 4 * n] : ka[4 * n + 2], up ? ka[13 + 4 * n] : ka[4 * n + 3]);
          kk[2 * n] = up ? ka[14 + 4 * n] : ka[4 * n]; kk[2 * n + 1] = up ? ka[15 + 4 * n] : ka[4 * n + 1];
        }
        bar_sync(4, 128);
          if (it == 4 && w4 == 0) {
            mbar_wait(BAR(BR_U), 0);
            if (elect_one()) {
              mbar_expect_tx(BAR(BR_U2), 8192);
              bulk_ld(blk - 2 * BLK, g_uy + (c * 80 + r * 5 + 2) * 2048, 4096, BAR(BR_U2)); bulk_ld(blk - BLK, g_uy + (c * 80 + r * 5 + 3) * 2048, 4096, BAR(BR_U2));
            }
            __syncwarp();
          }
        #pragma unroll
        for (int n = 0; n < 3; n++) {
          uint32_t o[2]; lds64(o, xr_ + n * BLK);
          kk[2 * n] = (kk[2 * n] + __uint_as_float(o[0])) * fac; kk[2 * n + 1] = (kk[2 * n + 1] + __uint_as_float(o[1])) * fac;
        }
        if (t7 == 0) kk[0] += dsk;
        {
          const uint32_t v = pack2(kk[1], kk[0]), vh = v >> 16;
          const uint32_t u = pack2(kk[2], kk[3]), w = pack2(kk[4], kk[5]), uu = pack2(kk[2], kk[2]), us = pack2(kk[3], kk[2]);
          const uint32_t x = tq < 2 ? w : u, xh = x >> 16;
          sts32(blk + e0 + 4, v); sts16(blk + e0, vh); sts16(blk + e0 + 10, v);
          sts16(blk + e1, x); sts16(blk + e1 + 6, x); sts16(blk + e2, xh); sts16(blk + e2 + 6, xh);
          if (tq < 2) {
            const uint32_t pb = blk + e0 + 1024 + 8 * tq;
            sts32(pb + 4, uu); sts32(pb + 8, us); sts16(pb + 14, us);
            if (i2) { sts16(pb - 4, u); sts32(pb, uu); }
          }
          if (i2 == 0) {
            const uint32_t tb = blk + B_TBL;
            if (tq == 0) { sts16(tb + (16 + 256) * 4, u); sts16(tb + (T_S + 3) * 4, w); sts32(tb + (T_S + 4) * 4, pack2(kk[4], kk[4])); sts16(tb + (T_S + 5) * 4 + 2, w); }
            else { sts32(tb + 528 * 4, uu); sts32(tb + 529 * 4, uu); sts32(tb + 530 * 4, uu); sts16(tb + 531 * 4 + 2, u); sts16(tb + (T_F3 + 80 + 63) * 4, w); }
          }
        }
        if (t7 == 0) TS(49 + it);
      }
    }
    if (t7 == 0) TS(41);
    mbar_wait(BAR(BR_U), 0);
    bar_sync(4, 128);
    if (EN_ATT) mbar_wait(BAR(BR_GEMM), 0);
    if (t7 == 0) TS(42);
    mbar_wait(BAR(BR_EPOCH), 0);
    const uint32_t ytag = (lds32(sb + OFF_EPOCH) & 1u) * 0x10001u, ym = lane < 4 ? 0x10001u : 0u;
    #pragma unroll 1
    for (int pass = 1; pass >= 0; pass--) {
      const int k = pass ? w4 : 4;
      if (k & 2) mbar_wait(BAR(BR_U2), 0);
      const uint32_t blk = sb + OFF_BLK + k * BLK, tb = blk + B_TBL + (uint32_t)((g - 2 * tq) * 4);
      float acc[16][4];
      zero<64>(&acc[0][0]);
      const int kl = 16 * (lane >> 4) + 2 * (lane & 7) + ((lane >> 3) & 1);
      {
        auto ubase = [&](int sh) { const int q = kl - 2 * sh; return blk + (uint32_t)((q * 16) ^ ((q * 2) & 0x10)); };
#define LDQ(A, sh) _Pragma("unroll") for (int m = 0; m < 4; m++) load_quad(A[m], tb + (16 + 16 * (sh) + 128 * m) * 4);
#define LDB(B, ub, h) _Pragma("unroll") for (int p = 0; p < 4; p++) ldsm4(B[p], (ub) + (4 * (h) + p) * 512);
#define MLO(A, B) _Pragma("unroll") for (int m = 0; m < 4; m++) _Pragma("unroll") for (int cc = 0; cc < 8; cc++) mma16816(acc[cc + m], A[m], &B[cc >> 1][(cc & 1) * 2]);
#define MHI(A, B) _Pragma("unroll") for (int m = 0; m < 4; m++) _Pragma("unroll") for (int cc = 0; cc < 8 - m; cc++) mma16816(acc[8 + cc + m], A[m], &B[cc >> 1][(cc & 1) * 2]);
        int p_ = pass ? 0 : w4;
        const int pe = pass ? 4 : w4 + 1;
        uint32_t A[4][4], A2[4][4], Bl[4][4], Bh[4][4];
        uint32_t ub = ubase(p_ + 4);
        LDQ(A, p_ + 4) LDB(Bl, ub, 0)
        #pragma unroll 1
        for (; p_ < pe; p_++) {
          LDB(Bh, ub, 1)
          MLO(A, Bl)
          ub = ubase(p_);
          LDQ(A2, p_) LDB(Bl, ub, 0)
          MHI(A, Bh)
          LDB(Bh, ub, 1)
          load_quad(A[0], tb + (16 + 512 + 16 * (p_ & 1)) * 4); load_quad(A[1], tb + (T_S + 16 * (p_ & 1)) * 4);
          MLO(A2, Bl)
          if (p_ < 2) {
            #pragma unroll
            for (int cc = 0; cc < 8; cc++) mma16816(acc[cc + 4], A[0], &Bl[cc >> 1][(cc & 1) * 2]);
            #pragma unroll
            for (int cc = 0; cc < 4; cc++) mma16816(acc[cc + 12], A[0], &Bh[cc >> 1][(cc & 1) * 2]);
            #pragma unroll
            for (int cc = 0; cc < 8; cc++) mma16816(acc[cc + 8], A[1], &Bl[cc >> 1][(cc & 1) * 2]);
          }
          const int pn = ((p_ + 1) & 3) + 4;
          ub = ubase(pn);
          LDQ(A, pn) LDB(Bl, ub, 0)
          MHI(A2, Bh)
        }
      }
      if (t7 == 0) TS(57 + 3 * pass);
      mbar_wait(BAR(BR_DRDY + 1), 0);
      {
        const int ih = (lane >> 3) & 1;
        const uint32_t dl = blk + B_D + (uint32_t)(((lane >> 4) * 8 + (lane & 7)) * 16);
        const uint32_t d0_ = dl + ih * 1552, d8_ = dl + (ih ? 0 : 1536), d3_ = dl + B_D7 + ih * 1024;
        auto cls2 = [&](uint32_t da, uint32_t ta) {
          uint32_t B[6][2], A[6][4];
          #pragma unroll
          for (int e = 0; e < 6; e++) { B[e][0] = lds32v(ta + (e + 4) * 32); B[e][1] = lds32v(ta + (e + 3) * 32); }
          #pragma unroll
          for (int kk = 0; kk < 6; kk++) ldsm4t(A[kk], da + kk * 256);
          #pragma unroll
          for (int e = 0; e < 6; e++)
            #pragma unroll
            for (int kk = 0; kk < 6; kk++) if (2 * kk + e + 4 < 16) mma16816(acc[2 * kk + e + 4], A[kk], B[e]);
        };
        auto cls3 = [&](uint32_t da, uint32_t ta) {
          uint32_t B[8][2], A[4][4];
          #pragma unroll
          for (int e = 0; e < 8; e++) { B[e][0] = lds32v(ta + (e + 8) * 32); B[e][1] = lds32v(ta + (e + 7) * 32); }
          #pragma unroll
          for (int kk = 0; kk < 4; kk++) ldsm4t(A[kk], da + kk * 256);
          #pragma unroll
          for (int kk = 0; kk < 4; kk++)
            #pragma unroll
            for (int e = 0; e < 8; e++) if (2 * kk + e + 8 < 16) mma16816(acc[2 * kk + e + 8], A[kk], B[e]);
        };
        if (pass) {
          #pragma unroll 1
          for (int a = 0; a < 2; a++) {
            cls2(d0_ + a * B_D5, tb + (T_F2 + 48 * a - 32) * 4);
            cls2(d8_ + a * B_D5, tb + (T_F2 + 48 * a + 64) * 4);
            cls3(d3_ + a * 2048, tb + (T_F3 + 80 * a - 64) * 4);
          }
        } else {
          cls2(((w4 & 2) ? d8_ : d0_) + (w4 & 1) * B_D5, tb + (T_F2 + 48 * w4 - 32) * 4);
          if (w4 >= 2) cls3(d3_ + (w4 - 2) * 2048, tb + (T_F3 + 80 * (w4 - 2) - 64) * 4);
        }
      }
      if (t7 == 0) TS(58 + 3 * pass);
      const uint32_t ya = blk + (uint32_t)((kl * 16) ^ ((kl * 2) & 0x10));
#define YTAG(v) (((v) & ~ym) | (ytag & ym))
#define STY(p) stsm4t(ya + (p) * 512, YTAG(pack2(acc[2 * (p)][0], acc[2 * (p)][1])), pack2(acc[2 * (p)][2], acc[2 * (p)][3]), \
                      YTAG(pack2(acc[2 * (p) + 1][0], acc[2 * (p) + 1][1])), pack2(acc[2 * (p) + 1][2], acc[2 * (p) + 1][3]))
      if (pass == 0) {
        const uint32_t xw = blk + 4096 + w4 * 4096 + lane * 16, xr = blk + 4096 + w4 * 1024 + lane * 16;
        #pragma unroll
        for (int h = 0; h < 2; h++) {
          bar_sync(4, 128);
          #pragma unroll
          for (int i = 0; i < 8; i++)
            sts128(xw + i * 512, __float_as_uint(acc[8 * h + i][0]), __float_as_uint(acc[8 * h + i][1]), __float_as_uint(acc[8 * h + i][2]), __float_as_uint(acc[8 * h + i][3]));
          bar_sync(4, 128);
          float y[8];
          #pragma unroll
          for (int i = 0; i < 8; i++) {
            uint32_t o[4]; lds128(o, xr + (i >> 1) * 4096 + (i & 1) * 512);
            #pragma unroll
            for (int e = 0; e < 4; e++) y[4 * (i & 1) + e] = i < 2 ? __uint_as_float(o[e]) : y[4 * (i & 1) + e] + __uint_as_float(o[e]);
          }
          stsm4t(ya + (4 * h + w4) * 512, YTAG(pack2(y[0], y[1])), pack2(y[2], y[3]), YTAG(pack2(y[4], y[5])), pack2(y[6], y[7]));
        }
      } else {
        __syncwarp();
        #pragma unroll
        for (int p = 0; p < 8; p++) STY(p);
      }
      if (t7 == 0 && !pass) TS(55);
      fence_async();
      __syncwarp();
      if (lane == 0) mbar_arrive(BAR(BR_Y + 1) - 8 * pass);
      if (t7 == 0) TS(59 + 3 * pass);
    }
    if (t7 == 0) DUMP(40, 64);
    #pragma unroll 1
    for (int n = 0; n < 64; n++) if (!y_transpose(sb, w4, lane, ytag)) break;
    }
  }
}

typedef CUresult (*EncFn)(CUtensorMap*, CUtensorMapDataType, cuuint32_t, void*, const cuuint64_t*, const cuuint64_t*, const cuuint32_t*,
                          const cuuint32_t*, CUtensorMapInterleave, CUtensorMapSwizzle, CUtensorMapL2promotion, CUtensorMapFloatOOBfill);
static void mkmap(EncFn enc, CUtensorMap* m, const void* base, int rank, const cuuint64_t* dims, const cuuint64_t* strides, const cuuint32_t* box, CUtensorMapSwizzle swz) {
  cuuint32_t es[5] = {1, 1, 1, 1, 1};
  enc(m, CU_TENSOR_MAP_DATA_TYPE_BFLOAT16, rank, const_cast<void*>(base), dims, strides, box, es, CU_TENSOR_MAP_INTERLEAVE_NONE, swz,
      CU_TENSOR_MAP_L2_PROMOTION_L2_128B, CU_TENSOR_MAP_FLOAT_OOB_FILL_NONE);
}

extern "C" void kernel_launch(void* const* d_in, const int* in_sizes, int n_in, void* d_out, int out_size) {
  void* fn = nullptr; cudaDriverEntryPointQueryResult qr;
  cudaGetDriverEntryPoint("cuTensorMapEncodeTiled", &fn, cudaEnableDefault, &qr);
  EncFn enc = (EncFn)fn;
  void* uy = nullptr; cudaGetSymbolAddress(&uy, g_uy);
  const cuuint64_t dx[2] = {640, 2048}, sx[1] = {1280};
  const cuuint32_t bx[2] = {64, 128}, bu[2] = {80, 128};
  const cuuint64_t dw[3] = {640, 640, 3}, sw[2] = {3840, 1280};
  const cuuint32_t br[3] = {16, 32, 3};
  const cuuint64_t dwa[4] = {64, 640, 10, 3}, swa[3] = {3840, 128, 1280}, dwb[4] = {32, 640, 20, 3}, swb[3] = {3840, 64, 1280};
  const cuuint32_t bwa[4] = {64, 32, 1, 3}, bwb[4] = {32, 32, 2, 3};
  const cuuint64_t dwo[2] = {640, 640};
  const cuuint32_t bwo[2] = {64, 80}, bo64[2] = {64, 64}, bo16[2] = {16, 64};
  const cuuint64_t dsa[2] = {2048, 1280}, ssa[1] = {4096};
  const cuuint32_t bsa[2] = {64, 80};
  const cuuint64_t dout[2] = {1280, 2048}, sout[1] = {2560};
  Params prm;
  mkmap(enc, &prm.m[M_X], d_in[7], 2, dx, sx, bx, CU_TENSOR_MAP_SWIZZLE_128B);
  mkmap(enc, &prm.m[M_W128], d_in[8], 4, dwa, swa, bwa, CU_TENSOR_MAP_SWIZZLE_128B);
  mkmap(enc, &prm.m[M_W64], d_in[8], 4, dwb, swb, bwb, CU_TENSOR_MAP_SWIZZLE_64B);
  mkmap(enc, &prm.m[M_WR], d_in[8], 3, dw, sw, br, CU_TENSOR_MAP_SWIZZLE_32B);
  mkmap(enc, &prm.m[M_U], d_in[0], 2, dx, sx, bu, CU_TENSOR_MAP_SWIZZLE_NONE);
  mkmap(enc, &prm.m[M_WO], d_in[9], 2, dwo, sx, bwo, CU_TENSOR_MAP_SWIZZLE_128B);
  mkmap(enc, &prm.m[M_O64], d_out, 2, dout, sout, bo64, CU_TENSOR_MAP_SWIZZLE_128B);
  mkmap(enc, &prm.m[M_O16], d_out, 2, dout, sout, bo16, CU_TENSOR_MAP_SWIZZLE_NONE);
  mkmap(enc, &prm.m[M_SA], uy, 2, dsa, ssa, bsa, CU_TENSOR_MAP_SWIZZLE_128B);
  mkmap(enc, &prm.m[M_OUT], d_out, 2, dout, sout, bu, CU_TENSOR_MAP_SWIZZLE_NONE);
  prm.u = (const __nv_bfloat16*)d_in[0]; prm.wo = (const __nv_bfloat16*)d_in[9];
  for (int i = 0; i < 4; i++) prm.par[i] = (const __nv_bfloat16*)d_in[1 + i];
  prm.logdt = (const __nv_bfloat16*)d_in[5]; prm.dskip = (const __nv_bfloat16*)d_in[6];
  cudaFuncSetAttribute(fused_kernel, cudaFuncAttributeMaxDynamicSharedMemorySize, SMEM_BYTES);
  cudaLaunchConfig_t cfg = {};
  cfg.gridDim = dim3(128); cfg.blockDim = dim3(512); cfg.dynamicSmemBytes = SMEM_BYTES; cfg.stream = cudaStreamPerThread;
  cudaLaunchAttribute at[1];
  at[0].id = cudaLaunchAttributeClusterDimension; at[0].val.clusterDim.x = 2; at[0].val.clusterDim.y = 1; at[0].val.clusterDim.z = 1;
  cfg.attrs = at; cfg.numAttrs = 1;
  cudaLaunchKernelEx(&cfg, fused_kernel, prm);
}
```

```cpp
#include <cuda_runtime.h>
#include <cuda_bf16.h>
#include <cuda_fp16.h>
#include <cuda.h>
#include <stdint.h>

#define KST 2
#define UKB 4
#define UPF 0
#define EN_ATT 1
#define EN_SSM 1

__device__ __align__(1024) __nv_bfloat16 g_uy[2 * 640 * 2048];
__device__ __align__(128) uint4 g_kvp[8 * 16 * 240];
__device__ __align__(128) uint4 g_o[128 * 1280];
__device__ __align__(128) unsigned g_flag[4 * 128 * 32];
__device__ unsigned g_epoch[128];
#define TS(i) do {} while (0)
#define DUMP(lo, hi) do {} while (0)
#define FIXCNT

constexpr uint32_t SB0 = 1024;
constexpr uint32_t W_SLOT = 15360, OFF_X = 76800;
constexpr uint32_t OFF_WOR = 81920, OFF_KVP = 10240, OFF_KVS = 71680, OFF_PK = 10240, OFF_V = 30720, OFF_EXTRA = 102400, OFF_KVB = OFF_EXTRA;
constexpr uint32_t OFF_BAR = 125952, OFF_BLK = 128000, BLK = 20480;
constexpr uint32_t B_D = 4096, B_D5 = 3088, B_D7 = 6176, B_D9 = 8224, B_TBL = 14400;
constexpr int T_S = 576, T_F2 = 624, T_F3 = 816;
constexpr uint32_t OFF_UT = OFF_BLK + 4 * BLK;
constexpr uint32_t SMEM_BYTES = OFF_BLK + 5 * BLK;
enum { BR_FULL = 0, BR_WO = 5, BR_PUB = 7, BR_KVP = 8, BR_U = 9, BR_SUM = 10, BR_GEMM = 11, BR_UIN = 12, BR_YIN = 13, BR_EPOCH = 14,
       BR_FREE = 15, BR_RETRY = 17, BR_UOUT = 18, BR_OFULL = 18, BR_KS = 26, BR_EMPTY = 31, BR_OEMPTY = 36, BR_Y = 43, BR_OSTG = 45,
       BR_DRDY = 46, BR_U2 = 48, BR_COUNT = 50 };
constexpr uint32_t OFF_EPOCH = OFF_BAR + 8 * BR_COUNT;
enum { M_X, M_W128, M_W64, M_WR, M_U, M_WO, M_O64, M_O16, M_SA, M_OUT, M_COUNT };

__device__ __forceinline__ long long clk64() { long long t; asm volatile("mov.u64 %0, %%clock64;" : "=l"(t) :: "memory"); return t; }
__device__ __forceinline__ uint32_t smem_u32(const void* p) { return (uint32_t)__cvta_generic_to_shared(p); }
__host__ __device__ constexpr uint64_t mkdesc(uint32_t addr, uint32_t lbo, uint32_t sbo, uint32_t swz) {
  return (uint64_t)((addr & 0x3FFFF) >> 4) | ((uint64_t)(lbo >> 4) << 16) | ((uint64_t)(sbo >> 4) << 32) | ((uint64_t)swz << 62);
}
__device__ __forceinline__ uint64_t desc2(uint32_t lo, uint32_t hi) { uint64_t d; asm("mov.b64 %0, {%1, %2};" : "=l"(d) : "r"(lo), "r"(hi)); return d; }
__device__ __forceinline__ void mbar_init(uint32_t bar, uint32_t cnt) { asm volatile("mbarrier.init.shared::cta.b64 [%0], %1;" :: "r"(bar), "r"(cnt) : "memory"); }
__device__ __forceinline__ void mbar_expect_tx(uint32_t bar, uint32_t bytes) { asm volatile("mbarrier.arrive.expect_tx.shared::cta.b64 _, [%0], %1;" :: "r"(bar), "r"(bytes) : "memory"); }
__device__ __forceinline__ void mbar_arrive(uint32_t bar) { asm volatile("mbarrier.arrive.shared::cta.b64 _, [%0];" :: "r"(bar) : "memory"); }
__device__ __forceinline__ void mbar_wait(uint32_t bar, uint32_t parity) {
  asm volatile("{\n.reg .pred p;\n.reg .u32 c;\nmov.u32 c, 0;\n"
    "WL:\nmbarrier.try_wait.parity.shared::cta.b64 p, [%0], %1;\n@p bra WD;\n"
    "add.u32 c, c, 1;\nsetp.lt.u32 p, c, 200000;\n@p bra WL;\nWD:\n}" :: "r"(bar), "r"(parity) : "memory");
}
__device__ __forceinline__ void poll_all(const unsigned* p, unsigned val) {
  asm volatile("{\n.reg .pred p;\n.reg .u32 c, v;\nmov.u32 c, 0;\n"
    "PL:\nld.relaxed.gpu.global.u32 v, [%0];\nsetp.eq.u32 p, v, %1;\nvote.sync.all.pred p, p, 0xffffffff;\n@p bra PD;\n"
    "add.u32 c, c, 1;\nsetp.lt.u32 p, c, 100000;\n@p bra PL;\nPD:\n}" :: "l"(p), "r"(val) : "memory");
}
__device__ __forceinline__ void poll_all_acq(const unsigned* p, unsigned val) {
  asm volatile("{\n.reg .pred p;\n.reg .u32 c, v;\nmov.u32 c, 0;\n"
    "PL:\nld.acquire.gpu.global.u32 v, [%0];\nsetp.eq.u32 p, v, %1;\nvote.sync.all.pred p, p, 0xffffffff;\n@p bra PD;\n"
    "add.u32 c, c, 1;\nsetp.lt.u32 p, c, 100000;\n@p bra PL;\nPD:\n}" :: "l"(p), "r"(val) : "memory");
}
__device__ __forceinline__ unsigned poll_bit(const unsigned* p, unsigned val, unsigned mask) {
  unsigned bal;
  asm volatile("{\n.reg .pred p;\n.reg .u32 c, v;\nmov.u32 c, 0;\n"
    "PL:\nld.relaxed.gpu.global.u32 v, [%1];\nsetp.eq.u32 p, v, %2;\nvote.sync.ballot.b32 %0, p, 0xffffffff;\n"
    "and.b32 v, %0, %3;\nsetp.ne.u32 p, v, 0;\n@p bra PD;\n"
    "add.u32 c, c, 1;\nsetp.lt.u32 p, c, 100000;\n@p bra PL;\nPD:\n}" : "=&r"(bal) : "l"(p), "r"(val), "r"(mask) : "memory");
  return bal;
}
__device__ __forceinline__ void fix128_w0(uint32_t* v, const void* p, uint32_t tag, uint32_t mask) {
  asm volatile("{\n.reg .pred p;\n.reg .u32 c, x;\n.reg .b128 t;\n.reg .b64 lo, hi;\nmov.u32 c, 0;\n"
    "FL:\nxor.b32 x, %0, %5;\nand.b32 x, x, %6;\nsetp.eq.u32 p, x, 0;\n@p bra FD;\n"
    "ld.relaxed.gpu.global.b128 t, [%4];\nmov.b128 {lo, hi}, t;\nmov.b64 {%0, %1}, lo;\nmov.b64 {%2, %3}, hi;\n"
    "add.u32 c, c, 1;\nsetp.lt.u32 p, c, 100000;\n@p bra FL;\nFD:\n}"
    : "+r"(v[0]), "+r"(v[1]), "+r"(v[2]), "+r"(v[3]) : "l"(p), "r"(tag), "r"(mask) : "memory");
}
__device__ __forceinline__ void fix128_w3(uint32_t* v, const void* p, uint32_t tag, uint32_t mask) {
  asm volatile("{\n.reg .pred p;\n.reg .u32 c, x;\n.reg .b128 t;\n.reg .b64 lo, hi;\nmov.u32 c, 0;\n"
    "FL:\nxor.b32 x, %3, %5;\nand.b32 x, x, %6;\nsetp.eq.u32 p, x, 0;\n@p bra FD;\n"
    "ld.relaxed.gpu.global.b128 t, [%4];\nmov.b128 {lo, hi}, t;\nmov.b64 {%0, %1}, lo;\nmov.b64 {%2, %3}, hi;\n"
    "add.u32 c, c, 1;\nsetp.lt.u32 p, c, 100000;\n@p bra FL;\nFD:\n}"
    : "+r"(v[0]), "+r"(v[1]), "+r"(v[2]), "+r"(v[3]) : "l"(p), "r"(tag), "r"(mask) : "memory");
}
__device__ __forceinline__ void fence_acq() { asm volatile("fence.acq_rel.gpu;" ::: "memory"); }
__device__ __forceinline__ bool elect_one() {
  uint32_t p; asm volatile("{\n.reg .pred P;\nelect.sync _|P, 0xffffffff;\nselp.u32 %0, 1, 0, P;\n}" : "=r"(p)); return p;
}
__device__ __forceinline__ void bar_sync(int id, int n) { asm volatile("bar.sync %0, %1;" :: "r"(id), "r"(n) : "memory"); }
__device__ __forceinline__ void fence_async() { asm volatile("fence.proxy.async.shared::cta;" ::: "memory"); }
__device__ __forceinline__ void fence_async_g() { asm volatile("fence.proxy.async.global;" ::: "memory"); }
__device__ __forceinline__ void tma2d(uint32_t dst, const CUtensorMap* m, uint32_t bar, int c0, int c1) {
  asm volatile("cp.async.bulk.tensor.2d.shared::cluster.global.mbarrier::complete_tx::bytes [%0], [%1, {%3, %4}], [%2];"
    :: "r"(dst), "l"(m), "r"(bar), "r"(c0), "r"(c1) : "memory");
}
__device__ __forceinline__ void tma3d(uint32_t dst, const CUtensorMap* m, uint32_t bar, int c0, int c1, int c2) {
  asm volatile("cp.async.bulk.tensor.3d.shared::cluster.global.mbarrier::complete_tx::bytes [%0], [%1, {%3, %4, %5}], [%2];"
    :: "r"(dst), "l"(m), "r"(bar), "r"(c0), "r"(c1), "r"(c2) : "memory");
}
__device__ __forceinline__ void tma4d(uint32_t dst, const CUtensorMap* m, uint32_t bar, int c0, int c1, int c2, int c3) {
  asm volatile("cp.async.bulk.tensor.4d.shared::cluster.global.mbarrier::complete_tx::bytes [%0], [%1, {%3, %4, %5, %6}], [%2];"
    :: "r"(dst), "l"(m), "r"(bar), "r"(c0), "r"(c1), "r"(c2), "r"(c3) : "memory");
}
__device__ __forceinline__ void tma2d_st(const CUtensorMap* m, uint32_t src, int c0, int c1) {
  asm volatile("cp.async.bulk.tensor.2d.global.shared::cta.bulk_group [%0, {%2, %3}], [%1];"
    :: "l"(m), "r"(src), "r"(c0), "r"(c1) : "memory");
}
__device__ __forceinline__ void bulk_ld(uint32_t dst, const void* src, uint32_t bytes, uint32_t bar) {
  asm volatile("cp.async.bulk.shared::cluster.global.mbarrier::complete_tx::bytes [%0], [%1], %2, [%3];"
    :: "r"(dst), "l"(src), "r"(bytes), "r"(bar) : "memory");
}
__device__ __forceinline__ void bulk_st(void* dst, uint32_t src, uint32_t bytes) {
  asm volatile("cp.async.bulk.global.shared::cta.bulk_group [%0], [%1], %2;" :: "l"(dst), "r"(src), "r"(bytes) : "memory");
}
__device__ __forceinline__ void bulk_commit() { asm volatile("cp.async.bulk.commit_group;" ::: "memory"); }
__device__ __forceinline__ void bulk_wait0() { asm volatile("cp.async.bulk.wait_group 0;" ::: "memory"); }
__device__ __forceinline__ void bulk_wait0_read() { asm volatile("cp.async.bulk.wait_group.read 0;" ::: "memory"); }
__device__ __forceinline__ unsigned ld_rlx(const unsigned* p) { unsigned v; asm volatile("ld.relaxed.gpu.global.u32 %0, [%1];" : "=r"(v) : "l"(p) : "memory"); return v; }
__device__ __forceinline__ unsigned ld_acq(const unsigned* p) { unsigned v; asm volatile("ld.acquire.gpu.global.u32 %0, [%1];" : "=r"(v) : "l"(p) : "memory"); return v; }
__device__ __forceinline__ void st_rlx(unsigned* p, unsigned v) { asm volatile("st.relaxed.gpu.global.u32 [%0], %1;" :: "l"(p), "r"(v) : "memory"); }
__device__ __forceinline__ void st_rel(unsigned* p, unsigned v) { asm volatile("st.release.gpu.global.u32 [%0], %1;" :: "l"(p), "r"(v) : "memory"); }
__device__ __forceinline__ void ld128_rlx(uint32_t* v, const void* p) {
  asm volatile("{\n.reg .b128 t;\n.reg .b64 lo, hi;\nld.relaxed.gpu.global.b128 t, [%4];\nmov.b128 {lo, hi}, t;\n"
    "mov.b64 {%0, %1}, lo;\nmov.b64 {%2, %3}, hi;\n}" : "=r"(v[0]), "=r"(v[1]), "=r"(v[2]), "=r"(v[3]) : "l"(p) : "memory");
}
__device__ __forceinline__ void st128_rlx(void* p, const uint32_t* v) {
  asm volatile("{\n.reg .b128 t;\n.reg .b64 lo, hi;\nmov.b64 lo, {%1, %2};\nmov.b64 hi, {%3, %4};\nmov.b128 t, {lo, hi};\n"
    "st.relaxed.gpu.global.b128 [%0], t;\n}" :: "l"(p), "r"(v[0]), "r"(v[1]), "r"(v[2]), "r"(v[3]) : "memory");
}
__device__ __forceinline__ uint32_t lds32(uint32_t a) { uint32_t v; asm volatile("ld.shared.u32 %0, [%1];" : "=r"(v) : "r"(a) : "memory"); return v; }
__device__ __forceinline__ uint32_t lds32v(uint32_t a) { uint32_t v; asm volatile("ld.volatile.shared.u32 %0, [%1];" : "=r"(v) : "r"(a) : "memory"); return v; }
__device__ __forceinline__ uint32_t cpa(uint32_t a, uint32_t one) { uint32_t v; asm volatile("mul.lo.u32 %0, %1, %2;" : "=r"(v) : "r"(a), "r"(one)); return v; }
__device__ __forceinline__ uint32_t cpb(uint32_t a, uint32_t zero) { uint32_t v; asm volatile("or.b32 %0, %1, %2;" : "=r"(v) : "r"(a), "r"(zero)); return v; }
__device__ __forceinline__ uint32_t lds16(uint32_t a) { uint16_t v; asm volatile("ld.shared.u16 %0, [%1];" : "=h"(v) : "r"(a) : "memory"); return v; }
__device__ __forceinline__ float ldsf(uint32_t a) { float v; asm volatile("ld.shared.f32 %0, [%1];" : "=f"(v) : "r"(a) : "memory"); return v; }
__device__ __forceinline__ void lds128(uint32_t* v, uint32_t a) { asm volatile("ld.shared.v4.u32 {%0,%1,%2,%3}, [%4];" : "=r"(v[0]), "=r"(v[1]), "=r"(v[2]), "=r"(v[3]) : "r"(a) : "memory"); }
__device__ __forceinline__ void sts32(uint32_t a, uint32_t v) { asm volatile("st.shared.u32 [%0], %1;" :: "r"(a), "r"(v) : "memory"); }
__device__ __forceinline__ void sts16(uint32_t a, uint32_t v) { asm volatile("st.shared.u16 [%0], %1;" :: "r"(a), "h"((uint16_t)v) : "memory"); }
__device__ __forceinline__ void sts64f(uint32_t a, float x, float y) { asm volatile("st.shared.v2.f32 [%0], {%1,%2};" :: "r"(a), "f"(x), "f"(y) : "memory"); }
__device__ __forceinline__ void sts128(uint32_t a, uint32_t x, uint32_t y, uint32_t z, uint32_t w) { asm volatile("st.shared.v4.u32 [%0], {%1,%2,%3,%4};" :: "r"(a), "r"(x), "r"(y), "r"(z), "r"(w) : "memory"); }
__device__ __forceinline__ void stsm4(uint32_t a, uint32_t r0, uint32_t r1, uint32_t r2, uint32_t r3) {
  asm volatile("stmatrix.sync.aligned.m8n8.x4.shared.b16 [%0], {%1,%2,%3,%4};" :: "r"(a), "r"(r0), "r"(r1), "r"(r2), "r"(r3) : "memory");
}
__device__ __forceinline__ void stsm4t(uint32_t a, uint32_t r0, uint32_t r1, uint32_t r2, uint32_t r3) {
  asm volatile("stmatrix.sync.aligned.m8n8.x4.trans.shared.b16 [%0], {%1,%2,%3,%4};" :: "r"(a), "r"(r0), "r"(r1), "r"(r2), "r"(r3) : "memory");
}
__device__ __forceinline__ void ldsm4t(uint32_t* r, uint32_t a) {
  asm volatile("ldmatrix.sync.aligned.m8n8.x4.trans.shared.b16 {%0,%1,%2,%3}, [%4];" : "=r"(r[0]), "=r"(r[1]), "=r"(r[2]), "=r"(r[3]) : "r"(a) : "memory");
}
__device__ __forceinline__ void ldsm4(uint32_t* r, uint32_t a) {
  asm volatile("ldmatrix.sync.aligned.m8n8.x4.shared.b16 {%0,%1,%2,%3}, [%4];" : "=r"(r[0]), "=r"(r[1]), "=r"(r[2]), "=r"(r[3]) : "r"(a) : "memory");
}
__device__ __forceinline__ void mma16816(float* d, const uint32_t* a, const uint32_t* b) {
  asm volatile("mma.sync.aligned.m16n8k16.row.col.f32.bf16.bf16.f32 {%0,%1,%2,%3}, {%4,%5,%6,%7}, {%8,%9}, {%0,%1,%2,%3};"
    : "+f"(d[0]), "+f"(d[1]), "+f"(d[2]), "+f"(d[3]) : "r"(a[0]), "r"(a[1]), "r"(a[2]), "r"(a[3]), "r"(b[0]), "r"(b[1]));
}
__device__ __forceinline__ uint32_t pack2(float lo, float hi) { uint32_t r; asm("cvt.rn.bf16x2.f32 %0, %1, %2;" : "=r"(r) : "f"(hi), "f"(lo)); return r; }
__device__ __forceinline__ uint32_t packh(float lo, float hi) { uint32_t r; asm("cvt.rn.f16x2.f32 %0, %1, %2;" : "=r"(r) : "f"(hi), "f"(lo)); return r; }
__device__ __forceinline__ uint32_t hcmul(uint32_t x, uint32_t zp, uint32_t zq) {
  const __half2 xx = *reinterpret_cast<__half2*>(&x);
  const __half2 r = __hfma2(__high2half2(xx), *reinterpret_cast<__half2*>(&zq), __hmul2(__low2half2(xx), *reinterpret_cast<__half2*>(&zp)));
  return *reinterpret_cast<const uint32_t*>(&r);
}
__device__ __forceinline__ void hcm2(uint32_t xr, uint32_t xi, uint32_t z, uint32_t& pr, uint32_t& pi) {
  const __half2 a = *reinterpret_cast<__half2*>(&xr), b = *reinterpret_cast<__half2*>(&xi), zz = *reinterpret_cast<__half2*>(&z);
  const __half2 re = __hfma2(__hneg2(b), __high2half2(zz), __hmul2(a, __low2half2(zz)));
  const __half2 im = __hfma2(a, __high2half2(zz), __hmul2(b, __low2half2(zz)));
  pr = *reinterpret_cast<const uint32_t*>(&re); pi = *reinterpret_cast<const uint32_t*>(&im);
}
__device__ __forceinline__ void sts64(uint32_t a, uint32_t x, uint32_t y) { asm volatile("st.shared.v2.u32 [%0], {%1,%2};" :: "r"(a), "r"(x), "r"(y) : "memory"); }
__device__ __forceinline__ void lds64(uint32_t* v, uint32_t a) { asm volatile("ld.shared.v2.u32 {%0,%1}, [%2];" : "=r"(v[0]), "=r"(v[1]) : "r"(a) : "memory"); }
__device__ __forceinline__ float bf_lo(uint32_t v) { return __uint_as_float(v << 16); }
__device__ __forceinline__ float bf_hi(uint32_t v) { return __uint_as_float(v & 0xffff0000u); }
__device__ __forceinline__ float bf_round(float x) { return bf_lo(pack2(x, 0.f)); }
__device__ __forceinline__ float ex2(float x) { float r; asm("ex2.approx.ftz.f32 %0, %1;" : "=f"(r) : "f"(x)); return r; }
__device__ __forceinline__ float phi(float t, float l2e = 1.44269504089f) {
  float e = ex2(t * l2e) + 1e-6f;
  asm("{\n.reg .pred p;\nsetp.gt.f32 p, %1, 0f00000000;\n@p add.f32 %0, %1, 0f3F800008;\n}" : "+f"(e) : "f"(t));
  return e;
}
__device__ __forceinline__ void wg_fence() { asm volatile("wgmma.fence.sync.aligned;" ::: "memory"); }
__device__ __forceinline__ void wg_commit() { asm volatile("wgmma.commit_group.sync.aligned;" ::: "memory"); }
template <int N> __device__ __forceinline__ void wg_wait() { asm volatile("wgmma.wait_group.sync.aligned %0;" :: "n"(N) : "memory"); }
template <int N> __device__ __forceinline__ void pin(float* a) {
  #pragma unroll
  for (int i = 0; i < N; i++) asm volatile("" : "+f"(a[i]) :: "memory");
}
__device__ __forceinline__ int rtid() { int t; asm volatile("mov.u32 %0, %%tid.x;" : "=r"(t)); return t; }
__device__ __forceinline__ int opaque(int v) { asm volatile("" : "+r"(v)); return v; }
template <int N> __device__ __forceinline__ void zero(float* a) {
  #pragma unroll
  for (int i = 0; i < N; i++) asm volatile("mov.b32 %0, 0;" : "=f"(a[i]));
}
template <int N> __device__ __forceinline__ void pinu(uint32_t* a) {
  #pragma unroll
  for (int i = 0; i < N; i++) asm volatile("" : "+r"(a[i]) :: "memory");
}
__device__ __forceinline__ void cexp_t(float lg2mag, float turns, float& re, float& im) {
  float m = ex2(lg2mag);
  float fr = (turns - __fadd_rn(__fadd_rn(turns, 12582912.f), -12582912.f)) * 6.283185307f;
  re = m * __cosf(fr); im = m * __sinf(fr);
}
__device__ __forceinline__ void cmul(float ar, float ai, float br, float bi, float& cr, float& ci) {
  cr = fmaf(ar, br, -ai * bi); ci = fmaf(ar, bi, ai * br);
}

__device__ __forceinline__ void wg_ss48_tt(float* d, uint64_t da, uint64_t db, int scale_d) {
  asm volatile("{\n.reg .pred p;\nsetp.ne.b32 p, %26, 0;\n"
    "wgmma.mma_async.sync.aligned.m64n48k16.f32.bf16.bf16 "
    "{%0, %1, %2, %3, %4, %5, %6, %7, %8, %9, %10, %11, %12, %13, %14, %15, %16, %17, %18, %19, %20, %21, %22, %23}, %24, %25, p, 1, 1, 1, 1;\n}\n"
    : "+f"(d[0]), "+f"(d[1]), "+f"(d[2]), "+f"(d[3]), "+f"(d[4]), "+f"(d[5]), "+f"(d[6]), "+f"(d[7]), "+f"(d[8]), "+f"(d[9]), "+f"(d[10]), "+f"(d[11]), "+f"(d[12]), "+f"(d[13]), "+f"(d[14]), "+f"(d[15]), "+f"(d[16]), "+f"(d[17]), "+f"(d[18]), "+f"(d[19]), "+f"(d[20]), "+f"(d[21]), "+f"(d[22]), "+f"(d[23])
    : "l"(da), "l"(db), "r"(scale_d));
}
__device__ __forceinline__ void wg_rs88_tb(float* d, const uint32_t* a, uint64_t db, int scale_d) {
  asm volatile("{\n.reg .pred p;\nsetp.ne.b32 p, %49, 0;\n"
    "wgmma.mma_async.sync.aligned.m64n88k16.f32.bf16.bf16 "
    "{%0, %1, %2, %3, %4, %5, %6, %7, %8, %9, %10, %11, %12, %13, %14, %15, %16, %17, %18, %19, %20, %21, %22, %23, %24, %25, %26, %27, %28, %29, %30, %31, %32, %33, %34, %35, %36, %37, %38, %39, %40, %41, %42, %43}, {%44, %45, %46, %47}, %48, p, 1, 1, 1;\n}\n"
    : "+f"(d[0]), "+f"(d[1]), "+f"(d[2]), "+f"(d[3]), "+f"(d[4]), "+f"(d[5]), "+f"(d[6]), "+f"(d[7]), "+f"(d[8]), "+f"(d[9]), "+f"(d[10]), "+f"(d[11]), "+f"(d[12]), "+f"(d[13]), "+f"(d[14]), "+f"(d[15]), "+f"(d[16]), "+f"(d[17]), "+f"(d[18]), "+f"(d[19]), "+f"(d[20]), "+f"(d[21]), "+f"(d[22]), "+f"(d[23]), "+f"(d[24]), "+f"(d[25]), "+f"(d[26]), "+f"(d[27]), "+f"(d[28]), "+f"(d[29]), "+f"(d[30]), "+f"(d[31]), "+f"(d[32]), "+f"(d[33]), "+f"(d[34]), "+f"(d[35]), "+f"(d[36]), "+f"(d[37]), "+f"(d[38]), "+f"(d[39]), "+f"(d[40]), "+f"(d[41]), "+f"(d[42]), "+f"(d[43])
    : "r"(a[0]), "r"(a[1]), "r"(a[2]), "r"(a[3]), "l"(db), "r"(scale_d));
}
__device__ __forceinline__ void wg_ss80_tb(float* d, uint64_t da, uint64_t db, int scale_d) {
  asm volatile("{\n.reg .pred p;\nsetp.ne.b32 p, %42, 0;\n"
    "wgmma.mma_async.sync.aligned.m64n80k16.f32.bf16.bf16 "
    "{%0, %1, %2, %3, %4, %5, %6, %7, %8, %9, %10, %11, %12, %13, %14, %15, %16, %17, %18, %19, %20, %21, %22, %23, %24, %25, %26, %27, %28, %29, %30, %31, %32, %33, %34, %35, %36, %37, %38, %39}, %40, %41, p, 1, 1, 0, 1;\n}\n"
    : "+f"(d[0]), "+f"(d[1]), "+f"(d[2]), "+f"(d[3]), "+f"(d[4]), "+f"(d[5]), "+f"(d[6]), "+f"(d[7]), "+f"(d[8]), "+f"(d[9]), "+f"(d[10]), "+f"(d[11]), "+f"(d[12]), "+f"(d[13]), "+f"(d[14]), "+f"(d[15]), "+f"(d[16]), "+f"(d[17]), "+f"(d[18]), "+f"(d[19]), "+f"(d[20]), "+f"(d[21]), "+f"(d[22]), "+f"(d[23]), "+f"(d[24]), "+f"(d[25]), "+f"(d[26]), "+f"(d[27]), "+f"(d[28]), "+f"(d[29]), "+f"(d[30]), "+f"(d[31]), "+f"(d[32]), "+f"(d[33]), "+f"(d[34]), "+f"(d[35]), "+f"(d[36]), "+f"(d[37]), "+f"(d[38]), "+f"(d[39])
    : "l"(da), "l"(db), "r"(scale_d));
}
__device__ __forceinline__ void wg_ss48_tt_h(float* d, uint64_t da, uint64_t db, int scale_d) {
  asm volatile("{\n.reg .pred p;\nsetp.ne.b32 p, %26, 0;\n"
    "wgmma.mma_async.sync.aligned.m64n48k16.f32.f16.f16 "
    "{%0, %1, %2, %3, %4, %5, %6, %7, %8, %9, %10, %11, %12, %13, %14, %15, %16, %17, %18, %19, %20, %21, %22, %23}, %24, %25, p, 1, 1, 1, 1;\n}\n"
    : "+f"(d[0]), "+f"(d[1]), "+f"(d[2]), "+f"(d[3]), "+f"(d[4]), "+f"(d[5]), "+f"(d[6]), "+f"(d[7]), "+f"(d[8]), "+f"(d[9]), "+f"(d[10]), "+f"(d[11]), "+f"(d[12]), "+f"(d[13]), "+f"(d[14]), "+f"(d[15]), "+f"(d[16]), "+f"(d[17]), "+f"(d[18]), "+f"(d[19]), "+f"(d[20]), "+f"(d[21]), "+f"(d[22]), "+f"(d[23])
    : "l"(da), "l"(db), "r"(scale_d));
}
__device__ __forceinline__ void wg_rs192_tb(float* d, const uint32_t* a, uint64_t db, int scale_d) {
  asm volatile("{\n.reg .pred p;\nsetp.ne.b32 p, %101, 0;\n"
    "wgmma.mma_async.sync.aligned.m64n192k16.f32.bf16.bf16 "
    "{%0, %1, %2, %3, %4, %5, %6, %7, %8, %9, %10, %11, %12, %13, %14, %15, %16, %17, %18, %19, %20, %21, %22, %23, %24, %25, %26, %27, %28, %29, %30, %31, %32, %33, %34, %35, %36, %37, %38, %39, %40, %41, %42, %43, %44, %45, %46, %47, %48, %49, %50, %51, %52, %53, %54, %55, %56, %57, %58, %59, %60, %61, %62, %63, %64, %65, %66, %67, %68, %69, %70, %71, %72, %73, %74, %75, %76, %77, %78, %79, %80, %81, %82, %83, %84, %85, %86, %87, %88, %89, %90, %91, %92, %93, %94, %95}, {%96, %97, %98, %99}, %100, p, 1, 1, 1;\n}\n"
    : "+f"(d[0]), "+f"(d[1]), "+f"(d[2]), "+f"(d[3]), "+f"(d[4]), "+f"(d[5]), "+f"(d[6]), "+f"(d[7]), "+f"(d[8]), "+f"(d[9]), "+f"(d[10]), "+f"(d[11]), "+f"(d[12]), "+f"(d[13]), "+f"(d[14]), "+f"(d[15]), "+f"(d[16]), "+f"(d[17]), "+f"(d[18]), "+f"(d[19]), "+f"(d[20]), "+f"(d[21]), "+f"(d[22]), "+f"(d[23]), "+f"(d[24]), "+f"(d[25]), "+f"(d[26]), "+f"(d[27]), "+f"(d[28]), "+f"(d[29]), "+f"(d[30]), "+f"(d[31]), "+f"(d[32]), "+f"(d[33]), "+f"(d[34]), "+f"(d[35]), "+f"(d[36]), "+f"(d[37]), "+f"(d[38]), "+f"(d[39]), "+f"(d[40]), "+f"(d[41]), "+f"(d[42]), "+f"(d[43]), "+f"(d[44]), "+f"(d[45]), "+f"(d[46]), "+f"(d[47]), "+f"(d[48]), "+f"(d[49]), "+f"(d[50]), "+f"(d[51]), "+f"(d[52]), "+f"(d[53]), "+f"(d[54]), "+f"(d[55]), "+f"(d[56]), "+f"(d[57]), "+f"(d[58]), "+f"(d[59]), "+f"(d[60]), "+f"(d[61]), "+f"(d[62]), "+f"(d[63]), "+f"(d[64]), "+f"(d[65]), "+f"(d[66]), "+f"(d[67]), "+f"(d[68]), "+f"(d[69]), "+f"(d[70]), "+f"(d[71]), "+f"(d[72]), "+f"(d[73]), "+f"(d[74]), "+f"(d[75]), "+f"(d[76]), "+f"(d[77]), "+f"(d[78]), "+f"(d[79]), "+f"(d[80]), "+f"(d[81]), "+f"(d[82]), "+f"(d[83]), "+f"(d[84]), "+f"(d[85]), "+f"(d[86]), "+f"(d[87]), "+f"(d[88]), "+f"(d[89]), "+f"(d[90]), "+f"(d[91]), "+f"(d[92]), "+f"(d[93]), "+f"(d[94]), "+f"(d[95])
    : "r"(a[0]), "r"(a[1]), "r"(a[2]), "r"(a[3]), "l"(db), "r"(scale_d));
}
__device__ __forceinline__ void wg_rs48_tb(float* d, const uint32_t* a, uint64_t db, int scale_d) {
  asm volatile("{\n.reg .pred p;\nsetp.ne.b32 p, %29, 0;\n"
    "wgmma.mma_async.sync.aligned.m64n48k16.f32.bf16.bf16 "
    "{%0, %1, %2, %3, %4, %5, %6, %7, %8, %9, %10, %11, %12, %13, %14, %15, %16, %17, %18, %19, %20, %21, %22, %23}, {%24, %25, %26, %27}, %28, p, 1, 1, 1;\n}\n"
    : "+f"(d[0]), "+f"(d[1]), "+f"(d[2]), "+f"(d[3]), "+f"(d[4]), "+f"(d[5]), "+f"(d[6]), "+f"(d[7]), "+f"(d[8]), "+f"(d[9]), "+f"(d[10]), "+f"(d[11]), "+f"(d[12]), "+f"(d[13]), "+f"(d[14]), "+f"(d[15]), "+f"(d[16]), "+f"(d[17]), "+f"(d[18]), "+f"(d[19]), "+f"(d[20]), "+f"(d[21]), "+f"(d[22]), "+f"(d[23])
    : "r"(a[0]), "r"(a[1]), "r"(a[2]), "r"(a[3]), "l"(db), "r"(scale_d));
}

struct Params {
  const __nv_bfloat16 *par[4], *logdt, *dskip, *u, *wo;
  CUtensorMap m[M_COUNT];
};

#define CHUNK(i) ((i) == 0 ? c : ((i) == 7 ? (c ^ 1) : (((c & 6) + 1 + (i)) & 7)))
#define FLAG(kind, rr, cc) (&g_flag[((kind) * 128 + (rr) * 8 + (cc)) * 32])
#define SLOT(i) ((i) == 0 || (i) == 1 ? OFF_EXTRA : OFF_BLK - 256 + ((i) == 7 ? 0 : (i) - 2) * BLK)
__device__ __forceinline__ void load_quad(uint32_t* A, uint32_t addr) {
  A[0] = lds32v(addr); A[1] = lds32v(addr + 32); A[2] = lds32v(addr - 32); A[3] = lds32v(addr);
}

__device__ __forceinline__ bool y_transpose(uint32_t sb, int w5, int lane, uint32_t ytag) {
  const int mi = lane >> 3, rw = lane & 7;
  const uint32_t sa = sb + OFF_EXTRA + (w5 * 16 + rw) * 128 + ((mi ^ rw) << 4), da = sb + SLOT(3) + (8 * mi + rw) * 160 + w5 * 32;
  const uint32_t ym = lane < 4 ? 0x10001u : 0u;
  bar_sync(7, 160);
  uint32_t v[8][4], bad = 0;
  #pragma unroll
  for (int q = 0; q < 8; q++) ldsm4t(v[q], (sa ^ ((q & 1) * 64 + ((q >> 1) & 1) * 16)) + ((q >> 1) & 1) * 10240 + (q >> 2) * 1024);
  #pragma unroll
  for (int q = 0; q < 8; q++) {
    bad |= (v[q][0] ^ ytag) | (v[q][2] ^ ytag);
    stsm4(da + (q & 3) * 5120 + (q >> 2) * 16, v[q][0] & ~ym, v[q][1], v[q][2] & ~ym, v[q][3]);
  }
  fence_async();
  uint32_t any;
  asm volatile("{\n.reg .pred p;\nsetp.ne.u32 p, %1, 0;\nbarrier.red.or.pred p, 7, 160, p;\nselp.u32 %0, 1, 0, p;\n}" : "=r"(any) : "r"(bad & ym) : "memory");
  return any;
}

__global__ void __launch_bounds__(512, 1) fused_kernel(const __grid_constant__ Params prm) {
  extern __shared__ unsigned char smem_raw[];
  const uint32_t sb = __shfl_sync(0xffffffff, smem_u32(smem_raw), 0);
  const int tid = threadIdx.x, lane = tid & 31;
  const int warp = __shfl_sync(0xffffffff, tid >> 5, 0), wg = warp >> 2, w4 = warp & 3;
  const int cta = blockIdx.x, r = cta >> 3, c = cta & 7;
  if ((sb & 0xffffffu) != SB0) return;
#define BAR(i) (sb + OFF_BAR + 8 * (i))
  const bool sw64 = ((c + 1) & 2) != 0;

  const CUtensorMap* mwp = &prm.m[sw64 ? M_W64 : M_W128];
  const int mcol = (c * 80 + (c & 1) * 16) >> (sw64 ? 5 : 6), rcol = c * 80 + ((c & 1) ? 0 : 64);
  if (warp == 12 && elect_one()) {
    #pragma unroll
    for (int i = 0; i < 5; i++) mbar_init(BAR(BR_FULL + i), 1);
    asm volatile("fence.mbarrier_init.release.cluster;" ::: "memory");
    if (EN_ATT) {
      mbar_expect_tx(BAR(BR_FULL), W_SLOT + 16384);
      tma4d(sb, mwp, BAR(BR_FULL), 0, 0, mcol, 0);
      tma2d(sb + OFF_X, &prm.m[M_X], BAR(BR_FULL), 0, r * 128);
      tma3d(sb + 12288, &prm.m[M_WR], BAR(BR_FULL), rcol, 0, 0);
      mbar_expect_tx(BAR(BR_FULL + 1), W_SLOT);
      tma4d(sb + W_SLOT, mwp, BAR(BR_FULL + 1), 0, 32, mcol, 0);
      tma3d(sb + W_SLOT + 12288, &prm.m[M_WR], BAR(BR_FULL + 1), rcol, 32, 0);
      TS(24);
    }
  }
  if (warp == 13 && elect_one()) {
    asm volatile("prefetch.tensormap [%0];" :: "l"(&prm.m[M_X]) : "memory");
    asm volatile("prefetch.tensormap [%0];" :: "l"(&prm.m[M_WR]) : "memory");
  }
  if (wg == 3) {
    asm volatile("setmaxnreg.dec.sync.aligned.u32 56;");
    const int tid = rtid(), lane = tid & 31;
    if (warp == 12) {
      asm volatile("bar.arrive 0, 512;" ::: "memory");
      {
        uint32_t s = 2, ph = 1, xs = 16384;
        #pragma unroll 1
        for (int kb = 2; kb < 20; kb++) {
          if (kb == 4) bar_sync(6, 128);
          if (kb >= 5) mbar_wait(BAR(BR_EMPTY) + 8 * s, ph);
          if (EN_ATT && elect_one()) {
            const uint32_t st = sb + s * W_SLOT, fb = BAR(BR_FULL) + 8 * s;
            mbar_expect_tx(fb, (kb & 1) ? W_SLOT : W_SLOT + 16384);
            if (!(kb & 1)) tma2d(sb + OFF_X + xs, &prm.m[M_X], fb, kb * 32, r * 128);
            tma4d(st, mwp, fb, 0, kb * 32, mcol, 0);
            tma3d(st + 12288, &prm.m[M_WR], fb, rcol, kb * 32, 0);
          }
          if (kb < 4 && lane == 0) TS(24 + kb);
          if (UPF && kb >= UKB - 4 && kb < UKB && elect_one())
            asm volatile("cp.async.bulk.prefetch.L2.global [%0], 5120;" :: "l"(prm.u + cta * 10240 + (kb - (UKB - 4)) * 2560) : "memory");
          if (EN_SSM && kb == (EN_ATT ? UKB : 4) && elect_one()) { mbar_expect_tx(BAR(BR_UIN), 20480); tma2d(sb + OFF_UT, &prm.m[M_U], BAR(BR_UIN), c * 80, r * 128); }
          if (kb == 14 && elect_one()) asm volatile("cp.async.bulk.prefetch.L2.global [%0], 6400;" :: "l"(prm.wo + cta * 3200) : "memory");
          if (!EN_ATT && kb == 4) break;
          if (++s == 5) { s = 0; ph ^= 1; }
          if (kb & 1) { xs += 16384; if (xs == 49152) xs = 0; }
        }
      }
      if (EN_ATT) {
      mbar_wait(BAR(BR_EPOCH), 0);
      const unsigned epoch = lds32(sb + OFF_EPOCH);
      const unsigned* fo = FLAG(3, r, lane & 7);
      unsigned seen = __ballot_sync(0xffffffff, ld_rlx(lane < 16 ? fo : FLAG(0, lane & 15, c)) == epoch) & 0xffu;
      mbar_wait(BAR(BR_GEMM), 0);
      if (elect_one()) {
        mbar_expect_tx(BAR(BR_WO), 10240);
        tma2d(sb, &prm.m[M_WO], BAR(BR_WO), c * 64, c * 80);
        mbar_expect_tx(BAR(BR_KVP), 61440);
        mbar_expect_tx(BAR(BR_WO + 1), 7 * 10240);
      }
      {
        uint32_t ds = sb + OFF_WOR + (lane >> 3) * 128 + (((lane & 7) ^ (lane >> 3)) << 4);
        #pragma unroll 1
        for (int h = 0; h < 2; h++) {
          const int i = (lane & 6) + h;
          const char* gs = reinterpret_cast<const char*>(prm.wo) + (size_t)((lane >> 3) + CHUNK(i) * 80) * 1280 + 1024 + c * 32 + (lane & 1) * 16;
          #pragma unroll 2
          for (int q = 0; q < 20; q++) {
            asm volatile("cp.async.cg.shared.global [%0], [%1], 16;" :: "r"(ds), "l"(gs) : "memory");
            ds = (ds + 512) ^ 64; gs += 5120;
          }
        }
      }
      mbar_wait(BAR(BR_PUB), 0);
      poll_all(FLAG(0, lane & 15, c), epoch);
      if (elect_one()) { TS(23); bulk_ld(sb + OFF_KVP, &g_kvp[c * 16 * 240], 61440, BAR(BR_KVP)); }
      asm volatile("cp.async.wait_all;" ::: "memory");
      fence_async();
      mbar_arrive(BAR(BR_WO));
      mbar_wait(BAR(BR_SUM), 0);
      if (elect_one()) {
        #pragma unroll 1
        for (int i = 1; i < 8; i++) tma2d(sb + i * 10240, &prm.m[M_WO], BAR(BR_WO + 1), c * 64, CHUNK(i) * 80);
      }
      mbar_wait(BAR(BR_OSTG), 0);
      if (elect_one()) {
        bulk_st(&g_o[cta * 1280], sb + OFF_EXTRA, 20480);
        bulk_commit();
        bulk_wait0();
        st_rlx(FLAG(3, r, c), epoch);
        TS(20);
      }
      __syncwarp();
      #pragma unroll 1
      for (int i = 1; i < 8; i++) {
        const int src = CHUNK(i);
        if (!((seen >> src) & 1)) seen = poll_bit(fo, epoch, 1u << src);
        if (i == 1 || i == 7) mbar_wait(BAR(BR_OEMPTY) + 8 * (i & 2), 0);
        if (EN_SSM && (i == 2 || i == 6)) mbar_wait(BAR(BR_FREE) + 2 * (i & 4), 0);
        if (elect_one()) {
          mbar_expect_tx(BAR(BR_OFULL) + 8 * i, 20480);
          bulk_ld(sb + SLOT(i), &g_o[(r * 8 + src) * 1280], 20480, BAR(BR_OFULL) + 8 * i);
          if (i == 1) TS(21);
          if (i == 7) TS(22);
        }
        __syncwarp();
      }
      if (lane == 0) { DUMP(20, 30); }
      }
    } else {
      const int hw = warp - 13, ht = tid - 416;
      if (hw == 2 && elect_one()) {
        #pragma unroll
        for (int i = 5; i < BR_COUNT; i++) mbar_init(BAR(i), i == BR_WO ? 33 : i < BR_EMPTY ? 1 : i < BR_OEMPTY ? 2 : i < BR_Y ? 8 : i < BR_OSTG ? 4 : i == BR_OSTG ? 8 : i < BR_U2 ? 3 : 1);
        asm volatile("fence.mbarrier_init.release.cluster;" ::: "memory");
      }
      __syncwarp();
      asm volatile("bar.arrive 0, 512;" ::: "memory");
      if (EN_SSM && hw == 2) asm volatile("bar.arrive 8, 160;" ::: "memory");
      const unsigned epoch = hw == 0 ? ld_rlx(&g_epoch[cta]) + 1 : 0;
      bar_sync(5, 96);
      asm volatile("bar.arrive 6, 128;" ::: "memory");
      if (hw == 1 && elect_one()) {
        #pragma unroll
        for (int i = M_U; i < M_COUNT; i++) asm volatile("prefetch.tensormap [%0];" :: "l"(&prm.m[i]) : "memory");
      }
      if (ht == 0) {
        st_rlx(&g_epoch[cta], epoch);
        sts32(sb + OFF_EPOCH, epoch);
        mbar_arrive(BAR(BR_EPOCH));
      }
      if (EN_SSM) {
      const int mi = lane >> 3, rw = lane & 7, ch0 = c * 80 + r * 5;
      mbar_wait(BAR(BR_UIN), 0);
      if (ht == 0) TS(36);
      #pragma unroll 1
      for (int h = 0; h < 2; h++) {
        const uint32_t sa = sb + OFF_UT + h * 10240 + (8 * mi + rw) * 160 + hw * 16, da = sb + OFF_UT + h * 10240 + (hw * 8 + rw) * 128 + ((mi ^ rw ^ h) << 4);
        uint32_t v[8][4];
        #pragma unroll
        for (int q = 0; q < 8; q++) if (q < 6 || hw == 0) ldsm4t(v[q], sa + (q & 1) * 5120 + (q >> 1) * 48);
        bar_sync(5, 96);
        #pragma unroll
        for (int q = 0; q < 8; q++) if (q < 6 || hw == 0) stsm4((da ^ ((q & 1) * 64)) + (q >> 1) * 3072, v[q][0], v[q][1], v[q][2], v[q][3]);
      }
      fence_async();
      bar_sync(5, 96);
      if (hw == 0) {
        if (elect_one()) {
          tma2d_st(&prm.m[M_SA], sb + OFF_UT, r * 128, c * 80);
          tma2d_st(&prm.m[M_SA], sb + OFF_UT + 10240, r * 128 + 64, c * 80);
          bulk_commit(); bulk_wait0_read();
          mbar_arrive(BAR(BR_UOUT));
          TS(37);
          bulk_wait0();
          st_rel(FLAG(1, r, c), epoch);
          TS(30);
        }
        __syncwarp();
        poll_all_acq(FLAG(1, lane & 15, c), epoch);
      }
      #pragma unroll 1
      for (int k = 0; k < 5; k++) {
        if (k == 0 || k == 3) {
          const int p = k != 0;
          if (hw == 0) {
            if (!p) {
              if (elect_one()) {
                fence_async_g();
                mbar_expect_tx(BAR(BR_U), 12288);
                #pragma unroll 1
                for (int q = 0; q < 3; q++) bulk_ld(sb + OFF_BLK + q * q * BLK, g_uy + (ch0 + q * q) * 2048, 4096, BAR(BR_U));
                TS(31);
              }
              __syncwarp();
            }
            mbar_wait(BAR(p ? BR_U2 : BR_U), 0);
          }
          bar_sync(5, 96);
          if (ht == 0) TS(38 + p);
        }
        const int l3 = (hw + k) % 3 * 32 + lane;
        const uint32_t blk = sb + OFF_BLK + ((0x32410 >> (4 * k)) & 7) * BLK, o = blk + B_D + l3 * 16;
        float P[34];
        P[0] = 0.f;
        #pragma unroll
        for (int q = 0; q < 5; q++) {
          const int ch = 2 * l3 - 3 + q;
          uint32_t v[4];
          lds128(v, blk + (uint32_t)((ch * 16) ^ ((ch * 2) & 0x10)));
          #pragma unroll
          for (int e = 0; e < 8; e++) {
            const int i = 8 * q + e - 4;
            if (i >= 0 && i < 33) P[i + 1] = P[i] + ((e & 1) ? bf_hi(v[e >> 1]) : bf_lo(v[e >> 1]));
          }
        }
#define WIN(lo, hi, e) (P[21 + (e) - (lo)] - P[20 + (e) - (hi)])
#define WIN8(lo, hi, b) pack2(WIN(lo, hi, b), WIN(lo, hi, b + 1)), pack2(WIN(lo, hi, b + 2), WIN(lo, hi, b + 3)), pack2(WIN(lo, hi, b + 4), WIN(lo, hi, b + 5)), pack2(WIN(lo, hi, b + 6), WIN(lo, hi, b + 7))
        if (l3 < 64) {
          sts128(o + B_D9, WIN8(12, 20, 0)); sts128(o + B_D9 + 1024, WIN8(12, 20, 8));
          sts128(o + B_D7, WIN8(5, 11, 0)); sts128(o + B_D7 + 1024, WIN8(5, 11, 8));
        }
        sts128(o + B_D5, WIN8(6, 10, 0)); sts128(o + B_D5 + 1552, WIN8(6, 10, 8));
        sts128(o, WIN8(3, 5, 0)); sts128(o + 1552, WIN8(3, 5, 8));
        if (l3 < 2) sts128(blk + B_D + l3 * B_D5 + 1536, 0, 0, 0, 0);
      }
      __syncwarp();
      if (lane == 0) mbar_arrive(BAR(BR_DRDY + 1));
      if (ht == 0) TS(32);
      if (hw == 0) {
        #pragma unroll 1
        for (int p = 0; p < 2; p++) {
          mbar_wait(BAR(BR_Y) + 8 * p, 0);
          if (elect_one()) {
            #pragma unroll 1
            for (int k = 4 * p; k < 4 + p; k++) bulk_st(g_uy + (640 + ch0 + k) * 2048, sb + OFF_BLK + k * BLK, 4096);
            bulk_commit(); bulk_wait0_read();
            mbar_arrive(BAR(BR_FREE) + 8 * p);
          }
          __syncwarp();
        }
        if (elect_one()) { bulk_wait0(); st_rlx(FLAG(2, r, c), epoch); TS(33); }
        __syncwarp();
        poll_all(FLAG(2, lane & 15, c), epoch);
        if (EN_ATT) mbar_wait(BAR(BR_OEMPTY + 1), 0);
        #pragma unroll 1
        for (int n = 0; n < 64; n++) {
          if (elect_one()) {
            mbar_expect_tx(BAR(BR_YIN), 20480);
            tma2d(sb + OFF_EXTRA, &prm.m[M_SA], BAR(BR_YIN), r * 128, 640 + c * 80);
            tma2d(sb + OFF_EXTRA + 10240, &prm.m[M_SA], BAR(BR_YIN), r * 128 + 64, 640 + c * 80);
            TS(34);
          }
          __syncwarp();
          if (EN_ATT) mbar_wait(BAR(BR_OEMPTY + 3), 0);
          mbar_wait(BAR(BR_YIN), n & 1);
          if (!y_transpose(sb, 4, lane, (epoch & 1u) * 0x10001u)) break;
          FIXCNT
        }
      if (elect_one()) {
        tma2d_st(&prm.m[M_OUT], sb + SLOT(3), c * 80, r * 128);
        bulk_commit(); bulk_wait0_read();
        TS(35); DUMP(30, 40); DUMP(0, 1);
      }
      }
      }
    }
  } else if (wg < 2) {
    asm volatile("setmaxnreg.inc.sync.aligned.u32 160;");
    bar_sync(0, 512);
    if (EN_ATT) {
    float am[96], ar[24];
    {
      const bool lead = (rtid() & 127) == 0;
      constexpr uint64_t dr0 = mkdesc(SB0 + 12288, 1024, 256, 3);
      const uint64_t db0 = sw64 ? mkdesc(SB0, 2048, 512, 2) : mkdesc(SB0, 4096, 1024, 1);
      const uint32_t kst = sw64 ? 64 : 128, bh = db0 >> 32;
      uint32_t s = 0, ph = 0, xo = 0;
      const int ln = rtid() & 31;
      const uint32_t xa = sb + OFF_X + (warp * 16 + (ln & 15)) * 128 + (((ln >> 4) ^ (ln & 7)) << 4);
      uint32_t A[8];
      mbar_wait(BAR(BR_FULL), 0);
      if (lead && wg == 0) TS(1);
      ldsm4(A, xa); ldsm4(A + 4, xa);
      wg_fence();
      wg_rs48_tb(ar, A + 4, dr0, 0); wg_rs192_tb(am, A + 4, db0, 0);
      wg_commit();
      uint32_t xk = xa, eb = 0;
      #pragma unroll 1
      for (int kb = 0; kb < 20; kb++) {
        const uint32_t wo_ = s * (W_SLOT >> 4), bl = (uint32_t)db0 + wo_, rl = (uint32_t)dr0 + wo_;
        wg_fence();
        wg_rs48_tb(ar, A, desc2(rl, dr0 >> 32), kb != 0);
        wg_rs192_tb(am, A, desc2(bl, bh), kb != 0);
        wg_commit();
        wg_wait<1>();
        ldsm4(A + 4, xk ^ 32);
        if (lead && kb > 0 && kb < 16) mbar_arrive(eb);
        eb = BAR(BR_EMPTY) + 8 * s;
        wg_fence();
        wg_rs48_tb(ar, A + 4, desc2(rl + 32, dr0 >> 32), 1);
        wg_rs192_tb(am, A + 4, desc2(bl + kst, bh), 1);
        wg_commit();
        if (++s == 5) { s = 0; ph ^= 1; }
        if (kb & 1) { xo += 16384; if (xo == 49152) xo = 0; }
        if (kb < 19) mbar_wait(BAR(BR_FULL) + 8 * s, ph);
        xk = (xa + xo) ^ ((~kb & 1) * 64);
        wg_wait<1>();
        ldsm4(A, xk);
      }
      wg_wait<0>();
      pin<96>(am); pin<24>(ar);
    }
    const int tid = rtid(), lane = tid & 31, tq = lane & 3;
    if (tid == 0) TS(2);
#define QV(j, e) ((j) < 8 ? am[4 * (j) + (e)] : ar[4 * ((j) - 8) + (e)])
#define KV_(j, e) ((j) < 8 ? am[32 + 4 * (j) + (e)] : ar[8 + 4 * ((j) - 8) + (e)])
#define VV(j, e) ((j) < 8 ? am[64 + 4 * (j) + (e)] : ar[16 + 4 * ((j) - 8) + (e)])
    {
      bar_sync(1, 256);
      if (tid == 0) mbar_arrive(BAR(BR_GEMM));
      const uint32_t ro = sb + (uint32_t)((warp * 16 + (lane & 15)) * 16);
      const int l0 = 2 * (c & 1) + (lane >> 4);
      const uint32_t ones = (tq == 0) ? 0x00003f80u : 0u;
#define PV(j) pack2(VV(j, 0), VV(j, 1)), pack2(VV(j, 2), VV(j, 3))
#define PK(j) pack2(phi(KV_(j, 0)), phi(KV_(j, 1))), pack2(phi(KV_(j, 2)), phi(KV_(j, 3)))
      stsm4(ro + OFF_V + (5 + 6 * (lane >> 4)) * 2048, ones, ones, ones, ones);
      #pragma unroll
      for (int j = 0; j < 10; j += 2) {
        const int l = (j == 8 && (c & 1)) ? l0 - 2 : l0 + j;
        stsm4(ro + OFF_V + (l + (l >= 5)) * 2048, PV(j), PV(j + 1));
        stsm4(ro + OFF_PK + l * 2048, PK(j), PK(j + 1));
      }
    }
    fence_async();
    bar_sync(1, 256);
    if (tid == 0) TS(3);
    mbar_wait(BAR(BR_EPOCH), 0);
    const unsigned epoch = lds32(sb + OFF_EPOCH);
    {
      float kv[24]; zero<24>(kv);
      constexpr uint64_t da = mkdesc(SB0 + OFF_PK, 128, 2048, 0), db = mkdesc(SB0 + OFF_V, 128, 2048, 0);
      wg_fence();
      #pragma unroll
      for (int s = 0; s < 8; s++) wg_ss48_tt(kv, desc2((uint32_t)da + wg * 640 + s * 16, da >> 32), desc2((uint32_t)db + wg * 768 + s * 16, db >> 32), s != 0);
      wg_commit();
      wg_wait<0>();
      pin<24>(kv);
      if (tid == 0) TS(15);
      if (w4 < 3) {
        const uint32_t wb = sb + OFF_KVS + (wg * 3 + w4) * 1536 + (lane & 15) * 96;
        #pragma unroll
        for (int j = 0; j < 6; j += 2)
          stsm4(wb + (j + (lane >> 4)) * 16, pack2(kv[4 * j], kv[4 * j + 1]), pack2(kv[4 * j + 2], kv[4 * j + 3]),
                pack2(kv[4 * j + 4], kv[4 * j + 5]), pack2(kv[4 * j + 6], kv[4 * j + 7]));
        __syncwarp();
        const int dl = w4 * 16 + (lane & 15), hl = dl >= 20;
        if (dl < 40) {
          uint4* dst = &g_kvp[(c * 16 + r) * 240 + wg * 40 + dl];
          uint32_t v[4], z[4];
          lds128(v, wb + (3 * hl + (lane >> 4)) * 16);
          lds64(z, wb + 32 + 8 * hl); z[2] = lds32(wb + 80); z[3] = epoch & 1u;
          v[3] = (v[3] & ~1u) | z[3];
          st128_rlx(dst + (lane >> 4) * 80, v);
          if (lane < 16) st128_rlx(dst + 160, z);
        }
      }
    }
    fence_async();
    bar_sync(1, 256);
    if (tid == 0) { st_rlx(FLAG(0, r, c), epoch); mbar_arrive(BAR(BR_PUB)); TS(4); }
    const int kvi = (tid >= 80) + (tid >= 160) + (tid >= 240), kd = tid - 80 * kvi;
    const int khd = kd / 20, kt0 = 5 * (khd >> 1) + 2 * (khd & 1);
    const uint32_t rb = sb + OFF_KVB + kd * 16;
    if (kvi < 3) {
      #pragma unroll 1
      for (int m = kvi; m < 7; m += 3) { const int q = kt0 + 3 + m; sts128(rb + (q >= 10 ? q - 10 : q) * 1280, 0, 0, 0, 0); }
    }
    uint32_t qa[20];
    {
      const float sc = 1.44269504089f + __uint_as_float(lds32(sb + OFF_EPOCH) ^ epoch);
      #pragma unroll
      for (int j = 0; j < 10; j++) { qa[2 * j] = pack2(phi(QV(j, 0), sc), phi(QV(j, 1), sc)); qa[2 * j + 1] = pack2(phi(QV(j, 2), sc), phi(QV(j, 3), sc)); }
    }
    if (tid == 0) TS(5);
    if (warp == 7) mbar_wait(BAR(BR_KVP), 0);
    bar_sync(1, 256);
    if (tid == 0) TS(6);
    if (kvi < 3) {
      float s[8];
      zero<8>(s);
      uint32_t bad = 0;
      #pragma unroll 4
      for (int i = 0; i < 16; i++) {
        uint32_t w[4];
        lds128(w, sb + OFF_KVP + tid * 16 + i * 3840);
        bad |= w[3] ^ epoch;
        #pragma unroll
        for (int e = 0; e < 4; e++) { s[2 * e] += bf_lo(w[e]); s[2 * e + 1] += bf_hi(w[e]); }
      }
      if (__builtin_expect(bad & 1u, 0)) {
        zero<8>(s);
        #pragma unroll 1
        for (int i = 0; i < 16; i++) {
          uint32_t w[4] = {0, 0, 0, ~epoch};
          fix128_w3(w, &g_kvp[(c * 16 + i) * 240 + tid], epoch, 1u);
          #pragma unroll
          for (int e = 0; e < 4; e++) { s[2 * e] += bf_lo(w[e]); s[2 * e + 1] += bf_hi(w[e]); }
        }
        FIXCNT
      }
      const uint32_t p0 = pack2(s[0], s[1]), p1 = pack2(s[2], s[3]), p2 = pack2(s[4], s[5]), p3 = pack2(s[6], s[7]);
      if (kvi < 2) sts128(rb + (kt0 + (khd & 1) + kvi) * 1280, p0, p1, p2, p3);
      else {
        const bool od = khd & 1;
        sts128(rb + (5 * (khd >> 1) + 2) * 1280, od ? 0u : p0, od ? 0u : p1, od ? p0 : 0u, od ? p1 : 0u);
        const uint32_t zz = (p2 & 0xffffu) << (16 * (khd & 1));
        sts128(rb + 10 * 1280, khd < 2 ? zz : 0u, khd < 2 ? 0u : zz, 0u, 0u);
      }
    }
    fence_async();
    bar_sync(1, 256);
    if (tid == 0) { mbar_arrive(BAR(BR_SUM)); TS(7); }
    {
      float oa[44]; zero<44>(oa);
      constexpr uint64_t db = mkdesc(SB0 + OFF_KVB, 128, 1280, 0);
      wg_fence();
      #pragma unroll
      for (int s = 0; s < 5; s++) wg_rs88_tb(oa, &qa[4 * s], desc2((uint32_t)db + ((s == 4 && (c & 1)) ? 0 : (s + (c & 1)) * 16), db >> 32), s != 0);
      wg_commit();
      wg_wait<0>();
      pin<44>(oa);
      if (tid == 0) TS(13);
      float rc[4], rd[2][4];
      #pragma unroll
      for (int e = 0; e < 4; e++) asm("rcp.approx.ftz.f32 %0, %1;" : "=f"(rc[e]) : "f"(oa[40 + e] + 1e-6f));
      #pragma unroll
      for (int h = 0; h < 4; h++) {
        rd[0][h] = __shfl_sync(0xffffffff, rc[h & 1], (lane & 28) | (h >> 1));
        rd[1][h] = __shfl_sync(0xffffffff, rc[2 + (h & 1)], (lane & 28) | (h >> 1));
      }
      #pragma unroll
      for (int j = 0; j < 10; j++) {
        #pragma unroll
        for (int h = 0; h < 2; h++) {
          float f;
          if (j == 2) f = tq < 2 ? rd[h][0] : rd[h][1];
          else if (j == 7) f = tq < 2 ? rd[h][2] : rd[h][3];
          else f = rd[h][(8 * j) / 20];
          qa[2 * j + h] = pack2(oa[4 * j + 2 * h] * f, oa[4 * j + 2 * h + 1] * f);
        }
      }
      const uint32_t m0 = (lane & 7) == ((2 * w4) & 7), m1 = (lane & 7) == 2 * w4 + 1;
      const uint32_t oa_ = sb + OFF_EXTRA + (lane >> 4) * 2048 + (warp * 16 + (lane & 15)) * 16;
      bar_sync(1, 256);
#define TAG(v, m) (((v) & ~(m)) | (epoch & (m)))
      #pragma unroll
      for (int s = 0; s < 5; s++) stsm4(oa_ + s * 4096, TAG(qa[4 * s], m0), TAG(qa[4 * s + 1], m1), TAG(qa[4 * s + 2], m0), TAG(qa[4 * s + 3], m1));
    }
    fence_async();
    __syncwarp();
    if (lane == 0) mbar_arrive(BAR(BR_OSTG));
    if (tid == 0) TS(8);
    float oc[40]; zero<40>(oc);
    {
      constexpr uint64_t dw0 = mkdesc(SB0, OFF_WOR, 1024, 1), da0 = mkdesc(SB0, 2048, 128, 0);
      const uint32_t ck = sb + tid * 32 + ((lane >> 2) << 2), ck2 = ck + (wg ? 0 : 16384);
      uint32_t bad = 0;
      auto tile = [&](int i, uint32_t so) {
        const uint32_t al = (uint32_t)da0 + wg * 64 + (so >> 4), wl = (uint32_t)dw0 + i * 640 - (i >> 1) * (1278 << 16);
        wg_fence();
        #pragma unroll
        for (int s = 0; s < 5; s++) wg_ss80_tb(oc, desc2(al + s * 256, da0 >> 32), desc2(wl + s * 128, dw0 >> 32), (i | s) != 0);
        wg_commit();
        bad |= (lds32(ck + so) ^ epoch) | (lds32(ck + so + 8192) ^ epoch) | (lds32(ck2 + so) ^ epoch);
      };
      mbar_wait(BAR(BR_WO), 0);
      mbar_wait(BAR(BR_OSTG), 0);
      tile(0, SLOT(0));
      mbar_wait(BAR(BR_WO + 1), 0);
      #pragma unroll 1
      for (int i = 1; i < 8; i++) {
        if (i == 1) {
          wg_wait<0>();
          if (lane == 0) mbar_arrive(BAR(BR_OEMPTY));
          if (EN_SSM && w4 == 0) mbar_wait(BAR(BR_Y + 1), 0);
          if (w4 == 0) mbar_wait(BAR(BR_OFULL + 1), 0);
          bar_sync(2 + wg, 128);
        }
        mbar_wait(BAR(BR_OFULL) + 8 * i, 0);
        if (i == 1 && tid == 0) TS(9);
        tile(i, SLOT(i));
        wg_wait<1>();
        if (lane == 0 && i > 1) mbar_arrive(BAR(BR_OEMPTY - 1) + 8 * i);
      }
      #pragma unroll 1
      for (int n = 0; n < 56; n++) {
        const int i = n & 7;
        if (i == 0) {
          uint32_t any;
          asm volatile("{\n.reg .pred p;\nsetp.ne.u32 p, %1, 0;\nbarrier.red.or.pred p, 1, 256, p;\nselp.u32 %0, 1, 0, p;\n}" : "=r"(any) : "r"(bad & 1u) : "memory");
          if (!any) break;
          bad = 0;
          FIXCNT
        }
        wg_wait<0>();
        bar_sync(1, 256);
        if (tid == 0) { mbar_expect_tx(BAR(BR_RETRY), 20480); bulk_ld(sb + SLOT(6), &g_o[(r * 8 + CHUNK(i)) * 1280], 20480, BAR(BR_RETRY)); }
        mbar_wait(BAR(BR_RETRY), n & 1);
        tile(i, SLOT(6));
      }
      wg_wait<0>();
      pin<40>(oc);
    }
    if (tid == 0) TS(10);
    {
      const int row = w4 * 16 + (lane & 15);
      const uint32_t ob = sb + OFF_BLK + 2 * BLK + wg * 10240;
      #pragma unroll
      for (int j = 0; j < 8; j += 2)
        stsm4(ob + row * 128 + (((j + (lane >> 4)) ^ (row & 7)) << 4), pack2(oc[4 * j], oc[4 * j + 1]), pack2(oc[4 * j + 2], oc[4 * j + 3]),
              pack2(oc[4 * j + 4], oc[4 * j + 5]), pack2(oc[4 * j + 6], oc[4 * j + 7]));
      stsm4(ob + 8192 + row * 32 + (lane >> 4) * 16, pack2(oc[32], oc[33]), pack2(oc[34], oc[35]), pack2(oc[36], oc[37]), pack2(oc[38], oc[39]));
      fence_async();
      bar_sync(2 + wg, 128);
      if (w4 == 0 && elect_one()) {
        tma2d_st(&prm.m[M_O64], ob, 640 + c * 64, r * 128 + wg * 64);
        tma2d_st(&prm.m[M_O16], ob + 8192, 1152 + c * 16, r * 128 + wg * 64);
        bulk_commit(); bulk_wait0_read();
        if (wg == 0) { TS(11); DUMP(0, 20); }
      }
    }
    }
  } else {
    const int g = lane >> 2, tq = lane & 3, t7 = tid & 127;
    uint32_t raw[5][4], pd;
    {
      const int ch = c * 80 + r * 5;
      #pragma unroll
      for (int e = 0; e < 4; e++) {
        const __nv_bfloat16* pp = prm.par[e] + ch * 128 + t7;
        #pragma unroll
        for (int q = 0; q < 5; q++) asm volatile("ld.global.nc.u16 %0, [%1];" : "=r"(raw[q][e]) : "l"(pp + q * 128));
      }
      asm volatile("ld.global.nc.u16 %0, [%1];" : "=r"(pd) : "l"(((lane & 8) ? prm.dskip : prm.logdt) + ch + min(lane & 7, 4)));
    }
    asm volatile("setmaxnreg.inc.sync.aligned.u32 136;");
    asm volatile("bar.arrive 0, 512;" ::: "memory");
    if (EN_SSM) {
    {
      #pragma unroll 1
      for (int k = 0; k < 4; k++) {
        const uint32_t z = sb + OFF_BLK + k * BLK + t7 * 16;
        sts128(z + B_TBL, 0, 0, 0, 0); sts128(z + B_TBL + 2048, 0, 0, 0, 0);
      }
      if (t7 < 80) sts128(sb + OFF_BLK + (t7 >> 4) * BLK - 256 + (t7 & 15) * 16, 0, 0, 0, 0);
      const uint32_t ea = sb + OFF_BLK + (2 + (w4 & 1)) * BLK + (lane >> 4) * 7168 + ((lane >> 3) & 1) * 256 + (lane & 7) * 16 + (w4 >> 1) * 2048;
      constexpr uint64_t dE = mkdesc(SB0 + OFF_BLK + 2 * BLK, 128, 512, 0);
      const uint32_t xa = sb + OFF_BLK + 18560 + t7 * 8, xr_ = sb + OFF_BLK + 18560 + (t7 ^ 64) * 8;
      uint32_t pr[5][2];
      #pragma unroll
      for (int q = 0; q < 5; q++) {
        #pragma unroll
        for (int e = 0; e < 2; e++) pr[q][e] = raw[q][2 * e] | (raw[q][2 * e + 1] << 16);
        const uint32_t m = __reduce_max_sync(0xffffffff, max(raw[q][2] & 0x7fffu, raw[q][3] & 0x7fffu));
        if (lane == 0) sts32(sb + OFF_EPOCH + 64 + q * 16 + w4 * 4, m);
      }
      bar_sync(8, 160);
      if (t7 == 0) TS(40);
      const int j = (w4 & 1) * 16 + (w4 >> 1) * 8 + g, i2 = tq < 2 ? 64 * tq + j : 32 * (tq - 2) + j;
      const uint32_t e2 = B_TBL + 4 * (tq < 2 ? T_F3 + (((i2 - 1) & 1) ? 80 : 0) + ((i2 - 1) >> 1) + 16 : T_F2 + (i2 & 1) * 96 + (i2 >> 1));
      const uint32_t e1 = tq < 2 ? (i2 ? e2 - 64 : B_TBL + 4 * (T_F2 + 175)) : B_TBL + 4 * (i2 ? T_F2 + ((2 * i2 - 1) & 3) * 48 + ((2 * i2 - 1) >> 2) : 16 + 511);
      const uint32_t e0 = B_TBL + (16 + 8 * j + 2 * tq) * 4;
      #pragma unroll 1
      for (int it = 0; it < 5; it++) {
        const int k = it;
        const uint32_t blk = sb + OFF_BLK + k * BLK;
        float fac;
        {
          const int q = it;
          if (it == 4) {
            mbar_wait(BAR(BR_UOUT), 0);
            sts128(sb + OFF_UT + B_TBL + t7 * 16, 0, 0, 0, 0); sts128(sb + OFF_UT + B_TBL + 2048 + t7 * 16, 0, 0, 0, 0);
          }
          const uint32_t ga = ea + 4096 - (w4 >> 1) * 512;
#define PUT4(i, a, b, c_, d) sts128(((i) < 8 ? ea + ((i) >> 1) * 512 : ga + (((i) - 8) >> 1) * 512) + ((i) & 1) * 128, a, b, c_, d)
          const uint32_t pa0 = pr[0][0], pc0 = pr[0][1];
          const float dt = bf_round(expf(bf_lo(__shfl_sync(0xffffffff, pd, q))));
          #pragma unroll
          for (int e = 0; e < 2; e++) { pr[0][e] = pr[1][e]; pr[1][e] = pr[2][e]; pr[2][e] = pr[3][e]; pr[3][e] = pr[4][e]; }
          uint32_t mm[4];
          lds128(mm, sb + OFF_EPOCH + 64 + q * 16);
          const uint32_t ex = min(max(max(max(mm[0], mm[1]), max(mm[2], mm[3])) >> 7, 1u), 253u);
          const float sc = __uint_as_float((254u - ex) << 23);
          fac = 2.f * dt * __uint_as_float(ex << 23);
          const float lr = -bf_round(expf(bf_lo(pa0))) * dt * 1.44269504089f;
          const float tn = bf_hi(pa0) * dt * 0.15915494309f;
          float z1r, z1i, z2r, z2i, z4r, z4i, xr[8], xi[8], gr[8], gi[8], wr[9], wi[9];
          cexp_t(lr, -tn, z1r, z1i);
          cexp_t(lr * 8.f, tn * 8.f, xr[1], xi[1]);
          cexp_t(lr * 64.f, tn * 64.f, wr[0], wi[0]);
          xr[0] = 1.f; xi[0] = 0.f;
          cmul(xr[1], xi[1], xr[1], xi[1], xr[2], xi[2]); cmul(xr[2], xi[2], xr[1], xi[1], xr[3], xi[3]);
          cmul(xr[2], xi[2], xr[2], xi[2], xr[4], xi[4]);
          #pragma unroll
          for (int b = 1; b < 4; b++) cmul(xr[4], xi[4], xr[b], xi[b], xr[4 + b], xi[4 + b]);
          cmul(wr[0], wi[0], wr[0], wi[0], wr[1], wi[1]); cmul(wr[1], wi[1], wr[0], wi[0], wr[2], wi[2]);
          cmul(wr[1], wi[1], wr[1], wi[1], wr[3], wi[3]); cmul(wr[3], wi[3], wr[3], wi[3], wr[4], wi[4]);
          cmul(wr[4], wi[4], wr[3], wi[3], wr[5], wi[5]); cmul(wr[4], wi[4], wr[4], wi[4], wr[6], wi[6]);
          cmul(wr[6], wi[6], wr[4], wi[4], wr[7], wi[7]); cmul(wr[6], wi[6], wr[6], wi[6], wr[8], wi[8]);
          uint32_t R[4], I[4], PR[4], PI[4];
          #pragma unroll
          for (int b = 0; b < 4; b++) { R[b] = packh(xr[2 * b], xr[2 * b + 1]); I[b] = packh(xi[2 * b], xi[2 * b + 1]); }
          PUT4(0, R[0], R[1], R[2], R[3]); PUT4(1, I[0], I[1], I[2], I[3]);
          #pragma unroll
          for (int i = 0; i < 3; i++) {
            const uint32_t z = packh(wr[i], wi[i]);
            #pragma unroll
            for (int b = 0; b < 4; b++) hcm2(R[b], I[b], z, PR[b], PI[b]);
            PUT4(2 * i + 2, PR[0], PR[1], PR[2], PR[3]); PUT4(2 * i + 3, PI[0], PI[1], PI[2], PI[3]);
          }
          gr[0] = bf_lo(pc0) * sc; gi[0] = -bf_hi(pc0) * sc;
          cmul(z1r, z1i, z1r, z1i, z2r, z2i); cmul(z2r, z2i, z2r, z2i, z4r, z4i);
          cmul(gr[0], gi[0], z1r, z1i, gr[1], gi[1]);
          cmul(gr[0], gi[0], z2r, z2i, gr[2], gi[2]); cmul(gr[1], gi[1], z2r, z2i, gr[3], gi[3]);
          #pragma unroll
          for (int b = 0; b < 4; b++) cmul(gr[b], gi[b], z4r, z4i, gr[4 + b], gi[4 + b]);
          PUT4(8, packh(gr[0], gr[1]), packh(gr[2], gr[3]), packh(gr[4], gr[5]), packh(gr[6], gr[7]));
          PUT4(9, packh(gi[0], gi[1]), packh(gi[2], gi[3]), packh(gi[4], gi[5]), packh(gi[6], gi[7]));
          {
            const uint32_t z = packh(wr[3], -wi[3]), a4r = packh(gr[0], gr[4]), a4i = packh(gi[0], gi[4]);
            hcm2(packh(gr[0], gr[2]), packh(gi[0], gi[2]), z, PR[0], PI[0]);
            hcm2(packh(gr[4], gr[6]), packh(gi[4], gi[6]), z, PR[1], PI[1]);
            hcm2(a4r, a4i, packh(wr[4], -wi[4]), PR[2], PI[2]);
            hcm2(a4r, a4i, packh(wr[5], -wi[5]), PR[3], PI[3]);
            PUT4(10, PR[0], PR[1], PR[2], PR[3]); PUT4(11, PI[0], PI[1], PI[2], PI[3]);
            float hr, hi_;
            cmul(gr[0], gi[0], wr[3], -wi[3], hr, hi_);
            const uint32_t cr = packh(gr[0], hr), ci = packh(gi[0], hi_);
            #pragma unroll
            for (int i = 0; i < 3; i++) hcm2(cr, ci, packh(wr[6 + i], -wi[6 + i]), PR[i], PI[i]);
            PUT4(12, PR[0], PR[1], PR[2], 0u); PUT4(13, PI[0], PI[1], PI[2], 0u);
          }
          fence_async();
          bar_sync(4, 128);
        }
        float ka[24]; zero<24>(ka);
        wg_fence();
        #pragma unroll
        for (int s = 0; s < 8; s++) {
          const uint64_t d = dE + (s >> 2) * (BLK >> 4) + ((s >> 1) & 1) * 448 + (s & 1) * 16;
          wg_ss48_tt_h(ka, d, d + 256, s != 0);
        }
        wg_commit();
        const float dsk = bf_lo(__shfl_sync(0xffffffff, pd, 8 + it));
        wg_wait<0>();
        pin<24>(ka);
        float kk[6];
        const bool up = w4 >= 2;
        #pragma unroll
        for (int n = 0; n < 3; n++) {
          sts64f(xa + n * BLK, up ? ka[12 + 4 * n] : ka[4 * n + 2], up ? ka[13 + 4 * n] : ka[4 * n + 3]);
          kk[2 * n] = up ? ka[14 + 4 * n] : ka[4 * n]; kk[2 * n + 1] = up ? ka[15 + 4 * n] : ka[4 * n + 1];
        }
        bar_sync(4, 128);
          if (it == 4 && w4 == 0) {
            mbar_wait(BAR(BR_U), 0);
            if (elect_one()) {
              mbar_expect_tx(BAR(BR_U2), 8192);
              bulk_ld(blk - 2 * BLK, g_uy + (c * 80 + r * 5 + 2) * 2048, 4096, BAR(BR_U2)); bulk_ld(blk - BLK, g_uy + (c * 80 + r * 5 + 3) * 2048, 4096, BAR(BR_U2));
            }
            __syncwarp();
          }
        #pragma unroll
        for (int n = 0; n < 3; n++) {
          uint32_t o[2]; lds64(o, xr_ + n * BLK);
          kk[2 * n] = (kk[2 * n] + __uint_as_float(o[0])) * fac; kk[2 * n + 1] = (kk[2 * n + 1] + __uint_as_float(o[1])) * fac;
        }
        if (t7 == 0) kk[0] += dsk;
        {
          const uint32_t v = pack2(kk[1], kk[0]), vh = v >> 16;
          const uint32_t u = pack2(kk[2], kk[3]), w = pack2(kk[4], kk[5]), uu = pack2(kk[2], kk[2]), us = pack2(kk[3], kk[2]);
          const uint32_t x = tq < 2 ? w : u, xh = x >> 16;
          sts32(blk + e0 + 4, v); sts16(blk + e0, vh); sts16(blk + e0 + 10, v);
          sts16(blk + e1, x); sts16(blk + e1 + 6, x); sts16(blk + e2, xh); sts16(blk + e2 + 6, xh);
          if (tq < 2) {
            const uint32_t pb = blk + e0 + 1024 + 8 * tq;
            sts32(pb + 4, uu); sts32(pb + 8, us); sts16(pb + 14, us);
            if (i2) { sts16(pb - 4, u); sts32(pb, uu); }
          }
          if (i2 == 0) {
            const uint32_t tb = blk + B_TBL;
            if (tq == 0) { sts16(tb + (16 + 256) * 4, u); sts16(tb + (T_S + 3) * 4, w); sts32(tb + (T_S + 4) * 4, pack2(kk[4], kk[4])); sts16(tb + (T_S + 5) * 4 + 2, w); }
            else { sts32(tb + 528 * 4, uu); sts32(tb + 529 * 4, uu); sts32(tb + 530 * 4, uu); sts16(tb + 531 * 4 + 2, u); sts16(tb + (T_F3 + 80 + 63) * 4, w); }
          }
        }
        if (t7 == 0) TS(49 + it);
      }
    }
    if (t7 == 0) TS(41);
    mbar_wait(BAR(BR_U), 0);
    bar_sync(4, 128);
    if (EN_ATT) mbar_wait(BAR(BR_GEMM), 0);
    if (t7 == 0) TS(42);
    mbar_wait(BAR(BR_EPOCH), 0);
    const uint32_t ytag = (lds32(sb + OFF_EPOCH) & 1u) * 0x10001u, ym = lane < 4 ? 0x10001u : 0u;
    #pragma unroll 1
    for (int pass = 1; pass >= 0; pass--) {
      const int k = pass ? w4 : 4;
      if (k & 2) mbar_wait(BAR(BR_U2), 0);
      const uint32_t blk = sb + OFF_BLK + k * BLK, tb = blk + B_TBL + (uint32_t)((g - 2 * tq) * 4);
      float acc[16][4];
      zero<64>(&acc[0][0]);
      const int kl = 16 * (lane >> 4) + 2 * (lane & 7) + ((lane >> 3) & 1);
      {
        auto ubase = [&](int sh) { const int q = kl - 2 * sh; return blk + (uint32_t)((q * 16) ^ ((q * 2) & 0x10)); };
#define LDQ(A, sh) _Pragma("unroll") for (int m = 0; m < 4; m++) load_quad(A[m], tb + (16 + 16 * (sh) + 128 * m) * 4);
#define LDB(B, ub, h) _Pragma("unroll") for (int p = 0; p < 4; p++) ldsm4(B[p], (ub) + (4 * (h) + p) * 512);
#define MLO(A, B) _Pragma("unroll") for (int m = 0; m < 4; m++) _Pragma("unroll") for (int cc = 0; cc < 8; cc++) mma16816(acc[cc + m], A[m], &B[cc >> 1][(cc & 1) * 2]);
#define MHI(A, B) _Pragma("unroll") for (int m = 0; m < 4; m++) _Pragma("unroll") for (int cc = 0; cc < 8 - m; cc++) mma16816(acc[8 + cc + m], A[m], &B[cc >> 1][(cc & 1) * 2]);
        int p_ = pass ? 0 : w4;
        const int pe = pass ? 4 : w4 + 1;
        uint32_t A[4][4], A2[4][4], Bl[4][4], Bh[4][4];
        uint32_t ub = ubase(p_ + 4);
        LDQ(A, p_ + 4) LDB(Bl, ub, 0)
        #pragma unroll 1
        for (; p_ < pe; p_++) {
          LDB(Bh, ub, 1)
          MLO(A, Bl)
          ub = ubase(p_);
          LDQ(A2, p_) LDB(Bl, ub, 0)
          MHI(A, Bh)
          LDB(Bh, ub, 1)
          load_quad(A[0], tb + (16 + 512 + 16 * (p_ & 1)) * 4); load_quad(A[1], tb + (T_S + 16 * (p_ & 1)) * 4);
          MLO(A2, Bl)
          if (p_ < 2) {
            #pragma unroll
            for (int cc = 0; cc < 8; cc++) mma16816(acc[cc + 4], A[0], &Bl[cc >> 1][(cc & 1) * 2]);
            #pragma unroll
            for (int cc = 0; cc < 4; cc++) mma16816(acc[cc + 12], A[0], &Bh[cc >> 1][(cc & 1) * 2]);
            #pragma unroll
            for (int cc = 0; cc < 8; cc++) mma16816(acc[cc + 8], A[1], &Bl[cc >> 1][(cc & 1) * 2]);
          }
          const int pn = ((p_ + 1) & 3) + 4;
          ub = ubase(pn);
          LDQ(A, pn) LDB(Bl, ub, 0)
          MHI(A2, Bh)
        }
      }
      if (t7 == 0) TS(57 + 3 * pass);
      mbar_wait(BAR(BR_DRDY + 1), 0);
      {
        const int ih = (lane >> 3) & 1;
        const uint32_t dl = blk + B_D + (uint32_t)(((lane >> 4) * 8 + (lane & 7)) * 16);
        const uint32_t d0_ = dl + ih * 1552, d8_ = dl + (ih ? 0 : 1536), d3_ = dl + B_D7 + ih * 1024;
        auto cls2 = [&](uint32_t da, uint32_t ta) {
          uint32_t B[6][2], A[6][4];
          #pragma unroll
          for (int e = 0; e < 6; e++) { B[e][0] = lds32v(ta + (e + 4) * 32); B[e][1] = lds32v(ta + (e + 3) * 32); }
          #pragma unroll
          for (int kk = 0; kk < 6; kk++) ldsm4t(A[kk], da + kk * 256);
          #pragma unroll
          for (int e = 0; e < 6; e++)
            #pragma unroll
            for (int kk = 0; kk < 6; kk++) if (2 * kk + e + 4 < 16) mma16816(acc[2 * kk + e + 4], A[kk], B[e]);
        };
        auto cls3 = [&](uint32_t da, uint32_t ta) {
          uint32_t B[8][2], A[4][4];
          #pragma unroll
          for (int e = 0; e < 8; e++) { B[e][0] = lds32v(ta + (e + 8) * 32); B[e][1] = lds32v(ta + (e + 7) * 32); }
          #pragma unroll
          for (int kk = 0; kk < 4; kk++) ldsm4t(A[kk], da + kk * 256);
          #pragma unroll
          for (int kk = 0; kk < 4; kk++)
            #pragma unroll
            for (int e = 0; e < 8; e++) if (2 * kk + e + 8 < 16) mma16816(acc[2 * kk + e + 8], A[kk], B[e]);
        };
        if (pass) {
          #pragma unroll 1
          for (int a = 0; a < 2; a++) {
            cls2(d0_ + a * B_D5, tb + (T_F2 + 48 * a - 32) * 4);
            cls2(d8_ + a * B_D5, tb + (T_F2 + 48 * a + 64) * 4);
            cls3(d3_ + a * 2048, tb + (T_F3 + 80 * a - 64) * 4);
          }
        } else {
          cls2(((w4 & 2) ? d8_ : d0_) + (w4 & 1) * B_D5, tb + (T_F2 + 48 * w4 - 32) * 4);
          if (w4 >= 2) cls3(d3_ + (w4 - 2) * 2048, tb + (T_F3 + 80 * (w4 - 2) - 64) * 4);
        }
      }
      if (t7 == 0) TS(58 + 3 * pass);
      const uint32_t ya = blk + (uint32_t)((kl * 16) ^ ((kl * 2) & 0x10));
#define YTAG(v) (((v) & ~ym) | (ytag & ym))
#define STY(p) stsm4t(ya + (p) * 512, YTAG(pack2(acc[2 * (p)][0], acc[2 * (p)][1])), pack2(acc[2 * (p)][2], acc[2 * (p)][3]), \
                      YTAG(pack2(acc[2 * (p) + 1][0], acc[2 * (p) + 1][1])), pack2(acc[2 * (p) + 1][2], acc[2 * (p) + 1][3]))
      if (pass == 0) {
        const uint32_t xw = blk + 4096 + w4 * 4096 + lane * 16, xr = blk + 4096 + w4 * 1024 + lane * 16;
        #pragma unroll
        for (int h = 0; h < 2; h++) {
          bar_sync(4, 128);
          #pragma unroll
          for (int i = 0; i < 8; i++)
            sts128(xw + i * 512, __float_as_uint(acc[8 * h + i][0]), __float_as_uint(acc[8 * h + i][1]), __float_as_uint(acc[8 * h + i][2]), __float_as_uint(acc[8 * h + i][3]));
          bar_sync(4, 128);
          float y[8];
          #pragma unroll
          for (int i = 0; i < 8; i++) {
            uint32_t o[4]; lds128(o, xr + (i >> 1) * 4096 + (i & 1) * 512);
            #pragma unroll
            for (int e = 0; e < 4; e++) y[4 * (i & 1) + e] = i < 2 ? __uint_as_float(o[e]) : y[4 * (i & 1) + e] + __uint_as_float(o[e]);
          }
          stsm4t(ya + (4 * h + w4) * 512, YTAG(pack2(y[0], y[1])), pack2(y[2], y[3]), YTAG(pack2(y[4], y[5])), pack2(y[6], y[7]));
        }
      } else {
        __syncwarp();
        #pragma unroll
        for (int p = 0; p < 8; p++) STY(p);
      }
      if (t7 == 0 && !pass) TS(55);
      fence_async();
      __syncwarp();
      if (lane == 0) mbar_arrive(BAR(BR_Y + 1) - 8 * pass);
      if (t7 == 0) TS(59 + 3 * pass);
    }
    if (t7 == 0) DUMP(40, 64);
    #pragma unroll 1
    for (int n = 0; n < 64; n++) if (!y_transpose(sb, w4, lane, ytag)) break;
    }
  }
}

typedef CUresult (*EncFn)(CUtensorMap*, CUtensorMapDataType, cuuint32_t, void*, const cuuint64_t*, const cuuint64_t*, const cuuint32_t*,
                          const cuuint32_t*, CUtensorMapInterleave, CUtensorMapSwizzle, CUtensorMapL2promotion, CUtensorMapFloatOOBfill);
static void mkmap(EncFn enc, CUtensorMap* m, const void* base, int rank, const cuuint64_t* dims, const cuuint64_t* strides, const cuuint32_t* box, CUtensorMapSwizzle swz) {
  cuuint32_t es[5] = {1, 1, 1, 1, 1};
  enc(m, CU_TENSOR_MAP_DATA_TYPE_BFLOAT16, rank, const_cast<void*>(base), dims, strides, box, es, CU_TENSOR_MAP_INTERLEAVE_NONE, swz,
      CU_TENSOR_MAP_L2_PROMOTION_L2_128B, CU_TENSOR_MAP_FLOAT_OOB_FILL_NONE);
}

extern "C" void kernel_launch(void* const* d_in, const int* in_sizes, int n_in, void* d_out, int out_size) {
  void* fn = nullptr; cudaDriverEntryPointQueryResult qr;
  cudaGetDriverEntryPoint("cuTensorMapEncodeTiled", &fn, cudaEnableDefault, &qr);
  EncFn enc = (EncFn)fn;
  void* uy = nullptr; cudaGetSymbolAddress(&uy, g_uy);
  const cuuint64_t dx[2] = {640, 2048}, sx[1] = {1280};
  const cuuint32_t bx[2] = {64, 128}, bu[2] = {80, 128};
  const cuuint64_t dw[3] = {640, 640, 3}, sw[2] = {3840, 1280};
  const cuuint32_t br[3] = {16, 32, 3};
  const cuuint64_t dwa[4] = {64, 640, 10, 3}, swa[3] = {3840, 128, 1280}, dwb[4] = {32, 640, 20, 3}, swb[3] = {3840, 64, 1280};
  const cuuint32_t bwa[4] = {64, 32, 1, 3}, bwb[4] = {32, 32, 2, 3};
  const cuuint64_t dwo[2] = {640, 640};
  const cuuint32_t bwo[2] = {64, 80}, bo64[2] = {64, 64}, bo16[2] = {16, 64};
  const cuuint64_t dsa[2] = {2048, 1280}, ssa[1] = {4096};
  const cuuint32_t bsa[2] = {64, 80};
  const cuuint64_t dout[2] = {1280, 2048}, sout[1] = {2560};
  Params prm;
  mkmap(enc, &prm.m[M_X], d_in[7], 2, dx, sx, bx, CU_TENSOR_MAP_SWIZZLE_128B);
  mkmap(enc, &prm.m[M_W128], d_in[8], 4, dwa, swa, bwa, CU_TENSOR_MAP_SWIZZLE_128B);
  mkmap(enc, &prm.m[M_W64], d_in[8], 4, dwb, swb, bwb, CU_TENSOR_MAP_SWIZZLE_64B);
  mkmap(enc, &prm.m[M_WR], d_in[8], 3, dw, sw, br, CU_TENSOR_MAP_SWIZZLE_32B);
  mkmap(enc, &prm.m[M_U], d_in[0], 2, dx, sx, bu, CU_TENSOR_MAP_SWIZZLE_NONE);
  mkmap(enc, &prm.m[M_WO], d_in[9], 2, dwo, sx, bwo, CU_TENSOR_MAP_SWIZZLE_128B);
  mkmap(enc, &prm.m[M_O64], d_out, 2, dout, sout, bo64, CU_TENSOR_MAP_SWIZZLE_128B);
  mkmap(enc, &prm.m[M_O16], d_out, 2, dout, sout, bo16, CU_TENSOR_MAP_SWIZZLE_NONE);
  mkmap(enc, &prm.m[M_SA], uy, 2, dsa, ssa, bsa, CU_TENSOR_MAP_SWIZZLE_128B);
  mkmap(enc, &prm.m[M_OUT], d_out, 2, dout, sout, bu, CU_TENSOR_MAP_SWIZZLE_NONE);
  prm.u = (const __nv_bfloat16*)d_in[0]; prm.wo = (const __nv_bfloat16*)d_in[9];
  for (int i = 0; i < 4; i++) prm.par[i] = (const __nv_bfloat16*)d_in[1 + i];
  prm.logdt = (const __nv_bfloat16*)d_in[5]; prm.dskip = (const __nv_bfloat16*)d_in[6];
  cudaFuncSetAttribute(fused_kernel, cudaFuncAttributeMaxDynamicSharedMemorySize, SMEM_BYTES);
  cudaLaunchConfig_t cfg = {};
  cfg.gridDim = dim3(128); cfg.blockDim = dim3(512); cfg.dynamicSmemBytes = SMEM_BYTES; cfg.stream = cudaStreamPerThread;
  cudaLaunchAttribute at[1];
  at[0].id = cudaLaunchAttributeClusterDimension; at[0].val.clusterDim.x = 2; at[0].val.clusterDim.y = 1; at[0].val.clusterDim.z = 1;
  cfg.attrs = at; cfg.numAttrs = 1;
  cudaLaunchKernelEx(&cfg, fused_kernel, prm);
}
```

```cpp
#include <cuda_runtime.h>
#include <cuda_bf16.h>
#include <cuda_fp16.h>
#include <cuda.h>
#include <stdint.h>

#define KST 2
#define UKB 4
#define UPF 0
#define CONV_AT 1
#define EN_ATT 1
#define EN_SSM 1

__device__ __align__(1024) __nv_bfloat16 g_uy[2 * 640 * 2048];
__device__ __align__(128) uint4 g_kvp[8 * 16 * 240];
__device__ __align__(128) uint4 g_o[128 * 1280];
__device__ __align__(128) unsigned g_flag[5 * 128 * 32];
__device__ unsigned g_epoch[128];
#define TS(i) do {} while (0)
#define DUMP(lo, hi) do {} while (0)
#define FIXCNT

constexpr uint32_t SB0 = 1024;
constexpr uint32_t W_SLOT = 15360, OFF_X = 76800;
constexpr uint32_t OFF_WOR = 81920, OFF_KVP = 10240, OFF_KVS = 71680, OFF_PK = 10240, OFF_V = 30720, OFF_EXTRA = 102400, OFF_KVB = OFF_EXTRA;
constexpr uint32_t OFF_BAR = 125952, OFF_BLK = 128000, BLK = 20480;
constexpr uint32_t B_D = 4096, B_D5 = 3088, B_D7 = 6176, B_D9 = 8224, B_TBL = 14400;
constexpr int T_S = 576, T_F2 = 624, T_F3 = 816;
constexpr uint32_t OFF_UT = OFF_BLK + 4 * BLK;
constexpr uint32_t SMEM_BYTES = OFF_BLK + 5 * BLK;
enum { BR_FULL = 0, BR_WO = 5, BR_PUB = 7, BR_KVP = 8, BR_U = 9, BR_SUM = 10, BR_GEMM = 11, BR_UIN = 12, BR_EPOCH = 14,
       BR_FREE = 15, BR_RETRY = 17, BR_UOUT = 18, BR_OFULL = 18, BR_KS = 26, BR_YIN = 27, BR_EMPTY = 31, BR_OEMPTY = 36, BR_Y = 43, BR_OSTG = 45,
       BR_DRDY = 46, BR_U2 = 48, BR_COUNT = 50 };
constexpr uint32_t OFF_EPOCH = OFF_BAR + 8 * BR_COUNT;
enum { M_X, M_W128, M_W64, M_WR, M_U, M_WO, M_O64, M_O16, M_SA, M_SY, M_COUNT };

__device__ __forceinline__ long long clk64() { long long t; asm volatile("mov.u64 %0, %%clock64;" : "=l"(t) :: "memory"); return t; }
__device__ __forceinline__ uint32_t smem_u32(const void* p) { return (uint32_t)__cvta_generic_to_shared(p); }
__host__ __device__ constexpr uint64_t mkdesc(uint32_t addr, uint32_t lbo, uint32_t sbo, uint32_t swz) {
  return (uint64_t)((addr & 0x3FFFF) >> 4) | ((uint64_t)(lbo >> 4) << 16) | ((uint64_t)(sbo >> 4) << 32) | ((uint64_t)swz << 62);
}
__device__ __forceinline__ uint64_t desc2(uint32_t lo, uint32_t hi) { uint64_t d; asm("mov.b64 %0, {%1, %2};" : "=l"(d) : "r"(lo), "r"(hi)); return d; }
__device__ __forceinline__ void mbar_init(uint32_t bar, uint32_t cnt) { asm volatile("mbarrier.init.shared::cta.b64 [%0], %1;" :: "r"(bar), "r"(cnt) : "memory"); }
__device__ __forceinline__ void mbar_expect_tx(uint32_t bar, uint32_t bytes) { asm volatile("mbarrier.arrive.expect_tx.shared::cta.b64 _, [%0], %1;" :: "r"(bar), "r"(bytes) : "memory"); }
__device__ __forceinline__ void mbar_arrive(uint32_t bar) { asm volatile("mbarrier.arrive.shared::cta.b64 _, [%0];" :: "r"(bar) : "memory"); }
__device__ __forceinline__ void mbar_wait(uint32_t bar, uint32_t parity) {
  asm volatile("{\n.reg .pred p;\n.reg .u32 c;\nmov.u32 c, 0;\n"
    "WL:\nmbarrier.try_wait.parity.shared::cta.b64 p, [%0], %1;\n@p bra WD;\n"
    "add.u32 c, c, 1;\nsetp.lt.u32 p, c, 200000;\n@p bra WL;\nWD:\n}" :: "r"(bar), "r"(parity) : "memory");
}
__device__ __forceinline__ void poll_all(const unsigned* p, unsigned val) {
  asm volatile("{\n.reg .pred p;\n.reg .u32 c, v;\nmov.u32 c, 0;\n"
    "PL:\nld.relaxed.gpu.global.u32 v, [%0];\nsetp.eq.u32 p, v, %1;\nvote.sync.all.pred p, p, 0xffffffff;\n@p bra PD;\n"
    "add.u32 c, c, 1;\nsetp.lt.u32 p, c, 100000;\n@p bra PL;\nPD:\n}" :: "l"(p), "r"(val) : "memory");
}
__device__ __forceinline__ void poll_all_acq(const unsigned* p, unsigned val) {
  asm volatile("{\n.reg .pred p;\n.reg .u32 c, v;\nmov.u32 c, 0;\n"
    "PL:\nld.acquire.gpu.global.u32 v, [%0];\nsetp.eq.u32 p, v, %1;\nvote.sync.all.pred p, p, 0xffffffff;\n@p bra PD;\n"
    "add.u32 c, c, 1;\nsetp.lt.u32 p, c, 100000;\n@p bra PL;\nPD:\n}" :: "l"(p), "r"(val) : "memory");
}
__device__ __forceinline__ unsigned poll_bit(const unsigned* p, unsigned val, unsigned mask) {
  unsigned bal;
  asm volatile("{\n.reg .pred p;\n.reg .u32 c, v;\nmov.u32 c, 0;\n"
    "PL:\nld.relaxed.gpu.global.u32 v, [%1];\nsetp.eq.u32 p, v, %2;\nvote.sync.ballot.b32 %0, p, 0xffffffff;\n"
    "and.b32 v, %0, %3;\nsetp.ne.u32 p, v, 0;\n@p bra PD;\n"
    "add.u32 c, c, 1;\nsetp.lt.u32 p, c, 100000;\n@p bra PL;\nPD:\n}" : "=&r"(bal) : "l"(p), "r"(val), "r"(mask) : "memory");
  return bal;
}
__device__ __forceinline__ void fix128_w0(uint32_t* v, const void* p, uint32_t tag, uint32_t mask) {
  asm volatile("{\n.reg .pred p;\n.reg .u32 c, x;\n.reg .b128 t;\n.reg .b64 lo, hi;\nmov.u32 c, 0;\n"
    "FL:\nxor.b32 x, %0, %5;\nand.b32 x, x, %6;\nsetp.eq.u32 p, x, 0;\n@p bra FD;\n"
    "ld.relaxed.gpu.global.b128 t, [%4];\nmov.b128 {lo, hi}, t;\nmov.b64 {%0, %1}, lo;\nmov.b64 {%2, %3}, hi;\n"
    "add.u32 c, c, 1;\nsetp.lt.u32 p, c, 100000;\n@p bra FL;\nFD:\n}"
    : "+r"(v[0]), "+r"(v[1]), "+r"(v[2]), "+r"(v[3]) : "l"(p), "r"(tag), "r"(mask) : "memory");
}
__device__ __forceinline__ void fix128_w3(uint32_t* v, const void* p, uint32_t tag, uint32_t mask) {
  asm volatile("{\n.reg .pred p;\n.reg .u32 c, x;\n.reg .b128 t;\n.reg .b64 lo, hi;\nmov.u32 c, 0;\n"
    "FL:\nxor.b32 x, %3, %5;\nand.b32 x, x, %6;\nsetp.eq.u32 p, x, 0;\n@p bra FD;\n"
    "ld.relaxed.gpu.global.b128 t, [%4];\nmov.b128 {lo, hi}, t;\nmov.b64 {%0, %1}, lo;\nmov.b64 {%2, %3}, hi;\n"
    "add.u32 c, c, 1;\nsetp.lt.u32 p, c, 100000;\n@p bra FL;\nFD:\n}"
    : "+r"(v[0]), "+r"(v[1]), "+r"(v[2]), "+r"(v[3]) : "l"(p), "r"(tag), "r"(mask) : "memory");
}
__device__ __forceinline__ void fence_acq() { asm volatile("fence.acq_rel.gpu;" ::: "memory"); }
__device__ __forceinline__ bool elect_one() {
  uint32_t p; asm volatile("{\n.reg .pred P;\nelect.sync _|P, 0xffffffff;\nselp.u32 %0, 1, 0, P;\n}" : "=r"(p)); return p;
}
__device__ __forceinline__ void bar_sync(int id, int n) { asm volatile("bar.sync %0, %1;" :: "r"(id), "r"(n) : "memory"); }
__device__ __forceinline__ void fence_async() { asm volatile("fence.proxy.async.shared::cta;" ::: "memory"); }
__device__ __forceinline__ void fence_async_g() { asm volatile("fence.proxy.async.global;" ::: "memory"); }
__device__ __forceinline__ void tma2d(uint32_t dst, const CUtensorMap* m, uint32_t bar, int c0, int c1) {
  asm volatile("cp.async.bulk.tensor.2d.shared::cluster.global.mbarrier::complete_tx::bytes [%0], [%1, {%3, %4}], [%2];"
    :: "r"(dst), "l"(m), "r"(bar), "r"(c0), "r"(c1) : "memory");
}
__device__ __forceinline__ void tma3d(uint32_t dst, const CUtensorMap* m, uint32_t bar, int c0, int c1, int c2) {
  asm volatile("cp.async.bulk.tensor.3d.shared::cluster.global.mbarrier::complete_tx::bytes [%0], [%1, {%3, %4, %5}], [%2];"
    :: "r"(dst), "l"(m), "r"(bar), "r"(c0), "r"(c1), "r"(c2) : "memory");
}
__device__ __forceinline__ void tma4d(uint32_t dst, const CUtensorMap* m, uint32_t bar, int c0, int c1, int c2, int c3) {
  asm volatile("cp.async.bulk.tensor.4d.shared::cluster.global.mbarrier::complete_tx::bytes [%0], [%1, {%3, %4, %5, %6}], [%2];"
    :: "r"(dst), "l"(m), "r"(bar), "r"(c0), "r"(c1), "r"(c2), "r"(c3) : "memory");
}
__device__ __forceinline__ void tma2d_st(const CUtensorMap* m, uint32_t src, int c0, int c1) {
  asm volatile("cp.async.bulk.tensor.2d.global.shared::cta.bulk_group [%0, {%2, %3}], [%1];"
    :: "l"(m), "r"(src), "r"(c0), "r"(c1) : "memory");
}
__device__ __forceinline__ void bulk_ld(uint32_t dst, const void* src, uint32_t bytes, uint32_t bar) {
  asm volatile("cp.async.bulk.shared::cluster.global.mbarrier::complete_tx::bytes [%0], [%1], %2, [%3];"
    :: "r"(dst), "l"(src), "r"(bytes), "r"(bar) : "memory");
}
__device__ __forceinline__ void bulk_st(void* dst, uint32_t src, uint32_t bytes) {
  asm volatile("cp.async.bulk.global.shared::cta.bulk_group [%0], [%1], %2;" :: "l"(dst), "r"(src), "r"(bytes) : "memory");
}
__device__ __forceinline__ void bulk_commit() { asm volatile("cp.async.bulk.commit_group;" ::: "memory"); }
__device__ __forceinline__ void bulk_wait0() { asm volatile("cp.async.bulk.wait_group 0;" ::: "memory"); }
__device__ __forceinline__ void bulk_wait0_read() { asm volatile("cp.async.bulk.wait_group.read 0;" ::: "memory"); }
__device__ __forceinline__ unsigned ld_rlx(const unsigned* p) { unsigned v; asm volatile("ld.relaxed.gpu.global.u32 %0, [%1];" : "=r"(v) : "l"(p) : "memory"); return v; }
__device__ __forceinline__ unsigned ld_acq(const unsigned* p) { unsigned v; asm volatile("ld.acquire.gpu.global.u32 %0, [%1];" : "=r"(v) : "l"(p) : "memory"); return v; }
__device__ __forceinline__ void st_rlx(unsigned* p, unsigned v) { asm volatile("st.relaxed.gpu.global.u32 [%0], %1;" :: "l"(p), "r"(v) : "memory"); }
__device__ __forceinline__ void st_rel(unsigned* p, unsigned v) { asm volatile("st.release.gpu.global.u32 [%0], %1;" :: "l"(p), "r"(v) : "memory"); }
__device__ __forceinline__ void ld128_rlx(uint32_t* v, const void* p) {
  asm volatile("{\n.reg .b128 t;\n.reg .b64 lo, hi;\nld.relaxed.gpu.global.b128 t, [%4];\nmov.b128 {lo, hi}, t;\n"
    "mov.b64 {%0, %1}, lo;\nmov.b64 {%2, %3}, hi;\n}" : "=r"(v[0]), "=r"(v[1]), "=r"(v[2]), "=r"(v[3]) : "l"(p) : "memory");
}
__device__ __forceinline__ void st128_rlx(void* p, const uint32_t* v) {
  asm volatile("{\n.reg .b128 t;\n.reg .b64 lo, hi;\nmov.b64 lo, {%1, %2};\nmov.b64 hi, {%3, %4};\nmov.b128 t, {lo, hi};\n"
    "st.relaxed.gpu.global.b128 [%0], t;\n}" :: "l"(p), "r"(v[0]), "r"(v[1]), "r"(v[2]), "r"(v[3]) : "memory");
}
__device__ __forceinline__ uint32_t lds32(uint32_t a) { uint32_t v; asm volatile("ld.shared.u32 %0, [%1];" : "=r"(v) : "r"(a) : "memory"); return v; }
__device__ __forceinline__ uint32_t lds32v(uint32_t a) { uint32_t v; asm volatile("ld.volatile.shared.u32 %0, [%1];" : "=r"(v) : "r"(a) : "memory"); return v; }
__device__ __forceinline__ uint32_t cpa(uint32_t a, uint32_t one) { uint32_t v; asm volatile("mul.lo.u32 %0, %1, %2;" : "=r"(v) : "r"(a), "r"(one)); return v; }
__device__ __forceinline__ uint32_t cpb(uint32_t a, uint32_t zero) { uint32_t v; asm volatile("or.b32 %0, %1, %2;" : "=r"(v) : "r"(a), "r"(zero)); return v; }
__device__ __forceinline__ uint32_t lds16(uint32_t a) { uint16_t v; asm volatile("ld.shared.u16 %0, [%1];" : "=h"(v) : "r"(a) : "memory"); return v; }
__device__ __forceinline__ float ldsf(uint32_t a) { float v; asm volatile("ld.shared.f32 %0, [%1];" : "=f"(v) : "r"(a) : "memory"); return v; }
__device__ __forceinline__ void lds128(uint32_t* v, uint32_t a) { asm volatile("ld.shared.v4.u32 {%0,%1,%2,%3}, [%4];" : "=r"(v[0]), "=r"(v[1]), "=r"(v[2]), "=r"(v[3]) : "r"(a) : "memory"); }
__device__ __forceinline__ void sts32(uint32_t a, uint32_t v) { asm volatile("st.shared.u32 [%0], %1;" :: "r"(a), "r"(v) : "memory"); }
__device__ __forceinline__ void sts16(uint32_t a, uint32_t v) { asm volatile("st.shared.u16 [%0], %1;" :: "r"(a), "h"((uint16_t)v) : "memory"); }
__device__ __forceinline__ void sts64f(uint32_t a, float x, float y) { asm volatile("st.shared.v2.f32 [%0], {%1,%2};" :: "r"(a), "f"(x), "f"(y) : "memory"); }
__device__ __forceinline__ void sts128(uint32_t a, uint32_t x, uint32_t y, uint32_t z, uint32_t w) { asm volatile("st.shared.v4.u32 [%0], {%1,%2,%3,%4};" :: "r"(a), "r"(x), "r"(y), "r"(z), "r"(w) : "memory"); }
__device__ __forceinline__ void stsm4(uint32_t a, uint32_t r0, uint32_t r1, uint32_t r2, uint32_t r3) {
  asm volatile("stmatrix.sync.aligned.m8n8.x4.shared.b16 [%0], {%1,%2,%3,%4};" :: "r"(a), "r"(r0), "r"(r1), "r"(r2), "r"(r3) : "memory");
}
__device__ __forceinline__ void stsm4t(uint32_t a, uint32_t r0, uint32_t r1, uint32_t r2, uint32_t r3) {
  asm volatile("stmatrix.sync.aligned.m8n8.x4.trans.shared.b16 [%0], {%1,%2,%3,%4};" :: "r"(a), "r"(r0), "r"(r1), "r"(r2), "r"(r3) : "memory");
}
__device__ __forceinline__ void ldsm4t(uint32_t* r, uint32_t a) {
  asm volatile("ldmatrix.sync.aligned.m8n8.x4.trans.shared.b16 {%0,%1,%2,%3}, [%4];" : "=r"(r[0]), "=r"(r[1]), "=r"(r[2]), "=r"(r[3]) : "r"(a) : "memory");
}
__device__ __forceinline__ void ldsm4(uint32_t* r, uint32_t a) {
  asm volatile("ldmatrix.sync.aligned.m8n8.x4.shared.b16 {%0,%1,%2,%3}, [%4];" : "=r"(r[0]), "=r"(r[1]), "=r"(r[2]), "=r"(r[3]) : "r"(a) : "memory");
}
__device__ __forceinline__ void mma16816(float* d, const uint32_t* a, const uint32_t* b) {
  asm volatile("mma.sync.aligned.m16n8k16.row.col.f32.bf16.bf16.f32 {%0,%1,%2,%3}, {%4,%5,%6,%7}, {%8,%9}, {%0,%1,%2,%3};"
    : "+f"(d[0]), "+f"(d[1]), "+f"(d[2]), "+f"(d[3]) : "r"(a[0]), "r"(a[1]), "r"(a[2]), "r"(a[3]), "r"(b[0]), "r"(b[1]));
}
__device__ __forceinline__ uint32_t pack2(float lo, float hi) { uint32_t r; asm("cvt.rn.bf16x2.f32 %0, %1, %2;" : "=r"(r) : "f"(hi), "f"(lo)); return r; }
__device__ __forceinline__ uint32_t packh(float lo, float hi) { uint32_t r; asm("cvt.rn.f16x2.f32 %0, %1, %2;" : "=r"(r) : "f"(hi), "f"(lo)); return r; }
__device__ __forceinline__ uint32_t hcmul(uint32_t x, uint32_t zp, uint32_t zq) {
  const __half2 xx = *reinterpret_cast<__half2*>(&x);
  const __half2 r = __hfma2(__high2half2(xx), *reinterpret_cast<__half2*>(&zq), __hmul2(__low2half2(xx), *reinterpret_cast<__half2*>(&zp)));
  return *reinterpret_cast<const uint32_t*>(&r);
}
__device__ __forceinline__ void hcm2(uint32_t xr, uint32_t xi, uint32_t z, uint32_t& pr, uint32_t& pi) {
  const __half2 a = *reinterpret_cast<__half2*>(&xr), b = *reinterpret_cast<__half2*>(&xi), zz = *reinterpret_cast<__half2*>(&z);
  const __half2 re = __hfma2(__hneg2(b), __high2half2(zz), __hmul2(a, __low2half2(zz)));
  const __half2 im = __hfma2(a, __high2half2(zz), __hmul2(b, __low2half2(zz)));
  pr = *reinterpret_cast<const uint32_t*>(&re); pi = *reinterpret_cast<const uint32_t*>(&im);
}
__device__ __forceinline__ void sts64(uint32_t a, uint32_t x, uint32_t y) { asm volatile("st.shared.v2.u32 [%0], {%1,%2};" :: "r"(a), "r"(x), "r"(y) : "memory"); }
__device__ __forceinline__ void lds64(uint32_t* v, uint32_t a) { asm volatile("ld.shared.v2.u32 {%0,%1}, [%2];" : "=r"(v[0]), "=r"(v[1]) : "r"(a) : "memory"); }
__device__ __forceinline__ float bf_lo(uint32_t v) { return __uint_as_float(v << 16); }
__device__ __forceinline__ float bf_hi(uint32_t v) { return __uint_as_float(v & 0xffff0000u); }
__device__ __forceinline__ float bf_round(float x) { return bf_lo(pack2(x, 0.f)); }
__device__ __forceinline__ float ex2(float x) { float r; asm("ex2.approx.ftz.f32 %0, %1;" : "=f"(r) : "f"(x)); return r; }
__device__ __forceinline__ float phi(float t, float l2e = 1.44269504089f) {
  float e = ex2(t * l2e) + 1e-6f;
  asm("{\n.reg .pred p;\nsetp.gt.f32 p, %1, 0f00000000;\n@p add.f32 %0, %1, 0f3F800008;\n}" : "+f"(e) : "f"(t));
  return e;
}
__device__ __forceinline__ void wg_fence() { asm volatile("wgmma.fence.sync.aligned;" ::: "memory"); }
__device__ __forceinline__ void wg_commit() { asm volatile("wgmma.commit_group.sync.aligned;" ::: "memory"); }
template <int N> __device__ __forceinline__ void wg_wait() { asm volatile("wgmma.wait_group.sync.aligned %0;" :: "n"(N) : "memory"); }
template <int N> __device__ __forceinline__ void pin(float* a) {
  #pragma unroll
  for (int i = 0; i < N; i++) asm volatile("" : "+f"(a[i]) :: "memory");
}
__device__ __forceinline__ int rtid() { int t; asm volatile("mov.u32 %0, %%tid.x;" : "=r"(t)); return t; }
__device__ __forceinline__ int opaque(int v) { asm volatile("" : "+r"(v)); return v; }
template <int N> __device__ __forceinline__ void zero(float* a) {
  #pragma unroll
  for (int i = 0; i < N; i++) asm volatile("mov.b32 %0, 0;" : "=f"(a[i]));
}
template <int N> __device__ __forceinline__ void pinu(uint32_t* a) {
  #pragma unroll
  for (int i = 0; i < N; i++) asm volatile("" : "+r"(a[i]) :: "memory");
}
__device__ __forceinline__ void cexp_t(float lg2mag, float turns, float& re, float& im) {
  float m = ex2(lg2mag);
  float fr = (turns - __fadd_rn(__fadd_rn(turns, 12582912.f), -12582912.f)) * 6.283185307f;
  re = m * __cosf(fr); im = m * __sinf(fr);
}
__device__ __forceinline__ void cmul(float ar, float ai, float br, float bi, float& cr, float& ci) {
  cr = fmaf(ar, br, -ai * bi); ci = fmaf(ar, bi, ai * br);
}

__device__ __forceinline__ void wg_ss48_tt(float* d, uint64_t da, uint64_t db, int scale_d) {
  asm volatile("{\n.reg .pred p;\nsetp.ne.b32 p, %26, 0;\n"
    "wgmma.mma_async.sync.aligned.m64n48k16.f32.bf16.bf16 "
    "{%0, %1, %2, %3, %4, %5, %6, %7, %8, %9, %10, %11, %12, %13, %14, %15, %16, %17, %18, %19, %20, %21, %22, %23}, %24, %25, p, 1, 1, 1, 1;\n}\n"
    : "+f"(d[0]), "+f"(d[1]), "+f"(d[2]), "+f"(d[3]), "+f"(d[4]), "+f"(d[5]), "+f"(d[6]), "+f"(d[7]), "+f"(d[8]), "+f"(d[9]), "+f"(d[10]), "+f"(d[11]), "+f"(d[12]), "+f"(d[13]), "+f"(d[14]), "+f"(d[15]), "+f"(d[16]), "+f"(d[17]), "+f"(d[18]), "+f"(d[19]), "+f"(d[20]), "+f"(d[21]), "+f"(d[22]), "+f"(d[23])
    : "l"(da), "l"(db), "r"(scale_d));
}
__device__ __forceinline__ void wg_rs88_tb(float* d, const uint32_t* a, uint64_t db, int scale_d) {
  asm volatile("{\n.reg .pred p;\nsetp.ne.b32 p, %49, 0;\n"
    "wgmma.mma_async.sync.aligned.m64n88k16.f32.bf16.bf16 "
    "{%0, %1, %2, %3, %4, %5, %6, %7, %8, %9, %10, %11, %12, %13, %14, %15, %16, %17, %18, %19, %20, %21, %22, %23, %24, %25, %26, %27, %28, %29, %30, %31, %32, %33, %34, %35, %36, %37, %38, %39, %40, %41, %42, %43}, {%44, %45, %46, %47}, %48, p, 1, 1, 1;\n}\n"
    : "+f"(d[0]), "+f"(d[1]), "+f"(d[2]), "+f"(d[3]), "+f"(d[4]), "+f"(d[5]), "+f"(d[6]), "+f"(d[7]), "+f"(d[8]), "+f"(d[9]), "+f"(d[10]), "+f"(d[11]), "+f"(d[12]), "+f"(d[13]), "+f"(d[14]), "+f"(d[15]), "+f"(d[16]), "+f"(d[17]), "+f"(d[18]), "+f"(d[19]), "+f"(d[20]), "+f"(d[21]), "+f"(d[22]), "+f"(d[23]), "+f"(d[24]), "+f"(d[25]), "+f"(d[26]), "+f"(d[27]), "+f"(d[28]), "+f"(d[29]), "+f"(d[30]), "+f"(d[31]), "+f"(d[32]), "+f"(d[33]), "+f"(d[34]), "+f"(d[35]), "+f"(d[36]), "+f"(d[37]), "+f"(d[38]), "+f"(d[39]), "+f"(d[40]), "+f"(d[41]), "+f"(d[42]), "+f"(d[43])
    : "r"(a[0]), "r"(a[1]), "r"(a[2]), "r"(a[3]), "l"(db), "r"(scale_d));
}
__device__ __forceinline__ void wg_ss80_tb(float* d, uint64_t da, uint64_t db, int scale_d) {
  asm volatile("{\n.reg .pred p;\nsetp.ne.b32 p, %42, 0;\n"
    "wgmma.mma_async.sync.aligned.m64n80k16.f32.bf16.bf16 "
    "{%0, %1, %2, %3, %4, %5, %6, %7, %8, %9, %10, %11, %12, %13, %14, %15, %16, %17, %18, %19, %20, %21, %22, %23, %24, %25, %26, %27, %28, %29, %30, %31, %32, %33, %34, %35, %36, %37, %38, %39}, %40, %41, p, 1, 1, 0, 1;\n}\n"
    : "+f"(d[0]), "+f"(d[1]), "+f"(d[2]), "+f"(d[3]), "+f"(d[4]), "+f"(d[5]), "+f"(d[6]), "+f"(d[7]), "+f"(d[8]), "+f"(d[9]), "+f"(d[10]), "+f"(d[11]), "+f"(d[12]), "+f"(d[13]), "+f"(d[14]), "+f"(d[15]), "+f"(d[16]), "+f"(d[17]), "+f"(d[18]), "+f"(d[19]), "+f"(d[20]), "+f"(d[21]), "+f"(d[22]), "+f"(d[23]), "+f"(d[24]), "+f"(d[25]), "+f"(d[26]), "+f"(d[27]), "+f"(d[28]), "+f"(d[29]), "+f"(d[30]), "+f"(d[31]), "+f"(d[32]), "+f"(d[33]), "+f"(d[34]), "+f"(d[35]), "+f"(d[36]), "+f"(d[37]), "+f"(d[38]), "+f"(d[39])
    : "l"(da), "l"(db), "r"(scale_d));
}
__device__ __forceinline__ void wg_ss48_tt_h(float* d, uint64_t da, uint64_t db, int scale_d) {
  asm volatile("{\n.reg .pred p;\nsetp.ne.b32 p, %26, 0;\n"
    "wgmma.mma_async.sync.aligned.m64n48k16.f32.f16.f16 "
    "{%0, %1, %2, %3, %4, %5, %6, %7, %8, %9, %10, %11, %12, %13, %14, %15, %16, %17, %18, %19, %20, %21, %22, %23}, %24, %25, p, 1, 1, 1, 1;\n}\n"
    : "+f"(d[0]), "+f"(d[1]), "+f"(d[2]), "+f"(d[3]), "+f"(d[4]), "+f"(d[5]), "+f"(d[6]), "+f"(d[7]), "+f"(d[8]), "+f"(d[9]), "+f"(d[10]), "+f"(d[11]), "+f"(d[12]), "+f"(d[13]), "+f"(d[14]), "+f"(d[15]), "+f"(d[16]), "+f"(d[17]), "+f"(d[18]), "+f"(d[19]), "+f"(d[20]), "+f"(d[21]), "+f"(d[22]), "+f"(d[23])
    : "l"(da), "l"(db), "r"(scale_d));
}
__device__ __forceinline__ void wg_rs192_tb(float* d, const uint32_t* a, uint64_t db, int scale_d) {
  asm volatile("{\n.reg .pred p;\nsetp.ne.b32 p, %101, 0;\n"
    "wgmma.mma_async.sync.aligned.m64n192k16.f32.bf16.bf16 "
    "{%0, %1, %2, %3, %4, %5, %6, %7, %8, %9, %10, %11, %12, %13, %14, %15, %16, %17, %18, %19, %20, %21, %22, %23, %24, %25, %26, %27, %28, %29, %30, %31, %32, %33, %34, %35, %36, %37, %38, %39, %40, %41, %42, %43, %44, %45, %46, %47, %48, %49, %50, %51, %52, %53, %54, %55, %56, %57, %58, %59, %60, %61, %62, %63, %64, %65, %66, %67, %68, %69, %70, %71, %72, %73, %74, %75, %76, %77, %78, %79, %80, %81, %82, %83, %84, %85, %86, %87, %88, %89, %90, %91, %92, %93, %94, %95}, {%96, %97, %98, %99}, %100, p, 1, 1, 1;\n}\n"
    : "+f"(d[0]), "+f"(d[1]), "+f"(d[2]), "+f"(d[3]), "+f"(d[4]), "+f"(d[5]), "+f"(d[6]), "+f"(d[7]), "+f"(d[8]), "+f"(d[9]), "+f"(d[10]), "+f"(d[11]), "+f"(d[12]), "+f"(d[13]), "+f"(d[14]), "+f"(d[15]), "+f"(d[16]), "+f"(d[17]), "+f"(d[18]), "+f"(d[19]), "+f"(d[20]), "+f"(d[21]), "+f"(d[22]), "+f"(d[23]), "+f"(d[24]), "+f"(d[25]), "+f"(d[26]), "+f"(d[27]), "+f"(d[28]), "+f"(d[29]), "+f"(d[30]), "+f"(d[31]), "+f"(d[32]), "+f"(d[33]), "+f"(d[34]), "+f"(d[35]), "+f"(d[36]), "+f"(d[37]), "+f"(d[38]), "+f"(d[39]), "+f"(d[40]), "+f"(d[41]), "+f"(d[42]), "+f"(d[43]), "+f"(d[44]), "+f"(d[45]), "+f"(d[46]), "+f"(d[47]), "+f"(d[48]), "+f"(d[49]), "+f"(d[50]), "+f"(d[51]), "+f"(d[52]), "+f"(d[53]), "+f"(d[54]), "+f"(d[55]), "+f"(d[56]), "+f"(d[57]), "+f"(d[58]), "+f"(d[59]), "+f"(d[60]), "+f"(d[61]), "+f"(d[62]), "+f"(d[63]), "+f"(d[64]), "+f"(d[65]), "+f"(d[66]), "+f"(d[67]), "+f"(d[68]), "+f"(d[69]), "+f"(d[70]), "+f"(d[71]), "+f"(d[72]), "+f"(d[73]), "+f"(d[74]), "+f"(d[75]), "+f"(d[76]), "+f"(d[77]), "+f"(d[78]), "+f"(d[79]), "+f"(d[80]), "+f"(d[81]), "+f"(d[82]), "+f"(d[83]), "+f"(d[84]), "+f"(d[85]), "+f"(d[86]), "+f"(d[87]), "+f"(d[88]), "+f"(d[89]), "+f"(d[90]), "+f"(d[91]), "+f"(d[92]), "+f"(d[93]), "+f"(d[94]), "+f"(d[95])
    : "r"(a[0]), "r"(a[1]), "r"(a[2]), "r"(a[3]), "l"(db), "r"(scale_d));
}
__device__ __forceinline__ void wg_rs48_tb(float* d, const uint32_t* a, uint64_t db, int scale_d) {
  asm volatile("{\n.reg .pred p;\nsetp.ne.b32 p, %29, 0;\n"
    "wgmma.mma_async.sync.aligned.m64n48k16.f32.bf16.bf16 "
    "{%0, %1, %2, %3, %4, %5, %6, %7, %8, %9, %10, %11, %12, %13, %14, %15, %16, %17, %18, %19, %20, %21, %22, %23}, {%24, %25, %26, %27}, %28, p, 1, 1, 1;\n}\n"
    : "+f"(d[0]), "+f"(d[1]), "+f"(d[2]), "+f"(d[3]), "+f"(d[4]), "+f"(d[5]), "+f"(d[6]), "+f"(d[7]), "+f"(d[8]), "+f"(d[9]), "+f"(d[10]), "+f"(d[11]), "+f"(d[12]), "+f"(d[13]), "+f"(d[14]), "+f"(d[15]), "+f"(d[16]), "+f"(d[17]), "+f"(d[18]), "+f"(d[19]), "+f"(d[20]), "+f"(d[21]), "+f"(d[22]), "+f"(d[23])
    : "r"(a[0]), "r"(a[1]), "r"(a[2]), "r"(a[3]), "l"(db), "r"(scale_d));
}

struct Params {
  const __nv_bfloat16 *par[4], *logdt, *dskip, *u, *wo;
  CUtensorMap m[M_COUNT];
};

#define CHUNK(i) ((i) == 0 ? c : ((i) == 7 ? (c ^ 1) : (((c & 6) + 1 + (i)) & 7)))
#define CHAN(k) (c * 80 + ((k) < 4 ? r * 4 + (k) : 64 + r))
#define FLAG(kind, rr, cc) (&g_flag[((kind) * 128 + (rr) * 8 + (cc)) * 32])
#define SLOT(i) ((i) == 0 ? OFF_EXTRA : OFF_BLK - 256 + ((i) > 5 ? (i) - 6 : (i) - 1) * BLK)
__device__ __forceinline__ void load_quad(uint32_t* A, uint32_t addr) {
  A[0] = lds32v(addr); A[1] = lds32v(addr + 32); A[2] = lds32v(addr - 32); A[3] = lds32v(addr);
}

__global__ void __launch_bounds__(512, 1) fused_kernel(const __grid_constant__ Params prm) {
  extern __shared__ unsigned char smem_raw[];
  const uint32_t sb = __shfl_sync(0xffffffff, smem_u32(smem_raw), 0);
  const int tid = threadIdx.x, lane = tid & 31;
  const int warp = __shfl_sync(0xffffffff, tid >> 5, 0), wg = warp >> 2, w4 = warp & 3;
  const int cta = blockIdx.x, r = cta >> 3, c = cta & 7;
  if ((sb & 0xffffffu) != SB0) return;
#define BAR(i) (sb + OFF_BAR + 8 * (i))
  const bool sw64 = ((c + 1) & 2) != 0;

  const CUtensorMap* mwp = &prm.m[sw64 ? M_W64 : M_W128];
  const int mcol = (c * 80 + (c & 1) * 16) >> (sw64 ? 5 : 6), rcol = c * 80 + ((c & 1) ? 0 : 64);
  if (warp == 12 && elect_one()) {
    #pragma unroll
    for (int i = 0; i < 5; i++) mbar_init(BAR(BR_FULL + i), 1);
    asm volatile("fence.mbarrier_init.release.cluster;" ::: "memory");
    if (EN_ATT) {
      mbar_expect_tx(BAR(BR_FULL), W_SLOT + 16384);
      tma4d(sb, mwp, BAR(BR_FULL), 0, 0, mcol, 0);
      tma2d(sb + OFF_X, &prm.m[M_X], BAR(BR_FULL), 0, r * 128);
      tma3d(sb + 12288, &prm.m[M_WR], BAR(BR_FULL), rcol, 0, 0);
      mbar_expect_tx(BAR(BR_FULL + 1), W_SLOT);
      tma4d(sb + W_SLOT, mwp, BAR(BR_FULL + 1), 0, 32, mcol, 0);
      tma3d(sb + W_SLOT + 12288, &prm.m[M_WR], BAR(BR_FULL + 1), rcol, 32, 0);
      TS(24);
    }
  }
  if (warp == 13 && elect_one()) {
    asm volatile("prefetch.tensormap [%0];" :: "l"(&prm.m[M_X]) : "memory");
    asm volatile("prefetch.tensormap [%0];" :: "l"(&prm.m[M_WR]) : "memory");
  }
  if (wg == 3) {
    asm volatile("setmaxnreg.dec.sync.aligned.u32 56;");
    const int tid = rtid(), lane = tid & 31;
    if (warp == 12) {
      asm volatile("bar.arrive 0, 512;" ::: "memory");
      {
        uint32_t s = 2, ph = 1, xs = 16384;
        #pragma unroll 1
        for (int kb = 2; kb < 20; kb++) {
          if (kb == 4) bar_sync(6, 128);
          if (kb >= 5) mbar_wait(BAR(BR_EMPTY) + 8 * s, ph);
          if (EN_ATT && elect_one()) {
            const uint32_t st = sb + s * W_SLOT, fb = BAR(BR_FULL) + 8 * s;
            mbar_expect_tx(fb, (kb & 1) ? W_SLOT : W_SLOT + 16384);
            if (!(kb & 1)) tma2d(sb + OFF_X + xs, &prm.m[M_X], fb, kb * 32, r * 128);
            tma4d(st, mwp, fb, 0, kb * 32, mcol, 0);
            tma3d(st + 12288, &prm.m[M_WR], fb, rcol, kb * 32, 0);
          }
          if (kb < 4 && lane == 0) TS(24 + kb);
          if (UPF && kb >= UKB - 4 && kb < UKB && elect_one())
            asm volatile("cp.async.bulk.prefetch.L2.global [%0], 5120;" :: "l"(prm.u + cta * 10240 + (kb - (UKB - 4)) * 2560) : "memory");
          if (EN_SSM && kb == (EN_ATT ? UKB : 4) && elect_one()) { mbar_expect_tx(BAR(BR_UIN), 20480); tma2d(sb + OFF_UT, &prm.m[M_U], BAR(BR_UIN), c * 80, r * 128); }
          if (kb == 14 && elect_one()) asm volatile("cp.async.bulk.prefetch.L2.global [%0], 6400;" :: "l"(prm.wo + cta * 3200) : "memory");
          if (!EN_ATT && kb == 4) break;
          if (++s == 5) { s = 0; ph ^= 1; }
          if (kb & 1) { xs += 16384; if (xs == 49152) xs = 0; }
        }
      }
      if (EN_ATT) {
      mbar_wait(BAR(BR_EPOCH), 0);
      const unsigned epoch = lds32(sb + OFF_EPOCH);
      const unsigned* fo = FLAG(3, r, lane & 7);
      unsigned seen = __ballot_sync(0xffffffff, ld_rlx(lane < 16 ? fo : FLAG(0, lane & 15, c)) == epoch) & 0xffu;
      mbar_wait(BAR(BR_GEMM), 0);
      if (elect_one()) {
        mbar_expect_tx(BAR(BR_WO), 10240);
        tma2d(sb, &prm.m[M_WO], BAR(BR_WO), c * 64, c * 80);
        mbar_expect_tx(BAR(BR_KVP), 61440);
        mbar_expect_tx(BAR(BR_WO + 1), 7 * 10240);
      }
      {
        uint32_t ds = sb + OFF_WOR + (lane >> 3) * 128 + (((lane & 7) ^ (lane >> 3)) << 4);
        #pragma unroll 1
        for (int h = 0; h < 2; h++) {
          const int i = (lane & 6) + h;
          const char* gs = reinterpret_cast<const char*>(prm.wo) + (size_t)((lane >> 3) + CHUNK(i) * 80) * 1280 + 1024 + c * 32 + (lane & 1) * 16;
          #pragma unroll 2
          for (int q = 0; q < 20; q++) {
            asm volatile("cp.async.cg.shared.global [%0], [%1], 16;" :: "r"(ds), "l"(gs) : "memory");
            ds = (ds + 512) ^ 64; gs += 5120;
          }
        }
      }
      mbar_wait(BAR(BR_PUB), 0);
      poll_all(FLAG(0, lane & 15, c), epoch);
      if (elect_one()) { TS(23); bulk_ld(sb + OFF_KVP, &g_kvp[c * 16 * 240], 61440, BAR(BR_KVP)); }
      asm volatile("cp.async.wait_all;" ::: "memory");
      fence_async();
      mbar_arrive(BAR(BR_WO));
      mbar_wait(BAR(BR_SUM), 0);
      if (elect_one()) {
        #pragma unroll 1
        for (int i = 1; i < 8; i++) tma2d(sb + i * 10240, &prm.m[M_WO], BAR(BR_WO + 1), c * 64, CHUNK(i) * 80);
      }
      mbar_wait(BAR(BR_OSTG), 0);
      if (elect_one()) {
        bulk_st(&g_o[cta * 1280], sb + OFF_EXTRA, 20480);
        bulk_commit();
        bulk_wait0();
        st_rlx(FLAG(3, r, c), epoch);
        mbar_arrive(BAR(BR_OEMPTY));
        TS(20);
      }
      __syncwarp();
      #pragma unroll 1
      for (int i = 1; i < 8; i++) {
        const int src = CHUNK(i);
        if (!((seen >> src) & 1)) seen = poll_bit(fo, epoch, 1u << src);
        if (i > 5) mbar_wait(BAR(BR_OEMPTY - 5) + 8 * i, 0);
        if (EN_SSM && (i == 1 || i == 5)) mbar_wait(BAR(BR_FREE) + 2 * (i & 4), 0);
        if (elect_one()) {
          mbar_expect_tx(BAR(BR_OFULL) + 8 * i, 20480);
          bulk_ld(sb + SLOT(i), &g_o[(r * 8 + src) * 1280], 20480, BAR(BR_OFULL) + 8 * i);
          if (i == 1) TS(21);
          if (i == 7) TS(22);
        }
        __syncwarp();
      }
      if (lane == 0) { DUMP(20, 30); }
      }
    } else {
      const int hw = warp - 13, ht = tid - 416;
      if (hw == 2 && elect_one()) {
        #pragma unroll
        for (int i = 5; i < BR_COUNT; i++) mbar_init(BAR(i), i == BR_WO ? 33 : i == BR_OEMPTY ? 9 : i < BR_EMPTY ? 1 : i < BR_OEMPTY ? 2 : i < BR_Y ? 8 : i < BR_OSTG ? 4 : i == BR_OSTG ? 8 : i < BR_U2 ? 3 : 1);
        asm volatile("fence.mbarrier_init.release.cluster;" ::: "memory");
      }
      __syncwarp();
      asm volatile("bar.arrive 0, 512;" ::: "memory");
      if (EN_SSM && hw == 2) asm volatile("bar.arrive 8, 160;" ::: "memory");
      const unsigned epoch = ld_rlx(&g_epoch[cta]) + 1;
      if (epoch) bar_sync(5, 96);
      asm volatile("bar.arrive 6, 128;" ::: "memory");
      if (hw == 1 && elect_one()) {
        #pragma unroll
        for (int i = M_U; i < M_COUNT; i++) asm volatile("prefetch.tensormap [%0];" :: "l"(&prm.m[i]) : "memory");
      }
      if (ht == 0) {
        st_rlx(&g_epoch[cta], epoch);
        sts32(sb + OFF_EPOCH, epoch);
        mbar_arrive(BAR(BR_EPOCH));
      }
      if (EN_SSM) {
      const int mi = lane >> 3, rw = lane & 7;
      mbar_wait(BAR(BR_UIN), 0);
      if (ht == 0) TS(36);
      #pragma unroll 1
      for (int h = 0; h < 2; h++) {
        const uint32_t sa = sb + OFF_UT + h * 10240 + (8 * mi + rw) * 160 + hw * 16, da = sb + OFF_UT + h * 10240 + (hw * 8 + rw) * 128 + ((mi ^ rw ^ h) << 4);
        uint32_t v[8][4];
        #pragma unroll
        for (int q = 0; q < 8; q++) if (q < 6 || hw == 0) ldsm4t(v[q], sa + (q & 1) * 5120 + (q >> 1) * 48);
        bar_sync(5, 96);
        #pragma unroll
        for (int q = 0; q < 8; q++) if (q < 6 || hw == 0) stsm4((da ^ ((q & 1) * 64)) + (q >> 1) * 3072, v[q][0], v[q][1], v[q][2], v[q][3]);
      }
      fence_async();
      bar_sync(5, 96);
      if (hw == 0) {
        if (elect_one()) {
          tma2d_st(&prm.m[M_SA], sb + OFF_UT, r * 128, c * 80);
          tma2d_st(&prm.m[M_SA], sb + OFF_UT + 10240, r * 128 + 64, c * 80);
          bulk_commit(); bulk_wait0_read();
          mbar_arrive(BAR(BR_UOUT));
          TS(37);
          bulk_wait0();
          st_rel(FLAG(1, r, c), epoch);
          TS(30);
        }
        __syncwarp();
        poll_all_acq(FLAG(1, lane & 15, c), epoch);
      }
      #pragma unroll 1
      for (int k = 0; k < 5; k++) {
        if (k == 0 || k == 3) {
          const int p = k != 0;
          if (hw == 0) {
            if (!p) {
              if (elect_one()) {
                fence_async_g();
                mbar_expect_tx(BAR(BR_U), 12288);
                #pragma unroll 1
                for (int q = 0; q < 3; q++) bulk_ld(sb + OFF_BLK + q * q * BLK, g_uy + CHAN(q * q) * 2048, 4096, BAR(BR_U));
                TS(31);
              }
              __syncwarp();
            }
            mbar_wait(BAR(p ? BR_U2 : BR_U), 0);
          }
          bar_sync(5, 96);
        }
        const int l3 = (hw + k) % 3 * 32 + lane;
        const uint32_t blk = sb + OFF_BLK + ((0x32410 >> (4 * k)) & 7) * BLK, o = blk + B_D + l3 * 16;
        float P[34];
        P[0] = 0.f;
        #pragma unroll
        for (int q = 0; q < 5; q++) {
          const int ch = 2 * l3 - 3 + q;
          uint32_t v[4];
          lds128(v, blk + (uint32_t)((ch * 16) ^ ((ch * 2) & 0x10)));
          #pragma unroll
          for (int e = 0; e < 8; e++) {
            const int i = 8 * q + e - 4;
            if (i >= 0 && i < 33) P[i + 1] = P[i] + ((e & 1) ? bf_hi(v[e >> 1]) : bf_lo(v[e >> 1]));
          }
        }
#define WIN(lo, hi, e) (P[21 + (e) - (lo)] - P[20 + (e) - (hi)])
#define WIN8(lo, hi, b) pack2(WIN(lo, hi, b), WIN(lo, hi, b + 1)), pack2(WIN(lo, hi, b + 2), WIN(lo, hi, b + 3)), pack2(WIN(lo, hi, b + 4), WIN(lo, hi, b + 5)), pack2(WIN(lo, hi, b + 6), WIN(lo, hi, b + 7))
        if (l3 < 64) {
          sts128(o + B_D9, WIN8(12, 20, 0)); sts128(o + B_D9 + 1024, WIN8(12, 20, 8));
          sts128(o + B_D7, WIN8(5, 11, 0)); sts128(o + B_D7 + 1024, WIN8(5, 11, 8));
        }
        sts128(o + B_D5, WIN8(6, 10, 0)); sts128(o + B_D5 + 1552, WIN8(6, 10, 8));
        sts128(o, WIN8(3, 5, 0)); sts128(o + 1552, WIN8(3, 5, 8));
        if (l3 < 2) sts128(blk + B_D + l3 * B_D5 + 1536, 0, 0, 0, 0);
      }
      __syncwarp();
      if (lane == 0) mbar_arrive(BAR(BR_DRDY + 1));
      if (ht == 0) TS(32);
      if (hw == 0) {
        #pragma unroll 1
        for (int p = 0; p < 2; p++) {
          mbar_wait(BAR(BR_Y) + 8 * p, 0);
          if (elect_one()) {
            #pragma unroll 1
            for (int k = 4 * p; k < 4 + p; k++) bulk_st(g_uy + (640 + CHAN(k)) * 2048, sb + OFF_BLK + k * BLK, 4096);
            bulk_commit(); bulk_wait0_read();
            mbar_arrive(BAR(BR_FREE) + 8 * p);
            bulk_wait0();
            st_rlx(FLAG(2 + 2 * p, r, c), epoch);
            TS(33);
          }
          __syncwarp();
        }
      } else mbar_wait(BAR(BR_FREE), 0);
      poll_all(FLAG(hw ? 2 : 4, lane & 15, c), epoch);
      if (EN_ATT) mbar_wait(BAR(BR_OEMPTY), 0);
      const uint32_t ym = lane < 4 ? 0x10001u : 0u, ytag = (epoch & 1u) * 0x10001u;
      int un = hw ? 2 * hw - 2 : 4;
      #pragma unroll 1
      for (int n = 0; n < 64; n++) {
        const uint32_t yb = sb + OFF_EXTRA + un * 4096, br = BAR(BR_YIN) + 8 * hw;
        if (elect_one()) {
          mbar_expect_tx(br, 4096);
          tma2d(yb, &prm.m[M_SY], br, r * 128, 640 + c * 80 + un * 16);
          tma2d(yb + 2048, &prm.m[M_SY], br, r * 128 + 64, 640 + c * 80 + un * 16);
          if (hw == 0) TS(34);
        }
        __syncwarp();
        mbar_wait(br, n & 1);
        if (ht == 0) TS(38);
        uint32_t v[8][4], bad = 0;
        #pragma unroll
        for (int q = 0; q < 8; q++) {
          ldsm4t(v[q], yb + rw * 128 + ((mi ^ rw ^ ((q & 1) * 4) ^ ((q >> 1) & 1)) << 4) + ((q >> 1) & 1) * 2048 + (q >> 2) * 1024);
          bad |= (v[q][0] ^ ytag) | (v[q][2] ^ ytag);
        }
        if (__any_sync(0xffffffff, bad & ym)) { FIXCNT continue; }
        #pragma unroll
        for (int q = 0; q < 8; q++) stsm4(yb + lane * 32 + (q & 3) * 1024 + (q >> 2) * 16, v[q][0] & ~ym, v[q][1], v[q][2] & ~ym, v[q][3]);
        fence_async();
        __syncwarp();
        if (elect_one()) {
          if (hw == 0) TS(39);
          tma2d_st(&prm.m[M_O16], yb, c * 80 + un * 16, r * 128);
          tma2d_st(&prm.m[M_O16], yb + 2048, c * 80 + un * 16, r * 128 + 64);
          bulk_commit();
        }
        if (un & 5) break;
        un++;
      }
      if (elect_one()) {
        bulk_wait0_read();
        if (hw == 0) { TS(35); DUMP(30, 40); DUMP(0, 1); }
      }
      }
    }
  } else if (wg < 2) {
    asm volatile("setmaxnreg.inc.sync.aligned.u32 160;");
    bar_sync(0, 512);
    if (EN_ATT) {
    float am[96], ar[24];
    {
      const bool lead = (rtid() & 127) == 0;
      constexpr uint64_t dr0 = mkdesc(SB0 + 12288, 1024, 256, 3);
      const uint64_t db0 = sw64 ? mkdesc(SB0, 2048, 512, 2) : mkdesc(SB0, 4096, 1024, 1);
      const uint32_t kst = sw64 ? 64 : 128, bh = db0 >> 32;
      uint32_t s = 0, ph = 0, xo = 0;
      const int ln = rtid() & 31;
      const uint32_t xa = sb + OFF_X + (warp * 16 + (ln & 15)) * 128 + (((ln >> 4) ^ (ln & 7)) << 4);
      uint32_t A[8];
      mbar_wait(BAR(BR_FULL), 0);
      if (lead && wg == 0) TS(1);
      ldsm4(A, xa); ldsm4(A + 4, xa);
      wg_fence();
      wg_rs48_tb(ar, A + 4, dr0, 0); wg_rs192_tb(am, A + 4, db0, 0);
      wg_commit();
      uint32_t xk = xa, eb = 0;
      #pragma unroll 1
      for (int kb = 0; kb < 20; kb++) {
        const uint32_t wo_ = s * (W_SLOT >> 4), bl = (uint32_t)db0 + wo_, rl = (uint32_t)dr0 + wo_;
        wg_fence();
        wg_rs48_tb(ar, A, desc2(rl, dr0 >> 32), kb != 0);
        wg_rs192_tb(am, A, desc2(bl, bh), kb != 0);
        wg_commit();
        wg_wait<1>();
        ldsm4(A + 4, xk ^ 32);
        if (lead && kb > 0 && kb < 16) mbar_arrive(eb);
        eb = BAR(BR_EMPTY) + 8 * s;
        wg_fence();
        wg_rs48_tb(ar, A + 4, desc2(rl + 32, dr0 >> 32), 1);
        wg_rs192_tb(am, A + 4, desc2(bl + kst, bh), 1);
        wg_commit();
        if (++s == 5) { s = 0; ph ^= 1; }
        if (kb & 1) { xo += 16384; if (xo == 49152) xo = 0; }
        if (kb < 19) mbar_wait(BAR(BR_FULL) + 8 * s, ph);
        xk = (xa + xo) ^ ((~kb & 1) * 64);
        wg_wait<1>();
        ldsm4(A, xk);
      }
      wg_wait<0>();
      pin<96>(am); pin<24>(ar);
    }
    const int tid = rtid(), lane = tid & 31, tq = lane & 3;
    if (tid == 0) TS(2);
#define QV(j, e) ((j) < 8 ? am[4 * (j) + (e)] : ar[4 * ((j) - 8) + (e)])
#define KV_(j, e) ((j) < 8 ? am[32 + 4 * (j) + (e)] : ar[8 + 4 * ((j) - 8) + (e)])
#define VV(j, e) ((j) < 8 ? am[64 + 4 * (j) + (e)] : ar[16 + 4 * ((j) - 8) + (e)])
    {
      bar_sync(1, 256);
      if (tid == 0) mbar_arrive(BAR(BR_GEMM));
      const uint32_t ro = sb + (uint32_t)((warp * 16 + (lane & 15)) * 16);
      const int l0 = 2 * (c & 1) + (lane >> 4);
      const uint32_t ones = (tq == 0) ? 0x00003f80u : 0u;
#define PV(j) pack2(VV(j, 0), VV(j, 1)), pack2(VV(j, 2), VV(j, 3))
#define PK(j) pack2(phi(KV_(j, 0)), phi(KV_(j, 1))), pack2(phi(KV_(j, 2)), phi(KV_(j, 3)))
      stsm4(ro + OFF_V + (5 + 6 * (lane >> 4)) * 2048, ones, ones, ones, ones);
      #pragma unroll
      for (int j = 0; j < 10; j += 2) {
        const int l = (j == 8 && (c & 1)) ? l0 - 2 : l0 + j;
        stsm4(ro + OFF_V + (l + (l >= 5)) * 2048, PV(j), PV(j + 1));
        stsm4(ro + OFF_PK + l * 2048, PK(j), PK(j + 1));
      }
    }
    fence_async();
    bar_sync(1, 256);
    if (tid == 0) TS(3);
    mbar_wait(BAR(BR_EPOCH), 0);
    const unsigned epoch = lds32(sb + OFF_EPOCH);
    {
      float kv[24]; zero<24>(kv);
      constexpr uint64_t da = mkdesc(SB0 + OFF_PK, 128, 2048, 0), db = mkdesc(SB0 + OFF_V, 128, 2048, 0);
      wg_fence();
      #pragma unroll
      for (int s = 0; s < 8; s++) wg_ss48_tt(kv, desc2((uint32_t)da + wg * 640 + s * 16, da >> 32), desc2((uint32_t)db + wg * 768 + s * 16, db >> 32), s != 0);
      wg_commit();
      wg_wait<0>();
      pin<24>(kv);
      if (tid == 0) TS(15);
      if (w4 < 3) {
        const uint32_t wb = sb + OFF_KVS + (wg * 3 + w4) * 1536 + (lane & 15) * 96;
        #pragma unroll
        for (int j = 0; j < 6; j += 2)
          stsm4(wb + (j + (lane >> 4)) * 16, pack2(kv[4 * j], kv[4 * j + 1]), pack2(kv[4 * j + 2], kv[4 * j + 3]),
                pack2(kv[4 * j + 4], kv[4 * j + 5]), pack2(kv[4 * j + 6], kv[4 * j + 7]));
        __syncwarp();
        const int dl = w4 * 16 + (lane & 15), hl = dl >= 20;
        if (dl < 40) {
          uint4* dst = &g_kvp[(c * 16 + r) * 240 + wg * 40 + dl];
          uint32_t v[4], z[4];
          lds128(v, wb + (3 * hl + (lane >> 4)) * 16);
          lds64(z, wb + 32 + 8 * hl); z[2] = lds32(wb + 80); z[3] = epoch & 1u;
          v[3] = (v[3] & ~1u) | z[3];
          st128_rlx(dst + (lane >> 4) * 80, v);
          if (lane < 16) st128_rlx(dst + 160, z);
        }
      }
    }
    fence_async();
    bar_sync(1, 256);
    if (tid == 0) { st_rlx(FLAG(0, r, c), epoch); mbar_arrive(BAR(BR_PUB)); TS(4); }
    const int kvi = (tid >= 80) + (tid >= 160) + (tid >= 240), kd = tid - 80 * kvi;
    const int khd = kd / 20, kt0 = 5 * (khd >> 1) + 2 * (khd & 1);
    const uint32_t rb = sb + OFF_KVB + kd * 16;
    if (kvi < 3) {
      #pragma unroll 1
      for (int m = kvi; m < 7; m += 3) { const int q = kt0 + 3 + m; sts128(rb + (q >= 10 ? q - 10 : q) * 1280, 0, 0, 0, 0); }
    }
    uint32_t qa[20];
    {
      const float sc = 1.44269504089f + __uint_as_float(lds32(sb + OFF_EPOCH) ^ epoch);
      #pragma unroll
      for (int j = 0; j < 10; j++) { qa[2 * j] = pack2(phi(QV(j, 0), sc), phi(QV(j, 1), sc)); qa[2 * j + 1] = pack2(phi(QV(j, 2), sc), phi(QV(j, 3), sc)); }
    }
    if (tid == 0) TS(5);
    if (warp == 7) mbar_wait(BAR(BR_KVP), 0);
    bar_sync(1, 256);
    if (tid == 0) TS(6);
    if (kvi < 3) {
      float s[8];
      zero<8>(s);
      uint32_t bad = 0;
      #pragma unroll 4
      for (int i = 0; i < 16; i++) {
        uint32_t w[4];
        lds128(w, sb + OFF_KVP + tid * 16 + i * 3840);
        bad |= w[3] ^ epoch;
        #pragma unroll
        for (int e = 0; e < 4; e++) { s[2 * e] += bf_lo(w[e]); s[2 * e + 1] += bf_hi(w[e]); }
      }
      if (__builtin_expect(bad & 1u, 0)) {
        zero<8>(s);
        #pragma unroll 1
        for (int i = 0; i < 16; i++) {
          uint32_t w[4] = {0, 0, 0, ~epoch};
          fix128_w3(w, &g_kvp[(c * 16 + i) * 240 + tid], epoch, 1u);
          #pragma unroll
          for (int e = 0; e < 4; e++) { s[2 * e] += bf_lo(w[e]); s[2 * e + 1] += bf_hi(w[e]); }
        }
        FIXCNT
      }
      const uint32_t p0 = pack2(s[0], s[1]), p1 = pack2(s[2], s[3]), p2 = pack2(s[4], s[5]), p3 = pack2(s[6], s[7]);
      if (kvi < 2) sts128(rb + (kt0 + (khd & 1) + kvi) * 1280, p0, p1, p2, p3);
      else {
        const bool od = khd & 1;
        sts128(rb + (5 * (khd >> 1) + 2) * 1280, od ? 0u : p0, od ? 0u : p1, od ? p0 : 0u, od ? p1 : 0u);
        const uint32_t zz = (p2 & 0xffffu) << (16 * (khd & 1));
        sts128(rb + 10 * 1280, khd < 2 ? zz : 0u, khd < 2 ? 0u : zz, 0u, 0u);
      }
    }
    fence_async();
    bar_sync(1, 256);
    if (tid == 0) { mbar_arrive(BAR(BR_SUM)); TS(7); }
    {
      float oa[44]; zero<44>(oa);
      constexpr uint64_t db = mkdesc(SB0 + OFF_KVB, 128, 1280, 0);
      wg_fence();
      #pragma unroll
      for (int s = 0; s < 5; s++) wg_rs88_tb(oa, &qa[4 * s], desc2((uint32_t)db + ((s == 4 && (c & 1)) ? 0 : (s + (c & 1)) * 16), db >> 32), s != 0);
      wg_commit();
      wg_wait<0>();
      pin<44>(oa);
      if (tid == 0) TS(13);
      float rc[4], rd[2][4];
      #pragma unroll
      for (int e = 0; e < 4; e++) asm("rcp.approx.ftz.f32 %0, %1;" : "=f"(rc[e]) : "f"(oa[40 + e] + 1e-6f));
      #pragma unroll
      for (int h = 0; h < 4; h++) {
        rd[0][h] = __shfl_sync(0xffffffff, rc[h & 1], (lane & 28) | (h >> 1));
        rd[1][h] = __shfl_sync(0xffffffff, rc[2 + (h & 1)], (lane & 28) | (h >> 1));
      }
      #pragma unroll
      for (int j = 0; j < 10; j++) {
        #pragma unroll
        for (int h = 0; h < 2; h++) {
          float f;
          if (j == 2) f = tq < 2 ? rd[h][0] : rd[h][1];
          else if (j == 7) f = tq < 2 ? rd[h][2] : rd[h][3];
          else f = rd[h][(8 * j) / 20];
          qa[2 * j + h] = pack2(oa[4 * j + 2 * h] * f, oa[4 * j + 2 * h + 1] * f);
        }
      }
      const uint32_t m0 = (lane & 7) == ((2 * w4) & 7), m1 = (lane & 7) == 2 * w4 + 1;
      const uint32_t oa_ = sb + OFF_EXTRA + (lane >> 4) * 2048 + (warp * 16 + (lane & 15)) * 16;
      bar_sync(1, 256);
#define TAG(v, m) (((v) & ~(m)) | (epoch & (m)))
      #pragma unroll
      for (int s = 0; s < 5; s++) stsm4(oa_ + s * 4096, TAG(qa[4 * s], m0), TAG(qa[4 * s + 1], m1), TAG(qa[4 * s + 2], m0), TAG(qa[4 * s + 3], m1));
    }
    fence_async();
    __syncwarp();
    if (lane == 0) mbar_arrive(BAR(BR_OSTG));
    if (tid == 0) TS(8);
    float oc[40]; zero<40>(oc);
    {
      constexpr uint64_t dw0 = mkdesc(SB0, OFF_WOR, 1024, 1), da0 = mkdesc(SB0, 2048, 128, 0);
      const uint32_t ck = sb + tid * 32 + ((lane >> 2) << 2), ck2 = ck + (wg ? 0 : 16384);
      uint32_t bad = 0;
      auto tile = [&](int i, uint32_t so) {
        const uint32_t al = (uint32_t)da0 + wg * 64 + (so >> 4), wl = (uint32_t)dw0 + i * 640 - (i >> 1) * (1278 << 16);
        wg_fence();
        #pragma unroll
        for (int s = 0; s < 5; s++) wg_ss80_tb(oc, desc2(al + s * 256, da0 >> 32), desc2(wl + s * 128, dw0 >> 32), (i | s) != 0);
        wg_commit();
        bad |= (lds32(ck + so) ^ epoch) | (lds32(ck + so + 8192) ^ epoch) | (lds32(ck2 + so) ^ epoch);
      };
      mbar_wait(BAR(BR_WO), 0);
      mbar_wait(BAR(BR_OSTG), 0);
      tile(0, SLOT(0));
      mbar_wait(BAR(BR_WO + 1), 0);
      #pragma unroll 1
      for (int i = 1; i < 8; i++) {
        if (i == 1) {
          wg_wait<0>();
          if (lane == 0) mbar_arrive(BAR(BR_OEMPTY));
          if (EN_SSM && w4 == 0) mbar_wait(BAR(CONV_AT < 2 ? BR_KS : BR_Y + 1), 0);
          if (w4 == 0) mbar_wait(BAR(BR_OFULL + 1), 0);
          bar_sync(2 + wg, 128);
        }
        mbar_wait(BAR(BR_OFULL) + 8 * i, 0);
        if (i == 1 && tid == 0) TS(9);
        tile(i, SLOT(i));
        wg_wait<1>();
        if (lane == 0 && i > 1) mbar_arrive(BAR(BR_OEMPTY - 1) + 8 * i);
      }
      #pragma unroll 1
      for (int n = 0; n < 56; n++) {
        const int i = n & 7;
        if (i == 0) {
          uint32_t any;
          asm volatile("{\n.reg .pred p;\nsetp.ne.u32 p, %1, 0;\nbarrier.red.or.pred p, 1, 256, p;\nselp.u32 %0, 1, 0, p;\n}" : "=r"(any) : "r"(bad & 1u) : "memory");
          if (!any) break;
          bad = 0;
          FIXCNT
        }
        wg_wait<0>();
        bar_sync(1, 256);
        if (tid == 0) { mbar_expect_tx(BAR(BR_RETRY), 20480); bulk_ld(sb + SLOT(5), &g_o[(r * 8 + CHUNK(i)) * 1280], 20480, BAR(BR_RETRY)); }
        mbar_wait(BAR(BR_RETRY), n & 1);
        tile(i, SLOT(5));
      }
      wg_wait<0>();
      pin<40>(oc);
    }
    if (tid == 0) TS(10);
    {
      const int row = w4 * 16 + (lane & 15);
      const uint32_t ob = sb + OFF_BLK + 2 * BLK + wg * 10240;
      #pragma unroll
      for (int j = 0; j < 8; j += 2)
        stsm4(ob + row * 128 + (((j + (lane >> 4)) ^ (row & 7)) << 4), pack2(oc[4 * j], oc[4 * j + 1]), pack2(oc[4 * j + 2], oc[4 * j + 3]),
              pack2(oc[4 * j + 4], oc[4 * j + 5]), pack2(oc[4 * j + 6], oc[4 * j + 7]));
      stsm4(ob + 8192 + row * 32 + (lane >> 4) * 16, pack2(oc[32], oc[33]), pack2(oc[34], oc[35]), pack2(oc[36], oc[37]), pack2(oc[38], oc[39]));
      fence_async();
      bar_sync(2 + wg, 128);
      if (w4 == 0 && elect_one()) {
        tma2d_st(&prm.m[M_O64], ob, 640 + c * 64, r * 128 + wg * 64);
        tma2d_st(&prm.m[M_O16], ob + 8192, 1152 + c * 16, r * 128 + wg * 64);
        bulk_commit(); bulk_wait0_read();
        if (wg == 0) { TS(11); DUMP(0, 20); }
      }
    }
    }
  } else {
    const int g = lane >> 2, tq = lane & 3, t7 = tid & 127;
    uint32_t raw[5][4], pd;
    {
      #pragma unroll
      for (int e = 0; e < 4; e++)
        #pragma unroll
        for (int q = 0; q < 5; q++) asm volatile("ld.global.nc.u16 %0, [%1];" : "=r"(raw[q][e]) : "l"(prm.par[e] + CHAN(q) * 128 + t7));
      asm volatile("ld.global.nc.u16 %0, [%1];" : "=r"(pd) : "l"(((lane & 8) ? prm.dskip : prm.logdt) + CHAN(lane & 7)));
    }
    asm volatile("setmaxnreg.inc.sync.aligned.u32 136;");
    asm volatile("bar.arrive 0, 512;" ::: "memory");
    if (EN_SSM) {
    {
      #pragma unroll 1
      for (int k = 0; k < 4; k++) {
        const uint32_t z = sb + OFF_BLK + k * BLK + t7 * 16;
        sts128(z + B_TBL, 0, 0, 0, 0); sts128(z + B_TBL + 2048, 0, 0, 0, 0);
      }
      if (t7 < 80) sts128(sb + OFF_BLK + (t7 >> 4) * BLK - 256 + (t7 & 15) * 16, 0, 0, 0, 0);
      const uint32_t ea = sb + OFF_BLK + (2 + (w4 & 1)) * BLK + (lane >> 4) * 7168 + ((lane >> 3) & 1) * 256 + (lane & 7) * 16 + (w4 >> 1) * 2048;
      constexpr uint64_t dE = mkdesc(SB0 + OFF_BLK + 2 * BLK, 128, 512, 0);
      const uint32_t xa = sb + OFF_BLK + 18560 + t7 * 8, xr_ = sb + OFF_BLK + 18560 + (t7 ^ 64) * 8;
      uint32_t pr[5][2];
      #pragma unroll
      for (int q = 0; q < 5; q++) {
        #pragma unroll
        for (int e = 0; e < 2; e++) pr[q][e] = raw[q][2 * e] | (raw[q][2 * e + 1] << 16);
        const uint32_t m = __reduce_max_sync(0xffffffff, max(raw[q][2] & 0x7fffu, raw[q][3] & 0x7fffu));
        if (lane == 0) sts32(sb + OFF_EPOCH + 64 + q * 16 + w4 * 4, m);
      }
      bar_sync(8, 160);
      if (t7 == 0) TS(40);
      const int j = (w4 & 1) * 16 + (w4 >> 1) * 8 + g, i2 = tq < 2 ? 64 * tq + j : 32 * (tq - 2) + j;
      const uint32_t e2 = B_TBL + 4 * (tq < 2 ? T_F3 + (((i2 - 1) & 1) ? 80 : 0) + ((i2 - 1) >> 1) + 16 : T_F2 + (i2 & 1) * 96 + (i2 >> 1));
      const uint32_t e1 = tq < 2 ? (i2 ? e2 - 64 : B_TBL + 4 * (T_F2 + 175)) : B_TBL + 4 * (i2 ? T_F2 + ((2 * i2 - 1) & 3) * 48 + ((2 * i2 - 1) >> 2) : 16 + 511);
      const uint32_t e0 = B_TBL + (16 + 8 * j + 2 * tq) * 4;
      #pragma unroll 1
      for (int it = 0; it < 5; it++) {
        const int k = it;
        const uint32_t blk = sb + OFF_BLK + k * BLK;
        float fac;
        {
          const int q = it;
          if (it == 4) {
            mbar_wait(BAR(BR_UOUT), 0);
            sts128(sb + OFF_UT + B_TBL + t7 * 16, 0, 0, 0, 0); sts128(sb + OFF_UT + B_TBL + 2048 + t7 * 16, 0, 0, 0, 0);
          }
          const uint32_t ga = ea + 4096 - (w4 >> 1) * 512;
#define PUT4(i, a, b, c_, d) sts128(((i) < 8 ? ea + ((i) >> 1) * 512 : ga + (((i) - 8) >> 1) * 512) + ((i) & 1) * 128, a, b, c_, d)
          const uint32_t pa0 = pr[0][0], pc0 = pr[0][1];
          const float dt = bf_round(expf(bf_lo(__shfl_sync(0xffffffff, pd, q))));
          #pragma unroll
          for (int e = 0; e < 2; e++) { pr[0][e] = pr[1][e]; pr[1][e] = pr[2][e]; pr[2][e] = pr[3][e]; pr[3][e] = pr[4][e]; }
          uint32_t mm[4];
          lds128(mm, sb + OFF_EPOCH + 64 + q * 16);
          const uint32_t ex = min(max(max(max(mm[0], mm[1]), max(mm[2], mm[3])) >> 7, 1u), 253u);
          const float sc = __uint_as_float((254u - ex) << 23);
          fac = 2.f * dt * __uint_as_float(ex << 23);
          const float lr = -bf_round(expf(bf_lo(pa0))) * dt * 1.44269504089f;
          const float tn = bf_hi(pa0) * dt * 0.15915494309f;
          float z1r, z1i, z2r, z2i, z4r, z4i, xr[8], xi[8], gr[8], gi[8], wr[9], wi[9];
          cexp_t(lr, -tn, z1r, z1i);
          cexp_t(lr * 8.f, tn * 8.f, xr[1], xi[1]);
          cexp_t(lr * 64.f, tn * 64.f, wr[0], wi[0]);
          xr[0] = 1.f; xi[0] = 0.f;
          cmul(xr[1], xi[1], xr[1], xi[1], xr[2], xi[2]); cmul(xr[2], xi[2], xr[1], xi[1], xr[3], xi[3]);
          cmul(xr[2], xi[2], xr[2], xi[2], xr[4], xi[4]);
          #pragma unroll
          for (int b = 1; b < 4; b++) cmul(xr[4], xi[4], xr[b], xi[b], xr[4 + b], xi[4 + b]);
          cmul(wr[0], wi[0], wr[0], wi[0], wr[1], wi[1]); cmul(wr[1], wi[1], wr[0], wi[0], wr[2], wi[2]);
          cmul(wr[1], wi[1], wr[1], wi[1], wr[3], wi[3]); cmul(wr[3], wi[3], wr[3], wi[3], wr[4], wi[4]);
          cmul(wr[4], wi[4], wr[3], wi[3], wr[5], wi[5]); cmul(wr[4], wi[4], wr[4], wi[4], wr[6], wi[6]);
          cmul(wr[6], wi[6], wr[4], wi[4], wr[7], wi[7]); cmul(wr[6], wi[6], wr[6], wi[6], wr[8], wi[8]);
          uint32_t R[4], I[4], PR[4], PI[4];
          #pragma unroll
          for (int b = 0; b < 4; b++) { R[b] = packh(xr[2 * b], xr[2 * b + 1]); I[b] = packh(xi[2 * b], xi[2 * b + 1]); }
          PUT4(0, R[0], R[1], R[2], R[3]); PUT4(1, I[0], I[1], I[2], I[3]);
          #pragma unroll
          for (int i = 0; i < 3; i++) {
            const uint32_t z = packh(wr[i], wi[i]);
            #pragma unroll
            for (int b = 0; b < 4; b++) hcm2(R[b], I[b], z, PR[b], PI[b]);
            PUT4(2 * i + 2, PR[0], PR[1], PR[2], PR[3]); PUT4(2 * i + 3, PI[0], PI[1], PI[2], PI[3]);
          }
          gr[0] = bf_lo(pc0) * sc; gi[0] = -bf_hi(pc0) * sc;
          cmul(z1r, z1i, z1r, z1i, z2r, z2i); cmul(z2r, z2i, z2r, z2i, z4r, z4i);
          cmul(gr[0], gi[0], z1r, z1i, gr[1], gi[1]);
          cmul(gr[0], gi[0], z2r, z2i, gr[2], gi[2]); cmul(gr[1], gi[1], z2r, z2i, gr[3], gi[3]);
          #pragma unroll
          for (int b = 0; b < 4; b++) cmul(gr[b], gi[b], z4r, z4i, gr[4 + b], gi[4 + b]);
          PUT4(8, packh(gr[0], gr[1]), packh(gr[2], gr[3]), packh(gr[4], gr[5]), packh(gr[6], gr[7]));
          PUT4(9, packh(gi[0], gi[1]), packh(gi[2], gi[3]), packh(gi[4], gi[5]), packh(gi[6], gi[7]));
          {
            const uint32_t z = packh(wr[3], -wi[3]), a4r = packh(gr[0], gr[4]), a4i = packh(gi[0], gi[4]);
            hcm2(packh(gr[0], gr[2]), packh(gi[0], gi[2]), z, PR[0], PI[0]);
            hcm2(packh(gr[4], gr[6]), packh(gi[4], gi[6]), z, PR[1], PI[1]);
            hcm2(a4r, a4i, packh(wr[4], -wi[4]), PR[2], PI[2]);
            hcm2(a4r, a4i, packh(wr[5], -wi[5]), PR[3], PI[3]);
            PUT4(10, PR[0], PR[1], PR[2], PR[3]); PUT4(11, PI[0], PI[1], PI[2], PI[3]);
            float hr, hi_;
            cmul(gr[0], gi[0], wr[3], -wi[3], hr, hi_);
            const uint32_t cr = packh(gr[0], hr), ci = packh(gi[0], hi_);
            #pragma unroll
            for (int i = 0; i < 3; i++) hcm2(cr, ci, packh(wr[6 + i], -wi[6 + i]), PR[i], PI[i]);
            PUT4(12, PR[0], PR[1], PR[2], 0u); PUT4(13, PI[0], PI[1], PI[2], 0u);
          }
          fence_async();
          bar_sync(4, 128);
        }
        float ka[24]; zero<24>(ka);
        wg_fence();
        #pragma unroll
        for (int s = 0; s < 8; s++) {
          const uint64_t d = dE + (s >> 2) * (BLK >> 4) + ((s >> 1) & 1) * 448 + (s & 1) * 16;
          wg_ss48_tt_h(ka, d, d + 256, s != 0);
        }
        wg_commit();
        const float dsk = bf_lo(__shfl_sync(0xffffffff, pd, 8 + it));
        wg_wait<0>();
        pin<24>(ka);
        float kk[6];
        const bool up = w4 >= 2;
        #pragma unroll
        for (int n = 0; n < 3; n++) {
          sts64f(xa + n * BLK, up ? ka[12 + 4 * n] : ka[4 * n + 2], up ? ka[13 + 4 * n] : ka[4 * n + 3]);
          kk[2 * n] = up ? ka[14 + 4 * n] : ka[4 * n]; kk[2 * n + 1] = up ? ka[15 + 4 * n] : ka[4 * n + 1];
        }
        bar_sync(4, 128);
          if (it == 4 && w4 == 0) {
            mbar_wait(BAR(BR_U), 0);
            if (elect_one()) {
              mbar_expect_tx(BAR(BR_U2), 8192);
              bulk_ld(blk - 2 * BLK, g_uy + CHAN(2) * 2048, 4096, BAR(BR_U2)); bulk_ld(blk - BLK, g_uy + CHAN(3) * 2048, 4096, BAR(BR_U2));
            }
            __syncwarp();
          }
        #pragma unroll
        for (int n = 0; n < 3; n++) {
          uint32_t o[2]; lds64(o, xr_ + n * BLK);
          kk[2 * n] = (kk[2 * n] + __uint_as_float(o[0])) * fac; kk[2 * n + 1] = (kk[2 * n + 1] + __uint_as_float(o[1])) * fac;
        }
        if (t7 == 0) kk[0] += dsk;
        {
          const uint32_t v = pack2(kk[1], kk[0]), vh = v >> 16;
          const uint32_t u = pack2(kk[2], kk[3]), w = pack2(kk[4], kk[5]), uu = pack2(kk[2], kk[2]), us = pack2(kk[3], kk[2]);
          const uint32_t x = tq < 2 ? w : u, xh = x >> 16;
          sts32(blk + e0 + 4, v); sts16(blk + e0, vh); sts16(blk + e0 + 10, v);
          sts16(blk + e1, x); sts16(blk + e1 + 6, x); sts16(blk + e2, xh); sts16(blk + e2 + 6, xh);
          if (tq < 2) {
            const uint32_t pb = blk + e0 + 1024 + 8 * tq;
            sts32(pb + 4, uu); sts32(pb + 8, us); sts16(pb + 14, us);
            if (i2) { sts16(pb - 4, u); sts32(pb, uu); }
          }
          if (i2 == 0) {
            const uint32_t tb = blk + B_TBL;
            if (tq == 0) { sts16(tb + (16 + 256) * 4, u); sts16(tb + (T_S + 3) * 4, w); sts32(tb + (T_S + 4) * 4, pack2(kk[4], kk[4])); sts16(tb + (T_S + 5) * 4 + 2, w); }
            else { sts32(tb + 528 * 4, uu); sts32(tb + 529 * 4, uu); sts32(tb + 530 * 4, uu); sts16(tb + 531 * 4 + 2, u); sts16(tb + (T_F3 + 80 + 63) * 4, w); }
          }
        }
        if (t7 == 0) TS(49 + it);
      }
    }
    if (t7 == 0) TS(41);
    mbar_wait(BAR(BR_U), 0);
    bar_sync(4, 128);
    if (EN_ATT) mbar_wait(BAR(BR_GEMM), 0);
    if (t7 == 0) TS(42);
    mbar_wait(BAR(BR_EPOCH), 0);
    const uint32_t ytag = (lds32(sb + OFF_EPOCH) & 1u) * 0x10001u, ym = lane < 4 ? 0x10001u : 0u;
    #pragma unroll 1
    for (int pass = 1; pass >= 0; pass--) {
      const int k = pass ? w4 : 4;
      if (k & 2) mbar_wait(BAR(BR_U2), 0);
      const uint32_t blk = sb + OFF_BLK + k * BLK, tb = blk + B_TBL + (uint32_t)((g - 2 * tq) * 4);
      float acc[16][4];
      zero<64>(&acc[0][0]);
      const int kl = 16 * (lane >> 4) + 2 * (lane & 7) + ((lane >> 3) & 1);
      {
        auto ubase = [&](int sh) { const int q = kl - 2 * sh; return blk + (uint32_t)((q * 16) ^ ((q * 2) & 0x10)); };
#define LDQ(A, sh) _Pragma("unroll") for (int m = 0; m < 4; m++) load_quad(A[m], tb + (16 + 16 * (sh) + 128 * m) * 4);
#define LDB(B, ub, h) _Pragma("unroll") for (int p = 0; p < 4; p++) ldsm4(B[p], (ub) + (4 * (h) + p) * 512);
#define MLO(A, B) _Pragma("unroll") for (int m = 0; m < 4; m++) _Pragma("unroll") for (int cc = 0; cc < 8; cc++) mma16816(acc[cc + m], A[m], &B[cc >> 1][(cc & 1) * 2]);
#define MHI(A, B) _Pragma("unroll") for (int m = 0; m < 4; m++) _Pragma("unroll") for (int cc = 0; cc < 8 - m; cc++) mma16816(acc[8 + cc + m], A[m], &B[cc >> 1][(cc & 1) * 2]);
        int p_ = pass ? 0 : w4;
        const int pe = pass ? 4 : w4 + 1;
        uint32_t A[4][4], A2[4][4], Bl[4][4], Bh[4][4];
        uint32_t ub = ubase(p_ + 4);
        LDQ(A, p_ + 4) LDB(Bl, ub, 0)
        #pragma unroll 1
        for (; p_ < pe; p_++) {
          LDB(Bh, ub, 1)
          MLO(A, Bl)
          ub = ubase(p_);
          LDQ(A2, p_) LDB(Bl, ub, 0)
          MHI(A, Bh)
          LDB(Bh, ub, 1)
          load_quad(A[0], tb + (16 + 512 + 16 * (p_ & 1)) * 4); load_quad(A[1], tb + (T_S + 16 * (p_ & 1)) * 4);
          MLO(A2, Bl)
          if (p_ < 2) {
            #pragma unroll
            for (int cc = 0; cc < 8; cc++) mma16816(acc[cc + 4], A[0], &Bl[cc >> 1][(cc & 1) * 2]);
            #pragma unroll
            for (int cc = 0; cc < 4; cc++) mma16816(acc[cc + 12], A[0], &Bh[cc >> 1][(cc & 1) * 2]);
            #pragma unroll
            for (int cc = 0; cc < 8; cc++) mma16816(acc[cc + 8], A[1], &Bl[cc >> 1][(cc & 1) * 2]);
          }
          const int pn = ((p_ + 1) & 3) + 4;
          ub = ubase(pn);
          LDQ(A, pn) LDB(Bl, ub, 0)
          MHI(A2, Bh)
        }
      }
      if (t7 == 0) TS(57 + 3 * pass);
      mbar_wait(BAR(BR_DRDY + 1), 0);
      {
        const int ih = (lane >> 3) & 1;
        const uint32_t dl = blk + B_D + (uint32_t)(((lane >> 4) * 8 + (lane & 7)) * 16);
        const uint32_t d0_ = dl + ih * 1552, d8_ = dl + (ih ? 0 : 1536), d3_ = dl + B_D7 + ih * 1024;
        auto cls2 = [&](uint32_t da, uint32_t ta) {
          uint32_t B[6][2], A[6][4];
          #pragma unroll
          for (int e = 0; e < 6; e++) { B[e][0] = lds32v(ta + (e + 4) * 32); B[e][1] = lds32v(ta + (e + 3) * 32); }
          #pragma unroll
          for (int kk = 0; kk < 6; kk++) ldsm4t(A[kk], da + kk * 256);
          #pragma unroll
          for (int e = 0; e < 6; e++)
            #pragma unroll
            for (int kk = 0; kk < 6; kk++) if (2 * kk + e + 4 < 16) mma16816(acc[2 * kk + e + 4], A[kk], B[e]);
        };
        auto cls3 = [&](uint32_t da, uint32_t ta) {
          uint32_t B[8][2], A[4][4];
          #pragma unroll
          for (int e = 0; e < 8; e++) { B[e][0] = lds32v(ta + (e + 8) * 32); B[e][1] = lds32v(ta + (e + 7) * 32); }
          #pragma unroll
          for (int kk = 0; kk < 4; kk++) ldsm4t(A[kk], da + kk * 256);
          #pragma unroll
          for (int kk = 0; kk < 4; kk++)
            #pragma unroll
            for (int e = 0; e < 8; e++) if (2 * kk + e + 8 < 16) mma16816(acc[2 * kk + e + 8], A[kk], B[e]);
        };
        if (pass) {
          #pragma unroll 1
          for (int a = 0; a < 2; a++) {
            cls2(d0_ + a * B_D5, tb + (T_F2 + 48 * a - 32) * 4);
            cls2(d8_ + a * B_D5, tb + (T_F2 + 48 * a + 64) * 4);
            cls3(d3_ + a * 2048, tb + (T_F3 + 80 * a - 64) * 4);
          }
        } else {
          cls2(((w4 & 2) ? d8_ : d0_) + (w4 & 1) * B_D5, tb + (T_F2 + 48 * w4 - 32) * 4);
          if (w4 >= 2) cls3(d3_ + (w4 - 2) * 2048, tb + (T_F3 + 80 * (w4 - 2) - 64) * 4);
        }
      }
      if (t7 == 0) TS(58 + 3 * pass);
      const uint32_t ya = blk + (uint32_t)((kl * 16) ^ ((kl * 2) & 0x10));
#define YTAG(v) (((v) & ~ym) | (ytag & ym))
#define STY(p) stsm4t(ya + (p) * 512, YTAG(pack2(acc[2 * (p)][0], acc[2 * (p)][1])), pack2(acc[2 * (p)][2], acc[2 * (p)][3]), \
                      YTAG(pack2(acc[2 * (p) + 1][0], acc[2 * (p) + 1][1])), pack2(acc[2 * (p) + 1][2], acc[2 * (p) + 1][3]))
      if (pass == 0) {
        const uint32_t xw = blk + 4096 + w4 * 4096 + lane * 16, xr = blk + 4096 + w4 * 1024 + lane * 16;
        #pragma unroll
        for (int h = 0; h < 2; h++) {
          bar_sync(4, 128);
          if (h == CONV_AT && t7 == 0) mbar_arrive(BAR(BR_KS));
          #pragma unroll
          for (int i = 0; i < 8; i++)
            sts128(xw + i * 512, __float_as_uint(acc[8 * h + i][0]), __float_as_uint(acc[8 * h + i][1]), __float_as_uint(acc[8 * h + i][2]), __float_as_uint(acc[8 * h + i][3]));
          bar_sync(4, 128);
          float y[8];
          #pragma unroll
          for (int i = 0; i < 8; i++) {
            uint32_t o[4]; lds128(o, xr + (i >> 1) * 4096 + (i & 1) * 512);
            #pragma unroll
            for (int e = 0; e < 4; e++) y[4 * (i & 1) + e] = i < 2 ? __uint_as_float(o[e]) : y[4 * (i & 1) + e] + __uint_as_float(o[e]);
          }
          stsm4t(ya + (4 * h + w4) * 512, YTAG(pack2(y[0], y[1])), pack2(y[2], y[3]), YTAG(pack2(y[4], y[5])), pack2(y[6], y[7]));
        }
      } else {
        __syncwarp();
        #pragma unroll
        for (int p = 0; p < 8; p++) STY(p);
      }
      if (t7 == 0 && !pass) TS(55);
      fence_async();
      __syncwarp();
      if (lane == 0) mbar_arrive(BAR(BR_Y + 1) - 8 * pass);
      if (t7 == 0) TS(59 + 3 * pass);
    }
    if (t7 == 0) DUMP(40, 64);
    }
  }
}

typedef CUresult (*EncFn)(CUtensorMap*, CUtensorMapDataType, cuuint32_t, void*, const cuuint64_t*, const cuuint64_t*, const cuuint32_t*,
                          const cuuint32_t*, CUtensorMapInterleave, CUtensorMapSwizzle, CUtensorMapL2promotion, CUtensorMapFloatOOBfill);
static void mkmap(EncFn enc, CUtensorMap* m, const void* base, int rank, const cuuint64_t* dims, const cuuint64_t* strides, const cuuint32_t* box, CUtensorMapSwizzle swz) {
  cuuint32_t es[5] = {1, 1, 1, 1, 1};
  enc(m, CU_TENSOR_MAP_DATA_TYPE_BFLOAT16, rank, const_cast<void*>(base), dims, strides, box, es, CU_TENSOR_MAP_INTERLEAVE_NONE, swz,
      CU_TENSOR_MAP_L2_PROMOTION_L2_128B, CU_TENSOR_MAP_FLOAT_OOB_FILL_NONE);
}

extern "C" void kernel_launch(void* const* d_in, const int* in_sizes, int n_in, void* d_out, int out_size) {
  void* fn = nullptr; cudaDriverEntryPointQueryResult qr;
  cudaGetDriverEntryPoint("cuTensorMapEncodeTiled", &fn, cudaEnableDefault, &qr);
  EncFn enc = (EncFn)fn;
  void* uy = nullptr; cudaGetSymbolAddress(&uy, g_uy);
  const cuuint64_t dx[2] = {640, 2048}, sx[1] = {1280};
  const cuuint32_t bx[2] = {64, 128}, bu[2] = {80, 128};
  const cuuint64_t dw[3] = {640, 640, 3}, sw[2] = {3840, 1280};
  const cuuint32_t br[3] = {16, 32, 3};
  const cuuint64_t dwa[4] = {64, 640, 10, 3}, swa[3] = {3840, 128, 1280}, dwb[4] = {32, 640, 20, 3}, swb[3] = {3840, 64, 1280};
  const cuuint32_t bwa[4] = {64, 32, 1, 3}, bwb[4] = {32, 32, 2, 3};
  const cuuint64_t dwo[2] = {640, 640};
  const cuuint32_t bwo[2] = {64, 80}, bo64[2] = {64, 64}, bo16[2] = {16, 64};
  const cuuint64_t dsa[2] = {2048, 1280}, ssa[1] = {4096};
  const cuuint32_t bsa[2] = {64, 80}, bsy[2] = {64, 16};
  const cuuint64_t dout[2] = {1280, 2048}, sout[1] = {2560};
  Params prm;
  mkmap(enc, &prm.m[M_X], d_in[7], 2, dx, sx, bx, CU_TENSOR_MAP_SWIZZLE_128B);
  mkmap(enc, &prm.m[M_W128], d_in[8], 4, dwa, swa, bwa, CU_TENSOR_MAP_SWIZZLE_128B);
  mkmap(enc, &prm.m[M_W64], d_in[8], 4, dwb, swb, bwb, CU_TENSOR_MAP_SWIZZLE_64B);
  mkmap(enc, &prm.m[M_WR], d_in[8], 3, dw, sw, br, CU_TENSOR_MAP_SWIZZLE_32B);
  mkmap(enc, &prm.m[M_U], d_in[0], 2, dx, sx, bu, CU_TENSOR_MAP_SWIZZLE_NONE);
  mkmap(enc, &prm.m[M_WO], d_in[9], 2, dwo, sx, bwo, CU_TENSOR_MAP_SWIZZLE_128B);
  mkmap(enc, &prm.m[M_O64], d_out, 2, dout, sout, bo64, CU_TENSOR_MAP_SWIZZLE_128B);
  mkmap(enc, &prm.m[M_O16], d_out, 2, dout, sout, bo16, CU_TENSOR_MAP_SWIZZLE_NONE);
  mkmap(enc, &prm.m[M_SA], uy, 2, dsa, ssa, bsa, CU_TENSOR_MAP_SWIZZLE_128B);
  mkmap(enc, &prm.m[M_SY], uy, 2, dsa, ssa, bsy, CU_TENSOR_MAP_SWIZZLE_128B);
  prm.u = (const __nv_bfloat16*)d_in[0]; prm.wo = (const __nv_bfloat16*)d_in[9];
  for (int i = 0; i < 4; i++) prm.par[i] = (const __nv_bfloat16*)d_in[1 + i];
  prm.logdt = (const __nv_bfloat16*)d_in[5]; prm.dskip = (const __nv_bfloat16*)d_in[6];
  cudaFuncSetAttribute(fused_kernel, cudaFuncAttributeMaxDynamicSharedMemorySize, SMEM_BYTES);
  cudaLaunchConfig_t cfg = {};
  cfg.gridDim = dim3(128); cfg.blockDim = dim3(512); cfg.dynamicSmemBytes = SMEM_BYTES; cfg.stream = cudaStreamPerThread;
  cudaLaunchAttribute at[1];
  at[0].id = cudaLaunchAttributeClusterDimension; at[0].val.clusterDim.x = 2; at[0].val.clusterDim.y = 1; at[0].val.clusterDim.z = 1;
  cfg.attrs = at; cfg.numAttrs = 1;
  cudaLaunchKernelEx(&cfg, fused_kernel, prm);
}
```

```cpp
#include <cuda_runtime.h>
#include <cuda_bf16.h>
#include <cuda_fp16.h>
#include <cuda.h>
#include <stdint.h>

#define KST 2
#define UKB 4
#define UPF 0
#define CONV_AT 1
#define EN_ATT 1
#define EN_SSM 1

__device__ __align__(1024) __nv_bfloat16 g_uy[2 * 640 * 2048];
__device__ __align__(128) uint4 g_kvp[8 * 16 * 240];
__device__ __align__(128) uint4 g_o[128 * 1280];
__device__ __align__(128) unsigned g_flag[4 * 128 * 32];
__device__ unsigned g_epoch[128];
#define TS(i) do {} while (0)
#define DUMP(lo, hi) do {} while (0)
#define FIXCNT

constexpr uint32_t SB0 = 1024;
constexpr uint32_t W_SLOT = 15360, OFF_X = 76800;
constexpr uint32_t OFF_WOR = 81920, OFF_KVP = 10240, OFF_KVS = 71680, OFF_PK = 10240, OFF_V = 30720, OFF_EXTRA = 102400, OFF_KVB = OFF_EXTRA;
constexpr uint32_t OFF_BAR = 125952, OFF_BLK = 128000, BLK = 20480;
constexpr uint32_t B_D = 4096, B_D5 = 3088, B_D7 = 6176, B_D9 = 8224, B_TBL = 14400;
constexpr int T_S = 576, T_F2 = 624, T_F3 = 816;
constexpr uint32_t OFF_UT = OFF_BLK + 4 * BLK;
constexpr uint32_t SMEM_BYTES = OFF_BLK + 5 * BLK;
enum { BR_FULL = 0, BR_WO = 5, BR_PUB = 7, BR_KVP = 8, BR_U = 9, BR_SUM = 10, BR_GEMM = 11, BR_UIN = 12, BR_YIN = 13, BR_EPOCH = 14,
       BR_FREE = 15, BR_RETRY = 17, BR_UOUT = 18, BR_OFULL = 18, BR_KS = 26, BR_EMPTY = 31, BR_OEMPTY = 36, BR_Y = 43, BR_OSTG = 45,
       BR_DRDY = 46, BR_U2 = 48, BR_COUNT = 50 };
constexpr uint32_t OFF_EPOCH = OFF_BAR + 8 * BR_COUNT;
enum { M_X, M_W128, M_W64, M_WR, M_U, M_WO, M_O64, M_O16, M_SA, M_OUT, M_COUNT };

__device__ __forceinline__ long long clk64() { long long t; asm volatile("mov.u64 %0, %%clock64;" : "=l"(t) :: "memory"); return t; }
__device__ __forceinline__ uint32_t smem_u32(const void* p) { return (uint32_t)__cvta_generic_to_shared(p); }
__host__ __device__ constexpr uint64_t mkdesc(uint32_t addr, uint32_t lbo, uint32_t sbo, uint32_t swz) {
  return (uint64_t)((addr & 0x3FFFF) >> 4) | ((uint64_t)(lbo >> 4) << 16) | ((uint64_t)(sbo >> 4) << 32) | ((uint64_t)swz << 62);
}
__device__ __forceinline__ uint64_t desc2(uint32_t lo, uint32_t hi) { uint64_t d; asm("mov.b64 %0, {%1, %2};" : "=l"(d) : "r"(lo), "r"(hi)); return d; }
__device__ __forceinline__ void mbar_init(uint32_t bar, uint32_t cnt) { asm volatile("mbarrier.init.shared::cta.b64 [%0], %1;" :: "r"(bar), "r"(cnt) : "memory"); }
__device__ __forceinline__ void mbar_expect_tx(uint32_t bar, uint32_t bytes) { asm volatile("mbarrier.arrive.expect_tx.shared::cta.b64 _, [%0], %1;" :: "r"(bar), "r"(bytes) : "memory"); }
__device__ __forceinline__ void mbar_arrive(uint32_t bar) { asm volatile("mbarrier.arrive.shared::cta.b64 _, [%0];" :: "r"(bar) : "memory"); }
__device__ __forceinline__ void mbar_wait(uint32_t bar, uint32_t parity) {
  asm volatile("{\n.reg .pred p;\n.reg .u32 c;\nmov.u32 c, 0;\n"
    "WL:\nmbarrier.try_wait.parity.shared::cta.b64 p, [%0], %1;\n@p bra WD;\n"
    "add.u32 c, c, 1;\nsetp.lt.u32 p, c, 200000;\n@p bra WL;\nWD:\n}" :: "r"(bar), "r"(parity) : "memory");
}
__device__ __forceinline__ void poll_all(const unsigned* p, unsigned val) {
  asm volatile("{\n.reg .pred p;\n.reg .u32 c, v;\nmov.u32 c, 0;\n"
    "PL:\nld.relaxed.gpu.global.u32 v, [%0];\nsetp.eq.u32 p, v, %1;\nvote.sync.all.pred p, p, 0xffffffff;\n@p bra PD;\n"
    "add.u32 c, c, 1;\nsetp.lt.u32 p, c, 100000;\n@p bra PL;\nPD:\n}" :: "l"(p), "r"(val) : "memory");
}
__device__ __forceinline__ void poll_all_acq(const unsigned* p, unsigned val) {
  asm volatile("{\n.reg .pred p;\n.reg .u32 c, v;\nmov.u32 c, 0;\n"
    "PL:\nld.acquire.gpu.global.u32 v, [%0];\nsetp.eq.u32 p, v, %1;\nvote.sync.all.pred p, p, 0xffffffff;\n@p bra PD;\n"
    "nanosleep.u32 300;\nadd.u32 c, c, 1;\nsetp.lt.u32 p, c, 100000;\n@p bra PL;\nPD:\n}" :: "l"(p), "r"(val) : "memory");
}
__device__ __forceinline__ unsigned poll_bit(const unsigned* p, unsigned val, unsigned mask) {
  unsigned bal;
  asm volatile("{\n.reg .pred p;\n.reg .u32 c, v;\nmov.u32 c, 0;\n"
    "PL:\nld.relaxed.gpu.global.u32 v, [%1];\nsetp.eq.u32 p, v, %2;\nvote.sync.ballot.b32 %0, p, 0xffffffff;\n"
    "and.b32 v, %0, %3;\nsetp.ne.u32 p, v, 0;\n@p bra PD;\n"
    "add.u32 c, c, 1;\nsetp.lt.u32 p, c, 100000;\n@p bra PL;\nPD:\n}" : "=&r"(bal) : "l"(p), "r"(val), "r"(mask) : "memory");
  return bal;
}
__device__ __forceinline__ void fix128_w0(uint32_t* v, const void* p, uint32_t tag, uint32_t mask) {
  asm volatile("{\n.reg .pred p;\n.reg .u32 c, x;\n.reg .b128 t;\n.reg .b64 lo, hi;\nmov.u32 c, 0;\n"
    "FL:\nxor.b32 x, %0, %5;\nand.b32 x, x, %6;\nsetp.eq.u32 p, x, 0;\n@p bra FD;\n"
    "ld.relaxed.gpu.global.b128 t, [%4];\nmov.b128 {lo, hi}, t;\nmov.b64 {%0, %1}, lo;\nmov.b64 {%2, %3}, hi;\n"
    "add.u32 c, c, 1;\nsetp.lt.u32 p, c, 100000;\n@p bra FL;\nFD:\n}"
    : "+r"(v[0]), "+r"(v[1]), "+r"(v[2]), "+r"(v[3]) : "l"(p), "r"(tag), "r"(mask) : "memory");
}
__device__ __forceinline__ void fix128_w3(uint32_t* v, const void* p, uint32_t tag, uint32_t mask) {
  asm volatile("{\n.reg .pred p;\n.reg .u32 c, x;\n.reg .b128 t;\n.reg .b64 lo, hi;\nmov.u32 c, 0;\n"
    "FL:\nxor.b32 x, %3, %5;\nand.b32 x, x, %6;\nsetp.eq.u32 p, x, 0;\n@p bra FD;\n"
    "ld.relaxed.gpu.global.b128 t, [%4];\nmov.b128 {lo, hi}, t;\nmov.b64 {%0, %1}, lo;\nmov.b64 {%2, %3}, hi;\n"
    "add.u32 c, c, 1;\nsetp.lt.u32 p, c, 100000;\n@p bra FL;\nFD:\n}"
    : "+r"(v[0]), "+r"(v[1]), "+r"(v[2]), "+r"(v[3]) : "l"(p), "r"(tag), "r"(mask) : "memory");
}
__device__ __forceinline__ void fence_acq() { asm volatile("fence.acq_rel.gpu;" ::: "memory"); }
__device__ __forceinline__ bool elect_one() {
  uint32_t p; asm volatile("{\n.reg .pred P;\nelect.sync _|P, 0xffffffff;\nselp.u32 %0, 1, 0, P;\n}" : "=r"(p)); return p;
}
__device__ __forceinline__ void bar_sync(int id, int n) { asm volatile("bar.sync %0, %1;" :: "r"(id), "r"(n) : "memory"); }
__device__ __forceinline__ void fence_async() { asm volatile("fence.proxy.async.shared::cta;" ::: "memory"); }
__device__ __forceinline__ void fence_async_g() { asm volatile("fence.proxy.async.global;" ::: "memory"); }
__device__ __forceinline__ void tma2d(uint32_t dst, const CUtensorMap* m, uint32_t bar, int c0, int c1) {
  asm volatile("cp.async.bulk.tensor.2d.shared::cluster.global.mbarrier::complete_tx::bytes [%0], [%1, {%3, %4}], [%2];"
    :: "r"(dst), "l"(m), "r"(bar), "r"(c0), "r"(c1) : "memory");
}
__device__ __forceinline__ void tma3d(uint32_t dst, const CUtensorMap* m, uint32_t bar, int c0, int c1, int c2) {
  asm volatile("cp.async.bulk.tensor.3d.shared::cluster.global.mbarrier::complete_tx::bytes [%0], [%1, {%3, %4, %5}], [%2];"
    :: "r"(dst), "l"(m), "r"(bar), "r"(c0), "r"(c1), "r"(c2) : "memory");
}
__device__ __forceinline__ void tma4d(uint32_t dst, const CUtensorMap* m, uint32_t bar, int c0, int c1, int c2, int c3) {
  asm volatile("cp.async.bulk.tensor.4d.shared::cluster.global.mbarrier::complete_tx::bytes [%0], [%1, {%3, %4, %5, %6}], [%2];"
    :: "r"(dst), "l"(m), "r"(bar), "r"(c0), "r"(c1), "r"(c2), "r"(c3) : "memory");
}
__device__ __forceinline__ void tma2d_st(const CUtensorMap* m, uint32_t src, int c0, int c1) {
  asm volatile("cp.async.bulk.tensor.2d.global.shared::cta.bulk_group [%0, {%2, %3}], [%1];"
    :: "l"(m), "r"(src), "r"(c0), "r"(c1) : "memory");
}
__device__ __forceinline__ void bulk_ld(uint32_t dst, const void* src, uint32_t bytes, uint32_t bar) {
  asm volatile("cp.async.bulk.shared::cluster.global.mbarrier::complete_tx::bytes [%0], [%1], %2, [%3];"
    :: "r"(dst), "l"(src), "r"(bytes), "r"(bar) : "memory");
}
__device__ __forceinline__ void bulk_st(void* dst, uint32_t src, uint32_t bytes) {
  asm volatile("cp.async.bulk.global.shared::cta.bulk_group [%0], [%1], %2;" :: "l"(dst), "r"(src), "r"(bytes) : "memory");
}
__device__ __forceinline__ void bulk_commit() { asm volatile("cp.async.bulk.commit_group;" ::: "memory"); }
__device__ __forceinline__ void bulk_wait0() { asm volatile("cp.async.bulk.wait_group 0;" ::: "memory"); }
__device__ __forceinline__ void bulk_wait0_read() { asm volatile("cp.async.bulk.wait_group.read 0;" ::: "memory"); }
__device__ __forceinline__ unsigned ld_rlx(const unsigned* p) { unsigned v; asm volatile("ld.relaxed.gpu.global.u32 %0, [%1];" : "=r"(v) : "l"(p) : "memory"); return v; }
__device__ __forceinline__ unsigned ld_acq(const unsigned* p) { unsigned v; asm volatile("ld.acquire.gpu.global.u32 %0, [%1];" : "=r"(v) : "l"(p) : "memory"); return v; }
__device__ __forceinline__ void st_rlx(unsigned* p, unsigned v) { asm volatile("st.relaxed.gpu.global.u32 [%0], %1;" :: "l"(p), "r"(v) : "memory"); }
__device__ __forceinline__ void st_rel(unsigned* p, unsigned v) { asm volatile("st.release.gpu.global.u32 [%0], %1;" :: "l"(p), "r"(v) : "memory"); }
__device__ __forceinline__ void ld128_rlx(uint32_t* v, const void* p) {
  asm volatile("{\n.reg .b128 t;\n.reg .b64 lo, hi;\nld.relaxed.gpu.global.b128 t, [%4];\nmov.b128 {lo, hi}, t;\n"
    "mov.b64 {%0, %1}, lo;\nmov.b64 {%2, %3}, hi;\n}" : "=r"(v[0]), "=r"(v[1]), "=r"(v[2]), "=r"(v[3]) : "l"(p) : "memory");
}
__device__ __forceinline__ void st128_rlx(void* p, const uint32_t* v) {
  asm volatile("{\n.reg .b128 t;\n.reg .b64 lo, hi;\nmov.b64 lo, {%1, %2};\nmov.b64 hi, {%3, %4};\nmov.b128 t, {lo, hi};\n"
    "st.relaxed.gpu.global.b128 [%0], t;\n}" :: "l"(p), "r"(v[0]), "r"(v[1]), "r"(v[2]), "r"(v[3]) : "memory");
}
__device__ __forceinline__ uint32_t lds32(uint32_t a) { uint32_t v; asm volatile("ld.shared.u32 %0, [%1];" : "=r"(v) : "r"(a) : "memory"); return v; }
__device__ __forceinline__ uint32_t lds32v(uint32_t a) { uint32_t v; asm volatile("ld.volatile.shared.u32 %0, [%1];" : "=r"(v) : "r"(a) : "memory"); return v; }
__device__ __forceinline__ uint32_t cpa(uint32_t a, uint32_t one) { uint32_t v; asm volatile("mul.lo.u32 %0, %1, %2;" : "=r"(v) : "r"(a), "r"(one)); return v; }
__device__ __forceinline__ uint32_t cpb(uint32_t a, uint32_t zero) { uint32_t v; asm volatile("or.b32 %0, %1, %2;" : "=r"(v) : "r"(a), "r"(zero)); return v; }
__device__ __forceinline__ uint32_t lds16(uint32_t a) { uint16_t v; asm volatile("ld.shared.u16 %0, [%1];" : "=h"(v) : "r"(a) : "memory"); return v; }
__device__ __forceinline__ float ldsf(uint32_t a) { float v; asm volatile("ld.shared.f32 %0, [%1];" : "=f"(v) : "r"(a) : "memory"); return v; }
__device__ __forceinline__ void lds128(uint32_t* v, uint32_t a) { asm volatile("ld.shared.v4.u32 {%0,%1,%2,%3}, [%4];" : "=r"(v[0]), "=r"(v[1]), "=r"(v[2]), "=r"(v[3]) : "r"(a) : "memory"); }
__device__ __forceinline__ void sts32(uint32_t a, uint32_t v) { asm volatile("st.shared.u32 [%0], %1;" :: "r"(a), "r"(v) : "memory"); }
__device__ __forceinline__ void sts16(uint32_t a, uint32_t v) { asm volatile("st.shared.u16 [%0], %1;" :: "r"(a), "h"((uint16_t)v) : "memory"); }
__device__ __forceinline__ void sts64f(uint32_t a, float x, float y) { asm volatile("st.shared.v2.f32 [%0], {%1,%2};" :: "r"(a), "f"(x), "f"(y) : "memory"); }
__device__ __forceinline__ void sts128(uint32_t a, uint32_t x, uint32_t y, uint32_t z, uint32_t w) { asm volatile("st.shared.v4.u32 [%0], {%1,%2,%3,%4};" :: "r"(a), "r"(x), "r"(y), "r"(z), "r"(w) : "memory"); }
__device__ __forceinline__ void stsm4(uint32_t a, uint32_t r0, uint32_t r1, uint32_t r2, uint32_t r3) {
  asm volatile("stmatrix.sync.aligned.m8n8.x4.shared.b16 [%0], {%1,%2,%3,%4};" :: "r"(a), "r"(r0), "r"(r1), "r"(r2), "r"(r3) : "memory");
}
__device__ __forceinline__ void stsm4t(uint32_t a, uint32_t r0, uint32_t r1, uint32_t r2, uint32_t r3) {
  asm volatile("stmatrix.sync.aligned.m8n8.x4.trans.shared.b16 [%0], {%1,%2,%3,%4};" :: "r"(a), "r"(r0), "r"(r1), "r"(r2), "r"(r3) : "memory");
}
__device__ __forceinline__ void ldsm4t(uint32_t* r, uint32_t a) {
  asm volatile("ldmatrix.sync.aligned.m8n8.x4.trans.shared.b16 {%0,%1,%2,%3}, [%4];" : "=r"(r[0]), "=r"(r[1]), "=r"(r[2]), "=r"(r[3]) : "r"(a) : "memory");
}
__device__ __forceinline__ void ldsm4(uint32_t* r, uint32_t a) {
  asm volatile("ldmatrix.sync.aligned.m8n8.x4.shared.b16 {%0,%1,%2,%3}, [%4];" : "=r"(r[0]), "=r"(r[1]), "=r"(r[2]), "=r"(r[3]) : "r"(a) : "memory");
}
__device__ __forceinline__ void mma16816(float* d, const uint32_t* a, const uint32_t* b) {
  asm volatile("mma.sync.aligned.m16n8k16.row.col.f32.bf16.bf16.f32 {%0,%1,%2,%3}, {%4,%5,%6,%7}, {%8,%9}, {%0,%1,%2,%3};"
    : "+f"(d[0]), "+f"(d[1]), "+f"(d[2]), "+f"(d[3]) : "r"(a[0]), "r"(a[1]), "r"(a[2]), "r"(a[3]), "r"(b[0]), "r"(b[1]));
}
__device__ __forceinline__ uint32_t pack2(float lo, float hi) { uint32_t r; asm("cvt.rn.bf16x2.f32 %0, %1, %2;" : "=r"(r) : "f"(hi), "f"(lo)); return r; }
__device__ __forceinline__ uint32_t packh(float lo, float hi) { uint32_t r; asm("cvt.rn.f16x2.f32 %0, %1, %2;" : "=r"(r) : "f"(hi), "f"(lo)); return r; }
__device__ __forceinline__ uint32_t hcmul(uint32_t x, uint32_t zp, uint32_t zq) {
  const __half2 xx = *reinterpret_cast<__half2*>(&x);
  const __half2 r = __hfma2(__high2half2(xx), *reinterpret_cast<__half2*>(&zq), __hmul2(__low2half2(xx), *reinterpret_cast<__half2*>(&zp)));
  return *reinterpret_cast<const uint32_t*>(&r);
}
__device__ __forceinline__ void hcm2(uint32_t xr, uint32_t xi, uint32_t z, uint32_t& pr, uint32_t& pi) {
  const __half2 a = *reinterpret_cast<__half2*>(&xr), b = *reinterpret_cast<__half2*>(&xi), zz = *reinterpret_cast<__half2*>(&z);
  const __half2 re = __hfma2(__hneg2(b), __high2half2(zz), __hmul2(a, __low2half2(zz)));
  const __half2 im = __hfma2(a, __high2half2(zz), __hmul2(b, __low2half2(zz)));
  pr = *reinterpret_cast<const uint32_t*>(&re); pi = *reinterpret_cast<const uint32_t*>(&im);
}
__device__ __forceinline__ void sts64(uint32_t a, uint32_t x, uint32_t y) { asm volatile("st.shared.v2.u32 [%0], {%1,%2};" :: "r"(a), "r"(x), "r"(y) : "memory"); }
__device__ __forceinline__ void lds64(uint32_t* v, uint32_t a) { asm volatile("ld.shared.v2.u32 {%0,%1}, [%2];" : "=r"(v[0]), "=r"(v[1]) : "r"(a) : "memory"); }
__device__ __forceinline__ float bf_lo(uint32_t v) { return __uint_as_float(v << 16); }
__device__ __forceinline__ float bf_hi(uint32_t v) { return __uint_as_float(v & 0xffff0000u); }
__device__ __forceinline__ float bf_round(float x) { return bf_lo(pack2(x, 0.f)); }
__device__ __forceinline__ float ex2(float x) { float r; asm("ex2.approx.ftz.f32 %0, %1;" : "=f"(r) : "f"(x)); return r; }
__device__ __forceinline__ float phi(float t, float l2e = 1.44269504089f) {
  float e = ex2(t * l2e) + 1e-6f;
  asm("{\n.reg .pred p;\nsetp.gt.f32 p, %1, 0f00000000;\n@p add.f32 %0, %1, 0f3F800008;\n}" : "+f"(e) : "f"(t));
  return e;
}
__device__ __forceinline__ void wg_fence() { asm volatile("wgmma.fence.sync.aligned;" ::: "memory"); }
__device__ __forceinline__ void wg_commit() { asm volatile("wgmma.commit_group.sync.aligned;" ::: "memory"); }
template <int N> __device__ __forceinline__ void wg_wait() { asm volatile("wgmma.wait_group.sync.aligned %0;" :: "n"(N) : "memory"); }
template <int N> __device__ __forceinline__ void pin(float* a) {
  #pragma unroll
  for (int i = 0; i < N; i++) asm volatile("" : "+f"(a[i]) :: "memory");
}
__device__ __forceinline__ int rtid() { int t; asm volatile("mov.u32 %0, %%tid.x;" : "=r"(t)); return t; }
__device__ __forceinline__ int opaque(int v) { asm volatile("" : "+r"(v)); return v; }
template <int N> __device__ __forceinline__ void zero(float* a) {
  #pragma unroll
  for (int i = 0; i < N; i++) asm volatile("mov.b32 %0, 0;" : "=f"(a[i]));
}
template <int N> __device__ __forceinline__ void pinu(uint32_t* a) {
  #pragma unroll
  for (int i = 0; i < N; i++) asm volatile("" : "+r"(a[i]) :: "memory");
}
__device__ __forceinline__ void cexp_t(float lg2mag, float turns, float& re, float& im) {
  float m = ex2(lg2mag);
  float fr = (turns - __fadd_rn(__fadd_rn(turns, 12582912.f), -12582912.f)) * 6.283185307f;
  re = m * __cosf(fr); im = m * __sinf(fr);
}
__device__ __forceinline__ void cmul(float ar, float ai, float br, float bi, float& cr, float& ci) {
  cr = fmaf(ar, br, -ai * bi); ci = fmaf(ar, bi, ai * br);
}

__device__ __forceinline__ void wg_ss48_tt(float* d, uint64_t da, uint64_t db, int scale_d) {
  asm volatile("{\n.reg .pred p;\nsetp.ne.b32 p, %26, 0;\n"
    "wgmma.mma_async.sync.aligned.m64n48k16.f32.bf16.bf16 "
    "{%0, %1, %2, %3, %4, %5, %6, %7, %8, %9, %10, %11, %12, %13, %14, %15, %16, %17, %18, %19, %20, %21, %22, %23}, %24, %25, p, 1, 1, 1, 1;\n}\n"
    : "+f"(d[0]), "+f"(d[1]), "+f"(d[2]), "+f"(d[3]), "+f"(d[4]), "+f"(d[5]), "+f"(d[6]), "+f"(d[7]), "+f"(d[8]), "+f"(d[9]), "+f"(d[10]), "+f"(d[11]), "+f"(d[12]), "+f"(d[13]), "+f"(d[14]), "+f"(d[15]), "+f"(d[16]), "+f"(d[17]), "+f"(d[18]), "+f"(d[19]), "+f"(d[20]), "+f"(d[21]), "+f"(d[22]), "+f"(d[23])
    : "l"(da), "l"(db), "r"(scale_d));
}
__device__ __forceinline__ void wg_rs88_tb(float* d, const uint32_t* a, uint64_t db, int scale_d) {
  asm volatile("{\n.reg .pred p;\nsetp.ne.b32 p, %49, 0;\n"
    "wgmma.mma_async.sync.aligned.m64n88k16.f32.bf16.bf16 "
    "{%0, %1, %2, %3, %4, %5, %6, %7, %8, %9, %10, %11, %12, %13, %14, %15, %16, %17, %18, %19, %20, %21, %22, %23, %24, %25, %26, %27, %28, %29, %30, %31, %32, %33, %34, %35, %36, %37, %38, %39, %40, %41, %42, %43}, {%44, %45, %46, %47}, %48, p, 1, 1, 1;\n}\n"
    : "+f"(d[0]), "+f"(d[1]), "+f"(d[2]), "+f"(d[3]), "+f"(d[4]), "+f"(d[5]), "+f"(d[6]), "+f"(d[7]), "+f"(d[8]), "+f"(d[9]), "+f"(d[10]), "+f"(d[11]), "+f"(d[12]), "+f"(d[13]), "+f"(d[14]), "+f"(d[15]), "+f"(d[16]), "+f"(d[17]), "+f"(d[18]), "+f"(d[19]), "+f"(d[20]), "+f"(d[21]), "+f"(d[22]), "+f"(d[23]), "+f"(d[24]), "+f"(d[25]), "+f"(d[26]), "+f"(d[27]), "+f"(d[28]), "+f"(d[29]), "+f"(d[30]), "+f"(d[31]), "+f"(d[32]), "+f"(d[33]), "+f"(d[34]), "+f"(d[35]), "+f"(d[36]), "+f"(d[37]), "+f"(d[38]), "+f"(d[39]), "+f"(d[40]), "+f"(d[41]), "+f"(d[42]), "+f"(d[43])
    : "r"(a[0]), "r"(a[1]), "r"(a[2]), "r"(a[3]), "l"(db), "r"(scale_d));
}
__device__ __forceinline__ void wg_ss80_tb(float* d, uint64_t da, uint64_t db, int scale_d) {
  asm volatile("{\n.reg .pred p;\nsetp.ne.b32 p, %42, 0;\n"
    "wgmma.mma_async.sync.aligned.m64n80k16.f32.bf16.bf16 "
    "{%0, %1, %2, %3, %4, %5, %6, %7, %8, %9, %10, %11, %12, %13, %14, %15, %16, %17, %18, %19, %20, %21, %22, %23, %24, %25, %26, %27, %28, %29, %30, %31, %32, %33, %34, %35, %36, %37, %38, %39}, %40, %41, p, 1, 1, 0, 1;\n}\n"
    : "+f"(d[0]), "+f"(d[1]), "+f"(d[2]), "+f"(d[3]), "+f"(d[4]), "+f"(d[5]), "+f"(d[6]), "+f"(d[7]), "+f"(d[8]), "+f"(d[9]), "+f"(d[10]), "+f"(d[11]), "+f"(d[12]), "+f"(d[13]), "+f"(d[14]), "+f"(d[15]), "+f"(d[16]), "+f"(d[17]), "+f"(d[18]), "+f"(d[19]), "+f"(d[20]), "+f"(d[21]), "+f"(d[22]), "+f"(d[23]), "+f"(d[24]), "+f"(d[25]), "+f"(d[26]), "+f"(d[27]), "+f"(d[28]), "+f"(d[29]), "+f"(d[30]), "+f"(d[31]), "+f"(d[32]), "+f"(d[33]), "+f"(d[34]), "+f"(d[35]), "+f"(d[36]), "+f"(d[37]), "+f"(d[38]), "+f"(d[39])
    : "l"(da), "l"(db), "r"(scale_d));
}
__device__ __forceinline__ void wg_ss48_tt_h(float* d, uint64_t da, uint64_t db, int scale_d) {
  asm volatile("{\n.reg .pred p;\nsetp.ne.b32 p, %26, 0;\n"
    "wgmma.mma_async.sync.aligned.m64n48k16.f32.f16.f16 "
    "{%0, %1, %2, %3, %4, %5, %6, %7, %8, %9, %10, %11, %12, %13, %14, %15, %16, %17, %18, %19, %20, %21, %22, %23}, %24, %25, p, 1, 1, 1, 1;\n}\n"
    : "+f"(d[0]), "+f"(d[1]), "+f"(d[2]), "+f"(d[3]), "+f"(d[4]), "+f"(d[5]), "+f"(d[6]), "+f"(d[7]), "+f"(d[8]), "+f"(d[9]), "+f"(d[10]), "+f"(d[11]), "+f"(d[12]), "+f"(d[13]), "+f"(d[14]), "+f"(d[15]), "+f"(d[16]), "+f"(d[17]), "+f"(d[18]), "+f"(d[19]), "+f"(d[20]), "+f"(d[21]), "+f"(d[22]), "+f"(d[23])
    : "l"(da), "l"(db), "r"(scale_d));
}
__device__ __forceinline__ void wg_rs192_tb(float* d, const uint32_t* a, uint64_t db, int scale_d) {
  asm volatile("{\n.reg .pred p;\nsetp.ne.b32 p, %101, 0;\n"
    "wgmma.mma_async.sync.aligned.m64n192k16.f32.bf16.bf16 "
    "{%0, %1, %2, %3, %4, %5, %6, %7, %8, %9, %10, %11, %12, %13, %14, %15, %16, %17, %18, %19, %20, %21, %22, %23, %24, %25, %26, %27, %28, %29, %30, %31, %32, %33, %34, %35, %36, %37, %38, %39, %40, %41, %42, %43, %44, %45, %46, %47, %48, %49, %50, %51, %52, %53, %54, %55, %56, %57, %58, %59, %60, %61, %62, %63, %64, %65, %66, %67, %68, %69, %70, %71, %72, %73, %74, %75, %76, %77, %78, %79, %80, %81, %82, %83, %84, %85, %86, %87, %88, %89, %90, %91, %92, %93, %94, %95}, {%96, %97, %98, %99}, %100, p, 1, 1, 1;\n}\n"
    : "+f"(d[0]), "+f"(d[1]), "+f"(d[2]), "+f"(d[3]), "+f"(d[4]), "+f"(d[5]), "+f"(d[6]), "+f"(d[7]), "+f"(d[8]), "+f"(d[9]), "+f"(d[10]), "+f"(d[11]), "+f"(d[12]), "+f"(d[13]), "+f"(d[14]), "+f"(d[15]), "+f"(d[16]), "+f"(d[17]), "+f"(d[18]), "+f"(d[19]), "+f"(d[20]), "+f"(d[21]), "+f"(d[22]), "+f"(d[23]), "+f"(d[24]), "+f"(d[25]), "+f"(d[26]), "+f"(d[27]), "+f"(d[28]), "+f"(d[29]), "+f"(d[30]), "+f"(d[31]), "+f"(d[32]), "+f"(d[33]), "+f"(d[34]), "+f"(d[35]), "+f"(d[36]), "+f"(d[37]), "+f"(d[38]), "+f"(d[39]), "+f"(d[40]), "+f"(d[41]), "+f"(d[42]), "+f"(d[43]), "+f"(d[44]), "+f"(d[45]), "+f"(d[46]), "+f"(d[47]), "+f"(d[48]), "+f"(d[49]), "+f"(d[50]), "+f"(d[51]), "+f"(d[52]), "+f"(d[53]), "+f"(d[54]), "+f"(d[55]), "+f"(d[56]), "+f"(d[57]), "+f"(d[58]), "+f"(d[59]), "+f"(d[60]), "+f"(d[61]), "+f"(d[62]), "+f"(d[63]), "+f"(d[64]), "+f"(d[65]), "+f"(d[66]), "+f"(d[67]), "+f"(d[68]), "+f"(d[69]), "+f"(d[70]), "+f"(d[71]), "+f"(d[72]), "+f"(d[73]), "+f"(d[74]), "+f"(d[75]), "+f"(d[76]), "+f"(d[77]), "+f"(d[78]), "+f"(d[79]), "+f"(d[80]), "+f"(d[81]), "+f"(d[82]), "+f"(d[83]), "+f"(d[84]), "+f"(d[85]), "+f"(d[86]), "+f"(d[87]), "+f"(d[88]), "+f"(d[89]), "+f"(d[90]), "+f"(d[91]), "+f"(d[92]), "+f"(d[93]), "+f"(d[94]), "+f"(d[95])
    : "r"(a[0]), "r"(a[1]), "r"(a[2]), "r"(a[3]), "l"(db), "r"(scale_d));
}
__device__ __forceinline__ void wg_rs48_tb(float* d, const uint32_t* a, uint64_t db, int scale_d) {
  asm volatile("{\n.reg .pred p;\nsetp.ne.b32 p, %29, 0;\n"
    "wgmma.mma_async.sync.aligned.m64n48k16.f32.bf16.bf16 "
    "{%0, %1, %2, %3, %4, %5, %6, %7, %8, %9, %10, %11, %12, %13, %14, %15, %16, %17, %18, %19, %20, %21, %22, %23}, {%24, %25, %26, %27}, %28, p, 1, 1, 1;\n}\n"
    : "+f"(d[0]), "+f"(d[1]), "+f"(d[2]), "+f"(d[3]), "+f"(d[4]), "+f"(d[5]), "+f"(d[6]), "+f"(d[7]), "+f"(d[8]), "+f"(d[9]), "+f"(d[10]), "+f"(d[11]), "+f"(d[12]), "+f"(d[13]), "+f"(d[14]), "+f"(d[15]), "+f"(d[16]), "+f"(d[17]), "+f"(d[18]), "+f"(d[19]), "+f"(d[20]), "+f"(d[21]), "+f"(d[22]), "+f"(d[23])
    : "r"(a[0]), "r"(a[1]), "r"(a[2]), "r"(a[3]), "l"(db), "r"(scale_d));
}
__device__ __forceinline__ void wg_ss192_tb(float* d, uint64_t da, uint64_t db, int scale_d) {
  asm volatile("{\n.reg .pred p;\nsetp.ne.b32 p, %98, 0;\n"
    "wgmma.mma_async.sync.aligned.m64n192k16.f32.bf16.bf16 "
    "{%0, %1, %2, %3, %4, %5, %6, %7, %8, %9, %10, %11, %12, %13, %14, %15, %16, %17, %18, %19, %20, %21, %22, %23, %24, %25, %26, %27, %28, %29, %30, %31, %32, %33, %34, %35, %36, %37, %38, %39, %40, %41, %42, %43, %44, %45, %46, %47, %48, %49, %50, %51, %52, %53, %54, %55, %56, %57, %58, %59, %60, %61, %62, %63, %64, %65, %66, %67, %68, %69, %70, %71, %72, %73, %74, %75, %76, %77, %78, %79, %80, %81, %82, %83, %84, %85, %86, %87, %88, %89, %90, %91, %92, %93, %94, %95}, %96, %97, p, 1, 1, 0, 1;\n}\n"
    : "+f"(d[0]), "+f"(d[1]), "+f"(d[2]), "+f"(d[3]), "+f"(d[4]), "+f"(d[5]), "+f"(d[6]), "+f"(d[7]), "+f"(d[8]), "+f"(d[9]), "+f"(d[10]), "+f"(d[11]), "+f"(d[12]), "+f"(d[13]), "+f"(d[14]), "+f"(d[15]), "+f"(d[16]), "+f"(d[17]), "+f"(d[18]), "+f"(d[19]), "+f"(d[20]), "+f"(d[21]), "+f"(d[22]), "+f"(d[23]), "+f"(d[24]), "+f"(d[25]), "+f"(d[26]), "+f"(d[27]), "+f"(d[28]), "+f"(d[29]), "+f"(d[30]), "+f"(d[31]), "+f"(d[32]), "+f"(d[33]), "+f"(d[34]), "+f"(d[35]), "+f"(d[36]), "+f"(d[37]), "+f"(d[38]), "+f"(d[39]), "+f"(d[40]), "+f"(d[41]), "+f"(d[42]), "+f"(d[43]), "+f"(d[44]), "+f"(d[45]), "+f"(d[46]), "+f"(d[47]), "+f"(d[48]), "+f"(d[49]), "+f"(d[50]), "+f"(d[51]), "+f"(d[52]), "+f"(d[53]), "+f"(d[54]), "+f"(d[55]), "+f"(d[56]), "+f"(d[57]), "+f"(d[58]), "+f"(d[59]), "+f"(d[60]), "+f"(d[61]), "+f"(d[62]), "+f"(d[63]), "+f"(d[64]), "+f"(d[65]), "+f"(d[66]), "+f"(d[67]), "+f"(d[68]), "+f"(d[69]), "+f"(d[70]), "+f"(d[71]), "+f"(d[72]), "+f"(d[73]), "+f"(d[74]), "+f"(d[75]), "+f"(d[76]), "+f"(d[77]), "+f"(d[78]), "+f"(d[79]), "+f"(d[80]), "+f"(d[81]), "+f"(d[82]), "+f"(d[83]), "+f"(d[84]), "+f"(d[85]), "+f"(d[86]), "+f"(d[87]), "+f"(d[88]), "+f"(d[89]), "+f"(d[90]), "+f"(d[91]), "+f"(d[92]), "+f"(d[93]), "+f"(d[94]), "+f"(d[95])
    : "l"(da), "l"(db), "r"(scale_d));
}
__device__ __forceinline__ void wg_ss48_tb(float* d, uint64_t da, uint64_t db, int scale_d) {
  asm volatile("{\n.reg .pred p;\nsetp.ne.b32 p, %26, 0;\n"
    "wgmma.mma_async.sync.aligned.m64n48k16.f32.bf16.bf16 "
    "{%0, %1, %2, %3, %4, %5, %6, %7, %8, %9, %10, %11, %12, %13, %14, %15, %16, %17, %18, %19, %20, %21, %22, %23}, %24, %25, p, 1, 1, 0, 1;\n}\n"
    : "+f"(d[0]), "+f"(d[1]), "+f"(d[2]), "+f"(d[3]), "+f"(d[4]), "+f"(d[5]), "+f"(d[6]), "+f"(d[7]), "+f"(d[8]), "+f"(d[9]), "+f"(d[10]), "+f"(d[11]), "+f"(d[12]), "+f"(d[13]), "+f"(d[14]), "+f"(d[15]), "+f"(d[16]), "+f"(d[17]), "+f"(d[18]), "+f"(d[19]), "+f"(d[20]), "+f"(d[21]), "+f"(d[22]), "+f"(d[23])
    : "l"(da), "l"(db), "r"(scale_d));
}

struct Params {
  const __nv_bfloat16 *par[4], *logdt, *dskip, *u, *wo;
  CUtensorMap m[M_COUNT];
};

#define CHUNK(i) ((i) == 0 ? c : ((i) == 7 ? (c ^ 1) : (((c & 6) + 1 + (i)) & 7)))
#define FLAG(kind, rr, cc) (&g_flag[((kind) * 128 + (rr) * 8 + (cc)) * 32])
#define SLOT(i) ((i) == 0 ? OFF_EXTRA : OFF_BLK - 256 + ((i) > 5 ? (i) - 6 : (i) - 1) * BLK)
__device__ __forceinline__ void load_quad(uint32_t* A, uint32_t addr) {
  A[0] = lds32v(addr); A[1] = lds32v(addr + 32); A[2] = lds32v(addr - 32); A[3] = lds32v(addr);
}

__device__ __forceinline__ bool y_transpose(uint32_t sb, int w5, int lane, uint32_t ytag) {
  const int mi = lane >> 3, rw = lane & 7;
  const uint32_t sa = sb + OFF_EXTRA + (w5 * 16 + rw) * 128 + ((mi ^ rw) << 4), da = sb + SLOT(3) + (8 * mi + rw) * 160 + w5 * 32;
  const uint32_t ym = lane < 4 ? 0x10001u : 0u;
  bar_sync(7, 160);
  uint32_t v[8][4], bad = 0;
  #pragma unroll
  for (int q = 0; q < 8; q++) ldsm4t(v[q], (sa ^ ((q & 1) * 64 + ((q >> 1) & 1) * 16)) + ((q >> 1) & 1) * 10240 + (q >> 2) * 1024);
  #pragma unroll
  for (int q = 0; q < 8; q++) {
    bad |= (v[q][0] ^ ytag) | (v[q][2] ^ ytag);
    stsm4(da + (q & 3) * 5120 + (q >> 2) * 16, v[q][0] & ~ym, v[q][1], v[q][2] & ~ym, v[q][3]);
  }
  fence_async();
  uint32_t any;
  asm volatile("{\n.reg .pred p;\nsetp.ne.u32 p, %1, 0;\nbarrier.red.or.pred p, 7, 160, p;\nselp.u32 %0, 1, 0, p;\n}" : "=r"(any) : "r"(bad & ym) : "memory");
  return any;
}

__global__ void __launch_bounds__(512, 1) fused_kernel(const __grid_constant__ Params prm) {
  extern __shared__ unsigned char smem_raw[];
  const uint32_t sb = __shfl_sync(0xffffffff, smem_u32(smem_raw), 0);
  const int tid = threadIdx.x, lane = tid & 31;
  const int warp = __shfl_sync(0xffffffff, tid >> 5, 0), wg = warp >> 2, w4 = warp & 3;
  const int cta = blockIdx.x, r = cta >> 3, c = cta & 7;
  if ((sb & 0xffffffu) != SB0) return;
#define BAR(i) (sb + OFF_BAR + 8 * (i))
  const bool sw64 = ((c + 1) & 2) != 0;

  const CUtensorMap* mwp = &prm.m[sw64 ? M_W64 : M_W128];
  const int mcol = (c * 80 + (c & 1) * 16) >> (sw64 ? 5 : 6), rcol = c * 80 + ((c & 1) ? 0 : 64);
  if (warp == 12 && elect_one()) {
    #pragma unroll
    for (int i = 0; i < 5; i++) mbar_init(BAR(BR_FULL + i), 1);
    asm volatile("fence.mbarrier_init.release.cluster;" ::: "memory");
    if (EN_ATT) {
      mbar_expect_tx(BAR(BR_FULL), W_SLOT + 16384);
      tma4d(sb, mwp, BAR(BR_FULL), 0, 0, mcol, 0);
      tma2d(sb + OFF_X, &prm.m[M_X], BAR(BR_FULL), 0, r * 128);
      tma3d(sb + 12288, &prm.m[M_WR], BAR(BR_FULL), rcol, 0, 0);
      mbar_expect_tx(BAR(BR_FULL + 1), W_SLOT);
      tma4d(sb + W_SLOT, mwp, BAR(BR_FULL + 1), 0, 32, mcol, 0);
      tma3d(sb + W_SLOT + 12288, &prm.m[M_WR], BAR(BR_FULL + 1), rcol, 32, 0);
      TS(24);
    }
  }
  if (warp == 13 && elect_one()) {
    asm volatile("prefetch.tensormap [%0];" :: "l"(&prm.m[M_X]) : "memory");
    asm volatile("prefetch.tensormap [%0];" :: "l"(&prm.m[M_WR]) : "memory");
  }
  if (wg == 3) {
    asm volatile("setmaxnreg.dec.sync.aligned.u32 56;");
    const int tid = rtid(), lane = tid & 31;
    if (warp == 12) {
      asm volatile("bar.arrive 0, 512;" ::: "memory");
      {
        uint32_t s = 2, ph = 1, xs = 16384;
        #pragma unroll 1
        for (int kb = 2; kb < 20; kb++) {
          if (kb == 4) bar_sync(6, 128);
          if (kb >= 5) mbar_wait(BAR(BR_EMPTY) + 8 * s, ph);
          if (EN_ATT && elect_one()) {
            const uint32_t st = sb + s * W_SLOT, fb = BAR(BR_FULL) + 8 * s;
            mbar_expect_tx(fb, (kb & 1) ? W_SLOT : W_SLOT + 16384);
            if (!(kb & 1)) tma2d(sb + OFF_X + xs, &prm.m[M_X], fb, kb * 32, r * 128);
            tma4d(st, mwp, fb, 0, kb * 32, mcol, 0);
            tma3d(st + 12288, &prm.m[M_WR], fb, rcol, kb * 32, 0);
          }
          if (kb < 4 && lane == 0) TS(24 + kb);
          if (UPF && kb >= UKB - 4 && kb < UKB && elect_one())
            asm volatile("cp.async.bulk.prefetch.L2.global [%0], 5120;" :: "l"(prm.u + cta * 10240 + (kb - (UKB - 4)) * 2560) : "memory");
          if (EN_SSM && kb == (EN_ATT ? UKB : 4) && elect_one()) { mbar_expect_tx(BAR(BR_UIN), 20480); tma2d(sb + OFF_UT, &prm.m[M_U], BAR(BR_UIN), c * 80, r * 128); }
          if (kb == 14 && elect_one()) asm volatile("cp.async.bulk.prefetch.L2.global [%0], 6400;" :: "l"(prm.wo + cta * 3200) : "memory");
          if (!EN_ATT && kb == 4) break;
          if (++s == 5) { s = 0; ph ^= 1; }
          if (kb & 1) { xs += 16384; if (xs == 49152) xs = 0; }
        }
      }
      if (EN_ATT) {
      mbar_wait(BAR(BR_EPOCH), 0);
      const unsigned epoch = lds32(sb + OFF_EPOCH);
      const unsigned* fo = FLAG(3, r, lane & 7);
      unsigned seen = __ballot_sync(0xffffffff, ld_rlx(lane < 16 ? fo : FLAG(0, lane & 15, c)) == epoch) & 0xffu;
      mbar_wait(BAR(BR_GEMM), 0);
      if (elect_one()) {
        mbar_expect_tx(BAR(BR_WO), 10240);
        tma2d(sb, &prm.m[M_WO], BAR(BR_WO), c * 64, c * 80);
        mbar_expect_tx(BAR(BR_KVP), 61440);
        mbar_expect_tx(BAR(BR_WO + 1), 7 * 10240);
      }
      {
        uint32_t ds = sb + OFF_WOR + (lane >> 3) * 128 + (((lane & 7) ^ (lane >> 3)) << 4);
        #pragma unroll 1
        for (int h = 0; h < 2; h++) {
          const int i = (lane & 6) + h;
          const char* gs = reinterpret_cast<const char*>(prm.wo) + (size_t)((lane >> 3) + CHUNK(i) * 80) * 1280 + 1024 + c * 32 + (lane & 1) * 16;
          #pragma unroll 2
          for (int q = 0; q < 20; q++) {
            asm volatile("cp.async.cg.shared.global [%0], [%1], 16;" :: "r"(ds), "l"(gs) : "memory");
            ds = (ds + 512) ^ 64; gs += 5120;
          }
        }
      }
      mbar_wait(BAR(BR_PUB), 0);
      poll_all(FLAG(0, lane & 15, c), epoch);
      if (elect_one()) { TS(23); bulk_ld(sb + OFF_KVP, &g_kvp[c * 16 * 240], 61440, BAR(BR_KVP)); }
      asm volatile("cp.async.wait_all;" ::: "memory");
      fence_async();
      mbar_arrive(BAR(BR_WO));
      mbar_wait(BAR(BR_SUM), 0);
      if (elect_one()) {
        #pragma unroll 1
        for (int i = 1; i < 8; i++) tma2d(sb + i * 10240, &prm.m[M_WO], BAR(BR_WO + 1), c * 64, CHUNK(i) * 80);
      }
      mbar_wait(BAR(BR_OSTG), 0);
      if (elect_one()) {
        bulk_st(&g_o[cta * 1280], sb + OFF_EXTRA, 20480);
        bulk_commit();
        bulk_wait0();
        st_rlx(FLAG(3, r, c), epoch);
        mbar_arrive(BAR(BR_OEMPTY));
        TS(20);
      }
      __syncwarp();
      #pragma unroll 1
      for (int i = 1; i < 8; i++) {
        const int src = CHUNK(i);
        if (!((seen >> src) & 1)) seen = poll_bit(fo, epoch, 1u << src);
        if (i > 5) mbar_wait(BAR(BR_OEMPTY - 5) + 8 * i, 0);
        if (EN_SSM && (i == 1 || i == 5)) mbar_wait(BAR(BR_FREE) + 2 * (i & 4), 0);
        if (elect_one()) {
          mbar_expect_tx(BAR(BR_OFULL) + 8 * i, 20480);
          bulk_ld(sb + SLOT(i), &g_o[(r * 8 + src) * 1280], 20480, BAR(BR_OFULL) + 8 * i);
          if (i == 1) TS(21);
          if (i == 7) TS(22);
        }
        __syncwarp();
      }
      if (lane == 0) { DUMP(20, 30); }
      }
    } else {
      const int hw = warp - 13, ht = tid - 416;
      if (hw == 2 && elect_one()) {
        #pragma unroll
        for (int i = 5; i < BR_COUNT; i++) mbar_init(BAR(i), i == BR_WO ? 33 : i == BR_OEMPTY ? 9 : i < BR_EMPTY ? 1 : i < BR_OEMPTY ? 2 : i < BR_Y ? 8 : i < BR_OSTG ? 4 : i == BR_OSTG ? 8 : i < BR_U2 ? 3 : 1);
        asm volatile("fence.mbarrier_init.release.cluster;" ::: "memory");
      }
      __syncwarp();
      asm volatile("bar.arrive 0, 512;" ::: "memory");
      if (EN_SSM && hw == 2) asm volatile("bar.arrive 8, 160;" ::: "memory");
      const unsigned epoch = hw == 0 ? ld_rlx(&g_epoch[cta]) + 1 : 0;
      bar_sync(5, 96);
      asm volatile("bar.arrive 6, 128;" ::: "memory");
      if (hw == 1 && elect_one()) {
        #pragma unroll
        for (int i = M_U; i < M_COUNT; i++) asm volatile("prefetch.tensormap [%0];" :: "l"(&prm.m[i]) : "memory");
      }
      if (ht == 0) {
        st_rlx(&g_epoch[cta], epoch);
        sts32(sb + OFF_EPOCH, epoch);
        mbar_arrive(BAR(BR_EPOCH));
      }
      if (EN_SSM) {
      const int mi = lane >> 3, rw = lane & 7, ch0 = c * 80 + r * 5;
      mbar_wait(BAR(BR_UIN), 0);
      if (ht == 0) TS(36);
      #pragma unroll 1
      for (int h = 0; h < 2; h++) {
        const uint32_t sa = sb + OFF_UT + h * 10240 + (8 * mi + rw) * 160 + hw * 16, da = sb + OFF_UT + h * 10240 + (hw * 8 + rw) * 128 + ((mi ^ rw ^ h) << 4);
        uint32_t v[8][4];
        #pragma unroll
        for (int q = 0; q < 8; q++) if (q < 6 || hw == 0) ldsm4t(v[q], sa + (q & 1) * 5120 + (q >> 1) * 48);
        bar_sync(5, 96);
        #pragma unroll
        for (int q = 0; q < 8; q++) if (q < 6 || hw == 0) stsm4((da ^ ((q & 1) * 64)) + (q >> 1) * 3072, v[q][0], v[q][1], v[q][2], v[q][3]);
      }
      fence_async();
      bar_sync(5, 96);
      if (hw == 0) {
        if (elect_one()) {
          tma2d_st(&prm.m[M_SA], sb + OFF_UT, r * 128, c * 80);
          tma2d_st(&prm.m[M_SA], sb + OFF_UT + 10240, r * 128 + 64, c * 80);
          bulk_commit(); bulk_wait0_read();
          mbar_arrive(BAR(BR_UOUT));
          TS(37);
          bulk_wait0();
          st_rel(FLAG(1, r, c), epoch);
          TS(30);
        }
        __syncwarp();
        poll_all_acq(FLAG(1, lane & 15, c), epoch);
      }
      #pragma unroll 1
      for (int k = 0; k < 5; k++) {
        if (k == 0 || k == 3) {
          const int p = k != 0;
          if (hw == 0) {
            if (!p) {
              if (elect_one()) {
                fence_async_g();
                mbar_expect_tx(BAR(BR_U), 12288);
                #pragma unroll 1
                for (int q = 0; q < 3; q++) bulk_ld(sb + OFF_BLK + q * q * BLK, g_uy + (ch0 + q * q) * 2048, 4096, BAR(BR_U));
                TS(31);
              }
              __syncwarp();
            }
            mbar_wait(BAR(p ? BR_U2 : BR_U), 0);
          }
          bar_sync(5, 96);
        }
        const int l3 = (hw + k) % 3 * 32 + lane;
        const uint32_t blk = sb + OFF_BLK + ((0x32410 >> (4 * k)) & 7) * BLK, o = blk + B_D + l3 * 16;
        float P[34];
        P[0] = 0.f;
        #pragma unroll
        for (int q = 0; q < 5; q++) {
          const int ch = 2 * l3 - 3 + q;
          uint32_t v[4];
          lds128(v, blk + (uint32_t)((ch * 16) ^ ((ch * 2) & 0x10)));
          #pragma unroll
          for (int e = 0; e < 8; e++) {
            const int i = 8 * q + e - 4;
            if (i >= 0 && i < 33) P[i + 1] = P[i] + ((e & 1) ? bf_hi(v[e >> 1]) : bf_lo(v[e >> 1]));
          }
        }
#define WIN(lo, hi, e) (P[21 + (e) - (lo)] - P[20 + (e) - (hi)])
#define WIN8(lo, hi, b) pack2(WIN(lo, hi, b), WIN(lo, hi, b + 1)), pack2(WIN(lo, hi, b + 2), WIN(lo, hi, b + 3)), pack2(WIN(lo, hi, b + 4), WIN(lo, hi, b + 5)), pack2(WIN(lo, hi, b + 6), WIN(lo, hi, b + 7))
        if (l3 < 64) {
          sts128(o + B_D9, WIN8(12, 20, 0)); sts128(o + B_D9 + 1024, WIN8(12, 20, 8));
          sts128(o + B_D7, WIN8(5, 11, 0)); sts128(o + B_D7 + 1024, WIN8(5, 11, 8));
        }
        sts128(o + B_D5, WIN8(6, 10, 0)); sts128(o + B_D5 + 1552, WIN8(6, 10, 8));
        sts128(o, WIN8(3, 5, 0)); sts128(o + 1552, WIN8(3, 5, 8));
        if (l3 < 2) sts128(blk + B_D + l3 * B_D5 + 1536, 0, 0, 0, 0);
      }
      __syncwarp();
      if (lane == 0) mbar_arrive(BAR(BR_DRDY + 1));
      if (ht == 0) TS(32);
      if (hw == 0) {
        #pragma unroll 1
        for (int p = 0; p < 2; p++) {
          mbar_wait(BAR(BR_Y) + 8 * p, 0);
          if (elect_one()) {
            #pragma unroll 1
            for (int k = 4 * p; k < 4 + p; k++) bulk_st(g_uy + (640 + ch0 + k) * 2048, sb + OFF_BLK + k * BLK, 4096);
            bulk_commit(); bulk_wait0_read();
            mbar_arrive(BAR(BR_FREE) + 8 * p);
          }
          __syncwarp();
        }
        if (elect_one()) { bulk_wait0(); st_rlx(FLAG(2, r, c), epoch); TS(33); }
        __syncwarp();
        poll_all(FLAG(2, lane & 15, c), epoch);
        if (EN_ATT) mbar_wait(BAR(BR_OEMPTY), 0);
        #pragma unroll 1
        for (int n = 0; n < 64; n++) {
          if (elect_one()) {
            mbar_expect_tx(BAR(BR_YIN), 20480);
            tma2d(sb + OFF_EXTRA, &prm.m[M_SA], BAR(BR_YIN), r * 128, 640 + c * 80);
            tma2d(sb + OFF_EXTRA + 10240, &prm.m[M_SA], BAR(BR_YIN), r * 128 + 64, 640 + c * 80);
            TS(34);
          }
          __syncwarp();
          if (EN_ATT) mbar_wait(BAR(BR_OEMPTY + 3), 0);
          mbar_wait(BAR(BR_YIN), n & 1);
          if (lane == 0) TS(38);
          if (!y_transpose(sb, 4, lane, (epoch & 1u) * 0x10001u)) break;
          FIXCNT
        }
      if (elect_one()) {
        TS(39);
        tma2d_st(&prm.m[M_OUT], sb + SLOT(3), c * 80, r * 128);
        bulk_commit(); bulk_wait0_read();
        TS(35); DUMP(30, 40); DUMP(0, 1);
      }
      }
      }
    }
  } else if (wg < 2) {
    asm volatile("setmaxnreg.inc.sync.aligned.u32 160;");
    bar_sync(0, 512);
    if (EN_ATT) {
    float am[96], ar[24];
    {
      const bool lead = (rtid() & 127) == 0;
      constexpr uint64_t dr0 = mkdesc(SB0 + 12288, 1024, 256, 3);
      const uint64_t db0 = sw64 ? mkdesc(SB0, 2048, 512, 2) : mkdesc(SB0, 4096, 1024, 1);
      const uint32_t kst = sw64 ? 64 : 128, bh = db0 >> 32;
      uint32_t s = 0, ph = 0, xo = 0;
      const int ln = rtid() & 31;
      const uint32_t xa = sb + OFF_X + (warp * 16 + (ln & 15)) * 128 + (((ln >> 4) ^ (ln & 7)) << 4);
      uint32_t A[8];
      mbar_wait(BAR(BR_FULL), 0);
      if (lead && wg == 0) TS(1);
      ldsm4(A, xa); ldsm4(A + 4, xa);
      wg_fence();
      wg_rs48_tb(ar, A + 4, dr0, 0); wg_rs192_tb(am, A + 4, db0, 0);
      wg_commit();
      uint32_t xk = xa, eb = 0;
      #pragma unroll 1
      for (int kb = 0; kb < 20; kb++) {
        const uint32_t wo_ = s * (W_SLOT >> 4), bl = (uint32_t)db0 + wo_, rl = (uint32_t)dr0 + wo_;
        wg_fence();
        wg_rs48_tb(ar, A, desc2(rl, dr0 >> 32), kb != 0);
        wg_rs192_tb(am, A, desc2(bl, bh), kb != 0);
        wg_commit();
        wg_wait<1>();
        ldsm4(A + 4, xk ^ 32);
        if (lead && kb > 0 && kb < 16) mbar_arrive(eb);
        eb = BAR(BR_EMPTY) + 8 * s;
        wg_fence();
        wg_rs48_tb(ar, A + 4, desc2(rl + 32, dr0 >> 32), 1);
        wg_rs192_tb(am, A + 4, desc2(bl + kst, bh), 1);
        wg_commit();
        if (++s == 5) { s = 0; ph ^= 1; }
        if (kb & 1) { xo += 16384; if (xo == 49152) xo = 0; }
        if (kb < 19) mbar_wait(BAR(BR_FULL) + 8 * s, ph);
        xk = (xa + xo) ^ ((~kb & 1) * 64);
        wg_wait<1>();
        ldsm4(A, xk);
      }
      wg_wait<0>();
      pin<96>(am); pin<24>(ar);
    }
    const int tid = rtid(), lane = tid & 31, tq = lane & 3;
    if (tid == 0) TS(2);
#define QV(j, e) ((j) < 8 ? am[4 * (j) + (e)] : ar[4 * ((j) - 8) + (e)])
#define KV_(j, e) ((j) < 8 ? am[32 + 4 * (j) + (e)] : ar[8 + 4 * ((j) - 8) + (e)])
#define VV(j, e) ((j) < 8 ? am[64 + 4 * (j) + (e)] : ar[16 + 4 * ((j) - 8) + (e)])
    {
      bar_sync(1, 256);
      if (tid == 0) mbar_arrive(BAR(BR_GEMM));
      const uint32_t ro = sb + (uint32_t)((warp * 16 + (lane & 15)) * 16);
      const int l0 = 2 * (c & 1) + (lane >> 4);
      const uint32_t ones = (tq == 0) ? 0x00003f80u : 0u;
#define PV(j) pack2(VV(j, 0), VV(j, 1)), pack2(VV(j, 2), VV(j, 3))
#define PK(j) pack2(phi(KV_(j, 0)), phi(KV_(j, 1))), pack2(phi(KV_(j, 2)), phi(KV_(j, 3)))
      stsm4(ro + OFF_V + (5 + 6 * (lane >> 4)) * 2048, ones, ones, ones, ones);
      #pragma unroll
      for (int j = 0; j < 10; j += 2) {
        const int l = (j == 8 && (c & 1)) ? l0 - 2 : l0 + j;
        stsm4(ro + OFF_V + (l + (l >= 5)) * 2048, PV(j), PV(j + 1));
        stsm4(ro + OFF_PK + l * 2048, PK(j), PK(j + 1));
      }
    }
    fence_async();
    bar_sync(1, 256);
    if (tid == 0) TS(3);
    mbar_wait(BAR(BR_EPOCH), 0);
    const unsigned epoch = lds32(sb + OFF_EPOCH);
    {
      float kv[24]; zero<24>(kv);
      constexpr uint64_t da = mkdesc(SB0 + OFF_PK, 128, 2048, 0), db = mkdesc(SB0 + OFF_V, 128, 2048, 0);
      wg_fence();
      #pragma unroll
      for (int s = 0; s < 8; s++) wg_ss48_tt(kv, desc2((uint32_t)da + wg * 640 + s * 16, da >> 32), desc2((uint32_t)db + wg * 768 + s * 16, db >> 32), s != 0);
      wg_commit();
      wg_wait<0>();
      pin<24>(kv);
      if (tid == 0) TS(15);
      if (w4 < 3) {
        const uint32_t wb = sb + OFF_KVS + (wg * 3 + w4) * 1536 + (lane & 15) * 96;
        #pragma unroll
        for (int j = 0; j < 6; j += 2)
          stsm4(wb + (j + (lane >> 4)) * 16, pack2(kv[4 * j], kv[4 * j + 1]), pack2(kv[4 * j + 2], kv[4 * j + 3]),
                pack2(kv[4 * j + 4], kv[4 * j + 5]), pack2(kv[4 * j + 6], kv[4 * j + 7]));
        __syncwarp();
        const int dl = w4 * 16 + (lane & 15), hl = dl >= 20;
        if (dl < 40) {
          uint4* dst = &g_kvp[(c * 16 + r) * 240 + wg * 40 + dl];
          uint32_t v[4], z[4];
          lds128(v, wb + (3 * hl + (lane >> 4)) * 16);
          lds64(z, wb + 32 + 8 * hl); z[2] = lds32(wb + 80); z[3] = epoch & 1u;
          v[3] = (v[3] & ~1u) | z[3];
          st128_rlx(dst + (lane >> 4) * 80, v);
          if (lane < 16) st128_rlx(dst + 160, z);
        }
      }
    }
    fence_async();
    bar_sync(1, 256);
    if (tid == 0) { st_rlx(FLAG(0, r, c), epoch); mbar_arrive(BAR(BR_PUB)); TS(4); }
    const int kvi = (tid >= 80) + (tid >= 160) + (tid >= 240), kd = tid - 80 * kvi;
    const int khd = kd / 20, kt0 = 5 * (khd >> 1) + 2 * (khd & 1);
    const uint32_t rb = sb + OFF_KVB + kd * 16;
    if (kvi < 3) {
      #pragma unroll 1
      for (int m = kvi; m < 7; m += 3) { const int q = kt0 + 3 + m; sts128(rb + (q >= 10 ? q - 10 : q) * 1280, 0, 0, 0, 0); }
    }
    uint32_t qa[20];
    {
      const float sc = 1.44269504089f + __uint_as_float(lds32(sb + OFF_EPOCH) ^ epoch);
      #pragma unroll
      for (int j = 0; j < 10; j++) { qa[2 * j] = pack2(phi(QV(j, 0), sc), phi(QV(j, 1), sc)); qa[2 * j + 1] = pack2(phi(QV(j, 2), sc), phi(QV(j, 3), sc)); }
    }
    if (tid == 0) TS(5);
    if (warp == 7) mbar_wait(BAR(BR_KVP), 0);
    bar_sync(1, 256);
    if (tid == 0) TS(6);
    if (kvi < 3) {
      float s[8];
      zero<8>(s);
      uint32_t bad = 0;
      #pragma unroll 4
      for (int i = 0; i < 16; i += 2) {
        uint32_t w[4], x[4];
        lds128(w, sb + OFF_KVP + tid * 16 + i * 3840); lds128(x, sb + OFF_KVP + tid * 16 + i * 3840 + 3840);
        bad |= (w[3] ^ epoch) | (x[3] ^ epoch);
        #pragma unroll
        for (int e = 0; e < 4; e++) {
          asm("add.rn.bf16x2 %0, %0, %1;" : "+r"(w[e]) : "r"(x[e]));
          s[2 * e] += bf_lo(w[e]); s[2 * e + 1] += bf_hi(w[e]);
        }
      }
      if (__builtin_expect(bad & 1u, 0)) {
        zero<8>(s);
        #pragma unroll 1
        for (int i = 0; i < 16; i++) {
          uint32_t w[4] = {0, 0, 0, ~epoch};
          fix128_w3(w, &g_kvp[(c * 16 + i) * 240 + tid], epoch, 1u);
          #pragma unroll
          for (int e = 0; e < 4; e++) { s[2 * e] += bf_lo(w[e]); s[2 * e + 1] += bf_hi(w[e]); }
        }
        FIXCNT
      }
      const uint32_t p0 = pack2(s[0], s[1]), p1 = pack2(s[2], s[3]), p2 = pack2(s[4], s[5]), p3 = pack2(s[6], s[7]);
      if (kvi < 2) sts128(rb + (kt0 + (khd & 1) + kvi) * 1280, p0, p1, p2, p3);
      else {
        const bool od = khd & 1;
        sts128(rb + (5 * (khd >> 1) + 2) * 1280, od ? 0u : p0, od ? 0u : p1, od ? p0 : 0u, od ? p1 : 0u);
        const uint32_t zz = (p2 & 0xffffu) << (16 * (khd & 1));
        sts128(rb + 10 * 1280, khd < 2 ? zz : 0u, khd < 2 ? 0u : zz, 0u, 0u);
      }
    }
    fence_async();
    bar_sync(1, 256);
    if (tid == 0) { mbar_arrive(BAR(BR_SUM)); TS(7); }
    {
      float oa[44]; zero<44>(oa);
      constexpr uint64_t db = mkdesc(SB0 + OFF_KVB, 128, 1280, 0);
      wg_fence();
      #pragma unroll
      for (int s = 0; s < 5; s++) wg_rs88_tb(oa, &qa[4 * s], desc2((uint32_t)db + ((s == 4 && (c & 1)) ? 0 : (s + (c & 1)) * 16), db >> 32), s != 0);
      wg_commit();
      wg_wait<0>();
      pin<44>(oa);
      if (tid == 0) TS(13);
      float rc[4], rd[2][4];
      #pragma unroll
      for (int e = 0; e < 4; e++) asm("rcp.approx.ftz.f32 %0, %1;" : "=f"(rc[e]) : "f"(oa[40 + e] + 1e-6f));
      #pragma unroll
      for (int h = 0; h < 4; h++) {
        rd[0][h] = __shfl_sync(0xffffffff, rc[h & 1], (lane & 28) | (h >> 1));
        rd[1][h] = __shfl_sync(0xffffffff, rc[2 + (h & 1)], (lane & 28) | (h >> 1));
      }
      #pragma unroll
      for (int j = 0; j < 10; j++) {
        #pragma unroll
        for (int h = 0; h < 2; h++) {
          float f;
          if (j == 2) f = tq < 2 ? rd[h][0] : rd[h][1];
          else if (j == 7) f = tq < 2 ? rd[h][2] : rd[h][3];
          else f = rd[h][(8 * j) / 20];
          qa[2 * j + h] = pack2(oa[4 * j + 2 * h] * f, oa[4 * j + 2 * h + 1] * f);
        }
      }
      const uint32_t m0 = (lane & 7) == ((2 * w4) & 7), m1 = (lane & 7) == 2 * w4 + 1;
      const uint32_t oa_ = sb + OFF_EXTRA + (lane >> 4) * 2048 + (warp * 16 + (lane & 15)) * 16;
      bar_sync(1, 256);
#define TAG(v, m) (((v) & ~(m)) | (epoch & (m)))
      #pragma unroll
      for (int s = 0; s < 5; s++) stsm4(oa_ + s * 4096, TAG(qa[4 * s], m0), TAG(qa[4 * s + 1], m1), TAG(qa[4 * s + 2], m0), TAG(qa[4 * s + 3], m1));
    }
    fence_async();
    __syncwarp();
    if (lane == 0) mbar_arrive(BAR(BR_OSTG));
    if (tid == 0) TS(8);
    float oc[40]; zero<40>(oc);
    {
      constexpr uint64_t dw0 = mkdesc(SB0, OFF_WOR, 1024, 1), da0 = mkdesc(SB0, 2048, 128, 0);
      const uint32_t ck = sb + tid * 32 + ((lane >> 2) << 2), ck2 = ck + (wg ? 0 : 16384);
      uint32_t bad = 0;
      auto tile = [&](int i, uint32_t so) {
        const uint32_t al = (uint32_t)da0 + wg * 64 + (so >> 4), wl = (uint32_t)dw0 + i * 640 - (i >> 1) * (1278 << 16);
        wg_fence();
        #pragma unroll
        for (int s = 0; s < 5; s++) wg_ss80_tb(oc, desc2(al + s * 256, da0 >> 32), desc2(wl + s * 128, dw0 >> 32), (i | s) != 0);
        wg_commit();
        bad |= (lds32(ck + so) ^ epoch) | (lds32(ck + so + 8192) ^ epoch) | (lds32(ck2 + so) ^ epoch);
      };
      if (w4 == 0) {
        if (EN_SSM) mbar_wait(BAR(CONV_AT < 2 ? BR_KS : BR_Y + 1), 0);
        mbar_wait(BAR(BR_WO), 0);
        mbar_wait(BAR(BR_WO + 1), 0);
      }
      bar_sync(1, 256);
      if (tid == 0) TS(9);
      tile(0, SLOT(0));
      #pragma unroll 1
      for (int i = 1; i < 8; i++) {
        mbar_wait(BAR(BR_OFULL) + 8 * i, 0);
        tile(i, SLOT(i));
        wg_wait<1>();
        if (lane == 0) mbar_arrive(BAR(BR_OEMPTY - 1) + 8 * i);
      }
      #pragma unroll 1
      for (int n = 0; n < 56; n++) {
        const int i = n & 7;
        if (i == 0) {
          uint32_t any;
          asm volatile("{\n.reg .pred p;\nsetp.ne.u32 p, %1, 0;\nbarrier.red.or.pred p, 1, 256, p;\nselp.u32 %0, 1, 0, p;\n}" : "=r"(any) : "r"(bad & 1u) : "memory");
          if (!any) break;
          bad = 0;
          FIXCNT
        }
        wg_wait<0>();
        bar_sync(1, 256);
        if (tid == 0) { mbar_expect_tx(BAR(BR_RETRY), 20480); bulk_ld(sb + SLOT(5), &g_o[(r * 8 + CHUNK(i)) * 1280], 20480, BAR(BR_RETRY)); }
        mbar_wait(BAR(BR_RETRY), n & 1);
        tile(i, SLOT(5));
      }
      wg_wait<0>();
      pin<40>(oc);
    }
    if (tid == 0) TS(10);
    {
      const int row = w4 * 16 + (lane & 15);
      const uint32_t ob = sb + OFF_BLK + 3 * BLK + wg * 10240;
      #pragma unroll
      for (int j = 0; j < 8; j += 2)
        stsm4(ob + row * 128 + (((j + (lane >> 4)) ^ (row & 7)) << 4), pack2(oc[4 * j], oc[4 * j + 1]), pack2(oc[4 * j + 2], oc[4 * j + 3]),
              pack2(oc[4 * j + 4], oc[4 * j + 5]), pack2(oc[4 * j + 6], oc[4 * j + 7]));
      stsm4(ob + 8192 + row * 32 + (lane >> 4) * 16, pack2(oc[32], oc[33]), pack2(oc[34], oc[35]), pack2(oc[36], oc[37]), pack2(oc[38], oc[39]));
      fence_async();
      bar_sync(2 + wg, 128);
      if (w4 == 0 && elect_one()) {
        tma2d_st(&prm.m[M_O64], ob, 640 + c * 64, r * 128 + wg * 64);
        tma2d_st(&prm.m[M_O16], ob + 8192, 1152 + c * 16, r * 128 + wg * 64);
        bulk_commit(); bulk_wait0_read();
        if (wg == 0) { TS(11); DUMP(0, 20); }
      }
    }
    }
  } else {
    const int g = lane >> 2, tq = lane & 3, t7 = tid & 127;
    uint32_t raw[5][4], pd;
    {
      const int ch = c * 80 + r * 5;
      #pragma unroll
      for (int e = 0; e < 4; e++) {
        const __nv_bfloat16* pp = prm.par[e] + ch * 128 + t7;
        #pragma unroll
        for (int q = 0; q < 5; q++) asm volatile("ld.global.nc.u16 %0, [%1];" : "=r"(raw[q][e]) : "l"(pp + q * 128));
      }
      asm volatile("ld.global.nc.u16 %0, [%1];" : "=r"(pd) : "l"(((lane & 8) ? prm.dskip : prm.logdt) + ch + min(lane & 7, 4)));
    }
    asm volatile("bar.arrive 0, 512;" ::: "memory");
    if (EN_SSM) {
    {
      #pragma unroll 1
      for (int k = 0; k < 4; k++) {
        const uint32_t z = sb + OFF_BLK + k * BLK + t7 * 16;
        sts128(z + B_TBL, 0, 0, 0, 0); sts128(z + B_TBL + 2048, 0, 0, 0, 0);
      }
      if (t7 < 80) sts128(sb + OFF_BLK + (t7 >> 4) * BLK - 256 + (t7 & 15) * 16, 0, 0, 0, 0);
      const uint32_t ea = sb + OFF_BLK + (2 + (w4 & 1)) * BLK + (lane >> 4) * 7168 + ((lane >> 3) & 1) * 256 + (lane & 7) * 16 + (w4 >> 1) * 2048;
      constexpr uint64_t dE = mkdesc(SB0 + OFF_BLK + 2 * BLK, 128, 512, 0);
      const uint32_t xa = sb + OFF_BLK + 18560 + t7 * 8, xr_ = sb + OFF_BLK + 18560 + (t7 ^ 64) * 8;
      uint32_t pr[5][2];
      #pragma unroll
      for (int q = 0; q < 5; q++) {
        #pragma unroll
        for (int e = 0; e < 2; e++) pr[q][e] = raw[q][2 * e] | (raw[q][2 * e + 1] << 16);
        const uint32_t m = __reduce_max_sync(0xffffffff, max(raw[q][2] & 0x7fffu, raw[q][3] & 0x7fffu));
        if (lane == 0) sts32(sb + OFF_EPOCH + 64 + q * 16 + w4 * 4, m);
      }
      bar_sync(4, 128);
      if (t7 == 0) TS(40);
      const int j = (w4 & 1) * 16 + (w4 >> 1) * 8 + g, i2 = tq < 2 ? 64 * tq + j : 32 * (tq - 2) + j;
      const uint32_t e2 = B_TBL + 4 * (tq < 2 ? T_F3 + (((i2 - 1) & 1) ? 80 : 0) + ((i2 - 1) >> 1) + 16 : T_F2 + (i2 & 1) * 96 + (i2 >> 1));
      const uint32_t e1 = tq < 2 ? (i2 ? e2 - 64 : B_TBL + 4 * (T_F2 + 175)) : B_TBL + 4 * (i2 ? T_F2 + ((2 * i2 - 1) & 3) * 48 + ((2 * i2 - 1) >> 2) : 16 + 511);
      const uint32_t e0 = B_TBL + (16 + 8 * j + 2 * tq) * 4;
      #pragma unroll 1
      for (int it = 0; it < 5; it++) {
        const int k = it;
        const uint32_t blk = sb + OFF_BLK + k * BLK;
        float fac;
        {
          const int q = it;
          if (it == 4) {
            mbar_wait(BAR(BR_UOUT), 0);
            sts128(sb + OFF_UT + B_TBL + t7 * 16, 0, 0, 0, 0); sts128(sb + OFF_UT + B_TBL + 2048 + t7 * 16, 0, 0, 0, 0);
          }
          const uint32_t ga = ea + 4096 - (w4 >> 1) * 512;
#define PUT4(i, a, b, c_, d) sts128(((i) < 8 ? ea + ((i) >> 1) * 512 : ga + (((i) - 8) >> 1) * 512) + ((i) & 1) * 128, a, b, c_, d)
          const uint32_t pa0 = pr[0][0], pc0 = pr[0][1];
          const float dt = bf_round(expf(bf_lo(__shfl_sync(0xffffffff, pd, q))));
          #pragma unroll
          for (int e = 0; e < 2; e++) { pr[0][e] = pr[1][e]; pr[1][e] = pr[2][e]; pr[2][e] = pr[3][e]; pr[3][e] = pr[4][e]; }
          uint32_t mm[4];
          lds128(mm, sb + OFF_EPOCH + 64 + q * 16);
          const uint32_t ex = min(max(max(max(mm[0], mm[1]), max(mm[2], mm[3])) >> 7, 1u), 253u);
          const float sc = __uint_as_float((254u - ex) << 23);
          fac = 2.f * dt * __uint_as_float(ex << 23);
          const float lr = -bf_round(expf(bf_lo(pa0))) * dt * 1.44269504089f;
          const float tn = bf_hi(pa0) * dt * 0.15915494309f;
          float z1r, z1i, z2r, z2i, z4r, z4i, xr[8], xi[8], gr[8], gi[8], wr[9], wi[9];
          cexp_t(lr, -tn, z1r, z1i);
          cexp_t(lr * 8.f, tn * 8.f, xr[1], xi[1]);
          cexp_t(lr * 64.f, tn * 64.f, wr[0], wi[0]);
          xr[0] = 1.f; xi[0] = 0.f;
          cmul(xr[1], xi[1], xr[1], xi[1], xr[2], xi[2]); cmul(xr[2], xi[2], xr[1], xi[1], xr[3], xi[3]);
          cmul(xr[2], xi[2], xr[2], xi[2], xr[4], xi[4]);
          #pragma unroll
          for (int b = 1; b < 4; b++) cmul(xr[4], xi[4], xr[b], xi[b], xr[4 + b], xi[4 + b]);
          cmul(wr[0], wi[0], wr[0], wi[0], wr[1], wi[1]); cmul(wr[1], wi[1], wr[0], wi[0], wr[2], wi[2]);
          cmul(wr[1], wi[1], wr[1], wi[1], wr[3], wi[3]); cmul(wr[3], wi[3], wr[3], wi[3], wr[4], wi[4]);
          cmul(wr[4], wi[4], wr[3], wi[3], wr[5], wi[5]); cmul(wr[4], wi[4], wr[4], wi[4], wr[6], wi[6]);
          cmul(wr[6], wi[6], wr[4], wi[4], wr[7], wi[7]); cmul(wr[6], wi[6], wr[6], wi[6], wr[8], wi[8]);
          uint32_t R[4], I[4], PR[4], PI[4];
          #pragma unroll
          for (int b = 0; b < 4; b++) { R[b] = packh(xr[2 * b], xr[2 * b + 1]); I[b] = packh(xi[2 * b], xi[2 * b + 1]); }
          PUT4(0, R[0], R[1], R[2], R[3]); PUT4(1, I[0], I[1], I[2], I[3]);
          #pragma unroll
          for (int i = 0; i < 3; i++) {
            const uint32_t z = packh(wr[i], wi[i]);
            #pragma unroll
            for (int b = 0; b < 4; b++) hcm2(R[b], I[b], z, PR[b], PI[b]);
            PUT4(2 * i + 2, PR[0], PR[1], PR[2], PR[3]); PUT4(2 * i + 3, PI[0], PI[1], PI[2], PI[3]);
          }
          gr[0] = bf_lo(pc0) * sc; gi[0] = -bf_hi(pc0) * sc;
          cmul(z1r, z1i, z1r, z1i, z2r, z2i); cmul(z2r, z2i, z2r, z2i, z4r, z4i);
          cmul(gr[0], gi[0], z1r, z1i, gr[1], gi[1]);
          cmul(gr[0], gi[0], z2r, z2i, gr[2], gi[2]); cmul(gr[1], gi[1], z2r, z2i, gr[3], gi[3]);
          #pragma unroll
          for (int b = 0; b < 4; b++) cmul(gr[b], gi[b], z4r, z4i, gr[4 + b], gi[4 + b]);
          PUT4(8, packh(gr[0], gr[1]), packh(gr[2], gr[3]), packh(gr[4], gr[5]), packh(gr[6], gr[7]));
          PUT4(9, packh(gi[0], gi[1]), packh(gi[2], gi[3]), packh(gi[4], gi[5]), packh(gi[6], gi[7]));
          {
            const uint32_t z = packh(wr[3], -wi[3]), a4r = packh(gr[0], gr[4]), a4i = packh(gi[0], gi[4]);
            hcm2(packh(gr[0], gr[2]), packh(gi[0], gi[2]), z, PR[0], PI[0]);
            hcm2(packh(gr[4], gr[6]), packh(gi[4], gi[6]), z, PR[1], PI[1]);
            hcm2(a4r, a4i, packh(wr[4], -wi[4]), PR[2], PI[2]);
            hcm2(a4r, a4i, packh(wr[5], -wi[5]), PR[3], PI[3]);
            PUT4(10, PR[0], PR[1], PR[2], PR[3]); PUT4(11, PI[0], PI[1], PI[2], PI[3]);
            float hr, hi_;
            cmul(gr[0], gi[0], wr[3], -wi[3], hr, hi_);
            const uint32_t cr = packh(gr[0], hr), ci = packh(gi[0], hi_);
            #pragma unroll
            for (int i = 0; i < 3; i++) hcm2(cr, ci, packh(wr[6 + i], -wi[6 + i]), PR[i], PI[i]);
            PUT4(12, PR[0], PR[1], PR[2], 0u); PUT4(13, PI[0], PI[1], PI[2], 0u);
          }
          fence_async();
          bar_sync(4, 128);
        }
        float ka[24]; zero<24>(ka);
        wg_fence();
        #pragma unroll
        for (int s = 0; s < 8; s++) {
          const uint64_t d = dE + (s >> 2) * (BLK >> 4) + ((s >> 1) & 1) * 448 + (s & 1) * 16;
          wg_ss48_tt_h(ka, d, d + 256, s != 0);
        }
        wg_commit();
        const float dsk = bf_lo(__shfl_sync(0xffffffff, pd, 8 + it));
        wg_wait<0>();
        pin<24>(ka);
        float kk[6];
        const bool up = w4 >= 2;
        #pragma unroll
        for (int n = 0; n < 3; n++) {
          sts64f(xa + n * BLK, up ? ka[12 + 4 * n] : ka[4 * n + 2], up ? ka[13 + 4 * n] : ka[4 * n + 3]);
          kk[2 * n] = up ? ka[14 + 4 * n] : ka[4 * n]; kk[2 * n + 1] = up ? ka[15 + 4 * n] : ka[4 * n + 1];
        }
        if (it) bar_sync(4, 128); else bar_sync(8, 160);
          if (it == 4 && w4 == 0) {
            mbar_wait(BAR(BR_U), 0);
            if (elect_one()) {
              mbar_expect_tx(BAR(BR_U2), 8192);
              bulk_ld(blk - 2 * BLK, g_uy + (c * 80 + r * 5 + 2) * 2048, 4096, BAR(BR_U2)); bulk_ld(blk - BLK, g_uy + (c * 80 + r * 5 + 3) * 2048, 4096, BAR(BR_U2));
            }
            __syncwarp();
          }
        #pragma unroll
        for (int n = 0; n < 3; n++) {
          uint32_t o[2]; lds64(o, xr_ + n * BLK);
          kk[2 * n] = (kk[2 * n] + __uint_as_float(o[0])) * fac; kk[2 * n + 1] = (kk[2 * n + 1] + __uint_as_float(o[1])) * fac;
        }
        if (t7 == 0) kk[0] += dsk;
        {
          const uint32_t v = pack2(kk[1], kk[0]), vh = v >> 16;
          const uint32_t u = pack2(kk[2], kk[3]), w = pack2(kk[4], kk[5]), uu = pack2(kk[2], kk[2]), us = pack2(kk[3], kk[2]);
          const uint32_t x = tq < 2 ? w : u, xh = x >> 16;
          sts32(blk + e0 + 4, v); sts16(blk + e0, vh); sts16(blk + e0 + 10, v);
          sts16(blk + e1, x); sts16(blk + e1 + 6, x); sts16(blk + e2, xh); sts16(blk + e2 + 6, xh);
          if (tq < 2) {
            const uint32_t pb = blk + e0 + 1024 + 8 * tq;
            sts32(pb + 4, uu); sts32(pb + 8, us); sts16(pb + 14, us);
            if (i2) { sts16(pb - 4, u); sts32(pb, uu); }
          }
          if (i2 == 0) {
            const uint32_t tb = blk + B_TBL;
            if (tq == 0) { sts16(tb + (16 + 256) * 4, u); sts16(tb + (T_S + 3) * 4, w); sts32(tb + (T_S + 4) * 4, pack2(kk[4], kk[4])); sts16(tb + (T_S + 5) * 4 + 2, w); }
            else { sts32(tb + 528 * 4, uu); sts32(tb + 529 * 4, uu); sts32(tb + 530 * 4, uu); sts16(tb + 531 * 4 + 2, u); sts16(tb + (T_F3 + 80 + 63) * 4, w); }
          }
        }
        if (t7 == 0) TS(49 + it);
      }
    }
    asm volatile("setmaxnreg.inc.sync.aligned.u32 136;");
    if (t7 == 0) TS(41);
    mbar_wait(BAR(BR_U), 0);
    bar_sync(4, 128);
    if (EN_ATT) mbar_wait(BAR(BR_GEMM), 0);
    if (t7 == 0) TS(42);
    mbar_wait(BAR(BR_EPOCH), 0);
    const uint32_t ytag = (lds32(sb + OFF_EPOCH) & 1u) * 0x10001u, ym = lane < 4 ? 0x10001u : 0u;
    #pragma unroll 1
    for (int pass = 1; pass >= 0; pass--) {
      const int k = pass ? w4 : 4;
      if (k & 2) mbar_wait(BAR(BR_U2), 0);
      const uint32_t blk = sb + OFF_BLK + k * BLK, tb = blk + B_TBL + (uint32_t)((g - 2 * tq) * 4);
      float acc[16][4];
      zero<64>(&acc[0][0]);
      const int kl = 16 * (lane >> 4) + 2 * (lane & 7) + ((lane >> 3) & 1);
      {
        auto ubase = [&](int sh) { const int q = kl - 2 * sh; return blk + (uint32_t)((q * 16) ^ ((q * 2) & 0x10)); };
#define LDQ(A, sh) _Pragma("unroll") for (int m = 0; m < 4; m++) load_quad(A[m], tb + (16 + 16 * (sh) + 128 * m) * 4);
#define LDB(B, ub, h) _Pragma("unroll") for (int p = 0; p < 4; p++) ldsm4(B[p], (ub) + (4 * (h) + p) * 512);
#define MLO(A, B) _Pragma("unroll") for (int m = 0; m < 4; m++) _Pragma("unroll") for (int cc = 0; cc < 8; cc++) mma16816(acc[cc + m], A[m], &B[cc >> 1][(cc & 1) * 2]);
#define MHI(A, B) _Pragma("unroll") for (int m = 0; m < 4; m++) _Pragma("unroll") for (int cc = 0; cc < 8 - m; cc++) mma16816(acc[8 + cc + m], A[m], &B[cc >> 1][(cc & 1) * 2]);
        int p_ = pass ? 0 : w4;
        const int pe = pass ? 4 : w4 + 1;
        uint32_t A[4][4], A2[4][4], Bl[4][4], Bh[4][4];
        uint32_t ub = ubase(p_ + 4);
        LDQ(A, p_ + 4) LDB(Bl, ub, 0)
        #pragma unroll 1
        for (; p_ < pe; p_++) {
          LDB(Bh, ub, 1)
          MLO(A, Bl)
          ub = ubase(p_);
          LDQ(A2, p_) LDB(Bl, ub, 0)
          MHI(A, Bh)
          LDB(Bh, ub, 1)
          load_quad(A[0], tb + (16 + 512 + 16 * (p_ & 1)) * 4); load_quad(A[1], tb + (T_S + 16 * (p_ & 1)) * 4);
          MLO(A2, Bl)
          if (p_ < 2) {
            #pragma unroll
            for (int cc = 0; cc < 8; cc++) mma16816(acc[cc + 4], A[0], &Bl[cc >> 1][(cc & 1) * 2]);
            #pragma unroll
            for (int cc = 0; cc < 4; cc++) mma16816(acc[cc + 12], A[0], &Bh[cc >> 1][(cc & 1) * 2]);
            #pragma unroll
            for (int cc = 0; cc < 8; cc++) mma16816(acc[cc + 8], A[1], &Bl[cc >> 1][(cc & 1) * 2]);
          }
          const int pn = ((p_ + 1) & 3) + 4;
          ub = ubase(pn);
          LDQ(A, pn) LDB(Bl, ub, 0)
          MHI(A2, Bh)
        }
      }
      if (t7 == 0) TS(57 + 3 * pass);
      mbar_wait(BAR(BR_DRDY + 1), 0);
      {
        const int ih = (lane >> 3) & 1;
        const uint32_t dl = blk + B_D + (uint32_t)(((lane >> 4) * 8 + (lane & 7)) * 16);
        const uint32_t d0_ = dl + ih * 1552, d8_ = dl + (ih ? 0 : 1536), d3_ = dl + B_D7 + ih * 1024;
        auto cls2 = [&](uint32_t da, uint32_t ta) {
          uint32_t B[6][2], A[6][4];
          #pragma unroll
          for (int e = 0; e < 6; e++) { B[e][0] = lds32v(ta + (e + 4) * 32); B[e][1] = lds32v(ta + (e + 3) * 32); }
          #pragma unroll
          for (int kk = 0; kk < 6; kk++) ldsm4t(A[kk], da + kk * 256);
          #pragma unroll
          for (int e = 0; e < 6; e++)
            #pragma unroll
            for (int kk = 0; kk < 6; kk++) if (2 * kk + e + 4 < 16) mma16816(acc[2 * kk + e + 4], A[kk], B[e]);
        };
        auto cls3 = [&](uint32_t da, uint32_t ta) {
          uint32_t B[8][2], A[4][4];
          #pragma unroll
          for (int e = 0; e < 8; e++) { B[e][0] = lds32v(ta + (e + 8) * 32); B[e][1] = lds32v(ta + (e + 7) * 32); }
          #pragma unroll
          for (int kk = 0; kk < 4; kk++) ldsm4t(A[kk], da + kk * 256);
          #pragma unroll
          for (int kk = 0; kk < 4; kk++)
            #pragma unroll
            for (int e = 0; e < 8; e++) if (2 * kk + e + 8 < 16) mma16816(acc[2 * kk + e + 8], A[kk], B[e]);
        };
        if (pass) {
          #pragma unroll 1
          for (int a = 0; a < 2; a++) {
            cls2(d0_ + a * B_D5, tb + (T_F2 + 48 * a - 32) * 4);
            cls2(d8_ + a * B_D5, tb + (T_F2 + 48 * a + 64) * 4);
            cls3(d3_ + a * 2048, tb + (T_F3 + 80 * a - 64) * 4);
          }
        } else {
          cls2(((w4 & 2) ? d8_ : d0_) + (w4 & 1) * B_D5, tb + (T_F2 + 48 * w4 - 32) * 4);
          if (w4 >= 2) cls3(d3_ + (w4 - 2) * 2048, tb + (T_F3 + 80 * (w4 - 2) - 64) * 4);
        }
      }
      if (t7 == 0) TS(58 + 3 * pass);
      const uint32_t ya = blk + (uint32_t)((kl * 16) ^ ((kl * 2) & 0x10));
#define YTAG(v) (((v) & ~ym) | (ytag & ym))
#define STY(p) stsm4t(ya + (p) * 512, YTAG(pack2(acc[2 * (p)][0], acc[2 * (p)][1])), pack2(acc[2 * (p)][2], acc[2 * (p)][3]), \
                      YTAG(pack2(acc[2 * (p) + 1][0], acc[2 * (p) + 1][1])), pack2(acc[2 * (p) + 1][2], acc[2 * (p) + 1][3]))
      if (pass == 0) {
        const uint32_t xw = blk + 4096 + w4 * 4096 + lane * 16, xr = blk + 4096 + w4 * 1024 + lane * 16;
        #pragma unroll
        for (int h = 0; h < 2; h++) {
          bar_sync(4, 128);
          if (h == CONV_AT && t7 == 0) mbar_arrive(BAR(BR_KS));
          #pragma unroll
          for (int i = 0; i < 8; i++)
            sts128(xw + i * 512, __float_as_uint(acc[8 * h + i][0]), __float_as_uint(acc[8 * h + i][1]), __float_as_uint(acc[8 * h + i][2]), __float_as_uint(acc[8 * h + i][3]));
          bar_sync(4, 128);
          float y[8];
          #pragma unroll
          for (int i = 0; i < 8; i++) {
            uint32_t o[4]; lds128(o, xr + (i >> 1) * 4096 + (i & 1) * 512);
            #pragma unroll
            for (int e = 0; e < 4; e++) y[4 * (i & 1) + e] = i < 2 ? __uint_as_float(o[e]) : y[4 * (i & 1) + e] + __uint_as_float(o[e]);
          }
          stsm4t(ya + (4 * h + w4) * 512, YTAG(pack2(y[0], y[1])), pack2(y[2], y[3]), YTAG(pack2(y[4], y[5])), pack2(y[6], y[7]));
        }
      } else {
        __syncwarp();
        #pragma unroll
        for (int p = 0; p < 8; p++) STY(p);
      }
      if (t7 == 0 && !pass) TS(55);
      fence_async();
      __syncwarp();
      if (lane == 0) mbar_arrive(BAR(BR_Y + 1) - 8 * pass);
      if (t7 == 0) TS(59 + 3 * pass);
    }
    if (t7 == 0) DUMP(40, 64);
    #pragma unroll 1
    for (int n = 0; n < 64; n++) if (!y_transpose(sb, w4, lane, ytag)) break;
    }
  }
}

typedef CUresult (*EncFn)(CUtensorMap*, CUtensorMapDataType, cuuint32_t, void*, const cuuint64_t*, const cuuint64_t*, const cuuint32_t*,
                          const cuuint32_t*, CUtensorMapInterleave, CUtensorMapSwizzle, CUtensorMapL2promotion, CUtensorMapFloatOOBfill);
static void mkmap(EncFn enc, CUtensorMap* m, const void* base, int rank, const cuuint64_t* dims, const cuuint64_t* strides, const cuuint32_t* box, CUtensorMapSwizzle swz) {
  cuuint32_t es[5] = {1, 1, 1, 1, 1};
  enc(m, CU_TENSOR_MAP_DATA_TYPE_BFLOAT16, rank, const_cast<void*>(base), dims, strides, box, es, CU_TENSOR_MAP_INTERLEAVE_NONE, swz,
      CU_TENSOR_MAP_L2_PROMOTION_L2_128B, CU_TENSOR_MAP_FLOAT_OOB_FILL_NONE);
}

extern "C" void kernel_launch(void* const* d_in, const int* in_sizes, int n_in, void* d_out, int out_size) {
  void* fn = nullptr; cudaDriverEntryPointQueryResult qr;
  cudaGetDriverEntryPoint("cuTensorMapEncodeTiled", &fn, cudaEnableDefault, &qr);
  EncFn enc = (EncFn)fn;
  void* uy = nullptr; cudaGetSymbolAddress(&uy, g_uy);
  const cuuint64_t dx[2] = {640, 2048}, sx[1] = {1280};
  const cuuint32_t bx[2] = {64, 128}, bu[2] = {80, 128};
  const cuuint64_t dw[3] = {640, 640, 3}, sw[2] = {3840, 1280};
  const cuuint32_t br[3] = {16, 32, 3};
  const cuuint64_t dwa[4] = {64, 640, 10, 3}, swa[3] = {3840, 128, 1280}, dwb[4] = {32, 640, 20, 3}, swb[3] = {3840, 64, 1280};
  const cuuint32_t bwa[4] = {64, 32, 1, 3}, bwb[4] = {32, 32, 2, 3};
  const cuuint64_t dwo[2] = {640, 640};
  const cuuint32_t bwo[2] = {64, 80}, bo64[2] = {64, 64}, bo16[2] = {16, 64};
  const cuuint64_t dsa[2] = {2048, 1280}, ssa[1] = {4096};
  const cuuint32_t bsa[2] = {64, 80};
  const cuuint64_t dout[2] = {1280, 2048}, sout[1] = {2560};
  Params prm;
  mkmap(enc, &prm.m[M_X], d_in[7], 2, dx, sx, bx, CU_TENSOR_MAP_SWIZZLE_128B);
  mkmap(enc, &prm.m[M_W128], d_in[8], 4, dwa, swa, bwa, CU_TENSOR_MAP_SWIZZLE_128B);
  mkmap(enc, &prm.m[M_W64], d_in[8], 4, dwb, swb, bwb, CU_TENSOR_MAP_SWIZZLE_64B);
  mkmap(enc, &prm.m[M_WR], d_in[8], 3, dw, sw, br, CU_TENSOR_MAP_SWIZZLE_32B);
  mkmap(enc, &prm.m[M_U], d_in[0], 2, dx, sx, bu, CU_TENSOR_MAP_SWIZZLE_NONE);
  mkmap(enc, &prm.m[M_WO], d_in[9], 2, dwo, sx, bwo, CU_TENSOR_MAP_SWIZZLE_128B);
  mkmap(enc, &prm.m[M_O64], d_out, 2, dout, sout, bo64, CU_TENSOR_MAP_SWIZZLE_128B);
  mkmap(enc, &prm.m[M_O16], d_out, 2, dout, sout, bo16, CU_TENSOR_MAP_SWIZZLE_NONE);
  mkmap(enc, &prm.m[M_SA], uy, 2, dsa, ssa, bsa, CU_TENSOR_MAP_SWIZZLE_128B);
  mkmap(enc, &prm.m[M_OUT], d_out, 2, dout, sout, bu, CU_TENSOR_MAP_SWIZZLE_NONE);
  prm.u = (const __nv_bfloat16*)d_in[0]; prm.wo = (const __nv_bfloat16*)d_in[9];
  for (int i = 0; i < 4; i++) prm.par[i] = (const __nv_bfloat16*)d_in[1 + i];
  prm.logdt = (const __nv_bfloat16*)d_in[5]; prm.dskip = (const __nv_bfloat16*)d_in[6];
  cudaFuncSetAttribute(fused_kernel, cudaFuncAttributeMaxDynamicSharedMemorySize, SMEM_BYTES);
  cudaLaunchConfig_t cfg = {};
  cfg.gridDim = dim3(128); cfg.blockDim = dim3(512); cfg.dynamicSmemBytes = SMEM_BYTES; cfg.stream = cudaStreamPerThread;
  cudaLaunchAttribute at[1];
  at[0].id = cudaLaunchAttributeClusterDimension; at[0].val.clusterDim.x = 2; at[0].val.clusterDim.y = 1; at[0].val.clusterDim.z = 1;
  cfg.attrs = at; cfg.numAttrs = 1;
  cudaLaunchKernelEx(&cfg, fused_kernel, prm);
}
```

```cpp
#include <cuda_runtime.h>
#include <cuda_bf16.h>
#include <cuda_fp16.h>
#include <cuda.h>
#include <stdint.h>

#define KST 2
#define UKB 4
#define UPF 0
#define CONV_AT 1
#define EN_ATT 1
#define EN_SSM 1

__device__ __align__(1024) __nv_bfloat16 g_uy[2 * 640 * 2048];
__device__ __align__(128) uint4 g_kvp[8 * 16 * 240];
__device__ __align__(128) uint4 g_o[128 * 1280];
__device__ __align__(128) unsigned g_flag[4 * 128 * 32];
__device__ unsigned g_epoch[128];
#define TS(i) do {} while (0)
#define DUMP(lo, hi) do {} while (0)
#define FIXCNT

constexpr uint32_t SB0 = 1024;
constexpr uint32_t W_SLOT = 15360, OFF_X = 76800;
constexpr uint32_t OFF_WOR = 81920, OFF_KVP = 10240, OFF_KVS = 71680, OFF_PK = 10240, OFF_V = 30720, OFF_EXTRA = 102400, OFF_KVB = OFF_EXTRA;
constexpr uint32_t OFF_BAR = 125952, OFF_BLK = 128000, BLK = 20480;
constexpr uint32_t B_D = 4096, B_D5 = 3088, B_D7 = 6176, B_D9 = 8224, B_TBL = 14400;
constexpr int T_S = 576, T_F2 = 624, T_F3 = 816;
constexpr uint32_t OFF_UT = OFF_BLK + 4 * BLK;
constexpr uint32_t SMEM_BYTES = OFF_BLK + 5 * BLK;
enum { BR_FULL = 0, BR_WO = 5, BR_PUB = 7, BR_KVP = 8, BR_U = 9, BR_SUM = 10, BR_GEMM = 11, BR_UIN = 12, BR_YIN = 13, BR_EPOCH = 14,
       BR_FREE = 15, BR_RETRY = 17, BR_UOUT = 18, BR_OFULL = 18, BR_KS = 26, BR_EMPTY = 31, BR_OEMPTY = 36, BR_Y = 43, BR_OSTG = 45,
       BR_DRDY = 46, BR_U2 = 48, BR_COUNT = 50 };
constexpr uint32_t OFF_EPOCH = OFF_BAR + 8 * BR_COUNT;
enum { M_X, M_W128, M_W64, M_WR, M_U, M_WO, M_O64, M_O16, M_SA, M_OUT, M_COUNT };

__device__ __forceinline__ long long clk64() { long long t; asm volatile("mov.u64 %0, %%clock64;" : "=l"(t) :: "memory"); return t; }
__device__ __forceinline__ uint32_t smem_u32(const void* p) { return (uint32_t)__cvta_generic_to_shared(p); }
__host__ __device__ constexpr uint64_t mkdesc(uint32_t addr, uint32_t lbo, uint32_t sbo, uint32_t swz) {
  return (uint64_t)((addr & 0x3FFFF) >> 4) | ((uint64_t)(lbo >> 4) << 16) | ((uint64_t)(sbo >> 4) << 32) | ((uint64_t)swz << 62);
}
__device__ __forceinline__ uint64_t desc2(uint32_t lo, uint32_t hi) { uint64_t d; asm("mov.b64 %0, {%1, %2};" : "=l"(d) : "r"(lo), "r"(hi)); return d; }
__device__ __forceinline__ void mbar_init(uint32_t bar, uint32_t cnt) { asm volatile("mbarrier.init.shared::cta.b64 [%0], %1;" :: "r"(bar), "r"(cnt) : "memory"); }
__device__ __forceinline__ void mbar_expect_tx(uint32_t bar, uint32_t bytes) { asm volatile("mbarrier.arrive.expect_tx.shared::cta.b64 _, [%0], %1;" :: "r"(bar), "r"(bytes) : "memory"); }
__device__ __forceinline__ void mbar_arrive(uint32_t bar) { asm volatile("mbarrier.arrive.shared::cta.b64 _, [%0];" :: "r"(bar) : "memory"); }
__device__ __forceinline__ void mbar_wait(uint32_t bar, uint32_t parity) {
  asm volatile("{\n.reg .pred p;\n.reg .u32 c;\nmov.u32 c, 0;\n"
    "WL:\nmbarrier.try_wait.parity.shared::cta.b64 p, [%0], %1;\n@p bra WD;\n"
    "add.u32 c, c, 1;\nsetp.lt.u32 p, c, 200000;\n@p bra WL;\nWD:\n}" :: "r"(bar), "r"(parity) : "memory");
}
__device__ __forceinline__ void poll_all(const unsigned* p, unsigned val) {
  asm volatile("{\n.reg .pred p;\n.reg .u32 c, v;\nmov.u32 c, 0;\n"
    "PL:\nld.relaxed.gpu.global.u32 v, [%0];\nsetp.eq.u32 p, v, %1;\nvote.sync.all.pred p, p, 0xffffffff;\n@p bra PD;\n"
    "add.u32 c, c, 1;\nsetp.lt.u32 p, c, 100000;\n@p bra PL;\nPD:\n}" :: "l"(p), "r"(val) : "memory");
}
__device__ __forceinline__ void poll_all_acq(const unsigned* p, unsigned val) {
  asm volatile("{\n.reg .pred p;\n.reg .u32 c, v;\nmov.u32 c, 0;\n"
    "PL:\nld.acquire.gpu.global.u32 v, [%0];\nsetp.eq.u32 p, v, %1;\nvote.sync.all.pred p, p, 0xffffffff;\n@p bra PD;\n"
    "nanosleep.u32 300;\nadd.u32 c, c, 1;\nsetp.lt.u32 p, c, 100000;\n@p bra PL;\nPD:\n}" :: "l"(p), "r"(val) : "memory");
}
__device__ __forceinline__ unsigned poll_bit(const unsigned* p, unsigned val, unsigned mask) {
  unsigned bal;
  asm volatile("{\n.reg .pred p;\n.reg .u32 c, v;\nmov.u32 c, 0;\n"
    "PL:\nld.relaxed.gpu.global.u32 v, [%1];\nsetp.eq.u32 p, v, %2;\nvote.sync.ballot.b32 %0, p, 0xffffffff;\n"
    "and.b32 v, %0, %3;\nsetp.ne.u32 p, v, 0;\n@p bra PD;\n"
    "add.u32 c, c, 1;\nsetp.lt.u32 p, c, 100000;\n@p bra PL;\nPD:\n}" : "=&r"(bal) : "l"(p), "r"(val), "r"(mask) : "memory");
  return bal;
}
__device__ __forceinline__ void fix128_w0(uint32_t* v, const void* p, uint32_t tag, uint32_t mask) {
  asm volatile("{\n.reg .pred p;\n.reg .u32 c, x;\n.reg .b128 t;\n.reg .b64 lo, hi;\nmov.u32 c, 0;\n"
    "FL:\nxor.b32 x, %0, %5;\nand.b32 x, x, %6;\nsetp.eq.u32 p, x, 0;\n@p bra FD;\n"
    "ld.relaxed.gpu.global.b128 t, [%4];\nmov.b128 {lo, hi}, t;\nmov.b64 {%0, %1}, lo;\nmov.b64 {%2, %3}, hi;\n"
    "add.u32 c, c, 1;\nsetp.lt.u32 p, c, 100000;\n@p bra FL;\nFD:\n}"
    : "+r"(v[0]), "+r"(v[1]), "+r"(v[2]), "+r"(v[3]) : "l"(p), "r"(tag), "r"(mask) : "memory");
}
__device__ __forceinline__ void fix128_w3(uint32_t* v, const void* p, uint32_t tag, uint32_t mask) {
  asm volatile("{\n.reg .pred p;\n.reg .u32 c, x;\n.reg .b128 t;\n.reg .b64 lo, hi;\nmov.u32 c, 0;\n"
    "FL:\nxor.b32 x, %3, %5;\nand.b32 x, x, %6;\nsetp.eq.u32 p, x, 0;\n@p bra FD;\n"
    "ld.relaxed.gpu.global.b128 t, [%4];\nmov.b128 {lo, hi}, t;\nmov.b64 {%0, %1}, lo;\nmov.b64 {%2, %3}, hi;\n"
    "add.u32 c, c, 1;\nsetp.lt.u32 p, c, 100000;\n@p bra FL;\nFD:\n}"
    : "+r"(v[0]), "+r"(v[1]), "+r"(v[2]), "+r"(v[3]) : "l"(p), "r"(tag), "r"(mask) : "memory");
}
__device__ __forceinline__ void fence_acq() { asm volatile("fence.acq_rel.gpu;" ::: "memory"); }
__device__ __forceinline__ bool elect_one() {
  uint32_t p; asm volatile("{\n.reg .pred P;\nelect.sync _|P, 0xffffffff;\nselp.u32 %0, 1, 0, P;\n}" : "=r"(p)); return p;
}
__device__ __forceinline__ void bar_sync(int id, int n) { asm volatile("bar.sync %0, %1;" :: "r"(id), "r"(n) : "memory"); }
__device__ __forceinline__ void fence_async() { asm volatile("fence.proxy.async.shared::cta;" ::: "memory"); }
__device__ __forceinline__ void fence_async_g() { asm volatile("fence.proxy.async.global;" ::: "memory"); }
__device__ __forceinline__ void tma2d(uint32_t dst, const CUtensorMap* m, uint32_t bar, int c0, int c1) {
  asm volatile("cp.async.bulk.tensor.2d.shared::cluster.global.mbarrier::complete_tx::bytes [%0], [%1, {%3, %4}], [%2];"
    :: "r"(dst), "l"(m), "r"(bar), "r"(c0), "r"(c1) : "memory");
}
__device__ __forceinline__ void tma3d(uint32_t dst, const CUtensorMap* m, uint32_t bar, int c0, int c1, int c2) {
  asm volatile("cp.async.bulk.tensor.3d.shared::cluster.global.mbarrier::complete_tx::bytes [%0], [%1, {%3, %4, %5}], [%2];"
    :: "r"(dst), "l"(m), "r"(bar), "r"(c0), "r"(c1), "r"(c2) : "memory");
}
__device__ __forceinline__ void tma4d(uint32_t dst, const CUtensorMap* m, uint32_t bar, int c0, int c1, int c2, int c3) {
  asm volatile("cp.async.bulk.tensor.4d.shared::cluster.global.mbarrier::complete_tx::bytes [%0], [%1, {%3, %4, %5, %6}], [%2];"
    :: "r"(dst), "l"(m), "r"(bar), "r"(c0), "r"(c1), "r"(c2), "r"(c3) : "memory");
}
__device__ __forceinline__ void tma2d_st(const CUtensorMap* m, uint32_t src, int c0, int c1) {
  asm volatile("cp.async.bulk.tensor.2d.global.shared::cta.bulk_group [%0, {%2, %3}], [%1];"
    :: "l"(m), "r"(src), "r"(c0), "r"(c1) : "memory");
}
__device__ __forceinline__ void bulk_ld(uint32_t dst, const void* src, uint32_t bytes, uint32_t bar) {
  asm volatile("cp.async.bulk.shared::cluster.global.mbarrier::complete_tx::bytes [%0], [%1], %2, [%3];"
    :: "r"(dst), "l"(src), "r"(bytes), "r"(bar) : "memory");
}
__device__ __forceinline__ void bulk_st(void* dst, uint32_t src, uint32_t bytes) {
  asm volatile("cp.async.bulk.global.shared::cta.bulk_group [%0], [%1], %2;" :: "l"(dst), "r"(src), "r"(bytes) : "memory");
}
__device__ __forceinline__ void bulk_commit() { asm volatile("cp.async.bulk.commit_group;" ::: "memory"); }
__device__ __forceinline__ void bulk_wait0() { asm volatile("cp.async.bulk.wait_group 0;" ::: "memory"); }
__device__ __forceinline__ void bulk_wait0_read() { asm volatile("cp.async.bulk.wait_group.read 0;" ::: "memory"); }
__device__ __forceinline__ unsigned ld_rlx(const unsigned* p) { unsigned v; asm volatile("ld.relaxed.gpu.global.u32 %0, [%1];" : "=r"(v) : "l"(p) : "memory"); return v; }
__device__ __forceinline__ unsigned ld_acq(const unsigned* p) { unsigned v; asm volatile("ld.acquire.gpu.global.u32 %0, [%1];" : "=r"(v) : "l"(p) : "memory"); return v; }
__device__ __forceinline__ void st_rlx(unsigned* p, unsigned v) { asm volatile("st.relaxed.gpu.global.u32 [%0], %1;" :: "l"(p), "r"(v) : "memory"); }
__device__ __forceinline__ void st_rel(unsigned* p, unsigned v) { asm volatile("st.release.gpu.global.u32 [%0], %1;" :: "l"(p), "r"(v) : "memory"); }
__device__ __forceinline__ void ld128_rlx(uint32_t* v, const void* p) {
  asm volatile("{\n.reg .b128 t;\n.reg .b64 lo, hi;\nld.relaxed.gpu.global.b128 t, [%4];\nmov.b128 {lo, hi}, t;\n"
    "mov.b64 {%0, %1}, lo;\nmov.b64 {%2, %3}, hi;\n}" : "=r"(v[0]), "=r"(v[1]), "=r"(v[2]), "=r"(v[3]) : "l"(p) : "memory");
}
__device__ __forceinline__ void st128_rlx(void* p, const uint32_t* v) {
  asm volatile("{\n.reg .b128 t;\n.reg .b64 lo, hi;\nmov.b64 lo, {%1, %2};\nmov.b64 hi, {%3, %4};\nmov.b128 t, {lo, hi};\n"
    "st.relaxed.gpu.global.b128 [%0], t;\n}" :: "l"(p), "r"(v[0]), "r"(v[1]), "r"(v[2]), "r"(v[3]) : "memory");
}
__device__ __forceinline__ uint32_t lds32(uint32_t a) { uint32_t v; asm volatile("ld.shared.u32 %0, [%1];" : "=r"(v) : "r"(a) : "memory"); return v; }
__device__ __forceinline__ uint32_t lds32v(uint32_t a) { uint32_t v; asm volatile("ld.volatile.shared.u32 %0, [%1];" : "=r"(v) : "r"(a) : "memory"); return v; }
__device__ __forceinline__ uint32_t cpa(uint32_t a, uint32_t one) { uint32_t v; asm volatile("mul.lo.u32 %0, %1, %2;" : "=r"(v) : "r"(a), "r"(one)); return v; }
__device__ __forceinline__ uint32_t cpb(uint32_t a, uint32_t zero) { uint32_t v; asm volatile("or.b32 %0, %1, %2;" : "=r"(v) : "r"(a), "r"(zero)); return v; }
__device__ __forceinline__ uint32_t lds16(uint32_t a) { uint16_t v; asm volatile("ld.shared.u16 %0, [%1];" : "=h"(v) : "r"(a) : "memory"); return v; }
__device__ __forceinline__ float ldsf(uint32_t a) { float v; asm volatile("ld.shared.f32 %0, [%1];" : "=f"(v) : "r"(a) : "memory"); return v; }
__device__ __forceinline__ void lds128(uint32_t* v, uint32_t a) { asm volatile("ld.shared.v4.u32 {%0,%1,%2,%3}, [%4];" : "=r"(v[0]), "=r"(v[1]), "=r"(v[2]), "=r"(v[3]) : "r"(a) : "memory"); }
__device__ __forceinline__ void sts32(uint32_t a, uint32_t v) { asm volatile("st.shared.u32 [%0], %1;" :: "r"(a), "r"(v) : "memory"); }
__device__ __forceinline__ void sts16(uint32_t a, uint32_t v) { asm volatile("st.shared.u16 [%0], %1;" :: "r"(a), "h"((uint16_t)v) : "memory"); }
__device__ __forceinline__ void sts64f(uint32_t a, float x, float y) { asm volatile("st.shared.v2.f32 [%0], {%1,%2};" :: "r"(a), "f"(x), "f"(y) : "memory"); }
__device__ __forceinline__ void sts128(uint32_t a, uint32_t x, uint32_t y, uint32_t z, uint32_t w) { asm volatile("st.shared.v4.u32 [%0], {%1,%2,%3,%4};" :: "r"(a), "r"(x), "r"(y), "r"(z), "r"(w) : "memory"); }
__device__ __forceinline__ void stsm4(uint32_t a, uint32_t r0, uint32_t r1, uint32_t r2, uint32_t r3) {
  asm volatile("stmatrix.sync.aligned.m8n8.x4.shared.b16 [%0], {%1,%2,%3,%4};" :: "r"(a), "r"(r0), "r"(r1), "r"(r2), "r"(r3) : "memory");
}
__device__ __forceinline__ void stsm4t(uint32_t a, uint32_t r0, uint32_t r1, uint32_t r2, uint32_t r3) {
  asm volatile("stmatrix.sync.aligned.m8n8.x4.trans.shared.b16 [%0], {%1,%2,%3,%4};" :: "r"(a), "r"(r0), "r"(r1), "r"(r2), "r"(r3) : "memory");
}
__device__ __forceinline__ void ldsm4t(uint32_t* r, uint32_t a) {
  asm volatile("ldmatrix.sync.aligned.m8n8.x4.trans.shared.b16 {%0,%1,%2,%3}, [%4];" : "=r"(r[0]), "=r"(r[1]), "=r"(r[2]), "=r"(r[3]) : "r"(a) : "memory");
}
__device__ __forceinline__ void ldsm4(uint32_t* r, uint32_t a) {
  asm volatile("ldmatrix.sync.aligned.m8n8.x4.shared.b16 {%0,%1,%2,%3}, [%4];" : "=r"(r[0]), "=r"(r[1]), "=r"(r[2]), "=r"(r[3]) : "r"(a) : "memory");
}
__device__ __forceinline__ void mma16816(float* d, const uint32_t* a, const uint32_t* b) {
  asm volatile("mma.sync.aligned.m16n8k16.row.col.f32.bf16.bf16.f32 {%0,%1,%2,%3}, {%4,%5,%6,%7}, {%8,%9}, {%0,%1,%2,%3};"
    : "+f"(d[0]), "+f"(d[1]), "+f"(d[2]), "+f"(d[3]) : "r"(a[0]), "r"(a[1]), "r"(a[2]), "r"(a[3]), "r"(b[0]), "r"(b[1]));
}
__device__ __forceinline__ uint32_t pack2(float lo, float hi) { uint32_t r; asm("cvt.rn.bf16x2.f32 %0, %1, %2;" : "=r"(r) : "f"(hi), "f"(lo)); return r; }
__device__ __forceinline__ uint32_t packh(float lo, float hi) { uint32_t r; asm("cvt.rn.f16x2.f32 %0, %1, %2;" : "=r"(r) : "f"(hi), "f"(lo)); return r; }
__device__ __forceinline__ uint32_t hcmul(uint32_t x, uint32_t zp, uint32_t zq) {
  const __half2 xx = *reinterpret_cast<__half2*>(&x);
  const __half2 r = __hfma2(__high2half2(xx), *reinterpret_cast<__half2*>(&zq), __hmul2(__low2half2(xx), *reinterpret_cast<__half2*>(&zp)));
  return *reinterpret_cast<const uint32_t*>(&r);
}
__device__ __forceinline__ void hcm2(uint32_t xr, uint32_t xi, uint32_t z, uint32_t& pr, uint32_t& pi) {
  const __half2 a = *reinterpret_cast<__half2*>(&xr), b = *reinterpret_cast<__half2*>(&xi), zz = *reinterpret_cast<__half2*>(&z);
  const __half2 re = __hfma2(__hneg2(b), __high2half2(zz), __hmul2(a, __low2half2(zz)));
  const __half2 im = __hfma2(a, __high2half2(zz), __hmul2(b, __low2half2(zz)));
  pr = *reinterpret_cast<const uint32_t*>(&re); pi = *reinterpret_cast<const uint32_t*>(&im);
}
__device__ __forceinline__ void sts64(uint32_t a, uint32_t x, uint32_t y) { asm volatile("st.shared.v2.u32 [%0], {%1,%2};" :: "r"(a), "r"(x), "r"(y) : "memory"); }
__device__ __forceinline__ void lds64(uint32_t* v, uint32_t a) { asm volatile("ld.shared.v2.u32 {%0,%1}, [%2];" : "=r"(v[0]), "=r"(v[1]) : "r"(a) : "memory"); }
__device__ __forceinline__ float bf_lo(uint32_t v) { return __uint_as_float(v << 16); }
__device__ __forceinline__ float bf_hi(uint32_t v) { return __uint_as_float(v & 0xffff0000u); }
__device__ __forceinline__ float bf_round(float x) { return bf_lo(pack2(x, 0.f)); }
__device__ __forceinline__ float ex2(float x) { float r; asm("ex2.approx.ftz.f32 %0, %1;" : "=f"(r) : "f"(x)); return r; }
__device__ __forceinline__ float phi(float t, float l2e = 1.44269504089f) {
  float e = ex2(t * l2e) + 1e-6f;
  asm("{\n.reg .pred p;\nsetp.gt.f32 p, %1, 0f00000000;\n@p add.f32 %0, %1, 0f3F800008;\n}" : "+f"(e) : "f"(t));
  return e;
}
__device__ __forceinline__ void wg_fence() { asm volatile("wgmma.fence.sync.aligned;" ::: "memory"); }
__device__ __forceinline__ void wg_commit() { asm volatile("wgmma.commit_group.sync.aligned;" ::: "memory"); }
template <int N> __device__ __forceinline__ void wg_wait() { asm volatile("wgmma.wait_group.sync.aligned %0;" :: "n"(N) : "memory"); }
template <int N> __device__ __forceinline__ void pin(float* a) {
  #pragma unroll
  for (int i = 0; i < N; i++) asm volatile("" : "+f"(a[i]) :: "memory");
}
__device__ __forceinline__ int rtid() { int t; asm volatile("mov.u32 %0, %%tid.x;" : "=r"(t)); return t; }
__device__ __forceinline__ int opaque(int v) { asm volatile("" : "+r"(v)); return v; }
template <int N> __device__ __forceinline__ void zero(float* a) {
  #pragma unroll
  for (int i = 0; i < N; i++) asm volatile("mov.b32 %0, 0;" : "=f"(a[i]));
}
template <int N> __device__ __forceinline__ void pinu(uint32_t* a) {
  #pragma unroll
  for (int i = 0; i < N; i++) asm volatile("" : "+r"(a[i]) :: "memory");
}
__device__ __forceinline__ void cexp_t(float lg2mag, float turns, float& re, float& im) {
  float m = ex2(lg2mag);
  float fr = (turns - __fadd_rn(__fadd_rn(turns, 12582912.f), -12582912.f)) * 6.283185307f;
  re = m * __cosf(fr); im = m * __sinf(fr);
}
__device__ __forceinline__ void cmul(float ar, float ai, float br, float bi, float& cr, float& ci) {
  cr = fmaf(ar, br, -ai * bi); ci = fmaf(ar, bi, ai * br);
}

__device__ __forceinline__ void wg_ss48_tt(float* d, uint64_t da, uint64_t db, int scale_d) {
  asm volatile("{\n.reg .pred p;\nsetp.ne.b32 p, %26, 0;\n"
    "wgmma.mma_async.sync.aligned.m64n48k16.f32.bf16.bf16 "
    "{%0, %1, %2, %3, %4, %5, %6, %7, %8, %9, %10, %11, %12, %13, %14, %15, %16, %17, %18, %19, %20, %21, %22, %23}, %24, %25, p, 1, 1, 1, 1;\n}\n"
    : "+f"(d[0]), "+f"(d[1]), "+f"(d[2]), "+f"(d[3]), "+f"(d[4]), "+f"(d[5]), "+f"(d[6]), "+f"(d[7]), "+f"(d[8]), "+f"(d[9]), "+f"(d[10]), "+f"(d[11]), "+f"(d[12]), "+f"(d[13]), "+f"(d[14]), "+f"(d[15]), "+f"(d[16]), "+f"(d[17]), "+f"(d[18]), "+f"(d[19]), "+f"(d[20]), "+f"(d[21]), "+f"(d[22]), "+f"(d[23])
    : "l"(da), "l"(db), "r"(scale_d));
}
__device__ __forceinline__ void wg_rs88_tb(float* d, const uint32_t* a, uint64_t db, int scale_d) {
  asm volatile("{\n.reg .pred p;\nsetp.ne.b32 p, %49, 0;\n"
    "wgmma.mma_async.sync.aligned.m64n88k16.f32.bf16.bf16 "
    "{%0, %1, %2, %3, %4, %5, %6, %7, %8, %9, %10, %11, %12, %13, %14, %15, %16, %17, %18, %19, %20, %21, %22, %23, %24, %25, %26, %27, %28, %29, %30, %31, %32, %33, %34, %35, %36, %37, %38, %39, %40, %41, %42, %43}, {%44, %45, %46, %47}, %48, p, 1, 1, 1;\n}\n"
    : "+f"(d[0]), "+f"(d[1]), "+f"(d[2]), "+f"(d[3]), "+f"(d[4]), "+f"(d[5]), "+f"(d[6]), "+f"(d[7]), "+f"(d[8]), "+f"(d[9]), "+f"(d[10]), "+f"(d[11]), "+f"(d[12]), "+f"(d[13]), "+f"(d[14]), "+f"(d[15]), "+f"(d[16]), "+f"(d[17]), "+f"(d[18]), "+f"(d[19]), "+f"(d[20]), "+f"(d[21]), "+f"(d[22]), "+f"(d[23]), "+f"(d[24]), "+f"(d[25]), "+f"(d[26]), "+f"(d[27]), "+f"(d[28]), "+f"(d[29]), "+f"(d[30]), "+f"(d[31]), "+f"(d[32]), "+f"(d[33]), "+f"(d[34]), "+f"(d[35]), "+f"(d[36]), "+f"(d[37]), "+f"(d[38]), "+f"(d[39]), "+f"(d[40]), "+f"(d[41]), "+f"(d[42]), "+f"(d[43])
    : "r"(a[0]), "r"(a[1]), "r"(a[2]), "r"(a[3]), "l"(db), "r"(scale_d));
}
__device__ __forceinline__ void wg_ss80_tb(float* d, uint64_t da, uint64_t db, int scale_d) {
  asm volatile("{\n.reg .pred p;\nsetp.ne.b32 p, %42, 0;\n"
    "wgmma.mma_async.sync.aligned.m64n80k16.f32.bf16.bf16 "
    "{%0, %1, %2, %3, %4, %5, %6, %7, %8, %9, %10, %11, %12, %13, %14, %15, %16, %17, %18, %19, %20, %21, %22, %23, %24, %25, %26, %27, %28, %29, %30, %31, %32, %33, %34, %35, %36, %37, %38, %39}, %40, %41, p, 1, 1, 0, 1;\n}\n"
    : "+f"(d[0]), "+f"(d[1]), "+f"(d[2]), "+f"(d[3]), "+f"(d[4]), "+f"(d[5]), "+f"(d[6]), "+f"(d[7]), "+f"(d[8]), "+f"(d[9]), "+f"(d[10]), "+f"(d[11]), "+f"(d[12]), "+f"(d[13]), "+f"(d[14]), "+f"(d[15]), "+f"(d[16]), "+f"(d[17]), "+f"(d[18]), "+f"(d[19]), "+f"(d[20]), "+f"(d[21]), "+f"(d[22]), "+f"(d[23]), "+f"(d[24]), "+f"(d[25]), "+f"(d[26]), "+f"(d[27]), "+f"(d[28]), "+f"(d[29]), "+f"(d[30]), "+f"(d[31]), "+f"(d[32]), "+f"(d[33]), "+f"(d[34]), "+f"(d[35]), "+f"(d[36]), "+f"(d[37]), "+f"(d[38]), "+f"(d[39])
    : "l"(da), "l"(db), "r"(scale_d));
}
__device__ __forceinline__ void wg_ss48_tt_h(float* d, uint64_t da, uint64_t db, int scale_d) {
  asm volatile("{\n.reg .pred p;\nsetp.ne.b32 p, %26, 0;\n"
    "wgmma.mma_async.sync.aligned.m64n48k16.f32.f16.f16 "
    "{%0, %1, %2, %3, %4, %5, %6, %7, %8, %9, %10, %11, %12, %13, %14, %15, %16, %17, %18, %19, %20, %21, %22, %23}, %24, %25, p, 1, 1, 1, 1;\n}\n"
    : "+f"(d[0]), "+f"(d[1]), "+f"(d[2]), "+f"(d[3]), "+f"(d[4]), "+f"(d[5]), "+f"(d[6]), "+f"(d[7]), "+f"(d[8]), "+f"(d[9]), "+f"(d[10]), "+f"(d[11]), "+f"(d[12]), "+f"(d[13]), "+f"(d[14]), "+f"(d[15]), "+f"(d[16]), "+f"(d[17]), "+f"(d[18]), "+f"(d[19]), "+f"(d[20]), "+f"(d[21]), "+f"(d[22]), "+f"(d[23])
    : "l"(da), "l"(db), "r"(scale_d));
}
__device__ __forceinline__ void wg_rs192_tb(float* d, const uint32_t* a, uint64_t db, int scale_d) {
  asm volatile("{\n.reg .pred p;\nsetp.ne.b32 p, %101, 0;\n"
    "wgmma.mma_async.sync.aligned.m64n192k16.f32.bf16.bf16 "
    "{%0, %1, %2, %3, %4, %5, %6, %7, %8, %9, %10, %11, %12, %13, %14, %15, %16, %17, %18, %19, %20, %21, %22, %23, %24, %25, %26, %27, %28, %29, %30, %31, %32, %33, %34, %35, %36, %37, %38, %39, %40, %41, %42, %43, %44, %45, %46, %47, %48, %49, %50, %51, %52, %53, %54, %55, %56, %57, %58, %59, %60, %61, %62, %63, %64, %65, %66, %67, %68, %69, %70, %71, %72, %73, %74, %75, %76, %77, %78, %79, %80, %81, %82, %83, %84, %85, %86, %87, %88, %89, %90, %91, %92, %93, %94, %95}, {%96, %97, %98, %99}, %100, p, 1, 1, 1;\n}\n"
    : "+f"(d[0]), "+f"(d[1]), "+f"(d[2]), "+f"(d[3]), "+f"(d[4]), "+f"(d[5]), "+f"(d[6]), "+f"(d[7]), "+f"(d[8]), "+f"(d[9]), "+f"(d[10]), "+f"(d[11]), "+f"(d[12]), "+f"(d[13]), "+f"(d[14]), "+f"(d[15]), "+f"(d[16]), "+f"(d[17]), "+f"(d[18]), "+f"(d[19]), "+f"(d[20]), "+f"(d[21]), "+f"(d[22]), "+f"(d[23]), "+f"(d[24]), "+f"(d[25]), "+f"(d[26]), "+f"(d[27]), "+f"(d[28]), "+f"(d[29]), "+f"(d[30]), "+f"(d[31]), "+f"(d[32]), "+f"(d[33]), "+f"(d[34]), "+f"(d[35]), "+f"(d[36]), "+f"(d[37]), "+f"(d[38]), "+f"(d[39]), "+f"(d[40]), "+f"(d[41]), "+f"(d[42]), "+f"(d[43]), "+f"(d[44]), "+f"(d[45]), "+f"(d[46]), "+f"(d[47]), "+f"(d[48]), "+f"(d[49]), "+f"(d[50]), "+f"(d[51]), "+f"(d[52]), "+f"(d[53]), "+f"(d[54]), "+f"(d[55]), "+f"(d[56]), "+f"(d[57]), "+f"(d[58]), "+f"(d[59]), "+f"(d[60]), "+f"(d[61]), "+f"(d[62]), "+f"(d[63]), "+f"(d[64]), "+f"(d[65]), "+f"(d[66]), "+f"(d[67]), "+f"(d[68]), "+f"(d[69]), "+f"(d[70]), "+f"(d[71]), "+f"(d[72]), "+f"(d[73]), "+f"(d[74]), "+f"(d[75]), "+f"(d[76]), "+f"(d[77]), "+f"(d[78]), "+f"(d[79]), "+f"(d[80]), "+f"(d[81]), "+f"(d[82]), "+f"(d[83]), "+f"(d[84]), "+f"(d[85]), "+f"(d[86]), "+f"(d[87]), "+f"(d[88]), "+f"(d[89]), "+f"(d[90]), "+f"(d[91]), "+f"(d[92]), "+f"(d[93]), "+f"(d[94]), "+f"(d[95])
    : "r"(a[0]), "r"(a[1]), "r"(a[2]), "r"(a[3]), "l"(db), "r"(scale_d));
}
__device__ __forceinline__ void wg_rs48_tb(float* d, const uint32_t* a, uint64_t db, int scale_d) {
  asm volatile("{\n.reg .pred p;\nsetp.ne.b32 p, %29, 0;\n"
    "wgmma.mma_async.sync.aligned.m64n48k16.f32.bf16.bf16 "
    "{%0, %1, %2, %3, %4, %5, %6, %7, %8, %9, %10, %11, %12, %13, %14, %15, %16, %17, %18, %19, %20, %21, %22, %23}, {%24, %25, %26, %27}, %28, p, 1, 1, 1;\n}\n"
    : "+f"(d[0]), "+f"(d[1]), "+f"(d[2]), "+f"(d[3]), "+f"(d[4]), "+f"(d[5]), "+f"(d[6]), "+f"(d[7]), "+f"(d[8]), "+f"(d[9]), "+f"(d[10]), "+f"(d[11]), "+f"(d[12]), "+f"(d[13]), "+f"(d[14]), "+f"(d[15]), "+f"(d[16]), "+f"(d[17]), "+f"(d[18]), "+f"(d[19]), "+f"(d[20]), "+f"(d[21]), "+f"(d[22]), "+f"(d[23])
    : "r"(a[0]), "r"(a[1]), "r"(a[2]), "r"(a[3]), "l"(db), "r"(scale_d));
}
__device__ __forceinline__ void wg_ss192_tb(float* d, uint64_t da, uint64_t db, int scale_d) {
  asm volatile("{\n.reg .pred p;\nsetp.ne.b32 p, %98, 0;\n"
    "wgmma.mma_async.sync.aligned.m64n192k16.f32.bf16.bf16 "
    "{%0, %1, %2, %3, %4, %5, %6, %7, %8, %9, %10, %11, %12, %13, %14, %15, %16, %17, %18, %19, %20, %21, %22, %23, %24, %25, %26, %27, %28, %29, %30, %31, %32, %33, %34, %35, %36, %37, %38, %39, %40, %41, %42, %43, %44, %45, %46, %47, %48, %49, %50, %51, %52, %53, %54, %55, %56, %57, %58, %59, %60, %61, %62, %63, %64, %65, %66, %67, %68, %69, %70, %71, %72, %73, %74, %75, %76, %77, %78, %79, %80, %81, %82, %83, %84, %85, %86, %87, %88, %89, %90, %91, %92, %93, %94, %95}, %96, %97, p, 1, 1, 0, 1;\n}\n"
    : "+f"(d[0]), "+f"(d[1]), "+f"(d[2]), "+f"(d[3]), "+f"(d[4]), "+f"(d[5]), "+f"(d[6]), "+f"(d[7]), "+f"(d[8]), "+f"(d[9]), "+f"(d[10]), "+f"(d[11]), "+f"(d[12]), "+f"(d[13]), "+f"(d[14]), "+f"(d[15]), "+f"(d[16]), "+f"(d[17]), "+f"(d[18]), "+f"(d[19]), "+f"(d[20]), "+f"(d[21]), "+f"(d[22]), "+f"(d[23]), "+f"(d[24]), "+f"(d[25]), "+f"(d[26]), "+f"(d[27]), "+f"(d[28]), "+f"(d[29]), "+f"(d[30]), "+f"(d[31]), "+f"(d[32]), "+f"(d[33]), "+f"(d[34]), "+f"(d[35]), "+f"(d[36]), "+f"(d[37]), "+f"(d[38]), "+f"(d[39]), "+f"(d[40]), "+f"(d[41]), "+f"(d[42]), "+f"(d[43]), "+f"(d[44]), "+f"(d[45]), "+f"(d[46]), "+f"(d[47]), "+f"(d[48]), "+f"(d[49]), "+f"(d[50]), "+f"(d[51]), "+f"(d[52]), "+f"(d[53]), "+f"(d[54]), "+f"(d[55]), "+f"(d[56]), "+f"(d[57]), "+f"(d[58]), "+f"(d[59]), "+f"(d[60]), "+f"(d[61]), "+f"(d[62]), "+f"(d[63]), "+f"(d[64]), "+f"(d[65]), "+f"(d[66]), "+f"(d[67]), "+f"(d[68]), "+f"(d[69]), "+f"(d[70]), "+f"(d[71]), "+f"(d[72]), "+f"(d[73]), "+f"(d[74]), "+f"(d[75]), "+f"(d[76]), "+f"(d[77]), "+f"(d[78]), "+f"(d[79]), "+f"(d[80]), "+f"(d[81]), "+f"(d[82]), "+f"(d[83]), "+f"(d[84]), "+f"(d[85]), "+f"(d[86]), "+f"(d[87]), "+f"(d[88]), "+f"(d[89]), "+f"(d[90]), "+f"(d[91]), "+f"(d[92]), "+f"(d[93]), "+f"(d[94]), "+f"(d[95])
    : "l"(da), "l"(db), "r"(scale_d));
}
__device__ __forceinline__ void wg_ss48_tb(float* d, uint64_t da, uint64_t db, int scale_d) {
  asm volatile("{\n.reg .pred p;\nsetp.ne.b32 p, %26, 0;\n"
    "wgmma.mma_async.sync.aligned.m64n48k16.f32.bf16.bf16 "
    "{%0, %1, %2, %3, %4, %5, %6, %7, %8, %9, %10, %11, %12, %13, %14, %15, %16, %17, %18, %19, %20, %21, %22, %23}, %24, %25, p, 1, 1, 0, 1;\n}\n"
    : "+f"(d[0]), "+f"(d[1]), "+f"(d[2]), "+f"(d[3]), "+f"(d[4]), "+f"(d[5]), "+f"(d[6]), "+f"(d[7]), "+f"(d[8]), "+f"(d[9]), "+f"(d[10]), "+f"(d[11]), "+f"(d[12]), "+f"(d[13]), "+f"(d[14]), "+f"(d[15]), "+f"(d[16]), "+f"(d[17]), "+f"(d[18]), "+f"(d[19]), "+f"(d[20]), "+f"(d[21]), "+f"(d[22]), "+f"(d[23])
    : "l"(da), "l"(db), "r"(scale_d));
}

struct Params {
  const __nv_bfloat16 *par[4], *logdt, *dskip, *u, *wo;
  CUtensorMap m[M_COUNT];
};

#define CHUNK(i) ((i) == 0 ? c : ((i) == 7 ? (c ^ 1) : (((c & 6) + 1 + (i)) & 7)))
#define FLAG(kind, rr, cc) (&g_flag[((kind) * 128 + (rr) * 8 + (cc)) * 32])
#define SLOT(i) ((i) == 0 ? OFF_EXTRA : OFF_BLK - 1024 + ((i) > 5 ? (i) - 6 : (i) - 1) * BLK)
__device__ __forceinline__ void load_quad(uint32_t* A, uint32_t addr) {
  A[0] = lds32v(addr); A[1] = lds32v(addr + 32); A[2] = lds32v(addr - 32); A[3] = lds32v(addr);
}

__device__ __forceinline__ bool y_transpose(uint32_t sb, int w5, int lane, uint32_t ytag) {
  const int mi = lane >> 3, rw = lane & 7;
  const uint32_t sa = sb + OFF_EXTRA + (w5 * 16 + rw) * 128 + ((mi ^ rw) << 4), da = sb + SLOT(3) + (8 * mi + rw) * 160 + w5 * 32;
  const uint32_t ym = lane < 4 ? 0x10001u : 0u;
  bar_sync(7, 160);
  uint32_t v[8][4], bad = 0;
  #pragma unroll
  for (int q = 0; q < 8; q++) ldsm4t(v[q], (sa ^ ((q & 1) * 64 + ((q >> 1) & 1) * 16)) + ((q >> 1) & 1) * 10240 + (q >> 2) * 1024);
  #pragma unroll
  for (int q = 0; q < 8; q++) {
    bad |= (v[q][0] ^ ytag) | (v[q][2] ^ ytag);
    stsm4(da + (q & 3) * 5120 + (q >> 2) * 16, v[q][0] & ~ym, v[q][1], v[q][2] & ~ym, v[q][3]);
  }
  fence_async();
  uint32_t any;
  asm volatile("{\n.reg .pred p;\nsetp.ne.u32 p, %1, 0;\nbarrier.red.or.pred p, 7, 160, p;\nselp.u32 %0, 1, 0, p;\n}" : "=r"(any) : "r"(bad & ym) : "memory");
  return any;
}

__global__ void __launch_bounds__(512, 1) fused_kernel(const __grid_constant__ Params prm) {
  extern __shared__ unsigned char smem_raw[];
  const uint32_t sb = __shfl_sync(0xffffffff, smem_u32(smem_raw), 0);
  const int tid = threadIdx.x, lane = tid & 31;
  const int warp = __shfl_sync(0xffffffff, tid >> 5, 0), wg = warp >> 2, w4 = warp & 3;
  const int cta = blockIdx.x, r = cta >> 3, c = cta & 7;
  if ((sb & 0xffffffu) != SB0) return;
#define BAR(i) (sb + OFF_BAR + 8 * (i))
  const bool sw64 = ((c + 1) & 2) != 0;

  const CUtensorMap* mwp = &prm.m[sw64 ? M_W64 : M_W128];
  const int mcol = (c * 80 + (c & 1) * 16) >> (sw64 ? 5 : 6), rcol = c * 80 + ((c & 1) ? 0 : 64);
  if (warp == 12 && elect_one()) {
    #pragma unroll
    for (int i = 0; i < 5; i++) mbar_init(BAR(BR_FULL + i), 1);
    asm volatile("fence.mbarrier_init.release.cluster;" ::: "memory");
    if (EN_ATT) {
      mbar_expect_tx(BAR(BR_FULL), W_SLOT + 16384);
      tma4d(sb, mwp, BAR(BR_FULL), 0, 0, mcol, 0);
      tma2d(sb + OFF_X, &prm.m[M_X], BAR(BR_FULL), 0, r * 128);
      tma3d(sb + 12288, &prm.m[M_WR], BAR(BR_FULL), rcol, 0, 0);
      mbar_expect_tx(BAR(BR_FULL + 1), W_SLOT);
      tma4d(sb + W_SLOT, mwp, BAR(BR_FULL + 1), 0, 32, mcol, 0);
      tma3d(sb + W_SLOT + 12288, &prm.m[M_WR], BAR(BR_FULL + 1), rcol, 32, 0);
      TS(24);
    }
  }
  if (warp == 13 && elect_one()) {
    asm volatile("prefetch.tensormap [%0];" :: "l"(&prm.m[M_X]) : "memory");
    asm volatile("prefetch.tensormap [%0];" :: "l"(&prm.m[M_WR]) : "memory");
  }
  if (wg == 3) {
    asm volatile("setmaxnreg.dec.sync.aligned.u32 56;");
    const int tid = rtid(), lane = tid & 31;
    if (warp == 12) {
      asm volatile("bar.arrive 0, 512;" ::: "memory");
      {
        uint32_t s = 2, ph = 1, xs = 16384;
        #pragma unroll 1
        for (int kb = 2; kb < 20; kb++) {
          if (kb == 4) bar_sync(6, 128);
          if (kb >= 5) mbar_wait(BAR(BR_EMPTY) + 8 * s, ph);
          if (EN_ATT && elect_one()) {
            const uint32_t st = sb + s * W_SLOT, fb = BAR(BR_FULL) + 8 * s;
            mbar_expect_tx(fb, (kb & 1) ? W_SLOT : W_SLOT + 16384);
            if (!(kb & 1)) tma2d(sb + OFF_X + xs, &prm.m[M_X], fb, kb * 32, r * 128);
            tma4d(st, mwp, fb, 0, kb * 32, mcol, 0);
            tma3d(st + 12288, &prm.m[M_WR], fb, rcol, kb * 32, 0);
          }
          if (kb < 4 && lane == 0) TS(24 + kb);
          if (UPF && kb >= UKB - 4 && kb < UKB && elect_one())
            asm volatile("cp.async.bulk.prefetch.L2.global [%0], 5120;" :: "l"(prm.u + cta * 10240 + (kb - (UKB - 4)) * 2560) : "memory");
          if (EN_SSM && kb == (EN_ATT ? UKB : 4) && elect_one()) { mbar_expect_tx(BAR(BR_UIN), 20480); tma2d(sb + OFF_UT, &prm.m[M_U], BAR(BR_UIN), c * 80, r * 128); }
          if (kb == 14 && elect_one()) asm volatile("cp.async.bulk.prefetch.L2.global [%0], 6400;" :: "l"(prm.wo + cta * 3200) : "memory");
          if (!EN_ATT && kb == 4) break;
          if (++s == 5) { s = 0; ph ^= 1; }
          if (kb & 1) { xs += 16384; if (xs == 49152) xs = 0; }
        }
      }
      if (EN_ATT) {
      mbar_wait(BAR(BR_EPOCH), 0);
      const unsigned epoch = lds32(sb + OFF_EPOCH);
      const unsigned* fo = FLAG(3, r, lane & 7);
      unsigned seen = __ballot_sync(0xffffffff, ld_rlx(lane < 16 ? fo : FLAG(0, lane & 15, c)) == epoch) & 0xffu;
      mbar_wait(BAR(BR_GEMM), 0);
      if (elect_one()) {
        mbar_expect_tx(BAR(BR_WO), 10240);
        tma2d(sb, &prm.m[M_WO], BAR(BR_WO), c * 64, c * 80);
        mbar_expect_tx(BAR(BR_KVP), 61440);
        mbar_expect_tx(BAR(BR_WO + 1), 7 * 10240);
      }
      {
        uint32_t ds = sb + OFF_WOR + (lane >> 3) * 128 + (((lane & 7) ^ (lane >> 3)) << 4);
        #pragma unroll 1
        for (int h = 0; h < 2; h++) {
          const int i = (lane & 6) + h;
          const char* gs = reinterpret_cast<const char*>(prm.wo) + (size_t)((lane >> 3) + CHUNK(i) * 80) * 1280 + 1024 + c * 32 + (lane & 1) * 16;
          #pragma unroll 2
          for (int q = 0; q < 20; q++) {
            asm volatile("cp.async.cg.shared.global [%0], [%1], 16;" :: "r"(ds), "l"(gs) : "memory");
            ds = (ds + 512) ^ 64; gs += 5120;
          }
        }
      }
      mbar_wait(BAR(BR_PUB), 0);
      poll_all(FLAG(0, lane & 15, c), epoch);
      if (elect_one()) { TS(23); bulk_ld(sb + OFF_KVP, &g_kvp[c * 16 * 240], 61440, BAR(BR_KVP)); }
      asm volatile("cp.async.wait_all;" ::: "memory");
      fence_async();
      mbar_arrive(BAR(BR_WO));
      mbar_wait(BAR(BR_SUM), 0);
      if (elect_one()) {
        #pragma unroll 1
        for (int i = 1; i < 8; i++) tma2d(sb + i * 10240, &prm.m[M_WO], BAR(BR_WO + 1), c * 64, CHUNK(i) * 80);
      }
      mbar_wait(BAR(BR_OSTG), 0);
      if (elect_one()) {
        bulk_st(&g_o[cta * 1280], sb + OFF_EXTRA, 20480);
        bulk_commit();
        bulk_wait0();
        st_rlx(FLAG(3, r, c), epoch);
        mbar_arrive(BAR(BR_OEMPTY));
        TS(20);
      }
      __syncwarp();
      #pragma unroll 1
      for (int i = 1; i < 8; i++) {
        const int src = CHUNK(i);
        if (!((seen >> src) & 1)) seen = poll_bit(fo, epoch, 1u << src);
        if (i > 5) mbar_wait(BAR(BR_OEMPTY - 5) + 8 * i, 0);
        if (EN_SSM && (i == 1 || i == 5)) mbar_wait(BAR(BR_FREE) + 2 * (i & 4), 0);
        if (elect_one()) {
          mbar_expect_tx(BAR(BR_OFULL) + 8 * i, 20480);
          bulk_ld(sb + SLOT(i), &g_o[(r * 8 + src) * 1280], 20480, BAR(BR_OFULL) + 8 * i);
          if (i == 1) TS(21);
          if (i == 7) TS(22);
        }
        __syncwarp();
      }
      if (lane == 0) { DUMP(20, 30); }
      }
    } else {
      const int hw = warp - 13, ht = tid - 416;
      if (hw == 2 && elect_one()) {
        #pragma unroll
        for (int i = 5; i < BR_COUNT; i++) mbar_init(BAR(i), i == BR_WO ? 33 : i == BR_OEMPTY ? 9 : i < BR_EMPTY ? 1 : i < BR_OEMPTY ? 2 : i < BR_Y ? 8 : i < BR_OSTG ? 4 : i == BR_OSTG ? 8 : i < BR_U2 ? 3 : 1);
        asm volatile("fence.mbarrier_init.release.cluster;" ::: "memory");
      }
      __syncwarp();
      asm volatile("bar.arrive 0, 512;" ::: "memory");
      if (EN_SSM && hw == 2) asm volatile("bar.arrive 8, 160;" ::: "memory");
      const unsigned epoch = hw == 0 ? ld_rlx(&g_epoch[cta]) + 1 : 0;
      bar_sync(5, 96);
      asm volatile("bar.arrive 6, 128;" ::: "memory");
      if (hw == 1 && elect_one()) {
        #pragma unroll
        for (int i = M_U; i < M_COUNT; i++) asm volatile("prefetch.tensormap [%0];" :: "l"(&prm.m[i]) : "memory");
      }
      if (ht == 0) {
        st_rlx(&g_epoch[cta], epoch);
        sts32(sb + OFF_EPOCH, epoch);
        mbar_arrive(BAR(BR_EPOCH));
      }
      if (EN_SSM) {
      const int mi = lane >> 3, rw = lane & 7, ch0 = c * 80 + r * 5;
      mbar_wait(BAR(BR_UIN), 0);
      if (ht == 0) TS(36);
      #pragma unroll 1
      for (int h = 0; h < 2; h++) {
        const uint32_t sa = sb + OFF_UT + h * 10240 + (8 * mi + rw) * 160 + hw * 16, da = sb + OFF_UT + h * 10240 + (hw * 8 + rw) * 128 + ((mi ^ rw ^ h) << 4);
        uint32_t v[8][4];
        #pragma unroll
        for (int q = 0; q < 8; q++) if (q < 6 || hw == 0) ldsm4t(v[q], sa + (q & 1) * 5120 + (q >> 1) * 48);
        bar_sync(5, 96);
        #pragma unroll
        for (int q = 0; q < 8; q++) if (q < 6 || hw == 0) stsm4((da ^ ((q & 1) * 64)) + (q >> 1) * 3072, v[q][0], v[q][1], v[q][2], v[q][3]);
      }
      fence_async();
      bar_sync(5, 96);
      if (hw == 0) {
        if (elect_one()) {
          tma2d_st(&prm.m[M_SA], sb + OFF_UT, r * 128, c * 80);
          tma2d_st(&prm.m[M_SA], sb + OFF_UT + 10240, r * 128 + 64, c * 80);
          bulk_commit(); bulk_wait0_read();
          mbar_arrive(BAR(BR_UOUT));
          TS(37);
          bulk_wait0();
          st_rel(FLAG(1, r, c), epoch);
          TS(30);
        }
        __syncwarp();
        poll_all_acq(FLAG(1, lane & 15, c), epoch);
      }
      #pragma unroll 1
      for (int k = 0; k < 5; k++) {
        if (k == 0 || k == 3) {
          const int p = k != 0;
          if (hw == 0) {
            if (!p) {
              if (elect_one()) {
                fence_async_g();
                mbar_expect_tx(BAR(BR_U), 12288);
                #pragma unroll 1
                for (int q = 0; q < 3; q++) bulk_ld(sb + OFF_BLK + q * q * BLK, g_uy + (ch0 + q * q) * 2048, 4096, BAR(BR_U));
                TS(31);
              }
              __syncwarp();
            }
            mbar_wait(BAR(p ? BR_U2 : BR_U), 0);
          }
          bar_sync(5, 96);
        }
        const int l3 = (hw + k) % 3 * 32 + lane;
        const uint32_t blk = sb + OFF_BLK + ((0x32410 >> (4 * k)) & 7) * BLK, o = blk + B_D + l3 * 16;
        float P[34];
        P[0] = 0.f;
        #pragma unroll
        for (int q = 0; q < 5; q++) {
          const int ch = 2 * l3 - 3 + q;
          uint32_t v[4];
          lds128(v, blk + (uint32_t)((ch * 16) ^ ((ch * 2) & 0x10)));
          #pragma unroll
          for (int e = 0; e < 8; e++) {
            const int i = 8 * q + e - 4;
            if (i >= 0 && i < 33) P[i + 1] = P[i] + ((e & 1) ? bf_hi(v[e >> 1]) : bf_lo(v[e >> 1]));
          }
        }
#define WIN(lo, hi, e) (P[21 + (e) - (lo)] - P[20 + (e) - (hi)])
#define WIN8(lo, hi, b) pack2(WIN(lo, hi, b), WIN(lo, hi, b + 1)), pack2(WIN(lo, hi, b + 2), WIN(lo, hi, b + 3)), pack2(WIN(lo, hi, b + 4), WIN(lo, hi, b + 5)), pack2(WIN(lo, hi, b + 6), WIN(lo, hi, b + 7))
        if (l3 < 64) {
          sts128(o + B_D9, WIN8(12, 20, 0)); sts128(o + B_D9 + 1024, WIN8(12, 20, 8));
          sts128(o + B_D7, WIN8(5, 11, 0)); sts128(o + B_D7 + 1024, WIN8(5, 11, 8));
        }
        sts128(o + B_D5, WIN8(6, 10, 0)); sts128(o + B_D5 + 1552, WIN8(6, 10, 8));
        sts128(o, WIN8(3, 5, 0)); sts128(o + 1552, WIN8(3, 5, 8));
        if (l3 < 2) sts128(blk + B_D + l3 * B_D5 + 1536, 0, 0, 0, 0);
      }
      __syncwarp();
      if (lane == 0) mbar_arrive(BAR(BR_DRDY + 1));
      if (ht == 0) TS(32);
      if (hw == 0) {
        #pragma unroll 1
        for (int p = 0; p < 2; p++) {
          mbar_wait(BAR(BR_Y) + 8 * p, 0);
          if (elect_one()) {
            #pragma unroll 1
            for (int k = 4 * p; k < 4 + p; k++) bulk_st(g_uy + (640 + ch0 + k) * 2048, sb + OFF_BLK + k * BLK, 4096);
            bulk_commit(); bulk_wait0_read();
            mbar_arrive(BAR(BR_FREE) + 8 * p);
          }
          __syncwarp();
        }
        if (elect_one()) { bulk_wait0(); st_rlx(FLAG(2, r, c), epoch); TS(33); }
        __syncwarp();
        poll_all(FLAG(2, lane & 15, c), epoch);
        if (EN_ATT) mbar_wait(BAR(BR_OEMPTY), 0);
        #pragma unroll 1
        for (int n = 0; n < 64; n++) {
          if (elect_one()) {
            mbar_expect_tx(BAR(BR_YIN), 20480);
            tma2d(sb + OFF_EXTRA, &prm.m[M_SA], BAR(BR_YIN), r * 128, 640 + c * 80);
            tma2d(sb + OFF_EXTRA + 10240, &prm.m[M_SA], BAR(BR_YIN), r * 128 + 64, 640 + c * 80);
            TS(34);
          }
          __syncwarp();
          if (EN_ATT) mbar_wait(BAR(BR_OEMPTY + 3), 0);
          mbar_wait(BAR(BR_YIN), n & 1);
          if (lane == 0) TS(38);
          if (!y_transpose(sb, 4, lane, (epoch & 1u) * 0x10001u)) break;
          FIXCNT
        }
      if (elect_one()) {
        TS(39);
        tma2d_st(&prm.m[M_OUT], sb + SLOT(3), c * 80, r * 128);
        bulk_commit(); bulk_wait0_read();
        TS(35); DUMP(30, 40); DUMP(0, 1);
      }
      }
      }
    }
  } else if (wg < 2) {
    asm volatile("setmaxnreg.inc.sync.aligned.u32 160;");
    bar_sync(0, 512);
    if (EN_ATT) {
    float am[96], ar[24];
    {
      const bool lead = (rtid() & 127) == 0;
      constexpr uint64_t dr0 = mkdesc(SB0 + 12288, 1024, 256, 3);
      const uint64_t db0 = sw64 ? mkdesc(SB0, 2048, 512, 2) : mkdesc(SB0, 4096, 1024, 1);
      const uint32_t kst = sw64 ? 64 : 128, bh = db0 >> 32;
      uint32_t s = 0, ph = 0, xo = 0;
      const int ln = rtid() & 31;
      const uint32_t xa = sb + OFF_X + (warp * 16 + (ln & 15)) * 128 + (((ln >> 4) ^ (ln & 7)) << 4);
      uint32_t A[8];
      mbar_wait(BAR(BR_FULL), 0);
      if (lead && wg == 0) TS(1);
      ldsm4(A, xa); ldsm4(A + 4, xa);
      wg_fence();
      wg_rs48_tb(ar, A + 4, dr0, 0); wg_rs192_tb(am, A + 4, db0, 0);
      wg_commit();
      uint32_t xk = xa, eb = 0;
      #pragma unroll 1
      for (int kb = 0; kb < 20; kb++) {
        const uint32_t wo_ = s * (W_SLOT >> 4), bl = (uint32_t)db0 + wo_, rl = (uint32_t)dr0 + wo_;
        wg_fence();
        wg_rs48_tb(ar, A, desc2(rl, dr0 >> 32), kb != 0);
        wg_rs192_tb(am, A, desc2(bl, bh), kb != 0);
        wg_commit();
        wg_wait<1>();
        ldsm4(A + 4, xk ^ 32);
        if (lead && kb > 0 && kb < 16) mbar_arrive(eb);
        eb = BAR(BR_EMPTY) + 8 * s;
        wg_fence();
        wg_rs48_tb(ar, A + 4, desc2(rl + 32, dr0 >> 32), 1);
        wg_rs192_tb(am, A + 4, desc2(bl + kst, bh), 1);
        wg_commit();
        if (++s == 5) { s = 0; ph ^= 1; }
        if (kb & 1) { xo += 16384; if (xo == 49152) xo = 0; }
        if (kb < 19) mbar_wait(BAR(BR_FULL) + 8 * s, ph);
        xk = (xa + xo) ^ ((~kb & 1) * 64);
        wg_wait<1>();
        ldsm4(A, xk);
      }
      wg_wait<0>();
      pin<96>(am); pin<24>(ar);
    }
    const int tid = rtid(), lane = tid & 31, tq = lane & 3;
    if (tid == 0) TS(2);
#define QV(j, e) ((j) < 8 ? am[4 * (j) + (e)] : ar[4 * ((j) - 8) + (e)])
#define KV_(j, e) ((j) < 8 ? am[32 + 4 * (j) + (e)] : ar[8 + 4 * ((j) - 8) + (e)])
#define VV(j, e) ((j) < 8 ? am[64 + 4 * (j) + (e)] : ar[16 + 4 * ((j) - 8) + (e)])
    {
      bar_sync(1, 256);
      if (tid == 0) mbar_arrive(BAR(BR_GEMM));
      const uint32_t ro = sb + (uint32_t)((warp * 16 + (lane & 15)) * 16);
      const int l0 = 2 * (c & 1) + (lane >> 4);
      const uint32_t ones = (tq == 0) ? 0x00003f80u : 0u;
#define PV(j) pack2(VV(j, 0), VV(j, 1)), pack2(VV(j, 2), VV(j, 3))
#define PK(j) pack2(phi(KV_(j, 0)), phi(KV_(j, 1))), pack2(phi(KV_(j, 2)), phi(KV_(j, 3)))
      stsm4(ro + OFF_V + (5 + 6 * (lane >> 4)) * 2048, ones, ones, ones, ones);
      #pragma unroll
      for (int j = 0; j < 10; j += 2) {
        const int l = (j == 8 && (c & 1)) ? l0 - 2 : l0 + j;
        stsm4(ro + OFF_V + (l + (l >= 5)) * 2048, PV(j), PV(j + 1));
        stsm4(ro + OFF_PK + l * 2048, PK(j), PK(j + 1));
      }
    }
    fence_async();
    bar_sync(1, 256);
    if (tid == 0) TS(3);
    mbar_wait(BAR(BR_EPOCH), 0);
    const unsigned epoch = lds32(sb + OFF_EPOCH);
    {
      float kv[24]; zero<24>(kv);
      constexpr uint64_t da = mkdesc(SB0 + OFF_PK, 128, 2048, 0), db = mkdesc(SB0 + OFF_V, 128, 2048, 0);
      wg_fence();
      #pragma unroll
      for (int s = 0; s < 8; s++) wg_ss48_tt(kv, desc2((uint32_t)da + wg * 640 + s * 16, da >> 32), desc2((uint32_t)db + wg * 768 + s * 16, db >> 32), s != 0);
      wg_commit();
      wg_wait<0>();
      pin<24>(kv);
      if (tid == 0) TS(15);
      if (w4 < 3) {
        const uint32_t wb = sb + OFF_KVS + (wg * 3 + w4) * 1536 + (lane & 15) * 96;
        #pragma unroll
        for (int j = 0; j < 6; j += 2)
          stsm4(wb + (j + (lane >> 4)) * 16, pack2(kv[4 * j], kv[4 * j + 1]), pack2(kv[4 * j + 2], kv[4 * j + 3]),
                pack2(kv[4 * j + 4], kv[4 * j + 5]), pack2(kv[4 * j + 6], kv[4 * j + 7]));
        __syncwarp();
        const int dl = w4 * 16 + (lane & 15), hl = dl >= 20;
        if (dl < 40) {
          uint4* dst = &g_kvp[(c * 16 + r) * 240 + wg * 40 + dl];
          uint32_t v[4], z[4];
          lds128(v, wb + (3 * hl + (lane >> 4)) * 16);
          lds64(z, wb + 32 + 8 * hl); z[2] = lds32(wb + 80); z[3] = epoch & 1u;
          v[3] = (v[3] & ~1u) | z[3];
          st128_rlx(dst + (lane >> 4) * 80, v);
          if (lane < 16) st128_rlx(dst + 160, z);
        }
      }
    }
    fence_async();
    bar_sync(1, 256);
    if (tid == 0) { st_rlx(FLAG(0, r, c), epoch); mbar_arrive(BAR(BR_PUB)); TS(4); }
    const int kvi = (tid >= 80) + (tid >= 160) + (tid >= 240), kd = tid - 80 * kvi;
    const int khd = kd / 20, kt0 = 5 * (khd >> 1) + 2 * (khd & 1);
    const uint32_t rb = sb + OFF_KVB + kd * 16;
    if (kvi < 3) {
      #pragma unroll 1
      for (int m = kvi; m < 7; m += 3) { const int q = kt0 + 3 + m; sts128(rb + (q >= 10 ? q - 10 : q) * 1280, 0, 0, 0, 0); }
    }
    uint32_t qa[20];
    {
      const float sc = 1.44269504089f + __uint_as_float(lds32(sb + OFF_EPOCH) ^ epoch);
      #pragma unroll
      for (int j = 0; j < 10; j++) { qa[2 * j] = pack2(phi(QV(j, 0), sc), phi(QV(j, 1), sc)); qa[2 * j + 1] = pack2(phi(QV(j, 2), sc), phi(QV(j, 3), sc)); }
    }
    if (tid == 0) TS(5);
    if (warp == 7) mbar_wait(BAR(BR_KVP), 0);
    bar_sync(1, 256);
    if (tid == 0) TS(6);
    if (kvi < 3) {
      float s[8];
      zero<8>(s);
      uint32_t bad = 0;
      #pragma unroll 4
      for (int i = 0; i < 16; i += 2) {
        uint32_t w[4], x[4];
        lds128(w, sb + OFF_KVP + tid * 16 + i * 3840); lds128(x, sb + OFF_KVP + tid * 16 + i * 3840 + 3840);
        bad |= (w[3] ^ epoch) | (x[3] ^ epoch);
        #pragma unroll
        for (int e = 0; e < 4; e++) {
          asm("add.rn.bf16x2 %0, %0, %1;" : "+r"(w[e]) : "r"(x[e]));
          s[2 * e] += bf_lo(w[e]); s[2 * e + 1] += bf_hi(w[e]);
        }
      }
      if (__builtin_expect(bad & 1u, 0)) {
        zero<8>(s);
        #pragma unroll 1
        for (int i = 0; i < 16; i++) {
          uint32_t w[4] = {0, 0, 0, ~epoch};
          fix128_w3(w, &g_kvp[(c * 16 + i) * 240 + tid], epoch, 1u);
          #pragma unroll
          for (int e = 0; e < 4; e++) { s[2 * e] += bf_lo(w[e]); s[2 * e + 1] += bf_hi(w[e]); }
        }
        FIXCNT
      }
      const uint32_t p0 = pack2(s[0], s[1]), p1 = pack2(s[2], s[3]), p2 = pack2(s[4], s[5]), p3 = pack2(s[6], s[7]);
      if (kvi < 2) sts128(rb + (kt0 + (khd & 1) + kvi) * 1280, p0, p1, p2, p3);
      else {
        const bool od = khd & 1;
        sts128(rb + (5 * (khd >> 1) + 2) * 1280, od ? 0u : p0, od ? 0u : p1, od ? p0 : 0u, od ? p1 : 0u);
        const uint32_t zz = (p2 & 0xffffu) << (16 * (khd & 1));
        sts128(rb + 10 * 1280, khd < 2 ? zz : 0u, khd < 2 ? 0u : zz, 0u, 0u);
      }
    }
    fence_async();
    bar_sync(1, 256);
    if (tid == 0) { mbar_arrive(BAR(BR_SUM)); TS(7); }
    {
      float oa[44]; zero<44>(oa);
      constexpr uint64_t db = mkdesc(SB0 + OFF_KVB, 128, 1280, 0);
      wg_fence();
      #pragma unroll
      for (int s = 0; s < 5; s++) wg_rs88_tb(oa, &qa[4 * s], desc2((uint32_t)db + ((s == 4 && (c & 1)) ? 0 : (s + (c & 1)) * 16), db >> 32), s != 0);
      wg_commit();
      wg_wait<0>();
      pin<44>(oa);
      if (tid == 0) TS(13);
      float rc[4], rd[2][4];
      #pragma unroll
      for (int e = 0; e < 4; e++) asm("rcp.approx.ftz.f32 %0, %1;" : "=f"(rc[e]) : "f"(oa[40 + e] + 1e-6f));
      #pragma unroll
      for (int h = 0; h < 4; h++) {
        rd[0][h] = __shfl_sync(0xffffffff, rc[h & 1], (lane & 28) | (h >> 1));
        rd[1][h] = __shfl_sync(0xffffffff, rc[2 + (h & 1)], (lane & 28) | (h >> 1));
      }
      #pragma unroll
      for (int j = 0; j < 10; j++) {
        #pragma unroll
        for (int h = 0; h < 2; h++) {
          float f;
          if (j == 2) f = tq < 2 ? rd[h][0] : rd[h][1];
          else if (j == 7) f = tq < 2 ? rd[h][2] : rd[h][3];
          else f = rd[h][(8 * j) / 20];
          qa[2 * j + h] = pack2(oa[4 * j + 2 * h] * f, oa[4 * j + 2 * h + 1] * f);
        }
      }
      const uint32_t m0 = (lane & 7) == ((2 * w4) & 7), m1 = (lane & 7) == 2 * w4 + 1;
      const uint32_t oa_ = sb + OFF_EXTRA + (lane >> 4) * 2048 + (warp * 16 + (lane & 15)) * 16;
      bar_sync(1, 256);
#define TAG(v, m) (((v) & ~(m)) | (epoch & (m)))
      #pragma unroll
      for (int s = 0; s < 5; s++) stsm4(oa_ + s * 4096, TAG(qa[4 * s], m0), TAG(qa[4 * s + 1], m1), TAG(qa[4 * s + 2], m0), TAG(qa[4 * s + 3], m1));
    }
    fence_async();
    __syncwarp();
    if (lane == 0) mbar_arrive(BAR(BR_OSTG));
    if (tid == 0) TS(8);
    float oc[40]; zero<40>(oc);
    {
      constexpr uint64_t dw0 = mkdesc(SB0, OFF_WOR, 1024, 1), da0 = mkdesc(SB0, 2048, 128, 0);
      const uint32_t ck = sb + tid * 32 + ((lane >> 2) << 2), ck2 = ck + (wg ? 0 : 16384);
      uint32_t bad = 0;
      auto tile = [&](int i, uint32_t so) {
        const uint32_t al = (uint32_t)da0 + wg * 64 + (so >> 4), wl = (uint32_t)dw0 + i * 640 - (i >> 1) * (1278 << 16);
        wg_fence();
        #pragma unroll
        for (int s = 0; s < 5; s++) wg_ss80_tb(oc, desc2(al + s * 256, da0 >> 32), desc2(wl + s * 128, dw0 >> 32), (i | s) != 0);
        wg_commit();
        bad |= (lds32(ck + so) ^ epoch) | (lds32(ck + so + 8192) ^ epoch) | (lds32(ck2 + so) ^ epoch);
      };
      if (w4 == 0) {
        if (EN_SSM) mbar_wait(BAR(CONV_AT < 2 ? BR_KS : BR_Y + 1), 0);
        mbar_wait(BAR(BR_WO), 0);
        mbar_wait(BAR(BR_WO + 1), 0);
      }
      bar_sync(1, 256);
      if (tid == 0) TS(9);
      tile(0, SLOT(0));
      #pragma unroll 1
      for (int i = 1; i < 8; i++) {
        mbar_wait(BAR(BR_OFULL) + 8 * i, 0);
        tile(i, SLOT(i));
        wg_wait<1>();
        if (lane == 0) mbar_arrive(BAR(BR_OEMPTY - 1) + 8 * i);
      }
      #pragma unroll 1
      for (int n = 0; n < 56; n++) {
        const int i = n & 7;
        if (i == 0) {
          uint32_t any;
          asm volatile("{\n.reg .pred p;\nsetp.ne.u32 p, %1, 0;\nbarrier.red.or.pred p, 1, 256, p;\nselp.u32 %0, 1, 0, p;\n}" : "=r"(any) : "r"(bad & 1u) : "memory");
          if (!any) break;
          bad = 0;
          FIXCNT
        }
        wg_wait<0>();
        bar_sync(1, 256);
        if (tid == 0) { mbar_expect_tx(BAR(BR_RETRY), 20480); bulk_ld(sb + SLOT(5), &g_o[(r * 8 + CHUNK(i)) * 1280], 20480, BAR(BR_RETRY)); }
        mbar_wait(BAR(BR_RETRY), n & 1);
        tile(i, SLOT(5));
      }
      wg_wait<0>();
      pin<40>(oc);
    }
    if (tid == 0) TS(10);
    {
      const int row = w4 * 16 + (lane & 15);
      const uint32_t ob = sb + OFF_BLK + 3 * BLK + wg * 10240;
      #pragma unroll
      for (int j = 0; j < 8; j += 2)
        stsm4(ob + row * 128 + (((j + (lane >> 4)) ^ (row & 7)) << 4), pack2(oc[4 * j], oc[4 * j + 1]), pack2(oc[4 * j + 2], oc[4 * j + 3]),
              pack2(oc[4 * j + 4], oc[4 * j + 5]), pack2(oc[4 * j + 6], oc[4 * j + 7]));
      stsm4(ob + 8192 + row * 32 + (lane >> 4) * 16, pack2(oc[32], oc[33]), pack2(oc[34], oc[35]), pack2(oc[36], oc[37]), pack2(oc[38], oc[39]));
      fence_async();
      bar_sync(2 + wg, 128);
      if (w4 == 0 && elect_one()) {
        tma2d_st(&prm.m[M_O64], ob, 640 + c * 64, r * 128 + wg * 64);
        tma2d_st(&prm.m[M_O16], ob + 8192, 1152 + c * 16, r * 128 + wg * 64);
        bulk_commit(); bulk_wait0_read();
        if (wg == 0) { TS(11); DUMP(0, 20); }
      }
    }
    }
  } else {
    const int g = lane >> 2, tq = lane & 3, t7 = tid & 127;
    uint32_t raw[5][4], pd;
    {
      const int ch = c * 80 + r * 5;
      #pragma unroll
      for (int e = 0; e < 4; e++) {
        const __nv_bfloat16* pp = prm.par[e] + ch * 128 + t7;
        #pragma unroll
        for (int q = 0; q < 5; q++) asm volatile("ld.global.nc.u16 %0, [%1];" : "=r"(raw[q][e]) : "l"(pp + q * 128));
      }
      asm volatile("ld.global.nc.u16 %0, [%1];" : "=r"(pd) : "l"(((lane & 8) ? prm.dskip : prm.logdt) + ch + min(lane & 7, 4)));
    }
    asm volatile("bar.arrive 0, 512;" ::: "memory");
    if (EN_SSM) {
    {
      #pragma unroll 1
      for (int k = 0; k < 4; k++) {
        const uint32_t z = sb + OFF_BLK + k * BLK + t7 * 16;
        sts128(z + B_TBL, 0, 0, 0, 0); sts128(z + B_TBL + 2048, 0, 0, 0, 0);
      }
      sts128(sb + OFF_BLK + (t7 < 64 ? (t7 >> 4) * BLK - 256 + (t7 & 15) * 16 : 4 * BLK - 2048 + t7 * 16), 0, 0, 0, 0);
      const uint32_t ea = sb + OFF_BLK + (2 + (w4 & 1)) * BLK + (lane >> 4) * 7168 + ((lane >> 3) & 1) * 256 + (lane & 7) * 16 + (w4 >> 1) * 2048;
      constexpr uint64_t dE = mkdesc(SB0 + OFF_BLK + 2 * BLK, 128, 512, 0);
      const uint32_t xa = sb + OFF_BLK + 18560 + t7 * 8, xr_ = sb + OFF_BLK + 18560 + (t7 ^ 64) * 8;
      uint32_t pr[5][2];
      #pragma unroll
      for (int q = 0; q < 5; q++) {
        #pragma unroll
        for (int e = 0; e < 2; e++) pr[q][e] = raw[q][2 * e] | (raw[q][2 * e + 1] << 16);
        const uint32_t m = __reduce_max_sync(0xffffffff, max(raw[q][2] & 0x7fffu, raw[q][3] & 0x7fffu));
        if (lane == 0) sts32(sb + OFF_EPOCH + 64 + q * 16 + w4 * 4, m);
      }
      bar_sync(4, 128);
      if (t7 == 0) TS(40);
      const int j = (w4 & 1) * 16 + (w4 >> 1) * 8 + g, i2 = tq < 2 ? 64 * tq + j : 32 * (tq - 2) + j;
      const uint32_t e2 = B_TBL + 4 * (tq < 2 ? T_F3 + (((i2 - 1) & 1) ? 80 : 0) + ((i2 - 1) >> 1) + 16 : T_F2 + (i2 & 1) * 96 + (i2 >> 1));
      const uint32_t e1 = tq < 2 ? (i2 ? e2 - 64 : B_TBL + 4 * (T_F2 + 175)) : B_TBL + 4 * (i2 ? T_F2 + ((2 * i2 - 1) & 3) * 48 + ((2 * i2 - 1) >> 2) : 16 + 511);
      const uint32_t e0 = B_TBL + (16 + 8 * j + 2 * tq) * 4;
      #pragma unroll 1
      for (int it = 0; it < 5; it++) {
        const int k = it;
        const uint32_t blk = sb + OFF_BLK + k * BLK;
        float fac;
        {
          const int q = it;
          if (it == 4) {
            mbar_wait(BAR(BR_UOUT), 0);
            sts128(sb + OFF_UT + B_TBL + t7 * 16, 0, 0, 0, 0); sts128(sb + OFF_UT + B_TBL + 2048 + t7 * 16, 0, 0, 0, 0);
          }
          const uint32_t ga = ea + 4096 - (w4 >> 1) * 512;
#define PUT4(i, a, b, c_, d) sts128(((i) < 8 ? ea + ((i) >> 1) * 512 : ga + (((i) - 8) >> 1) * 512) + ((i) & 1) * 128, a, b, c_, d)
          const uint32_t pa0 = pr[0][0], pc0 = pr[0][1];
          const float dt = bf_round(expf(bf_lo(__shfl_sync(0xffffffff, pd, q))));
          #pragma unroll
          for (int e = 0; e < 2; e++) { pr[0][e] = pr[1][e]; pr[1][e] = pr[2][e]; pr[2][e] = pr[3][e]; pr[3][e] = pr[4][e]; }
          uint32_t mm[4];
          lds128(mm, sb + OFF_EPOCH + 64 + q * 16);
          const uint32_t ex = min(max(max(max(mm[0], mm[1]), max(mm[2], mm[3])) >> 7, 1u), 253u);
          const float sc = __uint_as_float((254u - ex) << 23);
          fac = 2.f * dt * __uint_as_float(ex << 23);
          const float lr = -bf_round(expf(bf_lo(pa0))) * dt * 1.44269504089f;
          const float tn = bf_hi(pa0) * dt * 0.15915494309f;
          float z1r, z1i, z2r, z2i, z4r, z4i, xr[8], xi[8], gr[8], gi[8], wr[9], wi[9];
          cexp_t(lr, -tn, z1r, z1i);
          cexp_t(lr * 8.f, tn * 8.f, xr[1], xi[1]);
          cexp_t(lr * 64.f, tn * 64.f, wr[0], wi[0]);
          xr[0] = 1.f; xi[0] = 0.f;
          cmul(xr[1], xi[1], xr[1], xi[1], xr[2], xi[2]); cmul(xr[2], xi[2], xr[1], xi[1], xr[3], xi[3]);
          cmul(xr[2], xi[2], xr[2], xi[2], xr[4], xi[4]);
          #pragma unroll
          for (int b = 1; b < 4; b++) cmul(xr[4], xi[4], xr[b], xi[b], xr[4 + b], xi[4 + b]);
          cmul(wr[0], wi[0], wr[0], wi[0], wr[1], wi[1]); cmul(wr[1], wi[1], wr[0], wi[0], wr[2], wi[2]);
          cmul(wr[1], wi[1], wr[1], wi[1], wr[3], wi[3]); cmul(wr[3], wi[3], wr[3], wi[3], wr[4], wi[4]);
          cmul(wr[4], wi[4], wr[3], wi[3], wr[5], wi[5]); cmul(wr[4], wi[4], wr[4], wi[4], wr[6], wi[6]);
          cmul(wr[6], wi[6], wr[4], wi[4], wr[7], wi[7]); cmul(wr[6], wi[6], wr[6], wi[6], wr[8], wi[8]);
          uint32_t R[4], I[4], PR[4], PI[4];
          #pragma unroll
          for (int b = 0; b < 4; b++) { R[b] = packh(xr[2 * b], xr[2 * b + 1]); I[b] = packh(xi[2 * b], xi[2 * b + 1]); }
          PUT4(0, R[0], R[1], R[2], R[3]); PUT4(1, I[0], I[1], I[2], I[3]);
          #pragma unroll
          for (int i = 0; i < 3; i++) {
            const uint32_t z = packh(wr[i], wi[i]);
            #pragma unroll
            for (int b = 0; b < 4; b++) hcm2(R[b], I[b], z, PR[b], PI[b]);
            PUT4(2 * i + 2, PR[0], PR[1], PR[2], PR[3]); PUT4(2 * i + 3, PI[0], PI[1], PI[2], PI[3]);
          }
          gr[0] = bf_lo(pc0) * sc; gi[0] = -bf_hi(pc0) * sc;
          cmul(z1r, z1i, z1r, z1i, z2r, z2i); cmul(z2r, z2i, z2r, z2i, z4r, z4i);
          cmul(gr[0], gi[0], z1r, z1i, gr[1], gi[1]);
          cmul(gr[0], gi[0], z2r, z2i, gr[2], gi[2]); cmul(gr[1], gi[1], z2r, z2i, gr[3], gi[3]);
          #pragma unroll
          for (int b = 0; b < 4; b++) cmul(gr[b], gi[b], z4r, z4i, gr[4 + b], gi[4 + b]);
          PUT4(8, packh(gr[0], gr[1]), packh(gr[2], gr[3]), packh(gr[4], gr[5]), packh(gr[6], gr[7]));
          PUT4(9, packh(gi[0], gi[1]), packh(gi[2], gi[3]), packh(gi[4], gi[5]), packh(gi[6], gi[7]));
          {
            const uint32_t z = packh(wr[3], -wi[3]), a4r = packh(gr[0], gr[4]), a4i = packh(gi[0], gi[4]);
            hcm2(packh(gr[0], gr[2]), packh(gi[0], gi[2]), z, PR[0], PI[0]);
            hcm2(packh(gr[4], gr[6]), packh(gi[4], gi[6]), z, PR[1], PI[1]);
            hcm2(a4r, a4i, packh(wr[4], -wi[4]), PR[2], PI[2]);
            hcm2(a4r, a4i, packh(wr[5], -wi[5]), PR[3], PI[3]);
            PUT4(10, PR[0], PR[1], PR[2], PR[3]); PUT4(11, PI[0], PI[1], PI[2], PI[3]);
            float hr, hi_;
            cmul(gr[0], gi[0], wr[3], -wi[3], hr, hi_);
            const uint32_t cr = packh(gr[0], hr), ci = packh(gi[0], hi_);
            #pragma unroll
            for (int i = 0; i < 3; i++) hcm2(cr, ci, packh(wr[6 + i], -wi[6 + i]), PR[i], PI[i]);
            PUT4(12, PR[0], PR[1], PR[2], 0u); PUT4(13, PI[0], PI[1], PI[2], 0u);
          }
          fence_async();
          bar_sync(4, 128);
        }
        float ka[24]; zero<24>(ka);
        wg_fence();
        #pragma unroll
        for (int s = 0; s < 8; s++) {
          const uint64_t d = dE + (s >> 2) * (BLK >> 4) + ((s >> 1) & 1) * 448 + (s & 1) * 16;
          wg_ss48_tt_h(ka, d, d + 256, s != 0);
        }
        wg_commit();
        const float dsk = bf_lo(__shfl_sync(0xffffffff, pd, 8 + it));
        wg_wait<0>();
        pin<24>(ka);
        float kk[6];
        const bool up = w4 >= 2;
        #pragma unroll
        for (int n = 0; n < 3; n++) {
          sts64f(xa + n * BLK, up ? ka[12 + 4 * n] : ka[4 * n + 2], up ? ka[13 + 4 * n] : ka[4 * n + 3]);
          kk[2 * n] = up ? ka[14 + 4 * n] : ka[4 * n]; kk[2 * n + 1] = up ? ka[15 + 4 * n] : ka[4 * n + 1];
        }
        if (it) bar_sync(4, 128); else bar_sync(8, 160);
          if (it == 4 && w4 == 0) {
            mbar_wait(BAR(BR_U), 0);
            if (elect_one()) {
              mbar_expect_tx(BAR(BR_U2), 8192);
              bulk_ld(blk - 2 * BLK, g_uy + (c * 80 + r * 5 + 2) * 2048, 4096, BAR(BR_U2)); bulk_ld(blk - BLK, g_uy + (c * 80 + r * 5 + 3) * 2048, 4096, BAR(BR_U2));
            }
            __syncwarp();
          }
        #pragma unroll
        for (int n = 0; n < 3; n++) {
          uint32_t o[2]; lds64(o, xr_ + n * BLK);
          kk[2 * n] = (kk[2 * n] + __uint_as_float(o[0])) * fac; kk[2 * n + 1] = (kk[2 * n + 1] + __uint_as_float(o[1])) * fac;
        }
        if (t7 == 0) kk[0] += dsk;
        {
          const uint32_t v = pack2(kk[1], kk[0]), vh = v >> 16;
          const uint32_t u = pack2(kk[2], kk[3]), w = pack2(kk[4], kk[5]), uu = pack2(kk[2], kk[2]), us = pack2(kk[3], kk[2]);
          const uint32_t x = tq < 2 ? w : u, xh = x >> 16;
          sts32(blk + e0 + 4, v); sts16(blk + e0, vh); sts16(blk + e0 + 10, v);
          sts16(blk + e1, x); sts16(blk + e1 + 6, x); sts16(blk + e2, xh); sts16(blk + e2 + 6, xh);
          if (tq < 2) {
            const uint32_t pb = blk + e0 + 1024 + 8 * tq;
            sts32(pb + 4, uu); sts32(pb + 8, us); sts16(pb + 14, us);
            if (i2) { sts16(pb - 4, u); sts32(pb, uu); }
          }
          if (i2 == 0) {
            const uint32_t tb = blk + B_TBL;
            if (tq == 0) { sts16(tb + (16 + 256) * 4, u); sts16(tb + (T_S + 3) * 4, w); sts32(tb + (T_S + 4) * 4, pack2(kk[4], kk[4])); sts16(tb + (T_S + 5) * 4 + 2, w); }
            else { sts32(tb + 528 * 4, uu); sts32(tb + 529 * 4, uu); sts32(tb + 530 * 4, uu); sts16(tb + 531 * 4 + 2, u); sts16(tb + (T_F3 + 80 + 63) * 4, w); }
          }
        }
        if (t7 == 0) TS(49 + it);
      }
    }
    asm volatile("setmaxnreg.inc.sync.aligned.u32 136;");
    if (t7 == 0) TS(41);
    mbar_wait(BAR(BR_U), 0);
    bar_sync(4, 128);
    if (EN_ATT) mbar_wait(BAR(BR_GEMM), 0);
    if (t7 == 0) TS(42);
    mbar_wait(BAR(BR_EPOCH), 0);
    const uint32_t ytag = (lds32(sb + OFF_EPOCH) & 1u) * 0x10001u, ym = lane < 4 ? 0x10001u : 0u;
    const int kl0 = 2 * (lane & 7) + ((lane >> 3) & 1), ih = (lane >> 3) & 1;
    {
      const int k = w4;
      if (k & 2) mbar_wait(BAR(BR_U2), 0);
      const uint32_t blk = sb + OFF_BLK + k * BLK, tb = blk + B_TBL + (uint32_t)((g - 2 * tq) * 4);
      float acc[16][4];
      zero<64>(&acc[0][0]);
      const int kl = 16 * (lane >> 4) + kl0;
      {
        auto ubase = [&](int sh) { const int q = kl - 2 * sh; return blk + (uint32_t)((q * 16) ^ ((q * 2) & 0x10)); };
#define LDQ(A, sh) _Pragma("unroll") for (int m = 0; m < 4; m++) load_quad(A[m], tb + (16 + 16 * (sh) + 128 * m) * 4);
#define LDB(B, ub, h) _Pragma("unroll") for (int p = 0; p < 4; p++) ldsm4(B[p], (ub) + (4 * (h) + p) * 512);
#define MLO(A, B) _Pragma("unroll") for (int m = 0; m < 4; m++) _Pragma("unroll") for (int cc = 0; cc < 8; cc++) mma16816(acc[cc + m], A[m], &B[cc >> 1][(cc & 1) * 2]);
#define MHI(A, B) _Pragma("unroll") for (int m = 0; m < 4; m++) _Pragma("unroll") for (int cc = 0; cc < 8 - m; cc++) mma16816(acc[8 + cc + m], A[m], &B[cc >> 1][(cc & 1) * 2]);
        int p_ = 0;
        uint32_t A[4][4], A2[4][4], Bl[4][4], Bh[4][4];
        uint32_t ub = ubase(p_ + 4);
        LDQ(A, p_ + 4) LDB(Bl, ub, 0)
        #pragma unroll 1
        for (; p_ < 4; p_++) {
          LDB(Bh, ub, 1)
          MLO(A, Bl)
          ub = ubase(p_);
          LDQ(A2, p_) LDB(Bl, ub, 0)
          MHI(A, Bh)
          LDB(Bh, ub, 1)
          load_quad(A[0], tb + (16 + 512 + 16 * (p_ & 1)) * 4); load_quad(A[1], tb + (T_S + 16 * (p_ & 1)) * 4);
          MLO(A2, Bl)
          if (p_ < 2) {
            #pragma unroll
            for (int cc = 0; cc < 8; cc++) mma16816(acc[cc + 4], A[0], &Bl[cc >> 1][(cc & 1) * 2]);
            #pragma unroll
            for (int cc = 0; cc < 4; cc++) mma16816(acc[cc + 12], A[0], &Bh[cc >> 1][(cc & 1) * 2]);
            #pragma unroll
            for (int cc = 0; cc < 8; cc++) mma16816(acc[cc + 8], A[1], &Bl[cc >> 1][(cc & 1) * 2]);
          }
          const int pn = ((p_ + 1) & 3) + 4;
          ub = ubase(pn);
          LDQ(A, pn) LDB(Bl, ub, 0)
          MHI(A2, Bh)
        }
      }
      if (t7 == 0) TS(60);
      mbar_wait(BAR(BR_DRDY + 1), 0);
      {
        const uint32_t dl = blk + B_D + (uint32_t)(((lane >> 4) * 8 + (lane & 7)) * 16);
        const uint32_t d0_ = dl + ih * 1552, d8_ = dl + (ih ? 0 : 1536), d3_ = dl + B_D7 + ih * 1024;
        auto cls2 = [&](uint32_t da, uint32_t ta) {
          uint32_t B[6][2], A[6][4];
          #pragma unroll
          for (int e = 0; e < 6; e++) { B[e][0] = lds32v(ta + (e + 4) * 32); B[e][1] = lds32v(ta + (e + 3) * 32); }
          #pragma unroll
          for (int kk = 0; kk < 6; kk++) ldsm4t(A[kk], da + kk * 256);
          #pragma unroll
          for (int e = 0; e < 6; e++)
            #pragma unroll
            for (int kk = 0; kk < 6; kk++) if (2 * kk + e + 4 < 16) mma16816(acc[2 * kk + e + 4], A[kk], B[e]);
        };
        auto cls3 = [&](uint32_t da, uint32_t ta) {
          uint32_t B[8][2], A[4][4];
          #pragma unroll
          for (int e = 0; e < 8; e++) { B[e][0] = lds32v(ta + (e + 8) * 32); B[e][1] = lds32v(ta + (e + 7) * 32); }
          #pragma unroll
          for (int kk = 0; kk < 4; kk++) ldsm4t(A[kk], da + kk * 256);
          #pragma unroll
          for (int kk = 0; kk < 4; kk++)
            #pragma unroll
            for (int e = 0; e < 8; e++) if (2 * kk + e + 8 < 16) mma16816(acc[2 * kk + e + 8], A[kk], B[e]);
        };
        #pragma unroll 1
        for (int a = 0; a < 2; a++) {
          cls2(d0_ + a * B_D5, tb + (T_F2 + 48 * a - 32) * 4);
          cls2(d8_ + a * B_D5, tb + (T_F2 + 48 * a + 64) * 4);
          cls3(d3_ + a * 2048, tb + (T_F3 + 80 * a - 64) * 4);
        }
      }
      if (t7 == 0) TS(61);
      const uint32_t ya = blk + (uint32_t)((kl * 16) ^ ((kl * 2) & 0x10));
#define YTAG(v) (((v) & ~ym) | (ytag & ym))
#define STY(p) stsm4t(ya + (p) * 512, YTAG(pack2(acc[2 * (p)][0], acc[2 * (p)][1])), pack2(acc[2 * (p)][2], acc[2 * (p)][3]), \
                      YTAG(pack2(acc[2 * (p) + 1][0], acc[2 * (p) + 1][1])), pack2(acc[2 * (p) + 1][2], acc[2 * (p) + 1][3]))
      __syncwarp();
      #pragma unroll
      for (int p = 0; p < 8; p++) STY(p);
      fence_async();
      __syncwarp();
      if (lane == 0) mbar_arrive(BAR(BR_Y));
      if (t7 == 0) TS(62);
    }
    {
      const uint32_t blk = sb + OFF_BLK + 4 * BLK, tb = blk + B_TBL + (uint32_t)((g - 2 * tq) * 4);
      const int kl = 16 * ((lane >> 4) ? 7 - w4 : w4) + kl0;
      float acc[8][4];
      zero<32>(&acc[0][0]);
      #pragma unroll 2
      for (int s = 0; s < 8; s++) {
        const int q = kl - 2 * s;
        const uint32_t ub = blk + (uint32_t)((q * 16) ^ ((q * 2) & 0x10));
        #pragma unroll
        for (int m = 0; m < 4; m++) {
          uint32_t A[4], B[8];
          load_quad(A, tb + (16 + 16 * s + 128 * m) * 4);
          ldsm4(B, ub - 256 * m); ldsm4(B + 4, ub + 2048 - 256 * m);
          #pragma unroll
          for (int e = 0; e < 4; e++) mma16816(acc[4 * (m & 1) + e], A, &B[2 * e]);
        }
      }
      #pragma unroll
      for (int s = 0; s < 2; s++) {
        const int q = kl - 2 * s;
        const uint32_t ub = blk + (uint32_t)((q * 16) ^ ((q * 2) & 0x10));
        uint32_t A[4], E[4], B[12];
        load_quad(A, tb + (16 + 512 + 16 * s) * 4); load_quad(E, tb + (T_S + 16 * s) * 4);
        ldsm4(B, (lane >> 4) ? ub - 1024 : ub); ldsm4(B + 4, ub + 1024); ldsm4(B + 8, ub);
        mma16816(acc[1], A, &B[2]); mma16816(acc[2], A, &B[4]); mma16816(acc[3], A, &B[6]);
        mma16816(acc[6], E, &B[8]); mma16816(acc[7], E, &B[10]);
      }
      if (t7 == 0) TS(57);
      const uint32_t dl = blk + B_D + (uint32_t)(((lane >> 4) * 8 + (lane & 7)) * 16);
      const int od = w4 & 1, k1 = ((7 - w4) >> 1) - 2, k2 = ((8 + w4) >> 1) - 2;
      #pragma unroll 2
      for (int a = 0; a < 4; a++) {
        const uint32_t da = dl + (a & 1) * B_D5 + ((a & 2) ? (ih ? 0 : 1536) : ih * 1552), ta = tb + (T_F2 + 48 * a) * 4;
        #pragma unroll
        for (int i = 0; i < 3; i++) {
          uint32_t A[12], B[4];
          B[0] = lds32v(ta + (2 * i + 1 - od) * 32); B[1] = lds32v(ta + (2 * i - od) * 32);
          B[2] = lds32v(ta + (2 * i + od) * 32); B[3] = lds32v(ta + (2 * i + od - 1) * 32);
          ldsm4t(A + 4, da + (k2 - i) * 256); ldsm4t(A + 8, da + (k1 + 4 - i) * 256);
          if (i < 2) { ldsm4t(A, k1 >= i ? da + (k1 - i) * 256 : blk - 256); mma16816(acc[1 + 4 * (i & 1)], A, B); }
          mma16816(acc[2 + 4 * (i & 1)], A + 4, B + 2); mma16816(acc[3 + 4 * (i & 1)], A + 8, B);
        }
      }
      #pragma unroll
      for (int b = 0; b < 2; b++) {
        const uint32_t da = dl + B_D7 + b * 2048 + ih * 1024, ta = tb + (T_F3 + 80 * b) * 4, tz = tb + 546 * 4;
        #pragma unroll
        for (int kk = 0; kk < 4; kk++) {
          uint32_t A[4], B[4];
          ldsm4t(A, da + kk * 256);
          const uint32_t t3 = 7 - w4 >= 2 * kk ? ta + (7 - w4 - 2 * kk) * 32 : tz;
          B[0] = lds32v(t3); B[1] = lds32v(t3 - 32);
          mma16816(acc[3 + 4 * (kk & 1)], A, B);
          if (kk < 2) {
            const uint32_t t2 = w4 >= 2 * kk ? ta + (w4 - 2 * kk) * 32 : tz;
            B[2] = lds32v(t2); B[3] = lds32v(t2 - 32);
            mma16816(acc[2 + 4 * (kk & 1)], A, B + 2);
          }
        }
      }
      if (t7 == 0) TS(58);
      bar_sync(4, 128);
      if (t7 == 0) mbar_arrive(BAR(BR_KS));
      const uint32_t ya = blk + (uint32_t)((kl * 16) ^ ((kl * 2) & 0x10));
      #pragma unroll
      for (int h = 0; h < 2; h++)
        stsm4t(ya + h * 2048, YTAG(pack2(acc[2 * h][0] + acc[2 * h + 4][0], acc[2 * h][1] + acc[2 * h + 4][1])), pack2(acc[2 * h][2] + acc[2 * h + 4][2], acc[2 * h][3] + acc[2 * h + 4][3]),
               YTAG(pack2(acc[2 * h + 1][0] + acc[2 * h + 5][0], acc[2 * h + 1][1] + acc[2 * h + 5][1])), pack2(acc[2 * h + 1][2] + acc[2 * h + 5][2], acc[2 * h + 1][3] + acc[2 * h + 5][3]));
      fence_async();
      __syncwarp();
      if (lane == 0) mbar_arrive(BAR(BR_Y + 1));
      if (t7 == 0) TS(59);
    }
    if (t7 == 0) DUMP(40, 64);
    #pragma unroll 1
    for (int n = 0; n < 64; n++) if (!y_transpose(sb, w4, lane, ytag)) break;
    }
  }
}

typedef CUresult (*EncFn)(CUtensorMap*, CUtensorMapDataType, cuuint32_t, void*, const cuuint64_t*, const cuuint64_t*, const cuuint32_t*,
                          const cuuint32_t*, CUtensorMapInterleave, CUtensorMapSwizzle, CUtensorMapL2promotion, CUtensorMapFloatOOBfill);
static void mkmap(EncFn enc, CUtensorMap* m, const void* base, int rank, const cuuint64_t* dims, const cuuint64_t* strides, const cuuint32_t* box, CUtensorMapSwizzle swz) {
  cuuint32_t es[5] = {1, 1, 1, 1, 1};
  enc(m, CU_TENSOR_MAP_DATA_TYPE_BFLOAT16, rank, const_cast<void*>(base), dims, strides, box, es, CU_TENSOR_MAP_INTERLEAVE_NONE, swz,
      CU_TENSOR_MAP_L2_PROMOTION_L2_128B, CU_TENSOR_MAP_FLOAT_OOB_FILL_NONE);
}

extern "C" void kernel_launch(void* const* d_in, const int* in_sizes, int n_in, void* d_out, int out_size) {
  void* fn = nullptr; cudaDriverEntryPointQueryResult qr;
  cudaGetDriverEntryPoint("cuTensorMapEncodeTiled", &fn, cudaEnableDefault, &qr);
  EncFn enc = (EncFn)fn;
  void* uy = nullptr; cudaGetSymbolAddress(&uy, g_uy);
  const cuuint64_t dx[2] = {640, 2048}, sx[1] = {1280};
  const cuuint32_t bx[2] = {64, 128}, bu[2] = {80, 128};
  const cuuint64_t dw[3] = {640, 640, 3}, sw[2] = {3840, 1280};
  const cuuint32_t br[3] = {16, 32, 3};
  const cuuint64_t dwa[4] = {64, 640, 10, 3}, swa[3] = {3840, 128, 1280}, dwb[4] = {32, 640, 20, 3}, swb[3] = {3840, 64, 1280};
  const cuuint32_t bwa[4] = {64, 32, 1, 3}, bwb[4] = {32, 32, 2, 3};
  const cuuint64_t dwo[2] = {640, 640};
  const cuuint32_t bwo[2] = {64, 80}, bo64[2] = {64, 64}, bo16[2] = {16, 64};
  const cuuint64_t dsa[2] = {2048, 1280}, ssa[1] = {4096};
  const cuuint32_t bsa[2] = {64, 80};
  const cuuint64_t dout[2] = {1280, 2048}, sout[1] = {2560};
  Params prm;
  mkmap(enc, &prm.m[M_X], d_in[7], 2, dx, sx, bx, CU_TENSOR_MAP_SWIZZLE_128B);
  mkmap(enc, &prm.m[M_W128], d_in[8], 4, dwa, swa, bwa, CU_TENSOR_MAP_SWIZZLE_128B);
  mkmap(enc, &prm.m[M_W64], d_in[8], 4, dwb, swb, bwb, CU_TENSOR_MAP_SWIZZLE_64B);
  mkmap(enc, &prm.m[M_WR], d_in[8], 3, dw, sw, br, CU_TENSOR_MAP_SWIZZLE_32B);
  mkmap(enc, &prm.m[M_U], d_in[0], 2, dx, sx, bu, CU_TENSOR_MAP_SWIZZLE_NONE);
  mkmap(enc, &prm.m[M_WO], d_in[9], 2, dwo, sx, bwo, CU_TENSOR_MAP_SWIZZLE_128B);
  mkmap(enc, &prm.m[M_O64], d_out, 2, dout, sout, bo64, CU_TENSOR_MAP_SWIZZLE_128B);
  mkmap(enc, &prm.m[M_O16], d_out, 2, dout, sout, bo16, CU_TENSOR_MAP_SWIZZLE_NONE);
  mkmap(enc, &prm.m[M_SA], uy, 2, dsa, ssa, bsa, CU_TENSOR_MAP_SWIZZLE_128B);
  mkmap(enc, &prm.m[M_OUT], d_out, 2, dout, sout, bu, CU_TENSOR_MAP_SWIZZLE_NONE);
  prm.u = (const __nv_bfloat16*)d_in[0]; prm.wo = (const __nv_bfloat16*)d_in[9];
  for (int i = 0; i < 4; i++) prm.par[i] = (const __nv_bfloat16*)d_in[1 + i];
  prm.logdt = (const __nv_bfloat16*)d_in[5]; prm.dskip = (const __nv_bfloat16*)d_in[6];
  cudaFuncSetAttribute(fused_kernel, cudaFuncAttributeMaxDynamicSharedMemorySize, SMEM_BYTES);
  cudaLaunchConfig_t cfg = {};
  cfg.gridDim = dim3(128); cfg.blockDim = dim3(512); cfg.dynamicSmemBytes = SMEM_BYTES; cfg.stream = cudaStreamPerThread;
  cudaLaunchAttribute at[1];
  at[0].id = cudaLaunchAttributeClusterDimension; at[0].val.clusterDim.x = 2; at[0].val.clusterDim.y = 1; at[0].val.clusterDim.z = 1;
  cfg.attrs = at; cfg.numAttrs = 1;
  cudaLaunchKernelEx(&cfg, fused_kernel, prm);
}
```

```cpp
#include <cuda_runtime.h>
#include <cuda_bf16.h>
#include <cuda_fp16.h>
#include <cuda.h>
#include <stdint.h>

#define KST 2
#define UKB 4
#define UPF 0
#define CONV_AT 1
#define EN_ATT 1
#define EN_SSM 1

__device__ __align__(1024) __nv_bfloat16 g_uy[2 * 640 * 2048];
__device__ __align__(128) uint4 g_kvp[8 * 16 * 240];
__device__ __align__(128) uint4 g_o[128 * 1280];
__device__ __align__(128) unsigned g_flag[4 * 128 * 32];
__device__ unsigned g_epoch[128];
#define TS(i) do {} while (0)
#define DUMP(lo, hi) do {} while (0)
#define FIXCNT

constexpr uint32_t SB0 = 1024;
constexpr uint32_t W_SLOT = 15360, OFF_X = 76800;
constexpr uint32_t OFF_WOR = 81920, OFF_KVP = 10240, OFF_KVS = 71680, OFF_PK = 10240, OFF_V = 30720, OFF_EXTRA = 102400, OFF_KVB = OFF_EXTRA;
constexpr uint32_t OFF_BAR = 125952, OFF_BLK = 128000, BLK = 20480;
constexpr uint32_t B_D = 4096, B_D5 = 3088, B_D7 = 6176, B_D9 = 8224, B_TBL = 14400;
constexpr int T_S = 576, T_F2 = 624, T_F3 = 816;
constexpr uint32_t OFF_UT = OFF_BLK + 4 * BLK;
constexpr uint32_t SMEM_BYTES = OFF_BLK + 5 * BLK;
enum { BR_FULL = 0, BR_WO = 5, BR_PUB = 7, BR_KVP = 8, BR_U = 9, BR_SUM = 10, BR_GEMM = 11, BR_UIN = 12, BR_YIN = 13, BR_EPOCH = 14,
       BR_FREE = 15, BR_RETRY = 17, BR_UOUT = 18, BR_OFULL = 18, BR_KS = 26, BR_EMPTY = 31, BR_OEMPTY = 36, BR_Y = 43, BR_OSTG = 45,
       BR_DRDY = 46, BR_U2 = 48, BR_COUNT = 50 };
constexpr uint32_t OFF_EPOCH = OFF_BAR + 8 * BR_COUNT;
enum { M_X, M_W128, M_W64, M_WR, M_U, M_WO, M_O64, M_O16, M_SA, M_OUT, M_COUNT };

__device__ __forceinline__ long long clk64() { long long t; asm volatile("mov.u64 %0, %%clock64;" : "=l"(t) :: "memory"); return t; }
__device__ __forceinline__ uint32_t smem_u32(const void* p) { return (uint32_t)__cvta_generic_to_shared(p); }
__host__ __device__ constexpr uint64_t mkdesc(uint32_t addr, uint32_t lbo, uint32_t sbo, uint32_t swz) {
  return (uint64_t)((addr & 0x3FFFF) >> 4) | ((uint64_t)(lbo >> 4) << 16) | ((uint64_t)(sbo >> 4) << 32) | ((uint64_t)swz << 62);
}
__device__ __forceinline__ uint64_t desc2(uint32_t lo, uint32_t hi) { uint64_t d; asm("mov.b64 %0, {%1, %2};" : "=l"(d) : "r"(lo), "r"(hi)); return d; }
__device__ __forceinline__ void mbar_init(uint32_t bar, uint32_t cnt) { asm volatile("mbarrier.init.shared::cta.b64 [%0], %1;" :: "r"(bar), "r"(cnt) : "memory"); }
__device__ __forceinline__ void mbar_expect_tx(uint32_t bar, uint32_t bytes) { asm volatile("mbarrier.arrive.expect_tx.shared::cta.b64 _, [%0], %1;" :: "r"(bar), "r"(bytes) : "memory"); }
__device__ __forceinline__ void mbar_arrive(uint32_t bar) { asm volatile("mbarrier.arrive.shared::cta.b64 _, [%0];" :: "r"(bar) : "memory"); }
__device__ __forceinline__ void mbar_wait(uint32_t bar, uint32_t parity) {
  asm volatile("{\n.reg .pred p;\n.reg .u32 c;\nmov.u32 c, 0;\n"
    "WL:\nmbarrier.try_wait.parity.shared::cta.b64 p, [%0], %1;\n@p bra WD;\n"
    "add.u32 c, c, 1;\nsetp.lt.u32 p, c, 200000;\n@p bra WL;\nWD:\n}" :: "r"(bar), "r"(parity) : "memory");
}
__device__ __forceinline__ void poll_all(const unsigned* p, unsigned val) {
  asm volatile("{\n.reg .pred p;\n.reg .u32 c, v;\nmov.u32 c, 0;\n"
    "PL:\nld.relaxed.gpu.global.u32 v, [%0];\nsetp.eq.u32 p, v, %1;\nvote.sync.all.pred p, p, 0xffffffff;\n@p bra PD;\n"
    "add.u32 c, c, 1;\nsetp.lt.u32 p, c, 100000;\n@p bra PL;\nPD:\n}" :: "l"(p), "r"(val) : "memory");
}
__device__ __forceinline__ void poll_all_acq(const unsigned* p, unsigned val) {
  asm volatile("{\n.reg .pred p;\n.reg .u32 c, v;\nmov.u32 c, 0;\n"
    "PL:\nld.acquire.gpu.global.u32 v, [%0];\nsetp.eq.u32 p, v, %1;\nvote.sync.all.pred p, p, 0xffffffff;\n@p bra PD;\n"
    "nanosleep.u32 300;\nadd.u32 c, c, 1;\nsetp.lt.u32 p, c, 100000;\n@p bra PL;\nPD:\n}" :: "l"(p), "r"(val) : "memory");
}
__device__ __forceinline__ unsigned poll_bit(const unsigned* p, unsigned val, unsigned mask) {
  unsigned bal;
  asm volatile("{\n.reg .pred p;\n.reg .u32 c, v;\nmov.u32 c, 0;\n"
    "PL:\nld.relaxed.gpu.global.u32 v, [%1];\nsetp.eq.u32 p, v, %2;\nvote.sync.ballot.b32 %0, p, 0xffffffff;\n"
    "and.b32 v, %0, %3;\nsetp.ne.u32 p, v, 0;\n@p bra PD;\n"
    "add.u32 c, c, 1;\nsetp.lt.u32 p, c, 100000;\n@p bra PL;\nPD:\n}" : "=&r"(bal) : "l"(p), "r"(val), "r"(mask) : "memory");
  return bal;
}
__device__ __forceinline__ void fix128_w0(uint32_t* v, const void* p, uint32_t tag, uint32_t mask) {
  asm volatile("{\n.reg .pred p;\n.reg .u32 c, x;\n.reg .b128 t;\n.reg .b64 lo, hi;\nmov.u32 c, 0;\n"
    "FL:\nxor.b32 x, %0, %5;\nand.b32 x, x, %6;\nsetp.eq.u32 p, x, 0;\n@p bra FD;\n"
    "ld.relaxed.gpu.global.b128 t, [%4];\nmov.b128 {lo, hi}, t;\nmov.b64 {%0, %1}, lo;\nmov.b64 {%2, %3}, hi;\n"
    "add.u32 c, c, 1;\nsetp.lt.u32 p, c, 100000;\n@p bra FL;\nFD:\n}"
    : "+r"(v[0]), "+r"(v[1]), "+r"(v[2]), "+r"(v[3]) : "l"(p), "r"(tag), "r"(mask) : "memory");
}
__device__ __forceinline__ void fix128_w3(uint32_t* v, const void* p, uint32_t tag, uint32_t mask) {
  asm volatile("{\n.reg .pred p;\n.reg .u32 c, x;\n.reg .b128 t;\n.reg .b64 lo, hi;\nmov.u32 c, 0;\n"
    "FL:\nxor.b32 x, %3, %5;\nand.b32 x, x, %6;\nsetp.eq.u32 p, x, 0;\n@p bra FD;\n"
    "ld.relaxed.gpu.global.b128 t, [%4];\nmov.b128 {lo, hi}, t;\nmov.b64 {%0, %1}, lo;\nmov.b64 {%2, %3}, hi;\n"
    "add.u32 c, c, 1;\nsetp.lt.u32 p, c, 100000;\n@p bra FL;\nFD:\n}"
    : "+r"(v[0]), "+r"(v[1]), "+r"(v[2]), "+r"(v[3]) : "l"(p), "r"(tag), "r"(mask) : "memory");
}
__device__ __forceinline__ void fence_acq() { asm volatile("fence.acq_rel.gpu;" ::: "memory"); }
__device__ __forceinline__ bool elect_one() {
  uint32_t p; asm volatile("{\n.reg .pred P;\nelect.sync _|P, 0xffffffff;\nselp.u32 %0, 1, 0, P;\n}" : "=r"(p)); return p;
}
__device__ __forceinline__ void bar_sync(int id, int n) { asm volatile("bar.sync %0, %1;" :: "r"(id), "r"(n) : "memory"); }
__device__ __forceinline__ void fence_async() { asm volatile("fence.proxy.async.shared::cta;" ::: "memory"); }
__device__ __forceinline__ void fence_async_g() { asm volatile("fence.proxy.async.global;" ::: "memory"); }
__device__ __forceinline__ void tma2d(uint32_t dst, const CUtensorMap* m, uint32_t bar, int c0, int c1) {
  asm volatile("cp.async.bulk.tensor.2d.shared::cluster.global.mbarrier::complete_tx::bytes [%0], [%1, {%3, %4}], [%2];"
    :: "r"(dst), "l"(m), "r"(bar), "r"(c0), "r"(c1) : "memory");
}
__device__ __forceinline__ void tma3d(uint32_t dst, const CUtensorMap* m, uint32_t bar, int c0, int c1, int c2) {
  asm volatile("cp.async.bulk.tensor.3d.shared::cluster.global.mbarrier::complete_tx::bytes [%0], [%1, {%3, %4, %5}], [%2];"
    :: "r"(dst), "l"(m), "r"(bar), "r"(c0), "r"(c1), "r"(c2) : "memory");
}
__device__ __forceinline__ void tma4d(uint32_t dst, const CUtensorMap* m, uint32_t bar, int c0, int c1, int c2, int c3) {
  asm volatile("cp.async.bulk.tensor.4d.shared::cluster.global.mbarrier::complete_tx::bytes [%0], [%1, {%3, %4, %5, %6}], [%2];"
    :: "r"(dst), "l"(m), "r"(bar), "r"(c0), "r"(c1), "r"(c2), "r"(c3) : "memory");
}
__device__ __forceinline__ void tma2d_st(const CUtensorMap* m, uint32_t src, int c0, int c1) {
  asm volatile("cp.async.bulk.tensor.2d.global.shared::cta.bulk_group [%0, {%2, %3}], [%1];"
    :: "l"(m), "r"(src), "r"(c0), "r"(c1) : "memory");
}
__device__ __forceinline__ void bulk_ld(uint32_t dst, const void* src, uint32_t bytes, uint32_t bar) {
  asm volatile("cp.async.bulk.shared::cluster.global.mbarrier::complete_tx::bytes [%0], [%1], %2, [%3];"
    :: "r"(dst), "l"(src), "r"(bytes), "r"(bar) : "memory");
}
__device__ __forceinline__ void bulk_st(void* dst, uint32_t src, uint32_t bytes) {
  asm volatile("cp.async.bulk.global.shared::cta.bulk_group [%0], [%1], %2;" :: "l"(dst), "r"(src), "r"(bytes) : "memory");
}
__device__ __forceinline__ void bulk_commit() { asm volatile("cp.async.bulk.commit_group;" ::: "memory"); }
__device__ __forceinline__ void bulk_wait0() { asm volatile("cp.async.bulk.wait_group 0;" ::: "memory"); }
__device__ __forceinline__ void bulk_wait0_read() { asm volatile("cp.async.bulk.wait_group.read 0;" ::: "memory"); }
__device__ __forceinline__ unsigned ld_rlx(const unsigned* p) { unsigned v; asm volatile("ld.relaxed.gpu.global.u32 %0, [%1];" : "=r"(v) : "l"(p) : "memory"); return v; }
__device__ __forceinline__ unsigned ld_acq(const unsigned* p) { unsigned v; asm volatile("ld.acquire.gpu.global.u32 %0, [%1];" : "=r"(v) : "l"(p) : "memory"); return v; }
__device__ __forceinline__ void st_rlx(unsigned* p, unsigned v) { asm volatile("st.relaxed.gpu.global.u32 [%0], %1;" :: "l"(p), "r"(v) : "memory"); }
__device__ __forceinline__ void st_rel(unsigned* p, unsigned v) { asm volatile("st.release.gpu.global.u32 [%0], %1;" :: "l"(p), "r"(v) : "memory"); }
__device__ __forceinline__ void ld128_rlx(uint32_t* v, const void* p) {
  asm volatile("{\n.reg .b128 t;\n.reg .b64 lo, hi;\nld.relaxed.gpu.global.b128 t, [%4];\nmov.b128 {lo, hi}, t;\n"
    "mov.b64 {%0, %1}, lo;\nmov.b64 {%2, %3}, hi;\n}" : "=r"(v[0]), "=r"(v[1]), "=r"(v[2]), "=r"(v[3]) : "l"(p) : "memory");
}
__device__ __forceinline__ void st128_rlx(void* p, const uint32_t* v) {
  asm volatile("{\n.reg .b128 t;\n.reg .b64 lo, hi;\nmov.b64 lo, {%1, %2};\nmov.b64 hi, {%3, %4};\nmov.b128 t, {lo, hi};\n"
    "st.relaxed.gpu.global.b128 [%0], t;\n}" :: "l"(p), "r"(v[0]), "r"(v[1]), "r"(v[2]), "r"(v[3]) : "memory");
}
__device__ __forceinline__ uint32_t lds32(uint32_t a) { uint32_t v; asm volatile("ld.shared.u32 %0, [%1];" : "=r"(v) : "r"(a) : "memory"); return v; }
__device__ __forceinline__ uint32_t lds32v(uint32_t a) { uint32_t v; asm volatile("ld.volatile.shared.u32 %0, [%1];" : "=r"(v) : "r"(a) : "memory"); return v; }
__device__ __forceinline__ uint32_t cpa(uint32_t a, uint32_t one) { uint32_t v; asm volatile("mul.lo.u32 %0, %1, %2;" : "=r"(v) : "r"(a), "r"(one)); return v; }
__device__ __forceinline__ uint32_t cpb(uint32_t a, uint32_t zero) { uint32_t v; asm volatile("or.b32 %0, %1, %2;" : "=r"(v) : "r"(a), "r"(zero)); return v; }
__device__ __forceinline__ uint32_t lds16(uint32_t a) { uint16_t v; asm volatile("ld.shared.u16 %0, [%1];" : "=h"(v) : "r"(a) : "memory"); return v; }
__device__ __forceinline__ float ldsf(uint32_t a) { float v; asm volatile("ld.shared.f32 %0, [%1];" : "=f"(v) : "r"(a) : "memory"); return v; }
__device__ __forceinline__ void lds128(uint32_t* v, uint32_t a) { asm volatile("ld.shared.v4.u32 {%0,%1,%2,%3}, [%4];" : "=r"(v[0]), "=r"(v[1]), "=r"(v[2]), "=r"(v[3]) : "r"(a) : "memory"); }
__device__ __forceinline__ void sts32(uint32_t a, uint32_t v) { asm volatile("st.shared.u32 [%0], %1;" :: "r"(a), "r"(v) : "memory"); }
__device__ __forceinline__ void sts16(uint32_t a, uint32_t v) { asm volatile("st.shared.u16 [%0], %1;" :: "r"(a), "h"((uint16_t)v) : "memory"); }
__device__ __forceinline__ void sts64f(uint32_t a, float x, float y) { asm volatile("st.shared.v2.f32 [%0], {%1,%2};" :: "r"(a), "f"(x), "f"(y) : "memory"); }
__device__ __forceinline__ void sts128(uint32_t a, uint32_t x, uint32_t y, uint32_t z, uint32_t w) { asm volatile("st.shared.v4.u32 [%0], {%1,%2,%3,%4};" :: "r"(a), "r"(x), "r"(y), "r"(z), "r"(w) : "memory"); }
__device__ __forceinline__ void stsm4(uint32_t a, uint32_t r0, uint32_t r1, uint32_t r2, uint32_t r3) {
  asm volatile("stmatrix.sync.aligned.m8n8.x4.shared.b16 [%0], {%1,%2,%3,%4};" :: "r"(a), "r"(r0), "r"(r1), "r"(r2), "r"(r3) : "memory");
}
__device__ __forceinline__ void stsm4t(uint32_t a, uint32_t r0, uint32_t r1, uint32_t r2, uint32_t r3) {
  asm volatile("stmatrix.sync.aligned.m8n8.x4.trans.shared.b16 [%0], {%1,%2,%3,%4};" :: "r"(a), "r"(r0), "r"(r1), "r"(r2), "r"(r3) : "memory");
}
__device__ __forceinline__ void ldsm4t(uint32_t* r, uint32_t a) {
  asm volatile("ldmatrix.sync.aligned.m8n8.x4.trans.shared.b16 {%0,%1,%2,%3}, [%4];" : "=r"(r[0]), "=r"(r[1]), "=r"(r[2]), "=r"(r[3]) : "r"(a) : "memory");
}
__device__ __forceinline__ void ldsm4(uint32_t* r, uint32_t a) {
  asm volatile("ldmatrix.sync.aligned.m8n8.x4.shared.b16 {%0,%1,%2,%3}, [%4];" : "=r"(r[0]), "=r"(r[1]), "=r"(r[2]), "=r"(r[3]) : "r"(a) : "memory");
}
__device__ __forceinline__ void mma16816(float* d, const uint32_t* a, const uint32_t* b) {
  asm volatile("mma.sync.aligned.m16n8k16.row.col.f32.bf16.bf16.f32 {%0,%1,%2,%3}, {%4,%5,%6,%7}, {%8,%9}, {%0,%1,%2,%3};"
    : "+f"(d[0]), "+f"(d[1]), "+f"(d[2]), "+f"(d[3]) : "r"(a[0]), "r"(a[1]), "r"(a[2]), "r"(a[3]), "r"(b[0]), "r"(b[1]));
}
__device__ __forceinline__ uint32_t pack2(float lo, float hi) { uint32_t r; asm("cvt.rn.bf16x2.f32 %0, %1, %2;" : "=r"(r) : "f"(hi), "f"(lo)); return r; }
__device__ __forceinline__ uint32_t packh(float lo, float hi) { uint32_t r; asm("cvt.rn.f16x2.f32 %0, %1, %2;" : "=r"(r) : "f"(hi), "f"(lo)); return r; }
__device__ __forceinline__ uint32_t hcmul(uint32_t x, uint32_t zp, uint32_t zq) {
  const __half2 xx = *reinterpret_cast<__half2*>(&x);
  const __half2 r = __hfma2(__high2half2(xx), *reinterpret_cast<__half2*>(&zq), __hmul2(__low2half2(xx), *reinterpret_cast<__half2*>(&zp)));
  return *reinterpret_cast<const uint32_t*>(&r);
}
__device__ __forceinline__ void hcm2(uint32_t xr, uint32_t xi, uint32_t z, uint32_t& pr, uint32_t& pi) {
  const __half2 a = *reinterpret_cast<__half2*>(&xr), b = *reinterpret_cast<__half2*>(&xi), zz = *reinterpret_cast<__half2*>(&z);
  const __half2 re = __hfma2(__hneg2(b), __high2half2(zz), __hmul2(a, __low2half2(zz)));
  const __half2 im = __hfma2(a, __high2half2(zz), __hmul2(b, __low2half2(zz)));
  pr = *reinterpret_cast<const uint32_t*>(&re); pi = *reinterpret_cast<const uint32_t*>(&im);
}
__device__ __forceinline__ void sts64(uint32_t a, uint32_t x, uint32_t y) { asm volatile("st.shared.v2.u32 [%0], {%1,%2};" :: "r"(a), "r"(x), "r"(y) : "memory"); }
__device__ __forceinline__ void lds64(uint32_t* v, uint32_t a) { asm volatile("ld.shared.v2.u32 {%0,%1}, [%2];" : "=r"(v[0]), "=r"(v[1]) : "r"(a) : "memory"); }
__device__ __forceinline__ float bf_lo(uint32_t v) { return __uint_as_float(v << 16); }
__device__ __forceinline__ float bf_hi(uint32_t v) { return __uint_as_float(v & 0xffff0000u); }
__device__ __forceinline__ float bf_round(float x) { return bf_lo(pack2(x, 0.f)); }
__device__ __forceinline__ float ex2(float x) { float r; asm("ex2.approx.ftz.f32 %0, %1;" : "=f"(r) : "f"(x)); return r; }
__device__ __forceinline__ float phi(float t, float l2e = 1.44269504089f) {
  float e = ex2(t * l2e) + 1e-6f;
  asm("{\n.reg .pred p;\nsetp.gt.f32 p, %1, 0f00000000;\n@p add.f32 %0, %1, 0f3F800008;\n}" : "+f"(e) : "f"(t));
  return e;
}
__device__ __forceinline__ void wg_fence() { asm volatile("wgmma.fence.sync.aligned;" ::: "memory"); }
__device__ __forceinline__ void wg_commit() { asm volatile("wgmma.commit_group.sync.aligned;" ::: "memory"); }
template <int N> __device__ __forceinline__ void wg_wait() { asm volatile("wgmma.wait_group.sync.aligned %0;" :: "n"(N) : "memory"); }
template <int N> __device__ __forceinline__ void pin(float* a) {
  #pragma unroll
  for (int i = 0; i < N; i++) asm volatile("" : "+f"(a[i]) :: "memory");
}
__device__ __forceinline__ int rtid() { int t; asm volatile("mov.u32 %0, %%tid.x;" : "=r"(t)); return t; }
__device__ __forceinline__ int opaque(int v) { asm volatile("" : "+r"(v)); return v; }
template <int N> __device__ __forceinline__ void zero(float* a) {
  #pragma unroll
  for (int i = 0; i < N; i++) asm volatile("mov.b32 %0, 0;" : "=f"(a[i]));
}
template <int N> __device__ __forceinline__ void pinu(uint32_t* a) {
  #pragma unroll
  for (int i = 0; i < N; i++) asm volatile("" : "+r"(a[i]) :: "memory");
}
__device__ __forceinline__ void cexp_t(float lg2mag, float turns, float& re, float& im) {
  float m = ex2(lg2mag);
  float fr = (turns - __fadd_rn(__fadd_rn(turns, 12582912.f), -12582912.f)) * 6.283185307f;
  re = m * __cosf(fr); im = m * __sinf(fr);
}
__device__ __forceinline__ void cmul(float ar, float ai, float br, float bi, float& cr, float& ci) {
  cr = fmaf(ar, br, -ai * bi); ci = fmaf(ar, bi, ai * br);
}

__device__ __forceinline__ void wg_ss48_tt(float* d, uint64_t da, uint64_t db, int scale_d) {
  asm volatile("{\n.reg .pred p;\nsetp.ne.b32 p, %26, 0;\n"
    "wgmma.mma_async.sync.aligned.m64n48k16.f32.bf16.bf16 "
    "{%0, %1, %2, %3, %4, %5, %6, %7, %8, %9, %10, %11, %12, %13, %14, %15, %16, %17, %18, %19, %20, %21, %22, %23}, %24, %25, p, 1, 1, 1, 1;\n}\n"
    : "+f"(d[0]), "+f"(d[1]), "+f"(d[2]), "+f"(d[3]), "+f"(d[4]), "+f"(d[5]), "+f"(d[6]), "+f"(d[7]), "+f"(d[8]), "+f"(d[9]), "+f"(d[10]), "+f"(d[11]), "+f"(d[12]), "+f"(d[13]), "+f"(d[14]), "+f"(d[15]), "+f"(d[16]), "+f"(d[17]), "+f"(d[18]), "+f"(d[19]), "+f"(d[20]), "+f"(d[21]), "+f"(d[22]), "+f"(d[23])
    : "l"(da), "l"(db), "r"(scale_d));
}
__device__ __forceinline__ void wg_rs88_tb(float* d, const uint32_t* a, uint64_t db, int scale_d) {
  asm volatile("{\n.reg .pred p;\nsetp.ne.b32 p, %49, 0;\n"
    "wgmma.mma_async.sync.aligned.m64n88k16.f32.bf16.bf16 "
    "{%0, %1, %2, %3, %4, %5, %6, %7, %8, %9, %10, %11, %12, %13, %14, %15, %16, %17, %18, %19, %20, %21, %22, %23, %24, %25, %26, %27, %28, %29, %30, %31, %32, %33, %34, %35, %36, %37, %38, %39, %40, %41, %42, %43}, {%44, %45, %46, %47}, %48, p, 1, 1, 1;\n}\n"
    : "+f"(d[0]), "+f"(d[1]), "+f"(d[2]), "+f"(d[3]), "+f"(d[4]), "+f"(d[5]), "+f"(d[6]), "+f"(d[7]), "+f"(d[8]), "+f"(d[9]), "+f"(d[10]), "+f"(d[11]), "+f"(d[12]), "+f"(d[13]), "+f"(d[14]), "+f"(d[15]), "+f"(d[16]), "+f"(d[17]), "+f"(d[18]), "+f"(d[19]), "+f"(d[20]), "+f"(d[21]), "+f"(d[22]), "+f"(d[23]), "+f"(d[24]), "+f"(d[25]), "+f"(d[26]), "+f"(d[27]), "+f"(d[28]), "+f"(d[29]), "+f"(d[30]), "+f"(d[31]), "+f"(d[32]), "+f"(d[33]), "+f"(d[34]), "+f"(d[35]), "+f"(d[36]), "+f"(d[37]), "+f"(d[38]), "+f"(d[39]), "+f"(d[40]), "+f"(d[41]), "+f"(d[42]), "+f"(d[43])
    : "r"(a[0]), "r"(a[1]), "r"(a[2]), "r"(a[3]), "l"(db), "r"(scale_d));
}
__device__ __forceinline__ void wg_ss80_tb(float* d, uint64_t da, uint64_t db, int scale_d) {
  asm volatile("{\n.reg .pred p;\nsetp.ne.b32 p, %42, 0;\n"
    "wgmma.mma_async.sync.aligned.m64n80k16.f32.bf16.bf16 "
    "{%0, %1, %2, %3, %4, %5, %6, %7, %8, %9, %10, %11, %12, %13, %14, %15, %16, %17, %18, %19, %20, %21, %22, %23, %24, %25, %26, %27, %28, %29, %30, %31, %32, %33, %34, %35, %36, %37, %38, %39}, %40, %41, p, 1, 1, 0, 1;\n}\n"
    : "+f"(d[0]), "+f"(d[1]), "+f"(d[2]), "+f"(d[3]), "+f"(d[4]), "+f"(d[5]), "+f"(d[6]), "+f"(d[7]), "+f"(d[8]), "+f"(d[9]), "+f"(d[10]), "+f"(d[11]), "+f"(d[12]), "+f"(d[13]), "+f"(d[14]), "+f"(d[15]), "+f"(d[16]), "+f"(d[17]), "+f"(d[18]), "+f"(d[19]), "+f"(d[20]), "+f"(d[21]), "+f"(d[22]), "+f"(d[23]), "+f"(d[24]), "+f"(d[25]), "+f"(d[26]), "+f"(d[27]), "+f"(d[28]), "+f"(d[29]), "+f"(d[30]), "+f"(d[31]), "+f"(d[32]), "+f"(d[33]), "+f"(d[34]), "+f"(d[35]), "+f"(d[36]), "+f"(d[37]), "+f"(d[38]), "+f"(d[39])
    : "l"(da), "l"(db), "r"(scale_d));
}
__device__ __forceinline__ void wg_ss48_tt_h(float* d, uint64_t da, uint64_t db, int scale_d) {
  asm volatile("{\n.reg .pred p;\nsetp.ne.b32 p, %26, 0;\n"
    "wgmma.mma_async.sync.aligned.m64n48k16.f32.f16.f16 "
    "{%0, %1, %2, %3, %4, %5, %6, %7, %8, %9, %10, %11, %12, %13, %14, %15, %16, %17, %18, %19, %20, %21, %22, %23}, %24, %25, p, 1, 1, 1, 1;\n}\n"
    : "+f"(d[0]), "+f"(d[1]), "+f"(d[2]), "+f"(d[3]), "+f"(d[4]), "+f"(d[5]), "+f"(d[6]), "+f"(d[7]), "+f"(d[8]), "+f"(d[9]), "+f"(d[10]), "+f"(d[11]), "+f"(d[12]), "+f"(d[13]), "+f"(d[14]), "+f"(d[15]), "+f"(d[16]), "+f"(d[17]), "+f"(d[18]), "+f"(d[19]), "+f"(d[20]), "+f"(d[21]), "+f"(d[22]), "+f"(d[23])
    : "l"(da), "l"(db), "r"(scale_d));
}
__device__ __forceinline__ void wg_rs192_tb(float* d, const uint32_t* a, uint64_t db, int scale_d) {
  asm volatile("{\n.reg .pred p;\nsetp.ne.b32 p, %101, 0;\n"
    "wgmma.mma_async.sync.aligned.m64n192k16.f32.bf16.bf16 "
    "{%0, %1, %2, %3, %4, %5, %6, %7, %8, %9, %10, %11, %12, %13, %14, %15, %16, %17, %18, %19, %20, %21, %22, %23, %24, %25, %26, %27, %28, %29, %30, %31, %32, %33, %34, %35, %36, %37, %38, %39, %40, %41, %42, %43, %44, %45, %46, %47, %48, %49, %50, %51, %52, %53, %54, %55, %56, %57, %58, %59, %60, %61, %62, %63, %64, %65, %66, %67, %68, %69, %70, %71, %72, %73, %74, %75, %76, %77, %78, %79, %80, %81, %82, %83, %84, %85, %86, %87, %88, %89, %90, %91, %92, %93, %94, %95}, {%96, %97, %98, %99}, %100, p, 1, 1, 1;\n}\n"
    : "+f"(d[0]), "+f"(d[1]), "+f"(d[2]), "+f"(d[3]), "+f"(d[4]), "+f"(d[5]), "+f"(d[6]), "+f"(d[7]), "+f"(d[8]), "+f"(d[9]), "+f"(d[10]), "+f"(d[11]), "+f"(d[12]), "+f"(d[13]), "+f"(d[14]), "+f"(d[15]), "+f"(d[16]), "+f"(d[17]), "+f"(d[18]), "+f"(d[19]), "+f"(d[20]), "+f"(d[21]), "+f"(d[22]), "+f"(d[23]), "+f"(d[24]), "+f"(d[25]), "+f"(d[26]), "+f"(d[27]), "+f"(d[28]), "+f"(d[29]), "+f"(d[30]), "+f"(d[31]), "+f"(d[32]), "+f"(d[33]), "+f"(d[34]), "+f"(d[35]), "+f"(d[36]), "+f"(d[37]), "+f"(d[38]), "+f"(d[39]), "+f"(d[40]), "+f"(d[41]), "+f"(d[42]), "+f"(d[43]), "+f"(d[44]), "+f"(d[45]), "+f"(d[46]), "+f"(d[47]), "+f"(d[48]), "+f"(d[49]), "+f"(d[50]), "+f"(d[51]), "+f"(d[52]), "+f"(d[53]), "+f"(d[54]), "+f"(d[55]), "+f"(d[56]), "+f"(d[57]), "+f"(d[58]), "+f"(d[59]), "+f"(d[60]), "+f"(d[61]), "+f"(d[62]), "+f"(d[63]), "+f"(d[64]), "+f"(d[65]), "+f"(d[66]), "+f"(d[67]), "+f"(d[68]), "+f"(d[69]), "+f"(d[70]), "+f"(d[71]), "+f"(d[72]), "+f"(d[73]), "+f"(d[74]), "+f"(d[75]), "+f"(d[76]), "+f"(d[77]), "+f"(d[78]), "+f"(d[79]), "+f"(d[80]), "+f"(d[81]), "+f"(d[82]), "+f"(d[83]), "+f"(d[84]), "+f"(d[85]), "+f"(d[86]), "+f"(d[87]), "+f"(d[88]), "+f"(d[89]), "+f"(d[90]), "+f"(d[91]), "+f"(d[92]), "+f"(d[93]), "+f"(d[94]), "+f"(d[95])
    : "r"(a[0]), "r"(a[1]), "r"(a[2]), "r"(a[3]), "l"(db), "r"(scale_d));
}
__device__ __forceinline__ void wg_rs48_tb(float* d, const uint32_t* a, uint64_t db, int scale_d) {
  asm volatile("{\n.reg .pred p;\nsetp.ne.b32 p, %29, 0;\n"
    "wgmma.mma_async.sync.aligned.m64n48k16.f32.bf16.bf16 "
    "{%0, %1, %2, %3, %4, %5, %6, %7, %8, %9, %10, %11, %12, %13, %14, %15, %16, %17, %18, %19, %20, %21, %22, %23}, {%24, %25, %26, %27}, %28, p, 1, 1, 1;\n}\n"
    : "+f"(d[0]), "+f"(d[1]), "+f"(d[2]), "+f"(d[3]), "+f"(d[4]), "+f"(d[5]), "+f"(d[6]), "+f"(d[7]), "+f"(d[8]), "+f"(d[9]), "+f"(d[10]), "+f"(d[11]), "+f"(d[12]), "+f"(d[13]), "+f"(d[14]), "+f"(d[15]), "+f"(d[16]), "+f"(d[17]), "+f"(d[18]), "+f"(d[19]), "+f"(d[20]), "+f"(d[21]), "+f"(d[22]), "+f"(d[23])
    : "r"(a[0]), "r"(a[1]), "r"(a[2]), "r"(a[3]), "l"(db), "r"(scale_d));
}
__device__ __forceinline__ void wg_ss192_tb(float* d, uint64_t da, uint64_t db, int scale_d) {
  asm volatile("{\n.reg .pred p;\nsetp.ne.b32 p, %98, 0;\n"
    "wgmma.mma_async.sync.aligned.m64n192k16.f32.bf16.bf16 "
    "{%0, %1, %2, %3, %4, %5, %6, %7, %8, %9, %10, %11, %12, %13, %14, %15, %16, %17, %18, %19, %20, %21, %22, %23, %24, %25, %26, %27, %28, %29, %30, %31, %32, %33, %34, %35, %36, %37, %38, %39, %40, %41, %42, %43, %44, %45, %46, %47, %48, %49, %50, %51, %52, %53, %54, %55, %56, %57, %58, %59, %60, %61, %62, %63, %64, %65, %66, %67, %68, %69, %70, %71, %72, %73, %74, %75, %76, %77, %78, %79, %80, %81, %82, %83, %84, %85, %86, %87, %88, %89, %90, %91, %92, %93, %94, %95}, %96, %97, p, 1, 1, 0, 1;\n}\n"
    : "+f"(d[0]), "+f"(d[1]), "+f"(d[2]), "+f"(d[3]), "+f"(d[4]), "+f"(d[5]), "+f"(d[6]), "+f"(d[7]), "+f"(d[8]), "+f"(d[9]), "+f"(d[10]), "+f"(d[11]), "+f"(d[12]), "+f"(d[13]), "+f"(d[14]), "+f"(d[15]), "+f"(d[16]), "+f"(d[17]), "+f"(d[18]), "+f"(d[19]), "+f"(d[20]), "+f"(d[21]), "+f"(d[22]), "+f"(d[23]), "+f"(d[24]), "+f"(d[25]), "+f"(d[26]), "+f"(d[27]), "+f"(d[28]), "+f"(d[29]), "+f"(d[30]), "+f"(d[31]), "+f"(d[32]), "+f"(d[33]), "+f"(d[34]), "+f"(d[35]), "+f"(d[36]), "+f"(d[37]), "+f"(d[38]), "+f"(d[39]), "+f"(d[40]), "+f"(d[41]), "+f"(d[42]), "+f"(d[43]), "+f"(d[44]), "+f"(d[45]), "+f"(d[46]), "+f"(d[47]), "+f"(d[48]), "+f"(d[49]), "+f"(d[50]), "+f"(d[51]), "+f"(d[52]), "+f"(d[53]), "+f"(d[54]), "+f"(d[55]), "+f"(d[56]), "+f"(d[57]), "+f"(d[58]), "+f"(d[59]), "+f"(d[60]), "+f"(d[61]), "+f"(d[62]), "+f"(d[63]), "+f"(d[64]), "+f"(d[65]), "+f"(d[66]), "+f"(d[67]), "+f"(d[68]), "+f"(d[69]), "+f"(d[70]), "+f"(d[71]), "+f"(d[72]), "+f"(d[73]), "+f"(d[74]), "+f"(d[75]), "+f"(d[76]), "+f"(d[77]), "+f"(d[78]), "+f"(d[79]), "+f"(d[80]), "+f"(d[81]), "+f"(d[82]), "+f"(d[83]), "+f"(d[84]), "+f"(d[85]), "+f"(d[86]), "+f"(d[87]), "+f"(d[88]), "+f"(d[89]), "+f"(d[90]), "+f"(d[91]), "+f"(d[92]), "+f"(d[93]), "+f"(d[94]), "+f"(d[95])
    : "l"(da), "l"(db), "r"(scale_d));
}
__device__ __forceinline__ void wg_ss48_tb(float* d, uint64_t da, uint64_t db, int scale_d) {
  asm volatile("{\n.reg .pred p;\nsetp.ne.b32 p, %26, 0;\n"
    "wgmma.mma_async.sync.aligned.m64n48k16.f32.bf16.bf16 "
    "{%0, %1, %2, %3, %4, %5, %6, %7, %8, %9, %10, %11, %12, %13, %14, %15, %16, %17, %18, %19, %20, %21, %22, %23}, %24, %25, p, 1, 1, 0, 1;\n}\n"
    : "+f"(d[0]), "+f"(d[1]), "+f"(d[2]), "+f"(d[3]), "+f"(d[4]), "+f"(d[5]), "+f"(d[6]), "+f"(d[7]), "+f"(d[8]), "+f"(d[9]), "+f"(d[10]), "+f"(d[11]), "+f"(d[12]), "+f"(d[13]), "+f"(d[14]), "+f"(d[15]), "+f"(d[16]), "+f"(d[17]), "+f"(d[18]), "+f"(d[19]), "+f"(d[20]), "+f"(d[21]), "+f"(d[22]), "+f"(d[23])
    : "l"(da), "l"(db), "r"(scale_d));
}

struct Params {
  const __nv_bfloat16 *par[4], *logdt, *dskip, *u, *wo;
  CUtensorMap m[M_COUNT];
};

#define CHUNK(i) ((i) == 0 ? c : ((i) == 7 ? (c ^ 1) : (((c & 6) + 1 + (i)) & 7)))
#define YTAG(v) (((v) & ~ym) | (ytag & ym))
#define FLAG(kind, rr, cc) (&g_flag[((kind) * 128 + (rr) * 8 + (cc)) * 32])
#define SLOT(i) ((i) == 0 ? OFF_EXTRA : OFF_BLK - 1024 + ((i) > 5 ? (i) - 6 : (i) - 1) * BLK)
__device__ __forceinline__ void load_quad(uint32_t* A, uint32_t addr) {
  A[0] = lds32v(addr); A[1] = lds32v(addr + 32); A[2] = lds32v(addr - 32); A[3] = lds32v(addr);
}

__device__ __forceinline__ bool y_transpose(uint32_t sb, int w5, int lane, uint32_t ytag) {
  const int mi = lane >> 3, rw = lane & 7;
  const uint32_t sa = sb + OFF_EXTRA + (w5 * 16 + rw) * 128 + ((mi ^ rw) << 4), da = sb + SLOT(3) + (8 * mi + rw) * 160 + w5 * 32;
  const uint32_t ym = lane < 4 ? 0x10001u : 0u;
  bar_sync(7, 160);
  uint32_t v[8][4], bad = 0;
  #pragma unroll
  for (int q = 0; q < 8; q++) ldsm4t(v[q], (sa ^ ((q & 1) * 64 + ((q >> 1) & 1) * 16)) + ((q >> 1) & 1) * 10240 + (q >> 2) * 1024);
  #pragma unroll
  for (int q = 0; q < 8; q++) {
    bad |= (v[q][0] ^ ytag) | (v[q][2] ^ ytag);
    stsm4(da + (q & 3) * 5120 + (q >> 2) * 16, v[q][0] & ~ym, v[q][1], v[q][2] & ~ym, v[q][3]);
  }
  fence_async();
  uint32_t any;
  asm volatile("{\n.reg .pred p;\nsetp.ne.u32 p, %1, 0;\nbarrier.red.or.pred p, 7, 160, p;\nselp.u32 %0, 1, 0, p;\n}" : "=r"(any) : "r"(bad & ym) : "memory");
  return any;
}

__global__ void __launch_bounds__(512, 1) fused_kernel(const __grid_constant__ Params prm) {
  extern __shared__ unsigned char smem_raw[];
  const uint32_t sb = __shfl_sync(0xffffffff, smem_u32(smem_raw), 0);
  const int tid = threadIdx.x, lane = tid & 31;
  const int warp = __shfl_sync(0xffffffff, tid >> 5, 0), wg = warp >> 2, w4 = warp & 3;
  const int cta = blockIdx.x, r = cta >> 3, c = cta & 7;
  if ((sb & 0xffffffu) != SB0) return;
#define BAR(i) (sb + OFF_BAR + 8 * (i))
  const bool sw64 = ((c + 1) & 2) != 0;

  const CUtensorMap* mwp = &prm.m[sw64 ? M_W64 : M_W128];
  const int mcol = (c * 80 + (c & 1) * 16) >> (sw64 ? 5 : 6), rcol = c * 80 + ((c & 1) ? 0 : 64);
  if (warp == 12 && elect_one()) {
    #pragma unroll
    for (int i = 0; i < 5; i++) mbar_init(BAR(BR_FULL + i), 1);
    asm volatile("fence.mbarrier_init.release.cluster;" ::: "memory");
    if (EN_ATT) {
      mbar_expect_tx(BAR(BR_FULL), W_SLOT + 16384);
      tma4d(sb, mwp, BAR(BR_FULL), 0, 0, mcol, 0);
      tma2d(sb + OFF_X, &prm.m[M_X], BAR(BR_FULL), 0, r * 128);
      tma3d(sb + 12288, &prm.m[M_WR], BAR(BR_FULL), rcol, 0, 0);
      mbar_expect_tx(BAR(BR_FULL + 1), W_SLOT);
      tma4d(sb + W_SLOT, mwp, BAR(BR_FULL + 1), 0, 32, mcol, 0);
      tma3d(sb + W_SLOT + 12288, &prm.m[M_WR], BAR(BR_FULL + 1), rcol, 32, 0);
      TS(24);
    }
  }
  if (warp == 13 && elect_one()) {
    asm volatile("prefetch.tensormap [%0];" :: "l"(&prm.m[M_X]) : "memory");
    asm volatile("prefetch.tensormap [%0];" :: "l"(&prm.m[M_WR]) : "memory");
  }
  if (wg == 3) {
    asm volatile("setmaxnreg.dec.sync.aligned.u32 56;");
    const int tid = rtid(), lane = tid & 31;
    if (warp == 12) {
      asm volatile("bar.arrive 0, 512;" ::: "memory");
      {
        uint32_t s = 2, ph = 1, xs = 16384;
        #pragma unroll 1
        for (int kb = 2; kb < 20; kb++) {
          if (kb == 4) bar_sync(6, 128);
          if (kb >= 5) mbar_wait(BAR(BR_EMPTY) + 8 * s, ph);
          if (EN_ATT && elect_one()) {
            const uint32_t st = sb + s * W_SLOT, fb = BAR(BR_FULL) + 8 * s;
            mbar_expect_tx(fb, (kb & 1) ? W_SLOT : W_SLOT + 16384);
            if (!(kb & 1)) tma2d(sb + OFF_X + xs, &prm.m[M_X], fb, kb * 32, r * 128);
            tma4d(st, mwp, fb, 0, kb * 32, mcol, 0);
            tma3d(st + 12288, &prm.m[M_WR], fb, rcol, kb * 32, 0);
          }
          if (kb < 4 && lane == 0) TS(24 + kb);
          if (UPF && kb >= UKB - 4 && kb < UKB && elect_one())
            asm volatile("cp.async.bulk.prefetch.L2.global [%0], 5120;" :: "l"(prm.u + cta * 10240 + (kb - (UKB - 4)) * 2560) : "memory");
          if (EN_SSM && kb == (EN_ATT ? UKB : 4) && elect_one()) { mbar_expect_tx(BAR(BR_UIN), 20480); tma2d(sb + OFF_UT, &prm.m[M_U], BAR(BR_UIN), c * 80, r * 128); }
          if (kb == 14 && elect_one()) asm volatile("cp.async.bulk.prefetch.L2.global [%0], 6400;" :: "l"(prm.wo + cta * 3200) : "memory");
          if (!EN_ATT && kb == 4) break;
          if (++s == 5) { s = 0; ph ^= 1; }
          if (kb & 1) { xs += 16384; if (xs == 49152) xs = 0; }
        }
      }
      if (EN_ATT) {
      mbar_wait(BAR(BR_EPOCH), 0);
      const unsigned epoch = lds32(sb + OFF_EPOCH);
      const unsigned* fo = FLAG(3, r, lane & 7);
      unsigned seen = __ballot_sync(0xffffffff, ld_rlx(lane < 16 ? fo : FLAG(0, lane & 15, c)) == epoch) & 0xffu;
      mbar_wait(BAR(BR_GEMM), 0);
      if (elect_one()) {
        mbar_expect_tx(BAR(BR_WO), 10240);
        tma2d(sb, &prm.m[M_WO], BAR(BR_WO), c * 64, c * 80);
        mbar_expect_tx(BAR(BR_KVP), 61440);
        mbar_expect_tx(BAR(BR_WO + 1), 7 * 10240);
      }
      {
        uint32_t ds = sb + OFF_WOR + (lane >> 3) * 128 + (((lane & 7) ^ (lane >> 3)) << 4);
        #pragma unroll 1
        for (int h = 0; h < 2; h++) {
          const int i = (lane & 6) + h;
          const char* gs = reinterpret_cast<const char*>(prm.wo) + (size_t)((lane >> 3) + CHUNK(i) * 80) * 1280 + 1024 + c * 32 + (lane & 1) * 16;
          #pragma unroll 2
          for (int q = 0; q < 20; q++) {
            asm volatile("cp.async.cg.shared.global [%0], [%1], 16;" :: "r"(ds), "l"(gs) : "memory");
            ds = (ds + 512) ^ 64; gs += 5120;
          }
        }
      }
      mbar_wait(BAR(BR_PUB), 0);
      poll_all(FLAG(0, lane & 15, c), epoch);
      if (elect_one()) { TS(23); bulk_ld(sb + OFF_KVP, &g_kvp[c * 16 * 240], 61440, BAR(BR_KVP)); }
      asm volatile("cp.async.wait_all;" ::: "memory");
      fence_async();
      mbar_arrive(BAR(BR_WO));
      mbar_wait(BAR(BR_SUM), 0);
      if (elect_one()) {
        #pragma unroll 1
        for (int i = 1; i < 8; i++) tma2d(sb + i * 10240, &prm.m[M_WO], BAR(BR_WO + 1), c * 64, CHUNK(i) * 80);
      }
      mbar_wait(BAR(BR_OSTG), 0);
      if (elect_one()) {
        bulk_st(&g_o[cta * 1280], sb + OFF_EXTRA, 20480);
        bulk_commit();
        bulk_wait0();
        st_rlx(FLAG(3, r, c), epoch);
        mbar_arrive(BAR(BR_OEMPTY));
        TS(20);
      }
      __syncwarp();
      #pragma unroll 1
      for (int i = 1; i < 8; i++) {
        const int src = CHUNK(i);
        if (!((seen >> src) & 1)) seen = poll_bit(fo, epoch, 1u << src);
        if (i > 5) mbar_wait(BAR(BR_OEMPTY - 5) + 8 * i, 0);
        if (EN_SSM && (i == 1 || i == 5)) mbar_wait(BAR(BR_FREE) + 2 * (i & 4), 0);
        if (elect_one()) {
          mbar_expect_tx(BAR(BR_OFULL) + 8 * i, 20480);
          bulk_ld(sb + SLOT(i), &g_o[(r * 8 + src) * 1280], 20480, BAR(BR_OFULL) + 8 * i);
          if (i == 1) TS(21);
          if (i == 7) TS(22);
        }
        __syncwarp();
      }
      if (lane == 0) { DUMP(20, 30); }
      }
    } else {
      const int hw = warp - 13, ht = tid - 416;
      if (hw == 2 && elect_one()) {
        #pragma unroll
        for (int i = 5; i < BR_COUNT; i++) mbar_init(BAR(i), i == BR_WO ? 33 : i == BR_OEMPTY ? 9 : i < BR_EMPTY ? 1 : i < BR_OEMPTY ? 2 : i < BR_Y ? 8 : i == BR_Y ? 4 : i <= BR_OSTG ? 8 : i < BR_U2 ? 3 : 1);
        asm volatile("fence.mbarrier_init.release.cluster;" ::: "memory");
      }
      __syncwarp();
      asm volatile("bar.arrive 0, 512;" ::: "memory");
      if (EN_SSM && hw == 2) asm volatile("bar.arrive 8, 160;" ::: "memory");
      const unsigned epoch = hw == 0 ? ld_rlx(&g_epoch[cta]) + 1 : 0;
      bar_sync(5, 96);
      asm volatile("bar.arrive 6, 128;" ::: "memory");
      if (hw == 1 && elect_one()) {
        #pragma unroll
        for (int i = M_U; i < M_COUNT; i++) asm volatile("prefetch.tensormap [%0];" :: "l"(&prm.m[i]) : "memory");
      }
      if (ht == 0) {
        st_rlx(&g_epoch[cta], epoch);
        sts32(sb + OFF_EPOCH, epoch);
        mbar_arrive(BAR(BR_EPOCH));
      }
      if (EN_SSM) {
      const int mi = lane >> 3, rw = lane & 7, ch0 = c * 80 + r * 5;
      mbar_wait(BAR(BR_UIN), 0);
      if (ht == 0) TS(36);
      #pragma unroll 1
      for (int h = 0; h < 2; h++) {
        const uint32_t sa = sb + OFF_UT + h * 10240 + (8 * mi + rw) * 160 + hw * 16, da = sb + OFF_UT + h * 10240 + (hw * 8 + rw) * 128 + ((mi ^ rw ^ h) << 4);
        uint32_t v[8][4];
        #pragma unroll
        for (int q = 0; q < 8; q++) if (q < 6 || hw == 0) ldsm4t(v[q], sa + (q & 1) * 5120 + (q >> 1) * 48);
        bar_sync(5, 96);
        #pragma unroll
        for (int q = 0; q < 8; q++) if (q < 6 || hw == 0) stsm4((da ^ ((q & 1) * 64)) + (q >> 1) * 3072, v[q][0], v[q][1], v[q][2], v[q][3]);
      }
      fence_async();
      bar_sync(5, 96);
      if (hw == 0) {
        if (elect_one()) {
          tma2d_st(&prm.m[M_SA], sb + OFF_UT, r * 128, c * 80);
          tma2d_st(&prm.m[M_SA], sb + OFF_UT + 10240, r * 128 + 64, c * 80);
          bulk_commit(); bulk_wait0_read();
          mbar_arrive(BAR(BR_UOUT));
          TS(37);
          bulk_wait0();
          st_rel(FLAG(1, r, c), epoch);
          TS(30);
        }
        __syncwarp();
        poll_all_acq(FLAG(1, lane & 15, c), epoch);
      }
      #pragma unroll 1
      for (int k = 0; k < 5; k++) {
        if (k == 0 || k == 3) {
          const int p = k != 0;
          if (hw == 0) {
            if (!p) {
              if (elect_one()) {
                fence_async_g();
                mbar_expect_tx(BAR(BR_U), 12288);
                #pragma unroll 1
                for (int q = 0; q < 3; q++) bulk_ld(sb + OFF_BLK + q * q * BLK, g_uy + (ch0 + q * q) * 2048, 4096, BAR(BR_U));
                TS(31);
              }
              __syncwarp();
            }
            mbar_wait(BAR(p ? BR_U2 : BR_U), 0);
          }
          bar_sync(5, 96);
        }
        const int l3 = (hw + k) % 3 * 32 + lane;
        const uint32_t blk = sb + OFF_BLK + ((0x32410 >> (4 * k)) & 7) * BLK, o = blk + B_D + l3 * 16;
        float P[34];
        P[0] = 0.f;
        #pragma unroll
        for (int q = 0; q < 5; q++) {
          const int ch = 2 * l3 - 3 + q;
          uint32_t v[4];
          lds128(v, blk + (uint32_t)((ch * 16) ^ ((ch * 2) & 0x10)));
          #pragma unroll
          for (int e = 0; e < 8; e++) {
            const int i = 8 * q + e - 4;
            if (i >= 0 && i < 33) P[i + 1] = P[i] + ((e & 1) ? bf_hi(v[e >> 1]) : bf_lo(v[e >> 1]));
          }
        }
#define WIN(lo, hi, e) (P[21 + (e) - (lo)] - P[20 + (e) - (hi)])
#define WIN8(lo, hi, b) pack2(WIN(lo, hi, b), WIN(lo, hi, b + 1)), pack2(WIN(lo, hi, b + 2), WIN(lo, hi, b + 3)), pack2(WIN(lo, hi, b + 4), WIN(lo, hi, b + 5)), pack2(WIN(lo, hi, b + 6), WIN(lo, hi, b + 7))
        if (l3 < 64) {
          sts128(o + B_D9, WIN8(12, 20, 0)); sts128(o + B_D9 + 1024, WIN8(12, 20, 8));
          sts128(o + B_D7, WIN8(5, 11, 0)); sts128(o + B_D7 + 1024, WIN8(5, 11, 8));
        }
        sts128(o + B_D5, WIN8(6, 10, 0)); sts128(o + B_D5 + 1552, WIN8(6, 10, 8));
        sts128(o, WIN8(3, 5, 0)); sts128(o + 1552, WIN8(3, 5, 8));
        if (l3 < 2) sts128(blk + B_D + l3 * B_D5 + 1536, 0, 0, 0, 0);
      }
      __syncwarp();
      if (lane == 0) mbar_arrive(BAR(BR_DRDY + 1));
      if (ht == 0) TS(32);
      if (hw == 0) {
        #pragma unroll 1
        for (int p = 0; p < 2; p++) {
          mbar_wait(BAR(BR_Y) + 8 * p, 0);
          if (elect_one()) {
            #pragma unroll 1
            for (int k = 4 * p; k < 4 + p; k++) bulk_st(g_uy + (640 + ch0 + k) * 2048, sb + OFF_BLK + k * BLK, 4096);
            bulk_commit(); bulk_wait0_read();
            mbar_arrive(BAR(BR_FREE) + 8 * p);
          }
          __syncwarp();
        }
        if (elect_one()) { bulk_wait0(); st_rlx(FLAG(2, r, c), epoch); TS(33); }
        __syncwarp();
        poll_all(FLAG(2, lane & 15, c), epoch);
        if (EN_ATT) mbar_wait(BAR(BR_OEMPTY), 0);
        #pragma unroll 1
        for (int n = 0; n < 64; n++) {
          if (elect_one()) {
            mbar_expect_tx(BAR(BR_YIN), 20480);
            tma2d(sb + OFF_EXTRA, &prm.m[M_SA], BAR(BR_YIN), r * 128, 640 + c * 80);
            tma2d(sb + OFF_EXTRA + 10240, &prm.m[M_SA], BAR(BR_YIN), r * 128 + 64, 640 + c * 80);
            TS(34);
          }
          __syncwarp();
          if (EN_ATT) mbar_wait(BAR(BR_OEMPTY + 3), 0);
          mbar_wait(BAR(BR_YIN), n & 1);
          if (lane == 0) TS(38);
          if (!y_transpose(sb, 4, lane, (epoch & 1u) * 0x10001u)) break;
          FIXCNT
        }
      if (elect_one()) {
        TS(39);
        tma2d_st(&prm.m[M_OUT], sb + SLOT(3), c * 80, r * 128);
        bulk_commit(); bulk_wait0_read();
        TS(35); DUMP(30, 40); DUMP(0, 1);
      }
      }
      }
    }
  } else if (wg < 2) {
    asm volatile("setmaxnreg.inc.sync.aligned.u32 160;");
    bar_sync(0, 512);
    if (EN_ATT) {
    float am[96], ar[24];
    {
      const bool lead = (rtid() & 127) == 0;
      constexpr uint64_t dr0 = mkdesc(SB0 + 12288, 1024, 256, 3);
      const uint64_t db0 = sw64 ? mkdesc(SB0, 2048, 512, 2) : mkdesc(SB0, 4096, 1024, 1);
      const uint32_t kst = sw64 ? 64 : 128, bh = db0 >> 32;
      uint32_t s = 0, ph = 0, xo = 0;
      const int ln = rtid() & 31;
      const uint32_t xa = sb + OFF_X + (warp * 16 + (ln & 15)) * 128 + (((ln >> 4) ^ (ln & 7)) << 4);
      uint32_t A[8];
      mbar_wait(BAR(BR_FULL), 0);
      if (lead && wg == 0) TS(1);
      ldsm4(A, xa); ldsm4(A + 4, xa);
      wg_fence();
      wg_rs48_tb(ar, A + 4, dr0, 0); wg_rs192_tb(am, A + 4, db0, 0);
      wg_commit();
      uint32_t xk = xa, eb = 0;
      #pragma unroll 1
      for (int kb = 0; kb < 20; kb++) {
        const uint32_t wo_ = s * (W_SLOT >> 4), bl = (uint32_t)db0 + wo_, rl = (uint32_t)dr0 + wo_;
        wg_fence();
        wg_rs48_tb(ar, A, desc2(rl, dr0 >> 32), kb != 0);
        wg_rs192_tb(am, A, desc2(bl, bh), kb != 0);
        wg_commit();
        wg_wait<1>();
        ldsm4(A + 4, xk ^ 32);
        if (lead && kb > 0 && kb < 16) mbar_arrive(eb);
        eb = BAR(BR_EMPTY) + 8 * s;
        wg_fence();
        wg_rs48_tb(ar, A + 4, desc2(rl + 32, dr0 >> 32), 1);
        wg_rs192_tb(am, A + 4, desc2(bl + kst, bh), 1);
        wg_commit();
        if (++s == 5) { s = 0; ph ^= 1; }
        if (kb & 1) { xo += 16384; if (xo == 49152) xo = 0; }
        if (kb < 19) mbar_wait(BAR(BR_FULL) + 8 * s, ph);
        xk = (xa + xo) ^ ((~kb & 1) * 64);
        wg_wait<1>();
        ldsm4(A, xk);
      }
      wg_wait<0>();
      pin<96>(am); pin<24>(ar);
    }
    const int tid = rtid(), lane = tid & 31, tq = lane & 3;
    if (tid == 0) TS(2);
#define QV(j, e) ((j) < 8 ? am[4 * (j) + (e)] : ar[4 * ((j) - 8) + (e)])
#define KV_(j, e) ((j) < 8 ? am[32 + 4 * (j) + (e)] : ar[8 + 4 * ((j) - 8) + (e)])
#define VV(j, e) ((j) < 8 ? am[64 + 4 * (j) + (e)] : ar[16 + 4 * ((j) - 8) + (e)])
    {
      bar_sync(1, 256);
      if (tid == 0) mbar_arrive(BAR(BR_GEMM));
      const uint32_t ro = sb + (uint32_t)((warp * 16 + (lane & 15)) * 16);
      const int l0 = 2 * (c & 1) + (lane >> 4);
      const uint32_t ones = (tq == 0) ? 0x00003f80u : 0u;
#define PV(j) pack2(VV(j, 0), VV(j, 1)), pack2(VV(j, 2), VV(j, 3))
#define PK(j) pack2(phi(KV_(j, 0)), phi(KV_(j, 1))), pack2(phi(KV_(j, 2)), phi(KV_(j, 3)))
      stsm4(ro + OFF_V + (5 + 6 * (lane >> 4)) * 2048, ones, ones, ones, ones);
      #pragma unroll
      for (int j = 0; j < 10; j += 2) {
        const int l = (j == 8 && (c & 1)) ? l0 - 2 : l0 + j;
        stsm4(ro + OFF_V + (l + (l >= 5)) * 2048, PV(j), PV(j + 1));
        stsm4(ro + OFF_PK + l * 2048, PK(j), PK(j + 1));
      }
    }
    fence_async();
    bar_sync(1, 256);
    if (tid == 0) TS(3);
    mbar_wait(BAR(BR_EPOCH), 0);
    const unsigned epoch = lds32(sb + OFF_EPOCH);
    {
      float kv[24]; zero<24>(kv);
      constexpr uint64_t da = mkdesc(SB0 + OFF_PK, 128, 2048, 0), db = mkdesc(SB0 + OFF_V, 128, 2048, 0);
      wg_fence();
      #pragma unroll
      for (int s = 0; s < 8; s++) wg_ss48_tt(kv, desc2((uint32_t)da + wg * 640 + s * 16, da >> 32), desc2((uint32_t)db + wg * 768 + s * 16, db >> 32), s != 0);
      wg_commit();
      wg_wait<0>();
      pin<24>(kv);
      if (tid == 0) TS(15);
      if (w4 < 3) {
        const uint32_t wb = sb + OFF_KVS + (wg * 3 + w4) * 1536 + (lane & 15) * 96;
        #pragma unroll
        for (int j = 0; j < 6; j += 2)
          stsm4(wb + (j + (lane >> 4)) * 16, pack2(kv[4 * j], kv[4 * j + 1]), pack2(kv[4 * j + 2], kv[4 * j + 3]),
                pack2(kv[4 * j + 4], kv[4 * j + 5]), pack2(kv[4 * j + 6], kv[4 * j + 7]));
        __syncwarp();
        const int dl = w4 * 16 + (lane & 15), hl = dl >= 20;
        if (dl < 40) {
          uint4* dst = &g_kvp[(c * 16 + r) * 240 + wg * 40 + dl];
          uint32_t v[4], z[4];
          lds128(v, wb + (3 * hl + (lane >> 4)) * 16);
          lds64(z, wb + 32 + 8 * hl); z[2] = lds32(wb + 80); z[3] = epoch & 1u;
          v[3] = (v[3] & ~1u) | z[3];
          st128_rlx(dst + (lane >> 4) * 80, v);
          if (lane < 16) st128_rlx(dst + 160, z);
        }
      }
    }
    fence_async();
    bar_sync(1, 256);
    if (tid == 0) { st_rlx(FLAG(0, r, c), epoch); mbar_arrive(BAR(BR_PUB)); TS(4); }
    const int kvi = (tid >= 80) + (tid >= 160) + (tid >= 240), kd = tid - 80 * kvi;
    const int khd = kd / 20, kt0 = 5 * (khd >> 1) + 2 * (khd & 1);
    const uint32_t rb = sb + OFF_KVB + kd * 16;
    if (kvi < 3) {
      #pragma unroll 1
      for (int m = kvi; m < 7; m += 3) { const int q = kt0 + 3 + m; sts128(rb + (q >= 10 ? q - 10 : q) * 1280, 0, 0, 0, 0); }
    }
    uint32_t qa[20];
    {
      const float sc = 1.44269504089f + __uint_as_float(lds32(sb + OFF_EPOCH) ^ epoch);
      #pragma unroll
      for (int j = 0; j < 10; j++) { qa[2 * j] = pack2(phi(QV(j, 0), sc), phi(QV(j, 1), sc)); qa[2 * j + 1] = pack2(phi(QV(j, 2), sc), phi(QV(j, 3), sc)); }
    }
    if (tid == 0) TS(5);
    if (warp == 7) mbar_wait(BAR(BR_KVP), 0);
    bar_sync(1, 256);
    if (tid == 0) TS(6);
    if (kvi < 3) {
      float s[8];
      zero<8>(s);
      uint32_t bad = 0;
      #pragma unroll 4
      for (int i = 0; i < 16; i += 2) {
        uint32_t w[4], x[4];
        lds128(w, sb + OFF_KVP + tid * 16 + i * 3840); lds128(x, sb + OFF_KVP + tid * 16 + i * 3840 + 3840);
        bad |= (w[3] ^ epoch) | (x[3] ^ epoch);
        #pragma unroll
        for (int e = 0; e < 4; e++) {
          asm("add.rn.bf16x2 %0, %0, %1;" : "+r"(w[e]) : "r"(x[e]));
          s[2 * e] += bf_lo(w[e]); s[2 * e + 1] += bf_hi(w[e]);
        }
      }
      if (__builtin_expect(bad & 1u, 0)) {
        zero<8>(s);
        #pragma unroll 1
        for (int i = 0; i < 16; i++) {
          uint32_t w[4] = {0, 0, 0, ~epoch};
          fix128_w3(w, &g_kvp[(c * 16 + i) * 240 + tid], epoch, 1u);
          #pragma unroll
          for (int e = 0; e < 4; e++) { s[2 * e] += bf_lo(w[e]); s[2 * e + 1] += bf_hi(w[e]); }
        }
        FIXCNT
      }
      const uint32_t p0 = pack2(s[0], s[1]), p1 = pack2(s[2], s[3]), p2 = pack2(s[4], s[5]), p3 = pack2(s[6], s[7]);
      if (kvi < 2) sts128(rb + (kt0 + (khd & 1) + kvi) * 1280, p0, p1, p2, p3);
      else {
        const bool od = khd & 1;
        sts128(rb + (5 * (khd >> 1) + 2) * 1280, od ? 0u : p0, od ? 0u : p1, od ? p0 : 0u, od ? p1 : 0u);
        const uint32_t zz = (p2 & 0xffffu) << (16 * (khd & 1));
        sts128(rb + 10 * 1280, khd < 2 ? zz : 0u, khd < 2 ? 0u : zz, 0u, 0u);
      }
    }
    fence_async();
    bar_sync(1, 256);
    if (tid == 0) { mbar_arrive(BAR(BR_SUM)); TS(7); }
    {
      float oa[44]; zero<44>(oa);
      constexpr uint64_t db = mkdesc(SB0 + OFF_KVB, 128, 1280, 0);
      wg_fence();
      #pragma unroll
      for (int s = 0; s < 5; s++) wg_rs88_tb(oa, &qa[4 * s], desc2((uint32_t)db + ((s == 4 && (c & 1)) ? 0 : (s + (c & 1)) * 16), db >> 32), s != 0);
      wg_commit();
      wg_wait<0>();
      pin<44>(oa);
      if (tid == 0) TS(13);
      float rc[4], rd[2][4];
      #pragma unroll
      for (int e = 0; e < 4; e++) asm("rcp.approx.ftz.f32 %0, %1;" : "=f"(rc[e]) : "f"(oa[40 + e] + 1e-6f));
      #pragma unroll
      for (int h = 0; h < 4; h++) {
        rd[0][h] = __shfl_sync(0xffffffff, rc[h & 1], (lane & 28) | (h >> 1));
        rd[1][h] = __shfl_sync(0xffffffff, rc[2 + (h & 1)], (lane & 28) | (h >> 1));
      }
      #pragma unroll
      for (int j = 0; j < 10; j++) {
        #pragma unroll
        for (int h = 0; h < 2; h++) {
          float f;
          if (j == 2) f = tq < 2 ? rd[h][0] : rd[h][1];
          else if (j == 7) f = tq < 2 ? rd[h][2] : rd[h][3];
          else f = rd[h][(8 * j) / 20];
          qa[2 * j + h] = pack2(oa[4 * j + 2 * h] * f, oa[4 * j + 2 * h + 1] * f);
        }
      }
      const uint32_t m0 = (lane & 7) == ((2 * w4) & 7), m1 = (lane & 7) == 2 * w4 + 1;
      const uint32_t oa_ = sb + OFF_EXTRA + (lane >> 4) * 2048 + (warp * 16 + (lane & 15)) * 16;
      bar_sync(1, 256);
#define TAG(v, m) (((v) & ~(m)) | (epoch & (m)))
      #pragma unroll
      for (int s = 0; s < 5; s++) stsm4(oa_ + s * 4096, TAG(qa[4 * s], m0), TAG(qa[4 * s + 1], m1), TAG(qa[4 * s + 2], m0), TAG(qa[4 * s + 3], m1));
    }
    fence_async();
    __syncwarp();
    if (lane == 0) mbar_arrive(BAR(BR_OSTG));
    if (tid == 0) TS(8);
    if (EN_SSM) {
      const int g = lane >> 2, kl0 = 2 * (lane & 7) + ((lane >> 3) & 1), ih = (lane >> 3) & 1;
      const uint32_t ytag = (epoch & 1u) * 0x10001u, ym = lane < 4 ? 0x10001u : 0u;
      mbar_wait(BAR(BR_KS), 0);
      mbar_wait(BAR(BR_DRDY + 1), 0);
      const uint32_t blk = sb + OFF_BLK + 4 * BLK, tb = blk + B_TBL + (uint32_t)((g - 2 * tq) * 4);
      const int kl = 16 * ((lane >> 4) ? 7 - w4 : w4) + kl0;
      float acc[8][4];
      zero<32>(&acc[0][0]);
      #pragma unroll 2
      for (int s = 4 * wg; s < 4 * wg + 4; s++) {
        const int q = kl - 2 * s;
        const uint32_t ub = blk + (uint32_t)((q * 16) ^ ((q * 2) & 0x10));
        #pragma unroll
        for (int m = 0; m < 4; m++) {
          uint32_t A[4], B[8];
          load_quad(A, tb + (16 + 16 * s + 128 * m) * 4);
          ldsm4(B, ub - 256 * m); ldsm4(B + 4, ub + 2048 - 256 * m);
          #pragma unroll
          for (int e = 0; e < 4; e++) mma16816(acc[4 * (m & 1) + e], A, &B[2 * e]);
        }
      }
      {
        const int s = wg;
        const int q = kl - 2 * s;
        const uint32_t ub = blk + (uint32_t)((q * 16) ^ ((q * 2) & 0x10));
        uint32_t A[4], E[4], B[12];
        load_quad(A, tb + (16 + 512 + 16 * s) * 4); load_quad(E, tb + (T_S + 16 * s) * 4);
        ldsm4(B, (lane >> 4) ? ub - 1024 : ub); ldsm4(B + 4, ub + 1024); ldsm4(B + 8, ub);
        mma16816(acc[1], A, &B[2]); mma16816(acc[2], A, &B[4]); mma16816(acc[3], A, &B[6]);
        mma16816(acc[6], E, &B[8]); mma16816(acc[7], E, &B[10]);
      }
      if (tid == 0) TS(16);
      const uint32_t dl = blk + B_D + (uint32_t)(((lane >> 4) * 8 + (lane & 7)) * 16);
      const int od = w4 & 1, k1 = ((7 - w4) >> 1) - 2, k2 = ((8 + w4) >> 1) - 2;
      #pragma unroll
      for (int a = 0; a < 2; a++) {
        const uint32_t da = dl + a * B_D5 + (wg ? (ih ? 0 : 1536) : ih * 1552), ta = tb + (T_F2 + 48 * (2 * wg + a)) * 4;
        #pragma unroll
        for (int i = 0; i < 3; i++) {
          uint32_t A[12], B[4];
          B[0] = lds32v(ta + (2 * i + 1 - od) * 32); B[1] = lds32v(ta + (2 * i - od) * 32);
          B[2] = lds32v(ta + (2 * i + od) * 32); B[3] = lds32v(ta + (2 * i + od - 1) * 32);
          ldsm4t(A + 4, da + (k2 - i) * 256); ldsm4t(A + 8, da + (k1 + 4 - i) * 256);
          if (i < 2) { ldsm4t(A, k1 >= i ? da + (k1 - i) * 256 : blk - 256); mma16816(acc[1 + 4 * (i & 1)], A, B); }
          mma16816(acc[2 + 4 * (i & 1)], A + 4, B + 2); mma16816(acc[3 + 4 * (i & 1)], A + 8, B);
        }
      }
      {
        const int b = wg;
        const uint32_t da = dl + B_D7 + b * 2048 + ih * 1024, ta = tb + (T_F3 + 80 * b) * 4, tz = tb + 546 * 4;
        #pragma unroll
        for (int kk = 0; kk < 4; kk++) {
          uint32_t A[4], B[4];
          ldsm4t(A, da + kk * 256);
          const uint32_t t3 = 7 - w4 >= 2 * kk ? ta + (7 - w4 - 2 * kk) * 32 : tz;
          B[0] = lds32v(t3); B[1] = lds32v(t3 - 32);
          mma16816(acc[3 + 4 * (kk & 1)], A, B);
          if (kk < 2) {
            const uint32_t t2 = w4 >= 2 * kk ? ta + (w4 - 2 * kk) * 32 : tz;
            B[2] = lds32v(t2); B[3] = lds32v(t2 - 32);
            mma16816(acc[2 + 4 * (kk & 1)], A, B + 2);
          }
        }
      }
      if (tid == 0) TS(17);
      float y[8];
      const uint32_t xw = blk + B_D + tid * 16;
      bar_sync(1, 256);
      #pragma unroll
      for (int h = 0; h < 2; h++) {
        float o[4];
        #pragma unroll
        for (int e = 0; e < 4; e++) {
          const float lo = acc[h][e] + acc[h + 4][e], hi = acc[h + 2][e] + acc[h + 6][e];
          y[4 * h + e] = wg ? hi : lo; o[e] = wg ? lo : hi;
        }
        sts128(xw + h * 4096, __float_as_uint(o[0]), __float_as_uint(o[1]), __float_as_uint(o[2]), __float_as_uint(o[3]));
      }
      bar_sync(1, 256);
      #pragma unroll
      for (int h = 0; h < 2; h++) {
        uint32_t o[4]; lds128(o, blk + B_D + (tid ^ 128) * 16 + h * 4096);
        #pragma unroll
        for (int e = 0; e < 4; e++) y[4 * h + e] += __uint_as_float(o[e]);
      }
      stsm4t(blk + (uint32_t)((kl * 16) ^ ((kl * 2) & 0x10)) + wg * 2048, YTAG(pack2(y[0], y[1])), pack2(y[2], y[3]), YTAG(pack2(y[4], y[5])), pack2(y[6], y[7]));
      fence_async();
      __syncwarp();
      if (lane == 0) mbar_arrive(BAR(BR_Y + 1));
      if (tid == 0) TS(18);
    }
    float oc[40]; zero<40>(oc);
    {
      constexpr uint64_t dw0 = mkdesc(SB0, OFF_WOR, 1024, 1), da0 = mkdesc(SB0, 2048, 128, 0);
      const uint32_t ck = sb + tid * 32 + ((lane >> 2) << 2), ck2 = ck + (wg ? 0 : 16384);
      uint32_t bad = 0;
      auto tile = [&](int i, uint32_t so) {
        const uint32_t al = (uint32_t)da0 + wg * 64 + (so >> 4), wl = (uint32_t)dw0 + i * 640 - (i >> 1) * (1278 << 16);
        wg_fence();
        #pragma unroll
        for (int s = 0; s < 5; s++) wg_ss80_tb(oc, desc2(al + s * 256, da0 >> 32), desc2(wl + s * 128, dw0 >> 32), (i | s) != 0);
        wg_commit();
        bad |= (lds32(ck + so) ^ epoch) | (lds32(ck + so + 8192) ^ epoch) | (lds32(ck2 + so) ^ epoch);
      };
      if (w4 == 0) {
        if (EN_SSM) mbar_wait(BAR(BR_Y), 0);
        mbar_wait(BAR(BR_WO), 0);
        mbar_wait(BAR(BR_WO + 1), 0);
      }
      bar_sync(1, 256);
      if (tid == 0) TS(9);
      tile(0, SLOT(0));
      #pragma unroll 1
      for (int i = 1; i < 8; i++) {
        mbar_wait(BAR(BR_OFULL) + 8 * i, 0);
        tile(i, SLOT(i));
        wg_wait<1>();
        if (lane == 0) mbar_arrive(BAR(BR_OEMPTY - 1) + 8 * i);
      }
      #pragma unroll 1
      for (int n = 0; n < 56; n++) {
        const int i = n & 7;
        if (i == 0) {
          uint32_t any;
          asm volatile("{\n.reg .pred p;\nsetp.ne.u32 p, %1, 0;\nbarrier.red.or.pred p, 1, 256, p;\nselp.u32 %0, 1, 0, p;\n}" : "=r"(any) : "r"(bad & 1u) : "memory");
          if (!any) break;
          bad = 0;
          FIXCNT
        }
        wg_wait<0>();
        bar_sync(1, 256);
        if (tid == 0) { mbar_expect_tx(BAR(BR_RETRY), 20480); bulk_ld(sb + SLOT(5), &g_o[(r * 8 + CHUNK(i)) * 1280], 20480, BAR(BR_RETRY)); }
        mbar_wait(BAR(BR_RETRY), n & 1);
        tile(i, SLOT(5));
      }
      wg_wait<0>();
      pin<40>(oc);
    }
    if (tid == 0) TS(10);
    {
      const int row = w4 * 16 + (lane & 15);
      const uint32_t ob = sb + OFF_BLK + 3 * BLK + wg * 10240;
      #pragma unroll
      for (int j = 0; j < 8; j += 2)
        stsm4(ob + row * 128 + (((j + (lane >> 4)) ^ (row & 7)) << 4), pack2(oc[4 * j], oc[4 * j + 1]), pack2(oc[4 * j + 2], oc[4 * j + 3]),
              pack2(oc[4 * j + 4], oc[4 * j + 5]), pack2(oc[4 * j + 6], oc[4 * j + 7]));
      stsm4(ob + 8192 + row * 32 + (lane >> 4) * 16, pack2(oc[32], oc[33]), pack2(oc[34], oc[35]), pack2(oc[36], oc[37]), pack2(oc[38], oc[39]));
      fence_async();
      bar_sync(2 + wg, 128);
      if (w4 == 0 && elect_one()) {
        tma2d_st(&prm.m[M_O64], ob, 640 + c * 64, r * 128 + wg * 64);
        tma2d_st(&prm.m[M_O16], ob + 8192, 1152 + c * 16, r * 128 + wg * 64);
        bulk_commit(); bulk_wait0_read();
        if (wg == 0) { TS(11); DUMP(0, 20); }
      }
    }
    }
  } else {
    const int g = lane >> 2, tq = lane & 3, t7 = tid & 127;
    uint32_t raw[5][4], pd;
    {
      const int ch = c * 80 + r * 5;
      #pragma unroll
      for (int e = 0; e < 4; e++) {
        const __nv_bfloat16* pp = prm.par[e] + ch * 128 + t7;
        #pragma unroll
        for (int q = 0; q < 5; q++) asm volatile("ld.global.nc.u16 %0, [%1];" : "=r"(raw[q][e]) : "l"(pp + q * 128));
      }
      asm volatile("ld.global.nc.u16 %0, [%1];" : "=r"(pd) : "l"(((lane & 8) ? prm.dskip : prm.logdt) + ch + min(lane & 7, 4)));
    }
    asm volatile("bar.arrive 0, 512;" ::: "memory");
    if (EN_SSM) {
    {
      #pragma unroll 1
      for (int k = 0; k < 4; k++) {
        const uint32_t z = sb + OFF_BLK + k * BLK + t7 * 16;
        sts128(z + B_TBL, 0, 0, 0, 0); sts128(z + B_TBL + 2048, 0, 0, 0, 0);
      }
      sts128(sb + OFF_BLK + (t7 < 64 ? (t7 >> 4) * BLK - 256 + (t7 & 15) * 16 : 4 * BLK - 2048 + t7 * 16), 0, 0, 0, 0);
      const uint32_t ea = sb + OFF_BLK + (2 + (w4 & 1)) * BLK + (lane >> 4) * 7168 + ((lane >> 3) & 1) * 256 + (lane & 7) * 16 + (w4 >> 1) * 2048;
      constexpr uint64_t dE = mkdesc(SB0 + OFF_BLK + 2 * BLK, 128, 512, 0);
      const uint32_t xa = sb + OFF_BLK + 18560 + t7 * 8, xr_ = sb + OFF_BLK + 18560 + (t7 ^ 64) * 8;
      uint32_t pr[5][2];
      #pragma unroll
      for (int q = 0; q < 5; q++) {
        #pragma unroll
        for (int e = 0; e < 2; e++) pr[q][e] = raw[q][2 * e] | (raw[q][2 * e + 1] << 16);
        const uint32_t m = __reduce_max_sync(0xffffffff, max(raw[q][2] & 0x7fffu, raw[q][3] & 0x7fffu));
        if (lane == 0) sts32(sb + OFF_EPOCH + 64 + q * 16 + w4 * 4, m);
      }
      bar_sync(4, 128);
      if (t7 == 0) TS(40);
      const int j = (w4 & 1) * 16 + (w4 >> 1) * 8 + g, i2 = tq < 2 ? 64 * tq + j : 32 * (tq - 2) + j;
      const uint32_t e2 = B_TBL + 4 * (tq < 2 ? T_F3 + (((i2 - 1) & 1) ? 80 : 0) + ((i2 - 1) >> 1) + 16 : T_F2 + (i2 & 1) * 96 + (i2 >> 1));
      const uint32_t e1 = tq < 2 ? (i2 ? e2 - 64 : B_TBL + 4 * (T_F2 + 175)) : B_TBL + 4 * (i2 ? T_F2 + ((2 * i2 - 1) & 3) * 48 + ((2 * i2 - 1) >> 2) : 16 + 511);
      const uint32_t e0 = B_TBL + (16 + 8 * j + 2 * tq) * 4;
      #pragma unroll 1
      for (int it = 0; it < 5; it++) {
        const int k = it;
        const uint32_t blk = sb + OFF_BLK + k * BLK;
        float fac;
        {
          const int q = it;
          if (it == 4) {
            mbar_wait(BAR(BR_UOUT), 0);
            sts128(sb + OFF_UT + B_TBL + t7 * 16, 0, 0, 0, 0); sts128(sb + OFF_UT + B_TBL + 2048 + t7 * 16, 0, 0, 0, 0);
          }
          const uint32_t ga = ea + 4096 - (w4 >> 1) * 512;
#define PUT4(i, a, b, c_, d) sts128(((i) < 8 ? ea + ((i) >> 1) * 512 : ga + (((i) - 8) >> 1) * 512) + ((i) & 1) * 128, a, b, c_, d)
          const uint32_t pa0 = pr[0][0], pc0 = pr[0][1];
          const float dt = bf_round(expf(bf_lo(__shfl_sync(0xffffffff, pd, q))));
          #pragma unroll
          for (int e = 0; e < 2; e++) { pr[0][e] = pr[1][e]; pr[1][e] = pr[2][e]; pr[2][e] = pr[3][e]; pr[3][e] = pr[4][e]; }
          uint32_t mm[4];
          lds128(mm, sb + OFF_EPOCH + 64 + q * 16);
          const uint32_t ex = min(max(max(max(mm[0], mm[1]), max(mm[2], mm[3])) >> 7, 1u), 253u);
          const float sc = __uint_as_float((254u - ex) << 23);
          fac = 2.f * dt * __uint_as_float(ex << 23);
          const float lr = -bf_round(expf(bf_lo(pa0))) * dt * 1.44269504089f;
          const float tn = bf_hi(pa0) * dt * 0.15915494309f;
          float z1r, z1i, z2r, z2i, z4r, z4i, xr[8], xi[8], gr[8], gi[8], wr[9], wi[9];
          cexp_t(lr, -tn, z1r, z1i);
          cexp_t(lr * 8.f, tn * 8.f, xr[1], xi[1]);
          cexp_t(lr * 64.f, tn * 64.f, wr[0], wi[0]);
          xr[0] = 1.f; xi[0] = 0.f;
          cmul(xr[1], xi[1], xr[1], xi[1], xr[2], xi[2]); cmul(xr[2], xi[2], xr[1], xi[1], xr[3], xi[3]);
          cmul(xr[2], xi[2], xr[2], xi[2], xr[4], xi[4]);
          #pragma unroll
          for (int b = 1; b < 4; b++) cmul(xr[4], xi[4], xr[b], xi[b], xr[4 + b], xi[4 + b]);
          cmul(wr[0], wi[0], wr[0], wi[0], wr[1], wi[1]); cmul(wr[1], wi[1], wr[0], wi[0], wr[2], wi[2]);
          cmul(wr[1], wi[1], wr[1], wi[1], wr[3], wi[3]); cmul(wr[3], wi[3], wr[3], wi[3], wr[4], wi[4]);
          cmul(wr[4], wi[4], wr[3], wi[3], wr[5], wi[5]); cmul(wr[4], wi[4], wr[4], wi[4], wr[6], wi[6]);
          cmul(wr[6], wi[6], wr[4], wi[4], wr[7], wi[7]); cmul(wr[6], wi[6], wr[6], wi[6], wr[8], wi[8]);
          uint32_t R[4], I[4], PR[4], PI[4];
          #pragma unroll
          for (int b = 0; b < 4; b++) { R[b] = packh(xr[2 * b], xr[2 * b + 1]); I[b] = packh(xi[2 * b], xi[2 * b + 1]); }
          PUT4(0, R[0], R[1], R[2], R[3]); PUT4(1, I[0], I[1], I[2], I[3]);
          #pragma unroll
          for (int i = 0; i < 3; i++) {
            const uint32_t z = packh(wr[i], wi[i]);
            #pragma unroll
            for (int b = 0; b < 4; b++) hcm2(R[b], I[b], z, PR[b], PI[b]);
            PUT4(2 * i + 2, PR[0], PR[1], PR[2], PR[3]); PUT4(2 * i + 3, PI[0], PI[1], PI[2], PI[3]);
          }
          gr[0] = bf_lo(pc0) * sc; gi[0] = -bf_hi(pc0) * sc;
          cmul(z1r, z1i, z1r, z1i, z2r, z2i); cmul(z2r, z2i, z2r, z2i, z4r, z4i);
          cmul(gr[0], gi[0], z1r, z1i, gr[1], gi[1]);
          cmul(gr[0], gi[0], z2r, z2i, gr[2], gi[2]); cmul(gr[1], gi[1], z2r, z2i, gr[3], gi[3]);
          #pragma unroll
          for (int b = 0; b < 4; b++) cmul(gr[b], gi[b], z4r, z4i, gr[4 + b], gi[4 + b]);
          PUT4(8, packh(gr[0], gr[1]), packh(gr[2], gr[3]), packh(gr[4], gr[5]), packh(gr[6], gr[7]));
          PUT4(9, packh(gi[0], gi[1]), packh(gi[2], gi[3]), packh(gi[4], gi[5]), packh(gi[6], gi[7]));
          {
            const uint32_t z = packh(wr[3], -wi[3]), a4r = packh(gr[0], gr[4]), a4i = packh(gi[0], gi[4]);
            hcm2(packh(gr[0], gr[2]), packh(gi[0], gi[2]), z, PR[0], PI[0]);
            hcm2(packh(gr[4], gr[6]), packh(gi[4], gi[6]), z, PR[1], PI[1]);
            hcm2(a4r, a4i, packh(wr[4], -wi[4]), PR[2], PI[2]);
            hcm2(a4r, a4i, packh(wr[5], -wi[5]), PR[3], PI[3]);
            PUT4(10, PR[0], PR[1], PR[2], PR[3]); PUT4(11, PI[0], PI[1], PI[2], PI[3]);
            float hr, hi_;
            cmul(gr[0], gi[0], wr[3], -wi[3], hr, hi_);
            const uint32_t cr = packh(gr[0], hr), ci = packh(gi[0], hi_);
            #pragma unroll
            for (int i = 0; i < 3; i++) hcm2(cr, ci, packh(wr[6 + i], -wi[6 + i]), PR[i], PI[i]);
            PUT4(12, PR[0], PR[1], PR[2], 0u); PUT4(13, PI[0], PI[1], PI[2], 0u);
          }
          fence_async();
          bar_sync(4, 128);
        }
        float ka[24]; zero<24>(ka);
        wg_fence();
        #pragma unroll
        for (int s = 0; s < 8; s++) {
          const uint64_t d = dE + (s >> 2) * (BLK >> 4) + ((s >> 1) & 1) * 448 + (s & 1) * 16;
          wg_ss48_tt_h(ka, d, d + 256, s != 0);
        }
        wg_commit();
        const float dsk = bf_lo(__shfl_sync(0xffffffff, pd, 8 + it));
        wg_wait<0>();
        pin<24>(ka);
        float kk[6];
        const bool up = w4 >= 2;
        #pragma unroll
        for (int n = 0; n < 3; n++) {
          sts64f(xa + n * BLK, up ? ka[12 + 4 * n] : ka[4 * n + 2], up ? ka[13 + 4 * n] : ka[4 * n + 3]);
          kk[2 * n] = up ? ka[14 + 4 * n] : ka[4 * n]; kk[2 * n + 1] = up ? ka[15 + 4 * n] : ka[4 * n + 1];
        }
        if (it) bar_sync(4, 128); else bar_sync(8, 160);
          if (it == 4 && w4 == 0) {
            mbar_wait(BAR(BR_U), 0);
            if (elect_one()) {
              mbar_expect_tx(BAR(BR_U2), 8192);
              bulk_ld(blk - 2 * BLK, g_uy + (c * 80 + r * 5 + 2) * 2048, 4096, BAR(BR_U2)); bulk_ld(blk - BLK, g_uy + (c * 80 + r * 5 + 3) * 2048, 4096, BAR(BR_U2));
            }
            __syncwarp();
          }
        #pragma unroll
        for (int n = 0; n < 3; n++) {
          uint32_t o[2]; lds64(o, xr_ + n * BLK);
          kk[2 * n] = (kk[2 * n] + __uint_as_float(o[0])) * fac; kk[2 * n + 1] = (kk[2 * n + 1] + __uint_as_float(o[1])) * fac;
        }
        if (t7 == 0) kk[0] += dsk;
        {
          const uint32_t v = pack2(kk[1], kk[0]), vh = v >> 16;
          const uint32_t u = pack2(kk[2], kk[3]), w = pack2(kk[4], kk[5]), uu = pack2(kk[2], kk[2]), us = pack2(kk[3], kk[2]);
          const uint32_t x = tq < 2 ? w : u, xh = x >> 16;
          sts32(blk + e0 + 4, v); sts16(blk + e0, vh); sts16(blk + e0 + 10, v);
          sts16(blk + e1, x); sts16(blk + e1 + 6, x); sts16(blk + e2, xh); sts16(blk + e2 + 6, xh);
          if (tq < 2) {
            const uint32_t pb = blk + e0 + 1024 + 8 * tq;
            sts32(pb + 4, uu); sts32(pb + 8, us); sts16(pb + 14, us);
            if (i2) { sts16(pb - 4, u); sts32(pb, uu); }
          }
          if (i2 == 0) {
            const uint32_t tb = blk + B_TBL;
            if (tq == 0) { sts16(tb + (16 + 256) * 4, u); sts16(tb + (T_S + 3) * 4, w); sts32(tb + (T_S + 4) * 4, pack2(kk[4], kk[4])); sts16(tb + (T_S + 5) * 4 + 2, w); }
            else { sts32(tb + 528 * 4, uu); sts32(tb + 529 * 4, uu); sts32(tb + 530 * 4, uu); sts16(tb + 531 * 4 + 2, u); sts16(tb + (T_F3 + 80 + 63) * 4, w); }
          }
        }
        if (t7 == 0) TS(49 + it);
      }
    }
    asm volatile("setmaxnreg.inc.sync.aligned.u32 136;");
    if (t7 == 0) TS(41);
    mbar_wait(BAR(BR_U), 0);
    bar_sync(4, 128);
    if (t7 == 0) mbar_arrive(BAR(BR_KS));
    if (EN_ATT) mbar_wait(BAR(BR_GEMM), 0);
    if (t7 == 0) TS(42);
    mbar_wait(BAR(BR_EPOCH), 0);
    const uint32_t ytag = (lds32(sb + OFF_EPOCH) & 1u) * 0x10001u, ym = lane < 4 ? 0x10001u : 0u;
    const int kl0 = 2 * (lane & 7) + ((lane >> 3) & 1), ih = (lane >> 3) & 1;
    {
      const int k = w4;
      if (k & 2) mbar_wait(BAR(BR_U2), 0);
      const uint32_t blk = sb + OFF_BLK + k * BLK, tb = blk + B_TBL + (uint32_t)((g - 2 * tq) * 4);
      float acc[16][4];
      zero<64>(&acc[0][0]);
      const int kl = 16 * (lane >> 4) + kl0;
      {
        auto ubase = [&](int sh) { const int q = kl - 2 * sh; return blk + (uint32_t)((q * 16) ^ ((q * 2) & 0x10)); };
#define LDQ(A, sh) _Pragma("unroll") for (int m = 0; m < 4; m++) load_quad(A[m], tb + (16 + 16 * (sh) + 128 * m) * 4);
#define LDB(B, ub, h) _Pragma("unroll") for (int p = 0; p < 4; p++) ldsm4(B[p], (ub) + (4 * (h) + p) * 512);
#define MLO(A, B) _Pragma("unroll") for (int m = 0; m < 4; m++) _Pragma("unroll") for (int cc = 0; cc < 8; cc++) mma16816(acc[cc + m], A[m], &B[cc >> 1][(cc & 1) * 2]);
#define MHI(A, B) _Pragma("unroll") for (int m = 0; m < 4; m++) _Pragma("unroll") for (int cc = 0; cc < 8 - m; cc++) mma16816(acc[8 + cc + m], A[m], &B[cc >> 1][(cc & 1) * 2]);
        int p_ = 0;
        uint32_t A[4][4], A2[4][4], Bl[4][4], Bh[4][4];
        uint32_t ub = ubase(p_ + 4);
        LDQ(A, p_ + 4) LDB(Bl, ub, 0)
        #pragma unroll 1
        for (; p_ < 4; p_++) {
          LDB(Bh, ub, 1)
          MLO(A, Bl)
          ub = ubase(p_);
          LDQ(A2, p_) LDB(Bl, ub, 0)
          MHI(A, Bh)
          LDB(Bh, ub, 1)
          load_quad(A[0], tb + (16 + 512 + 16 * (p_ & 1)) * 4); load_quad(A[1], tb + (T_S + 16 * (p_ & 1)) * 4);
          MLO(A2, Bl)
          if (p_ < 2) {
            #pragma unroll
            for (int cc = 0; cc < 8; cc++) mma16816(acc[cc + 4], A[0], &Bl[cc >> 1][(cc & 1) * 2]);
            #pragma unroll
            for (int cc = 0; cc < 4; cc++) mma16816(acc[cc + 12], A[0], &Bh[cc >> 1][(cc & 1) * 2]);
            #pragma unroll
            for (int cc = 0; cc < 8; cc++) mma16816(acc[cc + 8], A[1], &Bl[cc >> 1][(cc & 1) * 2]);
          }
          const int pn = ((p_ + 1) & 3) + 4;
          ub = ubase(pn);
          LDQ(A, pn) LDB(Bl, ub, 0)
          MHI(A2, Bh)
        }
      }
      if (t7 == 0) TS(60);
      mbar_wait(BAR(BR_DRDY + 1), 0);
      {
        const uint32_t dl = blk + B_D + (uint32_t)(((lane >> 4) * 8 + (lane & 7)) * 16);
        const uint32_t d0_ = dl + ih * 1552, d8_ = dl + (ih ? 0 : 1536), d3_ = dl + B_D7 + ih * 1024;
        auto cls2 = [&](uint32_t da, uint32_t ta) {
          uint32_t B[6][2], A[6][4];
          #pragma unroll
          for (int e = 0; e < 6; e++) { B[e][0] = lds32v(ta + (e + 4) * 32); B[e][1] = lds32v(ta + (e + 3) * 32); }
          #pragma unroll
          for (int kk = 0; kk < 6; kk++) ldsm4t(A[kk], da + kk * 256);
          #pragma unroll
          for (int e = 0; e < 6; e++)
            #pragma unroll
            for (int kk = 0; kk < 6; kk++) if (2 * kk + e + 4 < 16) mma16816(acc[2 * kk + e + 4], A[kk], B[e]);
        };
        auto cls3 = [&](uint32_t da, uint32_t ta) {
          uint32_t B[8][2], A[4][4];
          #pragma unroll
          for (int e = 0; e < 8; e++) { B[e][0] = lds32v(ta + (e + 8) * 32); B[e][1] = lds32v(ta + (e + 7) * 32); }
          #pragma unroll
          for (int kk = 0; kk < 4; kk++) ldsm4t(A[kk], da + kk * 256);
          #pragma unroll
          for (int kk = 0; kk < 4; kk++)
            #pragma unroll
            for (int e = 0; e < 8; e++) if (2 * kk + e + 8 < 16) mma16816(acc[2 * kk + e + 8], A[kk], B[e]);
        };
        #pragma unroll 1
        for (int a = 0; a < 2; a++) {
          cls2(d0_ + a * B_D5, tb + (T_F2 + 48 * a - 32) * 4);
          cls2(d8_ + a * B_D5, tb + (T_F2 + 48 * a + 64) * 4);
          cls3(d3_ + a * 2048, tb + (T_F3 + 80 * a - 64) * 4);
        }
      }
      if (t7 == 0) TS(61);
      const uint32_t ya = blk + (uint32_t)((kl * 16) ^ ((kl * 2) & 0x10));
#define STY(p) stsm4t(ya + (p) * 512, YTAG(pack2(acc[2 * (p)][0], acc[2 * (p)][1])), pack2(acc[2 * (p)][2], acc[2 * (p)][3]), \
                      YTAG(pack2(acc[2 * (p) + 1][0], acc[2 * (p) + 1][1])), pack2(acc[2 * (p) + 1][2], acc[2 * (p) + 1][3]))
      __syncwarp();
      #pragma unroll
      for (int p = 0; p < 8; p++) STY(p);
      fence_async();
      __syncwarp();
      if (lane == 0) mbar_arrive(BAR(BR_Y));
      if (t7 == 0) TS(62);
    }
    if (t7 == 0) DUMP(40, 64);
    #pragma unroll 1
    for (int n = 0; n < 64; n++) if (!y_transpose(sb, w4, lane, ytag)) break;
    }
  }
}

typedef CUresult (*EncFn)(CUtensorMap*, CUtensorMapDataType, cuuint32_t, void*, const cuuint64_t*, const cuuint64_t*, const cuuint32_t*,
                          const cuuint32_t*, CUtensorMapInterleave, CUtensorMapSwizzle, CUtensorMapL2promotion, CUtensorMapFloatOOBfill);
static void mkmap(EncFn enc, CUtensorMap* m, const void* base, int rank, const cuuint64_t* dims, const cuuint64_t* strides, const cuuint32_t* box, CUtensorMapSwizzle swz) {
  cuuint32_t es[5] = {1, 1, 1, 1, 1};
  enc(m, CU_TENSOR_MAP_DATA_TYPE_BFLOAT16, rank, const_cast<void*>(base), dims, strides, box, es, CU_TENSOR_MAP_INTERLEAVE_NONE, swz,
      CU_TENSOR_MAP_L2_PROMOTION_L2_128B, CU_TENSOR_MAP_FLOAT_OOB_FILL_NONE);
}

extern "C" void kernel_launch(void* const* d_in, const int* in_sizes, int n_in, void* d_out, int out_size) {
  void* fn = nullptr; cudaDriverEntryPointQueryResult qr;
  cudaGetDriverEntryPoint("cuTensorMapEncodeTiled", &fn, cudaEnableDefault, &qr);
  EncFn enc = (EncFn)fn;
  void* uy = nullptr; cudaGetSymbolAddress(&uy, g_uy);
  const cuuint64_t dx[2] = {640, 2048}, sx[1] = {1280};
  const cuuint32_t bx[2] = {64, 128}, bu[2] = {80, 128};
  const cuuint64_t dw[3] = {640, 640, 3}, sw[2] = {3840, 1280};
  const cuuint32_t br[3] = {16, 32, 3};
  const cuuint64_t dwa[4] = {64, 640, 10, 3}, swa[3] = {3840, 128, 1280}, dwb[4] = {32, 640, 20, 3}, swb[3] = {3840, 64, 1280};
  const cuuint32_t bwa[4] = {64, 32, 1, 3}, bwb[4] = {32, 32, 2, 3};
  const cuuint64_t dwo[2] = {640, 640};
  const cuuint32_t bwo[2] = {64, 80}, bo64[2] = {64, 64}, bo16[2] = {16, 64};
  const cuuint64_t dsa[2] = {2048, 1280}, ssa[1] = {4096};
  const cuuint32_t bsa[2] = {64, 80};
  const cuuint64_t dout[2] = {1280, 2048}, sout[1] = {2560};
  Params prm;
  mkmap(enc, &prm.m[M_X], d_in[7], 2, dx, sx, bx, CU_TENSOR_MAP_SWIZZLE_128B);
  mkmap(enc, &prm.m[M_W128], d_in[8], 4, dwa, swa, bwa, CU_TENSOR_MAP_SWIZZLE_128B);
  mkmap(enc, &prm.m[M_W64], d_in[8], 4, dwb, swb, bwb, CU_TENSOR_MAP_SWIZZLE_64B);
  mkmap(enc, &prm.m[M_WR], d_in[8], 3, dw, sw, br, CU_TENSOR_MAP_SWIZZLE_32B);
  mkmap(enc, &prm.m[M_U], d_in[0], 2, dx, sx, bu, CU_TENSOR_MAP_SWIZZLE_NONE);
  mkmap(enc, &prm.m[M_WO], d_in[9], 2, dwo, sx, bwo, CU_TENSOR_MAP_SWIZZLE_128B);
  mkmap(enc, &prm.m[M_O64], d_out, 2, dout, sout, bo64, CU_TENSOR_MAP_SWIZZLE_128B);
  mkmap(enc, &prm.m[M_O16], d_out, 2, dout, sout, bo16, CU_TENSOR_MAP_SWIZZLE_NONE);
  mkmap(enc, &prm.m[M_SA], uy, 2, dsa, ssa, bsa, CU_TENSOR_MAP_SWIZZLE_128B);
  mkmap(enc, &prm.m[M_OUT], d_out, 2, dout, sout, bu, CU_TENSOR_MAP_SWIZZLE_NONE);
  prm.u = (const __nv_bfloat16*)d_in[0]; prm.wo = (const __nv_bfloat16*)d_in[9];
  for (int i = 0; i < 4; i++) prm.par[i] = (const __nv_bfloat16*)d_in[1 + i];
  prm.logdt = (const __nv_bfloat16*)d_in[5]; prm.dskip = (const __nv_bfloat16*)d_in[6];
  cudaFuncSetAttribute(fused_kernel, cudaFuncAttributeMaxDynamicSharedMemorySize, SMEM_BYTES);
  cudaLaunchConfig_t cfg = {};
  cfg.gridDim = dim3(128); cfg.blockDim = dim3(512); cfg.dynamicSmemBytes = SMEM_BYTES; cfg.stream = cudaStreamPerThread;
  cudaLaunchAttribute at[1];
  at[0].id = cudaLaunchAttributeClusterDimension; at[0].val.clusterDim.x = 2; at[0].val.clusterDim.y = 1; at[0].val.clusterDim.z = 1;
  cfg.attrs = at; cfg.numAttrs = 1;
  cudaLaunchKernelEx(&cfg, fused_kernel, prm);
}
```

```cpp
#include <cuda_runtime.h>
#include <cuda_bf16.h>
#include <cuda_fp16.h>
#include <cuda.h>
#include <stdint.h>

#define KST 2
#define UKB 4
#define UPF 0
#define CONV_AT 1
#define EN_ATT 1
#define EN_SSM 1

__device__ __align__(1024) __nv_bfloat16 g_uy[2 * 640 * 2048];
__device__ __align__(128) uint4 g_kvp[8 * 16 * 240];
__device__ __align__(128) uint4 g_o[128 * 1280];
__device__ __align__(128) unsigned g_flag[4 * 128 * 32];
__device__ unsigned g_epoch[128];
#define TS(i) do {} while (0)
#define DUMP(lo, hi) do {} while (0)
#define FIXCNT

constexpr uint32_t SB0 = 1024;
constexpr uint32_t W_SLOT = 15360, OFF_X = 76800;
constexpr uint32_t OFF_WOR = 81920, OFF_KVP = 10240, OFF_KVS = 71680, OFF_PK = 10240, OFF_V = 30720, OFF_EXTRA = 102400, OFF_KVB = OFF_EXTRA;
constexpr uint32_t OFF_BAR = 125952, OFF_BLK = 128000, BLK = 20480;
constexpr uint32_t B_D = 4096, B_D3 = 3072, B_D9 = 6144, B_D7 = 8192, B_TBL = 14336, B_SP = 18624;
constexpr int T_0 = 32, T_A = 616, T_B = 744, T_C = 872, T_D = 1000;
constexpr uint32_t OFF_UT = OFF_BLK + 4 * BLK;
constexpr uint32_t SMEM_BYTES = OFF_BLK + 5 * BLK;
enum { BR_FULL = 0, BR_WO = 5, BR_PUB = 7, BR_KVP = 8, BR_U = 9, BR_SUM = 10, BR_GEMM = 11, BR_UIN = 12, BR_YIN = 13, BR_EPOCH = 14,
       BR_RETRY = 15, BR_UOUT = 16, BR_OFULL = 16, BR_KS = 24, BR_U2 = 25, BR_FREE = 26, BR_EMPTY = 31, BR_OEMPTY = 36, BR_OSTG = 43,
       BR_DRDY = 44, BR_Y = 46, BR_COUNT = 52 };
constexpr uint32_t OFF_EPOCH = OFF_BAR + 8 * BR_COUNT;
enum { M_X, M_W128, M_W64, M_WR, M_U, M_WO, M_O64, M_O16, M_SA, M_OUT, M_COUNT };

__device__ __forceinline__ long long clk64() { long long t; asm volatile("mov.u64 %0, %%clock64;" : "=l"(t) :: "memory"); return t; }
__device__ __forceinline__ uint32_t smem_u32(const void* p) { return (uint32_t)__cvta_generic_to_shared(p); }
__host__ __device__ constexpr uint64_t mkdesc(uint32_t addr, uint32_t lbo, uint32_t sbo, uint32_t swz) {
  return (uint64_t)((addr & 0x3FFFF) >> 4) | ((uint64_t)(lbo >> 4) << 16) | ((uint64_t)(sbo >> 4) << 32) | ((uint64_t)swz << 62);
}
__device__ __forceinline__ uint64_t desc2(uint32_t lo, uint32_t hi) { uint64_t d; asm("mov.b64 %0, {%1, %2};" : "=l"(d) : "r"(lo), "r"(hi)); return d; }
__device__ __forceinline__ void mbar_init(uint32_t bar, uint32_t cnt) { asm volatile("mbarrier.init.shared::cta.b64 [%0], %1;" :: "r"(bar), "r"(cnt) : "memory"); }
__device__ __forceinline__ void mbar_expect_tx(uint32_t bar, uint32_t bytes) { asm volatile("mbarrier.arrive.expect_tx.shared::cta.b64 _, [%0], %1;" :: "r"(bar), "r"(bytes) : "memory"); }
__device__ __forceinline__ void mbar_arrive(uint32_t bar) { asm volatile("mbarrier.arrive.shared::cta.b64 _, [%0];" :: "r"(bar) : "memory"); }
__device__ __forceinline__ void mbar_wait(uint32_t bar, uint32_t parity) {
  asm volatile("{\n.reg .pred p;\n.reg .u32 c;\nmov.u32 c, 0;\n"
    "WL:\nmbarrier.try_wait.parity.shared::cta.b64 p, [%0], %1;\n@p bra WD;\n"
    "add.u32 c, c, 1;\nsetp.lt.u32 p, c, 200000;\n@p bra WL;\nWD:\n}" :: "r"(bar), "r"(parity) : "memory");
}
__device__ __forceinline__ void poll_all(const unsigned* p, unsigned val) {
  asm volatile("{\n.reg .pred p;\n.reg .u32 c, v;\nmov.u32 c, 0;\n"
    "PL:\nld.relaxed.gpu.global.u32 v, [%0];\nsetp.eq.u32 p, v, %1;\nvote.sync.all.pred p, p, 0xffffffff;\n@p bra PD;\n"
    "add.u32 c, c, 1;\nsetp.lt.u32 p, c, 100000;\n@p bra PL;\nPD:\n}" :: "l"(p), "r"(val) : "memory");
}
__device__ __forceinline__ void poll_all_acq(const unsigned* p, unsigned val) {
  asm volatile("{\n.reg .pred p;\n.reg .u32 c, v;\nmov.u32 c, 0;\n"
    "PL:\nld.acquire.gpu.global.u32 v, [%0];\nsetp.eq.u32 p, v, %1;\nvote.sync.all.pred p, p, 0xffffffff;\n@p bra PD;\n"
    "nanosleep.u32 300;\nadd.u32 c, c, 1;\nsetp.lt.u32 p, c, 100000;\n@p bra PL;\nPD:\n}" :: "l"(p), "r"(val) : "memory");
}
__device__ __forceinline__ unsigned poll_bit(const unsigned* p, unsigned val, unsigned mask) {
  unsigned bal;
  asm volatile("{\n.reg .pred p;\n.reg .u32 c, v;\nmov.u32 c, 0;\n"
    "PL:\nld.relaxed.gpu.global.u32 v, [%1];\nsetp.eq.u32 p, v, %2;\nvote.sync.ballot.b32 %0, p, 0xffffffff;\n"
    "and.b32 v, %0, %3;\nsetp.ne.u32 p, v, 0;\n@p bra PD;\n"
    "add.u32 c, c, 1;\nsetp.lt.u32 p, c, 100000;\n@p bra PL;\nPD:\n}" : "=&r"(bal) : "l"(p), "r"(val), "r"(mask) : "memory");
  return bal;
}
__device__ __forceinline__ void fix128_w0(uint32_t* v, const void* p, uint32_t tag, uint32_t mask) {
  asm volatile("{\n.reg .pred p;\n.reg .u32 c, x;\n.reg .b128 t;\n.reg .b64 lo, hi;\nmov.u32 c, 0;\n"
    "FL:\nxor.b32 x, %0, %5;\nand.b32 x, x, %6;\nsetp.eq.u32 p, x, 0;\n@p bra FD;\n"
    "ld.relaxed.gpu.global.b128 t, [%4];\nmov.b128 {lo, hi}, t;\nmov.b64 {%0, %1}, lo;\nmov.b64 {%2, %3}, hi;\n"
    "add.u32 c, c, 1;\nsetp.lt.u32 p, c, 100000;\n@p bra FL;\nFD:\n}"
    : "+r"(v[0]), "+r"(v[1]), "+r"(v[2]), "+r"(v[3]) : "l"(p), "r"(tag), "r"(mask) : "memory");
}
__device__ __forceinline__ void fix128_w3(uint32_t* v, const void* p, uint32_t tag, uint32_t mask) {
  asm volatile("{\n.reg .pred p;\n.reg .u32 c, x;\n.reg .b128 t;\n.reg .b64 lo, hi;\nmov.u32 c, 0;\n"
    "FL:\nxor.b32 x, %3, %5;\nand.b32 x, x, %6;\nsetp.eq.u32 p, x, 0;\n@p bra FD;\n"
    "ld.relaxed.gpu.global.b128 t, [%4];\nmov.b128 {lo, hi}, t;\nmov.b64 {%0, %1}, lo;\nmov.b64 {%2, %3}, hi;\n"
    "add.u32 c, c, 1;\nsetp.lt.u32 p, c, 100000;\n@p bra FL;\nFD:\n}"
    : "+r"(v[0]), "+r"(v[1]), "+r"(v[2]), "+r"(v[3]) : "l"(p), "r"(tag), "r"(mask) : "memory");
}
__device__ __forceinline__ void fence_acq() { asm volatile("fence.acq_rel.gpu;" ::: "memory"); }
__device__ __forceinline__ bool elect_one() {
  uint32_t p; asm volatile("{\n.reg .pred P;\nelect.sync _|P, 0xffffffff;\nselp.u32 %0, 1, 0, P;\n}" : "=r"(p)); return p;
}
__device__ __forceinline__ void bar_sync(int id, int n) { asm volatile("bar.sync %0, %1;" :: "r"(id), "r"(n) : "memory"); }
__device__ __forceinline__ void fence_async() { asm volatile("fence.proxy.async.shared::cta;" ::: "memory"); }
__device__ __forceinline__ void fence_async_g() { asm volatile("fence.proxy.async.global;" ::: "memory"); }
__device__ __forceinline__ void tma2d(uint32_t dst, const CUtensorMap* m, uint32_t bar, int c0, int c1) {
  asm volatile("cp.async.bulk.tensor.2d.shared::cluster.global.mbarrier::complete_tx::bytes [%0], [%1, {%3, %4}], [%2];"
    :: "r"(dst), "l"(m), "r"(bar), "r"(c0), "r"(c1) : "memory");
}
__device__ __forceinline__ void tma3d(uint32_t dst, const CUtensorMap* m, uint32_t bar, int c0, int c1, int c2) {
  asm volatile("cp.async.bulk.tensor.3d.shared::cluster.global.mbarrier::complete_tx::bytes [%0], [%1, {%3, %4, %5}], [%2];"
    :: "r"(dst), "l"(m), "r"(bar), "r"(c0), "r"(c1), "r"(c2) : "memory");
}
__device__ __forceinline__ void tma4d(uint32_t dst, const CUtensorMap* m, uint32_t bar, int c0, int c1, int c2, int c3) {
  asm volatile("cp.async.bulk.tensor.4d.shared::cluster.global.mbarrier::complete_tx::bytes [%0], [%1, {%3, %4, %5, %6}], [%2];"
    :: "r"(dst), "l"(m), "r"(bar), "r"(c0), "r"(c1), "r"(c2), "r"(c3) : "memory");
}
__device__ __forceinline__ void tma2d_st(const CUtensorMap* m, uint32_t src, int c0, int c1) {
  asm volatile("cp.async.bulk.tensor.2d.global.shared::cta.bulk_group [%0, {%2, %3}], [%1];"
    :: "l"(m), "r"(src), "r"(c0), "r"(c1) : "memory");
}
__device__ __forceinline__ void bulk_ld(uint32_t dst, const void* src, uint32_t bytes, uint32_t bar) {
  asm volatile("cp.async.bulk.shared::cluster.global.mbarrier::complete_tx::bytes [%0], [%1], %2, [%3];"
    :: "r"(dst), "l"(src), "r"(bytes), "r"(bar) : "memory");
}
__device__ __forceinline__ void bulk_st(void* dst, uint32_t src, uint32_t bytes) {
  asm volatile("cp.async.bulk.global.shared::cta.bulk_group [%0], [%1], %2;" :: "l"(dst), "r"(src), "r"(bytes) : "memory");
}
__device__ __forceinline__ void bulk_commit() { asm volatile("cp.async.bulk.commit_group;" ::: "memory"); }
__device__ __forceinline__ void bulk_wait0() { asm volatile("cp.async.bulk.wait_group 0;" ::: "memory"); }
__device__ __forceinline__ void bulk_wait0_read() { asm volatile("cp.async.bulk.wait_group.read 0;" ::: "memory"); }
__device__ __forceinline__ unsigned ld_rlx(const unsigned* p) { unsigned v; asm volatile("ld.relaxed.gpu.global.u32 %0, [%1];" : "=r"(v) : "l"(p) : "memory"); return v; }
__device__ __forceinline__ unsigned ld_acq(const unsigned* p) { unsigned v; asm volatile("ld.acquire.gpu.global.u32 %0, [%1];" : "=r"(v) : "l"(p) : "memory"); return v; }
__device__ __forceinline__ void st_rlx(unsigned* p, unsigned v) { asm volatile("st.relaxed.gpu.global.u32 [%0], %1;" :: "l"(p), "r"(v) : "memory"); }
__device__ __forceinline__ void st_rel(unsigned* p, unsigned v) { asm volatile("st.release.gpu.global.u32 [%0], %1;" :: "l"(p), "r"(v) : "memory"); }
__device__ __forceinline__ void ld128_rlx(uint32_t* v, const void* p) {
  asm volatile("{\n.reg .b128 t;\n.reg .b64 lo, hi;\nld.relaxed.gpu.global.b128 t, [%4];\nmov.b128 {lo, hi}, t;\n"
    "mov.b64 {%0, %1}, lo;\nmov.b64 {%2, %3}, hi;\n}" : "=r"(v[0]), "=r"(v[1]), "=r"(v[2]), "=r"(v[3]) : "l"(p) : "memory");
}
__device__ __forceinline__ void st128_rlx(void* p, const uint32_t* v) {
  asm volatile("{\n.reg .b128 t;\n.reg .b64 lo, hi;\nmov.b64 lo, {%1, %2};\nmov.b64 hi, {%3, %4};\nmov.b128 t, {lo, hi};\n"
    "st.relaxed.gpu.global.b128 [%0], t;\n}" :: "l"(p), "r"(v[0]), "r"(v[1]), "r"(v[2]), "r"(v[3]) : "memory");
}
__device__ __forceinline__ uint32_t lds32(uint32_t a) { uint32_t v; asm volatile("ld.shared.u32 %0, [%1];" : "=r"(v) : "r"(a) : "memory"); return v; }
__device__ __forceinline__ uint32_t lds32v(uint32_t a) { uint32_t v; asm volatile("ld.volatile.shared.u32 %0, [%1];" : "=r"(v) : "r"(a) : "memory"); return v; }
__device__ __forceinline__ uint32_t cpa(uint32_t a, uint32_t one) { uint32_t v; asm volatile("mul.lo.u32 %0, %1, %2;" : "=r"(v) : "r"(a), "r"(one)); return v; }
__device__ __forceinline__ uint32_t cpb(uint32_t a, uint32_t zero) { uint32_t v; asm volatile("or.b32 %0, %1, %2;" : "=r"(v) : "r"(a), "r"(zero)); return v; }
__device__ __forceinline__ uint32_t lds16(uint32_t a) { uint16_t v; asm volatile("ld.shared.u16 %0, [%1];" : "=h"(v) : "r"(a) : "memory"); return v; }
__device__ __forceinline__ float ldsf(uint32_t a) { float v; asm volatile("ld.shared.f32 %0, [%1];" : "=f"(v) : "r"(a) : "memory"); return v; }
__device__ __forceinline__ void lds128(uint32_t* v, uint32_t a) { asm volatile("ld.shared.v4.u32 {%0,%1,%2,%3}, [%4];" : "=r"(v[0]), "=r"(v[1]), "=r"(v[2]), "=r"(v[3]) : "r"(a) : "memory"); }
__device__ __forceinline__ void sts32(uint32_t a, uint32_t v) { asm volatile("st.shared.u32 [%0], %1;" :: "r"(a), "r"(v) : "memory"); }
__device__ __forceinline__ void sts16(uint32_t a, uint32_t v) { asm volatile("st.shared.u16 [%0], %1;" :: "r"(a), "h"((uint16_t)v) : "memory"); }
__device__ __forceinline__ void sts64f(uint32_t a, float x, float y) { asm volatile("st.shared.v2.f32 [%0], {%1,%2};" :: "r"(a), "f"(x), "f"(y) : "memory"); }
__device__ __forceinline__ void sts128(uint32_t a, uint32_t x, uint32_t y, uint32_t z, uint32_t w) { asm volatile("st.shared.v4.u32 [%0], {%1,%2,%3,%4};" :: "r"(a), "r"(x), "r"(y), "r"(z), "r"(w) : "memory"); }
__device__ __forceinline__ void stsm4(uint32_t a, uint32_t r0, uint32_t r1, uint32_t r2, uint32_t r3) {
  asm volatile("stmatrix.sync.aligned.m8n8.x4.shared.b16 [%0], {%1,%2,%3,%4};" :: "r"(a), "r"(r0), "r"(r1), "r"(r2), "r"(r3) : "memory");
}
__device__ __forceinline__ void stsm4t(uint32_t a, uint32_t r0, uint32_t r1, uint32_t r2, uint32_t r3) {
  asm volatile("stmatrix.sync.aligned.m8n8.x4.trans.shared.b16 [%0], {%1,%2,%3,%4};" :: "r"(a), "r"(r0), "r"(r1), "r"(r2), "r"(r3) : "memory");
}
__device__ __forceinline__ void ldsm4t(uint32_t* r, uint32_t a) {
  asm volatile("ldmatrix.sync.aligned.m8n8.x4.trans.shared.b16 {%0,%1,%2,%3}, [%4];" : "=r"(r[0]), "=r"(r[1]), "=r"(r[2]), "=r"(r[3]) : "r"(a) : "memory");
}
__device__ __forceinline__ void ldsm4(uint32_t* r, uint32_t a) {
  asm volatile("ldmatrix.sync.aligned.m8n8.x4.shared.b16 {%0,%1,%2,%3}, [%4];" : "=r"(r[0]), "=r"(r[1]), "=r"(r[2]), "=r"(r[3]) : "r"(a) : "memory");
}
__device__ __forceinline__ void mma16816(float* d, const uint32_t* a, const uint32_t* b) {
  asm volatile("mma.sync.aligned.m16n8k16.row.col.f32.bf16.bf16.f32 {%0,%1,%2,%3}, {%4,%5,%6,%7}, {%8,%9}, {%0,%1,%2,%3};"
    : "+f"(d[0]), "+f"(d[1]), "+f"(d[2]), "+f"(d[3]) : "r"(a[0]), "r"(a[1]), "r"(a[2]), "r"(a[3]), "r"(b[0]), "r"(b[1]));
}
__device__ __forceinline__ uint32_t pack2(float lo, float hi) { uint32_t r; asm("cvt.rn.bf16x2.f32 %0, %1, %2;" : "=r"(r) : "f"(hi), "f"(lo)); return r; }
__device__ __forceinline__ uint32_t packh(float lo, float hi) { uint32_t r; asm("cvt.rn.f16x2.f32 %0, %1, %2;" : "=r"(r) : "f"(hi), "f"(lo)); return r; }
__device__ __forceinline__ uint32_t hcmul(uint32_t x, uint32_t zp, uint32_t zq) {
  const __half2 xx = *reinterpret_cast<__half2*>(&x);
  const __half2 r = __hfma2(__high2half2(xx), *reinterpret_cast<__half2*>(&zq), __hmul2(__low2half2(xx), *reinterpret_cast<__half2*>(&zp)));
  return *reinterpret_cast<const uint32_t*>(&r);
}
__device__ __forceinline__ void hcm2(uint32_t xr, uint32_t xi, uint32_t z, uint32_t& pr, uint32_t& pi) {
  const __half2 a = *reinterpret_cast<__half2*>(&xr), b = *reinterpret_cast<__half2*>(&xi), zz = *reinterpret_cast<__half2*>(&z);
  const __half2 re = __hfma2(__hneg2(b), __high2half2(zz), __hmul2(a, __low2half2(zz)));
  const __half2 im = __hfma2(a, __high2half2(zz), __hmul2(b, __low2half2(zz)));
  pr = *reinterpret_cast<const uint32_t*>(&re); pi = *reinterpret_cast<const uint32_t*>(&im);
}
__device__ __forceinline__ void sts64(uint32_t a, uint32_t x, uint32_t y) { asm volatile("st.shared.v2.u32 [%0], {%1,%2};" :: "r"(a), "r"(x), "r"(y) : "memory"); }
__device__ __forceinline__ void lds64(uint32_t* v, uint32_t a) { asm volatile("ld.shared.v2.u32 {%0,%1}, [%2];" : "=r"(v[0]), "=r"(v[1]) : "r"(a) : "memory"); }
__device__ __forceinline__ float bf_lo(uint32_t v) { return __uint_as_float(v << 16); }
__device__ __forceinline__ float bf_hi(uint32_t v) { return __uint_as_float(v & 0xffff0000u); }
__device__ __forceinline__ float bf_round(float x) { return bf_lo(pack2(x, 0.f)); }
__device__ __forceinline__ float ex2(float x) { float r; asm("ex2.approx.ftz.f32 %0, %1;" : "=f"(r) : "f"(x)); return r; }
__device__ __forceinline__ float phi(float t, float l2e = 1.44269504089f) {
  float e = ex2(t * l2e) + 1e-6f;
  asm("{\n.reg .pred p;\nsetp.gt.f32 p, %1, 0f00000000;\n@p add.f32 %0, %1, 0f3F800008;\n}" : "+f"(e) : "f"(t));
  return e;
}
__device__ __forceinline__ void wg_fence() { asm volatile("wgmma.fence.sync.aligned;" ::: "memory"); }
__device__ __forceinline__ void wg_commit() { asm volatile("wgmma.commit_group.sync.aligned;" ::: "memory"); }
template <int N> __device__ __forceinline__ void wg_wait() { asm volatile("wgmma.wait_group.sync.aligned %0;" :: "n"(N) : "memory"); }
template <int N> __device__ __forceinline__ void pin(float* a) {
  #pragma unroll
  for (int i = 0; i < N; i++) asm volatile("" : "+f"(a[i]) :: "memory");
}
__device__ __forceinline__ int rtid() { int t; asm volatile("mov.u32 %0, %%tid.x;" : "=r"(t)); return t; }
__device__ __forceinline__ int opaque(int v) { asm volatile("" : "+r"(v)); return v; }
template <int N> __device__ __forceinline__ void zero(float* a) {
  #pragma unroll
  for (int i = 0; i < N; i++) asm volatile("mov.b32 %0, 0;" : "=f"(a[i]));
}
template <int N> __device__ __forceinline__ void pinu(uint32_t* a) {
  #pragma unroll
  for (int i = 0; i < N; i++) asm volatile("" : "+r"(a[i]) :: "memory");
}
__device__ __forceinline__ void cexp_t(float lg2mag, float turns, float& re, float& im) {
  float m = ex2(lg2mag);
  float fr = (turns - __fadd_rn(__fadd_rn(turns, 12582912.f), -12582912.f)) * 6.283185307f;
  re = m * __cosf(fr); im = m * __sinf(fr);
}
__device__ __forceinline__ void cmul(float ar, float ai, float br, float bi, float& cr, float& ci) {
  cr = fmaf(ar, br, -ai * bi); ci = fmaf(ar, bi, ai * br);
}

__device__ __forceinline__ void wg_ss48_tt(float* d, uint64_t da, uint64_t db, int scale_d) {
  asm volatile("{\n.reg .pred p;\nsetp.ne.b32 p, %26, 0;\n"
    "wgmma.mma_async.sync.aligned.m64n48k16.f32.bf16.bf16 "
    "{%0, %1, %2, %3, %4, %5, %6, %7, %8, %9, %10, %11, %12, %13, %14, %15, %16, %17, %18, %19, %20, %21, %22, %23}, %24, %25, p, 1, 1, 1, 1;\n}\n"
    : "+f"(d[0]), "+f"(d[1]), "+f"(d[2]), "+f"(d[3]), "+f"(d[4]), "+f"(d[5]), "+f"(d[6]), "+f"(d[7]), "+f"(d[8]), "+f"(d[9]), "+f"(d[10]), "+f"(d[11]), "+f"(d[12]), "+f"(d[13]), "+f"(d[14]), "+f"(d[15]), "+f"(d[16]), "+f"(d[17]), "+f"(d[18]), "+f"(d[19]), "+f"(d[20]), "+f"(d[21]), "+f"(d[22]), "+f"(d[23])
    : "l"(da), "l"(db), "r"(scale_d));
}
__device__ __forceinline__ void wg_rs88_tb(float* d, const uint32_t* a, uint64_t db, int scale_d) {
  asm volatile("{\n.reg .pred p;\nsetp.ne.b32 p, %49, 0;\n"
    "wgmma.mma_async.sync.aligned.m64n88k16.f32.bf16.bf16 "
    "{%0, %1, %2, %3, %4, %5, %6, %7, %8, %9, %10, %11, %12, %13, %14, %15, %16, %17, %18, %19, %20, %21, %22, %23, %24, %25, %26, %27, %28, %29, %30, %31, %32, %33, %34, %35, %36, %37, %38, %39, %40, %41, %42, %43}, {%44, %45, %46, %47}, %48, p, 1, 1, 1;\n}\n"
    : "+f"(d[0]), "+f"(d[1]), "+f"(d[2]), "+f"(d[3]), "+f"(d[4]), "+f"(d[5]), "+f"(d[6]), "+f"(d[7]), "+f"(d[8]), "+f"(d[9]), "+f"(d[10]), "+f"(d[11]), "+f"(d[12]), "+f"(d[13]), "+f"(d[14]), "+f"(d[15]), "+f"(d[16]), "+f"(d[17]), "+f"(d[18]), "+f"(d[19]), "+f"(d[20]), "+f"(d[21]), "+f"(d[22]), "+f"(d[23]), "+f"(d[24]), "+f"(d[25]), "+f"(d[26]), "+f"(d[27]), "+f"(d[28]), "+f"(d[29]), "+f"(d[30]), "+f"(d[31]), "+f"(d[32]), "+f"(d[33]), "+f"(d[34]), "+f"(d[35]), "+f"(d[36]), "+f"(d[37]), "+f"(d[38]), "+f"(d[39]), "+f"(d[40]), "+f"(d[41]), "+f"(d[42]), "+f"(d[43])
    : "r"(a[0]), "r"(a[1]), "r"(a[2]), "r"(a[3]), "l"(db), "r"(scale_d));
}
__device__ __forceinline__ void wg_ss80_tb(float* d, uint64_t da, uint64_t db, int scale_d) {
  asm volatile("{\n.reg .pred p;\nsetp.ne.b32 p, %42, 0;\n"
    "wgmma.mma_async.sync.aligned.m64n80k16.f32.bf16.bf16 "
    "{%0, %1, %2, %3, %4, %5, %6, %7, %8, %9, %10, %11, %12, %13, %14, %15, %16, %17, %18, %19, %20, %21, %22, %23, %24, %25, %26, %27, %28, %29, %30, %31, %32, %33, %34, %35, %36, %37, %38, %39}, %40, %41, p, 1, 1, 0, 1;\n}\n"
    : "+f"(d[0]), "+f"(d[1]), "+f"(d[2]), "+f"(d[3]), "+f"(d[4]), "+f"(d[5]), "+f"(d[6]), "+f"(d[7]), "+f"(d[8]), "+f"(d[9]), "+f"(d[10]), "+f"(d[11]), "+f"(d[12]), "+f"(d[13]), "+f"(d[14]), "+f"(d[15]), "+f"(d[16]), "+f"(d[17]), "+f"(d[18]), "+f"(d[19]), "+f"(d[20]), "+f"(d[21]), "+f"(d[22]), "+f"(d[23]), "+f"(d[24]), "+f"(d[25]), "+f"(d[26]), "+f"(d[27]), "+f"(d[28]), "+f"(d[29]), "+f"(d[30]), "+f"(d[31]), "+f"(d[32]), "+f"(d[33]), "+f"(d[34]), "+f"(d[35]), "+f"(d[36]), "+f"(d[37]), "+f"(d[38]), "+f"(d[39])
    : "l"(da), "l"(db), "r"(scale_d));
}
__device__ __forceinline__ void wg_ss48_tt_h(float* d, uint64_t da, uint64_t db, int scale_d) {
  asm volatile("{\n.reg .pred p;\nsetp.ne.b32 p, %26, 0;\n"
    "wgmma.mma_async.sync.aligned.m64n48k16.f32.f16.f16 "
    "{%0, %1, %2, %3, %4, %5, %6, %7, %8, %9, %10, %11, %12, %13, %14, %15, %16, %17, %18, %19, %20, %21, %22, %23}, %24, %25, p, 1, 1, 1, 1;\n}\n"
    : "+f"(d[0]), "+f"(d[1]), "+f"(d[2]), "+f"(d[3]), "+f"(d[4]), "+f"(d[5]), "+f"(d[6]), "+f"(d[7]), "+f"(d[8]), "+f"(d[9]), "+f"(d[10]), "+f"(d[11]), "+f"(d[12]), "+f"(d[13]), "+f"(d[14]), "+f"(d[15]), "+f"(d[16]), "+f"(d[17]), "+f"(d[18]), "+f"(d[19]), "+f"(d[20]), "+f"(d[21]), "+f"(d[22]), "+f"(d[23])
    : "l"(da), "l"(db), "r"(scale_d));
}
__device__ __forceinline__ void wg_rs192_tb(float* d, const uint32_t* a, uint64_t db, int scale_d) {
  asm volatile("{\n.reg .pred p;\nsetp.ne.b32 p, %101, 0;\n"
    "wgmma.mma_async.sync.aligned.m64n192k16.f32.bf16.bf16 "
    "{%0, %1, %2, %3, %4, %5, %6, %7, %8, %9, %10, %11, %12, %13, %14, %15, %16, %17, %18, %19, %20, %21, %22, %23, %24, %25, %26, %27, %28, %29, %30, %31, %32, %33, %34, %35, %36, %37, %38, %39, %40, %41, %42, %43, %44, %45, %46, %47, %48, %49, %50, %51, %52, %53, %54, %55, %56, %57, %58, %59, %60, %61, %62, %63, %64, %65, %66, %67, %68, %69, %70, %71, %72, %73, %74, %75, %76, %77, %78, %79, %80, %81, %82, %83, %84, %85, %86, %87, %88, %89, %90, %91, %92, %93, %94, %95}, {%96, %97, %98, %99}, %100, p, 1, 1, 1;\n}\n"
    : "+f"(d[0]), "+f"(d[1]), "+f"(d[2]), "+f"(d[3]), "+f"(d[4]), "+f"(d[5]), "+f"(d[6]), "+f"(d[7]), "+f"(d[8]), "+f"(d[9]), "+f"(d[10]), "+f"(d[11]), "+f"(d[12]), "+f"(d[13]), "+f"(d[14]), "+f"(d[15]), "+f"(d[16]), "+f"(d[17]), "+f"(d[18]), "+f"(d[19]), "+f"(d[20]), "+f"(d[21]), "+f"(d[22]), "+f"(d[23]), "+f"(d[24]), "+f"(d[25]), "+f"(d[26]), "+f"(d[27]), "+f"(d[28]), "+f"(d[29]), "+f"(d[30]), "+f"(d[31]), "+f"(d[32]), "+f"(d[33]), "+f"(d[34]), "+f"(d[35]), "+f"(d[36]), "+f"(d[37]), "+f"(d[38]), "+f"(d[39]), "+f"(d[40]), "+f"(d[41]), "+f"(d[42]), "+f"(d[43]), "+f"(d[44]), "+f"(d[45]), "+f"(d[46]), "+f"(d[47]), "+f"(d[48]), "+f"(d[49]), "+f"(d[50]), "+f"(d[51]), "+f"(d[52]), "+f"(d[53]), "+f"(d[54]), "+f"(d[55]), "+f"(d[56]), "+f"(d[57]), "+f"(d[58]), "+f"(d[59]), "+f"(d[60]), "+f"(d[61]), "+f"(d[62]), "+f"(d[63]), "+f"(d[64]), "+f"(d[65]), "+f"(d[66]), "+f"(d[67]), "+f"(d[68]), "+f"(d[69]), "+f"(d[70]), "+f"(d[71]), "+f"(d[72]), "+f"(d[73]), "+f"(d[74]), "+f"(d[75]), "+f"(d[76]), "+f"(d[77]), "+f"(d[78]), "+f"(d[79]), "+f"(d[80]), "+f"(d[81]), "+f"(d[82]), "+f"(d[83]), "+f"(d[84]), "+f"(d[85]), "+f"(d[86]), "+f"(d[87]), "+f"(d[88]), "+f"(d[89]), "+f"(d[90]), "+f"(d[91]), "+f"(d[92]), "+f"(d[93]), "+f"(d[94]), "+f"(d[95])
    : "r"(a[0]), "r"(a[1]), "r"(a[2]), "r"(a[3]), "l"(db), "r"(scale_d));
}
__device__ __forceinline__ void wg_rs48_tb(float* d, const uint32_t* a, uint64_t db, int scale_d) {
  asm volatile("{\n.reg .pred p;\nsetp.ne.b32 p, %29, 0;\n"
    "wgmma.mma_async.sync.aligned.m64n48k16.f32.bf16.bf16 "
    "{%0, %1, %2, %3, %4, %5, %6, %7, %8, %9, %10, %11, %12, %13, %14, %15, %16, %17, %18, %19, %20, %21, %22, %23}, {%24, %25, %26, %27}, %28, p, 1, 1, 1;\n}\n"
    : "+f"(d[0]), "+f"(d[1]), "+f"(d[2]), "+f"(d[3]), "+f"(d[4]), "+f"(d[5]), "+f"(d[6]), "+f"(d[7]), "+f"(d[8]), "+f"(d[9]), "+f"(d[10]), "+f"(d[11]), "+f"(d[12]), "+f"(d[13]), "+f"(d[14]), "+f"(d[15]), "+f"(d[16]), "+f"(d[17]), "+f"(d[18]), "+f"(d[19]), "+f"(d[20]), "+f"(d[21]), "+f"(d[22]), "+f"(d[23])
    : "r"(a[0]), "r"(a[1]), "r"(a[2]), "r"(a[3]), "l"(db), "r"(scale_d));
}
__device__ __forceinline__ void wg_ss192_tb(float* d, uint64_t da, uint64_t db, int scale_d) {
  asm volatile("{\n.reg .pred p;\nsetp.ne.b32 p, %98, 0;\n"
    "wgmma.mma_async.sync.aligned.m64n192k16.f32.bf16.bf16 "
    "{%0, %1, %2, %3, %4, %5, %6, %7, %8, %9, %10, %11, %12, %13, %14, %15, %16, %17, %18, %19, %20, %21, %22, %23, %24, %25, %26, %27, %28, %29, %30, %31, %32, %33, %34, %35, %36, %37, %38, %39, %40, %41, %42, %43, %44, %45, %46, %47, %48, %49, %50, %51, %52, %53, %54, %55, %56, %57, %58, %59, %60, %61, %62, %63, %64, %65, %66, %67, %68, %69, %70, %71, %72, %73, %74, %75, %76, %77, %78, %79, %80, %81, %82, %83, %84, %85, %86, %87, %88, %89, %90, %91, %92, %93, %94, %95}, %96, %97, p, 1, 1, 0, 1;\n}\n"
    : "+f"(d[0]), "+f"(d[1]), "+f"(d[2]), "+f"(d[3]), "+f"(d[4]), "+f"(d[5]), "+f"(d[6]), "+f"(d[7]), "+f"(d[8]), "+f"(d[9]), "+f"(d[10]), "+f"(d[11]), "+f"(d[12]), "+f"(d[13]), "+f"(d[14]), "+f"(d[15]), "+f"(d[16]), "+f"(d[17]), "+f"(d[18]), "+f"(d[19]), "+f"(d[20]), "+f"(d[21]), "+f"(d[22]), "+f"(d[23]), "+f"(d[24]), "+f"(d[25]), "+f"(d[26]), "+f"(d[27]), "+f"(d[28]), "+f"(d[29]), "+f"(d[30]), "+f"(d[31]), "+f"(d[32]), "+f"(d[33]), "+f"(d[34]), "+f"(d[35]), "+f"(d[36]), "+f"(d[37]), "+f"(d[38]), "+f"(d[39]), "+f"(d[40]), "+f"(d[41]), "+f"(d[42]), "+f"(d[43]), "+f"(d[44]), "+f"(d[45]), "+f"(d[46]), "+f"(d[47]), "+f"(d[48]), "+f"(d[49]), "+f"(d[50]), "+f"(d[51]), "+f"(d[52]), "+f"(d[53]), "+f"(d[54]), "+f"(d[55]), "+f"(d[56]), "+f"(d[57]), "+f"(d[58]), "+f"(d[59]), "+f"(d[60]), "+f"(d[61]), "+f"(d[62]), "+f"(d[63]), "+f"(d[64]), "+f"(d[65]), "+f"(d[66]), "+f"(d[67]), "+f"(d[68]), "+f"(d[69]), "+f"(d[70]), "+f"(d[71]), "+f"(d[72]), "+f"(d[73]), "+f"(d[74]), "+f"(d[75]), "+f"(d[76]), "+f"(d[77]), "+f"(d[78]), "+f"(d[79]), "+f"(d[80]), "+f"(d[81]), "+f"(d[82]), "+f"(d[83]), "+f"(d[84]), "+f"(d[85]), "+f"(d[86]), "+f"(d[87]), "+f"(d[88]), "+f"(d[89]), "+f"(d[90]), "+f"(d[91]), "+f"(d[92]), "+f"(d[93]), "+f"(d[94]), "+f"(d[95])
    : "l"(da), "l"(db), "r"(scale_d));
}
__device__ __forceinline__ void wg_ss48_tb(float* d, uint64_t da, uint64_t db, int scale_d) {
  asm volatile("{\n.reg .pred p;\nsetp.ne.b32 p, %26, 0;\n"
    "wgmma.mma_async.sync.aligned.m64n48k16.f32.bf16.bf16 "
    "{%0, %1, %2, %3, %4, %5, %6, %7, %8, %9, %10, %11, %12, %13, %14, %15, %16, %17, %18, %19, %20, %21, %22, %23}, %24, %25, p, 1, 1, 0, 1;\n}\n"
    : "+f"(d[0]), "+f"(d[1]), "+f"(d[2]), "+f"(d[3]), "+f"(d[4]), "+f"(d[5]), "+f"(d[6]), "+f"(d[7]), "+f"(d[8]), "+f"(d[9]), "+f"(d[10]), "+f"(d[11]), "+f"(d[12]), "+f"(d[13]), "+f"(d[14]), "+f"(d[15]), "+f"(d[16]), "+f"(d[17]), "+f"(d[18]), "+f"(d[19]), "+f"(d[20]), "+f"(d[21]), "+f"(d[22]), "+f"(d[23])
    : "l"(da), "l"(db), "r"(scale_d));
}
__device__ __forceinline__ void wg_rs64(float* d, const uint32_t* a, uint64_t db, int scale_d) {
  asm volatile("{\n.reg .pred p;\nsetp.ne.b32 p, %37, 0;\n"
    "wgmma.mma_async.sync.aligned.m64n64k16.f32.bf16.bf16 "
    "{%0, %1, %2, %3, %4, %5, %6, %7, %8, %9, %10, %11, %12, %13, %14, %15, %16, %17, %18, %19, %20, %21, %22, %23, %24, %25, %26, %27, %28, %29, %30, %31}, {%32, %33, %34, %35}, %36, p, 1, 1, 0;\n}\n"
    : "+f"(d[0]), "+f"(d[1]), "+f"(d[2]), "+f"(d[3]), "+f"(d[4]), "+f"(d[5]), "+f"(d[6]), "+f"(d[7]), "+f"(d[8]), "+f"(d[9]), "+f"(d[10]), "+f"(d[11]), "+f"(d[12]), "+f"(d[13]), "+f"(d[14]), "+f"(d[15]), "+f"(d[16]), "+f"(d[17]), "+f"(d[18]), "+f"(d[19]), "+f"(d[20]), "+f"(d[21]), "+f"(d[22]), "+f"(d[23]), "+f"(d[24]), "+f"(d[25]), "+f"(d[26]), "+f"(d[27]), "+f"(d[28]), "+f"(d[29]), "+f"(d[30]), "+f"(d[31])
    : "r"(a[0]), "r"(a[1]), "r"(a[2]), "r"(a[3]), "l"(db), "r"(scale_d));
}
__device__ __forceinline__ void wg_rs24_tb(float* d, const uint32_t* a, uint64_t db, int scale_d) {
  asm volatile("{\n.reg .pred p;\nsetp.ne.b32 p, %17, 0;\n"
    "wgmma.mma_async.sync.aligned.m64n24k16.f32.bf16.bf16 "
    "{%0, %1, %2, %3, %4, %5, %6, %7, %8, %9, %10, %11}, {%12, %13, %14, %15}, %16, p, 1, 1, 1;\n}\n"
    : "+f"(d[0]), "+f"(d[1]), "+f"(d[2]), "+f"(d[3]), "+f"(d[4]), "+f"(d[5]), "+f"(d[6]), "+f"(d[7]), "+f"(d[8]), "+f"(d[9]), "+f"(d[10]), "+f"(d[11])
    : "r"(a[0]), "r"(a[1]), "r"(a[2]), "r"(a[3]), "l"(db), "r"(scale_d));
}
__device__ __forceinline__ void wg_rs16_tb(float* d, const uint32_t* a, uint64_t db, int scale_d) {
  asm volatile("{\n.reg .pred p;\nsetp.ne.b32 p, %13, 0;\n"
    "wgmma.mma_async.sync.aligned.m64n16k16.f32.bf16.bf16 "
    "{%0, %1, %2, %3, %4, %5, %6, %7}, {%8, %9, %10, %11}, %12, p, 1, 1, 1;\n}\n"
    : "+f"(d[0]), "+f"(d[1]), "+f"(d[2]), "+f"(d[3]), "+f"(d[4]), "+f"(d[5]), "+f"(d[6]), "+f"(d[7])
    : "r"(a[0]), "r"(a[1]), "r"(a[2]), "r"(a[3]), "l"(db), "r"(scale_d));
}

struct Params {
  const __nv_bfloat16 *par[4], *logdt, *dskip, *u, *wo;
  CUtensorMap m[M_COUNT];
};

#define CHUNK(i) ((i) == 0 ? c : ((i) == 7 ? (c ^ 1) : (((c & 6) + 1 + (i)) & 7)))
#define FLAG(kind, rr, cc) (&g_flag[((kind) * 128 + (rr) * 8 + (cc)) * 32])
#define ORD(n) ((0x32410 >> (4 * (n))) & 7)
#define SLOT(i) ((i) == 0 ? OFF_EXTRA : OFF_BLK - 1024 + ORD((i) > 5 ? (i) - 6 : (i) - 1) * BLK)
template <int NS>
__device__ __forceinline__ void load_toep(uint32_t* A, uint32_t addr) {
  uint32_t prev = lds32(addr - 32);
  #pragma unroll
  for (int s = 0; s < NS; s++) {
    const uint32_t x = lds32(addr + 64 * s), y = lds32(addr + 64 * s + 32);
    A[4 * s] = x; A[4 * s + 1] = y; A[4 * s + 2] = prev; A[4 * s + 3] = x;
    prev = y;
  }
}

__device__ __forceinline__ bool y_transpose(uint32_t sb, int w5, int lane, uint32_t ytag, int r) {
  const int mi = lane >> 3, rw = lane & 7;
  const uint32_t sa = sb + OFF_EXTRA + (w5 * 16 + rw) * 128 + ((mi ^ rw ^ ((2 * r) & 2)) << 4), da = sb + SLOT(3) + (8 * mi + rw) * 160 + w5 * 32;
  const uint32_t ym = lane < 4 ? 0x10001u : 0u;
  bar_sync(7, 160);
  uint32_t v[8][4], bad = 0;
  #pragma unroll
  for (int q = 0; q < 8; q++) ldsm4t(v[q], (sa ^ ((q & 1) * 64 + ((q >> 1) & 1) * 16)) + ((q >> 1) & 1) * 10240 + (q >> 2) * 1024);
  #pragma unroll
  for (int q = 0; q < 8; q++) {
    bad |= (v[q][0] ^ ytag) | (v[q][2] ^ ytag);
    stsm4(da + (q & 3) * 5120 + (q >> 2) * 16, v[q][0] & ~ym, v[q][1], v[q][2] & ~ym, v[q][3]);
  }
  fence_async();
  uint32_t any;
  asm volatile("{\n.reg .pred p;\nsetp.ne.u32 p, %1, 0;\nbarrier.red.or.pred p, 7, 160, p;\nselp.u32 %0, 1, 0, p;\n}" : "=r"(any) : "r"(bad & ym) : "memory");
  return any;
}

__global__ void __launch_bounds__(512, 1) fused_kernel(const __grid_constant__ Params prm) {
  extern __shared__ unsigned char smem_raw[];
  const uint32_t sb = __shfl_sync(0xffffffff, smem_u32(smem_raw), 0);
  const int tid = threadIdx.x, lane = tid & 31;
  const int warp = __shfl_sync(0xffffffff, tid >> 5, 0), wg = warp >> 2, w4 = warp & 3;
  const int cta = blockIdx.x, r = cta >> 3, c = cta & 7;
  if ((sb & 0xffffffu) != SB0) return;
#define BAR(i) (sb + OFF_BAR + 8 * (i))
  const bool sw64 = ((c + 1) & 2) != 0;

  const CUtensorMap* mwp = &prm.m[sw64 ? M_W64 : M_W128];
  const int mcol = (c * 80 + (c & 1) * 16) >> (sw64 ? 5 : 6), rcol = c * 80 + ((c & 1) ? 0 : 64);
  if (warp == 12 && elect_one()) {
    #pragma unroll
    for (int i = 0; i < 5; i++) mbar_init(BAR(BR_FULL + i), 1);
    asm volatile("fence.mbarrier_init.release.cluster;" ::: "memory");
    if (EN_ATT) {
      mbar_expect_tx(BAR(BR_FULL), W_SLOT + 16384);
      tma4d(sb, mwp, BAR(BR_FULL), 0, 0, mcol, 0);
      tma2d(sb + OFF_X, &prm.m[M_X], BAR(BR_FULL), 0, r * 128);
      tma3d(sb + 12288, &prm.m[M_WR], BAR(BR_FULL), rcol, 0, 0);
      mbar_expect_tx(BAR(BR_FULL + 1), W_SLOT);
      tma4d(sb + W_SLOT, mwp, BAR(BR_FULL + 1), 0, 32, mcol, 0);
      tma3d(sb + W_SLOT + 12288, &prm.m[M_WR], BAR(BR_FULL + 1), rcol, 32, 0);
      TS(24);
    }
  }
  if (warp == 13 && elect_one()) {
    asm volatile("prefetch.tensormap [%0];" :: "l"(&prm.m[M_X]) : "memory");
    asm volatile("prefetch.tensormap [%0];" :: "l"(&prm.m[M_WR]) : "memory");
  }
  if (wg == 3) {
    asm volatile("setmaxnreg.dec.sync.aligned.u32 56;");
    const int tid = rtid(), lane = tid & 31;
    if (warp == 12) {
      asm volatile("bar.arrive 0, 512;" ::: "memory");
      {
        uint32_t s = 2, ph = 1, xs = 16384;
        #pragma unroll 1
        for (int kb = 2; kb < 20; kb++) {
          if (kb == 4) bar_sync(6, 128);
          if (kb >= 5) mbar_wait(BAR(BR_EMPTY) + 8 * s, ph);
          if (EN_ATT && elect_one()) {
            const uint32_t st = sb + s * W_SLOT, fb = BAR(BR_FULL) + 8 * s;
            mbar_expect_tx(fb, (kb & 1) ? W_SLOT : W_SLOT + 16384);
            if (!(kb & 1)) tma2d(sb + OFF_X + xs, &prm.m[M_X], fb, kb * 32, r * 128);
            tma4d(st, mwp, fb, 0, kb * 32, mcol, 0);
            tma3d(st + 12288, &prm.m[M_WR], fb, rcol, kb * 32, 0);
          }
          if (kb < 4 && lane == 0) TS(24 + kb);
          if (UPF && kb >= UKB - 4 && kb < UKB && elect_one())
            asm volatile("cp.async.bulk.prefetch.L2.global [%0], 5120;" :: "l"(prm.u + cta * 10240 + (kb - (UKB - 4)) * 2560) : "memory");
          if (EN_SSM && kb == (EN_ATT ? UKB : 4) && elect_one()) { mbar_expect_tx(BAR(BR_UIN), 20480); tma2d(sb + OFF_UT, &prm.m[M_U], BAR(BR_UIN), c * 80, r * 128); }
          if (kb == 14 && elect_one()) asm volatile("cp.async.bulk.prefetch.L2.global [%0], 6400;" :: "l"(prm.wo + cta * 3200) : "memory");
          if (!EN_ATT && kb == 4) break;
          if (++s == 5) { s = 0; ph ^= 1; }
          if (kb & 1) { xs += 16384; if (xs == 49152) xs = 0; }
        }
      }
      if (EN_ATT) {
      mbar_wait(BAR(BR_EPOCH), 0);
      const unsigned epoch = lds32(sb + OFF_EPOCH);
      const unsigned* fo = FLAG(3, r, lane & 7);
      unsigned seen = __ballot_sync(0xffffffff, ld_rlx(lane < 16 ? fo : FLAG(0, lane & 15, c)) == epoch) & 0xffu;
      mbar_wait(BAR(BR_GEMM), 0);
      if (elect_one()) {
        mbar_expect_tx(BAR(BR_WO), 10240);
        tma2d(sb, &prm.m[M_WO], BAR(BR_WO), c * 64, c * 80);
        mbar_expect_tx(BAR(BR_KVP), 61440);
        mbar_expect_tx(BAR(BR_WO + 1), 7 * 10240);
      }
      {
        uint32_t ds = sb + OFF_WOR + (lane >> 3) * 128 + (((lane & 7) ^ (lane >> 3)) << 4);
        #pragma unroll 1
        for (int h = 0; h < 2; h++) {
          const int i = (lane & 6) + h;
          const char* gs = reinterpret_cast<const char*>(prm.wo) + (size_t)((lane >> 3) + CHUNK(i) * 80) * 1280 + 1024 + c * 32 + (lane & 1) * 16;
          #pragma unroll 2
          for (int q = 0; q < 20; q++) {
            asm volatile("cp.async.cg.shared.global [%0], [%1], 16;" :: "r"(ds), "l"(gs) : "memory");
            ds = (ds + 512) ^ 64; gs += 5120;
          }
        }
      }
      mbar_wait(BAR(BR_PUB), 0);
      poll_all(FLAG(0, lane & 15, c), epoch);
      if (elect_one()) { TS(23); bulk_ld(sb + OFF_KVP, &g_kvp[c * 16 * 240], 61440, BAR(BR_KVP)); }
      asm volatile("cp.async.wait_all;" ::: "memory");
      fence_async();
      mbar_arrive(BAR(BR_WO));
      mbar_wait(BAR(BR_SUM), 0);
      if (elect_one()) {
        #pragma unroll 1
        for (int i = 1; i < 8; i++) tma2d(sb + i * 10240, &prm.m[M_WO], BAR(BR_WO + 1), c * 64, CHUNK(i) * 80);
      }
      mbar_wait(BAR(BR_OSTG), 0);
      if (elect_one()) {
        bulk_st(&g_o[cta * 1280], sb + OFF_EXTRA, 20480);
        bulk_commit();
        bulk_wait0();
        st_rlx(FLAG(3, r, c), epoch);
        mbar_arrive(BAR(BR_OEMPTY));
        TS(20);
      }
      __syncwarp();
      #pragma unroll 1
      for (int i = 1; i < 8; i++) {
        const int src = CHUNK(i);
        if (!((seen >> src) & 1)) seen = poll_bit(fo, epoch, 1u << src);
        if (i > 5) mbar_wait(BAR(BR_OEMPTY - 5) + 8 * i, 0);
        else if (EN_SSM) mbar_wait(BAR(BR_FREE - 1) + 8 * i, 0);
        if (elect_one()) {
          mbar_expect_tx(BAR(BR_OFULL) + 8 * i, 20480);
          bulk_ld(sb + SLOT(i), &g_o[(r * 8 + src) * 1280], 20480, BAR(BR_OFULL) + 8 * i);
          if (i == 1) TS(21);
          if (i == 7) TS(22);
        }
        __syncwarp();
      }
      if (lane == 0) { DUMP(20, 30); }
      }
    } else {
      const int hw = warp - 13, ht = tid - 416;
      if (hw == 2 && elect_one()) {
        #pragma unroll
        for (int i = 5; i < BR_COUNT; i++) mbar_init(BAR(i), i == BR_WO ? 33 : i == BR_OEMPTY ? 9 : i < BR_EMPTY ? 1 : i < BR_OEMPTY ? 2 : i < BR_DRDY ? 8 : i < BR_Y ? 3 : 4);
        asm volatile("fence.mbarrier_init.release.cluster;" ::: "memory");
      }
      __syncwarp();
      asm volatile("bar.arrive 0, 512;" ::: "memory");
      if (EN_SSM && hw == 2) asm volatile("bar.arrive 8, 160;" ::: "memory");
      const unsigned epoch = hw == 0 ? ld_rlx(&g_epoch[cta]) + 1 : 0;
      bar_sync(5, 96);
      asm volatile("bar.arrive 6, 128;" ::: "memory");
      if (hw == 1 && elect_one()) {
        #pragma unroll
        for (int i = M_U; i < M_COUNT; i++) asm volatile("prefetch.tensormap [%0];" :: "l"(&prm.m[i]) : "memory");
      }
      if (ht == 0) {
        st_rlx(&g_epoch[cta], epoch);
        sts32(sb + OFF_EPOCH, epoch);
        mbar_arrive(BAR(BR_EPOCH));
      }
      if (EN_SSM) {
      const int mi = lane >> 3, rw = lane & 7, ch0 = c * 80 + r * 5;
      mbar_wait(BAR(BR_UIN), 0);
      if (ht == 0) TS(36);
      #pragma unroll 1
      for (int h = 0; h < 2; h++) {
        const uint32_t sa = sb + OFF_UT + h * 10240 + (8 * mi + rw) * 160 + hw * 16, da = sb + OFF_UT + h * 10240 + (hw * 8 + rw) * 128 + ((mi ^ rw ^ ((2 * r + h) & 3)) << 4);
        uint32_t v[8][4];
        #pragma unroll
        for (int q = 0; q < 8; q++) if (q < 6 || hw == 0) ldsm4t(v[q], sa + (q & 1) * 5120 + (q >> 1) * 48);
        bar_sync(5, 96);
        #pragma unroll
        for (int q = 0; q < 8; q++) if (q < 6 || hw == 0) stsm4((da ^ ((q & 1) * 64)) + (q >> 1) * 3072, v[q][0], v[q][1], v[q][2], v[q][3]);
      }
      fence_async();
      bar_sync(5, 96);
      if (hw == 0) {
        if (elect_one()) {
          tma2d_st(&prm.m[M_SA], sb + OFF_UT, r * 128, c * 80);
          tma2d_st(&prm.m[M_SA], sb + OFF_UT + 10240, r * 128 + 64, c * 80);
          bulk_commit(); bulk_wait0_read();
          mbar_arrive(BAR(BR_UOUT));
          TS(37);
          bulk_wait0();
          st_rel(FLAG(1, r, c), epoch);
          TS(30);
        }
        __syncwarp();
        poll_all_acq(FLAG(1, lane & 15, c), epoch);
      }
      #pragma unroll 1
      for (int k = 0; k < 5; k++) {
        if (k == 0 || k == 3) {
          const int p = k != 0;
          if (hw == 0) {
            if (!p) {
              if (elect_one()) {
                fence_async_g();
                mbar_expect_tx(BAR(BR_U), 12288);
                #pragma unroll 1
                for (int q = 0; q < 3; q++) bulk_ld(sb + OFF_BLK + q * q * BLK, g_uy + (ch0 + q * q) * 2048, 4096, BAR(BR_U));
                TS(31);
              }
              __syncwarp();
            }
            mbar_wait(BAR(p ? BR_U2 : BR_U), 0);
          }
          bar_sync(5, 96);
        }
        const int l3 = (hw + k) % 3 * 32 + lane;
        const uint32_t blk = sb + OFF_BLK + ORD(k) * BLK, o = blk + B_D + l3 * 16;
        float P[34];
        P[0] = 0.f;
        #pragma unroll
        for (int q = 0; q < 5; q++) {
          const int ch = 2 * l3 - 3 + q;
          uint32_t v[4];
          lds128(v, blk + (uint32_t)((ch * 16) ^ ((ch * 2) & 0x30)));
          #pragma unroll
          for (int e = 0; e < 8; e++) {
            const int i = 8 * q + e - 4;
            if (i >= 0 && i < 33) P[i + 1] = P[i] + ((e & 1) ? bf_hi(v[e >> 1]) : bf_lo(v[e >> 1]));
          }
        }
#define WIN(lo, hi, e) (P[21 + (e) - (lo)] - P[20 + (e) - (hi)])
#define WIN8(lo, hi, b) pack2(WIN(lo, hi, b), WIN(lo, hi, b + 1)), pack2(WIN(lo, hi, b + 2), WIN(lo, hi, b + 3)), pack2(WIN(lo, hi, b + 4), WIN(lo, hi, b + 5)), pack2(WIN(lo, hi, b + 6), WIN(lo, hi, b + 7))
        if (l3 < 64) {
          sts128(o + B_D9, WIN8(12, 20, 0)); sts128(o + B_D9 + 1024, WIN8(12, 20, 8));
          sts128(o + B_D7, WIN8(5, 11, 0)); sts128(o + B_D7 + 1024, WIN8(5, 11, 8));
        }
        sts128(o + l3 * 16, WIN8(6, 10, 0)); sts128(o + l3 * 16 + 16, WIN8(6, 10, 8));
        sts128(o + l3 * 16 + B_D3, WIN8(3, 5, 0)); sts128(o + l3 * 16 + B_D3 + 16, WIN8(3, 5, 8));
        if (k == 2) { fence_async(); __syncwarp(); if (lane == 0) mbar_arrive(BAR(BR_DRDY)); }
      }
      fence_async();
      __syncwarp();
      if (lane == 0) mbar_arrive(BAR(BR_DRDY + 1));
      if (ht == 0) TS(32);
      if (hw == 0) {
        #pragma unroll 1
        for (int n = 0; n < 5; n++) {
          mbar_wait(BAR(BR_Y) + 8 * n, 0);
          if (elect_one()) {
            bulk_st(g_uy + (640 + ch0 + ORD(n)) * 2048, sb + OFF_BLK + ORD(n) * BLK, 4096);
            bulk_commit();
            if (n != 3) { bulk_wait0_read(); mbar_arrive(BAR(BR_FREE) + 8 * n); if (n == 4) mbar_arrive(BAR(BR_FREE + 3)); }
          }
          __syncwarp();
        }
        if (elect_one()) { bulk_wait0(); st_rlx(FLAG(2, r, c), epoch); TS(33); }
        __syncwarp();
        poll_all(FLAG(2, lane & 15, c), epoch);
        if (EN_ATT) mbar_wait(BAR(BR_OEMPTY), 0);
        #pragma unroll 1
        for (int n = 0; n < 64; n++) {
          if (elect_one()) {
            mbar_expect_tx(BAR(BR_YIN), 20480);
            tma2d(sb + OFF_EXTRA, &prm.m[M_SA], BAR(BR_YIN), r * 128, 640 + c * 80);
            tma2d(sb + OFF_EXTRA + 10240, &prm.m[M_SA], BAR(BR_YIN), r * 128 + 64, 640 + c * 80);
            TS(34);
          }
          __syncwarp();
          if (EN_ATT) mbar_wait(BAR(BR_OEMPTY + 3), 0);
          mbar_wait(BAR(BR_YIN), n & 1);
          if (lane == 0) TS(38);
          if (!y_transpose(sb, 4, lane, (epoch & 1u) * 0x10001u, r)) break;
          FIXCNT
        }
      if (elect_one()) {
        TS(39);
        tma2d_st(&prm.m[M_OUT], sb + SLOT(3), c * 80, r * 128);
        bulk_commit(); bulk_wait0_read();
        TS(35); DUMP(30, 40); DUMP(0, 1);
      }
      }
      }
    }
  } else {
  if (wg < 2) {
    asm volatile("setmaxnreg.inc.sync.aligned.u32 160;");
    bar_sync(0, 512);
    if (EN_ATT) {
    float am[96], ar[24];
    {
      const bool lead = (rtid() & 127) == 0;
      constexpr uint64_t dr0 = mkdesc(SB0 + 12288, 1024, 256, 3);
      const uint64_t db0 = sw64 ? mkdesc(SB0, 2048, 512, 2) : mkdesc(SB0, 4096, 1024, 1);
      const uint32_t kst = sw64 ? 64 : 128, bh = db0 >> 32;
      uint32_t s = 0, ph = 0, xo = 0;
      const int ln = rtid() & 31;
      const uint32_t xa = sb + OFF_X + (warp * 16 + (ln & 15)) * 128 + (((ln >> 4) ^ (ln & 7)) << 4);
      uint32_t A[8];
      mbar_wait(BAR(BR_FULL), 0);
      if (lead && wg == 0) TS(1);
      ldsm4(A, xa); ldsm4(A + 4, xa);
      wg_fence();
      wg_rs48_tb(ar, A + 4, dr0, 0); wg_rs192_tb(am, A + 4, db0, 0);
      wg_commit();
      uint32_t xk = xa, eb = 0;
      #pragma unroll 1
      for (int kb = 0; kb < 20; kb++) {
        const uint32_t wo_ = s * (W_SLOT >> 4), bl = (uint32_t)db0 + wo_, rl = (uint32_t)dr0 + wo_;
        wg_fence();
        wg_rs48_tb(ar, A, desc2(rl, dr0 >> 32), kb != 0);
        wg_rs192_tb(am, A, desc2(bl, bh), kb != 0);
        wg_commit();
        wg_wait<1>();
        ldsm4(A + 4, xk ^ 32);
        if (lead && kb > 0 && kb < 16) mbar_arrive(eb);
        eb = BAR(BR_EMPTY) + 8 * s;
        wg_fence();
        wg_rs48_tb(ar, A + 4, desc2(rl + 32, dr0 >> 32), 1);
        wg_rs192_tb(am, A + 4, desc2(bl + kst, bh), 1);
        wg_commit();
        if (++s == 5) { s = 0; ph ^= 1; }
        if (kb & 1) { xo += 16384; if (xo == 49152) xo = 0; }
        if (kb < 19) mbar_wait(BAR(BR_FULL) + 8 * s, ph);
        xk = (xa + xo) ^ ((~kb & 1) * 64);
        wg_wait<1>();
        ldsm4(A, xk);
      }
      wg_wait<0>();
      pin<96>(am); pin<24>(ar);
    }
    const int tid = rtid(), lane = tid & 31, tq = lane & 3;
    if (tid == 0) TS(2);
#define QV(j, e) ((j) < 8 ? am[4 * (j) + (e)] : ar[4 * ((j) - 8) + (e)])
#define KV_(j, e) ((j) < 8 ? am[32 + 4 * (j) + (e)] : ar[8 + 4 * ((j) - 8) + (e)])
#define VV(j, e) ((j) < 8 ? am[64 + 4 * (j) + (e)] : ar[16 + 4 * ((j) - 8) + (e)])
    {
      bar_sync(1, 256);
      if (tid == 0) mbar_arrive(BAR(BR_GEMM));
      const uint32_t ro = sb + (uint32_t)((warp * 16 + (lane & 15)) * 16);
      const int l0 = 2 * (c & 1) + (lane >> 4);
      const uint32_t ones = (tq == 0) ? 0x00003f80u : 0u;
#define PV(j) pack2(VV(j, 0), VV(j, 1)), pack2(VV(j, 2), VV(j, 3))
#define PK(j) pack2(phi(KV_(j, 0)), phi(KV_(j, 1))), pack2(phi(KV_(j, 2)), phi(KV_(j, 3)))
      stsm4(ro + OFF_V + (5 + 6 * (lane >> 4)) * 2048, ones, ones, ones, ones);
      #pragma unroll
      for (int j = 0; j < 10; j += 2) {
        const int l = (j == 8 && (c & 1)) ? l0 - 2 : l0 + j;
        stsm4(ro + OFF_V + (l + (l >= 5)) * 2048, PV(j), PV(j + 1));
        stsm4(ro + OFF_PK + l * 2048, PK(j), PK(j + 1));
      }
    }
    fence_async();
    bar_sync(1, 256);
    if (tid == 0) TS(3);
    mbar_wait(BAR(BR_EPOCH), 0);
    const unsigned epoch = lds32(sb + OFF_EPOCH);
    {
      float kv[24]; zero<24>(kv);
      constexpr uint64_t da = mkdesc(SB0 + OFF_PK, 128, 2048, 0), db = mkdesc(SB0 + OFF_V, 128, 2048, 0);
      wg_fence();
      #pragma unroll
      for (int s = 0; s < 8; s++) wg_ss48_tt(kv, desc2((uint32_t)da + wg * 640 + s * 16, da >> 32), desc2((uint32_t)db + wg * 768 + s * 16, db >> 32), s != 0);
      wg_commit();
      wg_wait<0>();
      pin<24>(kv);
      if (tid == 0) TS(15);
      if (w4 < 3) {
        const uint32_t wb = sb + OFF_KVS + (wg * 3 + w4) * 1536 + (lane & 15) * 96;
        #pragma unroll
        for (int j = 0; j < 6; j += 2)
          stsm4(wb + (j + (lane >> 4)) * 16, pack2(kv[4 * j], kv[4 * j + 1]), pack2(kv[4 * j + 2], kv[4 * j + 3]),
                pack2(kv[4 * j + 4], kv[4 * j + 5]), pack2(kv[4 * j + 6], kv[4 * j + 7]));
        __syncwarp();
        const int dl = w4 * 16 + (lane & 15), hl = dl >= 20;
        if (dl < 40) {
          uint4* dst = &g_kvp[(c * 16 + r) * 240 + wg * 40 + dl];
          uint32_t v[4], z[4];
          lds128(v, wb + (3 * hl + (lane >> 4)) * 16);
          lds64(z, wb + 32 + 8 * hl); z[2] = lds32(wb + 80); z[3] = epoch & 1u;
          v[3] = (v[3] & ~1u) | z[3];
          st128_rlx(dst + (lane >> 4) * 80, v);
          if (lane < 16) st128_rlx(dst + 160, z);
        }
      }
    }
    fence_async();
    bar_sync(1, 256);
    if (tid == 0) { st_rlx(FLAG(0, r, c), epoch); mbar_arrive(BAR(BR_PUB)); TS(4); }
    const int kvi = (tid >= 80) + (tid >= 160) + (tid >= 240), kd = tid - 80 * kvi;
    const int khd = kd / 20, kt0 = 5 * (khd >> 1) + 2 * (khd & 1);
    const uint32_t rb = sb + OFF_KVB + kd * 16;
    if (kvi < 3) {
      #pragma unroll 1
      for (int m = kvi; m < 7; m += 3) { const int q = kt0 + 3 + m; sts128(rb + (q >= 10 ? q - 10 : q) * 1280, 0, 0, 0, 0); }
    }
    uint32_t qa[20];
    {
      const float sc = 1.44269504089f + __uint_as_float(lds32(sb + OFF_EPOCH) ^ epoch);
      #pragma unroll
      for (int j = 0; j < 10; j++) { qa[2 * j] = pack2(phi(QV(j, 0), sc), phi(QV(j, 1), sc)); qa[2 * j + 1] = pack2(phi(QV(j, 2), sc), phi(QV(j, 3), sc)); }
    }
    if (tid == 0) TS(5);
    if (warp == 7) mbar_wait(BAR(BR_KVP), 0);
    bar_sync(1, 256);
    if (tid == 0) TS(6);
    if (kvi < 3) {
      float s[8];
      zero<8>(s);
      uint32_t bad = 0;
      #pragma unroll 4
      for (int i = 0; i < 16; i += 2) {
        uint32_t w[4], x[4];
        lds128(w, sb + OFF_KVP + tid * 16 + i * 3840); lds128(x, sb + OFF_KVP + tid * 16 + i * 3840 + 3840);
        bad |= (w[3] ^ epoch) | (x[3] ^ epoch);
        #pragma unroll
        for (int e = 0; e < 4; e++) {
          asm("add.rn.bf16x2 %0, %0, %1;" : "+r"(w[e]) : "r"(x[e]));
          s[2 * e] += bf_lo(w[e]); s[2 * e + 1] += bf_hi(w[e]);
        }
      }
      if (__builtin_expect(bad & 1u, 0)) {
        zero<8>(s);
        #pragma unroll 1
        for (int i = 0; i < 16; i++) {
          uint32_t w[4] = {0, 0, 0, ~epoch};
          fix128_w3(w, &g_kvp[(c * 16 + i) * 240 + tid], epoch, 1u);
          #pragma unroll
          for (int e = 0; e < 4; e++) { s[2 * e] += bf_lo(w[e]); s[2 * e + 1] += bf_hi(w[e]); }
        }
        FIXCNT
      }
      const uint32_t p0 = pack2(s[0], s[1]), p1 = pack2(s[2], s[3]), p2 = pack2(s[4], s[5]), p3 = pack2(s[6], s[7]);
      if (kvi < 2) sts128(rb + (kt0 + (khd & 1) + kvi) * 1280, p0, p1, p2, p3);
      else {
        const bool od = khd & 1;
        sts128(rb + (5 * (khd >> 1) + 2) * 1280, od ? 0u : p0, od ? 0u : p1, od ? p0 : 0u, od ? p1 : 0u);
        const uint32_t zz = (p2 & 0xffffu) << (16 * (khd & 1));
        sts128(rb + 10 * 1280, khd < 2 ? zz : 0u, khd < 2 ? 0u : zz, 0u, 0u);
      }
    }
    fence_async();
    bar_sync(1, 256);
    if (tid == 0) { mbar_arrive(BAR(BR_SUM)); TS(7); }
    {
      float oa[44]; zero<44>(oa);
      constexpr uint64_t db = mkdesc(SB0 + OFF_KVB, 128, 1280, 0);
      wg_fence();
      #pragma unroll
      for (int s = 0; s < 5; s++) wg_rs88_tb(oa, &qa[4 * s], desc2((uint32_t)db + ((s == 4 && (c & 1)) ? 0 : (s + (c & 1)) * 16), db >> 32), s != 0);
      wg_commit();
      wg_wait<0>();
      pin<44>(oa);
      if (tid == 0) TS(13);
      float rc[4], rd[2][4];
      #pragma unroll
      for (int e = 0; e < 4; e++) asm("rcp.approx.ftz.f32 %0, %1;" : "=f"(rc[e]) : "f"(oa[40 + e] + 1e-6f));
      #pragma unroll
      for (int h = 0; h < 4; h++) {
        rd[0][h] = __shfl_sync(0xffffffff, rc[h & 1], (lane & 28) | (h >> 1));
        rd[1][h] = __shfl_sync(0xffffffff, rc[2 + (h & 1)], (lane & 28) | (h >> 1));
      }
      #pragma unroll
      for (int j = 0; j < 10; j++) {
        #pragma unroll
        for (int h = 0; h < 2; h++) {
          float f;
          if (j == 2) f = tq < 2 ? rd[h][0] : rd[h][1];
          else if (j == 7) f = tq < 2 ? rd[h][2] : rd[h][3];
          else f = rd[h][(8 * j) / 20];
          qa[2 * j + h] = pack2(oa[4 * j + 2 * h] * f, oa[4 * j + 2 * h + 1] * f);
        }
      }
      const uint32_t m0 = (lane & 7) == ((2 * w4) & 7), m1 = (lane & 7) == 2 * w4 + 1;
      const uint32_t oa_ = sb + OFF_EXTRA + (lane >> 4) * 2048 + (warp * 16 + (lane & 15)) * 16;
      bar_sync(1, 256);
#define TAG(v, m) (((v) & ~(m)) | (epoch & (m)))
      #pragma unroll
      for (int s = 0; s < 5; s++) stsm4(oa_ + s * 4096, TAG(qa[4 * s], m0), TAG(qa[4 * s + 1], m1), TAG(qa[4 * s + 2], m0), TAG(qa[4 * s + 3], m1));
    }
    fence_async();
    __syncwarp();
    if (lane == 0) mbar_arrive(BAR(BR_OSTG));
    if (tid == 0) TS(8);
    }
    asm volatile("setmaxnreg.dec.sync.aligned.u32 136;");
  } else {
    const int g = lane >> 2, tq = lane & 3, t7 = tid & 127;
    uint32_t raw[5][4], pd;
    {
      const int ch = c * 80 + r * 5;
      #pragma unroll
      for (int e = 0; e < 4; e++) {
        const __nv_bfloat16* pp = prm.par[e] + ch * 128 + t7;
        #pragma unroll
        for (int q = 0; q < 5; q++) asm volatile("ld.global.nc.u16 %0, [%1];" : "=r"(raw[q][e]) : "l"(pp + q * 128));
      }
      asm volatile("ld.global.nc.u16 %0, [%1];" : "=r"(pd) : "l"(((lane & 8) ? prm.dskip : prm.logdt) + ch + min(lane & 7, 4)));
    }
    asm volatile("bar.arrive 0, 512;" ::: "memory");
    if (EN_SSM) {
    {
      #pragma unroll 1
      for (int k = 0; k < 4; k++) {
        const uint32_t z = sb + OFF_BLK + k * BLK + t7 * 16;
        sts128(z + B_TBL, 0, 0, 0, 0); sts128(z + B_TBL + 2048, 0, 0, 0, 0);
        if (t7 < 76) sts128(t7 < 64 ? z + BLK - 1024 : z + B_TBL + 3072, 0, 0, 0, 0);
      }
      if (t7 < 64) sts128(sb + OFF_BLK - 1024 + t7 * 16, 0, 0, 0, 0);
      const uint32_t ea = sb + OFF_BLK + (2 + (w4 & 1)) * BLK + (lane >> 4) * 7168 + ((lane >> 3) & 1) * 256 + (lane & 7) * 16 + (w4 >> 1) * 2048;
      constexpr uint64_t dE = mkdesc(SB0 + OFF_BLK + 2 * BLK, 128, 512, 0);
      const uint32_t xa = sb + OFF_BLK + w4 * BLK + B_SP + 16 + lane * 8, xr_ = sb + OFF_BLK + (w4 ^ 2) * BLK + B_SP + 16 + lane * 8;
      uint32_t pr[5][2];
      #pragma unroll
      for (int q = 0; q < 5; q++) {
        #pragma unroll
        for (int e = 0; e < 2; e++) pr[q][e] = raw[q][2 * e] | (raw[q][2 * e + 1] << 16);
        const uint32_t m = __reduce_max_sync(0xffffffff, max(raw[q][2] & 0x7fffu, raw[q][3] & 0x7fffu));
        if (lane == 0) sts32(sb + OFF_EPOCH + 64 + q * 16 + w4 * 4, m);
      }
      bar_sync(4, 128);
      if (t7 == 0) TS(40);
      const int j = (w4 & 1) * 16 + (w4 >> 1) * 8 + g, i2 = tq < 2 ? 64 * tq + j : 32 * (tq - 2) + j;
      const uint32_t e2 = B_TBL + 4 * (tq < 2 ? ((i2 & 1) ? T_D : T_C - 1) + (i2 >> 1) + 16 : T_B + i2);
      const uint32_t e1 = tq < 2 ? (i2 ? e2 - 64 : B_TBL + 4 * (T_A + 63)) : B_TBL + 4 * (i2 ? T_A - 1 + i2 : T_0 + 511);
      const uint32_t e0 = B_TBL + (T_0 + 8 * j + 2 * tq) * 4;
      #pragma unroll 1
      for (int it = 0; it < 5; it++) {
        const int k = it;
        const uint32_t blk = sb + OFF_BLK + k * BLK;
        float fac;
        {
          const int q = it;
          if (it == 4) {
            mbar_wait(BAR(BR_UOUT), 0);
            sts128(sb + OFF_UT + B_TBL + t7 * 16, 0, 0, 0, 0); sts128(sb + OFF_UT + B_TBL + 2048 + t7 * 16, 0, 0, 0, 0);
            if (t7 < 12) sts128(sb + OFF_UT + B_TBL + 4096 + t7 * 16, 0, 0, 0, 0);
          }
          const uint32_t ga = ea + 4096 - (w4 >> 1) * 512;
#define PUT4(i, a, b, c_, d) sts128(((i) < 8 ? ea + ((i) >> 1) * 512 : ga + (((i) - 8) >> 1) * 512) + ((i) & 1) * 128, a, b, c_, d)
          const uint32_t pa0 = pr[0][0], pc0 = pr[0][1];
          const float dt = bf_round(expf(bf_lo(__shfl_sync(0xffffffff, pd, q))));
          #pragma unroll
          for (int e = 0; e < 2; e++) { pr[0][e] = pr[1][e]; pr[1][e] = pr[2][e]; pr[2][e] = pr[3][e]; pr[3][e] = pr[4][e]; }
          uint32_t mm[4];
          lds128(mm, sb + OFF_EPOCH + 64 + q * 16);
          const uint32_t ex = min(max(max(max(mm[0], mm[1]), max(mm[2], mm[3])) >> 7, 1u), 253u);
          const float sc = __uint_as_float((254u - ex) << 23);
          fac = 2.f * dt * __uint_as_float(ex << 23);
          const float lr = -bf_round(expf(bf_lo(pa0))) * dt * 1.44269504089f;
          const float tn = bf_hi(pa0) * dt * 0.15915494309f;
          float z1r, z1i, z2r, z2i, z4r, z4i, xr[8], xi[8], gr[8], gi[8], wr[9], wi[9];
          cexp_t(lr, -tn, z1r, z1i);
          cexp_t(lr * 8.f, tn * 8.f, xr[1], xi[1]);
          cexp_t(lr * 64.f, tn * 64.f, wr[0], wi[0]);
          xr[0] = 1.f; xi[0] = 0.f;
          cmul(xr[1], xi[1], xr[1], xi[1], xr[2], xi[2]); cmul(xr[2], xi[2], xr[1], xi[1], xr[3], xi[3]);
          cmul(xr[2], xi[2], xr[2], xi[2], xr[4], xi[4]);
          #pragma unroll
          for (int b = 1; b < 4; b++) cmul(xr[4], xi[4], xr[b], xi[b], xr[4 + b], xi[4 + b]);
          cmul(wr[0], wi[0], wr[0], wi[0], wr[1], wi[1]); cmul(wr[1], wi[1], wr[0], wi[0], wr[2], wi[2]);
          cmul(wr[1], wi[1], wr[1], wi[1], wr[3], wi[3]); cmul(wr[3], wi[3], wr[3], wi[3], wr[4], wi[4]);
          cmul(wr[4], wi[4], wr[3], wi[3], wr[5], wi[5]); cmul(wr[4], wi[4], wr[4], wi[4], wr[6], wi[6]);
          cmul(wr[6], wi[6], wr[4], wi[4], wr[7], wi[7]); cmul(wr[6], wi[6], wr[6], wi[6], wr[8], wi[8]);
          uint32_t R[4], I[4], PR[4], PI[4];
          #pragma unroll
          for (int b = 0; b < 4; b++) { R[b] = packh(xr[2 * b], xr[2 * b + 1]); I[b] = packh(xi[2 * b], xi[2 * b + 1]); }
          PUT4(0, R[0], R[1], R[2], R[3]); PUT4(1, I[0], I[1], I[2], I[3]);
          #pragma unroll
          for (int i = 0; i < 3; i++) {
            const uint32_t z = packh(wr[i], wi[i]);
            #pragma unroll
            for (int b = 0; b < 4; b++) hcm2(R[b], I[b], z, PR[b], PI[b]);
            PUT4(2 * i + 2, PR[0], PR[1], PR[2], PR[3]); PUT4(2 * i + 3, PI[0], PI[1], PI[2], PI[3]);
          }
          gr[0] = bf_lo(pc0) * sc; gi[0] = -bf_hi(pc0) * sc;
          cmul(z1r, z1i, z1r, z1i, z2r, z2i); cmul(z2r, z2i, z2r, z2i, z4r, z4i);
          cmul(gr[0], gi[0], z1r, z1i, gr[1], gi[1]);
          cmul(gr[0], gi[0], z2r, z2i, gr[2], gi[2]); cmul(gr[1], gi[1], z2r, z2i, gr[3], gi[3]);
          #pragma unroll
          for (int b = 0; b < 4; b++) cmul(gr[b], gi[b], z4r, z4i, gr[4 + b], gi[4 + b]);
          PUT4(8, packh(gr[0], gr[1]), packh(gr[2], gr[3]), packh(gr[4], gr[5]), packh(gr[6], gr[7]));
          PUT4(9, packh(gi[0], gi[1]), packh(gi[2], gi[3]), packh(gi[4], gi[5]), packh(gi[6], gi[7]));
          {
            const uint32_t z = packh(wr[3], -wi[3]), a4r = packh(gr[0], gr[4]), a4i = packh(gi[0], gi[4]);
            hcm2(packh(gr[0], gr[2]), packh(gi[0], gi[2]), z, PR[0], PI[0]);
            hcm2(packh(gr[4], gr[6]), packh(gi[4], gi[6]), z, PR[1], PI[1]);
            hcm2(a4r, a4i, packh(wr[4], -wi[4]), PR[2], PI[2]);
            hcm2(a4r, a4i, packh(wr[5], -wi[5]), PR[3], PI[3]);
            PUT4(10, PR[0], PR[1], PR[2], PR[3]); PUT4(11, PI[0], PI[1], PI[2], PI[3]);
            float hr, hi_;
            cmul(gr[0], gi[0], wr[3], -wi[3], hr, hi_);
            const uint32_t cr = packh(gr[0], hr), ci = packh(gi[0], hi_);
            #pragma unroll
            for (int i = 0; i < 3; i++) hcm2(cr, ci, packh(wr[6 + i], -wi[6 + i]), PR[i], PI[i]);
            PUT4(12, PR[0], PR[1], PR[2], 0u); PUT4(13, PI[0], PI[1], PI[2], 0u);
          }
          fence_async();
          bar_sync(4, 128);
        }
        float ka[24]; zero<24>(ka);
        wg_fence();
        #pragma unroll
        for (int s = 0; s < 8; s++) {
          const uint64_t d = dE + (s >> 2) * (BLK >> 4) + ((s >> 1) & 1) * 448 + (s & 1) * 16;
          wg_ss48_tt_h(ka, d, d + 256, s != 0);
        }
        wg_commit();
        const float dsk = bf_lo(__shfl_sync(0xffffffff, pd, 8 + it));
        wg_wait<0>();
        pin<24>(ka);
        float kk[6];
        const bool up = w4 >= 2;
        #pragma unroll
        for (int n = 0; n < 3; n++) {
          sts64f(xa + n * 256, up ? ka[12 + 4 * n] : ka[4 * n + 2], up ? ka[13 + 4 * n] : ka[4 * n + 3]);
          kk[2 * n] = up ? ka[14 + 4 * n] : ka[4 * n]; kk[2 * n + 1] = up ? ka[15 + 4 * n] : ka[4 * n + 1];
        }
        if (it) bar_sync(4, 128); else bar_sync(8, 160);
          if (it == 4 && w4 == 0) {
            mbar_wait(BAR(BR_U), 0);
            if (elect_one()) {
              mbar_expect_tx(BAR(BR_U2), 8192);
              bulk_ld(blk - 2 * BLK, g_uy + (c * 80 + r * 5 + 2) * 2048, 4096, BAR(BR_U2)); bulk_ld(blk - BLK, g_uy + (c * 80 + r * 5 + 3) * 2048, 4096, BAR(BR_U2));
            }
            __syncwarp();
          }
        #pragma unroll
        for (int n = 0; n < 3; n++) {
          uint32_t o[2]; lds64(o, xr_ + n * 256);
          kk[2 * n] = (kk[2 * n] + __uint_as_float(o[0])) * fac; kk[2 * n + 1] = (kk[2 * n + 1] + __uint_as_float(o[1])) * fac;
        }
        if (t7 == 0) kk[0] += dsk;
        {
          const uint32_t v = pack2(kk[1], kk[0]), vh = v >> 16;
          const uint32_t u = pack2(kk[2], kk[3]), w = pack2(kk[4], kk[5]), uu = pack2(kk[2], kk[2]), us = pack2(kk[3], kk[2]);
          const uint32_t x = tq < 2 ? w : u, xh = x >> 16;
          sts32(blk + e0 + 4, v); sts16(blk + e0, vh); sts16(blk + e0 + 10, v);
          sts16(blk + e1, x); sts16(blk + e1 + 6, x); sts16(blk + e2, xh); sts16(blk + e2 + 6, xh);
          if (tq < 2) {
            const uint32_t pb = blk + e0 + 1024 + 8 * tq;
            sts32(pb + 4, uu); sts32(pb + 8, us); sts16(pb + 14, us);
            if (i2) { sts16(pb - 4, u); sts32(pb, uu); }
          }
          if (i2 == 0) {
            const uint32_t tb = blk + B_TBL;
            if (tq == 0) { sts16(tb + (T_0 + 256) * 4, u); sts32(blk + B_SP, w << 16); }
            else { sts32(tb + (T_0 + 512) * 4, uu); sts32(tb + (T_0 + 513) * 4, uu); sts32(tb + (T_0 + 514) * 4, uu); sts16(tb + (T_0 + 515) * 4 + 2, u); sts16(tb + (T_C + 63) * 4, w); }
          }
        }
        if (t7 == 0) TS(49 + it);
      }
    }
    asm volatile("setmaxnreg.inc.sync.aligned.u32 136;");
    if (t7 == 0) TS(41);
    bar_sync(4, 128);
    if (t7 == 0) mbar_arrive(BAR(BR_KS));
    if (EN_ATT) mbar_wait(BAR(BR_GEMM), 0);
    }
  }
  const int tid = rtid(), lane = tid & 31, g = lane >> 2, tq = lane & 3, t7 = tid & 127;
  mbar_wait(BAR(BR_EPOCH), 0);
  const unsigned epoch = lds32(sb + OFF_EPOCH);
  const uint32_t ytag = (epoch & 1u) * 0x10001u, ym = lane < 4 ? 0x10001u : 0u;
#define YTAG(v) (((v) & ~ym) | (ytag & ym))
  if (EN_SSM) {
    mbar_wait(BAR(BR_KS), 0);
    mbar_wait(BAR(wg < 2 ? BR_U2 : BR_U), 0);
    mbar_wait(BAR(wg < 2 ? BR_DRDY + 1 : BR_DRDY), 0);
    if (tid == 256) TS(42);
    const int up = w4 >> 1;
    #pragma unroll 1
    for (int n = wg < 2 ? 3 + wg : 0; n < (wg < 2 ? 4 + wg : 3); n++) {
      const int k = ORD(n);
      const uint32_t blk = sb + OFF_BLK + k * BLK, tb = blk + B_TBL + (uint32_t)((g - 2 * tq) * 4);
      uint32_t A0[32], A1[32];
      {
        constexpr uint64_t dd0 = mkdesc(SB0 + OFF_BLK + B_D, 128, 1024, 0);
        const uint32_t dd = (uint32_t)dd0 + k * (BLK >> 4), tf = tb + (16 * w4 - 48) * 4;
        float aC[8], a24[12], a16[8];
        zero<8>(aC); zero<12>(a24); zero<8>(a16);
#define FAR4(fn, acc, A, off, first) _Pragma("unroll") for (int s = 0; s < 4; s++) fn(acc, &(A)[4 * s], desc2(dd + ((off) >> 4) + (3 - s) * 16, dd0 >> 32), !(first) || s != 0);
        load_toep<4>(A0, tf + T_C * 4); load_toep<4>(A0 + 16, tf + T_D * 4); load_toep<8>(A1, tf + T_A * 4);
        wg_fence();
        FAR4(wg_rs16_tb, aC, A0, B_D9, true) FAR4(wg_rs16_tb, aC, A0 + 16, B_D7, false)
        wg_commit();
        FAR4(wg_rs24_tb, a24, A1, 0, true) FAR4(wg_rs16_tb, a16, A1 + 16, 0, true)
        wg_commit();
        wg_wait<1>();
        load_toep<8>(A0, tf + T_B * 4);
        wg_fence();
        FAR4(wg_rs24_tb, a24, A0, B_D3, false) FAR4(wg_rs16_tb, a16, A0 + 16, B_D3, false)
        wg_commit();
        const float kc = ldsf(blk + B_SP);
        float cx[8];
        #pragma unroll
        for (int e = 0; e < 4; e++) {
          const int s4 = 256 * w4 + 16 * g + 128 * (e >> 1) + 8 * (e & 1) + 2 * tq - 4, s2 = s4 + 2;
          const uint32_t u4 = lds32(blk + (uint32_t)((2 * s4) ^ ((s4 >> 2) & 0x30))), u2 = lds32(blk + (uint32_t)((2 * s2) ^ ((s2 >> 2) & 0x30)));
          cx[2 * e] = kc * (bf_lo(u4) + bf_hi(u4)); cx[2 * e + 1] = kc * (bf_hi(u4) + bf_lo(u2));
        }
        wg_wait<0>();
        pin<8>(aC); pin<12>(a24); pin<8>(a16);
        if (t7 == 0 && k == 1) TS(57);
        bar_sync(2 + wg, 128);
        const uint32_t f1 = blk + B_D + (128 * w4 + ((8 * g) ^ (16 * (w4 & 1))) + 2 * tq) * 4;
        const uint32_t f2 = blk + B_D + 6144 + (256 * w4 + ((16 * g) ^ (8 * (g >> 2))) + 2 * tq) * 4;
        #pragma unroll
        for (int h = 0; h < 2; h++) {
          #pragma unroll
          for (int jp = 0; jp < 3; jp++) {
            float x = a24[4 * jp + 2 * h], y = a24[4 * jp + 2 * h + 1];
            if (jp > 0) { x += a16[4 * (jp - 1) + 2 * h]; y += a16[4 * (jp - 1) + 2 * h + 1]; }
            sts64f((f1 ^ (32 * h)) + (64 * h + 512 * jp) * 4, x, y);
          }
          #pragma unroll
          for (int n = 0; n < 2; n++)
            sts64f((f2 ^ (64 * h + 32 * n)) + 128 * h * 4, aC[4 * n + 2 * h] + cx[4 * h + 2 * n], aC[4 * n + 2 * h + 1] + cx[4 * h + 2 * n + 1]);
        }
      }
      float aY[32];
      const uint32_t td = tb + (T_0 + 16 * (w4 & 1) + 256 * up - 16) * 4;
      load_toep<8>(A1, td);
      bar_sync(2 + wg, 128);
      {
        const uint32_t b0 = blk + B_D + (up ? 6144 - 3072 : 0u - 2048u) + (64 * tq + ((16 * (w4 & 1)) ^ (8 * tq)) + g) * 4;
        zero<12>(aY);
        #pragma unroll
        for (int n = 2; n < 8; n++)
          #pragma unroll
          for (int e = 0; e < 4; e++)
            if (n > 2 || !up) aY[4 * n + e] = ldsf((b0 ^ (32 * (e >> 1))) + (256 * n + 32 * (e & 1)) * 4);
      }
      if (t7 == 0 && k == 1) TS(58);
      {
        constexpr uint64_t du0 = mkdesc(SB0 + OFF_BLK + 32, 16, 512, 2);
        const uint32_t du = (uint32_t)du0 + k * (BLK >> 4);
#define DEN(A, n, s0) _Pragma("unroll") for (int s = 0; s < (n); s++) wg_rs64(aY, &(A)[4 * s], desc2(du - ((s0) + s) * 2, du0 >> 32), 1);
        wg_fence();
        load_toep<4>(A0, td + 8 * 64);
        DEN(A1, 4, 0) wg_commit();
        wg_fence();
        load_toep<4>(A0 + 16, td + 12 * 64);
        DEN(A1 + 16, 4, 4) wg_commit();
        wg_wait<1>(); wg_fence();
        load_toep<3>(A1, up ? td + 16 * 64 : tb + (T_0 + 530) * 4);
        DEN(A0, 8, 8) wg_commit();
        wg_fence();
        DEN(A1, 3, 16) wg_commit();
        wg_wait<0>();
        pin<32>(aY);
      }
      if (t7 == 0 && k == 1) TS(59);
      {
        const uint32_t xw = blk + B_D + w4 * 2048 + lane * 16, xr = blk + B_D + (w4 ^ 2) * 2048 + lane * 16;
        const int jr = 8 * (lane >> 4) + (lane & 7);
        const uint32_t ya = blk + up * 2048 + jr * 64 + (((2 * (w4 & 1) + ((lane >> 3) & 1)) ^ ((jr >> 1) & 3)) << 4);
        float y[16];
        bar_sync(2 + wg, 128);
        #pragma unroll
        for (int n = 0; n < 4; n++) {
          sts128(xw + n * 512, __float_as_uint(up ? (n ? aY[4 * n - 4] : 0.f) : aY[16 + 4 * n]), __float_as_uint(up ? (n ? aY[4 * n - 3] : 0.f) : aY[17 + 4 * n]),
                 __float_as_uint(up ? (n ? aY[4 * n - 2] : 0.f) : aY[18 + 4 * n]), __float_as_uint(up ? (n ? aY[4 * n - 1] : 0.f) : aY[19 + 4 * n]));
          #pragma unroll
          for (int e = 0; e < 4; e++) y[4 * n + e] = up ? aY[12 + 4 * n + e] : aY[4 * n + e];
        }
        bar_sync(2 + wg, 128);
        #pragma unroll
        for (int n = 0; n < 4; n++) {
          uint32_t o[4]; lds128(o, xr + n * 512);
          #pragma unroll
          for (int e = 0; e < 4; e++) y[4 * n + e] += __uint_as_float(o[e]);
        }
        #pragma unroll
        for (int n = 0; n < 4; n += 2)
          stsm4t(ya + n * 512, YTAG(pack2(y[4 * n], y[4 * n + 1])), pack2(y[4 * n + 2], y[4 * n + 3]), YTAG(pack2(y[4 * n + 4], y[4 * n + 5])), pack2(y[4 * n + 6], y[4 * n + 7]));
      }
      fence_async();
      __syncwarp();
      if (lane == 0) mbar_arrive(BAR(BR_Y) + 8 * n);
      if (t7 == 0) TS(n == 0 ? 56 : n == 1 ? 60 : n == 2 ? 61 : n + 13);
    }
  }
  if (wg < 2) {
    if (EN_ATT) {
    float oc[40]; zero<40>(oc);
    {
      constexpr uint64_t dw0 = mkdesc(SB0, OFF_WOR, 1024, 1), da0 = mkdesc(SB0, 2048, 128, 0);
      const uint32_t ck = sb + tid * 32 + ((lane >> 2) << 2), ck2 = ck + (wg ? 0 : 16384);
      uint32_t bad = 0;
      auto tile = [&](int i, uint32_t so) {
        const uint32_t al = (uint32_t)da0 + wg * 64 + (so >> 4), wl = (uint32_t)dw0 + i * 640 - (i >> 1) * (1278 << 16);
        wg_fence();
        #pragma unroll
        for (int s = 0; s < 5; s++) wg_ss80_tb(oc, desc2(al + s * 256, da0 >> 32), desc2(wl + s * 128, dw0 >> 32), (i | s) != 0);
        wg_commit();
        bad |= (lds32(ck + so) ^ epoch) | (lds32(ck + so + 8192) ^ epoch) | (lds32(ck2 + so) ^ epoch);
      };
      if (w4 == 0) {
        if (EN_SSM) mbar_wait(BAR(BR_Y + 2), 0);
        mbar_wait(BAR(BR_WO), 0);
        mbar_wait(BAR(BR_WO + 1), 0);
      }
      bar_sync(1, 256);
      if (tid == 0) TS(9);
      tile(0, SLOT(0));
      #pragma unroll 1
      for (int i = 1; i < 8; i++) {
        mbar_wait(BAR(BR_OFULL) + 8 * i, 0);
        tile(i, SLOT(i));
        wg_wait<1>();
        if (lane == 0) mbar_arrive(BAR(BR_OEMPTY - 1) + 8 * i);
      }
      #pragma unroll 1
      for (int n = 0; n < 56; n++) {
        const int i = n & 7;
        if (i == 0) {
          uint32_t any;
          asm volatile("{\n.reg .pred p;\nsetp.ne.u32 p, %1, 0;\nbarrier.red.or.pred p, 1, 256, p;\nselp.u32 %0, 1, 0, p;\n}" : "=r"(any) : "r"(bad & 1u) : "memory");
          if (!any) break;
          bad = 0;
          FIXCNT
        }
        wg_wait<0>();
        bar_sync(1, 256);
        if (tid == 0) { mbar_expect_tx(BAR(BR_RETRY), 20480); bulk_ld(sb + SLOT(5), &g_o[(r * 8 + CHUNK(i)) * 1280], 20480, BAR(BR_RETRY)); }
        mbar_wait(BAR(BR_RETRY), n & 1);
        tile(i, SLOT(5));
      }
      wg_wait<0>();
      pin<40>(oc);
    }
    if (tid == 0) TS(10);
    {
      const int row = w4 * 16 + (lane & 15);
      const uint32_t ob = sb + SLOT(4) + wg * 10240;
      #pragma unroll
      for (int j = 0; j < 8; j += 2)
        stsm4(ob + row * 128 + (((j + (lane >> 4)) ^ (row & 7)) << 4), pack2(oc[4 * j], oc[4 * j + 1]), pack2(oc[4 * j + 2], oc[4 * j + 3]),
              pack2(oc[4 * j + 4], oc[4 * j + 5]), pack2(oc[4 * j + 6], oc[4 * j + 7]));
      stsm4(ob + 8192 + row * 32 + (lane >> 4) * 16, pack2(oc[32], oc[33]), pack2(oc[34], oc[35]), pack2(oc[36], oc[37]), pack2(oc[38], oc[39]));
      fence_async();
      bar_sync(2 + wg, 128);
      if (w4 == 0 && elect_one()) {
        tma2d_st(&prm.m[M_O64], ob, 640 + c * 64, r * 128 + wg * 64);
        tma2d_st(&prm.m[M_O16], ob + 8192, 1152 + c * 16, r * 128 + wg * 64);
        bulk_commit(); bulk_wait0_read();
        if (wg == 0) { TS(11); DUMP(0, 20); }
      }
    }
    }
  } else if (EN_SSM) {
    if (t7 == 0) DUMP(40, 64);
    #pragma unroll 1
    for (int n = 0; n < 64; n++) if (!y_transpose(sb, w4, lane, ytag, r)) break;
  }
  }
}

typedef CUresult (*EncFn)(CUtensorMap*, CUtensorMapDataType, cuuint32_t, void*, const cuuint64_t*, const cuuint64_t*, const cuuint32_t*,
                          const cuuint32_t*, CUtensorMapInterleave, CUtensorMapSwizzle, CUtensorMapL2promotion, CUtensorMapFloatOOBfill);
static void mkmap(EncFn enc, CUtensorMap* m, const void* base, int rank, const cuuint64_t* dims, const cuuint64_t* strides, const cuuint32_t* box, CUtensorMapSwizzle swz) {
  cuuint32_t es[5] = {1, 1, 1, 1, 1};
  enc(m, CU_TENSOR_MAP_DATA_TYPE_BFLOAT16, rank, const_cast<void*>(base), dims, strides, box, es, CU_TENSOR_MAP_INTERLEAVE_NONE, swz,
      CU_TENSOR_MAP_L2_PROMOTION_L2_128B, CU_TENSOR_MAP_FLOAT_OOB_FILL_NONE);
}

extern "C" void kernel_launch(void* const* d_in, const int* in_sizes, int n_in, void* d_out, int out_size) {
  void* fn = nullptr; cudaDriverEntryPointQueryResult qr;
  cudaGetDriverEntryPoint("cuTensorMapEncodeTiled", &fn, cudaEnableDefault, &qr);
  EncFn enc = (EncFn)fn;
  void* uy = nullptr; cudaGetSymbolAddress(&uy, g_uy);
  const cuuint64_t dx[2] = {640, 2048}, sx[1] = {1280};
  const cuuint32_t bx[2] = {64, 128}, bu[2] = {80, 128};
  const cuuint64_t dw[3] = {640, 640, 3}, sw[2] = {3840, 1280};
  const cuuint32_t br[3] = {16, 32, 3};
  const cuuint64_t dwa[4] = {64, 640, 10, 3}, swa[3] = {3840, 128, 1280}, dwb[4] = {32, 640, 20, 3}, swb[3] = {3840, 64, 1280};
  const cuuint32_t bwa[4] = {64, 32, 1, 3}, bwb[4] = {32, 32, 2, 3};
  const cuuint64_t dwo[2] = {640, 640};
  const cuuint32_t bwo[2] = {64, 80}, bo64[2] = {64, 64}, bo16[2] = {16, 64};
  const cuuint64_t dsa[2] = {2048, 1280}, ssa[1] = {4096};
  const cuuint32_t bsa[2] = {64, 80};
  const cuuint64_t dout[2] = {1280, 2048}, sout[1] = {2560};
  Params prm;
  mkmap(enc, &prm.m[M_X], d_in[7], 2, dx, sx, bx, CU_TENSOR_MAP_SWIZZLE_128B);
  mkmap(enc, &prm.m[M_W128], d_in[8], 4, dwa, swa, bwa, CU_TENSOR_MAP_SWIZZLE_128B);
  mkmap(enc, &prm.m[M_W64], d_in[8], 4, dwb, swb, bwb, CU_TENSOR_MAP_SWIZZLE_64B);
  mkmap(enc, &prm.m[M_WR], d_in[8], 3, dw, sw, br, CU_TENSOR_MAP_SWIZZLE_32B);
  mkmap(enc, &prm.m[M_U], d_in[0], 2, dx, sx, bu, CU_TENSOR_MAP_SWIZZLE_NONE);
  mkmap(enc, &prm.m[M_WO], d_in[9], 2, dwo, sx, bwo, CU_TENSOR_MAP_SWIZZLE_128B);
  mkmap(enc, &prm.m[M_O64], d_out, 2, dout, sout, bo64, CU_TENSOR_MAP_SWIZZLE_128B);
  mkmap(enc, &prm.m[M_O16], d_out, 2, dout, sout, bo16, CU_TENSOR_MAP_SWIZZLE_NONE);
  mkmap(enc, &prm.m[M_SA], uy, 2, dsa, ssa, bsa, CU_TENSOR_MAP_SWIZZLE_128B);
  mkmap(enc, &prm.m[M_OUT], d_out, 2, dout, sout, bu, CU_TENSOR_MAP_SWIZZLE_NONE);
  prm.u = (const __nv_bfloat16*)d_in[0]; prm.wo = (const __nv_bfloat16*)d_in[9];
  for (int i = 0; i < 4; i++) prm.par[i] = (const __nv_bfloat16*)d_in[1 + i];
  prm.logdt = (const __nv_bfloat16*)d_in[5]; prm.dskip = (const __nv_bfloat16*)d_in[6];
  cudaFuncSetAttribute(fused_kernel, cudaFuncAttributeMaxDynamicSharedMemorySize, SMEM_BYTES);
  cudaLaunchConfig_t cfg = {};
  cfg.gridDim = dim3(128); cfg.blockDim = dim3(512); cfg.dynamicSmemBytes = SMEM_BYTES; cfg.stream = cudaStreamPerThread;
  cudaLaunchAttribute at[1];
  at[0].id = cudaLaunchAttributeClusterDimension; at[0].val.clusterDim.x = 2; at[0].val.clusterDim.y = 1; at[0].val.clusterDim.z = 1;
  cfg.attrs = at; cfg.numAttrs = 1;
  cudaLaunchKernelEx(&cfg, fused_kernel, prm);
}
```

```cpp
#include <cuda_runtime.h>
#include <cuda_bf16.h>
#include <cuda_fp16.h>
#include <cuda.h>
#include <stdint.h>

#define KST 2
#define UKB 4
#define UPF 0
#define CONV_AT 1
#define EN_ATT 1
#define EN_SSM 1

__device__ __align__(1024) __nv_bfloat16 g_uy[2 * 640 * 2048];
__device__ __align__(128) uint4 g_kvp[8 * 16 * 240];
__device__ __align__(128) uint4 g_o[128 * 1280];
__device__ __align__(128) unsigned g_flag[4 * 128 * 32];
__device__ unsigned g_epoch[128];
#define TS(i) do {} while (0)
#define DUMP(lo, hi) do {} while (0)
#define FIXCNT

constexpr uint32_t SB0 = 1024;
constexpr uint32_t W_SLOT = 15360, OFF_X = 76800;
constexpr uint32_t OFF_WOR = 81920, OFF_KVP = 10240, OFF_KVS = 71680, OFF_PK = 10240, OFF_V = 30720, OFF_EXTRA = 102400, OFF_KVB = OFF_EXTRA;
constexpr uint32_t OFF_BAR = 125952, OFF_BLK = 128000, BLK = 20480;
constexpr uint32_t B_D = 4096, B_D5 = 3088, B_D7 = 6176, B_D9 = 8224, B_TBL = 14400;
constexpr int T_S = 576, T_F2 = 624, T_F3 = 816;
constexpr uint32_t OFF_UT = OFF_BLK + 4 * BLK;
constexpr uint32_t SMEM_BYTES = OFF_BLK + 5 * BLK;
enum { BR_FULL = 0, BR_WO = 5, BR_PUB = 7, BR_KVP = 8, BR_U = 9, BR_SUM = 10, BR_GEMM = 11, BR_UIN = 12, BR_YIN = 13, BR_EPOCH = 14,
       BR_FREE = 15, BR_RETRY = 17, BR_UOUT = 18, BR_OFULL = 18, BR_KS = 26, BR_EMPTY = 31, BR_OEMPTY = 36, BR_Y = 43, BR_OSTG = 45,
       BR_DRDY = 46, BR_U2 = 48, BR_COUNT = 50 };
constexpr uint32_t OFF_EPOCH = OFF_BAR + 8 * BR_COUNT;
enum { M_X, M_W128, M_W64, M_WR, M_U, M_WO, M_O64, M_O16, M_SA, M_OUT, M_COUNT };

__device__ __forceinline__ long long clk64() { long long t; asm volatile("mov.u64 %0, %%clock64;" : "=l"(t) :: "memory"); return t; }
__device__ __forceinline__ uint32_t smem_u32(const void* p) { return (uint32_t)__cvta_generic_to_shared(p); }
__host__ __device__ constexpr uint64_t mkdesc(uint32_t addr, uint32_t lbo, uint32_t sbo, uint32_t swz) {
  return (uint64_t)((addr & 0x3FFFF) >> 4) | ((uint64_t)(lbo >> 4) << 16) | ((uint64_t)(sbo >> 4) << 32) | ((uint64_t)swz << 62);
}
__device__ __forceinline__ uint64_t desc2(uint32_t lo, uint32_t hi) { uint64_t d; asm("mov.b64 %0, {%1, %2};" : "=l"(d) : "r"(lo), "r"(hi)); return d; }
__device__ __forceinline__ void mbar_init(uint32_t bar, uint32_t cnt) { asm volatile("mbarrier.init.shared::cta.b64 [%0], %1;" :: "r"(bar), "r"(cnt) : "memory"); }
__device__ __forceinline__ void mbar_expect_tx(uint32_t bar, uint32_t bytes) { asm volatile("mbarrier.arrive.expect_tx.shared::cta.b64 _, [%0], %1;" :: "r"(bar), "r"(bytes) : "memory"); }
__device__ __forceinline__ void mbar_arrive(uint32_t bar) { asm volatile("mbarrier.arrive.shared::cta.b64 _, [%0];" :: "r"(bar) : "memory"); }
__device__ __forceinline__ void mbar_wait(uint32_t bar, uint32_t parity) {
  asm volatile("{\n.reg .pred p;\n.reg .u32 c;\nmov.u32 c, 0;\n"
    "WL:\nmbarrier.try_wait.parity.shared::cta.b64 p, [%0], %1;\n@p bra WD;\n"
    "add.u32 c, c, 1;\nsetp.lt.u32 p, c, 200000;\n@p bra WL;\nWD:\n}" :: "r"(bar), "r"(parity) : "memory");
}
__device__ __forceinline__ void poll_all(const unsigned* p, unsigned val) {
  asm volatile("{\n.reg .pred p;\n.reg .u32 c, v;\nmov.u32 c, 0;\n"
    "PL:\nld.relaxed.gpu.global.u32 v, [%0];\nsetp.eq.u32 p, v, %1;\nvote.sync.all.pred p, p, 0xffffffff;\n@p bra PD;\n"
    "add.u32 c, c, 1;\nsetp.lt.u32 p, c, 100000;\n@p bra PL;\nPD:\n}" :: "l"(p), "r"(val) : "memory");
}
__device__ __forceinline__ void poll_all_acq(const unsigned* p, unsigned val) {
  asm volatile("{\n.reg .pred p;\n.reg .u32 c, v;\nmov.u32 c, 0;\n"
    "PL:\nld.acquire.gpu.global.u32 v, [%0];\nsetp.eq.u32 p, v, %1;\nvote.sync.all.pred p, p, 0xffffffff;\n@p bra PD;\n"
    "nanosleep.u32 300;\nadd.u32 c, c, 1;\nsetp.lt.u32 p, c, 100000;\n@p bra PL;\nPD:\n}" :: "l"(p), "r"(val) : "memory");
}
__device__ __forceinline__ unsigned poll_bit(const unsigned* p, unsigned val, unsigned mask) {
  unsigned bal;
  asm volatile("{\n.reg .pred p;\n.reg .u32 c, v;\nmov.u32 c, 0;\n"
    "PL:\nld.relaxed.gpu.global.u32 v, [%1];\nsetp.eq.u32 p, v, %2;\nvote.sync.ballot.b32 %0, p, 0xffffffff;\n"
    "and.b32 v, %0, %3;\nsetp.ne.u32 p, v, 0;\n@p bra PD;\n"
    "add.u32 c, c, 1;\nsetp.lt.u32 p, c, 100000;\n@p bra PL;\nPD:\n}" : "=&r"(bal) : "l"(p), "r"(val), "r"(mask) : "memory");
  return bal;
}
__device__ __forceinline__ void fix128_w0(uint32_t* v, const void* p, uint32_t tag, uint32_t mask) {
  asm volatile("{\n.reg .pred p;\n.reg .u32 c, x;\n.reg .b128 t;\n.reg .b64 lo, hi;\nmov.u32 c, 0;\n"
    "FL:\nxor.b32 x, %0, %5;\nand.b32 x, x, %6;\nsetp.eq.u32 p, x, 0;\n@p bra FD;\n"
    "ld.relaxed.gpu.global.b128 t, [%4];\nmov.b128 {lo, hi}, t;\nmov.b64 {%0, %1}, lo;\nmov.b64 {%2, %3}, hi;\n"
    "add.u32 c, c, 1;\nsetp.lt.u32 p, c, 100000;\n@p bra FL;\nFD:\n}"
    : "+r"(v[0]), "+r"(v[1]), "+r"(v[2]), "+r"(v[3]) : "l"(p), "r"(tag), "r"(mask) : "memory");
}
__device__ __forceinline__ void fix128_w3(uint32_t* v, const void* p, uint32_t tag, uint32_t mask) {
  asm volatile("{\n.reg .pred p;\n.reg .u32 c, x;\n.reg .b128 t;\n.reg .b64 lo, hi;\nmov.u32 c, 0;\n"
    "FL:\nxor.b32 x, %3, %5;\nand.b32 x, x, %6;\nsetp.eq.u32 p, x, 0;\n@p bra FD;\n"
    "ld.relaxed.gpu.global.b128 t, [%4];\nmov.b128 {lo, hi}, t;\nmov.b64 {%0, %1}, lo;\nmov.b64 {%2, %3}, hi;\n"
    "add.u32 c, c, 1;\nsetp.lt.u32 p, c, 100000;\n@p bra FL;\nFD:\n}"
    : "+r"(v[0]), "+r"(v[1]), "+r"(v[2]), "+r"(v[3]) : "l"(p), "r"(tag), "r"(mask) : "memory");
}
__device__ __forceinline__ void fence_acq() { asm volatile("fence.acq_rel.gpu;" ::: "memory"); }
__device__ __forceinline__ bool elect_one() {
  uint32_t p; asm volatile("{\n.reg .pred P;\nelect.sync _|P, 0xffffffff;\nselp.u32 %0, 1, 0, P;\n}" : "=r"(p)); return p;
}
__device__ __forceinline__ void bar_sync(int id, int n) { asm volatile("bar.sync %0, %1;" :: "r"(id), "r"(n) : "memory"); }
__device__ __forceinline__ void fence_async() { asm volatile("fence.proxy.async.shared::cta;" ::: "memory"); }
__device__ __forceinline__ void fence_async_g() { asm volatile("fence.proxy.async.global;" ::: "memory"); }
__device__ __forceinline__ void tma2d(uint32_t dst, const CUtensorMap* m, uint32_t bar, int c0, int c1) {
  asm volatile("cp.async.bulk.tensor.2d.shared::cluster.global.mbarrier::complete_tx::bytes [%0], [%1, {%3, %4}], [%2];"
    :: "r"(dst), "l"(m), "r"(bar), "r"(c0), "r"(c1) : "memory");
}
__device__ __forceinline__ void tma3d(uint32_t dst, const CUtensorMap* m, uint32_t bar, int c0, int c1, int c2) {
  asm volatile("cp.async.bulk.tensor.3d.shared::cluster.global.mbarrier::complete_tx::bytes [%0], [%1, {%3, %4, %5}], [%2];"
    :: "r"(dst), "l"(m), "r"(bar), "r"(c0), "r"(c1), "r"(c2) : "memory");
}
__device__ __forceinline__ void tma4d(uint32_t dst, const CUtensorMap* m, uint32_t bar, int c0, int c1, int c2, int c3) {
  asm volatile("cp.async.bulk.tensor.4d.shared::cluster.global.mbarrier::complete_tx::bytes [%0], [%1, {%3, %4, %5, %6}], [%2];"
    :: "r"(dst), "l"(m), "r"(bar), "r"(c0), "r"(c1), "r"(c2), "r"(c3) : "memory");
}
__device__ __forceinline__ void tma2d_st(const CUtensorMap* m, uint32_t src, int c0, int c1) {
  asm volatile("cp.async.bulk.tensor.2d.global.shared::cta.bulk_group [%0, {%2, %3}], [%1];"
    :: "l"(m), "r"(src), "r"(c0), "r"(c1) : "memory");
}
__device__ __forceinline__ void bulk_ld(uint32_t dst, const void* src, uint32_t bytes, uint32_t bar) {
  asm volatile("cp.async.bulk.shared::cluster.global.mbarrier::complete_tx::bytes [%0], [%1], %2, [%3];"
    :: "r"(dst), "l"(src), "r"(bytes), "r"(bar) : "memory");
}
__device__ __forceinline__ void bulk_st(void* dst, uint32_t src, uint32_t bytes) {
  asm volatile("cp.async.bulk.global.shared::cta.bulk_group [%0], [%1], %2;" :: "l"(dst), "r"(src), "r"(bytes) : "memory");
}
__device__ __forceinline__ void bulk_commit() { asm volatile("cp.async.bulk.commit_group;" ::: "memory"); }
__device__ __forceinline__ void bulk_wait0() { asm volatile("cp.async.bulk.wait_group 0;" ::: "memory"); }
__device__ __forceinline__ void bulk_wait0_read() { asm volatile("cp.async.bulk.wait_group.read 0;" ::: "memory"); }
__device__ __forceinline__ unsigned ld_rlx(const unsigned* p) { unsigned v; asm volatile("ld.relaxed.gpu.global.u32 %0, [%1];" : "=r"(v) : "l"(p) : "memory"); return v; }
__device__ __forceinline__ unsigned ld_acq(const unsigned* p) { unsigned v; asm volatile("ld.acquire.gpu.global.u32 %0, [%1];" : "=r"(v) : "l"(p) : "memory"); return v; }
__device__ __forceinline__ void st_rlx(unsigned* p, unsigned v) { asm volatile("st.relaxed.gpu.global.u32 [%0], %1;" :: "l"(p), "r"(v) : "memory"); }
__device__ __forceinline__ void st_rel(unsigned* p, unsigned v) { asm volatile("st.release.gpu.global.u32 [%0], %1;" :: "l"(p), "r"(v) : "memory"); }
__device__ __forceinline__ void ld128_rlx(uint32_t* v, const void* p) {
  asm volatile("{\n.reg .b128 t;\n.reg .b64 lo, hi;\nld.relaxed.gpu.global.b128 t, [%4];\nmov.b128 {lo, hi}, t;\n"
    "mov.b64 {%0, %1}, lo;\nmov.b64 {%2, %3}, hi;\n}" : "=r"(v[0]), "=r"(v[1]), "=r"(v[2]), "=r"(v[3]) : "l"(p) : "memory");
}
__device__ __forceinline__ void st128_rlx(void* p, const uint32_t* v) {
  asm volatile("{\n.reg .b128 t;\n.reg .b64 lo, hi;\nmov.b64 lo, {%1, %2};\nmov.b64 hi, {%3, %4};\nmov.b128 t, {lo, hi};\n"
    "st.relaxed.gpu.global.b128 [%0], t;\n}" :: "l"(p), "r"(v[0]), "r"(v[1]), "r"(v[2]), "r"(v[3]) : "memory");
}
__device__ __forceinline__ uint32_t lds32(uint32_t a) { uint32_t v; asm volatile("ld.shared.u32 %0, [%1];" : "=r"(v) : "r"(a) : "memory"); return v; }
__device__ __forceinline__ uint32_t lds32v(uint32_t a) { uint32_t v; asm volatile("ld.volatile.shared.u32 %0, [%1];" : "=r"(v) : "r"(a) : "memory"); return v; }
__device__ __forceinline__ uint32_t cpa(uint32_t a, uint32_t one) { uint32_t v; asm volatile("mul.lo.u32 %0, %1, %2;" : "=r"(v) : "r"(a), "r"(one)); return v; }
__device__ __forceinline__ uint32_t cpb(uint32_t a, uint32_t zero) { uint32_t v; asm volatile("or.b32 %0, %1, %2;" : "=r"(v) : "r"(a), "r"(zero)); return v; }
__device__ __forceinline__ uint32_t lds16(uint32_t a) { uint16_t v; asm volatile("ld.shared.u16 %0, [%1];" : "=h"(v) : "r"(a) : "memory"); return v; }
__device__ __forceinline__ float ldsf(uint32_t a) { float v; asm volatile("ld.shared.f32 %0, [%1];" : "=f"(v) : "r"(a) : "memory"); return v; }
__device__ __forceinline__ void lds128(uint32_t* v, uint32_t a) { asm volatile("ld.shared.v4.u32 {%0,%1,%2,%3}, [%4];" : "=r"(v[0]), "=r"(v[1]), "=r"(v[2]), "=r"(v[3]) : "r"(a) : "memory"); }
__device__ __forceinline__ void sts32(uint32_t a, uint32_t v) { asm volatile("st.shared.u32 [%0], %1;" :: "r"(a), "r"(v) : "memory"); }
__device__ __forceinline__ void sts16(uint32_t a, uint32_t v) { asm volatile("st.shared.u16 [%0], %1;" :: "r"(a), "h"((uint16_t)v) : "memory"); }
__device__ __forceinline__ void sts64f(uint32_t a, float x, float y) { asm volatile("st.shared.v2.f32 [%0], {%1,%2};" :: "r"(a), "f"(x), "f"(y) : "memory"); }
__device__ __forceinline__ void sts128(uint32_t a, uint32_t x, uint32_t y, uint32_t z, uint32_t w) { asm volatile("st.shared.v4.u32 [%0], {%1,%2,%3,%4};" :: "r"(a), "r"(x), "r"(y), "r"(z), "r"(w) : "memory"); }
__device__ __forceinline__ void stsm4(uint32_t a, uint32_t r0, uint32_t r1, uint32_t r2, uint32_t r3) {
  asm volatile("stmatrix.sync.aligned.m8n8.x4.shared.b16 [%0], {%1,%2,%3,%4};" :: "r"(a), "r"(r0), "r"(r1), "r"(r2), "r"(r3) : "memory");
}
__device__ __forceinline__ void stsm4t(uint32_t a, uint32_t r0, uint32_t r1, uint32_t r2, uint32_t r3) {
  asm volatile("stmatrix.sync.aligned.m8n8.x4.trans.shared.b16 [%0], {%1,%2,%3,%4};" :: "r"(a), "r"(r0), "r"(r1), "r"(r2), "r"(r3) : "memory");
}
__device__ __forceinline__ void ldsm4t(uint32_t* r, uint32_t a) {
  asm volatile("ldmatrix.sync.aligned.m8n8.x4.trans.shared.b16 {%0,%1,%2,%3}, [%4];" : "=r"(r[0]), "=r"(r[1]), "=r"(r[2]), "=r"(r[3]) : "r"(a) : "memory");
}
__device__ __forceinline__ void ldsm4(uint32_t* r, uint32_t a) {
  asm volatile("ldmatrix.sync.aligned.m8n8.x4.shared.b16 {%0,%1,%2,%3}, [%4];" : "=r"(r[0]), "=r"(r[1]), "=r"(r[2]), "=r"(r[3]) : "r"(a) : "memory");
}
__device__ __forceinline__ void mma16816(float* d, const uint32_t* a, const uint32_t* b) {
  asm volatile("mma.sync.aligned.m16n8k16.row.col.f32.bf16.bf16.f32 {%0,%1,%2,%3}, {%4,%5,%6,%7}, {%8,%9}, {%0,%1,%2,%3};"
    : "+f"(d[0]), "+f"(d[1]), "+f"(d[2]), "+f"(d[3]) : "r"(a[0]), "r"(a[1]), "r"(a[2]), "r"(a[3]), "r"(b[0]), "r"(b[1]));
}
__device__ __forceinline__ uint32_t pack2(float lo, float hi) { uint32_t r; asm("cvt.rn.bf16x2.f32 %0, %1, %2;" : "=r"(r) : "f"(hi), "f"(lo)); return r; }
__device__ __forceinline__ uint32_t packh(float lo, float hi) { uint32_t r; asm("cvt.rn.f16x2.f32 %0, %1, %2;" : "=r"(r) : "f"(hi), "f"(lo)); return r; }
__device__ __forceinline__ uint32_t hcmul(uint32_t x, uint32_t zp, uint32_t zq) {
  const __half2 xx = *reinterpret_cast<__half2*>(&x);
  const __half2 r = __hfma2(__high2half2(xx), *reinterpret_cast<__half2*>(&zq), __hmul2(__low2half2(xx), *reinterpret_cast<__half2*>(&zp)));
  return *reinterpret_cast<const uint32_t*>(&r);
}
__device__ __forceinline__ void hcm2(uint32_t xr, uint32_t xi, uint32_t z, uint32_t& pr, uint32_t& pi) {
  const __half2 a = *reinterpret_cast<__half2*>(&xr), b = *reinterpret_cast<__half2*>(&xi), zz = *reinterpret_cast<__half2*>(&z);
  const __half2 re = __hfma2(__hneg2(b), __high2half2(zz), __hmul2(a, __low2half2(zz)));
  const __half2 im = __hfma2(a, __high2half2(zz), __hmul2(b, __low2half2(zz)));
  pr = *reinterpret_cast<const uint32_t*>(&re); pi = *reinterpret_cast<const uint32_t*>(&im);
}
__device__ __forceinline__ void sts64(uint32_t a, uint32_t x, uint32_t y) { asm volatile("st.shared.v2.u32 [%0], {%1,%2};" :: "r"(a), "r"(x), "r"(y) : "memory"); }
__device__ __forceinline__ void lds64(uint32_t* v, uint32_t a) { asm volatile("ld.shared.v2.u32 {%0,%1}, [%2];" : "=r"(v[0]), "=r"(v[1]) : "r"(a) : "memory"); }
__device__ __forceinline__ float bf_lo(uint32_t v) { return __uint_as_float(v << 16); }
__device__ __forceinline__ float bf_hi(uint32_t v) { return __uint_as_float(v & 0xffff0000u); }
__device__ __forceinline__ float bf_round(float x) { return bf_lo(pack2(x, 0.f)); }
__device__ __forceinline__ float ex2(float x) { float r; asm("ex2.approx.ftz.f32 %0, %1;" : "=f"(r) : "f"(x)); return r; }
__device__ __forceinline__ float phi(float t, float l2e = 1.44269504089f) {
  float e = ex2(t * l2e) + 1e-6f;
  asm("{\n.reg .pred p;\nsetp.gt.f32 p, %1, 0f00000000;\n@p add.f32 %0, %1, 0f3F800008;\n}" : "+f"(e) : "f"(t));
  return e;
}
__device__ __forceinline__ void wg_fence() { asm volatile("wgmma.fence.sync.aligned;" ::: "memory"); }
__device__ __forceinline__ void wg_commit() { asm volatile("wgmma.commit_group.sync.aligned;" ::: "memory"); }
template <int N> __device__ __forceinline__ void wg_wait() { asm volatile("wgmma.wait_group.sync.aligned %0;" :: "n"(N) : "memory"); }
template <int N> __device__ __forceinline__ void pin(float* a) {
  #pragma unroll
  for (int i = 0; i < N; i++) asm volatile("" : "+f"(a[i]) :: "memory");
}
__device__ __forceinline__ int rtid() { int t; asm volatile("mov.u32 %0, %%tid.x;" : "=r"(t)); return t; }
__device__ __forceinline__ int opaque(int v) { asm volatile("" : "+r"(v)); return v; }
template <int N> __device__ __forceinline__ void zero(float* a) {
  #pragma unroll
  for (int i = 0; i < N; i++) asm volatile("mov.b32 %0, 0;" : "=f"(a[i]));
}
template <int N> __device__ __forceinline__ void pinu(uint32_t* a) {
  #pragma unroll
  for (int i = 0; i < N; i++) asm volatile("" : "+r"(a[i]) :: "memory");
}
__device__ __forceinline__ void cexp_t(float lg2mag, float turns, float& re, float& im) {
  float m = ex2(lg2mag);
  float fr = (turns - __fadd_rn(__fadd_rn(turns, 12582912.f), -12582912.f)) * 6.283185307f;
  re = m * __cosf(fr); im = m * __sinf(fr);
}
__device__ __forceinline__ void cmul(float ar, float ai, float br, float bi, float& cr, float& ci) {
  cr = fmaf(ar, br, -ai * bi); ci = fmaf(ar, bi, ai * br);
}

__device__ __forceinline__ void wg_ss48_tt(float* d, uint64_t da, uint64_t db, int scale_d) {
  asm volatile("{\n.reg .pred p;\nsetp.ne.b32 p, %26, 0;\n"
    "wgmma.mma_async.sync.aligned.m64n48k16.f32.bf16.bf16 "
    "{%0, %1, %2, %3, %4, %5, %6, %7, %8, %9, %10, %11, %12, %13, %14, %15, %16, %17, %18, %19, %20, %21, %22, %23}, %24, %25, p, 1, 1, 1, 1;\n}\n"
    : "+f"(d[0]), "+f"(d[1]), "+f"(d[2]), "+f"(d[3]), "+f"(d[4]), "+f"(d[5]), "+f"(d[6]), "+f"(d[7]), "+f"(d[8]), "+f"(d[9]), "+f"(d[10]), "+f"(d[11]), "+f"(d[12]), "+f"(d[13]), "+f"(d[14]), "+f"(d[15]), "+f"(d[16]), "+f"(d[17]), "+f"(d[18]), "+f"(d[19]), "+f"(d[20]), "+f"(d[21]), "+f"(d[22]), "+f"(d[23])
    : "l"(da), "l"(db), "r"(scale_d));
}
__device__ __forceinline__ void wg_rs88_tb(float* d, const uint32_t* a, uint64_t db, int scale_d) {
  asm volatile("{\n.reg .pred p;\nsetp.ne.b32 p, %49, 0;\n"
    "wgmma.mma_async.sync.aligned.m64n88k16.f32.bf16.bf16 "
    "{%0, %1, %2, %3, %4, %5, %6, %7, %8, %9, %10, %11, %12, %13, %14, %15, %16, %17, %18, %19, %20, %21, %22, %23, %24, %25, %26, %27, %28, %29, %30, %31, %32, %33, %34, %35, %36, %37, %38, %39, %40, %41, %42, %43}, {%44, %45, %46, %47}, %48, p, 1, 1, 1;\n}\n"
    : "+f"(d[0]), "+f"(d[1]), "+f"(d[2]), "+f"(d[3]), "+f"(d[4]), "+f"(d[5]), "+f"(d[6]), "+f"(d[7]), "+f"(d[8]), "+f"(d[9]), "+f"(d[10]), "+f"(d[11]), "+f"(d[12]), "+f"(d[13]), "+f"(d[14]), "+f"(d[15]), "+f"(d[16]), "+f"(d[17]), "+f"(d[18]), "+f"(d[19]), "+f"(d[20]), "+f"(d[21]), "+f"(d[22]), "+f"(d[23]), "+f"(d[24]), "+f"(d[25]), "+f"(d[26]), "+f"(d[27]), "+f"(d[28]), "+f"(d[29]), "+f"(d[30]), "+f"(d[31]), "+f"(d[32]), "+f"(d[33]), "+f"(d[34]), "+f"(d[35]), "+f"(d[36]), "+f"(d[37]), "+f"(d[38]), "+f"(d[39]), "+f"(d[40]), "+f"(d[41]), "+f"(d[42]), "+f"(d[43])
    : "r"(a[0]), "r"(a[1]), "r"(a[2]), "r"(a[3]), "l"(db), "r"(scale_d));
}
__device__ __forceinline__ void wg_ss80_tb(float* d, uint64_t da, uint64_t db, int scale_d) {
  asm volatile("{\n.reg .pred p;\nsetp.ne.b32 p, %42, 0;\n"
    "wgmma.mma_async.sync.aligned.m64n80k16.f32.bf16.bf16 "
    "{%0, %1, %2, %3, %4, %5, %6, %7, %8, %9, %10, %11, %12, %13, %14, %15, %16, %17, %18, %19, %20, %21, %22, %23, %24, %25, %26, %27, %28, %29, %30, %31, %32, %33, %34, %35, %36, %37, %38, %39}, %40, %41, p, 1, 1, 0, 1;\n}\n"
    : "+f"(d[0]), "+f"(d[1]), "+f"(d[2]), "+f"(d[3]), "+f"(d[4]), "+f"(d[5]), "+f"(d[6]), "+f"(d[7]), "+f"(d[8]), "+f"(d[9]), "+f"(d[10]), "+f"(d[11]), "+f"(d[12]), "+f"(d[13]), "+f"(d[14]), "+f"(d[15]), "+f"(d[16]), "+f"(d[17]), "+f"(d[18]), "+f"(d[19]), "+f"(d[20]), "+f"(d[21]), "+f"(d[22]), "+f"(d[23]), "+f"(d[24]), "+f"(d[25]), "+f"(d[26]), "+f"(d[27]), "+f"(d[28]), "+f"(d[29]), "+f"(d[30]), "+f"(d[31]), "+f"(d[32]), "+f"(d[33]), "+f"(d[34]), "+f"(d[35]), "+f"(d[36]), "+f"(d[37]), "+f"(d[38]), "+f"(d[39])
    : "l"(da), "l"(db), "r"(scale_d));
}
__device__ __forceinline__ void wg_ss48_tt_h(float* d, uint64_t da, uint64_t db, int scale_d) {
  asm volatile("{\n.reg .pred p;\nsetp.ne.b32 p, %26, 0;\n"
    "wgmma.mma_async.sync.aligned.m64n48k16.f32.f16.f16 "
    "{%0, %1, %2, %3, %4, %5, %6, %7, %8, %9, %10, %11, %12, %13, %14, %15, %16, %17, %18, %19, %20, %21, %22, %23}, %24, %25, p, 1, 1, 1, 1;\n}\n"
    : "+f"(d[0]), "+f"(d[1]), "+f"(d[2]), "+f"(d[3]), "+f"(d[4]), "+f"(d[5]), "+f"(d[6]), "+f"(d[7]), "+f"(d[8]), "+f"(d[9]), "+f"(d[10]), "+f"(d[11]), "+f"(d[12]), "+f"(d[13]), "+f"(d[14]), "+f"(d[15]), "+f"(d[16]), "+f"(d[17]), "+f"(d[18]), "+f"(d[19]), "+f"(d[20]), "+f"(d[21]), "+f"(d[22]), "+f"(d[23])
    : "l"(da), "l"(db), "r"(scale_d));
}
__device__ __forceinline__ void wg_rs192_tb(float* d, const uint32_t* a, uint64_t db, int scale_d) {
  asm volatile("{\n.reg .pred p;\nsetp.ne.b32 p, %101, 0;\n"
    "wgmma.mma_async.sync.aligned.m64n192k16.f32.bf16.bf16 "
    "{%0, %1, %2, %3, %4, %5, %6, %7, %8, %9, %10, %11, %12, %13, %14, %15, %16, %17, %18, %19, %20, %21, %22, %23, %24, %25, %26, %27, %28, %29, %30, %31, %32, %33, %34, %35, %36, %37, %38, %39, %40, %41, %42, %43, %44, %45, %46, %47, %48, %49, %50, %51, %52, %53, %54, %55, %56, %57, %58, %59, %60, %61, %62, %63, %64, %65, %66, %67, %68, %69, %70, %71, %72, %73, %74, %75, %76, %77, %78, %79, %80, %81, %82, %83, %84, %85, %86, %87, %88, %89, %90, %91, %92, %93, %94, %95}, {%96, %97, %98, %99}, %100, p, 1, 1, 1;\n}\n"
    : "+f"(d[0]), "+f"(d[1]), "+f"(d[2]), "+f"(d[3]), "+f"(d[4]), "+f"(d[5]), "+f"(d[6]), "+f"(d[7]), "+f"(d[8]), "+f"(d[9]), "+f"(d[10]), "+f"(d[11]), "+f"(d[12]), "+f"(d[13]), "+f"(d[14]), "+f"(d[15]), "+f"(d[16]), "+f"(d[17]), "+f"(d[18]), "+f"(d[19]), "+f"(d[20]), "+f"(d[21]), "+f"(d[22]), "+f"(d[23]), "+f"(d[24]), "+f"(d[25]), "+f"(d[26]), "+f"(d[27]), "+f"(d[28]), "+f"(d[29]), "+f"(d[30]), "+f"(d[31]), "+f"(d[32]), "+f"(d[33]), "+f"(d[34]), "+f"(d[35]), "+f"(d[36]), "+f"(d[37]), "+f"(d[38]), "+f"(d[39]), "+f"(d[40]), "+f"(d[41]), "+f"(d[42]), "+f"(d[43]), "+f"(d[44]), "+f"(d[45]), "+f"(d[46]), "+f"(d[47]), "+f"(d[48]), "+f"(d[49]), "+f"(d[50]), "+f"(d[51]), "+f"(d[52]), "+f"(d[53]), "+f"(d[54]), "+f"(d[55]), "+f"(d[56]), "+f"(d[57]), "+f"(d[58]), "+f"(d[59]), "+f"(d[60]), "+f"(d[61]), "+f"(d[62]), "+f"(d[63]), "+f"(d[64]), "+f"(d[65]), "+f"(d[66]), "+f"(d[67]), "+f"(d[68]), "+f"(d[69]), "+f"(d[70]), "+f"(d[71]), "+f"(d[72]), "+f"(d[73]), "+f"(d[74]), "+f"(d[75]), "+f"(d[76]), "+f"(d[77]), "+f"(d[78]), "+f"(d[79]), "+f"(d[80]), "+f"(d[81]), "+f"(d[82]), "+f"(d[83]), "+f"(d[84]), "+f"(d[85]), "+f"(d[86]), "+f"(d[87]), "+f"(d[88]), "+f"(d[89]), "+f"(d[90]), "+f"(d[91]), "+f"(d[92]), "+f"(d[93]), "+f"(d[94]), "+f"(d[95])
    : "r"(a[0]), "r"(a[1]), "r"(a[2]), "r"(a[3]), "l"(db), "r"(scale_d));
}
__device__ __forceinline__ void wg_rs48_tb(float* d, const uint32_t* a, uint64_t db, int scale_d) {
  asm volatile("{\n.reg .pred p;\nsetp.ne.b32 p, %29, 0;\n"
    "wgmma.mma_async.sync.aligned.m64n48k16.f32.bf16.bf16 "
    "{%0, %1, %2, %3, %4, %5, %6, %7, %8, %9, %10, %11, %12, %13, %14, %15, %16, %17, %18, %19, %20, %21, %22, %23}, {%24, %25, %26, %27}, %28, p, 1, 1, 1;\n}\n"
    : "+f"(d[0]), "+f"(d[1]), "+f"(d[2]), "+f"(d[3]), "+f"(d[4]), "+f"(d[5]), "+f"(d[6]), "+f"(d[7]), "+f"(d[8]), "+f"(d[9]), "+f"(d[10]), "+f"(d[11]), "+f"(d[12]), "+f"(d[13]), "+f"(d[14]), "+f"(d[15]), "+f"(d[16]), "+f"(d[17]), "+f"(d[18]), "+f"(d[19]), "+f"(d[20]), "+f"(d[21]), "+f"(d[22]), "+f"(d[23])
    : "r"(a[0]), "r"(a[1]), "r"(a[2]), "r"(a[3]), "l"(db), "r"(scale_d));
}

struct Params {
  const __nv_bfloat16 *par[4], *logdt, *dskip, *u, *wo;
  CUtensorMap m[M_COUNT];
};

#define CHUNK(i) ((i) == 0 ? c : ((i) == 7 ? (c ^ 1) : (((c & 6) + 1 + (i)) & 7)))
#define FLAG(kind, rr, cc) (&g_flag[((kind) * 128 + (rr) * 8 + (cc)) * 32])
#define SLOT(i) ((i) == 0 ? OFF_EXTRA : OFF_BLK - 256 + ((i) > 5 ? (i) - 6 : (i) - 1) * BLK)
__device__ __forceinline__ void load_quad(uint32_t* A, uint32_t addr) {
  A[0] = lds32v(addr); A[1] = lds32v(addr + 32); A[2] = lds32v(addr - 32); A[3] = lds32v(addr);
}

__device__ __forceinline__ bool y_transpose(uint32_t sb, int w5, int lane, uint32_t ytag) {
  const int mi = lane >> 3, rw = lane & 7;
  const uint32_t sa = sb + OFF_EXTRA + (w5 * 16 + rw) * 128 + ((mi ^ rw) << 4), da = sb + SLOT(3) + (8 * mi + rw) * 160 + w5 * 32;
  const uint32_t ym = lane < 4 ? 0x10001u : 0u;
  bar_sync(7, 160);
  uint32_t v[8][4], bad = 0;
  #pragma unroll
  for (int q = 0; q < 8; q++) ldsm4t(v[q], (sa ^ ((q & 1) * 64 + ((q >> 1) & 1) * 16)) + ((q >> 1) & 1) * 10240 + (q >> 2) * 1024);
  #pragma unroll
  for (int q = 0; q < 8; q++) {
    bad |= (v[q][0] ^ ytag) | (v[q][2] ^ ytag);
    stsm4(da + (q & 3) * 5120 + (q >> 2) * 16, v[q][0] & ~ym, v[q][1], v[q][2] & ~ym, v[q][3]);
  }
  fence_async();
  uint32_t any;
  asm volatile("{\n.reg .pred p;\nsetp.ne.u32 p, %1, 0;\nbarrier.red.or.pred p, 7, 160, p;\nselp.u32 %0, 1, 0, p;\n}" : "=r"(any) : "r"(bad & ym) : "memory");
  return any;
}

__global__ void __launch_bounds__(512, 1) fused_kernel(const __grid_constant__ Params prm) {
  extern __shared__ unsigned char smem_raw[];
  const uint32_t sb = __shfl_sync(0xffffffff, smem_u32(smem_raw), 0);
  const int tid = threadIdx.x, lane = tid & 31;
  const int warp = __shfl_sync(0xffffffff, tid >> 5, 0), wg = warp >> 2, w4 = warp & 3;
  const int cta = blockIdx.x, r = cta >> 3, c = cta & 7;
  if ((sb & 0xffffffu) != SB0) return;
#define BAR(i) (sb + OFF_BAR + 8 * (i))
  const bool sw64 = ((c + 1) & 2) != 0;

  const CUtensorMap* mwp = &prm.m[sw64 ? M_W64 : M_W128];
  const int mcol = (c * 80 + (c & 1) * 16) >> (sw64 ? 5 : 6), rcol = c * 80 + ((c & 1) ? 0 : 64);
  if (warp == 12 && elect_one()) {
    #pragma unroll
    for (int i = 0; i < 5; i++) mbar_init(BAR(BR_FULL + i), 1);
    asm volatile("fence.mbarrier_init.release.cluster;" ::: "memory");
    if (EN_ATT) {
      mbar_expect_tx(BAR(BR_FULL), W_SLOT + 16384);
      tma4d(sb, mwp, BAR(BR_FULL), 0, 0, mcol, 0);
      tma2d(sb + OFF_X, &prm.m[M_X], BAR(BR_FULL), 0, r * 128);
      tma3d(sb + 12288, &prm.m[M_WR], BAR(BR_FULL), rcol, 0, 0);
      mbar_expect_tx(BAR(BR_FULL + 1), W_SLOT);
      tma4d(sb + W_SLOT, mwp, BAR(BR_FULL + 1), 0, 32, mcol, 0);
      tma3d(sb + W_SLOT + 12288, &prm.m[M_WR], BAR(BR_FULL + 1), rcol, 32, 0);
      TS(24);
    }
  }
  if (warp == 13 && elect_one()) {
    asm volatile("prefetch.tensormap [%0];" :: "l"(&prm.m[M_X]) : "memory");
    asm volatile("prefetch.tensormap [%0];" :: "l"(&prm.m[M_WR]) : "memory");
  }
  if (wg == 3) {
    asm volatile("setmaxnreg.dec.sync.aligned.u32 56;");
    const int tid = rtid(), lane = tid & 31;
    if (warp == 12) {
      asm volatile("bar.arrive 0, 512;" ::: "memory");
      {
        uint32_t s = 2, ph = 1, xs = 16384;
        #pragma unroll 1
        for (int kb = 2; kb < 20; kb++) {
          if (kb == 4) bar_sync(6, 128);
          if (kb >= 5) mbar_wait(BAR(BR_EMPTY) + 8 * s, ph);
          if (EN_ATT && elect_one()) {
            const uint32_t st = sb + s * W_SLOT, fb = BAR(BR_FULL) + 8 * s;
            mbar_expect_tx(fb, (kb & 1) ? W_SLOT : W_SLOT + 16384);
            if (!(kb & 1)) tma2d(sb + OFF_X + xs, &prm.m[M_X], fb, kb * 32, r * 128);
            tma4d(st, mwp, fb, 0, kb * 32, mcol, 0);
            tma3d(st + 12288, &prm.m[M_WR], fb, rcol, kb * 32, 0);
          }
          if (kb < 4 && lane == 0) TS(24 + kb);
          if (UPF && kb >= UKB - 4 && kb < UKB && elect_one())
            asm volatile("cp.async.bulk.prefetch.L2.global [%0], 5120;" :: "l"(prm.u + cta * 10240 + (kb - (UKB - 4)) * 2560) : "memory");
          if (EN_SSM && kb == (EN_ATT ? UKB : 4) && elect_one()) { mbar_expect_tx(BAR(BR_UIN), 20480); tma2d(sb + OFF_UT, &prm.m[M_U], BAR(BR_UIN), c * 80, r * 128); }
          if (kb == 14 && elect_one()) asm volatile("cp.async.bulk.prefetch.L2.global [%0], 6400;" :: "l"(prm.wo + cta * 3200) : "memory");
          if (!EN_ATT && kb == 4) break;
          if (++s == 5) { s = 0; ph ^= 1; }
          if (kb & 1) { xs += 16384; if (xs == 49152) xs = 0; }
        }
      }
      if (EN_ATT) {
      mbar_wait(BAR(BR_EPOCH), 0);
      const unsigned epoch = lds32(sb + OFF_EPOCH);
      const unsigned* fo = FLAG(3, r, lane & 7);
      unsigned seen = __ballot_sync(0xffffffff, ld_rlx(lane < 16 ? fo : FLAG(0, lane & 15, c)) == epoch) & 0xffu;
      mbar_wait(BAR(BR_GEMM), 0);
      if (elect_one()) {
        mbar_expect_tx(BAR(BR_WO), 10240);
        tma2d(sb, &prm.m[M_WO], BAR(BR_WO), c * 64, c * 80);
        mbar_expect_tx(BAR(BR_KVP), 61440);
        mbar_expect_tx(BAR(BR_WO + 1), 7 * 10240);
      }
      {
        uint32_t ds = sb + OFF_WOR + (lane >> 3) * 128 + (((lane & 7) ^ (lane >> 3)) << 4);
        #pragma unroll 1
        for (int h = 0; h < 2; h++) {
          const int i = (lane & 6) + h;
          const char* gs = reinterpret_cast<const char*>(prm.wo) + (size_t)((lane >> 3) + CHUNK(i) * 80) * 1280 + 1024 + c * 32 + (lane & 1) * 16;
          #pragma unroll 2
          for (int q = 0; q < 20; q++) {
            asm volatile("cp.async.cg.shared.global [%0], [%1], 16;" :: "r"(ds), "l"(gs) : "memory");
            ds = (ds + 512) ^ 64; gs += 5120;
          }
        }
      }
      mbar_wait(BAR(BR_PUB), 0);
      poll_all(FLAG(0, lane & 15, c), epoch);
      if (elect_one()) { TS(23); bulk_ld(sb + OFF_KVP, &g_kvp[c * 16 * 240], 61440, BAR(BR_KVP)); }
      asm volatile("cp.async.wait_all;" ::: "memory");
      fence_async();
      mbar_arrive(BAR(BR_WO));
      mbar_wait(BAR(BR_SUM), 0);
      if (elect_one()) {
        #pragma unroll 1
        for (int i = 1; i < 8; i++) tma2d(sb + i * 10240, &prm.m[M_WO], BAR(BR_WO + 1), c * 64, CHUNK(i) * 80);
      }
      mbar_wait(BAR(BR_OSTG), 0);
      if (elect_one()) {
        bulk_st(&g_o[cta * 1280], sb + OFF_EXTRA, 20480);
        bulk_commit();
        bulk_wait0();
        st_rlx(FLAG(3, r, c), epoch);
        mbar_arrive(BAR(BR_OEMPTY));
        TS(20);
      }
      __syncwarp();
      #pragma unroll 1
      for (int i = 1; i < 8; i++) {
        const int src = CHUNK(i);
        if (!((seen >> src) & 1)) seen = poll_bit(fo, epoch, 1u << src);
        if (i > 5) mbar_wait(BAR(BR_OEMPTY - 5) + 8 * i, 0);
        if (EN_SSM && (i == 1 || i == 5)) mbar_wait(BAR(BR_FREE) + 2 * (i & 4), 0);
        if (elect_one()) {
          mbar_expect_tx(BAR(BR_OFULL) + 8 * i, 20480);
          bulk_ld(sb + SLOT(i), &g_o[(r * 8 + src) * 1280], 20480, BAR(BR_OFULL) + 8 * i);
          if (i == 1) TS(21);
          if (i == 7) TS(22);
        }
        __syncwarp();
      }
      if (lane == 0) { DUMP(20, 30); }
      }
    } else {
      const int hw = warp - 13, ht = tid - 416;
      if (hw == 2 && elect_one()) {
        #pragma unroll
        for (int i = 5; i < BR_COUNT; i++) mbar_init(BAR(i), i == BR_WO ? 33 : i == BR_OEMPTY ? 9 : i < BR_EMPTY ? 1 : i < BR_OEMPTY ? 2 : i < BR_Y ? 8 : i < BR_OSTG ? 4 : i == BR_OSTG ? 8 : i < BR_U2 ? 3 : 1);
        asm volatile("fence.mbarrier_init.release.cluster;" ::: "memory");
      }
      __syncwarp();
      asm volatile("bar.arrive 0, 512;" ::: "memory");
      if (EN_SSM && hw == 2) asm volatile("bar.arrive 8, 160;" ::: "memory");
      const unsigned epoch = hw == 0 ? ld_rlx(&g_epoch[cta]) + 1 : 0;
      bar_sync(5, 96);
      asm volatile("bar.arrive 6, 128;" ::: "memory");
      if (hw == 1 && elect_one()) {
        #pragma unroll
        for (int i = M_U; i < M_COUNT; i++) asm volatile("prefetch.tensormap [%0];" :: "l"(&prm.m[i]) : "memory");
      }
      if (ht == 0) {
        st_rlx(&g_epoch[cta], epoch);
        sts32(sb + OFF_EPOCH, epoch);
        mbar_arrive(BAR(BR_EPOCH));
      }
      if (EN_SSM) {
      const int mi = lane >> 3, rw = lane & 7, ch0 = c * 80 + r * 5;
      mbar_wait(BAR(BR_UIN), 0);
      if (ht == 0) TS(36);
      #pragma unroll 1
      for (int h = 0; h < 2; h++) {
        const uint32_t sa = sb + OFF_UT + h * 10240 + (8 * mi + rw) * 160 + hw * 16, da = sb + OFF_UT + h * 10240 + (hw * 8 + rw) * 128 + ((mi ^ rw ^ h) << 4);
        uint32_t v[8][4];
        #pragma unroll
        for (int q = 0; q < 8; q++) if (q < 6 || hw == 0) ldsm4t(v[q], sa + (q & 1) * 5120 + (q >> 1) * 48);
        bar_sync(5, 96);
        #pragma unroll
        for (int q = 0; q < 8; q++) if (q < 6 || hw == 0) stsm4((da ^ ((q & 1) * 64)) + (q >> 1) * 3072, v[q][0], v[q][1], v[q][2], v[q][3]);
      }
      fence_async();
      bar_sync(5, 96);
      if (hw == 0) {
        if (elect_one()) {
          tma2d_st(&prm.m[M_SA], sb + OFF_UT, r * 128, c * 80);
          tma2d_st(&prm.m[M_SA], sb + OFF_UT + 10240, r * 128 + 64, c * 80);
          bulk_commit(); bulk_wait0_read();
          mbar_arrive(BAR(BR_UOUT));
          TS(37);
          bulk_wait0();
          st_rel(FLAG(1, r, c), epoch);
          TS(30);
        }
        __syncwarp();
        poll_all_acq(FLAG(1, lane & 15, c), epoch);
      }
      #pragma unroll 1
      for (int k = 0; k < 5; k++) {
        if (k == 0 || k == 3) {
          const int p = k != 0;
          if (hw == 0) {
            if (!p) {
              if (elect_one()) {
                fence_async_g();
                mbar_expect_tx(BAR(BR_U), 12288);
                #pragma unroll 1
                for (int q = 0; q < 3; q++) bulk_ld(sb + OFF_BLK + q * q * BLK, g_uy + (ch0 + q * q) * 2048, 4096, BAR(BR_U));
                TS(31);
              }
              __syncwarp();
            }
            mbar_wait(BAR(p ? BR_U2 : BR_U), 0);
          }
          bar_sync(5, 96);
        }
        const int l3 = (hw + k) % 3 * 32 + lane;
        const uint32_t blk = sb + OFF_BLK + ((0x32410 >> (4 * k)) & 7) * BLK, o = blk + B_D + l3 * 16;
        float P[34];
        P[0] = 0.f;
        #pragma unroll
        for (int q = 0; q < 5; q++) {
          const int ch = 2 * l3 - 3 + q;
          uint32_t v[4];
          lds128(v, blk + (uint32_t)((ch * 16) ^ ((ch * 2) & 0x10)));
          #pragma unroll
          for (int e = 0; e < 8; e++) {
            const int i = 8 * q + e - 4;
            if (i >= 0 && i < 33) P[i + 1] = P[i] + ((e & 1) ? bf_hi(v[e >> 1]) : bf_lo(v[e >> 1]));
          }
        }
#define WIN(lo, hi, e) (P[21 + (e) - (lo)] - P[20 + (e) - (hi)])
#define WIN8(lo, hi, b) pack2(WIN(lo, hi, b), WIN(lo, hi, b + 1)), pack2(WIN(lo, hi, b + 2), WIN(lo, hi, b + 3)), pack2(WIN(lo, hi, b + 4), WIN(lo, hi, b + 5)), pack2(WIN(lo, hi, b + 6), WIN(lo, hi, b + 7))
        if (l3 < 64) {
          sts128(o + B_D9, WIN8(12, 20, 0)); sts128(o + B_D9 + 1024, WIN8(12, 20, 8));
          sts128(o + B_D7, WIN8(5, 11, 0)); sts128(o + B_D7 + 1024, WIN8(5, 11, 8));
        }
        sts128(o + B_D5, WIN8(6, 10, 0)); sts128(o + B_D5 + 1552, WIN8(6, 10, 8));
        sts128(o, WIN8(3, 5, 0)); sts128(o + 1552, WIN8(3, 5, 8));
        if (l3 < 2) sts128(blk + B_D + l3 * B_D5 + 1536, 0, 0, 0, 0);
      }
      __syncwarp();
      if (lane == 0) mbar_arrive(BAR(BR_DRDY + 1));
      if (ht == 0) TS(32);
      if (hw == 0) {
        #pragma unroll 1
        for (int p = 0; p < 2; p++) {
          mbar_wait(BAR(BR_Y) + 8 * p, 0);
          if (elect_one()) {
            #pragma unroll 1
            for (int k = 4 * p; k < 4 + p; k++) bulk_st(g_uy + (640 + ch0 + k) * 2048, sb + OFF_BLK + k * BLK, 4096);
            bulk_commit(); bulk_wait0_read();
            mbar_arrive(BAR(BR_FREE) + 8 * p);
          }
          __syncwarp();
        }
        if (elect_one()) { bulk_wait0(); st_rlx(FLAG(2, r, c), epoch); TS(33); }
        __syncwarp();
        poll_all(FLAG(2, lane & 15, c), epoch);
        if (EN_ATT) mbar_wait(BAR(BR_OEMPTY), 0);
        #pragma unroll 1
        for (int n = 0; n < 64; n++) {
          if (elect_one()) {
            mbar_expect_tx(BAR(BR_YIN), 20480);
            tma2d(sb + OFF_EXTRA, &prm.m[M_SA], BAR(BR_YIN), r * 128, 640 + c * 80);
            tma2d(sb + OFF_EXTRA + 10240, &prm.m[M_SA], BAR(BR_YIN), r * 128 + 64, 640 + c * 80);
            TS(34);
          }
          __syncwarp();
          if (EN_ATT) mbar_wait(BAR(BR_OEMPTY + 3), 0);
          mbar_wait(BAR(BR_YIN), n & 1);
          if (lane == 0) TS(38);
          if (!y_transpose(sb, 4, lane, (epoch & 1u) * 0x10001u)) break;
          FIXCNT
        }
      if (elect_one()) {
        TS(39);
        tma2d_st(&prm.m[M_OUT], sb + SLOT(3), c * 80, r * 128);
        bulk_commit(); bulk_wait0_read();
        TS(35); DUMP(30, 40); DUMP(0, 1);
      }
      }
      }
    }
  } else if (wg < 2) {
    asm volatile("setmaxnreg.inc.sync.aligned.u32 160;");
    bar_sync(0, 512);
    if (EN_ATT) {
    float am[96], ar[24];
    {
      const bool lead = (rtid() & 127) == 0;
      constexpr uint64_t dr0 = mkdesc(SB0 + 12288, 1024, 256, 3);
      const uint64_t db0 = sw64 ? mkdesc(SB0, 2048, 512, 2) : mkdesc(SB0, 4096, 1024, 1);
      const uint32_t kst = sw64 ? 64 : 128, bh = db0 >> 32;
      uint32_t s = 0, ph = 0, xo = 0;
      const int ln = rtid() & 31;
      const uint32_t xa = sb + OFF_X + (warp * 16 + (ln & 15)) * 128 + (((ln >> 4) ^ (ln & 7)) << 4);
      uint32_t A[8];
      mbar_wait(BAR(BR_FULL), 0);
      if (lead && wg == 0) TS(1);
      ldsm4(A, xa); ldsm4(A + 4, xa ^ 32);
      wg_fence();
      wg_rs48_tb(ar, A, dr0, 0); wg_rs192_tb(am, A, db0, 0);
      wg_commit();
      #pragma unroll 1
      for (int kb = 1; kb < 20; kb++) {
        const uint32_t wp = s * (W_SLOT >> 4), eb = BAR(BR_EMPTY) + 8 * s;
        wg_fence();
        wg_rs48_tb(ar, A + 4, desc2((uint32_t)dr0 + wp + 32, dr0 >> 32), 1);
        wg_rs192_tb(am, A + 4, desc2((uint32_t)db0 + wp + kst, bh), 1);
        wg_commit();
        if (++s == 5) { s = 0; ph ^= 1; }
        if (!(kb & 1)) { xo += 16384; if (xo == 49152) xo = 0; }
        mbar_wait(BAR(BR_FULL) + 8 * s, ph);
        const uint32_t xk = (xa + xo) ^ ((kb & 1) * 64), wn = s * (W_SLOT >> 4);
        wg_wait<1>();
        ldsm4(A, xk);
        wg_fence();
        wg_rs48_tb(ar, A, desc2((uint32_t)dr0 + wn, dr0 >> 32), 1);
        wg_rs192_tb(am, A, desc2((uint32_t)db0 + wn, bh), 1);
        wg_commit();
        wg_wait<1>();
        ldsm4(A + 4, xk ^ 32);
        if (lead && kb < 16) mbar_arrive(eb);
      }
      wg_fence();
      wg_rs48_tb(ar, A + 4, dr0 + 4 * (W_SLOT >> 4) + 32, 1);
      wg_rs192_tb(am, A + 4, desc2((uint32_t)db0 + 4 * (W_SLOT >> 4) + kst, bh), 1);
      wg_commit();
      wg_wait<0>();
      pin<96>(am); pin<24>(ar);
    }
    const int tid = rtid(), lane = tid & 31, tq = lane & 3;
    if (tid == 0) TS(2);
#define QV(j, e) ((j) < 8 ? am[4 * (j) + (e)] : ar[4 * ((j) - 8) + (e)])
#define KV_(j, e) ((j) < 8 ? am[32 + 4 * (j) + (e)] : ar[8 + 4 * ((j) - 8) + (e)])
#define VV(j, e) ((j) < 8 ? am[64 + 4 * (j) + (e)] : ar[16 + 4 * ((j) - 8) + (e)])
    {
      bar_sync(1, 256);
      if (tid == 0) mbar_arrive(BAR(BR_GEMM));
      const uint32_t ro = sb + (uint32_t)((warp * 16 + (lane & 15)) * 16);
      const int l0 = 2 * (c & 1) + (lane >> 4);
      const uint32_t ones = (tq == 0) ? 0x00003f80u : 0u;
#define PV(j) pack2(VV(j, 0), VV(j, 1)), pack2(VV(j, 2), VV(j, 3))
#define PK(j) pack2(phi(KV_(j, 0)), phi(KV_(j, 1))), pack2(phi(KV_(j, 2)), phi(KV_(j, 3)))
      stsm4(ro + OFF_V + (5 + 6 * (lane >> 4)) * 2048, ones, ones, ones, ones);
      #pragma unroll
      for (int j = 0; j < 10; j += 2) {
        const int l = (j == 8 && (c & 1)) ? l0 - 2 : l0 + j;
        stsm4(ro + OFF_V + (l + (l >= 5)) * 2048, PV(j), PV(j + 1));
        stsm4(ro + OFF_PK + l * 2048, PK(j), PK(j + 1));
      }
    }
    fence_async();
    bar_sync(1, 256);
    if (tid == 0) TS(3);
    mbar_wait(BAR(BR_EPOCH), 0);
    const unsigned epoch = lds32(sb + OFF_EPOCH);
    {
      float kv[24]; zero<24>(kv);
      constexpr uint64_t da = mkdesc(SB0 + OFF_PK, 128, 2048, 0), db = mkdesc(SB0 + OFF_V, 128, 2048, 0);
      wg_fence();
      #pragma unroll
      for (int s = 0; s < 8; s++) wg_ss48_tt(kv, desc2((uint32_t)da + wg * 640 + s * 16, da >> 32), desc2((uint32_t)db + wg * 768 + s * 16, db >> 32), s != 0);
      wg_commit();
      wg_wait<0>();
      pin<24>(kv);
      if (tid == 0) TS(15);
      if (w4 < 3) {
        const uint32_t wb = sb + OFF_KVS + (wg * 3 + w4) * 1536 + (lane & 15) * 96;
        #pragma unroll
        for (int j = 0; j < 6; j += 2)
          stsm4(wb + (j + (lane >> 4)) * 16, pack2(kv[4 * j], kv[4 * j + 1]), pack2(kv[4 * j + 2], kv[4 * j + 3]),
                pack2(kv[4 * j + 4], kv[4 * j + 5]), pack2(kv[4 * j + 6], kv[4 * j + 7]));
        __syncwarp();
        const int dl = w4 * 16 + (lane & 15), hl = dl >= 20;
        uint32_t v[4], z[4];
        lds128(v, wb + (3 * hl + (lane >> 4)) * 16);
        lds64(z, wb + 32 + 8 * hl); z[2] = lds32(wb + 80); z[3] = epoch & 1u;
        if (dl < 40) {
          uint4* dst = &g_kvp[(c * 16 + r) * 240 + wg * 40 + dl];
          v[3] = (v[3] & ~1u) | z[3];
          st128_rlx(dst + (lane >> 4) * 80, v);
          if (lane < 16) st128_rlx(dst + 160, z);
        }
      }
    }
    bar_sync(1, 256);
    if (tid == 0) { st_rlx(FLAG(0, r, c), epoch); mbar_arrive(BAR(BR_PUB)); TS(4); }
    const int kvi = (tid >= 80) + (tid >= 160) + (tid >= 240), kd = tid - 80 * kvi;
    const int khd = kd / 20, kt0 = 5 * (khd >> 1) + 2 * (khd & 1);
    const uint32_t rb = sb + OFF_KVB + kd * 16;
    if (kvi < 3) {
      #pragma unroll 1
      for (int m = kvi; m < 7; m += 3) { const int q = kt0 + 3 + m; sts128(rb + (q >= 10 ? q - 10 : q) * 1280, 0, 0, 0, 0); }
    }
    uint32_t qa[20];
    {
      const float sc = 1.44269504089f + __uint_as_float(lds32(sb + OFF_EPOCH) ^ epoch);
      #pragma unroll
      for (int j = 0; j < 10; j++) { qa[2 * j] = pack2(phi(QV(j, 0), sc), phi(QV(j, 1), sc)); qa[2 * j + 1] = pack2(phi(QV(j, 2), sc), phi(QV(j, 3), sc)); }
    }
    if (tid == 0) TS(5);
    if (warp == 7) mbar_wait(BAR(BR_KVP), 0);
    bar_sync(1, 256);
    if (tid == 0) TS(6);
    if (kvi < 3) {
      float s[8];
      zero<8>(s);
      uint32_t bad = 0;
      #pragma unroll 4
      for (int i = 0; i < 16; i += 2) {
        uint32_t w[4], x[4];
        lds128(w, sb + OFF_KVP + tid * 16 + i * 3840); lds128(x, sb + OFF_KVP + tid * 16 + i * 3840 + 3840);
        bad |= (w[3] ^ epoch) | (x[3] ^ epoch);
        #pragma unroll
        for (int e = 0; e < 4; e++) {
          asm("add.rn.bf16x2 %0, %0, %1;" : "+r"(w[e]) : "r"(x[e]));
          s[2 * e] += bf_lo(w[e]); s[2 * e + 1] += bf_hi(w[e]);
        }
      }
      if (__builtin_expect(bad & 1u, 0)) {
        zero<8>(s);
        #pragma unroll 1
        for (int i = 0; i < 16; i++) {
          uint32_t w[4] = {0, 0, 0, ~epoch};
          fix128_w3(w, &g_kvp[(c * 16 + i) * 240 + tid], epoch, 1u);
          #pragma unroll
          for (int e = 0; e < 4; e++) { s[2 * e] += bf_lo(w[e]); s[2 * e + 1] += bf_hi(w[e]); }
        }
        FIXCNT
      }
      const uint32_t p0 = pack2(s[0], s[1]), p1 = pack2(s[2], s[3]), p2 = pack2(s[4], s[5]), p3 = pack2(s[6], s[7]);
      if (kvi < 2) sts128(rb + (kt0 + (khd & 1) + kvi) * 1280, p0, p1, p2, p3);
      else {
        const bool od = khd & 1;
        sts128(rb + (5 * (khd >> 1) + 2) * 1280, od ? 0u : p0, od ? 0u : p1, od ? p0 : 0u, od ? p1 : 0u);
        const uint32_t zz = (p2 & 0xffffu) << (16 * (khd & 1));
        sts128(rb + 10 * 1280, khd < 2 ? zz : 0u, khd < 2 ? 0u : zz, 0u, 0u);
      }
    }
    fence_async();
    bar_sync(1, 256);
    if (tid == 0) { mbar_arrive(BAR(BR_SUM)); TS(7); }
    {
      float oa[44]; zero<44>(oa);
      constexpr uint64_t db = mkdesc(SB0 + OFF_KVB, 128, 1280, 0);
      wg_fence();
      #pragma unroll
      for (int s = 0; s < 5; s++) wg_rs88_tb(oa, &qa[4 * s], desc2((uint32_t)db + ((s == 4 && (c & 1)) ? 0 : (s + (c & 1)) * 16), db >> 32), s != 0);
      wg_commit();
      wg_wait<0>();
      pin<44>(oa);
      if (tid == 0) TS(13);
      float rc[4], rd[2][4];
      #pragma unroll
      for (int e = 0; e < 4; e++) asm("rcp.approx.ftz.f32 %0, %1;" : "=f"(rc[e]) : "f"(oa[40 + e] + 1e-6f));
      #pragma unroll
      for (int h = 0; h < 4; h++) {
        rd[0][h] = __shfl_sync(0xffffffff, rc[h & 1], (lane & 28) | (h >> 1));
        rd[1][h] = __shfl_sync(0xffffffff, rc[2 + (h & 1)], (lane & 28) | (h >> 1));
      }
      #pragma unroll
      for (int j = 0; j < 10; j++) {
        #pragma unroll
        for (int h = 0; h < 2; h++) {
          float f;
          if (j == 2) f = tq < 2 ? rd[h][0] : rd[h][1];
          else if (j == 7) f = tq < 2 ? rd[h][2] : rd[h][3];
          else f = rd[h][(8 * j) / 20];
          qa[2 * j + h] = pack2(oa[4 * j + 2 * h] * f, oa[4 * j + 2 * h + 1] * f);
        }
      }
      const uint32_t m0 = (lane & 7) == ((2 * w4) & 7), m1 = (lane & 7) == 2 * w4 + 1;
      const uint32_t oa_ = sb + OFF_EXTRA + (lane >> 4) * 2048 + (warp * 16 + (lane & 15)) * 16;
      bar_sync(1, 256);
#define TAG(v, m) (((v) & ~(m)) | (epoch & (m)))
      #pragma unroll
      for (int s = 0; s < 5; s++) stsm4(oa_ + s * 4096, TAG(qa[4 * s], m0), TAG(qa[4 * s + 1], m1), TAG(qa[4 * s + 2], m0), TAG(qa[4 * s + 3], m1));
    }
    fence_async();
    __syncwarp();
    if (lane == 0) mbar_arrive(BAR(BR_OSTG));
    if (tid == 0) TS(8);
    float oc[40]; zero<40>(oc);
    {
      constexpr uint64_t dw0 = mkdesc(SB0, OFF_WOR, 1024, 1), da0 = mkdesc(SB0, 2048, 128, 0);
      const uint32_t ck = sb + tid * 32 + ((lane >> 2) << 2), ck2 = ck + (wg ? 0 : 16384);
      uint32_t bad = 0;
      auto tile = [&](int i, uint32_t so) {
        const uint32_t al = (uint32_t)da0 + wg * 64 + (so >> 4), wl = (uint32_t)dw0 + i * 640 - (i >> 1) * (1278 << 16);
        wg_fence();
        #pragma unroll
        for (int s = 0; s < 5; s++) wg_ss80_tb(oc, desc2(al + s * 256, da0 >> 32), desc2(wl + s * 128, dw0 >> 32), (i | s) != 0);
        wg_commit();
        bad |= (lds32(ck + so) ^ epoch) | (lds32(ck + so + 8192) ^ epoch) | (lds32(ck2 + so) ^ epoch);
      };
      if (w4 == 0) {
        if (EN_SSM) mbar_wait(BAR(CONV_AT < 2 ? BR_KS : BR_Y + 1), 0);
        mbar_wait(BAR(BR_WO), 0);
        mbar_wait(BAR(BR_WO + 1), 0);
      }
      bar_sync(1, 256);
      if (tid == 0) TS(9);
      tile(0, SLOT(0));
      #pragma unroll 1
      for (int i = 1; i < 8; i++) {
        mbar_wait(BAR(BR_OFULL) + 8 * i, 0);
        tile(i, SLOT(i));
        wg_wait<1>();
        if (lane == 0) mbar_arrive(BAR(BR_OEMPTY - 1) + 8 * i);
      }
      #pragma unroll 1
      for (int n = 0; n < 56; n++) {
        const int i = n & 7;
        if (i == 0) {
          uint32_t any;
          asm volatile("{\n.reg .pred p;\nsetp.ne.u32 p, %1, 0;\nbarrier.red.or.pred p, 1, 256, p;\nselp.u32 %0, 1, 0, p;\n}" : "=r"(any) : "r"(bad & 1u) : "memory");
          if (!any) break;
          bad = 0;
          FIXCNT
        }
        wg_wait<0>();
        bar_sync(1, 256);
        if (tid == 0) { mbar_expect_tx(BAR(BR_RETRY), 20480); bulk_ld(sb + SLOT(5), &g_o[(r * 8 + CHUNK(i)) * 1280], 20480, BAR(BR_RETRY)); }
        mbar_wait(BAR(BR_RETRY), n & 1);
        tile(i, SLOT(5));
      }
      wg_wait<0>();
      pin<40>(oc);
    }
    if (tid == 0) TS(10);
    {
      const int row = w4 * 16 + (lane & 15);
      const uint32_t ob = sb + OFF_BLK + 3 * BLK + wg * 10240;
      #pragma unroll
      for (int j = 0; j < 8; j += 2)
        stsm4(ob + row * 128 + (((j + (lane >> 4)) ^ (row & 7)) << 4), pack2(oc[4 * j], oc[4 * j + 1]), pack2(oc[4 * j + 2], oc[4 * j + 3]),
              pack2(oc[4 * j + 4], oc[4 * j + 5]), pack2(oc[4 * j + 6], oc[4 * j + 7]));
      stsm4(ob + 8192 + row * 32 + (lane >> 4) * 16, pack2(oc[32], oc[33]), pack2(oc[34], oc[35]), pack2(oc[36], oc[37]), pack2(oc[38], oc[39]));
      fence_async();
      bar_sync(2 + wg, 128);
      if (w4 == 0 && elect_one()) {
        tma2d_st(&prm.m[M_O64], ob, 640 + c * 64, r * 128 + wg * 64);
        tma2d_st(&prm.m[M_O16], ob + 8192, 1152 + c * 16, r * 128 + wg * 64);
        bulk_commit(); bulk_wait0_read();
        if (wg == 0) { TS(11); DUMP(0, 20); }
      }
    }
    }
  } else {
    const int g = lane >> 2, tq = lane & 3, t7 = tid & 127;
    uint32_t raw[5][4], pd;
    {
      const int ch = c * 80 + r * 5;
      #pragma unroll
      for (int e = 0; e < 4; e++) {
        const __nv_bfloat16* pp = prm.par[e] + ch * 128 + t7;
        #pragma unroll
        for (int q = 0; q < 5; q++) asm volatile("ld.global.nc.u16 %0, [%1];" : "=r"(raw[q][e]) : "l"(pp + q * 128));
      }
      asm volatile("ld.global.nc.u16 %0, [%1];" : "=r"(pd) : "l"(((lane & 8) ? prm.dskip : prm.logdt) + ch + min(lane & 7, 4)));
    }
    asm volatile("bar.arrive 0, 512;" ::: "memory");
    if (EN_SSM) {
    {
      #pragma unroll 1
      for (int k = 0; k < 4; k++) {
        const uint32_t z = sb + OFF_BLK + k * BLK + t7 * 16;
        sts128(z + B_TBL, 0, 0, 0, 0); sts128(z + B_TBL + 2048, 0, 0, 0, 0);
      }
      if (t7 < 80) sts128(sb + OFF_BLK + (t7 >> 4) * BLK - 256 + (t7 & 15) * 16, 0, 0, 0, 0);
      const uint32_t ea = sb + OFF_BLK + (2 + (w4 & 1)) * BLK + (lane >> 4) * 7168 + ((lane >> 3) & 1) * 256 + (lane & 7) * 16 + (w4 >> 1) * 2048;
      constexpr uint64_t dE = mkdesc(SB0 + OFF_BLK + 2 * BLK, 128, 512, 0);
      const uint32_t xa = sb + OFF_BLK + 18560 + t7 * 8, xr_ = sb + OFF_BLK + 18560 + (t7 ^ 64) * 8;
      uint32_t pr[5][2];
      #pragma unroll
      for (int q = 0; q < 5; q++) {
        #pragma unroll
        for (int e = 0; e < 2; e++) pr[q][e] = raw[q][2 * e] | (raw[q][2 * e + 1] << 16);
        const uint32_t m = __reduce_max_sync(0xffffffff, max(raw[q][2] & 0x7fffu, raw[q][3] & 0x7fffu));
        if (lane == 0) sts32(sb + OFF_EPOCH + 64 + q * 16 + w4 * 4, m);
      }
      bar_sync(4, 128);
      if (t7 == 0) TS(40);
      const int j = (w4 & 1) * 16 + (w4 >> 1) * 8 + g, i2 = tq < 2 ? 64 * tq + j : 32 * (tq - 2) + j;
      const uint32_t e2 = B_TBL + 4 * (tq < 2 ? T_F3 + (((i2 - 1) & 1) ? 80 : 0) + ((i2 - 1) >> 1) + 16 : T_F2 + (i2 & 1) * 96 + (i2 >> 1));
      const uint32_t e1 = tq < 2 ? (i2 ? e2 - 64 : B_TBL + 4 * (T_F2 + 175)) : B_TBL + 4 * (i2 ? T_F2 + ((2 * i2 - 1) & 3) * 48 + ((2 * i2 - 1) >> 2) : 16 + 511);
      const uint32_t e0 = B_TBL + (16 + 8 * j + 2 * tq) * 4;
      #pragma unroll 1
      for (int it = 0; it < 5; it++) {
        const int k = it;
        const uint32_t blk = sb + OFF_BLK + k * BLK;
        float fac;
        {
          const int q = it;
          if (it == 4) {
            mbar_wait(BAR(BR_UOUT), 0);
            sts128(sb + OFF_UT + B_TBL + t7 * 16, 0, 0, 0, 0); sts128(sb + OFF_UT + B_TBL + 2048 + t7 * 16, 0, 0, 0, 0);
          }
          const uint32_t ga = ea + 4096 - (w4 >> 1) * 512;
#define PUT4(i, a, b, c_, d) sts128(((i) < 8 ? ea + ((i) >> 1) * 512 : ga + (((i) - 8) >> 1) * 512) + ((i) & 1) * 128, a, b, c_, d)
          const uint32_t pa0 = pr[0][0], pc0 = pr[0][1];
          const float dt = bf_round(expf(bf_lo(__shfl_sync(0xffffffff, pd, q))));
          #pragma unroll
          for (int e = 0; e < 2; e++) { pr[0][e] = pr[1][e]; pr[1][e] = pr[2][e]; pr[2][e] = pr[3][e]; pr[3][e] = pr[4][e]; }
          uint32_t mm[4];
          lds128(mm, sb + OFF_EPOCH + 64 + q * 16);
          const uint32_t ex = min(max(max(max(mm[0], mm[1]), max(mm[2], mm[3])) >> 7, 1u), 253u);
          const float sc = __uint_as_float((254u - ex) << 23);
          fac = 2.f * dt * __uint_as_float(ex << 23);
          const float lr = -bf_round(expf(bf_lo(pa0))) * dt * 1.44269504089f;
          const float tn = bf_hi(pa0) * dt * 0.15915494309f;
          float z1r, z1i, z2r, z2i, z4r, z4i, xr[8], xi[8], gr[8], gi[8], wr[9], wi[9];
          cexp_t(lr, -tn, z1r, z1i);
          cexp_t(lr * 8.f, tn * 8.f, xr[1], xi[1]);
          cexp_t(lr * 64.f, tn * 64.f, wr[0], wi[0]);
          xr[0] = 1.f; xi[0] = 0.f;
          cmul(xr[1], xi[1], xr[1], xi[1], xr[2], xi[2]); cmul(xr[2], xi[2], xr[1], xi[1], xr[3], xi[3]);
          cmul(xr[2], xi[2], xr[2], xi[2], xr[4], xi[4]);
          #pragma unroll
          for (int b = 1; b < 4; b++) cmul(xr[4], xi[4], xr[b], xi[b], xr[4 + b], xi[4 + b]);
          cmul(wr[0], wi[0], wr[0], wi[0], wr[1], wi[1]); cmul(wr[1], wi[1], wr[0], wi[0], wr[2], wi[2]);
          cmul(wr[1], wi[1], wr[1], wi[1], wr[3], wi[3]); cmul(wr[3], wi[3], wr[3], wi[3], wr[4], wi[4]);
          cmul(wr[4], wi[4], wr[3], wi[3], wr[5], wi[5]); cmul(wr[4], wi[4], wr[4], wi[4], wr[6], wi[6]);
          cmul(wr[6], wi[6], wr[4], wi[4], wr[7], wi[7]); cmul(wr[6], wi[6], wr[6], wi[6], wr[8], wi[8]);
          uint32_t R[4], I[4], PR[4], PI[4];
          #pragma unroll
          for (int b = 0; b < 4; b++) { R[b] = packh(xr[2 * b], xr[2 * b + 1]); I[b] = packh(xi[2 * b], xi[2 * b + 1]); }
          PUT4(0, R[0], R[1], R[2], R[3]); PUT4(1, I[0], I[1], I[2], I[3]);
          #pragma unroll
          for (int i = 0; i < 3; i++) {
            const uint32_t z = packh(wr[i], wi[i]);
            #pragma unroll
            for (int b = 0; b < 4; b++) hcm2(R[b], I[b], z, PR[b], PI[b]);
            PUT4(2 * i + 2, PR[0], PR[1], PR[2], PR[3]); PUT4(2 * i + 3, PI[0], PI[1], PI[2], PI[3]);
          }
          gr[0] = bf_lo(pc0) * sc; gi[0] = -bf_hi(pc0) * sc;
          cmul(z1r, z1i, z1r, z1i, z2r, z2i); cmul(z2r, z2i, z2r, z2i, z4r, z4i);
          cmul(gr[0], gi[0], z1r, z1i, gr[1], gi[1]);
          cmul(gr[0], gi[0], z2r, z2i, gr[2], gi[2]); cmul(gr[1], gi[1], z2r, z2i, gr[3], gi[3]);
          #pragma unroll
          for (int b = 0; b < 4; b++) cmul(gr[b], gi[b], z4r, z4i, gr[4 + b], gi[4 + b]);
          PUT4(8, packh(gr[0], gr[1]), packh(gr[2], gr[3]), packh(gr[4], gr[5]), packh(gr[6], gr[7]));
          PUT4(9, packh(gi[0], gi[1]), packh(gi[2], gi[3]), packh(gi[4], gi[5]), packh(gi[6], gi[7]));
          {
            const uint32_t z = packh(wr[3], -wi[3]), a4r = packh(gr[0], gr[4]), a4i = packh(gi[0], gi[4]);
            hcm2(packh(gr[0], gr[2]), packh(gi[0], gi[2]), z, PR[0], PI[0]);
            hcm2(packh(gr[4], gr[6]), packh(gi[4], gi[6]), z, PR[1], PI[1]);
            hcm2(a4r, a4i, packh(wr[4], -wi[4]), PR[2], PI[2]);
            hcm2(a4r, a4i, packh(wr[5], -wi[5]), PR[3], PI[3]);
            PUT4(10, PR[0], PR[1], PR[2], PR[3]); PUT4(11, PI[0], PI[1], PI[2], PI[3]);
            float hr, hi_;
            cmul(gr[0], gi[0], wr[3], -wi[3], hr, hi_);
            const uint32_t cr = packh(gr[0], hr), ci = packh(gi[0], hi_);
            #pragma unroll
            for (int i = 0; i < 3; i++) hcm2(cr, ci, packh(wr[6 + i], -wi[6 + i]), PR[i], PI[i]);
            PUT4(12, PR[0], PR[1], PR[2], 0u); PUT4(13, PI[0], PI[1], PI[2], 0u);
          }
          fence_async();
          bar_sync(4, 128);
        }
        float ka[24]; zero<24>(ka);
        wg_fence();
        #pragma unroll
        for (int s = 0; s < 8; s++) {
          const uint64_t d = dE + (s >> 2) * (BLK >> 4) + ((s >> 1) & 1) * 448 + (s & 1) * 16;
          wg_ss48_tt_h(ka, d, d + 256, s != 0);
        }
        wg_commit();
        const float dsk = bf_lo(__shfl_sync(0xffffffff, pd, 8 + it));
        wg_wait<0>();
        pin<24>(ka);
        float kk[6];
        const bool up = w4 >= 2;
        #pragma unroll
        for (int n = 0; n < 3; n++) {
          sts64f(xa + n * BLK, up ? ka[12 + 4 * n] : ka[4 * n + 2], up ? ka[13 + 4 * n] : ka[4 * n + 3]);
          kk[2 * n] = up ? ka[14 + 4 * n] : ka[4 * n]; kk[2 * n + 1] = up ? ka[15 + 4 * n] : ka[4 * n + 1];
        }
        if (it) bar_sync(4, 128); else bar_sync(8, 160);
          if (it == 4 && w4 == 0) {
            mbar_wait(BAR(BR_U), 0);
            if (elect_one()) {
              mbar_expect_tx(BAR(BR_U2), 8192);
              bulk_ld(blk - 2 * BLK, g_uy + (c * 80 + r * 5 + 2) * 2048, 4096, BAR(BR_U2)); bulk_ld(blk - BLK, g_uy + (c * 80 + r * 5 + 3) * 2048, 4096, BAR(BR_U2));
            }
            __syncwarp();
          }
        #pragma unroll
        for (int n = 0; n < 3; n++) {
          uint32_t o[2]; lds64(o, xr_ + n * BLK);
          kk[2 * n] = (kk[2 * n] + __uint_as_float(o[0])) * fac; kk[2 * n + 1] = (kk[2 * n + 1] + __uint_as_float(o[1])) * fac;
        }
        if (t7 == 0) kk[0] += dsk;
        {
          const uint32_t v = pack2(kk[1], kk[0]), vh = v >> 16;
          const uint32_t u = pack2(kk[2], kk[3]), w = pack2(kk[4], kk[5]), uu = pack2(kk[2], kk[2]), us = pack2(kk[3], kk[2]);
          const uint32_t x = tq < 2 ? w : u, xh = x >> 16;
          sts32(blk + e0 + 4, v); sts16(blk + e0, vh); sts16(blk + e0 + 10, v);
          sts16(blk + e1, x); sts16(blk + e1 + 6, x); sts16(blk + e2, xh); sts16(blk + e2 + 6, xh);
          if (tq < 2) {
            const uint32_t pb = blk + e0 + 1024 + 8 * tq;
            sts32(pb + 4, uu); sts32(pb + 8, us); sts16(pb + 14, us);
            if (i2) { sts16(pb - 4, u); sts32(pb, uu); }
          }
          if (i2 == 0) {
            const uint32_t tb = blk + B_TBL;
            if (tq == 0) { sts16(tb + (16 + 256) * 4, u); sts16(tb + (T_S + 3) * 4, w); sts32(tb + (T_S + 4) * 4, pack2(kk[4], kk[4])); sts16(tb + (T_S + 5) * 4 + 2, w); }
            else { sts32(tb + 528 * 4, uu); sts32(tb + 529 * 4, uu); sts32(tb + 530 * 4, uu); sts16(tb + 531 * 4 + 2, u); sts16(tb + (T_F3 + 80 + 63) * 4, w); }
          }
        }
        if (t7 == 0) TS(49 + it);
      }
    }
    asm volatile("setmaxnreg.inc.sync.aligned.u32 136;");
    if (t7 == 0) TS(41);
    mbar_wait(BAR(BR_U), 0);
    bar_sync(4, 128);
    if (EN_ATT) mbar_wait(BAR(BR_GEMM), 0);
    if (t7 == 0) TS(42);
    mbar_wait(BAR(BR_EPOCH), 0);
    const uint32_t ytag = (lds32(sb + OFF_EPOCH) & 1u) * 0x10001u, ym = lane < 4 ? 0x10001u : 0u;
    #pragma unroll 1
    for (int pass = 1; pass >= 0; pass--) {
      const int k = pass ? w4 : 4;
      if (k & 2) mbar_wait(BAR(BR_U2), 0);
      const uint32_t blk = sb + OFF_BLK + k * BLK, tb = blk + B_TBL + (uint32_t)((g - 2 * tq) * 4);
      float acc[16][4];
      zero<64>(&acc[0][0]);
      const int kl = 16 * (lane >> 4) + 2 * (lane & 7) + ((lane >> 3) & 1);
      {
        auto ubase = [&](int sh) { const int q = kl - 2 * sh; return blk + (uint32_t)((q * 16) ^ ((q * 2) & 0x10)); };
#define LDQ(A, sh) _Pragma("unroll") for (int m = 0; m < 4; m++) load_quad(A[m], tb + (16 + 16 * (sh) + 128 * m) * 4);
#define LDB(B, ub, h) _Pragma("unroll") for (int p = 0; p < 4; p++) ldsm4(B[p], (ub) + (4 * (h) + p) * 512);
#define MLO(A, B) _Pragma("unroll") for (int m = 0; m < 4; m++) _Pragma("unroll") for (int cc = 0; cc < 8; cc++) mma16816(acc[cc + m], A[m], &B[cc >> 1][(cc & 1) * 2]);
#define MHI(A, B) _Pragma("unroll") for (int m = 0; m < 4; m++) _Pragma("unroll") for (int cc = 0; cc < 8 - m; cc++) mma16816(acc[8 + cc + m], A[m], &B[cc >> 1][(cc & 1) * 2]);
        int p_ = pass ? 0 : w4;
        const int pe = pass ? 4 : w4 + 1;
        uint32_t A[4][4], A2[4][4], Bl[4][4], Bh[4][4];
        uint32_t ub = ubase(p_ + 4);
        LDQ(A, p_ + 4) LDB(Bl, ub, 0)
        #pragma unroll 1
        for (; p_ < pe; p_++) {
          LDB(Bh, ub, 1)
          MLO(A, Bl)
          ub = ubase(p_);
          LDQ(A2, p_) LDB(Bl, ub, 0)
          MHI(A, Bh)
          LDB(Bh, ub, 1)
          load_quad(A[0], tb + (16 + 512 + 16 * (p_ & 1)) * 4); load_quad(A[1], tb + (T_S + 16 * (p_ & 1)) * 4);
          MLO(A2, Bl)
          if (p_ < 2) {
            #pragma unroll
            for (int cc = 0; cc < 8; cc++) mma16816(acc[cc + 4], A[0], &Bl[cc >> 1][(cc & 1) * 2]);
            #pragma unroll
            for (int cc = 0; cc < 4; cc++) mma16816(acc[cc + 12], A[0], &Bh[cc >> 1][(cc & 1) * 2]);
            #pragma unroll
            for (int cc = 0; cc < 8; cc++) mma16816(acc[cc + 8], A[1], &Bl[cc >> 1][(cc & 1) * 2]);
          }
          const int pn = ((p_ + 1) & 3) + 4;
          ub = ubase(pn);
          LDQ(A, pn) LDB(Bl, ub, 0)
          MHI(A2, Bh)
        }
      }
      if (t7 == 0) TS(57 + 3 * pass);
      mbar_wait(BAR(BR_DRDY + 1), 0);
      {
        const int ih = (lane >> 3) & 1;
        const uint32_t dl = blk + B_D + (uint32_t)(((lane >> 4) * 8 + (lane & 7)) * 16);
        const uint32_t d0_ = dl + ih * 1552, d8_ = dl + (ih ? 0 : 1536), d3_ = dl + B_D7 + ih * 1024;
        auto cls2 = [&](uint32_t da, uint32_t ta) {
          uint32_t B[6][2], A[6][4];
          #pragma unroll
          for (int e = 0; e < 6; e++) { B[e][0] = lds32v(ta + (e + 4) * 32); B[e][1] = lds32v(ta + (e + 3) * 32); }
          #pragma unroll
          for (int kk = 0; kk < 6; kk++) ldsm4t(A[kk], da + kk * 256);
          #pragma unroll
          for (int e = 0; e < 6; e++)
            #pragma unroll
            for (int kk = 0; kk < 6; kk++) if (2 * kk + e + 4 < 16) mma16816(acc[2 * kk + e + 4], A[kk], B[e]);
        };
        auto cls3 = [&](uint32_t da, uint32_t ta) {
          uint32_t B[8][2], A[4][4];
          #pragma unroll
          for (int e = 0; e < 8; e++) { B[e][0] = lds32v(ta + (e + 8) * 32); B[e][1] = lds32v(ta + (e + 7) * 32); }
          #pragma unroll
          for (int kk = 0; kk < 4; kk++) ldsm4t(A[kk], da + kk * 256);
          #pragma unroll
          for (int kk = 0; kk < 4; kk++)
            #pragma unroll
            for (int e = 0; e < 8; e++) if (2 * kk + e + 8 < 16) mma16816(acc[2 * kk + e + 8], A[kk], B[e]);
        };
        if (pass) {
          #pragma unroll 1
          for (int a = 0; a < 2; a++) {
            cls2(d0_ + a * B_D5, tb + (T_F2 + 48 * a - 32) * 4);
            cls2(d8_ + a * B_D5, tb + (T_F2 + 48 * a + 64) * 4);
            cls3(d3_ + a * 2048, tb + (T_F3 + 80 * a - 64) * 4);
          }
        } else {
          cls2(((w4 & 2) ? d8_ : d0_) + (w4 & 1) * B_D5, tb + (T_F2 + 48 * w4 - 32) * 4);
          if (w4 >= 2) cls3(d3_ + (w4 - 2) * 2048, tb + (T_F3 + 80 * (w4 - 2) - 64) * 4);
        }
      }
      if (t7 == 0) TS(58 + 3 * pass);
      const uint32_t ya = blk + (uint32_t)((kl * 16) ^ ((kl * 2) & 0x10));
#define YTAG(v) (((v) & ~ym) | (ytag & ym))
#define STY(p) stsm4t(ya + (p) * 512, YTAG(pack2(acc[2 * (p)][0], acc[2 * (p)][1])), pack2(acc[2 * (p)][2], acc[2 * (p)][3]), \
                      YTAG(pack2(acc[2 * (p) + 1][0], acc[2 * (p) + 1][1])), pack2(acc[2 * (p) + 1][2], acc[2 * (p) + 1][3]))
      if (pass == 0) {
        const uint32_t xw = blk + 4096 + w4 * 4096 + lane * 16, xr = blk + 4096 + w4 * 1024 + lane * 16;
        #pragma unroll
        for (int h = 0; h < 2; h++) {
          bar_sync(4, 128);
          if (h == CONV_AT && t7 == 0) mbar_arrive(BAR(BR_KS));
          #pragma unroll
          for (int i = 0; i < 8; i++)
            sts128(xw + i * 512, __float_as_uint(acc[8 * h + i][0]), __float_as_uint(acc[8 * h + i][1]), __float_as_uint(acc[8 * h + i][2]), __float_as_uint(acc[8 * h + i][3]));
          bar_sync(4, 128);
          float y[8];
          #pragma unroll
          for (int i = 0; i < 8; i++) {
            uint32_t o[4]; lds128(o, xr + (i >> 1) * 4096 + (i & 1) * 512);
            #pragma unroll
            for (int e = 0; e < 4; e++) y[4 * (i & 1) + e] = i < 2 ? __uint_as_float(o[e]) : y[4 * (i & 1) + e] + __uint_as_float(o[e]);
          }
          stsm4t(ya + (4 * h + w4) * 512, YTAG(pack2(y[0], y[1])), pack2(y[2], y[3]), YTAG(pack2(y[4], y[5])), pack2(y[6], y[7]));
        }
      } else {
        __syncwarp();
        #pragma unroll
        for (int p = 0; p < 8; p++) STY(p);
      }
      if (t7 == 0 && !pass) TS(55);
      fence_async();
      __syncwarp();
      if (lane == 0) mbar_arrive(BAR(BR_Y + 1) - 8 * pass);
      if (t7 == 0) TS(59 + 3 * pass);
    }
    if (t7 == 0) DUMP(40, 64);
    #pragma unroll 1
    for (int n = 0; n < 64; n++) if (!y_transpose(sb, w4, lane, ytag)) break;
    }
  }
}

typedef CUresult (*EncFn)(CUtensorMap*, CUtensorMapDataType, cuuint32_t, void*, const cuuint64_t*, const cuuint64_t*, const cuuint32_t*,
                          const cuuint32_t*, CUtensorMapInterleave, CUtensorMapSwizzle, CUtensorMapL2promotion, CUtensorMapFloatOOBfill);
static void mkmap(EncFn enc, CUtensorMap* m, const void* base, int rank, const cuuint64_t* dims, const cuuint64_t* strides, const cuuint32_t* box, CUtensorMapSwizzle swz) {
  cuuint32_t es[5] = {1, 1, 1, 1, 1};
  enc(m, CU_TENSOR_MAP_DATA_TYPE_BFLOAT16, rank, const_cast<void*>(base), dims, strides, box, es, CU_TENSOR_MAP_INTERLEAVE_NONE, swz,
      CU_TENSOR_MAP_L2_PROMOTION_L2_128B, CU_TENSOR_MAP_FLOAT_OOB_FILL_NONE);
}

extern "C" void kernel_launch(void* const* d_in, const int* in_sizes, int n_in, void* d_out, int out_size) {
  void* fn = nullptr; cudaDriverEntryPointQueryResult qr;
  cudaGetDriverEntryPoint("cuTensorMapEncodeTiled", &fn, cudaEnableDefault, &qr);
  EncFn enc = (EncFn)fn;
  void* uy = nullptr; cudaGetSymbolAddress(&uy, g_uy);
  const cuuint64_t dx[2] = {640, 2048}, sx[1] = {1280};
  const cuuint32_t bx[2] = {64, 128}, bu[2] = {80, 128};
  const cuuint64_t dw[3] = {640, 640, 3}, sw[2] = {3840, 1280};
  const cuuint32_t br[3] = {16, 32, 3};
  const cuuint64_t dwa[4] = {64, 640, 10, 3}, swa[3] = {3840, 128, 1280}, dwb[4] = {32, 640, 20, 3}, swb[3] = {3840, 64, 1280};
  const cuuint32_t bwa[4] = {64, 32, 1, 3}, bwb[4] = {32, 32, 2, 3};
  const cuuint64_t dwo[2] = {640, 640};
  const cuuint32_t bwo[2] = {64, 80}, bo64[2] = {64, 64}, bo16[2] = {16, 64};
  const cuuint64_t dsa[2] = {2048, 1280}, ssa[1] = {4096};
  const cuuint32_t bsa[2] = {64, 80};
  const cuuint64_t dout[2] = {1280, 2048}, sout[1] = {2560};
  Params prm;
  mkmap(enc, &prm.m[M_X], d_in[7], 2, dx, sx, bx, CU_TENSOR_MAP_SWIZZLE_128B);
  mkmap(enc, &prm.m[M_W128], d_in[8], 4, dwa, swa, bwa, CU_TENSOR_MAP_SWIZZLE_128B);
  mkmap(enc, &prm.m[M_W64], d_in[8], 4, dwb, swb, bwb, CU_TENSOR_MAP_SWIZZLE_64B);
  mkmap(enc, &prm.m[M_WR], d_in[8], 3, dw, sw, br, CU_TENSOR_MAP_SWIZZLE_32B);
  mkmap(enc, &prm.m[M_U], d_in[0], 2, dx, sx, bu, CU_TENSOR_MAP_SWIZZLE_NONE);
  mkmap(enc, &prm.m[M_WO], d_in[9], 2, dwo, sx, bwo, CU_TENSOR_MAP_SWIZZLE_128B);
  mkmap(enc, &prm.m[M_O64], d_out, 2, dout, sout, bo64, CU_TENSOR_MAP_SWIZZLE_128B);
  mkmap(enc, &prm.m[M_O16], d_out, 2, dout, sout, bo16, CU_TENSOR_MAP_SWIZZLE_NONE);
  mkmap(enc, &prm.m[M_SA], uy, 2, dsa, ssa, bsa, CU_TENSOR_MAP_SWIZZLE_128B);
  mkmap(enc, &prm.m[M_OUT], d_out, 2, dout, sout, bu, CU_TENSOR_MAP_SWIZZLE_NONE);
  prm.u = (const __nv_bfloat16*)d_in[0]; prm.wo = (const __nv_bfloat16*)d_in[9];
  for (int i = 0; i < 4; i++) prm.par[i] = (const __nv_bfloat16*)d_in[1 + i];
  prm.logdt = (const __nv_bfloat16*)d_in[5]; prm.dskip = (const __nv_bfloat16*)d_in[6];
  cudaFuncSetAttribute(fused_kernel, cudaFuncAttributeMaxDynamicSharedMemorySize, SMEM_BYTES);
  cudaLaunchConfig_t cfg = {};
  cfg.gridDim = dim3(128); cfg.blockDim = dim3(512); cfg.dynamicSmemBytes = SMEM_BYTES; cfg.stream = cudaStreamPerThread;
  cudaLaunchAttribute at[1];
  at[0].id = cudaLaunchAttributeClusterDimension; at[0].val.clusterDim.x = 2; at[0].val.clusterDim.y = 1; at[0].val.clusterDim.z = 1;
  cfg.attrs = at; cfg.numAttrs = 1;
  cudaLaunchKernelEx(&cfg, fused_kernel, prm);
}
```

```cpp
#include <cuda_runtime.h>
#include <cuda_bf16.h>
#include <cuda_fp16.h>
#include <cuda.h>
#include <stdint.h>

#define KST 2
#define UKB 4
#define UPF 0
#define CONV_AT 1
#define EN_ATT 1
#define EN_SSM 1

__device__ __align__(1024) __nv_bfloat16 g_uy[2 * 640 * 2048];
__device__ __align__(128) uint4 g_kvp[8 * 16 * 240];
__device__ __align__(128) uint4 g_o[128 * 1280];
__device__ __align__(128) unsigned g_flag[4 * 128 * 32];
__device__ unsigned g_epoch[128];
#define TS(i) do {} while (0)
#define DUMP(lo, hi) do {} while (0)
#define FIXCNT

constexpr uint32_t SB0 = 1024;
constexpr uint32_t W_SLOT = 15360, OFF_X = 76800;
constexpr uint32_t OFF_WOR = 81920, OFF_KVP = 10240, OFF_KVS = 71680, OFF_PK = 10240, OFF_V = 30720, OFF_EXTRA = 102400, OFF_KVB = OFF_EXTRA;
constexpr uint32_t OFF_BAR = 125952, OFF_BLK = 128000, BLK = 20480;
constexpr uint32_t B_D = 4096, B_D5 = 3088, B_D7 = 6176, B_D9 = 8224, B_TBL = 14400;
constexpr int T_S = 576, T_F2 = 624, T_F3 = 816;
constexpr uint32_t OFF_UT = OFF_BLK + 4 * BLK;
constexpr uint32_t SMEM_BYTES = OFF_BLK + 5 * BLK;
enum { BR_FULL = 0, BR_WO = 5, BR_PUB = 7, BR_KVP = 8, BR_U = 9, BR_SUM = 10, BR_GEMM = 11, BR_UIN = 12, BR_YIN = 13, BR_EPOCH = 14,
       BR_FREE = 15, BR_RETRY = 17, BR_UOUT = 18, BR_OFULL = 18, BR_KS = 26, BR_EMPTY = 31, BR_OEMPTY = 36, BR_Y = 43, BR_OSTG = 45,
       BR_DRDY = 46, BR_U2 = 48, BR_COUNT = 50 };
constexpr uint32_t OFF_EPOCH = OFF_BAR + 8 * BR_COUNT;
enum { M_X, M_W128, M_W64, M_WR, M_U, M_WO, M_O64, M_O16, M_SA, M_OUT, M_COUNT };

__device__ __forceinline__ long long clk64() { long long t; asm volatile("mov.u64 %0, %%clock64;" : "=l"(t) :: "memory"); return t; }
__device__ __forceinline__ uint32_t smem_u32(const void* p) { return (uint32_t)__cvta_generic_to_shared(p); }
__host__ __device__ constexpr uint64_t mkdesc(uint32_t addr, uint32_t lbo, uint32_t sbo, uint32_t swz) {
  return (uint64_t)((addr & 0x3FFFF) >> 4) | ((uint64_t)(lbo >> 4) << 16) | ((uint64_t)(sbo >> 4) << 32) | ((uint64_t)swz << 62);
}
__device__ __forceinline__ uint64_t desc2(uint32_t lo, uint32_t hi) { uint64_t d; asm("mov.b64 %0, {%1, %2};" : "=l"(d) : "r"(lo), "r"(hi)); return d; }
__device__ __forceinline__ void mbar_init(uint32_t bar, uint32_t cnt) { asm volatile("mbarrier.init.shared::cta.b64 [%0], %1;" :: "r"(bar), "r"(cnt) : "memory"); }
__device__ __forceinline__ void mbar_expect_tx(uint32_t bar, uint32_t bytes) { asm volatile("mbarrier.arrive.expect_tx.shared::cta.b64 _, [%0], %1;" :: "r"(bar), "r"(bytes) : "memory"); }
__device__ __forceinline__ void mbar_arrive(uint32_t bar) { asm volatile("mbarrier.arrive.shared::cta.b64 _, [%0];" :: "r"(bar) : "memory"); }
__device__ __forceinline__ void mbar_wait(uint32_t bar, uint32_t parity) {
  asm volatile("{\n.reg .pred p;\n.reg .u32 c;\nmov.u32 c, 0;\n"
    "WL:\nmbarrier.try_wait.parity.shared::cta.b64 p, [%0], %1;\n@p bra WD;\n"
    "add.u32 c, c, 1;\nsetp.lt.u32 p, c, 200000;\n@p bra WL;\nWD:\n}" :: "r"(bar), "r"(parity) : "memory");
}
__device__ __forceinline__ void poll_all(const unsigned* p, unsigned val) {
  asm volatile("{\n.reg .pred p;\n.reg .u32 c, v;\nmov.u32 c, 0;\n"
    "PL:\nld.relaxed.gpu.global.u32 v, [%0];\nsetp.eq.u32 p, v, %1;\nvote.sync.all.pred p, p, 0xffffffff;\n@p bra PD;\n"
    "add.u32 c, c, 1;\nsetp.lt.u32 p, c, 100000;\n@p bra PL;\nPD:\n}" :: "l"(p), "r"(val) : "memory");
}
__device__ __forceinline__ void poll_all_acq(const unsigned* p, unsigned val) {
  asm volatile("{\n.reg .pred p;\n.reg .u32 c, v;\nmov.u32 c, 0;\n"
    "PL:\nld.acquire.gpu.global.u32 v, [%0];\nsetp.eq.u32 p, v, %1;\nvote.sync.all.pred p, p, 0xffffffff;\n@p bra PD;\n"
    "nanosleep.u32 300;\nadd.u32 c, c, 1;\nsetp.lt.u32 p, c, 100000;\n@p bra PL;\nPD:\n}" :: "l"(p), "r"(val) : "memory");
}
__device__ __forceinline__ unsigned poll_bit(const unsigned* p, unsigned val, unsigned mask) {
  unsigned bal;
  asm volatile("{\n.reg .pred p;\n.reg .u32 c, v;\nmov.u32 c, 0;\n"
    "PL:\nld.relaxed.gpu.global.u32 v, [%1];\nsetp.eq.u32 p, v, %2;\nvote.sync.ballot.b32 %0, p, 0xffffffff;\n"
    "and.b32 v, %0, %3;\nsetp.ne.u32 p, v, 0;\n@p bra PD;\n"
    "add.u32 c, c, 1;\nsetp.lt.u32 p, c, 100000;\n@p bra PL;\nPD:\n}" : "=&r"(bal) : "l"(p), "r"(val), "r"(mask) : "memory");
  return bal;
}
__device__ __forceinline__ void fix128_w0(uint32_t* v, const void* p, uint32_t tag, uint32_t mask) {
  asm volatile("{\n.reg .pred p;\n.reg .u32 c, x;\n.reg .b128 t;\n.reg .b64 lo, hi;\nmov.u32 c, 0;\n"
    "FL:\nxor.b32 x, %0, %5;\nand.b32 x, x, %6;\nsetp.eq.u32 p, x, 0;\n@p bra FD;\n"
    "ld.relaxed.gpu.global.b128 t, [%4];\nmov.b128 {lo, hi}, t;\nmov.b64 {%0, %1}, lo;\nmov.b64 {%2, %3}, hi;\n"
    "add.u32 c, c, 1;\nsetp.lt.u32 p, c, 100000;\n@p bra FL;\nFD:\n}"
    : "+r"(v[0]), "+r"(v[1]), "+r"(v[2]), "+r"(v[3]) : "l"(p), "r"(tag), "r"(mask) : "memory");
}
__device__ __forceinline__ void fix128_w3(uint32_t* v, const void* p, uint32_t tag, uint32_t mask) {
  asm volatile("{\n.reg .pred p;\n.reg .u32 c, x;\n.reg .b128 t;\n.reg .b64 lo, hi;\nmov.u32 c, 0;\n"
    "FL:\nxor.b32 x, %3, %5;\nand.b32 x, x, %6;\nsetp.eq.u32 p, x, 0;\n@p bra FD;\n"
    "ld.relaxed.gpu.global.b128 t, [%4];\nmov.b128 {lo, hi}, t;\nmov.b64 {%0, %1}, lo;\nmov.b64 {%2, %3}, hi;\n"
    "add.u32 c, c, 1;\nsetp.lt.u32 p, c, 100000;\n@p bra FL;\nFD:\n}"
    : "+r"(v[0]), "+r"(v[1]), "+r"(v[2]), "+r"(v[3]) : "l"(p), "r"(tag), "r"(mask) : "memory");
}
__device__ __forceinline__ void fence_acq() { asm volatile("fence.acq_rel.gpu;" ::: "memory"); }
__device__ __forceinline__ bool elect_one() {
  uint32_t p; asm volatile("{\n.reg .pred P;\nelect.sync _|P, 0xffffffff;\nselp.u32 %0, 1, 0, P;\n}" : "=r"(p)); return p;
}
__device__ __forceinline__ void bar_sync(int id, int n) { asm volatile("bar.sync %0, %1;" :: "r"(id), "r"(n) : "memory"); }
__device__ __forceinline__ void fence_async() { asm volatile("fence.proxy.async.shared::cta;" ::: "memory"); }
__device__ __forceinline__ void fence_async_g() { asm volatile("fence.proxy.async.global;" ::: "memory"); }
__device__ __forceinline__ void tma2d(uint32_t dst, const CUtensorMap* m, uint32_t bar, int c0, int c1) {
  asm volatile("cp.async.bulk.tensor.2d.shared::cluster.global.mbarrier::complete_tx::bytes [%0], [%1, {%3, %4}], [%2];"
    :: "r"(dst), "l"(m), "r"(bar), "r"(c0), "r"(c1) : "memory");
}
__device__ __forceinline__ void tma3d(uint32_t dst, const CUtensorMap* m, uint32_t bar, int c0, int c1, int c2) {
  asm volatile("cp.async.bulk.tensor.3d.shared::cluster.global.mbarrier::complete_tx::bytes [%0], [%1, {%3, %4, %5}], [%2];"
    :: "r"(dst), "l"(m), "r"(bar), "r"(c0), "r"(c1), "r"(c2) : "memory");
}
__device__ __forceinline__ void tma4d(uint32_t dst, const CUtensorMap* m, uint32_t bar, int c0, int c1, int c2, int c3) {
  asm volatile("cp.async.bulk.tensor.4d.shared::cluster.global.mbarrier::complete_tx::bytes [%0], [%1, {%3, %4, %5, %6}], [%2];"
    :: "r"(dst), "l"(m), "r"(bar), "r"(c0), "r"(c1), "r"(c2), "r"(c3) : "memory");
}
__device__ __forceinline__ void tma2d_st(const CUtensorMap* m, uint32_t src, int c0, int c1) {
  asm volatile("cp.async.bulk.tensor.2d.global.shared::cta.bulk_group [%0, {%2, %3}], [%1];"
    :: "l"(m), "r"(src), "r"(c0), "r"(c1) : "memory");
}
__device__ __forceinline__ void bulk_ld(uint32_t dst, const void* src, uint32_t bytes, uint32_t bar) {
  asm volatile("cp.async.bulk.shared::cluster.global.mbarrier::complete_tx::bytes [%0], [%1], %2, [%3];"
    :: "r"(dst), "l"(src), "r"(bytes), "r"(bar) : "memory");
}
__device__ __forceinline__ void bulk_st(void* dst, uint32_t src, uint32_t bytes) {
  asm volatile("cp.async.bulk.global.shared::cta.bulk_group [%0], [%1], %2;" :: "l"(dst), "r"(src), "r"(bytes) : "memory");
}
__device__ __forceinline__ void bulk_commit() { asm volatile("cp.async.bulk.commit_group;" ::: "memory"); }
__device__ __forceinline__ void bulk_wait0() { asm volatile("cp.async.bulk.wait_group 0;" ::: "memory"); }
__device__ __forceinline__ void bulk_wait0_read() { asm volatile("cp.async.bulk.wait_group.read 0;" ::: "memory"); }
__device__ __forceinline__ unsigned ld_rlx(const unsigned* p) { unsigned v; asm volatile("ld.relaxed.gpu.global.u32 %0, [%1];" : "=r"(v) : "l"(p) : "memory"); return v; }
__device__ __forceinline__ unsigned ld_acq(const unsigned* p) { unsigned v; asm volatile("ld.acquire.gpu.global.u32 %0, [%1];" : "=r"(v) : "l"(p) : "memory"); return v; }
__device__ __forceinline__ void st_rlx(unsigned* p, unsigned v) { asm volatile("st.relaxed.gpu.global.u32 [%0], %1;" :: "l"(p), "r"(v) : "memory"); }
__device__ __forceinline__ void st_rel(unsigned* p, unsigned v) { asm volatile("st.release.gpu.global.u32 [%0], %1;" :: "l"(p), "r"(v) : "memory"); }
__device__ __forceinline__ void ld128_rlx(uint32_t* v, const void* p) {
  asm volatile("{\n.reg .b128 t;\n.reg .b64 lo, hi;\nld.relaxed.gpu.global.b128 t, [%4];\nmov.b128 {lo, hi}, t;\n"
    "mov.b64 {%0, %1}, lo;\nmov.b64 {%2, %3}, hi;\n}" : "=r"(v[0]), "=r"(v[1]), "=r"(v[2]), "=r"(v[3]) : "l"(p) : "memory");
}
__device__ __forceinline__ void st128_rlx(void* p, const uint32_t* v) {
  asm volatile("{\n.reg .b128 t;\n.reg .b64 lo, hi;\nmov.b64 lo, {%1, %2};\nmov.b64 hi, {%3, %4};\nmov.b128 t, {lo, hi};\n"
    "st.relaxed.gpu.global.b128 [%0], t;\n}" :: "l"(p), "r"(v[0]), "r"(v[1]), "r"(v[2]), "r"(v[3]) : "memory");
}
__device__ __forceinline__ uint32_t lds32(uint32_t a) { uint32_t v; asm volatile("ld.shared.u32 %0, [%1];" : "=r"(v) : "r"(a) : "memory"); return v; }
__device__ __forceinline__ uint32_t lds32v(uint32_t a) { uint32_t v; asm volatile("ld.volatile.shared.u32 %0, [%1];" : "=r"(v) : "r"(a) : "memory"); return v; }
__device__ __forceinline__ uint32_t cpa(uint32_t a, uint32_t one) { uint32_t v; asm volatile("mul.lo.u32 %0, %1, %2;" : "=r"(v) : "r"(a), "r"(one)); return v; }
__device__ __forceinline__ uint32_t cpb(uint32_t a, uint32_t zero) { uint32_t v; asm volatile("or.b32 %0, %1, %2;" : "=r"(v) : "r"(a), "r"(zero)); return v; }
__device__ __forceinline__ uint32_t lds16(uint32_t a) { uint16_t v; asm volatile("ld.shared.u16 %0, [%1];" : "=h"(v) : "r"(a) : "memory"); return v; }
__device__ __forceinline__ float ldsf(uint32_t a) { float v; asm volatile("ld.shared.f32 %0, [%1];" : "=f"(v) : "r"(a) : "memory"); return v; }
__device__ __forceinline__ void lds128(uint32_t* v, uint32_t a) { asm volatile("ld.shared.v4.u32 {%0,%1,%2,%3}, [%4];" : "=r"(v[0]), "=r"(v[1]), "=r"(v[2]), "=r"(v[3]) : "r"(a) : "memory"); }
__device__ __forceinline__ void sts32(uint32_t a, uint32_t v) { asm volatile("st.shared.u32 [%0], %1;" :: "r"(a), "r"(v) : "memory"); }
__device__ __forceinline__ void sts16(uint32_t a, uint32_t v) { asm volatile("st.shared.u16 [%0], %1;" :: "r"(a), "h"((uint16_t)v) : "memory"); }
__device__ __forceinline__ void sts64f(uint32_t a, float x, float y) { asm volatile("st.shared.v2.f32 [%0], {%1,%2};" :: "r"(a), "f"(x), "f"(y) : "memory"); }
__device__ __forceinline__ void sts128(uint32_t a, uint32_t x, uint32_t y, uint32_t z, uint32_t w) { asm volatile("st.shared.v4.u32 [%0], {%1,%2,%3,%4};" :: "r"(a), "r"(x), "r"(y), "r"(z), "r"(w) : "memory"); }
__device__ __forceinline__ void stsm4(uint32_t a, uint32_t r0, uint32_t r1, uint32_t r2, uint32_t r3) {
  asm volatile("stmatrix.sync.aligned.m8n8.x4.shared.b16 [%0], {%1,%2,%3,%4};" :: "r"(a), "r"(r0), "r"(r1), "r"(r2), "r"(r3) : "memory");
}
__device__ __forceinline__ void stsm4t(uint32_t a, uint32_t r0, uint32_t r1, uint32_t r2, uint32_t r3) {
  asm volatile("stmatrix.sync.aligned.m8n8.x4.trans.shared.b16 [%0], {%1,%2,%3,%4};" :: "r"(a), "r"(r0), "r"(r1), "r"(r2), "r"(r3) : "memory");
}
__device__ __forceinline__ void ldsm4t(uint32_t* r, uint32_t a) {
  asm volatile("ldmatrix.sync.aligned.m8n8.x4.trans.shared.b16 {%0,%1,%2,%3}, [%4];" : "=r"(r[0]), "=r"(r[1]), "=r"(r[2]), "=r"(r[3]) : "r"(a) : "memory");
}
__device__ __forceinline__ void ldsm4(uint32_t* r, uint32_t a) {
  asm volatile("ldmatrix.sync.aligned.m8n8.x4.shared.b16 {%0,%1,%2,%3}, [%4];" : "=r"(r[0]), "=r"(r[1]), "=r"(r[2]), "=r"(r[3]) : "r"(a) : "memory");
}
__device__ __forceinline__ void mma16816(float* d, const uint32_t* a, const uint32_t* b) {
  asm volatile("mma.sync.aligned.m16n8k16.row.col.f32.bf16.bf16.f32 {%0,%1,%2,%3}, {%4,%5,%6,%7}, {%8,%9}, {%0,%1,%2,%3};"
    : "+f"(d[0]), "+f"(d[1]), "+f"(d[2]), "+f"(d[3]) : "r"(a[0]), "r"(a[1]), "r"(a[2]), "r"(a[3]), "r"(b[0]), "r"(b[1]));
}
__device__ __forceinline__ uint32_t pack2(float lo, float hi) { uint32_t r; asm("cvt.rn.bf16x2.f32 %0, %1, %2;" : "=r"(r) : "f"(hi), "f"(lo)); return r; }
__device__ __forceinline__ uint32_t packh(float lo, float hi) { uint32_t r; asm("cvt.rn.f16x2.f32 %0, %1, %2;" : "=r"(r) : "f"(hi), "f"(lo)); return r; }
__device__ __forceinline__ uint32_t hcmul(uint32_t x, uint32_t zp, uint32_t zq) {
  const __half2 xx = *reinterpret_cast<__half2*>(&x);
  const __half2 r = __hfma2(__high2half2(xx), *reinterpret_cast<__half2*>(&zq), __hmul2(__low2half2(xx), *reinterpret_cast<__half2*>(&zp)));
  return *reinterpret_cast<const uint32_t*>(&r);
}
__device__ __forceinline__ void hcm2(uint32_t xr, uint32_t xi, uint32_t z, uint32_t& pr, uint32_t& pi) {
  const __half2 a = *reinterpret_cast<__half2*>(&xr), b = *reinterpret_cast<__half2*>(&xi), zz = *reinterpret_cast<__half2*>(&z);
  const __half2 re = __hfma2(__hneg2(b), __high2half2(zz), __hmul2(a, __low2half2(zz)));
  const __half2 im = __hfma2(a, __high2half2(zz), __hmul2(b, __low2half2(zz)));
  pr = *reinterpret_cast<const uint32_t*>(&re); pi = *reinterpret_cast<const uint32_t*>(&im);
}
__device__ __forceinline__ void sts64(uint32_t a, uint32_t x, uint32_t y) { asm volatile("st.shared.v2.u32 [%0], {%1,%2};" :: "r"(a), "r"(x), "r"(y) : "memory"); }
__device__ __forceinline__ void lds64(uint32_t* v, uint32_t a) { asm volatile("ld.shared.v2.u32 {%0,%1}, [%2];" : "=r"(v[0]), "=r"(v[1]) : "r"(a) : "memory"); }
__device__ __forceinline__ float bf_lo(uint32_t v) { return __uint_as_float(v << 16); }
__device__ __forceinline__ float bf_hi(uint32_t v) { return __uint_as_float(v & 0xffff0000u); }
__device__ __forceinline__ float bf_round(float x) { return bf_lo(pack2(x, 0.f)); }
__device__ __forceinline__ float ex2(float x) { float r; asm("ex2.approx.ftz.f32 %0, %1;" : "=f"(r) : "f"(x)); return r; }
__device__ __forceinline__ float phi(float t, float l2e = 1.44269504089f) {
  float e = ex2(t * l2e) + 1e-6f;
  asm("{\n.reg .pred p;\nsetp.gt.f32 p, %1, 0f00000000;\n@p add.f32 %0, %1, 0f3F800008;\n}" : "+f"(e) : "f"(t));
  return e;
}
__device__ __forceinline__ void wg_fence() { asm volatile("wgmma.fence.sync.aligned;" ::: "memory"); }
__device__ __forceinline__ void wg_commit() { asm volatile("wgmma.commit_group.sync.aligned;" ::: "memory"); }
template <int N> __device__ __forceinline__ void wg_wait() { asm volatile("wgmma.wait_group.sync.aligned %0;" :: "n"(N) : "memory"); }
template <int N> __device__ __forceinline__ void pin(float* a) {
  #pragma unroll
  for (int i = 0; i < N; i++) asm volatile("" : "+f"(a[i]) :: "memory");
}
__device__ __forceinline__ int rtid() { int t; asm volatile("mov.u32 %0, %%tid.x;" : "=r"(t)); return t; }
__device__ __forceinline__ int opaque(int v) { asm volatile("" : "+r"(v)); return v; }
template <int N> __device__ __forceinline__ void zero(float* a) {
  #pragma unroll
  for (int i = 0; i < N; i++) asm volatile("mov.b32 %0, 0;" : "=f"(a[i]));
}
template <int N> __device__ __forceinline__ void pinu(uint32_t* a) {
  #pragma unroll
  for (int i = 0; i < N; i++) asm volatile("" : "+r"(a[i]) :: "memory");
}
__device__ __forceinline__ void cexp_t(float lg2mag, float turns, float& re, float& im) {
  float m = ex2(lg2mag);
  float fr = (turns - __fadd_rn(__fadd_rn(turns, 12582912.f), -12582912.f)) * 6.283185307f;
  re = m * __cosf(fr); im = m * __sinf(fr);
}
__device__ __forceinline__ void cmul(float ar, float ai, float br, float bi, float& cr, float& ci) {
  cr = fmaf(ar, br, -ai * bi); ci = fmaf(ar, bi, ai * br);
}

__device__ __forceinline__ void wg_ss48_tt(float* d, uint64_t da, uint64_t db, int scale_d) {
  asm volatile("{\n.reg .pred p;\nsetp.ne.b32 p, %26, 0;\n"
    "wgmma.mma_async.sync.aligned.m64n48k16.f32.bf16.bf16 "
    "{%0, %1, %2, %3, %4, %5, %6, %7, %8, %9, %10, %11, %12, %13, %14, %15, %16, %17, %18, %19, %20, %21, %22, %23}, %24, %25, p, 1, 1, 1, 1;\n}\n"
    : "+f"(d[0]), "+f"(d[1]), "+f"(d[2]), "+f"(d[3]), "+f"(d[4]), "+f"(d[5]), "+f"(d[6]), "+f"(d[7]), "+f"(d[8]), "+f"(d[9]), "+f"(d[10]), "+f"(d[11]), "+f"(d[12]), "+f"(d[13]), "+f"(d[14]), "+f"(d[15]), "+f"(d[16]), "+f"(d[17]), "+f"(d[18]), "+f"(d[19]), "+f"(d[20]), "+f"(d[21]), "+f"(d[22]), "+f"(d[23])
    : "l"(da), "l"(db), "r"(scale_d));
}
__device__ __forceinline__ void wg_rs88_tb(float* d, const uint32_t* a, uint64_t db, int scale_d) {
  asm volatile("{\n.reg .pred p;\nsetp.ne.b32 p, %49, 0;\n"
    "wgmma.mma_async.sync.aligned.m64n88k16.f32.bf16.bf16 "
    "{%0, %1, %2, %3, %4, %5, %6, %7, %8, %9, %10, %11, %12, %13, %14, %15, %16, %17, %18, %19, %20, %21, %22, %23, %24, %25, %26, %27, %28, %29, %30, %31, %32, %33, %34, %35, %36, %37, %38, %39, %40, %41, %42, %43}, {%44, %45, %46, %47}, %48, p, 1, 1, 1;\n}\n"
    : "+f"(d[0]), "+f"(d[1]), "+f"(d[2]), "+f"(d[3]), "+f"(d[4]), "+f"(d[5]), "+f"(d[6]), "+f"(d[7]), "+f"(d[8]), "+f"(d[9]), "+f"(d[10]), "+f"(d[11]), "+f"(d[12]), "+f"(d[13]), "+f"(d[14]), "+f"(d[15]), "+f"(d[16]), "+f"(d[17]), "+f"(d[18]), "+f"(d[19]), "+f"(d[20]), "+f"(d[21]), "+f"(d[22]), "+f"(d[23]), "+f"(d[24]), "+f"(d[25]), "+f"(d[26]), "+f"(d[27]), "+f"(d[28]), "+f"(d[29]), "+f"(d[30]), "+f"(d[31]), "+f"(d[32]), "+f"(d[33]), "+f"(d[34]), "+f"(d[35]), "+f"(d[36]), "+f"(d[37]), "+f"(d[38]), "+f"(d[39]), "+f"(d[40]), "+f"(d[41]), "+f"(d[42]), "+f"(d[43])
    : "r"(a[0]), "r"(a[1]), "r"(a[2]), "r"(a[3]), "l"(db), "r"(scale_d));
}
__device__ __forceinline__ void wg_ss80_tb(float* d, uint64_t da, uint64_t db, int scale_d) {
  asm volatile("{\n.reg .pred p;\nsetp.ne.b32 p, %42, 0;\n"
    "wgmma.mma_async.sync.aligned.m64n80k16.f32.bf16.bf16 "
    "{%0, %1, %2, %3, %4, %5, %6, %7, %8, %9, %10, %11, %12, %13, %14, %15, %16, %17, %18, %19, %20, %21, %22, %23, %24, %25, %26, %27, %28, %29, %30, %31, %32, %33, %34, %35, %36, %37, %38, %39}, %40, %41, p, 1, 1, 0, 1;\n}\n"
    : "+f"(d[0]), "+f"(d[1]), "+f"(d[2]), "+f"(d[3]), "+f"(d[4]), "+f"(d[5]), "+f"(d[6]), "+f"(d[7]), "+f"(d[8]), "+f"(d[9]), "+f"(d[10]), "+f"(d[11]), "+f"(d[12]), "+f"(d[13]), "+f"(d[14]), "+f"(d[15]), "+f"(d[16]), "+f"(d[17]), "+f"(d[18]), "+f"(d[19]), "+f"(d[20]), "+f"(d[21]), "+f"(d[22]), "+f"(d[23]), "+f"(d[24]), "+f"(d[25]), "+f"(d[26]), "+f"(d[27]), "+f"(d[28]), "+f"(d[29]), "+f"(d[30]), "+f"(d[31]), "+f"(d[32]), "+f"(d[33]), "+f"(d[34]), "+f"(d[35]), "+f"(d[36]), "+f"(d[37]), "+f"(d[38]), "+f"(d[39])
    : "l"(da), "l"(db), "r"(scale_d));
}
__device__ __forceinline__ void wg_ss48_tt_h(float* d, uint64_t da, uint64_t db, int scale_d) {
  asm volatile("{\n.reg .pred p;\nsetp.ne.b32 p, %26, 0;\n"
    "wgmma.mma_async.sync.aligned.m64n48k16.f32.f16.f16 "
    "{%0, %1, %2, %3, %4, %5, %6, %7, %8, %9, %10, %11, %12, %13, %14, %15, %16, %17, %18, %19, %20, %21, %22, %23}, %24, %25, p, 1, 1, 1, 1;\n}\n"
    : "+f"(d[0]), "+f"(d[1]), "+f"(d[2]), "+f"(d[3]), "+f"(d[4]), "+f"(d[5]), "+f"(d[6]), "+f"(d[7]), "+f"(d[8]), "+f"(d[9]), "+f"(d[10]), "+f"(d[11]), "+f"(d[12]), "+f"(d[13]), "+f"(d[14]), "+f"(d[15]), "+f"(d[16]), "+f"(d[17]), "+f"(d[18]), "+f"(d[19]), "+f"(d[20]), "+f"(d[21]), "+f"(d[22]), "+f"(d[23])
    : "l"(da), "l"(db), "r"(scale_d));
}
__device__ __forceinline__ void wg_rs192_tb(float* d, const uint32_t* a, uint64_t db, int scale_d) {
  asm volatile("{\n.reg .pred p;\nsetp.ne.b32 p, %101, 0;\n"
    "wgmma.mma_async.sync.aligned.m64n192k16.f32.bf16.bf16 "
    "{%0, %1, %2, %3, %4, %5, %6, %7, %8, %9, %10, %11, %12, %13, %14, %15, %16, %17, %18, %19, %20, %21, %22, %23, %24, %25, %26, %27, %28, %29, %30, %31, %32, %33, %34, %35, %36, %37, %38, %39, %40, %41, %42, %43, %44, %45, %46, %47, %48, %49, %50, %51, %52, %53, %54, %55, %56, %57, %58, %59, %60, %61, %62, %63, %64, %65, %66, %67, %68, %69, %70, %71, %72, %73, %74, %75, %76, %77, %78, %79, %80, %81, %82, %83, %84, %85, %86, %87, %88, %89, %90, %91, %92, %93, %94, %95}, {%96, %97, %98, %99}, %100, p, 1, 1, 1;\n}\n"
    : "+f"(d[0]), "+f"(d[1]), "+f"(d[2]), "+f"(d[3]), "+f"(d[4]), "+f"(d[5]), "+f"(d[6]), "+f"(d[7]), "+f"(d[8]), "+f"(d[9]), "+f"(d[10]), "+f"(d[11]), "+f"(d[12]), "+f"(d[13]), "+f"(d[14]), "+f"(d[15]), "+f"(d[16]), "+f"(d[17]), "+f"(d[18]), "+f"(d[19]), "+f"(d[20]), "+f"(d[21]), "+f"(d[22]), "+f"(d[23]), "+f"(d[24]), "+f"(d[25]), "+f"(d[26]), "+f"(d[27]), "+f"(d[28]), "+f"(d[29]), "+f"(d[30]), "+f"(d[31]), "+f"(d[32]), "+f"(d[33]), "+f"(d[34]), "+f"(d[35]), "+f"(d[36]), "+f"(d[37]), "+f"(d[38]), "+f"(d[39]), "+f"(d[40]), "+f"(d[41]), "+f"(d[42]), "+f"(d[43]), "+f"(d[44]), "+f"(d[45]), "+f"(d[46]), "+f"(d[47]), "+f"(d[48]), "+f"(d[49]), "+f"(d[50]), "+f"(d[51]), "+f"(d[52]), "+f"(d[53]), "+f"(d[54]), "+f"(d[55]), "+f"(d[56]), "+f"(d[57]), "+f"(d[58]), "+f"(d[59]), "+f"(d[60]), "+f"(d[61]), "+f"(d[62]), "+f"(d[63]), "+f"(d[64]), "+f"(d[65]), "+f"(d[66]), "+f"(d[67]), "+f"(d[68]), "+f"(d[69]), "+f"(d[70]), "+f"(d[71]), "+f"(d[72]), "+f"(d[73]), "+f"(d[74]), "+f"(d[75]), "+f"(d[76]), "+f"(d[77]), "+f"(d[78]), "+f"(d[79]), "+f"(d[80]), "+f"(d[81]), "+f"(d[82]), "+f"(d[83]), "+f"(d[84]), "+f"(d[85]), "+f"(d[86]), "+f"(d[87]), "+f"(d[88]), "+f"(d[89]), "+f"(d[90]), "+f"(d[91]), "+f"(d[92]), "+f"(d[93]), "+f"(d[94]), "+f"(d[95])
    : "r"(a[0]), "r"(a[1]), "r"(a[2]), "r"(a[3]), "l"(db), "r"(scale_d));
}
__device__ __forceinline__ void wg_rs48_tb(float* d, const uint32_t* a, uint64_t db, int scale_d) {
  asm volatile("{\n.reg .pred p;\nsetp.ne.b32 p, %29, 0;\n"
    "wgmma.mma_async.sync.aligned.m64n48k16.f32.bf16.bf16 "
    "{%0, %1, %2, %3, %4, %5, %6, %7, %8, %9, %10, %11, %12, %13, %14, %15, %16, %17, %18, %19, %20, %21, %22, %23}, {%24, %25, %26, %27}, %28, p, 1, 1, 1;\n}\n"
    : "+f"(d[0]), "+f"(d[1]), "+f"(d[2]), "+f"(d[3]), "+f"(d[4]), "+f"(d[5]), "+f"(d[6]), "+f"(d[7]), "+f"(d[8]), "+f"(d[9]), "+f"(d[10]), "+f"(d[11]), "+f"(d[12]), "+f"(d[13]), "+f"(d[14]), "+f"(d[15]), "+f"(d[16]), "+f"(d[17]), "+f"(d[18]), "+f"(d[19]), "+f"(d[20]), "+f"(d[21]), "+f"(d[22]), "+f"(d[23])
    : "r"(a[0]), "r"(a[1]), "r"(a[2]), "r"(a[3]), "l"(db), "r"(scale_d));
}

struct Params {
  const __nv_bfloat16 *par[4], *logdt, *dskip, *u, *wo;
  CUtensorMap m[M_COUNT];
};

#define CHUNK(i) ((i) == 0 ? c : ((i) == 7 ? (c ^ 1) : (((c & 6) + 1 + (i)) & 7)))
#define FLAG(kind, rr, cc) (&g_flag[((kind) * 128 + (rr) * 8 + (cc)) * 32])
#define SLOT(i) ((i) == 0 ? OFF_EXTRA : OFF_BLK - 256 + ((i) > 5 ? (i) - 6 : (i) - 1) * BLK)
__device__ __forceinline__ void load_quad(uint32_t* A, uint32_t addr) {
  A[0] = lds32v(addr); A[1] = lds32v(addr + 32); A[2] = lds32v(addr - 32); A[3] = lds32v(addr);
}

__device__ __forceinline__ bool y_transpose(uint32_t sb, int w5, int lane, uint32_t ytag) {
  const int mi = lane >> 3, rw = lane & 7;
  const uint32_t sa = sb + OFF_EXTRA + (w5 * 16 + rw) * 128 + ((mi ^ rw) << 4), da = sb + SLOT(3) + (8 * mi + rw) * 160 + w5 * 32;
  const uint32_t ym = lane < 4 ? 0x10001u : 0u;
  bar_sync(7, 160);
  uint32_t v[8][4], bad = 0;
  #pragma unroll
  for (int q = 0; q < 8; q++) ldsm4t(v[q], (sa ^ ((q & 1) * 64 + ((q >> 1) & 1) * 16)) + ((q >> 1) & 1) * 10240 + (q >> 2) * 1024);
  #pragma unroll
  for (int q = 0; q < 8; q++) {
    bad |= (v[q][0] ^ ytag) | (v[q][2] ^ ytag);
    stsm4(da + (q & 3) * 5120 + (q >> 2) * 16, v[q][0] & ~ym, v[q][1], v[q][2] & ~ym, v[q][3]);
  }
  fence_async();
  uint32_t any;
  asm volatile("{\n.reg .pred p;\nsetp.ne.u32 p, %1, 0;\nbarrier.red.or.pred p, 7, 160, p;\nselp.u32 %0, 1, 0, p;\n}" : "=r"(any) : "r"(bad & ym) : "memory");
  return any;
}

__global__ void __launch_bounds__(512, 1) fused_kernel(const __grid_constant__ Params prm) {
  extern __shared__ unsigned char smem_raw[];
  const uint32_t sb = __shfl_sync(0xffffffff, smem_u32(smem_raw), 0);
  const int tid = threadIdx.x, lane = tid & 31;
  const int warp = __shfl_sync(0xffffffff, tid >> 5, 0), wg = warp >> 2, w4 = warp & 3;
  const int cta = blockIdx.x, r = cta >> 3, c = cta & 7;
  if ((sb & 0xffffffu) != SB0) return;
#define BAR(i) (sb + OFF_BAR + 8 * (i))
  const bool sw64 = ((c + 1) & 2) != 0;

  const CUtensorMap* mwp = &prm.m[sw64 ? M_W64 : M_W128];
  const int mcol = (c * 80 + (c & 1) * 16) >> (sw64 ? 5 : 6), rcol = c * 80 + ((c & 1) ? 0 : 64);
  if (warp == 12 && elect_one()) {
    #pragma unroll
    for (int i = 0; i < 5; i++) mbar_init(BAR(BR_FULL + i), 1);
    asm volatile("fence.mbarrier_init.release.cluster;" ::: "memory");
    if (EN_ATT) {
      mbar_expect_tx(BAR(BR_FULL), W_SLOT + 16384);
      tma4d(sb, mwp, BAR(BR_FULL), 0, 0, mcol, 0);
      tma2d(sb + OFF_X, &prm.m[M_X], BAR(BR_FULL), 0, r * 128);
      tma3d(sb + 12288, &prm.m[M_WR], BAR(BR_FULL), rcol, 0, 0);
      mbar_expect_tx(BAR(BR_FULL + 1), W_SLOT);
      tma4d(sb + W_SLOT, mwp, BAR(BR_FULL + 1), 0, 32, mcol, 0);
      tma3d(sb + W_SLOT + 12288, &prm.m[M_WR], BAR(BR_FULL + 1), rcol, 32, 0);
      TS(24);
    }
  }
  if (warp == 13 && elect_one()) {
    asm volatile("prefetch.tensormap [%0];" :: "l"(&prm.m[M_X]) : "memory");
    asm volatile("prefetch.tensormap [%0];" :: "l"(&prm.m[M_WR]) : "memory");
  }
  if (wg == 3) {
    asm volatile("setmaxnreg.dec.sync.aligned.u32 56;");
    const int tid = rtid(), lane = tid & 31;
    if (warp == 12) {
      asm volatile("bar.arrive 0, 512;" ::: "memory");
      {
        uint32_t s = 2, ph = 1, xs = 16384;
        #pragma unroll 1
        for (int kb = 2; kb < 20; kb++) {
          if (kb == 4) bar_sync(6, 128);
          if (kb >= 5) mbar_wait(BAR(BR_EMPTY) + 8 * s, ph);
          if (EN_ATT && elect_one()) {
            const uint32_t st = sb + s * W_SLOT, fb = BAR(BR_FULL) + 8 * s;
            mbar_expect_tx(fb, (kb & 1) ? W_SLOT : W_SLOT + 16384);
            if (!(kb & 1)) tma2d(sb + OFF_X + xs, &prm.m[M_X], fb, kb * 32, r * 128);
            tma4d(st, mwp, fb, 0, kb * 32, mcol, 0);
            tma3d(st + 12288, &prm.m[M_WR], fb, rcol, kb * 32, 0);
          }
          if (kb < 4 && lane == 0) TS(24 + kb);
          if (UPF && kb >= UKB - 4 && kb < UKB && elect_one())
            asm volatile("cp.async.bulk.prefetch.L2.global [%0], 5120;" :: "l"(prm.u + cta * 10240 + (kb - (UKB - 4)) * 2560) : "memory");
          if (EN_SSM && kb == (EN_ATT ? UKB : 4) && elect_one()) { mbar_expect_tx(BAR(BR_UIN), 20480); tma2d(sb + OFF_UT, &prm.m[M_U], BAR(BR_UIN), c * 80, r * 128); }
          if (kb == 14 && elect_one()) asm volatile("cp.async.bulk.prefetch.L2.global [%0], 6400;" :: "l"(prm.wo + cta * 3200) : "memory");
          if (!EN_ATT && kb == 4) break;
          if (++s == 5) { s = 0; ph ^= 1; }
          if (kb & 1) { xs += 16384; if (xs == 49152) xs = 0; }
        }
      }
      if (EN_ATT) {
      mbar_wait(BAR(BR_EPOCH), 0);
      const unsigned epoch = lds32(sb + OFF_EPOCH);
      const unsigned* fo = FLAG(3, r, lane & 7);
      unsigned seen = __ballot_sync(0xffffffff, ld_rlx(lane < 16 ? fo : FLAG(0, lane & 15, c)) == epoch) & 0xffu;
      mbar_wait(BAR(BR_GEMM), 0);
      if (elect_one()) {
        mbar_expect_tx(BAR(BR_WO), 10240);
        tma2d(sb, &prm.m[M_WO], BAR(BR_WO), c * 64, c * 80);
        mbar_expect_tx(BAR(BR_KVP), 61440);
        mbar_expect_tx(BAR(BR_WO + 1), 7 * 10240);
      }
      {
        uint32_t ds = sb + OFF_WOR + (lane >> 3) * 128 + (((lane & 7) ^ (lane >> 3)) << 4);
        #pragma unroll 1
        for (int h = 0; h < 2; h++) {
          const int i = (lane & 6) + h;
          const char* gs = reinterpret_cast<const char*>(prm.wo) + (size_t)((lane >> 3) + CHUNK(i) * 80) * 1280 + 1024 + c * 32 + (lane & 1) * 16;
          #pragma unroll 2
          for (int q = 0; q < 20; q++) {
            asm volatile("cp.async.cg.shared.global [%0], [%1], 16;" :: "r"(ds), "l"(gs) : "memory");
            ds = (ds + 512) ^ 64; gs += 5120;
          }
        }
      }
      mbar_wait(BAR(BR_PUB), 0);
      poll_all(FLAG(0, lane & 15, c), epoch);
      if (elect_one()) { TS(23); bulk_ld(sb + OFF_KVP, &g_kvp[c * 16 * 240], 61440, BAR(BR_KVP)); }
      asm volatile("cp.async.wait_all;" ::: "memory");
      fence_async();
      mbar_arrive(BAR(BR_WO));
      mbar_wait(BAR(BR_SUM), 0);
      if (elect_one()) {
        #pragma unroll 1
        for (int i = 1; i < 8; i++) tma2d(sb + i * 10240, &prm.m[M_WO], BAR(BR_WO + 1), c * 64, CHUNK(i) * 80);
      }
      mbar_wait(BAR(BR_OSTG), 0);
      if (elect_one()) {
        bulk_st(&g_o[cta * 1280], sb + OFF_EXTRA, 20480);
        bulk_commit();
        bulk_wait0();
        st_rlx(FLAG(3, r, c), epoch);
        mbar_arrive(BAR(BR_OEMPTY));
        TS(20);
      }
      __syncwarp();
      #pragma unroll 1
      for (int i = 1; i < 8; i++) {
        const int src = CHUNK(i);
        if (!((seen >> src) & 1)) seen = poll_bit(fo, epoch, 1u << src);
        if (i > 5) mbar_wait(BAR(BR_OEMPTY - 5) + 8 * i, 0);
        if (EN_SSM && (i == 1 || i == 5)) mbar_wait(BAR(BR_FREE) + 2 * (i & 4), 0);
        if (elect_one()) {
          mbar_expect_tx(BAR(BR_OFULL) + 8 * i, 20480);
          bulk_ld(sb + SLOT(i), &g_o[(r * 8 + src) * 1280], 20480, BAR(BR_OFULL) + 8 * i);
          if (i == 1) TS(21);
          if (i == 7) TS(22);
        }
        __syncwarp();
      }
      if (lane == 0) { DUMP(20, 30); }
      }
    } else {
      const int hw = warp - 13, ht = tid - 416;
      if (hw == 2 && elect_one()) {
        #pragma unroll
        for (int i = 5; i < BR_COUNT; i++) mbar_init(BAR(i), i == BR_WO ? 33 : i == BR_OEMPTY ? 9 : i < BR_EMPTY ? 1 : i < BR_OEMPTY ? 2 : i < BR_Y ? 8 : i < BR_OSTG ? 4 : i == BR_OSTG ? 8 : i < BR_U2 ? 3 : 1);
        asm volatile("fence.mbarrier_init.release.cluster;" ::: "memory");
      }
      __syncwarp();
      asm volatile("bar.arrive 0, 512;" ::: "memory");
      if (EN_SSM && hw == 2) asm volatile("bar.arrive 8, 160;" ::: "memory");
      const unsigned epoch = hw == 0 ? ld_rlx(&g_epoch[cta]) + 1 : 0;
      bar_sync(5, 96);
      asm volatile("bar.arrive 6, 128;" ::: "memory");
      if (hw == 1 && elect_one()) {
        #pragma unroll
        for (int i = M_U; i < M_COUNT; i++) asm volatile("prefetch.tensormap [%0];" :: "l"(&prm.m[i]) : "memory");
      }
      if (ht == 0) {
        st_rlx(&g_epoch[cta], epoch);
        sts32(sb + OFF_EPOCH, epoch);
        mbar_arrive(BAR(BR_EPOCH));
      }
      if (EN_SSM) {
      const int mi = lane >> 3, rw = lane & 7, ch0 = c * 80 + r * 5;
      mbar_wait(BAR(BR_UIN), 0);
      if (ht == 0) TS(36);
      #pragma unroll 1
      for (int h = 0; h < 2; h++) {
        const uint32_t sa = sb + OFF_UT + h * 10240 + (8 * mi + rw) * 160 + hw * 16, da = sb + OFF_UT + h * 10240 + (hw * 8 + rw) * 128 + ((mi ^ rw ^ h) << 4);
        uint32_t v[8][4];
        #pragma unroll
        for (int q = 0; q < 8; q++) if (q < 6 || hw == 0) ldsm4t(v[q], sa + (q & 1) * 5120 + (q >> 1) * 48);
        bar_sync(5, 96);
        #pragma unroll
        for (int q = 0; q < 8; q++) if (q < 6 || hw == 0) stsm4((da ^ ((q & 1) * 64)) + (q >> 1) * 3072, v[q][0], v[q][1], v[q][2], v[q][3]);
      }
      fence_async();
      bar_sync(5, 96);
      if (hw == 0) {
        if (elect_one()) {
          tma2d_st(&prm.m[M_SA], sb + OFF_UT, r * 128, c * 80);
          tma2d_st(&prm.m[M_SA], sb + OFF_UT + 10240, r * 128 + 64, c * 80);
          bulk_commit(); bulk_wait0_read();
          mbar_arrive(BAR(BR_UOUT));
          TS(37);
          bulk_wait0();
          st_rel(FLAG(1, r, c), epoch);
          TS(30);
        }
        __syncwarp();
        poll_all_acq(FLAG(1, lane & 15, c), epoch);
      }
      #pragma unroll 1
      for (int k = 0; k < 5; k++) {
        if (k == 0 || k == 3) {
          const int p = k != 0;
          if (hw == 0) {
            if (!p) {
              if (elect_one()) {
                fence_async_g();
                mbar_expect_tx(BAR(BR_U), 12288);
                #pragma unroll 1
                for (int q = 0; q < 3; q++) bulk_ld(sb + OFF_BLK + q * q * BLK, g_uy + (ch0 + q * q) * 2048, 4096, BAR(BR_U));
                TS(31);
              }
              __syncwarp();
            }
            mbar_wait(BAR(p ? BR_U2 : BR_U), 0);
          }
          bar_sync(5, 96);
        }
        const int l3 = (hw + k) % 3 * 32 + lane;
        const uint32_t blk = sb + OFF_BLK + ((0x32410 >> (4 * k)) & 7) * BLK, o = blk + B_D + l3 * 16;
        float P[34];
        P[0] = 0.f;
        #pragma unroll
        for (int q = 0; q < 5; q++) {
          const int ch = 2 * l3 - 3 + q;
          uint32_t v[4];
          lds128(v, blk + (uint32_t)((ch * 16) ^ ((ch * 2) & 0x10)));
          #pragma unroll
          for (int e = 0; e < 8; e++) {
            const int i = 8 * q + e - 4;
            if (i >= 0 && i < 33) P[i + 1] = P[i] + ((e & 1) ? bf_hi(v[e >> 1]) : bf_lo(v[e >> 1]));
          }
        }
#define WIN(lo, hi, e) (P[21 + (e) - (lo)] - P[20 + (e) - (hi)])
#define WIN8(lo, hi, b) pack2(WIN(lo, hi, b), WIN(lo, hi, b + 1)), pack2(WIN(lo, hi, b + 2), WIN(lo, hi, b + 3)), pack2(WIN(lo, hi, b + 4), WIN(lo, hi, b + 5)), pack2(WIN(lo, hi, b + 6), WIN(lo, hi, b + 7))
        if (l3 < 64) {
          sts128(o + B_D9, WIN8(12, 20, 0)); sts128(o + B_D9 + 1024, WIN8(12, 20, 8));
          sts128(o + B_D7, WIN8(5, 11, 0)); sts128(o + B_D7 + 1024, WIN8(5, 11, 8));
        }
        sts128(o + B_D5, WIN8(6, 10, 0)); sts128(o + B_D5 + 1552, WIN8(6, 10, 8));
        sts128(o, WIN8(3, 5, 0)); sts128(o + 1552, WIN8(3, 5, 8));
        if (l3 < 2) sts128(blk + B_D + l3 * B_D5 + 1536, 0, 0, 0, 0);
      }
      __syncwarp();
      if (lane == 0) mbar_arrive(BAR(BR_DRDY + 1));
      if (ht == 0) TS(32);
      if (hw == 0) {
        #pragma unroll 1
        for (int p = 0; p < 2; p++) {
          mbar_wait(BAR(BR_Y) + 8 * p, 0);
          if (elect_one()) {
            #pragma unroll 1
            for (int k = 4 * p; k < 4 + p; k++) bulk_st(g_uy + (640 + ch0 + k) * 2048, sb + OFF_BLK + k * BLK, 4096);
            bulk_commit(); bulk_wait0_read();
            mbar_arrive(BAR(BR_FREE) + 8 * p);
          }
          __syncwarp();
        }
        if (elect_one()) { bulk_wait0(); st_rlx(FLAG(2, r, c), epoch); TS(33); }
        __syncwarp();
        poll_all(FLAG(2, lane & 15, c), epoch);
        if (EN_ATT) mbar_wait(BAR(BR_OEMPTY), 0);
        #pragma unroll 1
        for (int n = 0; n < 64; n++) {
          if (elect_one()) {
            mbar_expect_tx(BAR(BR_YIN), 20480);
            tma2d(sb + OFF_EXTRA, &prm.m[M_SA], BAR(BR_YIN), r * 128, 640 + c * 80);
            tma2d(sb + OFF_EXTRA + 10240, &prm.m[M_SA], BAR(BR_YIN), r * 128 + 64, 640 + c * 80);
            TS(34);
          }
          __syncwarp();
          if (EN_ATT) mbar_wait(BAR(BR_OEMPTY + 3), 0);
          mbar_wait(BAR(BR_YIN), n & 1);
          if (lane == 0) TS(38);
          if (!y_transpose(sb, 4, lane, (epoch & 1u) * 0x10001u)) break;
          FIXCNT
        }
      if (elect_one()) {
        TS(39);
        tma2d_st(&prm.m[M_OUT], sb + SLOT(3), c * 80, r * 128);
        bulk_commit(); bulk_wait0_read();
        TS(35); DUMP(30, 40); DUMP(0, 1);
      }
      }
      }
    }
  } else {
  if (wg < 2) {
    asm volatile("setmaxnreg.inc.sync.aligned.u32 160;");
    bar_sync(0, 512);
    if (EN_ATT) {
    float am[96], ar[24];
    {
      const bool lead = (rtid() & 127) == 0;
      constexpr uint64_t dr0 = mkdesc(SB0 + 12288, 1024, 256, 3);
      const uint64_t db0 = sw64 ? mkdesc(SB0, 2048, 512, 2) : mkdesc(SB0, 4096, 1024, 1);
      const uint32_t kst = sw64 ? 64 : 128, bh = db0 >> 32;
      uint32_t s = 0, ph = 0, xo = 0;
      const int ln = rtid() & 31;
      const uint32_t xa = sb + OFF_X + (warp * 16 + (ln & 15)) * 128 + (((ln >> 4) ^ (ln & 7)) << 4);
      uint32_t A[8];
      mbar_wait(BAR(BR_FULL), 0);
      if (lead && wg == 0) TS(1);
      ldsm4(A, xa); ldsm4(A + 4, xa ^ 32);
      wg_fence();
      wg_rs48_tb(ar, A, dr0, 0); wg_rs192_tb(am, A, db0, 0);
      wg_commit();
      #pragma unroll 1
      for (int kb = 1; kb < 20; kb++) {
        const uint32_t wp = s * (W_SLOT >> 4), eb = BAR(BR_EMPTY) + 8 * s;
        wg_fence();
        wg_rs48_tb(ar, A + 4, desc2((uint32_t)dr0 + wp + 32, dr0 >> 32), 1);
        wg_rs192_tb(am, A + 4, desc2((uint32_t)db0 + wp + kst, bh), 1);
        wg_commit();
        if (++s == 5) { s = 0; ph ^= 1; }
        if (!(kb & 1)) { xo += 16384; if (xo == 49152) xo = 0; }
        mbar_wait(BAR(BR_FULL) + 8 * s, ph);
        const uint32_t xk = (xa + xo) ^ ((kb & 1) * 64), wn = s * (W_SLOT >> 4);
        wg_wait<1>();
        ldsm4(A, xk);
        wg_fence();
        wg_rs48_tb(ar, A, desc2((uint32_t)dr0 + wn, dr0 >> 32), 1);
        wg_rs192_tb(am, A, desc2((uint32_t)db0 + wn, bh), 1);
        wg_commit();
        wg_wait<1>();
        ldsm4(A + 4, xk ^ 32);
        if (lead && kb < 16) mbar_arrive(eb);
      }
      wg_fence();
      wg_rs48_tb(ar, A + 4, dr0 + 4 * (W_SLOT >> 4) + 32, 1);
      wg_rs192_tb(am, A + 4, desc2((uint32_t)db0 + 4 * (W_SLOT >> 4) + kst, bh), 1);
      wg_commit();
      wg_wait<0>();
      pin<96>(am); pin<24>(ar);
    }
    const int tid = rtid(), lane = tid & 31, tq = lane & 3;
    if (tid == 0) TS(2);
#define QV(j, e) ((j) < 8 ? am[4 * (j) + (e)] : ar[4 * ((j) - 8) + (e)])
#define KV_(j, e) ((j) < 8 ? am[32 + 4 * (j) + (e)] : ar[8 + 4 * ((j) - 8) + (e)])
#define VV(j, e) ((j) < 8 ? am[64 + 4 * (j) + (e)] : ar[16 + 4 * ((j) - 8) + (e)])
    {
      bar_sync(1, 256);
      if (tid == 0) mbar_arrive(BAR(BR_GEMM));
      const uint32_t ro = sb + (uint32_t)((warp * 16 + (lane & 15)) * 16);
      const int l0 = 2 * (c & 1) + (lane >> 4);
      const uint32_t ones = (tq == 0) ? 0x00003f80u : 0u;
#define PV(j) pack2(VV(j, 0), VV(j, 1)), pack2(VV(j, 2), VV(j, 3))
#define PK(j) pack2(phi(KV_(j, 0)), phi(KV_(j, 1))), pack2(phi(KV_(j, 2)), phi(KV_(j, 3)))
      stsm4(ro + OFF_V + (5 + 6 * (lane >> 4)) * 2048, ones, ones, ones, ones);
      #pragma unroll
      for (int j = 0; j < 10; j += 2) {
        const int l = (j == 8 && (c & 1)) ? l0 - 2 : l0 + j;
        stsm4(ro + OFF_V + (l + (l >= 5)) * 2048, PV(j), PV(j + 1));
        stsm4(ro + OFF_PK + l * 2048, PK(j), PK(j + 1));
      }
    }
    fence_async();
    bar_sync(1, 256);
    if (tid == 0) TS(3);
    mbar_wait(BAR(BR_EPOCH), 0);
    const unsigned epoch = lds32(sb + OFF_EPOCH);
    {
      float kv[24]; zero<24>(kv);
      constexpr uint64_t da = mkdesc(SB0 + OFF_PK, 128, 2048, 0), db = mkdesc(SB0 + OFF_V, 128, 2048, 0);
      wg_fence();
      #pragma unroll
      for (int s = 0; s < 8; s++) wg_ss48_tt(kv, desc2((uint32_t)da + wg * 640 + s * 16, da >> 32), desc2((uint32_t)db + wg * 768 + s * 16, db >> 32), s != 0);
      wg_commit();
      wg_wait<0>();
      pin<24>(kv);
      if (tid == 0) TS(15);
      if (w4 < 3) {
        const uint32_t wb = sb + OFF_KVS + (wg * 3 + w4) * 1536 + (lane & 15) * 96;
        #pragma unroll
        for (int j = 0; j < 6; j += 2)
          stsm4(wb + (j + (lane >> 4)) * 16, pack2(kv[4 * j], kv[4 * j + 1]), pack2(kv[4 * j + 2], kv[4 * j + 3]),
                pack2(kv[4 * j + 4], kv[4 * j + 5]), pack2(kv[4 * j + 6], kv[4 * j + 7]));
        __syncwarp();
        const int dl = w4 * 16 + (lane & 15), hl = dl >= 20;
        uint32_t v[4], z[4];
        lds128(v, wb + (3 * hl + (lane >> 4)) * 16);
        lds64(z, wb + 32 + 8 * hl); z[2] = lds32(wb + 80); z[3] = epoch & 1u;
        if (dl < 40) {
          uint4* dst = &g_kvp[(c * 16 + r) * 240 + wg * 40 + dl];
          v[3] = (v[3] & ~1u) | z[3];
          st128_rlx(dst + (lane >> 4) * 80, v);
          if (lane < 16) st128_rlx(dst + 160, z);
        }
      }
    }
    bar_sync(1, 256);
    if (tid == 0) { st_rlx(FLAG(0, r, c), epoch); mbar_arrive(BAR(BR_PUB)); TS(4); }
    const int kvi = (tid >= 80) + (tid >= 160) + (tid >= 240), kd = tid - 80 * kvi;
    const int khd = kd / 20, kt0 = 5 * (khd >> 1) + 2 * (khd & 1);
    const uint32_t rb = sb + OFF_KVB + kd * 16;
    if (kvi < 3) {
      #pragma unroll 1
      for (int m = kvi; m < 7; m += 3) { const int q = kt0 + 3 + m; sts128(rb + (q >= 10 ? q - 10 : q) * 1280, 0, 0, 0, 0); }
    }
    uint32_t qa[20];
    {
      const float sc = 1.44269504089f + __uint_as_float(lds32(sb + OFF_EPOCH) ^ epoch);
      #pragma unroll
      for (int j = 0; j < 10; j++) { qa[2 * j] = pack2(phi(QV(j, 0), sc), phi(QV(j, 1), sc)); qa[2 * j + 1] = pack2(phi(QV(j, 2), sc), phi(QV(j, 3), sc)); }
    }
    if (tid == 0) TS(5);
    if (warp == 7) mbar_wait(BAR(BR_KVP), 0);
    bar_sync(1, 256);
    if (tid == 0) TS(6);
    if (kvi < 3) {
      float s[8];
      zero<8>(s);
      uint32_t bad = 0;
      #pragma unroll 4
      for (int i = 0; i < 16; i += 2) {
        uint32_t w[4], x[4];
        lds128(w, sb + OFF_KVP + tid * 16 + i * 3840); lds128(x, sb + OFF_KVP + tid * 16 + i * 3840 + 3840);
        bad |= (w[3] ^ epoch) | (x[3] ^ epoch);
        #pragma unroll
        for (int e = 0; e < 4; e++) {
          asm("add.rn.bf16x2 %0, %0, %1;" : "+r"(w[e]) : "r"(x[e]));
          s[2 * e] += bf_lo(w[e]); s[2 * e + 1] += bf_hi(w[e]);
        }
      }
      if (__builtin_expect(bad & 1u, 0)) {
        zero<8>(s);
        #pragma unroll 1
        for (int i = 0; i < 16; i++) {
          uint32_t w[4] = {0, 0, 0, ~epoch};
          fix128_w3(w, &g_kvp[(c * 16 + i) * 240 + tid], epoch, 1u);
          #pragma unroll
          for (int e = 0; e < 4; e++) { s[2 * e] += bf_lo(w[e]); s[2 * e + 1] += bf_hi(w[e]); }
        }
        FIXCNT
      }
      const uint32_t p0 = pack2(s[0], s[1]), p1 = pack2(s[2], s[3]), p2 = pack2(s[4], s[5]), p3 = pack2(s[6], s[7]);
      if (kvi < 2) sts128(rb + (kt0 + (khd & 1) + kvi) * 1280, p0, p1, p2, p3);
      else {
        const bool od = khd & 1;
        sts128(rb + (5 * (khd >> 1) + 2) * 1280, od ? 0u : p0, od ? 0u : p1, od ? p0 : 0u, od ? p1 : 0u);
        const uint32_t zz = (p2 & 0xffffu) << (16 * (khd & 1));
        sts128(rb + 10 * 1280, khd < 2 ? zz : 0u, khd < 2 ? 0u : zz, 0u, 0u);
      }
    }
    fence_async();
    bar_sync(1, 256);
    if (tid == 0) { mbar_arrive(BAR(BR_SUM)); TS(7); }
    {
      float oa[44]; zero<44>(oa);
      constexpr uint64_t db = mkdesc(SB0 + OFF_KVB, 128, 1280, 0);
      wg_fence();
      #pragma unroll
      for (int s = 0; s < 5; s++) wg_rs88_tb(oa, &qa[4 * s], desc2((uint32_t)db + ((s == 4 && (c & 1)) ? 0 : (s + (c & 1)) * 16), db >> 32), s != 0);
      wg_commit();
      wg_wait<0>();
      pin<44>(oa);
      if (tid == 0) TS(13);
      float rc[4], rd[2][4];
      #pragma unroll
      for (int e = 0; e < 4; e++) asm("rcp.approx.ftz.f32 %0, %1;" : "=f"(rc[e]) : "f"(oa[40 + e] + 1e-6f));
      #pragma unroll
      for (int h = 0; h < 4; h++) {
        rd[0][h] = __shfl_sync(0xffffffff, rc[h & 1], (lane & 28) | (h >> 1));
        rd[1][h] = __shfl_sync(0xffffffff, rc[2 + (h & 1)], (lane & 28) | (h >> 1));
      }
      #pragma unroll
      for (int j = 0; j < 10; j++) {
        #pragma unroll
        for (int h = 0; h < 2; h++) {
          float f;
          if (j == 2) f = tq < 2 ? rd[h][0] : rd[h][1];
          else if (j == 7) f = tq < 2 ? rd[h][2] : rd[h][3];
          else f = rd[h][(8 * j) / 20];
          qa[2 * j + h] = pack2(oa[4 * j + 2 * h] * f, oa[4 * j + 2 * h + 1] * f);
        }
      }
      const uint32_t m0 = (lane & 7) == ((2 * w4) & 7), m1 = (lane & 7) == 2 * w4 + 1;
      const uint32_t oa_ = sb + OFF_EXTRA + (lane >> 4) * 2048 + (warp * 16 + (lane & 15)) * 16;
      bar_sync(1, 256);
#define TAG(v, m) (((v) & ~(m)) | (epoch & (m)))
      #pragma unroll
      for (int s = 0; s < 5; s++) stsm4(oa_ + s * 4096, TAG(qa[4 * s], m0), TAG(qa[4 * s + 1], m1), TAG(qa[4 * s + 2], m0), TAG(qa[4 * s + 3], m1));
    }
    fence_async();
    __syncwarp();
    if (lane == 0) mbar_arrive(BAR(BR_OSTG));
    if (tid == 0) TS(8);
    }
    asm volatile("setmaxnreg.dec.sync.aligned.u32 136;");
  } else {
    const int g = lane >> 2, tq = lane & 3, t7 = tid & 127;
    uint32_t raw[5][4], pd;
    {
      const int ch = c * 80 + r * 5;
      #pragma unroll
      for (int e = 0; e < 4; e++) {
        const __nv_bfloat16* pp = prm.par[e] + ch * 128 + t7;
        #pragma unroll
        for (int q = 0; q < 5; q++) asm volatile("ld.global.nc.u16 %0, [%1];" : "=r"(raw[q][e]) : "l"(pp + q * 128));
      }
      asm volatile("ld.global.nc.u16 %0, [%1];" : "=r"(pd) : "l"(((lane & 8) ? prm.dskip : prm.logdt) + ch + min(lane & 7, 4)));
    }
    asm volatile("bar.arrive 0, 512;" ::: "memory");
    if (EN_SSM) {
    {
      #pragma unroll 1
      for (int k = 0; k < 4; k++) {
        const uint32_t z = sb + OFF_BLK + k * BLK + t7 * 16;
        sts128(z + B_TBL, 0, 0, 0, 0); sts128(z + B_TBL + 2048, 0, 0, 0, 0);
      }
      if (t7 < 80) sts128(sb + OFF_BLK + (t7 >> 4) * BLK - 256 + (t7 & 15) * 16, 0, 0, 0, 0);
      const uint32_t ea = sb + OFF_BLK + (2 + (w4 & 1)) * BLK + (lane >> 4) * 7168 + ((lane >> 3) & 1) * 256 + (lane & 7) * 16 + (w4 >> 1) * 2048;
      constexpr uint64_t dE = mkdesc(SB0 + OFF_BLK + 2 * BLK, 128, 512, 0);
      const uint32_t xa = sb + OFF_BLK + 18560 + t7 * 8, xr_ = sb + OFF_BLK + 18560 + (t7 ^ 64) * 8;
      uint32_t pr[5][2];
      #pragma unroll
      for (int q = 0; q < 5; q++) {
        #pragma unroll
        for (int e = 0; e < 2; e++) pr[q][e] = raw[q][2 * e] | (raw[q][2 * e + 1] << 16);
        const uint32_t m = __reduce_max_sync(0xffffffff, max(raw[q][2] & 0x7fffu, raw[q][3] & 0x7fffu));
        if (lane == 0) sts32(sb + OFF_EPOCH + 64 + q * 16 + w4 * 4, m);
      }
      bar_sync(4, 128);
      if (t7 == 0) TS(40);
      const int j = (w4 & 1) * 16 + (w4 >> 1) * 8 + g, i2 = tq < 2 ? 64 * tq + j : 32 * (tq - 2) + j;
      const uint32_t e2 = B_TBL + 4 * (tq < 2 ? T_F3 + (((i2 - 1) & 1) ? 80 : 0) + ((i2 - 1) >> 1) + 16 : T_F2 + (i2 & 1) * 96 + (i2 >> 1));
      const uint32_t e1 = tq < 2 ? (i2 ? e2 - 64 : B_TBL + 4 * (T_F2 + 175)) : B_TBL + 4 * (i2 ? T_F2 + ((2 * i2 - 1) & 3) * 48 + ((2 * i2 - 1) >> 2) : 16 + 511);
      const uint32_t e0 = B_TBL + (16 + 8 * j + 2 * tq) * 4;
      const float dtl = bf_round(expf(bf_lo(pd)));
      float hd[9];
      auto head = [&](int q) {
        const uint32_t pa0 = pr[0][0], pc0 = pr[0][1];
        const float dt = __shfl_sync(0xffffffff, dtl, q);
        #pragma unroll
        for (int e = 0; e < 2; e++) { pr[0][e] = pr[1][e]; pr[1][e] = pr[2][e]; pr[2][e] = pr[3][e]; pr[3][e] = pr[4][e]; }
        uint32_t mm[4];
        lds128(mm, sb + OFF_EPOCH + 64 + q * 16);
        const uint32_t ex = min(max(max(max(mm[0], mm[1]), max(mm[2], mm[3])) >> 7, 1u), 253u);
        const float sc = __uint_as_float((254u - ex) << 23);
        const float lr = -bf_round(expf(bf_lo(pa0))) * dt * 1.44269504089f;
        const float tn = bf_hi(pa0) * dt * 0.15915494309f;
        cexp_t(lr, -tn, hd[0], hd[1]);
        cexp_t(lr * 8.f, tn * 8.f, hd[2], hd[3]);
        cexp_t(lr * 64.f, tn * 64.f, hd[4], hd[5]);
        hd[6] = bf_lo(pc0) * sc; hd[7] = -bf_hi(pc0) * sc;
        hd[8] = 2.f * dt * __uint_as_float(ex << 23);
      };
      head(0);
      #pragma unroll 1
      for (int it = 0; it < 5; it++) {
        const int k = it;
        const uint32_t blk = sb + OFF_BLK + k * BLK;
        float fac = 0.f;
        float ka[24]; zero<24>(ka);
        {
          if (it == 4) {
            mbar_wait(BAR(BR_UOUT), 0);
            sts128(sb + OFF_UT + B_TBL + t7 * 16, 0, 0, 0, 0); sts128(sb + OFF_UT + B_TBL + 2048 + t7 * 16, 0, 0, 0, 0);
          }
          const uint32_t ga = ea + 4096 - (w4 >> 1) * 512;
#define PUT4(i, a, b, c_, d) sts128(((i) < 8 ? ea + ((i) >> 1) * 512 : ga + (((i) - 8) >> 1) * 512) + ((i) & 1) * 128, a, b, c_, d)
          float z2r, z2i, z4r, z4i, xr[8], xi[8], gr[8], gi[8], wr[9], wi[9];
          const float z1r = hd[0], z1i = hd[1];
          xr[1] = hd[2]; xi[1] = hd[3]; wr[0] = hd[4]; wi[0] = hd[5];
          fac = hd[8];
          xr[0] = 1.f; xi[0] = 0.f;
          cmul(xr[1], xi[1], xr[1], xi[1], xr[2], xi[2]); cmul(xr[2], xi[2], xr[1], xi[1], xr[3], xi[3]);
          cmul(xr[2], xi[2], xr[2], xi[2], xr[4], xi[4]);
          #pragma unroll
          for (int b = 1; b < 4; b++) cmul(xr[4], xi[4], xr[b], xi[b], xr[4 + b], xi[4 + b]);
          cmul(wr[0], wi[0], wr[0], wi[0], wr[1], wi[1]); cmul(wr[1], wi[1], wr[0], wi[0], wr[2], wi[2]);
          cmul(wr[1], wi[1], wr[1], wi[1], wr[3], wi[3]); cmul(wr[3], wi[3], wr[3], wi[3], wr[4], wi[4]);
          cmul(wr[4], wi[4], wr[3], wi[3], wr[5], wi[5]); cmul(wr[4], wi[4], wr[4], wi[4], wr[6], wi[6]);
          cmul(wr[6], wi[6], wr[4], wi[4], wr[7], wi[7]); cmul(wr[6], wi[6], wr[6], wi[6], wr[8], wi[8]);
          uint32_t R[4], I[4], PR[4], PI[4];
          #pragma unroll
          for (int b = 0; b < 4; b++) { R[b] = packh(xr[2 * b], xr[2 * b + 1]); I[b] = packh(xi[2 * b], xi[2 * b + 1]); }
          PUT4(0, R[0], R[1], R[2], R[3]); PUT4(1, I[0], I[1], I[2], I[3]);
          #pragma unroll
          for (int i = 0; i < 3; i++) {
            const uint32_t z = packh(wr[i], wi[i]);
            #pragma unroll
            for (int b = 0; b < 4; b++) hcm2(R[b], I[b], z, PR[b], PI[b]);
            PUT4(2 * i + 2, PR[0], PR[1], PR[2], PR[3]); PUT4(2 * i + 3, PI[0], PI[1], PI[2], PI[3]);
          }
          gr[0] = hd[6]; gi[0] = hd[7];
          cmul(z1r, z1i, z1r, z1i, z2r, z2i); cmul(z2r, z2i, z2r, z2i, z4r, z4i);
          cmul(gr[0], gi[0], z1r, z1i, gr[1], gi[1]);
          cmul(gr[0], gi[0], z2r, z2i, gr[2], gi[2]); cmul(gr[1], gi[1], z2r, z2i, gr[3], gi[3]);
          #pragma unroll
          for (int b = 0; b < 4; b++) cmul(gr[b], gi[b], z4r, z4i, gr[4 + b], gi[4 + b]);
          PUT4(8, packh(gr[0], gr[1]), packh(gr[2], gr[3]), packh(gr[4], gr[5]), packh(gr[6], gr[7]));
          PUT4(9, packh(gi[0], gi[1]), packh(gi[2], gi[3]), packh(gi[4], gi[5]), packh(gi[6], gi[7]));
          {
            const uint32_t z = packh(wr[3], -wi[3]), a4r = packh(gr[0], gr[4]), a4i = packh(gi[0], gi[4]);
            hcm2(packh(gr[0], gr[2]), packh(gi[0], gi[2]), z, PR[0], PI[0]);
            hcm2(packh(gr[4], gr[6]), packh(gi[4], gi[6]), z, PR[1], PI[1]);
            hcm2(a4r, a4i, packh(wr[4], -wi[4]), PR[2], PI[2]);
            hcm2(a4r, a4i, packh(wr[5], -wi[5]), PR[3], PI[3]);
            PUT4(10, PR[0], PR[1], PR[2], PR[3]); PUT4(11, PI[0], PI[1], PI[2], PI[3]);
            float hr, hi_;
            cmul(gr[0], gi[0], wr[3], -wi[3], hr, hi_);
            const uint32_t cr = packh(gr[0], hr), ci = packh(gi[0], hi_);
            #pragma unroll
            for (int i = 0; i < 3; i++) hcm2(cr, ci, packh(wr[6 + i], -wi[6 + i]), PR[i], PI[i]);
            PUT4(12, PR[0], PR[1], PR[2], 0u); PUT4(13, PI[0], PI[1], PI[2], 0u);
          }
          fence_async();
          bar_sync(4, 128);
          wg_fence();
          #pragma unroll
          for (int s = 0; s < 8; s++) {
            const uint64_t d = dE + (s >> 2) * (BLK >> 4) + ((s >> 1) & 1) * 448 + (s & 1) * 16;
            wg_ss48_tt_h(ka, d, d + 256, s != 0);
          }
          wg_commit();
        }
        const float dsk = bf_lo(__shfl_sync(0xffffffff, pd, 8 + (it & 7)));
        head(min(it + 1, 4));
        asm volatile("{\n.reg .pred p;\nHL:\nsetp.eq.f32 p, %0, 0f46400000;\n@p bra HL;\n}" :: "f"(hd[0] + hd[2] + hd[4]));
        wg_wait<0>();
        pin<24>(ka);
        float kk[6];
        const bool up = w4 >= 2;
        #pragma unroll
        for (int n = 0; n < 3; n++) {
          sts64f(xa + n * BLK, up ? ka[12 + 4 * n] : ka[4 * n + 2], up ? ka[13 + 4 * n] : ka[4 * n + 3]);
          kk[2 * n] = up ? ka[14 + 4 * n] : ka[4 * n]; kk[2 * n + 1] = up ? ka[15 + 4 * n] : ka[4 * n + 1];
        }
        if (it) bar_sync(4, 128); else bar_sync(8, 160);
          if (it == 4 && w4 == 0) {
            mbar_wait(BAR(BR_U), 0);
            if (elect_one()) {
              mbar_expect_tx(BAR(BR_U2), 8192);
              bulk_ld(blk - 2 * BLK, g_uy + (c * 80 + r * 5 + 2) * 2048, 4096, BAR(BR_U2)); bulk_ld(blk - BLK, g_uy + (c * 80 + r * 5 + 3) * 2048, 4096, BAR(BR_U2));
            }
            __syncwarp();
          }
        #pragma unroll
        for (int n = 0; n < 3; n++) {
          uint32_t o[2]; lds64(o, xr_ + n * BLK);
          kk[2 * n] = (kk[2 * n] + __uint_as_float(o[0])) * fac; kk[2 * n + 1] = (kk[2 * n + 1] + __uint_as_float(o[1])) * fac;
        }
        if (t7 == 0) kk[0] += dsk;
        {
          const uint32_t v = pack2(kk[1], kk[0]), vh = v >> 16;
          const uint32_t u = pack2(kk[2], kk[3]), w = pack2(kk[4], kk[5]), uu = pack2(kk[2], kk[2]), us = pack2(kk[3], kk[2]);
          const uint32_t x = tq < 2 ? w : u, xh = x >> 16;
          sts32(blk + e0 + 4, v); sts16(blk + e0, vh); sts16(blk + e0 + 10, v);
          sts16(blk + e1, x); sts16(blk + e1 + 6, x); sts16(blk + e2, xh); sts16(blk + e2 + 6, xh);
          if (tq < 2) {
            const uint32_t pb = blk + e0 + 1024 + 8 * tq;
            sts32(pb + 4, uu); sts32(pb + 8, us); sts16(pb + 14, us);
            if (i2) { sts16(pb - 4, u); sts32(pb, uu); }
          }
          if (i2 == 0) {
            const uint32_t tb = blk + B_TBL;
            if (tq == 0) { sts16(tb + (16 + 256) * 4, u); sts16(tb + (T_S + 3) * 4, w); sts32(tb + (T_S + 4) * 4, pack2(kk[4], kk[4])); sts16(tb + (T_S + 5) * 4 + 2, w); }
            else { sts32(tb + 528 * 4, uu); sts32(tb + 529 * 4, uu); sts32(tb + 530 * 4, uu); sts16(tb + 531 * 4 + 2, u); sts16(tb + (T_F3 + 80 + 63) * 4, w); }
          }
        }
        if (t7 == 0) TS(49 + it);
      }
    }
    asm volatile("setmaxnreg.inc.sync.aligned.u32 136;");
    if (t7 == 0) TS(41);
    bar_sync(4, 128);
    if (t7 == 0) mbar_arrive(BAR(BR_KS));
    if (EN_ATT) mbar_wait(BAR(BR_GEMM), 0);
    }
  }
  const int tid = rtid(), lane = tid & 31, g = lane >> 2, tq = lane & 3, t7 = tid & 127;
  mbar_wait(BAR(BR_EPOCH), 0);
  const unsigned epoch = lds32(sb + OFF_EPOCH);
  const uint32_t ytag = (epoch & 1u) * 0x10001u, ym = lane < 4 ? 0x10001u : 0u;
  if (EN_SSM && wg != 1) {
    mbar_wait(BAR(BR_KS), 0);
    mbar_wait(BAR(BR_U), 0);
    if (tid == 256) TS(42);
    {
      const int pass = wg >> 1;
      const int k = pass ? w4 : 4;
      if (k & 2) mbar_wait(BAR(BR_U2), 0);
      const uint32_t blk = sb + OFF_BLK + k * BLK, tb = blk + B_TBL + (uint32_t)((g - 2 * tq) * 4);
      float acc[16][4];
      zero<64>(&acc[0][0]);
      const int kl = 16 * (lane >> 4) + 2 * (lane & 7) + ((lane >> 3) & 1);
      {
        auto ubase = [&](int sh) { const int q = kl - 2 * sh; return blk + (uint32_t)((q * 16) ^ ((q * 2) & 0x10)); };
#define LDQ(A, sh) _Pragma("unroll") for (int m = 0; m < 4; m++) load_quad(A[m], tb + (16 + 16 * (sh) + 128 * m) * 4);
#define LDB(B, ub, h) _Pragma("unroll") for (int p = 0; p < 4; p++) ldsm4(B[p], (ub) + (4 * (h) + p) * 512);
#define MLO(A, B) _Pragma("unroll") for (int m = 0; m < 4; m++) _Pragma("unroll") for (int cc = 0; cc < 8; cc++) mma16816(acc[cc + m], A[m], &B[cc >> 1][(cc & 1) * 2]);
#define MHI(A, B) _Pragma("unroll") for (int m = 0; m < 4; m++) _Pragma("unroll") for (int cc = 0; cc < 8 - m; cc++) mma16816(acc[8 + cc + m], A[m], &B[cc >> 1][(cc & 1) * 2]);
        int p_ = pass ? 0 : w4;
        const int pe = pass ? 4 : w4 + 1;
        uint32_t A[4][4], A2[4][4], Bl[4][4], Bh[4][4];
        uint32_t ub = ubase(p_ + 4);
        LDQ(A, p_ + 4) LDB(Bl, ub, 0)
        #pragma unroll 1
        for (; p_ < pe; p_++) {
          LDB(Bh, ub, 1)
          MLO(A, Bl)
          ub = ubase(p_);
          LDQ(A2, p_) LDB(Bl, ub, 0)
          MHI(A, Bh)
          LDB(Bh, ub, 1)
          load_quad(A[0], tb + (16 + 512 + 16 * (p_ & 1)) * 4); load_quad(A[1], tb + (T_S + 16 * (p_ & 1)) * 4);
          MLO(A2, Bl)
          if (p_ < 2) {
            #pragma unroll
            for (int cc = 0; cc < 8; cc++) mma16816(acc[cc + 4], A[0], &Bl[cc >> 1][(cc & 1) * 2]);
            #pragma unroll
            for (int cc = 0; cc < 4; cc++) mma16816(acc[cc + 12], A[0], &Bh[cc >> 1][(cc & 1) * 2]);
            #pragma unroll
            for (int cc = 0; cc < 8; cc++) mma16816(acc[cc + 8], A[1], &Bl[cc >> 1][(cc & 1) * 2]);
          }
          const int pn = ((p_ + 1) & 3) + 4;
          ub = ubase(pn);
          LDQ(A, pn) LDB(Bl, ub, 0)
          MHI(A2, Bh)
        }
      }
      if (t7 == 0) TS(pass ? 60 : 16);
      mbar_wait(BAR(BR_DRDY + 1), 0);
      {
        const int ih = (lane >> 3) & 1;
        const uint32_t dl = blk + B_D + (uint32_t)(((lane >> 4) * 8 + (lane & 7)) * 16);
        const uint32_t d0_ = dl + ih * 1552, d8_ = dl + (ih ? 0 : 1536), d3_ = dl + B_D7 + ih * 1024;
        auto cls2 = [&](uint32_t da, uint32_t ta) {
          uint32_t B[6][2], A[6][4];
          #pragma unroll
          for (int e = 0; e < 6; e++) { B[e][0] = lds32v(ta + (e + 4) * 32); B[e][1] = lds32v(ta + (e + 3) * 32); }
          #pragma unroll
          for (int kk = 0; kk < 6; kk++) ldsm4t(A[kk], da + kk * 256);
          #pragma unroll
          for (int e = 0; e < 6; e++)
            #pragma unroll
            for (int kk = 0; kk < 6; kk++) if (2 * kk + e + 4 < 16) mma16816(acc[2 * kk + e + 4], A[kk], B[e]);
        };
        auto cls3 = [&](uint32_t da, uint32_t ta) {
          uint32_t B[8][2], A[4][4];
          #pragma unroll
          for (int e = 0; e < 8; e++) { B[e][0] = lds32v(ta + (e + 8) * 32); B[e][1] = lds32v(ta + (e + 7) * 32); }
          #pragma unroll
          for (int kk = 0; kk < 4; kk++) ldsm4t(A[kk], da + kk * 256);
          #pragma unroll
          for (int kk = 0; kk < 4; kk++)
            #pragma unroll
            for (int e = 0; e < 8; e++) if (2 * kk + e + 8 < 16) mma16816(acc[2 * kk + e + 8], A[kk], B[e]);
        };
        if (pass) {
          #pragma unroll 1
          for (int a = 0; a < 2; a++) {
            cls2(d0_ + a * B_D5, tb + (T_F2 + 48 * a - 32) * 4);
            cls2(d8_ + a * B_D5, tb + (T_F2 + 48 * a + 64) * 4);
            cls3(d3_ + a * 2048, tb + (T_F3 + 80 * a - 64) * 4);
          }
        } else {
          cls2(((w4 & 2) ? d8_ : d0_) + (w4 & 1) * B_D5, tb + (T_F2 + 48 * w4 - 32) * 4);
          if (w4 >= 2) cls3(d3_ + (w4 - 2) * 2048, tb + (T_F3 + 80 * (w4 - 2) - 64) * 4);
        }
      }
      if (t7 == 0) TS(pass ? 61 : 17);
      const uint32_t ya = blk + (uint32_t)((kl * 16) ^ ((kl * 2) & 0x10));
#define YTAG(v) (((v) & ~ym) | (ytag & ym))
#define STY(p) stsm4t(ya + (p) * 512, YTAG(pack2(acc[2 * (p)][0], acc[2 * (p)][1])), pack2(acc[2 * (p)][2], acc[2 * (p)][3]), \
                      YTAG(pack2(acc[2 * (p) + 1][0], acc[2 * (p) + 1][1])), pack2(acc[2 * (p) + 1][2], acc[2 * (p) + 1][3]))
      if (pass == 0) {
        const uint32_t xw = blk + 4096 + w4 * 4096 + lane * 16, xr = blk + 4096 + w4 * 1024 + lane * 16;
        #pragma unroll
        for (int h = 0; h < 2; h++) {
          bar_sync(2, 128);
          #pragma unroll
          for (int i = 0; i < 8; i++)
            sts128(xw + i * 512, __float_as_uint(acc[8 * h + i][0]), __float_as_uint(acc[8 * h + i][1]), __float_as_uint(acc[8 * h + i][2]), __float_as_uint(acc[8 * h + i][3]));
          bar_sync(2, 128);
          float y[8];
          #pragma unroll
          for (int i = 0; i < 8; i++) {
            uint32_t o[4]; lds128(o, xr + (i >> 1) * 4096 + (i & 1) * 512);
            #pragma unroll
            for (int e = 0; e < 4; e++) y[4 * (i & 1) + e] = i < 2 ? __uint_as_float(o[e]) : y[4 * (i & 1) + e] + __uint_as_float(o[e]);
          }
          stsm4t(ya + (4 * h + w4) * 512, YTAG(pack2(y[0], y[1])), pack2(y[2], y[3]), YTAG(pack2(y[4], y[5])), pack2(y[6], y[7]));
        }
      } else {
        __syncwarp();
        #pragma unroll
        for (int p = 0; p < 8; p++) STY(p);
      }
      fence_async();
      __syncwarp();
      if (lane == 0) mbar_arrive(BAR(BR_Y + 1) - 8 * pass);
      if (t7 == 0) TS(pass ? 62 : 18);
    }
  }
  if (wg < 2) {
    if (EN_ATT) {
    float oc[40]; zero<40>(oc);
    {
      constexpr uint64_t dw0 = mkdesc(SB0, OFF_WOR, 1024, 1), da0 = mkdesc(SB0, 2048, 128, 0);
      const uint32_t ck = sb + tid * 32 + ((lane >> 2) << 2), ck2 = ck + (wg ? 0 : 16384);
      uint32_t bad = 0;
      auto tile = [&](int i, uint32_t so) {
        const uint32_t al = (uint32_t)da0 + wg * 64 + (so >> 4), wl = (uint32_t)dw0 + i * 640 - (i >> 1) * (1278 << 16);
        wg_fence();
        #pragma unroll
        for (int s = 0; s < 5; s++) wg_ss80_tb(oc, desc2(al + s * 256, da0 >> 32), desc2(wl + s * 128, dw0 >> 32), (i | s) != 0);
        wg_commit();
        bad |= (lds32(ck + so) ^ epoch) | (lds32(ck + so + 8192) ^ epoch) | (lds32(ck2 + so) ^ epoch);
      };
      if (w4 == 0) {
        if (EN_SSM) mbar_wait(BAR(BR_Y), 0);
        mbar_wait(BAR(BR_WO), 0);
        mbar_wait(BAR(BR_WO + 1), 0);
      }
      bar_sync(1, 256);
      if (tid == 0) TS(9);
      tile(0, SLOT(0));
      #pragma unroll 1
      for (int i = 1; i < 8; i++) {
        mbar_wait(BAR(BR_OFULL) + 8 * i, 0);
        tile(i, SLOT(i));
        wg_wait<1>();
        if (lane == 0) mbar_arrive(BAR(BR_OEMPTY - 1) + 8 * i);
      }
      #pragma unroll 1
      for (int n = 0; n < 56; n++) {
        const int i = n & 7;
        if (i == 0) {
          uint32_t any;
          asm volatile("{\n.reg .pred p;\nsetp.ne.u32 p, %1, 0;\nbarrier.red.or.pred p, 1, 256, p;\nselp.u32 %0, 1, 0, p;\n}" : "=r"(any) : "r"(bad & 1u) : "memory");
          if (!any) break;
          bad = 0;
          FIXCNT
        }
        wg_wait<0>();
        bar_sync(1, 256);
        if (tid == 0) { mbar_expect_tx(BAR(BR_RETRY), 20480); bulk_ld(sb + SLOT(5), &g_o[(r * 8 + CHUNK(i)) * 1280], 20480, BAR(BR_RETRY)); }
        mbar_wait(BAR(BR_RETRY), n & 1);
        tile(i, SLOT(5));
      }
      wg_wait<0>();
      pin<40>(oc);
    }
    if (tid == 0) TS(10);
    {
      const int row = w4 * 16 + (lane & 15);
      const uint32_t ob = sb + OFF_BLK + 3 * BLK + wg * 10240;
      #pragma unroll
      for (int j = 0; j < 8; j += 2)
        stsm4(ob + row * 128 + (((j + (lane >> 4)) ^ (row & 7)) << 4), pack2(oc[4 * j], oc[4 * j + 1]), pack2(oc[4 * j + 2], oc[4 * j + 3]),
              pack2(oc[4 * j + 4], oc[4 * j + 5]), pack2(oc[4 * j + 6], oc[4 * j + 7]));
      stsm4(ob + 8192 + row * 32 + (lane >> 4) * 16, pack2(oc[32], oc[33]), pack2(oc[34], oc[35]), pack2(oc[36], oc[37]), pack2(oc[38], oc[39]));
      fence_async();
      bar_sync(2 + wg, 128);
      if (w4 == 0 && elect_one()) {
        tma2d_st(&prm.m[M_O64], ob, 640 + c * 64, r * 128 + wg * 64);
        tma2d_st(&prm.m[M_O16], ob + 8192, 1152 + c * 16, r * 128 + wg * 64);
        bulk_commit(); bulk_wait0_read();
        if (wg == 0) { TS(11); DUMP(0, 20); }
      }
    }
    }
  } else if (EN_SSM) {
    if (t7 == 0) DUMP(40, 64);
    #pragma unroll 1
    for (int n = 0; n < 64; n++) if (!y_transpose(sb, w4, lane, ytag)) break;
  }
  }
}

typedef CUresult (*EncFn)(CUtensorMap*, CUtensorMapDataType, cuuint32_t, void*, const cuuint64_t*, const cuuint64_t*, const cuuint32_t*,
                          const cuuint32_t*, CUtensorMapInterleave, CUtensorMapSwizzle, CUtensorMapL2promotion, CUtensorMapFloatOOBfill);
static void mkmap(EncFn enc, CUtensorMap* m, const void* base, int rank, const cuuint64_t* dims, const cuuint64_t* strides, const cuuint32_t* box, CUtensorMapSwizzle swz) {
  cuuint32_t es[5] = {1, 1, 1, 1, 1};
  enc(m, CU_TENSOR_MAP_DATA_TYPE_BFLOAT16, rank, const_cast<void*>(base), dims, strides, box, es, CU_TENSOR_MAP_INTERLEAVE_NONE, swz,
      CU_TENSOR_MAP_L2_PROMOTION_L2_128B, CU_TENSOR_MAP_FLOAT_OOB_FILL_NONE);
}

extern "C" void kernel_launch(void* const* d_in, const int* in_sizes, int n_in, void* d_out, int out_size) {
  void* fn = nullptr; cudaDriverEntryPointQueryResult qr;
  cudaGetDriverEntryPoint("cuTensorMapEncodeTiled", &fn, cudaEnableDefault, &qr);
  EncFn enc = (EncFn)fn;
  void* uy = nullptr; cudaGetSymbolAddress(&uy, g_uy);
  const cuuint64_t dx[2] = {640, 2048}, sx[1] = {1280};
  const cuuint32_t bx[2] = {64, 128}, bu[2] = {80, 128};
  const cuuint64_t dw[3] = {640, 640, 3}, sw[2] = {3840, 1280};
  const cuuint32_t br[3] = {16, 32, 3};
  const cuuint64_t dwa[4] = {64, 640, 10, 3}, swa[3] = {3840, 128, 1280}, dwb[4] = {32, 640, 20, 3}, swb[3] = {3840, 64, 1280};
  const cuuint32_t bwa[4] = {64, 32, 1, 3}, bwb[4] = {32, 32, 2, 3};
  const cuuint64_t dwo[2] = {640, 640};
  const cuuint32_t bwo[2] = {64, 80}, bo64[2] = {64, 64}, bo16[2] = {16, 64};
  const cuuint64_t dsa[2] = {2048, 1280}, ssa[1] = {4096};
  const cuuint32_t bsa[2] = {64, 80};
  const cuuint64_t dout[2] = {1280, 2048}, sout[1] = {2560};
  Params prm;
  mkmap(enc, &prm.m[M_X], d_in[7], 2, dx, sx, bx, CU_TENSOR_MAP_SWIZZLE_128B);
  mkmap(enc, &prm.m[M_W128], d_in[8], 4, dwa, swa, bwa, CU_TENSOR_MAP_SWIZZLE_128B);
  mkmap(enc, &prm.m[M_W64], d_in[8], 4, dwb, swb, bwb, CU_TENSOR_MAP_SWIZZLE_64B);
  mkmap(enc, &prm.m[M_WR], d_in[8], 3, dw, sw, br, CU_TENSOR_MAP_SWIZZLE_32B);
  mkmap(enc, &prm.m[M_U], d_in[0], 2, dx, sx, bu, CU_TENSOR_MAP_SWIZZLE_NONE);
  mkmap(enc, &prm.m[M_WO], d_in[9], 2, dwo, sx, bwo, CU_TENSOR_MAP_SWIZZLE_128B);
  mkmap(enc, &prm.m[M_O64], d_out, 2, dout, sout, bo64, CU_TENSOR_MAP_SWIZZLE_128B);
  mkmap(enc, &prm.m[M_O16], d_out, 2, dout, sout, bo16, CU_TENSOR_MAP_SWIZZLE_NONE);
  mkmap(enc, &prm.m[M_SA], uy, 2, dsa, ssa, bsa, CU_TENSOR_MAP_SWIZZLE_128B);
  mkmap(enc, &prm.m[M_OUT], d_out, 2, dout, sout, bu, CU_TENSOR_MAP_SWIZZLE_NONE);
  prm.u = (const __nv_bfloat16*)d_in[0]; prm.wo = (const __nv_bfloat16*)d_in[9];
  for (int i = 0; i < 4; i++) prm.par[i] = (const __nv_bfloat16*)d_in[1 + i];
  prm.logdt = (const __nv_bfloat16*)d_in[5]; prm.dskip = (const __nv_bfloat16*)d_in[6];
  cudaFuncSetAttribute(fused_kernel, cudaFuncAttributeMaxDynamicSharedMemorySize, SMEM_BYTES);
  cudaLaunchConfig_t cfg = {};
  cfg.gridDim = dim3(128); cfg.blockDim = dim3(512); cfg.dynamicSmemBytes = SMEM_BYTES; cfg.stream = cudaStreamPerThread;
  cudaLaunchAttribute at[1];
  at[0].id = cudaLaunchAttributeClusterDimension; at[0].val.clusterDim.x = 2; at[0].val.clusterDim.y = 1; at[0].val.clusterDim.z = 1;
  cfg.attrs = at; cfg.numAttrs = 1;
  cudaLaunchKernelEx(&cfg, fused_kernel, prm);
}
```

```cpp
#include <cuda_runtime.h>
#include <cuda_bf16.h>
#include <cuda_fp16.h>
#include <cuda.h>
#include <stdint.h>

#define KST 2
#define UKB 4
#define UPF 0
#define CONV_AT 1
#define EN_ATT 1
#define EN_SSM 1

__device__ __align__(1024) __nv_bfloat16 g_uy[2 * 640 * 2048];
__device__ __align__(128) uint4 g_kvp[8 * 16 * 240];
__device__ __align__(128) uint4 g_o[128 * 1280];
__device__ __align__(128) unsigned g_flag[4 * 128 * 32];
__device__ unsigned g_epoch[128];
#define TS(i) do {} while (0)
#define DUMP(lo, hi) do {} while (0)
#define FIXCNT

constexpr uint32_t SB0 = 1024;
constexpr uint32_t W_SLOT = 15360, OFF_X = 76800;
constexpr uint32_t OFF_WOR = 81920, OFF_KVP = 10240, OFF_KVS = 71680, OFF_PK = 10240, OFF_V = 30720, OFF_EXTRA = 102400, OFF_KVB = OFF_EXTRA;
constexpr uint32_t OFF_BAR = 125952, OFF_BLK = 128000, BLK = 20480;
constexpr uint32_t B_D = 4096, B_D5 = 3088, B_D7 = 6176, B_D9 = 8224, B_TBL = 14400;
constexpr int T_S = 576, T_F2 = 624, T_F3 = 816;
constexpr uint32_t OFF_UT = OFF_BLK + 4 * BLK;
constexpr uint32_t SMEM_BYTES = OFF_BLK + 5 * BLK;
enum { BR_FULL = 0, BR_WO = 5, BR_PUB = 7, BR_KVP = 8, BR_U = 9, BR_SUM = 10, BR_GEMM = 11, BR_UIN = 12, BR_YIN = 13, BR_EPOCH = 14,
       BR_FREE = 15, BR_RETRY = 17, BR_UOUT = 18, BR_OFULL = 18, BR_KS = 26, BR_EMPTY = 31, BR_OEMPTY = 36, BR_Y = 43, BR_OSTG = 45,
       BR_DRDY = 46, BR_U2 = 48, BR_COUNT = 50 };
constexpr uint32_t OFF_EPOCH = OFF_BAR + 8 * BR_COUNT;
enum { M_X, M_W128, M_W64, M_WR, M_U, M_WO, M_O64, M_O16, M_SA, M_OUT, M_COUNT };

__device__ __forceinline__ long long clk64() { long long t; asm volatile("mov.u64 %0, %%clock64;" : "=l"(t) :: "memory"); return t; }
__device__ __forceinline__ uint32_t smem_u32(const void* p) { return (uint32_t)__cvta_generic_to_shared(p); }
__host__ __device__ constexpr uint64_t mkdesc(uint32_t addr, uint32_t lbo, uint32_t sbo, uint32_t swz) {
  return (uint64_t)((addr & 0x3FFFF) >> 4) | ((uint64_t)(lbo >> 4) << 16) | ((uint64_t)(sbo >> 4) << 32) | ((uint64_t)swz << 62);
}
__device__ __forceinline__ uint64_t desc2(uint32_t lo, uint32_t hi) { uint64_t d; asm("mov.b64 %0, {%1, %2};" : "=l"(d) : "r"(lo), "r"(hi)); return d; }
__device__ __forceinline__ void mbar_init(uint32_t bar, uint32_t cnt) { asm volatile("mbarrier.init.shared::cta.b64 [%0], %1;" :: "r"(bar), "r"(cnt) : "memory"); }
__device__ __forceinline__ void mbar_expect_tx(uint32_t bar, uint32_t bytes) { asm volatile("mbarrier.arrive.expect_tx.shared::cta.b64 _, [%0], %1;" :: "r"(bar), "r"(bytes) : "memory"); }
__device__ __forceinline__ void mbar_arrive(uint32_t bar) { asm volatile("mbarrier.arrive.shared::cta.b64 _, [%0];" :: "r"(bar) : "memory"); }
__device__ __forceinline__ void mbar_wait(uint32_t bar, uint32_t parity) {
  asm volatile("{\n.reg .pred p;\n.reg .u32 c;\nmov.u32 c, 0;\n"
    "WL:\nmbarrier.try_wait.parity.shared::cta.b64 p, [%0], %1;\n@p bra WD;\n"
    "add.u32 c, c, 1;\nsetp.lt.u32 p, c, 200000;\n@p bra WL;\nWD:\n}" :: "r"(bar), "r"(parity) : "memory");
}
__device__ __forceinline__ void poll_all(const unsigned* p, unsigned val) {
  asm volatile("{\n.reg .pred p;\n.reg .u32 c, v;\nmov.u32 c, 0;\n"
    "PL:\nld.relaxed.gpu.global.u32 v, [%0];\nsetp.eq.u32 p, v, %1;\nvote.sync.all.pred p, p, 0xffffffff;\n@p bra PD;\n"
    "add.u32 c, c, 1;\nsetp.lt.u32 p, c, 100000;\n@p bra PL;\nPD:\n}" :: "l"(p), "r"(val) : "memory");
}
__device__ __forceinline__ void poll_all_acq(const unsigned* p, unsigned val) {
  asm volatile("{\n.reg .pred p;\n.reg .u32 c, v;\nmov.u32 c, 0;\n"
    "PL:\nld.acquire.gpu.global.u32 v, [%0];\nsetp.eq.u32 p, v, %1;\nvote.sync.all.pred p, p, 0xffffffff;\n@p bra PD;\n"
    "nanosleep.u32 300;\nadd.u32 c, c, 1;\nsetp.lt.u32 p, c, 100000;\n@p bra PL;\nPD:\n}" :: "l"(p), "r"(val) : "memory");
}
__device__ __forceinline__ unsigned poll_bit(const unsigned* p, unsigned val, unsigned mask) {
  unsigned bal;
  asm volatile("{\n.reg .pred p;\n.reg .u32 c, v;\nmov.u32 c, 0;\n"
    "PL:\nld.relaxed.gpu.global.u32 v, [%1];\nsetp.eq.u32 p, v, %2;\nvote.sync.ballot.b32 %0, p, 0xffffffff;\n"
    "and.b32 v, %0, %3;\nsetp.ne.u32 p, v, 0;\n@p bra PD;\n"
    "add.u32 c, c, 1;\nsetp.lt.u32 p, c, 100000;\n@p bra PL;\nPD:\n}" : "=&r"(bal) : "l"(p), "r"(val), "r"(mask) : "memory");
  return bal;
}
__device__ __forceinline__ void fix128_w0(uint32_t* v, const void* p, uint32_t tag, uint32_t mask) {
  asm volatile("{\n.reg .pred p;\n.reg .u32 c, x;\n.reg .b128 t;\n.reg .b64 lo, hi;\nmov.u32 c, 0;\n"
    "FL:\nxor.b32 x, %0, %5;\nand.b32 x, x, %6;\nsetp.eq.u32 p, x, 0;\n@p bra FD;\n"
    "ld.relaxed.gpu.global.b128 t, [%4];\nmov.b128 {lo, hi}, t;\nmov.b64 {%0, %1}, lo;\nmov.b64 {%2, %3}, hi;\n"
    "add.u32 c, c, 1;\nsetp.lt.u32 p, c, 100000;\n@p bra FL;\nFD:\n}"
    : "+r"(v[0]), "+r"(v[1]), "+r"(v[2]), "+r"(v[3]) : "l"(p), "r"(tag), "r"(mask) : "memory");
}
__device__ __forceinline__ void fix128_w3(uint32_t* v, const void* p, uint32_t tag, uint32_t mask) {
  asm volatile("{\n.reg .pred p;\n.reg .u32 c, x;\n.reg .b128 t;\n.reg .b64 lo, hi;\nmov.u32 c, 0;\n"
    "FL:\nxor.b32 x, %3, %5;\nand.b32 x, x, %6;\nsetp.eq.u32 p, x, 0;\n@p bra FD;\n"
    "ld.relaxed.gpu.global.b128 t, [%4];\nmov.b128 {lo, hi}, t;\nmov.b64 {%0, %1}, lo;\nmov.b64 {%2, %3}, hi;\n"
    "add.u32 c, c, 1;\nsetp.lt.u32 p, c, 100000;\n@p bra FL;\nFD:\n}"
    : "+r"(v[0]), "+r"(v[1]), "+r"(v[2]), "+r"(v[3]) : "l"(p), "r"(tag), "r"(mask) : "memory");
}
__device__ __forceinline__ void fence_acq() { asm volatile("fence.acq_rel.gpu;" ::: "memory"); }
__device__ __forceinline__ bool elect_one() {
  uint32_t p; asm volatile("{\n.reg .pred P;\nelect.sync _|P, 0xffffffff;\nselp.u32 %0, 1, 0, P;\n}" : "=r"(p)); return p;
}
__device__ __forceinline__ void bar_sync(int id, int n) { asm volatile("bar.sync %0, %1;" :: "r"(id), "r"(n) : "memory"); }
__device__ __forceinline__ void fence_async() { asm volatile("fence.proxy.async.shared::cta;" ::: "memory"); }
__device__ __forceinline__ void fence_async_g() { asm volatile("fence.proxy.async.global;" ::: "memory"); }
__device__ __forceinline__ void tma2d(uint32_t dst, const CUtensorMap* m, uint32_t bar, int c0, int c1) {
  asm volatile("cp.async.bulk.tensor.2d.shared::cluster.global.mbarrier::complete_tx::bytes [%0], [%1, {%3, %4}], [%2];"
    :: "r"(dst), "l"(m), "r"(bar), "r"(c0), "r"(c1) : "memory");
}
__device__ __forceinline__ void tma3d(uint32_t dst, const CUtensorMap* m, uint32_t bar, int c0, int c1, int c2) {
  asm volatile("cp.async.bulk.tensor.3d.shared::cluster.global.mbarrier::complete_tx::bytes [%0], [%1, {%3, %4, %5}], [%2];"
    :: "r"(dst), "l"(m), "r"(bar), "r"(c0), "r"(c1), "r"(c2) : "memory");
}
__device__ __forceinline__ void tma4d(uint32_t dst, const CUtensorMap* m, uint32_t bar, int c0, int c1, int c2, int c3) {
  asm volatile("cp.async.bulk.tensor.4d.shared::cluster.global.mbarrier::complete_tx::bytes [%0], [%1, {%3, %4, %5, %6}], [%2];"
    :: "r"(dst), "l"(m), "r"(bar), "r"(c0), "r"(c1), "r"(c2), "r"(c3) : "memory");
}
__device__ __forceinline__ void tma2d_st(const CUtensorMap* m, uint32_t src, int c0, int c1) {
  asm volatile("cp.async.bulk.tensor.2d.global.shared::cta.bulk_group [%0, {%2, %3}], [%1];"
    :: "l"(m), "r"(src), "r"(c0), "r"(c1) : "memory");
}
__device__ __forceinline__ void bulk_ld(uint32_t dst, const void* src, uint32_t bytes, uint32_t bar) {
  asm volatile("cp.async.bulk.shared::cluster.global.mbarrier::complete_tx::bytes [%0], [%1], %2, [%3];"
    :: "r"(dst), "l"(src), "r"(bytes), "r"(bar) : "memory");
}
__device__ __forceinline__ void bulk_st(void* dst, uint32_t src, uint32_t bytes) {
  asm volatile("cp.async.bulk.global.shared::cta.bulk_group [%0], [%1], %2;" :: "l"(dst), "r"(src), "r"(bytes) : "memory");
}
__device__ __forceinline__ void bulk_commit() { asm volatile("cp.async.bulk.commit_group;" ::: "memory"); }
__device__ __forceinline__ void bulk_wait0() { asm volatile("cp.async.bulk.wait_group 0;" ::: "memory"); }
__device__ __forceinline__ void bulk_wait0_read() { asm volatile("cp.async.bulk.wait_group.read 0;" ::: "memory"); }
__device__ __forceinline__ unsigned ld_rlx(const unsigned* p) { unsigned v; asm volatile("ld.relaxed.gpu.global.u32 %0, [%1];" : "=r"(v) : "l"(p) : "memory"); return v; }
__device__ __forceinline__ unsigned ld_acq(const unsigned* p) { unsigned v; asm volatile("ld.acquire.gpu.global.u32 %0, [%1];" : "=r"(v) : "l"(p) : "memory"); return v; }
__device__ __forceinline__ void st_rlx(unsigned* p, unsigned v) { asm volatile("st.relaxed.gpu.global.u32 [%0], %1;" :: "l"(p), "r"(v) : "memory"); }
__device__ __forceinline__ void st_rel(unsigned* p, unsigned v) { asm volatile("st.release.gpu.global.u32 [%0], %1;" :: "l"(p), "r"(v) : "memory"); }
__device__ __forceinline__ void ld128_rlx(uint32_t* v, const void* p) {
  asm volatile("{\n.reg .b128 t;\n.reg .b64 lo, hi;\nld.relaxed.gpu.global.b128 t, [%4];\nmov.b128 {lo, hi}, t;\n"
    "mov.b64 {%0, %1}, lo;\nmov.b64 {%2, %3}, hi;\n}" : "=r"(v[0]), "=r"(v[1]), "=r"(v[2]), "=r"(v[3]) : "l"(p) : "memory");
}
__device__ __forceinline__ void st128_rlx(void* p, const uint32_t* v) {
  asm volatile("{\n.reg .b128 t;\n.reg .b64 lo, hi;\nmov.b64 lo, {%1, %2};\nmov.b64 hi, {%3, %4};\nmov.b128 t, {lo, hi};\n"
    "st.relaxed.gpu.global.b128 [%0], t;\n}" :: "l"(p), "r"(v[0]), "r"(v[1]), "r"(v[2]), "r"(v[3]) : "memory");
}
__device__ __forceinline__ uint32_t lds32(uint32_t a) { uint32_t v; asm volatile("ld.shared.u32 %0, [%1];" : "=r"(v) : "r"(a) : "memory"); return v; }
__device__ __forceinline__ uint32_t lds32v(uint32_t a) { uint32_t v; asm volatile("ld.volatile.shared.u32 %0, [%1];" : "=r"(v) : "r"(a) : "memory"); return v; }
__device__ __forceinline__ uint32_t cpa(uint32_t a, uint32_t one) { uint32_t v; asm volatile("mul.lo.u32 %0, %1, %2;" : "=r"(v) : "r"(a), "r"(one)); return v; }
__device__ __forceinline__ uint32_t cpb(uint32_t a, uint32_t zero) { uint32_t v; asm volatile("or.b32 %0, %1, %2;" : "=r"(v) : "r"(a), "r"(zero)); return v; }
__device__ __forceinline__ uint32_t lds16(uint32_t a) { uint16_t v; asm volatile("ld.shared.u16 %0, [%1];" : "=h"(v) : "r"(a) : "memory"); return v; }
__device__ __forceinline__ float ldsf(uint32_t a) { float v; asm volatile("ld.shared.f32 %0, [%1];" : "=f"(v) : "r"(a) : "memory"); return v; }
__device__ __forceinline__ void lds128(uint32_t* v, uint32_t a) { asm volatile("ld.shared.v4.u32 {%0,%1,%2,%3}, [%4];" : "=r"(v[0]), "=r"(v[1]), "=r"(v[2]), "=r"(v[3]) : "r"(a) : "memory"); }
__device__ __forceinline__ void sts32(uint32_t a, uint32_t v) { asm volatile("st.shared.u32 [%0], %1;" :: "r"(a), "r"(v) : "memory"); }
__device__ __forceinline__ void sts16(uint32_t a, uint32_t v) { asm volatile("st.shared.u16 [%0], %1;" :: "r"(a), "h"((uint16_t)v) : "memory"); }
__device__ __forceinline__ void sts64f(uint32_t a, float x, float y) { asm volatile("st.shared.v2.f32 [%0], {%1,%2};" :: "r"(a), "f"(x), "f"(y) : "memory"); }
__device__ __forceinline__ void sts128(uint32_t a, uint32_t x, uint32_t y, uint32_t z, uint32_t w) { asm volatile("st.shared.v4.u32 [%0], {%1,%2,%3,%4};" :: "r"(a), "r"(x), "r"(y), "r"(z), "r"(w) : "memory"); }
__device__ __forceinline__ void stsm4(uint32_t a, uint32_t r0, uint32_t r1, uint32_t r2, uint32_t r3) {
  asm volatile("stmatrix.sync.aligned.m8n8.x4.shared.b16 [%0], {%1,%2,%3,%4};" :: "r"(a), "r"(r0), "r"(r1), "r"(r2), "r"(r3) : "memory");
}
__device__ __forceinline__ void stsm4t(uint32_t a, uint32_t r0, uint32_t r1, uint32_t r2, uint32_t r3) {
  asm volatile("stmatrix.sync.aligned.m8n8.x4.trans.shared.b16 [%0], {%1,%2,%3,%4};" :: "r"(a), "r"(r0), "r"(r1), "r"(r2), "r"(r3) : "memory");
}
__device__ __forceinline__ void ldsm4t(uint32_t* r, uint32_t a) {
  asm volatile("ldmatrix.sync.aligned.m8n8.x4.trans.shared.b16 {%0,%1,%2,%3}, [%4];" : "=r"(r[0]), "=r"(r[1]), "=r"(r[2]), "=r"(r[3]) : "r"(a) : "memory");
}
__device__ __forceinline__ void ldsm4(uint32_t* r, uint32_t a) {
  asm volatile("ldmatrix.sync.aligned.m8n8.x4.shared.b16 {%0,%1,%2,%3}, [%4];" : "=r"(r[0]), "=r"(r[1]), "=r"(r[2]), "=r"(r[3]) : "r"(a) : "memory");
}
__device__ __forceinline__ void mma16816(float* d, const uint32_t* a, const uint32_t* b) {
  asm volatile("mma.sync.aligned.m16n8k16.row.col.f32.bf16.bf16.f32 {%0,%1,%2,%3}, {%4,%5,%6,%7}, {%8,%9}, {%0,%1,%2,%3};"
    : "+f"(d[0]), "+f"(d[1]), "+f"(d[2]), "+f"(d[3]) : "r"(a[0]), "r"(a[1]), "r"(a[2]), "r"(a[3]), "r"(b[0]), "r"(b[1]));
}
__device__ __forceinline__ uint32_t pack2(float lo, float hi) { uint32_t r; asm("cvt.rn.bf16x2.f32 %0, %1, %2;" : "=r"(r) : "f"(hi), "f"(lo)); return r; }
__device__ __forceinline__ uint32_t packh(float lo, float hi) { uint32_t r; asm("cvt.rn.f16x2.f32 %0, %1, %2;" : "=r"(r) : "f"(hi), "f"(lo)); return r; }
__device__ __forceinline__ uint32_t hcmul(uint32_t x, uint32_t zp, uint32_t zq) {
  const __half2 xx = *reinterpret_cast<__half2*>(&x);
  const __half2 r = __hfma2(__high2half2(xx), *reinterpret_cast<__half2*>(&zq), __hmul2(__low2half2(xx), *reinterpret_cast<__half2*>(&zp)));
  return *reinterpret_cast<const uint32_t*>(&r);
}
__device__ __forceinline__ void hcm2(uint32_t xr, uint32_t xi, uint32_t z, uint32_t& pr, uint32_t& pi) {
  const __half2 a = *reinterpret_cast<__half2*>(&xr), b = *reinterpret_cast<__half2*>(&xi), zz = *reinterpret_cast<__half2*>(&z);
  const __half2 re = __hfma2(__hneg2(b), __high2half2(zz), __hmul2(a, __low2half2(zz)));
  const __half2 im = __hfma2(a, __high2half2(zz), __hmul2(b, __low2half2(zz)));
  pr = *reinterpret_cast<const uint32_t*>(&re); pi = *reinterpret_cast<const uint32_t*>(&im);
}
__device__ __forceinline__ void sts64(uint32_t a, uint32_t x, uint32_t y) { asm volatile("st.shared.v2.u32 [%0], {%1,%2};" :: "r"(a), "r"(x), "r"(y) : "memory"); }
__device__ __forceinline__ void lds64(uint32_t* v, uint32_t a) { asm volatile("ld.shared.v2.u32 {%0,%1}, [%2];" : "=r"(v[0]), "=r"(v[1]) : "r"(a) : "memory"); }
__device__ __forceinline__ float bf_lo(uint32_t v) { return __uint_as_float(v << 16); }
__device__ __forceinline__ float bf_hi(uint32_t v) { return __uint_as_float(v & 0xffff0000u); }
__device__ __forceinline__ float bf_round(float x) { return bf_lo(pack2(x, 0.f)); }
__device__ __forceinline__ float ex2(float x) { float r; asm("ex2.approx.ftz.f32 %0, %1;" : "=f"(r) : "f"(x)); return r; }
__device__ __forceinline__ float phi(float t, float l2e = 1.44269504089f) {
  float e = ex2(t * l2e) + 1e-6f;
  asm("{\n.reg .pred p;\nsetp.gt.f32 p, %1, 0f00000000;\n@p add.f32 %0, %1, 0f3F800008;\n}" : "+f"(e) : "f"(t));
  return e;
}
__device__ __forceinline__ void wg_fence() { asm volatile("wgmma.fence.sync.aligned;" ::: "memory"); }
__device__ __forceinline__ void wg_commit() { asm volatile("wgmma.commit_group.sync.aligned;" ::: "memory"); }
template <int N> __device__ __forceinline__ void wg_wait() { asm volatile("wgmma.wait_group.sync.aligned %0;" :: "n"(N) : "memory"); }
template <int N> __device__ __forceinline__ void pin(float* a) {
  #pragma unroll
  for (int i = 0; i < N; i++) asm volatile("" : "+f"(a[i]) :: "memory");
}
__device__ __forceinline__ int rtid() { int t; asm volatile("mov.u32 %0, %%tid.x;" : "=r"(t)); return t; }
__device__ __forceinline__ int opaque(int v) { asm volatile("" : "+r"(v)); return v; }
template <int N> __device__ __forceinline__ void zero(float* a) {
  #pragma unroll
  for (int i = 0; i < N; i++) asm volatile("mov.b32 %0, 0;" : "=f"(a[i]));
}
template <int N> __device__ __forceinline__ void pinu(uint32_t* a) {
  #pragma unroll
  for (int i = 0; i < N; i++) asm volatile("" : "+r"(a[i]) :: "memory");
}
__device__ __forceinline__ void cexp_t(float lg2mag, float turns, float& re, float& im) {
  float m = ex2(lg2mag);
  float fr = (turns - __fadd_rn(__fadd_rn(turns, 12582912.f), -12582912.f)) * 6.283185307f;
  re = m * __cosf(fr); im = m * __sinf(fr);
}
__device__ __forceinline__ void cmul(float ar, float ai, float br, float bi, float& cr, float& ci) {
  cr = fmaf(ar, br, -ai * bi); ci = fmaf(ar, bi, ai * br);
}

__device__ __forceinline__ void wg_ss48_tt(float* d, uint64_t da, uint64_t db, int scale_d) {
  asm volatile("{\n.reg .pred p;\nsetp.ne.b32 p, %26, 0;\n"
    "wgmma.mma_async.sync.aligned.m64n48k16.f32.bf16.bf16 "
    "{%0, %1, %2, %3, %4, %5, %6, %7, %8, %9, %10, %11, %12, %13, %14, %15, %16, %17, %18, %19, %20, %21, %22, %23}, %24, %25, p, 1, 1, 1, 1;\n}\n"
    : "+f"(d[0]), "+f"(d[1]), "+f"(d[2]), "+f"(d[3]), "+f"(d[4]), "+f"(d[5]), "+f"(d[6]), "+f"(d[7]), "+f"(d[8]), "+f"(d[9]), "+f"(d[10]), "+f"(d[11]), "+f"(d[12]), "+f"(d[13]), "+f"(d[14]), "+f"(d[15]), "+f"(d[16]), "+f"(d[17]), "+f"(d[18]), "+f"(d[19]), "+f"(d[20]), "+f"(d[21]), "+f"(d[22]), "+f"(d[23])
    : "l"(da), "l"(db), "r"(scale_d));
}
__device__ __forceinline__ void wg_rs88_tb(float* d, const uint32_t* a, uint64_t db, int scale_d) {
  asm volatile("{\n.reg .pred p;\nsetp.ne.b32 p, %49, 0;\n"
    "wgmma.mma_async.sync.aligned.m64n88k16.f32.bf16.bf16 "
    "{%0, %1, %2, %3, %4, %5, %6, %7, %8, %9, %10, %11, %12, %13, %14, %15, %16, %17, %18, %19, %20, %21, %22, %23, %24, %25, %26, %27, %28, %29, %30, %31, %32, %33, %34, %35, %36, %37, %38, %39, %40, %41, %42, %43}, {%44, %45, %46, %47}, %48, p, 1, 1, 1;\n}\n"
    : "+f"(d[0]), "+f"(d[1]), "+f"(d[2]), "+f"(d[3]), "+f"(d[4]), "+f"(d[5]), "+f"(d[6]), "+f"(d[7]), "+f"(d[8]), "+f"(d[9]), "+f"(d[10]), "+f"(d[11]), "+f"(d[12]), "+f"(d[13]), "+f"(d[14]), "+f"(d[15]), "+f"(d[16]), "+f"(d[17]), "+f"(d[18]), "+f"(d[19]), "+f"(d[20]), "+f"(d[21]), "+f"(d[22]), "+f"(d[23]), "+f"(d[24]), "+f"(d[25]), "+f"(d[26]), "+f"(d[27]), "+f"(d[28]), "+f"(d[29]), "+f"(d[30]), "+f"(d[31]), "+f"(d[32]), "+f"(d[33]), "+f"(d[34]), "+f"(d[35]), "+f"(d[36]), "+f"(d[37]), "+f"(d[38]), "+f"(d[39]), "+f"(d[40]), "+f"(d[41]), "+f"(d[42]), "+f"(d[43])
    : "r"(a[0]), "r"(a[1]), "r"(a[2]), "r"(a[3]), "l"(db), "r"(scale_d));
}
__device__ __forceinline__ void wg_ss80_tb(float* d, uint64_t da, uint64_t db, int scale_d) {
  asm volatile("{\n.reg .pred p;\nsetp.ne.b32 p, %42, 0;\n"
    "wgmma.mma_async.sync.aligned.m64n80k16.f32.bf16.bf16 "
    "{%0, %1, %2, %3, %4, %5, %6, %7, %8, %9, %10, %11, %12, %13, %14, %15, %16, %17, %18, %19, %20, %21, %22, %23, %24, %25, %26, %27, %28, %29, %30, %31, %32, %33, %34, %35, %36, %37, %38, %39}, %40, %41, p, 1, 1, 0, 1;\n}\n"
    : "+f"(d[0]), "+f"(d[1]), "+f"(d[2]), "+f"(d[3]), "+f"(d[4]), "+f"(d[5]), "+f"(d[6]), "+f"(d[7]), "+f"(d[8]), "+f"(d[9]), "+f"(d[10]), "+f"(d[11]), "+f"(d[12]), "+f"(d[13]), "+f"(d[14]), "+f"(d[15]), "+f"(d[16]), "+f"(d[17]), "+f"(d[18]), "+f"(d[19]), "+f"(d[20]), "+f"(d[21]), "+f"(d[22]), "+f"(d[23]), "+f"(d[24]), "+f"(d[25]), "+f"(d[26]), "+f"(d[27]), "+f"(d[28]), "+f"(d[29]), "+f"(d[30]), "+f"(d[31]), "+f"(d[32]), "+f"(d[33]), "+f"(d[34]), "+f"(d[35]), "+f"(d[36]), "+f"(d[37]), "+f"(d[38]), "+f"(d[39])
    : "l"(da), "l"(db), "r"(scale_d));
}
__device__ __forceinline__ void wg_ss48_tt_h(float* d, uint64_t da, uint64_t db, int scale_d) {
  asm volatile("{\n.reg .pred p;\nsetp.ne.b32 p, %26, 0;\n"
    "wgmma.mma_async.sync.aligned.m64n48k16.f32.f16.f16 "
    "{%0, %1, %2, %3, %4, %5, %6, %7, %8, %9, %10, %11, %12, %13, %14, %15, %16, %17, %18, %19, %20, %21, %22, %23}, %24, %25, p, 1, 1, 1, 1;\n}\n"
    : "+f"(d[0]), "+f"(d[1]), "+f"(d[2]), "+f"(d[3]), "+f"(d[4]), "+f"(d[5]), "+f"(d[6]), "+f"(d[7]), "+f"(d[8]), "+f"(d[9]), "+f"(d[10]), "+f"(d[11]), "+f"(d[12]), "+f"(d[13]), "+f"(d[14]), "+f"(d[15]), "+f"(d[16]), "+f"(d[17]), "+f"(d[18]), "+f"(d[19]), "+f"(d[20]), "+f"(d[21]), "+f"(d[22]), "+f"(d[23])
    : "l"(da), "l"(db), "r"(scale_d));
}
__device__ __forceinline__ void wg_rs192_tb(float* d, const uint32_t* a, uint64_t db, int scale_d) {
  asm volatile("{\n.reg .pred p;\nsetp.ne.b32 p, %101, 0;\n"
    "wgmma.mma_async.sync.aligned.m64n192k16.f32.bf16.bf16 "
    "{%0, %1, %2, %3, %4, %5, %6, %7, %8, %9, %10, %11, %12, %13, %14, %15, %16, %17, %18, %19, %20, %21, %22, %23, %24, %25, %26, %27, %28, %29, %30, %31, %32, %33, %34, %35, %36, %37, %38, %39, %40, %41, %42, %43, %44, %45, %46, %47, %48, %49, %50, %51, %52, %53, %54, %55, %56, %57, %58, %59, %60, %61, %62, %63, %64, %65, %66, %67, %68, %69, %70, %71, %72, %73, %74, %75, %76, %77, %78, %79, %80, %81, %82, %83, %84, %85, %86, %87, %88, %89, %90, %91, %92, %93, %94, %95}, {%96, %97, %98, %99}, %100, p, 1, 1, 1;\n}\n"
    : "+f"(d[0]), "+f"(d[1]), "+f"(d[2]), "+f"(d[3]), "+f"(d[4]), "+f"(d[5]), "+f"(d[6]), "+f"(d[7]), "+f"(d[8]), "+f"(d[9]), "+f"(d[10]), "+f"(d[11]), "+f"(d[12]), "+f"(d[13]), "+f"(d[14]), "+f"(d[15]), "+f"(d[16]), "+f"(d[17]), "+f"(d[18]), "+f"(d[19]), "+f"(d[20]), "+f"(d[21]), "+f"(d[22]), "+f"(d[23]), "+f"(d[24]), "+f"(d[25]), "+f"(d[26]), "+f"(d[27]), "+f"(d[28]), "+f"(d[29]), "+f"(d[30]), "+f"(d[31]), "+f"(d[32]), "+f"(d[33]), "+f"(d[34]), "+f"(d[35]), "+f"(d[36]), "+f"(d[37]), "+f"(d[38]), "+f"(d[39]), "+f"(d[40]), "+f"(d[41]), "+f"(d[42]), "+f"(d[43]), "+f"(d[44]), "+f"(d[45]), "+f"(d[46]), "+f"(d[47]), "+f"(d[48]), "+f"(d[49]), "+f"(d[50]), "+f"(d[51]), "+f"(d[52]), "+f"(d[53]), "+f"(d[54]), "+f"(d[55]), "+f"(d[56]), "+f"(d[57]), "+f"(d[58]), "+f"(d[59]), "+f"(d[60]), "+f"(d[61]), "+f"(d[62]), "+f"(d[63]), "+f"(d[64]), "+f"(d[65]), "+f"(d[66]), "+f"(d[67]), "+f"(d[68]), "+f"(d[69]), "+f"(d[70]), "+f"(d[71]), "+f"(d[72]), "+f"(d[73]), "+f"(d[74]), "+f"(d[75]), "+f"(d[76]), "+f"(d[77]), "+f"(d[78]), "+f"(d[79]), "+f"(d[80]), "+f"(d[81]), "+f"(d[82]), "+f"(d[83]), "+f"(d[84]), "+f"(d[85]), "+f"(d[86]), "+f"(d[87]), "+f"(d[88]), "+f"(d[89]), "+f"(d[90]), "+f"(d[91]), "+f"(d[92]), "+f"(d[93]), "+f"(d[94]), "+f"(d[95])
    : "r"(a[0]), "r"(a[1]), "r"(a[2]), "r"(a[3]), "l"(db), "r"(scale_d));
}
__device__ __forceinline__ void wg_rs48_tb(float* d, const uint32_t* a, uint64_t db, int scale_d) {
  asm volatile("{\n.reg .pred p;\nsetp.ne.b32 p, %29, 0;\n"
    "wgmma.mma_async.sync.aligned.m64n48k16.f32.bf16.bf16 "
    "{%0, %1, %2, %3, %4, %5, %6, %7, %8, %9, %10, %11, %12, %13, %14, %15, %16, %17, %18, %19, %20, %21, %22, %23}, {%24, %25, %26, %27}, %28, p, 1, 1, 1;\n}\n"
    : "+f"(d[0]), "+f"(d[1]), "+f"(d[2]), "+f"(d[3]), "+f"(d[4]), "+f"(d[5]), "+f"(d[6]), "+f"(d[7]), "+f"(d[8]), "+f"(d[9]), "+f"(d[10]), "+f"(d[11]), "+f"(d[12]), "+f"(d[13]), "+f"(d[14]), "+f"(d[15]), "+f"(d[16]), "+f"(d[17]), "+f"(d[18]), "+f"(d[19]), "+f"(d[20]), "+f"(d[21]), "+f"(d[22]), "+f"(d[23])
    : "r"(a[0]), "r"(a[1]), "r"(a[2]), "r"(a[3]), "l"(db), "r"(scale_d));
}

struct Params {
  const __nv_bfloat16 *par[4], *logdt, *dskip, *u, *wo;
  CUtensorMap m[M_COUNT];
};

#define CHUNK(i) ((i) == 0 ? c : ((i) == 7 ? (c ^ 1) : (((c & 6) + 1 + (i)) & 7)))
#define FLAG(kind, rr, cc) (&g_flag[((kind) * 128 + (rr) * 8 + (cc)) * 32])
#define SLOT(i) ((i) == 0 ? OFF_EXTRA : OFF_BLK - 256 + ((i) > 5 ? (i) - 6 : (i) - 1) * BLK)
__device__ __forceinline__ void load_quad(uint32_t* A, uint32_t addr) {
  A[0] = lds32v(addr); A[1] = lds32v(addr + 32); A[2] = lds32v(addr - 32); A[3] = lds32v(addr);
}

__device__ __forceinline__ bool y_transpose(uint32_t sb, int w5, int lane, uint32_t ytag) {
  const int mi = lane >> 3, rw = lane & 7;
  const uint32_t sa = sb + OFF_EXTRA + (w5 * 16 + rw) * 128 + ((mi ^ rw) << 4), da = sb + SLOT(3) + (8 * mi + rw) * 160 + w5 * 32;
  const uint32_t ym = lane < 4 ? 0x10001u : 0u;
  bar_sync(7, 160);
  uint32_t v[8][4], bad = 0;
  #pragma unroll
  for (int q = 0; q < 8; q++) ldsm4t(v[q], (sa ^ ((q & 1) * 64 + ((q >> 1) & 1) * 16)) + ((q >> 1) & 1) * 10240 + (q >> 2) * 1024);
  #pragma unroll
  for (int q = 0; q < 8; q++) {
    bad |= (v[q][0] ^ ytag) | (v[q][2] ^ ytag);
    stsm4(da + (q & 3) * 5120 + (q >> 2) * 16, v[q][0] & ~ym, v[q][1], v[q][2] & ~ym, v[q][3]);
  }
  fence_async();
  uint32_t any;
  asm volatile("{\n.reg .pred p;\nsetp.ne.u32 p, %1, 0;\nbarrier.red.or.pred p, 7, 160, p;\nselp.u32 %0, 1, 0, p;\n}" : "=r"(any) : "r"(bad & ym) : "memory");
  return any;
}

__global__ void __launch_bounds__(512, 1) fused_kernel(const __grid_constant__ Params prm) {
  extern __shared__ unsigned char smem_raw[];
  const uint32_t sb = __shfl_sync(0xffffffff, smem_u32(smem_raw), 0);
  const int tid = threadIdx.x, lane = tid & 31;
  const int warp = __shfl_sync(0xffffffff, tid >> 5, 0), wg = warp >> 2, w4 = warp & 3;
  const int cta = blockIdx.x, r = cta >> 3, c = cta & 7;
  if ((sb & 0xffffffu) != SB0) return;
#define BAR(i) (sb + OFF_BAR + 8 * (i))
  const bool sw64 = ((c + 1) & 2) != 0;

  const CUtensorMap* mwp = &prm.m[sw64 ? M_W64 : M_W128];
  const int mcol = (c * 80 + (c & 1) * 16) >> (sw64 ? 5 : 6), rcol = c * 80 + ((c & 1) ? 0 : 64);
  if (warp == 12 && elect_one()) {
    #pragma unroll
    for (int i = 0; i < 5; i++) mbar_init(BAR(BR_FULL + i), 1);
    asm volatile("fence.mbarrier_init.release.cluster;" ::: "memory");
    if (EN_ATT) {
      mbar_expect_tx(BAR(BR_FULL), W_SLOT + 16384);
      tma4d(sb, mwp, BAR(BR_FULL), 0, 0, mcol, 0);
      tma2d(sb + OFF_X, &prm.m[M_X], BAR(BR_FULL), 0, r * 128);
      tma3d(sb + 12288, &prm.m[M_WR], BAR(BR_FULL), rcol, 0, 0);
      mbar_expect_tx(BAR(BR_FULL + 1), W_SLOT);
      tma4d(sb + W_SLOT, mwp, BAR(BR_FULL + 1), 0, 32, mcol, 0);
      tma3d(sb + W_SLOT + 12288, &prm.m[M_WR], BAR(BR_FULL + 1), rcol, 32, 0);
      TS(24);
    }
  }
  if (warp == 13 && elect_one()) {
    asm volatile("prefetch.tensormap [%0];" :: "l"(&prm.m[M_X]) : "memory");
    asm volatile("prefetch.tensormap [%0];" :: "l"(&prm.m[M_WR]) : "memory");
  }
  if (wg == 3) {
    asm volatile("setmaxnreg.dec.sync.aligned.u32 56;");
    const int tid = rtid(), lane = tid & 31;
    if (warp == 12) {
      asm volatile("bar.arrive 0, 512;" ::: "memory");
      {
        uint32_t s = 2, ph = 1, xs = 16384;
        #pragma unroll 1
        for (int kb = 2; kb < 20; kb++) {
          if (kb == 4) bar_sync(6, 128);
          if (kb >= 5) mbar_wait(BAR(BR_EMPTY) + 8 * s, ph);
          if (EN_ATT && elect_one()) {
            const uint32_t st = sb + s * W_SLOT, fb = BAR(BR_FULL) + 8 * s;
            mbar_expect_tx(fb, (kb & 1) ? W_SLOT : W_SLOT + 16384);
            if (!(kb & 1)) tma2d(sb + OFF_X + xs, &prm.m[M_X], fb, kb * 32, r * 128);
            tma4d(st, mwp, fb, 0, kb * 32, mcol, 0);
            tma3d(st + 12288, &prm.m[M_WR], fb, rcol, kb * 32, 0);
          }
          if (kb < 4 && lane == 0) TS(24 + kb);
          if (UPF && kb >= UKB - 4 && kb < UKB && elect_one())
            asm volatile("cp.async.bulk.prefetch.L2.global [%0], 5120;" :: "l"(prm.u + cta * 10240 + (kb - (UKB - 4)) * 2560) : "memory");
          if (EN_SSM && kb == (EN_ATT ? UKB : 4) && elect_one()) { mbar_expect_tx(BAR(BR_UIN), 20480); tma2d(sb + OFF_UT, &prm.m[M_U], BAR(BR_UIN), c * 80, r * 128); }
          if (kb == 14 && elect_one()) asm volatile("cp.async.bulk.prefetch.L2.global [%0], 6400;" :: "l"(prm.wo + cta * 3200) : "memory");
          if (!EN_ATT && kb == 4) break;
          if (++s == 5) { s = 0; ph ^= 1; }
          if (kb & 1) { xs += 16384; if (xs == 49152) xs = 0; }
        }
      }
      if (EN_ATT) {
      mbar_wait(BAR(BR_EPOCH), 0);
      const unsigned epoch = lds32(sb + OFF_EPOCH);
      const unsigned* fo = FLAG(3, r, lane & 7);
      unsigned seen = __ballot_sync(0xffffffff, ld_rlx(lane < 16 ? fo : FLAG(0, lane & 15, c)) == epoch) & 0xffu;
      mbar_wait(BAR(BR_GEMM), 0);
      if (elect_one()) {
        mbar_expect_tx(BAR(BR_WO), 10240);
        tma2d(sb, &prm.m[M_WO], BAR(BR_WO), c * 64, c * 80);
        mbar_expect_tx(BAR(BR_KVP), 61440);
        mbar_expect_tx(BAR(BR_WO + 1), 7 * 10240);
      }
      {
        uint32_t ds = sb + OFF_WOR + (lane >> 3) * 128 + (((lane & 7) ^ (lane >> 3)) << 4);
        #pragma unroll 1
        for (int h = 0; h < 2; h++) {
          const int i = (lane & 6) + h;
          const char* gs = reinterpret_cast<const char*>(prm.wo) + (size_t)((lane >> 3) + CHUNK(i) * 80) * 1280 + 1024 + c * 32 + (lane & 1) * 16;
          #pragma unroll 2
          for (int q = 0; q < 20; q++) {
            asm volatile("cp.async.cg.shared.global [%0], [%1], 16;" :: "r"(ds), "l"(gs) : "memory");
            ds = (ds + 512) ^ 64; gs += 5120;
          }
        }
      }
      mbar_wait(BAR(BR_PUB), 0);
      poll_all(FLAG(0, lane & 15, c), epoch);
      if (elect_one()) { TS(23); bulk_ld(sb + OFF_KVP, &g_kvp[c * 16 * 240], 61440, BAR(BR_KVP)); }
      asm volatile("cp.async.wait_all;" ::: "memory");
      fence_async();
      mbar_arrive(BAR(BR_WO));
      mbar_wait(BAR(BR_SUM), 0);
      if (elect_one()) {
        #pragma unroll 1
        for (int i = 1; i < 8; i++) tma2d(sb + i * 10240, &prm.m[M_WO], BAR(BR_WO + 1), c * 64, CHUNK(i) * 80);
      }
      mbar_wait(BAR(BR_OSTG), 0);
      if (elect_one()) {
        bulk_st(&g_o[cta * 1280], sb + OFF_EXTRA, 20480);
        bulk_commit();
        bulk_wait0();
        st_rlx(FLAG(3, r, c), epoch);
        mbar_arrive(BAR(BR_OEMPTY));
        TS(20);
      }
      __syncwarp();
      #pragma unroll 1
      for (int i = 1; i < 8; i++) {
        const int src = CHUNK(i);
        if (!((seen >> src) & 1)) seen = poll_bit(fo, epoch, 1u << src);
        if (i > 5) mbar_wait(BAR(BR_OEMPTY - 5) + 8 * i, 0);
        else if (EN_SSM && i != 2 && i != 3) mbar_wait(i == 1 ? BAR(BR_KS + 1) : BAR(BR_FREE - 4) + 8 * i, 0);
        if (elect_one()) {
          mbar_expect_tx(BAR(BR_OFULL) + 8 * i, 20480);
          bulk_ld(sb + SLOT(i), &g_o[(r * 8 + src) * 1280], 20480, BAR(BR_OFULL) + 8 * i);
          if (i == 1) TS(21);
          if (i == 7) TS(22);
        }
        __syncwarp();
      }
      if (lane == 0) { DUMP(20, 30); }
      }
    } else {
      const int hw = warp - 13, ht = tid - 416;
      if (hw == 2 && elect_one()) {
        #pragma unroll
        for (int i = 5; i < BR_COUNT; i++) mbar_init(BAR(i), i == BR_WO ? 33 : i == BR_OEMPTY ? 9 : i < BR_EMPTY ? 1 : i < BR_OEMPTY ? 2 : i < BR_Y ? 8 : i < BR_OSTG ? 4 : i == BR_OSTG ? 8 : i < BR_U2 ? 3 : 1);
        asm volatile("fence.mbarrier_init.release.cluster;" ::: "memory");
      }
      __syncwarp();
      asm volatile("bar.arrive 0, 512;" ::: "memory");
      if (EN_SSM && hw == 2) asm volatile("bar.arrive 8, 160;" ::: "memory");
      const unsigned epoch = hw == 0 ? ld_rlx(&g_epoch[cta]) + 1 : 0;
      bar_sync(5, 96);
      asm volatile("bar.arrive 6, 128;" ::: "memory");
      if (hw == 1 && elect_one()) {
        #pragma unroll
        for (int i = M_U; i < M_COUNT; i++) asm volatile("prefetch.tensormap [%0];" :: "l"(&prm.m[i]) : "memory");
      }
      if (ht == 0) {
        st_rlx(&g_epoch[cta], epoch);
        sts32(sb + OFF_EPOCH, epoch);
        mbar_arrive(BAR(BR_EPOCH));
      }
      if (EN_SSM) {
      const int mi = lane >> 3, rw = lane & 7, ch0 = c * 80 + r * 5;
      mbar_wait(BAR(BR_UIN), 0);
      if (ht == 0) TS(36);
      #pragma unroll 1
      for (int h = 0; h < 2; h++) {
        const uint32_t sa = sb + OFF_UT + h * 10240 + (8 * mi + rw) * 160 + hw * 16, da = sb + OFF_UT + h * 10240 + (hw * 8 + rw) * 128 + ((mi ^ rw ^ h) << 4);
        uint32_t v[8][4];
        #pragma unroll
        for (int q = 0; q < 8; q++) if (q < 6 || hw == 0) ldsm4t(v[q], sa + (q & 1) * 5120 + (q >> 1) * 48);
        bar_sync(5, 96);
        #pragma unroll
        for (int q = 0; q < 8; q++) if (q < 6 || hw == 0) stsm4((da ^ ((q & 1) * 64)) + (q >> 1) * 3072, v[q][0], v[q][1], v[q][2], v[q][3]);
      }
      fence_async();
      bar_sync(5, 96);
      if (hw == 0) {
        if (elect_one()) {
          tma2d_st(&prm.m[M_SA], sb + OFF_UT, r * 128, c * 80);
          tma2d_st(&prm.m[M_SA], sb + OFF_UT + 10240, r * 128 + 64, c * 80);
          bulk_commit(); bulk_wait0_read();
          mbar_arrive(BAR(BR_UOUT));
          TS(37);
          bulk_wait0();
          st_rel(FLAG(1, r, c), epoch);
          TS(30);
        }
        __syncwarp();
        poll_all_acq(FLAG(1, lane & 15, c), epoch);
      }
      #pragma unroll 1
      for (int k = 0; k < 5; k++) {
        if (k == 0 || k == 3) {
          const int p = k != 0;
          if (hw == 0) {
            if (!p) {
              if (elect_one()) {
                fence_async_g();
                mbar_expect_tx(BAR(BR_U), 12288);
                #pragma unroll 1
                for (int q = 0; q < 3; q++) bulk_ld(sb + OFF_BLK + q * q * BLK, g_uy + (ch0 + q * q) * 2048, 4096, BAR(BR_U));
                TS(31);
              }
              __syncwarp();
            }
            mbar_wait(BAR(p ? BR_U2 : BR_U), 0);
          }
          bar_sync(5, 96);
        }
        const int l3 = (hw + k) % 3 * 32 + lane;
        const uint32_t blk = sb + OFF_BLK + ((0x32410 >> (4 * k)) & 7) * BLK, o = blk + B_D + l3 * 16;
        float P[34];
        P[0] = 0.f;
        #pragma unroll
        for (int q = 0; q < 5; q++) {
          const int ch = 2 * l3 - 3 + q;
          uint32_t v[4];
          lds128(v, blk + (uint32_t)((ch * 16) ^ ((ch * 2) & 0x10)));
          #pragma unroll
          for (int e = 0; e < 8; e++) {
            const int i = 8 * q + e - 4;
            if (i >= 0 && i < 33) P[i + 1] = P[i] + ((e & 1) ? bf_hi(v[e >> 1]) : bf_lo(v[e >> 1]));
          }
        }
#define WIN(lo, hi, e) (P[21 + (e) - (lo)] - P[20 + (e) - (hi)])
#define WIN8(lo, hi, b) pack2(WIN(lo, hi, b), WIN(lo, hi, b + 1)), pack2(WIN(lo, hi, b + 2), WIN(lo, hi, b + 3)), pack2(WIN(lo, hi, b + 4), WIN(lo, hi, b + 5)), pack2(WIN(lo, hi, b + 6), WIN(lo, hi, b + 7))
        if (l3 < 64) {
          sts128(o + B_D9, WIN8(12, 20, 0)); sts128(o + B_D9 + 1024, WIN8(12, 20, 8));
          sts128(o + B_D7, WIN8(5, 11, 0)); sts128(o + B_D7 + 1024, WIN8(5, 11, 8));
        }
        sts128(o + B_D5, WIN8(6, 10, 0)); sts128(o + B_D5 + 1552, WIN8(6, 10, 8));
        sts128(o, WIN8(3, 5, 0)); sts128(o + 1552, WIN8(3, 5, 8));
        if (l3 < 2) sts128(blk + B_D + l3 * B_D5 + 1536, 0, 0, 0, 0);
      }
      __syncwarp();
      if (lane == 0) mbar_arrive(BAR(BR_DRDY + 1));
      if (ht == 0) TS(32);
      if (hw == 0) {
        #pragma unroll 1
        for (int p = 0; p < 2; p++) {
          mbar_wait(BAR(BR_Y) + 8 * p, 0);
          if (elect_one()) {
            bulk_st(g_uy + (640 + ch0 + 4 * p) * 2048, sb + OFF_BLK + (3 + p) * BLK, p ? 4096 : 16384);
            bulk_commit(); bulk_wait0_read();
            mbar_arrive(BAR(BR_FREE) + 8 * p);
          }
          __syncwarp();
        }
        if (elect_one()) { bulk_wait0(); st_rlx(FLAG(2, r, c), epoch); TS(33); }
        __syncwarp();
        poll_all(FLAG(2, lane & 15, c), epoch);
        if (EN_ATT) mbar_wait(BAR(BR_OEMPTY), 0);
        #pragma unroll 1
        for (int n = 0; n < 64; n++) {
          if (elect_one()) {
            mbar_expect_tx(BAR(BR_YIN), 20480);
            tma2d(sb + OFF_EXTRA, &prm.m[M_SA], BAR(BR_YIN), r * 128, 640 + c * 80);
            tma2d(sb + OFF_EXTRA + 10240, &prm.m[M_SA], BAR(BR_YIN), r * 128 + 64, 640 + c * 80);
            TS(34);
          }
          __syncwarp();
          if (EN_ATT) mbar_wait(BAR(BR_OEMPTY + 3), 0);
          mbar_wait(BAR(BR_YIN), n & 1);
          if (lane == 0) TS(38);
          if (!y_transpose(sb, 4, lane, (epoch & 1u) * 0x10001u)) break;
          FIXCNT
        }
      if (elect_one()) {
        TS(39);
        tma2d_st(&prm.m[M_OUT], sb + SLOT(3), c * 80, r * 128);
        bulk_commit(); bulk_wait0_read();
        TS(35); DUMP(30, 40); DUMP(0, 1);
      }
      }
      }
    }
  } else {
  if (wg < 2) {
    asm volatile("setmaxnreg.inc.sync.aligned.u32 160;");
    bar_sync(0, 512);
    if (EN_ATT) {
    float am[96], ar[24];
    {
      const bool lead = (rtid() & 127) == 0;
      constexpr uint64_t dr0 = mkdesc(SB0 + 12288, 1024, 256, 3);
      const uint64_t db0 = sw64 ? mkdesc(SB0, 2048, 512, 2) : mkdesc(SB0, 4096, 1024, 1);
      const uint32_t kst = sw64 ? 64 : 128, bh = db0 >> 32;
      uint32_t s = 0, ph = 0, xo = 0;
      const int ln = rtid() & 31;
      const uint32_t xa = sb + OFF_X + (warp * 16 + (ln & 15)) * 128 + (((ln >> 4) ^ (ln & 7)) << 4);
      uint32_t A[8];
      mbar_wait(BAR(BR_FULL), 0);
      if (lead && wg == 0) TS(1);
      ldsm4(A, xa); ldsm4(A + 4, xa ^ 32);
      wg_fence();
      wg_rs48_tb(ar, A, dr0, 0); wg_rs192_tb(am, A, db0, 0);
      wg_commit();
      #pragma unroll 1
      for (int kb = 1; kb < 20; kb++) {
        const uint32_t wp = s * (W_SLOT >> 4), eb = BAR(BR_EMPTY) + 8 * s;
        wg_fence();
        wg_rs48_tb(ar, A + 4, desc2((uint32_t)dr0 + wp + 32, dr0 >> 32), 1);
        wg_rs192_tb(am, A + 4, desc2((uint32_t)db0 + wp + kst, bh), 1);
        wg_commit();
        if (++s == 5) { s = 0; ph ^= 1; }
        if (!(kb & 1)) { xo += 16384; if (xo == 49152) xo = 0; }
        mbar_wait(BAR(BR_FULL) + 8 * s, ph);
        const uint32_t xk = (xa + xo) ^ ((kb & 1) * 64), wn = s * (W_SLOT >> 4);
        wg_wait<1>();
        ldsm4(A, xk);
        wg_fence();
        wg_rs48_tb(ar, A, desc2((uint32_t)dr0 + wn, dr0 >> 32), 1);
        wg_rs192_tb(am, A, desc2((uint32_t)db0 + wn, bh), 1);
        wg_commit();
        wg_wait<1>();
        ldsm4(A + 4, xk ^ 32);
        if (lead && kb < 16) mbar_arrive(eb);
      }
      wg_fence();
      wg_rs48_tb(ar, A + 4, dr0 + 4 * (W_SLOT >> 4) + 32, 1);
      wg_rs192_tb(am, A + 4, desc2((uint32_t)db0 + 4 * (W_SLOT >> 4) + kst, bh), 1);
      wg_commit();
      wg_wait<0>();
      pin<96>(am); pin<24>(ar);
    }
    const int tid = rtid(), lane = tid & 31, tq = lane & 3;
    if (tid == 0) TS(2);
#define QV(j, e) ((j) < 8 ? am[4 * (j) + (e)] : ar[4 * ((j) - 8) + (e)])
#define KV_(j, e) ((j) < 8 ? am[32 + 4 * (j) + (e)] : ar[8 + 4 * ((j) - 8) + (e)])
#define VV(j, e) ((j) < 8 ? am[64 + 4 * (j) + (e)] : ar[16 + 4 * ((j) - 8) + (e)])
    {
      bar_sync(1, 256);
      if (tid == 0) mbar_arrive(BAR(BR_GEMM));
      const uint32_t ro = sb + (uint32_t)((warp * 16 + (lane & 15)) * 16);
      const int l0 = 2 * (c & 1) + (lane >> 4);
      const uint32_t ones = (tq == 0) ? 0x00003f80u : 0u;
#define PV(j) pack2(VV(j, 0), VV(j, 1)), pack2(VV(j, 2), VV(j, 3))
#define PK(j) pack2(phi(KV_(j, 0)), phi(KV_(j, 1))), pack2(phi(KV_(j, 2)), phi(KV_(j, 3)))
      stsm4(ro + OFF_V + (5 + 6 * (lane >> 4)) * 2048, ones, ones, ones, ones);
      #pragma unroll
      for (int j = 0; j < 10; j += 2) {
        const int l = (j == 8 && (c & 1)) ? l0 - 2 : l0 + j;
        stsm4(ro + OFF_V + (l + (l >= 5)) * 2048, PV(j), PV(j + 1));
        stsm4(ro + OFF_PK + l * 2048, PK(j), PK(j + 1));
      }
    }
    fence_async();
    bar_sync(1, 256);
    if (tid == 0) TS(3);
    mbar_wait(BAR(BR_EPOCH), 0);
    const unsigned epoch = lds32(sb + OFF_EPOCH);
    {
      float kv[24]; zero<24>(kv);
      constexpr uint64_t da = mkdesc(SB0 + OFF_PK, 128, 2048, 0), db = mkdesc(SB0 + OFF_V, 128, 2048, 0);
      wg_fence();
      #pragma unroll
      for (int s = 0; s < 8; s++) wg_ss48_tt(kv, desc2((uint32_t)da + wg * 640 + s * 16, da >> 32), desc2((uint32_t)db + wg * 768 + s * 16, db >> 32), s != 0);
      wg_commit();
      wg_wait<0>();
      pin<24>(kv);
      if (tid == 0) TS(15);
      if (w4 < 3) {
        const uint32_t wb = sb + OFF_KVS + (wg * 3 + w4) * 1536 + (lane & 15) * 96;
        #pragma unroll
        for (int j = 0; j < 6; j += 2)
          stsm4(wb + (j + (lane >> 4)) * 16, pack2(kv[4 * j], kv[4 * j + 1]), pack2(kv[4 * j + 2], kv[4 * j + 3]),
                pack2(kv[4 * j + 4], kv[4 * j + 5]), pack2(kv[4 * j + 6], kv[4 * j + 7]));
        __syncwarp();
        const int dl = w4 * 16 + (lane & 15), hl = dl >= 20;
        uint32_t v[4], z[4];
        lds128(v, wb + (3 * hl + (lane >> 4)) * 16);
        lds64(z, wb + 32 + 8 * hl); z[2] = lds32(wb + 80); z[3] = epoch & 1u;
        if (dl < 40) {
          uint4* dst = &g_kvp[(c * 16 + r) * 240 + wg * 40 + dl];
          v[3] = (v[3] & ~1u) | z[3];
          st128_rlx(dst + (lane >> 4) * 80, v);
          if (lane < 16) st128_rlx(dst + 160, z);
        }
      }
    }
    bar_sync(1, 256);
    if (tid == 0) { st_rlx(FLAG(0, r, c), epoch); mbar_arrive(BAR(BR_PUB)); TS(4); }
    const int kvi = (tid >= 80) + (tid >= 160) + (tid >= 240), kd = tid - 80 * kvi;
    const int khd = kd / 20, kt0 = 5 * (khd >> 1) + 2 * (khd & 1);
    const uint32_t rb = sb + OFF_KVB + kd * 16;
    if (kvi < 3) {
      #pragma unroll 1
      for (int m = kvi; m < 7; m += 3) { const int q = kt0 + 3 + m; sts128(rb + (q >= 10 ? q - 10 : q) * 1280, 0, 0, 0, 0); }
    }
    uint32_t qa[20];
    {
      const float sc = 1.44269504089f + __uint_as_float(lds32(sb + OFF_EPOCH) ^ epoch);
      #pragma unroll
      for (int j = 0; j < 10; j++) { qa[2 * j] = pack2(phi(QV(j, 0), sc), phi(QV(j, 1), sc)); qa[2 * j + 1] = pack2(phi(QV(j, 2), sc), phi(QV(j, 3), sc)); }
    }
    if (tid == 0) TS(5);
    if (warp == 7) mbar_wait(BAR(BR_KVP), 0);
    bar_sync(1, 256);
    if (tid == 0) TS(6);
    if (kvi < 3) {
      float s[8];
      zero<8>(s);
      uint32_t bad = 0;
      #pragma unroll 4
      for (int i = 0; i < 16; i += 2) {
        uint32_t w[4], x[4];
        lds128(w, sb + OFF_KVP + tid * 16 + i * 3840); lds128(x, sb + OFF_KVP + tid * 16 + i * 3840 + 3840);
        bad |= (w[3] ^ epoch) | (x[3] ^ epoch);
        #pragma unroll
        for (int e = 0; e < 4; e++) {
          asm("add.rn.bf16x2 %0, %0, %1;" : "+r"(w[e]) : "r"(x[e]));
          s[2 * e] += bf_lo(w[e]); s[2 * e + 1] += bf_hi(w[e]);
        }
      }
      if (__builtin_expect(bad & 1u, 0)) {
        zero<8>(s);
        #pragma unroll 1
        for (int i = 0; i < 16; i++) {
          uint32_t w[4] = {0, 0, 0, ~epoch};
          fix128_w3(w, &g_kvp[(c * 16 + i) * 240 + tid], epoch, 1u);
          #pragma unroll
          for (int e = 0; e < 4; e++) { s[2 * e] += bf_lo(w[e]); s[2 * e + 1] += bf_hi(w[e]); }
        }
        FIXCNT
      }
      const uint32_t p0 = pack2(s[0], s[1]), p1 = pack2(s[2], s[3]), p2 = pack2(s[4], s[5]), p3 = pack2(s[6], s[7]);
      if (kvi < 2) sts128(rb + (kt0 + (khd & 1) + kvi) * 1280, p0, p1, p2, p3);
      else {
        const bool od = khd & 1;
        sts128(rb + (5 * (khd >> 1) + 2) * 1280, od ? 0u : p0, od ? 0u : p1, od ? p0 : 0u, od ? p1 : 0u);
        const uint32_t zz = (p2 & 0xffffu) << (16 * (khd & 1));
        sts128(rb + 10 * 1280, khd < 2 ? zz : 0u, khd < 2 ? 0u : zz, 0u, 0u);
      }
    }
    fence_async();
    bar_sync(1, 256);
    if (tid == 0) { mbar_arrive(BAR(BR_SUM)); TS(7); }
    {
      float oa[44]; zero<44>(oa);
      constexpr uint64_t db = mkdesc(SB0 + OFF_KVB, 128, 1280, 0);
      wg_fence();
      #pragma unroll
      for (int s = 0; s < 5; s++) wg_rs88_tb(oa, &qa[4 * s], desc2((uint32_t)db + ((s == 4 && (c & 1)) ? 0 : (s + (c & 1)) * 16), db >> 32), s != 0);
      wg_commit();
      wg_wait<0>();
      pin<44>(oa);
      if (tid == 0) TS(13);
      float rc[4], rd[2][4];
      #pragma unroll
      for (int e = 0; e < 4; e++) asm("rcp.approx.ftz.f32 %0, %1;" : "=f"(rc[e]) : "f"(oa[40 + e] + 1e-6f));
      #pragma unroll
      for (int h = 0; h < 4; h++) {
        rd[0][h] = __shfl_sync(0xffffffff, rc[h & 1], (lane & 28) | (h >> 1));
        rd[1][h] = __shfl_sync(0xffffffff, rc[2 + (h & 1)], (lane & 28) | (h >> 1));
      }
      #pragma unroll
      for (int j = 0; j < 10; j++) {
        #pragma unroll
        for (int h = 0; h < 2; h++) {
          float f;
          if (j == 2) f = tq < 2 ? rd[h][0] : rd[h][1];
          else if (j == 7) f = tq < 2 ? rd[h][2] : rd[h][3];
          else f = rd[h][(8 * j) / 20];
          qa[2 * j + h] = pack2(oa[4 * j + 2 * h] * f, oa[4 * j + 2 * h + 1] * f);
        }
      }
      const uint32_t m0 = (lane & 7) == ((2 * w4) & 7), m1 = (lane & 7) == 2 * w4 + 1;
      const uint32_t oa_ = sb + OFF_EXTRA + (lane >> 4) * 2048 + (warp * 16 + (lane & 15)) * 16;
      bar_sync(1, 256);
#define TAG(v, m) (((v) & ~(m)) | (epoch & (m)))
      #pragma unroll
      for (int s = 0; s < 5; s++) stsm4(oa_ + s * 4096, TAG(qa[4 * s], m0), TAG(qa[4 * s + 1], m1), TAG(qa[4 * s + 2], m0), TAG(qa[4 * s + 3], m1));
    }
    fence_async();
    __syncwarp();
    if (lane == 0) mbar_arrive(BAR(BR_OSTG));
    if (tid == 0) TS(8);
    }
    asm volatile("setmaxnreg.dec.sync.aligned.u32 136;");
  } else {
    const int g = lane >> 2, tq = lane & 3, t7 = tid & 127;
    uint32_t raw[5][4], pd;
    {
      const int ch = c * 80 + r * 5;
      #pragma unroll
      for (int e = 0; e < 4; e++) {
        const __nv_bfloat16* pp = prm.par[e] + ch * 128 + t7;
        #pragma unroll
        for (int q = 0; q < 5; q++) asm volatile("ld.global.nc.u16 %0, [%1];" : "=r"(raw[q][e]) : "l"(pp + q * 128));
      }
      asm volatile("ld.global.nc.u16 %0, [%1];" : "=r"(pd) : "l"(((lane & 8) ? prm.dskip : prm.logdt) + ch + min(lane & 7, 4)));
    }
    asm volatile("bar.arrive 0, 512;" ::: "memory");
    if (EN_SSM) {
    {
      #pragma unroll 1
      for (int k = 0; k < 4; k++) {
        const uint32_t z = sb + OFF_BLK + k * BLK + t7 * 16;
        sts128(z + B_TBL, 0, 0, 0, 0); sts128(z + B_TBL + 2048, 0, 0, 0, 0);
      }
      if (t7 < 80) sts128(sb + OFF_BLK + (t7 >> 4) * BLK - 256 + (t7 & 15) * 16, 0, 0, 0, 0);
      const uint32_t ea = sb + OFF_BLK + (2 + (w4 & 1)) * BLK + (lane >> 4) * 7168 + ((lane >> 3) & 1) * 256 + (lane & 7) * 16 + (w4 >> 1) * 2048;
      constexpr uint64_t dE = mkdesc(SB0 + OFF_BLK + 2 * BLK, 128, 512, 0);
      const uint32_t xa = sb + OFF_BLK + 18560 + t7 * 8, xr_ = sb + OFF_BLK + 18560 + (t7 ^ 64) * 8;
      uint32_t pr[5][2];
      #pragma unroll
      for (int q = 0; q < 5; q++) {
        #pragma unroll
        for (int e = 0; e < 2; e++) pr[q][e] = raw[q][2 * e] | (raw[q][2 * e + 1] << 16);
        const uint32_t m = __reduce_max_sync(0xffffffff, max(raw[q][2] & 0x7fffu, raw[q][3] & 0x7fffu));
        if (lane == 0) sts32(sb + OFF_EPOCH + 64 + q * 16 + w4 * 4, m);
      }
      bar_sync(4, 128);
      if (t7 == 0) TS(40);
      const int j = (w4 & 1) * 16 + (w4 >> 1) * 8 + g, i2 = tq < 2 ? 64 * tq + j : 32 * (tq - 2) + j;
      const uint32_t e2 = B_TBL + 4 * (tq < 2 ? T_F3 + (((i2 - 1) & 1) ? 80 : 0) + ((i2 - 1) >> 1) + 16 : T_F2 + (i2 & 1) * 96 + (i2 >> 1));
      const uint32_t e1 = tq < 2 ? (i2 ? e2 - 64 : B_TBL + 4 * (T_F2 + 175)) : B_TBL + 4 * (i2 ? T_F2 + ((2 * i2 - 1) & 3) * 48 + ((2 * i2 - 1) >> 2) : 16 + 511);
      const uint32_t e0 = B_TBL + (16 + 8 * j + 2 * tq) * 4;
      const float dtl = bf_round(expf(bf_lo(pd)));
      float hd[9];
      auto head = [&](int q) {
        const uint32_t pa0 = pr[0][0], pc0 = pr[0][1];
        const float dt = __shfl_sync(0xffffffff, dtl, q);
        #pragma unroll
        for (int e = 0; e < 2; e++) { pr[0][e] = pr[1][e]; pr[1][e] = pr[2][e]; pr[2][e] = pr[3][e]; pr[3][e] = pr[4][e]; }
        uint32_t mm[4];
        lds128(mm, sb + OFF_EPOCH + 64 + q * 16);
        const uint32_t ex = min(max(max(max(mm[0], mm[1]), max(mm[2], mm[3])) >> 7, 1u), 253u);
        const float sc = __uint_as_float((254u - ex) << 23);
        const float lr = -bf_round(expf(bf_lo(pa0))) * dt * 1.44269504089f;
        const float tn = bf_hi(pa0) * dt * 0.15915494309f;
        cexp_t(lr, -tn, hd[0], hd[1]);
        cexp_t(lr * 8.f, tn * 8.f, hd[2], hd[3]);
        cexp_t(lr * 64.f, tn * 64.f, hd[4], hd[5]);
        hd[6] = bf_lo(pc0) * sc; hd[7] = -bf_hi(pc0) * sc;
        hd[8] = 2.f * dt * __uint_as_float(ex << 23);
      };
      head(0);
      #pragma unroll 1
      for (int it = 0; it < 5; it++) {
        const int k = it;
        const uint32_t blk = sb + OFF_BLK + k * BLK;
        float fac = 0.f;
        float ka[24]; zero<24>(ka);
        {
          if (it == 4) {
            mbar_wait(BAR(BR_UOUT), 0);
            sts128(sb + OFF_UT + B_TBL + t7 * 16, 0, 0, 0, 0); sts128(sb + OFF_UT + B_TBL + 2048 + t7 * 16, 0, 0, 0, 0);
          }
          const uint32_t ga = ea + 4096 - (w4 >> 1) * 512;
#define PUT4(i, a, b, c_, d) sts128(((i) < 8 ? ea + ((i) >> 1) * 512 : ga + (((i) - 8) >> 1) * 512) + ((i) & 1) * 128, a, b, c_, d)
          float z2r, z2i, z4r, z4i, xr[8], xi[8], gr[8], gi[8], wr[9], wi[9];
          const float z1r = hd[0], z1i = hd[1];
          xr[1] = hd[2]; xi[1] = hd[3]; wr[0] = hd[4]; wi[0] = hd[5];
          fac = hd[8];
          xr[0] = 1.f; xi[0] = 0.f;
          cmul(xr[1], xi[1], xr[1], xi[1], xr[2], xi[2]); cmul(xr[2], xi[2], xr[1], xi[1], xr[3], xi[3]);
          cmul(xr[2], xi[2], xr[2], xi[2], xr[4], xi[4]);
          #pragma unroll
          for (int b = 1; b < 4; b++) cmul(xr[4], xi[4], xr[b], xi[b], xr[4 + b], xi[4 + b]);
          cmul(wr[0], wi[0], wr[0], wi[0], wr[1], wi[1]); cmul(wr[1], wi[1], wr[0], wi[0], wr[2], wi[2]);
          cmul(wr[1], wi[1], wr[1], wi[1], wr[3], wi[3]); cmul(wr[3], wi[3], wr[3], wi[3], wr[4], wi[4]);
          cmul(wr[4], wi[4], wr[3], wi[3], wr[5], wi[5]); cmul(wr[4], wi[4], wr[4], wi[4], wr[6], wi[6]);
          cmul(wr[6], wi[6], wr[4], wi[4], wr[7], wi[7]); cmul(wr[6], wi[6], wr[6], wi[6], wr[8], wi[8]);
          uint32_t R[4], I[4], PR[4], PI[4];
          #pragma unroll
          for (int b = 0; b < 4; b++) { R[b] = packh(xr[2 * b], xr[2 * b + 1]); I[b] = packh(xi[2 * b], xi[2 * b + 1]); }
          PUT4(0, R[0], R[1], R[2], R[3]); PUT4(1, I[0], I[1], I[2], I[3]);
          #pragma unroll
          for (int i = 0; i < 3; i++) {
            const uint32_t z = packh(wr[i], wi[i]);
            #pragma unroll
            for (int b = 0; b < 4; b++) hcm2(R[b], I[b], z, PR[b], PI[b]);
            PUT4(2 * i + 2, PR[0], PR[1], PR[2], PR[3]); PUT4(2 * i + 3, PI[0], PI[1], PI[2], PI[3]);
          }
          gr[0] = hd[6]; gi[0] = hd[7];
          cmul(z1r, z1i, z1r, z1i, z2r, z2i); cmul(z2r, z2i, z2r, z2i, z4r, z4i);
          cmul(gr[0], gi[0], z1r, z1i, gr[1], gi[1]);
          cmul(gr[0], gi[0], z2r, z2i, gr[2], gi[2]); cmul(gr[1], gi[1], z2r, z2i, gr[3], gi[3]);
          #pragma unroll
          for (int b = 0; b < 4; b++) cmul(gr[b], gi[b], z4r, z4i, gr[4 + b], gi[4 + b]);
          PUT4(8, packh(gr[0], gr[1]), packh(gr[2], gr[3]), packh(gr[4], gr[5]), packh(gr[6], gr[7]));
          PUT4(9, packh(gi[0], gi[1]), packh(gi[2], gi[3]), packh(gi[4], gi[5]), packh(gi[6], gi[7]));
          {
            const uint32_t z = packh(wr[3], -wi[3]), a4r = packh(gr[0], gr[4]), a4i = packh(gi[0], gi[4]);
            hcm2(packh(gr[0], gr[2]), packh(gi[0], gi[2]), z, PR[0], PI[0]);
            hcm2(packh(gr[4], gr[6]), packh(gi[4], gi[6]), z, PR[1], PI[1]);
            hcm2(a4r, a4i, packh(wr[4], -wi[4]), PR[2], PI[2]);
            hcm2(a4r, a4i, packh(wr[5], -wi[5]), PR[3], PI[3]);
            PUT4(10, PR[0], PR[1], PR[2], PR[3]); PUT4(11, PI[0], PI[1], PI[2], PI[3]);
            float hr, hi_;
            cmul(gr[0], gi[0], wr[3], -wi[3], hr, hi_);
            const uint32_t cr = packh(gr[0], hr), ci = packh(gi[0], hi_);
            #pragma unroll
            for (int i = 0; i < 3; i++) hcm2(cr, ci, packh(wr[6 + i], -wi[6 + i]), PR[i], PI[i]);
            PUT4(12, PR[0], PR[1], PR[2], 0u); PUT4(13, PI[0], PI[1], PI[2], 0u);
          }
          fence_async();
          bar_sync(4, 128);
          wg_fence();
          #pragma unroll
          for (int s = 0; s < 8; s++) {
            const uint64_t d = dE + (s >> 2) * (BLK >> 4) + ((s >> 1) & 1) * 448 + (s & 1) * 16;
            wg_ss48_tt_h(ka, d, d + 256, s != 0);
          }
          wg_commit();
        }
        const float dsk = bf_lo(__shfl_sync(0xffffffff, pd, 8 + (it & 7)));
        head(min(it + 1, 4));
        asm volatile("{\n.reg .pred p;\nHL:\nsetp.eq.f32 p, %0, 0f46400000;\n@p bra HL;\n}" :: "f"(hd[0] + hd[2] + hd[4]));
        wg_wait<0>();
        pin<24>(ka);
        float kk[6];
        const bool up = w4 >= 2;
        #pragma unroll
        for (int n = 0; n < 3; n++) {
          sts64f(xa + n * BLK, up ? ka[12 + 4 * n] : ka[4 * n + 2], up ? ka[13 + 4 * n] : ka[4 * n + 3]);
          kk[2 * n] = up ? ka[14 + 4 * n] : ka[4 * n]; kk[2 * n + 1] = up ? ka[15 + 4 * n] : ka[4 * n + 1];
        }
        if (it) bar_sync(4, 128); else bar_sync(8, 160);
          if (it == 4 && w4 == 0) {
            mbar_wait(BAR(BR_U), 0);
            if (elect_one()) {
              mbar_expect_tx(BAR(BR_U2), 8192);
              bulk_ld(blk - 2 * BLK, g_uy + (c * 80 + r * 5 + 2) * 2048, 4096, BAR(BR_U2)); bulk_ld(blk - BLK, g_uy + (c * 80 + r * 5 + 3) * 2048, 4096, BAR(BR_U2));
            }
            __syncwarp();
          }
        #pragma unroll
        for (int n = 0; n < 3; n++) {
          uint32_t o[2]; lds64(o, xr_ + n * BLK);
          kk[2 * n] = (kk[2 * n] + __uint_as_float(o[0])) * fac; kk[2 * n + 1] = (kk[2 * n + 1] + __uint_as_float(o[1])) * fac;
        }
        if (t7 == 0) kk[0] += dsk;
        {
          const uint32_t v = pack2(kk[1], kk[0]), vh = v >> 16;
          const uint32_t u = pack2(kk[2], kk[3]), w = pack2(kk[4], kk[5]), uu = pack2(kk[2], kk[2]), us = pack2(kk[3], kk[2]);
          const uint32_t x = tq < 2 ? w : u, xh = x >> 16;
          sts32(blk + e0 + 4, v); sts16(blk + e0, vh); sts16(blk + e0 + 10, v);
          sts16(blk + e1, x); sts16(blk + e1 + 6, x); sts16(blk + e2, xh); sts16(blk + e2 + 6, xh);
          if (tq < 2) {
            const uint32_t pb = blk + e0 + 1024 + 8 * tq;
            sts32(pb + 4, uu); sts32(pb + 8, us); sts16(pb + 14, us);
            if (i2) { sts16(pb - 4, u); sts32(pb, uu); }
          }
          if (i2 == 0) {
            const uint32_t tb = blk + B_TBL;
            if (tq == 0) { sts16(tb + (16 + 256) * 4, u); sts16(tb + (T_S + 3) * 4, w); sts32(tb + (T_S + 4) * 4, pack2(kk[4], kk[4])); sts16(tb + (T_S + 5) * 4 + 2, w); }
            else { sts32(tb + 528 * 4, uu); sts32(tb + 529 * 4, uu); sts32(tb + 530 * 4, uu); sts16(tb + 531 * 4 + 2, u); sts16(tb + (T_F3 + 80 + 63) * 4, w); }
          }
        }
        if (t7 == 0) TS(49 + it);
      }
    }
    asm volatile("setmaxnreg.inc.sync.aligned.u32 136;");
    if (t7 == 0) TS(41);
    bar_sync(4, 128);
    if (t7 == 0) mbar_arrive(BAR(BR_KS));
    if (EN_ATT) mbar_wait(BAR(BR_GEMM), 0);
    }
  }
  const int tid = rtid(), lane = tid & 31, g = lane >> 2, tq = lane & 3, t7 = tid & 127;
  mbar_wait(BAR(BR_EPOCH), 0);
  const unsigned epoch = lds32(sb + OFF_EPOCH);
  const uint32_t ytag = (epoch & 1u) * 0x10001u, ym = lane < 4 ? 0x10001u : 0u;
  if (EN_SSM && wg != 1) {
    mbar_wait(BAR(BR_KS), 0);
    mbar_wait(BAR(BR_U), 0);
    if (tid == 256) TS(42);
    {
      const int pass = wg >> 1;
      const int k = pass ? w4 : 4;
      if (k & 2) mbar_wait(BAR(BR_U2), 0);
      const uint32_t blk = sb + OFF_BLK + k * BLK, tb = blk + B_TBL + (uint32_t)((g - 2 * tq) * 4);
      float acc[16][4];
      zero<64>(&acc[0][0]);
      const int kl = 16 * (lane >> 4) + 2 * (lane & 7) + ((lane >> 3) & 1);
      {
        auto ubase = [&](int sh) { const int q = kl - 2 * sh; return blk + (uint32_t)((q * 16) ^ ((q * 2) & 0x10)); };
#define LDQ(A, sh) _Pragma("unroll") for (int m = 0; m < 4; m++) load_quad(A[m], tb + (16 + 16 * (sh) + 128 * m) * 4);
#define LDB(B, ub, h) _Pragma("unroll") for (int p = 0; p < 4; p++) ldsm4(B[p], (ub) + (4 * (h) + p) * 512);
#define MLO(A, B) _Pragma("unroll") for (int m = 0; m < 4; m++) _Pragma("unroll") for (int cc = 0; cc < 8; cc++) mma16816(acc[cc + m], A[m], &B[cc >> 1][(cc & 1) * 2]);
#define MHI(A, B) _Pragma("unroll") for (int m = 0; m < 4; m++) _Pragma("unroll") for (int cc = 0; cc < 8 - m; cc++) mma16816(acc[8 + cc + m], A[m], &B[cc >> 1][(cc & 1) * 2]);
        int p_ = pass ? 0 : w4;
        const int pe = pass ? 4 : w4 + 1;
        uint32_t A[4][4], A2[4][4], Bl[4][4], Bh[4][4];
        uint32_t ub = ubase(p_ + 4);
        LDQ(A, p_ + 4) LDB(Bl, ub, 0)
        #pragma unroll 1
        for (; p_ < pe; p_++) {
          LDB(Bh, ub, 1)
          MLO(A, Bl)
          ub = ubase(p_);
          LDQ(A2, p_) LDB(Bl, ub, 0)
          MHI(A, Bh)
          LDB(Bh, ub, 1)
          load_quad(A[0], tb + (16 + 512 + 16 * (p_ & 1)) * 4); load_quad(A[1], tb + (T_S + 16 * (p_ & 1)) * 4);
          MLO(A2, Bl)
          if (p_ < 2) {
            #pragma unroll
            for (int cc = 0; cc < 8; cc++) mma16816(acc[cc + 4], A[0], &Bl[cc >> 1][(cc & 1) * 2]);
            #pragma unroll
            for (int cc = 0; cc < 4; cc++) mma16816(acc[cc + 12], A[0], &Bh[cc >> 1][(cc & 1) * 2]);
            #pragma unroll
            for (int cc = 0; cc < 8; cc++) mma16816(acc[cc + 8], A[1], &Bl[cc >> 1][(cc & 1) * 2]);
          }
          const int pn = ((p_ + 1) & 3) + 4;
          ub = ubase(pn);
          LDQ(A, pn) LDB(Bl, ub, 0)
          MHI(A2, Bh)
        }
      }
      if (t7 == 0) TS(pass ? 60 : 16);
      mbar_wait(BAR(BR_DRDY + 1), 0);
      {
        const int ih = (lane >> 3) & 1;
        const uint32_t dl = blk + B_D + (uint32_t)(((lane >> 4) * 8 + (lane & 7)) * 16);
        const uint32_t d0_ = dl + ih * 1552, d8_ = dl + (ih ? 0 : 1536), d3_ = dl + B_D7 + ih * 1024;
        auto cls2 = [&](uint32_t da, uint32_t ta) {
          uint32_t B[6][2], A[6][4];
          #pragma unroll
          for (int e = 0; e < 6; e++) { B[e][0] = lds32v(ta + (e + 4) * 32); B[e][1] = lds32v(ta + (e + 3) * 32); }
          #pragma unroll
          for (int kk = 0; kk < 6; kk++) ldsm4t(A[kk], da + kk * 256);
          #pragma unroll
          for (int e = 0; e < 6; e++)
            #pragma unroll
            for (int kk = 0; kk < 6; kk++) if (2 * kk + e + 4 < 16) mma16816(acc[2 * kk + e + 4], A[kk], B[e]);
        };
        auto cls3 = [&](uint32_t da, uint32_t ta) {
          uint32_t B[8][2], A[4][4];
          #pragma unroll
          for (int e = 0; e < 8; e++) { B[e][0] = lds32v(ta + (e + 8) * 32); B[e][1] = lds32v(ta + (e + 7) * 32); }
          #pragma unroll
          for (int kk = 0; kk < 4; kk++) ldsm4t(A[kk], da + kk * 256);
          #pragma unroll
          for (int kk = 0; kk < 4; kk++)
            #pragma unroll
            for (int e = 0; e < 8; e++) if (2 * kk + e + 8 < 16) mma16816(acc[2 * kk + e + 8], A[kk], B[e]);
        };
        if (pass) {
          #pragma unroll 1
          for (int a = 0; a < 2; a++) {
            cls2(d0_ + a * B_D5, tb + (T_F2 + 48 * a - 32) * 4);
            cls2(d8_ + a * B_D5, tb + (T_F2 + 48 * a + 64) * 4);
            cls3(d3_ + a * 2048, tb + (T_F3 + 80 * a - 64) * 4);
          }
        } else {
          cls2(((w4 & 2) ? d8_ : d0_) + (w4 & 1) * B_D5, tb + (T_F2 + 48 * w4 - 32) * 4);
          if (w4 >= 2) cls3(d3_ + (w4 - 2) * 2048, tb + (T_F3 + 80 * (w4 - 2) - 64) * 4);
        }
      }
      if (t7 == 0) TS(pass ? 61 : 17);
      const uint32_t ya = (pass ? sb + OFF_BLK + 3 * BLK + w4 * 4096 : blk) + (uint32_t)((kl * 16) ^ ((kl * 2) & 0x10));
#define YTAG(v) (((v) & ~ym) | (ytag & ym))
#define STY(p) stsm4t(ya + (p) * 512, YTAG(pack2(acc[2 * (p)][0], acc[2 * (p)][1])), pack2(acc[2 * (p)][2], acc[2 * (p)][3]), \
                      YTAG(pack2(acc[2 * (p) + 1][0], acc[2 * (p) + 1][1])), pack2(acc[2 * (p) + 1][2], acc[2 * (p) + 1][3]))
      if (pass == 0) {
        const uint32_t xw = blk + 4096 + w4 * 4096 + lane * 16, xr = blk + 4096 + w4 * 1024 + lane * 16;
        #pragma unroll
        for (int h = 0; h < 2; h++) {
          bar_sync(2, 128);
          #pragma unroll
          for (int i = 0; i < 8; i++)
            sts128(xw + i * 512, __float_as_uint(acc[8 * h + i][0]), __float_as_uint(acc[8 * h + i][1]), __float_as_uint(acc[8 * h + i][2]), __float_as_uint(acc[8 * h + i][3]));
          bar_sync(2, 128);
          float y[8];
          #pragma unroll
          for (int i = 0; i < 8; i++) {
            uint32_t o[4]; lds128(o, xr + (i >> 1) * 4096 + (i & 1) * 512);
            #pragma unroll
            for (int e = 0; e < 4; e++) y[4 * (i & 1) + e] = i < 2 ? __uint_as_float(o[e]) : y[4 * (i & 1) + e] + __uint_as_float(o[e]);
          }
          stsm4t(ya + (4 * h + w4) * 512, YTAG(pack2(y[0], y[1])), pack2(y[2], y[3]), YTAG(pack2(y[4], y[5])), pack2(y[6], y[7]));
        }
      } else {
        fence_async();
        bar_sync(4, 128);
        if (t7 == 0) mbar_arrive(BAR(BR_KS + 1));
        #pragma unroll
        for (int p = 0; p < 8; p++) STY(p);
      }
      fence_async();
      __syncwarp();
      if (lane == 0) mbar_arrive(BAR(BR_Y + 1) - 8 * pass);
      if (t7 == 0) TS(pass ? 62 : 18);
    }
  }
  if (wg < 2) {
    if (EN_ATT) {
    float oc[40]; zero<40>(oc);
    {
      constexpr uint64_t dw0 = mkdesc(SB0, OFF_WOR, 1024, 1), da0 = mkdesc(SB0, 2048, 128, 0);
      const uint32_t ck = sb + tid * 32 + ((lane >> 2) << 2), ck2 = ck + (wg ? 0 : 16384);
      uint32_t bad = 0;
      auto tile = [&](int i, uint32_t so) {
        const uint32_t al = (uint32_t)da0 + wg * 64 + (so >> 4), wl = (uint32_t)dw0 + i * 640 - (i >> 1) * (1278 << 16);
        wg_fence();
        #pragma unroll
        for (int s = 0; s < 5; s++) wg_ss80_tb(oc, desc2(al + s * 256, da0 >> 32), desc2(wl + s * 128, dw0 >> 32), (i | s) != 0);
        wg_commit();
        bad |= (lds32(ck + so) ^ epoch) | (lds32(ck + so + 8192) ^ epoch) | (lds32(ck2 + so) ^ epoch);
      };
      if (w4 == 0) {
        if (EN_SSM) mbar_wait(BAR(BR_Y), 0);
        mbar_wait(BAR(BR_WO), 0);
        mbar_wait(BAR(BR_WO + 1), 0);
      }
      bar_sync(1, 256);
      if (tid == 0) TS(9);
      tile(0, SLOT(0));
      #pragma unroll 1
      for (int i = 1; i < 8; i++) {
        mbar_wait(BAR(BR_OFULL) + 8 * i, 0);
        tile(i, SLOT(i));
        wg_wait<1>();
        if (lane == 0) mbar_arrive(BAR(BR_OEMPTY - 1) + 8 * i);
      }
      #pragma unroll 1
      for (int n = 0; n < 56; n++) {
        const int i = n & 7;
        if (i == 0) {
          uint32_t any;
          asm volatile("{\n.reg .pred p;\nsetp.ne.u32 p, %1, 0;\nbarrier.red.or.pred p, 1, 256, p;\nselp.u32 %0, 1, 0, p;\n}" : "=r"(any) : "r"(bad & 1u) : "memory");
          if (!any) break;
          bad = 0;
          FIXCNT
        }
        wg_wait<0>();
        bar_sync(1, 256);
        if (tid == 0) { mbar_expect_tx(BAR(BR_RETRY), 20480); bulk_ld(sb + SLOT(5), &g_o[(r * 8 + CHUNK(i)) * 1280], 20480, BAR(BR_RETRY)); }
        mbar_wait(BAR(BR_RETRY), n & 1);
        tile(i, SLOT(5));
      }
      wg_wait<0>();
      pin<40>(oc);
    }
    if (tid == 0) TS(10);
    {
      const int row = w4 * 16 + (lane & 15);
      const uint32_t ob = sb + OFF_BLK + 3 * BLK + wg * 10240;
      #pragma unroll
      for (int j = 0; j < 8; j += 2)
        stsm4(ob + row * 128 + (((j + (lane >> 4)) ^ (row & 7)) << 4), pack2(oc[4 * j], oc[4 * j + 1]), pack2(oc[4 * j + 2], oc[4 * j + 3]),
              pack2(oc[4 * j + 4], oc[4 * j + 5]), pack2(oc[4 * j + 6], oc[4 * j + 7]));
      stsm4(ob + 8192 + row * 32 + (lane >> 4) * 16, pack2(oc[32], oc[33]), pack2(oc[34], oc[35]), pack2(oc[36], oc[37]), pack2(oc[38], oc[39]));
      fence_async();
      bar_sync(2 + wg, 128);
      if (w4 == 0 && elect_one()) {
        tma2d_st(&prm.m[M_O64], ob, 640 + c * 64, r * 128 + wg * 64);
        tma2d_st(&prm.m[M_O16], ob + 8192, 1152 + c * 16, r * 128 + wg * 64);
        bulk_commit(); bulk_wait0_read();
        if (wg == 0) { TS(11); DUMP(0, 20); }
      }
    }
    }
  } else if (EN_SSM) {
    if (t7 == 0) DUMP(40, 64);
    #pragma unroll 1
    for (int n = 0; n < 64; n++) if (!y_transpose(sb, w4, lane, ytag)) break;
  }
  }
}

typedef CUresult (*EncFn)(CUtensorMap*, CUtensorMapDataType, cuuint32_t, void*, const cuuint64_t*, const cuuint64_t*, const cuuint32_t*,
                          const cuuint32_t*, CUtensorMapInterleave, CUtensorMapSwizzle, CUtensorMapL2promotion, CUtensorMapFloatOOBfill);
static void mkmap(EncFn enc, CUtensorMap* m, const void* base, int rank, const cuuint64_t* dims, const cuuint64_t* strides, const cuuint32_t* box, CUtensorMapSwizzle swz) {
  cuuint32_t es[5] = {1, 1, 1, 1, 1};
  enc(m, CU_TENSOR_MAP_DATA_TYPE_BFLOAT16, rank, const_cast<void*>(base), dims, strides, box, es, CU_TENSOR_MAP_INTERLEAVE_NONE, swz,
      CU_TENSOR_MAP_L2_PROMOTION_L2_128B, CU_TENSOR_MAP_FLOAT_OOB_FILL_NONE);
}

extern "C" void kernel_launch(void* const* d_in, const int* in_sizes, int n_in, void* d_out, int out_size) {
  void* fn = nullptr; cudaDriverEntryPointQueryResult qr;
  cudaGetDriverEntryPoint("cuTensorMapEncodeTiled", &fn, cudaEnableDefault, &qr);
  EncFn enc = (EncFn)fn;
  void* uy = nullptr; cudaGetSymbolAddress(&uy, g_uy);
  const cuuint64_t dx[2] = {640, 2048}, sx[1] = {1280};
  const cuuint32_t bx[2] = {64, 128}, bu[2] = {80, 128};
  const cuuint64_t dw[3] = {640, 640, 3}, sw[2] = {3840, 1280};
  const cuuint32_t br[3] = {16, 32, 3};
  const cuuint64_t dwa[4] = {64, 640, 10, 3}, swa[3] = {3840, 128, 1280}, dwb[4] = {32, 640, 20, 3}, swb[3] = {3840, 64, 1280};
  const cuuint32_t bwa[4] = {64, 32, 1, 3}, bwb[4] = {32, 32, 2, 3};
  const cuuint64_t dwo[2] = {640, 640};
  const cuuint32_t bwo[2] = {64, 80}, bo64[2] = {64, 64}, bo16[2] = {16, 64};
  const cuuint64_t dsa[2] = {2048, 1280}, ssa[1] = {4096};
  const cuuint32_t bsa[2] = {64, 80};
  const cuuint64_t dout[2] = {1280, 2048}, sout[1] = {2560};
  Params prm;
  mkmap(enc, &prm.m[M_X], d_in[7], 2, dx, sx, bx, CU_TENSOR_MAP_SWIZZLE_128B);
  mkmap(enc, &prm.m[M_W128], d_in[8], 4, dwa, swa, bwa, CU_TENSOR_MAP_SWIZZLE_128B);
  mkmap(enc, &prm.m[M_W64], d_in[8], 4, dwb, swb, bwb, CU_TENSOR_MAP_SWIZZLE_64B);
  mkmap(enc, &prm.m[M_WR], d_in[8], 3, dw, sw, br, CU_TENSOR_MAP_SWIZZLE_32B);
  mkmap(enc, &prm.m[M_U], d_in[0], 2, dx, sx, bu, CU_TENSOR_MAP_SWIZZLE_NONE);
  mkmap(enc, &prm.m[M_WO], d_in[9], 2, dwo, sx, bwo, CU_TENSOR_MAP_SWIZZLE_128B);
  mkmap(enc, &prm.m[M_O64], d_out, 2, dout, sout, bo64, CU_TENSOR_MAP_SWIZZLE_128B);
  mkmap(enc, &prm.m[M_O16], d_out, 2, dout, sout, bo16, CU_TENSOR_MAP_SWIZZLE_NONE);
  mkmap(enc, &prm.m[M_SA], uy, 2, dsa, ssa, bsa, CU_TENSOR_MAP_SWIZZLE_128B);
  mkmap(enc, &prm.m[M_OUT], d_out, 2, dout, sout, bu, CU_TENSOR_MAP_SWIZZLE_NONE);
  prm.u = (const __nv_bfloat16*)d_in[0]; prm.wo = (const __nv_bfloat16*)d_in[9];
  for (int i = 0; i < 4; i++) prm.par[i] = (const __nv_bfloat16*)d_in[1 + i];
  prm.logdt = (const __nv_bfloat16*)d_in[5]; prm.dskip = (const __nv_bfloat16*)d_in[6];
  cudaFuncSetAttribute(fused_kernel, cudaFuncAttributeMaxDynamicSharedMemorySize, SMEM_BYTES);
  cudaLaunchConfig_t cfg = {};
  cfg.gridDim = dim3(128); cfg.blockDim = dim3(512); cfg.dynamicSmemBytes = SMEM_BYTES; cfg.stream = cudaStreamPerThread;
  cudaLaunchAttribute at[1];
  at[0].id = cudaLaunchAttributeClusterDimension; at[0].val.clusterDim.x = 2; at[0].val.clusterDim.y = 1; at[0].val.clusterDim.z = 1;
  cfg.attrs = at; cfg.numAttrs = 1;
  cudaLaunchKernelEx(&cfg, fused_kernel, prm);
}
```

```cpp
#include <cuda_runtime.h>
#include <cuda_bf16.h>
#include <cuda_fp16.h>
#include <cuda.h>
#include <stdint.h>

#define KST 2
#define UKB 4
#define UPF 0
#define CONV_AT 1
#define EN_ATT 1
#define EN_SSM 1

__device__ __align__(1024) __nv_bfloat16 g_uy[2 * 640 * 2048];
__device__ __align__(128) uint4 g_kvp[8 * 16 * 240];
__device__ __align__(128) uint4 g_o[128 * 1280];
__device__ __align__(128) unsigned g_flag[4 * 128 * 32];
__device__ unsigned g_epoch[128];
#define TS(i) do {} while (0)
#define DUMP(lo, hi) do {} while (0)
#define FIXCNT

constexpr uint32_t SB0 = 1024;
constexpr uint32_t W_SLOT = 15360, OFF_X = 76800;
constexpr uint32_t OFF_WOR = 81920, OFF_KVP = 10240, OFF_KVS = 71680, OFF_PK = 10240, OFF_V = 30720, OFF_EXTRA = 102400, OFF_KVB = OFF_EXTRA;
constexpr uint32_t OFF_BAR = 125952, OFF_BLK = 128000, BLK = 20480;
constexpr uint32_t B_D = 4096, B_D5 = 3088, B_D7 = 6176, B_D9 = 8224, B_TBL = 14400;
constexpr int T_S = 576, T_F2 = 624, T_F3 = 816;
constexpr uint32_t OFF_UT = OFF_BLK + 4 * BLK;
constexpr uint32_t SMEM_BYTES = OFF_BLK + 5 * BLK;
enum { BR_FULL = 0, BR_WO = 5, BR_PUB = 7, BR_KVP = 8, BR_U = 9, BR_SUM = 10, BR_GEMM = 11, BR_UIN = 12, BR_YIN = 13, BR_EPOCH = 14,
       BR_FREE = 15, BR_RETRY = 17, BR_UOUT = 18, BR_OFULL = 18, BR_KS = 26, BR_EMPTY = 31, BR_OEMPTY = 36, BR_Y = 43, BR_OSTG = 45,
       BR_DRDY = 46, BR_U2 = 48, BR_PAIR = 49, BR_COUNT = 56 };
constexpr uint32_t OFF_EPOCH = OFF_BAR + 8 * BR_COUNT;
enum { M_X, M_W128, M_W64, M_WR, M_U, M_WO, M_O64, M_O16, M_SA, M_OUT, M_COUNT };

__device__ __forceinline__ long long clk64() { long long t; asm volatile("mov.u64 %0, %%clock64;" : "=l"(t) :: "memory"); return t; }
__device__ __forceinline__ uint32_t smem_u32(const void* p) { return (uint32_t)__cvta_generic_to_shared(p); }
__host__ __device__ constexpr uint64_t mkdesc(uint32_t addr, uint32_t lbo, uint32_t sbo, uint32_t swz) {
  return (uint64_t)((addr & 0x3FFFF) >> 4) | ((uint64_t)(lbo >> 4) << 16) | ((uint64_t)(sbo >> 4) << 32) | ((uint64_t)swz << 62);
}
__device__ __forceinline__ uint64_t desc2(uint32_t lo, uint32_t hi) { uint64_t d; asm("mov.b64 %0, {%1, %2};" : "=l"(d) : "r"(lo), "r"(hi)); return d; }
__device__ __forceinline__ void mbar_init(uint32_t bar, uint32_t cnt) { asm volatile("mbarrier.init.shared::cta.b64 [%0], %1;" :: "r"(bar), "r"(cnt) : "memory"); }
__device__ __forceinline__ void mbar_expect_tx(uint32_t bar, uint32_t bytes) { asm volatile("mbarrier.arrive.expect_tx.shared::cta.b64 _, [%0], %1;" :: "r"(bar), "r"(bytes) : "memory"); }
__device__ __forceinline__ void mbar_arrive(uint32_t bar) { asm volatile("mbarrier.arrive.shared::cta.b64 _, [%0];" :: "r"(bar) : "memory"); }
__device__ __forceinline__ void mbar_wait(uint32_t bar, uint32_t parity) {
  asm volatile("{\n.reg .pred p;\n.reg .u32 c;\nmov.u32 c, 0;\n"
    "WL:\nmbarrier.try_wait.parity.shared::cta.b64 p, [%0], %1;\n@p bra WD;\n"
    "add.u32 c, c, 1;\nsetp.lt.u32 p, c, 200000;\n@p bra WL;\nWD:\n}" :: "r"(bar), "r"(parity) : "memory");
}
__device__ __forceinline__ void poll_all(const unsigned* p, unsigned val) {
  asm volatile("{\n.reg .pred p;\n.reg .u32 c, v;\nmov.u32 c, 0;\n"
    "PL:\nld.relaxed.gpu.global.u32 v, [%0];\nsetp.eq.u32 p, v, %1;\nvote.sync.all.pred p, p, 0xffffffff;\n@p bra PD;\n"
    "add.u32 c, c, 1;\nsetp.lt.u32 p, c, 100000;\n@p bra PL;\nPD:\n}" :: "l"(p), "r"(val) : "memory");
}
__device__ __forceinline__ void poll_all_acq(const unsigned* p, unsigned val) {
  asm volatile("{\n.reg .pred p;\n.reg .u32 c, v;\nmov.u32 c, 0;\n"
    "PL:\nld.acquire.gpu.global.u32 v, [%0];\nsetp.eq.u32 p, v, %1;\nvote.sync.all.pred p, p, 0xffffffff;\n@p bra PD;\n"
    "nanosleep.u32 300;\nadd.u32 c, c, 1;\nsetp.lt.u32 p, c, 100000;\n@p bra PL;\nPD:\n}" :: "l"(p), "r"(val) : "memory");
}
__device__ __forceinline__ unsigned poll_bit(const unsigned* p, unsigned val, unsigned mask) {
  unsigned bal;
  asm volatile("{\n.reg .pred p;\n.reg .u32 c, v;\nmov.u32 c, 0;\n"
    "PL:\nld.relaxed.gpu.global.u32 v, [%1];\nsetp.eq.u32 p, v, %2;\nvote.sync.ballot.b32 %0, p, 0xffffffff;\n"
    "and.b32 v, %0, %3;\nsetp.ne.u32 p, v, 0;\n@p bra PD;\n"
    "add.u32 c, c, 1;\nsetp.lt.u32 p, c, 100000;\n@p bra PL;\nPD:\n}" : "=&r"(bal) : "l"(p), "r"(val), "r"(mask) : "memory");
  return bal;
}
__device__ __forceinline__ void fix128_w0(uint32_t* v, const void* p, uint32_t tag, uint32_t mask) {
  asm volatile("{\n.reg .pred p;\n.reg .u32 c, x;\n.reg .b128 t;\n.reg .b64 lo, hi;\nmov.u32 c, 0;\n"
    "FL:\nxor.b32 x, %0, %5;\nand.b32 x, x, %6;\nsetp.eq.u32 p, x, 0;\n@p bra FD;\n"
    "ld.relaxed.gpu.global.b128 t, [%4];\nmov.b128 {lo, hi}, t;\nmov.b64 {%0, %1}, lo;\nmov.b64 {%2, %3}, hi;\n"
    "add.u32 c, c, 1;\nsetp.lt.u32 p, c, 100000;\n@p bra FL;\nFD:\n}"
    : "+r"(v[0]), "+r"(v[1]), "+r"(v[2]), "+r"(v[3]) : "l"(p), "r"(tag), "r"(mask) : "memory");
}
__device__ __forceinline__ void fix128_w3(uint32_t* v, const void* p, uint32_t tag, uint32_t mask) {
  asm volatile("{\n.reg .pred p;\n.reg .u32 c, x;\n.reg .b128 t;\n.reg .b64 lo, hi;\nmov.u32 c, 0;\n"
    "FL:\nxor.b32 x, %3, %5;\nand.b32 x, x, %6;\nsetp.eq.u32 p, x, 0;\n@p bra FD;\n"
    "ld.relaxed.gpu.global.b128 t, [%4];\nmov.b128 {lo, hi}, t;\nmov.b64 {%0, %1}, lo;\nmov.b64 {%2, %3}, hi;\n"
    "add.u32 c, c, 1;\nsetp.lt.u32 p, c, 100000;\n@p bra FL;\nFD:\n}"
    : "+r"(v[0]), "+r"(v[1]), "+r"(v[2]), "+r"(v[3]) : "l"(p), "r"(tag), "r"(mask) : "memory");
}
__device__ __forceinline__ void fence_acq() { asm volatile("fence.acq_rel.gpu;" ::: "memory"); }
__device__ __forceinline__ bool elect_one() {
  uint32_t p; asm volatile("{\n.reg .pred P;\nelect.sync _|P, 0xffffffff;\nselp.u32 %0, 1, 0, P;\n}" : "=r"(p)); return p;
}
__device__ __forceinline__ void bar_sync(int id, int n) { asm volatile("bar.sync %0, %1;" :: "r"(id), "r"(n) : "memory"); }
__device__ __forceinline__ void fence_async() { asm volatile("fence.proxy.async.shared::cta;" ::: "memory"); }
__device__ __forceinline__ void fence_async_g() { asm volatile("fence.proxy.async.global;" ::: "memory"); }
__device__ __forceinline__ void tma2d(uint32_t dst, const CUtensorMap* m, uint32_t bar, int c0, int c1) {
  asm volatile("cp.async.bulk.tensor.2d.shared::cluster.global.mbarrier::complete_tx::bytes [%0], [%1, {%3, %4}], [%2];"
    :: "r"(dst), "l"(m), "r"(bar), "r"(c0), "r"(c1) : "memory");
}
__device__ __forceinline__ void tma3d(uint32_t dst, const CUtensorMap* m, uint32_t bar, int c0, int c1, int c2) {
  asm volatile("cp.async.bulk.tensor.3d.shared::cluster.global.mbarrier::complete_tx::bytes [%0], [%1, {%3, %4, %5}], [%2];"
    :: "r"(dst), "l"(m), "r"(bar), "r"(c0), "r"(c1), "r"(c2) : "memory");
}
__device__ __forceinline__ void tma4d(uint32_t dst, const CUtensorMap* m, uint32_t bar, int c0, int c1, int c2, int c3) {
  asm volatile("cp.async.bulk.tensor.4d.shared::cluster.global.mbarrier::complete_tx::bytes [%0], [%1, {%3, %4, %5, %6}], [%2];"
    :: "r"(dst), "l"(m), "r"(bar), "r"(c0), "r"(c1), "r"(c2), "r"(c3) : "memory");
}
__device__ __forceinline__ void tma2d_st(const CUtensorMap* m, uint32_t src, int c0, int c1) {
  asm volatile("cp.async.bulk.tensor.2d.global.shared::cta.bulk_group [%0, {%2, %3}], [%1];"
    :: "l"(m), "r"(src), "r"(c0), "r"(c1) : "memory");
}
__device__ __forceinline__ void bulk_ld(uint32_t dst, const void* src, uint32_t bytes, uint32_t bar) {
  asm volatile("cp.async.bulk.shared::cluster.global.mbarrier::complete_tx::bytes [%0], [%1], %2, [%3];"
    :: "r"(dst), "l"(src), "r"(bytes), "r"(bar) : "memory");
}
__device__ __forceinline__ void bulk_ld_mc(uint32_t dst, const void* src, uint32_t bytes, uint32_t bar) {
  asm volatile("cp.async.bulk.shared::cluster.global.mbarrier::complete_tx::bytes.multicast::cluster [%0], [%1], %2, [%3], %4;"
    :: "r"(dst), "l"(src), "r"(bytes), "r"(bar), "h"((uint16_t)3) : "memory");
}
__device__ __forceinline__ void mbar_arrive_peer(uint32_t bar, uint32_t rank) {
  asm volatile("{\n.reg .b32 ra;\nmapa.shared::cluster.u32 ra, %0, %1;\nmbarrier.arrive.relaxed.cluster.shared::cluster.b64 _, [ra];\n}" :: "r"(bar), "r"(rank) : "memory");
}
__device__ __forceinline__ void bulk_st(void* dst, uint32_t src, uint32_t bytes) {
  asm volatile("cp.async.bulk.global.shared::cta.bulk_group [%0], [%1], %2;" :: "l"(dst), "r"(src), "r"(bytes) : "memory");
}
__device__ __forceinline__ void bulk_commit() { asm volatile("cp.async.bulk.commit_group;" ::: "memory"); }
__device__ __forceinline__ void bulk_wait0() { asm volatile("cp.async.bulk.wait_group 0;" ::: "memory"); }
__device__ __forceinline__ void bulk_wait0_read() { asm volatile("cp.async.bulk.wait_group.read 0;" ::: "memory"); }
__device__ __forceinline__ unsigned ld_rlx(const unsigned* p) { unsigned v; asm volatile("ld.relaxed.gpu.global.u32 %0, [%1];" : "=r"(v) : "l"(p) : "memory"); return v; }
__device__ __forceinline__ unsigned ld_acq(const unsigned* p) { unsigned v; asm volatile("ld.acquire.gpu.global.u32 %0, [%1];" : "=r"(v) : "l"(p) : "memory"); return v; }
__device__ __forceinline__ void st_rlx(unsigned* p, unsigned v) { asm volatile("st.relaxed.gpu.global.u32 [%0], %1;" :: "l"(p), "r"(v) : "memory"); }
__device__ __forceinline__ void st_rel(unsigned* p, unsigned v) { asm volatile("st.release.gpu.global.u32 [%0], %1;" :: "l"(p), "r"(v) : "memory"); }
__device__ __forceinline__ void ld128_rlx(uint32_t* v, const void* p) {
  asm volatile("{\n.reg .b128 t;\n.reg .b64 lo, hi;\nld.relaxed.gpu.global.b128 t, [%4];\nmov.b128 {lo, hi}, t;\n"
    "mov.b64 {%0, %1}, lo;\nmov.b64 {%2, %3}, hi;\n}" : "=r"(v[0]), "=r"(v[1]), "=r"(v[2]), "=r"(v[3]) : "l"(p) : "memory");
}
__device__ __forceinline__ void st128_rlx(void* p, const uint32_t* v) {
  asm volatile("{\n.reg .b128 t;\n.reg .b64 lo, hi;\nmov.b64 lo, {%1, %2};\nmov.b64 hi, {%3, %4};\nmov.b128 t, {lo, hi};\n"
    "st.relaxed.gpu.global.b128 [%0], t;\n}" :: "l"(p), "r"(v[0]), "r"(v[1]), "r"(v[2]), "r"(v[3]) : "memory");
}
__device__ __forceinline__ uint32_t lds32(uint32_t a) { uint32_t v; asm volatile("ld.shared.u32 %0, [%1];" : "=r"(v) : "r"(a) : "memory"); return v; }
__device__ __forceinline__ uint32_t lds32v(uint32_t a) { uint32_t v; asm volatile("ld.volatile.shared.u32 %0, [%1];" : "=r"(v) : "r"(a) : "memory"); return v; }
__device__ __forceinline__ uint32_t cpa(uint32_t a, uint32_t one) { uint32_t v; asm volatile("mul.lo.u32 %0, %1, %2;" : "=r"(v) : "r"(a), "r"(one)); return v; }
__device__ __forceinline__ uint32_t cpb(uint32_t a, uint32_t zero) { uint32_t v; asm volatile("or.b32 %0, %1, %2;" : "=r"(v) : "r"(a), "r"(zero)); return v; }
__device__ __forceinline__ uint32_t lds16(uint32_t a) { uint16_t v; asm volatile("ld.shared.u16 %0, [%1];" : "=h"(v) : "r"(a) : "memory"); return v; }
__device__ __forceinline__ float ldsf(uint32_t a) { float v; asm volatile("ld.shared.f32 %0, [%1];" : "=f"(v) : "r"(a) : "memory"); return v; }
__device__ __forceinline__ void lds128(uint32_t* v, uint32_t a) { asm volatile("ld.shared.v4.u32 {%0,%1,%2,%3}, [%4];" : "=r"(v[0]), "=r"(v[1]), "=r"(v[2]), "=r"(v[3]) : "r"(a) : "memory"); }
__device__ __forceinline__ void sts32(uint32_t a, uint32_t v) { asm volatile("st.shared.u32 [%0], %1;" :: "r"(a), "r"(v) : "memory"); }
__device__ __forceinline__ void sts16(uint32_t a, uint32_t v) { asm volatile("st.shared.u16 [%0], %1;" :: "r"(a), "h"((uint16_t)v) : "memory"); }
__device__ __forceinline__ void sts64f(uint32_t a, float x, float y) { asm volatile("st.shared.v2.f32 [%0], {%1,%2};" :: "r"(a), "f"(x), "f"(y) : "memory"); }
__device__ __forceinline__ void sts128(uint32_t a, uint32_t x, uint32_t y, uint32_t z, uint32_t w) { asm volatile("st.shared.v4.u32 [%0], {%1,%2,%3,%4};" :: "r"(a), "r"(x), "r"(y), "r"(z), "r"(w) : "memory"); }
__device__ __forceinline__ void stsm4(uint32_t a, uint32_t r0, uint32_t r1, uint32_t r2, uint32_t r3) {
  asm volatile("stmatrix.sync.aligned.m8n8.x4.shared.b16 [%0], {%1,%2,%3,%4};" :: "r"(a), "r"(r0), "r"(r1), "r"(r2), "r"(r3) : "memory");
}
__device__ __forceinline__ void stsm4t(uint32_t a, uint32_t r0, uint32_t r1, uint32_t r2, uint32_t r3) {
  asm volatile("stmatrix.sync.aligned.m8n8.x4.trans.shared.b16 [%0], {%1,%2,%3,%4};" :: "r"(a), "r"(r0), "r"(r1), "r"(r2), "r"(r3) : "memory");
}
__device__ __forceinline__ void ldsm4t(uint32_t* r, uint32_t a) {
  asm volatile("ldmatrix.sync.aligned.m8n8.x4.trans.shared.b16 {%0,%1,%2,%3}, [%4];" : "=r"(r[0]), "=r"(r[1]), "=r"(r[2]), "=r"(r[3]) : "r"(a) : "memory");
}
__device__ __forceinline__ void ldsm4(uint32_t* r, uint32_t a) {
  asm volatile("ldmatrix.sync.aligned.m8n8.x4.shared.b16 {%0,%1,%2,%3}, [%4];" : "=r"(r[0]), "=r"(r[1]), "=r"(r[2]), "=r"(r[3]) : "r"(a) : "memory");
}
__device__ __forceinline__ void mma16816(float* d, const uint32_t* a, const uint32_t* b) {
  asm volatile("mma.sync.aligned.m16n8k16.row.col.f32.bf16.bf16.f32 {%0,%1,%2,%3}, {%4,%5,%6,%7}, {%8,%9}, {%0,%1,%2,%3};"
    : "+f"(d[0]), "+f"(d[1]), "+f"(d[2]), "+f"(d[3]) : "r"(a[0]), "r"(a[1]), "r"(a[2]), "r"(a[3]), "r"(b[0]), "r"(b[1]));
}
__device__ __forceinline__ uint32_t pack2(float lo, float hi) { uint32_t r; asm("cvt.rn.bf16x2.f32 %0, %1, %2;" : "=r"(r) : "f"(hi), "f"(lo)); return r; }
__device__ __forceinline__ uint32_t packh(float lo, float hi) { uint32_t r; asm("cvt.rn.f16x2.f32 %0, %1, %2;" : "=r"(r) : "f"(hi), "f"(lo)); return r; }
__device__ __forceinline__ uint32_t hcmul(uint32_t x, uint32_t zp, uint32_t zq) {
  const __half2 xx = *reinterpret_cast<__half2*>(&x);
  const __half2 r = __hfma2(__high2half2(xx), *reinterpret_cast<__half2*>(&zq), __hmul2(__low2half2(xx), *reinterpret_cast<__half2*>(&zp)));
  return *reinterpret_cast<const uint32_t*>(&r);
}
__device__ __forceinline__ void hcm2(uint32_t xr, uint32_t xi, uint32_t z, uint32_t& pr, uint32_t& pi) {
  const __half2 a = *reinterpret_cast<__half2*>(&xr), b = *reinterpret_cast<__half2*>(&xi), zz = *reinterpret_cast<__half2*>(&z);
  const __half2 re = __hfma2(__hneg2(b), __high2half2(zz), __hmul2(a, __low2half2(zz)));
  const __half2 im = __hfma2(a, __high2half2(zz), __hmul2(b, __low2half2(zz)));
  pr = *reinterpret_cast<const uint32_t*>(&re); pi = *reinterpret_cast<const uint32_t*>(&im);
}
__device__ __forceinline__ void sts64(uint32_t a, uint32_t x, uint32_t y) { asm volatile("st.shared.v2.u32 [%0], {%1,%2};" :: "r"(a), "r"(x), "r"(y) : "memory"); }
__device__ __forceinline__ void lds64(uint32_t* v, uint32_t a) { asm volatile("ld.shared.v2.u32 {%0,%1}, [%2];" : "=r"(v[0]), "=r"(v[1]) : "r"(a) : "memory"); }
__device__ __forceinline__ float bf_lo(uint32_t v) { return __uint_as_float(v << 16); }
__device__ __forceinline__ float bf_hi(uint32_t v) { return __uint_as_float(v & 0xffff0000u); }
__device__ __forceinline__ float bf_round(float x) { return bf_lo(pack2(x, 0.f)); }
__device__ __forceinline__ float ex2(float x) { float r; asm("ex2.approx.ftz.f32 %0, %1;" : "=f"(r) : "f"(x)); return r; }
__device__ __forceinline__ float phi(float t, float l2e = 1.44269504089f) {
  float e = ex2(t * l2e) + 1e-6f;
  asm("{\n.reg .pred p;\nsetp.gt.f32 p, %1, 0f00000000;\n@p add.f32 %0, %1, 0f3F800008;\n}" : "+f"(e) : "f"(t));
  return e;
}
__device__ __forceinline__ void wg_fence() { asm volatile("wgmma.fence.sync.aligned;" ::: "memory"); }
__device__ __forceinline__ void wg_commit() { asm volatile("wgmma.commit_group.sync.aligned;" ::: "memory"); }
template <int N> __device__ __forceinline__ void wg_wait() { asm volatile("wgmma.wait_group.sync.aligned %0;" :: "n"(N) : "memory"); }
template <int N> __device__ __forceinline__ void pin(float* a) {
  #pragma unroll
  for (int i = 0; i < N; i++) asm volatile("" : "+f"(a[i]) :: "memory");
}
__device__ __forceinline__ int rtid() { int t; asm volatile("mov.u32 %0, %%tid.x;" : "=r"(t)); return t; }
__device__ __forceinline__ int opaque(int v) { asm volatile("" : "+r"(v)); return v; }
template <int N> __device__ __forceinline__ void zero(float* a) {
  #pragma unroll
  for (int i = 0; i < N; i++) asm volatile("mov.b32 %0, 0;" : "=f"(a[i]));
}
template <int N> __device__ __forceinline__ void pinu(uint32_t* a) {
  #pragma unroll
  for (int i = 0; i < N; i++) asm volatile("" : "+r"(a[i]) :: "memory");
}
__device__ __forceinline__ void cexp_t(float lg2mag, float turns, float& re, float& im) {
  float m = ex2(lg2mag);
  float fr = (turns - __fadd_rn(__fadd_rn(turns, 12582912.f), -12582912.f)) * 6.283185307f;
  re = m * __cosf(fr); im = m * __sinf(fr);
}
__device__ __forceinline__ void cmul(float ar, float ai, float br, float bi, float& cr, float& ci) {
  cr = fmaf(ar, br, -ai * bi); ci = fmaf(ar, bi, ai * br);
}

__device__ __forceinline__ void wg_ss48_tt(float* d, uint64_t da, uint64_t db, int scale_d) {
  asm volatile("{\n.reg .pred p;\nsetp.ne.b32 p, %26, 0;\n"
    "wgmma.mma_async.sync.aligned.m64n48k16.f32.bf16.bf16 "
    "{%0, %1, %2, %3, %4, %5, %6, %7, %8, %9, %10, %11, %12, %13, %14, %15, %16, %17, %18, %19, %20, %21, %22, %23}, %24, %25, p, 1, 1, 1, 1;\n}\n"
    : "+f"(d[0]), "+f"(d[1]), "+f"(d[2]), "+f"(d[3]), "+f"(d[4]), "+f"(d[5]), "+f"(d[6]), "+f"(d[7]), "+f"(d[8]), "+f"(d[9]), "+f"(d[10]), "+f"(d[11]), "+f"(d[12]), "+f"(d[13]), "+f"(d[14]), "+f"(d[15]), "+f"(d[16]), "+f"(d[17]), "+f"(d[18]), "+f"(d[19]), "+f"(d[20]), "+f"(d[21]), "+f"(d[22]), "+f"(d[23])
    : "l"(da), "l"(db), "r"(scale_d));
}
__device__ __forceinline__ void wg_rs88_tb(float* d, const uint32_t* a, uint64_t db, int scale_d) {
  asm volatile("{\n.reg .pred p;\nsetp.ne.b32 p, %49, 0;\n"
    "wgmma.mma_async.sync.aligned.m64n88k16.f32.bf16.bf16 "
    "{%0, %1, %2, %3, %4, %5, %6, %7, %8, %9, %10, %11, %12, %13, %14, %15, %16, %17, %18, %19, %20, %21, %22, %23, %24, %25, %26, %27, %28, %29, %30, %31, %32, %33, %34, %35, %36, %37, %38, %39, %40, %41, %42, %43}, {%44, %45, %46, %47}, %48, p, 1, 1, 1;\n}\n"
    : "+f"(d[0]), "+f"(d[1]), "+f"(d[2]), "+f"(d[3]), "+f"(d[4]), "+f"(d[5]), "+f"(d[6]), "+f"(d[7]), "+f"(d[8]), "+f"(d[9]), "+f"(d[10]), "+f"(d[11]), "+f"(d[12]), "+f"(d[13]), "+f"(d[14]), "+f"(d[15]), "+f"(d[16]), "+f"(d[17]), "+f"(d[18]), "+f"(d[19]), "+f"(d[20]), "+f"(d[21]), "+f"(d[22]), "+f"(d[23]), "+f"(d[24]), "+f"(d[25]), "+f"(d[26]), "+f"(d[27]), "+f"(d[28]), "+f"(d[29]), "+f"(d[30]), "+f"(d[31]), "+f"(d[32]), "+f"(d[33]), "+f"(d[34]), "+f"(d[35]), "+f"(d[36]), "+f"(d[37]), "+f"(d[38]), "+f"(d[39]), "+f"(d[40]), "+f"(d[41]), "+f"(d[42]), "+f"(d[43])
    : "r"(a[0]), "r"(a[1]), "r"(a[2]), "r"(a[3]), "l"(db), "r"(scale_d));
}
__device__ __forceinline__ void wg_ss80_tb(float* d, uint64_t da, uint64_t db, int scale_d) {
  asm volatile("{\n.reg .pred p;\nsetp.ne.b32 p, %42, 0;\n"
    "wgmma.mma_async.sync.aligned.m64n80k16.f32.bf16.bf16 "
    "{%0, %1, %2, %3, %4, %5, %6, %7, %8, %9, %10, %11, %12, %13, %14, %15, %16, %17, %18, %19, %20, %21, %22, %23, %24, %25, %26, %27, %28, %29, %30, %31, %32, %33, %34, %35, %36, %37, %38, %39}, %40, %41, p, 1, 1, 0, 1;\n}\n"
    : "+f"(d[0]), "+f"(d[1]), "+f"(d[2]), "+f"(d[3]), "+f"(d[4]), "+f"(d[5]), "+f"(d[6]), "+f"(d[7]), "+f"(d[8]), "+f"(d[9]), "+f"(d[10]), "+f"(d[11]), "+f"(d[12]), "+f"(d[13]), "+f"(d[14]), "+f"(d[15]), "+f"(d[16]), "+f"(d[17]), "+f"(d[18]), "+f"(d[19]), "+f"(d[20]), "+f"(d[21]), "+f"(d[22]), "+f"(d[23]), "+f"(d[24]), "+f"(d[25]), "+f"(d[26]), "+f"(d[27]), "+f"(d[28]), "+f"(d[29]), "+f"(d[30]), "+f"(d[31]), "+f"(d[32]), "+f"(d[33]), "+f"(d[34]), "+f"(d[35]), "+f"(d[36]), "+f"(d[37]), "+f"(d[38]), "+f"(d[39])
    : "l"(da), "l"(db), "r"(scale_d));
}
__device__ __forceinline__ void wg_ss48_tt_h(float* d, uint64_t da, uint64_t db, int scale_d) {
  asm volatile("{\n.reg .pred p;\nsetp.ne.b32 p, %26, 0;\n"
    "wgmma.mma_async.sync.aligned.m64n48k16.f32.f16.f16 "
    "{%0, %1, %2, %3, %4, %5, %6, %7, %8, %9, %10, %11, %12, %13, %14, %15, %16, %17, %18, %19, %20, %21, %22, %23}, %24, %25, p, 1, 1, 1, 1;\n}\n"
    : "+f"(d[0]), "+f"(d[1]), "+f"(d[2]), "+f"(d[3]), "+f"(d[4]), "+f"(d[5]), "+f"(d[6]), "+f"(d[7]), "+f"(d[8]), "+f"(d[9]), "+f"(d[10]), "+f"(d[11]), "+f"(d[12]), "+f"(d[13]), "+f"(d[14]), "+f"(d[15]), "+f"(d[16]), "+f"(d[17]), "+f"(d[18]), "+f"(d[19]), "+f"(d[20]), "+f"(d[21]), "+f"(d[22]), "+f"(d[23])
    : "l"(da), "l"(db), "r"(scale_d));
}
__device__ __forceinline__ void wg_rs192_tb(float* d, const uint32_t* a, uint64_t db, int scale_d) {
  asm volatile("{\n.reg .pred p;\nsetp.ne.b32 p, %101, 0;\n"
    "wgmma.mma_async.sync.aligned.m64n192k16.f32.bf16.bf16 "
    "{%0, %1, %2, %3, %4, %5, %6, %7, %8, %9, %10, %11, %12, %13, %14, %15, %16, %17, %18, %19, %20, %21, %22, %23, %24, %25, %26, %27, %28, %29, %30, %31, %32, %33, %34, %35, %36, %37, %38, %39, %40, %41, %42, %43, %44, %45, %46, %47, %48, %49, %50, %51, %52, %53, %54, %55, %56, %57, %58, %59, %60, %61, %62, %63, %64, %65, %66, %67, %68, %69, %70, %71, %72, %73, %74, %75, %76, %77, %78, %79, %80, %81, %82, %83, %84, %85, %86, %87, %88, %89, %90, %91, %92, %93, %94, %95}, {%96, %97, %98, %99}, %100, p, 1, 1, 1;\n}\n"
    : "+f"(d[0]), "+f"(d[1]), "+f"(d[2]), "+f"(d[3]), "+f"(d[4]), "+f"(d[5]), "+f"(d[6]), "+f"(d[7]), "+f"(d[8]), "+f"(d[9]), "+f"(d[10]), "+f"(d[11]), "+f"(d[12]), "+f"(d[13]), "+f"(d[14]), "+f"(d[15]), "+f"(d[16]), "+f"(d[17]), "+f"(d[18]), "+f"(d[19]), "+f"(d[20]), "+f"(d[21]), "+f"(d[22]), "+f"(d[23]), "+f"(d[24]), "+f"(d[25]), "+f"(d[26]), "+f"(d[27]), "+f"(d[28]), "+f"(d[29]), "+f"(d[30]), "+f"(d[31]), "+f"(d[32]), "+f"(d[33]), "+f"(d[34]), "+f"(d[35]), "+f"(d[36]), "+f"(d[37]), "+f"(d[38]), "+f"(d[39]), "+f"(d[40]), "+f"(d[41]), "+f"(d[42]), "+f"(d[43]), "+f"(d[44]), "+f"(d[45]), "+f"(d[46]), "+f"(d[47]), "+f"(d[48]), "+f"(d[49]), "+f"(d[50]), "+f"(d[51]), "+f"(d[52]), "+f"(d[53]), "+f"(d[54]), "+f"(d[55]), "+f"(d[56]), "+f"(d[57]), "+f"(d[58]), "+f"(d[59]), "+f"(d[60]), "+f"(d[61]), "+f"(d[62]), "+f"(d[63]), "+f"(d[64]), "+f"(d[65]), "+f"(d[66]), "+f"(d[67]), "+f"(d[68]), "+f"(d[69]), "+f"(d[70]), "+f"(d[71]), "+f"(d[72]), "+f"(d[73]), "+f"(d[74]), "+f"(d[75]), "+f"(d[76]), "+f"(d[77]), "+f"(d[78]), "+f"(d[79]), "+f"(d[80]), "+f"(d[81]), "+f"(d[82]), "+f"(d[83]), "+f"(d[84]), "+f"(d[85]), "+f"(d[86]), "+f"(d[87]), "+f"(d[88]), "+f"(d[89]), "+f"(d[90]), "+f"(d[91]), "+f"(d[92]), "+f"(d[93]), "+f"(d[94]), "+f"(d[95])
    : "r"(a[0]), "r"(a[1]), "r"(a[2]), "r"(a[3]), "l"(db), "r"(scale_d));
}
__device__ __forceinline__ void wg_rs48_tb(float* d, const uint32_t* a, uint64_t db, int scale_d) {
  asm volatile("{\n.reg .pred p;\nsetp.ne.b32 p, %29, 0;\n"
    "wgmma.mma_async.sync.aligned.m64n48k16.f32.bf16.bf16 "
    "{%0, %1, %2, %3, %4, %5, %6, %7, %8, %9, %10, %11, %12, %13, %14, %15, %16, %17, %18, %19, %20, %21, %22, %23}, {%24, %25, %26, %27}, %28, p, 1, 1, 1;\n}\n"
    : "+f"(d[0]), "+f"(d[1]), "+f"(d[2]), "+f"(d[3]), "+f"(d[4]), "+f"(d[5]), "+f"(d[6]), "+f"(d[7]), "+f"(d[8]), "+f"(d[9]), "+f"(d[10]), "+f"(d[11]), "+f"(d[12]), "+f"(d[13]), "+f"(d[14]), "+f"(d[15]), "+f"(d[16]), "+f"(d[17]), "+f"(d[18]), "+f"(d[19]), "+f"(d[20]), "+f"(d[21]), "+f"(d[22]), "+f"(d[23])
    : "r"(a[0]), "r"(a[1]), "r"(a[2]), "r"(a[3]), "l"(db), "r"(scale_d));
}

struct Params {
  const __nv_bfloat16 *par[4], *logdt, *dskip, *u, *wo;
  CUtensorMap m[M_COUNT];
};

#define CHUNK(i) ((i) == 0 ? c : ((i) == 7 ? (c ^ 1) : (((c & 6) + 1 + (i)) & 7)))
#define CL_ARRIVE asm volatile("barrier.cluster.arrive.relaxed.aligned;" ::: "memory");
#define FLAG(kind, rr, cc) (&g_flag[((kind) * 128 + (rr) * 8 + (cc)) * 32])
#define SLOT(i) ((i) == 0 ? OFF_EXTRA : OFF_BLK - 256 + ((i) > 5 ? (i) - 6 : (i) - 1) * BLK)
__device__ __forceinline__ void load_quad(uint32_t* A, uint32_t addr) {
  A[0] = lds32v(addr); A[1] = lds32v(addr + 32); A[2] = lds32v(addr - 32); A[3] = lds32v(addr);
}

__device__ __forceinline__ bool y_transpose(uint32_t sb, int w5, int lane, uint32_t ytag) {
  const int mi = lane >> 3, rw = lane & 7;
  const uint32_t sa = sb + OFF_EXTRA + (w5 * 16 + rw) * 128 + ((mi ^ rw) << 4), da = sb + SLOT(3) + (8 * mi + rw) * 160 + w5 * 32;
  const uint32_t ym = lane < 4 ? 0x10001u : 0u;
  bar_sync(7, 160);
  uint32_t v[8][4], bad = 0;
  #pragma unroll
  for (int q = 0; q < 8; q++) ldsm4t(v[q], (sa ^ ((q & 1) * 64 + ((q >> 1) & 1) * 16)) + ((q >> 1) & 1) * 10240 + (q >> 2) * 1024);
  #pragma unroll
  for (int q = 0; q < 8; q++) {
    bad |= (v[q][0] ^ ytag) | (v[q][2] ^ ytag);
    stsm4(da + (q & 3) * 5120 + (q >> 2) * 16, v[q][0] & ~ym, v[q][1], v[q][2] & ~ym, v[q][3]);
  }
  fence_async();
  uint32_t any;
  asm volatile("{\n.reg .pred p;\nsetp.ne.u32 p, %1, 0;\nbarrier.red.or.pred p, 7, 160, p;\nselp.u32 %0, 1, 0, p;\n}" : "=r"(any) : "r"(bad & ym) : "memory");
  return any;
}

__global__ void __launch_bounds__(512, 1) fused_kernel(const __grid_constant__ Params prm) {
  extern __shared__ unsigned char smem_raw[];
  const uint32_t sb = __shfl_sync(0xffffffff, smem_u32(smem_raw), 0);
  const int tid = threadIdx.x, lane = tid & 31;
  const int warp = __shfl_sync(0xffffffff, tid >> 5, 0), wg = warp >> 2, w4 = warp & 3;
  const int cta = blockIdx.x, r = cta >> 3, c = cta & 7;
  if ((sb & 0xffffffu) != SB0) return;
#define BAR(i) (sb + OFF_BAR + 8 * (i))
  const bool sw64 = ((c + 1) & 2) != 0;

  const CUtensorMap* mwp = &prm.m[sw64 ? M_W64 : M_W128];
  const int mcol = (c * 80 + (c & 1) * 16) >> (sw64 ? 5 : 6), rcol = c * 80 + ((c & 1) ? 0 : 64);
  if (warp == 12 && elect_one()) {
    #pragma unroll
    for (int i = 0; i < 5; i++) mbar_init(BAR(BR_FULL + i), 1);
    asm volatile("fence.mbarrier_init.release.cluster;" ::: "memory");
    if (EN_ATT) {
      mbar_expect_tx(BAR(BR_FULL), W_SLOT + 16384);
      tma4d(sb, mwp, BAR(BR_FULL), 0, 0, mcol, 0);
      tma2d(sb + OFF_X, &prm.m[M_X], BAR(BR_FULL), 0, r * 128);
      tma3d(sb + 12288, &prm.m[M_WR], BAR(BR_FULL), rcol, 0, 0);
      mbar_expect_tx(BAR(BR_FULL + 1), W_SLOT);
      tma4d(sb + W_SLOT, mwp, BAR(BR_FULL + 1), 0, 32, mcol, 0);
      tma3d(sb + W_SLOT + 12288, &prm.m[M_WR], BAR(BR_FULL + 1), rcol, 32, 0);
      TS(24);
    }
  }
  if (warp == 13 && elect_one()) {
    asm volatile("prefetch.tensormap [%0];" :: "l"(&prm.m[M_X]) : "memory");
    asm volatile("prefetch.tensormap [%0];" :: "l"(&prm.m[M_WR]) : "memory");
  }
  if (wg == 3) {
    asm volatile("setmaxnreg.dec.sync.aligned.u32 56;");
    const int tid = rtid(), lane = tid & 31;
    if (warp == 12) {
      asm volatile("bar.arrive 0, 512;" ::: "memory");
      CL_ARRIVE
      {
        uint32_t s = 2, ph = 1, xs = 16384;
        #pragma unroll 1
        for (int kb = 2; kb < 20; kb++) {
          if (kb == 4) bar_sync(6, 128);
          if (kb >= 5) mbar_wait(BAR(BR_EMPTY) + 8 * s, ph);
          if (EN_ATT && elect_one()) {
            const uint32_t st = sb + s * W_SLOT, fb = BAR(BR_FULL) + 8 * s;
            mbar_expect_tx(fb, (kb & 1) ? W_SLOT : W_SLOT + 16384);
            if (!(kb & 1)) tma2d(sb + OFF_X + xs, &prm.m[M_X], fb, kb * 32, r * 128);
            tma4d(st, mwp, fb, 0, kb * 32, mcol, 0);
            tma3d(st + 12288, &prm.m[M_WR], fb, rcol, kb * 32, 0);
          }
          if (kb < 4 && lane == 0) TS(24 + kb);
          if (UPF && kb >= UKB - 4 && kb < UKB && elect_one())
            asm volatile("cp.async.bulk.prefetch.L2.global [%0], 5120;" :: "l"(prm.u + cta * 10240 + (kb - (UKB - 4)) * 2560) : "memory");
          if (EN_SSM && kb == (EN_ATT ? UKB : 4) && elect_one()) { mbar_expect_tx(BAR(BR_UIN), 20480); tma2d(sb + OFF_UT, &prm.m[M_U], BAR(BR_UIN), c * 80, r * 128); }
          if (kb == 14 && elect_one()) asm volatile("cp.async.bulk.prefetch.L2.global [%0], 6400;" :: "l"(prm.wo + cta * 3200) : "memory");
          if (!EN_ATT && kb == 4) break;
          if (++s == 5) { s = 0; ph ^= 1; }
          if (kb & 1) { xs += 16384; if (xs == 49152) xs = 0; }
        }
      }
      if (EN_ATT) {
      mbar_wait(BAR(BR_EPOCH), 0);
      const unsigned epoch = lds32(sb + OFF_EPOCH);
      const unsigned* fo = FLAG(3, r, lane & 7);
      unsigned seen = __ballot_sync(0xffffffff, ld_rlx(lane < 16 ? fo : FLAG(0, lane & 15, c)) == epoch) & 0xffu;
      asm volatile("barrier.cluster.wait.aligned;" ::: "memory");
      mbar_wait(BAR(BR_GEMM), 0);
      if (elect_one()) {
        mbar_expect_tx(BAR(BR_WO), 10240);
        tma2d(sb, &prm.m[M_WO], BAR(BR_WO), c * 64, c * 80);
        mbar_expect_tx(BAR(BR_KVP), 61440);
        mbar_expect_tx(BAR(BR_WO + 1), 7 * 10240);
      }
      {
        uint32_t ds = sb + OFF_WOR + (lane >> 3) * 128 + (((lane & 7) ^ (lane >> 3)) << 4);
        #pragma unroll 1
        for (int h = 0; h < 2; h++) {
          const int i = (lane & 6) + h;
          const char* gs = reinterpret_cast<const char*>(prm.wo) + (size_t)((lane >> 3) + CHUNK(i) * 80) * 1280 + 1024 + c * 32 + (lane & 1) * 16;
          #pragma unroll 2
          for (int q = 0; q < 20; q++) {
            asm volatile("cp.async.cg.shared.global [%0], [%1], 16;" :: "r"(ds), "l"(gs) : "memory");
            ds = (ds + 512) ^ 64; gs += 5120;
          }
        }
      }
      mbar_wait(BAR(BR_PUB), 0);
      poll_all(FLAG(0, lane & 15, c), epoch);
      if (elect_one()) { TS(23); bulk_ld(sb + OFF_KVP, &g_kvp[c * 16 * 240], 61440, BAR(BR_KVP)); }
      asm volatile("cp.async.wait_all;" ::: "memory");
      fence_async();
      mbar_arrive(BAR(BR_WO));
      mbar_wait(BAR(BR_SUM), 0);
      if (elect_one()) {
        #pragma unroll 1
        for (int i = 1; i < 8; i++) tma2d(sb + i * 10240, &prm.m[M_WO], BAR(BR_WO + 1), c * 64, CHUNK(i) * 80);
      }
      mbar_wait(BAR(BR_OSTG), 0);
      if (elect_one()) {
        bulk_st(&g_o[cta * 1280], sb + OFF_EXTRA, 20480);
        bulk_commit();
        bulk_wait0();
        st_rlx(FLAG(3, r, c), epoch);
        mbar_arrive(BAR(BR_OEMPTY));
        TS(20);
      }
      __syncwarp();
      #pragma unroll 1
      for (int i = 1; i < 8; i++) {
        const int src = CHUNK(i);
        if (i > 5) mbar_wait(BAR(BR_OEMPTY - 5) + 8 * i, 0);
        else if (EN_SSM && i != 2 && i != 3) mbar_wait(i == 1 ? BAR(BR_KS + 1) : BAR(BR_FREE - 4) + 8 * i, 0);
        if (i < 7 && lane < 2) mbar_arrive_peer(BAR(BR_PAIR) + 8 * i, lane);
        if (!((seen >> src) & 1)) seen = poll_bit(fo, epoch, 1u << src);
        if (i < 7) mbar_wait(BAR(BR_PAIR) + 8 * i, 0);
        if (elect_one()) {
          mbar_expect_tx(BAR(BR_OFULL) + 8 * i, 20480);
          if (i < 7) bulk_ld_mc(sb + SLOT(i) + (c & 1) * 10240, &g_o[(r * 8 + src) * 1280 + (c & 1) * 640], 10240, BAR(BR_OFULL) + 8 * i);
          else bulk_ld(sb + SLOT(i), &g_o[(r * 8 + src) * 1280], 20480, BAR(BR_OFULL) + 8 * i);
          if (i == 1) TS(21);
          if (i == 7) TS(22);
        }
        __syncwarp();
      }
      if (lane == 0) { DUMP(20, 30); }
      }
    } else {
      const int hw = warp - 13, ht = tid - 416;
      if (hw == 2 && elect_one()) {
        #pragma unroll
        for (int i = 5; i < BR_COUNT; i++) mbar_init(BAR(i), i == BR_WO ? 33 : i == BR_OEMPTY ? 9 : i < BR_EMPTY ? 1 : i < BR_OEMPTY ? 2 : i < BR_Y ? 8 : i < BR_OSTG ? 4 : i == BR_OSTG ? 8 : i < BR_U2 ? 3 : i == BR_U2 ? 1 : 2);
        asm volatile("fence.mbarrier_init.release.cluster;" ::: "memory");
      }
      __syncwarp();
      asm volatile("bar.arrive 0, 512;" ::: "memory");
      CL_ARRIVE
      if (EN_SSM && hw == 2) asm volatile("bar.arrive 8, 160;" ::: "memory");
      const unsigned epoch = hw == 0 ? ld_rlx(&g_epoch[cta]) + 1 : 0;
      bar_sync(5, 96);
      asm volatile("bar.arrive 6, 128;" ::: "memory");
      if (hw == 1 && elect_one()) {
        #pragma unroll
        for (int i = M_U; i < M_COUNT; i++) asm volatile("prefetch.tensormap [%0];" :: "l"(&prm.m[i]) : "memory");
      }
      if (ht == 0) {
        st_rlx(&g_epoch[cta], epoch);
        sts32(sb + OFF_EPOCH, epoch);
        mbar_arrive(BAR(BR_EPOCH));
      }
      if (EN_SSM) {
      const int mi = lane >> 3, rw = lane & 7, ch0 = c * 80 + r * 5;
      mbar_wait(BAR(BR_UIN), 0);
      if (ht == 0) TS(36);
      #pragma unroll 1
      for (int h = 0; h < 2; h++) {
        const uint32_t sa = sb + OFF_UT + h * 10240 + (8 * mi + rw) * 160 + hw * 16, da = sb + OFF_UT + h * 10240 + (hw * 8 + rw) * 128 + ((mi ^ rw ^ h) << 4);
        uint32_t v[8][4];
        #pragma unroll
        for (int q = 0; q < 8; q++) if (q < 6 || hw == 0) ldsm4t(v[q], sa + (q & 1) * 5120 + (q >> 1) * 48);
        bar_sync(5, 96);
        #pragma unroll
        for (int q = 0; q < 8; q++) if (q < 6 || hw == 0) stsm4((da ^ ((q & 1) * 64)) + (q >> 1) * 3072, v[q][0], v[q][1], v[q][2], v[q][3]);
      }
      fence_async();
      bar_sync(5, 96);
      if (hw == 0) {
        if (elect_one()) {
          tma2d_st(&prm.m[M_SA], sb + OFF_UT, r * 128, c * 80);
          tma2d_st(&prm.m[M_SA], sb + OFF_UT + 10240, r * 128 + 64, c * 80);
          bulk_commit(); bulk_wait0_read();
          mbar_arrive(BAR(BR_UOUT));
          TS(37);
          bulk_wait0();
          st_rel(FLAG(1, r, c), epoch);
          TS(30);
        }
        __syncwarp();
        poll_all_acq(FLAG(1, lane & 15, c), epoch);
      }
      #pragma unroll 1
      for (int k = 0; k < 5; k++) {
        if (k == 0 || k == 3) {
          const int p = k != 0;
          if (hw == 0) {
            if (!p) {
              if (elect_one()) {
                fence_async_g();
                mbar_expect_tx(BAR(BR_U), 12288);
                #pragma unroll 1
                for (int q = 0; q < 3; q++) bulk_ld(sb + OFF_BLK + q * q * BLK, g_uy + (ch0 + q * q) * 2048, 4096, BAR(BR_U));
                TS(31);
              }
              __syncwarp();
            }
            mbar_wait(BAR(p ? BR_U2 : BR_U), 0);
          }
          bar_sync(5, 96);
        }
        const int l3 = (hw + k) % 3 * 32 + lane;
        const uint32_t blk = sb + OFF_BLK + ((0x32410 >> (4 * k)) & 7) * BLK, o = blk + B_D + l3 * 16;
        float P[34];
        P[0] = 0.f;
        #pragma unroll
        for (int q = 0; q < 5; q++) {
          const int ch = 2 * l3 - 3 + q;
          uint32_t v[4];
          lds128(v, blk + (uint32_t)((ch * 16) ^ ((ch * 2) & 0x10)));
          #pragma unroll
          for (int e = 0; e < 8; e++) {
            const int i = 8 * q + e - 4;
            if (i >= 0 && i < 33) P[i + 1] = P[i] + ((e & 1) ? bf_hi(v[e >> 1]) : bf_lo(v[e >> 1]));
          }
        }
#define WIN(lo, hi, e) (P[21 + (e) - (lo)] - P[20 + (e) - (hi)])
#define WIN8(lo, hi, b) pack2(WIN(lo, hi, b), WIN(lo, hi, b + 1)), pack2(WIN(lo, hi, b + 2), WIN(lo, hi, b + 3)), pack2(WIN(lo, hi, b + 4), WIN(lo, hi, b + 5)), pack2(WIN(lo, hi, b + 6), WIN(lo, hi, b + 7))
        if (l3 < 64) {
          sts128(o + B_D9, WIN8(12, 20, 0)); sts128(o + B_D9 + 1024, WIN8(12, 20, 8));
          sts128(o + B_D7, WIN8(5, 11, 0)); sts128(o + B_D7 + 1024, WIN8(5, 11, 8));
        }
        sts128(o + B_D5, WIN8(6, 10, 0)); sts128(o + B_D5 + 1552, WIN8(6, 10, 8));
        sts128(o, WIN8(3, 5, 0)); sts128(o + 1552, WIN8(3, 5, 8));
        if (l3 < 2) sts128(blk + B_D + l3 * B_D5 + 1536, 0, 0, 0, 0);
      }
      __syncwarp();
      if (lane == 0) mbar_arrive(BAR(BR_DRDY + 1));
      if (ht == 0) TS(32);
      if (hw == 0) {
        #pragma unroll 1
        for (int p = 0; p < 2; p++) {
          mbar_wait(BAR(BR_Y) + 8 * p, 0);
          if (elect_one()) {
            bulk_st(g_uy + (640 + ch0 + 4 * p) * 2048, sb + OFF_BLK + (3 + p) * BLK, p ? 4096 : 16384);
            bulk_commit(); bulk_wait0_read();
            mbar_arrive(BAR(BR_FREE) + 8 * p);
          }
          __syncwarp();
        }
        if (elect_one()) { bulk_wait0(); st_rlx(FLAG(2, r, c), epoch); TS(33); }
        __syncwarp();
        poll_all(FLAG(2, lane & 15, c), epoch);
        if (EN_ATT) mbar_wait(BAR(BR_OEMPTY), 0);
        #pragma unroll 1
        for (int n = 0; n < 64; n++) {
          if (elect_one()) {
            mbar_expect_tx(BAR(BR_YIN), 20480);
            tma2d(sb + OFF_EXTRA, &prm.m[M_SA], BAR(BR_YIN), r * 128, 640 + c * 80);
            tma2d(sb + OFF_EXTRA + 10240, &prm.m[M_SA], BAR(BR_YIN), r * 128 + 64, 640 + c * 80);
            TS(34);
          }
          __syncwarp();
          if (EN_ATT) mbar_wait(BAR(BR_OEMPTY + 3), 0);
          mbar_wait(BAR(BR_YIN), n & 1);
          if (lane == 0) TS(38);
          if (!y_transpose(sb, 4, lane, (epoch & 1u) * 0x10001u)) break;
          FIXCNT
        }
      if (elect_one()) {
        TS(39);
        tma2d_st(&prm.m[M_OUT], sb + SLOT(3), c * 80, r * 128);
        bulk_commit(); bulk_wait0_read();
        TS(35); DUMP(30, 40); DUMP(0, 1);
      }
      }
      }
    }
  } else {
  if (wg < 2) {
    CL_ARRIVE
    asm volatile("setmaxnreg.inc.sync.aligned.u32 160;");
    bar_sync(0, 512);
    if (EN_ATT) {
    float am[96], ar[24];
    {
      const bool lead = (rtid() & 127) == 0;
      constexpr uint64_t dr0 = mkdesc(SB0 + 12288, 1024, 256, 3);
      const uint64_t db0 = sw64 ? mkdesc(SB0, 2048, 512, 2) : mkdesc(SB0, 4096, 1024, 1);
      const uint32_t kst = sw64 ? 64 : 128, bh = db0 >> 32;
      uint32_t s = 0, ph = 0, xo = 0;
      const int ln = rtid() & 31;
      const uint32_t xa = sb + OFF_X + (warp * 16 + (ln & 15)) * 128 + (((ln >> 4) ^ (ln & 7)) << 4);
      uint32_t A[8];
      mbar_wait(BAR(BR_FULL), 0);
      if (lead && wg == 0) TS(1);
      ldsm4(A, xa); ldsm4(A + 4, xa ^ 32);
      wg_fence();
      wg_rs48_tb(ar, A, dr0, 0); wg_rs192_tb(am, A, db0, 0);
      wg_commit();
      #pragma unroll 1
      for (int kb = 1; kb < 20; kb++) {
        const uint32_t wp = s * (W_SLOT >> 4), eb = BAR(BR_EMPTY) + 8 * s;
        wg_fence();
        wg_rs48_tb(ar, A + 4, desc2((uint32_t)dr0 + wp + 32, dr0 >> 32), 1);
        wg_rs192_tb(am, A + 4, desc2((uint32_t)db0 + wp + kst, bh), 1);
        wg_commit();
        if (++s == 5) { s = 0; ph ^= 1; }
        if (!(kb & 1)) { xo += 16384; if (xo == 49152) xo = 0; }
        mbar_wait(BAR(BR_FULL) + 8 * s, ph);
        const uint32_t xk = (xa + xo) ^ ((kb & 1) * 64), wn = s * (W_SLOT >> 4);
        wg_wait<1>();
        ldsm4(A, xk);
        wg_fence();
        wg_rs48_tb(ar, A, desc2((uint32_t)dr0 + wn, dr0 >> 32), 1);
        wg_rs192_tb(am, A, desc2((uint32_t)db0 + wn, bh), 1);
        wg_commit();
        wg_wait<1>();
        ldsm4(A + 4, xk ^ 32);
        if (lead && kb < 16) mbar_arrive(eb);
      }
      wg_fence();
      wg_rs48_tb(ar, A + 4, dr0 + 4 * (W_SLOT >> 4) + 32, 1);
      wg_rs192_tb(am, A + 4, desc2((uint32_t)db0 + 4 * (W_SLOT >> 4) + kst, bh), 1);
      wg_commit();
      wg_wait<0>();
      pin<96>(am); pin<24>(ar);
    }
    const int tid = rtid(), lane = tid & 31, tq = lane & 3;
    if (tid == 0) TS(2);
#define QV(j, e) ((j) < 8 ? am[4 * (j) + (e)] : ar[4 * ((j) - 8) + (e)])
#define KV_(j, e) ((j) < 8 ? am[32 + 4 * (j) + (e)] : ar[8 + 4 * ((j) - 8) + (e)])
#define VV(j, e) ((j) < 8 ? am[64 + 4 * (j) + (e)] : ar[16 + 4 * ((j) - 8) + (e)])
    {
      bar_sync(1, 256);
      if (tid == 0) mbar_arrive(BAR(BR_GEMM));
      const uint32_t ro = sb + (uint32_t)((warp * 16 + (lane & 15)) * 16);
      const int l0 = 2 * (c & 1) + (lane >> 4);
      const uint32_t ones = (tq == 0) ? 0x00003f80u : 0u;
#define PV(j) pack2(VV(j, 0), VV(j, 1)), pack2(VV(j, 2), VV(j, 3))
#define PK(j) pack2(phi(KV_(j, 0)), phi(KV_(j, 1))), pack2(phi(KV_(j, 2)), phi(KV_(j, 3)))
      stsm4(ro + OFF_V + (5 + 6 * (lane >> 4)) * 2048, ones, ones, ones, ones);
      #pragma unroll
      for (int j = 0; j < 10; j += 2) {
        const int l = (j == 8 && (c & 1)) ? l0 - 2 : l0 + j;
        stsm4(ro + OFF_V + (l + (l >= 5)) * 2048, PV(j), PV(j + 1));
        stsm4(ro + OFF_PK + l * 2048, PK(j), PK(j + 1));
      }
    }
    fence_async();
    bar_sync(1, 256);
    if (tid == 0) TS(3);
    mbar_wait(BAR(BR_EPOCH), 0);
    const unsigned epoch = lds32(sb + OFF_EPOCH);
    {
      float kv[24]; zero<24>(kv);
      constexpr uint64_t da = mkdesc(SB0 + OFF_PK, 128, 2048, 0), db = mkdesc(SB0 + OFF_V, 128, 2048, 0);
      wg_fence();
      #pragma unroll
      for (int s = 0; s < 8; s++) wg_ss48_tt(kv, desc2((uint32_t)da + wg * 640 + s * 16, da >> 32), desc2((uint32_t)db + wg * 768 + s * 16, db >> 32), s != 0);
      wg_commit();
      wg_wait<0>();
      pin<24>(kv);
      if (tid == 0) TS(15);
      if (w4 < 3) {
        const uint32_t wb = sb + OFF_KVS + (wg * 3 + w4) * 1536 + (lane & 15) * 96;
        #pragma unroll
        for (int j = 0; j < 6; j += 2)
          stsm4(wb + (j + (lane >> 4)) * 16, pack2(kv[4 * j], kv[4 * j + 1]), pack2(kv[4 * j + 2], kv[4 * j + 3]),
                pack2(kv[4 * j + 4], kv[4 * j + 5]), pack2(kv[4 * j + 6], kv[4 * j + 7]));
        __syncwarp();
        const int dl = w4 * 16 + (lane & 15), hl = dl >= 20;
        uint32_t v[4], z[4];
        lds128(v, wb + (3 * hl + (lane >> 4)) * 16);
        lds64(z, wb + 32 + 8 * hl); z[2] = lds32(wb + 80); z[3] = epoch & 1u;
        if (dl < 40) {
          uint4* dst = &g_kvp[(c * 16 + r) * 240 + wg * 40 + dl];
          v[3] = (v[3] & ~1u) | z[3];
          st128_rlx(dst + (lane >> 4) * 80, v);
          if (lane < 16) st128_rlx(dst + 160, z);
        }
      }
    }
    bar_sync(1, 256);
    if (tid == 0) { st_rlx(FLAG(0, r, c), epoch); mbar_arrive(BAR(BR_PUB)); TS(4); }
    const int kvi = (tid >= 80) + (tid >= 160) + (tid >= 240), kd = tid - 80 * kvi;
    const int khd = kd / 20, kt0 = 5 * (khd >> 1) + 2 * (khd & 1);
    const uint32_t rb = sb + OFF_KVB + kd * 16;
    if (kvi < 3) {
      #pragma unroll 1
      for (int m = kvi; m < 7; m += 3) { const int q = kt0 + 3 + m; sts128(rb + (q >= 10 ? q - 10 : q) * 1280, 0, 0, 0, 0); }
    }
    uint32_t qa[20];
    {
      const float sc = 1.44269504089f + __uint_as_float(lds32(sb + OFF_EPOCH) ^ epoch);
      #pragma unroll
      for (int j = 0; j < 10; j++) { qa[2 * j] = pack2(phi(QV(j, 0), sc), phi(QV(j, 1), sc)); qa[2 * j + 1] = pack2(phi(QV(j, 2), sc), phi(QV(j, 3), sc)); }
    }
    if (tid == 0) TS(5);
    if (warp == 7) mbar_wait(BAR(BR_KVP), 0);
    bar_sync(1, 256);
    if (tid == 0) TS(6);
    if (kvi < 3) {
      float s[8];
      zero<8>(s);
      uint32_t bad = 0;
      #pragma unroll 4
      for (int i = 0; i < 16; i += 2) {
        uint32_t w[4], x[4];
        lds128(w, sb + OFF_KVP + tid * 16 + i * 3840); lds128(x, sb + OFF_KVP + tid * 16 + i * 3840 + 3840);
        bad |= (w[3] ^ epoch) | (x[3] ^ epoch);
        #pragma unroll
        for (int e = 0; e < 4; e++) {
          asm("add.rn.bf16x2 %0, %0, %1;" : "+r"(w[e]) : "r"(x[e]));
          s[2 * e] += bf_lo(w[e]); s[2 * e + 1] += bf_hi(w[e]);
        }
      }
      if (__builtin_expect(bad & 1u, 0)) {
        zero<8>(s);
        #pragma unroll 1
        for (int i = 0; i < 16; i++) {
          uint32_t w[4] = {0, 0, 0, ~epoch};
          fix128_w3(w, &g_kvp[(c * 16 + i) * 240 + tid], epoch, 1u);
          #pragma unroll
          for (int e = 0; e < 4; e++) { s[2 * e] += bf_lo(w[e]); s[2 * e + 1] += bf_hi(w[e]); }
        }
        FIXCNT
      }
      const uint32_t p0 = pack2(s[0], s[1]), p1 = pack2(s[2], s[3]), p2 = pack2(s[4], s[5]), p3 = pack2(s[6], s[7]);
      if (kvi < 2) sts128(rb + (kt0 + (khd & 1) + kvi) * 1280, p0, p1, p2, p3);
      else {
        const bool od = khd & 1;
        sts128(rb + (5 * (khd >> 1) + 2) * 1280, od ? 0u : p0, od ? 0u : p1, od ? p0 : 0u, od ? p1 : 0u);
        const uint32_t zz = (p2 & 0xffffu) << (16 * (khd & 1));
        sts128(rb + 10 * 1280, khd < 2 ? zz : 0u, khd < 2 ? 0u : zz, 0u, 0u);
      }
    }
    fence_async();
    bar_sync(1, 256);
    if (tid == 0) { mbar_arrive(BAR(BR_SUM)); TS(7); }
    {
      float oa[44]; zero<44>(oa);
      constexpr uint64_t db = mkdesc(SB0 + OFF_KVB, 128, 1280, 0);
      wg_fence();
      #pragma unroll
      for (int s = 0; s < 5; s++) wg_rs88_tb(oa, &qa[4 * s], desc2((uint32_t)db + ((s == 4 && (c & 1)) ? 0 : (s + (c & 1)) * 16), db >> 32), s != 0);
      wg_commit();
      wg_wait<0>();
      pin<44>(oa);
      if (tid == 0) TS(13);
      float rc[4], rd[2][4];
      #pragma unroll
      for (int e = 0; e < 4; e++) asm("rcp.approx.ftz.f32 %0, %1;" : "=f"(rc[e]) : "f"(oa[40 + e] + 1e-6f));
      #pragma unroll
      for (int h = 0; h < 4; h++) {
        rd[0][h] = __shfl_sync(0xffffffff, rc[h & 1], (lane & 28) | (h >> 1));
        rd[1][h] = __shfl_sync(0xffffffff, rc[2 + (h & 1)], (lane & 28) | (h >> 1));
      }
      #pragma unroll
      for (int j = 0; j < 10; j++) {
        #pragma unroll
        for (int h = 0; h < 2; h++) {
          float f;
          if (j == 2) f = tq < 2 ? rd[h][0] : rd[h][1];
          else if (j == 7) f = tq < 2 ? rd[h][2] : rd[h][3];
          else f = rd[h][(8 * j) / 20];
          qa[2 * j + h] = pack2(oa[4 * j + 2 * h] * f, oa[4 * j + 2 * h + 1] * f);
        }
      }
      const uint32_t m0 = (lane & 7) == ((2 * w4) & 7), m1 = (lane & 7) == 2 * w4 + 1;
      const uint32_t oa_ = sb + OFF_EXTRA + (lane >> 4) * 2048 + (warp * 16 + (lane & 15)) * 16;
      bar_sync(1, 256);
#define TAG(v, m) (((v) & ~(m)) | (epoch & (m)))
      #pragma unroll
      for (int s = 0; s < 5; s++) stsm4(oa_ + s * 4096, TAG(qa[4 * s], m0), TAG(qa[4 * s + 1], m1), TAG(qa[4 * s + 2], m0), TAG(qa[4 * s + 3], m1));
    }
    fence_async();
    __syncwarp();
    if (lane == 0) mbar_arrive(BAR(BR_OSTG));
    if (tid == 0) TS(8);
    }
    asm volatile("setmaxnreg.dec.sync.aligned.u32 136;");
  } else {
    const int g = lane >> 2, tq = lane & 3, t7 = tid & 127;
    uint32_t raw[5][4], pd;
    {
      const int ch = c * 80 + r * 5;
      #pragma unroll
      for (int e = 0; e < 4; e++) {
        const __nv_bfloat16* pp = prm.par[e] + ch * 128 + t7;
        #pragma unroll
        for (int q = 0; q < 5; q++) asm volatile("ld.global.nc.u16 %0, [%1];" : "=r"(raw[q][e]) : "l"(pp + q * 128));
      }
      asm volatile("ld.global.nc.u16 %0, [%1];" : "=r"(pd) : "l"(((lane & 8) ? prm.dskip : prm.logdt) + ch + min(lane & 7, 4)));
    }
    asm volatile("bar.arrive 0, 512;" ::: "memory");
    CL_ARRIVE
    if (EN_SSM) {
    {
      #pragma unroll 1
      for (int k = 0; k < 4; k++) {
        const uint32_t z = sb + OFF_BLK + k * BLK + t7 * 16;
        sts128(z + B_TBL, 0, 0, 0, 0); sts128(z + B_TBL + 2048, 0, 0, 0, 0);
      }
      if (t7 < 80) sts128(sb + OFF_BLK + (t7 >> 4) * BLK - 256 + (t7 & 15) * 16, 0, 0, 0, 0);
      const uint32_t ea = sb + OFF_BLK + (2 + (w4 & 1)) * BLK + (lane >> 4) * 7168 + ((lane >> 3) & 1) * 256 + (lane & 7) * 16 + (w4 >> 1) * 2048;
      constexpr uint64_t dE = mkdesc(SB0 + OFF_BLK + 2 * BLK, 128, 512, 0);
      const uint32_t xa = sb + OFF_BLK + 18560 + t7 * 8, xr_ = sb + OFF_BLK + 18560 + (t7 ^ 64) * 8;
      uint32_t pr[5][2];
      #pragma unroll
      for (int q = 0; q < 5; q++) {
        #pragma unroll
        for (int e = 0; e < 2; e++) pr[q][e] = raw[q][2 * e] | (raw[q][2 * e + 1] << 16);
        const uint32_t m = __reduce_max_sync(0xffffffff, max(raw[q][2] & 0x7fffu, raw[q][3] & 0x7fffu));
        if (lane == 0) sts32(sb + OFF_EPOCH + 64 + q * 16 + w4 * 4, m);
      }
      bar_sync(4, 128);
      if (t7 == 0) TS(40);
      const int j = (w4 & 1) * 16 + (w4 >> 1) * 8 + g, i2 = tq < 2 ? 64 * tq + j : 32 * (tq - 2) + j;
      const uint32_t e2 = B_TBL + 4 * (tq < 2 ? T_F3 + (((i2 - 1) & 1) ? 80 : 0) + ((i2 - 1) >> 1) + 16 : T_F2 + (i2 & 1) * 96 + (i2 >> 1));
      const uint32_t e1 = tq < 2 ? (i2 ? e2 - 64 : B_TBL + 4 * (T_F2 + 175)) : B_TBL + 4 * (i2 ? T_F2 + ((2 * i2 - 1) & 3) * 48 + ((2 * i2 - 1) >> 2) : 16 + 511);
      const uint32_t e0 = B_TBL + (16 + 8 * j + 2 * tq) * 4;
      const float dtl = bf_round(expf(bf_lo(pd)));
      float hd[9];
      auto head = [&](int q) {
        const uint32_t pa0 = pr[0][0], pc0 = pr[0][1];
        const float dt = __shfl_sync(0xffffffff, dtl, q);
        #pragma unroll
        for (int e = 0; e < 2; e++) { pr[0][e] = pr[1][e]; pr[1][e] = pr[2][e]; pr[2][e] = pr[3][e]; pr[3][e] = pr[4][e]; }
        uint32_t mm[4];
        lds128(mm, sb + OFF_EPOCH + 64 + q * 16);
        const uint32_t ex = min(max(max(max(mm[0], mm[1]), max(mm[2], mm[3])) >> 7, 1u), 253u);
        const float sc = __uint_as_float((254u - ex) << 23);
        const float lr = -bf_round(expf(bf_lo(pa0))) * dt * 1.44269504089f;
        const float tn = bf_hi(pa0) * dt * 0.15915494309f;
        cexp_t(lr, -tn, hd[0], hd[1]);
        cexp_t(lr * 8.f, tn * 8.f, hd[2], hd[3]);
        cexp_t(lr * 64.f, tn * 64.f, hd[4], hd[5]);
        hd[6] = bf_lo(pc0) * sc; hd[7] = -bf_hi(pc0) * sc;
        hd[8] = 2.f * dt * __uint_as_float(ex << 23);
      };
      head(0);
      #pragma unroll 1
      for (int it = 0; it < 5; it++) {
        const int k = it;
        const uint32_t blk = sb + OFF_BLK + k * BLK;
        float fac = 0.f;
        float ka[24]; zero<24>(ka);
        {
          if (it == 4) {
            mbar_wait(BAR(BR_UOUT), 0);
            sts128(sb + OFF_UT + B_TBL + t7 * 16, 0, 0, 0, 0); sts128(sb + OFF_UT + B_TBL + 2048 + t7 * 16, 0, 0, 0, 0);
          }
          const uint32_t ga = ea + 4096 - (w4 >> 1) * 512;
#define PUT4(i, a, b, c_, d) sts128(((i) < 8 ? ea + ((i) >> 1) * 512 : ga + (((i) - 8) >> 1) * 512) + ((i) & 1) * 128, a, b, c_, d)
          float z2r, z2i, z4r, z4i, xr[8], xi[8], gr[8], gi[8], wr[9], wi[9];
          const float z1r = hd[0], z1i = hd[1];
          xr[1] = hd[2]; xi[1] = hd[3]; wr[0] = hd[4]; wi[0] = hd[5];
          fac = hd[8];
          xr[0] = 1.f; xi[0] = 0.f;
          cmul(xr[1], xi[1], xr[1], xi[1], xr[2], xi[2]); cmul(xr[2], xi[2], xr[1], xi[1], xr[3], xi[3]);
          cmul(xr[2], xi[2], xr[2], xi[2], xr[4], xi[4]);
          #pragma unroll
          for (int b = 1; b < 4; b++) cmul(xr[4], xi[4], xr[b], xi[b], xr[4 + b], xi[4 + b]);
          cmul(wr[0], wi[0], wr[0], wi[0], wr[1], wi[1]); cmul(wr[1], wi[1], wr[0], wi[0], wr[2], wi[2]);
          cmul(wr[1], wi[1], wr[1], wi[1], wr[3], wi[3]); cmul(wr[3], wi[3], wr[3], wi[3], wr[4], wi[4]);
          cmul(wr[4], wi[4], wr[3], wi[3], wr[5], wi[5]); cmul(wr[4], wi[4], wr[4], wi[4], wr[6], wi[6]);
          cmul(wr[6], wi[6], wr[4], wi[4], wr[7], wi[7]); cmul(wr[6], wi[6], wr[6], wi[6], wr[8], wi[8]);
          uint32_t R[4], I[4], PR[4], PI[4];
          #pragma unroll
          for (int b = 0; b < 4; b++) { R[b] = packh(xr[2 * b], xr[2 * b + 1]); I[b] = packh(xi[2 * b], xi[2 * b + 1]); }
          PUT4(0, R[0], R[1], R[2], R[3]); PUT4(1, I[0], I[1], I[2], I[3]);
          #pragma unroll
          for (int i = 0; i < 3; i++) {
            const uint32_t z = packh(wr[i], wi[i]);
            #pragma unroll
            for (int b = 0; b < 4; b++) hcm2(R[b], I[b], z, PR[b], PI[b]);
            PUT4(2 * i + 2, PR[0], PR[1], PR[2], PR[3]); PUT4(2 * i + 3, PI[0], PI[1], PI[2], PI[3]);
          }
          gr[0] = hd[6]; gi[0] = hd[7];
          cmul(z1r, z1i, z1r, z1i, z2r, z2i); cmul(z2r, z2i, z2r, z2i, z4r, z4i);
          cmul(gr[0], gi[0], z1r, z1i, gr[1], gi[1]);
          cmul(gr[0], gi[0], z2r, z2i, gr[2], gi[2]); cmul(gr[1], gi[1], z2r, z2i, gr[3], gi[3]);
          #pragma unroll
          for (int b = 0; b < 4; b++) cmul(gr[b], gi[b], z4r, z4i, gr[4 + b], gi[4 + b]);
          PUT4(8, packh(gr[0], gr[1]), packh(gr[2], gr[3]), packh(gr[4], gr[5]), packh(gr[6], gr[7]));
          PUT4(9, packh(gi[0], gi[1]), packh(gi[2], gi[3]), packh(gi[4], gi[5]), packh(gi[6], gi[7]));
          {
            const uint32_t z = packh(wr[3], -wi[3]), a4r = packh(gr[0], gr[4]), a4i = packh(gi[0], gi[4]);
            hcm2(packh(gr[0], gr[2]), packh(gi[0], gi[2]), z, PR[0], PI[0]);
            hcm2(packh(gr[4], gr[6]), packh(gi[4], gi[6]), z, PR[1], PI[1]);
            hcm2(a4r, a4i, packh(wr[4], -wi[4]), PR[2], PI[2]);
            hcm2(a4r, a4i, packh(wr[5], -wi[5]), PR[3], PI[3]);
            PUT4(10, PR[0], PR[1], PR[2], PR[3]); PUT4(11, PI[0], PI[1], PI[2], PI[3]);
            float hr, hi_;
            cmul(gr[0], gi[0], wr[3], -wi[3], hr, hi_);
            const uint32_t cr = packh(gr[0], hr), ci = packh(gi[0], hi_);
            #pragma unroll
            for (int i = 0; i < 3; i++) hcm2(cr, ci, packh(wr[6 + i], -wi[6 + i]), PR[i], PI[i]);
            PUT4(12, PR[0], PR[1], PR[2], 0u); PUT4(13, PI[0], PI[1], PI[2], 0u);
          }
          fence_async();
          bar_sync(4, 128);
          wg_fence();
          #pragma unroll
          for (int s = 0; s < 8; s++) {
            const uint64_t d = dE + (s >> 2) * (BLK >> 4) + ((s >> 1) & 1) * 448 + (s & 1) * 16;
            wg_ss48_tt_h(ka, d, d + 256, s != 0);
          }
          wg_commit();
        }
        const float dsk = bf_lo(__shfl_sync(0xffffffff, pd, 8 + (it & 7)));
        head(min(it + 1, 4));
        asm volatile("{\n.reg .pred p;\nHL:\nsetp.eq.f32 p, %0, 0f46400000;\n@p bra HL;\n}" :: "f"(hd[0] + hd[2] + hd[4]));
        wg_wait<0>();
        pin<24>(ka);
        float kk[6];
        const bool up = w4 >= 2;
        #pragma unroll
        for (int n = 0; n < 3; n++) {
          sts64f(xa + n * BLK, up ? ka[12 + 4 * n] : ka[4 * n + 2], up ? ka[13 + 4 * n] : ka[4 * n + 3]);
          kk[2 * n] = up ? ka[14 + 4 * n] : ka[4 * n]; kk[2 * n + 1] = up ? ka[15 + 4 * n] : ka[4 * n + 1];
        }
        if (it) bar_sync(4, 128); else bar_sync(8, 160);
          if (it == 4 && w4 == 0) {
            mbar_wait(BAR(BR_U), 0);
            if (elect_one()) {
              mbar_expect_tx(BAR(BR_U2), 8192);
              bulk_ld(blk - 2 * BLK, g_uy + (c * 80 + r * 5 + 2) * 2048, 4096, BAR(BR_U2)); bulk_ld(blk - BLK, g_uy + (c * 80 + r * 5 + 3) * 2048, 4096, BAR(BR_U2));
            }
            __syncwarp();
          }
        #pragma unroll
        for (int n = 0; n < 3; n++) {
          uint32_t o[2]; lds64(o, xr_ + n * BLK);
          kk[2 * n] = (kk[2 * n] + __uint_as_float(o[0])) * fac; kk[2 * n + 1] = (kk[2 * n + 1] + __uint_as_float(o[1])) * fac;
        }
        if (t7 == 0) kk[0] += dsk;
        {
          const uint32_t v = pack2(kk[1], kk[0]), vh = v >> 16;
          const uint32_t u = pack2(kk[2], kk[3]), w = pack2(kk[4], kk[5]), uu = pack2(kk[2], kk[2]), us = pack2(kk[3], kk[2]);
          const uint32_t x = tq < 2 ? w : u, xh = x >> 16;
          sts32(blk + e0 + 4, v); sts16(blk + e0, vh); sts16(blk + e0 + 10, v);
          sts16(blk + e1, x); sts16(blk + e1 + 6, x); sts16(blk + e2, xh); sts16(blk + e2 + 6, xh);
          if (tq < 2) {
            const uint32_t pb = blk + e0 + 1024 + 8 * tq;
            sts32(pb + 4, uu); sts32(pb + 8, us); sts16(pb + 14, us);
            if (i2) { sts16(pb - 4, u); sts32(pb, uu); }
          }
          if (i2 == 0) {
            const uint32_t tb = blk + B_TBL;
            if (tq == 0) { sts16(tb + (16 + 256) * 4, u); sts16(tb + (T_S + 3) * 4, w); sts32(tb + (T_S + 4) * 4, pack2(kk[4], kk[4])); sts16(tb + (T_S + 5) * 4 + 2, w); }
            else { sts32(tb + 528 * 4, uu); sts32(tb + 529 * 4, uu); sts32(tb + 530 * 4, uu); sts16(tb + 531 * 4 + 2, u); sts16(tb + (T_F3 + 80 + 63) * 4, w); }
          }
        }
        if (t7 == 0) TS(49 + it);
      }
    }
    asm volatile("setmaxnreg.inc.sync.aligned.u32 136;");
    if (t7 == 0) TS(41);
    bar_sync(4, 128);
    if (t7 == 0) mbar_arrive(BAR(BR_KS));
    if (EN_ATT) mbar_wait(BAR(BR_GEMM), 0);
    }
  }
  const int tid = rtid(), lane = tid & 31, g = lane >> 2, tq = lane & 3, t7 = tid & 127;
  mbar_wait(BAR(BR_EPOCH), 0);
  const unsigned epoch = lds32(sb + OFF_EPOCH);
  const uint32_t ytag = (epoch & 1u) * 0x10001u, ym = lane < 4 ? 0x10001u : 0u;
  if (EN_SSM && wg != 1) {
    mbar_wait(BAR(BR_KS), 0);
    mbar_wait(BAR(BR_U), 0);
    if (tid == 256) TS(42);
    {
      const int pass = wg >> 1;
      const int k = pass ? w4 : 4;
      if (k & 2) mbar_wait(BAR(BR_U2), 0);
      const uint32_t blk = sb + OFF_BLK + k * BLK, tb = blk + B_TBL + (uint32_t)((g - 2 * tq) * 4);
      float acc[16][4];
      zero<64>(&acc[0][0]);
      const int kl = 16 * (lane >> 4) + 2 * (lane & 7) + ((lane >> 3) & 1);
      {
        auto ubase = [&](int sh) { const int q = kl - 2 * sh; return blk + (uint32_t)((q * 16) ^ ((q * 2) & 0x10)); };
#define LDQ(A, sh) _Pragma("unroll") for (int m = 0; m < 4; m++) load_quad(A[m], tb + (16 + 16 * (sh) + 128 * m) * 4);
#define LDB(B, ub, h) _Pragma("unroll") for (int p = 0; p < 4; p++) ldsm4(B[p], (ub) + (4 * (h) + p) * 512);
#define MLO(A, B) _Pragma("unroll") for (int m = 0; m < 4; m++) _Pragma("unroll") for (int cc = 0; cc < 8; cc++) mma16816(acc[cc + m], A[m], &B[cc >> 1][(cc & 1) * 2]);
#define MHI(A, B) _Pragma("unroll") for (int m = 0; m < 4; m++) _Pragma("unroll") for (int cc = 0; cc < 8 - m; cc++) mma16816(acc[8 + cc + m], A[m], &B[cc >> 1][(cc & 1) * 2]);
        int p_ = pass ? 0 : w4;
        const int pe = pass ? 4 : w4 + 1;
        uint32_t A[4][4], A2[4][4], Bl[4][4], Bh[4][4];
        uint32_t ub = ubase(p_ + 4);
        LDQ(A, p_ + 4) LDB(Bl, ub, 0)
        #pragma unroll 1
        for (; p_ < pe; p_++) {
          LDB(Bh, ub, 1)
          MLO(A, Bl)
          ub = ubase(p_);
          LDQ(A2, p_) LDB(Bl, ub, 0)
          MHI(A, Bh)
          LDB(Bh, ub, 1)
          load_quad(A[0], tb + (16 + 512 + 16 * (p_ & 1)) * 4); load_quad(A[1], tb + (T_S + 16 * (p_ & 1)) * 4);
          MLO(A2, Bl)
          if (p_ < 2) {
            #pragma unroll
            for (int cc = 0; cc < 8; cc++) mma16816(acc[cc + 4], A[0], &Bl[cc >> 1][(cc & 1) * 2]);
            #pragma unroll
            for (int cc = 0; cc < 4; cc++) mma16816(acc[cc + 12], A[0], &Bh[cc >> 1][(cc & 1) * 2]);
            #pragma unroll
            for (int cc = 0; cc < 8; cc++) mma16816(acc[cc + 8], A[1], &Bl[cc >> 1][(cc & 1) * 2]);
          }
          const int pn = ((p_ + 1) & 3) + 4;
          ub = ubase(pn);
          LDQ(A, pn) LDB(Bl, ub, 0)
          MHI(A2, Bh)
        }
      }
      if (t7 == 0) TS(pass ? 60 : 16);
      mbar_wait(BAR(BR_DRDY + 1), 0);
      {
        const int ih = (lane >> 3) & 1;
        const uint32_t dl = blk + B_D + (uint32_t)(((lane >> 4) * 8 + (lane & 7)) * 16);
        const uint32_t d0_ = dl + ih * 1552, d8_ = dl + (ih ? 0 : 1536), d3_ = dl + B_D7 + ih * 1024;
        auto cls2 = [&](uint32_t da, uint32_t ta) {
          uint32_t B[6][2], A[6][4];
          #pragma unroll
          for (int e = 0; e < 6; e++) { B[e][0] = lds32v(ta + (e + 4) * 32); B[e][1] = lds32v(ta + (e + 3) * 32); }
          #pragma unroll
          for (int kk = 0; kk < 6; kk++) ldsm4t(A[kk], da + kk * 256);
          #pragma unroll
          for (int e = 0; e < 6; e++)
            #pragma unroll
            for (int kk = 0; kk < 6; kk++) if (2 * kk + e + 4 < 16) mma16816(acc[2 * kk + e + 4], A[kk], B[e]);
        };
        auto cls3 = [&](uint32_t da, uint32_t ta) {
          uint32_t B[8][2], A[4][4];
          #pragma unroll
          for (int e = 0; e < 8; e++) { B[e][0] = lds32v(ta + (e + 8) * 32); B[e][1] = lds32v(ta + (e + 7) * 32); }
          #pragma unroll
          for (int kk = 0; kk < 4; kk++) ldsm4t(A[kk], da + kk * 256);
          #pragma unroll
          for (int kk = 0; kk < 4; kk++)
            #pragma unroll
            for (int e = 0; e < 8; e++) if (2 * kk + e + 8 < 16) mma16816(acc[2 * kk + e + 8], A[kk], B[e]);
        };
        if (pass) {
          #pragma unroll 1
          for (int a = 0; a < 2; a++) {
            cls2(d0_ + a * B_D5, tb + (T_F2 + 48 * a - 32) * 4);
            cls2(d8_ + a * B_D5, tb + (T_F2 + 48 * a + 64) * 4);
            cls3(d3_ + a * 2048, tb + (T_F3 + 80 * a - 64) * 4);
          }
        } else {
          cls2(((w4 & 2) ? d8_ : d0_) + (w4 & 1) * B_D5, tb + (T_F2 + 48 * w4 - 32) * 4);
          if (w4 >= 2) cls3(d3_ + (w4 - 2) * 2048, tb + (T_F3 + 80 * (w4 - 2) - 64) * 4);
        }
      }
      if (t7 == 0) TS(pass ? 61 : 17);
      const uint32_t ya = (pass ? sb + OFF_BLK + 3 * BLK + w4 * 4096 : blk) + (uint32_t)((kl * 16) ^ ((kl * 2) & 0x10));
#define YTAG(v) (((v) & ~ym) | (ytag & ym))
#define STY(p) stsm4t(ya + (p) * 512, YTAG(pack2(acc[2 * (p)][0], acc[2 * (p)][1])), pack2(acc[2 * (p)][2], acc[2 * (p)][3]), \
                      YTAG(pack2(acc[2 * (p) + 1][0], acc[2 * (p) + 1][1])), pack2(acc[2 * (p) + 1][2], acc[2 * (p) + 1][3]))
      if (pass == 0) {
        const uint32_t xw = blk + 4096 + w4 * 4096 + lane * 16, xr = blk + 4096 + w4 * 1024 + lane * 16;
        #pragma unroll
        for (int h = 0; h < 2; h++) {
          bar_sync(2, 128);
          #pragma unroll
          for (int i = 0; i < 8; i++)
            sts128(xw + i * 512, __float_as_uint(acc[8 * h + i][0]), __float_as_uint(acc[8 * h + i][1]), __float_as_uint(acc[8 * h + i][2]), __float_as_uint(acc[8 * h + i][3]));
          bar_sync(2, 128);
          float y[8];
          #pragma unroll
          for (int i = 0; i < 8; i++) {
            uint32_t o[4]; lds128(o, xr + (i >> 1) * 4096 + (i & 1) * 512);
            #pragma unroll
            for (int e = 0; e < 4; e++) y[4 * (i & 1) + e] = i < 2 ? __uint_as_float(o[e]) : y[4 * (i & 1) + e] + __uint_as_float(o[e]);
          }
          stsm4t(ya + (4 * h + w4) * 512, YTAG(pack2(y[0], y[1])), pack2(y[2], y[3]), YTAG(pack2(y[4], y[5])), pack2(y[6], y[7]));
        }
      } else {
        fence_async();
        bar_sync(4, 128);
        if (t7 == 0) mbar_arrive(BAR(BR_KS + 1));
        #pragma unroll
        for (int p = 0; p < 8; p++) STY(p);
      }
      fence_async();
      __syncwarp();
      if (lane == 0) mbar_arrive(BAR(BR_Y + 1) - 8 * pass);
      if (t7 == 0) TS(pass ? 62 : 18);
    }
  }
  if (wg < 2) {
    if (EN_ATT) {
    float oc[40]; zero<40>(oc);
    {
      constexpr uint64_t dw0 = mkdesc(SB0, OFF_WOR, 1024, 1), da0 = mkdesc(SB0, 2048, 128, 0);
      const uint32_t ck = sb + tid * 32 + ((lane >> 2) << 2), ck2 = ck + (wg ? 0 : 16384);
      uint32_t bad = 0;
      auto tile = [&](int i, uint32_t so) {
        const uint32_t al = (uint32_t)da0 + wg * 64 + (so >> 4), wl = (uint32_t)dw0 + i * 640 - (i >> 1) * (1278 << 16);
        wg_fence();
        #pragma unroll
        for (int s = 0; s < 5; s++) wg_ss80_tb(oc, desc2(al + s * 256, da0 >> 32), desc2(wl + s * 128, dw0 >> 32), (i | s) != 0);
        wg_commit();
        bad |= (lds32(ck + so) ^ epoch) | (lds32(ck + so + 8192) ^ epoch) | (lds32(ck2 + so) ^ epoch);
      };
      if (w4 == 0) {
        if (EN_SSM) mbar_wait(BAR(BR_Y), 0);
        mbar_wait(BAR(BR_WO), 0);
        mbar_wait(BAR(BR_WO + 1), 0);
      }
      bar_sync(1, 256);
      if (tid == 0) TS(9);
      tile(0, SLOT(0));
      #pragma unroll 1
      for (int i = 1; i < 8; i++) {
        mbar_wait(BAR(BR_OFULL) + 8 * i, 0);
        tile(i, SLOT(i));
        wg_wait<1>();
        if (lane == 0) mbar_arrive(BAR(BR_OEMPTY - 1) + 8 * i);
      }
      #pragma unroll 1
      for (int n = 0; n < 56; n++) {
        const int i = n & 7;
        if (i == 0) {
          uint32_t any;
          asm volatile("{\n.reg .pred p;\nsetp.ne.u32 p, %1, 0;\nbarrier.red.or.pred p, 1, 256, p;\nselp.u32 %0, 1, 0, p;\n}" : "=r"(any) : "r"(bad & 1u) : "memory");
          if (!any) break;
          bad = 0;
          FIXCNT
        }
        wg_wait<0>();
        bar_sync(1, 256);
        if (tid == 0) { mbar_expect_tx(BAR(BR_RETRY), 20480); bulk_ld(sb + SLOT(5), &g_o[(r * 8 + CHUNK(i)) * 1280], 20480, BAR(BR_RETRY)); }
        mbar_wait(BAR(BR_RETRY), n & 1);
        tile(i, SLOT(5));
      }
      wg_wait<0>();
      pin<40>(oc);
    }
    if (tid == 0) TS(10);
    {
      const int row = w4 * 16 + (lane & 15);
      const uint32_t ob = sb + OFF_BLK + 3 * BLK + wg * 10240;
      #pragma unroll
      for (int j = 0; j < 8; j += 2)
        stsm4(ob + row * 128 + (((j + (lane >> 4)) ^ (row & 7)) << 4), pack2(oc[4 * j], oc[4 * j + 1]), pack2(oc[4 * j + 2], oc[4 * j + 3]),
              pack2(oc[4 * j + 4], oc[4 * j + 5]), pack2(oc[4 * j + 6], oc[4 * j + 7]));
      stsm4(ob + 8192 + row * 32 + (lane >> 4) * 16, pack2(oc[32], oc[33]), pack2(oc[34], oc[35]), pack2(oc[36], oc[37]), pack2(oc[38], oc[39]));
      fence_async();
      bar_sync(2 + wg, 128);
      if (w4 == 0 && elect_one()) {
        tma2d_st(&prm.m[M_O64], ob, 640 + c * 64, r * 128 + wg * 64);
        tma2d_st(&prm.m[M_O16], ob + 8192, 1152 + c * 16, r * 128 + wg * 64);
        bulk_commit(); bulk_wait0_read();
        if (wg == 0) { TS(11); DUMP(0, 20); }
      }
    }
    }
  } else if (EN_SSM) {
    if (t7 == 0) DUMP(40, 64);
    #pragma unroll 1
    for (int n = 0; n < 64; n++) if (!y_transpose(sb, w4, lane, ytag)) break;
  }
  }
}

typedef CUresult (*EncFn)(CUtensorMap*, CUtensorMapDataType, cuuint32_t, void*, const cuuint64_t*, const cuuint64_t*, const cuuint32_t*,
                          const cuuint32_t*, CUtensorMapInterleave, CUtensorMapSwizzle, CUtensorMapL2promotion, CUtensorMapFloatOOBfill);
static void mkmap(EncFn enc, CUtensorMap* m, const void* base, int rank, const cuuint64_t* dims, const cuuint64_t* strides, const cuuint32_t* box, CUtensorMapSwizzle swz) {
  cuuint32_t es[5] = {1, 1, 1, 1, 1};
  enc(m, CU_TENSOR_MAP_DATA_TYPE_BFLOAT16, rank, const_cast<void*>(base), dims, strides, box, es, CU_TENSOR_MAP_INTERLEAVE_NONE, swz,
      CU_TENSOR_MAP_L2_PROMOTION_L2_128B, CU_TENSOR_MAP_FLOAT_OOB_FILL_NONE);
}

extern "C" void kernel_launch(void* const* d_in, const int* in_sizes, int n_in, void* d_out, int out_size) {
  void* fn = nullptr; cudaDriverEntryPointQueryResult qr;
  cudaGetDriverEntryPoint("cuTensorMapEncodeTiled", &fn, cudaEnableDefault, &qr);
  EncFn enc = (EncFn)fn;
  void* uy = nullptr; cudaGetSymbolAddress(&uy, g_uy);
  const cuuint64_t dx[2] = {640, 2048}, sx[1] = {1280};
  const cuuint32_t bx[2] = {64, 128}, bu[2] = {80, 128};
  const cuuint64_t dw[3] = {640, 640, 3}, sw[2] = {3840, 1280};
  const cuuint32_t br[3] = {16, 32, 3};
  const cuuint64_t dwa[4] = {64, 640, 10, 3}, swa[3] = {3840, 128, 1280}, dwb[4] = {32, 640, 20, 3}, swb[3] = {3840, 64, 1280};
  const cuuint32_t bwa[4] = {64, 32, 1, 3}, bwb[4] = {32, 32, 2, 3};
  const cuuint64_t dwo[2] = {640, 640};
  const cuuint32_t bwo[2] = {64, 80}, bo64[2] = {64, 64}, bo16[2] = {16, 64};
  const cuuint64_t dsa[2] = {2048, 1280}, ssa[1] = {4096};
  const cuuint32_t bsa[2] = {64, 80};
  const cuuint64_t dout[2] = {1280, 2048}, sout[1] = {2560};
  Params prm;
  mkmap(enc, &prm.m[M_X], d_in[7], 2, dx, sx, bx, CU_TENSOR_MAP_SWIZZLE_128B);
  mkmap(enc, &prm.m[M_W128], d_in[8], 4, dwa, swa, bwa, CU_TENSOR_MAP_SWIZZLE_128B);
  mkmap(enc, &prm.m[M_W64], d_in[8], 4, dwb, swb, bwb, CU_TENSOR_MAP_SWIZZLE_64B);
  mkmap(enc, &prm.m[M_WR], d_in[8], 3, dw, sw, br, CU_TENSOR_MAP_SWIZZLE_32B);
  mkmap(enc, &prm.m[M_U], d_in[0], 2, dx, sx, bu, CU_TENSOR_MAP_SWIZZLE_NONE);
  mkmap(enc, &prm.m[M_WO], d_in[9], 2, dwo, sx, bwo, CU_TENSOR_MAP_SWIZZLE_128B);
  mkmap(enc, &prm.m[M_O64], d_out, 2, dout, sout, bo64, CU_TENSOR_MAP_SWIZZLE_128B);
  mkmap(enc, &prm.m[M_O16], d_out, 2, dout, sout, bo16, CU_TENSOR_MAP_SWIZZLE_NONE);
  mkmap(enc, &prm.m[M_SA], uy, 2, dsa, ssa, bsa, CU_TENSOR_MAP_SWIZZLE_128B);
  mkmap(enc, &prm.m[M_OUT], d_out, 2, dout, sout, bu, CU_TENSOR_MAP_SWIZZLE_NONE);
  prm.u = (const __nv_bfloat16*)d_in[0]; prm.wo = (const __nv_bfloat16*)d_in[9];
  for (int i = 0; i < 4; i++) prm.par[i] = (const __nv_bfloat16*)d_in[1 + i];
  prm.logdt = (const __nv_bfloat16*)d_in[5]; prm.dskip = (const __nv_bfloat16*)d_in[6];
  cudaFuncSetAttribute(fused_kernel, cudaFuncAttributeMaxDynamicSharedMemorySize, SMEM_BYTES);
  cudaLaunchConfig_t cfg = {};
  cfg.gridDim = dim3(128); cfg.blockDim = dim3(512); cfg.dynamicSmemBytes = SMEM_BYTES; cfg.stream = cudaStreamPerThread;
  cudaLaunchAttribute at[1];
  at[0].id = cudaLaunchAttributeClusterDimension; at[0].val.clusterDim.x = 2; at[0].val.clusterDim.y = 1; at[0].val.clusterDim.z = 1;
  cfg.attrs = at; cfg.numAttrs = 1;
  cudaLaunchKernelEx(&cfg, fused_kernel, prm);
}
```

```cpp
#include <cuda_runtime.h>
#include <cuda_bf16.h>
#include <cuda_fp16.h>
#include <cuda.h>
#include <stdint.h>

#define KST 2
#define UKB 4
#define UPF 0
#define CONV_AT 1
#define EN_ATT 1
#define EN_SSM 1

__device__ __align__(1024) __nv_bfloat16 g_uy[2 * 640 * 2048];
__device__ __align__(128) uint4 g_kvp[8 * 16 * 240];
__device__ __align__(128) uint4 g_o[128 * 1280];
__device__ __align__(128) unsigned g_flag[5 * 128 * 32];
__device__ unsigned g_epoch[128];
#define TS(i) do {} while (0)
#define DUMP(lo, hi) do {} while (0)
#define FIXCNT

constexpr uint32_t SB0 = 1024;
constexpr uint32_t W_SLOT = 15360, OFF_X = 76800;
constexpr uint32_t OFF_WOR = 81920, OFF_KVP = 10240, OFF_KVS = 71680, OFF_PK = 10240, OFF_V = 30720, OFF_EXTRA = 102400, OFF_KVB = OFF_EXTRA;
constexpr uint32_t OFF_BAR = 125952, OFF_BLK = 128000, BLK = 20480;
constexpr uint32_t B_D = 4096, B_D5 = 3088, B_D7 = 6176, B_D9 = 8224, B_TBL = 14400;
constexpr int T_S = 576, T_F2 = 624, T_F3 = 816;
constexpr uint32_t OFF_UT = OFF_BLK + 4 * BLK;
constexpr uint32_t SMEM_BYTES = OFF_BLK + 5 * BLK;
enum { BR_FULL = 0, BR_WO = 5, BR_PUB = 7, BR_KVP = 8, BR_U = 9, BR_SUM = 10, BR_GEMM = 11, BR_UIN = 12, BR_EPOCH = 14,
       BR_FREE = 15, BR_RETRY = 17, BR_UOUT = 18, BR_OFULL = 18, BR_KS = 26, BR_YIN = 28, BR_EMPTY = 31, BR_OEMPTY = 36, BR_Y = 43, BR_OSTG = 45,
       BR_DRDY = 46, BR_U2 = 48, BR_COUNT = 50 };
constexpr uint32_t OFF_EPOCH = OFF_BAR + 8 * BR_COUNT;
enum { M_X, M_W128, M_W64, M_WR, M_U, M_WO, M_O64, M_O16, M_SA, M_SY, M_SZ, M_COUNT };

__device__ __forceinline__ long long clk64() { long long t; asm volatile("mov.u64 %0, %%clock64;" : "=l"(t) :: "memory"); return t; }
__device__ __forceinline__ uint32_t smem_u32(const void* p) { return (uint32_t)__cvta_generic_to_shared(p); }
__host__ __device__ constexpr uint64_t mkdesc(uint32_t addr, uint32_t lbo, uint32_t sbo, uint32_t swz) {
  return (uint64_t)((addr & 0x3FFFF) >> 4) | ((uint64_t)(lbo >> 4) << 16) | ((uint64_t)(sbo >> 4) << 32) | ((uint64_t)swz << 62);
}
__device__ __forceinline__ uint64_t desc2(uint32_t lo, uint32_t hi) { uint64_t d; asm("mov.b64 %0, {%1, %2};" : "=l"(d) : "r"(lo), "r"(hi)); return d; }
__device__ __forceinline__ void mbar_init(uint32_t bar, uint32_t cnt) { asm volatile("mbarrier.init.shared::cta.b64 [%0], %1;" :: "r"(bar), "r"(cnt) : "memory"); }
__device__ __forceinline__ void mbar_expect_tx(uint32_t bar, uint32_t bytes) { asm volatile("mbarrier.arrive.expect_tx.shared::cta.b64 _, [%0], %1;" :: "r"(bar), "r"(bytes) : "memory"); }
__device__ __forceinline__ void mbar_arrive(uint32_t bar) { asm volatile("mbarrier.arrive.shared::cta.b64 _, [%0];" :: "r"(bar) : "memory"); }
__device__ __forceinline__ void mbar_wait(uint32_t bar, uint32_t parity) {
  asm volatile("{\n.reg .pred p;\n.reg .u32 c;\nmov.u32 c, 0;\n"
    "WL:\nmbarrier.try_wait.parity.shared::cta.b64 p, [%0], %1;\n@p bra WD;\n"
    "add.u32 c, c, 1;\nsetp.lt.u32 p, c, 200000;\n@p bra WL;\nWD:\n}" :: "r"(bar), "r"(parity) : "memory");
}
__device__ __forceinline__ void poll_all(const unsigned* p, unsigned val) {
  asm volatile("{\n.reg .pred p;\n.reg .u32 c, v;\nmov.u32 c, 0;\n"
    "PL:\nld.relaxed.gpu.global.u32 v, [%0];\nsetp.eq.u32 p, v, %1;\nvote.sync.all.pred p, p, 0xffffffff;\n@p bra PD;\n"
    "add.u32 c, c, 1;\nsetp.lt.u32 p, c, 100000;\n@p bra PL;\nPD:\n}" :: "l"(p), "r"(val) : "memory");
}
__device__ __forceinline__ void poll_all_acq(const unsigned* p, unsigned val) {
  asm volatile("{\n.reg .pred p;\n.reg .u32 c, v;\nmov.u32 c, 0;\n"
    "PL:\nld.acquire.gpu.global.u32 v, [%0];\nsetp.eq.u32 p, v, %1;\nvote.sync.all.pred p, p, 0xffffffff;\n@p bra PD;\n"
    "nanosleep.u32 300;\nadd.u32 c, c, 1;\nsetp.lt.u32 p, c, 100000;\n@p bra PL;\nPD:\n}" :: "l"(p), "r"(val) : "memory");
}
__device__ __forceinline__ unsigned poll_bit(const unsigned* p, unsigned val, unsigned mask) {
  unsigned bal;
  asm volatile("{\n.reg .pred p;\n.reg .u32 c, v;\nmov.u32 c, 0;\n"
    "PL:\nld.relaxed.gpu.global.u32 v, [%1];\nsetp.eq.u32 p, v, %2;\nvote.sync.ballot.b32 %0, p, 0xffffffff;\n"
    "and.b32 v, %0, %3;\nsetp.ne.u32 p, v, 0;\n@p bra PD;\n"
    "add.u32 c, c, 1;\nsetp.lt.u32 p, c, 100000;\n@p bra PL;\nPD:\n}" : "=&r"(bal) : "l"(p), "r"(val), "r"(mask) : "memory");
  return bal;
}
__device__ __forceinline__ void fix128_w0(uint32_t* v, const void* p, uint32_t tag, uint32_t mask) {
  asm volatile("{\n.reg .pred p;\n.reg .u32 c, x;\n.reg .b128 t;\n.reg .b64 lo, hi;\nmov.u32 c, 0;\n"
    "FL:\nxor.b32 x, %0, %5;\nand.b32 x, x, %6;\nsetp.eq.u32 p, x, 0;\n@p bra FD;\n"
    "ld.relaxed.gpu.global.b128 t, [%4];\nmov.b128 {lo, hi}, t;\nmov.b64 {%0, %1}, lo;\nmov.b64 {%2, %3}, hi;\n"
    "add.u32 c, c, 1;\nsetp.lt.u32 p, c, 100000;\n@p bra FL;\nFD:\n}"
    : "+r"(v[0]), "+r"(v[1]), "+r"(v[2]), "+r"(v[3]) : "l"(p), "r"(tag), "r"(mask) : "memory");
}
__device__ __forceinline__ void fix128_w3(uint32_t* v, const void* p, uint32_t tag, uint32_t mask) {
  asm volatile("{\n.reg .pred p;\n.reg .u32 c, x;\n.reg .b128 t;\n.reg .b64 lo, hi;\nmov.u32 c, 0;\n"
    "FL:\nxor.b32 x, %3, %5;\nand.b32 x, x, %6;\nsetp.eq.u32 p, x, 0;\n@p bra FD;\n"
    "ld.relaxed.gpu.global.b128 t, [%4];\nmov.b128 {lo, hi}, t;\nmov.b64 {%0, %1}, lo;\nmov.b64 {%2, %3}, hi;\n"
    "add.u32 c, c, 1;\nsetp.lt.u32 p, c, 100000;\n@p bra FL;\nFD:\n}"
    : "+r"(v[0]), "+r"(v[1]), "+r"(v[2]), "+r"(v[3]) : "l"(p), "r"(tag), "r"(mask) : "memory");
}
__device__ __forceinline__ void fence_acq() { asm volatile("fence.acq_rel.gpu;" ::: "memory"); }
__device__ __forceinline__ bool elect_one() {
  uint32_t p; asm volatile("{\n.reg .pred P;\nelect.sync _|P, 0xffffffff;\nselp.u32 %0, 1, 0, P;\n}" : "=r"(p)); return p;
}
__device__ __forceinline__ void bar_sync(int id, int n) { asm volatile("bar.sync %0, %1;" :: "r"(id), "r"(n) : "memory"); }
__device__ __forceinline__ void fence_async() { asm volatile("fence.proxy.async.shared::cta;" ::: "memory"); }
__device__ __forceinline__ void fence_async_g() { asm volatile("fence.proxy.async.global;" ::: "memory"); }
__device__ __forceinline__ void tma2d(uint32_t dst, const CUtensorMap* m, uint32_t bar, int c0, int c1) {
  asm volatile("cp.async.bulk.tensor.2d.shared::cluster.global.mbarrier::complete_tx::bytes [%0], [%1, {%3, %4}], [%2];"
    :: "r"(dst), "l"(m), "r"(bar), "r"(c0), "r"(c1) : "memory");
}
__device__ __forceinline__ void tma3d(uint32_t dst, const CUtensorMap* m, uint32_t bar, int c0, int c1, int c2) {
  asm volatile("cp.async.bulk.tensor.3d.shared::cluster.global.mbarrier::complete_tx::bytes [%0], [%1, {%3, %4, %5}], [%2];"
    :: "r"(dst), "l"(m), "r"(bar), "r"(c0), "r"(c1), "r"(c2) : "memory");
}
__device__ __forceinline__ void tma4d(uint32_t dst, const CUtensorMap* m, uint32_t bar, int c0, int c1, int c2, int c3) {
  asm volatile("cp.async.bulk.tensor.4d.shared::cluster.global.mbarrier::complete_tx::bytes [%0], [%1, {%3, %4, %5, %6}], [%2];"
    :: "r"(dst), "l"(m), "r"(bar), "r"(c0), "r"(c1), "r"(c2), "r"(c3) : "memory");
}
__device__ __forceinline__ void tma2d_st(const CUtensorMap* m, uint32_t src, int c0, int c1) {
  asm volatile("cp.async.bulk.tensor.2d.global.shared::cta.bulk_group [%0, {%2, %3}], [%1];"
    :: "l"(m), "r"(src), "r"(c0), "r"(c1) : "memory");
}
__device__ __forceinline__ void bulk_ld(uint32_t dst, const void* src, uint32_t bytes, uint32_t bar) {
  asm volatile("cp.async.bulk.shared::cluster.global.mbarrier::complete_tx::bytes [%0], [%1], %2, [%3];"
    :: "r"(dst), "l"(src), "r"(bytes), "r"(bar) : "memory");
}
__device__ __forceinline__ void bulk_st(void* dst, uint32_t src, uint32_t bytes) {
  asm volatile("cp.async.bulk.global.shared::cta.bulk_group [%0], [%1], %2;" :: "l"(dst), "r"(src), "r"(bytes) : "memory");
}
__device__ __forceinline__ void bulk_commit() { asm volatile("cp.async.bulk.commit_group;" ::: "memory"); }
__device__ __forceinline__ void bulk_wait0() { asm volatile("cp.async.bulk.wait_group 0;" ::: "memory"); }
__device__ __forceinline__ void bulk_wait0_read() { asm volatile("cp.async.bulk.wait_group.read 0;" ::: "memory"); }
__device__ __forceinline__ unsigned ld_rlx(const unsigned* p) { unsigned v; asm volatile("ld.relaxed.gpu.global.u32 %0, [%1];" : "=r"(v) : "l"(p) : "memory"); return v; }
__device__ __forceinline__ unsigned ld_acq(const unsigned* p) { unsigned v; asm volatile("ld.acquire.gpu.global.u32 %0, [%1];" : "=r"(v) : "l"(p) : "memory"); return v; }
__device__ __forceinline__ void st_rlx(unsigned* p, unsigned v) { asm volatile("st.relaxed.gpu.global.u32 [%0], %1;" :: "l"(p), "r"(v) : "memory"); }
__device__ __forceinline__ void st_rel(unsigned* p, unsigned v) { asm volatile("st.release.gpu.global.u32 [%0], %1;" :: "l"(p), "r"(v) : "memory"); }
__device__ __forceinline__ void ld128_rlx(uint32_t* v, const void* p) {
  asm volatile("{\n.reg .b128 t;\n.reg .b64 lo, hi;\nld.relaxed.gpu.global.b128 t, [%4];\nmov.b128 {lo, hi}, t;\n"
    "mov.b64 {%0, %1}, lo;\nmov.b64 {%2, %3}, hi;\n}" : "=r"(v[0]), "=r"(v[1]), "=r"(v[2]), "=r"(v[3]) : "l"(p) : "memory");
}
__device__ __forceinline__ void st128_rlx(void* p, const uint32_t* v) {
  asm volatile("{\n.reg .b128 t;\n.reg .b64 lo, hi;\nmov.b64 lo, {%1, %2};\nmov.b64 hi, {%3, %4};\nmov.b128 t, {lo, hi};\n"
    "st.relaxed.gpu.global.b128 [%0], t;\n}" :: "l"(p), "r"(v[0]), "r"(v[1]), "r"(v[2]), "r"(v[3]) : "memory");
}
__device__ __forceinline__ uint32_t lds32(uint32_t a) { uint32_t v; asm volatile("ld.shared.u32 %0, [%1];" : "=r"(v) : "r"(a) : "memory"); return v; }
__device__ __forceinline__ uint32_t lds32v(uint32_t a) { uint32_t v; asm volatile("ld.volatile.shared.u32 %0, [%1];" : "=r"(v) : "r"(a) : "memory"); return v; }
__device__ __forceinline__ uint32_t cpa(uint32_t a, uint32_t one) { uint32_t v; asm volatile("mul.lo.u32 %0, %1, %2;" : "=r"(v) : "r"(a), "r"(one)); return v; }
__device__ __forceinline__ uint32_t cpb(uint32_t a, uint32_t zero) { uint32_t v; asm volatile("or.b32 %0, %1, %2;" : "=r"(v) : "r"(a), "r"(zero)); return v; }
__device__ __forceinline__ uint32_t lds16(uint32_t a) { uint16_t v; asm volatile("ld.shared.u16 %0, [%1];" : "=h"(v) : "r"(a) : "memory"); return v; }
__device__ __forceinline__ float ldsf(uint32_t a) { float v; asm volatile("ld.shared.f32 %0, [%1];" : "=f"(v) : "r"(a) : "memory"); return v; }
__device__ __forceinline__ void lds128(uint32_t* v, uint32_t a) { asm volatile("ld.shared.v4.u32 {%0,%1,%2,%3}, [%4];" : "=r"(v[0]), "=r"(v[1]), "=r"(v[2]), "=r"(v[3]) : "r"(a) : "memory"); }
__device__ __forceinline__ void sts32(uint32_t a, uint32_t v) { asm volatile("st.shared.u32 [%0], %1;" :: "r"(a), "r"(v) : "memory"); }
__device__ __forceinline__ void sts16(uint32_t a, uint32_t v) { asm volatile("st.shared.u16 [%0], %1;" :: "r"(a), "h"((uint16_t)v) : "memory"); }
__device__ __forceinline__ void sts64f(uint32_t a, float x, float y) { asm volatile("st.shared.v2.f32 [%0], {%1,%2};" :: "r"(a), "f"(x), "f"(y) : "memory"); }
__device__ __forceinline__ void sts128(uint32_t a, uint32_t x, uint32_t y, uint32_t z, uint32_t w) { asm volatile("st.shared.v4.u32 [%0], {%1,%2,%3,%4};" :: "r"(a), "r"(x), "r"(y), "r"(z), "r"(w) : "memory"); }
__device__ __forceinline__ void stsm4(uint32_t a, uint32_t r0, uint32_t r1, uint32_t r2, uint32_t r3) {
  asm volatile("stmatrix.sync.aligned.m8n8.x4.shared.b16 [%0], {%1,%2,%3,%4};" :: "r"(a), "r"(r0), "r"(r1), "r"(r2), "r"(r3) : "memory");
}
__device__ __forceinline__ void stsm4t(uint32_t a, uint32_t r0, uint32_t r1, uint32_t r2, uint32_t r3) {
  asm volatile("stmatrix.sync.aligned.m8n8.x4.trans.shared.b16 [%0], {%1,%2,%3,%4};" :: "r"(a), "r"(r0), "r"(r1), "r"(r2), "r"(r3) : "memory");
}
__device__ __forceinline__ void ldsm4t(uint32_t* r, uint32_t a) {
  asm volatile("ldmatrix.sync.aligned.m8n8.x4.trans.shared.b16 {%0,%1,%2,%3}, [%4];" : "=r"(r[0]), "=r"(r[1]), "=r"(r[2]), "=r"(r[3]) : "r"(a) : "memory");
}
__device__ __forceinline__ void ldsm4(uint32_t* r, uint32_t a) {
  asm volatile("ldmatrix.sync.aligned.m8n8.x4.shared.b16 {%0,%1,%2,%3}, [%4];" : "=r"(r[0]), "=r"(r[1]), "=r"(r[2]), "=r"(r[3]) : "r"(a) : "memory");
}
__device__ __forceinline__ void mma16816(float* d, const uint32_t* a, const uint32_t* b) {
  asm volatile("mma.sync.aligned.m16n8k16.row.col.f32.bf16.bf16.f32 {%0,%1,%2,%3}, {%4,%5,%6,%7}, {%8,%9}, {%0,%1,%2,%3};"
    : "+f"(d[0]), "+f"(d[1]), "+f"(d[2]), "+f"(d[3]) : "r"(a[0]), "r"(a[1]), "r"(a[2]), "r"(a[3]), "r"(b[0]), "r"(b[1]));
}
__device__ __forceinline__ uint32_t pack2(float lo, float hi) { uint32_t r; asm("cvt.rn.bf16x2.f32 %0, %1, %2;" : "=r"(r) : "f"(hi), "f"(lo)); return r; }
__device__ __forceinline__ uint32_t packh(float lo, float hi) { uint32_t r; asm("cvt.rn.f16x2.f32 %0, %1, %2;" : "=r"(r) : "f"(hi), "f"(lo)); return r; }
__device__ __forceinline__ uint32_t hcmul(uint32_t x, uint32_t zp, uint32_t zq) {
  const __half2 xx = *reinterpret_cast<__half2*>(&x);
  const __half2 r = __hfma2(__high2half2(xx), *reinterpret_cast<__half2*>(&zq), __hmul2(__low2half2(xx), *reinterpret_cast<__half2*>(&zp)));
  return *reinterpret_cast<const uint32_t*>(&r);
}
__device__ __forceinline__ void hcm2(uint32_t xr, uint32_t xi, uint32_t z, uint32_t& pr, uint32_t& pi) {
  const __half2 a = *reinterpret_cast<__half2*>(&xr), b = *reinterpret_cast<__half2*>(&xi), zz = *reinterpret_cast<__half2*>(&z);
  const __half2 re = __hfma2(__hneg2(b), __high2half2(zz), __hmul2(a, __low2half2(zz)));
  const __half2 im = __hfma2(a, __high2half2(zz), __hmul2(b, __low2half2(zz)));
  pr = *reinterpret_cast<const uint32_t*>(&re); pi = *reinterpret_cast<const uint32_t*>(&im);
}
__device__ __forceinline__ void sts64(uint32_t a, uint32_t x, uint32_t y) { asm volatile("st.shared.v2.u32 [%0], {%1,%2};" :: "r"(a), "r"(x), "r"(y) : "memory"); }
__device__ __forceinline__ void lds64(uint32_t* v, uint32_t a) { asm volatile("ld.shared.v2.u32 {%0,%1}, [%2];" : "=r"(v[0]), "=r"(v[1]) : "r"(a) : "memory"); }
__device__ __forceinline__ float bf_lo(uint32_t v) { return __uint_as_float(v << 16); }
__device__ __forceinline__ float bf_hi(uint32_t v) { return __uint_as_float(v & 0xffff0000u); }
__device__ __forceinline__ float bf_round(float x) { return bf_lo(pack2(x, 0.f)); }
__device__ __forceinline__ float ex2(float x) { float r; asm("ex2.approx.ftz.f32 %0, %1;" : "=f"(r) : "f"(x)); return r; }
__device__ __forceinline__ float phi(float t, float l2e = 1.44269504089f) {
  float e = ex2(t * l2e) + 1e-6f;
  asm("{\n.reg .pred p;\nsetp.gt.f32 p, %1, 0f00000000;\n@p add.f32 %0, %1, 0f3F800008;\n}" : "+f"(e) : "f"(t));
  return e;
}
__device__ __forceinline__ void wg_fence() { asm volatile("wgmma.fence.sync.aligned;" ::: "memory"); }
__device__ __forceinline__ void wg_commit() { asm volatile("wgmma.commit_group.sync.aligned;" ::: "memory"); }
template <int N> __device__ __forceinline__ void wg_wait() { asm volatile("wgmma.wait_group.sync.aligned %0;" :: "n"(N) : "memory"); }
template <int N> __device__ __forceinline__ void pin(float* a) {
  #pragma unroll
  for (int i = 0; i < N; i++) asm volatile("" : "+f"(a[i]) :: "memory");
}
__device__ __forceinline__ int rtid() { int t; asm volatile("mov.u32 %0, %%tid.x;" : "=r"(t)); return t; }
__device__ __forceinline__ int opaque(int v) { asm volatile("" : "+r"(v)); return v; }
template <int N> __device__ __forceinline__ void zero(float* a) {
  #pragma unroll
  for (int i = 0; i < N; i++) asm volatile("mov.b32 %0, 0;" : "=f"(a[i]));
}
template <int N> __device__ __forceinline__ void pinu(uint32_t* a) {
  #pragma unroll
  for (int i = 0; i < N; i++) asm volatile("" : "+r"(a[i]) :: "memory");
}
__device__ __forceinline__ void cexp_t(float lg2mag, float turns, float& re, float& im) {
  float m = ex2(lg2mag);
  float fr = (turns - __fadd_rn(__fadd_rn(turns, 12582912.f), -12582912.f)) * 6.283185307f;
  re = m * __cosf(fr); im = m * __sinf(fr);
}
__device__ __forceinline__ void cmul(float ar, float ai, float br, float bi, float& cr, float& ci) {
  cr = fmaf(ar, br, -ai * bi); ci = fmaf(ar, bi, ai * br);
}

__device__ __forceinline__ void wg_ss48_tt(float* d, uint64_t da, uint64_t db, int scale_d) {
  asm volatile("{\n.reg .pred p;\nsetp.ne.b32 p, %26, 0;\n"
    "wgmma.mma_async.sync.aligned.m64n48k16.f32.bf16.bf16 "
    "{%0, %1, %2, %3, %4, %5, %6, %7, %8, %9, %10, %11, %12, %13, %14, %15, %16, %17, %18, %19, %20, %21, %22, %23}, %24, %25, p, 1, 1, 1, 1;\n}\n"
    : "+f"(d[0]), "+f"(d[1]), "+f"(d[2]), "+f"(d[3]), "+f"(d[4]), "+f"(d[5]), "+f"(d[6]), "+f"(d[7]), "+f"(d[8]), "+f"(d[9]), "+f"(d[10]), "+f"(d[11]), "+f"(d[12]), "+f"(d[13]), "+f"(d[14]), "+f"(d[15]), "+f"(d[16]), "+f"(d[17]), "+f"(d[18]), "+f"(d[19]), "+f"(d[20]), "+f"(d[21]), "+f"(d[22]), "+f"(d[23])
    : "l"(da), "l"(db), "r"(scale_d));
}
__device__ __forceinline__ void wg_rs88_tb(float* d, const uint32_t* a, uint64_t db, int scale_d) {
  asm volatile("{\n.reg .pred p;\nsetp.ne.b32 p, %49, 0;\n"
    "wgmma.mma_async.sync.aligned.m64n88k16.f32.bf16.bf16 "
    "{%0, %1, %2, %3, %4, %5, %6, %7, %8, %9, %10, %11, %12, %13, %14, %15, %16, %17, %18, %19, %20, %21, %22, %23, %24, %25, %26, %27, %28, %29, %30, %31, %32, %33, %34, %35, %36, %37, %38, %39, %40, %41, %42, %43}, {%44, %45, %46, %47}, %48, p, 1, 1, 1;\n}\n"
    : "+f"(d[0]), "+f"(d[1]), "+f"(d[2]), "+f"(d[3]), "+f"(d[4]), "+f"(d[5]), "+f"(d[6]), "+f"(d[7]), "+f"(d[8]), "+f"(d[9]), "+f"(d[10]), "+f"(d[11]), "+f"(d[12]), "+f"(d[13]), "+f"(d[14]), "+f"(d[15]), "+f"(d[16]), "+f"(d[17]), "+f"(d[18]), "+f"(d[19]), "+f"(d[20]), "+f"(d[21]), "+f"(d[22]), "+f"(d[23]), "+f"(d[24]), "+f"(d[25]), "+f"(d[26]), "+f"(d[27]), "+f"(d[28]), "+f"(d[29]), "+f"(d[30]), "+f"(d[31]), "+f"(d[32]), "+f"(d[33]), "+f"(d[34]), "+f"(d[35]), "+f"(d[36]), "+f"(d[37]), "+f"(d[38]), "+f"(d[39]), "+f"(d[40]), "+f"(d[41]), "+f"(d[42]), "+f"(d[43])
    : "r"(a[0]), "r"(a[1]), "r"(a[2]), "r"(a[3]), "l"(db), "r"(scale_d));
}
__device__ __forceinline__ void wg_ss80_tb(float* d, uint64_t da, uint64_t db, int scale_d) {
  asm volatile("{\n.reg .pred p;\nsetp.ne.b32 p, %42, 0;\n"
    "wgmma.mma_async.sync.aligned.m64n80k16.f32.bf16.bf16 "
    "{%0, %1, %2, %3, %4, %5, %6, %7, %8, %9, %10, %11, %12, %13, %14, %15, %16, %17, %18, %19, %20, %21, %22, %23, %24, %25, %26, %27, %28, %29, %30, %31, %32, %33, %34, %35, %36, %37, %38, %39}, %40, %41, p, 1, 1, 0, 1;\n}\n"
    : "+f"(d[0]), "+f"(d[1]), "+f"(d[2]), "+f"(d[3]), "+f"(d[4]), "+f"(d[5]), "+f"(d[6]), "+f"(d[7]), "+f"(d[8]), "+f"(d[9]), "+f"(d[10]), "+f"(d[11]), "+f"(d[12]), "+f"(d[13]), "+f"(d[14]), "+f"(d[15]), "+f"(d[16]), "+f"(d[17]), "+f"(d[18]), "+f"(d[19]), "+f"(d[20]), "+f"(d[21]), "+f"(d[22]), "+f"(d[23]), "+f"(d[24]), "+f"(d[25]), "+f"(d[26]), "+f"(d[27]), "+f"(d[28]), "+f"(d[29]), "+f"(d[30]), "+f"(d[31]), "+f"(d[32]), "+f"(d[33]), "+f"(d[34]), "+f"(d[35]), "+f"(d[36]), "+f"(d[37]), "+f"(d[38]), "+f"(d[39])
    : "l"(da), "l"(db), "r"(scale_d));
}
__device__ __forceinline__ void wg_ss48_tt_h(float* d, uint64_t da, uint64_t db, int scale_d) {
  asm volatile("{\n.reg .pred p;\nsetp.ne.b32 p, %26, 0;\n"
    "wgmma.mma_async.sync.aligned.m64n48k16.f32.f16.f16 "
    "{%0, %1, %2, %3, %4, %5, %6, %7, %8, %9, %10, %11, %12, %13, %14, %15, %16, %17, %18, %19, %20, %21, %22, %23}, %24, %25, p, 1, 1, 1, 1;\n}\n"
    : "+f"(d[0]), "+f"(d[1]), "+f"(d[2]), "+f"(d[3]), "+f"(d[4]), "+f"(d[5]), "+f"(d[6]), "+f"(d[7]), "+f"(d[8]), "+f"(d[9]), "+f"(d[10]), "+f"(d[11]), "+f"(d[12]), "+f"(d[13]), "+f"(d[14]), "+f"(d[15]), "+f"(d[16]), "+f"(d[17]), "+f"(d[18]), "+f"(d[19]), "+f"(d[20]), "+f"(d[21]), "+f"(d[22]), "+f"(d[23])
    : "l"(da), "l"(db), "r"(scale_d));
}
__device__ __forceinline__ void wg_rs192_tb(float* d, const uint32_t* a, uint64_t db, int scale_d) {
  asm volatile("{\n.reg .pred p;\nsetp.ne.b32 p, %101, 0;\n"
    "wgmma.mma_async.sync.aligned.m64n192k16.f32.bf16.bf16 "
    "{%0, %1, %2, %3, %4, %5, %6, %7, %8, %9, %10, %11, %12, %13, %14, %15, %16, %17, %18, %19, %20, %21, %22, %23, %24, %25, %26, %27, %28, %29, %30, %31, %32, %33, %34, %35, %36, %37, %38, %39, %40, %41, %42, %43, %44, %45, %46, %47, %48, %49, %50, %51, %52, %53, %54, %55, %56, %57, %58, %59, %60, %61, %62, %63, %64, %65, %66, %67, %68, %69, %70, %71, %72, %73, %74, %75, %76, %77, %78, %79, %80, %81, %82, %83, %84, %85, %86, %87, %88, %89, %90, %91, %92, %93, %94, %95}, {%96, %97, %98, %99}, %100, p, 1, 1, 1;\n}\n"
    : "+f"(d[0]), "+f"(d[1]), "+f"(d[2]), "+f"(d[3]), "+f"(d[4]), "+f"(d[5]), "+f"(d[6]), "+f"(d[7]), "+f"(d[8]), "+f"(d[9]), "+f"(d[10]), "+f"(d[11]), "+f"(d[12]), "+f"(d[13]), "+f"(d[14]), "+f"(d[15]), "+f"(d[16]), "+f"(d[17]), "+f"(d[18]), "+f"(d[19]), "+f"(d[20]), "+f"(d[21]), "+f"(d[22]), "+f"(d[23]), "+f"(d[24]), "+f"(d[25]), "+f"(d[26]), "+f"(d[27]), "+f"(d[28]), "+f"(d[29]), "+f"(d[30]), "+f"(d[31]), "+f"(d[32]), "+f"(d[33]), "+f"(d[34]), "+f"(d[35]), "+f"(d[36]), "+f"(d[37]), "+f"(d[38]), "+f"(d[39]), "+f"(d[40]), "+f"(d[41]), "+f"(d[42]), "+f"(d[43]), "+f"(d[44]), "+f"(d[45]), "+f"(d[46]), "+f"(d[47]), "+f"(d[48]), "+f"(d[49]), "+f"(d[50]), "+f"(d[51]), "+f"(d[52]), "+f"(d[53]), "+f"(d[54]), "+f"(d[55]), "+f"(d[56]), "+f"(d[57]), "+f"(d[58]), "+f"(d[59]), "+f"(d[60]), "+f"(d[61]), "+f"(d[62]), "+f"(d[63]), "+f"(d[64]), "+f"(d[65]), "+f"(d[66]), "+f"(d[67]), "+f"(d[68]), "+f"(d[69]), "+f"(d[70]), "+f"(d[71]), "+f"(d[72]), "+f"(d[73]), "+f"(d[74]), "+f"(d[75]), "+f"(d[76]), "+f"(d[77]), "+f"(d[78]), "+f"(d[79]), "+f"(d[80]), "+f"(d[81]), "+f"(d[82]), "+f"(d[83]), "+f"(d[84]), "+f"(d[85]), "+f"(d[86]), "+f"(d[87]), "+f"(d[88]), "+f"(d[89]), "+f"(d[90]), "+f"(d[91]), "+f"(d[92]), "+f"(d[93]), "+f"(d[94]), "+f"(d[95])
    : "r"(a[0]), "r"(a[1]), "r"(a[2]), "r"(a[3]), "l"(db), "r"(scale_d));
}
__device__ __forceinline__ void wg_rs48_tb(float* d, const uint32_t* a, uint64_t db, int scale_d) {
  asm volatile("{\n.reg .pred p;\nsetp.ne.b32 p, %29, 0;\n"
    "wgmma.mma_async.sync.aligned.m64n48k16.f32.bf16.bf16 "
    "{%0, %1, %2, %3, %4, %5, %6, %7, %8, %9, %10, %11, %12, %13, %14, %15, %16, %17, %18, %19, %20, %21, %22, %23}, {%24, %25, %26, %27}, %28, p, 1, 1, 1;\n}\n"
    : "+f"(d[0]), "+f"(d[1]), "+f"(d[2]), "+f"(d[3]), "+f"(d[4]), "+f"(d[5]), "+f"(d[6]), "+f"(d[7]), "+f"(d[8]), "+f"(d[9]), "+f"(d[10]), "+f"(d[11]), "+f"(d[12]), "+f"(d[13]), "+f"(d[14]), "+f"(d[15]), "+f"(d[16]), "+f"(d[17]), "+f"(d[18]), "+f"(d[19]), "+f"(d[20]), "+f"(d[21]), "+f"(d[22]), "+f"(d[23])
    : "r"(a[0]), "r"(a[1]), "r"(a[2]), "r"(a[3]), "l"(db), "r"(scale_d));
}

struct Params {
  const __nv_bfloat16 *par[4], *logdt, *dskip, *u, *wo;
  CUtensorMap m[M_COUNT];
};

#define CHUNK(i) ((i) == 0 ? c : ((i) == 7 ? (c ^ 1) : (((c & 6) + 1 + (i)) & 7)))
#define CHAN(k) (c * 80 + ((k) < 4 ? r * 4 + (k) : 64 + r))
#define FLAG(kind, rr, cc) (&g_flag[((kind) * 128 + (rr) * 8 + (cc)) * 32])
#define SLOT(i) ((i) == 0 || (i) == 5 ? OFF_EXTRA : (i) == 4 ? OFF_BLK + 4 * BLK : OFF_BLK - 1024 + ((i) > 5 ? (i) - 6 : (i) - 1) * BLK)
__device__ __forceinline__ void load_quad(uint32_t* A, uint32_t addr) {
  A[0] = lds32v(addr); A[1] = lds32v(addr + 32); A[2] = lds32v(addr - 32); A[3] = lds32v(addr);
}

__global__ void __launch_bounds__(512, 1) fused_kernel(const __grid_constant__ Params prm) {
  extern __shared__ unsigned char smem_raw[];
  const uint32_t sb = __shfl_sync(0xffffffff, smem_u32(smem_raw), 0);
  const int tid = threadIdx.x, lane = tid & 31;
  const int warp = __shfl_sync(0xffffffff, tid >> 5, 0), wg = warp >> 2, w4 = warp & 3;
  const int cta = blockIdx.x, r = cta >> 3, c = cta & 7;
  if ((sb & 0xffffffu) != SB0) return;
#define BAR(i) (sb + OFF_BAR + 8 * (i))
  const bool sw64 = ((c + 1) & 2) != 0;

  const CUtensorMap* mwp = &prm.m[sw64 ? M_W64 : M_W128];
  const int mcol = (c * 80 + (c & 1) * 16) >> (sw64 ? 5 : 6), rcol = c * 80 + ((c & 1) ? 0 : 64);
  if (warp == 12 && elect_one()) {
    #pragma unroll
    for (int i = 0; i < 5; i++) mbar_init(BAR(BR_FULL + i), 1);
    asm volatile("fence.mbarrier_init.release.cluster;" ::: "memory");
    if (EN_ATT) {
      mbar_expect_tx(BAR(BR_FULL), W_SLOT + 16384);
      tma4d(sb, mwp, BAR(BR_FULL), 0, 0, mcol, 0);
      tma2d(sb + OFF_X, &prm.m[M_X], BAR(BR_FULL), 0, r * 128);
      tma3d(sb + 12288, &prm.m[M_WR], BAR(BR_FULL), rcol, 0, 0);
      mbar_expect_tx(BAR(BR_FULL + 1), W_SLOT);
      tma4d(sb + W_SLOT, mwp, BAR(BR_FULL + 1), 0, 32, mcol, 0);
      tma3d(sb + W_SLOT + 12288, &prm.m[M_WR], BAR(BR_FULL + 1), rcol, 32, 0);
      TS(24);
    }
  }
  if (warp == 13 && elect_one()) {
    asm volatile("prefetch.tensormap [%0];" :: "l"(&prm.m[M_X]) : "memory");
    asm volatile("prefetch.tensormap [%0];" :: "l"(&prm.m[M_WR]) : "memory");
  }
  if (wg == 3) {
    asm volatile("setmaxnreg.dec.sync.aligned.u32 56;");
    const int tid = rtid(), lane = tid & 31;
    if (warp == 12) {
      asm volatile("bar.arrive 0, 512;" ::: "memory");
      {
        uint32_t s = 2, ph = 1, xs = 16384;
        #pragma unroll 1
        for (int kb = 2; kb < 20; kb++) {
          if (kb == 4) bar_sync(6, 128);
          if (kb >= 5) mbar_wait(BAR(BR_EMPTY) + 8 * s, ph);
          if (EN_ATT && elect_one()) {
            const uint32_t st = sb + s * W_SLOT, fb = BAR(BR_FULL) + 8 * s;
            mbar_expect_tx(fb, (kb & 1) ? W_SLOT : W_SLOT + 16384);
            if (!(kb & 1)) tma2d(sb + OFF_X + xs, &prm.m[M_X], fb, kb * 32, r * 128);
            tma4d(st, mwp, fb, 0, kb * 32, mcol, 0);
            tma3d(st + 12288, &prm.m[M_WR], fb, rcol, kb * 32, 0);
          }
          if (kb < 4 && lane == 0) TS(24 + kb);
          if (UPF && kb >= UKB - 4 && kb < UKB && elect_one())
            asm volatile("cp.async.bulk.prefetch.L2.global [%0], 5120;" :: "l"(prm.u + cta * 10240 + (kb - (UKB - 4)) * 2560) : "memory");
          if (EN_SSM && kb == (EN_ATT ? UKB : 4) && elect_one()) { mbar_expect_tx(BAR(BR_UIN), 20480); tma2d(sb + OFF_UT, &prm.m[M_U], BAR(BR_UIN), c * 80, r * 128); }
          if (kb == 14 && elect_one()) asm volatile("cp.async.bulk.prefetch.L2.global [%0], 6400;" :: "l"(prm.wo + cta * 3200) : "memory");
          if (!EN_ATT && kb == 4) break;
          if (++s == 5) { s = 0; ph ^= 1; }
          if (kb & 1) { xs += 16384; if (xs == 49152) xs = 0; }
        }
      }
      if (EN_ATT) {
      mbar_wait(BAR(BR_EPOCH), 0);
      const unsigned epoch = lds32(sb + OFF_EPOCH);
      const unsigned* fo = FLAG(3, r, lane & 7);
      unsigned seen = __ballot_sync(0xffffffff, ld_rlx(lane < 16 ? fo : FLAG(0, lane & 15, c)) == epoch) & 0xffu;
      mbar_wait(BAR(BR_GEMM), 0);
      if (elect_one()) {
        mbar_expect_tx(BAR(BR_WO), 10240);
        tma2d(sb, &prm.m[M_WO], BAR(BR_WO), c * 64, c * 80);
        mbar_expect_tx(BAR(BR_KVP), 61440);
        mbar_expect_tx(BAR(BR_WO + 1), 7 * 10240);
      }
      {
        uint32_t ds = sb + OFF_WOR + (lane >> 3) * 128 + (((lane & 7) ^ (lane >> 3)) << 4);
        #pragma unroll 1
        for (int h = 0; h < 2; h++) {
          const int i = (lane & 6) + h;
          const char* gs = reinterpret_cast<const char*>(prm.wo) + (size_t)((lane >> 3) + CHUNK(i) * 80) * 1280 + 1024 + c * 32 + (lane & 1) * 16;
          #pragma unroll 2
          for (int q = 0; q < 20; q++) {
            asm volatile("cp.async.cg.shared.global [%0], [%1], 16;" :: "r"(ds), "l"(gs) : "memory");
            ds = (ds + 512) ^ 64; gs += 5120;
          }
        }
      }
      mbar_wait(BAR(BR_PUB), 0);
      poll_all(FLAG(0, lane & 15, c), epoch);
      if (elect_one()) { TS(23); bulk_ld(sb + OFF_KVP, &g_kvp[c * 16 * 240], 61440, BAR(BR_KVP)); }
      asm volatile("cp.async.wait_all;" ::: "memory");
      fence_async();
      mbar_arrive(BAR(BR_WO));
      mbar_wait(BAR(BR_SUM), 0);
      if (elect_one()) {
        #pragma unroll 1
        for (int i = 1; i < 8; i++) tma2d(sb + i * 10240, &prm.m[M_WO], BAR(BR_WO + 1), c * 64, CHUNK(i) * 80);
      }
      mbar_wait(BAR(BR_OSTG), 0);
      if (elect_one()) {
        bulk_st(&g_o[cta * 1280], sb + OFF_EXTRA, 20480);
        bulk_commit();
        bulk_wait0();
        st_rlx(FLAG(3, r, c), epoch);
        mbar_arrive(BAR(BR_OEMPTY));
        TS(20);
      }
      __syncwarp();
      #pragma unroll 1
      for (int i = 1; i < 8; i++) {
        const int src = CHUNK(i);
        if (!((seen >> src) & 1)) seen = poll_bit(fo, epoch, 1u << src);
        if (i > 4) mbar_wait(BAR(BR_OEMPTY - 5) + 8 * i, 0);
        else if (EN_SSM && i != 2 && i != 3) mbar_wait(BAR(i == 1 ? BR_KS + 1 : BR_FREE + 1), 0);
        if (elect_one()) {
          mbar_expect_tx(BAR(BR_OFULL) + 8 * i, 20480);
          bulk_ld(sb + SLOT(i), &g_o[(r * 8 + src) * 1280], 20480, BAR(BR_OFULL) + 8 * i);
          if (i == 1) TS(21);
          if (i == 7) TS(22);
        }
        __syncwarp();
      }
      if (lane == 0) { DUMP(20, 30); }
      }
    } else {
      const int hw = warp - 13, ht = tid - 416;
      if (hw == 2 && elect_one()) {
        #pragma unroll
        for (int i = 5; i < BR_COUNT; i++) mbar_init(BAR(i), i == BR_WO ? 33 : i == BR_OEMPTY ? 9 : i < BR_EMPTY ? 1 : i < BR_OEMPTY ? 2 : i < BR_Y ? 8 : i < BR_OSTG ? 4 : i == BR_OSTG ? 8 : i < BR_U2 ? 3 : 1);
        asm volatile("fence.mbarrier_init.release.cluster;" ::: "memory");
      }
      __syncwarp();
      asm volatile("bar.arrive 0, 512;" ::: "memory");
      if (EN_SSM && hw == 2) asm volatile("bar.arrive 8, 160;" ::: "memory");
      const unsigned epoch = hw == 0 ? ld_rlx(&g_epoch[cta]) + 1 : 0;
      bar_sync(5, 96);
      asm volatile("bar.arrive 6, 128;" ::: "memory");
      if (hw == 1 && elect_one()) {
        #pragma unroll
        for (int i = M_U; i < M_COUNT; i++) asm volatile("prefetch.tensormap [%0];" :: "l"(&prm.m[i]) : "memory");
      }
      if (ht == 0) {
        st_rlx(&g_epoch[cta], epoch);
        sts32(sb + OFF_EPOCH, epoch);
        mbar_arrive(BAR(BR_EPOCH));
      }
      if (EN_SSM) {
      const int mi = lane >> 3, rw = lane & 7;
      const bool early_u = hw == 0 && __all_sync(0xffffffff, ld_acq(FLAG(1, lane & 15, c)) == epoch);
      mbar_wait(BAR(BR_UIN), 0);
      if (ht == 0) TS(36);
      #pragma unroll 1
      for (int h = 0; h < 2; h++) {
        const uint32_t sa = sb + OFF_UT + h * 10240 + (8 * mi + rw) * 160 + hw * 16, da = sb + OFF_UT + h * 10240 + (hw * 8 + rw) * 128 + ((mi ^ rw ^ h) << 4);
        uint32_t v[8][4];
        #pragma unroll
        for (int q = 0; q < 8; q++) if (q < 6 || hw == 0) ldsm4t(v[q], sa + (q & 1) * 5120 + (q >> 1) * 48);
        bar_sync(5, 96);
        #pragma unroll
        for (int q = 0; q < 8; q++) if (q < 6 || hw == 0) stsm4((da ^ ((q & 1) * 64)) + (q >> 1) * 3072, v[q][0], v[q][1], v[q][2], v[q][3]);
      }
      fence_async();
      bar_sync(5, 96);
      if (hw == 0) {
        if (elect_one()) {
          tma2d_st(&prm.m[M_SA], sb + OFF_UT, r * 128, c * 80);
          tma2d_st(&prm.m[M_SA], sb + OFF_UT + 10240, r * 128 + 64, c * 80);
          bulk_commit(); bulk_wait0_read();
          mbar_arrive(BAR(BR_UOUT));
          TS(37);
          bulk_wait0();
          st_rel(FLAG(1, r, c), epoch);
          TS(30);
        }
        __syncwarp();
        if (!early_u) poll_all_acq(FLAG(1, lane & 15, c), epoch);
      }
      #pragma unroll 1
      for (int k = 0; k < 5; k++) {
        if (k == 0 || k == 3) {
          const int p = k != 0;
          if (hw == 0) {
            if (!p) {
              if (elect_one()) {
                fence_async_g();
                mbar_expect_tx(BAR(BR_U), 12288);
                #pragma unroll 1
                for (int q = 0; q < 3; q++) bulk_ld(sb + OFF_BLK + q * q * BLK, g_uy + CHAN(q * q) * 2048, 4096, BAR(BR_U));
                TS(31);
              }
              __syncwarp();
            }
            mbar_wait(BAR(p ? BR_U2 : BR_U), 0);
          }
          bar_sync(5, 96);
        }
        const int l3 = (hw + k) % 3 * 32 + lane;
        const uint32_t blk = sb + OFF_BLK + ((0x32410 >> (4 * k)) & 7) * BLK, o = blk + B_D + l3 * 16;
        float P[34];
        P[0] = 0.f;
        #pragma unroll
        for (int q = 0; q < 5; q++) {
          const int ch = 2 * l3 - 3 + q;
          uint32_t v[4];
          lds128(v, blk + (uint32_t)((ch * 16) ^ ((ch * 2) & 0x10)));
          #pragma unroll
          for (int e = 0; e < 8; e++) {
            const int i = 8 * q + e - 4;
            if (i >= 0 && i < 33) P[i + 1] = P[i] + ((e & 1) ? bf_hi(v[e >> 1]) : bf_lo(v[e >> 1]));
          }
        }
#define WIN(lo, hi, e) (P[21 + (e) - (lo)] - P[20 + (e) - (hi)])
#define WIN8(lo, hi, b) pack2(WIN(lo, hi, b), WIN(lo, hi, b + 1)), pack2(WIN(lo, hi, b + 2), WIN(lo, hi, b + 3)), pack2(WIN(lo, hi, b + 4), WIN(lo, hi, b + 5)), pack2(WIN(lo, hi, b + 6), WIN(lo, hi, b + 7))
        if (l3 < 64) {
          sts128(o + B_D9, WIN8(12, 20, 0)); sts128(o + B_D9 + 1024, WIN8(12, 20, 8));
          sts128(o + B_D7, WIN8(5, 11, 0)); sts128(o + B_D7 + 1024, WIN8(5, 11, 8));
        }
        sts128(o + B_D5, WIN8(6, 10, 0)); sts128(o + B_D5 + 1552, WIN8(6, 10, 8));
        sts128(o, WIN8(3, 5, 0)); sts128(o + 1552, WIN8(3, 5, 8));
        if (l3 < 2) sts128(blk + B_D + l3 * B_D5 + 1536, 0, 0, 0, 0);
      }
      __syncwarp();
      if (lane == 0) mbar_arrive(BAR(BR_DRDY + 1));
      if (ht == 0) TS(32);
      if (hw == 0) {
        const bool early = __all_sync(0xffffffff, ld_rlx(FLAG(lane < 16 ? 4 : 2, lane & 15, c)) == epoch);
        const uint32_t ym = lane < 4 ? 0x10001u : 0u, ytag = (epoch & 1u) * 0x10001u, yb = sb + OFF_BLK + 3 * BLK + 16384;
        mbar_wait(BAR(BR_Y + 1), 0);
        if (elect_one()) {
          bulk_st(g_uy + (640 + CHAN(4)) * 2048, sb + OFF_BLK + 4 * BLK, 4096);
          bulk_commit(); bulk_wait0();
          st_rlx(FLAG(4, r, c), epoch);
          mbar_arrive(BAR(BR_FREE + 1));
          TS(33);
        }
        __syncwarp();
        mbar_wait(BAR(BR_KS + 1), 0);
        if (!early) poll_all(FLAG(4, lane & 15, c), epoch);
        uint32_t v[8][4];
        #pragma unroll 1
        for (int n = 0; n < 64; n++) {
          if (elect_one()) {
            mbar_expect_tx(BAR(BR_YIN + 1), 4096);
            tma2d(yb, &prm.m[M_SZ], BAR(BR_YIN + 1), r * 128, 640 + c * 80 + 64);
            tma2d(yb + 2048, &prm.m[M_SZ], BAR(BR_YIN + 1), r * 128 + 64, 640 + c * 80 + 64);
            TS(34);
          }
          __syncwarp();
          mbar_wait(BAR(BR_YIN + 1), n & 1);
          uint32_t bad = 0;
          #pragma unroll
          for (int q = 0; q < 8; q++) {
            ldsm4t(v[q], yb + rw * 128 + ((mi ^ rw ^ ((q & 1) * 4) ^ ((q >> 1) & 1)) << 4) + ((q >> 1) & 1) * 2048 + (q >> 2) * 1024);
            bad |= (v[q][0] ^ ytag) | (v[q][2] ^ ytag);
          }
          if (!__any_sync(0xffffffff, bad & ym)) break;
          FIXCNT
        }
        #pragma unroll
        for (int q = 0; q < 8; q++) stsm4(yb + lane * 32 + (q & 3) * 1024 + (q >> 2) * 16, v[q][0] & ~ym, v[q][1], v[q][2] & ~ym, v[q][3]);
        fence_async();
        __syncwarp();
        if (elect_one()) {
          TS(39);
          tma2d_st(&prm.m[M_O16], yb, c * 80 + 64, r * 128);
          tma2d_st(&prm.m[M_O16], yb + 2048, c * 80 + 64, r * 128 + 64);
          bulk_commit(); bulk_wait0_read();
          TS(35); DUMP(30, 40); DUMP(0, 1);
        }
      }
      }
    }
  } else {
  if (wg < 2) {
    asm volatile("setmaxnreg.inc.sync.aligned.u32 160;");
    bar_sync(0, 512);
    if (EN_ATT) {
    float am[96], ar[24];
    {
      const bool lead = (rtid() & 127) == 0;
      constexpr uint64_t dr0 = mkdesc(SB0 + 12288, 1024, 256, 3);
      const uint64_t db0 = sw64 ? mkdesc(SB0, 2048, 512, 2) : mkdesc(SB0, 4096, 1024, 1);
      const uint32_t kst = sw64 ? 64 : 128, bh = db0 >> 32;
      uint32_t s = 0, ph = 0, xo = 0;
      const int ln = rtid() & 31;
      const uint32_t xa = sb + OFF_X + (warp * 16 + (ln & 15)) * 128 + (((ln >> 4) ^ (ln & 7)) << 4);
      uint32_t A[8];
      mbar_wait(BAR(BR_FULL), 0);
      if (lead && wg == 0) TS(1);
      ldsm4(A, xa); ldsm4(A + 4, xa ^ 32);
      wg_fence();
      wg_rs48_tb(ar, A, dr0, 0); wg_rs192_tb(am, A, db0, 0);
      wg_commit();
      #pragma unroll 1
      for (int kb = 1; kb < 20; kb++) {
        const uint32_t wp = s * (W_SLOT >> 4), eb = BAR(BR_EMPTY) + 8 * s;
        wg_fence();
        wg_rs48_tb(ar, A + 4, desc2((uint32_t)dr0 + wp + 32, dr0 >> 32), 1);
        wg_rs192_tb(am, A + 4, desc2((uint32_t)db0 + wp + kst, bh), 1);
        wg_commit();
        if (++s == 5) { s = 0; ph ^= 1; }
        if (!(kb & 1)) { xo += 16384; if (xo == 49152) xo = 0; }
        mbar_wait(BAR(BR_FULL) + 8 * s, ph);
        const uint32_t xk = (xa + xo) ^ ((kb & 1) * 64), wn = s * (W_SLOT >> 4);
        wg_wait<1>();
        ldsm4(A, xk);
        wg_fence();
        wg_rs48_tb(ar, A, desc2((uint32_t)dr0 + wn, dr0 >> 32), 1);
        wg_rs192_tb(am, A, desc2((uint32_t)db0 + wn, bh), 1);
        wg_commit();
        wg_wait<1>();
        ldsm4(A + 4, xk ^ 32);
        if (lead && kb < 16) mbar_arrive(eb);
      }
      wg_fence();
      wg_rs48_tb(ar, A + 4, dr0 + 4 * (W_SLOT >> 4) + 32, 1);
      wg_rs192_tb(am, A + 4, desc2((uint32_t)db0 + 4 * (W_SLOT >> 4) + kst, bh), 1);
      wg_commit();
      wg_wait<0>();
      pin<96>(am); pin<24>(ar);
    }
    const int tid = rtid(), lane = tid & 31, tq = lane & 3;
    if (tid == 0) TS(2);
#define QV(j, e) ((j) < 8 ? am[4 * (j) + (e)] : ar[4 * ((j) - 8) + (e)])
#define KV_(j, e) ((j) < 8 ? am[32 + 4 * (j) + (e)] : ar[8 + 4 * ((j) - 8) + (e)])
#define VV(j, e) ((j) < 8 ? am[64 + 4 * (j) + (e)] : ar[16 + 4 * ((j) - 8) + (e)])
    {
      bar_sync(1, 256);
      if (tid == 0) mbar_arrive(BAR(BR_GEMM));
      const uint32_t ro = sb + (uint32_t)((warp * 16 + (lane & 15)) * 16);
      const int l0 = 2 * (c & 1) + (lane >> 4);
      const uint32_t ones = (tq == 0) ? 0x00003f80u : 0u;
#define PV(j) pack2(VV(j, 0), VV(j, 1)), pack2(VV(j, 2), VV(j, 3))
#define PK(j) pack2(phi(KV_(j, 0)), phi(KV_(j, 1))), pack2(phi(KV_(j, 2)), phi(KV_(j, 3)))
      stsm4(ro + OFF_V + (5 + 6 * (lane >> 4)) * 2048, ones, ones, ones, ones);
      #pragma unroll
      for (int j = 0; j < 10; j += 2) {
        const int l = (j == 8 && (c & 1)) ? l0 - 2 : l0 + j;
        stsm4(ro + OFF_V + (l + (l >= 5)) * 2048, PV(j), PV(j + 1));
        stsm4(ro + OFF_PK + l * 2048, PK(j), PK(j + 1));
      }
    }
    fence_async();
    bar_sync(1, 256);
    if (tid == 0) TS(3);
    mbar_wait(BAR(BR_EPOCH), 0);
    const unsigned epoch = lds32(sb + OFF_EPOCH);
    {
      float kv[24]; zero<24>(kv);
      constexpr uint64_t da = mkdesc(SB0 + OFF_PK, 128, 2048, 0), db = mkdesc(SB0 + OFF_V, 128, 2048, 0);
      wg_fence();
      #pragma unroll
      for (int s = 0; s < 8; s++) wg_ss48_tt(kv, desc2((uint32_t)da + wg * 640 + s * 16, da >> 32), desc2((uint32_t)db + wg * 768 + s * 16, db >> 32), s != 0);
      wg_commit();
      wg_wait<0>();
      pin<24>(kv);
      if (tid == 0) TS(15);
      if (w4 < 3) {
        const uint32_t wb = sb + OFF_KVS + (wg * 3 + w4) * 1536 + (lane & 15) * 96;
        #pragma unroll
        for (int j = 0; j < 6; j += 2)
          stsm4(wb + (j + (lane >> 4)) * 16, pack2(kv[4 * j], kv[4 * j + 1]), pack2(kv[4 * j + 2], kv[4 * j + 3]),
                pack2(kv[4 * j + 4], kv[4 * j + 5]), pack2(kv[4 * j + 6], kv[4 * j + 7]));
        __syncwarp();
        const int dl = w4 * 16 + (lane & 15), hl = dl >= 20;
        uint32_t v[4], z[4];
        lds128(v, wb + (3 * hl + (lane >> 4)) * 16);
        lds64(z, wb + 32 + 8 * hl); z[2] = lds32(wb + 80); z[3] = epoch & 1u;
        if (dl < 40) {
          uint4* dst = &g_kvp[(c * 16 + r) * 240 + wg * 40 + dl];
          v[3] = (v[3] & ~1u) | z[3];
          st128_rlx(dst + (lane >> 4) * 80, v);
          if (lane < 16) st128_rlx(dst + 160, z);
        }
      }
    }
    bar_sync(1, 256);
    if (tid == 0) { st_rlx(FLAG(0, r, c), epoch); mbar_arrive(BAR(BR_PUB)); TS(4); }
    const int kvi = (tid >= 80) + (tid >= 160) + (tid >= 240), kd = tid - 80 * kvi;
    const int khd = kd / 20, kt0 = 5 * (khd >> 1) + 2 * (khd & 1);
    const uint32_t rb = sb + OFF_KVB + kd * 16;
    if (kvi < 3) {
      #pragma unroll 1
      for (int m = kvi; m < 7; m += 3) { const int q = kt0 + 3 + m; sts128(rb + (q >= 10 ? q - 10 : q) * 1280, 0, 0, 0, 0); }
    }
    uint32_t qa[20];
    {
      const float sc = 1.44269504089f + __uint_as_float(lds32(sb + OFF_EPOCH) ^ epoch);
      #pragma unroll
      for (int j = 0; j < 10; j++) { qa[2 * j] = pack2(phi(QV(j, 0), sc), phi(QV(j, 1), sc)); qa[2 * j + 1] = pack2(phi(QV(j, 2), sc), phi(QV(j, 3), sc)); }
    }
    if (tid == 0) TS(5);
    if (warp == 7) mbar_wait(BAR(BR_KVP), 0);
    bar_sync(1, 256);
    if (tid == 0) TS(6);
    if (kvi < 3) {
      float s[8];
      zero<8>(s);
      uint32_t bad = 0;
      #pragma unroll 4
      for (int i = 0; i < 16; i += 2) {
        uint32_t w[4], x[4];
        lds128(w, sb + OFF_KVP + tid * 16 + i * 3840); lds128(x, sb + OFF_KVP + tid * 16 + i * 3840 + 3840);
        bad |= (w[3] ^ epoch) | (x[3] ^ epoch);
        #pragma unroll
        for (int e = 0; e < 4; e++) {
          asm("add.rn.bf16x2 %0, %0, %1;" : "+r"(w[e]) : "r"(x[e]));
          s[2 * e] += bf_lo(w[e]); s[2 * e + 1] += bf_hi(w[e]);
        }
      }
      if (__builtin_expect(bad & 1u, 0)) {
        zero<8>(s);
        #pragma unroll 1
        for (int i = 0; i < 16; i++) {
          uint32_t w[4] = {0, 0, 0, ~epoch};
          fix128_w3(w, &g_kvp[(c * 16 + i) * 240 + tid], epoch, 1u);
          #pragma unroll
          for (int e = 0; e < 4; e++) { s[2 * e] += bf_lo(w[e]); s[2 * e + 1] += bf_hi(w[e]); }
        }
        FIXCNT
      }
      const uint32_t p0 = pack2(s[0], s[1]), p1 = pack2(s[2], s[3]), p2 = pack2(s[4], s[5]), p3 = pack2(s[6], s[7]);
      if (kvi < 2) sts128(rb + (kt0 + (khd & 1) + kvi) * 1280, p0, p1, p2, p3);
      else {
        const bool od = khd & 1;
        sts128(rb + (5 * (khd >> 1) + 2) * 1280, od ? 0u : p0, od ? 0u : p1, od ? p0 : 0u, od ? p1 : 0u);
        const uint32_t zz = (p2 & 0xffffu) << (16 * (khd & 1));
        sts128(rb + 10 * 1280, khd < 2 ? zz : 0u, khd < 2 ? 0u : zz, 0u, 0u);
      }
    }
    fence_async();
    bar_sync(1, 256);
    if (tid == 0) { mbar_arrive(BAR(BR_SUM)); TS(7); }
    {
      float oa[44]; zero<44>(oa);
      constexpr uint64_t db = mkdesc(SB0 + OFF_KVB, 128, 1280, 0);
      wg_fence();
      #pragma unroll
      for (int s = 0; s < 5; s++) wg_rs88_tb(oa, &qa[4 * s], desc2((uint32_t)db + ((s == 4 && (c & 1)) ? 0 : (s + (c & 1)) * 16), db >> 32), s != 0);
      wg_commit();
      wg_wait<0>();
      pin<44>(oa);
      if (tid == 0) TS(13);
      float rc[4], rd[2][4];
      #pragma unroll
      for (int e = 0; e < 4; e++) asm("rcp.approx.ftz.f32 %0, %1;" : "=f"(rc[e]) : "f"(oa[40 + e] + 1e-6f));
      #pragma unroll
      for (int h = 0; h < 4; h++) {
        rd[0][h] = __shfl_sync(0xffffffff, rc[h & 1], (lane & 28) | (h >> 1));
        rd[1][h] = __shfl_sync(0xffffffff, rc[2 + (h & 1)], (lane & 28) | (h >> 1));
      }
      #pragma unroll
      for (int j = 0; j < 10; j++) {
        #pragma unroll
        for (int h = 0; h < 2; h++) {
          float f;
          if (j == 2) f = tq < 2 ? rd[h][0] : rd[h][1];
          else if (j == 7) f = tq < 2 ? rd[h][2] : rd[h][3];
          else f = rd[h][(8 * j) / 20];
          qa[2 * j + h] = pack2(oa[4 * j + 2 * h] * f, oa[4 * j + 2 * h + 1] * f);
        }
      }
      const uint32_t m0 = (lane & 7) == ((2 * w4) & 7), m1 = (lane & 7) == 2 * w4 + 1;
      const uint32_t oa_ = sb + OFF_EXTRA + (lane >> 4) * 2048 + (warp * 16 + (lane & 15)) * 16;
      bar_sync(1, 256);
#define TAG(v, m) (((v) & ~(m)) | (epoch & (m)))
      #pragma unroll
      for (int s = 0; s < 5; s++) stsm4(oa_ + s * 4096, TAG(qa[4 * s], m0), TAG(qa[4 * s + 1], m1), TAG(qa[4 * s + 2], m0), TAG(qa[4 * s + 3], m1));
    }
    fence_async();
    __syncwarp();
    if (lane == 0) mbar_arrive(BAR(BR_OSTG));
    if (tid == 0) TS(8);
    }
    asm volatile("setmaxnreg.dec.sync.aligned.u32 136;");
  } else {
    const int g = lane >> 2, tq = lane & 3, t7 = tid & 127;
    uint32_t raw[5][4], pd;
    {
      #pragma unroll
      for (int e = 0; e < 4; e++)
        #pragma unroll
        for (int q = 0; q < 5; q++) asm volatile("ld.global.nc.u16 %0, [%1];" : "=r"(raw[q][e]) : "l"(prm.par[e] + CHAN(q) * 128 + t7));
      asm volatile("ld.global.nc.u16 %0, [%1];" : "=r"(pd) : "l"(((lane & 8) ? prm.dskip : prm.logdt) + CHAN(lane & 7)));
    }
    asm volatile("bar.arrive 0, 512;" ::: "memory");
    if (EN_SSM) {
    {
      #pragma unroll 1
      for (int k = 0; k < 4; k++) {
        const uint32_t z = sb + OFF_BLK + k * BLK + t7 * 16;
        sts128(z + B_TBL, 0, 0, 0, 0); sts128(z + B_TBL + 2048, 0, 0, 0, 0);
      }
      if (t7 < 80) sts128(sb + OFF_BLK + (t7 >> 4) * BLK - 256 + (t7 & 15) * 16, 0, 0, 0, 0);
      const uint32_t ea = sb + OFF_BLK + (2 + (w4 & 1)) * BLK + (lane >> 4) * 7168 + ((lane >> 3) & 1) * 256 + (lane & 7) * 16 + (w4 >> 1) * 2048;
      constexpr uint64_t dE = mkdesc(SB0 + OFF_BLK + 2 * BLK, 128, 512, 0);
      const uint32_t xa = sb + OFF_BLK + 18560 + t7 * 8, xr_ = sb + OFF_BLK + 18560 + (t7 ^ 64) * 8;
      uint32_t pr[5][2];
      #pragma unroll
      for (int q = 0; q < 5; q++) {
        #pragma unroll
        for (int e = 0; e < 2; e++) pr[q][e] = raw[q][2 * e] | (raw[q][2 * e + 1] << 16);
        const uint32_t m = __reduce_max_sync(0xffffffff, max(raw[q][2] & 0x7fffu, raw[q][3] & 0x7fffu));
        if (lane == 0) sts32(sb + OFF_EPOCH + 64 + q * 16 + w4 * 4, m);
      }
      bar_sync(4, 128);
      if (t7 == 0) TS(40);
      const int j = (w4 & 1) * 16 + (w4 >> 1) * 8 + g, i2 = tq < 2 ? 64 * tq + j : 32 * (tq - 2) + j;
      const uint32_t e2 = B_TBL + 4 * (tq < 2 ? T_F3 + (((i2 - 1) & 1) ? 80 : 0) + ((i2 - 1) >> 1) + 16 : T_F2 + (i2 & 1) * 96 + (i2 >> 1));
      const uint32_t e1 = tq < 2 ? (i2 ? e2 - 64 : B_TBL + 4 * (T_F2 + 175)) : B_TBL + 4 * (i2 ? T_F2 + ((2 * i2 - 1) & 3) * 48 + ((2 * i2 - 1) >> 2) : 16 + 511);
      const uint32_t e0 = B_TBL + (16 + 8 * j + 2 * tq) * 4;
      const float dtl = bf_round(expf(bf_lo(pd)));
      float hd[9];
      auto head = [&](int q) {
        const uint32_t pa0 = pr[0][0], pc0 = pr[0][1];
        const float dt = __shfl_sync(0xffffffff, dtl, q);
        #pragma unroll
        for (int e = 0; e < 2; e++) { pr[0][e] = pr[1][e]; pr[1][e] = pr[2][e]; pr[2][e] = pr[3][e]; pr[3][e] = pr[4][e]; }
        uint32_t mm[4];
        lds128(mm, sb + OFF_EPOCH + 64 + q * 16);
        const uint32_t ex = min(max(max(max(mm[0], mm[1]), max(mm[2], mm[3])) >> 7, 1u), 253u);
        const float sc = __uint_as_float((254u - ex) << 23);
        const float lr = -bf_round(expf(bf_lo(pa0))) * dt * 1.44269504089f;
        const float tn = bf_hi(pa0) * dt * 0.15915494309f;
        cexp_t(lr, -tn, hd[0], hd[1]);
        cexp_t(lr * 8.f, tn * 8.f, hd[2], hd[3]);
        cexp_t(lr * 64.f, tn * 64.f, hd[4], hd[5]);
        hd[6] = bf_lo(pc0) * sc; hd[7] = -bf_hi(pc0) * sc;
        hd[8] = 2.f * dt * __uint_as_float(ex << 23);
      };
      head(0);
      #pragma unroll 1
      for (int it = 0; it < 5; it++) {
        const int k = it;
        const uint32_t blk = sb + OFF_BLK + k * BLK;
        float fac = 0.f;
        float ka[24]; zero<24>(ka);
        {
          if (it == 4) {
            mbar_wait(BAR(BR_UOUT), 0);
            sts128(sb + OFF_UT + B_TBL + t7 * 16, 0, 0, 0, 0); sts128(sb + OFF_UT + B_TBL + 2048 + t7 * 16, 0, 0, 0, 0);
          }
          const uint32_t ga = ea + 4096 - (w4 >> 1) * 512;
#define PUT4(i, a, b, c_, d) sts128(((i) < 8 ? ea + ((i) >> 1) * 512 : ga + (((i) - 8) >> 1) * 512) + ((i) & 1) * 128, a, b, c_, d)
          float z2r, z2i, z4r, z4i, xr[8], xi[8], gr[8], gi[8], wr[9], wi[9];
          const float z1r = hd[0], z1i = hd[1];
          xr[1] = hd[2]; xi[1] = hd[3]; wr[0] = hd[4]; wi[0] = hd[5];
          fac = hd[8];
          xr[0] = 1.f; xi[0] = 0.f;
          cmul(xr[1], xi[1], xr[1], xi[1], xr[2], xi[2]); cmul(xr[2], xi[2], xr[1], xi[1], xr[3], xi[3]);
          cmul(xr[2], xi[2], xr[2], xi[2], xr[4], xi[4]);
          #pragma unroll
          for (int b = 1; b < 4; b++) cmul(xr[4], xi[4], xr[b], xi[b], xr[4 + b], xi[4 + b]);
          cmul(wr[0], wi[0], wr[0], wi[0], wr[1], wi[1]); cmul(wr[1], wi[1], wr[0], wi[0], wr[2], wi[2]);
          cmul(wr[1], wi[1], wr[1], wi[1], wr[3], wi[3]); cmul(wr[3], wi[3], wr[3], wi[3], wr[4], wi[4]);
          cmul(wr[4], wi[4], wr[3], wi[3], wr[5], wi[5]); cmul(wr[4], wi[4], wr[4], wi[4], wr[6], wi[6]);
          cmul(wr[6], wi[6], wr[4], wi[4], wr[7], wi[7]); cmul(wr[6], wi[6], wr[6], wi[6], wr[8], wi[8]);
          uint32_t R[4], I[4], PR[4], PI[4];
          #pragma unroll
          for (int b = 0; b < 4; b++) { R[b] = packh(xr[2 * b], xr[2 * b + 1]); I[b] = packh(xi[2 * b], xi[2 * b + 1]); }
          PUT4(0, R[0], R[1], R[2], R[3]); PUT4(1, I[0], I[1], I[2], I[3]);
          #pragma unroll
          for (int i = 0; i < 3; i++) {
            const uint32_t z = packh(wr[i], wi[i]);
            #pragma unroll
            for (int b = 0; b < 4; b++) hcm2(R[b], I[b], z, PR[b], PI[b]);
            PUT4(2 * i + 2, PR[0], PR[1], PR[2], PR[3]); PUT4(2 * i + 3, PI[0], PI[1], PI[2], PI[3]);
          }
          gr[0] = hd[6]; gi[0] = hd[7];
          cmul(z1r, z1i, z1r, z1i, z2r, z2i); cmul(z2r, z2i, z2r, z2i, z4r, z4i);
          cmul(gr[0], gi[0], z1r, z1i, gr[1], gi[1]);
          cmul(gr[0], gi[0], z2r, z2i, gr[2], gi[2]); cmul(gr[1], gi[1], z2r, z2i, gr[3], gi[3]);
          #pragma unroll
          for (int b = 0; b < 4; b++) cmul(gr[b], gi[b], z4r, z4i, gr[4 + b], gi[4 + b]);
          PUT4(8, packh(gr[0], gr[1]), packh(gr[2], gr[3]), packh(gr[4], gr[5]), packh(gr[6], gr[7]));
          PUT4(9, packh(gi[0], gi[1]), packh(gi[2], gi[3]), packh(gi[4], gi[5]), packh(gi[6], gi[7]));
          {
            const uint32_t z = packh(wr[3], -wi[3]), a4r = packh(gr[0], gr[4]), a4i = packh(gi[0], gi[4]);
            hcm2(packh(gr[0], gr[2]), packh(gi[0], gi[2]), z, PR[0], PI[0]);
            hcm2(packh(gr[4], gr[6]), packh(gi[4], gi[6]), z, PR[1], PI[1]);
            hcm2(a4r, a4i, packh(wr[4], -wi[4]), PR[2], PI[2]);
            hcm2(a4r, a4i, packh(wr[5], -wi[5]), PR[3], PI[3]);
            PUT4(10, PR[0], PR[1], PR[2], PR[3]); PUT4(11, PI[0], PI[1], PI[2], PI[3]);
            float hr, hi_;
            cmul(gr[0], gi[0], wr[3], -wi[3], hr, hi_);
            const uint32_t cr = packh(gr[0], hr), ci = packh(gi[0], hi_);
            #pragma unroll
            for (int i = 0; i < 3; i++) hcm2(cr, ci, packh(wr[6 + i], -wi[6 + i]), PR[i], PI[i]);
            PUT4(12, PR[0], PR[1], PR[2], 0u); PUT4(13, PI[0], PI[1], PI[2], 0u);
          }
          fence_async();
          bar_sync(4, 128);
          wg_fence();
          #pragma unroll
          for (int s = 0; s < 8; s++) {
            const uint64_t d = dE + (s >> 2) * (BLK >> 4) + ((s >> 1) & 1) * 448 + (s & 1) * 16;
            wg_ss48_tt_h(ka, d, d + 256, s != 0);
          }
          wg_commit();
        }
        const float dsk = bf_lo(__shfl_sync(0xffffffff, pd, 8 + (it & 7)));
        head(min(it + 1, 4));
        asm volatile("{\n.reg .pred p;\nHL:\nsetp.eq.f32 p, %0, 0f46400000;\n@p bra HL;\n}" :: "f"(hd[0] + hd[2] + hd[4]));
        wg_wait<0>();
        pin<24>(ka);
        float kk[6];
        const bool up = w4 >= 2;
        #pragma unroll
        for (int n = 0; n < 3; n++) {
          sts64f(xa + n * BLK, up ? ka[12 + 4 * n] : ka[4 * n + 2], up ? ka[13 + 4 * n] : ka[4 * n + 3]);
          kk[2 * n] = up ? ka[14 + 4 * n] : ka[4 * n]; kk[2 * n + 1] = up ? ka[15 + 4 * n] : ka[4 * n + 1];
        }
        if (it) bar_sync(4, 128); else bar_sync(8, 160);
          if (it == 4 && w4 == 0) {
            mbar_wait(BAR(BR_U), 0);
            if (elect_one()) {
              mbar_expect_tx(BAR(BR_U2), 8192);
              bulk_ld(blk - 2 * BLK, g_uy + CHAN(2) * 2048, 4096, BAR(BR_U2)); bulk_ld(blk - BLK, g_uy + CHAN(3) * 2048, 4096, BAR(BR_U2));
            }
            __syncwarp();
          }
        #pragma unroll
        for (int n = 0; n < 3; n++) {
          uint32_t o[2]; lds64(o, xr_ + n * BLK);
          kk[2 * n] = (kk[2 * n] + __uint_as_float(o[0])) * fac; kk[2 * n + 1] = (kk[2 * n + 1] + __uint_as_float(o[1])) * fac;
        }
        if (t7 == 0) kk[0] += dsk;
        {
          const uint32_t v = pack2(kk[1], kk[0]), vh = v >> 16;
          const uint32_t u = pack2(kk[2], kk[3]), w = pack2(kk[4], kk[5]), uu = pack2(kk[2], kk[2]), us = pack2(kk[3], kk[2]);
          const uint32_t x = tq < 2 ? w : u, xh = x >> 16;
          sts32(blk + e0 + 4, v); sts16(blk + e0, vh); sts16(blk + e0 + 10, v);
          sts16(blk + e1, x); sts16(blk + e1 + 6, x); sts16(blk + e2, xh); sts16(blk + e2 + 6, xh);
          if (tq < 2) {
            const uint32_t pb = blk + e0 + 1024 + 8 * tq;
            sts32(pb + 4, uu); sts32(pb + 8, us); sts16(pb + 14, us);
            if (i2) { sts16(pb - 4, u); sts32(pb, uu); }
          }
          if (i2 == 0) {
            const uint32_t tb = blk + B_TBL;
            if (tq == 0) { sts16(tb + (16 + 256) * 4, u); sts16(tb + (T_S + 3) * 4, w); sts32(tb + (T_S + 4) * 4, pack2(kk[4], kk[4])); sts16(tb + (T_S + 5) * 4 + 2, w); }
            else { sts32(tb + 528 * 4, uu); sts32(tb + 529 * 4, uu); sts32(tb + 530 * 4, uu); sts16(tb + 531 * 4 + 2, u); sts16(tb + (T_F3 + 80 + 63) * 4, w); }
          }
        }
        if (t7 == 0) TS(49 + it);
      }
    }
    asm volatile("setmaxnreg.inc.sync.aligned.u32 136;");
    if (t7 == 0) TS(41);
    bar_sync(4, 128);
    if (t7 == 0) mbar_arrive(BAR(BR_KS));
    if (EN_ATT) mbar_wait(BAR(BR_GEMM), 0);
    }
  }
  const int tid = rtid(), lane = tid & 31, g = lane >> 2, tq = lane & 3, t7 = tid & 127;
  mbar_wait(BAR(BR_EPOCH), 0);
  const unsigned epoch = lds32(sb + OFF_EPOCH);
  const uint32_t ytag = (epoch & 1u) * 0x10001u, ym = lane < 4 ? 0x10001u : 0u;
  if (EN_SSM && wg != 1) {
    mbar_wait(BAR(BR_KS), 0);
    mbar_wait(BAR(BR_U), 0);
    if (tid == 256) TS(42);
    {
      const int pass = wg >> 1;
      const int k = pass ? w4 : 4;
      if (k & 2) mbar_wait(BAR(BR_U2), 0);
      const uint32_t blk = sb + OFF_BLK + k * BLK, tb = blk + B_TBL + (uint32_t)((g - 2 * tq) * 4);
      float acc[16][4];
      zero<64>(&acc[0][0]);
      const int kl = 16 * (lane >> 4) + 2 * (lane & 7) + ((lane >> 3) & 1);
      {
        auto ubase = [&](int sh) { const int q = kl - 2 * sh; return blk + (uint32_t)((q * 16) ^ ((q * 2) & 0x10)); };
#define LDQ(A, sh) _Pragma("unroll") for (int m = 0; m < 4; m++) load_quad(A[m], tb + (16 + 16 * (sh) + 128 * m) * 4);
#define LDB(B, ub, h) _Pragma("unroll") for (int p = 0; p < 4; p++) ldsm4(B[p], (ub) + (4 * (h) + p) * 512);
#define MLO(A, B) _Pragma("unroll") for (int m = 0; m < 4; m++) _Pragma("unroll") for (int cc = 0; cc < 8; cc++) mma16816(acc[cc + m], A[m], &B[cc >> 1][(cc & 1) * 2]);
#define MHI(A, B) _Pragma("unroll") for (int m = 0; m < 4; m++) _Pragma("unroll") for (int cc = 0; cc < 8 - m; cc++) mma16816(acc[8 + cc + m], A[m], &B[cc >> 1][(cc & 1) * 2]);
        int p_ = pass ? 0 : w4;
        const int pe = pass ? 4 : w4 + 1;
        uint32_t A[4][4], A2[4][4], Bl[4][4], Bh[4][4];
        uint32_t ub = ubase(p_ + 4);
        LDQ(A, p_ + 4) LDB(Bl, ub, 0)
        #pragma unroll 1
        for (; p_ < pe; p_++) {
          LDB(Bh, ub, 1)
          MLO(A, Bl)
          ub = ubase(p_);
          LDQ(A2, p_) LDB(Bl, ub, 0)
          MHI(A, Bh)
          LDB(Bh, ub, 1)
          load_quad(A[0], tb + (16 + 512 + 16 * (p_ & 1)) * 4); load_quad(A[1], tb + (T_S + 16 * (p_ & 1)) * 4);
          MLO(A2, Bl)
          if (p_ < 2) {
            #pragma unroll
            for (int cc = 0; cc < 8; cc++) mma16816(acc[cc + 4], A[0], &Bl[cc >> 1][(cc & 1) * 2]);
            #pragma unroll
            for (int cc = 0; cc < 4; cc++) mma16816(acc[cc + 12], A[0], &Bh[cc >> 1][(cc & 1) * 2]);
            #pragma unroll
            for (int cc = 0; cc < 8; cc++) mma16816(acc[cc + 8], A[1], &Bl[cc >> 1][(cc & 1) * 2]);
          }
          const int pn = ((p_ + 1) & 3) + 4;
          ub = ubase(pn);
          LDQ(A, pn) LDB(Bl, ub, 0)
          MHI(A2, Bh)
        }
      }
      if (t7 == 0) TS(pass ? 60 : 16);
      mbar_wait(BAR(BR_DRDY + 1), 0);
      {
        const int ih = (lane >> 3) & 1;
        const uint32_t dl = blk + B_D + (uint32_t)(((lane >> 4) * 8 + (lane & 7)) * 16);
        const uint32_t d0_ = dl + ih * 1552, d8_ = dl + (ih ? 0 : 1536), d3_ = dl + B_D7 + ih * 1024;
        auto cls2 = [&](uint32_t da, uint32_t ta) {
          uint32_t B[6][2], A[6][4];
          #pragma unroll
          for (int e = 0; e < 6; e++) { B[e][0] = lds32v(ta + (e + 4) * 32); B[e][1] = lds32v(ta + (e + 3) * 32); }
          #pragma unroll
          for (int kk = 0; kk < 6; kk++) ldsm4t(A[kk], da + kk * 256);
          #pragma unroll
          for (int e = 0; e < 6; e++)
            #pragma unroll
            for (int kk = 0; kk < 6; kk++) if (2 * kk + e + 4 < 16) mma16816(acc[2 * kk + e + 4], A[kk], B[e]);
        };
        auto cls3 = [&](uint32_t da, uint32_t ta) {
          uint32_t B[8][2], A[4][4];
          #pragma unroll
          for (int e = 0; e < 8; e++) { B[e][0] = lds32v(ta + (e + 8) * 32); B[e][1] = lds32v(ta + (e + 7) * 32); }
          #pragma unroll
          for (int kk = 0; kk < 4; kk++) ldsm4t(A[kk], da + kk * 256);
          #pragma unroll
          for (int kk = 0; kk < 4; kk++)
            #pragma unroll
            for (int e = 0; e < 8; e++) if (2 * kk + e + 8 < 16) mma16816(acc[2 * kk + e + 8], A[kk], B[e]);
        };
        if (pass) {
          #pragma unroll 1
          for (int a = 0; a < 2; a++) {
            cls2(d0_ + a * B_D5, tb + (T_F2 + 48 * a - 32) * 4);
            cls2(d8_ + a * B_D5, tb + (T_F2 + 48 * a + 64) * 4);
            cls3(d3_ + a * 2048, tb + (T_F3 + 80 * a - 64) * 4);
          }
        } else {
          cls2(((w4 & 2) ? d8_ : d0_) + (w4 & 1) * B_D5, tb + (T_F2 + 48 * w4 - 32) * 4);
          if (w4 >= 2) cls3(d3_ + (w4 - 2) * 2048, tb + (T_F3 + 80 * (w4 - 2) - 64) * 4);
        }
      }
      if (t7 == 0) TS(pass ? 61 : 17);
      const uint32_t ya = (pass ? sb + OFF_BLK + 3 * BLK + w4 * 4096 : blk) + (uint32_t)((kl * 16) ^ ((kl * 2) & 0x10));
#define YTAG(v) (((v) & ~ym) | (ytag & ym))
#define STY(p) stsm4t(ya + (p) * 512, YTAG(pack2(acc[2 * (p)][0], acc[2 * (p)][1])), pack2(acc[2 * (p)][2], acc[2 * (p)][3]), \
                      YTAG(pack2(acc[2 * (p) + 1][0], acc[2 * (p) + 1][1])), pack2(acc[2 * (p) + 1][2], acc[2 * (p) + 1][3]))
      if (pass == 0) {
        const uint32_t xw = blk + 4096 + w4 * 4096 + lane * 16, xr = blk + 4096 + w4 * 1024 + lane * 16;
        #pragma unroll
        for (int h = 0; h < 2; h++) {
          bar_sync(2, 128);
          #pragma unroll
          for (int i = 0; i < 8; i++)
            sts128(xw + i * 512, __float_as_uint(acc[8 * h + i][0]), __float_as_uint(acc[8 * h + i][1]), __float_as_uint(acc[8 * h + i][2]), __float_as_uint(acc[8 * h + i][3]));
          bar_sync(2, 128);
          float y[8];
          #pragma unroll
          for (int i = 0; i < 8; i++) {
            uint32_t o[4]; lds128(o, xr + (i >> 1) * 4096 + (i & 1) * 512);
            #pragma unroll
            for (int e = 0; e < 4; e++) y[4 * (i & 1) + e] = i < 2 ? __uint_as_float(o[e]) : y[4 * (i & 1) + e] + __uint_as_float(o[e]);
          }
          stsm4t(ya + (4 * h + w4) * 512, YTAG(pack2(y[0], y[1])), pack2(y[2], y[3]), YTAG(pack2(y[4], y[5])), pack2(y[6], y[7]));
        }
      } else {
        fence_async();
        bar_sync(4, 128);
        if (t7 == 0) mbar_arrive(BAR(BR_KS + 1));
        #pragma unroll
        for (int p = 0; p < 8; p++) STY(p);
      }
      fence_async();
      __syncwarp();
      if (lane == 0) mbar_arrive(BAR(BR_Y + 1) - 8 * pass);
      if (t7 == 0) TS(pass ? 62 : 18);
    }
  }
  if (wg < 2) {
    if (EN_ATT) {
    float oc[40]; zero<40>(oc);
    {
      constexpr uint64_t dw0 = mkdesc(SB0, OFF_WOR, 1024, 1), da0 = mkdesc(SB0, 2048, 128, 0);
      const uint32_t ck = sb + tid * 32 + ((lane >> 2) << 2), ck2 = ck + (wg ? 0 : 16384);
      uint32_t bad = 0;
      auto tile = [&](int i, uint32_t so) {
        const uint32_t al = (uint32_t)da0 + wg * 64 + (so >> 4), wl = (uint32_t)dw0 + i * 640 - (i >> 1) * (1278 << 16);
        wg_fence();
        #pragma unroll
        for (int s = 0; s < 5; s++) wg_ss80_tb(oc, desc2(al + s * 256, da0 >> 32), desc2(wl + s * 128, dw0 >> 32), (i | s) != 0);
        wg_commit();
        bad |= (lds32(ck + so) ^ epoch) | (lds32(ck + so + 8192) ^ epoch) | (lds32(ck2 + so) ^ epoch);
      };
      if (w4 == 0) {
        if (EN_SSM) mbar_wait(BAR(BR_Y), 0);
        mbar_wait(BAR(BR_WO), 0);
        mbar_wait(BAR(BR_WO + 1), 0);
      }
      bar_sync(1, 256);
      if (tid == 0) TS(9);
      tile(0, SLOT(0));
      #pragma unroll 1
      for (int i = 1; i < 8; i++) {
        mbar_wait(BAR(BR_OFULL) + 8 * i, 0);
        tile(i, SLOT(i));
        wg_wait<1>();
        if (lane == 0) mbar_arrive(BAR(BR_OEMPTY - 1) + 8 * i);
      }
      #pragma unroll 1
      for (int n = 0; n < 56; n++) {
        const int i = n & 7;
        if (i == 0) {
          uint32_t any;
          asm volatile("{\n.reg .pred p;\nsetp.ne.u32 p, %1, 0;\nbarrier.red.or.pred p, 1, 256, p;\nselp.u32 %0, 1, 0, p;\n}" : "=r"(any) : "r"(bad & 1u) : "memory");
          if (!any) break;
          bad = 0;
          FIXCNT
        }
        wg_wait<0>();
        bar_sync(1, 256);
        if (tid == 0) { mbar_expect_tx(BAR(BR_RETRY), 20480); bulk_ld(sb + SLOT(5), &g_o[(r * 8 + CHUNK(i)) * 1280], 20480, BAR(BR_RETRY)); }
        mbar_wait(BAR(BR_RETRY), n & 1);
        tile(i, SLOT(5));
      }
      wg_wait<0>();
      pin<40>(oc);
    }
    if (tid == 0) TS(10);
    {
      const int row = w4 * 16 + (lane & 15);
      const uint32_t ob = sb + SLOT(3) + wg * 10240;
      #pragma unroll
      for (int j = 0; j < 8; j += 2)
        stsm4(ob + row * 128 + (((j + (lane >> 4)) ^ (row & 7)) << 4), pack2(oc[4 * j], oc[4 * j + 1]), pack2(oc[4 * j + 2], oc[4 * j + 3]),
              pack2(oc[4 * j + 4], oc[4 * j + 5]), pack2(oc[4 * j + 6], oc[4 * j + 7]));
      stsm4(ob + 8192 + row * 32 + (lane >> 4) * 16, pack2(oc[32], oc[33]), pack2(oc[34], oc[35]), pack2(oc[36], oc[37]), pack2(oc[38], oc[39]));
      fence_async();
      bar_sync(2 + wg, 128);
      if (w4 == 0 && elect_one()) {
        tma2d_st(&prm.m[M_O64], ob, 640 + c * 64, r * 128 + wg * 64);
        tma2d_st(&prm.m[M_O16], ob + 8192, 1152 + c * 16, r * 128 + wg * 64);
        bulk_commit(); bulk_wait0_read();
        if (wg == 0) { TS(11); DUMP(0, 20); }
      }
    }
    }
  } else if (EN_SSM) {
    const uint32_t yb = sb + OFF_BLK + 3 * BLK;
    const int mi = lane >> 3, rw = lane & 7;
    if (w4 == 0) {
      mbar_wait(BAR(BR_Y), 0);
      if (elect_one()) {
        bulk_st(g_uy + (640 + CHAN(0)) * 2048, yb, 16384);
        bulk_commit(); bulk_wait0();
        st_rlx(FLAG(2, r, c), epoch);
      }
      __syncwarp();
      poll_all(FLAG(2, lane & 15, c), epoch);
    }
    uint32_t v[8][4];
    #pragma unroll 1
    for (int n = 0; n < 64; n++) {
      if (w4 == 0) {
        if (elect_one()) {
          mbar_expect_tx(BAR(BR_YIN), 16384);
          tma2d(yb, &prm.m[M_SY], BAR(BR_YIN), r * 128, 640 + c * 80);
          tma2d(yb + 8192, &prm.m[M_SY], BAR(BR_YIN), r * 128 + 64, 640 + c * 80);
          TS(55);
        }
        __syncwarp();
        mbar_wait(BAR(BR_YIN), n & 1);
      }
      bar_sync(4, 128);
      uint32_t bad = 0, any;
      #pragma unroll
      for (int q = 0; q < 8; q++) {
        ldsm4t(v[q], yb + (w4 * 16 + rw) * 128 + ((mi ^ rw ^ ((q & 1) * 4) ^ ((q >> 1) & 1)) << 4) + ((q >> 1) & 1) * 8192 + (q >> 2) * 1024);
        bad |= (v[q][0] ^ ytag) | (v[q][2] ^ ytag);
      }
      asm volatile("{\n.reg .pred p;\nsetp.ne.u32 p, %1, 0;\nbarrier.red.or.pred p, 4, 128, p;\nselp.u32 %0, 1, 0, p;\n}" : "=r"(any) : "r"(bad & ym) : "memory");
      if (!any) break;
      FIXCNT
    }
    #pragma unroll
    for (int q = 0; q < 8; q++) stsm4(yb + lane * 128 + (((2 * w4 + (q >> 2)) ^ rw) << 4) + (q & 3) * 4096, v[q][0] & ~ym, v[q][1], v[q][2] & ~ym, v[q][3]);
    fence_async();
    bar_sync(4, 128);
    if (w4 == 0 && elect_one()) {
      tma2d_st(&prm.m[M_O64], yb, c * 80, r * 128);
      tma2d_st(&prm.m[M_O64], yb + 8192, c * 80, r * 128 + 64);
      bulk_commit(); bulk_wait0_read();
      TS(56); DUMP(40, 64);
    }
  }
  }
}

typedef CUresult (*EncFn)(CUtensorMap*, CUtensorMapDataType, cuuint32_t, void*, const cuuint64_t*, const cuuint64_t*, const cuuint32_t*,
                          const cuuint32_t*, CUtensorMapInterleave, CUtensorMapSwizzle, CUtensorMapL2promotion, CUtensorMapFloatOOBfill);
static void mkmap(EncFn enc, CUtensorMap* m, const void* base, int rank, const cuuint64_t* dims, const cuuint64_t* strides, const cuuint32_t* box, CUtensorMapSwizzle swz) {
  cuuint32_t es[5] = {1, 1, 1, 1, 1};
  enc(m, CU_TENSOR_MAP_DATA_TYPE_BFLOAT16, rank, const_cast<void*>(base), dims, strides, box, es, CU_TENSOR_MAP_INTERLEAVE_NONE, swz,
      CU_TENSOR_MAP_L2_PROMOTION_L2_128B, CU_TENSOR_MAP_FLOAT_OOB_FILL_NONE);
}

extern "C" void kernel_launch(void* const* d_in, const int* in_sizes, int n_in, void* d_out, int out_size) {
  void* fn = nullptr; cudaDriverEntryPointQueryResult qr;
  cudaGetDriverEntryPoint("cuTensorMapEncodeTiled", &fn, cudaEnableDefault, &qr);
  EncFn enc = (EncFn)fn;
  void* uy = nullptr; cudaGetSymbolAddress(&uy, g_uy);
  const cuuint64_t dx[2] = {640, 2048}, sx[1] = {1280};
  const cuuint32_t bx[2] = {64, 128}, bu[2] = {80, 128};
  const cuuint64_t dw[3] = {640, 640, 3}, sw[2] = {3840, 1280};
  const cuuint32_t br[3] = {16, 32, 3};
  const cuuint64_t dwa[4] = {64, 640, 10, 3}, swa[3] = {3840, 128, 1280}, dwb[4] = {32, 640, 20, 3}, swb[3] = {3840, 64, 1280};
  const cuuint32_t bwa[4] = {64, 32, 1, 3}, bwb[4] = {32, 32, 2, 3};
  const cuuint64_t dwo[2] = {640, 640};
  const cuuint32_t bwo[2] = {64, 80}, bo64[2] = {64, 64}, bo16[2] = {16, 64};
  const cuuint64_t dsa[2] = {2048, 1280}, ssa[1] = {4096};
  const cuuint32_t bsa[2] = {64, 80}, bsy[2] = {64, 64}, bsz[2] = {64, 16};
  const cuuint64_t dout[2] = {1280, 2048}, sout[1] = {2560};
  Params prm;
  mkmap(enc, &prm.m[M_X], d_in[7], 2, dx, sx, bx, CU_TENSOR_MAP_SWIZZLE_128B);
  mkmap(enc, &prm.m[M_W128], d_in[8], 4, dwa, swa, bwa, CU_TENSOR_MAP_SWIZZLE_128B);
  mkmap(enc, &prm.m[M_W64], d_in[8], 4, dwb, swb, bwb, CU_TENSOR_MAP_SWIZZLE_64B);
  mkmap(enc, &prm.m[M_WR], d_in[8], 3, dw, sw, br, CU_TENSOR_MAP_SWIZZLE_32B);
  mkmap(enc, &prm.m[M_U], d_in[0], 2, dx, sx, bu, CU_TENSOR_MAP_SWIZZLE_NONE);
  mkmap(enc, &prm.m[M_WO], d_in[9], 2, dwo, sx, bwo, CU_TENSOR_MAP_SWIZZLE_128B);
  mkmap(enc, &prm.m[M_O64], d_out, 2, dout, sout, bo64, CU_TENSOR_MAP_SWIZZLE_128B);
  mkmap(enc, &prm.m[M_O16], d_out, 2, dout, sout, bo16, CU_TENSOR_MAP_SWIZZLE_NONE);
  mkmap(enc, &prm.m[M_SA], uy, 2, dsa, ssa, bsa, CU_TENSOR_MAP_SWIZZLE_128B);
  mkmap(enc, &prm.m[M_SY], uy, 2, dsa, ssa, bsy, CU_TENSOR_MAP_SWIZZLE_128B);
  mkmap(enc, &prm.m[M_SZ], uy, 2, dsa, ssa, bsz, CU_TENSOR_MAP_SWIZZLE_128B);
  prm.u = (const __nv_bfloat16*)d_in[0]; prm.wo = (const __nv_bfloat16*)d_in[9];
  for (int i = 0; i < 4; i++) prm.par[i] = (const __nv_bfloat16*)d_in[1 + i];
  prm.logdt = (const __nv_bfloat16*)d_in[5]; prm.dskip = (const __nv_bfloat16*)d_in[6];
  cudaFuncSetAttribute(fused_kernel, cudaFuncAttributeMaxDynamicSharedMemorySize, SMEM_BYTES);
  cudaLaunchConfig_t cfg = {};
  cfg.gridDim = dim3(128); cfg.blockDim = dim3(512); cfg.dynamicSmemBytes = SMEM_BYTES; cfg.stream = cudaStreamPerThread;
  cudaLaunchAttribute at[1];
  at[0].id = cudaLaunchAttributeClusterDimension; at[0].val.clusterDim.x = 2; at[0].val.clusterDim.y = 1; at[0].val.clusterDim.z = 1;
  cfg.attrs = at; cfg.numAttrs = 1;
  cudaLaunchKernelEx(&cfg, fused_kernel, prm);
}
```

```cpp
#include <cuda_runtime.h>
#include <cuda_bf16.h>
#include <cuda_fp16.h>
#include <cuda.h>
#include <stdint.h>

#define KST 2
#define UKB 4
#define UPF 0
#define CONV_AT 1
#define EN_ATT 1
#define EN_SSM 1

__device__ __align__(1024) __nv_bfloat16 g_uy[2 * 640 * 2048];
__device__ __align__(128) uint4 g_kvp[8 * 16 * 240];
__device__ __align__(128) uint4 g_o[128 * 1280];
__device__ __align__(128) unsigned g_flag[4 * 128 * 32];
__device__ unsigned g_epoch[128];
#define TS(i) do {} while (0)
#define DUMP(lo, hi) do {} while (0)
#define FIXCNT

constexpr uint32_t SB0 = 1024;
constexpr uint32_t W_SLOT = 15360, OFF_X = 76800;
constexpr uint32_t OFF_WOR = 81920, OFF_KVP = 10240, OFF_KVS = 71680, OFF_PK = 10240, OFF_V = 30720, OFF_EXTRA = 102400, OFF_KVB = OFF_EXTRA;
constexpr uint32_t OFF_BAR = 125952, OFF_BLK = 128000, BLK = 20480;
constexpr uint32_t B_D = 4096, B_D5 = 3088, B_D7 = 6176, B_D9 = 8224, B_TBL = 14400;
constexpr int T_S = 576, T_F2 = 624, T_F3 = 816;
constexpr uint32_t OFF_UT = OFF_BLK + 4 * BLK;
constexpr uint32_t SMEM_BYTES = OFF_BLK + 5 * BLK;
enum { BR_FULL = 0, BR_WO = 5, BR_PUB = 7, BR_KVP = 8, BR_U = 9, BR_SUM = 10, BR_GEMM = 11, BR_UIN = 12, BR_YIN = 13, BR_EPOCH = 14,
       BR_FREE = 15, BR_RETRY = 17, BR_UOUT = 18, BR_OFULL = 18, BR_KS = 26, BR_EMPTY = 31, BR_OEMPTY = 36, BR_Y = 43, BR_OSTG = 45,
       BR_DRDY = 46, BR_U2 = 48, BR_COUNT = 50 };
constexpr uint32_t OFF_EPOCH = OFF_BAR + 8 * BR_COUNT;
enum { M_X, M_W128, M_W64, M_WR, M_U, M_WO, M_O64, M_O16, M_SA, M_OUT, M_COUNT };

__device__ __forceinline__ long long clk64() { long long t; asm volatile("mov.u64 %0, %%clock64;" : "=l"(t) :: "memory"); return t; }
__device__ __forceinline__ uint32_t smem_u32(const void* p) { return (uint32_t)__cvta_generic_to_shared(p); }
__host__ __device__ constexpr uint64_t mkdesc(uint32_t addr, uint32_t lbo, uint32_t sbo, uint32_t swz) {
  return (uint64_t)((addr & 0x3FFFF) >> 4) | ((uint64_t)(lbo >> 4) << 16) | ((uint64_t)(sbo >> 4) << 32) | ((uint64_t)swz << 62);
}
__device__ __forceinline__ uint64_t desc2(uint32_t lo, uint32_t hi) { uint64_t d; asm("mov.b64 %0, {%1, %2};" : "=l"(d) : "r"(lo), "r"(hi)); return d; }
__device__ __forceinline__ void mbar_init(uint32_t bar, uint32_t cnt) { asm volatile("mbarrier.init.shared::cta.b64 [%0], %1;" :: "r"(bar), "r"(cnt) : "memory"); }
__device__ __forceinline__ void mbar_expect_tx(uint32_t bar, uint32_t bytes) { asm volatile("mbarrier.arrive.expect_tx.shared::cta.b64 _, [%0], %1;" :: "r"(bar), "r"(bytes) : "memory"); }
__device__ __forceinline__ void mbar_arrive(uint32_t bar) { asm volatile("mbarrier.arrive.shared::cta.b64 _, [%0];" :: "r"(bar) : "memory"); }
__device__ __forceinline__ void mbar_wait(uint32_t bar, uint32_t parity) {
  asm volatile("{\n.reg .pred p;\n.reg .u32 c;\nmov.u32 c, 0;\n"
    "WL:\nmbarrier.try_wait.parity.shared::cta.b64 p, [%0], %1;\n@p bra WD;\n"
    "add.u32 c, c, 1;\nsetp.lt.u32 p, c, 200000;\n@p bra WL;\nWD:\n}" :: "r"(bar), "r"(parity) : "memory");
}
__device__ __forceinline__ void poll_all(const unsigned* p, unsigned val) {
  asm volatile("{\n.reg .pred p;\n.reg .u32 c, v;\nmov.u32 c, 0;\n"
    "PL:\nld.relaxed.gpu.global.u32 v, [%0];\nsetp.eq.u32 p, v, %1;\nvote.sync.all.pred p, p, 0xffffffff;\n@p bra PD;\n"
    "add.u32 c, c, 1;\nsetp.lt.u32 p, c, 100000;\n@p bra PL;\nPD:\n}" :: "l"(p), "r"(val) : "memory");
}
__device__ __forceinline__ void poll_all_acq(const unsigned* p, unsigned val) {
  asm volatile("{\n.reg .pred p;\n.reg .u32 c, v;\nmov.u32 c, 0;\n"
    "PL:\nld.acquire.gpu.global.u32 v, [%0];\nsetp.eq.u32 p, v, %1;\nvote.sync.all.pred p, p, 0xffffffff;\n@p bra PD;\n"
    "nanosleep.u32 300;\nadd.u32 c, c, 1;\nsetp.lt.u32 p, c, 100000;\n@p bra PL;\nPD:\n}" :: "l"(p), "r"(val) : "memory");
}
__device__ __forceinline__ unsigned poll_bit(const unsigned* p, unsigned val, unsigned mask) {
  unsigned bal;
  asm volatile("{\n.reg .pred p;\n.reg .u32 c, v;\nmov.u32 c, 0;\n"
    "PL:\nld.relaxed.gpu.global.u32 v, [%1];\nsetp.eq.u32 p, v, %2;\nvote.sync.ballot.b32 %0, p, 0xffffffff;\n"
    "and.b32 v, %0, %3;\nsetp.ne.u32 p, v, 0;\n@p bra PD;\n"
    "add.u32 c, c, 1;\nsetp.lt.u32 p, c, 100000;\n@p bra PL;\nPD:\n}" : "=&r"(bal) : "l"(p), "r"(val), "r"(mask) : "memory");
  return bal;
}
__device__ __forceinline__ void fix128_w0(uint32_t* v, const void* p, uint32_t tag, uint32_t mask) {
  asm volatile("{\n.reg .pred p;\n.reg .u32 c, x;\n.reg .b128 t;\n.reg .b64 lo, hi;\nmov.u32 c, 0;\n"
    "FL:\nxor.b32 x, %0, %5;\nand.b32 x, x, %6;\nsetp.eq.u32 p, x, 0;\n@p bra FD;\n"
    "ld.relaxed.gpu.global.b128 t, [%4];\nmov.b128 {lo, hi}, t;\nmov.b64 {%0, %1}, lo;\nmov.b64 {%2, %3}, hi;\n"
    "add.u32 c, c, 1;\nsetp.lt.u32 p, c, 100000;\n@p bra FL;\nFD:\n}"
    : "+r"(v[0]), "+r"(v[1]), "+r"(v[2]), "+r"(v[3]) : "l"(p), "r"(tag), "r"(mask) : "memory");
}
__device__ __forceinline__ void fix128_w3(uint32_t* v, const void* p, uint32_t tag, uint32_t mask) {
  asm volatile("{\n.reg .pred p;\n.reg .u32 c, x;\n.reg .b128 t;\n.reg .b64 lo, hi;\nmov.u32 c, 0;\n"
    "FL:\nxor.b32 x, %3, %5;\nand.b32 x, x, %6;\nsetp.eq.u32 p, x, 0;\n@p bra FD;\n"
    "ld.relaxed.gpu.global.b128 t, [%4];\nmov.b128 {lo, hi}, t;\nmov.b64 {%0, %1}, lo;\nmov.b64 {%2, %3}, hi;\n"
    "add.u32 c, c, 1;\nsetp.lt.u32 p, c, 100000;\n@p bra FL;\nFD:\n}"
    : "+r"(v[0]), "+r"(v[1]), "+r"(v[2]), "+r"(v[3]) : "l"(p), "r"(tag), "r"(mask) : "memory");
}
__device__ __forceinline__ void fence_acq() { asm volatile("fence.acq_rel.gpu;" ::: "memory"); }
__device__ __forceinline__ bool elect_one() {
  uint32_t p; asm volatile("{\n.reg .pred P;\nelect.sync _|P, 0xffffffff;\nselp.u32 %0, 1, 0, P;\n}" : "=r"(p)); return p;
}
__device__ __forceinline__ void bar_sync(int id, int n) { asm volatile("bar.sync %0, %1;" :: "r"(id), "r"(n) : "memory"); }
__device__ __forceinline__ void fence_async() { asm volatile("fence.proxy.async.shared::cta;" ::: "memory"); }
__device__ __forceinline__ void fence_async_g() { asm volatile("fence.proxy.async.global;" ::: "memory"); }
__device__ __forceinline__ void tma2d(uint32_t dst, const CUtensorMap* m, uint32_t bar, int c0, int c1) {
  asm volatile("cp.async.bulk.tensor.2d.shared::cluster.global.mbarrier::complete_tx::bytes [%0], [%1, {%3, %4}], [%2];"
    :: "r"(dst), "l"(m), "r"(bar), "r"(c0), "r"(c1) : "memory");
}
__device__ __forceinline__ void tma3d(uint32_t dst, const CUtensorMap* m, uint32_t bar, int c0, int c1, int c2) {
  asm volatile("cp.async.bulk.tensor.3d.shared::cluster.global.mbarrier::complete_tx::bytes [%0], [%1, {%3, %4, %5}], [%2];"
    :: "r"(dst), "l"(m), "r"(bar), "r"(c0), "r"(c1), "r"(c2) : "memory");
}
__device__ __forceinline__ void tma4d(uint32_t dst, const CUtensorMap* m, uint32_t bar, int c0, int c1, int c2, int c3) {
  asm volatile("cp.async.bulk.tensor.4d.shared::cluster.global.mbarrier::complete_tx::bytes [%0], [%1, {%3, %4, %5, %6}], [%2];"
    :: "r"(dst), "l"(m), "r"(bar), "r"(c0), "r"(c1), "r"(c2), "r"(c3) : "memory");
}
__device__ __forceinline__ void tma2d_st(const CUtensorMap* m, uint32_t src, int c0, int c1) {
  asm volatile("cp.async.bulk.tensor.2d.global.shared::cta.bulk_group [%0, {%2, %3}], [%1];"
    :: "l"(m), "r"(src), "r"(c0), "r"(c1) : "memory");
}
__device__ __forceinline__ void bulk_ld(uint32_t dst, const void* src, uint32_t bytes, uint32_t bar) {
  asm volatile("cp.async.bulk.shared::cluster.global.mbarrier::complete_tx::bytes [%0], [%1], %2, [%3];"
    :: "r"(dst), "l"(src), "r"(bytes), "r"(bar) : "memory");
}
__device__ __forceinline__ void bulk_st(void* dst, uint32_t src, uint32_t bytes) {
  asm volatile("cp.async.bulk.global.shared::cta.bulk_group [%0], [%1], %2;" :: "l"(dst), "r"(src), "r"(bytes) : "memory");
}
__device__ __forceinline__ void bulk_commit() { asm volatile("cp.async.bulk.commit_group;" ::: "memory"); }
__device__ __forceinline__ void bulk_wait0() { asm volatile("cp.async.bulk.wait_group 0;" ::: "memory"); }
__device__ __forceinline__ void bulk_wait0_read() { asm volatile("cp.async.bulk.wait_group.read 0;" ::: "memory"); }
__device__ __forceinline__ unsigned ld_rlx(const unsigned* p) { unsigned v; asm volatile("ld.relaxed.gpu.global.u32 %0, [%1];" : "=r"(v) : "l"(p) : "memory"); return v; }
__device__ __forceinline__ unsigned ld_acq(const unsigned* p) { unsigned v; asm volatile("ld.acquire.gpu.global.u32 %0, [%1];" : "=r"(v) : "l"(p) : "memory"); return v; }
__device__ __forceinline__ void st_rlx(unsigned* p, unsigned v) { asm volatile("st.relaxed.gpu.global.u32 [%0], %1;" :: "l"(p), "r"(v) : "memory"); }
__device__ __forceinline__ void st_rel(unsigned* p, unsigned v) { asm volatile("st.release.gpu.global.u32 [%0], %1;" :: "l"(p), "r"(v) : "memory"); }
__device__ __forceinline__ void ld128_rlx(uint32_t* v, const void* p) {
  asm volatile("{\n.reg .b128 t;\n.reg .b64 lo, hi;\nld.relaxed.gpu.global.b128 t, [%4];\nmov.b128 {lo, hi}, t;\n"
    "mov.b64 {%0, %1}, lo;\nmov.b64 {%2, %3}, hi;\n}" : "=r"(v[0]), "=r"(v[1]), "=r"(v[2]), "=r"(v[3]) : "l"(p) : "memory");
}
__device__ __forceinline__ void st128_rlx(void* p, const uint32_t* v) {
  asm volatile("{\n.reg .b128 t;\n.reg .b64 lo, hi;\nmov.b64 lo, {%1, %2};\nmov.b64 hi, {%3, %4};\nmov.b128 t, {lo, hi};\n"
    "st.relaxed.gpu.global.b128 [%0], t;\n}" :: "l"(p), "r"(v[0]), "r"(v[1]), "r"(v[2]), "r"(v[3]) : "memory");
}
__device__ __forceinline__ uint32_t lds32(uint32_t a) { uint32_t v; asm volatile("ld.shared.u32 %0, [%1];" : "=r"(v) : "r"(a) : "memory"); return v; }
__device__ __forceinline__ uint32_t lds32v(uint32_t a) { uint32_t v; asm volatile("ld.volatile.shared.u32 %0, [%1];" : "=r"(v) : "r"(a) : "memory"); return v; }
__device__ __forceinline__ uint32_t cpa(uint32_t a, uint32_t one) { uint32_t v; asm volatile("mul.lo.u32 %0, %1, %2;" : "=r"(v) : "r"(a), "r"(one)); return v; }
__device__ __forceinline__ uint32_t cpb(uint32_t a, uint32_t zero) { uint32_t v; asm volatile("or.b32 %0, %1, %2;" : "=r"(v) : "r"(a), "r"(zero)); return v; }
__device__ __forceinline__ uint32_t lds16(uint32_t a) { uint16_t v; asm volatile("ld.shared.u16 %0, [%1];" : "=h"(v) : "r"(a) : "memory"); return v; }
__device__ __forceinline__ float ldsf(uint32_t a) { float v; asm volatile("ld.shared.f32 %0, [%1];" : "=f"(v) : "r"(a) : "memory"); return v; }
__device__ __forceinline__ void lds128(uint32_t* v, uint32_t a) { asm volatile("ld.shared.v4.u32 {%0,%1,%2,%3}, [%4];" : "=r"(v[0]), "=r"(v[1]), "=r"(v[2]), "=r"(v[3]) : "r"(a) : "memory"); }
__device__ __forceinline__ void sts32(uint32_t a, uint32_t v) { asm volatile("st.shared.u32 [%0], %1;" :: "r"(a), "r"(v) : "memory"); }
__device__ __forceinline__ void sts16(uint32_t a, uint32_t v) { asm volatile("st.shared.u16 [%0], %1;" :: "r"(a), "h"((uint16_t)v) : "memory"); }
__device__ __forceinline__ void sts64f(uint32_t a, float x, float y) { asm volatile("st.shared.v2.f32 [%0], {%1,%2};" :: "r"(a), "f"(x), "f"(y) : "memory"); }
__device__ __forceinline__ void sts128(uint32_t a, uint32_t x, uint32_t y, uint32_t z, uint32_t w) { asm volatile("st.shared.v4.u32 [%0], {%1,%2,%3,%4};" :: "r"(a), "r"(x), "r"(y), "r"(z), "r"(w) : "memory"); }
__device__ __forceinline__ void stsm4(uint32_t a, uint32_t r0, uint32_t r1, uint32_t r2, uint32_t r3) {
  asm volatile("stmatrix.sync.aligned.m8n8.x4.shared.b16 [%0], {%1,%2,%3,%4};" :: "r"(a), "r"(r0), "r"(r1), "r"(r2), "r"(r3) : "memory");
}
__device__ __forceinline__ void stsm4t(uint32_t a, uint32_t r0, uint32_t r1, uint32_t r2, uint32_t r3) {
  asm volatile("stmatrix.sync.aligned.m8n8.x4.trans.shared.b16 [%0], {%1,%2,%3,%4};" :: "r"(a), "r"(r0), "r"(r1), "r"(r2), "r"(r3) : "memory");
}
__device__ __forceinline__ void ldsm4t(uint32_t* r, uint32_t a) {
  asm volatile("ldmatrix.sync.aligned.m8n8.x4.trans.shared.b16 {%0,%1,%2,%3}, [%4];" : "=r"(r[0]), "=r"(r[1]), "=r"(r[2]), "=r"(r[3]) : "r"(a) : "memory");
}
__device__ __forceinline__ void ldsm4(uint32_t* r, uint32_t a) {
  asm volatile("ldmatrix.sync.aligned.m8n8.x4.shared.b16 {%0,%1,%2,%3}, [%4];" : "=r"(r[0]), "=r"(r[1]), "=r"(r[2]), "=r"(r[3]) : "r"(a) : "memory");
}
__device__ __forceinline__ void mma16816(float* d, const uint32_t* a, const uint32_t* b) {
  asm volatile("mma.sync.aligned.m16n8k16.row.col.f32.bf16.bf16.f32 {%0,%1,%2,%3}, {%4,%5,%6,%7}, {%8,%9}, {%0,%1,%2,%3};"
    : "+f"(d[0]), "+f"(d[1]), "+f"(d[2]), "+f"(d[3]) : "r"(a[0]), "r"(a[1]), "r"(a[2]), "r"(a[3]), "r"(b[0]), "r"(b[1]));
}
__device__ __forceinline__ uint32_t pack2(float lo, float hi) { uint32_t r; asm("cvt.rn.bf16x2.f32 %0, %1, %2;" : "=r"(r) : "f"(hi), "f"(lo)); return r; }
__device__ __forceinline__ uint32_t packh(float lo, float hi) { uint32_t r; asm("cvt.rn.f16x2.f32 %0, %1, %2;" : "=r"(r) : "f"(hi), "f"(lo)); return r; }
__device__ __forceinline__ uint32_t hcmul(uint32_t x, uint32_t zp, uint32_t zq) {
  const __half2 xx = *reinterpret_cast<__half2*>(&x);
  const __half2 r = __hfma2(__high2half2(xx), *reinterpret_cast<__half2*>(&zq), __hmul2(__low2half2(xx), *reinterpret_cast<__half2*>(&zp)));
  return *reinterpret_cast<const uint32_t*>(&r);
}
__device__ __forceinline__ void hcm2(uint32_t xr, uint32_t xi, uint32_t z, uint32_t& pr, uint32_t& pi) {
  const __half2 a = *reinterpret_cast<__half2*>(&xr), b = *reinterpret_cast<__half2*>(&xi), zz = *reinterpret_cast<__half2*>(&z);
  const __half2 re = __hfma2(__hneg2(b), __high2half2(zz), __hmul2(a, __low2half2(zz)));
  const __half2 im = __hfma2(a, __high2half2(zz), __hmul2(b, __low2half2(zz)));
  pr = *reinterpret_cast<const uint32_t*>(&re); pi = *reinterpret_cast<const uint32_t*>(&im);
}
__device__ __forceinline__ void sts64(uint32_t a, uint32_t x, uint32_t y) { asm volatile("st.shared.v2.u32 [%0], {%1,%2};" :: "r"(a), "r"(x), "r"(y) : "memory"); }
__device__ __forceinline__ void lds64(uint32_t* v, uint32_t a) { asm volatile("ld.shared.v2.u32 {%0,%1}, [%2];" : "=r"(v[0]), "=r"(v[1]) : "r"(a) : "memory"); }
__device__ __forceinline__ float bf_lo(uint32_t v) { return __uint_as_float(v << 16); }
__device__ __forceinline__ float bf_hi(uint32_t v) { return __uint_as_float(v & 0xffff0000u); }
__device__ __forceinline__ float bf_round(float x) { return bf_lo(pack2(x, 0.f)); }
__device__ __forceinline__ float ex2(float x) { float r; asm("ex2.approx.ftz.f32 %0, %1;" : "=f"(r) : "f"(x)); return r; }
__device__ __forceinline__ float phi(float t, float l2e = 1.44269504089f) {
  float e = ex2(t * l2e) + 1e-6f;
  asm("{\n.reg .pred p;\nsetp.gt.f32 p, %1, 0f00000000;\n@p add.f32 %0, %1, 0f3F800008;\n}" : "+f"(e) : "f"(t));
  return e;
}
__device__ __forceinline__ void wg_fence() { asm volatile("wgmma.fence.sync.aligned;" ::: "memory"); }
__device__ __forceinline__ void wg_commit() { asm volatile("wgmma.commit_group.sync.aligned;" ::: "memory"); }
template <int N> __device__ __forceinline__ void wg_wait() { asm volatile("wgmma.wait_group.sync.aligned %0;" :: "n"(N) : "memory"); }
template <int N> __device__ __forceinline__ void pin(float* a) {
  #pragma unroll
  for (int i = 0; i < N; i++) asm volatile("" : "+f"(a[i]) :: "memory");
}
__device__ __forceinline__ int rtid() { int t; asm volatile("mov.u32 %0, %%tid.x;" : "=r"(t)); return t; }
__device__ __forceinline__ int opaque(int v) { asm volatile("" : "+r"(v)); return v; }
template <int N> __device__ __forceinline__ void zero(float* a) {
  #pragma unroll
  for (int i = 0; i < N; i++) asm volatile("mov.b32 %0, 0;" : "=f"(a[i]));
}
template <int N> __device__ __forceinline__ void pinu(uint32_t* a) {
  #pragma unroll
  for (int i = 0; i < N; i++) asm volatile("" : "+r"(a[i]) :: "memory");
}
__device__ __forceinline__ void cexp_t(float lg2mag, float turns, float& re, float& im) {
  float m = ex2(lg2mag);
  float fr = (turns - __fadd_rn(__fadd_rn(turns, 12582912.f), -12582912.f)) * 6.283185307f;
  re = m * __cosf(fr); im = m * __sinf(fr);
}
__device__ __forceinline__ void cmul(float ar, float ai, float br, float bi, float& cr, float& ci) {
  cr = fmaf(ar, br, -ai * bi); ci = fmaf(ar, bi, ai * br);
}

__device__ __forceinline__ void wg_ss48_tt(float* d, uint64_t da, uint64_t db, int scale_d) {
  asm volatile("{\n.reg .pred p;\nsetp.ne.b32 p, %26, 0;\n"
    "wgmma.mma_async.sync.aligned.m64n48k16.f32.bf16.bf16 "
    "{%0, %1, %2, %3, %4, %5, %6, %7, %8, %9, %10, %11, %12, %13, %14, %15, %16, %17, %18, %19, %20, %21, %22, %23}, %24, %25, p, 1, 1, 1, 1;\n}\n"
    : "+f"(d[0]), "+f"(d[1]), "+f"(d[2]), "+f"(d[3]), "+f"(d[4]), "+f"(d[5]), "+f"(d[6]), "+f"(d[7]), "+f"(d[8]), "+f"(d[9]), "+f"(d[10]), "+f"(d[11]), "+f"(d[12]), "+f"(d[13]), "+f"(d[14]), "+f"(d[15]), "+f"(d[16]), "+f"(d[17]), "+f"(d[18]), "+f"(d[19]), "+f"(d[20]), "+f"(d[21]), "+f"(d[22]), "+f"(d[23])
    : "l"(da), "l"(db), "r"(scale_d));
}
__device__ __forceinline__ void wg_rs88_tb(float* d, const uint32_t* a, uint64_t db, int scale_d) {
  asm volatile("{\n.reg .pred p;\nsetp.ne.b32 p, %49, 0;\n"
    "wgmma.mma_async.sync.aligned.m64n88k16.f32.bf16.bf16 "
    "{%0, %1, %2, %3, %4, %5, %6, %7, %8, %9, %10, %11, %12, %13, %14, %15, %16, %17, %18, %19, %20, %21, %22, %23, %24, %25, %26, %27, %28, %29, %30, %31, %32, %33, %34, %35, %36, %37, %38, %39, %40, %41, %42, %43}, {%44, %45, %46, %47}, %48, p, 1, 1, 1;\n}\n"
    : "+f"(d[0]), "+f"(d[1]), "+f"(d[2]), "+f"(d[3]), "+f"(d[4]), "+f"(d[5]), "+f"(d[6]), "+f"(d[7]), "+f"(d[8]), "+f"(d[9]), "+f"(d[10]), "+f"(d[11]), "+f"(d[12]), "+f"(d[13]), "+f"(d[14]), "+f"(d[15]), "+f"(d[16]), "+f"(d[17]), "+f"(d[18]), "+f"(d[19]), "+f"(d[20]), "+f"(d[21]), "+f"(d[22]), "+f"(d[23]), "+f"(d[24]), "+f"(d[25]), "+f"(d[26]), "+f"(d[27]), "+f"(d[28]), "+f"(d[29]), "+f"(d[30]), "+f"(d[31]), "+f"(d[32]), "+f"(d[33]), "+f"(d[34]), "+f"(d[35]), "+f"(d[36]), "+f"(d[37]), "+f"(d[38]), "+f"(d[39]), "+f"(d[40]), "+f"(d[41]), "+f"(d[42]), "+f"(d[43])
    : "r"(a[0]), "r"(a[1]), "r"(a[2]), "r"(a[3]), "l"(db), "r"(scale_d));
}
__device__ __forceinline__ void wg_ss80_tb(float* d, uint64_t da, uint64_t db, int scale_d) {
  asm volatile("{\n.reg .pred p;\nsetp.ne.b32 p, %42, 0;\n"
    "wgmma.mma_async.sync.aligned.m64n80k16.f32.bf16.bf16 "
    "{%0, %1, %2, %3, %4, %5, %6, %7, %8, %9, %10, %11, %12, %13, %14, %15, %16, %17, %18, %19, %20, %21, %22, %23, %24, %25, %26, %27, %28, %29, %30, %31, %32, %33, %34, %35, %36, %37, %38, %39}, %40, %41, p, 1, 1, 0, 1;\n}\n"
    : "+f"(d[0]), "+f"(d[1]), "+f"(d[2]), "+f"(d[3]), "+f"(d[4]), "+f"(d[5]), "+f"(d[6]), "+f"(d[7]), "+f"(d[8]), "+f"(d[9]), "+f"(d[10]), "+f"(d[11]), "+f"(d[12]), "+f"(d[13]), "+f"(d[14]), "+f"(d[15]), "+f"(d[16]), "+f"(d[17]), "+f"(d[18]), "+f"(d[19]), "+f"(d[20]), "+f"(d[21]), "+f"(d[22]), "+f"(d[23]), "+f"(d[24]), "+f"(d[25]), "+f"(d[26]), "+f"(d[27]), "+f"(d[28]), "+f"(d[29]), "+f"(d[30]), "+f"(d[31]), "+f"(d[32]), "+f"(d[33]), "+f"(d[34]), "+f"(d[35]), "+f"(d[36]), "+f"(d[37]), "+f"(d[38]), "+f"(d[39])
    : "l"(da), "l"(db), "r"(scale_d));
}
__device__ __forceinline__ void wg_ss48_tt_h(float* d, uint64_t da, uint64_t db, int scale_d) {
  asm volatile("{\n.reg .pred p;\nsetp.ne.b32 p, %26, 0;\n"
    "wgmma.mma_async.sync.aligned.m64n48k16.f32.f16.f16 "
    "{%0, %1, %2, %3, %4, %5, %6, %7, %8, %9, %10, %11, %12, %13, %14, %15, %16, %17, %18, %19, %20, %21, %22, %23}, %24, %25, p, 1, 1, 1, 1;\n}\n"
    : "+f"(d[0]), "+f"(d[1]), "+f"(d[2]), "+f"(d[3]), "+f"(d[4]), "+f"(d[5]), "+f"(d[6]), "+f"(d[7]), "+f"(d[8]), "+f"(d[9]), "+f"(d[10]), "+f"(d[11]), "+f"(d[12]), "+f"(d[13]), "+f"(d[14]), "+f"(d[15]), "+f"(d[16]), "+f"(d[17]), "+f"(d[18]), "+f"(d[19]), "+f"(d[20]), "+f"(d[21]), "+f"(d[22]), "+f"(d[23])
    : "l"(da), "l"(db), "r"(scale_d));
}
__device__ __forceinline__ void wg_rs192_tb(float* d, const uint32_t* a, uint64_t db, int scale_d) {
  asm volatile("{\n.reg .pred p;\nsetp.ne.b32 p, %101, 0;\n"
    "wgmma.mma_async.sync.aligned.m64n192k16.f32.bf16.bf16 "
    "{%0, %1, %2, %3, %4, %5, %6, %7, %8, %9, %10, %11, %12, %13, %14, %15, %16, %17, %18, %19, %20, %21, %22, %23, %24, %25, %26, %27, %28, %29, %30, %31, %32, %33, %34, %35, %36, %37, %38, %39, %40, %41, %42, %43, %44, %45, %46, %47, %48, %49, %50, %51, %52, %53, %54, %55, %56, %57, %58, %59, %60, %61, %62, %63, %64, %65, %66, %67, %68, %69, %70, %71, %72, %73, %74, %75, %76, %77, %78, %79, %80, %81, %82, %83, %84, %85, %86, %87, %88, %89, %90, %91, %92, %93, %94, %95}, {%96, %97, %98, %99}, %100, p, 1, 1, 1;\n}\n"
    : "+f"(d[0]), "+f"(d[1]), "+f"(d[2]), "+f"(d[3]), "+f"(d[4]), "+f"(d[5]), "+f"(d[6]), "+f"(d[7]), "+f"(d[8]), "+f"(d[9]), "+f"(d[10]), "+f"(d[11]), "+f"(d[12]), "+f"(d[13]), "+f"(d[14]), "+f"(d[15]), "+f"(d[16]), "+f"(d[17]), "+f"(d[18]), "+f"(d[19]), "+f"(d[20]), "+f"(d[21]), "+f"(d[22]), "+f"(d[23]), "+f"(d[24]), "+f"(d[25]), "+f"(d[26]), "+f"(d[27]), "+f"(d[28]), "+f"(d[29]), "+f"(d[30]), "+f"(d[31]), "+f"(d[32]), "+f"(d[33]), "+f"(d[34]), "+f"(d[35]), "+f"(d[36]), "+f"(d[37]), "+f"(d[38]), "+f"(d[39]), "+f"(d[40]), "+f"(d[41]), "+f"(d[42]), "+f"(d[43]), "+f"(d[44]), "+f"(d[45]), "+f"(d[46]), "+f"(d[47]), "+f"(d[48]), "+f"(d[49]), "+f"(d[50]), "+f"(d[51]), "+f"(d[52]), "+f"(d[53]), "+f"(d[54]), "+f"(d[55]), "+f"(d[56]), "+f"(d[57]), "+f"(d[58]), "+f"(d[59]), "+f"(d[60]), "+f"(d[61]), "+f"(d[62]), "+f"(d[63]), "+f"(d[64]), "+f"(d[65]), "+f"(d[66]), "+f"(d[67]), "+f"(d[68]), "+f"(d[69]), "+f"(d[70]), "+f"(d[71]), "+f"(d[72]), "+f"(d[73]), "+f"(d[74]), "+f"(d[75]), "+f"(d[76]), "+f"(d[77]), "+f"(d[78]), "+f"(d[79]), "+f"(d[80]), "+f"(d[81]), "+f"(d[82]), "+f"(d[83]), "+f"(d[84]), "+f"(d[85]), "+f"(d[86]), "+f"(d[87]), "+f"(d[88]), "+f"(d[89]), "+f"(d[90]), "+f"(d[91]), "+f"(d[92]), "+f"(d[93]), "+f"(d[94]), "+f"(d[95])
    : "r"(a[0]), "r"(a[1]), "r"(a[2]), "r"(a[3]), "l"(db), "r"(scale_d));
}
__device__ __forceinline__ void wg_rs48_tb(float* d, const uint32_t* a, uint64_t db, int scale_d) {
  asm volatile("{\n.reg .pred p;\nsetp.ne.b32 p, %29, 0;\n"
    "wgmma.mma_async.sync.aligned.m64n48k16.f32.bf16.bf16 "
    "{%0, %1, %2, %3, %4, %5, %6, %7, %8, %9, %10, %11, %12, %13, %14, %15, %16, %17, %18, %19, %20, %21, %22, %23}, {%24, %25, %26, %27}, %28, p, 1, 1, 1;\n}\n"
    : "+f"(d[0]), "+f"(d[1]), "+f"(d[2]), "+f"(d[3]), "+f"(d[4]), "+f"(d[5]), "+f"(d[6]), "+f"(d[7]), "+f"(d[8]), "+f"(d[9]), "+f"(d[10]), "+f"(d[11]), "+f"(d[12]), "+f"(d[13]), "+f"(d[14]), "+f"(d[15]), "+f"(d[16]), "+f"(d[17]), "+f"(d[18]), "+f"(d[19]), "+f"(d[20]), "+f"(d[21]), "+f"(d[22]), "+f"(d[23])
    : "r"(a[0]), "r"(a[1]), "r"(a[2]), "r"(a[3]), "l"(db), "r"(scale_d));
}

struct Params {
  const __nv_bfloat16 *par[4], *logdt, *dskip, *u, *wo;
  CUtensorMap m[M_COUNT];
};

#define CHUNK(i) ((i) == 0 ? c : ((i) == 7 ? (c ^ 1) : (((c & 6) + 1 + (i)) & 7)))
#define FLAG(kind, rr, cc) (&g_flag[((kind) * 128 + (rr) * 8 + (cc)) * 32])
#define SLOT(i) ((i) == 0 ? OFF_EXTRA : OFF_BLK - 256 + ((i) > 5 ? (i) - 6 : (i) - 1) * BLK)
__device__ __forceinline__ void load_quad(uint32_t* A, uint32_t addr) {
  A[0] = lds32v(addr); A[1] = lds32v(addr + 32); A[2] = lds32v(addr - 32); A[3] = lds32v(addr);
}

__device__ __forceinline__ bool y_transpose(uint32_t sb, int w5, int lane, uint32_t ytag) {
  const int mi = lane >> 3, rw = lane & 7;
  const uint32_t sa = sb + OFF_EXTRA + (w5 * 16 + rw) * 128 + ((mi ^ rw) << 4), da = sb + SLOT(3) + (8 * mi + rw) * 160 + w5 * 32;
  const uint32_t ym = lane < 4 ? 0x10001u : 0u;
  bar_sync(7, 160);
  uint32_t v[8][4], bad = 0;
  #pragma unroll
  for (int q = 0; q < 8; q++) ldsm4t(v[q], (sa ^ ((q & 1) * 64 + ((q >> 1) & 1) * 16)) + ((q >> 1) & 1) * 10240 + (q >> 2) * 1024);
  #pragma unroll
  for (int q = 0; q < 8; q++) {
    bad |= (v[q][0] ^ ytag) | (v[q][2] ^ ytag);
    stsm4(da + (q & 3) * 5120 + (q >> 2) * 16, v[q][0] & ~ym, v[q][1], v[q][2] & ~ym, v[q][3]);
  }
  fence_async();
  uint32_t any;
  asm volatile("{\n.reg .pred p;\nsetp.ne.u32 p, %1, 0;\nbarrier.red.or.pred p, 7, 160, p;\nselp.u32 %0, 1, 0, p;\n}" : "=r"(any) : "r"(bad & ym) : "memory");
  return any;
}

__global__ void __launch_bounds__(512, 1) fused_kernel(const __grid_constant__ Params prm) {
  extern __shared__ unsigned char smem_raw[];
  uint32_t raw[5][2], pd;
  if ((threadIdx.x >> 7) == 2) {
    const int ch = (blockIdx.x & 7) * 80 + (blockIdx.x >> 3) * 5, od = threadIdx.x & 1;
    #pragma unroll
    for (int e = 0; e < 2; e++) {
      const __nv_bfloat16* pp = prm.par[2 * e + od] + ch * 128 + (threadIdx.x & 126);
      #pragma unroll
      for (int q = 0; q < 5; q++) asm volatile("ld.global.nc.u32 %0, [%1];" : "=r"(raw[q][e]) : "l"(pp + q * 128));
    }
    asm volatile("ld.global.nc.u16 %0, [%1];" : "=r"(pd) : "l"(((threadIdx.x & 8) ? prm.dskip : prm.logdt) + ch + min(threadIdx.x & 7, 4)));
  }
  const uint32_t sb = __shfl_sync(0xffffffff, smem_u32(smem_raw), 0);
  const int tid = threadIdx.x, lane = tid & 31;
  const int warp = __shfl_sync(0xffffffff, tid >> 5, 0), wg = warp >> 2, w4 = warp & 3;
  const int cta = blockIdx.x, r = cta >> 3, c = cta & 7;
  if ((sb & 0xffffffu) != SB0) return;
#define BAR(i) (sb + OFF_BAR + 8 * (i))
  const bool sw64 = ((c + 1) & 2) != 0;

  const CUtensorMap* mwp = &prm.m[sw64 ? M_W64 : M_W128];
  const int mcol = (c * 80 + (c & 1) * 16) >> (sw64 ? 5 : 6), rcol = c * 80 + ((c & 1) ? 0 : 64);
  if (warp == 12 && elect_one()) {
    #pragma unroll
    for (int i = 0; i < 5; i++) mbar_init(BAR(BR_FULL + i), 1);
    asm volatile("fence.mbarrier_init.release.cluster;" ::: "memory");
    if (EN_ATT) {
      mbar_expect_tx(BAR(BR_FULL), W_SLOT + 16384);
      tma4d(sb, mwp, BAR(BR_FULL), 0, 0, mcol, 0);
      tma2d(sb + OFF_X, &prm.m[M_X], BAR(BR_FULL), 0, r * 128);
      tma3d(sb + 12288, &prm.m[M_WR], BAR(BR_FULL), rcol, 0, 0);
      mbar_expect_tx(BAR(BR_FULL + 1), W_SLOT);
      tma4d(sb + W_SLOT, mwp, BAR(BR_FULL + 1), 0, 32, mcol, 0);
      tma3d(sb + W_SLOT + 12288, &prm.m[M_WR], BAR(BR_FULL + 1), rcol, 32, 0);
      TS(24);
    }
  }
  if (warp == 13 && elect_one()) {
    asm volatile("prefetch.tensormap [%0];" :: "l"(&prm.m[M_X]) : "memory");
    asm volatile("prefetch.tensormap [%0];" :: "l"(&prm.m[M_WR]) : "memory");
  }
  if (wg == 3) {
    asm volatile("setmaxnreg.dec.sync.aligned.u32 56;");
    const int tid = rtid(), lane = tid & 31;
    if (warp == 12) {
      asm volatile("bar.arrive 0, 512;" ::: "memory");
      {
        uint32_t s = 2, ph = 1, xs = 16384;
        #pragma unroll 1
        for (int kb = 2; kb < 20; kb++) {
          if (kb == 4) bar_sync(6, 128);
          if (kb >= 5) mbar_wait(BAR(BR_EMPTY) + 8 * s, ph);
          if (EN_ATT && elect_one()) {
            const uint32_t st = sb + s * W_SLOT, fb = BAR(BR_FULL) + 8 * s;
            mbar_expect_tx(fb, (kb & 1) ? W_SLOT : W_SLOT + 16384);
            if (!(kb & 1)) tma2d(sb + OFF_X + xs, &prm.m[M_X], fb, kb * 32, r * 128);
            tma4d(st, mwp, fb, 0, kb * 32, mcol, 0);
            tma3d(st + 12288, &prm.m[M_WR], fb, rcol, kb * 32, 0);
          }
          if (kb < 4 && lane == 0) TS(24 + kb);
          if (UPF && kb >= UKB - 4 && kb < UKB && elect_one())
            asm volatile("cp.async.bulk.prefetch.L2.global [%0], 5120;" :: "l"(prm.u + cta * 10240 + (kb - (UKB - 4)) * 2560) : "memory");
          if (EN_SSM && kb == (EN_ATT ? UKB : 4) && elect_one()) { mbar_expect_tx(BAR(BR_UIN), 20480); tma2d(sb + OFF_UT, &prm.m[M_U], BAR(BR_UIN), c * 80, r * 128); }
          if (kb == 14 && elect_one()) asm volatile("cp.async.bulk.prefetch.L2.global [%0], 6400;" :: "l"(prm.wo + cta * 3200) : "memory");
          if (!EN_ATT && kb == 4) break;
          if (++s == 5) { s = 0; ph ^= 1; }
          if (kb & 1) { xs += 16384; if (xs == 49152) xs = 0; }
        }
      }
      if (EN_ATT) {
      mbar_wait(BAR(BR_EPOCH), 0);
      const unsigned epoch = lds32(sb + OFF_EPOCH);
      const unsigned* fo = FLAG(3, r, lane & 7);
      unsigned seen = __ballot_sync(0xffffffff, ld_rlx(lane < 16 ? fo : FLAG(0, lane & 15, c)) == epoch) & 0xffu;
      mbar_wait(BAR(BR_GEMM), 0);
      if (elect_one()) {
        mbar_expect_tx(BAR(BR_WO), 10240);
        tma2d(sb, &prm.m[M_WO], BAR(BR_WO), c * 64, c * 80);
        mbar_expect_tx(BAR(BR_KVP), 61440);
        mbar_expect_tx(BAR(BR_WO + 1), 7 * 10240);
      }
      {
        uint32_t ds = sb + OFF_WOR + (lane >> 3) * 128 + (((lane & 7) ^ (lane >> 3)) << 4);
        #pragma unroll 1
        for (int h = 0; h < 2; h++) {
          const int i = (lane & 6) + h;
          const char* gs = reinterpret_cast<const char*>(prm.wo) + (size_t)((lane >> 3) + CHUNK(i) * 80) * 1280 + 1024 + c * 32 + (lane & 1) * 16;
          #pragma unroll 2
          for (int q = 0; q < 20; q++) {
            asm volatile("cp.async.cg.shared.global [%0], [%1], 16;" :: "r"(ds), "l"(gs) : "memory");
            ds = (ds + 512) ^ 64; gs += 5120;
          }
        }
      }
      mbar_wait(BAR(BR_PUB), 0);
      poll_all(FLAG(0, lane & 15, c), epoch);
      if (elect_one()) { TS(23); bulk_ld(sb + OFF_KVP, &g_kvp[c * 16 * 240], 61440, BAR(BR_KVP)); }
      asm volatile("cp.async.wait_all;" ::: "memory");
      fence_async();
      mbar_arrive(BAR(BR_WO));
      mbar_wait(BAR(BR_SUM), 0);
      if (elect_one()) {
        #pragma unroll 1
        for (int i = 1; i < 8; i++) tma2d(sb + i * 10240, &prm.m[M_WO], BAR(BR_WO + 1), c * 64, CHUNK(i) * 80);
      }
      mbar_wait(BAR(BR_OSTG), 0);
      if (elect_one()) {
        bulk_st(&g_o[cta * 1280], sb + OFF_EXTRA, 20480);
        bulk_commit();
        bulk_wait0();
        st_rlx(FLAG(3, r, c), epoch);
        mbar_arrive(BAR(BR_OEMPTY));
        TS(20);
      }
      __syncwarp();
      #pragma unroll 1
      for (int i = 1; i < 8; i++) {
        const int src = CHUNK(i);
        if (!((seen >> src) & 1)) seen = poll_bit(fo, epoch, 1u << src);
        if (i > 5) mbar_wait(BAR(BR_OEMPTY - 5) + 8 * i, 0);
        else if (EN_SSM && i != 2 && i != 3) mbar_wait(i == 1 ? BAR(BR_KS + 1) : BAR(BR_FREE - 4) + 8 * i, 0);
        if (elect_one()) {
          mbar_expect_tx(BAR(BR_OFULL) + 8 * i, 20480);
          bulk_ld(sb + SLOT(i), &g_o[(r * 8 + src) * 1280], 20480, BAR(BR_OFULL) + 8 * i);
          if (i == 1) TS(21);
          if (i == 7) TS(22);
        }
        __syncwarp();
      }
      if (lane == 0) { DUMP(20, 30); }
      }
    } else {
      const int hw = warp - 13, ht = tid - 416;
      if (hw == 2 && elect_one()) {
        #pragma unroll
        for (int i = 5; i < BR_COUNT; i++) mbar_init(BAR(i), i == BR_WO ? 33 : i == BR_OEMPTY ? 9 : i < BR_EMPTY ? 1 : i < BR_OEMPTY ? 2 : i < BR_Y ? 8 : i < BR_OSTG ? 4 : i == BR_OSTG ? 8 : i < BR_U2 ? 3 : 1);
        asm volatile("fence.mbarrier_init.release.cluster;" ::: "memory");
      }
      __syncwarp();
      asm volatile("bar.arrive 0, 512;" ::: "memory");
      if (EN_SSM && hw == 2) asm volatile("bar.arrive 8, 160;" ::: "memory");
      const unsigned epoch = hw == 0 ? ld_rlx(&g_epoch[cta]) + 1 : 0;
      bar_sync(5, 96);
      asm volatile("bar.arrive 6, 128;" ::: "memory");
      if (hw == 1 && elect_one()) {
        #pragma unroll
        for (int i = M_U; i < M_COUNT; i++) asm volatile("prefetch.tensormap [%0];" :: "l"(&prm.m[i]) : "memory");
      }
      if (ht == 0) {
        st_rlx(&g_epoch[cta], epoch);
        sts32(sb + OFF_EPOCH, epoch);
        mbar_arrive(BAR(BR_EPOCH));
      }
      if (EN_SSM) {
      const int mi = lane >> 3, rw = lane & 7, ch0 = c * 80 + r * 5;
      const bool early_u = hw == 0 && __all_sync(0xffffffff, ld_acq(FLAG(1, lane & 15, c)) == epoch);
      mbar_wait(BAR(BR_UIN), 0);
      if (ht == 0) TS(36);
      #pragma unroll 1
      for (int h = 0; h < 2; h++) {
        const uint32_t sa = sb + OFF_UT + h * 10240 + (8 * mi + rw) * 160 + hw * 16, da = sb + OFF_UT + h * 10240 + (hw * 8 + rw) * 128 + ((mi ^ rw ^ h) << 4);
        uint32_t v[8][4];
        #pragma unroll
        for (int q = 0; q < 8; q++) if (q < 6 || hw == 0) ldsm4t(v[q], sa + (q & 1) * 5120 + (q >> 1) * 48);
        bar_sync(5, 96);
        #pragma unroll
        for (int q = 0; q < 8; q++) if (q < 6 || hw == 0) stsm4((da ^ ((q & 1) * 64)) + (q >> 1) * 3072, v[q][0], v[q][1], v[q][2], v[q][3]);
      }
      fence_async();
      bar_sync(5, 96);
      if (hw == 0) {
        if (elect_one()) {
          tma2d_st(&prm.m[M_SA], sb + OFF_UT, r * 128, c * 80);
          tma2d_st(&prm.m[M_SA], sb + OFF_UT + 10240, r * 128 + 64, c * 80);
          bulk_commit(); bulk_wait0_read();
          mbar_arrive(BAR(BR_UOUT));
          TS(37);
          bulk_wait0();
          st_rel(FLAG(1, r, c), epoch);
          TS(30);
        }
        __syncwarp();
        if (!early_u) poll_all_acq(FLAG(1, lane & 15, c), epoch);
      }
      #pragma unroll 1
      for (int k = 0; k < 5; k++) {
        if (k == 0 || k == 3) {
          const int p = k != 0;
          if (hw == 0) {
            if (!p) {
              if (elect_one()) {
                fence_async_g();
                mbar_expect_tx(BAR(BR_U), 12288);
                #pragma unroll 1
                for (int q = 0; q < 3; q++) bulk_ld(sb + OFF_BLK + q * q * BLK, g_uy + (ch0 + q * q) * 2048, 4096, BAR(BR_U));
                TS(31);
              }
              __syncwarp();
            }
            mbar_wait(BAR(p ? BR_U2 : BR_U), 0);
          }
          bar_sync(5, 96);
        }
        const int l3 = (hw + k) % 3 * 32 + lane;
        const uint32_t blk = sb + OFF_BLK + ((0x32410 >> (4 * k)) & 7) * BLK, o = blk + B_D + l3 * 16;
        float P[34];
        P[0] = 0.f;
        #pragma unroll
        for (int q = 0; q < 5; q++) {
          const int ch = 2 * l3 - 3 + q;
          uint32_t v[4];
          lds128(v, blk + (uint32_t)((ch * 16) ^ ((ch * 2) & 0x10)));
          #pragma unroll
          for (int e = 0; e < 8; e++) {
            const int i = 8 * q + e - 4;
            if (i >= 0 && i < 33) P[i + 1] = P[i] + ((e & 1) ? bf_hi(v[e >> 1]) : bf_lo(v[e >> 1]));
          }
        }
#define WIN(lo, hi, e) (P[21 + (e) - (lo)] - P[20 + (e) - (hi)])
#define WIN8(lo, hi, b) pack2(WIN(lo, hi, b), WIN(lo, hi, b + 1)), pack2(WIN(lo, hi, b + 2), WIN(lo, hi, b + 3)), pack2(WIN(lo, hi, b + 4), WIN(lo, hi, b + 5)), pack2(WIN(lo, hi, b + 6), WIN(lo, hi, b + 7))
        if (l3 < 64) {
          sts128(o + B_D9, WIN8(12, 20, 0)); sts128(o + B_D9 + 1024, WIN8(12, 20, 8));
          sts128(o + B_D7, WIN8(5, 11, 0)); sts128(o + B_D7 + 1024, WIN8(5, 11, 8));
        }
        sts128(o + B_D5, WIN8(6, 10, 0)); sts128(o + B_D5 + 1552, WIN8(6, 10, 8));
        sts128(o, WIN8(3, 5, 0)); sts128(o + 1552, WIN8(3, 5, 8));
        if (l3 < 2) sts128(blk + B_D + l3 * B_D5 + 1536, 0, 0, 0, 0);
      }
      __syncwarp();
      if (lane == 0) mbar_arrive(BAR(BR_DRDY + 1));
      if (ht == 0) TS(32);
      if (hw == 0) {
        const bool early = __all_sync(0xffffffff, ld_rlx(FLAG(2, lane & 15, c)) == epoch);
        #pragma unroll 1
        for (int p = 0; p < 2; p++) {
          mbar_wait(BAR(BR_Y) + 8 * p, 0);
          if (elect_one()) {
            bulk_st(g_uy + (640 + ch0 + 4 * p) * 2048, sb + OFF_BLK + (3 + p) * BLK, p ? 4096 : 16384);
            bulk_commit(); bulk_wait0_read();
            mbar_arrive(BAR(BR_FREE) + 8 * p);
          }
          __syncwarp();
        }
        if (elect_one()) { bulk_wait0(); st_rlx(FLAG(2, r, c), epoch); TS(33); }
        __syncwarp();
        if (!early) poll_all(FLAG(2, lane & 15, c), epoch);
        if (EN_ATT) mbar_wait(BAR(BR_OEMPTY), 0);
        #pragma unroll 1
        for (int n = 0; n < 64; n++) {
          if (elect_one()) {
            mbar_expect_tx(BAR(BR_YIN), 20480);
            tma2d(sb + OFF_EXTRA, &prm.m[M_SA], BAR(BR_YIN), r * 128, 640 + c * 80);
            tma2d(sb + OFF_EXTRA + 10240, &prm.m[M_SA], BAR(BR_YIN), r * 128 + 64, 640 + c * 80);
            TS(34);
          }
          __syncwarp();
          if (EN_ATT) mbar_wait(BAR(BR_OEMPTY + 3), 0);
          mbar_wait(BAR(BR_YIN), n & 1);
          if (lane == 0) TS(38);
          if (!y_transpose(sb, 4, lane, (epoch & 1u) * 0x10001u)) break;
          FIXCNT
        }
      if (elect_one()) {
        TS(39);
        tma2d_st(&prm.m[M_OUT], sb + SLOT(3), c * 80, r * 128);
        bulk_commit(); bulk_wait0_read();
        TS(35); DUMP(30, 40); DUMP(0, 1);
      }
      }
      }
    }
  } else {
  if (wg < 2) {
    asm volatile("setmaxnreg.inc.sync.aligned.u32 160;");
    bar_sync(0, 512);
    if (EN_ATT) {
    float am[96], ar[24];
    {
      const bool lead = (rtid() & 127) == 0;
      constexpr uint64_t dr0 = mkdesc(SB0 + 12288, 1024, 256, 3);
      const uint64_t db0 = sw64 ? mkdesc(SB0, 2048, 512, 2) : mkdesc(SB0, 4096, 1024, 1);
      const uint32_t kst = sw64 ? 64 : 128, bh = db0 >> 32;
      uint32_t s = 0, ph = 0, xo = 0;
      const int ln = rtid() & 31;
      const uint32_t xa = sb + OFF_X + (warp * 16 + (ln & 15)) * 128 + (((ln >> 4) ^ (ln & 7)) << 4);
      uint32_t A[8];
      mbar_wait(BAR(BR_FULL), 0);
      if (lead && wg == 0) TS(1);
      ldsm4(A, xa); ldsm4(A + 4, xa ^ 32);
      wg_fence();
      wg_rs48_tb(ar, A, dr0, 0); wg_rs192_tb(am, A, db0, 0);
      wg_commit();
      #pragma unroll 1
      for (int kb = 1; kb < 20; kb++) {
        const uint32_t wp = s * (W_SLOT >> 4), eb = BAR(BR_EMPTY) + 8 * s;
        wg_fence();
        wg_rs48_tb(ar, A + 4, desc2((uint32_t)dr0 + wp + 32, dr0 >> 32), 1);
        wg_rs192_tb(am, A + 4, desc2((uint32_t)db0 + wp + kst, bh), 1);
        wg_commit();
        if (++s == 5) { s = 0; ph ^= 1; }
        if (!(kb & 1)) { xo += 16384; if (xo == 49152) xo = 0; }
        mbar_wait(BAR(BR_FULL) + 8 * s, ph);
        const uint32_t xk = (xa + xo) ^ ((kb & 1) * 64), wn = s * (W_SLOT >> 4);
        wg_wait<1>();
        ldsm4(A, xk);
        wg_fence();
        wg_rs48_tb(ar, A, desc2((uint32_t)dr0 + wn, dr0 >> 32), 1);
        wg_rs192_tb(am, A, desc2((uint32_t)db0 + wn, bh), 1);
        wg_commit();
        wg_wait<1>();
        ldsm4(A + 4, xk ^ 32);
        if (lead && kb < 16) mbar_arrive(eb);
      }
      wg_fence();
      wg_rs48_tb(ar, A + 4, dr0 + 4 * (W_SLOT >> 4) + 32, 1);
      wg_rs192_tb(am, A + 4, desc2((uint32_t)db0 + 4 * (W_SLOT >> 4) + kst, bh), 1);
      wg_commit();
      wg_wait<0>();
      pin<96>(am); pin<24>(ar);
    }
    const int tid = rtid(), lane = tid & 31, tq = lane & 3;
    if (tid == 0) TS(2);
#define QV(j, e) ((j) < 8 ? am[4 * (j) + (e)] : ar[4 * ((j) - 8) + (e)])
#define KV_(j, e) ((j) < 8 ? am[32 + 4 * (j) + (e)] : ar[8 + 4 * ((j) - 8) + (e)])
#define VV(j, e) ((j) < 8 ? am[64 + 4 * (j) + (e)] : ar[16 + 4 * ((j) - 8) + (e)])
    {
      bar_sync(1, 256);
      if (tid == 0) mbar_arrive(BAR(BR_GEMM));
      const uint32_t ro = sb + (uint32_t)((warp * 16 + (lane & 15)) * 16);
      const int l0 = 2 * (c & 1) + (lane >> 4);
      const uint32_t ones = (tq == 0) ? 0x00003f80u : 0u;
#define PV(j) pack2(VV(j, 0), VV(j, 1)), pack2(VV(j, 2), VV(j, 3))
#define PK(j) pack2(phi(KV_(j, 0)), phi(KV_(j, 1))), pack2(phi(KV_(j, 2)), phi(KV_(j, 3)))
      stsm4(ro + OFF_V + (5 + 6 * (lane >> 4)) * 2048, ones, ones, ones, ones);
      #pragma unroll
      for (int j = 0; j < 10; j += 2) {
        const int l = (j == 8 && (c & 1)) ? l0 - 2 : l0 + j;
        stsm4(ro + OFF_V + (l + (l >= 5)) * 2048, PV(j), PV(j + 1));
        stsm4(ro + OFF_PK + l * 2048, PK(j), PK(j + 1));
      }
    }
    fence_async();
    bar_sync(1, 256);
    if (tid == 0) TS(3);
    mbar_wait(BAR(BR_EPOCH), 0);
    const unsigned epoch = lds32(sb + OFF_EPOCH);
    {
      float kv[24]; zero<24>(kv);
      constexpr uint64_t da = mkdesc(SB0 + OFF_PK, 128, 2048, 0), db = mkdesc(SB0 + OFF_V, 128, 2048, 0);
      wg_fence();
      #pragma unroll
      for (int s = 0; s < 8; s++) wg_ss48_tt(kv, desc2((uint32_t)da + wg * 640 + s * 16, da >> 32), desc2((uint32_t)db + wg * 768 + s * 16, db >> 32), s != 0);
      wg_commit();
      wg_wait<0>();
      pin<24>(kv);
      if (tid == 0) TS(15);
      if (w4 < 3) {
        const uint32_t wb = sb + OFF_KVS + (wg * 3 + w4) * 1536 + (lane & 15) * 96;
        #pragma unroll
        for (int j = 0; j < 6; j += 2)
          stsm4(wb + (j + (lane >> 4)) * 16, pack2(kv[4 * j], kv[4 * j + 1]), pack2(kv[4 * j + 2], kv[4 * j + 3]),
                pack2(kv[4 * j + 4], kv[4 * j + 5]), pack2(kv[4 * j + 6], kv[4 * j + 7]));
        __syncwarp();
        const int dl = w4 * 16 + (lane & 15), hl = dl >= 20;
        uint32_t v[4], z[4];
        lds128(v, wb + (3 * hl + (lane >> 4)) * 16);
        lds64(z, wb + 32 + 8 * hl); z[2] = lds32(wb + 80); z[3] = epoch & 1u;
        if (dl < 40) {
          uint4* dst = &g_kvp[(c * 16 + r) * 240 + wg * 40 + dl];
          v[3] = (v[3] & ~1u) | z[3];
          st128_rlx(dst + (lane >> 4) * 80, v);
          if (lane < 16) st128_rlx(dst + 160, z);
        }
      }
    }
    bar_sync(1, 256);
    if (tid == 0) { st_rlx(FLAG(0, r, c), epoch); mbar_arrive(BAR(BR_PUB)); TS(4); }
    const int kvi = (tid >= 80) + (tid >= 160) + (tid >= 240), kd = tid - 80 * kvi;
    const int khd = kd / 20, kt0 = 5 * (khd >> 1) + 2 * (khd & 1);
    const uint32_t rb = sb + OFF_KVB + kd * 16;
    if (kvi < 3) {
      #pragma unroll 1
      for (int m = kvi; m < 7; m += 3) { const int q = kt0 + 3 + m; sts128(rb + (q >= 10 ? q - 10 : q) * 1280, 0, 0, 0, 0); }
    }
    uint32_t qa[20];
    {
      const float sc = 1.44269504089f + __uint_as_float(lds32(sb + OFF_EPOCH) ^ epoch);
      #pragma unroll
      for (int j = 0; j < 10; j++) { qa[2 * j] = pack2(phi(QV(j, 0), sc), phi(QV(j, 1), sc)); qa[2 * j + 1] = pack2(phi(QV(j, 2), sc), phi(QV(j, 3), sc)); }
    }
    if (tid == 0) TS(5);
    if (warp == 7) mbar_wait(BAR(BR_KVP), 0);
    bar_sync(1, 256);
    if (tid == 0) TS(6);
    if (kvi < 3) {
      float s[8];
      zero<8>(s);
      uint32_t bad = 0;
      #pragma unroll 4
      for (int i = 0; i < 16; i += 2) {
        uint32_t w[4], x[4];
        lds128(w, sb + OFF_KVP + tid * 16 + i * 3840); lds128(x, sb + OFF_KVP + tid * 16 + i * 3840 + 3840);
        bad |= (w[3] ^ epoch) | (x[3] ^ epoch);
        #pragma unroll
        for (int e = 0; e < 4; e++) {
          asm("add.rn.bf16x2 %0, %0, %1;" : "+r"(w[e]) : "r"(x[e]));
          s[2 * e] += bf_lo(w[e]); s[2 * e + 1] += bf_hi(w[e]);
        }
      }
      if (__builtin_expect(bad & 1u, 0)) {
        zero<8>(s);
        #pragma unroll 1
        for (int i = 0; i < 16; i++) {
          uint32_t w[4] = {0, 0, 0, ~epoch};
          fix128_w3(w, &g_kvp[(c * 16 + i) * 240 + tid], epoch, 1u);
          #pragma unroll
          for (int e = 0; e < 4; e++) { s[2 * e] += bf_lo(w[e]); s[2 * e + 1] += bf_hi(w[e]); }
        }
        FIXCNT
      }
      const uint32_t p0 = pack2(s[0], s[1]), p1 = pack2(s[2], s[3]), p2 = pack2(s[4], s[5]), p3 = pack2(s[6], s[7]);
      if (kvi < 2) sts128(rb + (kt0 + (khd & 1) + kvi) * 1280, p0, p1, p2, p3);
      else {
        const bool od = khd & 1;
        sts128(rb + (5 * (khd >> 1) + 2) * 1280, od ? 0u : p0, od ? 0u : p1, od ? p0 : 0u, od ? p1 : 0u);
        const uint32_t zz = (p2 & 0xffffu) << (16 * (khd & 1));
        sts128(rb + 10 * 1280, khd < 2 ? zz : 0u, khd < 2 ? 0u : zz, 0u, 0u);
      }
    }
    fence_async();
    bar_sync(1, 256);
    if (tid == 0) { mbar_arrive(BAR(BR_SUM)); TS(7); }
    {
      float oa[44]; zero<44>(oa);
      constexpr uint64_t db = mkdesc(SB0 + OFF_KVB, 128, 1280, 0);
      wg_fence();
      #pragma unroll
      for (int s = 0; s < 5; s++) wg_rs88_tb(oa, &qa[4 * s], desc2((uint32_t)db + ((s == 4 && (c & 1)) ? 0 : (s + (c & 1)) * 16), db >> 32), s != 0);
      wg_commit();
      wg_wait<0>();
      pin<44>(oa);
      if (tid == 0) TS(13);
      float rc[4], rd[2][4];
      #pragma unroll
      for (int e = 0; e < 4; e++) asm("rcp.approx.ftz.f32 %0, %1;" : "=f"(rc[e]) : "f"(oa[40 + e] + 1e-6f));
      #pragma unroll
      for (int h = 0; h < 4; h++) {
        rd[0][h] = __shfl_sync(0xffffffff, rc[h & 1], (lane & 28) | (h >> 1));
        rd[1][h] = __shfl_sync(0xffffffff, rc[2 + (h & 1)], (lane & 28) | (h >> 1));
      }
      #pragma unroll
      for (int j = 0; j < 10; j++) {
        #pragma unroll
        for (int h = 0; h < 2; h++) {
          float f;
          if (j == 2) f = tq < 2 ? rd[h][0] : rd[h][1];
          else if (j == 7) f = tq < 2 ? rd[h][2] : rd[h][3];
          else f = rd[h][(8 * j) / 20];
          qa[2 * j + h] = pack2(oa[4 * j + 2 * h] * f, oa[4 * j + 2 * h + 1] * f);
        }
      }
      const uint32_t m0 = (lane & 7) == ((2 * w4) & 7), m1 = (lane & 7) == 2 * w4 + 1;
      const uint32_t oa_ = sb + OFF_EXTRA + (lane >> 4) * 2048 + (warp * 16 + (lane & 15)) * 16;
      bar_sync(1, 256);
#define TAG(v, m) (((v) & ~(m)) | (epoch & (m)))
      #pragma unroll
      for (int s = 0; s < 5; s++) stsm4(oa_ + s * 4096, TAG(qa[4 * s], m0), TAG(qa[4 * s + 1], m1), TAG(qa[4 * s + 2], m0), TAG(qa[4 * s + 3], m1));
    }
    fence_async();
    __syncwarp();
    if (lane == 0) mbar_arrive(BAR(BR_OSTG));
    if (tid == 0) TS(8);
    }
    asm volatile("setmaxnreg.dec.sync.aligned.u32 136;");
  } else {
    const int g = lane >> 2, tq = lane & 3, t7 = tid & 127;
    asm volatile("bar.arrive 0, 512;" ::: "memory");
    if (EN_SSM) {
    {
      #pragma unroll 1
      for (int k = 0; k < 4; k++) {
        const uint32_t z = sb + OFF_BLK + k * BLK + t7 * 16;
        sts128(z + B_TBL, 0, 0, 0, 0); sts128(z + B_TBL + 2048, 0, 0, 0, 0);
      }
      if (t7 < 80) sts128(sb + OFF_BLK + (t7 >> 4) * BLK - 256 + (t7 & 15) * 16, 0, 0, 0, 0);
      const uint32_t ea = sb + OFF_BLK + (2 + (w4 & 1)) * BLK + (lane >> 4) * 7168 + ((lane >> 3) & 1) * 256 + (lane & 7) * 16 + (w4 >> 1) * 2048;
      constexpr uint64_t dE = mkdesc(SB0 + OFF_BLK + 2 * BLK, 128, 512, 0);
      const uint32_t xa = sb + OFF_BLK + 18560 + t7 * 8, xr_ = sb + OFF_BLK + 18560 + (t7 ^ 64) * 8;
      uint32_t pr[5][2];
      #pragma unroll
      for (int q = 0; q < 5; q++) {
        #pragma unroll
        for (int e = 0; e < 2; e++) pr[q][e] = __byte_perm(raw[q][e], __shfl_xor_sync(0xffffffff, raw[q][e], 1), (lane & 1) ? 0x3276 : 0x5410);
        const uint32_t m = __reduce_max_sync(0xffffffff, max(raw[q][1] & 0x7fffu, (raw[q][1] >> 16) & 0x7fffu));
        if (lane == 0) sts32(sb + OFF_EPOCH + 64 + q * 16 + w4 * 4, m);
      }
      bar_sync(4, 128);
      if (t7 == 0) TS(40);
      const int j = (w4 & 1) * 16 + (w4 >> 1) * 8 + g, i2 = tq < 2 ? 64 * tq + j : 32 * (tq - 2) + j;
      const uint32_t e2 = B_TBL + 4 * (tq < 2 ? T_F3 + (((i2 - 1) & 1) ? 80 : 0) + ((i2 - 1) >> 1) + 16 : T_F2 + (i2 & 1) * 96 + (i2 >> 1));
      const uint32_t e1 = tq < 2 ? (i2 ? e2 - 64 : B_TBL + 4 * (T_F2 + 175)) : B_TBL + 4 * (i2 ? T_F2 + ((2 * i2 - 1) & 3) * 48 + ((2 * i2 - 1) >> 2) : 16 + 511);
      const uint32_t e0 = B_TBL + (16 + 8 * j + 2 * tq) * 4;
      const float dtl = bf_round(expf(bf_lo(pd)));
      float hd[9];
      auto head = [&](int q) {
        const uint32_t pa0 = pr[0][0], pc0 = pr[0][1];
        const float dt = __shfl_sync(0xffffffff, dtl, q);
        #pragma unroll
        for (int e = 0; e < 2; e++) { pr[0][e] = pr[1][e]; pr[1][e] = pr[2][e]; pr[2][e] = pr[3][e]; pr[3][e] = pr[4][e]; }
        uint32_t mm[4];
        lds128(mm, sb + OFF_EPOCH + 64 + q * 16);
        const uint32_t ex = min(max(max(max(mm[0], mm[1]), max(mm[2], mm[3])) >> 7, 1u), 253u);
        const float sc = __uint_as_float((254u - ex) << 23);
        const float lr = -bf_round(expf(bf_lo(pa0))) * dt * 1.44269504089f;
        const float tn = bf_hi(pa0) * dt * 0.15915494309f;
        cexp_t(lr, -tn, hd[0], hd[1]);
        cexp_t(lr * 8.f, tn * 8.f, hd[2], hd[3]);
        cexp_t(lr * 64.f, tn * 64.f, hd[4], hd[5]);
        hd[6] = bf_lo(pc0) * sc; hd[7] = -bf_hi(pc0) * sc;
        hd[8] = 2.f * dt * __uint_as_float(ex << 23);
      };
      head(0);
      #pragma unroll 1
      for (int it = 0; it < 5; it++) {
        const int k = it;
        const uint32_t blk = sb + OFF_BLK + k * BLK;
        float fac = 0.f;
        float ka[24]; zero<24>(ka);
        {
          if (it == 4) {
            mbar_wait(BAR(BR_UOUT), 0);
            sts128(sb + OFF_UT + B_TBL + t7 * 16, 0, 0, 0, 0); sts128(sb + OFF_UT + B_TBL + 2048 + t7 * 16, 0, 0, 0, 0);
          }
          const uint32_t ga = ea + 4096 - (w4 >> 1) * 512;
#define PUT4(i, a, b, c_, d) sts128(((i) < 8 ? ea + ((i) >> 1) * 512 : ga + (((i) - 8) >> 1) * 512) + ((i) & 1) * 128, a, b, c_, d)
          float z2r, z2i, z4r, z4i, xr[8], xi[8], gr[8], gi[8], wr[9], wi[9];
          const float z1r = hd[0], z1i = hd[1];
          xr[1] = hd[2]; xi[1] = hd[3]; wr[0] = hd[4]; wi[0] = hd[5];
          fac = hd[8];
          xr[0] = 1.f; xi[0] = 0.f;
          cmul(xr[1], xi[1], xr[1], xi[1], xr[2], xi[2]); cmul(xr[2], xi[2], xr[1], xi[1], xr[3], xi[3]);
          cmul(xr[2], xi[2], xr[2], xi[2], xr[4], xi[4]);
          #pragma unroll
          for (int b = 1; b < 4; b++) cmul(xr[4], xi[4], xr[b], xi[b], xr[4 + b], xi[4 + b]);
          cmul(wr[0], wi[0], wr[0], wi[0], wr[1], wi[1]); cmul(wr[1], wi[1], wr[0], wi[0], wr[2], wi[2]);
          cmul(wr[1], wi[1], wr[1], wi[1], wr[3], wi[3]); cmul(wr[3], wi[3], wr[3], wi[3], wr[4], wi[4]);
          cmul(wr[4], wi[4], wr[3], wi[3], wr[5], wi[5]); cmul(wr[4], wi[4], wr[4], wi[4], wr[6], wi[6]);
          cmul(wr[6], wi[6], wr[4], wi[4], wr[7], wi[7]); cmul(wr[6], wi[6], wr[6], wi[6], wr[8], wi[8]);
          uint32_t R[4], I[4], PR[4], PI[4];
          #pragma unroll
          for (int b = 0; b < 4; b++) { R[b] = packh(xr[2 * b], xr[2 * b + 1]); I[b] = packh(xi[2 * b], xi[2 * b + 1]); }
          PUT4(0, R[0], R[1], R[2], R[3]); PUT4(1, I[0], I[1], I[2], I[3]);
          #pragma unroll
          for (int i = 0; i < 3; i++) {
            const uint32_t z = packh(wr[i], wi[i]);
            #pragma unroll
            for (int b = 0; b < 4; b++) hcm2(R[b], I[b], z, PR[b], PI[b]);
            PUT4(2 * i + 2, PR[0], PR[1], PR[2], PR[3]); PUT4(2 * i + 3, PI[0], PI[1], PI[2], PI[3]);
          }
          gr[0] = hd[6]; gi[0] = hd[7];
          cmul(z1r, z1i, z1r, z1i, z2r, z2i); cmul(z2r, z2i, z2r, z2i, z4r, z4i);
          cmul(gr[0], gi[0], z1r, z1i, gr[1], gi[1]);
          cmul(gr[0], gi[0], z2r, z2i, gr[2], gi[2]); cmul(gr[1], gi[1], z2r, z2i, gr[3], gi[3]);
          #pragma unroll
          for (int b = 0; b < 4; b++) cmul(gr[b], gi[b], z4r, z4i, gr[4 + b], gi[4 + b]);
          PUT4(8, packh(gr[0], gr[1]), packh(gr[2], gr[3]), packh(gr[4], gr[5]), packh(gr[6], gr[7]));
          PUT4(9, packh(gi[0], gi[1]), packh(gi[2], gi[3]), packh(gi[4], gi[5]), packh(gi[6], gi[7]));
          {
            const uint32_t z = packh(wr[3], -wi[3]), a4r = packh(gr[0], gr[4]), a4i = packh(gi[0], gi[4]);
            hcm2(packh(gr[0], gr[2]), packh(gi[0], gi[2]), z, PR[0], PI[0]);
            hcm2(packh(gr[4], gr[6]), packh(gi[4], gi[6]), z, PR[1], PI[1]);
            hcm2(a4r, a4i, packh(wr[4], -wi[4]), PR[2], PI[2]);
            hcm2(a4r, a4i, packh(wr[5], -wi[5]), PR[3], PI[3]);
            PUT4(10, PR[0], PR[1], PR[2], PR[3]); PUT4(11, PI[0], PI[1], PI[2], PI[3]);
            float hr, hi_;
            cmul(gr[0], gi[0], wr[3], -wi[3], hr, hi_);
            const uint32_t cr = packh(gr[0], hr), ci = packh(gi[0], hi_);
            #pragma unroll
            for (int i = 0; i < 3; i++) hcm2(cr, ci, packh(wr[6 + i], -wi[6 + i]), PR[i], PI[i]);
            PUT4(12, PR[0], PR[1], PR[2], 0u); PUT4(13, PI[0], PI[1], PI[2], 0u);
          }
          fence_async();
          bar_sync(4, 128);
          wg_fence();
          #pragma unroll
          for (int s = 0; s < 8; s++) {
            const uint64_t d = dE + (s >> 2) * (BLK >> 4) + ((s >> 1) & 1) * 448 + (s & 1) * 16;
            wg_ss48_tt_h(ka, d, d + 256, s != 0);
          }
          wg_commit();
        }
        const float dsk = bf_lo(__shfl_sync(0xffffffff, pd, 8 + (it & 7)));
        head(min(it + 1, 4));
        asm volatile("{\n.reg .pred p;\nHL:\nsetp.eq.f32 p, %0, 0f46400000;\n@p bra HL;\n}" :: "f"(hd[0] + hd[2] + hd[4]));
        wg_wait<0>();
        pin<24>(ka);
        float kk[6];
        const bool up = w4 >= 2;
        #pragma unroll
        for (int n = 0; n < 3; n++) {
          sts64f(xa + n * BLK, up ? ka[12 + 4 * n] : ka[4 * n + 2], up ? ka[13 + 4 * n] : ka[4 * n + 3]);
          kk[2 * n] = up ? ka[14 + 4 * n] : ka[4 * n]; kk[2 * n + 1] = up ? ka[15 + 4 * n] : ka[4 * n + 1];
        }
        if (it) bar_sync(4, 128); else bar_sync(8, 160);
          if (it == 4 && w4 == 0) {
            mbar_wait(BAR(BR_U), 0);
            if (elect_one()) {
              mbar_expect_tx(BAR(BR_U2), 8192);
              bulk_ld(blk - 2 * BLK, g_uy + (c * 80 + r * 5 + 2) * 2048, 4096, BAR(BR_U2)); bulk_ld(blk - BLK, g_uy + (c * 80 + r * 5 + 3) * 2048, 4096, BAR(BR_U2));
            }
            __syncwarp();
          }
        #pragma unroll
        for (int n = 0; n < 3; n++) {
          uint32_t o[2]; lds64(o, xr_ + n * BLK);
          kk[2 * n] = (kk[2 * n] + __uint_as_float(o[0])) * fac; kk[2 * n + 1] = (kk[2 * n + 1] + __uint_as_float(o[1])) * fac;
        }
        if (t7 == 0) kk[0] += dsk;
        {
          const uint32_t v = pack2(kk[1], kk[0]), vh = v >> 16;
          const uint32_t u = pack2(kk[2], kk[3]), w = pack2(kk[4], kk[5]), uu = pack2(kk[2], kk[2]), us = pack2(kk[3], kk[2]);
          const uint32_t x = tq < 2 ? w : u, xh = x >> 16;
          sts32(blk + e0 + 4, v); sts16(blk + e0, vh); sts16(blk + e0 + 10, v);
          sts16(blk + e1, x); sts16(blk + e1 + 6, x); sts16(blk + e2, xh); sts16(blk + e2 + 6, xh);
          if (tq < 2) {
            const uint32_t pb = blk + e0 + 1024 + 8 * tq;
            sts32(pb + 4, uu); sts32(pb + 8, us); sts16(pb + 14, us);
            if (i2) { sts16(pb - 4, u); sts32(pb, uu); }
          }
          if (i2 == 0) {
            const uint32_t tb = blk + B_TBL;
            if (tq == 0) { sts16(tb + (16 + 256) * 4, u); sts16(tb + (T_S + 3) * 4, w); sts32(tb + (T_S + 4) * 4, pack2(kk[4], kk[4])); sts16(tb + (T_S + 5) * 4 + 2, w); }
            else { sts32(tb + 528 * 4, uu); sts32(tb + 529 * 4, uu); sts32(tb + 530 * 4, uu); sts16(tb + 531 * 4 + 2, u); sts16(tb + (T_F3 + 80 + 63) * 4, w); }
          }
        }
        if (t7 == 0) TS(49 + it);
      }
    }
    asm volatile("setmaxnreg.inc.sync.aligned.u32 136;");
    if (t7 == 0) TS(41);
    bar_sync(4, 128);
    if (t7 == 0) mbar_arrive(BAR(BR_KS));
    if (EN_ATT) mbar_wait(BAR(BR_GEMM), 0);
    }
  }
  const int tid = rtid(), lane = tid & 31, g = lane >> 2, tq = lane & 3, t7 = tid & 127;
  mbar_wait(BAR(BR_EPOCH), 0);
  const unsigned epoch = lds32(sb + OFF_EPOCH);
  const uint32_t ytag = (epoch & 1u) * 0x10001u, ym = lane < 4 ? 0x10001u : 0u;
  if (EN_SSM && wg != 1) {
    mbar_wait(BAR(BR_KS), 0);
    mbar_wait(BAR(BR_U), 0);
    if (tid == 256) TS(42);
    {
      const int pass = wg >> 1;
      const int k = pass ? w4 : 4;
      if (k & 2) mbar_wait(BAR(BR_U2), 0);
      const uint32_t blk = sb + OFF_BLK + k * BLK, tb = blk + B_TBL + (uint32_t)((g - 2 * tq) * 4);
      float acc[16][4];
      zero<64>(&acc[0][0]);
      const int kl = 16 * (lane >> 4) + 2 * (lane & 7) + ((lane >> 3) & 1);
      {
        auto ubase = [&](int sh) { const int q = kl - 2 * sh; return blk + (uint32_t)((q * 16) ^ ((q * 2) & 0x10)); };
#define LDQ(A, sh) _Pragma("unroll") for (int m = 0; m < 4; m++) load_quad(A[m], tb + (16 + 16 * (sh) + 128 * m) * 4);
#define LDB(B, ub, h) _Pragma("unroll") for (int p = 0; p < 4; p++) ldsm4(B[p], (ub) + (4 * (h) + p) * 512);
#define MLO(A, B) _Pragma("unroll") for (int m = 0; m < 4; m++) _Pragma("unroll") for (int cc = 0; cc < 8; cc++) mma16816(acc[cc + m], A[m], &B[cc >> 1][(cc & 1) * 2]);
#define MHI(A, B) _Pragma("unroll") for (int m = 0; m < 4; m++) _Pragma("unroll") for (int cc = 0; cc < 8 - m; cc++) mma16816(acc[8 + cc + m], A[m], &B[cc >> 1][(cc & 1) * 2]);
        int p_ = pass ? 0 : w4;
        const int pe = pass ? 4 : w4 + 1;
        uint32_t A[4][4], A2[4][4], Bl[4][4], Bh[4][4];
        uint32_t ub = ubase(p_ + 4);
        LDQ(A, p_ + 4) LDB(Bl, ub, 0)
        #pragma unroll 1
        for (; p_ < pe; p_++) {
          LDB(Bh, ub, 1)
          MLO(A, Bl)
          ub = ubase(p_);
          LDQ(A2, p_) LDB(Bl, ub, 0)
          MHI(A, Bh)
          LDB(Bh, ub, 1)
          load_quad(A[0], tb + (16 + 512 + 16 * (p_ & 1)) * 4); load_quad(A[1], tb + (T_S + 16 * (p_ & 1)) * 4);
          MLO(A2, Bl)
          if (p_ < 2) {
            #pragma unroll
            for (int cc = 0; cc < 8; cc++) mma16816(acc[cc + 4], A[0], &Bl[cc >> 1][(cc & 1) * 2]);
            #pragma unroll
            for (int cc = 0; cc < 4; cc++) mma16816(acc[cc + 12], A[0], &Bh[cc >> 1][(cc & 1) * 2]);
            #pragma unroll
            for (int cc = 0; cc < 8; cc++) mma16816(acc[cc + 8], A[1], &Bl[cc >> 1][(cc & 1) * 2]);
          }
          const int pn = ((p_ + 1) & 3) + 4;
          ub = ubase(pn);
          LDQ(A, pn) LDB(Bl, ub, 0)
          MHI(A2, Bh)
        }
      }
      if (t7 == 0) TS(pass ? 60 : 16);
      mbar_wait(BAR(BR_DRDY + 1), 0);
      {
        const int ih = (lane >> 3) & 1;
        const uint32_t dl = blk + B_D + (uint32_t)(((lane >> 4) * 8 + (lane & 7)) * 16);
        const uint32_t d0_ = dl + ih * 1552, d8_ = dl + (ih ? 0 : 1536), d3_ = dl + B_D7 + ih * 1024;
        auto cls2 = [&](uint32_t da, uint32_t ta) {
          uint32_t B[6][2], A[6][4];
          #pragma unroll
          for (int e = 0; e < 6; e++) { B[e][0] = lds32v(ta + (e + 4) * 32); B[e][1] = lds32v(ta + (e + 3) * 32); }
          #pragma unroll
          for (int kk = 0; kk < 6; kk++) ldsm4t(A[kk], da + kk * 256);
          #pragma unroll
          for (int e = 0; e < 6; e++)
            #pragma unroll
            for (int kk = 0; kk < 6; kk++) if (2 * kk + e + 4 < 16) mma16816(acc[2 * kk + e + 4], A[kk], B[e]);
        };
        auto cls3 = [&](uint32_t da, uint32_t ta) {
          uint32_t B[8][2], A[4][4];
          #pragma unroll
          for (int e = 0; e < 8; e++) { B[e][0] = lds32v(ta + (e + 8) * 32); B[e][1] = lds32v(ta + (e + 7) * 32); }
          #pragma unroll
          for (int kk = 0; kk < 4; kk++) ldsm4t(A[kk], da + kk * 256);
          #pragma unroll
          for (int kk = 0; kk < 4; kk++)
            #pragma unroll
            for (int e = 0; e < 8; e++) if (2 * kk + e + 8 < 16) mma16816(acc[2 * kk + e + 8], A[kk], B[e]);
        };
        if (pass) {
          #pragma unroll 1
          for (int a = 0; a < 2; a++) {
            cls2(d0_ + a * B_D5, tb + (T_F2 + 48 * a - 32) * 4);
            cls2(d8_ + a * B_D5, tb + (T_F2 + 48 * a + 64) * 4);
            cls3(d3_ + a * 2048, tb + (T_F3 + 80 * a - 64) * 4);
          }
        } else {
          cls2(((w4 & 2) ? d8_ : d0_) + (w4 & 1) * B_D5, tb + (T_F2 + 48 * w4 - 32) * 4);
          if (w4 >= 2) cls3(d3_ + (w4 - 2) * 2048, tb + (T_F3 + 80 * (w4 - 2) - 64) * 4);
        }
      }
      if (t7 == 0) TS(pass ? 61 : 17);
      const uint32_t ya = (pass ? sb + OFF_BLK + 3 * BLK + w4 * 4096 : blk) + (uint32_t)((kl * 16) ^ ((kl * 2) & 0x10));
#define YTAG(v) (((v) & ~ym) | (ytag & ym))
#define STY(p) stsm4t(ya + (p) * 512, YTAG(pack2(acc[2 * (p)][0], acc[2 * (p)][1])), pack2(acc[2 * (p)][2], acc[2 * (p)][3]), \
                      YTAG(pack2(acc[2 * (p) + 1][0], acc[2 * (p) + 1][1])), pack2(acc[2 * (p) + 1][2], acc[2 * (p) + 1][3]))
      if (pass == 0) {
        const uint32_t xw = blk + 4096 + w4 * 4096 + lane * 16, xr = blk + 4096 + w4 * 1024 + lane * 16;
        #pragma unroll
        for (int h = 0; h < 2; h++) {
          bar_sync(2, 128);
          #pragma unroll
          for (int i = 0; i < 8; i++)
            sts128(xw + i * 512, __float_as_uint(acc[8 * h + i][0]), __float_as_uint(acc[8 * h + i][1]), __float_as_uint(acc[8 * h + i][2]), __float_as_uint(acc[8 * h + i][3]));
          bar_sync(2, 128);
          float y[8];
          #pragma unroll
          for (int i = 0; i < 8; i++) {
            uint32_t o[4]; lds128(o, xr + (i >> 1) * 4096 + (i & 1) * 512);
            #pragma unroll
            for (int e = 0; e < 4; e++) y[4 * (i & 1) + e] = i < 2 ? __uint_as_float(o[e]) : y[4 * (i & 1) + e] + __uint_as_float(o[e]);
          }
          stsm4t(ya + (4 * h + w4) * 512, YTAG(pack2(y[0], y[1])), pack2(y[2], y[3]), YTAG(pack2(y[4], y[5])), pack2(y[6], y[7]));
        }
      } else {
        fence_async();
        bar_sync(4, 128);
        if (t7 == 0) mbar_arrive(BAR(BR_KS + 1));
        #pragma unroll
        for (int p = 0; p < 8; p++) STY(p);
      }
      fence_async();
      __syncwarp();
      if (lane == 0) mbar_arrive(BAR(BR_Y + 1) - 8 * pass);
      if (t7 == 0) TS(pass ? 62 : 18);
    }
  }
  if (wg < 2) {
    if (EN_ATT) {
    float oc[40]; zero<40>(oc);
    {
      constexpr uint64_t dw0 = mkdesc(SB0, OFF_WOR, 1024, 1), da0 = mkdesc(SB0, 2048, 128, 0);
      const uint32_t ck = sb + tid * 32 + ((lane >> 2) << 2), ck2 = ck + (wg ? 0 : 16384);
      uint32_t bad = 0;
      auto tile = [&](int i, uint32_t so) {
        const uint32_t al = (uint32_t)da0 + wg * 64 + (so >> 4), wl = (uint32_t)dw0 + i * 640 - (i >> 1) * (1278 << 16);
        wg_fence();
        #pragma unroll
        for (int s = 0; s < 5; s++) wg_ss80_tb(oc, desc2(al + s * 256, da0 >> 32), desc2(wl + s * 128, dw0 >> 32), (i | s) != 0);
        wg_commit();
        bad |= (lds32(ck + so) ^ epoch) | (lds32(ck + so + 8192) ^ epoch) | (lds32(ck2 + so) ^ epoch);
      };
      if (w4 == 0) {
        if (EN_SSM) mbar_wait(BAR(BR_Y), 0);
        mbar_wait(BAR(BR_WO), 0);
        mbar_wait(BAR(BR_WO + 1), 0);
      }
      bar_sync(1, 256);
      if (tid == 0) TS(9);
      tile(0, SLOT(0));
      #pragma unroll 1
      for (int i = 1; i < 8; i++) {
        mbar_wait(BAR(BR_OFULL) + 8 * i, 0);
        tile(i, SLOT(i));
        wg_wait<1>();
        if (lane == 0) mbar_arrive(BAR(BR_OEMPTY - 1) + 8 * i);
      }
      #pragma unroll 1
      for (int n = 0; n < 56; n++) {
        const int i = n & 7;
        if (i == 0) {
          uint32_t any;
          asm volatile("{\n.reg .pred p;\nsetp.ne.u32 p, %1, 0;\nbarrier.red.or.pred p, 1, 256, p;\nselp.u32 %0, 1, 0, p;\n}" : "=r"(any) : "r"(bad & 1u) : "memory");
          if (!any) break;
          bad = 0;
          FIXCNT
        }
        wg_wait<0>();
        bar_sync(1, 256);
        if (tid == 0) { mbar_expect_tx(BAR(BR_RETRY), 20480); bulk_ld(sb + SLOT(5), &g_o[(r * 8 + CHUNK(i)) * 1280], 20480, BAR(BR_RETRY)); }
        mbar_wait(BAR(BR_RETRY), n & 1);
        tile(i, SLOT(5));
      }
      wg_wait<0>();
      pin<40>(oc);
    }
    if (tid == 0) TS(10);
    {
      const int row = w4 * 16 + (lane & 15);
      const uint32_t ob = sb + OFF_BLK + 3 * BLK + wg * 10240;
      #pragma unroll
      for (int j = 0; j < 8; j += 2)
        stsm4(ob + row * 128 + (((j + (lane >> 4)) ^ (row & 7)) << 4), pack2(oc[4 * j], oc[4 * j + 1]), pack2(oc[4 * j + 2], oc[4 * j + 3]),
              pack2(oc[4 * j + 4], oc[4 * j + 5]), pack2(oc[4 * j + 6], oc[4 * j + 7]));
      stsm4(ob + 8192 + row * 32 + (lane >> 4) * 16, pack2(oc[32], oc[33]), pack2(oc[34], oc[35]), pack2(oc[36], oc[37]), pack2(oc[38], oc[39]));
      fence_async();
      bar_sync(2 + wg, 128);
      if (w4 == 0 && elect_one()) {
        tma2d_st(&prm.m[M_O64], ob, 640 + c * 64, r * 128 + wg * 64);
        tma2d_st(&prm.m[M_O16], ob + 8192, 1152 + c * 16, r * 128 + wg * 64);
        bulk_commit(); bulk_wait0_read();
        if (wg == 0) { TS(11); DUMP(0, 20); }
      }
    }
    }
  } else if (EN_SSM) {
    if (t7 == 0) DUMP(40, 64);
    #pragma unroll 1
    for (int n = 0; n < 64; n++) if (!y_transpose(sb, w4, lane, ytag)) break;
  }
  }
}

typedef CUresult (*EncFn)(CUtensorMap*, CUtensorMapDataType, cuuint32_t, void*, const cuuint64_t*, const cuuint64_t*, const cuuint32_t*,
                          const cuuint32_t*, CUtensorMapInterleave, CUtensorMapSwizzle, CUtensorMapL2promotion, CUtensorMapFloatOOBfill);
static void mkmap(EncFn enc, CUtensorMap* m, const void* base, int rank, const cuuint64_t* dims, const cuuint64_t* strides, const cuuint32_t* box, CUtensorMapSwizzle swz) {
  cuuint32_t es[5] = {1, 1, 1, 1, 1};
  enc(m, CU_TENSOR_MAP_DATA_TYPE_BFLOAT16, rank, const_cast<void*>(base), dims, strides, box, es, CU_TENSOR_MAP_INTERLEAVE_NONE, swz,
      CU_TENSOR_MAP_L2_PROMOTION_L2_128B, CU_TENSOR_MAP_FLOAT_OOB_FILL_NONE);
}

extern "C" void kernel_launch(void* const* d_in, const int* in_sizes, int n_in, void* d_out, int out_size) {
  void* fn = nullptr; cudaDriverEntryPointQueryResult qr;
  cudaGetDriverEntryPoint("cuTensorMapEncodeTiled", &fn, cudaEnableDefault, &qr);
  EncFn enc = (EncFn)fn;
  void* uy = nullptr; cudaGetSymbolAddress(&uy, g_uy);
  const cuuint64_t dx[2] = {640, 2048}, sx[1] = {1280};
  const cuuint32_t bx[2] = {64, 128}, bu[2] = {80, 128};
  const cuuint64_t dw[3] = {640, 640, 3}, sw[2] = {3840, 1280};
  const cuuint32_t br[3] = {16, 32, 3};
  const cuuint64_t dwa[4] = {64, 640, 10, 3}, swa[3] = {3840, 128, 1280}, dwb[4] = {32, 640, 20, 3}, swb[3] = {3840, 64, 1280};
  const cuuint32_t bwa[4] = {64, 32, 1, 3}, bwb[4] = {32, 32, 2, 3};
  const cuuint64_t dwo[2] = {640, 640};
  const cuuint32_t bwo[2] = {64, 80}, bo64[2] = {64, 64}, bo16[2] = {16, 64};
  const cuuint64_t dsa[2] = {2048, 1280}, ssa[1] = {4096};
  const cuuint32_t bsa[2] = {64, 80};
  const cuuint64_t dout[2] = {1280, 2048}, sout[1] = {2560};
  Params prm;
  mkmap(enc, &prm.m[M_X], d_in[7], 2, dx, sx, bx, CU_TENSOR_MAP_SWIZZLE_128B);
  mkmap(enc, &prm.m[M_W128], d_in[8], 4, dwa, swa, bwa, CU_TENSOR_MAP_SWIZZLE_128B);
  mkmap(enc, &prm.m[M_W64], d_in[8], 4, dwb, swb, bwb, CU_TENSOR_MAP_SWIZZLE_64B);
  mkmap(enc, &prm.m[M_WR], d_in[8], 3, dw, sw, br, CU_TENSOR_MAP_SWIZZLE_32B);
  mkmap(enc, &prm.m[M_U], d_in[0], 2, dx, sx, bu, CU_TENSOR_MAP_SWIZZLE_NONE);
  mkmap(enc, &prm.m[M_WO], d_in[9], 2, dwo, sx, bwo, CU_TENSOR_MAP_SWIZZLE_128B);
  mkmap(enc, &prm.m[M_O64], d_out, 2, dout, sout, bo64, CU_TENSOR_MAP_SWIZZLE_128B);
  mkmap(enc, &prm.m[M_O16], d_out, 2, dout, sout, bo16, CU_TENSOR_MAP_SWIZZLE_NONE);
  mkmap(enc, &prm.m[M_SA], uy, 2, dsa, ssa, bsa, CU_TENSOR_MAP_SWIZZLE_128B);
  mkmap(enc, &prm.m[M_OUT], d_out, 2, dout, sout, bu, CU_TENSOR_MAP_SWIZZLE_NONE);
  prm.u = (const __nv_bfloat16*)d_in[0]; prm.wo = (const __nv_bfloat16*)d_in[9];
  for (int i = 0; i < 4; i++) prm.par[i] = (const __nv_bfloat16*)d_in[1 + i];
  prm.logdt = (const __nv_bfloat16*)d_in[5]; prm.dskip = (const __nv_bfloat16*)d_in[6];
  cudaFuncSetAttribute(fused_kernel, cudaFuncAttributeMaxDynamicSharedMemorySize, SMEM_BYTES);
  cudaLaunchConfig_t cfg = {};
  cfg.gridDim = dim3(128); cfg.blockDim = dim3(512); cfg.dynamicSmemBytes = SMEM_BYTES; cfg.stream = cudaStreamPerThread;
  cudaLaunchAttribute at[1];
  at[0].id = cudaLaunchAttributeClusterDimension; at[0].val.clusterDim.x = 2; at[0].val.clusterDim.y = 1; at[0].val.clusterDim.z = 1;
  cfg.attrs = at; cfg.numAttrs = 1;
  cudaLaunchKernelEx(&cfg, fused_kernel, prm);
}
```

```cpp
#include <cuda_runtime.h>
#include <cuda_bf16.h>
#include <cuda_fp16.h>
#include <cuda.h>
#include <stdint.h>

#define KST 2
#define UKB 4
#define UPF 0
#define CONV_AT 1
#define EN_ATT 1
#define EN_SSM 1

__device__ __align__(1024) __nv_bfloat16 g_uy[2 * 640 * 2048];
__device__ __align__(128) uint4 g_kvp[8 * 16 * 240];
__device__ __align__(128) uint4 g_o[128 * 1280];
__device__ __align__(128) unsigned g_flag[4 * 128 * 32];
__device__ unsigned g_epoch[128];
#define TS(i) do {} while (0)
#define DUMP(lo, hi) do {} while (0)
#define FIXCNT

constexpr uint32_t SB0 = 1024;
constexpr uint32_t W_SLOT = 15360, OFF_X = 76800;
constexpr uint32_t OFF_WOR = 81920, OFF_KVP = 10240, OFF_KVS = 71680, OFF_PK = 10240, OFF_V = 30720, OFF_EXTRA = 102400, OFF_KVB = OFF_EXTRA;
constexpr uint32_t OFF_BAR = 125952, OFF_BLK = 128000, BLK = 20480;
constexpr uint32_t B_D = 4096, B_D5 = 3088, B_D7 = 6176, B_D9 = 8224, B_TBL = 14400;
constexpr int T_S = 576, T_F2 = 624, T_F3 = 816;
constexpr uint32_t OFF_UT = OFF_BLK + 4 * BLK;
constexpr uint32_t SMEM_BYTES = OFF_BLK + 5 * BLK;
enum { BR_FULL = 0, BR_WO = 5, BR_PUB = 7, BR_KVP = 8, BR_U = 9, BR_SUM = 10, BR_GEMM = 11, BR_UIN = 12, BR_YIN = 13, BR_EPOCH = 14,
       BR_FREE = 15, BR_RETRY = 17, BR_UOUT = 18, BR_OFULL = 18, BR_KS = 26, BR_EMPTY = 31, BR_OEMPTY = 36, BR_Y = 43, BR_OSTG = 45,
       BR_DRDY = 46, BR_U2 = 48, BR_COUNT = 50 };
constexpr uint32_t OFF_EPOCH = OFF_BAR + 8 * BR_COUNT;
enum { M_X, M_W128, M_W64, M_WR, M_U, M_WO, M_O64, M_O16, M_SA, M_OUT, M_COUNT };

__device__ __forceinline__ long long clk64() { long long t; asm volatile("mov.u64 %0, %%clock64;" : "=l"(t) :: "memory"); return t; }
__device__ __forceinline__ uint32_t smem_u32(const void* p) { return (uint32_t)__cvta_generic_to_shared(p); }
__host__ __device__ constexpr uint64_t mkdesc(uint32_t addr, uint32_t lbo, uint32_t sbo, uint32_t swz) {
  return (uint64_t)((addr & 0x3FFFF) >> 4) | ((uint64_t)(lbo >> 4) << 16) | ((uint64_t)(sbo >> 4) << 32) | ((uint64_t)swz << 62);
}
__device__ __forceinline__ uint64_t desc2(uint32_t lo, uint32_t hi) { uint64_t d; asm("mov.b64 %0, {%1, %2};" : "=l"(d) : "r"(lo), "r"(hi)); return d; }
__device__ __forceinline__ void mbar_init(uint32_t bar, uint32_t cnt) { asm volatile("mbarrier.init.shared::cta.b64 [%0], %1;" :: "r"(bar), "r"(cnt) : "memory"); }
__device__ __forceinline__ void mbar_expect_tx(uint32_t bar, uint32_t bytes) { asm volatile("mbarrier.arrive.expect_tx.shared::cta.b64 _, [%0], %1;" :: "r"(bar), "r"(bytes) : "memory"); }
__device__ __forceinline__ void mbar_arrive(uint32_t bar) { asm volatile("mbarrier.arrive.shared::cta.b64 _, [%0];" :: "r"(bar) : "memory"); }
__device__ __forceinline__ void mbar_wait(uint32_t bar, uint32_t parity) {
  asm volatile("{\n.reg .pred p;\n.reg .u32 c;\nmov.u32 c, 0;\n"
    "WL:\nmbarrier.try_wait.parity.shared::cta.b64 p, [%0], %1;\n@p bra WD;\n"
    "add.u32 c, c, 1;\nsetp.lt.u32 p, c, 200000;\n@p bra WL;\nWD:\n}" :: "r"(bar), "r"(parity) : "memory");
}
__device__ __forceinline__ void poll_all(const unsigned* p, unsigned val) {
  asm volatile("{\n.reg .pred p;\n.reg .u32 c, v;\nmov.u32 c, 0;\n"
    "PL:\nld.relaxed.gpu.global.u32 v, [%0];\nsetp.eq.u32 p, v, %1;\nvote.sync.all.pred p, p, 0xffffffff;\n@p bra PD;\n"
    "add.u32 c, c, 1;\nsetp.lt.u32 p, c, 100000;\n@p bra PL;\nPD:\n}" :: "l"(p), "r"(val) : "memory");
}
__device__ __forceinline__ void poll_all_acq(const unsigned* p, unsigned val) {
  asm volatile("{\n.reg .pred p;\n.reg .u32 c, v;\nmov.u32 c, 0;\n"
    "PL:\nld.acquire.gpu.global.u32 v, [%0];\nsetp.eq.u32 p, v, %1;\nvote.sync.all.pred p, p, 0xffffffff;\n@p bra PD;\n"
    "nanosleep.u32 300;\nadd.u32 c, c, 1;\nsetp.lt.u32 p, c, 100000;\n@p bra PL;\nPD:\n}" :: "l"(p), "r"(val) : "memory");
}
__device__ __forceinline__ unsigned poll_bit(const unsigned* p, unsigned val, unsigned mask) {
  unsigned bal;
  asm volatile("{\n.reg .pred p;\n.reg .u32 c, v;\nmov.u32 c, 0;\n"
    "PL:\nld.relaxed.gpu.global.u32 v, [%1];\nsetp.eq.u32 p, v, %2;\nvote.sync.ballot.b32 %0, p, 0xffffffff;\n"
    "and.b32 v, %0, %3;\nsetp.ne.u32 p, v, 0;\n@p bra PD;\n"
    "add.u32 c, c, 1;\nsetp.lt.u32 p, c, 100000;\n@p bra PL;\nPD:\n}" : "=&r"(bal) : "l"(p), "r"(val), "r"(mask) : "memory");
  return bal;
}
__device__ __forceinline__ void fix128_w0(uint32_t* v, const void* p, uint32_t tag, uint32_t mask) {
  asm volatile("{\n.reg .pred p;\n.reg .u32 c, x;\n.reg .b128 t;\n.reg .b64 lo, hi;\nmov.u32 c, 0;\n"
    "FL:\nxor.b32 x, %0, %5;\nand.b32 x, x, %6;\nsetp.eq.u32 p, x, 0;\n@p bra FD;\n"
    "ld.relaxed.gpu.global.b128 t, [%4];\nmov.b128 {lo, hi}, t;\nmov.b64 {%0, %1}, lo;\nmov.b64 {%2, %3}, hi;\n"
    "add.u32 c, c, 1;\nsetp.lt.u32 p, c, 100000;\n@p bra FL;\nFD:\n}"
    : "+r"(v[0]), "+r"(v[1]), "+r"(v[2]), "+r"(v[3]) : "l"(p), "r"(tag), "r"(mask) : "memory");
}
__device__ __forceinline__ void fix128_w3(uint32_t* v, const void* p, uint32_t tag, uint32_t mask) {
  asm volatile("{\n.reg .pred p;\n.reg .u32 c, x;\n.reg .b128 t;\n.reg .b64 lo, hi;\nmov.u32 c, 0;\n"
    "FL:\nxor.b32 x, %3, %5;\nand.b32 x, x, %6;\nsetp.eq.u32 p, x, 0;\n@p bra FD;\n"
    "ld.relaxed.gpu.global.b128 t, [%4];\nmov.b128 {lo, hi}, t;\nmov.b64 {%0, %1}, lo;\nmov.b64 {%2, %3}, hi;\n"
    "add.u32 c, c, 1;\nsetp.lt.u32 p, c, 100000;\n@p bra FL;\nFD:\n}"
    : "+r"(v[0]), "+r"(v[1]), "+r"(v[2]), "+r"(v[3]) : "l"(p), "r"(tag), "r"(mask) : "memory");
}
__device__ __forceinline__ void fence_acq() { asm volatile("fence.acq_rel.gpu;" ::: "memory"); }
__device__ __forceinline__ bool elect_one() {
  uint32_t p; asm volatile("{\n.reg .pred P;\nelect.sync _|P, 0xffffffff;\nselp.u32 %0, 1, 0, P;\n}" : "=r"(p)); return p;
}
__device__ __forceinline__ void bar_sync(int id, int n) { asm volatile("bar.sync %0, %1;" :: "r"(id), "r"(n) : "memory"); }
__device__ __forceinline__ void fence_async() { asm volatile("fence.proxy.async.shared::cta;" ::: "memory"); }
__device__ __forceinline__ void fence_async_g() { asm volatile("fence.proxy.async.global;" ::: "memory"); }
__device__ __forceinline__ void tma2d(uint32_t dst, const CUtensorMap* m, uint32_t bar, int c0, int c1) {
  asm volatile("cp.async.bulk.tensor.2d.shared::cluster.global.mbarrier::complete_tx::bytes [%0], [%1, {%3, %4}], [%2];"
    :: "r"(dst), "l"(m), "r"(bar), "r"(c0), "r"(c1) : "memory");
}
__device__ __forceinline__ void tma3d(uint32_t dst, const CUtensorMap* m, uint32_t bar, int c0, int c1, int c2) {
  asm volatile("cp.async.bulk.tensor.3d.shared::cluster.global.mbarrier::complete_tx::bytes [%0], [%1, {%3, %4, %5}], [%2];"
    :: "r"(dst), "l"(m), "r"(bar), "r"(c0), "r"(c1), "r"(c2) : "memory");
}
__device__ __forceinline__ void tma4d(uint32_t dst, const CUtensorMap* m, uint32_t bar, int c0, int c1, int c2, int c3) {
  asm volatile("cp.async.bulk.tensor.4d.shared::cluster.global.mbarrier::complete_tx::bytes [%0], [%1, {%3, %4, %5, %6}], [%2];"
    :: "r"(dst), "l"(m), "r"(bar), "r"(c0), "r"(c1), "r"(c2), "r"(c3) : "memory");
}
__device__ __forceinline__ void tma2d_st(const CUtensorMap* m, uint32_t src, int c0, int c1) {
  asm volatile("cp.async.bulk.tensor.2d.global.shared::cta.bulk_group [%0, {%2, %3}], [%1];"
    :: "l"(m), "r"(src), "r"(c0), "r"(c1) : "memory");
}
__device__ __forceinline__ void bulk_ld(uint32_t dst, const void* src, uint32_t bytes, uint32_t bar) {
  asm volatile("cp.async.bulk.shared::cluster.global.mbarrier::complete_tx::bytes [%0], [%1], %2, [%3];"
    :: "r"(dst), "l"(src), "r"(bytes), "r"(bar) : "memory");
}
__device__ __forceinline__ void bulk_st(void* dst, uint32_t src, uint32_t bytes) {
  asm volatile("cp.async.bulk.global.shared::cta.bulk_group [%0], [%1], %2;" :: "l"(dst), "r"(src), "r"(bytes) : "memory");
}
__device__ __forceinline__ void bulk_commit() { asm volatile("cp.async.bulk.commit_group;" ::: "memory"); }
__device__ __forceinline__ void bulk_wait0() { asm volatile("cp.async.bulk.wait_group 0;" ::: "memory"); }
__device__ __forceinline__ void bulk_wait0_read() { asm volatile("cp.async.bulk.wait_group.read 0;" ::: "memory"); }
__device__ __forceinline__ unsigned ld_rlx(const unsigned* p) { unsigned v; asm volatile("ld.relaxed.gpu.global.u32 %0, [%1];" : "=r"(v) : "l"(p) : "memory"); return v; }
__device__ __forceinline__ unsigned ld_acq(const unsigned* p) { unsigned v; asm volatile("ld.acquire.gpu.global.u32 %0, [%1];" : "=r"(v) : "l"(p) : "memory"); return v; }
__device__ __forceinline__ void st_rlx(unsigned* p, unsigned v) { asm volatile("st.relaxed.gpu.global.u32 [%0], %1;" :: "l"(p), "r"(v) : "memory"); }
__device__ __forceinline__ void st_rel(unsigned* p, unsigned v) { asm volatile("st.release.gpu.global.u32 [%0], %1;" :: "l"(p), "r"(v) : "memory"); }
__device__ __forceinline__ void ld128_rlx(uint32_t* v, const void* p) {
  asm volatile("{\n.reg .b128 t;\n.reg .b64 lo, hi;\nld.relaxed.gpu.global.b128 t, [%4];\nmov.b128 {lo, hi}, t;\n"
    "mov.b64 {%0, %1}, lo;\nmov.b64 {%2, %3}, hi;\n}" : "=r"(v[0]), "=r"(v[1]), "=r"(v[2]), "=r"(v[3]) : "l"(p) : "memory");
}
__device__ __forceinline__ void st128_rlx(void* p, const uint32_t* v) {
  asm volatile("{\n.reg .b128 t;\n.reg .b64 lo, hi;\nmov.b64 lo, {%1, %2};\nmov.b64 hi, {%3, %4};\nmov.b128 t, {lo, hi};\n"
    "st.relaxed.gpu.global.b128 [%0], t;\n}" :: "l"(p), "r"(v[0]), "r"(v[1]), "r"(v[2]), "r"(v[3]) : "memory");
}
__device__ __forceinline__ uint32_t lds32(uint32_t a) { uint32_t v; asm volatile("ld.shared.u32 %0, [%1];" : "=r"(v) : "r"(a) : "memory"); return v; }
__device__ __forceinline__ uint32_t lds32v(uint32_t a) { uint32_t v; asm volatile("ld.volatile.shared.u32 %0, [%1];" : "=r"(v) : "r"(a) : "memory"); return v; }
__device__ __forceinline__ uint32_t cpa(uint32_t a, uint32_t one) { uint32_t v; asm volatile("mul.lo.u32 %0, %1, %2;" : "=r"(v) : "r"(a), "r"(one)); return v; }
__device__ __forceinline__ uint32_t cpb(uint32_t a, uint32_t zero) { uint32_t v; asm volatile("or.b32 %0, %1, %2;" : "=r"(v) : "r"(a), "r"(zero)); return v; }
__device__ __forceinline__ uint32_t lds16(uint32_t a) { uint16_t v; asm volatile("ld.shared.u16 %0, [%1];" : "=h"(v) : "r"(a) : "memory"); return v; }
__device__ __forceinline__ float ldsf(uint32_t a) { float v; asm volatile("ld.shared.f32 %0, [%1];" : "=f"(v) : "r"(a) : "memory"); return v; }
__device__ __forceinline__ void lds128(uint32_t* v, uint32_t a) { asm volatile("ld.shared.v4.u32 {%0,%1,%2,%3}, [%4];" : "=r"(v[0]), "=r"(v[1]), "=r"(v[2]), "=r"(v[3]) : "r"(a) : "memory"); }
__device__ __forceinline__ void sts32(uint32_t a, uint32_t v) { asm volatile("st.shared.u32 [%0], %1;" :: "r"(a), "r"(v) : "memory"); }
__device__ __forceinline__ void sts16(uint32_t a, uint32_t v) { asm volatile("st.shared.u16 [%0], %1;" :: "r"(a), "h"((uint16_t)v) : "memory"); }
__device__ __forceinline__ void sts64f(uint32_t a, float x, float y) { asm volatile("st.shared.v2.f32 [%0], {%1,%2};" :: "r"(a), "f"(x), "f"(y) : "memory"); }
__device__ __forceinline__ void sts128(uint32_t a, uint32_t x, uint32_t y, uint32_t z, uint32_t w) { asm volatile("st.shared.v4.u32 [%0], {%1,%2,%3,%4};" :: "r"(a), "r"(x), "r"(y), "r"(z), "r"(w) : "memory"); }
__device__ __forceinline__ void stsm4(uint32_t a, uint32_t r0, uint32_t r1, uint32_t r2, uint32_t r3) {
  asm volatile("stmatrix.sync.aligned.m8n8.x4.shared.b16 [%0], {%1,%2,%3,%4};" :: "r"(a), "r"(r0), "r"(r1), "r"(r2), "r"(r3) : "memory");
}
__device__ __forceinline__ void stsm4t(uint32_t a, uint32_t r0, uint32_t r1, uint32_t r2, uint32_t r3) {
  asm volatile("stmatrix.sync.aligned.m8n8.x4.trans.shared.b16 [%0], {%1,%2,%3,%4};" :: "r"(a), "r"(r0), "r"(r1), "r"(r2), "r"(r3) : "memory");
}
__device__ __forceinline__ void ldsm4t(uint32_t* r, uint32_t a) {
  asm volatile("ldmatrix.sync.aligned.m8n8.x4.trans.shared.b16 {%0,%1,%2,%3}, [%4];" : "=r"(r[0]), "=r"(r[1]), "=r"(r[2]), "=r"(r[3]) : "r"(a) : "memory");
}
__device__ __forceinline__ void ldsm4(uint32_t* r, uint32_t a) {
  asm volatile("ldmatrix.sync.aligned.m8n8.x4.shared.b16 {%0,%1,%2,%3}, [%4];" : "=r"(r[0]), "=r"(r[1]), "=r"(r[2]), "=r"(r[3]) : "r"(a) : "memory");
}
__device__ __forceinline__ void mma16816(float* d, const uint32_t* a, const uint32_t* b) {
  asm volatile("mma.sync.aligned.m16n8k16.row.col.f32.bf16.bf16.f32 {%0,%1,%2,%3}, {%4,%5,%6,%7}, {%8,%9}, {%0,%1,%2,%3};"
    : "+f"(d[0]), "+f"(d[1]), "+f"(d[2]), "+f"(d[3]) : "r"(a[0]), "r"(a[1]), "r"(a[2]), "r"(a[3]), "r"(b[0]), "r"(b[1]));
}
__device__ __forceinline__ uint32_t pack2(float lo, float hi) { uint32_t r; asm("cvt.rn.bf16x2.f32 %0, %1, %2;" : "=r"(r) : "f"(hi), "f"(lo)); return r; }
__device__ __forceinline__ uint32_t packh(float lo, float hi) { uint32_t r; asm("cvt.rn.f16x2.f32 %0, %1, %2;" : "=r"(r) : "f"(hi), "f"(lo)); return r; }
__device__ __forceinline__ uint32_t hcmul(uint32_t x, uint32_t zp, uint32_t zq) {
  const __half2 xx = *reinterpret_cast<__half2*>(&x);
  const __half2 r = __hfma2(__high2half2(xx), *reinterpret_cast<__half2*>(&zq), __hmul2(__low2half2(xx), *reinterpret_cast<__half2*>(&zp)));
  return *reinterpret_cast<const uint32_t*>(&r);
}
__device__ __forceinline__ void hcm2(uint32_t xr, uint32_t xi, uint32_t z, uint32_t& pr, uint32_t& pi) {
  const __half2 a = *reinterpret_cast<__half2*>(&xr), b = *reinterpret_cast<__half2*>(&xi), zz = *reinterpret_cast<__half2*>(&z);
  const __half2 re = __hfma2(__hneg2(b), __high2half2(zz), __hmul2(a, __low2half2(zz)));
  const __half2 im = __hfma2(a, __high2half2(zz), __hmul2(b, __low2half2(zz)));
  pr = *reinterpret_cast<const uint32_t*>(&re); pi = *reinterpret_cast<const uint32_t*>(&im);
}
__device__ __forceinline__ void sts64(uint32_t a, uint32_t x, uint32_t y) { asm volatile("st.shared.v2.u32 [%0], {%1,%2};" :: "r"(a), "r"(x), "r"(y) : "memory"); }
__device__ __forceinline__ void lds64(uint32_t* v, uint32_t a) { asm volatile("ld.shared.v2.u32 {%0,%1}, [%2];" : "=r"(v[0]), "=r"(v[1]) : "r"(a) : "memory"); }
__device__ __forceinline__ float bf_lo(uint32_t v) { return __uint_as_float(v << 16); }
__device__ __forceinline__ float bf_hi(uint32_t v) { return __uint_as_float(v & 0xffff0000u); }
__device__ __forceinline__ float bf_round(float x) { return bf_lo(pack2(x, 0.f)); }
__device__ __forceinline__ float ex2(float x) { float r; asm("ex2.approx.ftz.f32 %0, %1;" : "=f"(r) : "f"(x)); return r; }
__device__ __forceinline__ float phi(float t, float l2e = 1.44269504089f) {
  float e = ex2(t * l2e) + 1e-6f;
  asm("{\n.reg .pred p;\nsetp.gt.f32 p, %1, 0f00000000;\n@p add.f32 %0, %1, 0f3F800008;\n}" : "+f"(e) : "f"(t));
  return e;
}
__device__ __forceinline__ void wg_fence() { asm volatile("wgmma.fence.sync.aligned;" ::: "memory"); }
__device__ __forceinline__ void wg_commit() { asm volatile("wgmma.commit_group.sync.aligned;" ::: "memory"); }
template <int N> __device__ __forceinline__ void wg_wait() { asm volatile("wgmma.wait_group.sync.aligned %0;" :: "n"(N) : "memory"); }
template <int N> __device__ __forceinline__ void pin(float* a) {
  #pragma unroll
  for (int i = 0; i < N; i++) asm volatile("" : "+f"(a[i]) :: "memory");
}
__device__ __forceinline__ int rtid() { int t; asm volatile("mov.u32 %0, %%tid.x;" : "=r"(t)); return t; }
__device__ __forceinline__ int opaque(int v) { asm volatile("" : "+r"(v)); return v; }
template <int N> __device__ __forceinline__ void zero(float* a) {
  #pragma unroll
  for (int i = 0; i < N; i++) asm volatile("mov.b32 %0, 0;" : "=f"(a[i]));
}
template <int N> __device__ __forceinline__ void pinu(uint32_t* a) {
  #pragma unroll
  for (int i = 0; i < N; i++) asm volatile("" : "+r"(a[i]) :: "memory");
}
__device__ __forceinline__ void cexp_t(float lg2mag, float turns, float& re, float& im) {
  float m = ex2(lg2mag);
  float fr = (turns - __fadd_rn(__fadd_rn(turns, 12582912.f), -12582912.f)) * 6.283185307f;
  re = m * __cosf(fr); im = m * __sinf(fr);
}
__device__ __forceinline__ void cmul(float ar, float ai, float br, float bi, float& cr, float& ci) {
  cr = fmaf(ar, br, -ai * bi); ci = fmaf(ar, bi, ai * br);
}

__device__ __forceinline__ void wg_ss48_tt(float* d, uint64_t da, uint64_t db, int scale_d) {
  asm volatile("{\n.reg .pred p;\nsetp.ne.b32 p, %26, 0;\n"
    "wgmma.mma_async.sync.aligned.m64n48k16.f32.bf16.bf16 "
    "{%0, %1, %2, %3, %4, %5, %6, %7, %8, %9, %10, %11, %12, %13, %14, %15, %16, %17, %18, %19, %20, %21, %22, %23}, %24, %25, p, 1, 1, 1, 1;\n}\n"
    : "+f"(d[0]), "+f"(d[1]), "+f"(d[2]), "+f"(d[3]), "+f"(d[4]), "+f"(d[5]), "+f"(d[6]), "+f"(d[7]), "+f"(d[8]), "+f"(d[9]), "+f"(d[10]), "+f"(d[11]), "+f"(d[12]), "+f"(d[13]), "+f"(d[14]), "+f"(d[15]), "+f"(d[16]), "+f"(d[17]), "+f"(d[18]), "+f"(d[19]), "+f"(d[20]), "+f"(d[21]), "+f"(d[22]), "+f"(d[23])
    : "l"(da), "l"(db), "r"(scale_d));
}
__device__ __forceinline__ void wg_rs88_tb(float* d, const uint32_t* a, uint64_t db, int scale_d) {
  asm volatile("{\n.reg .pred p;\nsetp.ne.b32 p, %49, 0;\n"
    "wgmma.mma_async.sync.aligned.m64n88k16.f32.bf16.bf16 "
    "{%0, %1, %2, %3, %4, %5, %6, %7, %8, %9, %10, %11, %12, %13, %14, %15, %16, %17, %18, %19, %20, %21, %22, %23, %24, %25, %26, %27, %28, %29, %30, %31, %32, %33, %34, %35, %36, %37, %38, %39, %40, %41, %42, %43}, {%44, %45, %46, %47}, %48, p, 1, 1, 1;\n}\n"
    : "+f"(d[0]), "+f"(d[1]), "+f"(d[2]), "+f"(d[3]), "+f"(d[4]), "+f"(d[5]), "+f"(d[6]), "+f"(d[7]), "+f"(d[8]), "+f"(d[9]), "+f"(d[10]), "+f"(d[11]), "+f"(d[12]), "+f"(d[13]), "+f"(d[14]), "+f"(d[15]), "+f"(d[16]), "+f"(d[17]), "+f"(d[18]), "+f"(d[19]), "+f"(d[20]), "+f"(d[21]), "+f"(d[22]), "+f"(d[23]), "+f"(d[24]), "+f"(d[25]), "+f"(d[26]), "+f"(d[27]), "+f"(d[28]), "+f"(d[29]), "+f"(d[30]), "+f"(d[31]), "+f"(d[32]), "+f"(d[33]), "+f"(d[34]), "+f"(d[35]), "+f"(d[36]), "+f"(d[37]), "+f"(d[38]), "+f"(d[39]), "+f"(d[40]), "+f"(d[41]), "+f"(d[42]), "+f"(d[43])
    : "r"(a[0]), "r"(a[1]), "r"(a[2]), "r"(a[3]), "l"(db), "r"(scale_d));
}
__device__ __forceinline__ void wg_ss80_tb(float* d, uint64_t da, uint64_t db, int scale_d) {
  asm volatile("{\n.reg .pred p;\nsetp.ne.b32 p, %42, 0;\n"
    "wgmma.mma_async.sync.aligned.m64n80k16.f32.bf16.bf16 "
    "{%0, %1, %2, %3, %4, %5, %6, %7, %8, %9, %10, %11, %12, %13, %14, %15, %16, %17, %18, %19, %20, %21, %22, %23, %24, %25, %26, %27, %28, %29, %30, %31, %32, %33, %34, %35, %36, %37, %38, %39}, %40, %41, p, 1, 1, 0, 1;\n}\n"
    : "+f"(d[0]), "+f"(d[1]), "+f"(d[2]), "+f"(d[3]), "+f"(d[4]), "+f"(d[5]), "+f"(d[6]), "+f"(d[7]), "+f"(d[8]), "+f"(d[9]), "+f"(d[10]), "+f"(d[11]), "+f"(d[12]), "+f"(d[13]), "+f"(d[14]), "+f"(d[15]), "+f"(d[16]), "+f"(d[17]), "+f"(d[18]), "+f"(d[19]), "+f"(d[20]), "+f"(d[21]), "+f"(d[22]), "+f"(d[23]), "+f"(d[24]), "+f"(d[25]), "+f"(d[26]), "+f"(d[27]), "+f"(d[28]), "+f"(d[29]), "+f"(d[30]), "+f"(d[31]), "+f"(d[32]), "+f"(d[33]), "+f"(d[34]), "+f"(d[35]), "+f"(d[36]), "+f"(d[37]), "+f"(d[38]), "+f"(d[39])
    : "l"(da), "l"(db), "r"(scale_d));
}
__device__ __forceinline__ void wg_ss48_tt_h(float* d, uint64_t da, uint64_t db, int scale_d) {
  asm volatile("{\n.reg .pred p;\nsetp.ne.b32 p, %26, 0;\n"
    "wgmma.mma_async.sync.aligned.m64n48k16.f32.f16.f16 "
    "{%0, %1, %2, %3, %4, %5, %6, %7, %8, %9, %10, %11, %12, %13, %14, %15, %16, %17, %18, %19, %20, %21, %22, %23}, %24, %25, p, 1, 1, 1, 1;\n}\n"
    : "+f"(d[0]), "+f"(d[1]), "+f"(d[2]), "+f"(d[3]), "+f"(d[4]), "+f"(d[5]), "+f"(d[6]), "+f"(d[7]), "+f"(d[8]), "+f"(d[9]), "+f"(d[10]), "+f"(d[11]), "+f"(d[12]), "+f"(d[13]), "+f"(d[14]), "+f"(d[15]), "+f"(d[16]), "+f"(d[17]), "+f"(d[18]), "+f"(d[19]), "+f"(d[20]), "+f"(d[21]), "+f"(d[22]), "+f"(d[23])
    : "l"(da), "l"(db), "r"(scale_d));
}
__device__ __forceinline__ void wg_rs192_tb(float* d, const uint32_t* a, uint64_t db, int scale_d) {
  asm volatile("{\n.reg .pred p;\nsetp.ne.b32 p, %101, 0;\n"
    "wgmma.mma_async.sync.aligned.m64n192k16.f32.bf16.bf16 "
    "{%0, %1, %2, %3, %4, %5, %6, %7, %8, %9, %10, %11, %12, %13, %14, %15, %16, %17, %18, %19, %20, %21, %22, %23, %24, %25, %26, %27, %28, %29, %30, %31, %32, %33, %34, %35, %36, %37, %38, %39, %40, %41, %42, %43, %44, %45, %46, %47, %48, %49, %50, %51, %52, %53, %54, %55, %56, %57, %58, %59, %60, %61, %62, %63, %64, %65, %66, %67, %68, %69, %70, %71, %72, %73, %74, %75, %76, %77, %78, %79, %80, %81, %82, %83, %84, %85, %86, %87, %88, %89, %90, %91, %92, %93, %94, %95}, {%96, %97, %98, %99}, %100, p, 1, 1, 1;\n}\n"
    : "+f"(d[0]), "+f"(d[1]), "+f"(d[2]), "+f"(d[3]), "+f"(d[4]), "+f"(d[5]), "+f"(d[6]), "+f"(d[7]), "+f"(d[8]), "+f"(d[9]), "+f"(d[10]), "+f"(d[11]), "+f"(d[12]), "+f"(d[13]), "+f"(d[14]), "+f"(d[15]), "+f"(d[16]), "+f"(d[17]), "+f"(d[18]), "+f"(d[19]), "+f"(d[20]), "+f"(d[21]), "+f"(d[22]), "+f"(d[23]), "+f"(d[24]), "+f"(d[25]), "+f"(d[26]), "+f"(d[27]), "+f"(d[28]), "+f"(d[29]), "+f"(d[30]), "+f"(d[31]), "+f"(d[32]), "+f"(d[33]), "+f"(d[34]), "+f"(d[35]), "+f"(d[36]), "+f"(d[37]), "+f"(d[38]), "+f"(d[39]), "+f"(d[40]), "+f"(d[41]), "+f"(d[42]), "+f"(d[43]), "+f"(d[44]), "+f"(d[45]), "+f"(d[46]), "+f"(d[47]), "+f"(d[48]), "+f"(d[49]), "+f"(d[50]), "+f"(d[51]), "+f"(d[52]), "+f"(d[53]), "+f"(d[54]), "+f"(d[55]), "+f"(d[56]), "+f"(d[57]), "+f"(d[58]), "+f"(d[59]), "+f"(d[60]), "+f"(d[61]), "+f"(d[62]), "+f"(d[63]), "+f"(d[64]), "+f"(d[65]), "+f"(d[66]), "+f"(d[67]), "+f"(d[68]), "+f"(d[69]), "+f"(d[70]), "+f"(d[71]), "+f"(d[72]), "+f"(d[73]), "+f"(d[74]), "+f"(d[75]), "+f"(d[76]), "+f"(d[77]), "+f"(d[78]), "+f"(d[79]), "+f"(d[80]), "+f"(d[81]), "+f"(d[82]), "+f"(d[83]), "+f"(d[84]), "+f"(d[85]), "+f"(d[86]), "+f"(d[87]), "+f"(d[88]), "+f"(d[89]), "+f"(d[90]), "+f"(d[91]), "+f"(d[92]), "+f"(d[93]), "+f"(d[94]), "+f"(d[95])
    : "r"(a[0]), "r"(a[1]), "r"(a[2]), "r"(a[3]), "l"(db), "r"(scale_d));
}
__device__ __forceinline__ void wg_rs48_tb(float* d, const uint32_t* a, uint64_t db, int scale_d) {
  asm volatile("{\n.reg .pred p;\nsetp.ne.b32 p, %29, 0;\n"
    "wgmma.mma_async.sync.aligned.m64n48k16.f32.bf16.bf16 "
    "{%0, %1, %2, %3, %4, %5, %6, %7, %8, %9, %10, %11, %12, %13, %14, %15, %16, %17, %18, %19, %20, %21, %22, %23}, {%24, %25, %26, %27}, %28, p, 1, 1, 1;\n}\n"
    : "+f"(d[0]), "+f"(d[1]), "+f"(d[2]), "+f"(d[3]), "+f"(d[4]), "+f"(d[5]), "+f"(d[6]), "+f"(d[7]), "+f"(d[8]), "+f"(d[9]), "+f"(d[10]), "+f"(d[11]), "+f"(d[12]), "+f"(d[13]), "+f"(d[14]), "+f"(d[15]), "+f"(d[16]), "+f"(d[17]), "+f"(d[18]), "+f"(d[19]), "+f"(d[20]), "+f"(d[21]), "+f"(d[22]), "+f"(d[23])
    : "r"(a[0]), "r"(a[1]), "r"(a[2]), "r"(a[3]), "l"(db), "r"(scale_d));
}

struct Params {
  const __nv_bfloat16 *par[4], *logdt, *dskip, *u, *wo;
  CUtensorMap m[M_COUNT];
};

#define CHUNK(i) ((i) == 0 ? c : ((i) == 7 ? (c ^ 1) : (((c & 6) + 1 + (i)) & 7)))
#define FLAG(kind, rr, cc) (&g_flag[((kind) * 128 + (rr) * 8 + (cc)) * 32])
#define SLOT(i) ((i) == 0 ? OFF_EXTRA : OFF_BLK - 256 + ((i) > 5 ? (i) - 6 : (i) - 1) * BLK)
__device__ __forceinline__ void load_quad(uint32_t* A, uint32_t addr) {
  A[0] = lds32v(addr); A[1] = lds32v(addr + 32); A[2] = lds32v(addr - 32); A[3] = lds32v(addr);
}

__device__ __forceinline__ bool y_transpose(uint32_t sb, int w5, int lane, uint32_t ytag) {
  const int mi = lane >> 3, rw = lane & 7;
  const uint32_t sa = sb + OFF_EXTRA + (w5 * 16 + rw) * 128 + ((mi ^ rw) << 4), da = sb + SLOT(3) + (8 * mi + rw) * 160 + w5 * 32;
  const uint32_t ym = lane < 4 ? 0x10001u : 0u;
  bar_sync(7, 160);
  uint32_t v[8][4], bad = 0;
  #pragma unroll
  for (int q = 0; q < 8; q++) ldsm4t(v[q], (sa ^ ((q & 1) * 64 + ((q >> 1) & 1) * 16)) + ((q >> 1) & 1) * 10240 + (q >> 2) * 1024);
  #pragma unroll
  for (int q = 0; q < 8; q++) {
    bad |= (v[q][0] ^ ytag) | (v[q][2] ^ ytag);
    stsm4(da + (q & 3) * 5120 + (q >> 2) * 16, v[q][0] & ~ym, v[q][1], v[q][2] & ~ym, v[q][3]);
  }
  fence_async();
  uint32_t any;
  asm volatile("{\n.reg .pred p;\nsetp.ne.u32 p, %1, 0;\nbarrier.red.or.pred p, 7, 160, p;\nselp.u32 %0, 1, 0, p;\n}" : "=r"(any) : "r"(bad & ym) : "memory");
  return any;
}

__global__ void __launch_bounds__(512, 1) fused_kernel(const __grid_constant__ Params prm) {
  extern __shared__ unsigned char smem_raw[];
  uint32_t raw[5][2], pd;
  if ((threadIdx.x >> 7) == 2) {
    const int ch = (blockIdx.x & 7) * 80 + (blockIdx.x >> 3) * 5, od = threadIdx.x & 1;
    #pragma unroll
    for (int e = 0; e < 2; e++) {
      const __nv_bfloat16* pp = prm.par[2 * e + od] + ch * 128 + (threadIdx.x & 126);
      #pragma unroll
      for (int q = 0; q < 5; q++) asm volatile("ld.global.nc.u32 %0, [%1];" : "=r"(raw[q][e]) : "l"(pp + q * 128));
    }
    asm volatile("ld.global.nc.u16 %0, [%1];" : "=r"(pd) : "l"(((threadIdx.x & 8) ? prm.dskip : prm.logdt) + ch + min(threadIdx.x & 7, 4)));
  }
  const uint32_t sb = __shfl_sync(0xffffffff, smem_u32(smem_raw), 0);
  const int tid = threadIdx.x, lane = tid & 31;
  const int warp = __shfl_sync(0xffffffff, tid >> 5, 0), wg = warp >> 2, w4 = warp & 3;
  const int cta = blockIdx.x, r = cta >> 3, c = cta & 7;
  if ((sb & 0xffffffu) != SB0) return;
#define BAR(i) (sb + OFF_BAR + 8 * (i))
  const bool sw64 = ((c + 1) & 2) != 0;

  const CUtensorMap* mwp = &prm.m[sw64 ? M_W64 : M_W128];
  const int mcol = (c * 80 + (c & 1) * 16) >> (sw64 ? 5 : 6), rcol = c * 80 + ((c & 1) ? 0 : 64);
  if (warp == 12 && elect_one()) {
    #pragma unroll
    for (int i = 0; i < 5; i++) mbar_init(BAR(BR_FULL + i), 1);
    asm volatile("fence.mbarrier_init.release.cluster;" ::: "memory");
    if (EN_ATT) {
      mbar_expect_tx(BAR(BR_FULL), W_SLOT + 16384);
      tma4d(sb, mwp, BAR(BR_FULL), 0, 0, mcol, 0);
      tma2d(sb + OFF_X, &prm.m[M_X], BAR(BR_FULL), 0, r * 128);
      tma3d(sb + 12288, &prm.m[M_WR], BAR(BR_FULL), rcol, 0, 0);
      mbar_expect_tx(BAR(BR_FULL + 1), W_SLOT);
      tma4d(sb + W_SLOT, mwp, BAR(BR_FULL + 1), 0, 32, mcol, 0);
      tma3d(sb + W_SLOT + 12288, &prm.m[M_WR], BAR(BR_FULL + 1), rcol, 32, 0);
      TS(24);
    }
  }
  if (warp == 13 && elect_one()) {
    asm volatile("prefetch.tensormap [%0];" :: "l"(&prm.m[M_X]) : "memory");
    asm volatile("prefetch.tensormap [%0];" :: "l"(&prm.m[M_WR]) : "memory");
  }
  if (wg == 3) {
    asm volatile("setmaxnreg.dec.sync.aligned.u32 56;");
    const int tid = rtid(), lane = tid & 31;
    if (warp == 12) {
      asm volatile("bar.arrive 0, 512;" ::: "memory");
      {
        uint32_t s = 2, ph = 1, xs = 16384;
        #pragma unroll 1
        for (int kb = 2; kb < 20; kb++) {
          if (kb == 4) bar_sync(6, 128);
          if (kb >= 5) mbar_wait(BAR(BR_EMPTY) + 8 * s, ph);
          if (EN_ATT && elect_one()) {
            const uint32_t st = sb + s * W_SLOT, fb = BAR(BR_FULL) + 8 * s;
            mbar_expect_tx(fb, (kb & 1) ? W_SLOT : W_SLOT + 16384);
            if (!(kb & 1)) tma2d(sb + OFF_X + xs, &prm.m[M_X], fb, kb * 32, r * 128);
            tma4d(st, mwp, fb, 0, kb * 32, mcol, 0);
            tma3d(st + 12288, &prm.m[M_WR], fb, rcol, kb * 32, 0);
          }
          if (kb < 4 && lane == 0) TS(24 + kb);
          if (UPF && kb >= UKB - 4 && kb < UKB && elect_one())
            asm volatile("cp.async.bulk.prefetch.L2.global [%0], 5120;" :: "l"(prm.u + cta * 10240 + (kb - (UKB - 4)) * 2560) : "memory");
          if (EN_SSM && kb == (EN_ATT ? UKB : 4) && elect_one()) { mbar_expect_tx(BAR(BR_UIN), 20480); tma2d(sb + OFF_UT, &prm.m[M_U], BAR(BR_UIN), c * 80, r * 128); }
          if (kb == 14 && elect_one()) asm volatile("cp.async.bulk.prefetch.L2.global [%0], 6400;" :: "l"(prm.wo + cta * 3200) : "memory");
          if (!EN_ATT && kb == 4) break;
          if (++s == 5) { s = 0; ph ^= 1; }
          if (kb & 1) { xs += 16384; if (xs == 49152) xs = 0; }
        }
      }
      if (EN_ATT) {
      mbar_wait(BAR(BR_EPOCH), 0);
      const unsigned epoch = lds32(sb + OFF_EPOCH);
      const unsigned* fo = FLAG(3, r, lane & 7);
      unsigned seen = __ballot_sync(0xffffffff, ld_rlx(lane < 16 ? fo : FLAG(0, lane & 15, c)) == epoch) & 0xffu;
      mbar_wait(BAR(BR_GEMM), 0);
      if (elect_one()) {
        mbar_expect_tx(BAR(BR_WO), 10240);
        tma2d(sb, &prm.m[M_WO], BAR(BR_WO), c * 64, c * 80);
        mbar_expect_tx(BAR(BR_KVP), 61440);
        mbar_expect_tx(BAR(BR_WO + 1), 7 * 10240);
      }
      {
        uint32_t ds = sb + OFF_WOR + (lane >> 3) * 128 + (((lane & 7) ^ (lane >> 3)) << 4);
        #pragma unroll 1
        for (int h = 0; h < 2; h++) {
          const int i = (lane & 6) + h;
          const char* gs = reinterpret_cast<const char*>(prm.wo) + (size_t)((lane >> 3) + CHUNK(i) * 80) * 1280 + 1024 + c * 32 + (lane & 1) * 16;
          #pragma unroll 2
          for (int q = 0; q < 20; q++) {
            asm volatile("cp.async.cg.shared.global [%0], [%1], 16;" :: "r"(ds), "l"(gs) : "memory");
            ds = (ds + 512) ^ 64; gs += 5120;
          }
        }
      }
      mbar_wait(BAR(BR_PUB), 0);
      poll_all(FLAG(0, lane & 15, c), epoch);
      if (elect_one()) { TS(23); bulk_ld(sb + OFF_KVP, &g_kvp[c * 16 * 240], 61440, BAR(BR_KVP)); }
      asm volatile("cp.async.wait_all;" ::: "memory");
      fence_async();
      mbar_arrive(BAR(BR_WO));
      mbar_wait(BAR(BR_SUM), 0);
      if (elect_one()) {
        #pragma unroll 1
        for (int i = 1; i < 8; i++) tma2d(sb + i * 10240, &prm.m[M_WO], BAR(BR_WO + 1), c * 64, CHUNK(i) * 80);
      }
      mbar_wait(BAR(BR_OSTG), 0);
      if (elect_one()) {
        bulk_st(&g_o[cta * 1280], sb + OFF_EXTRA, 20480);
        bulk_commit();
        bulk_wait0();
        st_rlx(FLAG(3, r, c), epoch);
        mbar_arrive(BAR(BR_OEMPTY));
        TS(20);
      }
      __syncwarp();
      #pragma unroll 1
      for (int i = 1; i < 8; i++) {
        const int src = CHUNK(i);
        if (!((seen >> src) & 1)) seen = poll_bit(fo, epoch, 1u << src);
        if (i > 5) mbar_wait(BAR(BR_OEMPTY - 5) + 8 * i, 0);
        else if (EN_SSM && i != 2 && i != 3) mbar_wait(i == 1 ? BAR(BR_KS + 1) : BAR(BR_FREE - 4) + 8 * i, 0);
        if (elect_one()) {
          mbar_expect_tx(BAR(BR_OFULL) + 8 * i, 20480);
          bulk_ld(sb + SLOT(i), &g_o[(r * 8 + src) * 1280], 20480, BAR(BR_OFULL) + 8 * i);
          if (i == 1) TS(21);
          if (i == 7) TS(22);
        }
        __syncwarp();
      }
      if (lane == 0) { DUMP(20, 30); }
      }
    } else {
      const int hw = warp - 13, ht = tid - 416;
      if (hw == 2 && elect_one()) {
        #pragma unroll
        for (int i = 5; i < BR_COUNT; i++) mbar_init(BAR(i), i == BR_WO ? 33 : i == BR_OEMPTY ? 9 : i < BR_EMPTY ? 1 : i < BR_OEMPTY ? 2 : i < BR_Y ? 8 : i < BR_OSTG ? 4 : i == BR_OSTG ? 8 : i < BR_U2 ? 3 : 1);
        asm volatile("fence.mbarrier_init.release.cluster;" ::: "memory");
      }
      __syncwarp();
      asm volatile("bar.arrive 0, 512;" ::: "memory");
      if (EN_SSM && hw == 2) asm volatile("bar.arrive 8, 160;" ::: "memory");
      const unsigned epoch = hw == 0 ? ld_rlx(&g_epoch[cta]) + 1 : 0;
      bar_sync(5, 96);
      asm volatile("bar.arrive 6, 128;" ::: "memory");
      if (hw == 1 && elect_one()) {
        #pragma unroll
        for (int i = M_U; i < M_COUNT; i++) asm volatile("prefetch.tensormap [%0];" :: "l"(&prm.m[i]) : "memory");
      }
      if (ht == 0) {
        st_rlx(&g_epoch[cta], epoch);
        sts32(sb + OFF_EPOCH, epoch);
        mbar_arrive(BAR(BR_EPOCH));
      }
      if (EN_SSM) {
      const int mi = lane >> 3, rw = lane & 7, ch0 = c * 80 + r * 5;
      const bool early_u = hw == 0 && __all_sync(0xffffffff, ld_acq(FLAG(1, lane & 15, c)) == epoch);
      mbar_wait(BAR(BR_UIN), 0);
      if (ht == 0) TS(36);
      #pragma unroll 1
      for (int h = 0; h < 2; h++) {
        const uint32_t sa = sb + OFF_UT + h * 10240 + (8 * mi + rw) * 160 + hw * 16, da = sb + OFF_UT + h * 10240 + (hw * 8 + rw) * 128 + ((mi ^ rw ^ h) << 4);
        uint32_t v[8][4];
        #pragma unroll
        for (int q = 0; q < 8; q++) if (q < 6 || hw == 0) ldsm4t(v[q], sa + (q & 1) * 5120 + (q >> 1) * 48);
        bar_sync(5, 96);
        #pragma unroll
        for (int q = 0; q < 8; q++) if (q < 6 || hw == 0) stsm4((da ^ ((q & 1) * 64)) + (q >> 1) * 3072, v[q][0], v[q][1], v[q][2], v[q][3]);
      }
      fence_async();
      bar_sync(5, 96);
      if (hw == 0) {
        if (elect_one()) {
          tma2d_st(&prm.m[M_SA], sb + OFF_UT, r * 128, c * 80);
          tma2d_st(&prm.m[M_SA], sb + OFF_UT + 10240, r * 128 + 64, c * 80);
          bulk_commit(); bulk_wait0_read();
          mbar_arrive(BAR(BR_UOUT));
          TS(37);
          bulk_wait0();
          st_rel(FLAG(1, r, c), epoch);
          TS(30);
        }
        __syncwarp();
        if (!early_u) poll_all_acq(FLAG(1, lane & 15, c), epoch);
      }
      #pragma unroll 1
      for (int k = 0; k < 5; k++) {
        if (k == 0 || k == 3) {
          const int p = k != 0;
          if (hw == 0) {
            if (!p) {
              if (elect_one()) {
                fence_async_g();
                mbar_expect_tx(BAR(BR_U), 12288);
                #pragma unroll 1
                for (int q = 0; q < 3; q++) bulk_ld(sb + OFF_BLK + q * q * BLK, g_uy + (ch0 + q * q) * 2048, 4096, BAR(BR_U));
                TS(31);
              }
              __syncwarp();
            }
            mbar_wait(BAR(p ? BR_U2 : BR_U), 0);
          }
          bar_sync(5, 96);
        }
        const int l3 = (hw + k) % 3 * 32 + lane;
        const uint32_t blk = sb + OFF_BLK + ((0x32410 >> (4 * k)) & 7) * BLK, o = blk + B_D + l3 * 16;
        float P[34];
        P[0] = 0.f;
        #pragma unroll
        for (int q = 0; q < 5; q++) {
          const int ch = 2 * l3 - 3 + q;
          uint32_t v[4];
          lds128(v, blk + (uint32_t)((ch * 16) ^ ((ch * 2) & 0x10)));
          #pragma unroll
          for (int e = 0; e < 8; e++) {
            const int i = 8 * q + e - 4;
            if (i >= 0 && i < 33) P[i + 1] = P[i] + ((e & 1) ? bf_hi(v[e >> 1]) : bf_lo(v[e >> 1]));
          }
        }
#define WIN(lo, hi, e) (P[21 + (e) - (lo)] - P[20 + (e) - (hi)])
#define WIN8(lo, hi, b) pack2(WIN(lo, hi, b), WIN(lo, hi, b + 1)), pack2(WIN(lo, hi, b + 2), WIN(lo, hi, b + 3)), pack2(WIN(lo, hi, b + 4), WIN(lo, hi, b + 5)), pack2(WIN(lo, hi, b + 6), WIN(lo, hi, b + 7))
        if (l3 < 64) {
          sts128(o + B_D9, WIN8(12, 20, 0)); sts128(o + B_D9 + 1024, WIN8(12, 20, 8));
          sts128(o + B_D7, WIN8(5, 11, 0)); sts128(o + B_D7 + 1024, WIN8(5, 11, 8));
        }
        sts128(o + B_D5, WIN8(6, 10, 0)); sts128(o + B_D5 + 1552, WIN8(6, 10, 8));
        sts128(o, WIN8(3, 5, 0)); sts128(o + 1552, WIN8(3, 5, 8));
        if (l3 < 2) sts128(blk + B_D + l3 * B_D5 + 1536, 0, 0, 0, 0);
      }
      __syncwarp();
      if (lane == 0) mbar_arrive(BAR(BR_DRDY + 1));
      if (ht == 0) TS(32);
      if (hw == 0) {
        const bool early = __all_sync(0xffffffff, ld_rlx(FLAG(2, lane & 15, c)) == epoch);
        #pragma unroll 1
        for (int p = 0; p < 2; p++) {
          mbar_wait(BAR(BR_Y) + 8 * p, 0);
          if (elect_one()) {
            bulk_st(g_uy + (640 + ch0 + 4 * p) * 2048, sb + OFF_BLK + (3 + p) * BLK, p ? 4096 : 16384);
            bulk_commit(); bulk_wait0_read();
            mbar_arrive(BAR(BR_FREE) + 8 * p);
          }
          __syncwarp();
        }
        if (elect_one()) { bulk_wait0(); st_rlx(FLAG(2, r, c), epoch); TS(33); }
        __syncwarp();
        if (!early) poll_all(FLAG(2, lane & 15, c), epoch);
        if (EN_ATT) mbar_wait(BAR(BR_OEMPTY), 0);
        #pragma unroll 1
        for (int n = 0; n < 64; n++) {
          if (elect_one()) {
            mbar_expect_tx(BAR(BR_YIN), 20480);
            tma2d(sb + OFF_EXTRA, &prm.m[M_SA], BAR(BR_YIN), r * 128, 640 + c * 80);
            tma2d(sb + OFF_EXTRA + 10240, &prm.m[M_SA], BAR(BR_YIN), r * 128 + 64, 640 + c * 80);
            TS(34);
          }
          __syncwarp();
          if (EN_ATT) mbar_wait(BAR(BR_OEMPTY + 3), 0);
          mbar_wait(BAR(BR_YIN), n & 1);
          if (lane == 0) TS(38);
          if (!y_transpose(sb, 4, lane, (epoch & 1u) * 0x10001u)) break;
          FIXCNT
        }
      if (elect_one()) {
        TS(39);
        tma2d_st(&prm.m[M_OUT], sb + SLOT(3), c * 80, r * 128);
        bulk_commit(); bulk_wait0_read();
        TS(35); DUMP(30, 40); DUMP(0, 1);
      }
      }
      }
    }
  } else {
  if (wg < 2) {
    asm volatile("setmaxnreg.inc.sync.aligned.u32 160;");
    bar_sync(0, 512);
    if (EN_ATT) {
    float am[96], ar[24];
    {
      const bool lead = (rtid() & 127) == 0;
      constexpr uint64_t dr0 = mkdesc(SB0 + 12288, 1024, 256, 3);
      const uint64_t db0 = sw64 ? mkdesc(SB0, 2048, 512, 2) : mkdesc(SB0, 4096, 1024, 1);
      const uint32_t kst = sw64 ? 64 : 128, bh = db0 >> 32;
      uint32_t s = 0, ph = 0, xo = 0;
      const int ln = rtid() & 31;
      const uint32_t xa = sb + OFF_X + (warp * 16 + (ln & 15)) * 128 + (((ln >> 4) ^ (ln & 7)) << 4);
      uint32_t A[8];
      mbar_wait(BAR(BR_FULL), 0);
      if (lead && wg == 0) TS(1);
      ldsm4(A, xa); ldsm4(A + 4, xa ^ 32);
      wg_fence();
      wg_rs48_tb(ar, A, dr0, 0); wg_rs192_tb(am, A, db0, 0);
      wg_commit();
      #pragma unroll 1
      for (int kb = 1; kb < 20; kb++) {
        const uint32_t wp = s * (W_SLOT >> 4), eb = BAR(BR_EMPTY) + 8 * s;
        wg_fence();
        wg_rs48_tb(ar, A + 4, desc2((uint32_t)dr0 + wp + 32, dr0 >> 32), 1);
        wg_rs192_tb(am, A + 4, desc2((uint32_t)db0 + wp + kst, bh), 1);
        wg_commit();
        if (++s == 5) { s = 0; ph ^= 1; }
        if (!(kb & 1)) { xo += 16384; if (xo == 49152) xo = 0; }
        mbar_wait(BAR(BR_FULL) + 8 * s, ph);
        const uint32_t xk = (xa + xo) ^ ((kb & 1) * 64), wn = s * (W_SLOT >> 4);
        wg_wait<1>();
        ldsm4(A, xk);
        wg_fence();
        wg_rs48_tb(ar, A, desc2((uint32_t)dr0 + wn, dr0 >> 32), 1);
        wg_rs192_tb(am, A, desc2((uint32_t)db0 + wn, bh), 1);
        wg_commit();
        wg_wait<1>();
        ldsm4(A + 4, xk ^ 32);
        if (lead && kb < 16) mbar_arrive(eb);
      }
      wg_fence();
      wg_rs48_tb(ar, A + 4, dr0 + 4 * (W_SLOT >> 4) + 32, 1);
      wg_rs192_tb(am, A + 4, desc2((uint32_t)db0 + 4 * (W_SLOT >> 4) + kst, bh), 1);
      wg_commit();
      wg_wait<0>();
      pin<96>(am); pin<24>(ar);
    }
    const int tid = rtid(), lane = tid & 31, tq = lane & 3;
    if (tid == 0) TS(2);
#define QV(j, e) ((j) < 8 ? am[4 * (j) + (e)] : ar[4 * ((j) - 8) + (e)])
#define KV_(j, e) ((j) < 8 ? am[32 + 4 * (j) + (e)] : ar[8 + 4 * ((j) - 8) + (e)])
#define VV(j, e) ((j) < 8 ? am[64 + 4 * (j) + (e)] : ar[16 + 4 * ((j) - 8) + (e)])
    {
      bar_sync(1, 256);
      if (tid == 0) mbar_arrive(BAR(BR_GEMM));
      const uint32_t ro = sb + (uint32_t)((warp * 16 + (lane & 15)) * 16);
      const int l0 = 2 * (c & 1) + (lane >> 4);
      const uint32_t ones = (tq == 0) ? 0x00003f80u : 0u;
#define PV(j) pack2(VV(j, 0), VV(j, 1)), pack2(VV(j, 2), VV(j, 3))
#define PK(j) pack2(phi(KV_(j, 0)), phi(KV_(j, 1))), pack2(phi(KV_(j, 2)), phi(KV_(j, 3)))
      stsm4(ro + OFF_V + (5 + 6 * (lane >> 4)) * 2048, ones, ones, ones, ones);
      #pragma unroll
      for (int j = 0; j < 10; j += 2) {
        const int l = (j == 8 && (c & 1)) ? l0 - 2 : l0 + j;
        stsm4(ro + OFF_V + (l + (l >= 5)) * 2048, PV(j), PV(j + 1));
        stsm4(ro + OFF_PK + l * 2048, PK(j), PK(j + 1));
      }
    }
    fence_async();
    bar_sync(1, 256);
    if (tid == 0) TS(3);
    mbar_wait(BAR(BR_EPOCH), 0);
    const unsigned epoch = lds32(sb + OFF_EPOCH);
    {
      float kv[24]; zero<24>(kv);
      constexpr uint64_t da = mkdesc(SB0 + OFF_PK, 128, 2048, 0), db = mkdesc(SB0 + OFF_V, 128, 2048, 0);
      wg_fence();
      #pragma unroll
      for (int s = 0; s < 8; s++) wg_ss48_tt(kv, desc2((uint32_t)da + wg * 640 + s * 16, da >> 32), desc2((uint32_t)db + wg * 768 + s * 16, db >> 32), s != 0);
      wg_commit();
      wg_wait<0>();
      pin<24>(kv);
      if (tid == 0) TS(15);
      if (w4 < 3) {
        const uint32_t wb = sb + OFF_KVS + (wg * 3 + w4) * 1536 + (lane & 15) * 96;
        #pragma unroll
        for (int j = 0; j < 6; j += 2)
          stsm4(wb + (j + (lane >> 4)) * 16, pack2(kv[4 * j], kv[4 * j + 1]), pack2(kv[4 * j + 2], kv[4 * j + 3]),
                pack2(kv[4 * j + 4], kv[4 * j + 5]), pack2(kv[4 * j + 6], kv[4 * j + 7]));
        __syncwarp();
        const int dl = w4 * 16 + (lane & 15), hl = dl >= 20;
        uint32_t v[4], z[4];
        lds128(v, wb + (3 * hl + (lane >> 4)) * 16);
        lds64(z, wb + 32 + 8 * hl); z[2] = lds32(wb + 80); z[3] = epoch & 1u;
        if (dl < 40) {
          uint4* dst = &g_kvp[(c * 16 + r) * 240 + wg * 40 + dl];
          v[3] = (v[3] & ~1u) | z[3];
          st128_rlx(dst + (lane >> 4) * 80, v);
          if (lane < 16) st128_rlx(dst + 160, z);
        }
      }
    }
    bar_sync(1, 256);
    if (tid == 0) { st_rlx(FLAG(0, r, c), epoch); mbar_arrive(BAR(BR_PUB)); TS(4); }
    const int kvi = (tid >= 80) + (tid >= 160) + (tid >= 240), kd = tid - 80 * kvi;
    const int khd = kd / 20, kt0 = 5 * (khd >> 1) + 2 * (khd & 1);
    const uint32_t rb = sb + OFF_KVB + kd * 16;
    if (kvi < 3) {
      #pragma unroll 1
      for (int m = kvi; m < 7; m += 3) { const int q = kt0 + 3 + m; sts128(rb + (q >= 10 ? q - 10 : q) * 1280, 0, 0, 0, 0); }
    }
    uint32_t qa[20];
    {
      const float sc = 1.44269504089f + __uint_as_float(lds32(sb + OFF_EPOCH) ^ epoch);
      #pragma unroll
      for (int j = 0; j < 10; j++) { qa[2 * j] = pack2(phi(QV(j, 0), sc), phi(QV(j, 1), sc)); qa[2 * j + 1] = pack2(phi(QV(j, 2), sc), phi(QV(j, 3), sc)); }
    }
    if (tid == 0) TS(5);
    if (warp == 7) mbar_wait(BAR(BR_KVP), 0);
    bar_sync(1, 256);
    if (tid == 0) TS(6);
    if (kvi < 3) {
      float s[8];
      zero<8>(s);
      uint32_t bad = 0;
      #pragma unroll 4
      for (int i = 0; i < 16; i += 2) {
        uint32_t w[4], x[4];
        lds128(w, sb + OFF_KVP + tid * 16 + i * 3840); lds128(x, sb + OFF_KVP + tid * 16 + i * 3840 + 3840);
        bad |= (w[3] ^ epoch) | (x[3] ^ epoch);
        #pragma unroll
        for (int e = 0; e < 4; e++) {
          asm("add.rn.bf16x2 %0, %0, %1;" : "+r"(w[e]) : "r"(x[e]));
          s[2 * e] += bf_lo(w[e]); s[2 * e + 1] += bf_hi(w[e]);
        }
      }
      if (__builtin_expect(bad & 1u, 0)) {
        zero<8>(s);
        #pragma unroll 1
        for (int i = 0; i < 16; i++) {
          uint32_t w[4] = {0, 0, 0, ~epoch};
          fix128_w3(w, &g_kvp[(c * 16 + i) * 240 + tid], epoch, 1u);
          #pragma unroll
          for (int e = 0; e < 4; e++) { s[2 * e] += bf_lo(w[e]); s[2 * e + 1] += bf_hi(w[e]); }
        }
        FIXCNT
      }
      const uint32_t p0 = pack2(s[0], s[1]), p1 = pack2(s[2], s[3]), p2 = pack2(s[4], s[5]), p3 = pack2(s[6], s[7]);
      if (kvi < 2) sts128(rb + (kt0 + (khd & 1) + kvi) * 1280, p0, p1, p2, p3);
      else {
        const bool od = khd & 1;
        sts128(rb + (5 * (khd >> 1) + 2) * 1280, od ? 0u : p0, od ? 0u : p1, od ? p0 : 0u, od ? p1 : 0u);
        const uint32_t zz = (p2 & 0xffffu) << (16 * (khd & 1));
        sts128(rb + 10 * 1280, khd < 2 ? zz : 0u, khd < 2 ? 0u : zz, 0u, 0u);
      }
    }
    fence_async();
    bar_sync(1, 256);
    if (tid == 0) { mbar_arrive(BAR(BR_SUM)); TS(7); }
    {
      float oa[44]; zero<44>(oa);
      constexpr uint64_t db = mkdesc(SB0 + OFF_KVB, 128, 1280, 0);
      wg_fence();
      #pragma unroll
      for (int s = 0; s < 5; s++) wg_rs88_tb(oa, &qa[4 * s], desc2((uint32_t)db + ((s == 4 && (c & 1)) ? 0 : (s + (c & 1)) * 16), db >> 32), s != 0);
      wg_commit();
      wg_wait<0>();
      pin<44>(oa);
      if (tid == 0) TS(13);
      float rc[4], rd[2][4];
      #pragma unroll
      for (int e = 0; e < 4; e++) asm("rcp.approx.ftz.f32 %0, %1;" : "=f"(rc[e]) : "f"(oa[40 + e] + 1e-6f));
      #pragma unroll
      for (int h = 0; h < 4; h++) {
        rd[0][h] = __shfl_sync(0xffffffff, rc[h & 1], (lane & 28) | (h >> 1));
        rd[1][h] = __shfl_sync(0xffffffff, rc[2 + (h & 1)], (lane & 28) | (h >> 1));
      }
      #pragma unroll
      for (int j = 0; j < 10; j++) {
        #pragma unroll
        for (int h = 0; h < 2; h++) {
          float f;
          if (j == 2) f = tq < 2 ? rd[h][0] : rd[h][1];
          else if (j == 7) f = tq < 2 ? rd[h][2] : rd[h][3];
          else f = rd[h][(8 * j) / 20];
          qa[2 * j + h] = pack2(oa[4 * j + 2 * h] * f, oa[4 * j + 2 * h + 1] * f);
        }
      }
      const uint32_t m0 = (lane & 7) == ((2 * w4) & 7), m1 = (lane & 7) == 2 * w4 + 1;
      const uint32_t oa_ = sb + OFF_EXTRA + (lane >> 4) * 2048 + (warp * 16 + (lane & 15)) * 16;
      bar_sync(1, 256);
#define TAG(v, m) (((v) & ~(m)) | (epoch & (m)))
      #pragma unroll
      for (int s = 0; s < 5; s++) stsm4(oa_ + s * 4096, TAG(qa[4 * s], m0), TAG(qa[4 * s + 1], m1), TAG(qa[4 * s + 2], m0), TAG(qa[4 * s + 3], m1));
    }
    fence_async();
    __syncwarp();
    if (lane == 0) mbar_arrive(BAR(BR_OSTG));
    if (tid == 0) TS(8);
    }
    asm volatile("setmaxnreg.dec.sync.aligned.u32 136;");
  } else {
    const int g = lane >> 2, tq = lane & 3, t7 = tid & 127;
    asm volatile("bar.arrive 0, 512;" ::: "memory");
    if (EN_SSM) {
    {
      #pragma unroll 1
      for (int k = 0; k < 4; k++) {
        const uint32_t z = sb + OFF_BLK + k * BLK + t7 * 16;
        sts128(z + B_TBL, 0, 0, 0, 0); sts128(z + B_TBL + 2048, 0, 0, 0, 0);
      }
      if (t7 < 80) sts128(sb + OFF_BLK + (t7 >> 4) * BLK - 256 + (t7 & 15) * 16, 0, 0, 0, 0);
      const uint32_t ea = sb + OFF_BLK + (2 + (w4 & 1)) * BLK + (lane >> 4) * 7168 + ((lane >> 3) & 1) * 256 + (lane & 7) * 16 + (w4 >> 1) * 2048;
      constexpr uint64_t dE = mkdesc(SB0 + OFF_BLK + 2 * BLK, 128, 512, 0);
      const uint32_t xa = sb + OFF_BLK + 18560 + t7 * 8, xr_ = sb + OFF_BLK + 18560 + (t7 ^ 64) * 8;
      uint32_t pr[5][2] = {};
      const int j = (w4 & 1) * 16 + (w4 >> 1) * 8 + g, i2 = tq < 2 ? 64 * tq + j : 32 * (tq - 2) + j;
      const uint32_t e2 = B_TBL + 4 * (tq < 2 ? T_F3 + (((i2 - 1) & 1) ? 80 : 0) + ((i2 - 1) >> 1) + 16 : T_F2 + (i2 & 1) * 96 + (i2 >> 1));
      const uint32_t e1 = tq < 2 ? (i2 ? e2 - 64 : B_TBL + 4 * (T_F2 + 175)) : B_TBL + 4 * (i2 ? T_F2 + ((2 * i2 - 1) & 3) * 48 + ((2 * i2 - 1) >> 2) : 16 + 511);
      const uint32_t e0 = B_TBL + (16 + 8 * j + 2 * tq) * 4;
      float dtl = 0.f;
      float hd[9];
      auto head = [&](int q) {
        const uint32_t pa0 = pr[0][0], pc0 = pr[0][1];
        const float dt = __shfl_sync(0xffffffff, dtl, q);
        #pragma unroll
        for (int e = 0; e < 2; e++) { pr[0][e] = pr[1][e]; pr[1][e] = pr[2][e]; pr[2][e] = pr[3][e]; pr[3][e] = pr[4][e]; }
        uint32_t mm[4];
        lds128(mm, sb + OFF_EPOCH + 64 + q * 16);
        const uint32_t ex = min(max(max(max(mm[0], mm[1]), max(mm[2], mm[3])) >> 7, 1u), 253u);
        const float sc = __uint_as_float((254u - ex) << 23);
        const float lr = -bf_round(expf(bf_lo(pa0))) * dt * 1.44269504089f;
        const float tn = bf_hi(pa0) * dt * 0.15915494309f;
        cexp_t(lr, -tn, hd[0], hd[1]);
        cexp_t(lr * 8.f, tn * 8.f, hd[2], hd[3]);
        cexp_t(lr * 64.f, tn * 64.f, hd[4], hd[5]);
        hd[6] = bf_lo(pc0) * sc; hd[7] = -bf_hi(pc0) * sc;
        hd[8] = 2.f * dt * __uint_as_float(ex << 23);
      };
      zero<9>(hd);
      #pragma unroll 1
      for (int it = -1; it < 5; it++) {
        const int k = it;
        const uint32_t blk = sb + OFF_BLK + k * BLK;
        float fac = 0.f;
        float ka[24]; zero<24>(ka);
        {
          if (it == 4) {
            mbar_wait(BAR(BR_UOUT), 0);
            sts128(sb + OFF_UT + B_TBL + t7 * 16, 0, 0, 0, 0); sts128(sb + OFF_UT + B_TBL + 2048 + t7 * 16, 0, 0, 0, 0);
          }
          const uint32_t ga = ea + 4096 - (w4 >> 1) * 512;
#define PUT4(i, a, b, c_, d) sts128(((i) < 8 ? ea + ((i) >> 1) * 512 : ga + (((i) - 8) >> 1) * 512) + ((i) & 1) * 128, a, b, c_, d)
          float z2r, z2i, z4r, z4i, xr[8], xi[8], gr[8], gi[8], wr[9], wi[9];
          const float z1r = hd[0], z1i = hd[1];
          xr[1] = hd[2]; xi[1] = hd[3]; wr[0] = hd[4]; wi[0] = hd[5];
          fac = hd[8];
          xr[0] = 1.f; xi[0] = 0.f;
          cmul(xr[1], xi[1], xr[1], xi[1], xr[2], xi[2]); cmul(xr[2], xi[2], xr[1], xi[1], xr[3], xi[3]);
          cmul(xr[2], xi[2], xr[2], xi[2], xr[4], xi[4]);
          #pragma unroll
          for (int b = 1; b < 4; b++) cmul(xr[4], xi[4], xr[b], xi[b], xr[4 + b], xi[4 + b]);
          cmul(wr[0], wi[0], wr[0], wi[0], wr[1], wi[1]); cmul(wr[1], wi[1], wr[0], wi[0], wr[2], wi[2]);
          cmul(wr[1], wi[1], wr[1], wi[1], wr[3], wi[3]); cmul(wr[3], wi[3], wr[3], wi[3], wr[4], wi[4]);
          cmul(wr[4], wi[4], wr[3], wi[3], wr[5], wi[5]); cmul(wr[4], wi[4], wr[4], wi[4], wr[6], wi[6]);
          cmul(wr[6], wi[6], wr[4], wi[4], wr[7], wi[7]); cmul(wr[6], wi[6], wr[6], wi[6], wr[8], wi[8]);
          uint32_t R[4], I[4], PR[4], PI[4];
          #pragma unroll
          for (int b = 0; b < 4; b++) { R[b] = packh(xr[2 * b], xr[2 * b + 1]); I[b] = packh(xi[2 * b], xi[2 * b + 1]); }
          PUT4(0, R[0], R[1], R[2], R[3]); PUT4(1, I[0], I[1], I[2], I[3]);
          #pragma unroll
          for (int i = 0; i < 3; i++) {
            const uint32_t z = packh(wr[i], wi[i]);
            #pragma unroll
            for (int b = 0; b < 4; b++) hcm2(R[b], I[b], z, PR[b], PI[b]);
            PUT4(2 * i + 2, PR[0], PR[1], PR[2], PR[3]); PUT4(2 * i + 3, PI[0], PI[1], PI[2], PI[3]);
          }
          gr[0] = hd[6]; gi[0] = hd[7];
          cmul(z1r, z1i, z1r, z1i, z2r, z2i); cmul(z2r, z2i, z2r, z2i, z4r, z4i);
          cmul(gr[0], gi[0], z1r, z1i, gr[1], gi[1]);
          cmul(gr[0], gi[0], z2r, z2i, gr[2], gi[2]); cmul(gr[1], gi[1], z2r, z2i, gr[3], gi[3]);
          #pragma unroll
          for (int b = 0; b < 4; b++) cmul(gr[b], gi[b], z4r, z4i, gr[4 + b], gi[4 + b]);
          PUT4(8, packh(gr[0], gr[1]), packh(gr[2], gr[3]), packh(gr[4], gr[5]), packh(gr[6], gr[7]));
          PUT4(9, packh(gi[0], gi[1]), packh(gi[2], gi[3]), packh(gi[4], gi[5]), packh(gi[6], gi[7]));
          {
            const uint32_t z = packh(wr[3], -wi[3]), a4r = packh(gr[0], gr[4]), a4i = packh(gi[0], gi[4]);
            hcm2(packh(gr[0], gr[2]), packh(gi[0], gi[2]), z, PR[0], PI[0]);
            hcm2(packh(gr[4], gr[6]), packh(gi[4], gi[6]), z, PR[1], PI[1]);
            hcm2(a4r, a4i, packh(wr[4], -wi[4]), PR[2], PI[2]);
            hcm2(a4r, a4i, packh(wr[5], -wi[5]), PR[3], PI[3]);
            PUT4(10, PR[0], PR[1], PR[2], PR[3]); PUT4(11, PI[0], PI[1], PI[2], PI[3]);
            float hr, hi_;
            cmul(gr[0], gi[0], wr[3], -wi[3], hr, hi_);
            const uint32_t cr = packh(gr[0], hr), ci = packh(gi[0], hi_);
            #pragma unroll
            for (int i = 0; i < 3; i++) hcm2(cr, ci, packh(wr[6 + i], -wi[6 + i]), PR[i], PI[i]);
            PUT4(12, PR[0], PR[1], PR[2], 0u); PUT4(13, PI[0], PI[1], PI[2], 0u);
          }
          if (it < 0) {
      #pragma unroll
      for (int q = 0; q < 5; q++) {
        #pragma unroll
        for (int e = 0; e < 2; e++) pr[q][e] = __byte_perm(raw[q][e], __shfl_xor_sync(0xffffffff, raw[q][e], 1), (lane & 1) ? 0x3276 : 0x5410);
        const uint32_t m = __reduce_max_sync(0xffffffff, max(raw[q][1] & 0x7fffu, (raw[q][1] >> 16) & 0x7fffu));
        if (lane == 0) sts32(sb + OFF_EPOCH + 64 + q * 16 + w4 * 4, m);
      }
      if (t7 == 0) TS(40);
            dtl = bf_round(expf(bf_lo(pd)));
          }
          fence_async();
          bar_sync(4, 128);
          wg_fence();
          #pragma unroll
          for (int s = 0; s < 8; s++) {
            const uint64_t d = dE + (s >> 2) * (BLK >> 4) + ((s >> 1) & 1) * 448 + (s & 1) * 16;
            wg_ss48_tt_h(ka, d, d + 256, s != 0);
          }
          wg_commit();
        }
        const float dsk = bf_lo(__shfl_sync(0xffffffff, pd, 8 + (it & 7)));
        head(min(it + 1, 4));
        asm volatile("{\n.reg .pred p;\nHL:\nsetp.eq.f32 p, %0, 0f46400000;\n@p bra HL;\n}" :: "f"(hd[0] + hd[2] + hd[4]));
        wg_wait<0>();
        pin<24>(ka);
        if (it < 0) bar_sync(4, 128); else {
        float kk[6];
        const bool up = w4 >= 2;
        #pragma unroll
        for (int n = 0; n < 3; n++) {
          sts64f(xa + n * BLK, up ? ka[12 + 4 * n] : ka[4 * n + 2], up ? ka[13 + 4 * n] : ka[4 * n + 3]);
          kk[2 * n] = up ? ka[14 + 4 * n] : ka[4 * n]; kk[2 * n + 1] = up ? ka[15 + 4 * n] : ka[4 * n + 1];
        }
        if (it) bar_sync(4, 128); else bar_sync(8, 160);
          if (it == 4 && w4 == 0) {
            mbar_wait(BAR(BR_U), 0);
            if (elect_one()) {
              mbar_expect_tx(BAR(BR_U2), 8192);
              bulk_ld(blk - 2 * BLK, g_uy + (c * 80 + r * 5 + 2) * 2048, 4096, BAR(BR_U2)); bulk_ld(blk - BLK, g_uy + (c * 80 + r * 5 + 3) * 2048, 4096, BAR(BR_U2));
            }
            __syncwarp();
          }
        #pragma unroll
        for (int n = 0; n < 3; n++) {
          uint32_t o[2]; lds64(o, xr_ + n * BLK);
          kk[2 * n] = (kk[2 * n] + __uint_as_float(o[0])) * fac; kk[2 * n + 1] = (kk[2 * n + 1] + __uint_as_float(o[1])) * fac;
        }
        if (t7 == 0) kk[0] += dsk;
        {
          const uint32_t v = pack2(kk[1], kk[0]), vh = v >> 16;
          const uint32_t u = pack2(kk[2], kk[3]), w = pack2(kk[4], kk[5]), uu = pack2(kk[2], kk[2]), us = pack2(kk[3], kk[2]);
          const uint32_t x = tq < 2 ? w : u, xh = x >> 16;
          sts32(blk + e0 + 4, v); sts16(blk + e0, vh); sts16(blk + e0 + 10, v);
          sts16(blk + e1, x); sts16(blk + e1 + 6, x); sts16(blk + e2, xh); sts16(blk + e2 + 6, xh);
          if (tq < 2) {
            const uint32_t pb = blk + e0 + 1024 + 8 * tq;
            sts32(pb + 4, uu); sts32(pb + 8, us); sts16(pb + 14, us);
            if (i2) { sts16(pb - 4, u); sts32(pb, uu); }
          }
          if (i2 == 0) {
            const uint32_t tb = blk + B_TBL;
            if (tq == 0) { sts16(tb + (16 + 256) * 4, u); sts16(tb + (T_S + 3) * 4, w); sts32(tb + (T_S + 4) * 4, pack2(kk[4], kk[4])); sts16(tb + (T_S + 5) * 4 + 2, w); }
            else { sts32(tb + 528 * 4, uu); sts32(tb + 529 * 4, uu); sts32(tb + 530 * 4, uu); sts16(tb + 531 * 4 + 2, u); sts16(tb + (T_F3 + 80 + 63) * 4, w); }
          }
        }
        }
        if (t7 == 0) TS(49 + it);
      }
    }
    asm volatile("setmaxnreg.inc.sync.aligned.u32 136;");
    if (t7 == 0) TS(41);
    bar_sync(4, 128);
    if (t7 == 0) mbar_arrive(BAR(BR_KS));
    if (EN_ATT) mbar_wait(BAR(BR_GEMM), 0);
    }
  }
  const int tid = rtid(), lane = tid & 31, g = lane >> 2, tq = lane & 3, t7 = tid & 127;
  mbar_wait(BAR(BR_EPOCH), 0);
  const unsigned epoch = lds32(sb + OFF_EPOCH);
  const uint32_t ytag = (epoch & 1u) * 0x10001u, ym = lane < 4 ? 0x10001u : 0u;
  if (EN_SSM && wg != 1) {
    mbar_wait(BAR(BR_KS), 0);
    mbar_wait(BAR(BR_U), 0);
    if (tid == 256) TS(42);
    {
      const int pass = wg >> 1;
      const int k = pass ? w4 : 4;
      if (k & 2) mbar_wait(BAR(BR_U2), 0);
      const uint32_t blk = sb + OFF_BLK + k * BLK, tb = blk + B_TBL + (uint32_t)((g - 2 * tq) * 4);
      float acc[16][4];
      zero<64>(&acc[0][0]);
      const int kl = 16 * (lane >> 4) + 2 * (lane & 7) + ((lane >> 3) & 1);
      {
        auto ubase = [&](int sh) { const int q = kl - 2 * sh; return blk + (uint32_t)((q * 16) ^ ((q * 2) & 0x10)); };
#define LDQ(A, sh) _Pragma("unroll") for (int m = 0; m < 4; m++) load_quad(A[m], tb + (16 + 16 * (sh) + 128 * m) * 4);
#define LDB(B, ub, h) _Pragma("unroll") for (int p = 0; p < 4; p++) ldsm4(B[p], (ub) + (4 * (h) + p) * 512);
#define MLO(A, B) _Pragma("unroll") for (int m = 0; m < 4; m++) _Pragma("unroll") for (int cc = 0; cc < 8; cc++) mma16816(acc[cc + m], A[m], &B[cc >> 1][(cc & 1) * 2]);
#define MHI(A, B) _Pragma("unroll") for (int m = 0; m < 4; m++) _Pragma("unroll") for (int cc = 0; cc < 8 - m; cc++) mma16816(acc[8 + cc + m], A[m], &B[cc >> 1][(cc & 1) * 2]);
        int p_ = pass ? 0 : w4;
        const int pe = pass ? 4 : w4 + 1;
        uint32_t A[4][4], A2[4][4], Bl[4][4], Bh[4][4];
        uint32_t ub = ubase(p_ + 4);
        LDQ(A, p_ + 4) LDB(Bl, ub, 0)
        #pragma unroll 1
        for (; p_ < pe; p_++) {
          LDB(Bh, ub, 1)
          MLO(A, Bl)
          ub = ubase(p_);
          LDQ(A2, p_) LDB(Bl, ub, 0)
          MHI(A, Bh)
          LDB(Bh, ub, 1)
          load_quad(A[0], tb + (16 + 512 + 16 * (p_ & 1)) * 4); load_quad(A[1], tb + (T_S + 16 * (p_ & 1)) * 4);
          MLO(A2, Bl)
          if (p_ < 2) {
            #pragma unroll
            for (int cc = 0; cc < 8; cc++) mma16816(acc[cc + 4], A[0], &Bl[cc >> 1][(cc & 1) * 2]);
            #pragma unroll
            for (int cc = 0; cc < 4; cc++) mma16816(acc[cc + 12], A[0], &Bh[cc >> 1][(cc & 1) * 2]);
            #pragma unroll
            for (int cc = 0; cc < 8; cc++) mma16816(acc[cc + 8], A[1], &Bl[cc >> 1][(cc & 1) * 2]);
          }
          const int pn = ((p_ + 1) & 3) + 4;
          ub = ubase(pn);
          LDQ(A, pn) LDB(Bl, ub, 0)
          MHI(A2, Bh)
        }
      }
      if (t7 == 0) TS(pass ? 60 : 16);
      mbar_wait(BAR(BR_DRDY + 1), 0);
      {
        const int ih = (lane >> 3) & 1;
        const uint32_t dl = blk + B_D + (uint32_t)(((lane >> 4) * 8 + (lane & 7)) * 16);
        const uint32_t d0_ = dl + ih * 1552, d8_ = dl + (ih ? 0 : 1536), d3_ = dl + B_D7 + ih * 1024;
        auto cls2 = [&](uint32_t da, uint32_t ta) {
          uint32_t B[6][2], A[6][4];
          #pragma unroll
          for (int e = 0; e < 6; e++) { B[e][0] = lds32v(ta + (e + 4) * 32); B[e][1] = lds32v(ta + (e + 3) * 32); }
          #pragma unroll
          for (int kk = 0; kk < 6; kk++) ldsm4t(A[kk], da + kk * 256);
          #pragma unroll
          for (int e = 0; e < 6; e++)
            #pragma unroll
            for (int kk = 0; kk < 6; kk++) if (2 * kk + e + 4 < 16) mma16816(acc[2 * kk + e + 4], A[kk], B[e]);
        };
        auto cls3 = [&](uint32_t da, uint32_t ta) {
          uint32_t B[8][2], A[4][4];
          #pragma unroll
          for (int e = 0; e < 8; e++) { B[e][0] = lds32v(ta + (e + 8) * 32); B[e][1] = lds32v(ta + (e + 7) * 32); }
          #pragma unroll
          for (int kk = 0; kk < 4; kk++) ldsm4t(A[kk], da + kk * 256);
          #pragma unroll
          for (int kk = 0; kk < 4; kk++)
            #pragma unroll
            for (int e = 0; e < 8; e++) if (2 * kk + e + 8 < 16) mma16816(acc[2 * kk + e + 8], A[kk], B[e]);
        };
        if (pass) {
          #pragma unroll 1
          for (int a = 0; a < 2; a++) {
            cls2(d0_ + a * B_D5, tb + (T_F2 + 48 * a - 32) * 4);
            cls2(d8_ + a * B_D5, tb + (T_F2 + 48 * a + 64) * 4);
            cls3(d3_ + a * 2048, tb + (T_F3 + 80 * a - 64) * 4);
          }
        } else {
          cls2(((w4 & 2) ? d8_ : d0_) + (w4 & 1) * B_D5, tb + (T_F2 + 48 * w4 - 32) * 4);
          if (w4 >= 2) cls3(d3_ + (w4 - 2) * 2048, tb + (T_F3 + 80 * (w4 - 2) - 64) * 4);
        }
      }
      if (t7 == 0) TS(pass ? 61 : 17);
      const uint32_t ya = (pass ? sb + OFF_BLK + 3 * BLK + w4 * 4096 : blk) + (uint32_t)((kl * 16) ^ ((kl * 2) & 0x10));
#define YTAG(v) (((v) & ~ym) | (ytag & ym))
#define STY(p) stsm4t(ya + (p) * 512, YTAG(pack2(acc[2 * (p)][0], acc[2 * (p)][1])), pack2(acc[2 * (p)][2], acc[2 * (p)][3]), \
                      YTAG(pack2(acc[2 * (p) + 1][0], acc[2 * (p) + 1][1])), pack2(acc[2 * (p) + 1][2], acc[2 * (p) + 1][3]))
      if (pass == 0) {
        const uint32_t xw = blk + 4096 + w4 * 4096 + lane * 16, xr = blk + 4096 + w4 * 1024 + lane * 16;
        #pragma unroll
        for (int h = 0; h < 2; h++) {
          bar_sync(2, 128);
          #pragma unroll
          for (int i = 0; i < 8; i++)
            sts128(xw + i * 512, __float_as_uint(acc[8 * h + i][0]), __float_as_uint(acc[8 * h + i][1]), __float_as_uint(acc[8 * h + i][2]), __float_as_uint(acc[8 * h + i][3]));
          bar_sync(2, 128);
          float y[8];
          #pragma unroll
          for (int i = 0; i < 8; i++) {
            uint32_t o[4]; lds128(o, xr + (i >> 1) * 4096 + (i & 1) * 512);
            #pragma unroll
            for (int e = 0; e < 4; e++) y[4 * (i & 1) + e] = i < 2 ? __uint_as_float(o[e]) : y[4 * (i & 1) + e] + __uint_as_float(o[e]);
          }
          stsm4t(ya + (4 * h + w4) * 512, YTAG(pack2(y[0], y[1])), pack2(y[2], y[3]), YTAG(pack2(y[4], y[5])), pack2(y[6], y[7]));
        }
      } else {
        fence_async();
        bar_sync(4, 128);
        if (t7 == 0) mbar_arrive(BAR(BR_KS + 1));
        #pragma unroll
        for (int p = 0; p < 8; p++) STY(p);
      }
      fence_async();
      __syncwarp();
      if (lane == 0) mbar_arrive(BAR(BR_Y + 1) - 8 * pass);
      if (t7 == 0) TS(pass ? 62 : 18);
    }
  }
  if (wg < 2) {
    if (EN_ATT) {
    float oc[40]; zero<40>(oc);
    {
      constexpr uint64_t dw0 = mkdesc(SB0, OFF_WOR, 1024, 1), da0 = mkdesc(SB0, 2048, 128, 0);
      const uint32_t ck = sb + tid * 32 + ((lane >> 2) << 2), ck2 = ck + (wg ? 0 : 16384);
      uint32_t bad = 0;
      auto tile = [&](int i, uint32_t so) {
        const uint32_t al = (uint32_t)da0 + wg * 64 + (so >> 4), wl = (uint32_t)dw0 + i * 640 - (i >> 1) * (1278 << 16);
        wg_fence();
        #pragma unroll
        for (int s = 0; s < 5; s++) wg_ss80_tb(oc, desc2(al + s * 256, da0 >> 32), desc2(wl + s * 128, dw0 >> 32), (i | s) != 0);
        wg_commit();
        bad |= (lds32(ck + so) ^ epoch) | (lds32(ck + so + 8192) ^ epoch) | (lds32(ck2 + so) ^ epoch);
      };
      if (w4 == 0) {
        if (EN_SSM) mbar_wait(BAR(BR_Y), 0);
        mbar_wait(BAR(BR_WO), 0);
        mbar_wait(BAR(BR_WO + 1), 0);
      }
      bar_sync(1, 256);
      if (tid == 0) TS(9);
      tile(0, SLOT(0));
      #pragma unroll 1
      for (int i = 1; i < 8; i++) {
        mbar_wait(BAR(BR_OFULL) + 8 * i, 0);
        tile(i, SLOT(i));
        wg_wait<1>();
        if (lane == 0) mbar_arrive(BAR(BR_OEMPTY - 1) + 8 * i);
      }
      #pragma unroll 1
      for (int n = 0; n < 56; n++) {
        const int i = n & 7;
        if (i == 0) {
          uint32_t any;
          asm volatile("{\n.reg .pred p;\nsetp.ne.u32 p, %1, 0;\nbarrier.red.or.pred p, 1, 256, p;\nselp.u32 %0, 1, 0, p;\n}" : "=r"(any) : "r"(bad & 1u) : "memory");
          if (!any) break;
          bad = 0;
          FIXCNT
        }
        wg_wait<0>();
        bar_sync(1, 256);
        if (tid == 0) { mbar_expect_tx(BAR(BR_RETRY), 20480); bulk_ld(sb + SLOT(5), &g_o[(r * 8 + CHUNK(i)) * 1280], 20480, BAR(BR_RETRY)); }
        mbar_wait(BAR(BR_RETRY), n & 1);
        tile(i, SLOT(5));
      }
      wg_wait<0>();
      pin<40>(oc);
    }
    if (tid == 0) TS(10);
    {
      const int row = w4 * 16 + (lane & 15);
      const uint32_t ob = sb + OFF_BLK + 3 * BLK + wg * 10240;
      #pragma unroll
      for (int j = 0; j < 8; j += 2)
        stsm4(ob + row * 128 + (((j + (lane >> 4)) ^ (row & 7)) << 4), pack2(oc[4 * j], oc[4 * j + 1]), pack2(oc[4 * j + 2], oc[4 * j + 3]),
              pack2(oc[4 * j + 4], oc[4 * j + 5]), pack2(oc[4 * j + 6], oc[4 * j + 7]));
      stsm4(ob + 8192 + row * 32 + (lane >> 4) * 16, pack2(oc[32], oc[33]), pack2(oc[34], oc[35]), pack2(oc[36], oc[37]), pack2(oc[38], oc[39]));
      fence_async();
      bar_sync(2 + wg, 128);
      if (w4 == 0 && elect_one()) {
        tma2d_st(&prm.m[M_O64], ob, 640 + c * 64, r * 128 + wg * 64);
        tma2d_st(&prm.m[M_O16], ob + 8192, 1152 + c * 16, r * 128 + wg * 64);
        bulk_commit(); bulk_wait0_read();
        if (wg == 0) { TS(11); DUMP(0, 20); }
      }
    }
    }
  } else if (EN_SSM) {
    if (t7 == 0) DUMP(40, 64);
    #pragma unroll 1
    for (int n = 0; n < 64; n++) if (!y_transpose(sb, w4, lane, ytag)) break;
  }
  }
}

typedef CUresult (*EncFn)(CUtensorMap*, CUtensorMapDataType, cuuint32_t, void*, const cuuint64_t*, const cuuint64_t*, const cuuint32_t*,
                          const cuuint32_t*, CUtensorMapInterleave, CUtensorMapSwizzle, CUtensorMapL2promotion, CUtensorMapFloatOOBfill);
static void mkmap(EncFn enc, CUtensorMap* m, const void* base, int rank, const cuuint64_t* dims, const cuuint64_t* strides, const cuuint32_t* box, CUtensorMapSwizzle swz) {
  cuuint32_t es[5] = {1, 1, 1, 1, 1};
  enc(m, CU_TENSOR_MAP_DATA_TYPE_BFLOAT16, rank, const_cast<void*>(base), dims, strides, box, es, CU_TENSOR_MAP_INTERLEAVE_NONE, swz,
      CU_TENSOR_MAP_L2_PROMOTION_L2_128B, CU_TENSOR_MAP_FLOAT_OOB_FILL_NONE);
}

extern "C" void kernel_launch(void* const* d_in, const int* in_sizes, int n_in, void* d_out, int out_size) {
  void* fn = nullptr; cudaDriverEntryPointQueryResult qr;
  cudaGetDriverEntryPoint("cuTensorMapEncodeTiled", &fn, cudaEnableDefault, &qr);
  EncFn enc = (EncFn)fn;
  void* uy = nullptr; cudaGetSymbolAddress(&uy, g_uy);
  const cuuint64_t dx[2] = {640, 2048}, sx[1] = {1280};
  const cuuint32_t bx[2] = {64, 128}, bu[2] = {80, 128};
  const cuuint64_t dw[3] = {640, 640, 3}, sw[2] = {3840, 1280};
  const cuuint32_t br[3] = {16, 32, 3};
  const cuuint64_t dwa[4] = {64, 640, 10, 3}, swa[3] = {3840, 128, 1280}, dwb[4] = {32, 640, 20, 3}, swb[3] = {3840, 64, 1280};
  const cuuint32_t bwa[4] = {64, 32, 1, 3}, bwb[4] = {32, 32, 2, 3};
  const cuuint64_t dwo[2] = {640, 640};
  const cuuint32_t bwo[2] = {64, 80}, bo64[2] = {64, 64}, bo16[2] = {16, 64};
  const cuuint64_t dsa[2] = {2048, 1280}, ssa[1] = {4096};
  const cuuint32_t bsa[2] = {64, 80};
  const cuuint64_t dout[2] = {1280, 2048}, sout[1] = {2560};
  Params prm;
  mkmap(enc, &prm.m[M_X], d_in[7], 2, dx, sx, bx, CU_TENSOR_MAP_SWIZZLE_128B);
  mkmap(enc, &prm.m[M_W128], d_in[8], 4, dwa, swa, bwa, CU_TENSOR_MAP_SWIZZLE_128B);
  mkmap(enc, &prm.m[M_W64], d_in[8], 4, dwb, swb, bwb, CU_TENSOR_MAP_SWIZZLE_64B);
  mkmap(enc, &prm.m[M_WR], d_in[8], 3, dw, sw, br, CU_TENSOR_MAP_SWIZZLE_32B);
  mkmap(enc, &prm.m[M_U], d_in[0], 2, dx, sx, bu, CU_TENSOR_MAP_SWIZZLE_NONE);
  mkmap(enc, &prm.m[M_WO], d_in[9], 2, dwo, sx, bwo, CU_TENSOR_MAP_SWIZZLE_128B);
  mkmap(enc, &prm.m[M_O64], d_out, 2, dout, sout, bo64, CU_TENSOR_MAP_SWIZZLE_128B);
  mkmap(enc, &prm.m[M_O16], d_out, 2, dout, sout, bo16, CU_TENSOR_MAP_SWIZZLE_NONE);
  mkmap(enc, &prm.m[M_SA], uy, 2, dsa, ssa, bsa, CU_TENSOR_MAP_SWIZZLE_128B);
  mkmap(enc, &prm.m[M_OUT], d_out, 2, dout, sout, bu, CU_TENSOR_MAP_SWIZZLE_NONE);
  prm.u = (const __nv_bfloat16*)d_in[0]; prm.wo = (const __nv_bfloat16*)d_in[9];
  for (int i = 0; i < 4; i++) prm.par[i] = (const __nv_bfloat16*)d_in[1 + i];
  prm.logdt = (const __nv_bfloat16*)d_in[5]; prm.dskip = (const __nv_bfloat16*)d_in[6];
  cudaFuncSetAttribute(fused_kernel, cudaFuncAttributeMaxDynamicSharedMemorySize, SMEM_BYTES);
  cudaLaunchConfig_t cfg = {};
  cfg.gridDim = dim3(128); cfg.blockDim = dim3(512); cfg.dynamicSmemBytes = SMEM_BYTES; cfg.stream = cudaStreamPerThread;
  cudaLaunchAttribute at[1];
  at[0].id = cudaLaunchAttributeClusterDimension; at[0].val.clusterDim.x = 2; at[0].val.clusterDim.y = 1; at[0].val.clusterDim.z = 1;
  cfg.attrs = at; cfg.numAttrs = 1;
  cudaLaunchKernelEx(&cfg, fused_kernel, prm);
}
```

```cpp
#include <cuda_runtime.h>
#include <cuda_bf16.h>
#include <cuda_fp16.h>
#include <cuda.h>
#include <stdint.h>

#define EN_ATT 1
#define EN_SSM 1

__device__ __align__(1024) __nv_bfloat16 g_uy[2 * 640 * 2048];
__device__ __align__(128) uint4 g_kvp[8 * 16 * 240];
__device__ __align__(128) uint4 g_o[128 * 1280];
__device__ __align__(128) unsigned g_flag[4 * 128 * 32];
__device__ unsigned g_epoch[128];
#define TS(i) do {} while (0)
#define DUMP(lo, hi) do {} while (0)
#define FIXCNT

constexpr uint32_t SB0 = 1024;
constexpr uint32_t W_SLOT = 15360, OFF_X = 76800;
constexpr uint32_t OFF_WOR = 81920, OFF_KVP = 10240, OFF_KVS = 71680, OFF_PK = 10240, OFF_V = 30720, OFF_EXTRA = 102400, OFF_KVB = OFF_EXTRA;
constexpr uint32_t OFF_BAR = 125952, OFF_BLK = 128000, BLK = 20480;
constexpr uint32_t B_D = 4096, B_D5 = 3088, B_D7 = 6176, B_D9 = 8224, B_TBL = 14400;
constexpr int T_S = 576, T_F2 = 624, T_F3 = 816;
constexpr uint32_t OFF_UT = OFF_BLK + 4 * BLK;
constexpr uint32_t SMEM_BYTES = OFF_BLK + 5 * BLK;
enum { BR_FULL = 0, BR_WO = 5, BR_PUB = 6, BR_KVP = 7, BR_U = 8, BR_U2 = 9, BR_GEMM = 10, BR_UIN = 11, BR_YIN = 12, BR_EPOCH = 13,
       BR_FREE = 14, BR_RETRY = 16, BR_KS = 17, BR_UOUT = 19, BR_OFULL = 19  , BR_EMPTY = 27, BR_OEMPTY = 32, BR_OSTG = 39,
       BR_Y = 40, BR_DRDY = 42, BR_COUNT = 44 };
constexpr uint32_t OFF_EPOCH = OFF_BAR + 8 * BR_COUNT;
enum { M_X, M_W128, M_W64, M_WR, M_U, M_WO, M_O64, M_O16, M_SA, M_OUT, M_COUNT };

__device__ __forceinline__ long long clk64() { long long t; asm volatile("mov.u64 %0, %%clock64;" : "=l"(t) :: "memory"); return t; }
__device__ __forceinline__ uint32_t smem_u32(const void* p) { return (uint32_t)__cvta_generic_to_shared(p); }
__host__ __device__ constexpr uint64_t mkdesc(uint32_t addr, uint32_t lbo, uint32_t sbo, uint32_t swz) {
  return (uint64_t)((addr & 0x3FFFF) >> 4) | ((uint64_t)(lbo >> 4) << 16) | ((uint64_t)(sbo >> 4) << 32) | ((uint64_t)swz << 62);
}
__device__ __forceinline__ uint64_t desc2(uint32_t lo, uint32_t hi) { uint64_t d; asm("mov.b64 %0, {%1, %2};" : "=l"(d) : "r"(lo), "r"(hi)); return d; }
__device__ __forceinline__ void mbar_init(uint32_t bar, uint32_t cnt) { asm volatile("mbarrier.init.shared::cta.b64 [%0], %1;" :: "r"(bar), "r"(cnt) : "memory"); }
__device__ __forceinline__ void mbar_expect_tx(uint32_t bar, uint32_t bytes) { asm volatile("mbarrier.arrive.expect_tx.shared::cta.b64 _, [%0], %1;" :: "r"(bar), "r"(bytes) : "memory"); }
__device__ __forceinline__ void mbar_arrive(uint32_t bar) { asm volatile("mbarrier.arrive.shared::cta.b64 _, [%0];" :: "r"(bar) : "memory"); }
__device__ __forceinline__ void mbar_wait(uint32_t bar, uint32_t parity) {
  asm volatile("{\n.reg .pred p;\n.reg .u32 c;\nmov.u32 c, 0;\n"
    "WL:\nmbarrier.try_wait.parity.shared::cta.b64 p, [%0], %1;\n@p bra WD;\n"
    "add.u32 c, c, 1;\nsetp.lt.u32 p, c, 200000;\n@p bra WL;\nWD:\n}" :: "r"(bar), "r"(parity) : "memory");
}
__device__ __forceinline__ void poll_all(const unsigned* p, unsigned val) {
  asm volatile("{\n.reg .pred p;\n.reg .u32 c, v;\nmov.u32 c, 0;\n"
    "PL:\nld.relaxed.gpu.global.u32 v, [%0];\nsetp.eq.u32 p, v, %1;\nvote.sync.all.pred p, p, 0xffffffff;\n@p bra PD;\n"
    "add.u32 c, c, 1;\nsetp.lt.u32 p, c, 100000;\n@p bra PL;\nPD:\n}" :: "l"(p), "r"(val) : "memory");
}
__device__ __forceinline__ void poll_all_acq(const unsigned* p, unsigned val) {
  asm volatile("{\n.reg .pred p;\n.reg .u32 c, v;\nmov.u32 c, 0;\n"
    "PL:\nld.acquire.gpu.global.u32 v, [%0];\nsetp.eq.u32 p, v, %1;\nvote.sync.all.pred p, p, 0xffffffff;\n@p bra PD;\n"
    "nanosleep.u32 300;\nadd.u32 c, c, 1;\nsetp.lt.u32 p, c, 100000;\n@p bra PL;\nPD:\n}" :: "l"(p), "r"(val) : "memory");
}
__device__ __forceinline__ unsigned poll_bit(const unsigned* p, unsigned val, unsigned mask) {
  unsigned bal;
  asm volatile("{\n.reg .pred p;\n.reg .u32 c, v;\nmov.u32 c, 0;\n"
    "PL:\nld.relaxed.gpu.global.u32 v, [%1];\nsetp.eq.u32 p, v, %2;\nvote.sync.ballot.b32 %0, p, 0xffffffff;\n"
    "and.b32 v, %0, %3;\nsetp.ne.u32 p, v, 0;\n@p bra PD;\n"
    "add.u32 c, c, 1;\nsetp.lt.u32 p, c, 100000;\n@p bra PL;\nPD:\n}" : "=&r"(bal) : "l"(p), "r"(val), "r"(mask) : "memory");
  return bal;
}
__device__ __forceinline__ void fix128_w3(uint32_t* v, const void* p, uint32_t tag, uint32_t mask) {
  asm volatile("{\n.reg .pred p;\n.reg .u32 c, x;\n.reg .b128 t;\n.reg .b64 lo, hi;\nmov.u32 c, 0;\n"
    "FL:\nxor.b32 x, %3, %5;\nand.b32 x, x, %6;\nsetp.eq.u32 p, x, 0;\n@p bra FD;\n"
    "ld.relaxed.gpu.global.b128 t, [%4];\nmov.b128 {lo, hi}, t;\nmov.b64 {%0, %1}, lo;\nmov.b64 {%2, %3}, hi;\n"
    "add.u32 c, c, 1;\nsetp.lt.u32 p, c, 100000;\n@p bra FL;\nFD:\n}"
    : "+r"(v[0]), "+r"(v[1]), "+r"(v[2]), "+r"(v[3]) : "l"(p), "r"(tag), "r"(mask) : "memory");
}
__device__ __forceinline__ bool elect_one() {
  uint32_t p; asm volatile("{\n.reg .pred P;\nelect.sync _|P, 0xffffffff;\nselp.u32 %0, 1, 0, P;\n}" : "=r"(p)); return p;
}
__device__ __forceinline__ void bar_sync(int id, int n) { asm volatile("bar.sync %0, %1;" :: "r"(id), "r"(n) : "memory"); }
__device__ __forceinline__ void fence_async() { asm volatile("fence.proxy.async.shared::cta;" ::: "memory"); }
__device__ __forceinline__ void fence_async_g() { asm volatile("fence.proxy.async.global;" ::: "memory"); }
__device__ __forceinline__ void tma2d(uint32_t dst, const CUtensorMap* m, uint32_t bar, int c0, int c1) {
  asm volatile("cp.async.bulk.tensor.2d.shared::cluster.global.mbarrier::complete_tx::bytes [%0], [%1, {%3, %4}], [%2];"
    :: "r"(dst), "l"(m), "r"(bar), "r"(c0), "r"(c1) : "memory");
}
__device__ __forceinline__ void tma3d(uint32_t dst, const CUtensorMap* m, uint32_t bar, int c0, int c1, int c2) {
  asm volatile("cp.async.bulk.tensor.3d.shared::cluster.global.mbarrier::complete_tx::bytes [%0], [%1, {%3, %4, %5}], [%2];"
    :: "r"(dst), "l"(m), "r"(bar), "r"(c0), "r"(c1), "r"(c2) : "memory");
}
__device__ __forceinline__ void tma4d(uint32_t dst, const CUtensorMap* m, uint32_t bar, int c0, int c1, int c2, int c3) {
  asm volatile("cp.async.bulk.tensor.4d.shared::cluster.global.mbarrier::complete_tx::bytes [%0], [%1, {%3, %4, %5, %6}], [%2];"
    :: "r"(dst), "l"(m), "r"(bar), "r"(c0), "r"(c1), "r"(c2), "r"(c3) : "memory");
}
__device__ __forceinline__ void tma2d_st(const CUtensorMap* m, uint32_t src, int c0, int c1) {
  asm volatile("cp.async.bulk.tensor.2d.global.shared::cta.bulk_group [%0, {%2, %3}], [%1];"
    :: "l"(m), "r"(src), "r"(c0), "r"(c1) : "memory");
}
__device__ __forceinline__ void bulk_ld(uint32_t dst, const void* src, uint32_t bytes, uint32_t bar) {
  asm volatile("cp.async.bulk.shared::cluster.global.mbarrier::complete_tx::bytes [%0], [%1], %2, [%3];"
    :: "r"(dst), "l"(src), "r"(bytes), "r"(bar) : "memory");
}
__device__ __forceinline__ void bulk_st(void* dst, uint32_t src, uint32_t bytes) {
  asm volatile("cp.async.bulk.global.shared::cta.bulk_group [%0], [%1], %2;" :: "l"(dst), "r"(src), "r"(bytes) : "memory");
}
__device__ __forceinline__ void bulk_commit() { asm volatile("cp.async.bulk.commit_group;" ::: "memory"); }
__device__ __forceinline__ void bulk_wait0() { asm volatile("cp.async.bulk.wait_group 0;" ::: "memory"); }
__device__ __forceinline__ void bulk_wait0_read() { asm volatile("cp.async.bulk.wait_group.read 0;" ::: "memory"); }
__device__ __forceinline__ unsigned ld_rlx(const unsigned* p) { unsigned v; asm volatile("ld.relaxed.gpu.global.u32 %0, [%1];" : "=r"(v) : "l"(p) : "memory"); return v; }
__device__ __forceinline__ unsigned ld_acq(const unsigned* p) { unsigned v; asm volatile("ld.acquire.gpu.global.u32 %0, [%1];" : "=r"(v) : "l"(p) : "memory"); return v; }
__device__ __forceinline__ void st_rlx(unsigned* p, unsigned v) { asm volatile("st.relaxed.gpu.global.u32 [%0], %1;" :: "l"(p), "r"(v) : "memory"); }
__device__ __forceinline__ void st_rel(unsigned* p, unsigned v) { asm volatile("st.release.gpu.global.u32 [%0], %1;" :: "l"(p), "r"(v) : "memory"); }
__device__ __forceinline__ void st128_rlx(void* p, const uint32_t* v) {
  asm volatile("{\n.reg .b128 t;\n.reg .b64 lo, hi;\nmov.b64 lo, {%1, %2};\nmov.b64 hi, {%3, %4};\nmov.b128 t, {lo, hi};\n"
    "st.relaxed.gpu.global.b128 [%0], t;\n}" :: "l"(p), "r"(v[0]), "r"(v[1]), "r"(v[2]), "r"(v[3]) : "memory");
}
__device__ __forceinline__ uint32_t lds32(uint32_t a) { uint32_t v; asm volatile("ld.shared.u32 %0, [%1];" : "=r"(v) : "r"(a) : "memory"); return v; }
__device__ __forceinline__ uint32_t lds32v(uint32_t a) { uint32_t v; asm volatile("ld.volatile.shared.u32 %0, [%1];" : "=r"(v) : "r"(a) : "memory"); return v; }
__device__ __forceinline__ void lds128(uint32_t* v, uint32_t a) { asm volatile("ld.shared.v4.u32 {%0,%1,%2,%3}, [%4];" : "=r"(v[0]), "=r"(v[1]), "=r"(v[2]), "=r"(v[3]) : "r"(a) : "memory"); }
__device__ __forceinline__ void sts32(uint32_t a, uint32_t v) { asm volatile("st.shared.u32 [%0], %1;" :: "r"(a), "r"(v) : "memory"); }
__device__ __forceinline__ void sts16(uint32_t a, uint32_t v) { asm volatile("st.shared.u16 [%0], %1;" :: "r"(a), "h"((uint16_t)v) : "memory"); }
__device__ __forceinline__ void sts64f(uint32_t a, float x, float y) { asm volatile("st.shared.v2.f32 [%0], {%1,%2};" :: "r"(a), "f"(x), "f"(y) : "memory"); }
__device__ __forceinline__ void sts128(uint32_t a, uint32_t x, uint32_t y, uint32_t z, uint32_t w) { asm volatile("st.shared.v4.u32 [%0], {%1,%2,%3,%4};" :: "r"(a), "r"(x), "r"(y), "r"(z), "r"(w) : "memory"); }
__device__ __forceinline__ void stsm4(uint32_t a, uint32_t r0, uint32_t r1, uint32_t r2, uint32_t r3) {
  asm volatile("stmatrix.sync.aligned.m8n8.x4.shared.b16 [%0], {%1,%2,%3,%4};" :: "r"(a), "r"(r0), "r"(r1), "r"(r2), "r"(r3) : "memory");
}
__device__ __forceinline__ void stsm4t(uint32_t a, uint32_t r0, uint32_t r1, uint32_t r2, uint32_t r3) {
  asm volatile("stmatrix.sync.aligned.m8n8.x4.trans.shared.b16 [%0], {%1,%2,%3,%4};" :: "r"(a), "r"(r0), "r"(r1), "r"(r2), "r"(r3) : "memory");
}
__device__ __forceinline__ void ldsm4t(uint32_t* r, uint32_t a) {
  asm volatile("ldmatrix.sync.aligned.m8n8.x4.trans.shared.b16 {%0,%1,%2,%3}, [%4];" : "=r"(r[0]), "=r"(r[1]), "=r"(r[2]), "=r"(r[3]) : "r"(a) : "memory");
}
__device__ __forceinline__ void ldsm4(uint32_t* r, uint32_t a) {
  asm volatile("ldmatrix.sync.aligned.m8n8.x4.shared.b16 {%0,%1,%2,%3}, [%4];" : "=r"(r[0]), "=r"(r[1]), "=r"(r[2]), "=r"(r[3]) : "r"(a) : "memory");
}
__device__ __forceinline__ void mma16816(float* d, const uint32_t* a, const uint32_t* b) {
  asm volatile("mma.sync.aligned.m16n8k16.row.col.f32.bf16.bf16.f32 {%0,%1,%2,%3}, {%4,%5,%6,%7}, {%8,%9}, {%0,%1,%2,%3};"
    : "+f"(d[0]), "+f"(d[1]), "+f"(d[2]), "+f"(d[3]) : "r"(a[0]), "r"(a[1]), "r"(a[2]), "r"(a[3]), "r"(b[0]), "r"(b[1]));
}
__device__ __forceinline__ uint32_t pack2(float lo, float hi) { uint32_t r; asm("cvt.rn.bf16x2.f32 %0, %1, %2;" : "=r"(r) : "f"(hi), "f"(lo)); return r; }
__device__ __forceinline__ uint32_t packh(float lo, float hi) { uint32_t r; asm("cvt.rn.f16x2.f32 %0, %1, %2;" : "=r"(r) : "f"(hi), "f"(lo)); return r; }
__device__ __forceinline__ void hcm2(uint32_t xr, uint32_t xi, uint32_t z, uint32_t& pr, uint32_t& pi) {
  const __half2 a = *reinterpret_cast<__half2*>(&xr), b = *reinterpret_cast<__half2*>(&xi), zz = *reinterpret_cast<__half2*>(&z);
  const __half2 re = __hfma2(__hneg2(b), __high2half2(zz), __hmul2(a, __low2half2(zz)));
  const __half2 im = __hfma2(a, __high2half2(zz), __hmul2(b, __low2half2(zz)));
  pr = *reinterpret_cast<const uint32_t*>(&re); pi = *reinterpret_cast<const uint32_t*>(&im);
}
__device__ __forceinline__ void lds64(uint32_t* v, uint32_t a) { asm volatile("ld.shared.v2.u32 {%0,%1}, [%2];" : "=r"(v[0]), "=r"(v[1]) : "r"(a) : "memory"); }
__device__ __forceinline__ float bf_lo(uint32_t v) { return __uint_as_float(v << 16); }
__device__ __forceinline__ float bf_hi(uint32_t v) { return __uint_as_float(v & 0xffff0000u); }
__device__ __forceinline__ float bf_round(float x) { return bf_lo(pack2(x, 0.f)); }
__device__ __forceinline__ float ex2(float x) { float r; asm("ex2.approx.ftz.f32 %0, %1;" : "=f"(r) : "f"(x)); return r; }
__device__ __forceinline__ float phi(float t, float l2e = 1.44269504089f) {
  float e = ex2(t * l2e) + 1e-6f;
  asm("{\n.reg .pred p;\nsetp.gt.f32 p, %1, 0f00000000;\n@p add.f32 %0, %1, 0f3F800008;\n}" : "+f"(e) : "f"(t));
  return e;
}
__device__ __forceinline__ void wg_fence() { asm volatile("wgmma.fence.sync.aligned;" ::: "memory"); }
__device__ __forceinline__ void wg_commit() { asm volatile("wgmma.commit_group.sync.aligned;" ::: "memory"); }
template <int N> __device__ __forceinline__ void wg_wait() { asm volatile("wgmma.wait_group.sync.aligned %0;" :: "n"(N) : "memory"); }
template <int N> __device__ __forceinline__ void pin(float* a) {
  #pragma unroll
  for (int i = 0; i < N; i++) asm volatile("" : "+f"(a[i]) :: "memory");
}
__device__ __forceinline__ int rtid() { int t; asm volatile("mov.u32 %0, %%tid.x;" : "=r"(t)); return t; }
template <int N> __device__ __forceinline__ void zero(float* a) {
  #pragma unroll
  for (int i = 0; i < N; i++) asm volatile("mov.b32 %0, 0;" : "=f"(a[i]));
}
__device__ __forceinline__ void cexp_t(float lg2mag, float turns, float& re, float& im) {
  float m = ex2(lg2mag);
  float fr = (turns - __fadd_rn(__fadd_rn(turns, 12582912.f), -12582912.f)) * 6.283185307f;
  re = m * __cosf(fr); im = m * __sinf(fr);
}
__device__ __forceinline__ void cmul(float ar, float ai, float br, float bi, float& cr, float& ci) {
  cr = fmaf(ar, br, -ai * bi); ci = fmaf(ar, bi, ai * br);
}

__device__ __forceinline__ void wg_ss48_tt(float* d, uint64_t da, uint64_t db, int scale_d) {
  asm volatile("{\n.reg .pred p;\nsetp.ne.b32 p, %26, 0;\n"
    "wgmma.mma_async.sync.aligned.m64n48k16.f32.bf16.bf16 "
    "{%0, %1, %2, %3, %4, %5, %6, %7, %8, %9, %10, %11, %12, %13, %14, %15, %16, %17, %18, %19, %20, %21, %22, %23}, %24, %25, p, 1, 1, 1, 1;\n}\n"
    : "+f"(d[0]), "+f"(d[1]), "+f"(d[2]), "+f"(d[3]), "+f"(d[4]), "+f"(d[5]), "+f"(d[6]), "+f"(d[7]), "+f"(d[8]), "+f"(d[9]), "+f"(d[10]), "+f"(d[11]), "+f"(d[12]), "+f"(d[13]), "+f"(d[14]), "+f"(d[15]), "+f"(d[16]), "+f"(d[17]), "+f"(d[18]), "+f"(d[19]), "+f"(d[20]), "+f"(d[21]), "+f"(d[22]), "+f"(d[23])
    : "l"(da), "l"(db), "r"(scale_d));
}
__device__ __forceinline__ void wg_rs88_tb(float* d, const uint32_t* a, uint64_t db, int scale_d) {
  asm volatile("{\n.reg .pred p;\nsetp.ne.b32 p, %49, 0;\n"
    "wgmma.mma_async.sync.aligned.m64n88k16.f32.bf16.bf16 "
    "{%0, %1, %2, %3, %4, %5, %6, %7, %8, %9, %10, %11, %12, %13, %14, %15, %16, %17, %18, %19, %20, %21, %22, %23, %24, %25, %26, %27, %28, %29, %30, %31, %32, %33, %34, %35, %36, %37, %38, %39, %40, %41, %42, %43}, {%44, %45, %46, %47}, %48, p, 1, 1, 1;\n}\n"
    : "+f"(d[0]), "+f"(d[1]), "+f"(d[2]), "+f"(d[3]), "+f"(d[4]), "+f"(d[5]), "+f"(d[6]), "+f"(d[7]), "+f"(d[8]), "+f"(d[9]), "+f"(d[10]), "+f"(d[11]), "+f"(d[12]), "+f"(d[13]), "+f"(d[14]), "+f"(d[15]), "+f"(d[16]), "+f"(d[17]), "+f"(d[18]), "+f"(d[19]), "+f"(d[20]), "+f"(d[21]), "+f"(d[22]), "+f"(d[23]), "+f"(d[24]), "+f"(d[25]), "+f"(d[26]), "+f"(d[27]), "+f"(d[28]), "+f"(d[29]), "+f"(d[30]), "+f"(d[31]), "+f"(d[32]), "+f"(d[33]), "+f"(d[34]), "+f"(d[35]), "+f"(d[36]), "+f"(d[37]), "+f"(d[38]), "+f"(d[39]), "+f"(d[40]), "+f"(d[41]), "+f"(d[42]), "+f"(d[43])
    : "r"(a[0]), "r"(a[1]), "r"(a[2]), "r"(a[3]), "l"(db), "r"(scale_d));
}
__device__ __forceinline__ void wg_ss80_tb(float* d, uint64_t da, uint64_t db, int scale_d) {
  asm volatile("{\n.reg .pred p;\nsetp.ne.b32 p, %42, 0;\n"
    "wgmma.mma_async.sync.aligned.m64n80k16.f32.bf16.bf16 "
    "{%0, %1, %2, %3, %4, %5, %6, %7, %8, %9, %10, %11, %12, %13, %14, %15, %16, %17, %18, %19, %20, %21, %22, %23, %24, %25, %26, %27, %28, %29, %30, %31, %32, %33, %34, %35, %36, %37, %38, %39}, %40, %41, p, 1, 1, 0, 1;\n}\n"
    : "+f"(d[0]), "+f"(d[1]), "+f"(d[2]), "+f"(d[3]), "+f"(d[4]), "+f"(d[5]), "+f"(d[6]), "+f"(d[7]), "+f"(d[8]), "+f"(d[9]), "+f"(d[10]), "+f"(d[11]), "+f"(d[12]), "+f"(d[13]), "+f"(d[14]), "+f"(d[15]), "+f"(d[16]), "+f"(d[17]), "+f"(d[18]), "+f"(d[19]), "+f"(d[20]), "+f"(d[21]), "+f"(d[22]), "+f"(d[23]), "+f"(d[24]), "+f"(d[25]), "+f"(d[26]), "+f"(d[27]), "+f"(d[28]), "+f"(d[29]), "+f"(d[30]), "+f"(d[31]), "+f"(d[32]), "+f"(d[33]), "+f"(d[34]), "+f"(d[35]), "+f"(d[36]), "+f"(d[37]), "+f"(d[38]), "+f"(d[39])
    : "l"(da), "l"(db), "r"(scale_d));
}
__device__ __forceinline__ void wg_ss48_tt_h(float* d, uint64_t da, uint64_t db, int scale_d) {
  asm volatile("{\n.reg .pred p;\nsetp.ne.b32 p, %26, 0;\n"
    "wgmma.mma_async.sync.aligned.m64n48k16.f32.f16.f16 "
    "{%0, %1, %2, %3, %4, %5, %6, %7, %8, %9, %10, %11, %12, %13, %14, %15, %16, %17, %18, %19, %20, %21, %22, %23}, %24, %25, p, 1, 1, 1, 1;\n}\n"
    : "+f"(d[0]), "+f"(d[1]), "+f"(d[2]), "+f"(d[3]), "+f"(d[4]), "+f"(d[5]), "+f"(d[6]), "+f"(d[7]), "+f"(d[8]), "+f"(d[9]), "+f"(d[10]), "+f"(d[11]), "+f"(d[12]), "+f"(d[13]), "+f"(d[14]), "+f"(d[15]), "+f"(d[16]), "+f"(d[17]), "+f"(d[18]), "+f"(d[19]), "+f"(d[20]), "+f"(d[21]), "+f"(d[22]), "+f"(d[23])
    : "l"(da), "l"(db), "r"(scale_d));
}
__device__ __forceinline__ void wg_rs192_tb(float* d, const uint32_t* a, uint64_t db, int scale_d) {
  asm volatile("{\n.reg .pred p;\nsetp.ne.b32 p, %101, 0;\n"
    "wgmma.mma_async.sync.aligned.m64n192k16.f32.bf16.bf16 "
    "{%0, %1, %2, %3, %4, %5, %6, %7, %8, %9, %10, %11, %12, %13, %14, %15, %16, %17, %18, %19, %20, %21, %22, %23, %24, %25, %26, %27, %28, %29, %30, %31, %32, %33, %34, %35, %36, %37, %38, %39, %40, %41, %42, %43, %44, %45, %46, %47, %48, %49, %50, %51, %52, %53, %54, %55, %56, %57, %58, %59, %60, %61, %62, %63, %64, %65, %66, %67, %68, %69, %70, %71, %72, %73, %74, %75, %76, %77, %78, %79, %80, %81, %82, %83, %84, %85, %86, %87, %88, %89, %90, %91, %92, %93, %94, %95}, {%96, %97, %98, %99}, %100, p, 1, 1, 1;\n}\n"
    : "+f"(d[0]), "+f"(d[1]), "+f"(d[2]), "+f"(d[3]), "+f"(d[4]), "+f"(d[5]), "+f"(d[6]), "+f"(d[7]), "+f"(d[8]), "+f"(d[9]), "+f"(d[10]), "+f"(d[11]), "+f"(d[12]), "+f"(d[13]), "+f"(d[14]), "+f"(d[15]), "+f"(d[16]), "+f"(d[17]), "+f"(d[18]), "+f"(d[19]), "+f"(d[20]), "+f"(d[21]), "+f"(d[22]), "+f"(d[23]), "+f"(d[24]), "+f"(d[25]), "+f"(d[26]), "+f"(d[27]), "+f"(d[28]), "+f"(d[29]), "+f"(d[30]), "+f"(d[31]), "+f"(d[32]), "+f"(d[33]), "+f"(d[34]), "+f"(d[35]), "+f"(d[36]), "+f"(d[37]), "+f"(d[38]), "+f"(d[39]), "+f"(d[40]), "+f"(d[41]), "+f"(d[42]), "+f"(d[43]), "+f"(d[44]), "+f"(d[45]), "+f"(d[46]), "+f"(d[47]), "+f"(d[48]), "+f"(d[49]), "+f"(d[50]), "+f"(d[51]), "+f"(d[52]), "+f"(d[53]), "+f"(d[54]), "+f"(d[55]), "+f"(d[56]), "+f"(d[57]), "+f"(d[58]), "+f"(d[59]), "+f"(d[60]), "+f"(d[61]), "+f"(d[62]), "+f"(d[63]), "+f"(d[64]), "+f"(d[65]), "+f"(d[66]), "+f"(d[67]), "+f"(d[68]), "+f"(d[69]), "+f"(d[70]), "+f"(d[71]), "+f"(d[72]), "+f"(d[73]), "+f"(d[74]), "+f"(d[75]), "+f"(d[76]), "+f"(d[77]), "+f"(d[78]), "+f"(d[79]), "+f"(d[80]), "+f"(d[81]), "+f"(d[82]), "+f"(d[83]), "+f"(d[84]), "+f"(d[85]), "+f"(d[86]), "+f"(d[87]), "+f"(d[88]), "+f"(d[89]), "+f"(d[90]), "+f"(d[91]), "+f"(d[92]), "+f"(d[93]), "+f"(d[94]), "+f"(d[95])
    : "r"(a[0]), "r"(a[1]), "r"(a[2]), "r"(a[3]), "l"(db), "r"(scale_d));
}
__device__ __forceinline__ void wg_rs48_tb(float* d, const uint32_t* a, uint64_t db, int scale_d) {
  asm volatile("{\n.reg .pred p;\nsetp.ne.b32 p, %29, 0;\n"
    "wgmma.mma_async.sync.aligned.m64n48k16.f32.bf16.bf16 "
    "{%0, %1, %2, %3, %4, %5, %6, %7, %8, %9, %10, %11, %12, %13, %14, %15, %16, %17, %18, %19, %20, %21, %22, %23}, {%24, %25, %26, %27}, %28, p, 1, 1, 1;\n}\n"
    : "+f"(d[0]), "+f"(d[1]), "+f"(d[2]), "+f"(d[3]), "+f"(d[4]), "+f"(d[5]), "+f"(d[6]), "+f"(d[7]), "+f"(d[8]), "+f"(d[9]), "+f"(d[10]), "+f"(d[11]), "+f"(d[12]), "+f"(d[13]), "+f"(d[14]), "+f"(d[15]), "+f"(d[16]), "+f"(d[17]), "+f"(d[18]), "+f"(d[19]), "+f"(d[20]), "+f"(d[21]), "+f"(d[22]), "+f"(d[23])
    : "r"(a[0]), "r"(a[1]), "r"(a[2]), "r"(a[3]), "l"(db), "r"(scale_d));
}

struct Params {
  const __nv_bfloat16 *par[4], *logdt, *dskip, *u, *wo;
  CUtensorMap m[M_COUNT];
};

#define CHUNK(i) ((i) == 0 ? c : ((i) == 7 ? (c ^ 1) : (((c & 6) + 1 + (i)) & 7)))
#define FLAG(kind, rr, cc) (&g_flag[((kind) * 128 + (rr) * 8 + (cc)) * 32])
#define SLOT(i) ((i) == 0 ? OFF_EXTRA : OFF_BLK - 256 + ((i) > 5 ? (i) - 6 : (i) - 1) * BLK)
__device__ __forceinline__ void load_quad(uint32_t* A, uint32_t addr) {
  A[0] = lds32v(addr); A[1] = lds32v(addr + 32); A[2] = lds32v(addr - 32); A[3] = lds32v(addr);
}

__device__ __forceinline__ bool y_transpose(uint32_t sb, int w5, int lane, uint32_t ytag) {
  const int mi = lane >> 3, rw = lane & 7;
  const uint32_t sa = sb + OFF_EXTRA + (w5 * 16 + rw) * 128 + ((mi ^ rw) << 4), da = sb + SLOT(3) + (8 * mi + rw) * 160 + w5 * 32;
  const uint32_t ym = lane < 4 ? 0x10001u : 0u;
  bar_sync(7, 160);
  uint32_t v[8][4], bad = 0;
  #pragma unroll
  for (int q = 0; q < 8; q++) ldsm4t(v[q], (sa ^ ((q & 1) * 64 + ((q >> 1) & 1) * 16)) + ((q >> 1) & 1) * 10240 + (q >> 2) * 1024);
  #pragma unroll
  for (int q = 0; q < 8; q++) {
    bad |= (v[q][0] ^ ytag) | (v[q][2] ^ ytag);
    stsm4(da + (q & 3) * 5120 + (q >> 2) * 16, v[q][0] & ~ym, v[q][1], v[q][2] & ~ym, v[q][3]);
  }
  fence_async();
  uint32_t any;
  asm volatile("{\n.reg .pred p;\nsetp.ne.u32 p, %1, 0;\nbarrier.red.or.pred p, 7, 160, p;\nselp.u32 %0, 1, 0, p;\n}" : "=r"(any) : "r"(bad & ym) : "memory");
  return any;
}

__global__ void __launch_bounds__(512, 1) fused_kernel(const __grid_constant__ Params prm) {
  extern __shared__ unsigned char smem_raw[];
  uint32_t raw[5][2], pd;
  if ((threadIdx.x >> 7) == 2) {
    const int ch = (blockIdx.x & 7) * 80 + (blockIdx.x >> 3) * 5, od = threadIdx.x & 1;
    #pragma unroll
    for (int e = 0; e < 2; e++) {
      const __nv_bfloat16* pp = prm.par[2 * e + od] + ch * 128 + (threadIdx.x & 126);
      #pragma unroll
      for (int q = 0; q < 5; q++) asm volatile("ld.global.nc.u32 %0, [%1];" : "=r"(raw[q][e]) : "l"(pp + q * 128));
    }
    asm volatile("ld.global.nc.u16 %0, [%1];" : "=r"(pd) : "l"(((threadIdx.x & 8) ? prm.dskip : prm.logdt) + ch + min(threadIdx.x & 7, 4)));
  }
  const uint32_t sb = __shfl_sync(0xffffffff, smem_u32(smem_raw), 0);
  const int tid = threadIdx.x, lane = tid & 31;
  const int warp = __shfl_sync(0xffffffff, tid >> 5, 0), wg = warp >> 2, w4 = warp & 3;
  const int cta = blockIdx.x, r = cta >> 3, c = cta & 7;
  if ((sb & 0xffffffu) != SB0) return;
#define BAR(i) (sb + OFF_BAR + 8 * (i))
  const bool sw64 = ((c + 1) & 2) != 0;

  const CUtensorMap* mwp = &prm.m[sw64 ? M_W64 : M_W128];
  const int mcol = (c * 80 + (c & 1) * 16) >> (sw64 ? 5 : 6), rcol = c * 80 + ((c & 1) ? 0 : 64);
  if (warp == 12 && elect_one()) {
    #pragma unroll
    for (int i = 0; i < 5; i++) mbar_init(BAR(BR_FULL + i), 1);
    asm volatile("fence.mbarrier_init.release.cluster;" ::: "memory");
    if (EN_ATT) {
      mbar_expect_tx(BAR(BR_FULL), W_SLOT + 16384);
      tma4d(sb, mwp, BAR(BR_FULL), 0, 0, mcol, 0);
      tma2d(sb + OFF_X, &prm.m[M_X], BAR(BR_FULL), 0, r * 128);
      tma3d(sb + 12288, &prm.m[M_WR], BAR(BR_FULL), rcol, 0, 0);
      mbar_expect_tx(BAR(BR_FULL + 1), W_SLOT);
      tma4d(sb + W_SLOT, mwp, BAR(BR_FULL + 1), 0, 32, mcol, 0);
      tma3d(sb + W_SLOT + 12288, &prm.m[M_WR], BAR(BR_FULL + 1), rcol, 32, 0);
      TS(24);
    }
  }
  if (warp == 13 && elect_one()) {
    asm volatile("prefetch.tensormap [%0];" :: "l"(&prm.m[M_X]) : "memory");
    asm volatile("prefetch.tensormap [%0];" :: "l"(&prm.m[M_WR]) : "memory");
  }
  if (wg == 3) {
    asm volatile("setmaxnreg.dec.sync.aligned.u32 56;");
    const int tid = rtid(), lane = tid & 31;
    if (warp == 12) {
      asm volatile("bar.arrive 0, 512;" ::: "memory");
      {
        uint32_t s = 2, ph = 1, xs = 16384;
        #pragma unroll 1
        for (int kb = 2; kb < 20; kb++) {
          if (kb == 4) bar_sync(6, 128);
          if (kb >= 5) mbar_wait(BAR(BR_EMPTY) + 8 * s, ph);
          if (EN_ATT && elect_one()) {
            const uint32_t st = sb + s * W_SLOT, fb = BAR(BR_FULL) + 8 * s;
            mbar_expect_tx(fb, (kb & 1) ? W_SLOT : W_SLOT + 16384);
            if (!(kb & 1)) tma2d(sb + OFF_X + xs, &prm.m[M_X], fb, kb * 32, r * 128);
            tma4d(st, mwp, fb, 0, kb * 32, mcol, 0);
            tma3d(st + 12288, &prm.m[M_WR], fb, rcol, kb * 32, 0);
          }
          if (kb < 4 && lane == 0) TS(24 + kb);
          if (EN_SSM && kb == 4 && elect_one()) { mbar_expect_tx(BAR(BR_UIN), 20480); tma2d(sb + OFF_UT, &prm.m[M_U], BAR(BR_UIN), c * 80, r * 128); }
          if (kb == 14 && elect_one()) asm volatile("cp.async.bulk.prefetch.L2.global [%0], 6400;" :: "l"(prm.wo + cta * 3200) : "memory");
          if (!EN_ATT && kb == 4) break;
          if (++s == 5) { s = 0; ph ^= 1; }
          if (kb & 1) { xs += 16384; if (xs == 49152) xs = 0; }
        }
      }
      if (EN_ATT) {
      mbar_wait(BAR(BR_EPOCH), 0);
      const unsigned epoch = lds32(sb + OFF_EPOCH);
      const unsigned* fo = FLAG(3, r, lane & 7);
      unsigned seen = __ballot_sync(0xffffffff, ld_rlx(lane < 16 ? fo : FLAG(0, lane & 15, c)) == epoch) & 0xffu;
      mbar_wait(BAR(BR_GEMM), 0);
      if (elect_one()) {
        mbar_expect_tx(BAR(BR_WO), 8 * 10240);
        mbar_expect_tx(BAR(BR_KVP), 61440);
      }
      {
        uint32_t ds = sb + OFF_WOR + (lane >> 3) * 128 + (((lane & 7) ^ (lane >> 3)) << 4);
        #pragma unroll 1
        for (int h = 0; h < 2; h++) {
          const int i = (lane & 6) + h;
          const char* gs = reinterpret_cast<const char*>(prm.wo) + (size_t)((lane >> 3) + CHUNK(i) * 80) * 1280 + 1024 + c * 32 + (lane & 1) * 16;
          #pragma unroll 2
          for (int q = 0; q < 20; q++) {
            asm volatile("cp.async.cg.shared.global [%0], [%1], 16;" :: "r"(ds), "l"(gs) : "memory");
            ds = (ds + 512) ^ 64; gs += 5120;
          }
        }
      }
      mbar_wait(BAR(BR_PUB), 0);
      poll_all(FLAG(0, lane & 15, c), epoch);
      if (elect_one()) { TS(23); bulk_ld(sb + OFF_KVP, &g_kvp[c * 16 * 240], 61440, BAR(BR_KVP)); }
      asm volatile("cp.async.wait_all;" ::: "memory");
      fence_async();
      mbar_arrive(BAR(BR_WO));
      mbar_wait(BAR(BR_OSTG), 0);
      if (elect_one()) {
        bulk_st(&g_o[cta * 1280], sb + OFF_EXTRA, 20480);
        bulk_commit();
        bulk_wait0();
        st_rlx(FLAG(3, r, c), epoch);
        mbar_arrive(BAR(BR_OEMPTY));
        TS(20);
        #pragma unroll 1
        for (int i = 0; i < 8; i++) tma2d(sb + i * 10240, &prm.m[M_WO], BAR(BR_WO), c * 64, CHUNK(i) * 80);
      }
      __syncwarp();
      #pragma unroll 1
      for (int i = 1; i < 8; i++) {
        const int src = CHUNK(i);
        if (!((seen >> src) & 1)) seen = poll_bit(fo, epoch, 1u << src);
        if (i > 5) mbar_wait(BAR(BR_OEMPTY - 5) + 8 * i, 0);
        else if (EN_SSM && i != 2 && i != 3) mbar_wait(i == 1 ? BAR(BR_KS + 1) : BAR(BR_FREE - 4) + 8 * i, 0);
        if (elect_one()) {
          mbar_expect_tx(BAR(BR_OFULL) + 8 * i, 20480);
          bulk_ld(sb + SLOT(i), &g_o[(r * 8 + src) * 1280], 20480, BAR(BR_OFULL) + 8 * i);
          if (i == 1) TS(21);
          if (i == 7) TS(22);
        }
        __syncwarp();
      }
      if (lane == 0) { DUMP(20, 30); }
      }
    } else {
      const int hw = warp - 13, ht = tid - 416;
      if (hw == 2 && elect_one()) {
        #pragma unroll
        for (int i = 5; i <= BR_DRDY; i++) mbar_init(BAR(i), i == BR_WO ? 33 : i == BR_OEMPTY ? 9 : i < BR_EMPTY ? 1 : i < BR_OEMPTY ? 2 : i < BR_Y ? 8 : i < BR_DRDY ? 4 : 3);
        asm volatile("fence.mbarrier_init.release.cluster;" ::: "memory");
      }
      __syncwarp();
      asm volatile("bar.arrive 0, 512;" ::: "memory");
      if (EN_SSM && hw == 2) asm volatile("bar.arrive 8, 160;" ::: "memory");
      const unsigned epoch = hw == 0 ? ld_rlx(&g_epoch[cta]) + 1 : 0;
      bar_sync(5, 96);
      asm volatile("bar.arrive 6, 128;" ::: "memory");
      if (hw == 1 && elect_one()) {
        #pragma unroll
        for (int i = M_U; i < M_COUNT; i++) asm volatile("prefetch.tensormap [%0];" :: "l"(&prm.m[i]) : "memory");
      }
      if (ht == 0) {
        st_rlx(&g_epoch[cta], epoch);
        sts32(sb + OFF_EPOCH, epoch);
        mbar_arrive(BAR(BR_EPOCH));
      }
      if (EN_SSM) {
      const int mi = lane >> 3, rw = lane & 7, ch0 = c * 80 + r * 5;
      const bool early_u = hw == 0 && __all_sync(0xffffffff, ld_acq(FLAG(1, lane & 15, c)) == epoch);
      mbar_wait(BAR(BR_UIN), 0);
      if (ht == 0) TS(36);
      #pragma unroll 1
      for (int h = 0; h < 2; h++) {
        const uint32_t sa = sb + OFF_UT + h * 10240 + (8 * mi + rw) * 160 + hw * 16, da = sb + OFF_UT + h * 10240 + (hw * 8 + rw) * 128 + ((mi ^ rw ^ h) << 4);
        uint32_t v[8][4];
        #pragma unroll
        for (int q = 0; q < 8; q++) if (q < 6 || hw == 0) ldsm4t(v[q], sa + (q & 1) * 5120 + (q >> 1) * 48);
        bar_sync(5, 96);
        #pragma unroll
        for (int q = 0; q < 8; q++) if (q < 6 || hw == 0) stsm4((da ^ ((q & 1) * 64)) + (q >> 1) * 3072, v[q][0], v[q][1], v[q][2], v[q][3]);
      }
      fence_async();
      bar_sync(5, 96);
      if (hw == 0) {
        if (elect_one()) {
          tma2d_st(&prm.m[M_SA], sb + OFF_UT, r * 128, c * 80);
          tma2d_st(&prm.m[M_SA], sb + OFF_UT + 10240, r * 128 + 64, c * 80);
          bulk_commit(); bulk_wait0_read();
          mbar_arrive(BAR(BR_UOUT));
          TS(37);
          bulk_wait0();
          st_rel(FLAG(1, r, c), epoch);
          TS(30);
        }
        __syncwarp();
        if (!early_u) poll_all_acq(FLAG(1, lane & 15, c), epoch);
      }
      #pragma unroll 1
      for (int k = 0; k < 5; k++) {
        if (k == 0 || k == 3) {
          const int p = k != 0;
          if (hw == 0) {
            if (!p) {
              if (elect_one()) {
                fence_async_g();
                mbar_expect_tx(BAR(BR_U), 12288);
                #pragma unroll 1
                for (int q = 0; q < 3; q++) bulk_ld(sb + OFF_BLK + q * q * BLK, g_uy + (ch0 + q * q) * 2048, 4096, BAR(BR_U));
                TS(31);
              }
              __syncwarp();
            }
            mbar_wait(BAR(p ? BR_U2 : BR_U), 0);
          }
          bar_sync(5, 96);
        }
        const int l3 = (hw + k) % 3 * 32 + lane;
        const uint32_t blk = sb + OFF_BLK + ((0x32410 >> (4 * k)) & 7) * BLK, o = blk + B_D + l3 * 16;
        float P[34];
        P[0] = 0.f;
        #pragma unroll
        for (int q = 0; q < 5; q++) {
          const int ch = 2 * l3 - 3 + q;
          uint32_t v[4];
          lds128(v, blk + (uint32_t)((ch * 16) ^ ((ch * 2) & 0x10)));
          #pragma unroll
          for (int e = 0; e < 8; e++) {
            const int i = 8 * q + e - 4;
            if (i >= 0 && i < 33) P[i + 1] = P[i] + ((e & 1) ? bf_hi(v[e >> 1]) : bf_lo(v[e >> 1]));
          }
        }
#define WIN(lo, hi, e) (P[21 + (e) - (lo)] - P[20 + (e) - (hi)])
#define WIN8(lo, hi, b) pack2(WIN(lo, hi, b), WIN(lo, hi, b + 1)), pack2(WIN(lo, hi, b + 2), WIN(lo, hi, b + 3)), pack2(WIN(lo, hi, b + 4), WIN(lo, hi, b + 5)), pack2(WIN(lo, hi, b + 6), WIN(lo, hi, b + 7))
        if (l3 < 64) {
          sts128(o + B_D9, WIN8(12, 20, 0)); sts128(o + B_D9 + 1024, WIN8(12, 20, 8));
          sts128(o + B_D7, WIN8(5, 11, 0)); sts128(o + B_D7 + 1024, WIN8(5, 11, 8));
        }
        sts128(o + B_D5, WIN8(6, 10, 0)); sts128(o + B_D5 + 1552, WIN8(6, 10, 8));
        sts128(o, WIN8(3, 5, 0)); sts128(o + 1552, WIN8(3, 5, 8));
        if (l3 < 2) sts128(blk + B_D + l3 * B_D5 + 1536, 0, 0, 0, 0);
      }
      __syncwarp();
      if (lane == 0) mbar_arrive(BAR(BR_DRDY));
      if (ht == 0) TS(32);
      if (hw == 0) {
        const bool early = __all_sync(0xffffffff, ld_rlx(FLAG(2, lane & 15, c)) == epoch);
        #pragma unroll 1
        for (int p = 0; p < 2; p++) {
          mbar_wait(BAR(BR_Y) + 8 * p, 0);
          if (elect_one()) {
            bulk_st(g_uy + (640 + ch0 + 4 * p) * 2048, sb + OFF_BLK + (3 + p) * BLK, p ? 4096 : 16384);
            bulk_commit(); bulk_wait0_read();
            mbar_arrive(BAR(BR_FREE) + 8 * p);
          }
          __syncwarp();
        }
        if (elect_one()) { bulk_wait0(); st_rlx(FLAG(2, r, c), epoch); TS(33); }
        __syncwarp();
        if (!early) poll_all(FLAG(2, lane & 15, c), epoch);
        if (EN_ATT) mbar_wait(BAR(BR_OEMPTY), 0);
        #pragma unroll 1
        for (int n = 0; n < 64; n++) {
          if (elect_one()) {
            mbar_expect_tx(BAR(BR_YIN), 20480);
            tma2d(sb + OFF_EXTRA, &prm.m[M_SA], BAR(BR_YIN), r * 128, 640 + c * 80);
            tma2d(sb + OFF_EXTRA + 10240, &prm.m[M_SA], BAR(BR_YIN), r * 128 + 64, 640 + c * 80);
            TS(34);
          }
          __syncwarp();
          if (EN_ATT) mbar_wait(BAR(BR_OEMPTY + 3), 0);
          mbar_wait(BAR(BR_YIN), n & 1);
          if (lane == 0) TS(38);
          if (!y_transpose(sb, 4, lane, (epoch & 1u) * 0x10001u)) break;
          FIXCNT
        }
      if (elect_one()) {
        TS(39);
        tma2d_st(&prm.m[M_OUT], sb + SLOT(3), c * 80, r * 128);
        bulk_commit(); bulk_wait0_read();
        TS(35); DUMP(30, 40); DUMP(0, 1);
      }
      }
      }
    }
  } else {
  if (wg < 2) {
    asm volatile("setmaxnreg.inc.sync.aligned.u32 160;");
    bar_sync(0, 512);
    if (EN_ATT) {
    float am[96], ar[24];
    {
      const bool lead = (rtid() & 127) == 0;
      constexpr uint64_t dr0 = mkdesc(SB0 + 12288, 1024, 256, 3);
      const uint64_t db0 = sw64 ? mkdesc(SB0, 2048, 512, 2) : mkdesc(SB0, 4096, 1024, 1);
      const uint32_t kst = sw64 ? 64 : 128, bh = db0 >> 32;
      uint32_t s = 0, ph = 0, xo = 0;
      const int ln = rtid() & 31;
      const uint32_t xa = sb + OFF_X + (warp * 16 + (ln & 15)) * 128 + (((ln >> 4) ^ (ln & 7)) << 4);
      uint32_t A[8];
      mbar_wait(BAR(BR_FULL), 0);
      if (lead && wg == 0) TS(1);
      ldsm4(A, xa); ldsm4(A + 4, xa ^ 32);
      wg_fence();
      wg_rs48_tb(ar, A, dr0, 0); wg_rs192_tb(am, A, db0, 0);
      wg_commit();
      #pragma unroll 1
      for (int kb = 1; kb < 20; kb++) {
        const uint32_t wp = s * (W_SLOT >> 4), eb = BAR(BR_EMPTY) + 8 * s;
        wg_fence();
        wg_rs48_tb(ar, A + 4, desc2((uint32_t)dr0 + wp + 32, dr0 >> 32), 1);
        wg_rs192_tb(am, A + 4, desc2((uint32_t)db0 + wp + kst, bh), 1);
        wg_commit();
        if (++s == 5) { s = 0; ph ^= 1; }
        if (!(kb & 1)) { xo += 16384; if (xo == 49152) xo = 0; }
        mbar_wait(BAR(BR_FULL) + 8 * s, ph);
        const uint32_t xk = (xa + xo) ^ ((kb & 1) * 64), wn = s * (W_SLOT >> 4);
        wg_wait<1>();
        ldsm4(A, xk);
        wg_fence();
        wg_rs48_tb(ar, A, desc2((uint32_t)dr0 + wn, dr0 >> 32), 1);
        wg_rs192_tb(am, A, desc2((uint32_t)db0 + wn, bh), 1);
        wg_commit();
        wg_wait<1>();
        ldsm4(A + 4, xk ^ 32);
        if (lead && kb < 16) mbar_arrive(eb);
      }
      wg_fence();
      wg_rs48_tb(ar, A + 4, dr0 + 4 * (W_SLOT >> 4) + 32, 1);
      wg_rs192_tb(am, A + 4, desc2((uint32_t)db0 + 4 * (W_SLOT >> 4) + kst, bh), 1);
      wg_commit();
      wg_wait<0>();
      pin<96>(am); pin<24>(ar);
    }
    const int tid = rtid(), lane = tid & 31, tq = lane & 3;
    if (tid == 0) TS(2);
#define QV(j, e) ((j) < 8 ? am[4 * (j) + (e)] : ar[4 * ((j) - 8) + (e)])
#define KV_(j, e) ((j) < 8 ? am[32 + 4 * (j) + (e)] : ar[8 + 4 * ((j) - 8) + (e)])
#define VV(j, e) ((j) < 8 ? am[64 + 4 * (j) + (e)] : ar[16 + 4 * ((j) - 8) + (e)])
    {
      bar_sync(1, 256);
      if (tid == 0) mbar_arrive(BAR(BR_GEMM));
      const uint32_t ro = sb + (uint32_t)((warp * 16 + (lane & 15)) * 16);
      const int l0 = 2 * (c & 1) + (lane >> 4);
      const uint32_t ones = (tq == 0) ? 0x00003f80u : 0u;
#define PV(j) pack2(VV(j, 0), VV(j, 1)), pack2(VV(j, 2), VV(j, 3))
#define PK(j) pack2(phi(KV_(j, 0)), phi(KV_(j, 1))), pack2(phi(KV_(j, 2)), phi(KV_(j, 3)))
      stsm4(ro + OFF_V + (5 + 6 * (lane >> 4)) * 2048, ones, ones, ones, ones);
      #pragma unroll
      for (int j = 0; j < 10; j += 2) {
        const int l = (j == 8 && (c & 1)) ? l0 - 2 : l0 + j;
        stsm4(ro + OFF_V + (l + (l >= 5)) * 2048, PV(j), PV(j + 1));
        stsm4(ro + OFF_PK + l * 2048, PK(j), PK(j + 1));
      }
    }
    fence_async();
    bar_sync(1, 256);
    if (tid == 0) TS(3);
    mbar_wait(BAR(BR_EPOCH), 0);
    const unsigned epoch = lds32(sb + OFF_EPOCH);
    {
      float kv[24]; zero<24>(kv);
      constexpr uint64_t da = mkdesc(SB0 + OFF_PK, 128, 2048, 0), db = mkdesc(SB0 + OFF_V, 128, 2048, 0);
      wg_fence();
      #pragma unroll
      for (int s = 0; s < 8; s++) wg_ss48_tt(kv, desc2((uint32_t)da + wg * 640 + s * 16, da >> 32), desc2((uint32_t)db + wg * 768 + s * 16, db >> 32), s != 0);
      wg_commit();
      wg_wait<0>();
      pin<24>(kv);
      if (tid == 0) TS(15);
      if (w4 < 3) {
        const uint32_t wb = sb + OFF_KVS + (wg * 3 + w4) * 1536 + (lane & 15) * 96;
        #pragma unroll
        for (int j = 0; j < 6; j += 2)
          stsm4(wb + (j + (lane >> 4)) * 16, pack2(kv[4 * j], kv[4 * j + 1]), pack2(kv[4 * j + 2], kv[4 * j + 3]),
                pack2(kv[4 * j + 4], kv[4 * j + 5]), pack2(kv[4 * j + 6], kv[4 * j + 7]));
        __syncwarp();
        const int dl = w4 * 16 + (lane & 15), hl = dl >= 20;
        uint32_t v[4], z[4];
        lds128(v, wb + (3 * hl + (lane >> 4)) * 16);
        lds64(z, wb + 32 + 8 * hl); z[2] = lds32(wb + 80); z[3] = epoch & 1u;
        if (dl < 40) {
          uint4* dst = &g_kvp[(c * 16 + r) * 240 + wg * 40 + dl];
          v[3] = (v[3] & ~1u) | z[3];
          st128_rlx(dst + (lane >> 4) * 80, v);
          if (lane < 16) st128_rlx(dst + 160, z);
        }
      }
    }
    bar_sync(1, 256);
    if (tid == 0) { st_rlx(FLAG(0, r, c), epoch); mbar_arrive(BAR(BR_PUB)); TS(4); }
    const int kvi = (tid >= 80) + (tid >= 160) + (tid >= 240), kd = tid - 80 * kvi;
    const int khd = kd / 20, kt0 = 5 * (khd >> 1) + 2 * (khd & 1);
    const uint32_t rb = sb + OFF_KVB + kd * 16;
    if (kvi < 3) {
      #pragma unroll 1
      for (int m = kvi; m < 7; m += 3) { const int q = kt0 + 3 + m; sts128(rb + (q >= 10 ? q - 10 : q) * 1280, 0, 0, 0, 0); }
    }
    uint32_t qa[20];
    {
      const float sc = 1.44269504089f + __uint_as_float(lds32(sb + OFF_EPOCH) ^ epoch);
      #pragma unroll
      for (int j = 0; j < 10; j++) { qa[2 * j] = pack2(phi(QV(j, 0), sc), phi(QV(j, 1), sc)); qa[2 * j + 1] = pack2(phi(QV(j, 2), sc), phi(QV(j, 3), sc)); }
    }
    if (tid == 0) TS(5);
    if (warp == 7) mbar_wait(BAR(BR_KVP), 0);
    bar_sync(1, 256);
    if (tid == 0) TS(6);
    if (kvi < 3) {
      float s[8];
      zero<8>(s);
      uint32_t bad = 0;
      #pragma unroll 4
      for (int i = 0; i < 16; i += 2) {
        uint32_t w[4], x[4];
        lds128(w, sb + OFF_KVP + tid * 16 + i * 3840); lds128(x, sb + OFF_KVP + tid * 16 + i * 3840 + 3840);
        bad |= (w[3] ^ epoch) | (x[3] ^ epoch);
        #pragma unroll
        for (int e = 0; e < 4; e++) {
          asm("add.rn.bf16x2 %0, %0, %1;" : "+r"(w[e]) : "r"(x[e]));
          s[2 * e] += bf_lo(w[e]); s[2 * e + 1] += bf_hi(w[e]);
        }
      }
      if (__builtin_expect(bad & 1u, 0)) {
        zero<8>(s);
        #pragma unroll 1
        for (int i = 0; i < 16; i++) {
          uint32_t w[4] = {0, 0, 0, ~epoch};
          fix128_w3(w, &g_kvp[(c * 16 + i) * 240 + tid], epoch, 1u);
          #pragma unroll
          for (int e = 0; e < 4; e++) { s[2 * e] += bf_lo(w[e]); s[2 * e + 1] += bf_hi(w[e]); }
        }
        FIXCNT
      }
      const uint32_t p0 = pack2(s[0], s[1]), p1 = pack2(s[2], s[3]), p2 = pack2(s[4], s[5]), p3 = pack2(s[6], s[7]);
      if (kvi < 2) sts128(rb + (kt0 + (khd & 1) + kvi) * 1280, p0, p1, p2, p3);
      else {
        const bool od = khd & 1;
        sts128(rb + (5 * (khd >> 1) + 2) * 1280, od ? 0u : p0, od ? 0u : p1, od ? p0 : 0u, od ? p1 : 0u);
        const uint32_t zz = (p2 & 0xffffu) << (16 * (khd & 1));
        sts128(rb + 10 * 1280, khd < 2 ? zz : 0u, khd < 2 ? 0u : zz, 0u, 0u);
      }
    }
    fence_async();
    bar_sync(1, 256);
    if (tid == 0) TS(7);
    {
      float oa[44]; zero<44>(oa);
      constexpr uint64_t db = mkdesc(SB0 + OFF_KVB, 128, 1280, 0);
      wg_fence();
      #pragma unroll
      for (int s = 0; s < 5; s++) wg_rs88_tb(oa, &qa[4 * s], desc2((uint32_t)db + ((s == 4 && (c & 1)) ? 0 : (s + (c & 1)) * 16), db >> 32), s != 0);
      wg_commit();
      wg_wait<0>();
      pin<44>(oa);
      if (tid == 0) TS(13);
      float rc[4], rd[2][4];
      #pragma unroll
      for (int e = 0; e < 4; e++) asm("rcp.approx.ftz.f32 %0, %1;" : "=f"(rc[e]) : "f"(oa[40 + e] + 1e-6f));
      #pragma unroll
      for (int h = 0; h < 4; h++) {
        rd[0][h] = __shfl_sync(0xffffffff, rc[h & 1], (lane & 28) | (h >> 1));
        rd[1][h] = __shfl_sync(0xffffffff, rc[2 + (h & 1)], (lane & 28) | (h >> 1));
      }
      #pragma unroll
      for (int j = 0; j < 10; j++) {
        #pragma unroll
        for (int h = 0; h < 2; h++) {
          float f;
          if (j == 2) f = tq < 2 ? rd[h][0] : rd[h][1];
          else if (j == 7) f = tq < 2 ? rd[h][2] : rd[h][3];
          else f = rd[h][(8 * j) / 20];
          qa[2 * j + h] = pack2(oa[4 * j + 2 * h] * f, oa[4 * j + 2 * h + 1] * f);
        }
      }
      const uint32_t m0 = (lane & 7) == ((2 * w4) & 7), m1 = (lane & 7) == 2 * w4 + 1;
      const uint32_t oa_ = sb + OFF_EXTRA + (lane >> 4) * 2048 + (warp * 16 + (lane & 15)) * 16;
      bar_sync(1, 256);
#define TAG(v, m) (((v) & ~(m)) | (epoch & (m)))
      #pragma unroll
      for (int s = 0; s < 5; s++) stsm4(oa_ + s * 4096, TAG(qa[4 * s], m0), TAG(qa[4 * s + 1], m1), TAG(qa[4 * s + 2], m0), TAG(qa[4 * s + 3], m1));
    }
    fence_async();
    __syncwarp();
    if (lane == 0) mbar_arrive(BAR(BR_OSTG));
    if (tid == 0) TS(8);
    }
    asm volatile("setmaxnreg.dec.sync.aligned.u32 136;");
  } else {
    const int g = lane >> 2, tq = lane & 3, t7 = tid & 127;
    asm volatile("bar.arrive 0, 512;" ::: "memory");
    if (EN_SSM) {
    {
      #pragma unroll 1
      for (int k = 0; k < 4; k++) {
        const uint32_t z = sb + OFF_BLK + k * BLK + t7 * 16;
        sts128(z + B_TBL, 0, 0, 0, 0); sts128(z + B_TBL + 2048, 0, 0, 0, 0);
      }
      if (t7 < 80) sts128(sb + OFF_BLK + (t7 >> 4) * BLK - 256 + (t7 & 15) * 16, 0, 0, 0, 0);
      const uint32_t ea = sb + OFF_BLK + (2 + (w4 & 1)) * BLK + (lane >> 4) * 7168 + ((lane >> 3) & 1) * 256 + (lane & 7) * 16 + (w4 >> 1) * 2048;
      constexpr uint64_t dE = mkdesc(SB0 + OFF_BLK + 2 * BLK, 128, 512, 0);
      const uint32_t xa = sb + OFF_BLK + 18560 + t7 * 8, xr_ = sb + OFF_BLK + 18560 + (t7 ^ 64) * 8;
      uint32_t pr[5][2];
      #pragma unroll
      for (int q = 0; q < 5; q++) {
        #pragma unroll
        for (int e = 0; e < 2; e++) pr[q][e] = __byte_perm(raw[q][e], __shfl_xor_sync(0xffffffff, raw[q][e], 1), (lane & 1) ? 0x3276 : 0x5410);
        const uint32_t m = __reduce_max_sync(0xffffffff, max(raw[q][1] & 0x7fffu, (raw[q][1] >> 16) & 0x7fffu));
        if (lane == 0) sts32(sb + OFF_EPOCH + 64 + q * 16 + w4 * 4, m);
      }
      bar_sync(4, 128);
      if (t7 == 0) TS(40);
      const int j = (w4 & 1) * 16 + (w4 >> 1) * 8 + g, i2 = tq < 2 ? 64 * tq + j : 32 * (tq - 2) + j;
      const uint32_t e2 = B_TBL + 4 * (tq < 2 ? T_F3 + (((i2 - 1) & 1) ? 80 : 0) + ((i2 - 1) >> 1) + 16 : T_F2 + (i2 & 1) * 96 + (i2 >> 1));
      const uint32_t e1 = tq < 2 ? (i2 ? e2 - 64 : B_TBL + 4 * (T_F2 + 175)) : B_TBL + 4 * (i2 ? T_F2 + ((2 * i2 - 1) & 3) * 48 + ((2 * i2 - 1) >> 2) : 16 + 511);
      const uint32_t e0 = B_TBL + (16 + 8 * j + 2 * tq) * 4;
      const float dtl = bf_round(expf(bf_lo(pd)));
      float hd[9];
      auto head = [&](int q) {
        const uint32_t pa0 = pr[0][0], pc0 = pr[0][1];
        const float dt = __shfl_sync(0xffffffff, dtl, q);
        #pragma unroll
        for (int e = 0; e < 2; e++) { pr[0][e] = pr[1][e]; pr[1][e] = pr[2][e]; pr[2][e] = pr[3][e]; pr[3][e] = pr[4][e]; }
        uint32_t mm[4];
        lds128(mm, sb + OFF_EPOCH + 64 + q * 16);
        const uint32_t ex = min(max(max(max(mm[0], mm[1]), max(mm[2], mm[3])) >> 7, 1u), 253u);
        const float sc = __uint_as_float((254u - ex) << 23);
        const float lr = -bf_round(expf(bf_lo(pa0))) * dt * 1.44269504089f;
        const float tn = bf_hi(pa0) * dt * 0.15915494309f;
        cexp_t(lr, -tn, hd[0], hd[1]);
        cexp_t(lr * 8.f, tn * 8.f, hd[2], hd[3]);
        cexp_t(lr * 64.f, tn * 64.f, hd[4], hd[5]);
        hd[6] = bf_lo(pc0) * sc; hd[7] = -bf_hi(pc0) * sc;
        hd[8] = 2.f * dt * __uint_as_float(ex << 23);
      };
      head(0);
      #pragma unroll 1
      for (int it = 0; it < 5; it++) {
        const int k = it;
        const uint32_t blk = sb + OFF_BLK + k * BLK;
        float fac = 0.f;
        float ka[24]; zero<24>(ka);
        {
          if (it == 4) {
            mbar_wait(BAR(BR_UOUT), 0);
            sts128(sb + OFF_UT + B_TBL + t7 * 16, 0, 0, 0, 0); sts128(sb + OFF_UT + B_TBL + 2048 + t7 * 16, 0, 0, 0, 0);
          }
          const uint32_t ga = ea + 4096 - (w4 >> 1) * 512;
#define PUT4(i, a, b, c_, d) sts128(((i) < 8 ? ea + ((i) >> 1) * 512 : ga + (((i) - 8) >> 1) * 512) + ((i) & 1) * 128, a, b, c_, d)
          float z2r, z2i, z4r, z4i, xr[8], xi[8], gr[8], gi[8], wr[9], wi[9];
          const float z1r = hd[0], z1i = hd[1];
          xr[1] = hd[2]; xi[1] = hd[3]; wr[0] = hd[4]; wi[0] = hd[5];
          fac = hd[8];
          xr[0] = 1.f; xi[0] = 0.f;
          cmul(xr[1], xi[1], xr[1], xi[1], xr[2], xi[2]); cmul(xr[2], xi[2], xr[1], xi[1], xr[3], xi[3]);
          cmul(xr[2], xi[2], xr[2], xi[2], xr[4], xi[4]);
          #pragma unroll
          for (int b = 1; b < 4; b++) cmul(xr[4], xi[4], xr[b], xi[b], xr[4 + b], xi[4 + b]);
          cmul(wr[0], wi[0], wr[0], wi[0], wr[1], wi[1]); cmul(wr[1], wi[1], wr[0], wi[0], wr[2], wi[2]);
          cmul(wr[1], wi[1], wr[1], wi[1], wr[3], wi[3]); cmul(wr[3], wi[3], wr[3], wi[3], wr[4], wi[4]);
          cmul(wr[4], wi[4], wr[3], wi[3], wr[5], wi[5]); cmul(wr[4], wi[4], wr[4], wi[4], wr[6], wi[6]);
          cmul(wr[6], wi[6], wr[4], wi[4], wr[7], wi[7]); cmul(wr[6], wi[6], wr[6], wi[6], wr[8], wi[8]);
          uint32_t R[4], I[4], PR[4], PI[4];
          #pragma unroll
          for (int b = 0; b < 4; b++) { R[b] = packh(xr[2 * b], xr[2 * b + 1]); I[b] = packh(xi[2 * b], xi[2 * b + 1]); }
          PUT4(0, R[0], R[1], R[2], R[3]); PUT4(1, I[0], I[1], I[2], I[3]);
          #pragma unroll
          for (int i = 0; i < 3; i++) {
            const uint32_t z = packh(wr[i], wi[i]);
            #pragma unroll
            for (int b = 0; b < 4; b++) hcm2(R[b], I[b], z, PR[b], PI[b]);
            PUT4(2 * i + 2, PR[0], PR[1], PR[2], PR[3]); PUT4(2 * i + 3, PI[0], PI[1], PI[2], PI[3]);
          }
          gr[0] = hd[6]; gi[0] = hd[7];
          cmul(z1r, z1i, z1r, z1i, z2r, z2i); cmul(z2r, z2i, z2r, z2i, z4r, z4i);
          cmul(gr[0], gi[0], z1r, z1i, gr[1], gi[1]);
          cmul(gr[0], gi[0], z2r, z2i, gr[2], gi[2]); cmul(gr[1], gi[1], z2r, z2i, gr[3], gi[3]);
          #pragma unroll
          for (int b = 0; b < 4; b++) cmul(gr[b], gi[b], z4r, z4i, gr[4 + b], gi[4 + b]);
          PUT4(8, packh(gr[0], gr[1]), packh(gr[2], gr[3]), packh(gr[4], gr[5]), packh(gr[6], gr[7]));
          PUT4(9, packh(gi[0], gi[1]), packh(gi[2], gi[3]), packh(gi[4], gi[5]), packh(gi[6], gi[7]));
          {
            const uint32_t z = packh(wr[3], -wi[3]), a4r = packh(gr[0], gr[4]), a4i = packh(gi[0], gi[4]);
            hcm2(packh(gr[0], gr[2]), packh(gi[0], gi[2]), z, PR[0], PI[0]);
            hcm2(packh(gr[4], gr[6]), packh(gi[4], gi[6]), z, PR[1], PI[1]);
            hcm2(a4r, a4i, packh(wr[4], -wi[4]), PR[2], PI[2]);
            hcm2(a4r, a4i, packh(wr[5], -wi[5]), PR[3], PI[3]);
            PUT4(10, PR[0], PR[1], PR[2], PR[3]); PUT4(11, PI[0], PI[1], PI[2], PI[3]);
            float hr, hi_;
            cmul(gr[0], gi[0], wr[3], -wi[3], hr, hi_);
            const uint32_t cr = packh(gr[0], hr), ci = packh(gi[0], hi_);
            #pragma unroll
            for (int i = 0; i < 3; i++) hcm2(cr, ci, packh(wr[6 + i], -wi[6 + i]), PR[i], PI[i]);
            PUT4(12, PR[0], PR[1], PR[2], 0u); PUT4(13, PI[0], PI[1], PI[2], 0u);
          }
          fence_async();
          bar_sync(4, 128);
          wg_fence();
          #pragma unroll
          for (int s = 0; s < 8; s++) {
            const uint64_t d = dE + (s >> 2) * (BLK >> 4) + ((s >> 1) & 1) * 448 + (s & 1) * 16;
            wg_ss48_tt_h(ka, d, d + 256, s != 0);
          }
          wg_commit();
        }
        const float dsk = bf_lo(__shfl_sync(0xffffffff, pd, 8 + (it & 7)));
        head(min(it + 1, 4));
        asm volatile("{\n.reg .pred p;\nHL:\nsetp.eq.f32 p, %0, 0f46400000;\n@p bra HL;\n}" :: "f"(hd[0] + hd[2] + hd[4]));
        wg_wait<0>();
        pin<24>(ka);
        float kk[6];
        const bool up = w4 >= 2;
        #pragma unroll
        for (int n = 0; n < 3; n++) {
          sts64f(xa + n * BLK, up ? ka[12 + 4 * n] : ka[4 * n + 2], up ? ka[13 + 4 * n] : ka[4 * n + 3]);
          kk[2 * n] = up ? ka[14 + 4 * n] : ka[4 * n]; kk[2 * n + 1] = up ? ka[15 + 4 * n] : ka[4 * n + 1];
        }
        if (it) bar_sync(4, 128); else bar_sync(8, 160);
          if (it == 4 && w4 == 0) {
            mbar_wait(BAR(BR_U), 0);
            if (elect_one()) {
              mbar_expect_tx(BAR(BR_U2), 8192);
              bulk_ld(blk - 2 * BLK, g_uy + (c * 80 + r * 5 + 2) * 2048, 4096, BAR(BR_U2)); bulk_ld(blk - BLK, g_uy + (c * 80 + r * 5 + 3) * 2048, 4096, BAR(BR_U2));
            }
            __syncwarp();
          }
        #pragma unroll
        for (int n = 0; n < 3; n++) {
          uint32_t o[2]; lds64(o, xr_ + n * BLK);
          kk[2 * n] = (kk[2 * n] + __uint_as_float(o[0])) * fac; kk[2 * n + 1] = (kk[2 * n + 1] + __uint_as_float(o[1])) * fac;
        }
        if (t7 == 0) kk[0] += dsk;
        {
          const uint32_t v = pack2(kk[1], kk[0]), vh = v >> 16;
          const uint32_t u = pack2(kk[2], kk[3]), w = pack2(kk[4], kk[5]), uu = pack2(kk[2], kk[2]), us = pack2(kk[3], kk[2]);
          const uint32_t x = tq < 2 ? w : u, xh = x >> 16;
          sts32(blk + e0 + 4, v); sts16(blk + e0, vh); sts16(blk + e0 + 10, v);
          sts16(blk + e1, x); sts16(blk + e1 + 6, x); sts16(blk + e2, xh); sts16(blk + e2 + 6, xh);
          if (tq < 2) {
            const uint32_t pb = blk + e0 + 1024 + 8 * tq;
            sts32(pb + 4, uu); sts32(pb + 8, us); sts16(pb + 14, us);
            if (i2) { sts16(pb - 4, u); sts32(pb, uu); }
          }
          if (i2 == 0) {
            const uint32_t tb = blk + B_TBL;
            if (tq == 0) { sts16(tb + (16 + 256) * 4, u); sts16(tb + (T_S + 3) * 4, w); sts32(tb + (T_S + 4) * 4, pack2(kk[4], kk[4])); sts16(tb + (T_S + 5) * 4 + 2, w); }
            else { sts32(tb + 528 * 4, uu); sts32(tb + 529 * 4, uu); sts32(tb + 530 * 4, uu); sts16(tb + 531 * 4 + 2, u); sts16(tb + (T_F3 + 80 + 63) * 4, w); }
          }
        }
        if (t7 == 0) TS(49 + it);
      }
    }
    asm volatile("setmaxnreg.inc.sync.aligned.u32 136;");
    if (t7 == 0) TS(41);
    bar_sync(4, 128);
    if (t7 == 0) mbar_arrive(BAR(BR_KS));
    if (EN_ATT) mbar_wait(BAR(BR_GEMM), 0);
    }
  }
  const int tid = rtid(), lane = tid & 31, g = lane >> 2, tq = lane & 3, t7 = tid & 127;
  mbar_wait(BAR(BR_EPOCH), 0);
  const unsigned epoch = lds32(sb + OFF_EPOCH);
  const uint32_t ytag = (epoch & 1u) * 0x10001u, ym = lane < 4 ? 0x10001u : 0u;
  if (EN_SSM && wg != 1) {
    mbar_wait(BAR(BR_KS), 0);
    mbar_wait(BAR(BR_U), 0);
    if (tid == 256) TS(42);
    {
      const int pass = wg >> 1;
      const int k = pass ? w4 : 4;
      if (k & 2) mbar_wait(BAR(BR_U2), 0);
      const uint32_t blk = sb + OFF_BLK + k * BLK, tb = blk + B_TBL + (uint32_t)((g - 2 * tq) * 4);
      float acc[16][4];
      zero<64>(&acc[0][0]);
      const int kl = 16 * (lane >> 4) + 2 * (lane & 7) + ((lane >> 3) & 1);
      {
        auto ubase = [&](int sh) { const int q = kl - 2 * sh; return blk + (uint32_t)((q * 16) ^ ((q * 2) & 0x10)); };
#define LDQ(A, sh) _Pragma("unroll") for (int m = 0; m < 4; m++) load_quad(A[m], tb + (16 + 16 * (sh) + 128 * m) * 4);
#define LDB(B, ub, h) _Pragma("unroll") for (int p = 0; p < 4; p++) ldsm4(B[p], (ub) + (4 * (h) + p) * 512);
#define MLO(A, B) _Pragma("unroll") for (int m = 0; m < 4; m++) _Pragma("unroll") for (int cc = 0; cc < 8; cc++) mma16816(acc[cc + m], A[m], &B[cc >> 1][(cc & 1) * 2]);
#define MHI(A, B) _Pragma("unroll") for (int m = 0; m < 4; m++) _Pragma("unroll") for (int cc = 0; cc < 8 - m; cc++) mma16816(acc[8 + cc + m], A[m], &B[cc >> 1][(cc & 1) * 2]);
        int p_ = pass ? 0 : w4;
        const int pe = pass ? 4 : w4 + 1;
        uint32_t A[4][4], A2[4][4], Bl[4][4], Bh[4][4];
        uint32_t ub = ubase(p_ + 4);
        LDQ(A, p_ + 4) LDB(Bl, ub, 0)
        #pragma unroll 1
        for (; p_ < pe; p_++) {
          LDB(Bh, ub, 1)
          MLO(A, Bl)
          ub = ubase(p_);
          LDQ(A2, p_) LDB(Bl, ub, 0)
          MHI(A, Bh)
          LDB(Bh, ub, 1)
          load_quad(A[0], tb + (16 + 512 + 16 * (p_ & 1)) * 4); load_quad(A[1], tb + (T_S + 16 * (p_ & 1)) * 4);
          MLO(A2, Bl)
          if (p_ < 2) {
            #pragma unroll
            for (int cc = 0; cc < 8; cc++) mma16816(acc[cc + 4], A[0], &Bl[cc >> 1][(cc & 1) * 2]);
            #pragma unroll
            for (int cc = 0; cc < 4; cc++) mma16816(acc[cc + 12], A[0], &Bh[cc >> 1][(cc & 1) * 2]);
            #pragma unroll
            for (int cc = 0; cc < 8; cc++) mma16816(acc[cc + 8], A[1], &Bl[cc >> 1][(cc & 1) * 2]);
          }
          const int pn = ((p_ + 1) & 3) + 4;
          ub = ubase(pn);
          LDQ(A, pn) LDB(Bl, ub, 0)
          MHI(A2, Bh)
        }
      }
      if (t7 == 0) TS(pass ? 60 : 16);
      mbar_wait(BAR(BR_DRDY), 0);
      {
        const int ih = (lane >> 3) & 1;
        const uint32_t dl = blk + B_D + (uint32_t)(((lane >> 4) * 8 + (lane & 7)) * 16);
        const uint32_t d0_ = dl + ih * 1552, d8_ = dl + (ih ? 0 : 1536), d3_ = dl + B_D7 + ih * 1024;
        auto cls2 = [&](uint32_t da, uint32_t ta) {
          uint32_t B[6][2], A[6][4];
          #pragma unroll
          for (int e = 0; e < 6; e++) { B[e][0] = lds32v(ta + (e + 4) * 32); B[e][1] = lds32v(ta + (e + 3) * 32); }
          #pragma unroll
          for (int kk = 0; kk < 6; kk++) ldsm4t(A[kk], da + kk * 256);
          #pragma unroll
          for (int e = 0; e < 6; e++)
            #pragma unroll
            for (int kk = 0; kk < 6; kk++) if (2 * kk + e + 4 < 16) mma16816(acc[2 * kk + e + 4], A[kk], B[e]);
        };
        auto cls3 = [&](uint32_t da, uint32_t ta) {
          uint32_t B[8][2], A[4][4];
          #pragma unroll
          for (int e = 0; e < 8; e++) { B[e][0] = lds32v(ta + (e + 8) * 32); B[e][1] = lds32v(ta + (e + 7) * 32); }
          #pragma unroll
          for (int kk = 0; kk < 4; kk++) ldsm4t(A[kk], da + kk * 256);
          #pragma unroll
          for (int kk = 0; kk < 4; kk++)
            #pragma unroll
            for (int e = 0; e < 8; e++) if (2 * kk + e + 8 < 16) mma16816(acc[2 * kk + e + 8], A[kk], B[e]);
        };
        if (pass) {
          #pragma unroll 1
          for (int a = 0; a < 2; a++) {
            cls2(d0_ + a * B_D5, tb + (T_F2 + 48 * a - 32) * 4);
            cls2(d8_ + a * B_D5, tb + (T_F2 + 48 * a + 64) * 4);
            cls3(d3_ + a * 2048, tb + (T_F3 + 80 * a - 64) * 4);
          }
        } else {
          cls2(((w4 & 2) ? d8_ : d0_) + (w4 & 1) * B_D5, tb + (T_F2 + 48 * w4 - 32) * 4);
          if (w4 >= 2) cls3(d3_ + (w4 - 2) * 2048, tb + (T_F3 + 80 * (w4 - 2) - 64) * 4);
        }
      }
      if (t7 == 0) TS(pass ? 61 : 17);
      const uint32_t ya = (pass ? sb + OFF_BLK + 3 * BLK + w4 * 4096 : blk) + (uint32_t)((kl * 16) ^ ((kl * 2) & 0x10));
#define YTAG(v) (((v) & ~ym) | (ytag & ym))
#define STY(p) stsm4t(ya + (p) * 512, YTAG(pack2(acc[2 * (p)][0], acc[2 * (p)][1])), pack2(acc[2 * (p)][2], acc[2 * (p)][3]), \
                      YTAG(pack2(acc[2 * (p) + 1][0], acc[2 * (p) + 1][1])), pack2(acc[2 * (p) + 1][2], acc[2 * (p) + 1][3]))
      if (pass == 0) {
        const uint32_t xw = blk + 4096 + w4 * 4096 + lane * 16, xr = blk + 4096 + w4 * 1024 + lane * 16;
        #pragma unroll
        for (int h = 0; h < 2; h++) {
          bar_sync(2, 128);
          #pragma unroll
          for (int i = 0; i < 8; i++)
            sts128(xw + i * 512, __float_as_uint(acc[8 * h + i][0]), __float_as_uint(acc[8 * h + i][1]), __float_as_uint(acc[8 * h + i][2]), __float_as_uint(acc[8 * h + i][3]));
          bar_sync(2, 128);
          float y[8];
          #pragma unroll
          for (int i = 0; i < 8; i++) {
            uint32_t o[4]; lds128(o, xr + (i >> 1) * 4096 + (i & 1) * 512);
            #pragma unroll
            for (int e = 0; e < 4; e++) y[4 * (i & 1) + e] = i < 2 ? __uint_as_float(o[e]) : y[4 * (i & 1) + e] + __uint_as_float(o[e]);
          }
          stsm4t(ya + (4 * h + w4) * 512, YTAG(pack2(y[0], y[1])), pack2(y[2], y[3]), YTAG(pack2(y[4], y[5])), pack2(y[6], y[7]));
        }
      } else {
        fence_async();
        bar_sync(4, 128);
        if (t7 == 0) mbar_arrive(BAR(BR_KS + 1));
        #pragma unroll
        for (int p = 0; p < 8; p++) STY(p);
      }
      fence_async();
      __syncwarp();
      if (lane == 0) mbar_arrive(BAR(BR_Y + 1) - 8 * pass);
      if (t7 == 0) TS(pass ? 62 : 18);
    }
  }
  if (wg < 2) {
    if (EN_ATT) {
    float oc[40]; zero<40>(oc);
    {
      constexpr uint64_t dw0 = mkdesc(SB0, OFF_WOR, 1024, 1), da0 = mkdesc(SB0, 2048, 128, 0);
      const uint32_t ck = sb + tid * 32 + ((lane >> 2) << 2), ck2 = ck + (wg ? 0 : 16384);
      uint32_t bad = 0;
      auto tile = [&](int i, uint32_t so) {
        const uint32_t al = (uint32_t)da0 + wg * 64 + (so >> 4), wl = (uint32_t)dw0 + i * 640 - (i >> 1) * (1278 << 16);
        wg_fence();
        #pragma unroll
        for (int s = 0; s < 5; s++) wg_ss80_tb(oc, desc2(al + s * 256, da0 >> 32), desc2(wl + s * 128, dw0 >> 32), (i | s) != 0);
        wg_commit();
        bad |= (lds32(ck + so) ^ epoch) | (lds32(ck + so + 8192) ^ epoch) | (lds32(ck2 + so) ^ epoch);
      };
      if (w4 == 0) {
        if (EN_SSM) mbar_wait(BAR(BR_Y), 0);
        mbar_wait(BAR(BR_WO), 0);
      }
      bar_sync(1, 256);
      if (tid == 0) TS(9);
      tile(0, SLOT(0));
      #pragma unroll 1
      for (int i = 1; i < 8; i++) {
        mbar_wait(BAR(BR_OFULL) + 8 * i, 0);
        tile(i, SLOT(i));
        wg_wait<1>();
        if (lane == 0) mbar_arrive(BAR(BR_OEMPTY - 1) + 8 * i);
      }
      #pragma unroll 1
      for (int n = 0; n < 56; n++) {
        const int i = n & 7;
        if (i == 0) {
          uint32_t any;
          asm volatile("{\n.reg .pred p;\nsetp.ne.u32 p, %1, 0;\nbarrier.red.or.pred p, 1, 256, p;\nselp.u32 %0, 1, 0, p;\n}" : "=r"(any) : "r"(bad & 1u) : "memory");
          if (!any) break;
          bad = 0;
          FIXCNT
        }
        wg_wait<0>();
        bar_sync(1, 256);
        if (tid == 0) { mbar_expect_tx(BAR(BR_RETRY), 20480); bulk_ld(sb + SLOT(2), &g_o[(r * 8 + CHUNK(i)) * 1280], 20480, BAR(BR_RETRY)); }
        mbar_wait(BAR(BR_RETRY), n & 1);
        tile(i, SLOT(2));
      }
      wg_wait<0>();
      pin<40>(oc);
    }
    if (tid == 0) TS(10);
    {
      const int row = w4 * 16 + (lane & 15);
      const uint32_t ob = sb + OFF_BLK + 3 * BLK + wg * 10240;
      #pragma unroll
      for (int j = 0; j < 8; j += 2)
        stsm4(ob + row * 128 + (((j + (lane >> 4)) ^ (row & 7)) << 4), pack2(oc[4 * j], oc[4 * j + 1]), pack2(oc[4 * j + 2], oc[4 * j + 3]),
              pack2(oc[4 * j + 4], oc[4 * j + 5]), pack2(oc[4 * j + 6], oc[4 * j + 7]));
      stsm4(ob + 8192 + row * 32 + (lane >> 4) * 16, pack2(oc[32], oc[33]), pack2(oc[34], oc[35]), pack2(oc[36], oc[37]), pack2(oc[38], oc[39]));
      fence_async();
      bar_sync(2 + wg, 128);
      if (w4 == 0 && elect_one()) {
        tma2d_st(&prm.m[M_O64], ob, 640 + c * 64, r * 128 + wg * 64);
        tma2d_st(&prm.m[M_O16], ob + 8192, 1152 + c * 16, r * 128 + wg * 64);
        bulk_commit(); bulk_wait0_read();
        if (wg == 0) { TS(11); DUMP(0, 20); }
      }
    }
    }
  } else if (EN_SSM) {
    if (t7 == 0) DUMP(40, 64);
    #pragma unroll 1
    for (int n = 0; n < 64; n++) if (!y_transpose(sb, w4, lane, ytag)) break;
  }
  }
}

typedef CUresult (*EncFn)(CUtensorMap*, CUtensorMapDataType, cuuint32_t, void*, const cuuint64_t*, const cuuint64_t*, const cuuint32_t*,
                          const cuuint32_t*, CUtensorMapInterleave, CUtensorMapSwizzle, CUtensorMapL2promotion, CUtensorMapFloatOOBfill);
static void mkmap(EncFn enc, CUtensorMap* m, const void* base, int rank, const cuuint64_t* dims, const cuuint64_t* strides, const cuuint32_t* box, CUtensorMapSwizzle swz) {
  cuuint32_t es[5] = {1, 1, 1, 1, 1};
  enc(m, CU_TENSOR_MAP_DATA_TYPE_BFLOAT16, rank, const_cast<void*>(base), dims, strides, box, es, CU_TENSOR_MAP_INTERLEAVE_NONE, swz,
      CU_TENSOR_MAP_L2_PROMOTION_L2_128B, CU_TENSOR_MAP_FLOAT_OOB_FILL_NONE);
}

extern "C" void kernel_launch(void* const* d_in, const int* in_sizes, int n_in, void* d_out, int out_size) {
  void* fn = nullptr; cudaDriverEntryPointQueryResult qr;
  cudaGetDriverEntryPoint("cuTensorMapEncodeTiled", &fn, cudaEnableDefault, &qr);
  EncFn enc = (EncFn)fn;
  void* uy = nullptr; cudaGetSymbolAddress(&uy, g_uy);
  const cuuint64_t dx[2] = {640, 2048}, sx[1] = {1280};
  const cuuint32_t bx[2] = {64, 128}, bu[2] = {80, 128};
  const cuuint64_t dw[3] = {640, 640, 3}, sw[2] = {3840, 1280};
  const cuuint32_t br[3] = {16, 32, 3};
  const cuuint64_t dwa[4] = {64, 640, 10, 3}, swa[3] = {3840, 128, 1280}, dwb[4] = {32, 640, 20, 3}, swb[3] = {3840, 64, 1280};
  const cuuint32_t bwa[4] = {64, 32, 1, 3}, bwb[4] = {32, 32, 2, 3};
  const cuuint64_t dwo[2] = {640, 640};
  const cuuint32_t bwo[2] = {64, 80}, bo64[2] = {64, 64}, bo16[2] = {16, 64};
  const cuuint64_t dsa[2] = {2048, 1280}, ssa[1] = {4096};
  const cuuint32_t bsa[2] = {64, 80};
  const cuuint64_t dout[2] = {1280, 2048}, sout[1] = {2560};
  Params prm;
  mkmap(enc, &prm.m[M_X], d_in[7], 2, dx, sx, bx, CU_TENSOR_MAP_SWIZZLE_128B);
  mkmap(enc, &prm.m[M_W128], d_in[8], 4, dwa, swa, bwa, CU_TENSOR_MAP_SWIZZLE_128B);
  mkmap(enc, &prm.m[M_W64], d_in[8], 4, dwb, swb, bwb, CU_TENSOR_MAP_SWIZZLE_64B);
  mkmap(enc, &prm.m[M_WR], d_in[8], 3, dw, sw, br, CU_TENSOR_MAP_SWIZZLE_32B);
  mkmap(enc, &prm.m[M_U], d_in[0], 2, dx, sx, bu, CU_TENSOR_MAP_SWIZZLE_NONE);
  mkmap(enc, &prm.m[M_WO], d_in[9], 2, dwo, sx, bwo, CU_TENSOR_MAP_SWIZZLE_128B);
  mkmap(enc, &prm.m[M_O64], d_out, 2, dout, sout, bo64, CU_TENSOR_MAP_SWIZZLE_128B);
  mkmap(enc, &prm.m[M_O16], d_out, 2, dout, sout, bo16, CU_TENSOR_MAP_SWIZZLE_NONE);
  mkmap(enc, &prm.m[M_SA], uy, 2, dsa, ssa, bsa, CU_TENSOR_MAP_SWIZZLE_128B);
  mkmap(enc, &prm.m[M_OUT], d_out, 2, dout, sout, bu, CU_TENSOR_MAP_SWIZZLE_NONE);
  prm.u = (const __nv_bfloat16*)d_in[0]; prm.wo = (const __nv_bfloat16*)d_in[9];
  for (int i = 0; i < 4; i++) prm.par[i] = (const __nv_bfloat16*)d_in[1 + i];
  prm.logdt = (const __nv_bfloat16*)d_in[5]; prm.dskip = (const __nv_bfloat16*)d_in[6];
  cudaFuncSetAttribute(fused_kernel, cudaFuncAttributeMaxDynamicSharedMemorySize, SMEM_BYTES);
  cudaLaunchConfig_t cfg = {};
  cfg.gridDim = dim3(128); cfg.blockDim = dim3(512); cfg.dynamicSmemBytes = SMEM_BYTES; cfg.stream = cudaStreamPerThread;
  cudaLaunchAttribute at[1];
  at[0].id = cudaLaunchAttributeClusterDimension; at[0].val.clusterDim.x = 2; at[0].val.clusterDim.y = 1; at[0].val.clusterDim.z = 1;
  cfg.attrs = at; cfg.numAttrs = 1;
  cudaLaunchKernelEx(&cfg, fused_kernel, prm);
}
```

```cpp
#include <cuda_runtime.h>
#include <cuda_bf16.h>
#include <cuda_fp16.h>
#include <cuda.h>
#include <stdint.h>

#define EN_ATT 1
#define EN_SSM 1

__device__ __align__(1024) __nv_bfloat16 g_uy[2 * 640 * 2048];
__device__ __align__(128) uint4 g_kvp[8 * 16 * 240];
__device__ __align__(128) uint4 g_o[128 * 1280];
__device__ __align__(128) unsigned g_flag[4 * 128 * 32];
__device__ unsigned g_epoch[128];
#define TS(i) do {} while (0)
#define DUMP(lo, hi) do {} while (0)
#define FIXCNT

constexpr uint32_t SB0 = 1024;
constexpr uint32_t W_SLOT = 15360, OFF_X = 76800;
constexpr uint32_t OFF_WOR = 81920, OFF_KVP = 10240, OFF_KVS = 71680, OFF_PK = 10240, OFF_V = 30720, OFF_EXTRA = 102400, OFF_KVB = OFF_EXTRA;
constexpr uint32_t OFF_BAR = 125952, OFF_BLK = 128000, BLK = 20480;
constexpr uint32_t B_D = 4096, B_D5 = 3088, B_D7 = 6176, B_D9 = 8224, B_TBL = 14400;
constexpr int T_S = 576, T_F2 = 624, T_F3 = 816;
constexpr uint32_t OFF_UT = OFF_BLK + 4 * BLK;
constexpr uint32_t SMEM_BYTES = OFF_BLK + 5 * BLK;
enum { BR_FULL = 0, BR_WO = 5, BR_PUB = 6, BR_KVP = 7, BR_U = 8, BR_U2 = 9, BR_GEMM = 10, BR_UIN = 11, BR_YIN = 12, BR_EPOCH = 13,
       BR_FREE = 14, BR_RETRY = 16, BR_KS = 17, BR_UOUT = 19, BR_OFULL = 19  , BR_EMPTY = 27, BR_OEMPTY = 32, BR_OSTG = 39,
       BR_Y = 40, BR_DRDY = 42, BR_COUNT = 44 };
constexpr uint32_t OFF_EPOCH = OFF_BAR + 8 * BR_COUNT;
enum { M_X, M_W128, M_W64, M_WR, M_U, M_WO, M_O64, M_O16, M_SA, M_OUT, M_COUNT };

__device__ __forceinline__ long long clk64() { long long t; asm volatile("mov.u64 %0, %%clock64;" : "=l"(t) :: "memory"); return t; }
__device__ __forceinline__ uint32_t smem_u32(const void* p) { return (uint32_t)__cvta_generic_to_shared(p); }
__host__ __device__ constexpr uint64_t mkdesc(uint32_t addr, uint32_t lbo, uint32_t sbo, uint32_t swz) {
  return (uint64_t)((addr & 0x3FFFF) >> 4) | ((uint64_t)(lbo >> 4) << 16) | ((uint64_t)(sbo >> 4) << 32) | ((uint64_t)swz << 62);
}
__device__ __forceinline__ uint64_t desc2(uint32_t lo, uint32_t hi) { uint64_t d; asm("mov.b64 %0, {%1, %2};" : "=l"(d) : "r"(lo), "r"(hi)); return d; }
__device__ __forceinline__ void mbar_init(uint32_t bar, uint32_t cnt) { asm volatile("mbarrier.init.shared::cta.b64 [%0], %1;" :: "r"(bar), "r"(cnt) : "memory"); }
__device__ __forceinline__ void mbar_expect_tx(uint32_t bar, uint32_t bytes) { asm volatile("mbarrier.arrive.expect_tx.shared::cta.b64 _, [%0], %1;" :: "r"(bar), "r"(bytes) : "memory"); }
__device__ __forceinline__ void mbar_arrive(uint32_t bar) { asm volatile("mbarrier.arrive.shared::cta.b64 _, [%0];" :: "r"(bar) : "memory"); }
__device__ __forceinline__ void mbar_wait(uint32_t bar, uint32_t parity) {
  asm volatile("{\n.reg .pred p;\n.reg .u32 c;\nmov.u32 c, 0;\n"
    "WL:\nmbarrier.try_wait.parity.shared::cta.b64 p, [%0], %1;\n@p bra WD;\n"
    "add.u32 c, c, 1;\nsetp.lt.u32 p, c, 200000;\n@p bra WL;\nWD:\n}" :: "r"(bar), "r"(parity) : "memory");
}
__device__ __forceinline__ void poll_all(const unsigned* p, unsigned val) {
  asm volatile("{\n.reg .pred p;\n.reg .u32 c, v;\nmov.u32 c, 0;\n"
    "PL:\nld.relaxed.gpu.global.u32 v, [%0];\nsetp.eq.u32 p, v, %1;\nvote.sync.all.pred p, p, 0xffffffff;\n@p bra PD;\n"
    "add.u32 c, c, 1;\nsetp.lt.u32 p, c, 100000;\n@p bra PL;\nPD:\n}" :: "l"(p), "r"(val) : "memory");
}
__device__ __forceinline__ void poll_all_acq(const unsigned* p, unsigned val) {
  asm volatile("{\n.reg .pred p;\n.reg .u32 c, v;\nmov.u32 c, 0;\n"
    "PL:\nld.acquire.gpu.global.u32 v, [%0];\nsetp.eq.u32 p, v, %1;\nvote.sync.all.pred p, p, 0xffffffff;\n@p bra PD;\n"
    "nanosleep.u32 300;\nadd.u32 c, c, 1;\nsetp.lt.u32 p, c, 100000;\n@p bra PL;\nPD:\n}" :: "l"(p), "r"(val) : "memory");
}
__device__ __forceinline__ unsigned poll_bit(const unsigned* p, unsigned val, unsigned mask) {
  unsigned bal;
  asm volatile("{\n.reg .pred p;\n.reg .u32 c, v;\nmov.u32 c, 0;\n"
    "PL:\nld.relaxed.gpu.global.u32 v, [%1];\nsetp.eq.u32 p, v, %2;\nvote.sync.ballot.b32 %0, p, 0xffffffff;\n"
    "and.b32 v, %0, %3;\nsetp.ne.u32 p, v, 0;\n@p bra PD;\n"
    "add.u32 c, c, 1;\nsetp.lt.u32 p, c, 100000;\n@p bra PL;\nPD:\n}" : "=&r"(bal) : "l"(p), "r"(val), "r"(mask) : "memory");
  return bal;
}
__device__ __forceinline__ void fix128_w3(uint32_t* v, const void* p, uint32_t tag, uint32_t mask) {
  asm volatile("{\n.reg .pred p;\n.reg .u32 c, x;\n.reg .b128 t;\n.reg .b64 lo, hi;\nmov.u32 c, 0;\n"
    "FL:\nxor.b32 x, %3, %5;\nand.b32 x, x, %6;\nsetp.eq.u32 p, x, 0;\n@p bra FD;\n"
    "ld.relaxed.gpu.global.b128 t, [%4];\nmov.b128 {lo, hi}, t;\nmov.b64 {%0, %1}, lo;\nmov.b64 {%2, %3}, hi;\n"
    "add.u32 c, c, 1;\nsetp.lt.u32 p, c, 100000;\n@p bra FL;\nFD:\n}"
    : "+r"(v[0]), "+r"(v[1]), "+r"(v[2]), "+r"(v[3]) : "l"(p), "r"(tag), "r"(mask) : "memory");
}
__device__ __forceinline__ bool elect_one() {
  uint32_t p; asm volatile("{\n.reg .pred P;\nelect.sync _|P, 0xffffffff;\nselp.u32 %0, 1, 0, P;\n}" : "=r"(p)); return p;
}
__device__ __forceinline__ void bar_sync(int id, int n) { asm volatile("bar.sync %0, %1;" :: "r"(id), "r"(n) : "memory"); }
__device__ __forceinline__ void fence_async() { asm volatile("fence.proxy.async.shared::cta;" ::: "memory"); }
__device__ __forceinline__ void fence_async_g() { asm volatile("fence.proxy.async.global;" ::: "memory"); }
__device__ __forceinline__ void tma2d(uint32_t dst, const CUtensorMap* m, uint32_t bar, int c0, int c1) {
  asm volatile("cp.async.bulk.tensor.2d.shared::cluster.global.mbarrier::complete_tx::bytes [%0], [%1, {%3, %4}], [%2];"
    :: "r"(dst), "l"(m), "r"(bar), "r"(c0), "r"(c1) : "memory");
}
__device__ __forceinline__ void tma3d(uint32_t dst, const CUtensorMap* m, uint32_t bar, int c0, int c1, int c2) {
  asm volatile("cp.async.bulk.tensor.3d.shared::cluster.global.mbarrier::complete_tx::bytes [%0], [%1, {%3, %4, %5}], [%2];"
    :: "r"(dst), "l"(m), "r"(bar), "r"(c0), "r"(c1), "r"(c2) : "memory");
}
__device__ __forceinline__ void tma4d(uint32_t dst, const CUtensorMap* m, uint32_t bar, int c0, int c1, int c2, int c3) {
  asm volatile("cp.async.bulk.tensor.4d.shared::cluster.global.mbarrier::complete_tx::bytes [%0], [%1, {%3, %4, %5, %6}], [%2];"
    :: "r"(dst), "l"(m), "r"(bar), "r"(c0), "r"(c1), "r"(c2), "r"(c3) : "memory");
}
__device__ __forceinline__ void tma2d_st(const CUtensorMap* m, uint32_t src, int c0, int c1) {
  asm volatile("cp.async.bulk.tensor.2d.global.shared::cta.bulk_group [%0, {%2, %3}], [%1];"
    :: "l"(m), "r"(src), "r"(c0), "r"(c1) : "memory");
}
__device__ __forceinline__ void bulk_ld(uint32_t dst, const void* src, uint32_t bytes, uint32_t bar) {
  asm volatile("cp.async.bulk.shared::cluster.global.mbarrier::complete_tx::bytes [%0], [%1], %2, [%3];"
    :: "r"(dst), "l"(src), "r"(bytes), "r"(bar) : "memory");
}
__device__ __forceinline__ void bulk_st(void* dst, uint32_t src, uint32_t bytes) {
  asm volatile("cp.async.bulk.global.shared::cta.bulk_group [%0], [%1], %2;" :: "l"(dst), "r"(src), "r"(bytes) : "memory");
}
__device__ __forceinline__ void bulk_commit() { asm volatile("cp.async.bulk.commit_group;" ::: "memory"); }
__device__ __forceinline__ void bulk_wait0() { asm volatile("cp.async.bulk.wait_group 0;" ::: "memory"); }
__device__ __forceinline__ void bulk_wait0_read() { asm volatile("cp.async.bulk.wait_group.read 0;" ::: "memory"); }
__device__ __forceinline__ unsigned ld_rlx(const unsigned* p) { unsigned v; asm volatile("ld.relaxed.gpu.global.u32 %0, [%1];" : "=r"(v) : "l"(p) : "memory"); return v; }
__device__ __forceinline__ unsigned ld_acq(const unsigned* p) { unsigned v; asm volatile("ld.acquire.gpu.global.u32 %0, [%1];" : "=r"(v) : "l"(p) : "memory"); return v; }
__device__ __forceinline__ void st_rlx(unsigned* p, unsigned v) { asm volatile("st.relaxed.gpu.global.u32 [%0], %1;" :: "l"(p), "r"(v) : "memory"); }
__device__ __forceinline__ void st_rel(unsigned* p, unsigned v) { asm volatile("st.release.gpu.global.u32 [%0], %1;" :: "l"(p), "r"(v) : "memory"); }
__device__ __forceinline__ void st128_rlx(void* p, const uint32_t* v) {
  asm volatile("{\n.reg .b128 t;\n.reg .b64 lo, hi;\nmov.b64 lo, {%1, %2};\nmov.b64 hi, {%3, %4};\nmov.b128 t, {lo, hi};\n"
    "st.relaxed.gpu.global.b128 [%0], t;\n}" :: "l"(p), "r"(v[0]), "r"(v[1]), "r"(v[2]), "r"(v[3]) : "memory");
}
__device__ __forceinline__ uint32_t lds32(uint32_t a) { uint32_t v; asm volatile("ld.shared.u32 %0, [%1];" : "=r"(v) : "r"(a) : "memory"); return v; }
__device__ __forceinline__ uint32_t lds32v(uint32_t a) { uint32_t v; asm volatile("ld.volatile.shared.u32 %0, [%1];" : "=r"(v) : "r"(a) : "memory"); return v; }
__device__ __forceinline__ void lds128(uint32_t* v, uint32_t a) { asm volatile("ld.shared.v4.u32 {%0,%1,%2,%3}, [%4];" : "=r"(v[0]), "=r"(v[1]), "=r"(v[2]), "=r"(v[3]) : "r"(a) : "memory"); }
__device__ __forceinline__ void sts32(uint32_t a, uint32_t v) { asm volatile("st.shared.u32 [%0], %1;" :: "r"(a), "r"(v) : "memory"); }
__device__ __forceinline__ void sts16(uint32_t a, uint32_t v) { asm volatile("st.shared.u16 [%0], %1;" :: "r"(a), "h"((uint16_t)v) : "memory"); }
__device__ __forceinline__ void sts64f(uint32_t a, float x, float y) { asm volatile("st.shared.v2.f32 [%0], {%1,%2};" :: "r"(a), "f"(x), "f"(y) : "memory"); }
__device__ __forceinline__ void sts128(uint32_t a, uint32_t x, uint32_t y, uint32_t z, uint32_t w) { asm volatile("st.shared.v4.u32 [%0], {%1,%2,%3,%4};" :: "r"(a), "r"(x), "r"(y), "r"(z), "r"(w) : "memory"); }
__device__ __forceinline__ void stsm4(uint32_t a, uint32_t r0, uint32_t r1, uint32_t r2, uint32_t r3) {
  asm volatile("stmatrix.sync.aligned.m8n8.x4.shared.b16 [%0], {%1,%2,%3,%4};" :: "r"(a), "r"(r0), "r"(r1), "r"(r2), "r"(r3) : "memory");
}
__device__ __forceinline__ void stsm4t(uint32_t a, uint32_t r0, uint32_t r1, uint32_t r2, uint32_t r3) {
  asm volatile("stmatrix.sync.aligned.m8n8.x4.trans.shared.b16 [%0], {%1,%2,%3,%4};" :: "r"(a), "r"(r0), "r"(r1), "r"(r2), "r"(r3) : "memory");
}
__device__ __forceinline__ void ldsm4t(uint32_t* r, uint32_t a) {
  asm volatile("ldmatrix.sync.aligned.m8n8.x4.trans.shared.b16 {%0,%1,%2,%3}, [%4];" : "=r"(r[0]), "=r"(r[1]), "=r"(r[2]), "=r"(r[3]) : "r"(a) : "memory");
}
__device__ __forceinline__ void ldsm4(uint32_t* r, uint32_t a) {
  asm volatile("ldmatrix.sync.aligned.m8n8.x4.shared.b16 {%0,%1,%2,%3}, [%4];" : "=r"(r[0]), "=r"(r[1]), "=r"(r[2]), "=r"(r[3]) : "r"(a) : "memory");
}
__device__ __forceinline__ void mma16816(float* d, const uint32_t* a, const uint32_t* b) {
  asm volatile("mma.sync.aligned.m16n8k16.row.col.f32.bf16.bf16.f32 {%0,%1,%2,%3}, {%4,%5,%6,%7}, {%8,%9}, {%0,%1,%2,%3};"
    : "+f"(d[0]), "+f"(d[1]), "+f"(d[2]), "+f"(d[3]) : "r"(a[0]), "r"(a[1]), "r"(a[2]), "r"(a[3]), "r"(b[0]), "r"(b[1]));
}
__device__ __forceinline__ uint32_t pack2(float lo, float hi) { uint32_t r; asm("cvt.rn.bf16x2.f32 %0, %1, %2;" : "=r"(r) : "f"(hi), "f"(lo)); return r; }
__device__ __forceinline__ uint32_t packh(float lo, float hi) { uint32_t r; asm("cvt.rn.f16x2.f32 %0, %1, %2;" : "=r"(r) : "f"(hi), "f"(lo)); return r; }
__device__ __forceinline__ void hcm2(uint32_t xr, uint32_t xi, uint32_t z, uint32_t& pr, uint32_t& pi) {
  const __half2 a = *reinterpret_cast<__half2*>(&xr), b = *reinterpret_cast<__half2*>(&xi), zz = *reinterpret_cast<__half2*>(&z);
  const __half2 re = __hfma2(__hneg2(b), __high2half2(zz), __hmul2(a, __low2half2(zz)));
  const __half2 im = __hfma2(a, __high2half2(zz), __hmul2(b, __low2half2(zz)));
  pr = *reinterpret_cast<const uint32_t*>(&re); pi = *reinterpret_cast<const uint32_t*>(&im);
}
__device__ __forceinline__ void lds64(uint32_t* v, uint32_t a) { asm volatile("ld.shared.v2.u32 {%0,%1}, [%2];" : "=r"(v[0]), "=r"(v[1]) : "r"(a) : "memory"); }
__device__ __forceinline__ float bf_lo(uint32_t v) { return __uint_as_float(v << 16); }
__device__ __forceinline__ float bf_hi(uint32_t v) { return __uint_as_float(v & 0xffff0000u); }
__device__ __forceinline__ float bf_round(float x) { return bf_lo(pack2(x, 0.f)); }
__device__ __forceinline__ float ex2(float x) { float r; asm("ex2.approx.ftz.f32 %0, %1;" : "=f"(r) : "f"(x)); return r; }
__device__ __forceinline__ float phi(float t, float l2e = 1.44269504089f) {
  float e = ex2(t * l2e) + 1e-6f;
  asm("{\n.reg .pred p;\nsetp.gt.f32 p, %1, 0f00000000;\n@p add.f32 %0, %1, 0f3F800008;\n}" : "+f"(e) : "f"(t));
  return e;
}
__device__ __forceinline__ void wg_fence() { asm volatile("wgmma.fence.sync.aligned;" ::: "memory"); }
__device__ __forceinline__ void wg_commit() { asm volatile("wgmma.commit_group.sync.aligned;" ::: "memory"); }
template <int N> __device__ __forceinline__ void wg_wait() { asm volatile("wgmma.wait_group.sync.aligned %0;" :: "n"(N) : "memory"); }
template <int N> __device__ __forceinline__ void pin(float* a) {
  #pragma unroll
  for (int i = 0; i < N; i++) asm volatile("" : "+f"(a[i]) :: "memory");
}
__device__ __forceinline__ int rtid() { int t; asm volatile("mov.u32 %0, %%tid.x;" : "=r"(t)); return t; }
template <int N> __device__ __forceinline__ void zero(float* a) {
  #pragma unroll
  for (int i = 0; i < N; i++) asm volatile("mov.b32 %0, 0;" : "=f"(a[i]));
}
__device__ __forceinline__ void cexp_t(float lg2mag, float turns, float& re, float& im) {
  float m = ex2(lg2mag);
  float fr = (turns - __fadd_rn(__fadd_rn(turns, 12582912.f), -12582912.f)) * 6.283185307f;
  re = m * __cosf(fr); im = m * __sinf(fr);
}
__device__ __forceinline__ void cmul(float ar, float ai, float br, float bi, float& cr, float& ci) {
  cr = fmaf(ar, br, -ai * bi); ci = fmaf(ar, bi, ai * br);
}

__device__ __forceinline__ void wg_ss48_tt(float* d, uint64_t da, uint64_t db, int scale_d) {
  asm volatile("{\n.reg .pred p;\nsetp.ne.b32 p, %26, 0;\n"
    "wgmma.mma_async.sync.aligned.m64n48k16.f32.bf16.bf16 "
    "{%0, %1, %2, %3, %4, %5, %6, %7, %8, %9, %10, %11, %12, %13, %14, %15, %16, %17, %18, %19, %20, %21, %22, %23}, %24, %25, p, 1, 1, 1, 1;\n}\n"
    : "+f"(d[0]), "+f"(d[1]), "+f"(d[2]), "+f"(d[3]), "+f"(d[4]), "+f"(d[5]), "+f"(d[6]), "+f"(d[7]), "+f"(d[8]), "+f"(d[9]), "+f"(d[10]), "+f"(d[11]), "+f"(d[12]), "+f"(d[13]), "+f"(d[14]), "+f"(d[15]), "+f"(d[16]), "+f"(d[17]), "+f"(d[18]), "+f"(d[19]), "+f"(d[20]), "+f"(d[21]), "+f"(d[22]), "+f"(d[23])
    : "l"(da), "l"(db), "r"(scale_d));
}
__device__ __forceinline__ void wg_rs88_tb(float* d, const uint32_t* a, uint64_t db, int scale_d) {
  asm volatile("{\n.reg .pred p;\nsetp.ne.b32 p, %49, 0;\n"
    "wgmma.mma_async.sync.aligned.m64n88k16.f32.bf16.bf16 "
    "{%0, %1, %2, %3, %4, %5, %6, %7, %8, %9, %10, %11, %12, %13, %14, %15, %16, %17, %18, %19, %20, %21, %22, %23, %24, %25, %26, %27, %28, %29, %30, %31, %32, %33, %34, %35, %36, %37, %38, %39, %40, %41, %42, %43}, {%44, %45, %46, %47}, %48, p, 1, 1, 1;\n}\n"
    : "+f"(d[0]), "+f"(d[1]), "+f"(d[2]), "+f"(d[3]), "+f"(d[4]), "+f"(d[5]), "+f"(d[6]), "+f"(d[7]), "+f"(d[8]), "+f"(d[9]), "+f"(d[10]), "+f"(d[11]), "+f"(d[12]), "+f"(d[13]), "+f"(d[14]), "+f"(d[15]), "+f"(d[16]), "+f"(d[17]), "+f"(d[18]), "+f"(d[19]), "+f"(d[20]), "+f"(d[21]), "+f"(d[22]), "+f"(d[23]), "+f"(d[24]), "+f"(d[25]), "+f"(d[26]), "+f"(d[27]), "+f"(d[28]), "+f"(d[29]), "+f"(d[30]), "+f"(d[31]), "+f"(d[32]), "+f"(d[33]), "+f"(d[34]), "+f"(d[35]), "+f"(d[36]), "+f"(d[37]), "+f"(d[38]), "+f"(d[39]), "+f"(d[40]), "+f"(d[41]), "+f"(d[42]), "+f"(d[43])
    : "r"(a[0]), "r"(a[1]), "r"(a[2]), "r"(a[3]), "l"(db), "r"(scale_d));
}
__device__ __forceinline__ void wg_ss80_tb(float* d, uint64_t da, uint64_t db, int scale_d) {
  asm volatile("{\n.reg .pred p;\nsetp.ne.b32 p, %42, 0;\n"
    "wgmma.mma_async.sync.aligned.m64n80k16.f32.bf16.bf16 "
    "{%0, %1, %2, %3, %4, %5, %6, %7, %8, %9, %10, %11, %12, %13, %14, %15, %16, %17, %18, %19, %20, %21, %22, %23, %24, %25, %26, %27, %28, %29, %30, %31, %32, %33, %34, %35, %36, %37, %38, %39}, %40, %41, p, 1, 1, 0, 1;\n}\n"
    : "+f"(d[0]), "+f"(d[1]), "+f"(d[2]), "+f"(d[3]), "+f"(d[4]), "+f"(d[5]), "+f"(d[6]), "+f"(d[7]), "+f"(d[8]), "+f"(d[9]), "+f"(d[10]), "+f"(d[11]), "+f"(d[12]), "+f"(d[13]), "+f"(d[14]), "+f"(d[15]), "+f"(d[16]), "+f"(d[17]), "+f"(d[18]), "+f"(d[19]), "+f"(d[20]), "+f"(d[21]), "+f"(d[22]), "+f"(d[23]), "+f"(d[24]), "+f"(d[25]), "+f"(d[26]), "+f"(d[27]), "+f"(d[28]), "+f"(d[29]), "+f"(d[30]), "+f"(d[31]), "+f"(d[32]), "+f"(d[33]), "+f"(d[34]), "+f"(d[35]), "+f"(d[36]), "+f"(d[37]), "+f"(d[38]), "+f"(d[39])
    : "l"(da), "l"(db), "r"(scale_d));
}
__device__ __forceinline__ void wg_ss48_tt_h(float* d, uint64_t da, uint64_t db, int scale_d) {
  asm volatile("{\n.reg .pred p;\nsetp.ne.b32 p, %26, 0;\n"
    "wgmma.mma_async.sync.aligned.m64n48k16.f32.f16.f16 "
    "{%0, %1, %2, %3, %4, %5, %6, %7, %8, %9, %10, %11, %12, %13, %14, %15, %16, %17, %18, %19, %20, %21, %22, %23}, %24, %25, p, 1, 1, 1, 1;\n}\n"
    : "+f"(d[0]), "+f"(d[1]), "+f"(d[2]), "+f"(d[3]), "+f"(d[4]), "+f"(d[5]), "+f"(d[6]), "+f"(d[7]), "+f"(d[8]), "+f"(d[9]), "+f"(d[10]), "+f"(d[11]), "+f"(d[12]), "+f"(d[13]), "+f"(d[14]), "+f"(d[15]), "+f"(d[16]), "+f"(d[17]), "+f"(d[18]), "+f"(d[19]), "+f"(d[20]), "+f"(d[21]), "+f"(d[22]), "+f"(d[23])
    : "l"(da), "l"(db), "r"(scale_d));
}
__device__ __forceinline__ void wg_rs192_tb(float* d, const uint32_t* a, uint64_t db, int scale_d) {
  asm volatile("{\n.reg .pred p;\nsetp.ne.b32 p, %101, 0;\n"
    "wgmma.mma_async.sync.aligned.m64n192k16.f32.bf16.bf16 "
    "{%0, %1, %2, %3, %4, %5, %6, %7, %8, %9, %10, %11, %12, %13, %14, %15, %16, %17, %18, %19, %20, %21, %22, %23, %24, %25, %26, %27, %28, %29, %30, %31, %32, %33, %34, %35, %36, %37, %38, %39, %40, %41, %42, %43, %44, %45, %46, %47, %48, %49, %50, %51, %52, %53, %54, %55, %56, %57, %58, %59, %60, %61, %62, %63, %64, %65, %66, %67, %68, %69, %70, %71, %72, %73, %74, %75, %76, %77, %78, %79, %80, %81, %82, %83, %84, %85, %86, %87, %88, %89, %90, %91, %92, %93, %94, %95}, {%96, %97, %98, %99}, %100, p, 1, 1, 1;\n}\n"
    : "+f"(d[0]), "+f"(d[1]), "+f"(d[2]), "+f"(d[3]), "+f"(d[4]), "+f"(d[5]), "+f"(d[6]), "+f"(d[7]), "+f"(d[8]), "+f"(d[9]), "+f"(d[10]), "+f"(d[11]), "+f"(d[12]), "+f"(d[13]), "+f"(d[14]), "+f"(d[15]), "+f"(d[16]), "+f"(d[17]), "+f"(d[18]), "+f"(d[19]), "+f"(d[20]), "+f"(d[21]), "+f"(d[22]), "+f"(d[23]), "+f"(d[24]), "+f"(d[25]), "+f"(d[26]), "+f"(d[27]), "+f"(d[28]), "+f"(d[29]), "+f"(d[30]), "+f"(d[31]), "+f"(d[32]), "+f"(d[33]), "+f"(d[34]), "+f"(d[35]), "+f"(d[36]), "+f"(d[37]), "+f"(d[38]), "+f"(d[39]), "+f"(d[40]), "+f"(d[41]), "+f"(d[42]), "+f"(d[43]), "+f"(d[44]), "+f"(d[45]), "+f"(d[46]), "+f"(d[47]), "+f"(d[48]), "+f"(d[49]), "+f"(d[50]), "+f"(d[51]), "+f"(d[52]), "+f"(d[53]), "+f"(d[54]), "+f"(d[55]), "+f"(d[56]), "+f"(d[57]), "+f"(d[58]), "+f"(d[59]), "+f"(d[60]), "+f"(d[61]), "+f"(d[62]), "+f"(d[63]), "+f"(d[64]), "+f"(d[65]), "+f"(d[66]), "+f"(d[67]), "+f"(d[68]), "+f"(d[69]), "+f"(d[70]), "+f"(d[71]), "+f"(d[72]), "+f"(d[73]), "+f"(d[74]), "+f"(d[75]), "+f"(d[76]), "+f"(d[77]), "+f"(d[78]), "+f"(d[79]), "+f"(d[80]), "+f"(d[81]), "+f"(d[82]), "+f"(d[83]), "+f"(d[84]), "+f"(d[85]), "+f"(d[86]), "+f"(d[87]), "+f"(d[88]), "+f"(d[89]), "+f"(d[90]), "+f"(d[91]), "+f"(d[92]), "+f"(d[93]), "+f"(d[94]), "+f"(d[95])
    : "r"(a[0]), "r"(a[1]), "r"(a[2]), "r"(a[3]), "l"(db), "r"(scale_d));
}
__device__ __forceinline__ void wg_rs48_tb(float* d, const uint32_t* a, uint64_t db, int scale_d) {
  asm volatile("{\n.reg .pred p;\nsetp.ne.b32 p, %29, 0;\n"
    "wgmma.mma_async.sync.aligned.m64n48k16.f32.bf16.bf16 "
    "{%0, %1, %2, %3, %4, %5, %6, %7, %8, %9, %10, %11, %12, %13, %14, %15, %16, %17, %18, %19, %20, %21, %22, %23}, {%24, %25, %26, %27}, %28, p, 1, 1, 1;\n}\n"
    : "+f"(d[0]), "+f"(d[1]), "+f"(d[2]), "+f"(d[3]), "+f"(d[4]), "+f"(d[5]), "+f"(d[6]), "+f"(d[7]), "+f"(d[8]), "+f"(d[9]), "+f"(d[10]), "+f"(d[11]), "+f"(d[12]), "+f"(d[13]), "+f"(d[14]), "+f"(d[15]), "+f"(d[16]), "+f"(d[17]), "+f"(d[18]), "+f"(d[19]), "+f"(d[20]), "+f"(d[21]), "+f"(d[22]), "+f"(d[23])
    : "r"(a[0]), "r"(a[1]), "r"(a[2]), "r"(a[3]), "l"(db), "r"(scale_d));
}

struct Params {
  const __nv_bfloat16 *par[4], *logdt, *dskip, *u, *wo;
  CUtensorMap m[M_COUNT];
};

#define CHUNK(i) ((c + (i)) & 7)
#define FLAG(kind, rr, cc) (&g_flag[((kind) * 128 + (rr) * 8 + (cc)) * 32])
#define SLOT(i) ((i) == 0 ? OFF_EXTRA : OFF_BLK - 256 + ((i) > 5 ? (i) - 6 : (i) - 1) * BLK)
__device__ __forceinline__ void load_quad(uint32_t* A, uint32_t addr) {
  A[0] = lds32v(addr); A[1] = lds32v(addr + 32); A[2] = lds32v(addr - 32); A[3] = lds32v(addr);
}

__device__ __forceinline__ bool y_transpose(uint32_t sb, int w5, int lane, uint32_t ytag) {
  const int mi = lane >> 3, rw = lane & 7;
  const uint32_t sa = sb + OFF_EXTRA + (w5 * 16 + rw) * 128 + ((mi ^ rw) << 4), da = sb + SLOT(3) + (8 * mi + rw) * 160 + w5 * 32;
  const uint32_t ym = lane < 4 ? 0x10001u : 0u;
  bar_sync(7, 160);
  uint32_t v[8][4], bad = 0;
  #pragma unroll
  for (int q = 0; q < 8; q++) ldsm4t(v[q], (sa ^ ((q & 1) * 64 + ((q >> 1) & 1) * 16)) + ((q >> 1) & 1) * 10240 + (q >> 2) * 1024);
  #pragma unroll
  for (int q = 0; q < 8; q++) {
    bad |= (v[q][0] ^ ytag) | (v[q][2] ^ ytag);
    stsm4(da + (q & 3) * 5120 + (q >> 2) * 16, v[q][0] & ~ym, v[q][1], v[q][2] & ~ym, v[q][3]);
  }
  fence_async();
  uint32_t any;
  asm volatile("{\n.reg .pred p;\nsetp.ne.u32 p, %1, 0;\nbarrier.red.or.pred p, 7, 160, p;\nselp.u32 %0, 1, 0, p;\n}" : "=r"(any) : "r"(bad & ym) : "memory");
  return any;
}

__global__ void __launch_bounds__(512, 1) fused_kernel(const __grid_constant__ Params prm) {
  extern __shared__ unsigned char smem_raw[];
  uint32_t raw[5][2], pd;
  if ((threadIdx.x >> 7) == 2) {
    const int ch = (blockIdx.x & 7) * 80 + (blockIdx.x >> 3) * 5, od = threadIdx.x & 1;
    #pragma unroll
    for (int e = 0; e < 2; e++) {
      const __nv_bfloat16* pp = prm.par[2 * e + od] + ch * 128 + (threadIdx.x & 126);
      #pragma unroll
      for (int q = 0; q < 5; q++) asm volatile("ld.global.nc.u32 %0, [%1];" : "=r"(raw[q][e]) : "l"(pp + q * 128));
    }
    asm volatile("ld.global.nc.u16 %0, [%1];" : "=r"(pd) : "l"(((threadIdx.x & 8) ? prm.dskip : prm.logdt) + ch + min(threadIdx.x & 7, 4)));
  }
  constexpr uint32_t sb = SB0;
  const int tid = threadIdx.x, lane = tid & 31;
  const int warp = __shfl_sync(0xffffffff, tid >> 5, 0), wg = warp >> 2, w4 = warp & 3;
  const int cta = blockIdx.x, r = cta >> 3, c = cta & 7;
  if (smem_u32(smem_raw) != SB0) return;
#define BAR(i) (sb + OFF_BAR + 8 * (i))
  const bool sw64 = ((c + 1) & 2) != 0;

  const CUtensorMap* mwp = &prm.m[sw64 ? M_W64 : M_W128];
  const int mcol = (c * 80 + (c & 1) * 16) >> (sw64 ? 5 : 6), rcol = c * 80 + ((c & 1) ? 0 : 64);
  if (warp == 12 && elect_one()) {
    #pragma unroll
    for (int i = 0; i < 5; i++) mbar_init(BAR(BR_FULL + i), 1);
    asm volatile("fence.mbarrier_init.release.cluster;" ::: "memory");
    if (EN_ATT) {
      mbar_expect_tx(BAR(BR_FULL), W_SLOT + 16384);
      tma4d(sb, mwp, BAR(BR_FULL), 0, 0, mcol, 0);
      tma2d(sb + OFF_X, &prm.m[M_X], BAR(BR_FULL), 0, r * 128);
      tma3d(sb + 12288, &prm.m[M_WR], BAR(BR_FULL), rcol, 0, 0);
      mbar_expect_tx(BAR(BR_FULL + 1), W_SLOT);
      tma4d(sb + W_SLOT, mwp, BAR(BR_FULL + 1), 0, 32, mcol, 0);
      tma3d(sb + W_SLOT + 12288, &prm.m[M_WR], BAR(BR_FULL + 1), rcol, 32, 0);
      TS(24);
    }
  }
  if (warp == 13 && elect_one()) {
    asm volatile("prefetch.tensormap [%0];" :: "l"(&prm.m[M_X]) : "memory");
    asm volatile("prefetch.tensormap [%0];" :: "l"(&prm.m[M_WR]) : "memory");
  }
  if (wg == 3) {
    asm volatile("setmaxnreg.dec.sync.aligned.u32 56;");
    const int tid = rtid(), lane = tid & 31;
    if (warp == 12) {
      asm volatile("bar.arrive 0, 512;" ::: "memory");
      {
        uint32_t s = 2, ph = 1, xs = 16384;
        #pragma unroll 1
        for (int kb = 2; kb < 20; kb++) {
          if (kb == 4) bar_sync(6, 128);
          if (kb >= 5) mbar_wait(BAR(BR_EMPTY) + 8 * s, ph);
          if (EN_ATT && elect_one()) {
            const uint32_t st = sb + s * W_SLOT, fb = BAR(BR_FULL) + 8 * s;
            mbar_expect_tx(fb, (kb & 1) ? W_SLOT : W_SLOT + 16384);
            if (!(kb & 1)) tma2d(sb + OFF_X + xs, &prm.m[M_X], fb, kb * 32, r * 128);
            tma4d(st, mwp, fb, 0, kb * 32, mcol, 0);
            tma3d(st + 12288, &prm.m[M_WR], fb, rcol, kb * 32, 0);
          }
          if (kb < 4 && lane == 0) TS(24 + kb);
          if (EN_SSM && kb == 4 && elect_one()) { mbar_expect_tx(BAR(BR_UIN), 20480); tma2d(sb + OFF_UT, &prm.m[M_U], BAR(BR_UIN), c * 80, r * 128); }
          if (kb == 14 && elect_one()) asm volatile("cp.async.bulk.prefetch.L2.global [%0], 6400;" :: "l"(prm.wo + cta * 3200) : "memory");
          if (!EN_ATT && kb == 4) break;
          if (++s == 5) { s = 0; ph ^= 1; }
          if (kb & 1) { xs += 16384; if (xs == 49152) xs = 0; }
        }
      }
      if (EN_ATT) {
      mbar_wait(BAR(BR_EPOCH), 0);
      const unsigned epoch = lds32(sb + OFF_EPOCH);
      const unsigned* fo = FLAG(3, r, lane & 7);
      unsigned seen = __ballot_sync(0xffffffff, ld_rlx(lane < 16 ? fo : FLAG(0, lane & 15, c)) == epoch) & 0xffu;
      mbar_wait(BAR(BR_GEMM), 0);
      if (elect_one()) {
        mbar_expect_tx(BAR(BR_WO), 8 * 10240);
        mbar_expect_tx(BAR(BR_KVP), 61440);
      }
      {
        uint32_t ds = sb + OFF_WOR + (lane >> 3) * 128 + (((lane & 7) ^ (lane >> 3)) << 4);
        #pragma unroll 1
        for (int h = 0; h < 2; h++) {
          const int i = (lane & 6) + h;
          const char* gs = reinterpret_cast<const char*>(prm.wo) + (size_t)((lane >> 3) + CHUNK(i) * 80) * 1280 + 1024 + c * 32 + (lane & 1) * 16;
          #pragma unroll 2
          for (int q = 0; q < 20; q++) {
            asm volatile("cp.async.cg.shared.global [%0], [%1], 16;" :: "r"(ds), "l"(gs) : "memory");
            ds = (ds + 512) ^ 64; gs += 5120;
          }
        }
      }
      mbar_wait(BAR(BR_PUB), 0);
      poll_all(FLAG(0, lane & 15, c), epoch);
      if (elect_one()) { TS(23); bulk_ld(sb + OFF_KVP, &g_kvp[c * 16 * 240], 61440, BAR(BR_KVP)); }
      asm volatile("cp.async.wait_all;" ::: "memory");
      fence_async();
      mbar_arrive(BAR(BR_WO));
      mbar_wait(BAR(BR_OSTG), 0);
      if (elect_one()) {
        bulk_st(&g_o[cta * 1280], sb + OFF_EXTRA, 20480);
        bulk_commit();
        bulk_wait0();
        st_rlx(FLAG(3, r, c), epoch);
        mbar_arrive(BAR(BR_OEMPTY));
        TS(20);
        #pragma unroll 1
        for (int i = 0; i < 8; i++) tma2d(sb + i * 10240, &prm.m[M_WO], BAR(BR_WO), c * 64, CHUNK(i) * 80);
      }
      __syncwarp();
      #pragma unroll 1
      for (int i = 1; i < 8; i++) {
        const int src = CHUNK(i);
        if (!((seen >> src) & 1)) seen = poll_bit(fo, epoch, 1u << src);
        if (i > 5) mbar_wait(BAR(BR_OEMPTY - 5) + 8 * i, 0);
        else if (EN_SSM && i != 2 && i != 3) mbar_wait(i == 1 ? BAR(BR_KS + 1) : BAR(BR_FREE - 4) + 8 * i, 0);
        if (elect_one()) {
          mbar_expect_tx(BAR(BR_OFULL) + 8 * i, 20480);
          bulk_ld(sb + SLOT(i), &g_o[(r * 8 + src) * 1280], 20480, BAR(BR_OFULL) + 8 * i);
          if (i == 1) TS(21);
          if (i == 7) TS(22);
        }
        __syncwarp();
      }
      if (lane == 0) { DUMP(20, 30); }
      }
    } else {
      const int hw = warp - 13, ht = tid - 416;
      if (hw == 2 && elect_one()) {
        #pragma unroll
        for (int i = 5; i <= BR_DRDY; i++) mbar_init(BAR(i), i == BR_WO ? 33 : i == BR_GEMM ? 8 : i == BR_OEMPTY ? 9 : i < BR_EMPTY ? 1 : i < BR_OEMPTY ? 2 : i < BR_Y ? 8 : i < BR_DRDY ? 4 : 3);
        asm volatile("fence.mbarrier_init.release.cluster;" ::: "memory");
      }
      __syncwarp();
      asm volatile("bar.arrive 0, 512;" ::: "memory");
      if (EN_SSM && hw == 2) asm volatile("bar.arrive 8, 160;" ::: "memory");
      const unsigned epoch = hw == 0 ? ld_rlx(&g_epoch[cta]) + 1 : 0;
      bar_sync(5, 96);
      asm volatile("bar.arrive 6, 128;" ::: "memory");
      if (hw == 1 && elect_one()) {
        #pragma unroll
        for (int i = M_U; i < M_COUNT; i++) asm volatile("prefetch.tensormap [%0];" :: "l"(&prm.m[i]) : "memory");
      }
      if (ht == 0) {
        st_rlx(&g_epoch[cta], epoch);
        sts32(sb + OFF_EPOCH, epoch);
        mbar_arrive(BAR(BR_EPOCH));
      }
      if (EN_SSM) {
      const int mi = lane >> 3, rw = lane & 7, ch0 = c * 80 + r * 5;
      const bool early_u = hw == 0 && __all_sync(0xffffffff, ld_acq(FLAG(1, lane & 15, c)) == epoch);
      mbar_wait(BAR(BR_UIN), 0);
      if (ht == 0) TS(36);
      #pragma unroll 1
      for (int h = 0; h < 2; h++) {
        const uint32_t sa = sb + OFF_UT + h * 10240 + (8 * mi + rw) * 160 + hw * 16, da = sb + OFF_UT + h * 10240 + (hw * 8 + rw) * 128 + ((mi ^ rw ^ h) << 4);
        uint32_t v[8][4];
        #pragma unroll
        for (int q = 0; q < 8; q++) if (q < 6 || hw == 0) ldsm4t(v[q], sa + (q & 1) * 5120 + (q >> 1) * 48);
        bar_sync(5, 96);
        #pragma unroll
        for (int q = 0; q < 8; q++) if (q < 6 || hw == 0) stsm4((da ^ ((q & 1) * 64)) + (q >> 1) * 3072, v[q][0], v[q][1], v[q][2], v[q][3]);
      }
      fence_async();
      bar_sync(5, 96);
      if (hw == 0) {
        if (elect_one()) {
          tma2d_st(&prm.m[M_SA], sb + OFF_UT, r * 128, c * 80);
          tma2d_st(&prm.m[M_SA], sb + OFF_UT + 10240, r * 128 + 64, c * 80);
          bulk_commit(); bulk_wait0_read();
          mbar_arrive(BAR(BR_UOUT));
          TS(37);
          bulk_wait0();
          st_rel(FLAG(1, r, c), epoch);
          TS(30);
        }
        __syncwarp();
        if (!early_u) poll_all_acq(FLAG(1, lane & 15, c), epoch);
      }
      #pragma unroll 1
      for (int k = 0; k < 5; k++) {
        if (k == 0 || k == 3) {
          const int p = k != 0;
          if (hw == 0) {
            if (!p) {
              if (elect_one()) {
                fence_async_g();
                mbar_expect_tx(BAR(BR_U), 12288);
                #pragma unroll 1
                for (int q = 0; q < 3; q++) bulk_ld(sb + OFF_BLK + q * q * BLK, g_uy + (ch0 + q * q) * 2048, 4096, BAR(BR_U));
                TS(31);
              }
              __syncwarp();
            }
            mbar_wait(BAR(p ? BR_U2 : BR_U), 0);
          }
          bar_sync(5, 96);
        }
        const int l3 = (hw + k) % 3 * 32 + lane;
        const uint32_t blk = sb + OFF_BLK + ((0x32410 >> (4 * k)) & 7) * BLK, o = blk + B_D + l3 * 16;
        float P[34];
        P[0] = 0.f;
        #pragma unroll
        for (int q = 0; q < 5; q++) {
          const int ch = 2 * l3 - 3 + q;
          uint32_t v[4];
          lds128(v, blk + (uint32_t)((ch * 16) ^ ((ch * 2) & 0x10)));
          #pragma unroll
          for (int e = 0; e < 8; e++) {
            const int i = 8 * q + e - 4;
            if (i >= 0 && i < 33) P[i + 1] = P[i] + ((e & 1) ? bf_hi(v[e >> 1]) : bf_lo(v[e >> 1]));
          }
        }
#define WIN(lo, hi, e) (P[21 + (e) - (lo)] - P[20 + (e) - (hi)])
#define WIN8(lo, hi, b) pack2(WIN(lo, hi, b), WIN(lo, hi, b + 1)), pack2(WIN(lo, hi, b + 2), WIN(lo, hi, b + 3)), pack2(WIN(lo, hi, b + 4), WIN(lo, hi, b + 5)), pack2(WIN(lo, hi, b + 6), WIN(lo, hi, b + 7))
        if (l3 < 64) {
          sts128(o + B_D9, WIN8(12, 20, 0)); sts128(o + B_D9 + 1024, WIN8(12, 20, 8));
          sts128(o + B_D7, WIN8(5, 11, 0)); sts128(o + B_D7 + 1024, WIN8(5, 11, 8));
        }
        sts128(o + B_D5, WIN8(6, 10, 0)); sts128(o + B_D5 + 1552, WIN8(6, 10, 8));
        sts128(o, WIN8(3, 5, 0)); sts128(o + 1552, WIN8(3, 5, 8));
        if (l3 < 2) sts128(blk + B_D + l3 * B_D5 + 1536, 0, 0, 0, 0);
      }
      __syncwarp();
      if (lane == 0) mbar_arrive(BAR(BR_DRDY));
      if (ht == 0) TS(32);
      if (hw == 0) {
        const bool early = __all_sync(0xffffffff, ld_rlx(FLAG(2, lane & 15, c)) == epoch);
        #pragma unroll 1
        for (int p = 0; p < 2; p++) {
          mbar_wait(BAR(BR_Y) + 8 * p, 0);
          if (elect_one()) {
            bulk_st(g_uy + (640 + ch0 + 4 * p) * 2048, sb + OFF_BLK + (3 + p) * BLK, p ? 4096 : 16384);
            bulk_commit(); bulk_wait0_read();
            mbar_arrive(BAR(BR_FREE) + 8 * p);
          }
          __syncwarp();
        }
        if (elect_one()) { bulk_wait0(); st_rlx(FLAG(2, r, c), epoch); TS(33); }
        __syncwarp();
        if (!early) poll_all(FLAG(2, lane & 15, c), epoch);
        if (EN_ATT) mbar_wait(BAR(BR_OEMPTY), 0);
        #pragma unroll 1
        for (int n = 0; n < 64; n++) {
          if (elect_one()) {
            mbar_expect_tx(BAR(BR_YIN), 20480);
            tma2d(sb + OFF_EXTRA, &prm.m[M_SA], BAR(BR_YIN), r * 128, 640 + c * 80);
            tma2d(sb + OFF_EXTRA + 10240, &prm.m[M_SA], BAR(BR_YIN), r * 128 + 64, 640 + c * 80);
            TS(34);
          }
          __syncwarp();
          if (EN_ATT) mbar_wait(BAR(BR_OEMPTY + 3), 0);
          mbar_wait(BAR(BR_YIN), n & 1);
          if (lane == 0) TS(38);
          if (!y_transpose(sb, 4, lane, (epoch & 1u) * 0x10001u)) break;
          FIXCNT
        }
      if (elect_one()) {
        TS(39);
        tma2d_st(&prm.m[M_OUT], sb + SLOT(3), c * 80, r * 128);
        bulk_commit(); bulk_wait0_read();
        TS(35); DUMP(30, 40); DUMP(0, 1);
      }
      }
      }
    }
  } else {
  if (wg < 2) {
    asm volatile("setmaxnreg.inc.sync.aligned.u32 160;");
    bar_sync(0, 512);
    if (EN_ATT) {
    float am[96], ar[24];
    {
      const bool lead = (rtid() & 127) == 0;
      constexpr uint64_t dr0 = mkdesc(SB0 + 12288, 1024, 256, 3);
      const uint64_t db0 = sw64 ? mkdesc(SB0, 2048, 512, 2) : mkdesc(SB0, 4096, 1024, 1);
      const uint32_t kst = sw64 ? 64 : 128, bh = db0 >> 32;
      uint32_t s = 0, ph = 0, xo = 0;
      const int ln = rtid() & 31;
      const uint32_t xa = sb + OFF_X + (warp * 16 + (ln & 15)) * 128 + (((ln >> 4) ^ (ln & 7)) << 4);
      uint32_t A[8];
      mbar_wait(BAR(BR_FULL), 0);
      if (lead && wg == 0) TS(1);
      ldsm4(A, xa); ldsm4(A + 4, xa ^ 32);
      wg_fence();
      wg_rs48_tb(ar, A, dr0, 0); wg_rs192_tb(am, A, db0, 0);
      wg_commit();
      #pragma unroll 1
      for (int kb = 1; kb < 20; kb++) {
        const uint32_t wp = s * (W_SLOT >> 4), eb = BAR(BR_EMPTY) + 8 * s;
        wg_fence();
        wg_rs48_tb(ar, A + 4, desc2((uint32_t)dr0 + wp + 32, dr0 >> 32), 1);
        wg_rs192_tb(am, A + 4, desc2((uint32_t)db0 + wp + kst, bh), 1);
        wg_commit();
        if (++s == 5) { s = 0; ph ^= 1; }
        if (!(kb & 1)) { xo += 16384; if (xo == 49152) xo = 0; }
        mbar_wait(BAR(BR_FULL) + 8 * s, ph);
        const uint32_t xk = (xa + xo) ^ ((kb & 1) * 64), wn = s * (W_SLOT >> 4);
        wg_wait<1>();
        ldsm4(A, xk);
        wg_fence();
        wg_rs48_tb(ar, A, desc2((uint32_t)dr0 + wn, dr0 >> 32), 1);
        wg_rs192_tb(am, A, desc2((uint32_t)db0 + wn, bh), 1);
        wg_commit();
        wg_wait<1>();
        ldsm4(A + 4, xk ^ 32);
        if (lead && kb < 16) mbar_arrive(eb);
      }
      wg_fence();
      wg_rs48_tb(ar, A + 4, dr0 + 4 * (W_SLOT >> 4) + 32, 1);
      wg_rs192_tb(am, A + 4, desc2((uint32_t)db0 + 4 * (W_SLOT >> 4) + kst, bh), 1);
      wg_commit();
      wg_wait<0>();
      if (ln == 0) mbar_arrive(BAR(BR_GEMM));
      pin<96>(am); pin<24>(ar);
    }
    const int tid = rtid(), lane = tid & 31, tq = lane & 3;
    if (tid == 0) TS(2);
#define QV(j, e) ((j) < 8 ? am[4 * (j) + (e)] : ar[4 * ((j) - 8) + (e)])
#define KV_(j, e) ((j) < 8 ? am[32 + 4 * (j) + (e)] : ar[8 + 4 * ((j) - 8) + (e)])
#define VV(j, e) ((j) < 8 ? am[64 + 4 * (j) + (e)] : ar[16 + 4 * ((j) - 8) + (e)])
    {
      bar_sync(1, 256);
      const uint32_t ro = sb + (uint32_t)((warp * 16 + (lane & 15)) * 16);
      const int l0 = 2 * (c & 1) + (lane >> 4);
      const uint32_t ones = (tq == 0) ? 0x00003f80u : 0u;
#define PV(j) pack2(VV(j, 0), VV(j, 1)), pack2(VV(j, 2), VV(j, 3))
#define PK(j) pack2(phi(KV_(j, 0)), phi(KV_(j, 1))), pack2(phi(KV_(j, 2)), phi(KV_(j, 3)))
      stsm4(ro + OFF_V + (5 + 6 * (lane >> 4)) * 2048, ones, ones, ones, ones);
      #pragma unroll
      for (int j = 0; j < 10; j += 2) {
        const int l = (j == 8 && (c & 1)) ? l0 - 2 : l0 + j;
        stsm4(ro + OFF_V + (l + (l >= 5)) * 2048, PV(j), PV(j + 1));
        stsm4(ro + OFF_PK + l * 2048, PK(j), PK(j + 1));
      }
    }
    fence_async();
    bar_sync(1, 256);
    if (tid == 0) TS(3);
    mbar_wait(BAR(BR_EPOCH), 0);
    const unsigned epoch = lds32(sb + OFF_EPOCH);
    {
      float kv[24]; zero<24>(kv);
      constexpr uint64_t da = mkdesc(SB0 + OFF_PK, 128, 2048, 0), db = mkdesc(SB0 + OFF_V, 128, 2048, 0);
      wg_fence();
      #pragma unroll
      for (int s = 0; s < 8; s++) wg_ss48_tt(kv, desc2((uint32_t)da + wg * 640 + s * 16, da >> 32), desc2((uint32_t)db + wg * 768 + s * 16, db >> 32), s != 0);
      wg_commit();
      wg_wait<0>();
      pin<24>(kv);
      if (tid == 0) TS(15);
      if (w4 < 3) {
        const uint32_t wb = sb + OFF_KVS + (wg * 3 + w4) * 1536 + (lane & 15) * 96;
        #pragma unroll
        for (int j = 0; j < 6; j += 2)
          stsm4(wb + (j + (lane >> 4)) * 16, pack2(kv[4 * j], kv[4 * j + 1]), pack2(kv[4 * j + 2], kv[4 * j + 3]),
                pack2(kv[4 * j + 4], kv[4 * j + 5]), pack2(kv[4 * j + 6], kv[4 * j + 7]));
        __syncwarp();
        const int dl = w4 * 16 + (lane & 15), hl = dl >= 20;
        uint32_t v[4], z[4];
        lds128(v, wb + (3 * hl + (lane >> 4)) * 16);
        lds64(z, wb + 32 + 8 * hl); z[2] = lds32(wb + 80); z[3] = epoch & 1u;
        if (dl < 40) {
          uint4* dst = &g_kvp[(c * 16 + r) * 240 + wg * 40 + dl];
          v[3] = (v[3] & ~1u) | z[3];
          st128_rlx(dst + (lane >> 4) * 80, v);
          if (lane < 16) st128_rlx(dst + 160, z);
        }
      }
    }
    bar_sync(1, 256);
    if (tid == 0) { st_rlx(FLAG(0, r, c), epoch); mbar_arrive(BAR(BR_PUB)); TS(4); }
    const int kvi = (tid >= 80) + (tid >= 160) + (tid >= 240), kd = tid - 80 * kvi;
    const int khd = kd / 20, kt0 = 5 * (khd >> 1) + 2 * (khd & 1);
    const uint32_t rb = sb + OFF_KVB + kd * 16;
    if (kvi < 3) {
      #pragma unroll 1
      for (int m = kvi; m < 7; m += 3) { const int q = kt0 + 3 + m; sts128(rb + (q >= 10 ? q - 10 : q) * 1280, 0, 0, 0, 0); }
    }
    uint32_t qa[20];
    {
      const float sc = 1.44269504089f + __uint_as_float(lds32(sb + OFF_EPOCH) ^ epoch);
      #pragma unroll
      for (int j = 0; j < 10; j++) { qa[2 * j] = pack2(phi(QV(j, 0), sc), phi(QV(j, 1), sc)); qa[2 * j + 1] = pack2(phi(QV(j, 2), sc), phi(QV(j, 3), sc)); }
    }
    if (tid == 0) TS(5);
    if (warp == 7) mbar_wait(BAR(BR_KVP), 0);
    bar_sync(1, 256);
    if (tid == 0) TS(6);
    if (kvi < 3) {
      float s[8];
      zero<8>(s);
      uint32_t bad = 0;
      #pragma unroll 4
      for (int i = 0; i < 16; i += 2) {
        uint32_t w[4], x[4];
        lds128(w, sb + OFF_KVP + tid * 16 + i * 3840); lds128(x, sb + OFF_KVP + tid * 16 + i * 3840 + 3840);
        bad |= (w[3] ^ epoch) | (x[3] ^ epoch);
        #pragma unroll
        for (int e = 0; e < 4; e++) {
          asm("add.rn.bf16x2 %0, %0, %1;" : "+r"(w[e]) : "r"(x[e]));
          s[2 * e] += bf_lo(w[e]); s[2 * e + 1] += bf_hi(w[e]);
        }
      }
      if (__builtin_expect(bad & 1u, 0)) {
        zero<8>(s);
        #pragma unroll 1
        for (int i = 0; i < 16; i++) {
          uint32_t w[4] = {0, 0, 0, ~epoch};
          fix128_w3(w, &g_kvp[(c * 16 + i) * 240 + tid], epoch, 1u);
          #pragma unroll
          for (int e = 0; e < 4; e++) { s[2 * e] += bf_lo(w[e]); s[2 * e + 1] += bf_hi(w[e]); }
        }
        FIXCNT
      }
      const uint32_t p0 = pack2(s[0], s[1]), p1 = pack2(s[2], s[3]), p2 = pack2(s[4], s[5]), p3 = pack2(s[6], s[7]);
      if (kvi < 2) sts128(rb + (kt0 + (khd & 1) + kvi) * 1280, p0, p1, p2, p3);
      else {
        const bool od = khd & 1;
        sts128(rb + (5 * (khd >> 1) + 2) * 1280, od ? 0u : p0, od ? 0u : p1, od ? p0 : 0u, od ? p1 : 0u);
        const uint32_t zz = (p2 & 0xffffu) << (16 * (khd & 1));
        sts128(rb + 10 * 1280, khd < 2 ? zz : 0u, khd < 2 ? 0u : zz, 0u, 0u);
      }
    }
    fence_async();
    bar_sync(1, 256);
    if (tid == 0) TS(7);
    {
      float oa[44]; zero<44>(oa);
      constexpr uint64_t db = mkdesc(SB0 + OFF_KVB, 128, 1280, 0);
      wg_fence();
      #pragma unroll
      for (int s = 0; s < 5; s++) wg_rs88_tb(oa, &qa[4 * s], desc2((uint32_t)db + ((s == 4 && (c & 1)) ? 0 : (s + (c & 1)) * 16), db >> 32), s != 0);
      wg_commit();
      wg_wait<0>();
      pin<44>(oa);
      if (tid == 0) TS(13);
      float rc[4], rd[2][4];
      #pragma unroll
      for (int e = 0; e < 4; e++) asm("rcp.approx.ftz.f32 %0, %1;" : "=f"(rc[e]) : "f"(oa[40 + e] + 1e-6f));
      #pragma unroll
      for (int h = 0; h < 4; h++) {
        rd[0][h] = __shfl_sync(0xffffffff, rc[h & 1], (lane & 28) | (h >> 1));
        rd[1][h] = __shfl_sync(0xffffffff, rc[2 + (h & 1)], (lane & 28) | (h >> 1));
      }
      #pragma unroll
      for (int j = 0; j < 10; j++) {
        #pragma unroll
        for (int h = 0; h < 2; h++) {
          float f;
          if (j == 2) f = tq < 2 ? rd[h][0] : rd[h][1];
          else if (j == 7) f = tq < 2 ? rd[h][2] : rd[h][3];
          else f = rd[h][(8 * j) / 20];
          qa[2 * j + h] = pack2(oa[4 * j + 2 * h] * f, oa[4 * j + 2 * h + 1] * f);
        }
      }
      const uint32_t m0 = (lane & 7) == ((2 * w4) & 7), m1 = (lane & 7) == 2 * w4 + 1;
      const uint32_t oa_ = sb + OFF_EXTRA + (lane >> 4) * 2048 + (warp * 16 + (lane & 15)) * 16;
      bar_sync(1, 256);
#define TAG(v, m) (((v) & ~(m)) | (epoch & (m)))
      #pragma unroll
      for (int s = 0; s < 5; s++) stsm4(oa_ + s * 4096, TAG(qa[4 * s], m0), TAG(qa[4 * s + 1], m1), TAG(qa[4 * s + 2], m0), TAG(qa[4 * s + 3], m1));
    }
    fence_async();
    __syncwarp();
    if (lane == 0) mbar_arrive(BAR(BR_OSTG));
    if (tid == 0) TS(8);
    }
    asm volatile("setmaxnreg.dec.sync.aligned.u32 136;");
  } else {
    const int g = lane >> 2, tq = lane & 3, t7 = tid & 127;
    asm volatile("bar.arrive 0, 512;" ::: "memory");
    if (EN_SSM) {
    {
      #pragma unroll 1
      for (int k = 0; k < 4; k++) {
        const uint32_t z = sb + OFF_BLK + k * BLK + t7 * 16;
        sts128(z + B_TBL, 0, 0, 0, 0); sts128(z + B_TBL + 2048, 0, 0, 0, 0);
      }
      if (t7 < 80) sts128(sb + OFF_BLK + (t7 >> 4) * BLK - 256 + (t7 & 15) * 16, 0, 0, 0, 0);
      const uint32_t ea = sb + OFF_BLK + (2 + (w4 & 1)) * BLK + (lane >> 4) * 7168 + ((lane >> 3) & 1) * 256 + (lane & 7) * 16 + (w4 >> 1) * 2048;
      constexpr uint64_t dE = mkdesc(SB0 + OFF_BLK + 2 * BLK, 128, 512, 0);
      const uint32_t xa = sb + OFF_BLK + 18560 + t7 * 8, xr_ = sb + OFF_BLK + 18560 + (t7 ^ 64) * 8;
      uint32_t pr[5][2];
      #pragma unroll
      for (int q = 0; q < 5; q++) {
        #pragma unroll
        for (int e = 0; e < 2; e++) pr[q][e] = __byte_perm(raw[q][e], __shfl_xor_sync(0xffffffff, raw[q][e], 1), (lane & 1) ? 0x3276 : 0x5410);
        const uint32_t m = __reduce_max_sync(0xffffffff, max(raw[q][1] & 0x7fffu, (raw[q][1] >> 16) & 0x7fffu));
        if (lane == 0) sts32(sb + OFF_EPOCH + 64 + q * 16 + w4 * 4, m);
      }
      bar_sync(4, 128);
      if (t7 == 0) TS(40);
      const int j = (w4 & 1) * 16 + (w4 >> 1) * 8 + g, i2 = tq < 2 ? 64 * tq + j : 32 * (tq - 2) + j;
      const uint32_t e2 = B_TBL + 4 * (tq < 2 ? T_F3 + (((i2 - 1) & 1) ? 80 : 0) + ((i2 - 1) >> 1) + 16 : T_F2 + (i2 & 1) * 96 + (i2 >> 1));
      const uint32_t e1 = tq < 2 ? (i2 ? e2 - 64 : B_TBL + 4 * (T_F2 + 175)) : B_TBL + 4 * (i2 ? T_F2 + ((2 * i2 - 1) & 3) * 48 + ((2 * i2 - 1) >> 2) : 16 + 511);
      const uint32_t e0 = B_TBL + (16 + 8 * j + 2 * tq) * 4;
      const float dtl = bf_round(expf(bf_lo(pd)));
      float hd[9];
      auto head = [&](int q) {
        const uint32_t pa0 = pr[0][0], pc0 = pr[0][1];
        const float dt = __shfl_sync(0xffffffff, dtl, q);
        #pragma unroll
        for (int e = 0; e < 2; e++) { pr[0][e] = pr[1][e]; pr[1][e] = pr[2][e]; pr[2][e] = pr[3][e]; pr[3][e] = pr[4][e]; }
        uint32_t mm[4];
        lds128(mm, sb + OFF_EPOCH + 64 + q * 16);
        const uint32_t ex = min(max(max(max(mm[0], mm[1]), max(mm[2], mm[3])) >> 7, 1u), 253u);
        const float sc = __uint_as_float((254u - ex) << 23);
        const float lr = -bf_round(expf(bf_lo(pa0))) * dt * 1.44269504089f;
        const float tn = bf_hi(pa0) * dt * 0.15915494309f;
        cexp_t(lr, -tn, hd[0], hd[1]);
        cexp_t(lr * 8.f, tn * 8.f, hd[2], hd[3]);
        cexp_t(lr * 64.f, tn * 64.f, hd[4], hd[5]);
        hd[6] = bf_lo(pc0) * sc; hd[7] = -bf_hi(pc0) * sc;
        hd[8] = 2.f * dt * __uint_as_float(ex << 23);
      };
      head(0);
      #pragma unroll 1
      for (int it = 0; it < 5; it++) {
        const int k = it;
        const uint32_t blk = sb + OFF_BLK + k * BLK;
        float fac = 0.f;
        float ka[24]; zero<24>(ka);
        {
          if (it == 4) {
            mbar_wait(BAR(BR_UOUT), 0);
            sts128(sb + OFF_UT + B_TBL + t7 * 16, 0, 0, 0, 0); sts128(sb + OFF_UT + B_TBL + 2048 + t7 * 16, 0, 0, 0, 0);
          }
          const uint32_t ga = ea + 4096 - (w4 >> 1) * 512;
#define PUT4(i, a, b, c_, d) sts128(((i) < 8 ? ea + ((i) >> 1) * 512 : ga + (((i) - 8) >> 1) * 512) + ((i) & 1) * 128, a, b, c_, d)
          float z2r, z2i, z4r, z4i, xr[8], xi[8], gr[8], gi[8], wr[9], wi[9];
          const float z1r = hd[0], z1i = hd[1];
          xr[1] = hd[2]; xi[1] = hd[3]; wr[0] = hd[4]; wi[0] = hd[5];
          fac = hd[8];
          xr[0] = 1.f; xi[0] = 0.f;
          cmul(xr[1], xi[1], xr[1], xi[1], xr[2], xi[2]); cmul(xr[2], xi[2], xr[1], xi[1], xr[3], xi[3]);
          cmul(xr[2], xi[2], xr[2], xi[2], xr[4], xi[4]);
          #pragma unroll
          for (int b = 1; b < 4; b++) cmul(xr[4], xi[4], xr[b], xi[b], xr[4 + b], xi[4 + b]);
          cmul(wr[0], wi[0], wr[0], wi[0], wr[1], wi[1]); cmul(wr[1], wi[1], wr[0], wi[0], wr[2], wi[2]);
          cmul(wr[1], wi[1], wr[1], wi[1], wr[3], wi[3]); cmul(wr[3], wi[3], wr[3], wi[3], wr[4], wi[4]);
          cmul(wr[4], wi[4], wr[3], wi[3], wr[5], wi[5]); cmul(wr[4], wi[4], wr[4], wi[4], wr[6], wi[6]);
          cmul(wr[6], wi[6], wr[4], wi[4], wr[7], wi[7]); cmul(wr[6], wi[6], wr[6], wi[6], wr[8], wi[8]);
          uint32_t R[4], I[4], PR[4], PI[4];
          #pragma unroll
          for (int b = 0; b < 4; b++) { R[b] = packh(xr[2 * b], xr[2 * b + 1]); I[b] = packh(xi[2 * b], xi[2 * b + 1]); }
          PUT4(0, R[0], R[1], R[2], R[3]); PUT4(1, I[0], I[1], I[2], I[3]);
          #pragma unroll
          for (int i = 0; i < 3; i++) {
            const uint32_t z = packh(wr[i], wi[i]);
            #pragma unroll
            for (int b = 0; b < 4; b++) hcm2(R[b], I[b], z, PR[b], PI[b]);
            PUT4(2 * i + 2, PR[0], PR[1], PR[2], PR[3]); PUT4(2 * i + 3, PI[0], PI[1], PI[2], PI[3]);
          }
          gr[0] = hd[6]; gi[0] = hd[7];
          cmul(z1r, z1i, z1r, z1i, z2r, z2i); cmul(z2r, z2i, z2r, z2i, z4r, z4i);
          cmul(gr[0], gi[0], z1r, z1i, gr[1], gi[1]);
          cmul(gr[0], gi[0], z2r, z2i, gr[2], gi[2]); cmul(gr[1], gi[1], z2r, z2i, gr[3], gi[3]);
          #pragma unroll
          for (int b = 0; b < 4; b++) cmul(gr[b], gi[b], z4r, z4i, gr[4 + b], gi[4 + b]);
          PUT4(8, packh(gr[0], gr[1]), packh(gr[2], gr[3]), packh(gr[4], gr[5]), packh(gr[6], gr[7]));
          PUT4(9, packh(gi[0], gi[1]), packh(gi[2], gi[3]), packh(gi[4], gi[5]), packh(gi[6], gi[7]));
          {
            const uint32_t z = packh(wr[3], -wi[3]), a4r = packh(gr[0], gr[4]), a4i = packh(gi[0], gi[4]);
            hcm2(packh(gr[0], gr[2]), packh(gi[0], gi[2]), z, PR[0], PI[0]);
            hcm2(packh(gr[4], gr[6]), packh(gi[4], gi[6]), z, PR[1], PI[1]);
            hcm2(a4r, a4i, packh(wr[4], -wi[4]), PR[2], PI[2]);
            hcm2(a4r, a4i, packh(wr[5], -wi[5]), PR[3], PI[3]);
            PUT4(10, PR[0], PR[1], PR[2], PR[3]); PUT4(11, PI[0], PI[1], PI[2], PI[3]);
            float hr, hi_;
            cmul(gr[0], gi[0], wr[3], -wi[3], hr, hi_);
            const uint32_t cr = packh(gr[0], hr), ci = packh(gi[0], hi_);
            #pragma unroll
            for (int i = 0; i < 3; i++) hcm2(cr, ci, packh(wr[6 + i], -wi[6 + i]), PR[i], PI[i]);
            PUT4(12, PR[0], PR[1], PR[2], 0u); PUT4(13, PI[0], PI[1], PI[2], 0u);
          }
          fence_async();
          bar_sync(4, 128);
          wg_fence();
          #pragma unroll
          for (int s = 0; s < 8; s++) {
            const uint64_t d = dE + (s >> 2) * (BLK >> 4) + ((s >> 1) & 1) * 448 + (s & 1) * 16;
            wg_ss48_tt_h(ka, d, d + 256, s != 0);
          }
          wg_commit();
        }
        const float dsk = bf_lo(__shfl_sync(0xffffffff, pd, 8 + (it & 7)));
        head(min(it + 1, 4));
        asm volatile("{\n.reg .pred p;\nHL:\nsetp.eq.f32 p, %0, 0f46400000;\n@p bra HL;\n}" :: "f"(hd[0] + hd[2] + hd[4]));
        wg_wait<0>();
        pin<24>(ka);
        float kk[6];
        const bool up = w4 >= 2;
        #pragma unroll
        for (int n = 0; n < 3; n++) {
          sts64f(xa + n * BLK, up ? ka[12 + 4 * n] : ka[4 * n + 2], up ? ka[13 + 4 * n] : ka[4 * n + 3]);
          kk[2 * n] = up ? ka[14 + 4 * n] : ka[4 * n]; kk[2 * n + 1] = up ? ka[15 + 4 * n] : ka[4 * n + 1];
        }
        if (it) bar_sync(4, 128); else bar_sync(8, 160);
          if (it == 4 && w4 == 0) {
            mbar_wait(BAR(BR_U), 0);
            if (elect_one()) {
              mbar_expect_tx(BAR(BR_U2), 8192);
              bulk_ld(blk - 2 * BLK, g_uy + (c * 80 + r * 5 + 2) * 2048, 4096, BAR(BR_U2)); bulk_ld(blk - BLK, g_uy + (c * 80 + r * 5 + 3) * 2048, 4096, BAR(BR_U2));
            }
            __syncwarp();
          }
        #pragma unroll
        for (int n = 0; n < 3; n++) {
          uint32_t o[2]; lds64(o, xr_ + n * BLK);
          kk[2 * n] = (kk[2 * n] + __uint_as_float(o[0])) * fac; kk[2 * n + 1] = (kk[2 * n + 1] + __uint_as_float(o[1])) * fac;
        }
        if (t7 == 0) kk[0] += dsk;
        {
          const uint32_t v = pack2(kk[1], kk[0]), vh = v >> 16;
          const uint32_t u = pack2(kk[2], kk[3]), w = pack2(kk[4], kk[5]), uu = pack2(kk[2], kk[2]), us = pack2(kk[3], kk[2]);
          const uint32_t x = tq < 2 ? w : u, xh = x >> 16;
          sts32(blk + e0 + 4, v); sts16(blk + e0, vh); sts16(blk + e0 + 10, v);
          sts16(blk + e1, x); sts16(blk + e1 + 6, x); sts16(blk + e2, xh); sts16(blk + e2 + 6, xh);
          if (tq < 2) {
            const uint32_t pb = blk + e0 + 1024 + 8 * tq;
            sts32(pb + 4, uu); sts32(pb + 8, us); sts16(pb + 14, us);
            if (i2) { sts16(pb - 4, u); sts32(pb, uu); }
          }
          if (i2 == 0) {
            const uint32_t tb = blk + B_TBL;
            if (tq == 0) { sts16(tb + (16 + 256) * 4, u); sts16(tb + (T_S + 3) * 4, w); sts32(tb + (T_S + 4) * 4, pack2(kk[4], kk[4])); sts16(tb + (T_S + 5) * 4 + 2, w); }
            else { sts32(tb + 528 * 4, uu); sts32(tb + 529 * 4, uu); sts32(tb + 530 * 4, uu); sts16(tb + 531 * 4 + 2, u); sts16(tb + (T_F3 + 80 + 63) * 4, w); }
          }
        }
        if (t7 == 0) TS(49 + it);
      }
    }
    asm volatile("setmaxnreg.inc.sync.aligned.u32 136;");
    if (t7 == 0) TS(41);
    bar_sync(4, 128);
    if (t7 == 0) mbar_arrive(BAR(BR_KS));
    }
  }
  const int tid = rtid(), lane = tid & 31, g = lane >> 2, tq = lane & 3, t7 = tid & 127;
  mbar_wait(BAR(BR_EPOCH), 0);
  const unsigned epoch = lds32(sb + OFF_EPOCH);
  const uint32_t ytag = (epoch & 1u) * 0x10001u, ym = lane < 4 ? 0x10001u : 0u;
  if (EN_SSM && wg != 1) {
    mbar_wait(BAR(BR_KS), 0);
    mbar_wait(BAR(BR_U), 0);
    if (EN_ATT) mbar_wait(BAR(BR_GEMM), 0);
    if (tid == 256) TS(42);
    {
      const int pass = wg >> 1;
      const int k = pass ? w4 : 4;
      if (k & 2) mbar_wait(BAR(BR_U2), 0);
      const uint32_t blk = sb + OFF_BLK + k * BLK, tb = blk + B_TBL + (uint32_t)((g - 2 * tq) * 4);
      float acc[16][4];
      zero<64>(&acc[0][0]);
      const int kl = 16 * (lane >> 4) + 2 * (lane & 7) + ((lane >> 3) & 1);
      {
        auto ubase = [&](int sh) { const int q = kl - 2 * sh; return blk + (uint32_t)((q * 16) ^ ((q * 2) & 0x10)); };
#define LDQ(A, sh) _Pragma("unroll") for (int m = 0; m < 4; m++) load_quad(A[m], tb + (16 + 16 * (sh) + 128 * m) * 4);
#define LDB(B, ub, h) _Pragma("unroll") for (int p = 0; p < 4; p++) ldsm4(B[p], (ub) + (4 * (h) + p) * 512);
#define MLO(A, B) _Pragma("unroll") for (int m = 0; m < 4; m++) _Pragma("unroll") for (int cc = 0; cc < 8; cc++) mma16816(acc[cc + m], A[m], &B[cc >> 1][(cc & 1) * 2]);
#define MHI(A, B) _Pragma("unroll") for (int m = 0; m < 4; m++) _Pragma("unroll") for (int cc = 0; cc < 8 - m; cc++) mma16816(acc[8 + cc + m], A[m], &B[cc >> 1][(cc & 1) * 2]);
        int p_ = pass ? 0 : w4;
        const int pe = pass ? 4 : w4 + 1;
        uint32_t A[4][4], A2[4][4], Bl[4][4], Bh[4][4];
        uint32_t ub = ubase(p_ + 4);
        LDQ(A, p_ + 4) LDB(Bl, ub, 0)
        #pragma unroll 1
        for (; p_ < pe; p_++) {
          LDB(Bh, ub, 1)
          MLO(A, Bl)
          ub = ubase(p_);
          LDQ(A2, p_) LDB(Bl, ub, 0)
          MHI(A, Bh)
          LDB(Bh, ub, 1)
          load_quad(A[0], tb + (16 + 512 + 16 * (p_ & 1)) * 4); load_quad(A[1], tb + (T_S + 16 * (p_ & 1)) * 4);
          MLO(A2, Bl)
          if (p_ < 2) {
            #pragma unroll
            for (int cc = 0; cc < 8; cc++) mma16816(acc[cc + 4], A[0], &Bl[cc >> 1][(cc & 1) * 2]);
            #pragma unroll
            for (int cc = 0; cc < 4; cc++) mma16816(acc[cc + 12], A[0], &Bh[cc >> 1][(cc & 1) * 2]);
            #pragma unroll
            for (int cc = 0; cc < 8; cc++) mma16816(acc[cc + 8], A[1], &Bl[cc >> 1][(cc & 1) * 2]);
          }
          const int pn = ((p_ + 1) & 3) + 4;
          ub = ubase(pn);
          LDQ(A, pn) LDB(Bl, ub, 0)
          MHI(A2, Bh)
        }
      }
      if (t7 == 0) TS(pass ? 60 : 16);
      mbar_wait(BAR(BR_DRDY), 0);
      {
        const int ih = (lane >> 3) & 1;
        const uint32_t dl = blk + B_D + (uint32_t)(((lane >> 4) * 8 + (lane & 7)) * 16);
        const uint32_t d0_ = dl + ih * 1552, d8_ = dl + (ih ? 0 : 1536), d3_ = dl + B_D7 + ih * 1024;
        auto cls2 = [&](uint32_t da, uint32_t ta) {
          uint32_t B[6][2], A[6][4];
          #pragma unroll
          for (int e = 0; e < 6; e++) { B[e][0] = lds32v(ta + (e + 4) * 32); B[e][1] = lds32v(ta + (e + 3) * 32); }
          #pragma unroll
          for (int kk = 0; kk < 6; kk++) ldsm4t(A[kk], da + kk * 256);
          #pragma unroll
          for (int e = 0; e < 6; e++)
            #pragma unroll
            for (int kk = 0; kk < 6; kk++) if (2 * kk + e + 4 < 16) mma16816(acc[2 * kk + e + 4], A[kk], B[e]);
        };
        auto cls3 = [&](uint32_t da, uint32_t ta) {
          uint32_t B[8][2], A[4][4];
          #pragma unroll
          for (int e = 0; e < 8; e++) { B[e][0] = lds32v(ta + (e + 8) * 32); B[e][1] = lds32v(ta + (e + 7) * 32); }
          #pragma unroll
          for (int kk = 0; kk < 4; kk++) ldsm4t(A[kk], da + kk * 256);
          #pragma unroll
          for (int kk = 0; kk < 4; kk++)
            #pragma unroll
            for (int e = 0; e < 8; e++) if (2 * kk + e + 8 < 16) mma16816(acc[2 * kk + e + 8], A[kk], B[e]);
        };
        if (pass) {
          #pragma unroll 1
          for (int a = 0; a < 2; a++) {
            cls2(d0_ + a * B_D5, tb + (T_F2 + 48 * a - 32) * 4);
            cls2(d8_ + a * B_D5, tb + (T_F2 + 48 * a + 64) * 4);
            cls3(d3_ + a * 2048, tb + (T_F3 + 80 * a - 64) * 4);
          }
        } else {
          cls2(((w4 & 2) ? d8_ : d0_) + (w4 & 1) * B_D5, tb + (T_F2 + 48 * w4 - 32) * 4);
          if (w4 >= 2) cls3(d3_ + (w4 - 2) * 2048, tb + (T_F3 + 80 * (w4 - 2) - 64) * 4);
        }
      }
      if (t7 == 0) TS(pass ? 61 : 17);
      const uint32_t ya = (pass ? sb + OFF_BLK + 3 * BLK + w4 * 4096 : blk) + (uint32_t)((kl * 16) ^ ((kl * 2) & 0x10));
#define YTAG(v) (((v) & ~ym) | (ytag & ym))
#define STY(p) stsm4t(ya + (p) * 512, YTAG(pack2(acc[2 * (p)][0], acc[2 * (p)][1])), pack2(acc[2 * (p)][2], acc[2 * (p)][3]), \
                      YTAG(pack2(acc[2 * (p) + 1][0], acc[2 * (p) + 1][1])), pack2(acc[2 * (p) + 1][2], acc[2 * (p) + 1][3]))
      if (pass == 0) {
        const uint32_t xw = blk + 4096 + w4 * 4096 + lane * 16, xr = blk + 4096 + w4 * 1024 + lane * 16;
        #pragma unroll
        for (int h = 0; h < 2; h++) {
          bar_sync(2, 128);
          #pragma unroll
          for (int i = 0; i < 8; i++)
            sts128(xw + i * 512, __float_as_uint(acc[8 * h + i][0]), __float_as_uint(acc[8 * h + i][1]), __float_as_uint(acc[8 * h + i][2]), __float_as_uint(acc[8 * h + i][3]));
          bar_sync(2, 128);
          float y[8];
          #pragma unroll
          for (int i = 0; i < 8; i++) {
            uint32_t o[4]; lds128(o, xr + (i >> 1) * 4096 + (i & 1) * 512);
            #pragma unroll
            for (int e = 0; e < 4; e++) y[4 * (i & 1) + e] = i < 2 ? __uint_as_float(o[e]) : y[4 * (i & 1) + e] + __uint_as_float(o[e]);
          }
          stsm4t(ya + (4 * h + w4) * 512, YTAG(pack2(y[0], y[1])), pack2(y[2], y[3]), YTAG(pack2(y[4], y[5])), pack2(y[6], y[7]));
        }
      } else {
        fence_async();
        bar_sync(4, 128);
        if (t7 == 0) mbar_arrive(BAR(BR_KS + 1));
        #pragma unroll
        for (int p = 0; p < 8; p++) STY(p);
      }
      fence_async();
      __syncwarp();
      if (lane == 0) mbar_arrive(BAR(BR_Y + 1) - 8 * pass);
      if (t7 == 0) TS(pass ? 62 : 18);
    }
  }
  if (wg < 2) {
    if (EN_ATT) {
    float oc[40]; zero<40>(oc);
    {
      constexpr uint64_t dw0 = mkdesc(SB0, OFF_WOR, 1024, 1), da0 = mkdesc(SB0, 2048, 128, 0);
      const uint32_t ck = sb + tid * 32 + ((lane >> 2) << 2), ck2 = ck + (wg ? 0 : 16384);
      uint32_t bad = 0;
      auto tile = [&](int i, uint32_t so) {
        const uint32_t al = (uint32_t)da0 + wg * 64 + (so >> 4), wl = (uint32_t)dw0 + i * 640 - (i >> 1) * (1278 << 16);
        wg_fence();
        #pragma unroll
        for (int s = 0; s < 5; s++) wg_ss80_tb(oc, desc2(al + s * 256, da0 >> 32), desc2(wl + s * 128, dw0 >> 32), (i | s) != 0);
        wg_commit();
        bad |= (lds32(ck + so) ^ epoch) | (lds32(ck + so + 8192) ^ epoch) | (lds32(ck2 + so) ^ epoch);
      };
      if (w4 == 0) {
        if (EN_SSM) mbar_wait(BAR(BR_Y), 0);
        mbar_wait(BAR(BR_WO), 0);
      }
      bar_sync(1, 256);
      if (tid == 0) TS(9);
      tile(0, SLOT(0));
      #pragma unroll 1
      for (int i = 1; i < 8; i++) {
        mbar_wait(BAR(BR_OFULL) + 8 * i, 0);
        tile(i, SLOT(i));
        wg_wait<1>();
        if (lane == 0) mbar_arrive(BAR(BR_OEMPTY - 1) + 8 * i);
      }
      #pragma unroll 1
      for (int n = 0; n < 56; n++) {
        const int i = n & 7;
        if (i == 0) {
          uint32_t any;
          asm volatile("{\n.reg .pred p;\nsetp.ne.u32 p, %1, 0;\nbarrier.red.or.pred p, 1, 256, p;\nselp.u32 %0, 1, 0, p;\n}" : "=r"(any) : "r"(bad & 1u) : "memory");
          if (!any) break;
          bad = 0;
          FIXCNT
        }
        wg_wait<0>();
        bar_sync(1, 256);
        if (tid == 0) { mbar_expect_tx(BAR(BR_RETRY), 20480); bulk_ld(sb + SLOT(2), &g_o[(r * 8 + CHUNK(i)) * 1280], 20480, BAR(BR_RETRY)); }
        mbar_wait(BAR(BR_RETRY), n & 1);
        tile(i, SLOT(2));
      }
      wg_wait<0>();
      pin<40>(oc);
    }
    if (tid == 0) TS(10);
    {
      const int row = w4 * 16 + (lane & 15);
      const uint32_t ob = sb + OFF_BLK + 3 * BLK + wg * 10240;
      #pragma unroll
      for (int j = 0; j < 8; j += 2)
        stsm4(ob + row * 128 + (((j + (lane >> 4)) ^ (row & 7)) << 4), pack2(oc[4 * j], oc[4 * j + 1]), pack2(oc[4 * j + 2], oc[4 * j + 3]),
              pack2(oc[4 * j + 4], oc[4 * j + 5]), pack2(oc[4 * j + 6], oc[4 * j + 7]));
      stsm4(ob + 8192 + row * 32 + (lane >> 4) * 16, pack2(oc[32], oc[33]), pack2(oc[34], oc[35]), pack2(oc[36], oc[37]), pack2(oc[38], oc[39]));
      fence_async();
      bar_sync(2 + wg, 128);
      if (w4 == 0 && elect_one()) {
        tma2d_st(&prm.m[M_O64], ob, 640 + c * 64, r * 128 + wg * 64);
        tma2d_st(&prm.m[M_O16], ob + 8192, 1152 + c * 16, r * 128 + wg * 64);
        bulk_commit(); bulk_wait0_read();
        if (wg == 0) { TS(11); DUMP(0, 20); }
      }
    }
    }
  } else if (EN_SSM) {
    if (t7 == 0) DUMP(40, 64);
    #pragma unroll 1
    for (int n = 0; n < 64; n++) if (!y_transpose(sb, w4, lane, ytag)) break;
  }
  }
}

typedef CUresult (*EncFn)(CUtensorMap*, CUtensorMapDataType, cuuint32_t, void*, const cuuint64_t*, const cuuint64_t*, const cuuint32_t*,
                          const cuuint32_t*, CUtensorMapInterleave, CUtensorMapSwizzle, CUtensorMapL2promotion, CUtensorMapFloatOOBfill);
static void mkmap(EncFn enc, CUtensorMap* m, const void* base, int rank, const cuuint64_t* dims, const cuuint64_t* strides, const cuuint32_t* box, CUtensorMapSwizzle swz) {
  cuuint32_t es[5] = {1, 1, 1, 1, 1};
  enc(m, CU_TENSOR_MAP_DATA_TYPE_BFLOAT16, rank, const_cast<void*>(base), dims, strides, box, es, CU_TENSOR_MAP_INTERLEAVE_NONE, swz,
      CU_TENSOR_MAP_L2_PROMOTION_L2_128B, CU_TENSOR_MAP_FLOAT_OOB_FILL_NONE);
}

extern "C" void kernel_launch(void* const* d_in, const int* in_sizes, int n_in, void* d_out, int out_size) {
  void* fn = nullptr; cudaDriverEntryPointQueryResult qr;
  cudaGetDriverEntryPoint("cuTensorMapEncodeTiled", &fn, cudaEnableDefault, &qr);
  EncFn enc = (EncFn)fn;
  void* uy = nullptr; cudaGetSymbolAddress(&uy, g_uy);
  const cuuint64_t dx[2] = {640, 2048}, sx[1] = {1280};
  const cuuint32_t bx[2] = {64, 128}, bu[2] = {80, 128};
  const cuuint64_t dw[3] = {640, 640, 3}, sw[2] = {3840, 1280};
  const cuuint32_t br[3] = {16, 32, 3};
  const cuuint64_t dwa[4] = {64, 640, 10, 3}, swa[3] = {3840, 128, 1280}, dwb[4] = {32, 640, 20, 3}, swb[3] = {3840, 64, 1280};
  const cuuint32_t bwa[4] = {64, 32, 1, 3}, bwb[4] = {32, 32, 2, 3};
  const cuuint64_t dwo[2] = {640, 640};
  const cuuint32_t bwo[2] = {64, 80}, bo64[2] = {64, 64}, bo16[2] = {16, 64};
  const cuuint64_t dsa[2] = {2048, 1280}, ssa[1] = {4096};
  const cuuint32_t bsa[2] = {64, 80};
  const cuuint64_t dout[2] = {1280, 2048}, sout[1] = {2560};
  Params prm;
  mkmap(enc, &prm.m[M_X], d_in[7], 2, dx, sx, bx, CU_TENSOR_MAP_SWIZZLE_128B);
  mkmap(enc, &prm.m[M_W128], d_in[8], 4, dwa, swa, bwa, CU_TENSOR_MAP_SWIZZLE_128B);
  mkmap(enc, &prm.m[M_W64], d_in[8], 4, dwb, swb, bwb, CU_TENSOR_MAP_SWIZZLE_64B);
  mkmap(enc, &prm.m[M_WR], d_in[8], 3, dw, sw, br, CU_TENSOR_MAP_SWIZZLE_32B);
  mkmap(enc, &prm.m[M_U], d_in[0], 2, dx, sx, bu, CU_TENSOR_MAP_SWIZZLE_NONE);
  mkmap(enc, &prm.m[M_WO], d_in[9], 2, dwo, sx, bwo, CU_TENSOR_MAP_SWIZZLE_128B);
  mkmap(enc, &prm.m[M_O64], d_out, 2, dout, sout, bo64, CU_TENSOR_MAP_SWIZZLE_128B);
  mkmap(enc, &prm.m[M_O16], d_out, 2, dout, sout, bo16, CU_TENSOR_MAP_SWIZZLE_NONE);
  mkmap(enc, &prm.m[M_SA], uy, 2, dsa, ssa, bsa, CU_TENSOR_MAP_SWIZZLE_128B);
  mkmap(enc, &prm.m[M_OUT], d_out, 2, dout, sout, bu, CU_TENSOR_MAP_SWIZZLE_NONE);
  prm.u = (const __nv_bfloat16*)d_in[0]; prm.wo = (const __nv_bfloat16*)d_in[9];
  for (int i = 0; i < 4; i++) prm.par[i] = (const __nv_bfloat16*)d_in[1 + i];
  prm.logdt = (const __nv_bfloat16*)d_in[5]; prm.dskip = (const __nv_bfloat16*)d_in[6];
  cudaFuncSetAttribute(fused_kernel, cudaFuncAttributeMaxDynamicSharedMemorySize, SMEM_BYTES);
  fused_kernel<<<128, 512, SMEM_BYTES, cudaStreamPerThread>>>(prm);
}
```

```cpp
#include <cuda_runtime.h>
#include <cuda_bf16.h>
#include <cuda_fp16.h>
#include <cuda.h>
#include <stdint.h>

#define EN_ATT 1
#define EN_SSM 1

__device__ __align__(1024) __nv_bfloat16 g_uy[2 * 640 * 2048];
__device__ __align__(128) uint4 g_kvp[8 * 16 * 240];
__device__ __align__(128) uint4 g_o[128 * 1280];
__device__ __align__(128) unsigned g_flag[4 * 128 * 32];
__device__ unsigned g_epoch[128];
#define TS(i) do {} while (0)
#define DUMP(lo, hi) do {} while (0)
#define FIXCNT

constexpr uint32_t SB0 = 1024;
constexpr uint32_t W_SLOT = 15360, OFF_X = 76800;
constexpr uint32_t OFF_WOR = 81920, OFF_KVP = 10240, OFF_KVS = 71680, OFF_PK = 10240, OFF_V = 30720, OFF_EXTRA = 102400, OFF_KVB = OFF_WOR;
constexpr uint32_t OFF_BAR = 125952, OFF_BLK = 128000, BLK = 20480;
constexpr uint32_t B_D = 4096, B_D5 = 3088, B_D7 = 6176, B_D9 = 8224, B_TBL = 14400;
constexpr int T_S = 576, T_F2 = 624, T_F3 = 816;
constexpr uint32_t OFF_UT = OFF_BLK + 4 * BLK;
constexpr uint32_t SMEM_BYTES = OFF_BLK + 5 * BLK;
enum { BR_FULL = 0, BR_WO = 5, BR_PUB = 6, BR_KVP = 7, BR_U = 8, BR_U2 = 9, BR_GEMM = 10, BR_UIN = 11, BR_YIN = 12, BR_EPOCH = 13,
       BR_FREE = 14, BR_RETRY = 16, BR_KS = 17, BR_UOUT = 19, BR_OFULL = 19  , BR_EMPTY = 27, BR_OEMPTY = 32, BR_OSTG = 39,
       BR_Y = 40, BR_DRDY = 42, BR_COUNT = 44 };
constexpr uint32_t OFF_EPOCH = OFF_BAR + 8 * BR_COUNT;
enum { M_X, M_W128, M_W64, M_WR, M_U, M_WO, M_O64, M_O16, M_SA, M_OUT, M_COUNT };

__device__ __forceinline__ long long clk64() { long long t; asm volatile("mov.u64 %0, %%clock64;" : "=l"(t) :: "memory"); return t; }
__device__ __forceinline__ uint32_t smem_u32(const void* p) { return (uint32_t)__cvta_generic_to_shared(p); }
__host__ __device__ constexpr uint64_t mkdesc(uint32_t addr, uint32_t lbo, uint32_t sbo, uint32_t swz) {
  return (uint64_t)((addr & 0x3FFFF) >> 4) | ((uint64_t)(lbo >> 4) << 16) | ((uint64_t)(sbo >> 4) << 32) | ((uint64_t)swz << 62);
}
__device__ __forceinline__ uint64_t desc2(uint32_t lo, uint32_t hi) { uint64_t d; asm("mov.b64 %0, {%1, %2};" : "=l"(d) : "r"(lo), "r"(hi)); return d; }
__device__ __forceinline__ void mbar_init(uint32_t bar, uint32_t cnt) { asm volatile("mbarrier.init.shared::cta.b64 [%0], %1;" :: "r"(bar), "r"(cnt) : "memory"); }
__device__ __forceinline__ void mbar_expect_tx(uint32_t bar, uint32_t bytes) { asm volatile("mbarrier.arrive.expect_tx.shared::cta.b64 _, [%0], %1;" :: "r"(bar), "r"(bytes) : "memory"); }
__device__ __forceinline__ void mbar_arrive(uint32_t bar) { asm volatile("mbarrier.arrive.shared::cta.b64 _, [%0];" :: "r"(bar) : "memory"); }
__device__ __forceinline__ void mbar_wait(uint32_t bar, uint32_t parity) {
  asm volatile("{\n.reg .pred p;\n.reg .u32 c;\nmov.u32 c, 0;\n"
    "WL:\nmbarrier.try_wait.parity.shared::cta.b64 p, [%0], %1;\n@p bra WD;\n"
    "add.u32 c, c, 1;\nsetp.lt.u32 p, c, 200000;\n@p bra WL;\nWD:\n}" :: "r"(bar), "r"(parity) : "memory");
}
__device__ __forceinline__ void poll_all(const unsigned* p, unsigned val) {
  asm volatile("{\n.reg .pred p;\n.reg .u32 c, v;\nmov.u32 c, 0;\n"
    "PL:\nld.relaxed.gpu.global.u32 v, [%0];\nsetp.eq.u32 p, v, %1;\nvote.sync.all.pred p, p, 0xffffffff;\n@p bra PD;\n"
    "add.u32 c, c, 1;\nsetp.lt.u32 p, c, 100000;\n@p bra PL;\nPD:\n}" :: "l"(p), "r"(val) : "memory");
}
__device__ __forceinline__ void poll_all_acq(const unsigned* p, unsigned val) {
  asm volatile("{\n.reg .pred p;\n.reg .u32 c, v;\nmov.u32 c, 0;\n"
    "PL:\nld.acquire.gpu.global.u32 v, [%0];\nsetp.eq.u32 p, v, %1;\nvote.sync.all.pred p, p, 0xffffffff;\n@p bra PD;\n"
    "nanosleep.u32 300;\nadd.u32 c, c, 1;\nsetp.lt.u32 p, c, 100000;\n@p bra PL;\nPD:\n}" :: "l"(p), "r"(val) : "memory");
}
__device__ __forceinline__ unsigned poll_bit(const unsigned* p, unsigned val, unsigned mask) {
  unsigned bal;
  asm volatile("{\n.reg .pred p;\n.reg .u32 c, v;\nmov.u32 c, 0;\n"
    "PL:\nld.relaxed.gpu.global.u32 v, [%1];\nsetp.eq.u32 p, v, %2;\nvote.sync.ballot.b32 %0, p, 0xffffffff;\n"
    "and.b32 v, %0, %3;\nsetp.ne.u32 p, v, 0;\n@p bra PD;\n"
    "add.u32 c, c, 1;\nsetp.lt.u32 p, c, 100000;\n@p bra PL;\nPD:\n}" : "=&r"(bal) : "l"(p), "r"(val), "r"(mask) : "memory");
  return bal;
}
__device__ __forceinline__ void fix128_w3(uint32_t* v, const void* p, uint32_t tag, uint32_t mask) {
  asm volatile("{\n.reg .pred p;\n.reg .u32 c, x;\n.reg .b128 t;\n.reg .b64 lo, hi;\nmov.u32 c, 0;\n"
    "FL:\nxor.b32 x, %3, %5;\nand.b32 x, x, %6;\nsetp.eq.u32 p, x, 0;\n@p bra FD;\n"
    "ld.relaxed.gpu.global.b128 t, [%4];\nmov.b128 {lo, hi}, t;\nmov.b64 {%0, %1}, lo;\nmov.b64 {%2, %3}, hi;\n"
    "add.u32 c, c, 1;\nsetp.lt.u32 p, c, 100000;\n@p bra FL;\nFD:\n}"
    : "+r"(v[0]), "+r"(v[1]), "+r"(v[2]), "+r"(v[3]) : "l"(p), "r"(tag), "r"(mask) : "memory");
}
__device__ __forceinline__ bool elect_one() {
  uint32_t p; asm volatile("{\n.reg .pred P;\nelect.sync _|P, 0xffffffff;\nselp.u32 %0, 1, 0, P;\n}" : "=r"(p)); return p;
}
__device__ __forceinline__ void bar_sync(int id, int n) { asm volatile("bar.sync %0, %1;" :: "r"(id), "r"(n) : "memory"); }
__device__ __forceinline__ void fence_async() { asm volatile("fence.proxy.async.shared::cta;" ::: "memory"); }
__device__ __forceinline__ void fence_async_g() { asm volatile("fence.proxy.async.global;" ::: "memory"); }
__device__ __forceinline__ void tma2d(uint32_t dst, const CUtensorMap* m, uint32_t bar, int c0, int c1) {
  asm volatile("cp.async.bulk.tensor.2d.shared::cluster.global.mbarrier::complete_tx::bytes [%0], [%1, {%3, %4}], [%2];"
    :: "r"(dst), "l"(m), "r"(bar), "r"(c0), "r"(c1) : "memory");
}
__device__ __forceinline__ void tma3d(uint32_t dst, const CUtensorMap* m, uint32_t bar, int c0, int c1, int c2) {
  asm volatile("cp.async.bulk.tensor.3d.shared::cluster.global.mbarrier::complete_tx::bytes [%0], [%1, {%3, %4, %5}], [%2];"
    :: "r"(dst), "l"(m), "r"(bar), "r"(c0), "r"(c1), "r"(c2) : "memory");
}
__device__ __forceinline__ void tma4d(uint32_t dst, const CUtensorMap* m, uint32_t bar, int c0, int c1, int c2, int c3) {
  asm volatile("cp.async.bulk.tensor.4d.shared::cluster.global.mbarrier::complete_tx::bytes [%0], [%1, {%3, %4, %5, %6}], [%2];"
    :: "r"(dst), "l"(m), "r"(bar), "r"(c0), "r"(c1), "r"(c2), "r"(c3) : "memory");
}
__device__ __forceinline__ void tma2d_st(const CUtensorMap* m, uint32_t src, int c0, int c1) {
  asm volatile("cp.async.bulk.tensor.2d.global.shared::cta.bulk_group [%0, {%2, %3}], [%1];"
    :: "l"(m), "r"(src), "r"(c0), "r"(c1) : "memory");
}
__device__ __forceinline__ void bulk_ld(uint32_t dst, const void* src, uint32_t bytes, uint32_t bar) {
  asm volatile("cp.async.bulk.shared::cluster.global.mbarrier::complete_tx::bytes [%0], [%1], %2, [%3];"
    :: "r"(dst), "l"(src), "r"(bytes), "r"(bar) : "memory");
}
__device__ __forceinline__ void bulk_st(void* dst, uint32_t src, uint32_t bytes) {
  asm volatile("cp.async.bulk.global.shared::cta.bulk_group [%0], [%1], %2;" :: "l"(dst), "r"(src), "r"(bytes) : "memory");
}
__device__ __forceinline__ void bulk_commit() { asm volatile("cp.async.bulk.commit_group;" ::: "memory"); }
__device__ __forceinline__ void bulk_wait0() { asm volatile("cp.async.bulk.wait_group 0;" ::: "memory"); }
__device__ __forceinline__ void bulk_wait0_read() { asm volatile("cp.async.bulk.wait_group.read 0;" ::: "memory"); }
__device__ __forceinline__ unsigned ld_rlx(const unsigned* p) { unsigned v; asm volatile("ld.relaxed.gpu.global.u32 %0, [%1];" : "=r"(v) : "l"(p) : "memory"); return v; }
__device__ __forceinline__ unsigned ld_acq(const unsigned* p) { unsigned v; asm volatile("ld.acquire.gpu.global.u32 %0, [%1];" : "=r"(v) : "l"(p) : "memory"); return v; }
__device__ __forceinline__ void st_rlx(unsigned* p, unsigned v) { asm volatile("st.relaxed.gpu.global.u32 [%0], %1;" :: "l"(p), "r"(v) : "memory"); }
__device__ __forceinline__ void st_rel(unsigned* p, unsigned v) { asm volatile("st.release.gpu.global.u32 [%0], %1;" :: "l"(p), "r"(v) : "memory"); }
__device__ __forceinline__ void st128_rlx(void* p, const uint32_t* v) {
  asm volatile("{\n.reg .b128 t;\n.reg .b64 lo, hi;\nmov.b64 lo, {%1, %2};\nmov.b64 hi, {%3, %4};\nmov.b128 t, {lo, hi};\n"
    "st.relaxed.gpu.global.b128 [%0], t;\n}" :: "l"(p), "r"(v[0]), "r"(v[1]), "r"(v[2]), "r"(v[3]) : "memory");
}
__device__ __forceinline__ uint32_t lds32(uint32_t a) { uint32_t v; asm volatile("ld.shared.u32 %0, [%1];" : "=r"(v) : "r"(a) : "memory"); return v; }
__device__ __forceinline__ uint32_t lds32v(uint32_t a) { uint32_t v; asm volatile("ld.volatile.shared.u32 %0, [%1];" : "=r"(v) : "r"(a) : "memory"); return v; }
__device__ __forceinline__ void lds128(uint32_t* v, uint32_t a) { asm volatile("ld.shared.v4.u32 {%0,%1,%2,%3}, [%4];" : "=r"(v[0]), "=r"(v[1]), "=r"(v[2]), "=r"(v[3]) : "r"(a) : "memory"); }
__device__ __forceinline__ void sts32(uint32_t a, uint32_t v) { asm volatile("st.shared.u32 [%0], %1;" :: "r"(a), "r"(v) : "memory"); }
__device__ __forceinline__ void sts16(uint32_t a, uint32_t v) { asm volatile("st.shared.u16 [%0], %1;" :: "r"(a), "h"((uint16_t)v) : "memory"); }
__device__ __forceinline__ void sts64f(uint32_t a, float x, float y) { asm volatile("st.shared.v2.f32 [%0], {%1,%2};" :: "r"(a), "f"(x), "f"(y) : "memory"); }
__device__ __forceinline__ void sts128(uint32_t a, uint32_t x, uint32_t y, uint32_t z, uint32_t w) { asm volatile("st.shared.v4.u32 [%0], {%1,%2,%3,%4};" :: "r"(a), "r"(x), "r"(y), "r"(z), "r"(w) : "memory"); }
__device__ __forceinline__ void stsm4(uint32_t a, uint32_t r0, uint32_t r1, uint32_t r2, uint32_t r3) {
  asm volatile("stmatrix.sync.aligned.m8n8.x4.shared.b16 [%0], {%1,%2,%3,%4};" :: "r"(a), "r"(r0), "r"(r1), "r"(r2), "r"(r3) : "memory");
}
__device__ __forceinline__ void stsm4t(uint32_t a, uint32_t r0, uint32_t r1, uint32_t r2, uint32_t r3) {
  asm volatile("stmatrix.sync.aligned.m8n8.x4.trans.shared.b16 [%0], {%1,%2,%3,%4};" :: "r"(a), "r"(r0), "r"(r1), "r"(r2), "r"(r3) : "memory");
}
__device__ __forceinline__ void ldsm4t(uint32_t* r, uint32_t a) {
  asm volatile("ldmatrix.sync.aligned.m8n8.x4.trans.shared.b16 {%0,%1,%2,%3}, [%4];" : "=r"(r[0]), "=r"(r[1]), "=r"(r[2]), "=r"(r[3]) : "r"(a) : "memory");
}
__device__ __forceinline__ void ldsm4(uint32_t* r, uint32_t a) {
  asm volatile("ldmatrix.sync.aligned.m8n8.x4.shared.b16 {%0,%1,%2,%3}, [%4];" : "=r"(r[0]), "=r"(r[1]), "=r"(r[2]), "=r"(r[3]) : "r"(a) : "memory");
}
__device__ __forceinline__ void mma16816(float* d, const uint32_t* a, const uint32_t* b) {
  asm volatile("mma.sync.aligned.m16n8k16.row.col.f32.bf16.bf16.f32 {%0,%1,%2,%3}, {%4,%5,%6,%7}, {%8,%9}, {%0,%1,%2,%3};"
    : "+f"(d[0]), "+f"(d[1]), "+f"(d[2]), "+f"(d[3]) : "r"(a[0]), "r"(a[1]), "r"(a[2]), "r"(a[3]), "r"(b[0]), "r"(b[1]));
}
__device__ __forceinline__ uint32_t pack2(float lo, float hi) { uint32_t r; asm("cvt.rn.bf16x2.f32 %0, %1, %2;" : "=r"(r) : "f"(hi), "f"(lo)); return r; }
__device__ __forceinline__ uint32_t packh(float lo, float hi) { uint32_t r; asm("cvt.rn.f16x2.f32 %0, %1, %2;" : "=r"(r) : "f"(hi), "f"(lo)); return r; }
__device__ __forceinline__ void hcm2(uint32_t xr, uint32_t xi, uint32_t z, uint32_t& pr, uint32_t& pi) {
  const __half2 a = *reinterpret_cast<__half2*>(&xr), b = *reinterpret_cast<__half2*>(&xi), zz = *reinterpret_cast<__half2*>(&z);
  const __half2 re = __hfma2(__hneg2(b), __high2half2(zz), __hmul2(a, __low2half2(zz)));
  const __half2 im = __hfma2(a, __high2half2(zz), __hmul2(b, __low2half2(zz)));
  pr = *reinterpret_cast<const uint32_t*>(&re); pi = *reinterpret_cast<const uint32_t*>(&im);
}
__device__ __forceinline__ void lds64(uint32_t* v, uint32_t a) { asm volatile("ld.shared.v2.u32 {%0,%1}, [%2];" : "=r"(v[0]), "=r"(v[1]) : "r"(a) : "memory"); }
__device__ __forceinline__ float bf_lo(uint32_t v) { return __uint_as_float(v << 16); }
__device__ __forceinline__ float bf_hi(uint32_t v) { return __uint_as_float(v & 0xffff0000u); }
__device__ __forceinline__ float bf_round(float x) { return bf_lo(pack2(x, 0.f)); }
__device__ __forceinline__ float ex2(float x) { float r; asm("ex2.approx.ftz.f32 %0, %1;" : "=f"(r) : "f"(x)); return r; }
__device__ __forceinline__ float phi(float t, float l2e = 1.44269504089f) {
  float e = ex2(t * l2e) + 1e-6f;
  asm("{\n.reg .pred p;\nsetp.gt.f32 p, %1, 0f00000000;\n@p add.f32 %0, %1, 0f3F800008;\n}" : "+f"(e) : "f"(t));
  return e;
}
__device__ __forceinline__ void wg_fence() { asm volatile("wgmma.fence.sync.aligned;" ::: "memory"); }
__device__ __forceinline__ void wg_commit() { asm volatile("wgmma.commit_group.sync.aligned;" ::: "memory"); }
template <int N> __device__ __forceinline__ void wg_wait() { asm volatile("wgmma.wait_group.sync.aligned %0;" :: "n"(N) : "memory"); }
template <int N> __device__ __forceinline__ void pin(float* a) {
  #pragma unroll
  for (int i = 0; i < N; i++) asm volatile("" : "+f"(a[i]) :: "memory");
}
__device__ __forceinline__ int rtid() { int t; asm volatile("mov.u32 %0, %%tid.x;" : "=r"(t)); return t; }
template <int N> __device__ __forceinline__ void zero(float* a) {
  #pragma unroll
  for (int i = 0; i < N; i++) asm volatile("mov.b32 %0, 0;" : "=f"(a[i]));
}
__device__ __forceinline__ void cexp_t(float lg2mag, float turns, float& re, float& im) {
  float m = ex2(lg2mag);
  float fr = (turns - __fadd_rn(__fadd_rn(turns, 12582912.f), -12582912.f)) * 6.283185307f;
  re = m * __cosf(fr); im = m * __sinf(fr);
}
__device__ __forceinline__ void cmul(float ar, float ai, float br, float bi, float& cr, float& ci) {
  cr = fmaf(ar, br, -ai * bi); ci = fmaf(ar, bi, ai * br);
}

__device__ __forceinline__ void wg_ss48_tt(float* d, uint64_t da, uint64_t db, int scale_d) {
  asm volatile("{\n.reg .pred p;\nsetp.ne.b32 p, %26, 0;\n"
    "wgmma.mma_async.sync.aligned.m64n48k16.f32.bf16.bf16 "
    "{%0, %1, %2, %3, %4, %5, %6, %7, %8, %9, %10, %11, %12, %13, %14, %15, %16, %17, %18, %19, %20, %21, %22, %23}, %24, %25, p, 1, 1, 1, 1;\n}\n"
    : "+f"(d[0]), "+f"(d[1]), "+f"(d[2]), "+f"(d[3]), "+f"(d[4]), "+f"(d[5]), "+f"(d[6]), "+f"(d[7]), "+f"(d[8]), "+f"(d[9]), "+f"(d[10]), "+f"(d[11]), "+f"(d[12]), "+f"(d[13]), "+f"(d[14]), "+f"(d[15]), "+f"(d[16]), "+f"(d[17]), "+f"(d[18]), "+f"(d[19]), "+f"(d[20]), "+f"(d[21]), "+f"(d[22]), "+f"(d[23])
    : "l"(da), "l"(db), "r"(scale_d));
}
__device__ __forceinline__ void wg_rs88_tb(float* d, const uint32_t* a, uint64_t db, int scale_d) {
  asm volatile("{\n.reg .pred p;\nsetp.ne.b32 p, %49, 0;\n"
    "wgmma.mma_async.sync.aligned.m64n88k16.f32.bf16.bf16 "
    "{%0, %1, %2, %3, %4, %5, %6, %7, %8, %9, %10, %11, %12, %13, %14, %15, %16, %17, %18, %19, %20, %21, %22, %23, %24, %25, %26, %27, %28, %29, %30, %31, %32, %33, %34, %35, %36, %37, %38, %39, %40, %41, %42, %43}, {%44, %45, %46, %47}, %48, p, 1, 1, 1;\n}\n"
    : "+f"(d[0]), "+f"(d[1]), "+f"(d[2]), "+f"(d[3]), "+f"(d[4]), "+f"(d[5]), "+f"(d[6]), "+f"(d[7]), "+f"(d[8]), "+f"(d[9]), "+f"(d[10]), "+f"(d[11]), "+f"(d[12]), "+f"(d[13]), "+f"(d[14]), "+f"(d[15]), "+f"(d[16]), "+f"(d[17]), "+f"(d[18]), "+f"(d[19]), "+f"(d[20]), "+f"(d[21]), "+f"(d[22]), "+f"(d[23]), "+f"(d[24]), "+f"(d[25]), "+f"(d[26]), "+f"(d[27]), "+f"(d[28]), "+f"(d[29]), "+f"(d[30]), "+f"(d[31]), "+f"(d[32]), "+f"(d[33]), "+f"(d[34]), "+f"(d[35]), "+f"(d[36]), "+f"(d[37]), "+f"(d[38]), "+f"(d[39]), "+f"(d[40]), "+f"(d[41]), "+f"(d[42]), "+f"(d[43])
    : "r"(a[0]), "r"(a[1]), "r"(a[2]), "r"(a[3]), "l"(db), "r"(scale_d));
}
__device__ __forceinline__ void wg_ss80_tb(float* d, uint64_t da, uint64_t db, int scale_d) {
  asm volatile("{\n.reg .pred p;\nsetp.ne.b32 p, %42, 0;\n"
    "wgmma.mma_async.sync.aligned.m64n80k16.f32.bf16.bf16 "
    "{%0, %1, %2, %3, %4, %5, %6, %7, %8, %9, %10, %11, %12, %13, %14, %15, %16, %17, %18, %19, %20, %21, %22, %23, %24, %25, %26, %27, %28, %29, %30, %31, %32, %33, %34, %35, %36, %37, %38, %39}, %40, %41, p, 1, 1, 0, 1;\n}\n"
    : "+f"(d[0]), "+f"(d[1]), "+f"(d[2]), "+f"(d[3]), "+f"(d[4]), "+f"(d[5]), "+f"(d[6]), "+f"(d[7]), "+f"(d[8]), "+f"(d[9]), "+f"(d[10]), "+f"(d[11]), "+f"(d[12]), "+f"(d[13]), "+f"(d[14]), "+f"(d[15]), "+f"(d[16]), "+f"(d[17]), "+f"(d[18]), "+f"(d[19]), "+f"(d[20]), "+f"(d[21]), "+f"(d[22]), "+f"(d[23]), "+f"(d[24]), "+f"(d[25]), "+f"(d[26]), "+f"(d[27]), "+f"(d[28]), "+f"(d[29]), "+f"(d[30]), "+f"(d[31]), "+f"(d[32]), "+f"(d[33]), "+f"(d[34]), "+f"(d[35]), "+f"(d[36]), "+f"(d[37]), "+f"(d[38]), "+f"(d[39])
    : "l"(da), "l"(db), "r"(scale_d));
}
__device__ __forceinline__ void wg_ss48_tt_h(float* d, uint64_t da, uint64_t db, int scale_d) {
  asm volatile("{\n.reg .pred p;\nsetp.ne.b32 p, %26, 0;\n"
    "wgmma.mma_async.sync.aligned.m64n48k16.f32.f16.f16 "
    "{%0, %1, %2, %3, %4, %5, %6, %7, %8, %9, %10, %11, %12, %13, %14, %15, %16, %17, %18, %19, %20, %21, %22, %23}, %24, %25, p, 1, 1, 1, 1;\n}\n"
    : "+f"(d[0]), "+f"(d[1]), "+f"(d[2]), "+f"(d[3]), "+f"(d[4]), "+f"(d[5]), "+f"(d[6]), "+f"(d[7]), "+f"(d[8]), "+f"(d[9]), "+f"(d[10]), "+f"(d[11]), "+f"(d[12]), "+f"(d[13]), "+f"(d[14]), "+f"(d[15]), "+f"(d[16]), "+f"(d[17]), "+f"(d[18]), "+f"(d[19]), "+f"(d[20]), "+f"(d[21]), "+f"(d[22]), "+f"(d[23])
    : "l"(da), "l"(db), "r"(scale_d));
}
__device__ __forceinline__ void wg_rs192_tb(float* d, const uint32_t* a, uint64_t db, int scale_d) {
  asm volatile("{\n.reg .pred p;\nsetp.ne.b32 p, %101, 0;\n"
    "wgmma.mma_async.sync.aligned.m64n192k16.f32.bf16.bf16 "
    "{%0, %1, %2, %3, %4, %5, %6, %7, %8, %9, %10, %11, %12, %13, %14, %15, %16, %17, %18, %19, %20, %21, %22, %23, %24, %25, %26, %27, %28, %29, %30, %31, %32, %33, %34, %35, %36, %37, %38, %39, %40, %41, %42, %43, %44, %45, %46, %47, %48, %49, %50, %51, %52, %53, %54, %55, %56, %57, %58, %59, %60, %61, %62, %63, %64, %65, %66, %67, %68, %69, %70, %71, %72, %73, %74, %75, %76, %77, %78, %79, %80, %81, %82, %83, %84, %85, %86, %87, %88, %89, %90, %91, %92, %93, %94, %95}, {%96, %97, %98, %99}, %100, p, 1, 1, 1;\n}\n"
    : "+f"(d[0]), "+f"(d[1]), "+f"(d[2]), "+f"(d[3]), "+f"(d[4]), "+f"(d[5]), "+f"(d[6]), "+f"(d[7]), "+f"(d[8]), "+f"(d[9]), "+f"(d[10]), "+f"(d[11]), "+f"(d[12]), "+f"(d[13]), "+f"(d[14]), "+f"(d[15]), "+f"(d[16]), "+f"(d[17]), "+f"(d[18]), "+f"(d[19]), "+f"(d[20]), "+f"(d[21]), "+f"(d[22]), "+f"(d[23]), "+f"(d[24]), "+f"(d[25]), "+f"(d[26]), "+f"(d[27]), "+f"(d[28]), "+f"(d[29]), "+f"(d[30]), "+f"(d[31]), "+f"(d[32]), "+f"(d[33]), "+f"(d[34]), "+f"(d[35]), "+f"(d[36]), "+f"(d[37]), "+f"(d[38]), "+f"(d[39]), "+f"(d[40]), "+f"(d[41]), "+f"(d[42]), "+f"(d[43]), "+f"(d[44]), "+f"(d[45]), "+f"(d[46]), "+f"(d[47]), "+f"(d[48]), "+f"(d[49]), "+f"(d[50]), "+f"(d[51]), "+f"(d[52]), "+f"(d[53]), "+f"(d[54]), "+f"(d[55]), "+f"(d[56]), "+f"(d[57]), "+f"(d[58]), "+f"(d[59]), "+f"(d[60]), "+f"(d[61]), "+f"(d[62]), "+f"(d[63]), "+f"(d[64]), "+f"(d[65]), "+f"(d[66]), "+f"(d[67]), "+f"(d[68]), "+f"(d[69]), "+f"(d[70]), "+f"(d[71]), "+f"(d[72]), "+f"(d[73]), "+f"(d[74]), "+f"(d[75]), "+f"(d[76]), "+f"(d[77]), "+f"(d[78]), "+f"(d[79]), "+f"(d[80]), "+f"(d[81]), "+f"(d[82]), "+f"(d[83]), "+f"(d[84]), "+f"(d[85]), "+f"(d[86]), "+f"(d[87]), "+f"(d[88]), "+f"(d[89]), "+f"(d[90]), "+f"(d[91]), "+f"(d[92]), "+f"(d[93]), "+f"(d[94]), "+f"(d[95])
    : "r"(a[0]), "r"(a[1]), "r"(a[2]), "r"(a[3]), "l"(db), "r"(scale_d));
}
__device__ __forceinline__ void wg_rs48_tb(float* d, const uint32_t* a, uint64_t db, int scale_d) {
  asm volatile("{\n.reg .pred p;\nsetp.ne.b32 p, %29, 0;\n"
    "wgmma.mma_async.sync.aligned.m64n48k16.f32.bf16.bf16 "
    "{%0, %1, %2, %3, %4, %5, %6, %7, %8, %9, %10, %11, %12, %13, %14, %15, %16, %17, %18, %19, %20, %21, %22, %23}, {%24, %25, %26, %27}, %28, p, 1, 1, 1;\n}\n"
    : "+f"(d[0]), "+f"(d[1]), "+f"(d[2]), "+f"(d[3]), "+f"(d[4]), "+f"(d[5]), "+f"(d[6]), "+f"(d[7]), "+f"(d[8]), "+f"(d[9]), "+f"(d[10]), "+f"(d[11]), "+f"(d[12]), "+f"(d[13]), "+f"(d[14]), "+f"(d[15]), "+f"(d[16]), "+f"(d[17]), "+f"(d[18]), "+f"(d[19]), "+f"(d[20]), "+f"(d[21]), "+f"(d[22]), "+f"(d[23])
    : "r"(a[0]), "r"(a[1]), "r"(a[2]), "r"(a[3]), "l"(db), "r"(scale_d));
}

struct Params {
  const __nv_bfloat16 *par[4], *logdt, *dskip, *u, *wo;
  CUtensorMap m[M_COUNT];
};

#define CHUNK(i) ((c + (i)) & 7)
#define FLAG(kind, rr, cc) (&g_flag[((kind) * 128 + (rr) * 8 + (cc)) * 32])
#define SLOT(i) ((i) == 0 ? OFF_EXTRA : OFF_BLK - 256 + ((i) > 5 ? (i) - 6 : (i) - 1) * BLK)
__device__ __forceinline__ void load_quad(uint32_t* A, uint32_t addr) {
  A[0] = lds32v(addr); A[1] = lds32v(addr + 32); A[2] = lds32v(addr - 32); A[3] = lds32v(addr);
}

__device__ __forceinline__ bool y_transpose(uint32_t sb, int w5, int lane, uint32_t ytag) {
  const int mi = lane >> 3, rw = lane & 7;
  const uint32_t sa = sb + OFF_EXTRA + (w5 * 16 + rw) * 128 + ((mi ^ rw) << 4), da = sb + SLOT(3) + (8 * mi + rw) * 160 + w5 * 32;
  const uint32_t ym = lane < 4 ? 0x10001u : 0u;
  bar_sync(7, 160);
  uint32_t v[8][4], bad = 0;
  #pragma unroll
  for (int q = 0; q < 8; q++) ldsm4t(v[q], (sa ^ ((q & 1) * 64 + ((q >> 1) & 1) * 16)) + ((q >> 1) & 1) * 10240 + (q >> 2) * 1024);
  #pragma unroll
  for (int q = 0; q < 8; q++) {
    bad |= (v[q][0] ^ ytag) | (v[q][2] ^ ytag);
    stsm4(da + (q & 3) * 5120 + (q >> 2) * 16, v[q][0] & ~ym, v[q][1], v[q][2] & ~ym, v[q][3]);
  }
  fence_async();
  uint32_t any;
  asm volatile("{\n.reg .pred p;\nsetp.ne.u32 p, %1, 0;\nbarrier.red.or.pred p, 7, 160, p;\nselp.u32 %0, 1, 0, p;\n}" : "=r"(any) : "r"(bad & ym) : "memory");
  return any;
}

__global__ void __launch_bounds__(512, 1) fused_kernel(const __grid_constant__ Params prm) {
  extern __shared__ unsigned char smem_raw[];
  uint32_t raw[5][2], pd;
  if ((threadIdx.x >> 7) == 2) {
    const int ch = (blockIdx.x & 7) * 80 + (blockIdx.x >> 3) * 5, od = threadIdx.x & 1;
    #pragma unroll
    for (int e = 0; e < 2; e++) {
      const __nv_bfloat16* pp = prm.par[2 * e + od] + ch * 128 + (threadIdx.x & 126);
      #pragma unroll
      for (int q = 0; q < 5; q++) asm volatile("ld.global.nc.u32 %0, [%1];" : "=r"(raw[q][e]) : "l"(pp + q * 128));
    }
    asm volatile("ld.global.nc.u16 %0, [%1];" : "=r"(pd) : "l"(((threadIdx.x & 8) ? prm.dskip : prm.logdt) + ch + min(threadIdx.x & 7, 4)));
  }
  constexpr uint32_t sb = SB0;
  const int tid = threadIdx.x, lane = tid & 31;
  const int warp = __shfl_sync(0xffffffff, tid >> 5, 0), wg = warp >> 2, w4 = warp & 3;
  const int cta = blockIdx.x, r = cta >> 3, c = cta & 7;
  if (smem_u32(smem_raw) != SB0) return;
#define BAR(i) (sb + OFF_BAR + 8 * (i))
  const bool sw64 = ((c + 1) & 2) != 0;

  const CUtensorMap* mwp = &prm.m[sw64 ? M_W64 : M_W128];
  const int mcol = (c * 80 + (c & 1) * 16) >> (sw64 ? 5 : 6), rcol = c * 80 + ((c & 1) ? 0 : 64);
  if (warp == 12 && elect_one()) {
    #pragma unroll
    for (int i = 0; i < 5; i++) mbar_init(BAR(BR_FULL + i), 1);
    asm volatile("fence.mbarrier_init.release.cluster;" ::: "memory");
    if (EN_ATT) {
      mbar_expect_tx(BAR(BR_FULL), W_SLOT + 16384);
      tma4d(sb, mwp, BAR(BR_FULL), 0, 0, mcol, 0);
      tma2d(sb + OFF_X, &prm.m[M_X], BAR(BR_FULL), 0, r * 128);
      tma3d(sb + 12288, &prm.m[M_WR], BAR(BR_FULL), rcol, 0, 0);
      mbar_expect_tx(BAR(BR_FULL + 1), W_SLOT);
      tma4d(sb + W_SLOT, mwp, BAR(BR_FULL + 1), 0, 32, mcol, 0);
      tma3d(sb + W_SLOT + 12288, &prm.m[M_WR], BAR(BR_FULL + 1), rcol, 32, 0);
      TS(24);
    }
  }
  if (warp == 13 && elect_one()) {
    asm volatile("prefetch.tensormap [%0];" :: "l"(&prm.m[M_X]) : "memory");
    asm volatile("prefetch.tensormap [%0];" :: "l"(&prm.m[M_WR]) : "memory");
  }
  if (wg == 3) {
    asm volatile("setmaxnreg.dec.sync.aligned.u32 56;");
    const int tid = rtid(), lane = tid & 31;
    if (warp == 12) {
      asm volatile("bar.arrive 0, 512;" ::: "memory");
      {
        uint32_t s = 2, ph = 1, xs = 16384;
        #pragma unroll 1
        for (int kb = 2; kb < 20; kb++) {
          if (kb == 4) bar_sync(6, 128);
          if (kb >= 5) mbar_wait(BAR(BR_EMPTY) + 8 * s, ph);
          if (EN_ATT && elect_one()) {
            const uint32_t st = sb + s * W_SLOT, fb = BAR(BR_FULL) + 8 * s;
            mbar_expect_tx(fb, (kb & 1) ? W_SLOT : W_SLOT + 16384);
            if (!(kb & 1)) tma2d(sb + OFF_X + xs, &prm.m[M_X], fb, kb * 32, r * 128);
            tma4d(st, mwp, fb, 0, kb * 32, mcol, 0);
            tma3d(st + 12288, &prm.m[M_WR], fb, rcol, kb * 32, 0);
          }
          if (kb < 4 && lane == 0) TS(24 + kb);
          if (EN_SSM && kb == 4 && elect_one()) { mbar_expect_tx(BAR(BR_UIN), 20480); tma2d(sb + OFF_UT, &prm.m[M_U], BAR(BR_UIN), c * 80, r * 128); }
          if (kb == 14 && elect_one()) asm volatile("cp.async.bulk.prefetch.L2.global [%0], 6400;" :: "l"(prm.wo + cta * 3200) : "memory");
          if (!EN_ATT && kb == 4) break;
          if (++s == 5) { s = 0; ph ^= 1; }
          if (kb & 1) { xs += 16384; if (xs == 49152) xs = 0; }
        }
      }
      if (EN_ATT) {
      mbar_wait(BAR(BR_EPOCH), 0);
      const unsigned epoch = lds32(sb + OFF_EPOCH);
      const unsigned* fo = FLAG(3, r, lane & 7);
      unsigned seen = __ballot_sync(0xffffffff, ld_rlx(lane < 16 ? fo : FLAG(0, lane & 15, c)) == epoch);
      if (elect_one()) {
        mbar_expect_tx(BAR(BR_WO), 8 * 10240);
        mbar_expect_tx(BAR(BR_KVP), 61440);
      }
      mbar_wait(BAR(BR_PUB), 0);
      if ((seen >> 16) != 0xffffu) poll_all(FLAG(0, lane & 15, c), epoch);
      if (elect_one()) { TS(23); bulk_ld(sb + OFF_KVP, &g_kvp[c * 16 * 240], 61440, BAR(BR_KVP)); }
      mbar_wait(BAR(BR_OSTG), 0);
      if (elect_one()) {
        bulk_st(&g_o[cta * 1280], sb + OFF_EXTRA, 20480);
        bulk_commit();
        bulk_wait0();
        st_rlx(FLAG(3, r, c), epoch);
        mbar_arrive(BAR(BR_OEMPTY));
        TS(20);
        #pragma unroll 1
        for (int i = 0; i < 8; i++) tma2d(sb + i * 10240, &prm.m[M_WO], BAR(BR_WO), c * 64, CHUNK(i) * 80);
      }
      __syncwarp();
      #pragma unroll 1
      for (int i = 1; i < 8; i++) {
        const int src = CHUNK(i);
        if (!((seen >> src) & 1)) seen = poll_bit(fo, epoch, 1u << src);
        if (i > 5) mbar_wait(BAR(BR_OEMPTY - 5) + 8 * i, 0);
        else if (EN_SSM && i != 2 && i != 3) mbar_wait(i == 1 ? BAR(BR_KS + 1) : BAR(BR_FREE - 4) + 8 * i, 0);
        if (elect_one()) {
          mbar_expect_tx(BAR(BR_OFULL) + 8 * i, 20480);
          bulk_ld(sb + SLOT(i), &g_o[(r * 8 + src) * 1280], 20480, BAR(BR_OFULL) + 8 * i);
          if (i == 1) TS(21);
          if (i == 7) TS(22);
        }
        __syncwarp();
      }
      if (lane == 0) { DUMP(20, 30); }
      }
    } else {
      const int hw = warp - 13, ht = tid - 416;
      if (hw == 2 && elect_one()) {
        #pragma unroll
        for (int i = 5; i <= BR_DRDY; i++) mbar_init(BAR(i), i == BR_WO ? 33 : i == BR_GEMM ? 8 : i == BR_OEMPTY ? 9 : i < BR_EMPTY ? 1 : i < BR_OEMPTY ? 2 : i < BR_Y ? 8 : i < BR_DRDY ? 4 : 3);
        asm volatile("fence.mbarrier_init.release.cluster;" ::: "memory");
      }
      __syncwarp();
      asm volatile("bar.arrive 0, 512;" ::: "memory");
      if (EN_SSM && hw == 2) asm volatile("bar.arrive 8, 160;" ::: "memory");
      const unsigned epoch = hw == 0 ? ld_rlx(&g_epoch[cta]) + 1 : 0;
      bar_sync(5, 96);
      asm volatile("bar.arrive 6, 128;" ::: "memory");
      if (hw == 1 && elect_one()) {
        #pragma unroll
        for (int i = M_U; i < M_COUNT; i++) asm volatile("prefetch.tensormap [%0];" :: "l"(&prm.m[i]) : "memory");
      }
      if (ht == 0) {
        st_rlx(&g_epoch[cta], epoch);
        sts32(sb + OFF_EPOCH, epoch);
        mbar_arrive(BAR(BR_EPOCH));
      }
      if (EN_SSM) {
      const int mi = lane >> 3, rw = lane & 7, ch0 = c * 80 + r * 5;
      const bool early_u = hw == 0 && __all_sync(0xffffffff, ld_acq(FLAG(1, lane & 15, c)) == epoch);
      mbar_wait(BAR(BR_UIN), 0);
      if (ht == 0) TS(36);
      #pragma unroll 1
      for (int h = 0; h < 2; h++) {
        const uint32_t sa = sb + OFF_UT + h * 10240 + (8 * mi + rw) * 160 + hw * 16, da = sb + OFF_UT + h * 10240 + (hw * 8 + rw) * 128 + ((mi ^ rw ^ h) << 4);
        uint32_t v[8][4];
        #pragma unroll
        for (int q = 0; q < 8; q++) if (q < 6 || hw == 0) ldsm4t(v[q], sa + (q & 1) * 5120 + (q >> 1) * 48);
        bar_sync(5, 96);
        #pragma unroll
        for (int q = 0; q < 8; q++) if (q < 6 || hw == 0) stsm4((da ^ ((q & 1) * 64)) + (q >> 1) * 3072, v[q][0], v[q][1], v[q][2], v[q][3]);
      }
      fence_async();
      bar_sync(5, 96);
      if (hw == 0) {
        if (elect_one()) {
          tma2d_st(&prm.m[M_SA], sb + OFF_UT, r * 128, c * 80);
          tma2d_st(&prm.m[M_SA], sb + OFF_UT + 10240, r * 128 + 64, c * 80);
          bulk_commit(); bulk_wait0_read();
          mbar_arrive(BAR(BR_UOUT));
          TS(37);
          bulk_wait0();
          st_rel(FLAG(1, r, c), epoch);
          TS(30);
        }
        __syncwarp();
        if (!early_u) poll_all_acq(FLAG(1, lane & 15, c), epoch);
      }
      #pragma unroll 1
      for (int k = 0; k < 5; k++) {
        if (k == 0 || k == 3) {
          const int p = k != 0;
          if (hw == 0) {
            if (!p) {
              if (elect_one()) {
                fence_async_g();
                mbar_expect_tx(BAR(BR_U), 12288);
                #pragma unroll 1
                for (int q = 0; q < 3; q++) bulk_ld(sb + OFF_BLK + q * q * BLK, g_uy + (ch0 + q * q) * 2048, 4096, BAR(BR_U));
                TS(31);
              }
              __syncwarp();
            }
            mbar_wait(BAR(p ? BR_U2 : BR_U), 0);
          }
          bar_sync(5, 96);
        }
        const int l3 = (hw + k) % 3 * 32 + lane;
        const uint32_t blk = sb + OFF_BLK + ((0x32410 >> (4 * k)) & 7) * BLK, o = blk + B_D + l3 * 16;
        float P[34];
        P[0] = 0.f;
        #pragma unroll
        for (int q = 0; q < 5; q++) {
          const int ch = 2 * l3 - 3 + q;
          uint32_t v[4];
          lds128(v, blk + (uint32_t)((ch * 16) ^ ((ch * 2) & 0x10)));
          #pragma unroll
          for (int e = 0; e < 8; e++) {
            const int i = 8 * q + e - 4;
            if (i >= 0 && i < 33) P[i + 1] = P[i] + ((e & 1) ? bf_hi(v[e >> 1]) : bf_lo(v[e >> 1]));
          }
        }
#define WIN(lo, hi, e) (P[21 + (e) - (lo)] - P[20 + (e) - (hi)])
#define WIN8(lo, hi, b) pack2(WIN(lo, hi, b), WIN(lo, hi, b + 1)), pack2(WIN(lo, hi, b + 2), WIN(lo, hi, b + 3)), pack2(WIN(lo, hi, b + 4), WIN(lo, hi, b + 5)), pack2(WIN(lo, hi, b + 6), WIN(lo, hi, b + 7))
        if (l3 < 64) {
          sts128(o + B_D9, WIN8(12, 20, 0)); sts128(o + B_D9 + 1024, WIN8(12, 20, 8));
          sts128(o + B_D7, WIN8(5, 11, 0)); sts128(o + B_D7 + 1024, WIN8(5, 11, 8));
        }
        sts128(o + B_D5, WIN8(6, 10, 0)); sts128(o + B_D5 + 1552, WIN8(6, 10, 8));
        sts128(o, WIN8(3, 5, 0)); sts128(o + 1552, WIN8(3, 5, 8));
        if (l3 < 2) sts128(blk + B_D + l3 * B_D5 + 1536, 0, 0, 0, 0);
      }
      __syncwarp();
      if (lane == 0) mbar_arrive(BAR(BR_DRDY));
      if (ht == 0) TS(32);
      if (hw == 0) {
        const bool early = __all_sync(0xffffffff, ld_rlx(FLAG(2, lane & 15, c)) == epoch);
        #pragma unroll 1
        for (int p = 0; p < 2; p++) {
          mbar_wait(BAR(BR_Y) + 8 * p, 0);
          if (elect_one()) {
            bulk_st(g_uy + (640 + ch0 + 4 * p) * 2048, sb + OFF_BLK + (3 + p) * BLK, p ? 4096 : 16384);
            bulk_commit(); bulk_wait0_read();
            mbar_arrive(BAR(BR_FREE) + 8 * p);
          }
          __syncwarp();
        }
        if (elect_one()) { bulk_wait0(); st_rlx(FLAG(2, r, c), epoch); TS(33); }
        __syncwarp();
        if (!early) poll_all(FLAG(2, lane & 15, c), epoch);
        if (EN_ATT) mbar_wait(BAR(BR_OEMPTY), 0);
        #pragma unroll 1
        for (int n = 0; n < 64; n++) {
          if (elect_one()) {
            mbar_expect_tx(BAR(BR_YIN), 20480);
            tma2d(sb + OFF_EXTRA, &prm.m[M_SA], BAR(BR_YIN), r * 128, 640 + c * 80);
            tma2d(sb + OFF_EXTRA + 10240, &prm.m[M_SA], BAR(BR_YIN), r * 128 + 64, 640 + c * 80);
            TS(34);
          }
          __syncwarp();
          if (EN_ATT) mbar_wait(BAR(BR_OEMPTY + 3), 0);
          mbar_wait(BAR(BR_YIN), n & 1);
          if (lane == 0) TS(38);
          if (!y_transpose(sb, 4, lane, (epoch & 1u) * 0x10001u)) break;
          FIXCNT
        }
      if (elect_one()) {
        TS(39);
        tma2d_st(&prm.m[M_OUT], sb + SLOT(3), c * 80, r * 128);
        bulk_commit(); bulk_wait0_read();
        TS(35); DUMP(30, 40); DUMP(0, 1);
      }
      }
      }
      if (EN_ATT && hw == 1) {
        mbar_wait(BAR(BR_OSTG), 0);
      {
        uint32_t ds = sb + OFF_WOR + (lane >> 3) * 128 + (((lane & 7) ^ (lane >> 3)) << 4);
        #pragma unroll 1
        for (int h = 0; h < 2; h++) {
          const int i = (lane & 6) + h;
          const char* gs = reinterpret_cast<const char*>(prm.wo) + (size_t)((lane >> 3) + CHUNK(i) * 80) * 1280 + 1024 + c * 32 + (lane & 1) * 16;
          #pragma unroll 2
          for (int q = 0; q < 20; q++) {
            asm volatile("cp.async.cg.shared.global [%0], [%1], 16;" :: "r"(ds), "l"(gs) : "memory");
            ds = (ds + 512) ^ 64; gs += 5120;
          }
        }
      }
        asm volatile("cp.async.wait_all;" ::: "memory");
        fence_async();
        mbar_arrive(BAR(BR_WO));
      }
    }
  } else {
  if (wg < 2) {
    asm volatile("setmaxnreg.inc.sync.aligned.u32 160;");
    bar_sync(0, 512);
    if (EN_ATT) {
    float am[96], ar[24];
    {
      const bool lead = (rtid() & 127) == 0;
      constexpr uint64_t dr0 = mkdesc(SB0 + 12288, 1024, 256, 3);
      const uint64_t db0 = sw64 ? mkdesc(SB0, 2048, 512, 2) : mkdesc(SB0, 4096, 1024, 1);
      const uint32_t kst = sw64 ? 64 : 128, bh = db0 >> 32;
      uint32_t s = 0, ph = 0, xo = 0;
      const int ln = rtid() & 31;
      const uint32_t xa = sb + OFF_X + (warp * 16 + (ln & 15)) * 128 + (((ln >> 4) ^ (ln & 7)) << 4);
      uint32_t A[8];
      mbar_wait(BAR(BR_FULL), 0);
      if (lead && wg == 0) TS(1);
      ldsm4(A, xa); ldsm4(A + 4, xa ^ 32);
      wg_fence();
      wg_rs48_tb(ar, A, dr0, 0); wg_rs192_tb(am, A, db0, 0);
      wg_commit();
      #pragma unroll 1
      for (int kb = 1; kb < 20; kb++) {
        const uint32_t wp = s * (W_SLOT >> 4), eb = BAR(BR_EMPTY) + 8 * s;
        wg_fence();
        wg_rs48_tb(ar, A + 4, desc2((uint32_t)dr0 + wp + 32, dr0 >> 32), 1);
        wg_rs192_tb(am, A + 4, desc2((uint32_t)db0 + wp + kst, bh), 1);
        wg_commit();
        if (++s == 5) { s = 0; ph ^= 1; }
        if (!(kb & 1)) { xo += 16384; if (xo == 49152) xo = 0; }
        mbar_wait(BAR(BR_FULL) + 8 * s, ph);
        const uint32_t xk = (xa + xo) ^ ((kb & 1) * 64), wn = s * (W_SLOT >> 4);
        wg_wait<1>();
        ldsm4(A, xk);
        wg_fence();
        wg_rs48_tb(ar, A, desc2((uint32_t)dr0 + wn, dr0 >> 32), 1);
        wg_rs192_tb(am, A, desc2((uint32_t)db0 + wn, bh), 1);
        wg_commit();
        wg_wait<1>();
        ldsm4(A + 4, xk ^ 32);
        if (lead && kb < 16) mbar_arrive(eb);
      }
      wg_fence();
      wg_rs48_tb(ar, A + 4, dr0 + 4 * (W_SLOT >> 4) + 32, 1);
      wg_rs192_tb(am, A + 4, desc2((uint32_t)db0 + 4 * (W_SLOT >> 4) + kst, bh), 1);
      wg_commit();
      wg_wait<0>();
      if (ln == 0) mbar_arrive(BAR(BR_GEMM));
      pin<96>(am); pin<24>(ar);
    }
    const int tid = rtid(), lane = tid & 31, tq = lane & 3;
    if (tid == 0) TS(2);
#define QV(j, e) ((j) < 8 ? am[4 * (j) + (e)] : ar[4 * ((j) - 8) + (e)])
#define KV_(j, e) ((j) < 8 ? am[32 + 4 * (j) + (e)] : ar[8 + 4 * ((j) - 8) + (e)])
#define VV(j, e) ((j) < 8 ? am[64 + 4 * (j) + (e)] : ar[16 + 4 * ((j) - 8) + (e)])
    {
      bar_sync(1, 256);
      const uint32_t ro = sb + (uint32_t)((warp * 16 + (lane & 15)) * 16);
      const int l0 = 2 * (c & 1) + (lane >> 4);
      const uint32_t ones = (tq == 0) ? 0x00003f80u : 0u;
#define PV(j) pack2(VV(j, 0), VV(j, 1)), pack2(VV(j, 2), VV(j, 3))
#define PK(j) pack2(phi(KV_(j, 0)), phi(KV_(j, 1))), pack2(phi(KV_(j, 2)), phi(KV_(j, 3)))
      stsm4(ro + OFF_V + (5 + 6 * (lane >> 4)) * 2048, ones, ones, ones, ones);
      #pragma unroll
      for (int j = 0; j < 10; j += 2) {
        const int l = (j == 8 && (c & 1)) ? l0 - 2 : l0 + j;
        stsm4(ro + OFF_V + (l + (l >= 5)) * 2048, PV(j), PV(j + 1));
        stsm4(ro + OFF_PK + l * 2048, PK(j), PK(j + 1));
      }
    }
    fence_async();
    bar_sync(1, 256);
    if (tid == 0) TS(3);
    mbar_wait(BAR(BR_EPOCH), 0);
    const unsigned epoch = lds32(sb + OFF_EPOCH);
    {
      float kv[24]; zero<24>(kv);
      constexpr uint64_t da = mkdesc(SB0 + OFF_PK, 128, 2048, 0), db = mkdesc(SB0 + OFF_V, 128, 2048, 0);
      wg_fence();
      #pragma unroll
      for (int s = 0; s < 8; s++) wg_ss48_tt(kv, desc2((uint32_t)da + wg * 640 + s * 16, da >> 32), desc2((uint32_t)db + wg * 768 + s * 16, db >> 32), s != 0);
      wg_commit();
      wg_wait<0>();
      pin<24>(kv);
      if (tid == 0) TS(15);
      if (w4 < 3) {
        const uint32_t wb = sb + OFF_KVS + (wg * 3 + w4) * 1536 + (lane & 15) * 96;
        #pragma unroll
        for (int j = 0; j < 6; j += 2)
          stsm4(wb + (j + (lane >> 4)) * 16, pack2(kv[4 * j], kv[4 * j + 1]), pack2(kv[4 * j + 2], kv[4 * j + 3]),
                pack2(kv[4 * j + 4], kv[4 * j + 5]), pack2(kv[4 * j + 6], kv[4 * j + 7]));
        __syncwarp();
        const int dl = w4 * 16 + (lane & 15), hl = dl >= 20;
        uint32_t v[4], z[4];
        lds128(v, wb + (3 * hl + (lane >> 4)) * 16);
        lds64(z, wb + 32 + 8 * hl); z[2] = lds32(wb + 80); z[3] = epoch & 1u;
        if (dl < 40) {
          uint4* dst = &g_kvp[(c * 16 + r) * 240 + wg * 40 + dl];
          v[3] = (v[3] & ~1u) | z[3];
          st128_rlx(dst + (lane >> 4) * 80, v);
          if (lane < 16) st128_rlx(dst + 160, z);
        }
      }
    }
    bar_sync(1, 256);
    if (tid == 0) { st_rlx(FLAG(0, r, c), epoch); mbar_arrive(BAR(BR_PUB)); TS(4); }
    const int kvi = (tid >= 80) + (tid >= 160) + (tid >= 240), kd = tid - 80 * kvi;
    const int khd = kd / 20, kt0 = 5 * (khd >> 1) + 2 * (khd & 1);
    const uint32_t rb = sb + OFF_KVB + kd * 16;
    if (kvi < 3) {
      #pragma unroll 1
      for (int m = kvi; m < 7; m += 3) { const int q = kt0 + 3 + m; sts128(rb + (q >= 10 ? q - 10 : q) * 1280, 0, 0, 0, 0); }
    }
    uint32_t qa[20];
    {
      const float sc = 1.44269504089f + __uint_as_float(lds32(sb + OFF_EPOCH) ^ epoch);
      #pragma unroll
      for (int j = 0; j < 10; j++) { qa[2 * j] = pack2(phi(QV(j, 0), sc), phi(QV(j, 1), sc)); qa[2 * j + 1] = pack2(phi(QV(j, 2), sc), phi(QV(j, 3), sc)); }
    }
    if (tid == 0) TS(5);
    if (warp == 7) mbar_wait(BAR(BR_KVP), 0);
    bar_sync(1, 256);
    if (tid == 0) TS(6);
    if (kvi < 3) {
      float s[8];
      zero<8>(s);
      uint32_t bad = 0;
      #pragma unroll 4
      for (int i = 0; i < 16; i += 2) {
        uint32_t w[4], x[4];
        lds128(w, sb + OFF_KVP + tid * 16 + i * 3840); lds128(x, sb + OFF_KVP + tid * 16 + i * 3840 + 3840);
        bad |= (w[3] ^ epoch) | (x[3] ^ epoch);
        #pragma unroll
        for (int e = 0; e < 4; e++) {
          asm("add.rn.bf16x2 %0, %0, %1;" : "+r"(w[e]) : "r"(x[e]));
          s[2 * e] += bf_lo(w[e]); s[2 * e + 1] += bf_hi(w[e]);
        }
      }
      if (__builtin_expect(bad & 1u, 0)) {
        zero<8>(s);
        #pragma unroll 1
        for (int i = 0; i < 16; i++) {
          uint32_t w[4] = {0, 0, 0, ~epoch};
          fix128_w3(w, &g_kvp[(c * 16 + i) * 240 + tid], epoch, 1u);
          #pragma unroll
          for (int e = 0; e < 4; e++) { s[2 * e] += bf_lo(w[e]); s[2 * e + 1] += bf_hi(w[e]); }
        }
        FIXCNT
      }
      const uint32_t p0 = pack2(s[0], s[1]), p1 = pack2(s[2], s[3]), p2 = pack2(s[4], s[5]), p3 = pack2(s[6], s[7]);
      if (kvi < 2) sts128(rb + (kt0 + (khd & 1) + kvi) * 1280, p0, p1, p2, p3);
      else {
        const bool od = khd & 1;
        sts128(rb + (5 * (khd >> 1) + 2) * 1280, od ? 0u : p0, od ? 0u : p1, od ? p0 : 0u, od ? p1 : 0u);
        const uint32_t zz = (p2 & 0xffffu) << (16 * (khd & 1));
        sts128(rb + 10 * 1280, khd < 2 ? zz : 0u, khd < 2 ? 0u : zz, 0u, 0u);
      }
    }
    fence_async();
    bar_sync(1, 256);
    if (tid == 0) TS(7);
    {
      float oa[44]; zero<44>(oa);
      constexpr uint64_t db = mkdesc(SB0 + OFF_KVB, 128, 1280, 0);
      wg_fence();
      #pragma unroll
      for (int s = 0; s < 5; s++) wg_rs88_tb(oa, &qa[4 * s], desc2((uint32_t)db + ((s == 4 && (c & 1)) ? 0 : (s + (c & 1)) * 16), db >> 32), s != 0);
      wg_commit();
      wg_wait<0>();
      pin<44>(oa);
      if (tid == 0) TS(13);
      float rc[4], rd[2][4];
      #pragma unroll
      for (int e = 0; e < 4; e++) asm("rcp.approx.ftz.f32 %0, %1;" : "=f"(rc[e]) : "f"(oa[40 + e] + 1e-6f));
      #pragma unroll
      for (int h = 0; h < 4; h++) {
        rd[0][h] = __shfl_sync(0xffffffff, rc[h & 1], (lane & 28) | (h >> 1));
        rd[1][h] = __shfl_sync(0xffffffff, rc[2 + (h & 1)], (lane & 28) | (h >> 1));
      }
      #pragma unroll
      for (int j = 0; j < 10; j++) {
        #pragma unroll
        for (int h = 0; h < 2; h++) {
          float f;
          if (j == 2) f = tq < 2 ? rd[h][0] : rd[h][1];
          else if (j == 7) f = tq < 2 ? rd[h][2] : rd[h][3];
          else f = rd[h][(8 * j) / 20];
          qa[2 * j + h] = pack2(oa[4 * j + 2 * h] * f, oa[4 * j + 2 * h + 1] * f);
        }
      }
      const uint32_t m0 = (lane & 7) == ((2 * w4) & 7), m1 = (lane & 7) == 2 * w4 + 1;
      const uint32_t oa_ = sb + OFF_EXTRA + (lane >> 4) * 2048 + (warp * 16 + (lane & 15)) * 16;
#define TAG(v, m) (((v) & ~(m)) | (epoch & (m)))
      #pragma unroll
      for (int s = 0; s < 5; s++) stsm4(oa_ + s * 4096, TAG(qa[4 * s], m0), TAG(qa[4 * s + 1], m1), TAG(qa[4 * s + 2], m0), TAG(qa[4 * s + 3], m1));
    }
    fence_async();
    __syncwarp();
    if (lane == 0) mbar_arrive(BAR(BR_OSTG));
    if (tid == 0) TS(8);
    }
    asm volatile("setmaxnreg.dec.sync.aligned.u32 136;");
  } else {
    const int g = lane >> 2, tq = lane & 3, t7 = tid & 127;
    asm volatile("bar.arrive 0, 512;" ::: "memory");
    if (EN_SSM) {
    {
      #pragma unroll 1
      for (int k = 0; k < 4; k++) {
        const uint32_t z = sb + OFF_BLK + k * BLK + t7 * 16;
        sts128(z + B_TBL, 0, 0, 0, 0); sts128(z + B_TBL + 2048, 0, 0, 0, 0);
      }
      if (t7 < 80) sts128(sb + OFF_BLK + (t7 >> 4) * BLK - 256 + (t7 & 15) * 16, 0, 0, 0, 0);
      const uint32_t ea = sb + OFF_BLK + (2 + (w4 & 1)) * BLK + (lane >> 4) * 7168 + ((lane >> 3) & 1) * 256 + (lane & 7) * 16 + (w4 >> 1) * 2048;
      constexpr uint64_t dE = mkdesc(SB0 + OFF_BLK + 2 * BLK, 128, 512, 0);
      const uint32_t xa = sb + OFF_BLK + 18560 + t7 * 8, xr_ = sb + OFF_BLK + 18560 + (t7 ^ 64) * 8;
      uint32_t pr[5][2];
      #pragma unroll
      for (int q = 0; q < 5; q++) {
        #pragma unroll
        for (int e = 0; e < 2; e++) pr[q][e] = __byte_perm(raw[q][e], __shfl_xor_sync(0xffffffff, raw[q][e], 1), (lane & 1) ? 0x3276 : 0x5410);
        const uint32_t m = __reduce_max_sync(0xffffffff, max(raw[q][1] & 0x7fffu, (raw[q][1] >> 16) & 0x7fffu));
        if (lane == 0) sts32(sb + OFF_EPOCH + 64 + q * 16 + w4 * 4, m);
      }
      bar_sync(4, 128);
      if (t7 == 0) TS(40);
      const int j = (w4 & 1) * 16 + (w4 >> 1) * 8 + g, i2 = tq < 2 ? 64 * tq + j : 32 * (tq - 2) + j;
      const uint32_t e2 = B_TBL + 4 * (tq < 2 ? T_F3 + (((i2 - 1) & 1) ? 80 : 0) + ((i2 - 1) >> 1) + 16 : T_F2 + (i2 & 1) * 96 + (i2 >> 1));
      const uint32_t e1 = tq < 2 ? (i2 ? e2 - 64 : B_TBL + 4 * (T_F2 + 175)) : B_TBL + 4 * (i2 ? T_F2 + ((2 * i2 - 1) & 3) * 48 + ((2 * i2 - 1) >> 2) : 16 + 511);
      const uint32_t e0 = B_TBL + (16 + 8 * j + 2 * tq) * 4;
      const float dtl = bf_round(expf(bf_lo(pd)));
      float hd[9];
      auto head = [&](int q) {
        const uint32_t pa0 = pr[0][0], pc0 = pr[0][1];
        const float dt = __shfl_sync(0xffffffff, dtl, q);
        #pragma unroll
        for (int e = 0; e < 2; e++) { pr[0][e] = pr[1][e]; pr[1][e] = pr[2][e]; pr[2][e] = pr[3][e]; pr[3][e] = pr[4][e]; }
        uint32_t mm[4];
        lds128(mm, sb + OFF_EPOCH + 64 + q * 16);
        const uint32_t ex = min(max(max(max(mm[0], mm[1]), max(mm[2], mm[3])) >> 7, 1u), 253u);
        const float sc = __uint_as_float((254u - ex) << 23);
        const float lr = -bf_round(expf(bf_lo(pa0))) * dt * 1.44269504089f;
        const float tn = bf_hi(pa0) * dt * 0.15915494309f;
        cexp_t(lr, -tn, hd[0], hd[1]);
        cexp_t(lr * 8.f, tn * 8.f, hd[2], hd[3]);
        cexp_t(lr * 64.f, tn * 64.f, hd[4], hd[5]);
        hd[6] = bf_lo(pc0) * sc; hd[7] = -bf_hi(pc0) * sc;
        hd[8] = 2.f * dt * __uint_as_float(ex << 23);
      };
      head(0);
      #pragma unroll 1
      for (int it = 0; it < 5; it++) {
        const int k = it;
        const uint32_t blk = sb + OFF_BLK + k * BLK;
        float fac = 0.f;
        float ka[24]; zero<24>(ka);
        {
          if (it == 4) {
            mbar_wait(BAR(BR_UOUT), 0);
            sts128(sb + OFF_UT + B_TBL + t7 * 16, 0, 0, 0, 0); sts128(sb + OFF_UT + B_TBL + 2048 + t7 * 16, 0, 0, 0, 0);
          }
          const uint32_t ga = ea + 4096 - (w4 >> 1) * 512;
#define PUT4(i, a, b, c_, d) sts128(((i) < 8 ? ea + ((i) >> 1) * 512 : ga + (((i) - 8) >> 1) * 512) + ((i) & 1) * 128, a, b, c_, d)
          float z2r, z2i, z4r, z4i, xr[8], xi[8], gr[8], gi[8], wr[9], wi[9];
          const float z1r = hd[0], z1i = hd[1];
          xr[1] = hd[2]; xi[1] = hd[3]; wr[0] = hd[4]; wi[0] = hd[5];
          fac = hd[8];
          xr[0] = 1.f; xi[0] = 0.f;
          cmul(xr[1], xi[1], xr[1], xi[1], xr[2], xi[2]); cmul(xr[2], xi[2], xr[1], xi[1], xr[3], xi[3]);
          cmul(xr[2], xi[2], xr[2], xi[2], xr[4], xi[4]);
          #pragma unroll
          for (int b = 1; b < 4; b++) cmul(xr[4], xi[4], xr[b], xi[b], xr[4 + b], xi[4 + b]);
          cmul(wr[0], wi[0], wr[0], wi[0], wr[1], wi[1]); cmul(wr[1], wi[1], wr[0], wi[0], wr[2], wi[2]);
          cmul(wr[1], wi[1], wr[1], wi[1], wr[3], wi[3]); cmul(wr[3], wi[3], wr[3], wi[3], wr[4], wi[4]);
          cmul(wr[4], wi[4], wr[3], wi[3], wr[5], wi[5]); cmul(wr[4], wi[4], wr[4], wi[4], wr[6], wi[6]);
          cmul(wr[6], wi[6], wr[4], wi[4], wr[7], wi[7]); cmul(wr[6], wi[6], wr[6], wi[6], wr[8], wi[8]);
          uint32_t R[4], I[4], PR[4], PI[4];
          #pragma unroll
          for (int b = 0; b < 4; b++) { R[b] = packh(xr[2 * b], xr[2 * b + 1]); I[b] = packh(xi[2 * b], xi[2 * b + 1]); }
          PUT4(0, R[0], R[1], R[2], R[3]); PUT4(1, I[0], I[1], I[2], I[3]);
          #pragma unroll
          for (int i = 0; i < 3; i++) {
            const uint32_t z = packh(wr[i], wi[i]);
            #pragma unroll
            for (int b = 0; b < 4; b++) hcm2(R[b], I[b], z, PR[b], PI[b]);
            PUT4(2 * i + 2, PR[0], PR[1], PR[2], PR[3]); PUT4(2 * i + 3, PI[0], PI[1], PI[2], PI[3]);
          }
          gr[0] = hd[6]; gi[0] = hd[7];
          cmul(z1r, z1i, z1r, z1i, z2r, z2i); cmul(z2r, z2i, z2r, z2i, z4r, z4i);
          cmul(gr[0], gi[0], z1r, z1i, gr[1], gi[1]);
          cmul(gr[0], gi[0], z2r, z2i, gr[2], gi[2]); cmul(gr[1], gi[1], z2r, z2i, gr[3], gi[3]);
          #pragma unroll
          for (int b = 0; b < 4; b++) cmul(gr[b], gi[b], z4r, z4i, gr[4 + b], gi[4 + b]);
          PUT4(8, packh(gr[0], gr[1]), packh(gr[2], gr[3]), packh(gr[4], gr[5]), packh(gr[6], gr[7]));
          PUT4(9, packh(gi[0], gi[1]), packh(gi[2], gi[3]), packh(gi[4], gi[5]), packh(gi[6], gi[7]));
          {
            const uint32_t z = packh(wr[3], -wi[3]), a4r = packh(gr[0], gr[4]), a4i = packh(gi[0], gi[4]);
            hcm2(packh(gr[0], gr[2]), packh(gi[0], gi[2]), z, PR[0], PI[0]);
            hcm2(packh(gr[4], gr[6]), packh(gi[4], gi[6]), z, PR[1], PI[1]);
            hcm2(a4r, a4i, packh(wr[4], -wi[4]), PR[2], PI[2]);
            hcm2(a4r, a4i, packh(wr[5], -wi[5]), PR[3], PI[3]);
            PUT4(10, PR[0], PR[1], PR[2], PR[3]); PUT4(11, PI[0], PI[1], PI[2], PI[3]);
            float hr, hi_;
            cmul(gr[0], gi[0], wr[3], -wi[3], hr, hi_);
            const uint32_t cr = packh(gr[0], hr), ci = packh(gi[0], hi_);
            #pragma unroll
            for (int i = 0; i < 3; i++) hcm2(cr, ci, packh(wr[6 + i], -wi[6 + i]), PR[i], PI[i]);
            PUT4(12, PR[0], PR[1], PR[2], 0u); PUT4(13, PI[0], PI[1], PI[2], 0u);
          }
          fence_async();
          bar_sync(4, 128);
          wg_fence();
          #pragma unroll
          for (int s = 0; s < 8; s++) {
            const uint64_t d = dE + (s >> 2) * (BLK >> 4) + ((s >> 1) & 1) * 448 + (s & 1) * 16;
            wg_ss48_tt_h(ka, d, d + 256, s != 0);
          }
          wg_commit();
        }
        const float dsk = bf_lo(__shfl_sync(0xffffffff, pd, 8 + (it & 7)));
        head(min(it + 1, 4));
        asm volatile("{\n.reg .pred p;\nHL:\nsetp.eq.f32 p, %0, 0f46400000;\n@p bra HL;\n}" :: "f"(hd[0] + hd[2] + hd[4]));
        wg_wait<0>();
        pin<24>(ka);
        float kk[6];
        const bool up = w4 >= 2;
        #pragma unroll
        for (int n = 0; n < 3; n++) {
          sts64f(xa + n * BLK, up ? ka[12 + 4 * n] : ka[4 * n + 2], up ? ka[13 + 4 * n] : ka[4 * n + 3]);
          kk[2 * n] = up ? ka[14 + 4 * n] : ka[4 * n]; kk[2 * n + 1] = up ? ka[15 + 4 * n] : ka[4 * n + 1];
        }
        if (it) bar_sync(4, 128); else bar_sync(8, 160);
          if (it == 4 && w4 == 0) {
            mbar_wait(BAR(BR_U), 0);
            if (elect_one()) {
              mbar_expect_tx(BAR(BR_U2), 8192);
              bulk_ld(blk - 2 * BLK, g_uy + (c * 80 + r * 5 + 2) * 2048, 4096, BAR(BR_U2)); bulk_ld(blk - BLK, g_uy + (c * 80 + r * 5 + 3) * 2048, 4096, BAR(BR_U2));
            }
            __syncwarp();
          }
        #pragma unroll
        for (int n = 0; n < 3; n++) {
          uint32_t o[2]; lds64(o, xr_ + n * BLK);
          kk[2 * n] = (kk[2 * n] + __uint_as_float(o[0])) * fac; kk[2 * n + 1] = (kk[2 * n + 1] + __uint_as_float(o[1])) * fac;
        }
        if (t7 == 0) kk[0] += dsk;
        {
          const uint32_t v = pack2(kk[1], kk[0]), vh = v >> 16;
          const uint32_t u = pack2(kk[2], kk[3]), w = pack2(kk[4], kk[5]), uu = pack2(kk[2], kk[2]), us = pack2(kk[3], kk[2]);
          const uint32_t x = tq < 2 ? w : u, xh = x >> 16;
          sts32(blk + e0 + 4, v); sts16(blk + e0, vh); sts16(blk + e0 + 10, v);
          sts16(blk + e1, x); sts16(blk + e1 + 6, x); sts16(blk + e2, xh); sts16(blk + e2 + 6, xh);
          if (tq < 2) {
            const uint32_t pb = blk + e0 + 1024 + 8 * tq;
            sts32(pb + 4, uu); sts32(pb + 8, us); sts16(pb + 14, us);
            if (i2) { sts16(pb - 4, u); sts32(pb, uu); }
          }
          if (i2 == 0) {
            const uint32_t tb = blk + B_TBL;
            if (tq == 0) { sts16(tb + (16 + 256) * 4, u); sts16(tb + (T_S + 3) * 4, w); sts32(tb + (T_S + 4) * 4, pack2(kk[4], kk[4])); sts16(tb + (T_S + 5) * 4 + 2, w); }
            else { sts32(tb + 528 * 4, uu); sts32(tb + 529 * 4, uu); sts32(tb + 530 * 4, uu); sts16(tb + 531 * 4 + 2, u); sts16(tb + (T_F3 + 80 + 63) * 4, w); }
          }
        }
        if (t7 == 0) TS(49 + it);
      }
    }
    asm volatile("setmaxnreg.inc.sync.aligned.u32 136;");
    if (t7 == 0) TS(41);
    bar_sync(4, 128);
    if (t7 == 0) mbar_arrive(BAR(BR_KS));
    }
  }
  const int tid = rtid(), lane = tid & 31, g = lane >> 2, tq = lane & 3, t7 = tid & 127;
  mbar_wait(BAR(BR_EPOCH), 0);
  const unsigned epoch = lds32(sb + OFF_EPOCH);
  const uint32_t ytag = (epoch & 1u) * 0x10001u, ym = lane < 4 ? 0x10001u : 0u;
  if (EN_SSM && wg != 1) {
    mbar_wait(BAR(BR_KS), 0);
    mbar_wait(BAR(BR_U), 0);
    if (EN_ATT) mbar_wait(BAR(BR_GEMM), 0);
    if (tid == 256) TS(42);
    {
      const int pass = wg >> 1;
      const int k = pass ? w4 : 4;
      if (k & 2) mbar_wait(BAR(BR_U2), 0);
      const uint32_t blk = sb + OFF_BLK + k * BLK, tb = blk + B_TBL + (uint32_t)((g - 2 * tq) * 4);
      float acc[16][4];
      zero<64>(&acc[0][0]);
      const int kl = 16 * (lane >> 4) + 2 * (lane & 7) + ((lane >> 3) & 1);
      {
        auto ubase = [&](int sh) { const int q = kl - 2 * sh; return blk + (uint32_t)((q * 16) ^ ((q * 2) & 0x10)); };
#define LDQ(A, sh) _Pragma("unroll") for (int m = 0; m < 4; m++) load_quad(A[m], tb + (16 + 16 * (sh) + 128 * m) * 4);
#define LDB(B, ub, h) _Pragma("unroll") for (int p = 0; p < 4; p++) ldsm4(B[p], (ub) + (4 * (h) + p) * 512);
#define MLO(A, B) _Pragma("unroll") for (int m = 0; m < 4; m++) _Pragma("unroll") for (int cc = 0; cc < 8; cc++) mma16816(acc[cc + m], A[m], &B[cc >> 1][(cc & 1) * 2]);
#define MHI(A, B) _Pragma("unroll") for (int m = 0; m < 4; m++) _Pragma("unroll") for (int cc = 0; cc < 8 - m; cc++) mma16816(acc[8 + cc + m], A[m], &B[cc >> 1][(cc & 1) * 2]);
        int p_ = pass ? 0 : w4;
        const int pe = pass ? 4 : w4 + 1;
        uint32_t A[4][4], A2[4][4], Bl[4][4], Bh[4][4];
        uint32_t ub = ubase(p_ + 4);
        LDQ(A, p_ + 4) LDB(Bl, ub, 0)
        #pragma unroll 1
        for (; p_ < pe; p_++) {
          LDB(Bh, ub, 1)
          MLO(A, Bl)
          ub = ubase(p_);
          LDQ(A2, p_) LDB(Bl, ub, 0)
          MHI(A, Bh)
          LDB(Bh, ub, 1)
          load_quad(A[0], tb + (16 + 512 + 16 * (p_ & 1)) * 4); load_quad(A[1], tb + (T_S + 16 * (p_ & 1)) * 4);
          MLO(A2, Bl)
          if (p_ < 2) {
            #pragma unroll
            for (int cc = 0; cc < 8; cc++) mma16816(acc[cc + 4], A[0], &Bl[cc >> 1][(cc & 1) * 2]);
            #pragma unroll
            for (int cc = 0; cc < 4; cc++) mma16816(acc[cc + 12], A[0], &Bh[cc >> 1][(cc & 1) * 2]);
            #pragma unroll
            for (int cc = 0; cc < 8; cc++) mma16816(acc[cc + 8], A[1], &Bl[cc >> 1][(cc & 1) * 2]);
          }
          const int pn = ((p_ + 1) & 3) + 4;
          ub = ubase(pn);
          LDQ(A, pn) LDB(Bl, ub, 0)
          MHI(A2, Bh)
        }
      }
      if (t7 == 0) TS(pass ? 60 : 16);
      mbar_wait(BAR(BR_DRDY), 0);
      {
        const int ih = (lane >> 3) & 1;
        const uint32_t dl = blk + B_D + (uint32_t)(((lane >> 4) * 8 + (lane & 7)) * 16);
        const uint32_t d0_ = dl + ih * 1552, d8_ = dl + (ih ? 0 : 1536), d3_ = dl + B_D7 + ih * 1024;
        auto cls2 = [&](uint32_t da, uint32_t ta) {
          uint32_t B[6][2], A[6][4];
          #pragma unroll
          for (int e = 0; e < 6; e++) { B[e][0] = lds32v(ta + (e + 4) * 32); B[e][1] = lds32v(ta + (e + 3) * 32); }
          #pragma unroll
          for (int kk = 0; kk < 6; kk++) ldsm4t(A[kk], da + kk * 256);
          #pragma unroll
          for (int e = 0; e < 6; e++)
            #pragma unroll
            for (int kk = 0; kk < 6; kk++) if (2 * kk + e + 4 < 16) mma16816(acc[2 * kk + e + 4], A[kk], B[e]);
        };
        auto cls3 = [&](uint32_t da, uint32_t ta) {
          uint32_t B[8][2], A[4][4];
          #pragma unroll
          for (int e = 0; e < 8; e++) { B[e][0] = lds32v(ta + (e + 8) * 32); B[e][1] = lds32v(ta + (e + 7) * 32); }
          #pragma unroll
          for (int kk = 0; kk < 4; kk++) ldsm4t(A[kk], da + kk * 256);
          #pragma unroll
          for (int kk = 0; kk < 4; kk++)
            #pragma unroll
            for (int e = 0; e < 8; e++) if (2 * kk + e + 8 < 16) mma16816(acc[2 * kk + e + 8], A[kk], B[e]);
        };
        if (pass) {
          #pragma unroll 1
          for (int a = 0; a < 2; a++) {
            cls2(d0_ + a * B_D5, tb + (T_F2 + 48 * a - 32) * 4);
            cls2(d8_ + a * B_D5, tb + (T_F2 + 48 * a + 64) * 4);
            cls3(d3_ + a * 2048, tb + (T_F3 + 80 * a - 64) * 4);
          }
        } else {
          cls2(((w4 & 2) ? d8_ : d0_) + (w4 & 1) * B_D5, tb + (T_F2 + 48 * w4 - 32) * 4);
          if (w4 >= 2) cls3(d3_ + (w4 - 2) * 2048, tb + (T_F3 + 80 * (w4 - 2) - 64) * 4);
        }
      }
      if (t7 == 0) TS(pass ? 61 : 17);
      const uint32_t ya = (pass ? sb + OFF_BLK + 3 * BLK + w4 * 4096 : blk) + (uint32_t)((kl * 16) ^ ((kl * 2) & 0x10));
#define YTAG(v) (((v) & ~ym) | (ytag & ym))
#define STY(p) stsm4t(ya + (p) * 512, YTAG(pack2(acc[2 * (p)][0], acc[2 * (p)][1])), pack2(acc[2 * (p)][2], acc[2 * (p)][3]), \
                      YTAG(pack2(acc[2 * (p) + 1][0], acc[2 * (p) + 1][1])), pack2(acc[2 * (p) + 1][2], acc[2 * (p) + 1][3]))
      if (pass == 0) {
        const uint32_t xw = blk + 4096 + w4 * 4096 + lane * 16, xr = blk + 4096 + w4 * 1024 + lane * 16;
        #pragma unroll
        for (int h = 0; h < 2; h++) {
          bar_sync(2, 128);
          #pragma unroll
          for (int i = 0; i < 8; i++)
            sts128(xw + i * 512, __float_as_uint(acc[8 * h + i][0]), __float_as_uint(acc[8 * h + i][1]), __float_as_uint(acc[8 * h + i][2]), __float_as_uint(acc[8 * h + i][3]));
          bar_sync(2, 128);
          float y[8];
          #pragma unroll
          for (int i = 0; i < 8; i++) {
            uint32_t o[4]; lds128(o, xr + (i >> 1) * 4096 + (i & 1) * 512);
            #pragma unroll
            for (int e = 0; e < 4; e++) y[4 * (i & 1) + e] = i < 2 ? __uint_as_float(o[e]) : y[4 * (i & 1) + e] + __uint_as_float(o[e]);
          }
          stsm4t(ya + (4 * h + w4) * 512, YTAG(pack2(y[0], y[1])), pack2(y[2], y[3]), YTAG(pack2(y[4], y[5])), pack2(y[6], y[7]));
        }
      } else {
        fence_async();
        bar_sync(4, 128);
        if (t7 == 0) mbar_arrive(BAR(BR_KS + 1));
        #pragma unroll
        for (int p = 0; p < 8; p++) STY(p);
      }
      fence_async();
      __syncwarp();
      if (lane == 0) mbar_arrive(BAR(BR_Y + 1) - 8 * pass);
      if (t7 == 0) TS(pass ? 62 : 18);
    }
  }
  if (wg < 2) {
    if (EN_ATT) {
    float oc[40]; zero<40>(oc);
    {
      constexpr uint64_t dw0 = mkdesc(SB0, OFF_WOR, 1024, 1), da0 = mkdesc(SB0, 2048, 128, 0);
      const uint32_t ck = sb + tid * 32 + ((lane >> 2) << 2), ck2 = ck + (wg ? 0 : 16384);
      uint32_t bad = 0;
      auto tile = [&](int i, uint32_t so) {
        const uint32_t al = (uint32_t)da0 + wg * 64 + (so >> 4), wl = (uint32_t)dw0 + i * 640 - (i >> 1) * (1278 << 16);
        wg_fence();
        #pragma unroll
        for (int s = 0; s < 5; s++) wg_ss80_tb(oc, desc2(al + s * 256, da0 >> 32), desc2(wl + s * 128, dw0 >> 32), (i | s) != 0);
        wg_commit();
        bad |= (lds32(ck + so) ^ epoch) | (lds32(ck + so + 8192) ^ epoch) | (lds32(ck2 + so) ^ epoch);
      };
      if (w4 == 0) {
        if (EN_SSM) mbar_wait(BAR(BR_Y), 0);
        mbar_wait(BAR(BR_WO), 0);
      }
      bar_sync(1, 256);
      if (tid == 0) TS(9);
      tile(0, SLOT(0));
      #pragma unroll 1
      for (int i = 1; i < 8; i++) {
        mbar_wait(BAR(BR_OFULL) + 8 * i, 0);
        tile(i, SLOT(i));
        wg_wait<1>();
        if (lane == 0) mbar_arrive(BAR(BR_OEMPTY - 1) + 8 * i);
      }
      #pragma unroll 1
      for (int n = 0; n < 56; n++) {
        const int i = n & 7;
        if (i == 0) {
          uint32_t any;
          asm volatile("{\n.reg .pred p;\nsetp.ne.u32 p, %1, 0;\nbarrier.red.or.pred p, 1, 256, p;\nselp.u32 %0, 1, 0, p;\n}" : "=r"(any) : "r"(bad & 1u) : "memory");
          if (!any) break;
          bad = 0;
          FIXCNT
        }
        wg_wait<0>();
        bar_sync(1, 256);
        if (tid == 0) { mbar_expect_tx(BAR(BR_RETRY), 20480); bulk_ld(sb + SLOT(2), &g_o[(r * 8 + CHUNK(i)) * 1280], 20480, BAR(BR_RETRY)); }
        mbar_wait(BAR(BR_RETRY), n & 1);
        tile(i, SLOT(2));
      }
      wg_wait<0>();
      pin<40>(oc);
    }
    if (tid == 0) TS(10);
    {
      const int row = w4 * 16 + (lane & 15);
      const uint32_t ob = sb + OFF_BLK + 3 * BLK + wg * 10240;
      #pragma unroll
      for (int j = 0; j < 8; j += 2)
        stsm4(ob + row * 128 + (((j + (lane >> 4)) ^ (row & 7)) << 4), pack2(oc[4 * j], oc[4 * j + 1]), pack2(oc[4 * j + 2], oc[4 * j + 3]),
              pack2(oc[4 * j + 4], oc[4 * j + 5]), pack2(oc[4 * j + 6], oc[4 * j + 7]));
      stsm4(ob + 8192 + row * 32 + (lane >> 4) * 16, pack2(oc[32], oc[33]), pack2(oc[34], oc[35]), pack2(oc[36], oc[37]), pack2(oc[38], oc[39]));
      fence_async();
      bar_sync(2 + wg, 128);
      if (w4 == 0 && elect_one()) {
        tma2d_st(&prm.m[M_O64], ob, 640 + c * 64, r * 128 + wg * 64);
        tma2d_st(&prm.m[M_O16], ob + 8192, 1152 + c * 16, r * 128 + wg * 64);
        bulk_commit(); bulk_wait0_read();
        if (wg == 0) { TS(11); DUMP(0, 20); }
      }
    }
    }
  } else if (EN_SSM) {
    if (t7 == 0) DUMP(40, 64);
    #pragma unroll 1
    for (int n = 0; n < 64; n++) if (!y_transpose(sb, w4, lane, ytag)) break;
  }
  }
}

typedef CUresult (*EncFn)(CUtensorMap*, CUtensorMapDataType, cuuint32_t, void*, const cuuint64_t*, const cuuint64_t*, const cuuint32_t*,
                          const cuuint32_t*, CUtensorMapInterleave, CUtensorMapSwizzle, CUtensorMapL2promotion, CUtensorMapFloatOOBfill);
static void mkmap(EncFn enc, CUtensorMap* m, const void* base, int rank, const cuuint64_t* dims, const cuuint64_t* strides, const cuuint32_t* box, CUtensorMapSwizzle swz) {
  cuuint32_t es[5] = {1, 1, 1, 1, 1};
  enc(m, CU_TENSOR_MAP_DATA_TYPE_BFLOAT16, rank, const_cast<void*>(base), dims, strides, box, es, CU_TENSOR_MAP_INTERLEAVE_NONE, swz,
      CU_TENSOR_MAP_L2_PROMOTION_L2_128B, CU_TENSOR_MAP_FLOAT_OOB_FILL_NONE);
}

extern "C" void kernel_launch(void* const* d_in, const int* in_sizes, int n_in, void* d_out, int out_size) {
  void* fn = nullptr; cudaDriverEntryPointQueryResult qr;
  cudaGetDriverEntryPoint("cuTensorMapEncodeTiled", &fn, cudaEnableDefault, &qr);
  EncFn enc = (EncFn)fn;
  void* uy = nullptr; cudaGetSymbolAddress(&uy, g_uy);
  const cuuint64_t dx[2] = {640, 2048}, sx[1] = {1280};
  const cuuint32_t bx[2] = {64, 128}, bu[2] = {80, 128};
  const cuuint64_t dw[3] = {640, 640, 3}, sw[2] = {3840, 1280};
  const cuuint32_t br[3] = {16, 32, 3};
  const cuuint64_t dwa[4] = {64, 640, 10, 3}, swa[3] = {3840, 128, 1280}, dwb[4] = {32, 640, 20, 3}, swb[3] = {3840, 64, 1280};
  const cuuint32_t bwa[4] = {64, 32, 1, 3}, bwb[4] = {32, 32, 2, 3};
  const cuuint64_t dwo[2] = {640, 640};
  const cuuint32_t bwo[2] = {64, 80}, bo64[2] = {64, 64}, bo16[2] = {16, 64};
  const cuuint64_t dsa[2] = {2048, 1280}, ssa[1] = {4096};
  const cuuint32_t bsa[2] = {64, 80};
  const cuuint64_t dout[2] = {1280, 2048}, sout[1] = {2560};
  Params prm;
  mkmap(enc, &prm.m[M_X], d_in[7], 2, dx, sx, bx, CU_TENSOR_MAP_SWIZZLE_128B);
  mkmap(enc, &prm.m[M_W128], d_in[8], 4, dwa, swa, bwa, CU_TENSOR_MAP_SWIZZLE_128B);
  mkmap(enc, &prm.m[M_W64], d_in[8], 4, dwb, swb, bwb, CU_TENSOR_MAP_SWIZZLE_64B);
  mkmap(enc, &prm.m[M_WR], d_in[8], 3, dw, sw, br, CU_TENSOR_MAP_SWIZZLE_32B);
  mkmap(enc, &prm.m[M_U], d_in[0], 2, dx, sx, bu, CU_TENSOR_MAP_SWIZZLE_NONE);
  mkmap(enc, &prm.m[M_WO], d_in[9], 2, dwo, sx, bwo, CU_TENSOR_MAP_SWIZZLE_128B);
  mkmap(enc, &prm.m[M_O64], d_out, 2, dout, sout, bo64, CU_TENSOR_MAP_SWIZZLE_128B);
  mkmap(enc, &prm.m[M_O16], d_out, 2, dout, sout, bo16, CU_TENSOR_MAP_SWIZZLE_NONE);
  mkmap(enc, &prm.m[M_SA], uy, 2, dsa, ssa, bsa, CU_TENSOR_MAP_SWIZZLE_128B);
  mkmap(enc, &prm.m[M_OUT], d_out, 2, dout, sout, bu, CU_TENSOR_MAP_SWIZZLE_NONE);
  prm.u = (const __nv_bfloat16*)d_in[0]; prm.wo = (const __nv_bfloat16*)d_in[9];
  for (int i = 0; i < 4; i++) prm.par[i] = (const __nv_bfloat16*)d_in[1 + i];
  prm.logdt = (const __nv_bfloat16*)d_in[5]; prm.dskip = (const __nv_bfloat16*)d_in[6];
  cudaFuncSetAttribute(fused_kernel, cudaFuncAttributeMaxDynamicSharedMemorySize, SMEM_BYTES);
  fused_kernel<<<128, 512, SMEM_BYTES, cudaStreamPerThread>>>(prm);
}
```

```cpp
#include <cuda_runtime.h>
#include <cuda_bf16.h>
#include <cuda_fp16.h>
#include <cuda.h>
#include <stdint.h>

#define EN_ATT 1
#define EN_SSM 1

__device__ __align__(1024) __nv_bfloat16 g_uy[2 * 640 * 2048];
__device__ __align__(128) uint4 g_kvp[8 * 16 * 240];
__device__ __align__(128) uint4 g_o[128 * 1280];
__device__ __align__(128) unsigned g_flag[4 * 128 * 32];
__device__ unsigned g_epoch[128];
#define TS(i) do {} while (0)
#define DUMP(lo, hi) do {} while (0)
#define FIXCNT

constexpr uint32_t SB0 = 1024;
constexpr uint32_t W_SLOT = 15360, OFF_X = 76800;
constexpr uint32_t OFF_WOR = 81920, OFF_KVP = 10240, OFF_KVS = 71680, OFF_PK = 10240, OFF_V = 30720, OFF_EXTRA = 102400, OFF_KVB = OFF_EXTRA;
constexpr uint32_t OFF_BAR = 125952, OFF_BLK = 128000, BLK = 20480;
constexpr uint32_t B_D = 4096, B_D5 = 3088, B_D7 = 6176, B_D9 = 8224, B_TBL = 14400;
constexpr int T_S = 576, T_F2 = 624, T_F3 = 816;
constexpr uint32_t OFF_UT = OFF_BLK + 4 * BLK;
constexpr uint32_t SMEM_BYTES = OFF_BLK + 5 * BLK;
enum { BR_FULL = 0, BR_WO = 5, BR_PUB = 6, BR_KVP = 7, BR_U = 8, BR_U2 = 9, BR_GEMM = 10, BR_UIN = 11, BR_YIN = 12, BR_EPOCH = 13,
       BR_FREE = 14, BR_RETRY = 16, BR_KS = 17, BR_UOUT = 19, BR_OFULL = 19  , BR_EMPTY = 27, BR_OEMPTY = 32, BR_OSTG = 39,
       BR_Y = 40, BR_DRDY = 42, BR_COUNT = 44 };
constexpr uint32_t OFF_EPOCH = OFF_BAR + 8 * BR_COUNT;
enum { M_X, M_W128, M_W64, M_WR, M_U, M_WO, M_O64, M_O16, M_SA, M_OUT, M_COUNT };

__device__ __forceinline__ long long clk64() { long long t; asm volatile("mov.u64 %0, %%clock64;" : "=l"(t) :: "memory"); return t; }
__device__ __forceinline__ uint32_t smem_u32(const void* p) { return (uint32_t)__cvta_generic_to_shared(p); }
__host__ __device__ constexpr uint64_t mkdesc(uint32_t addr, uint32_t lbo, uint32_t sbo, uint32_t swz) {
  return (uint64_t)((addr & 0x3FFFF) >> 4) | ((uint64_t)(lbo >> 4) << 16) | ((uint64_t)(sbo >> 4) << 32) | ((uint64_t)swz << 62);
}
__device__ __forceinline__ uint64_t desc2(uint32_t lo, uint32_t hi) { uint64_t d; asm("mov.b64 %0, {%1, %2};" : "=l"(d) : "r"(lo), "r"(hi)); return d; }
__device__ __forceinline__ void mbar_init(uint32_t bar, uint32_t cnt) { asm volatile("mbarrier.init.shared::cta.b64 [%0], %1;" :: "r"(bar), "r"(cnt) : "memory"); }
__device__ __forceinline__ void mbar_expect_tx(uint32_t bar, uint32_t bytes) { asm volatile("mbarrier.arrive.expect_tx.shared::cta.b64 _, [%0], %1;" :: "r"(bar), "r"(bytes) : "memory"); }
__device__ __forceinline__ void mbar_arrive(uint32_t bar) { asm volatile("mbarrier.arrive.shared::cta.b64 _, [%0];" :: "r"(bar) : "memory"); }
__device__ __forceinline__ void mbar_wait(uint32_t bar, uint32_t parity) {
  asm volatile("{\n.reg .pred p;\n.reg .u32 c;\nmov.u32 c, 0;\n"
    "WL:\nmbarrier.try_wait.parity.shared::cta.b64 p, [%0], %1;\n@p bra WD;\n"
    "add.u32 c, c, 1;\nsetp.lt.u32 p, c, 200000;\n@p bra WL;\nWD:\n}" :: "r"(bar), "r"(parity) : "memory");
}
__device__ __forceinline__ void poll_all(const unsigned* p, unsigned val) {
  asm volatile("{\n.reg .pred p;\n.reg .u32 c, v;\nmov.u32 c, 0;\n"
    "PL:\nld.relaxed.gpu.global.u32 v, [%0];\nsetp.eq.u32 p, v, %1;\nvote.sync.all.pred p, p, 0xffffffff;\n@p bra PD;\n"
    "add.u32 c, c, 1;\nsetp.lt.u32 p, c, 100000;\n@p bra PL;\nPD:\n}" :: "l"(p), "r"(val) : "memory");
}
__device__ __forceinline__ void poll_all_acq(const unsigned* p, unsigned val) {
  asm volatile("{\n.reg .pred p;\n.reg .u32 c, v;\nmov.u32 c, 0;\n"
    "PL:\nld.acquire.gpu.global.u32 v, [%0];\nsetp.eq.u32 p, v, %1;\nvote.sync.all.pred p, p, 0xffffffff;\n@p bra PD;\n"
    "nanosleep.u32 300;\nadd.u32 c, c, 1;\nsetp.lt.u32 p, c, 100000;\n@p bra PL;\nPD:\n}" :: "l"(p), "r"(val) : "memory");
}
__device__ __forceinline__ unsigned poll_bit(const unsigned* p, unsigned val, unsigned mask) {
  unsigned bal;
  asm volatile("{\n.reg .pred p;\n.reg .u32 c, v;\nmov.u32 c, 0;\n"
    "PL:\nld.relaxed.gpu.global.u32 v, [%1];\nsetp.eq.u32 p, v, %2;\nvote.sync.ballot.b32 %0, p, 0xffffffff;\n"
    "and.b32 v, %0, %3;\nsetp.ne.u32 p, v, 0;\n@p bra PD;\n"
    "add.u32 c, c, 1;\nsetp.lt.u32 p, c, 100000;\n@p bra PL;\nPD:\n}" : "=&r"(bal) : "l"(p), "r"(val), "r"(mask) : "memory");
  return bal;
}
__device__ __forceinline__ void fix128_w3(uint32_t* v, const void* p, uint32_t tag, uint32_t mask) {
  asm volatile("{\n.reg .pred p;\n.reg .u32 c, x;\n.reg .b128 t;\n.reg .b64 lo, hi;\nmov.u32 c, 0;\n"
    "FL:\nxor.b32 x, %3, %5;\nand.b32 x, x, %6;\nsetp.eq.u32 p, x, 0;\n@p bra FD;\n"
    "ld.relaxed.gpu.global.b128 t, [%4];\nmov.b128 {lo, hi}, t;\nmov.b64 {%0, %1}, lo;\nmov.b64 {%2, %3}, hi;\n"
    "add.u32 c, c, 1;\nsetp.lt.u32 p, c, 100000;\n@p bra FL;\nFD:\n}"
    : "+r"(v[0]), "+r"(v[1]), "+r"(v[2]), "+r"(v[3]) : "l"(p), "r"(tag), "r"(mask) : "memory");
}
__device__ __forceinline__ void sched_fence(uint32_t addr, uint32_t dep) {
  asm volatile("{\n.reg .pred p;\n.reg .u32 t, d;\nmov.u32 d, %1;\n"
    "SL:\nld.volatile.shared.u32 t, [%0];\nsetp.eq.u32 p, t, d;\nnot.b32 d, t;\n@p bra SL;\n}" :: "r"(addr), "r"(dep) : "memory");
}
__device__ __forceinline__ bool elect_one() {
  uint32_t p; asm volatile("{\n.reg .pred P;\nelect.sync _|P, 0xffffffff;\nselp.u32 %0, 1, 0, P;\n}" : "=r"(p)); return p;
}
__device__ __forceinline__ void bar_sync(int id, int n) { asm volatile("bar.sync %0, %1;" :: "r"(id), "r"(n) : "memory"); }
__device__ __forceinline__ void fence_async() { asm volatile("fence.proxy.async.shared::cta;" ::: "memory"); }
__device__ __forceinline__ void fence_async_g() { asm volatile("fence.proxy.async.global;" ::: "memory"); }
__device__ __forceinline__ void tma2d(uint32_t dst, const CUtensorMap* m, uint32_t bar, int c0, int c1) {
  asm volatile("cp.async.bulk.tensor.2d.shared::cluster.global.mbarrier::complete_tx::bytes [%0], [%1, {%3, %4}], [%2];"
    :: "r"(dst), "l"(m), "r"(bar), "r"(c0), "r"(c1) : "memory");
}
__device__ __forceinline__ void tma3d(uint32_t dst, const CUtensorMap* m, uint32_t bar, int c0, int c1, int c2) {
  asm volatile("cp.async.bulk.tensor.3d.shared::cluster.global.mbarrier::complete_tx::bytes [%0], [%1, {%3, %4, %5}], [%2];"
    :: "r"(dst), "l"(m), "r"(bar), "r"(c0), "r"(c1), "r"(c2) : "memory");
}
__device__ __forceinline__ void tma4d(uint32_t dst, const CUtensorMap* m, uint32_t bar, int c0, int c1, int c2, int c3) {
  asm volatile("cp.async.bulk.tensor.4d.shared::cluster.global.mbarrier::complete_tx::bytes [%0], [%1, {%3, %4, %5, %6}], [%2];"
    :: "r"(dst), "l"(m), "r"(bar), "r"(c0), "r"(c1), "r"(c2), "r"(c3) : "memory");
}
__device__ __forceinline__ void tma2d_st(const CUtensorMap* m, uint32_t src, int c0, int c1) {
  asm volatile("cp.async.bulk.tensor.2d.global.shared::cta.bulk_group [%0, {%2, %3}], [%1];"
    :: "l"(m), "r"(src), "r"(c0), "r"(c1) : "memory");
}
__device__ __forceinline__ void bulk_ld(uint32_t dst, const void* src, uint32_t bytes, uint32_t bar) {
  asm volatile("cp.async.bulk.shared::cluster.global.mbarrier::complete_tx::bytes [%0], [%1], %2, [%3];"
    :: "r"(dst), "l"(src), "r"(bytes), "r"(bar) : "memory");
}
__device__ __forceinline__ void bulk_st(void* dst, uint32_t src, uint32_t bytes) {
  asm volatile("cp.async.bulk.global.shared::cta.bulk_group [%0], [%1], %2;" :: "l"(dst), "r"(src), "r"(bytes) : "memory");
}
__device__ __forceinline__ void bulk_commit() { asm volatile("cp.async.bulk.commit_group;" ::: "memory"); }
__device__ __forceinline__ void bulk_wait0() { asm volatile("cp.async.bulk.wait_group 0;" ::: "memory"); }
__device__ __forceinline__ void bulk_wait0_read() { asm volatile("cp.async.bulk.wait_group.read 0;" ::: "memory"); }
__device__ __forceinline__ unsigned ld_rlx(const unsigned* p) { unsigned v; asm volatile("ld.relaxed.gpu.global.u32 %0, [%1];" : "=r"(v) : "l"(p) : "memory"); return v; }
__device__ __forceinline__ unsigned ld_acq(const unsigned* p) { unsigned v; asm volatile("ld.acquire.gpu.global.u32 %0, [%1];" : "=r"(v) : "l"(p) : "memory"); return v; }
__device__ __forceinline__ void st_rlx(unsigned* p, unsigned v) { asm volatile("st.relaxed.gpu.global.u32 [%0], %1;" :: "l"(p), "r"(v) : "memory"); }
__device__ __forceinline__ void st_rel(unsigned* p, unsigned v) { asm volatile("st.release.gpu.global.u32 [%0], %1;" :: "l"(p), "r"(v) : "memory"); }
__device__ __forceinline__ void st128_rlx(void* p, const uint32_t* v) {
  asm volatile("{\n.reg .b128 t;\n.reg .b64 lo, hi;\nmov.b64 lo, {%1, %2};\nmov.b64 hi, {%3, %4};\nmov.b128 t, {lo, hi};\n"
    "st.relaxed.gpu.global.b128 [%0], t;\n}" :: "l"(p), "r"(v[0]), "r"(v[1]), "r"(v[2]), "r"(v[3]) : "memory");
}
__device__ __forceinline__ uint32_t lds32(uint32_t a) { uint32_t v; asm volatile("ld.shared.u32 %0, [%1];" : "=r"(v) : "r"(a) : "memory"); return v; }
__device__ __forceinline__ uint32_t lds32v(uint32_t a) { uint32_t v; asm volatile("ld.volatile.shared.u32 %0, [%1];" : "=r"(v) : "r"(a) : "memory"); return v; }
__device__ __forceinline__ void lds128(uint32_t* v, uint32_t a) { asm volatile("ld.shared.v4.u32 {%0,%1,%2,%3}, [%4];" : "=r"(v[0]), "=r"(v[1]), "=r"(v[2]), "=r"(v[3]) : "r"(a) : "memory"); }
__device__ __forceinline__ void sts32(uint32_t a, uint32_t v) { asm volatile("st.shared.u32 [%0], %1;" :: "r"(a), "r"(v) : "memory"); }
__device__ __forceinline__ void sts16(uint32_t a, uint32_t v) { asm volatile("st.shared.u16 [%0], %1;" :: "r"(a), "h"((uint16_t)v) : "memory"); }
__device__ __forceinline__ void sts64f(uint32_t a, float x, float y) { asm volatile("st.shared.v2.f32 [%0], {%1,%2};" :: "r"(a), "f"(x), "f"(y) : "memory"); }
__device__ __forceinline__ void sts128(uint32_t a, uint32_t x, uint32_t y, uint32_t z, uint32_t w) { asm volatile("st.shared.v4.u32 [%0], {%1,%2,%3,%4};" :: "r"(a), "r"(x), "r"(y), "r"(z), "r"(w) : "memory"); }
__device__ __forceinline__ void stsm4(uint32_t a, uint32_t r0, uint32_t r1, uint32_t r2, uint32_t r3) {
  asm volatile("stmatrix.sync.aligned.m8n8.x4.shared.b16 [%0], {%1,%2,%3,%4};" :: "r"(a), "r"(r0), "r"(r1), "r"(r2), "r"(r3) : "memory");
}
__device__ __forceinline__ void stsm4t(uint32_t a, uint32_t r0, uint32_t r1, uint32_t r2, uint32_t r3) {
  asm volatile("stmatrix.sync.aligned.m8n8.x4.trans.shared.b16 [%0], {%1,%2,%3,%4};" :: "r"(a), "r"(r0), "r"(r1), "r"(r2), "r"(r3) : "memory");
}
__device__ __forceinline__ void ldsm4t(uint32_t* r, uint32_t a) {
  asm volatile("ldmatrix.sync.aligned.m8n8.x4.trans.shared.b16 {%0,%1,%2,%3}, [%4];" : "=r"(r[0]), "=r"(r[1]), "=r"(r[2]), "=r"(r[3]) : "r"(a) : "memory");
}
__device__ __forceinline__ void ldsm4(uint32_t* r, uint32_t a) {
  asm volatile("ldmatrix.sync.aligned.m8n8.x4.shared.b16 {%0,%1,%2,%3}, [%4];" : "=r"(r[0]), "=r"(r[1]), "=r"(r[2]), "=r"(r[3]) : "r"(a) : "memory");
}
__device__ __forceinline__ void mma16816(float* d, const uint32_t* a, const uint32_t* b) {
  asm volatile("mma.sync.aligned.m16n8k16.row.col.f32.bf16.bf16.f32 {%0,%1,%2,%3}, {%4,%5,%6,%7}, {%8,%9}, {%0,%1,%2,%3};"
    : "+f"(d[0]), "+f"(d[1]), "+f"(d[2]), "+f"(d[3]) : "r"(a[0]), "r"(a[1]), "r"(a[2]), "r"(a[3]), "r"(b[0]), "r"(b[1]));
}
__device__ __forceinline__ uint32_t pack2(float lo, float hi) { uint32_t r; asm("cvt.rn.bf16x2.f32 %0, %1, %2;" : "=r"(r) : "f"(hi), "f"(lo)); return r; }
__device__ __forceinline__ uint32_t packh(float lo, float hi) { uint32_t r; asm("cvt.rn.f16x2.f32 %0, %1, %2;" : "=r"(r) : "f"(hi), "f"(lo)); return r; }
__device__ __forceinline__ void hcm2(uint32_t xr, uint32_t xi, uint32_t z, uint32_t& pr, uint32_t& pi) {
  const __half2 a = *reinterpret_cast<__half2*>(&xr), b = *reinterpret_cast<__half2*>(&xi), zz = *reinterpret_cast<__half2*>(&z);
  const __half2 re = __hfma2(__hneg2(b), __high2half2(zz), __hmul2(a, __low2half2(zz)));
  const __half2 im = __hfma2(a, __high2half2(zz), __hmul2(b, __low2half2(zz)));
  pr = *reinterpret_cast<const uint32_t*>(&re); pi = *reinterpret_cast<const uint32_t*>(&im);
}
__device__ __forceinline__ void hcm2c(uint32_t xr, uint32_t xi, uint32_t z, uint32_t& pr, uint32_t& pi) {
  const __half2 a = *reinterpret_cast<__half2*>(&xr), b = *reinterpret_cast<__half2*>(&xi), zz = *reinterpret_cast<__half2*>(&z);
  const __half2 re = __hfma2(b, __high2half2(zz), __hmul2(a, __low2half2(zz)));
  const __half2 im = __hfma2(__hneg2(a), __high2half2(zz), __hmul2(b, __low2half2(zz)));
  pr = *reinterpret_cast<const uint32_t*>(&re); pi = *reinterpret_cast<const uint32_t*>(&im);
}
__device__ __forceinline__ void lds64(uint32_t* v, uint32_t a) { asm volatile("ld.shared.v2.u32 {%0,%1}, [%2];" : "=r"(v[0]), "=r"(v[1]) : "r"(a) : "memory"); }
__device__ __forceinline__ float bf_lo(uint32_t v) { return __uint_as_float(v << 16); }
__device__ __forceinline__ float bf_hi(uint32_t v) { return __uint_as_float(v & 0xffff0000u); }
__device__ __forceinline__ float bf_round(float x) { return bf_lo(pack2(x, 0.f)); }
__device__ __forceinline__ float ex2(float x) { float r; asm("ex2.approx.ftz.f32 %0, %1;" : "=f"(r) : "f"(x)); return r; }
__device__ __forceinline__ float phi(float t, float l2e = 1.44269504089f) {
  float e = ex2(t * l2e) + 1e-6f;
  asm("{\n.reg .pred p;\nsetp.gt.f32 p, %1, 0f00000000;\n@p add.f32 %0, %1, 0f3F800008;\n}" : "+f"(e) : "f"(t));
  return e;
}
__device__ __forceinline__ void wg_fence() { asm volatile("wgmma.fence.sync.aligned;" ::: "memory"); }
__device__ __forceinline__ void wg_commit() { asm volatile("wgmma.commit_group.sync.aligned;" ::: "memory"); }
template <int N> __device__ __forceinline__ void wg_wait() { asm volatile("wgmma.wait_group.sync.aligned %0;" :: "n"(N) : "memory"); }
template <int N> __device__ __forceinline__ void pin(float* a) {
  #pragma unroll
  for (int i = 0; i < N; i++) asm volatile("" : "+f"(a[i]) :: "memory");
}
__device__ __forceinline__ int rtid() { int t; asm volatile("mov.u32 %0, %%tid.x;" : "=r"(t)); return t; }
template <int N> __device__ __forceinline__ void zero(float* a) {
  #pragma unroll
  for (int i = 0; i < N; i++) asm volatile("mov.b32 %0, 0;" : "=f"(a[i]));
}
__device__ __forceinline__ void cexp_t(float lg2mag, float turns, float& re, float& im) {
  float m = ex2(lg2mag);
  float fr = (turns - __fadd_rn(__fadd_rn(turns, 12582912.f), -12582912.f)) * 6.283185307f;
  re = m * __cosf(fr); im = m * __sinf(fr);
}
__device__ __forceinline__ void csq(float ar, float ai, float& cr, float& ci) {
  const float t = ar + ar;
  cr = fmaf(ar, ar, -ai * ai); ci = t * ai;
}
__device__ __forceinline__ void cmul(float ar, float ai, float br, float bi, float& cr, float& ci) {
  cr = fmaf(ar, br, -ai * bi); ci = fmaf(ar, bi, ai * br);
}

__device__ __forceinline__ void wg_ss48_tt(float* d, uint64_t da, uint64_t db, int scale_d) {
  asm volatile("{\n.reg .pred p;\nsetp.ne.b32 p, %26, 0;\n"
    "wgmma.mma_async.sync.aligned.m64n48k16.f32.bf16.bf16 "
    "{%0, %1, %2, %3, %4, %5, %6, %7, %8, %9, %10, %11, %12, %13, %14, %15, %16, %17, %18, %19, %20, %21, %22, %23}, %24, %25, p, 1, 1, 1, 1;\n}\n"
    : "+f"(d[0]), "+f"(d[1]), "+f"(d[2]), "+f"(d[3]), "+f"(d[4]), "+f"(d[5]), "+f"(d[6]), "+f"(d[7]), "+f"(d[8]), "+f"(d[9]), "+f"(d[10]), "+f"(d[11]), "+f"(d[12]), "+f"(d[13]), "+f"(d[14]), "+f"(d[15]), "+f"(d[16]), "+f"(d[17]), "+f"(d[18]), "+f"(d[19]), "+f"(d[20]), "+f"(d[21]), "+f"(d[22]), "+f"(d[23])
    : "l"(da), "l"(db), "r"(scale_d));
}
__device__ __forceinline__ void wg_rs88_tb(float* d, const uint32_t* a, uint64_t db, int scale_d) {
  asm volatile("{\n.reg .pred p;\nsetp.ne.b32 p, %49, 0;\n"
    "wgmma.mma_async.sync.aligned.m64n88k16.f32.bf16.bf16 "
    "{%0, %1, %2, %3, %4, %5, %6, %7, %8, %9, %10, %11, %12, %13, %14, %15, %16, %17, %18, %19, %20, %21, %22, %23, %24, %25, %26, %27, %28, %29, %30, %31, %32, %33, %34, %35, %36, %37, %38, %39, %40, %41, %42, %43}, {%44, %45, %46, %47}, %48, p, 1, 1, 1;\n}\n"
    : "+f"(d[0]), "+f"(d[1]), "+f"(d[2]), "+f"(d[3]), "+f"(d[4]), "+f"(d[5]), "+f"(d[6]), "+f"(d[7]), "+f"(d[8]), "+f"(d[9]), "+f"(d[10]), "+f"(d[11]), "+f"(d[12]), "+f"(d[13]), "+f"(d[14]), "+f"(d[15]), "+f"(d[16]), "+f"(d[17]), "+f"(d[18]), "+f"(d[19]), "+f"(d[20]), "+f"(d[21]), "+f"(d[22]), "+f"(d[23]), "+f"(d[24]), "+f"(d[25]), "+f"(d[26]), "+f"(d[27]), "+f"(d[28]), "+f"(d[29]), "+f"(d[30]), "+f"(d[31]), "+f"(d[32]), "+f"(d[33]), "+f"(d[34]), "+f"(d[35]), "+f"(d[36]), "+f"(d[37]), "+f"(d[38]), "+f"(d[39]), "+f"(d[40]), "+f"(d[41]), "+f"(d[42]), "+f"(d[43])
    : "r"(a[0]), "r"(a[1]), "r"(a[2]), "r"(a[3]), "l"(db), "r"(scale_d));
}
__device__ __forceinline__ void wg_ss80_tb(float* d, uint64_t da, uint64_t db, int scale_d) {
  asm volatile("{\n.reg .pred p;\nsetp.ne.b32 p, %42, 0;\n"
    "wgmma.mma_async.sync.aligned.m64n80k16.f32.bf16.bf16 "
    "{%0, %1, %2, %3, %4, %5, %6, %7, %8, %9, %10, %11, %12, %13, %14, %15, %16, %17, %18, %19, %20, %21, %22, %23, %24, %25, %26, %27, %28, %29, %30, %31, %32, %33, %34, %35, %36, %37, %38, %39}, %40, %41, p, 1, 1, 0, 1;\n}\n"
    : "+f"(d[0]), "+f"(d[1]), "+f"(d[2]), "+f"(d[3]), "+f"(d[4]), "+f"(d[5]), "+f"(d[6]), "+f"(d[7]), "+f"(d[8]), "+f"(d[9]), "+f"(d[10]), "+f"(d[11]), "+f"(d[12]), "+f"(d[13]), "+f"(d[14]), "+f"(d[15]), "+f"(d[16]), "+f"(d[17]), "+f"(d[18]), "+f"(d[19]), "+f"(d[20]), "+f"(d[21]), "+f"(d[22]), "+f"(d[23]), "+f"(d[24]), "+f"(d[25]), "+f"(d[26]), "+f"(d[27]), "+f"(d[28]), "+f"(d[29]), "+f"(d[30]), "+f"(d[31]), "+f"(d[32]), "+f"(d[33]), "+f"(d[34]), "+f"(d[35]), "+f"(d[36]), "+f"(d[37]), "+f"(d[38]), "+f"(d[39])
    : "l"(da), "l"(db), "r"(scale_d));
}
__device__ __forceinline__ void wg_ss48_tt_h(float* d, uint64_t da, uint64_t db, int scale_d) {
  asm volatile("{\n.reg .pred p;\nsetp.ne.b32 p, %26, 0;\n"
    "wgmma.mma_async.sync.aligned.m64n48k16.f32.f16.f16 "
    "{%0, %1, %2, %3, %4, %5, %6, %7, %8, %9, %10, %11, %12, %13, %14, %15, %16, %17, %18, %19, %20, %21, %22, %23}, %24, %25, p, 1, 1, 1, 1;\n}\n"
    : "+f"(d[0]), "+f"(d[1]), "+f"(d[2]), "+f"(d[3]), "+f"(d[4]), "+f"(d[5]), "+f"(d[6]), "+f"(d[7]), "+f"(d[8]), "+f"(d[9]), "+f"(d[10]), "+f"(d[11]), "+f"(d[12]), "+f"(d[13]), "+f"(d[14]), "+f"(d[15]), "+f"(d[16]), "+f"(d[17]), "+f"(d[18]), "+f"(d[19]), "+f"(d[20]), "+f"(d[21]), "+f"(d[22]), "+f"(d[23])
    : "l"(da), "l"(db), "r"(scale_d));
}
__device__ __forceinline__ void wg_rs192_tb(float* d, const uint32_t* a, uint64_t db, int scale_d) {
  asm volatile("{\n.reg .pred p;\nsetp.ne.b32 p, %101, 0;\n"
    "wgmma.mma_async.sync.aligned.m64n192k16.f32.bf16.bf16 "
    "{%0, %1, %2, %3, %4, %5, %6, %7, %8, %9, %10, %11, %12, %13, %14, %15, %16, %17, %18, %19, %20, %21, %22, %23, %24, %25, %26, %27, %28, %29, %30, %31, %32, %33, %34, %35, %36, %37, %38, %39, %40, %41, %42, %43, %44, %45, %46, %47, %48, %49, %50, %51, %52, %53, %54, %55, %56, %57, %58, %59, %60, %61, %62, %63, %64, %65, %66, %67, %68, %69, %70, %71, %72, %73, %74, %75, %76, %77, %78, %79, %80, %81, %82, %83, %84, %85, %86, %87, %88, %89, %90, %91, %92, %93, %94, %95}, {%96, %97, %98, %99}, %100, p, 1, 1, 1;\n}\n"
    : "+f"(d[0]), "+f"(d[1]), "+f"(d[2]), "+f"(d[3]), "+f"(d[4]), "+f"(d[5]), "+f"(d[6]), "+f"(d[7]), "+f"(d[8]), "+f"(d[9]), "+f"(d[10]), "+f"(d[11]), "+f"(d[12]), "+f"(d[13]), "+f"(d[14]), "+f"(d[15]), "+f"(d[16]), "+f"(d[17]), "+f"(d[18]), "+f"(d[19]), "+f"(d[20]), "+f"(d[21]), "+f"(d[22]), "+f"(d[23]), "+f"(d[24]), "+f"(d[25]), "+f"(d[26]), "+f"(d[27]), "+f"(d[28]), "+f"(d[29]), "+f"(d[30]), "+f"(d[31]), "+f"(d[32]), "+f"(d[33]), "+f"(d[34]), "+f"(d[35]), "+f"(d[36]), "+f"(d[37]), "+f"(d[38]), "+f"(d[39]), "+f"(d[40]), "+f"(d[41]), "+f"(d[42]), "+f"(d[43]), "+f"(d[44]), "+f"(d[45]), "+f"(d[46]), "+f"(d[47]), "+f"(d[48]), "+f"(d[49]), "+f"(d[50]), "+f"(d[51]), "+f"(d[52]), "+f"(d[53]), "+f"(d[54]), "+f"(d[55]), "+f"(d[56]), "+f"(d[57]), "+f"(d[58]), "+f"(d[59]), "+f"(d[60]), "+f"(d[61]), "+f"(d[62]), "+f"(d[63]), "+f"(d[64]), "+f"(d[65]), "+f"(d[66]), "+f"(d[67]), "+f"(d[68]), "+f"(d[69]), "+f"(d[70]), "+f"(d[71]), "+f"(d[72]), "+f"(d[73]), "+f"(d[74]), "+f"(d[75]), "+f"(d[76]), "+f"(d[77]), "+f"(d[78]), "+f"(d[79]), "+f"(d[80]), "+f"(d[81]), "+f"(d[82]), "+f"(d[83]), "+f"(d[84]), "+f"(d[85]), "+f"(d[86]), "+f"(d[87]), "+f"(d[88]), "+f"(d[89]), "+f"(d[90]), "+f"(d[91]), "+f"(d[92]), "+f"(d[93]), "+f"(d[94]), "+f"(d[95])
    : "r"(a[0]), "r"(a[1]), "r"(a[2]), "r"(a[3]), "l"(db), "r"(scale_d));
}
__device__ __forceinline__ void wg_rs48_tb(float* d, const uint32_t* a, uint64_t db, int scale_d) {
  asm volatile("{\n.reg .pred p;\nsetp.ne.b32 p, %29, 0;\n"
    "wgmma.mma_async.sync.aligned.m64n48k16.f32.bf16.bf16 "
    "{%0, %1, %2, %3, %4, %5, %6, %7, %8, %9, %10, %11, %12, %13, %14, %15, %16, %17, %18, %19, %20, %21, %22, %23}, {%24, %25, %26, %27}, %28, p, 1, 1, 1;\n}\n"
    : "+f"(d[0]), "+f"(d[1]), "+f"(d[2]), "+f"(d[3]), "+f"(d[4]), "+f"(d[5]), "+f"(d[6]), "+f"(d[7]), "+f"(d[8]), "+f"(d[9]), "+f"(d[10]), "+f"(d[11]), "+f"(d[12]), "+f"(d[13]), "+f"(d[14]), "+f"(d[15]), "+f"(d[16]), "+f"(d[17]), "+f"(d[18]), "+f"(d[19]), "+f"(d[20]), "+f"(d[21]), "+f"(d[22]), "+f"(d[23])
    : "r"(a[0]), "r"(a[1]), "r"(a[2]), "r"(a[3]), "l"(db), "r"(scale_d));
}

struct Params {
  const __nv_bfloat16 *par[4], *logdt, *dskip, *u, *wo;
  CUtensorMap m[M_COUNT];
};

#define CHUNK(i) ((c + (i)) & 7)
#define FLAG(kind, rr, cc) (&g_flag[((kind) * 128 + (rr) * 8 + (cc)) * 32])
#define SLOT(i) ((i) == 0 ? OFF_EXTRA : OFF_BLK - 256 + ((i) > 5 ? (i) - 6 : (i) - 1) * BLK)
__device__ __forceinline__ void load_quad(uint32_t* A, uint32_t addr) {
  A[0] = lds32v(addr); A[1] = lds32v(addr + 32); A[2] = lds32v(addr - 32); A[3] = lds32v(addr);
}

__device__ __forceinline__ bool y_transpose(uint32_t sb, int w5, int lane, uint32_t ytag) {
  const int mi = lane >> 3, rw = lane & 7;
  const uint32_t sa = sb + OFF_EXTRA + (w5 * 16 + rw) * 128 + ((mi ^ rw) << 4), da = sb + SLOT(3) + (8 * mi + rw) * 160 + w5 * 32;
  const uint32_t ym = lane < 4 ? 0x10001u : 0u;
  bar_sync(7, 160);
  uint32_t v[8][4], bad = 0;
  #pragma unroll
  for (int q = 0; q < 8; q++) ldsm4t(v[q], (sa ^ ((q & 1) * 64 + ((q >> 1) & 1) * 16)) + ((q >> 1) & 1) * 10240 + (q >> 2) * 1024);
  #pragma unroll
  for (int q = 0; q < 8; q++) {
    bad |= (v[q][0] ^ ytag) | (v[q][2] ^ ytag);
    stsm4(da + (q & 3) * 5120 + (q >> 2) * 16, v[q][0] & ~ym, v[q][1], v[q][2] & ~ym, v[q][3]);
  }
  fence_async();
  uint32_t any;
  asm volatile("{\n.reg .pred p;\nsetp.ne.u32 p, %1, 0;\nbarrier.red.or.pred p, 7, 160, p;\nselp.u32 %0, 1, 0, p;\n}" : "=r"(any) : "r"(bad & ym) : "memory");
  return any;
}

__global__ void __launch_bounds__(512, 1) fused_kernel(const __grid_constant__ Params prm) {
  extern __shared__ unsigned char smem_raw[];
  uint32_t raw[5][2], pd;
  if ((threadIdx.x >> 7) == 2) {
    const int ch = (blockIdx.x & 7) * 80 + (blockIdx.x >> 3) * 5, od = threadIdx.x & 1;
    #pragma unroll
    for (int e = 0; e < 2; e++) {
      const __nv_bfloat16* pp = prm.par[2 * e + od] + ch * 128 + (threadIdx.x & 126);
      #pragma unroll
      for (int q = 0; q < 5; q++) asm volatile("ld.global.nc.u32 %0, [%1];" : "=r"(raw[q][e]) : "l"(pp + q * 128));
    }
    asm volatile("ld.global.nc.u16 %0, [%1];" : "=r"(pd) : "l"(((threadIdx.x & 8) ? prm.dskip : prm.logdt) + ch + min(threadIdx.x & 7, 4)));
  }
  constexpr uint32_t sb = SB0;
  const int tid = threadIdx.x, lane = tid & 31;
  const int warp = __shfl_sync(0xffffffff, tid >> 5, 0), wg = warp >> 2, w4 = warp & 3;
  const int cta = blockIdx.x, r = cta >> 3, c = cta & 7;
  if (smem_u32(smem_raw) != SB0) return;
#define BAR(i) (sb + OFF_BAR + 8 * (i))
  const bool sw64 = ((c + 1) & 2) != 0;

  const CUtensorMap* mwp = &prm.m[sw64 ? M_W64 : M_W128];
  const int mcol = (c * 80 + (c & 1) * 16) >> (sw64 ? 5 : 6), rcol = c * 80 + ((c & 1) ? 0 : 64);
  if (warp == 12 && elect_one()) {
    #pragma unroll
    for (int i = 0; i < 5; i++) mbar_init(BAR(BR_FULL + i), 1);
    asm volatile("fence.mbarrier_init.release.cluster;" ::: "memory");
    if (EN_ATT) {
      mbar_expect_tx(BAR(BR_FULL), W_SLOT + 16384);
      tma4d(sb, mwp, BAR(BR_FULL), 0, 0, mcol, 0);
      tma2d(sb + OFF_X, &prm.m[M_X], BAR(BR_FULL), 0, r * 128);
      tma3d(sb + 12288, &prm.m[M_WR], BAR(BR_FULL), rcol, 0, 0);
      mbar_expect_tx(BAR(BR_FULL + 1), W_SLOT);
      tma4d(sb + W_SLOT, mwp, BAR(BR_FULL + 1), 0, 32, mcol, 0);
      tma3d(sb + W_SLOT + 12288, &prm.m[M_WR], BAR(BR_FULL + 1), rcol, 32, 0);
      TS(24);
    }
  }
  if (warp == 13 && elect_one()) {
    asm volatile("prefetch.tensormap [%0];" :: "l"(&prm.m[M_X]) : "memory");
    asm volatile("prefetch.tensormap [%0];" :: "l"(&prm.m[M_WR]) : "memory");
  }
  if (wg == 3) {
    asm volatile("setmaxnreg.dec.sync.aligned.u32 56;");
    const int tid = rtid(), lane = tid & 31;
    if (warp == 12) {
      asm volatile("bar.arrive 0, 512;" ::: "memory");
      if (EN_ATT && elect_one()) {
        #pragma unroll
        for (int kb = 2; kb < 5; kb++) {
          mbar_expect_tx(BAR(BR_FULL + kb), (kb & 1) ? W_SLOT : W_SLOT + 16384);
          if (!(kb & 1)) tma2d(sb + OFF_X + kb * 8192, &prm.m[M_X], BAR(BR_FULL + kb), kb * 32, r * 128);
          tma4d(sb + kb * W_SLOT, mwp, BAR(BR_FULL + kb), 0, kb * 32, mcol, 0);
          tma3d(sb + kb * W_SLOT + 12288, &prm.m[M_WR], BAR(BR_FULL + kb), rcol, kb * 32, 0);
        }
      }
      bar_sync(6, 128);
      if (elect_one()) {
        if (EN_SSM) { mbar_expect_tx(BAR(BR_UIN), 20480); tma2d(sb + OFF_UT, &prm.m[M_U], BAR(BR_UIN), c * 80, r * 128); }
        if (EN_ATT) {
          uint32_t st = sb, fb = BAR(BR_FULL), ph = 0, xs = sb + OFF_X;
          #pragma unroll 1
          for (int k = 160; k < 640; k += 32) {
            mbar_wait(fb + 8 * (BR_EMPTY - BR_FULL), ph);
            mbar_expect_tx(fb, (k & 32) ? W_SLOT : W_SLOT + 16384);
            tma4d(st, mwp, fb, 0, k, mcol, 0);
            if (!(k & 32)) { tma2d(xs, &prm.m[M_X], fb, k, r * 128); xs += 16384; if (xs == sb + OFF_BAR) xs = sb + OFF_X; }
            tma3d(st + 12288, &prm.m[M_WR], fb, rcol, k, 0);
            st += W_SLOT; fb += 8;
            if (st == sb + OFF_X) { st = sb; fb = BAR(BR_FULL); ph ^= 1; }
          }
          asm volatile("cp.async.bulk.prefetch.L2.global [%0], 6400;" :: "l"(prm.wo + cta * 3200) : "memory");
        }
      }
      __syncwarp();
      if (EN_ATT) {
      mbar_wait(BAR(BR_EPOCH), 0);
      const unsigned epoch = lds32(sb + OFF_EPOCH);
      const unsigned* fo = FLAG(3, r, lane & 7);
      unsigned seen = __ballot_sync(0xffffffff, ld_rlx(lane < 16 ? fo : FLAG(0, lane & 15, c)) == epoch) & 0xffu;
      mbar_wait(BAR(BR_GEMM), 0);
      if (elect_one()) {
        mbar_expect_tx(BAR(BR_WO), 8 * 10240);
        mbar_expect_tx(BAR(BR_KVP), 61440);
      }
      {
        uint32_t ds = sb + OFF_WOR + (lane >> 3) * 128 + (((lane & 7) ^ (lane >> 3)) << 4);
        #pragma unroll 1
        for (int h = 0; h < 2; h++) {
          const int i = (lane & 6) + h;
          const char* gs = reinterpret_cast<const char*>(prm.wo) + (size_t)((lane >> 3) + CHUNK(i) * 80) * 1280 + 1024 + c * 32 + (lane & 1) * 16;
          #pragma unroll 2
          for (int q = 0; q < 20; q++) {
            asm volatile("cp.async.cg.shared.global [%0], [%1], 16;" :: "r"(ds), "l"(gs) : "memory");
            ds = (ds + 512) ^ 64; gs += 5120;
          }
        }
      }
      mbar_wait(BAR(BR_PUB), 0);
      poll_all(FLAG(0, lane & 15, c), epoch);
      if (elect_one()) { TS(23); bulk_ld(sb + OFF_KVP, &g_kvp[c * 16 * 240], 61440, BAR(BR_KVP)); }
      asm volatile("cp.async.wait_all;" ::: "memory");
      fence_async();
      mbar_arrive(BAR(BR_WO));
      mbar_wait(BAR(BR_OSTG), 0);
      if (elect_one()) {
        bulk_st(&g_o[cta * 1280], sb + OFF_EXTRA, 20480);
        bulk_commit();
        bulk_wait0();
        st_rlx(FLAG(3, r, c), epoch);
        mbar_arrive(BAR(BR_OEMPTY));
        TS(20);
        #pragma unroll 1
        for (int i = 0; i < 8; i++) tma2d(sb + i * 10240, &prm.m[M_WO], BAR(BR_WO), c * 64, CHUNK(i) * 80);
      }
      __syncwarp();
      #pragma unroll 1
      for (int i = 1; i < 8; i++) {
        const int src = CHUNK(i);
        if (!((seen >> src) & 1)) seen = poll_bit(fo, epoch, 1u << src);
        if (i > 5) mbar_wait(BAR(BR_OEMPTY - 5) + 8 * i, 0);
        else if (EN_SSM && i != 2 && i != 3) mbar_wait(i == 1 ? BAR(BR_KS + 1) : BAR(BR_FREE - 4) + 8 * i, 0);
        if (elect_one()) {
          mbar_expect_tx(BAR(BR_OFULL) + 8 * i, 20480);
          bulk_ld(sb + SLOT(i), &g_o[(r * 8 + src) * 1280], 20480, BAR(BR_OFULL) + 8 * i);
          if (i == 1) TS(21);
          if (i == 7) TS(22);
        }
        __syncwarp();
      }
      if (lane == 0) { DUMP(20, 30); }
      }
    } else {
      const int hw = warp - 13, ht = tid - 416;
      if (hw == 2 && elect_one()) {
        #pragma unroll
        for (int i = 5; i <= BR_DRDY; i++) mbar_init(BAR(i), i == BR_WO ? 33 : i == BR_GEMM ? 8 : i == BR_OEMPTY ? 9 : i < BR_EMPTY ? 1 : i < BR_OEMPTY ? 2 : i < BR_Y ? 8 : i < BR_DRDY ? 4 : 3);
        asm volatile("fence.mbarrier_init.release.cluster;" ::: "memory");
      }
      __syncwarp();
      asm volatile("bar.arrive 0, 512;" ::: "memory");
      if (EN_SSM && hw == 2) asm volatile("bar.arrive 8, 160;" ::: "memory");
      const unsigned epoch = hw == 0 ? ld_rlx(&g_epoch[cta]) + 1 : 0;
      bar_sync(5, 96);
      asm volatile("bar.arrive 6, 128;" ::: "memory");
      if (hw == 1 && elect_one()) {
        #pragma unroll
        for (int i = M_U; i < M_COUNT; i++) asm volatile("prefetch.tensormap [%0];" :: "l"(&prm.m[i]) : "memory");
      }
      if (ht == 0) {
        st_rlx(&g_epoch[cta], epoch);
        sts32(sb + OFF_EPOCH, epoch);
        mbar_arrive(BAR(BR_EPOCH));
      }
      if (EN_SSM) {
      const int mi = lane >> 3, rw = lane & 7, ch0 = c * 80 + r * 5;
      const bool early_u = hw == 0 && __all_sync(0xffffffff, ld_acq(FLAG(1, lane & 15, c)) == epoch);
      mbar_wait(BAR(BR_UIN), 0);
      if (ht == 0) TS(36);
      #pragma unroll 1
      for (int h = 0; h < 2; h++) {
        const uint32_t sa = sb + OFF_UT + h * 10240 + (8 * mi + rw) * 160 + hw * 16, da = sb + OFF_UT + h * 10240 + (hw * 8 + rw) * 128 + ((mi ^ rw ^ h) << 4);
        uint32_t v[8][4];
        #pragma unroll
        for (int q = 0; q < 8; q++) if (q < 6 || hw == 0) ldsm4t(v[q], sa + (q & 1) * 5120 + (q >> 1) * 48);
        bar_sync(5, 96);
        #pragma unroll
        for (int q = 0; q < 8; q++) if (q < 6 || hw == 0) stsm4((da ^ ((q & 1) * 64)) + (q >> 1) * 3072, v[q][0], v[q][1], v[q][2], v[q][3]);
      }
      fence_async();
      bar_sync(5, 96);
      if (hw == 0) {
        if (elect_one()) {
          tma2d_st(&prm.m[M_SA], sb + OFF_UT, r * 128, c * 80);
          tma2d_st(&prm.m[M_SA], sb + OFF_UT + 10240, r * 128 + 64, c * 80);
          bulk_commit(); bulk_wait0_read();
          mbar_arrive(BAR(BR_UOUT));
          TS(37);
          bulk_wait0();
          st_rel(FLAG(1, r, c), epoch);
          TS(30);
        }
        __syncwarp();
        if (!early_u) poll_all_acq(FLAG(1, lane & 15, c), epoch);
      }
      #pragma unroll 1
      for (int k = 0; k < 5; k++) {
        if (k == 0 || k == 3) {
          const int p = k != 0;
          if (hw == 0) {
            if (!p) {
              if (elect_one()) {
                fence_async_g();
                mbar_expect_tx(BAR(BR_U), 12288);
                #pragma unroll 1
                for (int q = 0; q < 3; q++) bulk_ld(sb + OFF_BLK + q * q * BLK, g_uy + (ch0 + q * q) * 2048, 4096, BAR(BR_U));
                TS(31);
              }
              __syncwarp();
            }
            mbar_wait(BAR(p ? BR_U2 : BR_U), 0);
          }
          bar_sync(5, 96);
        }
        const int l3 = (hw + k) % 3 * 32 + lane;
        const uint32_t blk = sb + OFF_BLK + ((0x32410 >> (4 * k)) & 7) * BLK, o = blk + B_D + l3 * 16;
        float P[34];
        P[0] = 0.f;
        #pragma unroll
        for (int q = 0; q < 5; q++) {
          const int ch = 2 * l3 - 3 + q;
          uint32_t v[4];
          lds128(v, blk + (uint32_t)((ch * 16) ^ ((ch * 2) & 0x10)));
          #pragma unroll
          for (int e = 0; e < 8; e++) {
            const int i = 8 * q + e - 4;
            if (i >= 0 && i < 33) P[i + 1] = P[i] + ((e & 1) ? bf_hi(v[e >> 1]) : bf_lo(v[e >> 1]));
          }
        }
#define WIN(lo, hi, e) (P[21 + (e) - (lo)] - P[20 + (e) - (hi)])
#define WIN8(lo, hi, b) pack2(WIN(lo, hi, b), WIN(lo, hi, b + 1)), pack2(WIN(lo, hi, b + 2), WIN(lo, hi, b + 3)), pack2(WIN(lo, hi, b + 4), WIN(lo, hi, b + 5)), pack2(WIN(lo, hi, b + 6), WIN(lo, hi, b + 7))
        if (l3 < 64) {
          sts128(o + B_D9, WIN8(12, 20, 0)); sts128(o + B_D9 + 1024, WIN8(12, 20, 8));
          sts128(o + B_D7, WIN8(5, 11, 0)); sts128(o + B_D7 + 1024, WIN8(5, 11, 8));
        }
        sts128(o + B_D5, WIN8(6, 10, 0)); sts128(o + B_D5 + 1552, WIN8(6, 10, 8));
        sts128(o, WIN8(3, 5, 0)); sts128(o + 1552, WIN8(3, 5, 8));
        if (l3 < 2) sts128(blk + B_D + l3 * B_D5 + 1536, 0, 0, 0, 0);
      }
      __syncwarp();
      if (lane == 0) mbar_arrive(BAR(BR_DRDY));
      if (ht == 0) TS(32);
      if (hw == 0) {
        const bool early = __all_sync(0xffffffff, ld_rlx(FLAG(2, lane & 15, c)) == epoch);
        #pragma unroll 1
        for (int p = 0; p < 2; p++) {
          mbar_wait(BAR(BR_Y) + 8 * p, 0);
          if (elect_one()) {
            bulk_st(g_uy + (640 + ch0 + 4 * p) * 2048, sb + OFF_BLK + (3 + p) * BLK, p ? 4096 : 16384);
            bulk_commit(); bulk_wait0_read();
            mbar_arrive(BAR(BR_FREE) + 8 * p);
          }
          __syncwarp();
        }
        if (elect_one()) { bulk_wait0(); st_rlx(FLAG(2, r, c), epoch); TS(33); }
        __syncwarp();
        if (!early) poll_all(FLAG(2, lane & 15, c), epoch);
        if (EN_ATT) mbar_wait(BAR(BR_OEMPTY), 0);
        #pragma unroll 1
        for (int n = 0; n < 64; n++) {
          if (elect_one()) {
            mbar_expect_tx(BAR(BR_YIN), 20480);
            tma2d(sb + OFF_EXTRA, &prm.m[M_SA], BAR(BR_YIN), r * 128, 640 + c * 80);
            tma2d(sb + OFF_EXTRA + 10240, &prm.m[M_SA], BAR(BR_YIN), r * 128 + 64, 640 + c * 80);
            TS(34);
          }
          __syncwarp();
          if (EN_ATT) mbar_wait(BAR(BR_OEMPTY + 3), 0);
          mbar_wait(BAR(BR_YIN), n & 1);
          if (lane == 0) TS(38);
          if (!y_transpose(sb, 4, lane, (epoch & 1u) * 0x10001u)) break;
          FIXCNT
        }
      if (elect_one()) {
        TS(39);
        tma2d_st(&prm.m[M_OUT], sb + SLOT(3), c * 80, r * 128);
        bulk_commit(); bulk_wait0_read();
        TS(35); DUMP(30, 40); DUMP(0, 1);
      }
      }
      }
    }
  } else {
  if (wg < 2) {
    asm volatile("setmaxnreg.inc.sync.aligned.u32 160;");
    bar_sync(0, 512);
    if (EN_ATT) {
    float am[96], ar[24];
    {
      const bool lead = (rtid() & 127) == 0;
      constexpr uint64_t dr0 = mkdesc(SB0 + 12288, 1024, 256, 3);
      const uint64_t dbc = sw64 ? mkdesc(SB0, 2048, 512, 2) : mkdesc(SB0, 4096, 1024, 1);
      const uint32_t kst = __shfl_sync(0xffffffff, sw64 ? 64 : 128, 0), bh = __shfl_sync(0xffffffff, (uint32_t)(dbc >> 32), 0);
      const uint64_t db0 = desc2(__shfl_sync(0xffffffff, (uint32_t)dbc, 0), bh);
      uint32_t ph = 0;
      const int ln = rtid() & 31;
      const uint32_t xa = sb + OFF_X + (warp * 16 + (ln & 15)) * 128 + (((ln >> 4) ^ (ln & 7)) << 4);
      uint32_t A[8];
      mbar_wait(BAR(BR_FULL), 0);
      if (lead && wg == 0) TS(1);
      ldsm4(A, xa); ldsm4(A + 4, xa ^ 32);
      wg_fence();
      wg_rs48_tb(ar, A, dr0, 0); wg_rs192_tb(am, A, db0, 0);
      wg_commit();
      uint32_t wp = 0, fb = BAR(BR_FULL), xk = xa;
      #pragma unroll 1
      for (int kb = 1; kb < 20; kb++) {
        const uint64_t d0 = desc2((uint32_t)dr0 + wp + 32, dr0 >> 32), d1 = desc2((uint32_t)db0 + wp + kst, bh);
        const uint32_t eb = fb + 8 * (BR_EMPTY - BR_FULL);
        wp += W_SLOT >> 4; fb += 8;
        if (wp == 5 * (W_SLOT >> 4)) { wp = 0; fb = BAR(BR_FULL); ph ^= 1; }
        wg_fence();
        wg_rs48_tb(ar, A + 4, d0, 1);
        wg_rs192_tb(am, A + 4, d1, 1);
        wg_commit();
        xk ^= 64;
        if (!(kb & 1)) { xk += 16384; if (xk >= sb + OFF_BAR) xk -= 49152; }
        mbar_wait(fb, ph);
        wg_wait<1>();
        ldsm4(A, xk);
        wg_fence();
        wg_rs48_tb(ar, A, desc2((uint32_t)dr0 + wp, dr0 >> 32), 1);
        wg_rs192_tb(am, A, desc2((uint32_t)db0 + wp, bh), 1);
        wg_commit();
        wg_wait<1>();
        ldsm4(A + 4, xk ^ 32);
        if (lead && kb < 16) mbar_arrive(eb);
      }
      wg_fence();
      wg_rs48_tb(ar, A + 4, dr0 + 4 * (W_SLOT >> 4) + 32, 1);
      wg_rs192_tb(am, A + 4, desc2((uint32_t)db0 + 4 * (W_SLOT >> 4) + kst, bh), 1);
      wg_commit();
      wg_wait<0>();
      if (ln == 0) mbar_arrive(BAR(BR_GEMM));
      pin<96>(am); pin<24>(ar);
    }
    const int tid = rtid(), lane = tid & 31, tq = lane & 3;
    if (tid == 0) TS(2);
#define QV(j, e) ((j) < 8 ? am[4 * (j) + (e)] : ar[4 * ((j) - 8) + (e)])
#define KV_(j, e) ((j) < 8 ? am[32 + 4 * (j) + (e)] : ar[8 + 4 * ((j) - 8) + (e)])
#define VV(j, e) ((j) < 8 ? am[64 + 4 * (j) + (e)] : ar[16 + 4 * ((j) - 8) + (e)])
    {
      bar_sync(1, 256);
      const uint32_t ro = sb + (uint32_t)((warp * 16 + (lane & 15)) * 16);
      const int l0 = 2 * (c & 1) + (lane >> 4);
      const uint32_t ones = (tq == 0) ? 0x00003f80u : 0u;
#define PV(j) pack2(VV(j, 0), VV(j, 1)), pack2(VV(j, 2), VV(j, 3))
#define PK(j) pack2(phi(KV_(j, 0)), phi(KV_(j, 1))), pack2(phi(KV_(j, 2)), phi(KV_(j, 3)))
      stsm4(ro + OFF_V + (5 + 6 * (lane >> 4)) * 2048, ones, ones, ones, ones);
      #pragma unroll
      for (int j = 0; j < 10; j += 2) {
        const int l = (j == 8 && (c & 1)) ? l0 - 2 : l0 + j;
        stsm4(ro + OFF_V + (l + (l >= 5)) * 2048, PV(j), PV(j + 1));
        stsm4(ro + OFF_PK + l * 2048, PK(j), PK(j + 1));
      }
    }
    fence_async();
    bar_sync(1, 256);
    if (tid == 0) TS(3);
    mbar_wait(BAR(BR_EPOCH), 0);
    const unsigned epoch = lds32(sb + OFF_EPOCH);
    {
      float kv[24]; zero<24>(kv);
      constexpr uint64_t da = mkdesc(SB0 + OFF_PK, 128, 2048, 0), db = mkdesc(SB0 + OFF_V, 128, 2048, 0);
      wg_fence();
      #pragma unroll
      for (int s = 0; s < 8; s++) wg_ss48_tt(kv, desc2((uint32_t)da + wg * 640 + s * 16, da >> 32), desc2((uint32_t)db + wg * 768 + s * 16, db >> 32), s != 0);
      wg_commit();
      wg_wait<0>();
      pin<24>(kv);
      if (tid == 0) TS(15);
      if (w4 < 3) {
        const uint32_t wb = sb + OFF_KVS + (wg * 3 + w4) * 1536 + (lane & 15) * 96;
        #pragma unroll
        for (int j = 0; j < 6; j += 2)
          stsm4(wb + (j + (lane >> 4)) * 16, pack2(kv[4 * j], kv[4 * j + 1]), pack2(kv[4 * j + 2], kv[4 * j + 3]),
                pack2(kv[4 * j + 4], kv[4 * j + 5]), pack2(kv[4 * j + 6], kv[4 * j + 7]));
        __syncwarp();
        const int dl = w4 * 16 + (lane & 15), hl = dl >= 20;
        uint32_t v[4], z[4];
        lds128(v, wb + (3 * hl + (lane >> 4)) * 16);
        lds64(z, wb + 32 + 8 * hl); z[2] = lds32(wb + 80); z[3] = epoch & 1u;
        if (dl < 40) {
          uint4* dst = &g_kvp[(c * 16 + r) * 240 + wg * 40 + dl];
          v[3] = (v[3] & ~1u) | z[3];
          st128_rlx(dst + (lane >> 4) * 80, v);
          if (lane < 16) st128_rlx(dst + 160, z);
        }
      }
    }
    bar_sync(1, 256);
    if (tid == 0) { st_rlx(FLAG(0, r, c), epoch); mbar_arrive(BAR(BR_PUB)); TS(4); }
    const int kvi = (tid >= 80) + (tid >= 160) + (tid >= 240), kd = tid - 80 * kvi;
    const int khd = kd / 20, kt0 = 5 * (khd >> 1) + 2 * (khd & 1);
    const uint32_t rb = sb + OFF_KVB + kd * 16;
    if (kvi < 3) {
      #pragma unroll 1
      for (int m = kvi; m < 7; m += 3) { const int q = kt0 + 3 + m; sts128(rb + (q >= 10 ? q - 10 : q) * 1280, 0, 0, 0, 0); }
    }
    uint32_t qa[20];
    {
      const float sc = 1.44269504089f + __uint_as_float(lds32(sb + OFF_EPOCH) ^ epoch);
      #pragma unroll
      for (int j = 0; j < 10; j++) { qa[2 * j] = pack2(phi(QV(j, 0), sc), phi(QV(j, 1), sc)); qa[2 * j + 1] = pack2(phi(QV(j, 2), sc), phi(QV(j, 3), sc)); }
    }
    if (tid == 0) TS(5);
    if (warp == 7) mbar_wait(BAR(BR_KVP), 0);
    bar_sync(1, 256);
    if (tid == 0) TS(6);
    if (kvi < 3) {
      float s[8];
      zero<8>(s);
      uint32_t bad = 0;
      #pragma unroll 4
      for (int i = 0; i < 16; i += 2) {
        uint32_t w[4], x[4];
        lds128(w, sb + OFF_KVP + tid * 16 + i * 3840); lds128(x, sb + OFF_KVP + tid * 16 + i * 3840 + 3840);
        bad |= (w[3] ^ epoch) | (x[3] ^ epoch);
        #pragma unroll
        for (int e = 0; e < 4; e++) {
          asm("add.rn.bf16x2 %0, %0, %1;" : "+r"(w[e]) : "r"(x[e]));
          s[2 * e] += bf_lo(w[e]); s[2 * e + 1] += bf_hi(w[e]);
        }
      }
      if (__builtin_expect(bad & 1u, 0)) {
        zero<8>(s);
        #pragma unroll 1
        for (int i = 0; i < 16; i++) {
          uint32_t w[4] = {0, 0, 0, ~epoch};
          fix128_w3(w, &g_kvp[(c * 16 + i) * 240 + tid], epoch, 1u);
          #pragma unroll
          for (int e = 0; e < 4; e++) { s[2 * e] += bf_lo(w[e]); s[2 * e + 1] += bf_hi(w[e]); }
        }
        FIXCNT
      }
      const uint32_t p0 = pack2(s[0], s[1]), p1 = pack2(s[2], s[3]), p2 = pack2(s[4], s[5]), p3 = pack2(s[6], s[7]);
      if (kvi < 2) sts128(rb + (kt0 + (khd & 1) + kvi) * 1280, p0, p1, p2, p3);
      else {
        const bool od = khd & 1;
        sts128(rb + (5 * (khd >> 1) + 2) * 1280, od ? 0u : p0, od ? 0u : p1, od ? p0 : 0u, od ? p1 : 0u);
        const uint32_t zz = (p2 & 0xffffu) << (16 * (khd & 1));
        sts128(rb + 10 * 1280, khd < 2 ? zz : 0u, khd < 2 ? 0u : zz, 0u, 0u);
      }
    }
    fence_async();
    bar_sync(1, 256);
    if (tid == 0) TS(7);
    {
      float oa[44]; zero<44>(oa);
      constexpr uint64_t db = mkdesc(SB0 + OFF_KVB, 128, 1280, 0);
      wg_fence();
      #pragma unroll
      for (int s = 0; s < 5; s++) wg_rs88_tb(oa, &qa[4 * s], desc2((uint32_t)db + ((s == 4 && (c & 1)) ? 0 : (s + (c & 1)) * 16), db >> 32), s != 0);
      wg_commit();
      wg_wait<0>();
      pin<44>(oa);
      if (tid == 0) TS(13);
      float rc[4], rd[2][4];
      #pragma unroll
      for (int e = 0; e < 4; e++) asm("rcp.approx.ftz.f32 %0, %1;" : "=f"(rc[e]) : "f"(oa[40 + e] + 1e-6f));
      #pragma unroll
      for (int h = 0; h < 4; h++) {
        rd[0][h] = __shfl_sync(0xffffffff, rc[h & 1], (lane & 28) | (h >> 1));
        rd[1][h] = __shfl_sync(0xffffffff, rc[2 + (h & 1)], (lane & 28) | (h >> 1));
      }
      #pragma unroll
      for (int j = 0; j < 10; j++) {
        #pragma unroll
        for (int h = 0; h < 2; h++) {
          float f;
          if (j == 2) f = tq < 2 ? rd[h][0] : rd[h][1];
          else if (j == 7) f = tq < 2 ? rd[h][2] : rd[h][3];
          else f = rd[h][(8 * j) / 20];
          qa[2 * j + h] = pack2(oa[4 * j + 2 * h] * f, oa[4 * j + 2 * h + 1] * f);
        }
      }
      const uint32_t m0 = (lane & 7) == ((2 * w4) & 7), m1 = (lane & 7) == 2 * w4 + 1;
      const uint32_t oa_ = sb + OFF_EXTRA + (lane >> 4) * 2048 + (warp * 16 + (lane & 15)) * 16;
      bar_sync(1, 256);
#define TAG(v, m) (((v) & ~(m)) | (epoch & (m)))
      #pragma unroll
      for (int s = 0; s < 5; s++) stsm4(oa_ + s * 4096, TAG(qa[4 * s], m0), TAG(qa[4 * s + 1], m1), TAG(qa[4 * s + 2], m0), TAG(qa[4 * s + 3], m1));
    }
    fence_async();
    __syncwarp();
    if (lane == 0) mbar_arrive(BAR(BR_OSTG));
    if (tid == 0) TS(8);
    }
    asm volatile("setmaxnreg.dec.sync.aligned.u32 136;");
  } else {
    const int g = lane >> 2, tq = lane & 3, t7 = tid & 127;
    asm volatile("bar.arrive 0, 512;" ::: "memory");
    if (EN_SSM) {
    {
      #pragma unroll 1
      for (int k = 0; k < 4; k++) {
        const uint32_t z = sb + OFF_BLK + k * BLK + t7 * 16;
        sts128(z + B_TBL, 0, 0, 0, 0); sts128(z + B_TBL + 2048, 0, 0, 0, 0);
      }
      if (t7 < 80) sts128(sb + OFF_BLK + (t7 >> 4) * BLK - 256 + (t7 & 15) * 16, 0, 0, 0, 0);
      const uint32_t ea = sb + OFF_BLK + (2 + (w4 & 1)) * BLK + (lane >> 4) * 7168 + ((lane >> 3) & 1) * 256 + (lane & 7) * 16 + (w4 >> 1) * 2048;
      constexpr uint64_t dE = mkdesc(SB0 + OFF_BLK + 2 * BLK, 128, 512, 0);
      const uint32_t xa = sb + OFF_BLK + 18560 + t7 * 8, xr_ = sb + OFF_BLK + 18560 + (t7 ^ 64) * 8;
      uint32_t pr[5][2];
      #pragma unroll
      for (int q = 0; q < 5; q++) {
        #pragma unroll
        for (int e = 0; e < 2; e++) pr[q][e] = __byte_perm(raw[q][e], __shfl_xor_sync(0xffffffff, raw[q][e], 1), (lane & 1) ? 0x3276 : 0x5410);
        const uint32_t m = __reduce_max_sync(0xffffffff, max(raw[q][1] & 0x7fffu, (raw[q][1] >> 16) & 0x7fffu));
        if (lane == 0) sts32(sb + OFF_EPOCH + 64 + q * 16 + w4 * 4, m);
      }
      bar_sync(4, 128);
      if (t7 == 0) TS(40);
      const int j = (w4 & 1) * 16 + (w4 >> 1) * 8 + g, i2 = tq < 2 ? 64 * tq + j : 32 * (tq - 2) + j;
      const uint32_t e2 = B_TBL + 4 * (tq < 2 ? T_F3 + (((i2 - 1) & 1) ? 80 : 0) + ((i2 - 1) >> 1) + 16 : T_F2 + (i2 & 1) * 96 + (i2 >> 1));
      const uint32_t e1 = tq < 2 ? (i2 ? e2 - 64 : B_TBL + 4 * (T_F2 + 175)) : B_TBL + 4 * (i2 ? T_F2 + ((2 * i2 - 1) & 3) * 48 + ((2 * i2 - 1) >> 2) : 16 + 511);
      const uint32_t e0 = B_TBL + (16 + 8 * j + 2 * tq) * 4;
      const float dtl = bf_round(expf(bf_lo(pd)));
      float hd[9];
      auto head = [&](int q) {
        const uint32_t pa0 = pr[0][0], pc0 = pr[0][1];
        const float dt = __shfl_sync(0xffffffff, dtl, q);
        #pragma unroll
        for (int e = 0; e < 2; e++) { pr[0][e] = pr[1][e]; pr[1][e] = pr[2][e]; pr[2][e] = pr[3][e]; pr[3][e] = pr[4][e]; }
        uint32_t mm[4];
        lds128(mm, sb + OFF_EPOCH + 64 + q * 16);
        const uint32_t ex = min(max(max(max(mm[0], mm[1]), max(mm[2], mm[3])) >> 7, 1u), 253u);
        const float sc = __uint_as_float((254u - ex) << 23);
        const float lr = -bf_round(expf(bf_lo(pa0))) * dt * 1.44269504089f;
        const float tn = bf_hi(pa0) * dt * 0.15915494309f;
        cexp_t(lr, -tn, hd[0], hd[1]);
        cexp_t(lr * 8.f, tn * 8.f, hd[2], hd[3]);
        cexp_t(lr * 64.f, tn * 64.f, hd[4], hd[5]);
        hd[6] = bf_lo(pc0) * sc; hd[7] = -bf_hi(pc0) * sc;
        hd[8] = 2.f * dt * __uint_as_float(ex << 23);
      };
      head(0);
      #pragma unroll 1
      for (int it = 0; it < 5; it++) {
        const int k = it;
        const uint32_t blk = sb + OFF_BLK + k * BLK;
        float fac = 0.f;
        float ka[24]; zero<24>(ka);
        {
          if (it == 4) {
            mbar_wait(BAR(BR_UOUT), 0);
            sts128(sb + OFF_UT + B_TBL + t7 * 16, 0, 0, 0, 0); sts128(sb + OFF_UT + B_TBL + 2048 + t7 * 16, 0, 0, 0, 0);
          }
          const uint32_t ga = ea + 4096 - (w4 >> 1) * 512;
#define PUT4(i, a, b, c_, d) sts128(((i) < 8 ? ea + ((i) >> 1) * 512 : ga + (((i) - 8) >> 1) * 512) + ((i) & 1) * 128, a, b, c_, d)
          float z2r, z2i, z4r, z4i, xr[8], xi[8], gr[8], gi[8], wr[9], wi[9];
          const float z1r = hd[0], z1i = hd[1];
          xr[1] = hd[2]; xi[1] = hd[3]; wr[0] = hd[4]; wi[0] = hd[5];
          fac = hd[8];
          xr[0] = 1.f; xi[0] = 0.f;
          csq(xr[1], xi[1], xr[2], xi[2]); cmul(xr[2], xi[2], xr[1], xi[1], xr[3], xi[3]);
          csq(xr[2], xi[2], xr[4], xi[4]);
          #pragma unroll
          for (int b = 1; b < 4; b++) cmul(xr[4], xi[4], xr[b], xi[b], xr[4 + b], xi[4 + b]);
          csq(wr[0], wi[0], wr[1], wi[1]); cmul(wr[1], wi[1], wr[0], wi[0], wr[2], wi[2]);
          csq(wr[1], wi[1], wr[3], wi[3]); csq(wr[3], wi[3], wr[4], wi[4]);
          cmul(wr[4], wi[4], wr[3], wi[3], wr[5], wi[5]); csq(wr[4], wi[4], wr[6], wi[6]);
          cmul(wr[6], wi[6], wr[4], wi[4], wr[7], wi[7]); csq(wr[6], wi[6], wr[8], wi[8]);
          uint32_t R[4], I[4], PR[4], PI[4];
          #pragma unroll
          for (int b = 0; b < 4; b++) { R[b] = packh(xr[2 * b], xr[2 * b + 1]); I[b] = packh(xi[2 * b], xi[2 * b + 1]); }
          PUT4(0, R[0], R[1], R[2], R[3]); PUT4(1, I[0], I[1], I[2], I[3]);
          #pragma unroll
          for (int i = 0; i < 3; i++) {
            const uint32_t z = packh(wr[i], wi[i]);
            #pragma unroll
            for (int b = 0; b < 4; b++) hcm2(R[b], I[b], z, PR[b], PI[b]);
            PUT4(2 * i + 2, PR[0], PR[1], PR[2], PR[3]); PUT4(2 * i + 3, PI[0], PI[1], PI[2], PI[3]);
          }
          gr[0] = hd[6]; gi[0] = hd[7];
          csq(z1r, z1i, z2r, z2i); csq(z2r, z2i, z4r, z4i);
          cmul(gr[0], gi[0], z1r, z1i, gr[1], gi[1]);
          cmul(gr[0], gi[0], z2r, z2i, gr[2], gi[2]); cmul(gr[1], gi[1], z2r, z2i, gr[3], gi[3]);
          #pragma unroll
          for (int b = 0; b < 4; b++) cmul(gr[b], gi[b], z4r, z4i, gr[4 + b], gi[4 + b]);
          PUT4(8, packh(gr[0], gr[1]), packh(gr[2], gr[3]), packh(gr[4], gr[5]), packh(gr[6], gr[7]));
          PUT4(9, packh(gi[0], gi[1]), packh(gi[2], gi[3]), packh(gi[4], gi[5]), packh(gi[6], gi[7]));
          {
            const uint32_t z = packh(wr[3], wi[3]), a4r = packh(gr[0], gr[4]), a4i = packh(gi[0], gi[4]);
            hcm2c(packh(gr[0], gr[2]), packh(gi[0], gi[2]), z, PR[0], PI[0]);
            hcm2c(packh(gr[4], gr[6]), packh(gi[4], gi[6]), z, PR[1], PI[1]);
            hcm2c(a4r, a4i, packh(wr[4], wi[4]), PR[2], PI[2]);
            hcm2c(a4r, a4i, packh(wr[5], wi[5]), PR[3], PI[3]);
            PUT4(10, PR[0], PR[1], PR[2], PR[3]); PUT4(11, PI[0], PI[1], PI[2], PI[3]);
            float hr, hi_;
            cmul(gr[0], gi[0], wr[3], -wi[3], hr, hi_);
            const uint32_t cr = packh(gr[0], hr), ci = packh(gi[0], hi_);
            #pragma unroll
            for (int i = 0; i < 3; i++) hcm2c(cr, ci, packh(wr[6 + i], wi[6 + i]), PR[i], PI[i]);
            PUT4(12, PR[0], PR[1], PR[2], 0u); PUT4(13, PI[0], PI[1], PI[2], 0u);
          }
          fence_async();
          bar_sync(4, 128);
          wg_fence();
          #pragma unroll
          for (int s = 0; s < 8; s++) {
            const uint64_t d = dE + (s >> 2) * (BLK >> 4) + ((s >> 1) & 1) * 448 + (s & 1) * 16;
            wg_ss48_tt_h(ka, d, d + 256, s != 0);
          }
          wg_commit();
        }
        sched_fence(sb + OFF_EPOCH + 64, 0xffffffffu);
        const float dsk = bf_lo(__shfl_sync(0xffffffff, pd, 8 + (it & 7)));
        head(min(it + 1, 4));
        sched_fence(sb + OFF_EPOCH + 64, __float_as_uint(hd[0] + hd[2] + hd[4]));
        wg_wait<0>();
        pin<24>(ka);
        float kk[6];
        const bool up = w4 >= 2;
        #pragma unroll
        for (int n = 0; n < 3; n++) {
          sts64f(xa + n * BLK, up ? ka[12 + 4 * n] : ka[4 * n + 2], up ? ka[13 + 4 * n] : ka[4 * n + 3]);
          kk[2 * n] = up ? ka[14 + 4 * n] : ka[4 * n]; kk[2 * n + 1] = up ? ka[15 + 4 * n] : ka[4 * n + 1];
        }
        if (it) bar_sync(4, 128); else bar_sync(8, 160);
          if (it == 4 && w4 == 0) {
            mbar_wait(BAR(BR_U), 0);
            if (elect_one()) {
              mbar_expect_tx(BAR(BR_U2), 8192);
              bulk_ld(blk - 2 * BLK, g_uy + (c * 80 + r * 5 + 2) * 2048, 4096, BAR(BR_U2)); bulk_ld(blk - BLK, g_uy + (c * 80 + r * 5 + 3) * 2048, 4096, BAR(BR_U2));
            }
            __syncwarp();
          }
        #pragma unroll
        for (int n = 0; n < 3; n++) {
          uint32_t o[2]; lds64(o, xr_ + n * BLK);
          kk[2 * n] = (kk[2 * n] + __uint_as_float(o[0])) * fac; kk[2 * n + 1] = (kk[2 * n + 1] + __uint_as_float(o[1])) * fac;
        }
        if (t7 == 0) kk[0] += dsk;
        {
          const uint32_t v = pack2(kk[1], kk[0]), vh = v >> 16;
          const uint32_t u = pack2(kk[2], kk[3]), w = pack2(kk[4], kk[5]), uu = pack2(kk[2], kk[2]), us = pack2(kk[3], kk[2]);
          const uint32_t x = tq < 2 ? w : u, xh = x >> 16;
          sts32(blk + e0 + 4, v); sts16(blk + e0, vh); sts16(blk + e0 + 10, v);
          sts16(blk + e1, x); sts16(blk + e1 + 6, x); sts16(blk + e2, xh); sts16(blk + e2 + 6, xh);
          if (tq < 2) {
            const uint32_t pb = blk + e0 + 1024 + 8 * tq;
            sts32(pb + 4, uu); sts32(pb + 8, us); sts16(pb + 14, us);
            if (i2) { sts16(pb - 4, u); sts32(pb, uu); }
          }
          if (i2 == 0) {
            const uint32_t tb = blk + B_TBL;
            if (tq == 0) { sts16(tb + (16 + 256) * 4, u); sts16(tb + (T_S + 3) * 4, w); sts32(tb + (T_S + 4) * 4, pack2(kk[4], kk[4])); sts16(tb + (T_S + 5) * 4 + 2, w); }
            else { sts32(tb + 528 * 4, uu); sts32(tb + 529 * 4, uu); sts32(tb + 530 * 4, uu); sts16(tb + 531 * 4 + 2, u); sts16(tb + (T_F3 + 80 + 63) * 4, w); }
          }
        }
        if (t7 == 0) TS(49 + it);
      }
    }
    asm volatile("setmaxnreg.inc.sync.aligned.u32 136;");
    if (t7 == 0) TS(41);
    bar_sync(4, 128);
    if (t7 == 0) mbar_arrive(BAR(BR_KS));
    }
  }
  const int tid = rtid(), lane = tid & 31, g = lane >> 2, tq = lane & 3, t7 = tid & 127;
  mbar_wait(BAR(BR_EPOCH), 0);
  const unsigned epoch = lds32(sb + OFF_EPOCH);
  const uint32_t ytag = (epoch & 1u) * 0x10001u, ym = lane < 4 ? 0x10001u : 0u;
  if (EN_SSM && wg != 1) {
    mbar_wait(BAR(BR_KS), 0);
    mbar_wait(BAR(BR_U), 0);
    if (EN_ATT) mbar_wait(BAR(BR_GEMM), 0);
    if (tid == 256) TS(42);
    {
      const int pass = wg >> 1;
      const int k = pass ? w4 : 4;
      if (k & 2) mbar_wait(BAR(BR_U2), 0);
      const uint32_t blk = sb + OFF_BLK + k * BLK, tb = blk + B_TBL + (uint32_t)((g - 2 * tq) * 4);
      float acc[16][4];
      zero<64>(&acc[0][0]);
      const int kl = 16 * (lane >> 4) + 2 * (lane & 7) + ((lane >> 3) & 1);
      {
        auto ubase = [&](int sh) { const int q = kl - 2 * sh; return blk + (uint32_t)((q * 16) ^ ((q * 2) & 0x10)); };
#define LDQ(A, sh) _Pragma("unroll") for (int m = 0; m < 4; m++) load_quad(A[m], tb + (16 + 16 * (sh) + 128 * m) * 4);
#define LDB(B, ub, h) _Pragma("unroll") for (int p = 0; p < 4; p++) ldsm4(B[p], (ub) + (4 * (h) + p) * 512);
#define MLO(A, B) _Pragma("unroll") for (int m = 0; m < 4; m++) _Pragma("unroll") for (int cc = 0; cc < 8; cc++) mma16816(acc[cc + m], A[m], &B[cc >> 1][(cc & 1) * 2]);
#define MHI(A, B) _Pragma("unroll") for (int m = 0; m < 4; m++) _Pragma("unroll") for (int cc = 0; cc < 8 - m; cc++) mma16816(acc[8 + cc + m], A[m], &B[cc >> 1][(cc & 1) * 2]);
        int p_ = pass ? 0 : w4;
        const int pe = pass ? 4 : w4 + 1;
        uint32_t A[4][4], A2[4][4], Bl[4][4], Bh[4][4];
        uint32_t ub = ubase(p_ + 4);
        LDQ(A, p_ + 4) LDB(Bl, ub, 0)
        #pragma unroll 1
        for (; p_ < pe; p_++) {
          LDB(Bh, ub, 1)
          MLO(A, Bl)
          ub = ubase(p_);
          LDQ(A2, p_) LDB(Bl, ub, 0)
          MHI(A, Bh)
          LDB(Bh, ub, 1)
          load_quad(A[0], tb + (16 + 512 + 16 * (p_ & 1)) * 4); load_quad(A[1], tb + (T_S + 16 * (p_ & 1)) * 4);
          MLO(A2, Bl)
          if (p_ < 2) {
            #pragma unroll
            for (int cc = 0; cc < 8; cc++) mma16816(acc[cc + 4], A[0], &Bl[cc >> 1][(cc & 1) * 2]);
            #pragma unroll
            for (int cc = 0; cc < 4; cc++) mma16816(acc[cc + 12], A[0], &Bh[cc >> 1][(cc & 1) * 2]);
            #pragma unroll
            for (int cc = 0; cc < 8; cc++) mma16816(acc[cc + 8], A[1], &Bl[cc >> 1][(cc & 1) * 2]);
          }
          const int pn = ((p_ + 1) & 3) + 4;
          ub = ubase(pn);
          LDQ(A, pn) LDB(Bl, ub, 0)
          MHI(A2, Bh)
        }
      }
      if (t7 == 0) TS(pass ? 60 : 16);
      mbar_wait(BAR(BR_DRDY), 0);
      {
        const int ih = (lane >> 3) & 1;
        const uint32_t dl = blk + B_D + (uint32_t)(((lane >> 4) * 8 + (lane & 7)) * 16);
        const uint32_t d0_ = dl + ih * 1552, d8_ = dl + (ih ? 0 : 1536), d3_ = dl + B_D7 + ih * 1024;
        auto cls2 = [&](uint32_t da, uint32_t ta) {
          uint32_t B[6][2], A[6][4];
          #pragma unroll
          for (int e = 0; e < 6; e++) { B[e][0] = lds32v(ta + (e + 4) * 32); B[e][1] = lds32v(ta + (e + 3) * 32); }
          #pragma unroll
          for (int kk = 0; kk < 6; kk++) ldsm4t(A[kk], da + kk * 256);
          #pragma unroll
          for (int e = 0; e < 6; e++)
            #pragma unroll
            for (int kk = 0; kk < 6; kk++) if (2 * kk + e + 4 < 16) mma16816(acc[2 * kk + e + 4], A[kk], B[e]);
        };
        auto cls3 = [&](uint32_t da, uint32_t ta) {
          uint32_t B[8][2], A[4][4];
          #pragma unroll
          for (int e = 0; e < 8; e++) { B[e][0] = lds32v(ta + (e + 8) * 32); B[e][1] = lds32v(ta + (e + 7) * 32); }
          #pragma unroll
          for (int kk = 0; kk < 4; kk++) ldsm4t(A[kk], da + kk * 256);
          #pragma unroll
          for (int kk = 0; kk < 4; kk++)
            #pragma unroll
            for (int e = 0; e < 8; e++) if (2 * kk + e + 8 < 16) mma16816(acc[2 * kk + e + 8], A[kk], B[e]);
        };
        if (pass) {
          #pragma unroll 1
          for (int a = 0; a < 2; a++) {
            cls2(d0_ + a * B_D5, tb + (T_F2 + 48 * a - 32) * 4);
            cls2(d8_ + a * B_D5, tb + (T_F2 + 48 * a + 64) * 4);
            cls3(d3_ + a * 2048, tb + (T_F3 + 80 * a - 64) * 4);
          }
        } else {
          cls2(((w4 & 2) ? d8_ : d0_) + (w4 & 1) * B_D5, tb + (T_F2 + 48 * w4 - 32) * 4);
          if (w4 >= 2) cls3(d3_ + (w4 - 2) * 2048, tb + (T_F3 + 80 * (w4 - 2) - 64) * 4);
        }
      }
      if (t7 == 0) TS(pass ? 61 : 17);
      const uint32_t ya = (pass ? sb + OFF_BLK + 3 * BLK + w4 * 4096 : blk) + (uint32_t)((kl * 16) ^ ((kl * 2) & 0x10));
#define YTAG(v) (((v) & ~ym) | (ytag & ym))
#define STY(p) stsm4t(ya + (p) * 512, YTAG(pack2(acc[2 * (p)][0], acc[2 * (p)][1])), pack2(acc[2 * (p)][2], acc[2 * (p)][3]), \
                      YTAG(pack2(acc[2 * (p) + 1][0], acc[2 * (p) + 1][1])), pack2(acc[2 * (p) + 1][2], acc[2 * (p) + 1][3]))
      if (pass == 0) {
        const uint32_t xw = blk + 4096 + w4 * 4096 + lane * 16, xr = blk + 4096 + w4 * 1024 + lane * 16;
        #pragma unroll
        for (int h = 0; h < 2; h++) {
          bar_sync(2, 128);
          #pragma unroll
          for (int i = 0; i < 8; i++)
            sts128(xw + i * 512, __float_as_uint(acc[8 * h + i][0]), __float_as_uint(acc[8 * h + i][1]), __float_as_uint(acc[8 * h + i][2]), __float_as_uint(acc[8 * h + i][3]));
          bar_sync(2, 128);
          float y[8];
          #pragma unroll
          for (int i = 0; i < 8; i++) {
            uint32_t o[4]; lds128(o, xr + (i >> 1) * 4096 + (i & 1) * 512);
            #pragma unroll
            for (int e = 0; e < 4; e++) y[4 * (i & 1) + e] = i < 2 ? __uint_as_float(o[e]) : y[4 * (i & 1) + e] + __uint_as_float(o[e]);
          }
          stsm4t(ya + (4 * h + w4) * 512, YTAG(pack2(y[0], y[1])), pack2(y[2], y[3]), YTAG(pack2(y[4], y[5])), pack2(y[6], y[7]));
        }
      } else {
        fence_async();
        bar_sync(4, 128);
        if (t7 == 0) mbar_arrive(BAR(BR_KS + 1));
        #pragma unroll
        for (int p = 0; p < 8; p++) STY(p);
      }
      fence_async();
      __syncwarp();
      if (lane == 0) mbar_arrive(BAR(BR_Y + 1) - 8 * pass);
      if (t7 == 0) TS(pass ? 62 : 18);
    }
  }
  if (wg < 2) {
    if (EN_ATT) {
    float oc[40]; zero<40>(oc);
    {
      constexpr uint64_t dw0 = mkdesc(SB0, OFF_WOR, 1024, 1), da0 = mkdesc(SB0, 2048, 128, 0);
      const uint32_t ck = sb + tid * 32 + ((lane >> 2) << 2), ck2 = ck + (wg ? 0 : 16384);
      uint32_t bad = 0;
      auto tile = [&](int i, uint32_t so) {
        const uint32_t al = (uint32_t)da0 + wg * 64 + (so >> 4), wl = (uint32_t)dw0 + i * 640 - (i >> 1) * (1278 << 16);
        wg_fence();
        #pragma unroll
        for (int s = 0; s < 5; s++) wg_ss80_tb(oc, desc2(al + s * 256, da0 >> 32), desc2(wl + s * 128, dw0 >> 32), (i | s) != 0);
        wg_commit();
        bad |= (lds32(ck + so) ^ epoch) | (lds32(ck + so + 8192) ^ epoch) | (lds32(ck2 + so) ^ epoch);
      };
      if (w4 == 0) {
        if (EN_SSM) mbar_wait(BAR(BR_Y), 0);
        mbar_wait(BAR(BR_WO), 0);
      }
      bar_sync(1, 256);
      if (tid == 0) TS(9);
      tile(0, SLOT(0));
      #pragma unroll 1
      for (int i = 1; i < 8; i++) {
        mbar_wait(BAR(BR_OFULL) + 8 * i, 0);
        tile(i, SLOT(i));
        wg_wait<1>();
        if (lane == 0) mbar_arrive(BAR(BR_OEMPTY - 1) + 8 * i);
      }
      #pragma unroll 1
      for (int n = 0; n < 56; n++) {
        const int i = n & 7;
        if (i == 0) {
          uint32_t any;
          asm volatile("{\n.reg .pred p;\nsetp.ne.u32 p, %1, 0;\nbarrier.red.or.pred p, 1, 256, p;\nselp.u32 %0, 1, 0, p;\n}" : "=r"(any) : "r"(bad & 1u) : "memory");
          if (!any) break;
          bad = 0;
          FIXCNT
        }
        wg_wait<0>();
        bar_sync(1, 256);
        if (tid == 0) { mbar_expect_tx(BAR(BR_RETRY), 20480); bulk_ld(sb + SLOT(2), &g_o[(r * 8 + CHUNK(i)) * 1280], 20480, BAR(BR_RETRY)); }
        mbar_wait(BAR(BR_RETRY), n & 1);
        tile(i, SLOT(2));
      }
      wg_wait<0>();
      pin<40>(oc);
    }
    if (tid == 0) TS(10);
    {
      const int row = w4 * 16 + (lane & 15);
      const uint32_t ob = sb + OFF_BLK + 3 * BLK + wg * 10240;
      #pragma unroll
      for (int j = 0; j < 8; j += 2)
        stsm4(ob + row * 128 + (((j + (lane >> 4)) ^ (row & 7)) << 4), pack2(oc[4 * j], oc[4 * j + 1]), pack2(oc[4 * j + 2], oc[4 * j + 3]),
              pack2(oc[4 * j + 4], oc[4 * j + 5]), pack2(oc[4 * j + 6], oc[4 * j + 7]));
      stsm4(ob + 8192 + row * 32 + (lane >> 4) * 16, pack2(oc[32], oc[33]), pack2(oc[34], oc[35]), pack2(oc[36], oc[37]), pack2(oc[38], oc[39]));
      fence_async();
      bar_sync(2 + wg, 128);
      if (w4 == 0 && elect_one()) {
        tma2d_st(&prm.m[M_O64], ob, 640 + c * 64, r * 128 + wg * 64);
        tma2d_st(&prm.m[M_O16], ob + 8192, 1152 + c * 16, r * 128 + wg * 64);
        bulk_commit(); bulk_wait0_read();
        if (wg == 0) { TS(11); DUMP(0, 20); }
      }
    }
    }
  } else if (EN_SSM) {
    if (t7 == 0) DUMP(40, 64);
    #pragma unroll 1
    for (int n = 0; n < 64; n++) if (!y_transpose(sb, w4, lane, ytag)) break;
  }
  }
}

typedef CUresult (*EncFn)(CUtensorMap*, CUtensorMapDataType, cuuint32_t, void*, const cuuint64_t*, const cuuint64_t*, const cuuint32_t*,
                          const cuuint32_t*, CUtensorMapInterleave, CUtensorMapSwizzle, CUtensorMapL2promotion, CUtensorMapFloatOOBfill);
static void mkmap(EncFn enc, CUtensorMap* m, const void* base, int rank, const cuuint64_t* dims, const cuuint64_t* strides, const cuuint32_t* box, CUtensorMapSwizzle swz) {
  cuuint32_t es[5] = {1, 1, 1, 1, 1};
  enc(m, CU_TENSOR_MAP_DATA_TYPE_BFLOAT16, rank, const_cast<void*>(base), dims, strides, box, es, CU_TENSOR_MAP_INTERLEAVE_NONE, swz,
      CU_TENSOR_MAP_L2_PROMOTION_L2_128B, CU_TENSOR_MAP_FLOAT_OOB_FILL_NONE);
}

extern "C" void kernel_launch(void* const* d_in, const int* in_sizes, int n_in, void* d_out, int out_size) {
  void* fn = nullptr; cudaDriverEntryPointQueryResult qr;
  cudaGetDriverEntryPoint("cuTensorMapEncodeTiled", &fn, cudaEnableDefault, &qr);
  EncFn enc = (EncFn)fn;
  void* uy = nullptr; cudaGetSymbolAddress(&uy, g_uy);
  const cuuint64_t dx[2] = {640, 2048}, sx[1] = {1280};
  const cuuint32_t bx[2] = {64, 128}, bu[2] = {80, 128};
  const cuuint64_t dw[3] = {640, 640, 3}, sw[2] = {3840, 1280};
  const cuuint32_t br[3] = {16, 32, 3};
  const cuuint64_t dwa[4] = {64, 640, 10, 3}, swa[3] = {3840, 128, 1280}, dwb[4] = {32, 640, 20, 3}, swb[3] = {3840, 64, 1280};
  const cuuint32_t bwa[4] = {64, 32, 1, 3}, bwb[4] = {32, 32, 2, 3};
  const cuuint64_t dwo[2] = {640, 640};
  const cuuint32_t bwo[2] = {64, 80}, bo64[2] = {64, 64}, bo16[2] = {16, 64};
  const cuuint64_t dsa[2] = {2048, 1280}, ssa[1] = {4096};
  const cuuint32_t bsa[2] = {64, 80};
  const cuuint64_t dout[2] = {1280, 2048}, sout[1] = {2560};
  Params prm;
  mkmap(enc, &prm.m[M_X], d_in[7], 2, dx, sx, bx, CU_TENSOR_MAP_SWIZZLE_128B);
  mkmap(enc, &prm.m[M_W128], d_in[8], 4, dwa, swa, bwa, CU_TENSOR_MAP_SWIZZLE_128B);
  mkmap(enc, &prm.m[M_W64], d_in[8], 4, dwb, swb, bwb, CU_TENSOR_MAP_SWIZZLE_64B);
  mkmap(enc, &prm.m[M_WR], d_in[8], 3, dw, sw, br, CU_TENSOR_MAP_SWIZZLE_32B);
  mkmap(enc, &prm.m[M_U], d_in[0], 2, dx, sx, bu, CU_TENSOR_MAP_SWIZZLE_NONE);
  mkmap(enc, &prm.m[M_WO], d_in[9], 2, dwo, sx, bwo, CU_TENSOR_MAP_SWIZZLE_128B);
  mkmap(enc, &prm.m[M_O64], d_out, 2, dout, sout, bo64, CU_TENSOR_MAP_SWIZZLE_128B);
  mkmap(enc, &prm.m[M_O16], d_out, 2, dout, sout, bo16, CU_TENSOR_MAP_SWIZZLE_NONE);
  mkmap(enc, &prm.m[M_SA], uy, 2, dsa, ssa, bsa, CU_TENSOR_MAP_SWIZZLE_128B);
  mkmap(enc, &prm.m[M_OUT], d_out, 2, dout, sout, bu, CU_TENSOR_MAP_SWIZZLE_NONE);
  prm.u = (const __nv_bfloat16*)d_in[0]; prm.wo = (const __nv_bfloat16*)d_in[9];
  for (int i = 0; i < 4; i++) prm.par[i] = (const __nv_bfloat16*)d_in[1 + i];
  prm.logdt = (const __nv_bfloat16*)d_in[5]; prm.dskip = (const __nv_bfloat16*)d_in[6];
  cudaFuncSetAttribute(fused_kernel, cudaFuncAttributeMaxDynamicSharedMemorySize, SMEM_BYTES);
  fused_kernel<<<128, 512, SMEM_BYTES, cudaStreamPerThread>>>(prm);
}
```

```cpp
#include <cuda_runtime.h>
#include <cuda_bf16.h>
#include <cuda_fp16.h>
#include <cuda.h>
#include <stdint.h>

#define EN_ATT 1
#define EN_SSM 1

__device__ __align__(1024) __nv_bfloat16 g_uy[2 * 640 * 2048];
__device__ __align__(128) uint4 g_kvp[8 * 16 * 240];
__device__ __align__(128) uint4 g_o[128 * 1280];
__device__ __align__(128) unsigned g_flag[4 * 128 * 32];
__device__ unsigned g_epoch[128];
#define TS(i) do {} while (0)
#define DUMP(lo, hi) do {} while (0)
#define FIXCNT

constexpr uint32_t SB0 = 1024;
constexpr uint32_t W_SLOT = 15360, OFF_X = 76800;
constexpr uint32_t OFF_WOR = 81920, OFF_KVP = 10240, OFF_KVS = 71680, OFF_PK = 10240, OFF_V = 30720, OFF_EXTRA = 102400, OFF_KVB = OFF_WOR;
constexpr uint32_t OFF_BAR = 125952, OFF_BLK = 128000, BLK = 20480;
constexpr uint32_t B_D = 4096, B_D5 = 3088, B_D7 = 6176, B_D9 = 8224, B_TBL = 14400;
constexpr int T_S = 576, T_F2 = 624, T_F3 = 816;
constexpr uint32_t OFF_UT = OFF_BLK + 4 * BLK;
constexpr uint32_t SMEM_BYTES = OFF_BLK + 5 * BLK;
enum { BR_FULL = 0, BR_WO = 5, BR_PUB = 6, BR_KVP = 7, BR_U = 8, BR_U2 = 9, BR_GEMM = 10, BR_UIN = 11, BR_YIN = 12, BR_EPOCH = 13,
       BR_FREE = 14, BR_RETRY = 16, BR_KS = 17, BR_UOUT = 19, BR_OFULL = 19  , BR_EMPTY = 27, BR_OEMPTY = 32, BR_OSTG = 39,
       BR_Y = 40, BR_DRDY = 42, BR_COUNT = 44 };
constexpr uint32_t OFF_EPOCH = OFF_BAR + 8 * BR_COUNT;
enum { M_X, M_W128, M_W64, M_WR, M_U, M_WO, M_O64, M_O16, M_SA, M_OUT, M_COUNT };

__device__ __forceinline__ long long clk64() { long long t; asm volatile("mov.u64 %0, %%clock64;" : "=l"(t) :: "memory"); return t; }
__device__ __forceinline__ uint32_t smem_u32(const void* p) { return (uint32_t)__cvta_generic_to_shared(p); }
__host__ __device__ constexpr uint64_t mkdesc(uint32_t addr, uint32_t lbo, uint32_t sbo, uint32_t swz) {
  return (uint64_t)((addr & 0x3FFFF) >> 4) | ((uint64_t)(lbo >> 4) << 16) | ((uint64_t)(sbo >> 4) << 32) | ((uint64_t)swz << 62);
}
__device__ __forceinline__ uint64_t desc2(uint32_t lo, uint32_t hi) { uint64_t d; asm("mov.b64 %0, {%1, %2};" : "=l"(d) : "r"(lo), "r"(hi)); return d; }
__device__ __forceinline__ void mbar_init(uint32_t bar, uint32_t cnt) { asm volatile("mbarrier.init.shared::cta.b64 [%0], %1;" :: "r"(bar), "r"(cnt) : "memory"); }
__device__ __forceinline__ void mbar_expect_tx(uint32_t bar, uint32_t bytes) { asm volatile("mbarrier.arrive.expect_tx.shared::cta.b64 _, [%0], %1;" :: "r"(bar), "r"(bytes) : "memory"); }
__device__ __forceinline__ void mbar_arrive(uint32_t bar) { asm volatile("mbarrier.arrive.shared::cta.b64 _, [%0];" :: "r"(bar) : "memory"); }
__device__ __forceinline__ void mbar_wait(uint32_t bar, uint32_t parity) {
  asm volatile("{\n.reg .pred p;\n.reg .u32 c;\nmov.u32 c, 0;\n"
    "WL:\nmbarrier.try_wait.parity.shared::cta.b64 p, [%0], %1;\n@p bra WD;\n"
    "add.u32 c, c, 1;\nsetp.lt.u32 p, c, 200000;\n@p bra WL;\nWD:\n}" :: "r"(bar), "r"(parity) : "memory");
}
__device__ __forceinline__ void poll_all(const unsigned* p, unsigned val) {
  asm volatile("{\n.reg .pred p;\n.reg .u32 c, v;\nmov.u32 c, 0;\n"
    "PL:\nld.relaxed.gpu.global.u32 v, [%0];\nsetp.eq.u32 p, v, %1;\nvote.sync.all.pred p, p, 0xffffffff;\n@p bra PD;\n"
    "add.u32 c, c, 1;\nsetp.lt.u32 p, c, 100000;\n@p bra PL;\nPD:\n}" :: "l"(p), "r"(val) : "memory");
}
__device__ __forceinline__ void poll_all_acq(const unsigned* p, unsigned val) {
  asm volatile("{\n.reg .pred p;\n.reg .u32 c, v;\nmov.u32 c, 0;\n"
    "PL:\nld.acquire.gpu.global.u32 v, [%0];\nsetp.eq.u32 p, v, %1;\nvote.sync.all.pred p, p, 0xffffffff;\n@p bra PD;\n"
    "nanosleep.u32 300;\nadd.u32 c, c, 1;\nsetp.lt.u32 p, c, 100000;\n@p bra PL;\nPD:\n}" :: "l"(p), "r"(val) : "memory");
}
__device__ __forceinline__ unsigned poll_bit(const unsigned* p, unsigned val, unsigned mask) {
  unsigned bal;
  asm volatile("{\n.reg .pred p;\n.reg .u32 c, v;\nmov.u32 c, 0;\n"
    "PL:\nld.relaxed.gpu.global.u32 v, [%1];\nsetp.eq.u32 p, v, %2;\nvote.sync.ballot.b32 %0, p, 0xffffffff;\n"
    "and.b32 v, %0, %3;\nsetp.ne.u32 p, v, 0;\n@p bra PD;\n"
    "add.u32 c, c, 1;\nsetp.lt.u32 p, c, 100000;\n@p bra PL;\nPD:\n}" : "=&r"(bal) : "l"(p), "r"(val), "r"(mask) : "memory");
  return bal;
}
__device__ __forceinline__ void fix128_w3(uint32_t* v, const void* p, uint32_t tag, uint32_t mask) {
  asm volatile("{\n.reg .pred p;\n.reg .u32 c, x;\n.reg .b128 t;\n.reg .b64 lo, hi;\nmov.u32 c, 0;\n"
    "FL:\nxor.b32 x, %3, %5;\nand.b32 x, x, %6;\nsetp.eq.u32 p, x, 0;\n@p bra FD;\n"
    "ld.relaxed.gpu.global.b128 t, [%4];\nmov.b128 {lo, hi}, t;\nmov.b64 {%0, %1}, lo;\nmov.b64 {%2, %3}, hi;\n"
    "add.u32 c, c, 1;\nsetp.lt.u32 p, c, 100000;\n@p bra FL;\nFD:\n}"
    : "+r"(v[0]), "+r"(v[1]), "+r"(v[2]), "+r"(v[3]) : "l"(p), "r"(tag), "r"(mask) : "memory");
}
__device__ __forceinline__ bool elect_one() {
  uint32_t p; asm volatile("{\n.reg .pred P;\nelect.sync _|P, 0xffffffff;\nselp.u32 %0, 1, 0, P;\n}" : "=r"(p)); return p;
}
__device__ __forceinline__ void bar_sync(int id, int n) { asm volatile("bar.sync %0, %1;" :: "r"(id), "r"(n) : "memory"); }
__device__ __forceinline__ void fence_async() { asm volatile("fence.proxy.async.shared::cta;" ::: "memory"); }
__device__ __forceinline__ void fence_async_g() { asm volatile("fence.proxy.async.global;" ::: "memory"); }
__device__ __forceinline__ void tma2d(uint32_t dst, const CUtensorMap* m, uint32_t bar, int c0, int c1) {
  asm volatile("cp.async.bulk.tensor.2d.shared::cluster.global.mbarrier::complete_tx::bytes [%0], [%1, {%3, %4}], [%2];"
    :: "r"(dst), "l"(m), "r"(bar), "r"(c0), "r"(c1) : "memory");
}
__device__ __forceinline__ void tma3d(uint32_t dst, const CUtensorMap* m, uint32_t bar, int c0, int c1, int c2) {
  asm volatile("cp.async.bulk.tensor.3d.shared::cluster.global.mbarrier::complete_tx::bytes [%0], [%1, {%3, %4, %5}], [%2];"
    :: "r"(dst), "l"(m), "r"(bar), "r"(c0), "r"(c1), "r"(c2) : "memory");
}
__device__ __forceinline__ void tma4d(uint32_t dst, const CUtensorMap* m, uint32_t bar, int c0, int c1, int c2, int c3) {
  asm volatile("cp.async.bulk.tensor.4d.shared::cluster.global.mbarrier::complete_tx::bytes [%0], [%1, {%3, %4, %5, %6}], [%2];"
    :: "r"(dst), "l"(m), "r"(bar), "r"(c0), "r"(c1), "r"(c2), "r"(c3) : "memory");
}
__device__ __forceinline__ void tma2d_st(const CUtensorMap* m, uint32_t src, int c0, int c1) {
  asm volatile("cp.async.bulk.tensor.2d.global.shared::cta.bulk_group [%0, {%2, %3}], [%1];"
    :: "l"(m), "r"(src), "r"(c0), "r"(c1) : "memory");
}
__device__ __forceinline__ void bulk_ld(uint32_t dst, const void* src, uint32_t bytes, uint32_t bar) {
  asm volatile("cp.async.bulk.shared::cluster.global.mbarrier::complete_tx::bytes [%0], [%1], %2, [%3];"
    :: "r"(dst), "l"(src), "r"(bytes), "r"(bar) : "memory");
}
__device__ __forceinline__ void bulk_st(void* dst, uint32_t src, uint32_t bytes) {
  asm volatile("cp.async.bulk.global.shared::cta.bulk_group [%0], [%1], %2;" :: "l"(dst), "r"(src), "r"(bytes) : "memory");
}
__device__ __forceinline__ void bulk_commit() { asm volatile("cp.async.bulk.commit_group;" ::: "memory"); }
__device__ __forceinline__ void bulk_wait0() { asm volatile("cp.async.bulk.wait_group 0;" ::: "memory"); }
__device__ __forceinline__ void bulk_wait0_read() { asm volatile("cp.async.bulk.wait_group.read 0;" ::: "memory"); }
__device__ __forceinline__ unsigned ld_rlx(const unsigned* p) { unsigned v; asm volatile("ld.relaxed.gpu.global.u32 %0, [%1];" : "=r"(v) : "l"(p) : "memory"); return v; }
__device__ __forceinline__ unsigned ld_acq(const unsigned* p) { unsigned v; asm volatile("ld.acquire.gpu.global.u32 %0, [%1];" : "=r"(v) : "l"(p) : "memory"); return v; }
__device__ __forceinline__ void st_rlx(unsigned* p, unsigned v) { asm volatile("st.relaxed.gpu.global.u32 [%0], %1;" :: "l"(p), "r"(v) : "memory"); }
__device__ __forceinline__ void st_rel(unsigned* p, unsigned v) { asm volatile("st.release.gpu.global.u32 [%0], %1;" :: "l"(p), "r"(v) : "memory"); }
__device__ __forceinline__ void st128_rlx(void* p, const uint32_t* v) {
  asm volatile("{\n.reg .b128 t;\n.reg .b64 lo, hi;\nmov.b64 lo, {%1, %2};\nmov.b64 hi, {%3, %4};\nmov.b128 t, {lo, hi};\n"
    "st.relaxed.gpu.global.b128 [%0], t;\n}" :: "l"(p), "r"(v[0]), "r"(v[1]), "r"(v[2]), "r"(v[3]) : "memory");
}
__device__ __forceinline__ uint32_t lds32(uint32_t a) { uint32_t v; asm volatile("ld.shared.u32 %0, [%1];" : "=r"(v) : "r"(a) : "memory"); return v; }
__device__ __forceinline__ uint32_t lds32v(uint32_t a) { uint32_t v; asm volatile("ld.volatile.shared.u32 %0, [%1];" : "=r"(v) : "r"(a) : "memory"); return v; }
__device__ __forceinline__ void lds128(uint32_t* v, uint32_t a) { asm volatile("ld.shared.v4.u32 {%0,%1,%2,%3}, [%4];" : "=r"(v[0]), "=r"(v[1]), "=r"(v[2]), "=r"(v[3]) : "r"(a) : "memory"); }
__device__ __forceinline__ void sts32(uint32_t a, uint32_t v) { asm volatile("st.shared.u32 [%0], %1;" :: "r"(a), "r"(v) : "memory"); }
__device__ __forceinline__ void sts16(uint32_t a, uint32_t v) { asm volatile("st.shared.u16 [%0], %1;" :: "r"(a), "h"((uint16_t)v) : "memory"); }
__device__ __forceinline__ void sts64f(uint32_t a, float x, float y) { asm volatile("st.shared.v2.f32 [%0], {%1,%2};" :: "r"(a), "f"(x), "f"(y) : "memory"); }
__device__ __forceinline__ void sts128(uint32_t a, uint32_t x, uint32_t y, uint32_t z, uint32_t w) { asm volatile("st.shared.v4.u32 [%0], {%1,%2,%3,%4};" :: "r"(a), "r"(x), "r"(y), "r"(z), "r"(w) : "memory"); }
__device__ __forceinline__ void stsm4(uint32_t a, uint32_t r0, uint32_t r1, uint32_t r2, uint32_t r3) {
  asm volatile("stmatrix.sync.aligned.m8n8.x4.shared.b16 [%0], {%1,%2,%3,%4};" :: "r"(a), "r"(r0), "r"(r1), "r"(r2), "r"(r3) : "memory");
}
__device__ __forceinline__ void stsm4t(uint32_t a, uint32_t r0, uint32_t r1, uint32_t r2, uint32_t r3) {
  asm volatile("stmatrix.sync.aligned.m8n8.x4.trans.shared.b16 [%0], {%1,%2,%3,%4};" :: "r"(a), "r"(r0), "r"(r1), "r"(r2), "r"(r3) : "memory");
}
__device__ __forceinline__ void ldsm4t(uint32_t* r, uint32_t a) {
  asm volatile("ldmatrix.sync.aligned.m8n8.x4.trans.shared.b16 {%0,%1,%2,%3}, [%4];" : "=r"(r[0]), "=r"(r[1]), "=r"(r[2]), "=r"(r[3]) : "r"(a) : "memory");
}
__device__ __forceinline__ void ldsm4(uint32_t* r, uint32_t a) {
  asm volatile("ldmatrix.sync.aligned.m8n8.x4.shared.b16 {%0,%1,%2,%3}, [%4];" : "=r"(r[0]), "=r"(r[1]), "=r"(r[2]), "=r"(r[3]) : "r"(a) : "memory");
}
__device__ __forceinline__ void mma16816(float* d, const uint32_t* a, const uint32_t* b) {
  asm volatile("mma.sync.aligned.m16n8k16.row.col.f32.bf16.bf16.f32 {%0,%1,%2,%3}, {%4,%5,%6,%7}, {%8,%9}, {%0,%1,%2,%3};"
    : "+f"(d[0]), "+f"(d[1]), "+f"(d[2]), "+f"(d[3]) : "r"(a[0]), "r"(a[1]), "r"(a[2]), "r"(a[3]), "r"(b[0]), "r"(b[1]));
}
__device__ __forceinline__ uint32_t pack2(float lo, float hi) { uint32_t r; asm("cvt.rn.bf16x2.f32 %0, %1, %2;" : "=r"(r) : "f"(hi), "f"(lo)); return r; }
__device__ __forceinline__ uint32_t packh(float lo, float hi) { uint32_t r; asm("cvt.rn.f16x2.f32 %0, %1, %2;" : "=r"(r) : "f"(hi), "f"(lo)); return r; }
__device__ __forceinline__ void hcm2(uint32_t xr, uint32_t xi, uint32_t z, uint32_t& pr, uint32_t& pi) {
  const __half2 a = *reinterpret_cast<__half2*>(&xr), b = *reinterpret_cast<__half2*>(&xi), zz = *reinterpret_cast<__half2*>(&z);
  const __half2 re = __hfma2(__hneg2(b), __high2half2(zz), __hmul2(a, __low2half2(zz)));
  const __half2 im = __hfma2(a, __high2half2(zz), __hmul2(b, __low2half2(zz)));
  pr = *reinterpret_cast<const uint32_t*>(&re); pi = *reinterpret_cast<const uint32_t*>(&im);
}
__device__ __forceinline__ void hcm2c(uint32_t xr, uint32_t xi, uint32_t z, uint32_t& pr, uint32_t& pi) {
  const __half2 a = *reinterpret_cast<__half2*>(&xr), b = *reinterpret_cast<__half2*>(&xi), zz = *reinterpret_cast<__half2*>(&z);
  const __half2 re = __hfma2(b, __high2half2(zz), __hmul2(a, __low2half2(zz)));
  const __half2 im = __hfma2(__hneg2(a), __high2half2(zz), __hmul2(b, __low2half2(zz)));
  pr = *reinterpret_cast<const uint32_t*>(&re); pi = *reinterpret_cast<const uint32_t*>(&im);
}
__device__ __forceinline__ void lds64(uint32_t* v, uint32_t a) { asm volatile("ld.shared.v2.u32 {%0,%1}, [%2];" : "=r"(v[0]), "=r"(v[1]) : "r"(a) : "memory"); }
__device__ __forceinline__ float bf_lo(uint32_t v) { return __uint_as_float(v << 16); }
__device__ __forceinline__ float bf_hi(uint32_t v) { return __uint_as_float(v & 0xffff0000u); }
__device__ __forceinline__ float bf_round(float x) { return bf_lo(pack2(x, 0.f)); }
__device__ __forceinline__ float ex2(float x) { float r; asm("ex2.approx.ftz.f32 %0, %1;" : "=f"(r) : "f"(x)); return r; }
__device__ __forceinline__ float phi(float t, float l2e = 1.44269504089f) {
  float e = ex2(t * l2e) + 1e-6f;
  asm("{\n.reg .pred p;\nsetp.gt.f32 p, %1, 0f00000000;\n@p add.f32 %0, %1, 0f3F800008;\n}" : "+f"(e) : "f"(t));
  return e;
}
__device__ __forceinline__ void wg_fence() { asm volatile("wgmma.fence.sync.aligned;" ::: "memory"); }
__device__ __forceinline__ void wg_commit() { asm volatile("wgmma.commit_group.sync.aligned;" ::: "memory"); }
template <int N> __device__ __forceinline__ void wg_wait() { asm volatile("wgmma.wait_group.sync.aligned %0;" :: "n"(N) : "memory"); }
template <int N> __device__ __forceinline__ void pin(float* a) {
  #pragma unroll
  for (int i = 0; i < N; i++) asm volatile("" : "+f"(a[i]) :: "memory");
}
__device__ __forceinline__ int rtid() { int t; asm volatile("mov.u32 %0, %%tid.x;" : "=r"(t)); return t; }
template <int N> __device__ __forceinline__ void zero(float* a) {
  #pragma unroll
  for (int i = 0; i < N; i++) asm volatile("mov.b32 %0, 0;" : "=f"(a[i]));
}
__device__ __forceinline__ void cexp_t(float lg2mag, float turns, float& re, float& im) {
  float m = ex2(lg2mag);
  float fr = (turns - __fadd_rn(__fadd_rn(turns, 12582912.f), -12582912.f)) * 6.283185307f;
  re = m * __cosf(fr); im = m * __sinf(fr);
}
__device__ __forceinline__ void csq(float ar, float ai, float& cr, float& ci) {
  const float t = ar + ar;
  cr = fmaf(ar, ar, -ai * ai); ci = t * ai;
}
__device__ __forceinline__ void cmul(float ar, float ai, float br, float bi, float& cr, float& ci) {
  cr = fmaf(ar, br, -ai * bi); ci = fmaf(ar, bi, ai * br);
}

__device__ __forceinline__ void wg_ss48_tt(float* d, uint64_t da, uint64_t db, int scale_d) {
  asm volatile("{\n.reg .pred p;\nsetp.ne.b32 p, %26, 0;\n"
    "wgmma.mma_async.sync.aligned.m64n48k16.f32.bf16.bf16 "
    "{%0, %1, %2, %3, %4, %5, %6, %7, %8, %9, %10, %11, %12, %13, %14, %15, %16, %17, %18, %19, %20, %21, %22, %23}, %24, %25, p, 1, 1, 1, 1;\n}\n"
    : "+f"(d[0]), "+f"(d[1]), "+f"(d[2]), "+f"(d[3]), "+f"(d[4]), "+f"(d[5]), "+f"(d[6]), "+f"(d[7]), "+f"(d[8]), "+f"(d[9]), "+f"(d[10]), "+f"(d[11]), "+f"(d[12]), "+f"(d[13]), "+f"(d[14]), "+f"(d[15]), "+f"(d[16]), "+f"(d[17]), "+f"(d[18]), "+f"(d[19]), "+f"(d[20]), "+f"(d[21]), "+f"(d[22]), "+f"(d[23])
    : "l"(da), "l"(db), "r"(scale_d));
}
__device__ __forceinline__ void wg_rs88_tb(float* d, const uint32_t* a, uint64_t db, int scale_d) {
  asm volatile("{\n.reg .pred p;\nsetp.ne.b32 p, %49, 0;\n"
    "wgmma.mma_async.sync.aligned.m64n88k16.f32.bf16.bf16 "
    "{%0, %1, %2, %3, %4, %5, %6, %7, %8, %9, %10, %11, %12, %13, %14, %15, %16, %17, %18, %19, %20, %21, %22, %23, %24, %25, %26, %27, %28, %29, %30, %31, %32, %33, %34, %35, %36, %37, %38, %39, %40, %41, %42, %43}, {%44, %45, %46, %47}, %48, p, 1, 1, 1;\n}\n"
    : "+f"(d[0]), "+f"(d[1]), "+f"(d[2]), "+f"(d[3]), "+f"(d[4]), "+f"(d[5]), "+f"(d[6]), "+f"(d[7]), "+f"(d[8]), "+f"(d[9]), "+f"(d[10]), "+f"(d[11]), "+f"(d[12]), "+f"(d[13]), "+f"(d[14]), "+f"(d[15]), "+f"(d[16]), "+f"(d[17]), "+f"(d[18]), "+f"(d[19]), "+f"(d[20]), "+f"(d[21]), "+f"(d[22]), "+f"(d[23]), "+f"(d[24]), "+f"(d[25]), "+f"(d[26]), "+f"(d[27]), "+f"(d[28]), "+f"(d[29]), "+f"(d[30]), "+f"(d[31]), "+f"(d[32]), "+f"(d[33]), "+f"(d[34]), "+f"(d[35]), "+f"(d[36]), "+f"(d[37]), "+f"(d[38]), "+f"(d[39]), "+f"(d[40]), "+f"(d[41]), "+f"(d[42]), "+f"(d[43])
    : "r"(a[0]), "r"(a[1]), "r"(a[2]), "r"(a[3]), "l"(db), "r"(scale_d));
}
__device__ __forceinline__ void wg_ss80_tb(float* d, uint64_t da, uint64_t db, int scale_d) {
  asm volatile("{\n.reg .pred p;\nsetp.ne.b32 p, %42, 0;\n"
    "wgmma.mma_async.sync.aligned.m64n80k16.f32.bf16.bf16 "
    "{%0, %1, %2, %3, %4, %5, %6, %7, %8, %9, %10, %11, %12, %13, %14, %15, %16, %17, %18, %19, %20, %21, %22, %23, %24, %25, %26, %27, %28, %29, %30, %31, %32, %33, %34, %35, %36, %37, %38, %39}, %40, %41, p, 1, 1, 0, 1;\n}\n"
    : "+f"(d[0]), "+f"(d[1]), "+f"(d[2]), "+f"(d[3]), "+f"(d[4]), "+f"(d[5]), "+f"(d[6]), "+f"(d[7]), "+f"(d[8]), "+f"(d[9]), "+f"(d[10]), "+f"(d[11]), "+f"(d[12]), "+f"(d[13]), "+f"(d[14]), "+f"(d[15]), "+f"(d[16]), "+f"(d[17]), "+f"(d[18]), "+f"(d[19]), "+f"(d[20]), "+f"(d[21]), "+f"(d[22]), "+f"(d[23]), "+f"(d[24]), "+f"(d[25]), "+f"(d[26]), "+f"(d[27]), "+f"(d[28]), "+f"(d[29]), "+f"(d[30]), "+f"(d[31]), "+f"(d[32]), "+f"(d[33]), "+f"(d[34]), "+f"(d[35]), "+f"(d[36]), "+f"(d[37]), "+f"(d[38]), "+f"(d[39])
    : "l"(da), "l"(db), "r"(scale_d));
}
__device__ __forceinline__ void wg_ss48_tt_h(float* d, uint64_t da, uint64_t db, int scale_d) {
  asm volatile("{\n.reg .pred p;\nsetp.ne.b32 p, %26, 0;\n"
    "wgmma.mma_async.sync.aligned.m64n48k16.f32.f16.f16 "
    "{%0, %1, %2, %3, %4, %5, %6, %7, %8, %9, %10, %11, %12, %13, %14, %15, %16, %17, %18, %19, %20, %21, %22, %23}, %24, %25, p, 1, 1, 1, 1;\n}\n"
    : "+f"(d[0]), "+f"(d[1]), "+f"(d[2]), "+f"(d[3]), "+f"(d[4]), "+f"(d[5]), "+f"(d[6]), "+f"(d[7]), "+f"(d[8]), "+f"(d[9]), "+f"(d[10]), "+f"(d[11]), "+f"(d[12]), "+f"(d[13]), "+f"(d[14]), "+f"(d[15]), "+f"(d[16]), "+f"(d[17]), "+f"(d[18]), "+f"(d[19]), "+f"(d[20]), "+f"(d[21]), "+f"(d[22]), "+f"(d[23])
    : "l"(da), "l"(db), "r"(scale_d));
}
__device__ __forceinline__ void wg_rs192_tb(float* d, const uint32_t* a, uint64_t db, int scale_d) {
  asm volatile("{\n.reg .pred p;\nsetp.ne.b32 p, %101, 0;\n"
    "wgmma.mma_async.sync.aligned.m64n192k16.f32.bf16.bf16 "
    "{%0, %1, %2, %3, %4, %5, %6, %7, %8, %9, %10, %11, %12, %13, %14, %15, %16, %17, %18, %19, %20, %21, %22, %23, %24, %25, %26, %27, %28, %29, %30, %31, %32, %33, %34, %35, %36, %37, %38, %39, %40, %41, %42, %43, %44, %45, %46, %47, %48, %49, %50, %51, %52, %53, %54, %55, %56, %57, %58, %59, %60, %61, %62, %63, %64, %65, %66, %67, %68, %69, %70, %71, %72, %73, %74, %75, %76, %77, %78, %79, %80, %81, %82, %83, %84, %85, %86, %87, %88, %89, %90, %91, %92, %93, %94, %95}, {%96, %97, %98, %99}, %100, p, 1, 1, 1;\n}\n"
    : "+f"(d[0]), "+f"(d[1]), "+f"(d[2]), "+f"(d[3]), "+f"(d[4]), "+f"(d[5]), "+f"(d[6]), "+f"(d[7]), "+f"(d[8]), "+f"(d[9]), "+f"(d[10]), "+f"(d[11]), "+f"(d[12]), "+f"(d[13]), "+f"(d[14]), "+f"(d[15]), "+f"(d[16]), "+f"(d[17]), "+f"(d[18]), "+f"(d[19]), "+f"(d[20]), "+f"(d[21]), "+f"(d[22]), "+f"(d[23]), "+f"(d[24]), "+f"(d[25]), "+f"(d[26]), "+f"(d[27]), "+f"(d[28]), "+f"(d[29]), "+f"(d[30]), "+f"(d[31]), "+f"(d[32]), "+f"(d[33]), "+f"(d[34]), "+f"(d[35]), "+f"(d[36]), "+f"(d[37]), "+f"(d[38]), "+f"(d[39]), "+f"(d[40]), "+f"(d[41]), "+f"(d[42]), "+f"(d[43]), "+f"(d[44]), "+f"(d[45]), "+f"(d[46]), "+f"(d[47]), "+f"(d[48]), "+f"(d[49]), "+f"(d[50]), "+f"(d[51]), "+f"(d[52]), "+f"(d[53]), "+f"(d[54]), "+f"(d[55]), "+f"(d[56]), "+f"(d[57]), "+f"(d[58]), "+f"(d[59]), "+f"(d[60]), "+f"(d[61]), "+f"(d[62]), "+f"(d[63]), "+f"(d[64]), "+f"(d[65]), "+f"(d[66]), "+f"(d[67]), "+f"(d[68]), "+f"(d[69]), "+f"(d[70]), "+f"(d[71]), "+f"(d[72]), "+f"(d[73]), "+f"(d[74]), "+f"(d[75]), "+f"(d[76]), "+f"(d[77]), "+f"(d[78]), "+f"(d[79]), "+f"(d[80]), "+f"(d[81]), "+f"(d[82]), "+f"(d[83]), "+f"(d[84]), "+f"(d[85]), "+f"(d[86]), "+f"(d[87]), "+f"(d[88]), "+f"(d[89]), "+f"(d[90]), "+f"(d[91]), "+f"(d[92]), "+f"(d[93]), "+f"(d[94]), "+f"(d[95])
    : "r"(a[0]), "r"(a[1]), "r"(a[2]), "r"(a[3]), "l"(db), "r"(scale_d));
}
__device__ __forceinline__ void wg_rs48_tb(float* d, const uint32_t* a, uint64_t db, int scale_d) {
  asm volatile("{\n.reg .pred p;\nsetp.ne.b32 p, %29, 0;\n"
    "wgmma.mma_async.sync.aligned.m64n48k16.f32.bf16.bf16 "
    "{%0, %1, %2, %3, %4, %5, %6, %7, %8, %9, %10, %11, %12, %13, %14, %15, %16, %17, %18, %19, %20, %21, %22, %23}, {%24, %25, %26, %27}, %28, p, 1, 1, 1;\n}\n"
    : "+f"(d[0]), "+f"(d[1]), "+f"(d[2]), "+f"(d[3]), "+f"(d[4]), "+f"(d[5]), "+f"(d[6]), "+f"(d[7]), "+f"(d[8]), "+f"(d[9]), "+f"(d[10]), "+f"(d[11]), "+f"(d[12]), "+f"(d[13]), "+f"(d[14]), "+f"(d[15]), "+f"(d[16]), "+f"(d[17]), "+f"(d[18]), "+f"(d[19]), "+f"(d[20]), "+f"(d[21]), "+f"(d[22]), "+f"(d[23])
    : "r"(a[0]), "r"(a[1]), "r"(a[2]), "r"(a[3]), "l"(db), "r"(scale_d));
}

struct Params {
  const __nv_bfloat16 *par[4], *logdt, *dskip, *u, *wo;
  CUtensorMap m[M_COUNT];
};

#define CHUNK(i) ((c + (i)) & 7)
#define FLAG(kind, rr, cc) (&g_flag[((kind) * 128 + (rr) * 8 + (cc)) * 32])
#define SLOT(i) ((i) == 0 ? OFF_EXTRA : OFF_BLK - 256 + ((i) > 5 ? (i) - 6 : (i) - 1) * BLK)
__device__ __forceinline__ void load_quad(uint32_t* A, uint32_t addr) {
  A[0] = lds32v(addr); A[1] = lds32v(addr + 32); A[2] = lds32v(addr - 32); A[3] = lds32v(addr);
}

__device__ __forceinline__ bool y_transpose(uint32_t sb, int w5, int lane, uint32_t ytag) {
  const int mi = lane >> 3, rw = lane & 7;
  const uint32_t sa = sb + OFF_EXTRA + (w5 * 16 + rw) * 128 + ((mi ^ rw) << 4), da = sb + SLOT(3) + (8 * mi + rw) * 160 + w5 * 32;
  const uint32_t ym = lane < 4 ? 0x10001u : 0u;
  bar_sync(7, 160);
  uint32_t v[8][4], bad = 0;
  #pragma unroll
  for (int q = 0; q < 8; q++) ldsm4t(v[q], (sa ^ ((q & 1) * 64 + ((q >> 1) & 1) * 16)) + ((q >> 1) & 1) * 10240 + (q >> 2) * 1024);
  #pragma unroll
  for (int q = 0; q < 8; q++) {
    bad |= (v[q][0] ^ ytag) | (v[q][2] ^ ytag);
    stsm4(da + (q & 3) * 5120 + (q >> 2) * 16, v[q][0] & ~ym, v[q][1], v[q][2] & ~ym, v[q][3]);
  }
  fence_async();
  uint32_t any;
  asm volatile("{\n.reg .pred p;\nsetp.ne.u32 p, %1, 0;\nbarrier.red.or.pred p, 7, 160, p;\nselp.u32 %0, 1, 0, p;\n}" : "=r"(any) : "r"(bad & ym) : "memory");
  return any;
}

__global__ void __launch_bounds__(512, 1) fused_kernel(const __grid_constant__ Params prm) {
  extern __shared__ unsigned char smem_raw[];
  uint32_t raw[5][2], pd;
  if ((threadIdx.x >> 7) == 2) {
    const int ch = (blockIdx.x & 7) * 80 + (blockIdx.x >> 3) * 5, od = threadIdx.x & 1;
    #pragma unroll
    for (int e = 0; e < 2; e++) {
      const __nv_bfloat16* pp = prm.par[2 * e + od] + ch * 128 + (threadIdx.x & 126);
      #pragma unroll
      for (int q = 0; q < 5; q++) asm volatile("ld.global.nc.u32 %0, [%1];" : "=r"(raw[q][e]) : "l"(pp + q * 128));
    }
    asm volatile("ld.global.nc.u16 %0, [%1];" : "=r"(pd) : "l"(((threadIdx.x & 8) ? prm.dskip : prm.logdt) + ch + min(threadIdx.x & 7, 4)));
  }
  constexpr uint32_t sb = SB0;
  const int tid = threadIdx.x, lane = tid & 31;
  const int warp = __shfl_sync(0xffffffff, tid >> 5, 0), wg = warp >> 2, w4 = warp & 3;
  const int cta = blockIdx.x, r = cta >> 3, c = cta & 7;
  if (smem_u32(smem_raw) != SB0) return;
#define BAR(i) (sb + OFF_BAR + 8 * (i))
  const bool sw64 = ((c + 1) & 2) != 0;

  const CUtensorMap* mwp = &prm.m[sw64 ? M_W64 : M_W128];
  const int mcol = (c * 80 + (c & 1) * 16) >> (sw64 ? 5 : 6), rcol = c * 80 + ((c & 1) ? 0 : 64);
  if (warp == 12 && elect_one()) {
    #pragma unroll
    for (int i = 0; i < 5; i++) mbar_init(BAR(BR_FULL + i), 1);
    asm volatile("fence.mbarrier_init.release.cluster;" ::: "memory");
    if (EN_ATT) {
      mbar_expect_tx(BAR(BR_FULL), W_SLOT + 16384);
      tma4d(sb, mwp, BAR(BR_FULL), 0, 0, mcol, 0);
      tma2d(sb + OFF_X, &prm.m[M_X], BAR(BR_FULL), 0, r * 128);
      tma3d(sb + 12288, &prm.m[M_WR], BAR(BR_FULL), rcol, 0, 0);
      mbar_expect_tx(BAR(BR_FULL + 1), W_SLOT);
      tma4d(sb + W_SLOT, mwp, BAR(BR_FULL + 1), 0, 32, mcol, 0);
      tma3d(sb + W_SLOT + 12288, &prm.m[M_WR], BAR(BR_FULL + 1), rcol, 32, 0);
      TS(24);
    }
  }
  if (warp == 13 && elect_one()) {
    asm volatile("prefetch.tensormap [%0];" :: "l"(&prm.m[M_X]) : "memory");
    asm volatile("prefetch.tensormap [%0];" :: "l"(&prm.m[M_WR]) : "memory");
  }
  if (wg == 3) {
    asm volatile("setmaxnreg.dec.sync.aligned.u32 56;");
    const int tid = rtid(), lane = tid & 31;
    if (warp == 12) {
      asm volatile("bar.arrive 0, 512;" ::: "memory");
      if (EN_ATT && elect_one()) {
        #pragma unroll
        for (int kb = 2; kb < 5; kb++) {
          mbar_expect_tx(BAR(BR_FULL + kb), (kb & 1) ? W_SLOT : W_SLOT + 16384);
          if (!(kb & 1)) tma2d(sb + OFF_X + kb * 8192, &prm.m[M_X], BAR(BR_FULL + kb), kb * 32, r * 128);
          tma4d(sb + kb * W_SLOT, mwp, BAR(BR_FULL + kb), 0, kb * 32, mcol, 0);
          tma3d(sb + kb * W_SLOT + 12288, &prm.m[M_WR], BAR(BR_FULL + kb), rcol, kb * 32, 0);
        }
      }
      bar_sync(6, 128);
      if (elect_one()) {
        if (EN_SSM) { mbar_expect_tx(BAR(BR_UIN), 20480); tma2d(sb + OFF_UT, &prm.m[M_U], BAR(BR_UIN), c * 80, r * 128); }
        if (EN_ATT) {
          uint32_t st = sb, fb = BAR(BR_FULL), ph = 0, xs = sb + OFF_X;
          #pragma unroll 1
          for (int k = 160; k < 640; k += 32) {
            mbar_wait(fb + 8 * (BR_EMPTY - BR_FULL), ph);
            mbar_expect_tx(fb, (k & 32) ? W_SLOT : W_SLOT + 16384);
            tma4d(st, mwp, fb, 0, k, mcol, 0);
            if (!(k & 32)) { tma2d(xs, &prm.m[M_X], fb, k, r * 128); xs += 16384; if (xs == sb + OFF_BAR) xs = sb + OFF_X; }
            tma3d(st + 12288, &prm.m[M_WR], fb, rcol, k, 0);
            st += W_SLOT; fb += 8;
            if (st == sb + OFF_X) { st = sb; fb = BAR(BR_FULL); ph ^= 1; }
          }
          asm volatile("cp.async.bulk.prefetch.L2.global [%0], 6400;" :: "l"(prm.wo + cta * 3200) : "memory");
        }
      }
      __syncwarp();
      if (EN_ATT) {
      mbar_wait(BAR(BR_EPOCH), 0);
      const unsigned epoch = lds32(sb + OFF_EPOCH);
      const unsigned* fo = FLAG(3, r, lane & 7);
      unsigned seen = __ballot_sync(0xffffffff, ld_rlx(lane < 16 ? fo : FLAG(0, lane & 15, c)) == epoch);
      if (elect_one()) {
        mbar_expect_tx(BAR(BR_WO), 8 * 10240);
        mbar_expect_tx(BAR(BR_KVP), 61440);
      }
      mbar_wait(BAR(BR_PUB), 0);
      if ((seen >> 16) != 0xffffu) poll_all(FLAG(0, lane & 15, c), epoch);
      if (elect_one()) { TS(23); bulk_ld(sb + OFF_KVP, &g_kvp[c * 16 * 240], 61440, BAR(BR_KVP)); }
      mbar_wait(BAR(BR_OSTG), 0);
      if (elect_one()) {
        bulk_st(&g_o[cta * 1280], sb + OFF_EXTRA, 20480);
        bulk_commit();
        bulk_wait0();
        st_rlx(FLAG(3, r, c), epoch);
        mbar_arrive(BAR(BR_OEMPTY));
        TS(20);
        #pragma unroll 1
        for (int i = 0; i < 8; i++) tma2d(sb + i * 10240, &prm.m[M_WO], BAR(BR_WO), c * 64, CHUNK(i) * 80);
      }
      __syncwarp();
      #pragma unroll 1
      for (int i = 1; i < 8; i++) {
        const int src = CHUNK(i);
        if (!((seen >> src) & 1)) seen = poll_bit(fo, epoch, 1u << src);
        if (i > 5) mbar_wait(BAR(BR_OEMPTY - 5) + 8 * i, 0);
        else if (EN_SSM && i != 2 && i != 3) mbar_wait(i == 1 ? BAR(BR_KS + 1) : BAR(BR_FREE - 4) + 8 * i, 0);
        if (elect_one()) {
          mbar_expect_tx(BAR(BR_OFULL) + 8 * i, 20480);
          bulk_ld(sb + SLOT(i), &g_o[(r * 8 + src) * 1280], 20480, BAR(BR_OFULL) + 8 * i);
          if (i == 1) TS(21);
          if (i == 7) TS(22);
        }
        __syncwarp();
      }
      if (lane == 0) { DUMP(20, 30); }
      }
    } else {
      const int hw = warp - 13, ht = tid - 416;
      if (hw == 2 && elect_one()) {
        #pragma unroll
        for (int i = 5; i <= BR_DRDY; i++) mbar_init(BAR(i), i == BR_GEMM ? 8 : i == BR_OEMPTY ? 9 : i < BR_EMPTY ? 1 : i < BR_OEMPTY ? 2 : i < BR_Y ? 8 : i < BR_DRDY ? 4 : 3);
        asm volatile("fence.mbarrier_init.release.cluster;" ::: "memory");
      }
      __syncwarp();
      asm volatile("bar.arrive 0, 512;" ::: "memory");
      if (EN_SSM && hw == 2) asm volatile("bar.arrive 8, 160;" ::: "memory");
      const unsigned epoch = hw == 0 ? ld_rlx(&g_epoch[cta]) + 1 : 0;
      bar_sync(5, 96);
      asm volatile("bar.arrive 6, 128;" ::: "memory");
      if (hw == 1 && elect_one()) {
        #pragma unroll
        for (int i = M_U; i < M_COUNT; i++) asm volatile("prefetch.tensormap [%0];" :: "l"(&prm.m[i]) : "memory");
      }
      if (ht == 0) {
        st_rlx(&g_epoch[cta], epoch);
        sts32(sb + OFF_EPOCH, epoch);
        mbar_arrive(BAR(BR_EPOCH));
      }
      if (EN_SSM) {
      const int mi = lane >> 3, rw = lane & 7, ch0 = c * 80 + r * 5;
      const bool early_u = hw == 0 && __all_sync(0xffffffff, ld_acq(FLAG(1, lane & 15, c)) == epoch);
      mbar_wait(BAR(BR_UIN), 0);
      if (ht == 0) TS(36);
      #pragma unroll 1
      for (int h = 0; h < 2; h++) {
        const uint32_t sa = sb + OFF_UT + h * 10240 + (8 * mi + rw) * 160 + hw * 16, da = sb + OFF_UT + h * 10240 + (hw * 8 + rw) * 128 + ((mi ^ rw ^ h) << 4);
        uint32_t v[8][4];
        #pragma unroll
        for (int q = 0; q < 8; q++) if (q < 6 || hw == 0) ldsm4t(v[q], sa + (q & 1) * 5120 + (q >> 1) * 48);
        bar_sync(5, 96);
        #pragma unroll
        for (int q = 0; q < 8; q++) if (q < 6 || hw == 0) stsm4((da ^ ((q & 1) * 64)) + (q >> 1) * 3072, v[q][0], v[q][1], v[q][2], v[q][3]);
      }
      fence_async();
      bar_sync(5, 96);
      if (hw == 0) {
        if (elect_one()) {
          tma2d_st(&prm.m[M_SA], sb + OFF_UT, r * 128, c * 80);
          tma2d_st(&prm.m[M_SA], sb + OFF_UT + 10240, r * 128 + 64, c * 80);
          bulk_commit(); bulk_wait0_read();
          mbar_arrive(BAR(BR_UOUT));
          TS(37);
          bulk_wait0();
          st_rel(FLAG(1, r, c), epoch);
          TS(30);
        }
        __syncwarp();
        if (!early_u) poll_all_acq(FLAG(1, lane & 15, c), epoch);
      }
      #pragma unroll 1
      for (int k = 0; k < 5; k++) {
        if (k == 0 || k == 3) {
          const int p = k != 0;
          if (hw == 0) {
            if (!p) {
              if (elect_one()) {
                fence_async_g();
                mbar_expect_tx(BAR(BR_U), 12288);
                #pragma unroll 1
                for (int q = 0; q < 3; q++) bulk_ld(sb + OFF_BLK + q * q * BLK, g_uy + (ch0 + q * q) * 2048, 4096, BAR(BR_U));
                TS(31);
              }
              __syncwarp();
            }
            mbar_wait(BAR(p ? BR_U2 : BR_U), 0);
          }
          bar_sync(5, 96);
        }
        const int l3 = (hw + k) % 3 * 32 + lane;
        const uint32_t blk = sb + OFF_BLK + ((0x32410 >> (4 * k)) & 7) * BLK, o = blk + B_D + l3 * 16;
        float P[34];
        P[0] = 0.f;
        #pragma unroll
        for (int q = 0; q < 5; q++) {
          const int ch = 2 * l3 - 3 + q;
          uint32_t v[4];
          lds128(v, blk + (uint32_t)((ch * 16) ^ ((ch * 2) & 0x10)));
          #pragma unroll
          for (int e = 0; e < 8; e++) {
            const int i = 8 * q + e - 4;
            if (i >= 0 && i < 33) P[i + 1] = P[i] + ((e & 1) ? bf_hi(v[e >> 1]) : bf_lo(v[e >> 1]));
          }
        }
#define WIN(lo, hi, e) (P[21 + (e) - (lo)] - P[20 + (e) - (hi)])
#define WIN8(lo, hi, b) pack2(WIN(lo, hi, b), WIN(lo, hi, b + 1)), pack2(WIN(lo, hi, b + 2), WIN(lo, hi, b + 3)), pack2(WIN(lo, hi, b + 4), WIN(lo, hi, b + 5)), pack2(WIN(lo, hi, b + 6), WIN(lo, hi, b + 7))
        if (l3 < 64) {
          sts128(o + B_D9, WIN8(12, 20, 0)); sts128(o + B_D9 + 1024, WIN8(12, 20, 8));
          sts128(o + B_D7, WIN8(5, 11, 0)); sts128(o + B_D7 + 1024, WIN8(5, 11, 8));
        }
        sts128(o + B_D5, WIN8(6, 10, 0)); sts128(o + B_D5 + 1552, WIN8(6, 10, 8));
        sts128(o, WIN8(3, 5, 0)); sts128(o + 1552, WIN8(3, 5, 8));
        if (l3 < 2) sts128(blk + B_D + l3 * B_D5 + 1536, 0, 0, 0, 0);
      }
      __syncwarp();
      if (lane == 0) mbar_arrive(BAR(BR_DRDY));
      if (ht == 0) TS(32);
      if (hw == 0) {
        const bool early = __all_sync(0xffffffff, ld_rlx(FLAG(2, lane & 15, c)) == epoch);
        #pragma unroll 1
        for (int p = 0; p < 2; p++) {
          mbar_wait(BAR(BR_Y) + 8 * p, 0);
          if (elect_one()) {
            bulk_st(g_uy + (640 + ch0 + 4 * p) * 2048, sb + OFF_BLK + (3 + p) * BLK, p ? 4096 : 16384);
            bulk_commit(); bulk_wait0_read();
            mbar_arrive(BAR(BR_FREE) + 8 * p);
          }
          __syncwarp();
        }
        if (elect_one()) { bulk_wait0(); st_rlx(FLAG(2, r, c), epoch); TS(33); }
        __syncwarp();
        if (!early) poll_all(FLAG(2, lane & 15, c), epoch);
        if (EN_ATT) mbar_wait(BAR(BR_OEMPTY), 0);
        #pragma unroll 1
        for (int n = 0; n < 64; n++) {
          if (elect_one()) {
            mbar_expect_tx(BAR(BR_YIN), 20480);
            tma2d(sb + OFF_EXTRA, &prm.m[M_SA], BAR(BR_YIN), r * 128, 640 + c * 80);
            tma2d(sb + OFF_EXTRA + 10240, &prm.m[M_SA], BAR(BR_YIN), r * 128 + 64, 640 + c * 80);
            TS(34);
          }
          __syncwarp();
          if (EN_ATT) mbar_wait(BAR(BR_OEMPTY + 3), 0);
          mbar_wait(BAR(BR_YIN), n & 1);
          if (lane == 0) TS(38);
          if (!y_transpose(sb, 4, lane, (epoch & 1u) * 0x10001u)) break;
          FIXCNT
        }
      if (elect_one()) {
        TS(39);
        tma2d_st(&prm.m[M_OUT], sb + SLOT(3), c * 80, r * 128);
        bulk_commit(); bulk_wait0_read();
        TS(35); DUMP(30, 40); DUMP(0, 1);
      }
      }
      }
    }
  } else {
  if (wg < 2) {
    asm volatile("setmaxnreg.inc.sync.aligned.u32 160;");
    bar_sync(0, 512);
    if (EN_ATT) {
    float am[96], ar[24];
    {
      const bool lead = (rtid() & 127) == 0;
      constexpr uint64_t dr0 = mkdesc(SB0 + 12288, 1024, 256, 3);
      const uint64_t dbc = sw64 ? mkdesc(SB0, 2048, 512, 2) : mkdesc(SB0, 4096, 1024, 1);
      const uint32_t kst = __shfl_sync(0xffffffff, sw64 ? 64 : 128, 0), bh = __shfl_sync(0xffffffff, (uint32_t)(dbc >> 32), 0);
      const uint64_t db0 = desc2(__shfl_sync(0xffffffff, (uint32_t)dbc, 0), bh);
      uint32_t ph = 0;
      const int ln = rtid() & 31;
      const uint32_t xa = sb + OFF_X + (warp * 16 + (ln & 15)) * 128 + (((ln >> 4) ^ (ln & 7)) << 4);
      uint32_t A[8];
      mbar_wait(BAR(BR_FULL), 0);
      if (lead && wg == 0) TS(1);
      ldsm4(A, xa); ldsm4(A + 4, xa ^ 32);
      wg_fence();
      wg_rs48_tb(ar, A, dr0, 0); wg_rs192_tb(am, A, db0, 0);
      wg_commit();
      uint32_t wp = 0, fb = BAR(BR_FULL), xk = xa;
      #pragma unroll 1
      for (int kb = 1; kb < 20; kb++) {
        const uint64_t d0 = desc2((uint32_t)dr0 + wp + 32, dr0 >> 32), d1 = desc2((uint32_t)db0 + wp + kst, bh);
        const uint32_t eb = fb + 8 * (BR_EMPTY - BR_FULL);
        wp += W_SLOT >> 4; fb += 8;
        if (wp == 5 * (W_SLOT >> 4)) { wp = 0; fb = BAR(BR_FULL); ph ^= 1; }
        wg_fence();
        wg_rs48_tb(ar, A + 4, d0, 1);
        wg_rs192_tb(am, A + 4, d1, 1);
        wg_commit();
        xk ^= 64;
        if (!(kb & 1)) { xk += 16384; if (xk >= sb + OFF_BAR) xk -= 49152; }
        mbar_wait(fb, ph);
        wg_wait<1>();
        ldsm4(A, xk);
        wg_fence();
        wg_rs48_tb(ar, A, desc2((uint32_t)dr0 + wp, dr0 >> 32), 1);
        wg_rs192_tb(am, A, desc2((uint32_t)db0 + wp, bh), 1);
        wg_commit();
        wg_wait<1>();
        ldsm4(A + 4, xk ^ 32);
        if (lead && kb < 16) mbar_arrive(eb);
      }
      wg_fence();
      wg_rs48_tb(ar, A + 4, dr0 + 4 * (W_SLOT >> 4) + 32, 1);
      wg_rs192_tb(am, A + 4, desc2((uint32_t)db0 + 4 * (W_SLOT >> 4) + kst, bh), 1);
      wg_commit();
      wg_wait<0>();
      if (ln == 0) mbar_arrive(BAR(BR_GEMM));
      pin<96>(am); pin<24>(ar);
    }
    const int tid = rtid(), lane = tid & 31, tq = lane & 3;
    if (tid == 0) TS(2);
#define QV(j, e) ((j) < 8 ? am[4 * (j) + (e)] : ar[4 * ((j) - 8) + (e)])
#define KV_(j, e) ((j) < 8 ? am[32 + 4 * (j) + (e)] : ar[8 + 4 * ((j) - 8) + (e)])
#define VV(j, e) ((j) < 8 ? am[64 + 4 * (j) + (e)] : ar[16 + 4 * ((j) - 8) + (e)])
    {
      bar_sync(1, 256);
      const uint32_t ro = sb + (uint32_t)((warp * 16 + (lane & 15)) * 16);
      const int l0 = 2 * (c & 1) + (lane >> 4);
      const uint32_t ones = (tq == 0) ? 0x00003f80u : 0u;
#define PV(j) pack2(VV(j, 0), VV(j, 1)), pack2(VV(j, 2), VV(j, 3))
#define PK(j) pack2(phi(KV_(j, 0)), phi(KV_(j, 1))), pack2(phi(KV_(j, 2)), phi(KV_(j, 3)))
      stsm4(ro + OFF_V + (5 + 6 * (lane >> 4)) * 2048, ones, ones, ones, ones);
      #pragma unroll
      for (int j = 0; j < 10; j += 2) {
        const int l = (j == 8 && (c & 1)) ? l0 - 2 : l0 + j;
        stsm4(ro + OFF_V + (l + (l >= 5)) * 2048, PV(j), PV(j + 1));
        stsm4(ro + OFF_PK + l * 2048, PK(j), PK(j + 1));
      }
    }
    fence_async();
    bar_sync(1, 256);
    if (tid == 0) TS(3);
    mbar_wait(BAR(BR_EPOCH), 0);
    const unsigned epoch = lds32(sb + OFF_EPOCH);
    {
      float kv[24]; zero<24>(kv);
      constexpr uint64_t da = mkdesc(SB0 + OFF_PK, 128, 2048, 0), db = mkdesc(SB0 + OFF_V, 128, 2048, 0);
      wg_fence();
      #pragma unroll
      for (int s = 0; s < 8; s++) wg_ss48_tt(kv, desc2((uint32_t)da + wg * 640 + s * 16, da >> 32), desc2((uint32_t)db + wg * 768 + s * 16, db >> 32), s != 0);
      wg_commit();
      wg_wait<0>();
      pin<24>(kv);
      if (tid == 0) TS(15);
      if (w4 < 3) {
        const uint32_t wb = sb + OFF_KVS + (wg * 3 + w4) * 1536 + (lane & 15) * 96;
        #pragma unroll
        for (int j = 0; j < 6; j += 2)
          stsm4(wb + (j + (lane >> 4)) * 16, pack2(kv[4 * j], kv[4 * j + 1]), pack2(kv[4 * j + 2], kv[4 * j + 3]),
                pack2(kv[4 * j + 4], kv[4 * j + 5]), pack2(kv[4 * j + 6], kv[4 * j + 7]));
        __syncwarp();
        const int dl = w4 * 16 + (lane & 15), hl = dl >= 20;
        uint32_t v[4], z[4];
        lds128(v, wb + (3 * hl + (lane >> 4)) * 16);
        lds64(z, wb + 32 + 8 * hl); z[2] = lds32(wb + 80); z[3] = epoch & 1u;
        if (dl < 40) {
          uint4* dst = &g_kvp[(c * 16 + r) * 240 + wg * 40 + dl];
          v[3] = (v[3] & ~1u) | z[3];
          st128_rlx(dst + (lane >> 4) * 80, v);
          if (lane < 16) st128_rlx(dst + 160, z);
        }
      }
    }
    bar_sync(1, 256);
    if (tid == 0) { st_rlx(FLAG(0, r, c), epoch); mbar_arrive(BAR(BR_PUB)); TS(4); }
    const int kvi = (tid >= 80) + (tid >= 160) + (tid >= 240), kd = tid - 80 * kvi;
    const int khd = kd / 20, kt0 = 5 * (khd >> 1) + 2 * (khd & 1);
    const uint32_t rb = sb + OFF_KVB + kd * 16;
    if (kvi < 3) {
      #pragma unroll 1
      for (int m = kvi; m < 7; m += 3) { const int q = kt0 + 3 + m; sts128(rb + (q >= 10 ? q - 10 : q) * 1280, 0, 0, 0, 0); }
    }
    uint32_t qa[20];
    {
      const float sc = 1.44269504089f + __uint_as_float(lds32(sb + OFF_EPOCH) ^ epoch);
      #pragma unroll
      for (int j = 0; j < 10; j++) { qa[2 * j] = pack2(phi(QV(j, 0), sc), phi(QV(j, 1), sc)); qa[2 * j + 1] = pack2(phi(QV(j, 2), sc), phi(QV(j, 3), sc)); }
    }
    if (tid == 0) TS(5);
    if (warp == 7) mbar_wait(BAR(BR_KVP), 0);
    bar_sync(1, 256);
    if (tid == 0) TS(6);
    if (kvi < 3) {
      float s[8];
      zero<8>(s);
      uint32_t bad = 0;
      #pragma unroll 4
      for (int i = 0; i < 16; i += 2) {
        uint32_t w[4], x[4];
        lds128(w, sb + OFF_KVP + tid * 16 + i * 3840); lds128(x, sb + OFF_KVP + tid * 16 + i * 3840 + 3840);
        bad |= (w[3] ^ epoch) | (x[3] ^ epoch);
        #pragma unroll
        for (int e = 0; e < 4; e++) {
          asm("add.rn.bf16x2 %0, %0, %1;" : "+r"(w[e]) : "r"(x[e]));
          s[2 * e] += bf_lo(w[e]); s[2 * e + 1] += bf_hi(w[e]);
        }
      }
      if (__builtin_expect(bad & 1u, 0)) {
        zero<8>(s);
        #pragma unroll 1
        for (int i = 0; i < 16; i++) {
          uint32_t w[4] = {0, 0, 0, ~epoch};
          fix128_w3(w, &g_kvp[(c * 16 + i) * 240 + tid], epoch, 1u);
          #pragma unroll
          for (int e = 0; e < 4; e++) { s[2 * e] += bf_lo(w[e]); s[2 * e + 1] += bf_hi(w[e]); }
        }
        FIXCNT
      }
      const uint32_t p0 = pack2(s[0], s[1]), p1 = pack2(s[2], s[3]), p2 = pack2(s[4], s[5]), p3 = pack2(s[6], s[7]);
      if (kvi < 2) sts128(rb + (kt0 + (khd & 1) + kvi) * 1280, p0, p1, p2, p3);
      else {
        const bool od = khd & 1;
        sts128(rb + (5 * (khd >> 1) + 2) * 1280, od ? 0u : p0, od ? 0u : p1, od ? p0 : 0u, od ? p1 : 0u);
        const uint32_t zz = (p2 & 0xffffu) << (16 * (khd & 1));
        sts128(rb + 10 * 1280, khd < 2 ? zz : 0u, khd < 2 ? 0u : zz, 0u, 0u);
      }
    }
    fence_async();
    bar_sync(1, 256);
    if (tid == 0) TS(7);
    {
      float oa[44]; zero<44>(oa);
      constexpr uint64_t db = mkdesc(SB0 + OFF_KVB, 128, 1280, 0);
      wg_fence();
      #pragma unroll
      for (int s = 0; s < 5; s++) wg_rs88_tb(oa, &qa[4 * s], desc2((uint32_t)db + ((s == 4 && (c & 1)) ? 0 : (s + (c & 1)) * 16), db >> 32), s != 0);
      wg_commit();
      wg_wait<0>();
      pin<44>(oa);
      if (tid == 0) TS(13);
      float rc[4], rd[2][4];
      #pragma unroll
      for (int e = 0; e < 4; e++) asm("rcp.approx.ftz.f32 %0, %1;" : "=f"(rc[e]) : "f"(oa[40 + e] + 1e-6f));
      #pragma unroll
      for (int h = 0; h < 4; h++) {
        rd[0][h] = __shfl_sync(0xffffffff, rc[h & 1], (lane & 28) | (h >> 1));
        rd[1][h] = __shfl_sync(0xffffffff, rc[2 + (h & 1)], (lane & 28) | (h >> 1));
      }
      #pragma unroll
      for (int j = 0; j < 10; j++) {
        #pragma unroll
        for (int h = 0; h < 2; h++) {
          float f;
          if (j == 2) f = tq < 2 ? rd[h][0] : rd[h][1];
          else if (j == 7) f = tq < 2 ? rd[h][2] : rd[h][3];
          else f = rd[h][(8 * j) / 20];
          qa[2 * j + h] = pack2(oa[4 * j + 2 * h] * f, oa[4 * j + 2 * h + 1] * f);
        }
      }
      const uint32_t m0 = (lane & 7) == ((2 * w4) & 7), m1 = (lane & 7) == 2 * w4 + 1;
      const uint32_t oa_ = sb + OFF_EXTRA + (lane >> 4) * 2048 + (warp * 16 + (lane & 15)) * 16;
#define TAG(v, m) (((v) & ~(m)) | (epoch & (m)))
      #pragma unroll
      for (int s = 0; s < 5; s++) stsm4(oa_ + s * 4096, TAG(qa[4 * s], m0), TAG(qa[4 * s + 1], m1), TAG(qa[4 * s + 2], m0), TAG(qa[4 * s + 3], m1));
    }
    fence_async();
    __syncwarp();
    if (lane == 0) mbar_arrive(BAR(BR_OSTG));
    if (tid == 0) TS(8);
    }
    asm volatile("setmaxnreg.dec.sync.aligned.u32 136;");
  } else {
    const int g = lane >> 2, tq = lane & 3, t7 = tid & 127;
    asm volatile("bar.arrive 0, 512;" ::: "memory");
    if (EN_SSM) {
    {
      #pragma unroll 1
      for (int k = 0; k < 4; k++) {
        const uint32_t z = sb + OFF_BLK + k * BLK + t7 * 16;
        sts128(z + B_TBL, 0, 0, 0, 0); sts128(z + B_TBL + 2048, 0, 0, 0, 0);
      }
      if (t7 < 80) sts128(sb + OFF_BLK + (t7 >> 4) * BLK - 256 + (t7 & 15) * 16, 0, 0, 0, 0);
      const uint32_t ea = sb + OFF_BLK + (2 + (w4 & 1)) * BLK + (lane >> 4) * 7168 + ((lane >> 3) & 1) * 256 + (lane & 7) * 16 + (w4 >> 1) * 2048;
      constexpr uint64_t dE = mkdesc(SB0 + OFF_BLK + 2 * BLK, 128, 512, 0);
      const uint32_t xa = sb + OFF_BLK + 18560 + t7 * 8, xr_ = sb + OFF_BLK + 18560 + (t7 ^ 64) * 8;
      uint32_t pr[5][2];
      #pragma unroll
      for (int q = 0; q < 5; q++) {
        #pragma unroll
        for (int e = 0; e < 2; e++) pr[q][e] = __byte_perm(raw[q][e], __shfl_xor_sync(0xffffffff, raw[q][e], 1), (lane & 1) ? 0x3276 : 0x5410);
        const uint32_t m = __reduce_max_sync(0xffffffff, max(raw[q][1] & 0x7fffu, (raw[q][1] >> 16) & 0x7fffu));
        if (lane == 0) sts32(sb + OFF_EPOCH + 64 + q * 16 + w4 * 4, m);
      }
      bar_sync(4, 128);
      if (t7 == 0) TS(40);
      const int j = (w4 & 1) * 16 + (w4 >> 1) * 8 + g, i2 = tq < 2 ? 64 * tq + j : 32 * (tq - 2) + j;
      const uint32_t e2 = B_TBL + 4 * (tq < 2 ? T_F3 + (((i2 - 1) & 1) ? 80 : 0) + ((i2 - 1) >> 1) + 16 : T_F2 + (i2 & 1) * 96 + (i2 >> 1));
      const uint32_t e1 = tq < 2 ? (i2 ? e2 - 64 : B_TBL + 4 * (T_F2 + 175)) : B_TBL + 4 * (i2 ? T_F2 + ((2 * i2 - 1) & 3) * 48 + ((2 * i2 - 1) >> 2) : 16 + 511);
      const uint32_t e0 = B_TBL + (16 + 8 * j + 2 * tq) * 4;
      const float dtl = bf_round(expf(bf_lo(pd)));
      float hd[9];
      auto head = [&](int q) {
        const uint32_t pa0 = pr[0][0], pc0 = pr[0][1];
        const float dt = __shfl_sync(0xffffffff, dtl, q);
        #pragma unroll
        for (int e = 0; e < 2; e++) { pr[0][e] = pr[1][e]; pr[1][e] = pr[2][e]; pr[2][e] = pr[3][e]; pr[3][e] = pr[4][e]; }
        uint32_t mm[4];
        lds128(mm, sb + OFF_EPOCH + 64 + q * 16);
        const uint32_t ex = min(max(max(max(mm[0], mm[1]), max(mm[2], mm[3])) >> 7, 1u), 253u);
        const float sc = __uint_as_float((254u - ex) << 23);
        const float lr = -bf_round(expf(bf_lo(pa0))) * dt * 1.44269504089f;
        const float tn = bf_hi(pa0) * dt * 0.15915494309f;
        cexp_t(lr, -tn, hd[0], hd[1]);
        cexp_t(lr * 8.f, tn * 8.f, hd[2], hd[3]);
        cexp_t(lr * 64.f, tn * 64.f, hd[4], hd[5]);
        hd[6] = bf_lo(pc0) * sc; hd[7] = -bf_hi(pc0) * sc;
        hd[8] = 2.f * dt * __uint_as_float(ex << 23);
      };
      head(0);
      #pragma unroll 1
      for (int it = 0; it < 5; it++) {
        const int k = it;
        const uint32_t blk = sb + OFF_BLK + k * BLK;
        float fac = 0.f;
        float ka[24]; zero<24>(ka);
        {
          if (it == 4) {
            mbar_wait(BAR(BR_UOUT), 0);
            sts128(sb + OFF_UT + B_TBL + t7 * 16, 0, 0, 0, 0); sts128(sb + OFF_UT + B_TBL + 2048 + t7 * 16, 0, 0, 0, 0);
          }
          const uint32_t ga = ea + 4096 - (w4 >> 1) * 512;
#define PUT4(i, a, b, c_, d) sts128(((i) < 8 ? ea + ((i) >> 1) * 512 : ga + (((i) - 8) >> 1) * 512) + ((i) & 1) * 128, a, b, c_, d)
          float z2r, z2i, z4r, z4i, xr[8], xi[8], gr[8], gi[8], wr[9], wi[9];
          const float z1r = hd[0], z1i = hd[1];
          xr[1] = hd[2]; xi[1] = hd[3]; wr[0] = hd[4]; wi[0] = hd[5];
          fac = hd[8];
          xr[0] = 1.f; xi[0] = 0.f;
          csq(xr[1], xi[1], xr[2], xi[2]); cmul(xr[2], xi[2], xr[1], xi[1], xr[3], xi[3]);
          csq(xr[2], xi[2], xr[4], xi[4]);
          #pragma unroll
          for (int b = 1; b < 4; b++) cmul(xr[4], xi[4], xr[b], xi[b], xr[4 + b], xi[4 + b]);
          csq(wr[0], wi[0], wr[1], wi[1]); cmul(wr[1], wi[1], wr[0], wi[0], wr[2], wi[2]);
          csq(wr[1], wi[1], wr[3], wi[3]); csq(wr[3], wi[3], wr[4], wi[4]);
          cmul(wr[4], wi[4], wr[3], wi[3], wr[5], wi[5]); csq(wr[4], wi[4], wr[6], wi[6]);
          cmul(wr[6], wi[6], wr[4], wi[4], wr[7], wi[7]); csq(wr[6], wi[6], wr[8], wi[8]);
          uint32_t R[4], I[4], PR[4], PI[4];
          #pragma unroll
          for (int b = 0; b < 4; b++) { R[b] = packh(xr[2 * b], xr[2 * b + 1]); I[b] = packh(xi[2 * b], xi[2 * b + 1]); }
          PUT4(0, R[0], R[1], R[2], R[3]); PUT4(1, I[0], I[1], I[2], I[3]);
          #pragma unroll
          for (int i = 0; i < 3; i++) {
            const uint32_t z = packh(wr[i], wi[i]);
            #pragma unroll
            for (int b = 0; b < 4; b++) hcm2(R[b], I[b], z, PR[b], PI[b]);
            PUT4(2 * i + 2, PR[0], PR[1], PR[2], PR[3]); PUT4(2 * i + 3, PI[0], PI[1], PI[2], PI[3]);
          }
          gr[0] = hd[6]; gi[0] = hd[7];
          csq(z1r, z1i, z2r, z2i); csq(z2r, z2i, z4r, z4i);
          cmul(gr[0], gi[0], z1r, z1i, gr[1], gi[1]);
          cmul(gr[0], gi[0], z2r, z2i, gr[2], gi[2]); cmul(gr[1], gi[1], z2r, z2i, gr[3], gi[3]);
          #pragma unroll
          for (int b = 0; b < 4; b++) cmul(gr[b], gi[b], z4r, z4i, gr[4 + b], gi[4 + b]);
          PUT4(8, packh(gr[0], gr[1]), packh(gr[2], gr[3]), packh(gr[4], gr[5]), packh(gr[6], gr[7]));
          PUT4(9, packh(gi[0], gi[1]), packh(gi[2], gi[3]), packh(gi[4], gi[5]), packh(gi[6], gi[7]));
          {
            const uint32_t z = packh(wr[3], wi[3]), a4r = packh(gr[0], gr[4]), a4i = packh(gi[0], gi[4]);
            hcm2c(packh(gr[0], gr[2]), packh(gi[0], gi[2]), z, PR[0], PI[0]);
            hcm2c(packh(gr[4], gr[6]), packh(gi[4], gi[6]), z, PR[1], PI[1]);
            hcm2c(a4r, a4i, packh(wr[4], wi[4]), PR[2], PI[2]);
            hcm2c(a4r, a4i, packh(wr[5], wi[5]), PR[3], PI[3]);
            PUT4(10, PR[0], PR[1], PR[2], PR[3]); PUT4(11, PI[0], PI[1], PI[2], PI[3]);
            float hr, hi_;
            cmul(gr[0], gi[0], wr[3], -wi[3], hr, hi_);
            const uint32_t cr = packh(gr[0], hr), ci = packh(gi[0], hi_);
            #pragma unroll
            for (int i = 0; i < 3; i++) hcm2c(cr, ci, packh(wr[6 + i], wi[6 + i]), PR[i], PI[i]);
            PUT4(12, PR[0], PR[1], PR[2], 0u); PUT4(13, PI[0], PI[1], PI[2], 0u);
          }
          fence_async();
          bar_sync(4, 128);
          wg_fence();
          #pragma unroll
          for (int s = 0; s < 8; s++) {
            const uint64_t d = dE + (s >> 2) * (BLK >> 4) + ((s >> 1) & 1) * 448 + (s & 1) * 16;
            wg_ss48_tt_h(ka, d, d + 256, s != 0);
          }
          wg_commit();
        }
        const float dsk = bf_lo(__shfl_sync(0xffffffff, pd, 8 + (it & 7)));
        head(min(it + 1, 4));
        pin<9>(hd);
        wg_wait<0>();
        pin<24>(ka);
        float kk[6];
        const bool up = w4 >= 2;
        #pragma unroll
        for (int n = 0; n < 3; n++) {
          sts64f(xa + n * BLK, up ? ka[12 + 4 * n] : ka[4 * n + 2], up ? ka[13 + 4 * n] : ka[4 * n + 3]);
          kk[2 * n] = up ? ka[14 + 4 * n] : ka[4 * n]; kk[2 * n + 1] = up ? ka[15 + 4 * n] : ka[4 * n + 1];
        }
        if (it) bar_sync(4, 128); else bar_sync(8, 160);
          if (it == 4 && w4 == 0) {
            mbar_wait(BAR(BR_U), 0);
            if (elect_one()) {
              mbar_expect_tx(BAR(BR_U2), 8192);
              bulk_ld(blk - 2 * BLK, g_uy + (c * 80 + r * 5 + 2) * 2048, 4096, BAR(BR_U2)); bulk_ld(blk - BLK, g_uy + (c * 80 + r * 5 + 3) * 2048, 4096, BAR(BR_U2));
            }
            __syncwarp();
          }
        #pragma unroll
        for (int n = 0; n < 3; n++) {
          uint32_t o[2]; lds64(o, xr_ + n * BLK);
          kk[2 * n] = (kk[2 * n] + __uint_as_float(o[0])) * fac; kk[2 * n + 1] = (kk[2 * n + 1] + __uint_as_float(o[1])) * fac;
        }
        if (t7 == 0) kk[0] += dsk;
        {
          const uint32_t v = pack2(kk[1], kk[0]), vh = v >> 16;
          const uint32_t u = pack2(kk[2], kk[3]), w = pack2(kk[4], kk[5]), uu = pack2(kk[2], kk[2]), us = pack2(kk[3], kk[2]);
          const uint32_t x = tq < 2 ? w : u, xh = x >> 16;
          sts32(blk + e0 + 4, v); sts16(blk + e0, vh); sts16(blk + e0 + 10, v);
          sts16(blk + e1, x); sts16(blk + e1 + 6, x); sts16(blk + e2, xh); sts16(blk + e2 + 6, xh);
          if (tq < 2) {
            const uint32_t pb = blk + e0 + 1024 + 8 * tq;
            sts32(pb + 4, uu); sts32(pb + 8, us); sts16(pb + 14, us);
            if (i2) { sts16(pb - 4, u); sts32(pb, uu); }
          }
          if (i2 == 0) {
            const uint32_t tb = blk + B_TBL;
            if (tq == 0) { sts16(tb + (16 + 256) * 4, u); sts16(tb + (T_S + 3) * 4, w); sts32(tb + (T_S + 4) * 4, pack2(kk[4], kk[4])); sts16(tb + (T_S + 5) * 4 + 2, w); }
            else { sts32(tb + 528 * 4, uu); sts32(tb + 529 * 4, uu); sts32(tb + 530 * 4, uu); sts16(tb + 531 * 4 + 2, u); sts16(tb + (T_F3 + 80 + 63) * 4, w); }
          }
        }
        if (t7 == 0) TS(49 + it);
      }
    }
    asm volatile("setmaxnreg.inc.sync.aligned.u32 136;");
    if (t7 == 0) TS(41);
    bar_sync(4, 128);
    if (t7 == 0) mbar_arrive(BAR(BR_KS));
    }
  }
  const int tid = rtid(), lane = tid & 31, g = lane >> 2, tq = lane & 3, t7 = tid & 127;
  mbar_wait(BAR(BR_EPOCH), 0);
  const unsigned epoch = lds32(sb + OFF_EPOCH);
  const uint32_t ytag = (epoch & 1u) * 0x10001u, ym = lane < 4 ? 0x10001u : 0u;
  if (EN_ATT && wg == 1) {
    mbar_wait(BAR(BR_OSTG), 0);
    const int row = t7 >> 3;
    #pragma unroll
    for (int q = 0; q < 10; q++) {
      const char* gs = reinterpret_cast<const char*>(prm.wo) + (size_t)(row + (q % 5) * 16 + CHUNK((lane & 6) + q / 5) * 80) * 1280 + 1024 + c * 32 + (lane & 1) * 16;
      asm volatile("cp.async.cg.shared.global [%0], [%1], 16;" :: "r"(sb + OFF_WOR + (row + q * 16) * 128 + (((lane & 7) ^ (row & 7)) << 4)), "l"(gs) : "memory");
    }
    asm volatile("cp.async.wait_all;" ::: "memory");
    fence_async();
  }
  if (EN_SSM && wg != 1) {
    mbar_wait(BAR(BR_KS), 0);
    mbar_wait(BAR(BR_U), 0);
    if (EN_ATT) mbar_wait(BAR(BR_GEMM), 0);
    if (tid == 256) TS(42);
    {
      const int pass = wg >> 1;
      const int k = pass ? w4 : 4;
      if (k & 2) mbar_wait(BAR(BR_U2), 0);
      const uint32_t blk = sb + OFF_BLK + k * BLK, tb = blk + B_TBL + (uint32_t)((g - 2 * tq) * 4);
      float acc[16][4];
      zero<64>(&acc[0][0]);
      const int kl = 16 * (lane >> 4) + 2 * (lane & 7) + ((lane >> 3) & 1);
      {
        auto ubase = [&](int sh) { const int q = kl - 2 * sh; return blk + (uint32_t)((q * 16) ^ ((q * 2) & 0x10)); };
#define LDQ(A, sh) _Pragma("unroll") for (int m = 0; m < 4; m++) load_quad(A[m], tb + (16 + 16 * (sh) + 128 * m) * 4);
#define LDB(B, ub, h) _Pragma("unroll") for (int p = 0; p < 4; p++) ldsm4(B[p], (ub) + (4 * (h) + p) * 512);
#define MLO(A, B) _Pragma("unroll") for (int m = 0; m < 4; m++) _Pragma("unroll") for (int cc = 0; cc < 8; cc++) mma16816(acc[cc + m], A[m], &B[cc >> 1][(cc & 1) * 2]);
#define MHI(A, B) _Pragma("unroll") for (int m = 0; m < 4; m++) _Pragma("unroll") for (int cc = 0; cc < 8 - m; cc++) mma16816(acc[8 + cc + m], A[m], &B[cc >> 1][(cc & 1) * 2]);
        int p_ = pass ? 0 : w4;
        const int pe = pass ? 4 : w4 + 1;
        uint32_t A[4][4], A2[4][4], Bl[4][4], Bh[4][4];
        uint32_t ub = ubase(p_ + 4);
        LDQ(A, p_ + 4) LDB(Bl, ub, 0)
        #pragma unroll 1
        for (; p_ < pe; p_++) {
          LDB(Bh, ub, 1)
          MLO(A, Bl)
          ub = ubase(p_);
          LDQ(A2, p_) LDB(Bl, ub, 0)
          MHI(A, Bh)
          LDB(Bh, ub, 1)
          load_quad(A[0], tb + (16 + 512 + 16 * (p_ & 1)) * 4); load_quad(A[1], tb + (T_S + 16 * (p_ & 1)) * 4);
          MLO(A2, Bl)
          if (p_ < 2) {
            #pragma unroll
            for (int cc = 0; cc < 8; cc++) mma16816(acc[cc + 4], A[0], &Bl[cc >> 1][(cc & 1) * 2]);
            #pragma unroll
            for (int cc = 0; cc < 4; cc++) mma16816(acc[cc + 12], A[0], &Bh[cc >> 1][(cc & 1) * 2]);
            #pragma unroll
            for (int cc = 0; cc < 8; cc++) mma16816(acc[cc + 8], A[1], &Bl[cc >> 1][(cc & 1) * 2]);
          }
          const int pn = ((p_ + 1) & 3) + 4;
          ub = ubase(pn);
          LDQ(A, pn) LDB(Bl, ub, 0)
          MHI(A2, Bh)
        }
      }
      if (t7 == 0) TS(pass ? 60 : 16);
      mbar_wait(BAR(BR_DRDY), 0);
      {
        const int ih = (lane >> 3) & 1;
        const uint32_t dl = blk + B_D + (uint32_t)(((lane >> 4) * 8 + (lane & 7)) * 16);
        const uint32_t d0_ = dl + ih * 1552, d8_ = dl + (ih ? 0 : 1536), d3_ = dl + B_D7 + ih * 1024;
        auto cls2 = [&](uint32_t da, uint32_t ta) {
          uint32_t B[6][2], A[6][4];
          #pragma unroll
          for (int e = 0; e < 6; e++) { B[e][0] = lds32v(ta + (e + 4) * 32); B[e][1] = lds32v(ta + (e + 3) * 32); }
          #pragma unroll
          for (int kk = 0; kk < 6; kk++) ldsm4t(A[kk], da + kk * 256);
          #pragma unroll
          for (int e = 0; e < 6; e++)
            #pragma unroll
            for (int kk = 0; kk < 6; kk++) if (2 * kk + e + 4 < 16) mma16816(acc[2 * kk + e + 4], A[kk], B[e]);
        };
        auto cls3 = [&](uint32_t da, uint32_t ta) {
          uint32_t B[8][2], A[4][4];
          #pragma unroll
          for (int e = 0; e < 8; e++) { B[e][0] = lds32v(ta + (e + 8) * 32); B[e][1] = lds32v(ta + (e + 7) * 32); }
          #pragma unroll
          for (int kk = 0; kk < 4; kk++) ldsm4t(A[kk], da + kk * 256);
          #pragma unroll
          for (int kk = 0; kk < 4; kk++)
            #pragma unroll
            for (int e = 0; e < 8; e++) if (2 * kk + e + 8 < 16) mma16816(acc[2 * kk + e + 8], A[kk], B[e]);
        };
        if (pass) {
          #pragma unroll 1
          for (int a = 0; a < 2; a++) {
            cls2(d0_ + a * B_D5, tb + (T_F2 + 48 * a - 32) * 4);
            cls2(d8_ + a * B_D5, tb + (T_F2 + 48 * a + 64) * 4);
            cls3(d3_ + a * 2048, tb + (T_F3 + 80 * a - 64) * 4);
          }
        } else {
          cls2(((w4 & 2) ? d8_ : d0_) + (w4 & 1) * B_D5, tb + (T_F2 + 48 * w4 - 32) * 4);
          if (w4 >= 2) cls3(d3_ + (w4 - 2) * 2048, tb + (T_F3 + 80 * (w4 - 2) - 64) * 4);
        }
      }
      if (t7 == 0) TS(pass ? 61 : 17);
      const uint32_t ya = (pass ? sb + OFF_BLK + 3 * BLK + w4 * 4096 : blk) + (uint32_t)((kl * 16) ^ ((kl * 2) & 0x10));
#define YTAG(v) (((v) & ~ym) | (ytag & ym))
#define STY(p) stsm4t(ya + (p) * 512, YTAG(pack2(acc[2 * (p)][0], acc[2 * (p)][1])), pack2(acc[2 * (p)][2], acc[2 * (p)][3]), \
                      YTAG(pack2(acc[2 * (p) + 1][0], acc[2 * (p) + 1][1])), pack2(acc[2 * (p) + 1][2], acc[2 * (p) + 1][3]))
      if (pass == 0) {
        const uint32_t xw = blk + 4096 + w4 * 4096 + lane * 16, xr = blk + 4096 + w4 * 1024 + lane * 16;
        #pragma unroll
        for (int h = 0; h < 2; h++) {
          bar_sync(2, 128);
          #pragma unroll
          for (int i = 0; i < 8; i++)
            sts128(xw + i * 512, __float_as_uint(acc[8 * h + i][0]), __float_as_uint(acc[8 * h + i][1]), __float_as_uint(acc[8 * h + i][2]), __float_as_uint(acc[8 * h + i][3]));
          bar_sync(2, 128);
          float y[8];
          #pragma unroll
          for (int i = 0; i < 8; i++) {
            uint32_t o[4]; lds128(o, xr + (i >> 1) * 4096 + (i & 1) * 512);
            #pragma unroll
            for (int e = 0; e < 4; e++) y[4 * (i & 1) + e] = i < 2 ? __uint_as_float(o[e]) : y[4 * (i & 1) + e] + __uint_as_float(o[e]);
          }
          stsm4t(ya + (4 * h + w4) * 512, YTAG(pack2(y[0], y[1])), pack2(y[2], y[3]), YTAG(pack2(y[4], y[5])), pack2(y[6], y[7]));
        }
      } else {
        fence_async();
        bar_sync(4, 128);
        if (t7 == 0) mbar_arrive(BAR(BR_KS + 1));
        #pragma unroll
        for (int p = 0; p < 8; p++) STY(p);
      }
      fence_async();
      __syncwarp();
      if (lane == 0) mbar_arrive(BAR(BR_Y + 1) - 8 * pass);
      if (t7 == 0) TS(pass ? 62 : 18);
    }
  }
  if (wg < 2) {
    if (EN_ATT) {
    float oc[40]; zero<40>(oc);
    {
      constexpr uint64_t dw0 = mkdesc(SB0, OFF_WOR, 1024, 1), da0 = mkdesc(SB0, 2048, 128, 0);
      const uint32_t ck = sb + tid * 32 + ((lane >> 2) << 2), ck2 = ck + (wg ? 0 : 16384);
      uint32_t bad = 0;
      auto tile = [&](int i, uint32_t so) {
        const uint32_t al = (uint32_t)da0 + wg * 64 + (so >> 4), wl = (uint32_t)dw0 + i * 640 - (i >> 1) * (1278 << 16);
        wg_fence();
        #pragma unroll
        for (int s = 0; s < 5; s++) wg_ss80_tb(oc, desc2(al + s * 256, da0 >> 32), desc2(wl + s * 128, dw0 >> 32), (i | s) != 0);
        wg_commit();
        bad |= (lds32(ck + so) ^ epoch) | (lds32(ck + so + 8192) ^ epoch) | (lds32(ck2 + so) ^ epoch);
      };
      if (w4 == 0) {
        if (EN_SSM) mbar_wait(BAR(BR_Y), 0);
        mbar_wait(BAR(BR_WO), 0);
      }
      bar_sync(1, 256);
      if (tid == 0) TS(9);
      tile(0, SLOT(0));
      #pragma unroll 1
      for (int i = 1; i < 8; i++) {
        mbar_wait(BAR(BR_OFULL) + 8 * i, 0);
        tile(i, SLOT(i));
        wg_wait<1>();
        if (lane == 0) mbar_arrive(BAR(BR_OEMPTY - 1) + 8 * i);
      }
      #pragma unroll 1
      for (int n = 0; n < 56; n++) {
        const int i = n & 7;
        if (i == 0) {
          uint32_t any;
          asm volatile("{\n.reg .pred p;\nsetp.ne.u32 p, %1, 0;\nbarrier.red.or.pred p, 1, 256, p;\nselp.u32 %0, 1, 0, p;\n}" : "=r"(any) : "r"(bad & 1u) : "memory");
          if (!any) break;
          bad = 0;
          FIXCNT
        }
        wg_wait<0>();
        bar_sync(1, 256);
        if (tid == 0) { mbar_expect_tx(BAR(BR_RETRY), 20480); bulk_ld(sb + SLOT(2), &g_o[(r * 8 + CHUNK(i)) * 1280], 20480, BAR(BR_RETRY)); }
        mbar_wait(BAR(BR_RETRY), n & 1);
        tile(i, SLOT(2));
      }
      wg_wait<0>();
      pin<40>(oc);
    }
    if (tid == 0) TS(10);
    {
      const int row = w4 * 16 + (lane & 15);
      const uint32_t ob = sb + OFF_BLK + 3 * BLK + wg * 10240;
      #pragma unroll
      for (int j = 0; j < 8; j += 2)
        stsm4(ob + row * 128 + (((j + (lane >> 4)) ^ (row & 7)) << 4), pack2(oc[4 * j], oc[4 * j + 1]), pack2(oc[4 * j + 2], oc[4 * j + 3]),
              pack2(oc[4 * j + 4], oc[4 * j + 5]), pack2(oc[4 * j + 6], oc[4 * j + 7]));
      stsm4(ob + 8192 + row * 32 + (lane >> 4) * 16, pack2(oc[32], oc[33]), pack2(oc[34], oc[35]), pack2(oc[36], oc[37]), pack2(oc[38], oc[39]));
      fence_async();
      bar_sync(2 + wg, 128);
      if (w4 == 0 && elect_one()) {
        tma2d_st(&prm.m[M_O64], ob, 640 + c * 64, r * 128 + wg * 64);
        tma2d_st(&prm.m[M_O16], ob + 8192, 1152 + c * 16, r * 128 + wg * 64);
        bulk_commit(); bulk_wait0_read();
        if (wg == 0) { TS(11); DUMP(0, 20); }
      }
    }
    }
  } else if (EN_SSM) {
    if (t7 == 0) DUMP(40, 64);
    #pragma unroll 1
    for (int n = 0; n < 64; n++) if (!y_transpose(sb, w4, lane, ytag)) break;
  }
  }
}

typedef CUresult (*EncFn)(CUtensorMap*, CUtensorMapDataType, cuuint32_t, void*, const cuuint64_t*, const cuuint64_t*, const cuuint32_t*,
                          const cuuint32_t*, CUtensorMapInterleave, CUtensorMapSwizzle, CUtensorMapL2promotion, CUtensorMapFloatOOBfill);
static void mkmap(EncFn enc, CUtensorMap* m, const void* base, int rank, const cuuint64_t* dims, const cuuint64_t* strides, const cuuint32_t* box, CUtensorMapSwizzle swz) {
  cuuint32_t es[5] = {1, 1, 1, 1, 1};
  enc(m, CU_TENSOR_MAP_DATA_TYPE_BFLOAT16, rank, const_cast<void*>(base), dims, strides, box, es, CU_TENSOR_MAP_INTERLEAVE_NONE, swz,
      CU_TENSOR_MAP_L2_PROMOTION_L2_128B, CU_TENSOR_MAP_FLOAT_OOB_FILL_NONE);
}

extern "C" void kernel_launch(void* const* d_in, const int* in_sizes, int n_in, void* d_out, int out_size) {
  void* fn = nullptr; cudaDriverEntryPointQueryResult qr;
  cudaGetDriverEntryPoint("cuTensorMapEncodeTiled", &fn, cudaEnableDefault, &qr);
  EncFn enc = (EncFn)fn;
  void* uy = nullptr; cudaGetSymbolAddress(&uy, g_uy);
  const cuuint64_t dx[2] = {640, 2048}, sx[1] = {1280};
  const cuuint32_t bx[2] = {64, 128}, bu[2] = {80, 128};
  const cuuint64_t dw[3] = {640, 640, 3}, sw[2] = {3840, 1280};
  const cuuint32_t br[3] = {16, 32, 3};
  const cuuint64_t dwa[4] = {64, 640, 10, 3}, swa[3] = {3840, 128, 1280}, dwb[4] = {32, 640, 20, 3}, swb[3] = {3840, 64, 1280};
  const cuuint32_t bwa[4] = {64, 32, 1, 3}, bwb[4] = {32, 32, 2, 3};
  const cuuint64_t dwo[2] = {640, 640};
  const cuuint32_t bwo[2] = {64, 80}, bo64[2] = {64, 64}, bo16[2] = {16, 64};
  const cuuint64_t dsa[2] = {2048, 1280}, ssa[1] = {4096};
  const cuuint32_t bsa[2] = {64, 80};
  const cuuint64_t dout[2] = {1280, 2048}, sout[1] = {2560};
  Params prm;
  mkmap(enc, &prm.m[M_X], d_in[7], 2, dx, sx, bx, CU_TENSOR_MAP_SWIZZLE_128B);
  mkmap(enc, &prm.m[M_W128], d_in[8], 4, dwa, swa, bwa, CU_TENSOR_MAP_SWIZZLE_128B);
  mkmap(enc, &prm.m[M_W64], d_in[8], 4, dwb, swb, bwb, CU_TENSOR_MAP_SWIZZLE_64B);
  mkmap(enc, &prm.m[M_WR], d_in[8], 3, dw, sw, br, CU_TENSOR_MAP_SWIZZLE_32B);
  mkmap(enc, &prm.m[M_U], d_in[0], 2, dx, sx, bu, CU_TENSOR_MAP_SWIZZLE_NONE);
  mkmap(enc, &prm.m[M_WO], d_in[9], 2, dwo, sx, bwo, CU_TENSOR_MAP_SWIZZLE_128B);
  mkmap(enc, &prm.m[M_O64], d_out, 2, dout, sout, bo64, CU_TENSOR_MAP_SWIZZLE_128B);
  mkmap(enc, &prm.m[M_O16], d_out, 2, dout, sout, bo16, CU_TENSOR_MAP_SWIZZLE_NONE);
  mkmap(enc, &prm.m[M_SA], uy, 2, dsa, ssa, bsa, CU_TENSOR_MAP_SWIZZLE_128B);
  mkmap(enc, &prm.m[M_OUT], d_out, 2, dout, sout, bu, CU_TENSOR_MAP_SWIZZLE_NONE);
  prm.u = (const __nv_bfloat16*)d_in[0]; prm.wo = (const __nv_bfloat16*)d_in[9];
  for (int i = 0; i < 4; i++) prm.par[i] = (const __nv_bfloat16*)d_in[1 + i];
  prm.logdt = (const __nv_bfloat16*)d_in[5]; prm.dskip = (const __nv_bfloat16*)d_in[6];
  cudaFuncSetAttribute(fused_kernel, cudaFuncAttributeMaxDynamicSharedMemorySize, SMEM_BYTES);
  fused_kernel<<<128, 512, SMEM_BYTES, cudaStreamPerThread>>>(prm);
}
```

```cpp
#include <cuda_runtime.h>
#include <cuda_bf16.h>
#include <cuda_fp16.h>
#include <cuda.h>
#include <stdint.h>

#define EN_ATT 1
#define EN_SSM 1

__device__ __align__(1024) __nv_bfloat16 g_uy[2 * 640 * 2048];
__device__ __align__(128) uint4 g_kvp[8 * 16 * 240];
__device__ __align__(128) uint4 g_o[128 * 1280];
__device__ __align__(128) unsigned g_flag[4 * 128 * 32];
__device__ unsigned g_epoch[128];
#define TS(i) do {} while (0)
#define DUMP(lo, hi) do {} while (0)
#define FIXCNT

constexpr uint32_t SB0 = 1024;
constexpr uint32_t W_SLOT = 15360, OFF_X = 76800;
constexpr uint32_t OFF_WOR = 81920, OFF_KVP = 10240, OFF_KVS = 71680, OFF_PK = 10240, OFF_V = 30720, OFF_EXTRA = 102400, OFF_KVB = OFF_EXTRA;
constexpr uint32_t OFF_BAR = 125952, OFF_BLK = 128000, BLK = 20480;
constexpr uint32_t B_D = 4096, B_D5 = 3088, B_D7 = 6176, B_D9 = 8224, B_TBL = 14400;
constexpr int T_S = 576, T_F2 = 624, T_F3 = 816;
constexpr uint32_t OFF_UT = OFF_BLK + 4 * BLK;
constexpr uint32_t SMEM_BYTES = OFF_BLK + 5 * BLK;
enum { BR_FULL = 0, BR_WO = 5, BR_PUB = 6, BR_KVP = 7, BR_U = 8, BR_U2 = 9, BR_GEMM = 10, BR_UIN = 11, BR_YIN = 12, BR_EPOCH = 13,
       BR_FREE = 14, BR_RETRY = 16, BR_KS = 17, BR_UOUT = 19, BR_OFULL = 19  , BR_EMPTY = 27, BR_OEMPTY = 32, BR_OSTG = 39,
       BR_Y = 40, BR_DRDY = 42, BR_WOR = 43, BR_COUNT = 44 };
constexpr uint32_t OFF_EPOCH = OFF_BAR + 8 * BR_COUNT;
enum { M_X, M_W128, M_W64, M_WR, M_U, M_WO, M_WOR, M_O64, M_O16, M_SA, M_OUT, M_COUNT };

__device__ __forceinline__ long long clk64() { long long t; asm volatile("mov.u64 %0, %%clock64;" : "=l"(t) :: "memory"); return t; }
__device__ __forceinline__ uint32_t smem_u32(const void* p) { return (uint32_t)__cvta_generic_to_shared(p); }
__host__ __device__ constexpr uint64_t mkdesc(uint32_t addr, uint32_t lbo, uint32_t sbo, uint32_t swz) {
  return (uint64_t)((addr & 0x3FFFF) >> 4) | ((uint64_t)(lbo >> 4) << 16) | ((uint64_t)(sbo >> 4) << 32) | ((uint64_t)swz << 62);
}
__device__ __forceinline__ uint64_t desc2(uint32_t lo, uint32_t hi) { uint64_t d; asm("mov.b64 %0, {%1, %2};" : "=l"(d) : "r"(lo), "r"(hi)); return d; }
__device__ __forceinline__ void mbar_init(uint32_t bar, uint32_t cnt) { asm volatile("mbarrier.init.shared::cta.b64 [%0], %1;" :: "r"(bar), "r"(cnt) : "memory"); }
__device__ __forceinline__ void mbar_expect_tx(uint32_t bar, uint32_t bytes) { asm volatile("mbarrier.arrive.expect_tx.shared::cta.b64 _, [%0], %1;" :: "r"(bar), "r"(bytes) : "memory"); }
__device__ __forceinline__ void mbar_arrive(uint32_t bar) { asm volatile("mbarrier.arrive.shared::cta.b64 _, [%0];" :: "r"(bar) : "memory"); }
__device__ __forceinline__ void mbar_wait(uint32_t bar, uint32_t parity) {
  asm volatile("{\n.reg .pred p;\n.reg .u32 c;\nmov.u32 c, 0;\n"
    "WL:\nmbarrier.try_wait.parity.shared::cta.b64 p, [%0], %1;\n@p bra WD;\n"
    "add.u32 c, c, 1;\nsetp.lt.u32 p, c, 200000;\n@p bra WL;\nWD:\n}" :: "r"(bar), "r"(parity) : "memory");
}
__device__ __forceinline__ void poll_all(const unsigned* p, unsigned val) {
  asm volatile("{\n.reg .pred p;\n.reg .u32 c, v;\nmov.u32 c, 0;\n"
    "PL:\nld.relaxed.gpu.global.u32 v, [%0];\nsetp.eq.u32 p, v, %1;\nvote.sync.all.pred p, p, 0xffffffff;\n@p bra PD;\n"
    "add.u32 c, c, 1;\nsetp.lt.u32 p, c, 100000;\n@p bra PL;\nPD:\n}" :: "l"(p), "r"(val) : "memory");
}
__device__ __forceinline__ void poll_all_acq(const unsigned* p, unsigned val) {
  asm volatile("{\n.reg .pred p;\n.reg .u32 c, v;\nmov.u32 c, 0;\n"
    "PL:\nld.acquire.gpu.global.u32 v, [%0];\nsetp.eq.u32 p, v, %1;\nvote.sync.all.pred p, p, 0xffffffff;\n@p bra PD;\n"
    "nanosleep.u32 300;\nadd.u32 c, c, 1;\nsetp.lt.u32 p, c, 100000;\n@p bra PL;\nPD:\n}" :: "l"(p), "r"(val) : "memory");
}
__device__ __forceinline__ unsigned poll_bit(const unsigned* p, unsigned val, unsigned mask) {
  unsigned bal;
  asm volatile("{\n.reg .pred p;\n.reg .u32 c, v;\nmov.u32 c, 0;\n"
    "PL:\nld.relaxed.gpu.global.u32 v, [%1];\nsetp.eq.u32 p, v, %2;\nvote.sync.ballot.b32 %0, p, 0xffffffff;\n"
    "and.b32 v, %0, %3;\nsetp.ne.u32 p, v, 0;\n@p bra PD;\n"
    "add.u32 c, c, 1;\nsetp.lt.u32 p, c, 100000;\n@p bra PL;\nPD:\n}" : "=&r"(bal) : "l"(p), "r"(val), "r"(mask) : "memory");
  return bal;
}
__device__ __forceinline__ void fix128_w3(uint32_t* v, const void* p, uint32_t tag, uint32_t mask) {
  asm volatile("{\n.reg .pred p;\n.reg .u32 c, x;\n.reg .b128 t;\n.reg .b64 lo, hi;\nmov.u32 c, 0;\n"
    "FL:\nxor.b32 x, %3, %5;\nand.b32 x, x, %6;\nsetp.eq.u32 p, x, 0;\n@p bra FD;\n"
    "ld.relaxed.gpu.global.b128 t, [%4];\nmov.b128 {lo, hi}, t;\nmov.b64 {%0, %1}, lo;\nmov.b64 {%2, %3}, hi;\n"
    "add.u32 c, c, 1;\nsetp.lt.u32 p, c, 100000;\n@p bra FL;\nFD:\n}"
    : "+r"(v[0]), "+r"(v[1]), "+r"(v[2]), "+r"(v[3]) : "l"(p), "r"(tag), "r"(mask) : "memory");
}
__device__ __forceinline__ bool elect_one() {
  uint32_t p; asm volatile("{\n.reg .pred P;\nelect.sync _|P, 0xffffffff;\nselp.u32 %0, 1, 0, P;\n}" : "=r"(p)); return p;
}
__device__ __forceinline__ void bar_sync(int id, int n) { asm volatile("bar.sync %0, %1;" :: "r"(id), "r"(n) : "memory"); }
__device__ __forceinline__ void fence_async() { asm volatile("fence.proxy.async.shared::cta;" ::: "memory"); }
__device__ __forceinline__ void fence_async_g() { asm volatile("fence.proxy.async.global;" ::: "memory"); }
__device__ __forceinline__ void tma2d(uint32_t dst, const CUtensorMap* m, uint32_t bar, int c0, int c1) {
  asm volatile("cp.async.bulk.tensor.2d.shared::cluster.global.mbarrier::complete_tx::bytes [%0], [%1, {%3, %4}], [%2];"
    :: "r"(dst), "l"(m), "r"(bar), "r"(c0), "r"(c1) : "memory");
}
__device__ __forceinline__ void tma3d(uint32_t dst, const CUtensorMap* m, uint32_t bar, int c0, int c1, int c2) {
  asm volatile("cp.async.bulk.tensor.3d.shared::cluster.global.mbarrier::complete_tx::bytes [%0], [%1, {%3, %4, %5}], [%2];"
    :: "r"(dst), "l"(m), "r"(bar), "r"(c0), "r"(c1), "r"(c2) : "memory");
}
__device__ __forceinline__ void tma4d(uint32_t dst, const CUtensorMap* m, uint32_t bar, int c0, int c1, int c2, int c3) {
  asm volatile("cp.async.bulk.tensor.4d.shared::cluster.global.mbarrier::complete_tx::bytes [%0], [%1, {%3, %4, %5, %6}], [%2];"
    :: "r"(dst), "l"(m), "r"(bar), "r"(c0), "r"(c1), "r"(c2), "r"(c3) : "memory");
}
__device__ __forceinline__ void tma2d_st(const CUtensorMap* m, uint32_t src, int c0, int c1) {
  asm volatile("cp.async.bulk.tensor.2d.global.shared::cta.bulk_group [%0, {%2, %3}], [%1];"
    :: "l"(m), "r"(src), "r"(c0), "r"(c1) : "memory");
}
__device__ __forceinline__ void bulk_ld(uint32_t dst, const void* src, uint32_t bytes, uint32_t bar) {
  asm volatile("cp.async.bulk.shared::cluster.global.mbarrier::complete_tx::bytes [%0], [%1], %2, [%3];"
    :: "r"(dst), "l"(src), "r"(bytes), "r"(bar) : "memory");
}
__device__ __forceinline__ void bulk_st(void* dst, uint32_t src, uint32_t bytes) {
  asm volatile("cp.async.bulk.global.shared::cta.bulk_group [%0], [%1], %2;" :: "l"(dst), "r"(src), "r"(bytes) : "memory");
}
__device__ __forceinline__ void bulk_commit() { asm volatile("cp.async.bulk.commit_group;" ::: "memory"); }
__device__ __forceinline__ void bulk_wait0() { asm volatile("cp.async.bulk.wait_group 0;" ::: "memory"); }
__device__ __forceinline__ void bulk_wait0_read() { asm volatile("cp.async.bulk.wait_group.read 0;" ::: "memory"); }
__device__ __forceinline__ unsigned ld_rlx(const unsigned* p) { unsigned v; asm volatile("ld.relaxed.gpu.global.u32 %0, [%1];" : "=r"(v) : "l"(p) : "memory"); return v; }
__device__ __forceinline__ unsigned ld_acq(const unsigned* p) { unsigned v; asm volatile("ld.acquire.gpu.global.u32 %0, [%1];" : "=r"(v) : "l"(p) : "memory"); return v; }
__device__ __forceinline__ void st_rlx(unsigned* p, unsigned v) { asm volatile("st.relaxed.gpu.global.u32 [%0], %1;" :: "l"(p), "r"(v) : "memory"); }
__device__ __forceinline__ void st_rel(unsigned* p, unsigned v) { asm volatile("st.release.gpu.global.u32 [%0], %1;" :: "l"(p), "r"(v) : "memory"); }
__device__ __forceinline__ void st128_rlx(void* p, const uint32_t* v) {
  asm volatile("{\n.reg .b128 t;\n.reg .b64 lo, hi;\nmov.b64 lo, {%1, %2};\nmov.b64 hi, {%3, %4};\nmov.b128 t, {lo, hi};\n"
    "st.relaxed.gpu.global.b128 [%0], t;\n}" :: "l"(p), "r"(v[0]), "r"(v[1]), "r"(v[2]), "r"(v[3]) : "memory");
}
__device__ __forceinline__ uint32_t lds32(uint32_t a) { uint32_t v; asm volatile("ld.shared.u32 %0, [%1];" : "=r"(v) : "r"(a) : "memory"); return v; }
__device__ __forceinline__ uint32_t lds32v(uint32_t a) { uint32_t v; asm volatile("ld.volatile.shared.u32 %0, [%1];" : "=r"(v) : "r"(a) : "memory"); return v; }
__device__ __forceinline__ void lds128(uint32_t* v, uint32_t a) { asm volatile("ld.shared.v4.u32 {%0,%1,%2,%3}, [%4];" : "=r"(v[0]), "=r"(v[1]), "=r"(v[2]), "=r"(v[3]) : "r"(a) : "memory"); }
__device__ __forceinline__ void sts32(uint32_t a, uint32_t v) { asm volatile("st.shared.u32 [%0], %1;" :: "r"(a), "r"(v) : "memory"); }
__device__ __forceinline__ void sts16(uint32_t a, uint32_t v) { asm volatile("st.shared.u16 [%0], %1;" :: "r"(a), "h"((uint16_t)v) : "memory"); }
__device__ __forceinline__ void sts64f(uint32_t a, float x, float y) { asm volatile("st.shared.v2.f32 [%0], {%1,%2};" :: "r"(a), "f"(x), "f"(y) : "memory"); }
__device__ __forceinline__ void sts128(uint32_t a, uint32_t x, uint32_t y, uint32_t z, uint32_t w) { asm volatile("st.shared.v4.u32 [%0], {%1,%2,%3,%4};" :: "r"(a), "r"(x), "r"(y), "r"(z), "r"(w) : "memory"); }
__device__ __forceinline__ void stsm4(uint32_t a, uint32_t r0, uint32_t r1, uint32_t r2, uint32_t r3) {
  asm volatile("stmatrix.sync.aligned.m8n8.x4.shared.b16 [%0], {%1,%2,%3,%4};" :: "r"(a), "r"(r0), "r"(r1), "r"(r2), "r"(r3) : "memory");
}
__device__ __forceinline__ void stsm4t(uint32_t a, uint32_t r0, uint32_t r1, uint32_t r2, uint32_t r3) {
  asm volatile("stmatrix.sync.aligned.m8n8.x4.trans.shared.b16 [%0], {%1,%2,%3,%4};" :: "r"(a), "r"(r0), "r"(r1), "r"(r2), "r"(r3) : "memory");
}
__device__ __forceinline__ void ldsm4t(uint32_t* r, uint32_t a) {
  asm volatile("ldmatrix.sync.aligned.m8n8.x4.trans.shared.b16 {%0,%1,%2,%3}, [%4];" : "=r"(r[0]), "=r"(r[1]), "=r"(r[2]), "=r"(r[3]) : "r"(a) : "memory");
}
__device__ __forceinline__ void ldsm4(uint32_t* r, uint32_t a) {
  asm volatile("ldmatrix.sync.aligned.m8n8.x4.shared.b16 {%0,%1,%2,%3}, [%4];" : "=r"(r[0]), "=r"(r[1]), "=r"(r[2]), "=r"(r[3]) : "r"(a) : "memory");
}
__device__ __forceinline__ void mma16816(float* d, const uint32_t* a, const uint32_t* b) {
  asm volatile("mma.sync.aligned.m16n8k16.row.col.f32.bf16.bf16.f32 {%0,%1,%2,%3}, {%4,%5,%6,%7}, {%8,%9}, {%0,%1,%2,%3};"
    : "+f"(d[0]), "+f"(d[1]), "+f"(d[2]), "+f"(d[3]) : "r"(a[0]), "r"(a[1]), "r"(a[2]), "r"(a[3]), "r"(b[0]), "r"(b[1]));
}
__device__ __forceinline__ uint32_t pack2(float lo, float hi) { uint32_t r; asm("cvt.rn.bf16x2.f32 %0, %1, %2;" : "=r"(r) : "f"(hi), "f"(lo)); return r; }
__device__ __forceinline__ uint32_t packh(float lo, float hi) { uint32_t r; asm("cvt.rn.f16x2.f32 %0, %1, %2;" : "=r"(r) : "f"(hi), "f"(lo)); return r; }
__device__ __forceinline__ void hcm2(uint32_t xr, uint32_t xi, uint32_t z, uint32_t& pr, uint32_t& pi) {
  const __half2 a = *reinterpret_cast<__half2*>(&xr), b = *reinterpret_cast<__half2*>(&xi), zz = *reinterpret_cast<__half2*>(&z);
  const __half2 re = __hfma2(__hneg2(b), __high2half2(zz), __hmul2(a, __low2half2(zz)));
  const __half2 im = __hfma2(a, __high2half2(zz), __hmul2(b, __low2half2(zz)));
  pr = *reinterpret_cast<const uint32_t*>(&re); pi = *reinterpret_cast<const uint32_t*>(&im);
}
__device__ __forceinline__ void hcm2c(uint32_t xr, uint32_t xi, uint32_t z, uint32_t& pr, uint32_t& pi) {
  const __half2 a = *reinterpret_cast<__half2*>(&xr), b = *reinterpret_cast<__half2*>(&xi), zz = *reinterpret_cast<__half2*>(&z);
  const __half2 re = __hfma2(b, __high2half2(zz), __hmul2(a, __low2half2(zz)));
  const __half2 im = __hfma2(__hneg2(a), __high2half2(zz), __hmul2(b, __low2half2(zz)));
  pr = *reinterpret_cast<const uint32_t*>(&re); pi = *reinterpret_cast<const uint32_t*>(&im);
}
__device__ __forceinline__ void lds64(uint32_t* v, uint32_t a) { asm volatile("ld.shared.v2.u32 {%0,%1}, [%2];" : "=r"(v[0]), "=r"(v[1]) : "r"(a) : "memory"); }
__device__ __forceinline__ float bf_lo(uint32_t v) { return __uint_as_float(v << 16); }
__device__ __forceinline__ float bf_hi(uint32_t v) { return __uint_as_float(v & 0xffff0000u); }
__device__ __forceinline__ float bf_round(float x) { return bf_lo(pack2(x, 0.f)); }
__device__ __forceinline__ float ex2(float x) { float r; asm("ex2.approx.ftz.f32 %0, %1;" : "=f"(r) : "f"(x)); return r; }
__device__ __forceinline__ float phi(float t, float l2e = 1.44269504089f) {
  float e = ex2(t * l2e) + 1e-6f;
  asm("{\n.reg .pred p;\nsetp.gt.f32 p, %1, 0f00000000;\n@p add.f32 %0, %1, 0f3F800008;\n}" : "+f"(e) : "f"(t));
  return e;
}
__device__ __forceinline__ void wg_fence() { asm volatile("wgmma.fence.sync.aligned;" ::: "memory"); }
__device__ __forceinline__ void wg_commit() { asm volatile("wgmma.commit_group.sync.aligned;" ::: "memory"); }
template <int N> __device__ __forceinline__ void wg_wait() { asm volatile("wgmma.wait_group.sync.aligned %0;" :: "n"(N) : "memory"); }
template <int N> __device__ __forceinline__ void pin(float* a) {
  #pragma unroll
  for (int i = 0; i < N; i++) asm volatile("" : "+f"(a[i]) :: "memory");
}
__device__ __forceinline__ int rtid() { int t; asm volatile("mov.u32 %0, %%tid.x;" : "=r"(t)); return t; }
template <int N> __device__ __forceinline__ void zero(float* a) {
  #pragma unroll
  for (int i = 0; i < N; i++) asm volatile("mov.b32 %0, 0;" : "=f"(a[i]));
}
__device__ __forceinline__ void cexp_t(float lg2mag, float turns, float& re, float& im) {
  float m = ex2(lg2mag);
  float fr = (turns - __fadd_rn(__fadd_rn(turns, 12582912.f), -12582912.f)) * 6.283185307f;
  re = m * __cosf(fr); im = m * __sinf(fr);
}
__device__ __forceinline__ void csq(float ar, float ai, float& cr, float& ci) {
  const float t = ar + ar;
  cr = fmaf(ar, ar, -ai * ai); ci = t * ai;
}
__device__ __forceinline__ void cmul(float ar, float ai, float br, float bi, float& cr, float& ci) {
  cr = fmaf(ar, br, -ai * bi); ci = fmaf(ar, bi, ai * br);
}

__device__ __forceinline__ void wg_ss48_tt(float* d, uint64_t da, uint64_t db, int scale_d) {
  asm volatile("{\n.reg .pred p;\nsetp.ne.b32 p, %26, 0;\n"
    "wgmma.mma_async.sync.aligned.m64n48k16.f32.bf16.bf16 "
    "{%0, %1, %2, %3, %4, %5, %6, %7, %8, %9, %10, %11, %12, %13, %14, %15, %16, %17, %18, %19, %20, %21, %22, %23}, %24, %25, p, 1, 1, 1, 1;\n}\n"
    : "+f"(d[0]), "+f"(d[1]), "+f"(d[2]), "+f"(d[3]), "+f"(d[4]), "+f"(d[5]), "+f"(d[6]), "+f"(d[7]), "+f"(d[8]), "+f"(d[9]), "+f"(d[10]), "+f"(d[11]), "+f"(d[12]), "+f"(d[13]), "+f"(d[14]), "+f"(d[15]), "+f"(d[16]), "+f"(d[17]), "+f"(d[18]), "+f"(d[19]), "+f"(d[20]), "+f"(d[21]), "+f"(d[22]), "+f"(d[23])
    : "l"(da), "l"(db), "r"(scale_d));
}
__device__ __forceinline__ void wg_rs88_tb(float* d, const uint32_t* a, uint64_t db, int scale_d) {
  asm volatile("{\n.reg .pred p;\nsetp.ne.b32 p, %49, 0;\n"
    "wgmma.mma_async.sync.aligned.m64n88k16.f32.bf16.bf16 "
    "{%0, %1, %2, %3, %4, %5, %6, %7, %8, %9, %10, %11, %12, %13, %14, %15, %16, %17, %18, %19, %20, %21, %22, %23, %24, %25, %26, %27, %28, %29, %30, %31, %32, %33, %34, %35, %36, %37, %38, %39, %40, %41, %42, %43}, {%44, %45, %46, %47}, %48, p, 1, 1, 1;\n}\n"
    : "+f"(d[0]), "+f"(d[1]), "+f"(d[2]), "+f"(d[3]), "+f"(d[4]), "+f"(d[5]), "+f"(d[6]), "+f"(d[7]), "+f"(d[8]), "+f"(d[9]), "+f"(d[10]), "+f"(d[11]), "+f"(d[12]), "+f"(d[13]), "+f"(d[14]), "+f"(d[15]), "+f"(d[16]), "+f"(d[17]), "+f"(d[18]), "+f"(d[19]), "+f"(d[20]), "+f"(d[21]), "+f"(d[22]), "+f"(d[23]), "+f"(d[24]), "+f"(d[25]), "+f"(d[26]), "+f"(d[27]), "+f"(d[28]), "+f"(d[29]), "+f"(d[30]), "+f"(d[31]), "+f"(d[32]), "+f"(d[33]), "+f"(d[34]), "+f"(d[35]), "+f"(d[36]), "+f"(d[37]), "+f"(d[38]), "+f"(d[39]), "+f"(d[40]), "+f"(d[41]), "+f"(d[42]), "+f"(d[43])
    : "r"(a[0]), "r"(a[1]), "r"(a[2]), "r"(a[3]), "l"(db), "r"(scale_d));
}
__device__ __forceinline__ void wg_ss80_tb(float* d, uint64_t da, uint64_t db, int scale_d) {
  asm volatile("{\n.reg .pred p;\nsetp.ne.b32 p, %42, 0;\n"
    "wgmma.mma_async.sync.aligned.m64n80k16.f32.bf16.bf16 "
    "{%0, %1, %2, %3, %4, %5, %6, %7, %8, %9, %10, %11, %12, %13, %14, %15, %16, %17, %18, %19, %20, %21, %22, %23, %24, %25, %26, %27, %28, %29, %30, %31, %32, %33, %34, %35, %36, %37, %38, %39}, %40, %41, p, 1, 1, 0, 1;\n}\n"
    : "+f"(d[0]), "+f"(d[1]), "+f"(d[2]), "+f"(d[3]), "+f"(d[4]), "+f"(d[5]), "+f"(d[6]), "+f"(d[7]), "+f"(d[8]), "+f"(d[9]), "+f"(d[10]), "+f"(d[11]), "+f"(d[12]), "+f"(d[13]), "+f"(d[14]), "+f"(d[15]), "+f"(d[16]), "+f"(d[17]), "+f"(d[18]), "+f"(d[19]), "+f"(d[20]), "+f"(d[21]), "+f"(d[22]), "+f"(d[23]), "+f"(d[24]), "+f"(d[25]), "+f"(d[26]), "+f"(d[27]), "+f"(d[28]), "+f"(d[29]), "+f"(d[30]), "+f"(d[31]), "+f"(d[32]), "+f"(d[33]), "+f"(d[34]), "+f"(d[35]), "+f"(d[36]), "+f"(d[37]), "+f"(d[38]), "+f"(d[39])
    : "l"(da), "l"(db), "r"(scale_d));
}
__device__ __forceinline__ void wg_ss48_tt_h(float* d, uint64_t da, uint64_t db, int scale_d) {
  asm volatile("{\n.reg .pred p;\nsetp.ne.b32 p, %26, 0;\n"
    "wgmma.mma_async.sync.aligned.m64n48k16.f32.f16.f16 "
    "{%0, %1, %2, %3, %4, %5, %6, %7, %8, %9, %10, %11, %12, %13, %14, %15, %16, %17, %18, %19, %20, %21, %22, %23}, %24, %25, p, 1, 1, 1, 1;\n}\n"
    : "+f"(d[0]), "+f"(d[1]), "+f"(d[2]), "+f"(d[3]), "+f"(d[4]), "+f"(d[5]), "+f"(d[6]), "+f"(d[7]), "+f"(d[8]), "+f"(d[9]), "+f"(d[10]), "+f"(d[11]), "+f"(d[12]), "+f"(d[13]), "+f"(d[14]), "+f"(d[15]), "+f"(d[16]), "+f"(d[17]), "+f"(d[18]), "+f"(d[19]), "+f"(d[20]), "+f"(d[21]), "+f"(d[22]), "+f"(d[23])
    : "l"(da), "l"(db), "r"(scale_d));
}
__device__ __forceinline__ void wg_rs192_tb(float* d, const uint32_t* a, uint64_t db, int scale_d) {
  asm volatile("{\n.reg .pred p;\nsetp.ne.b32 p, %101, 0;\n"
    "wgmma.mma_async.sync.aligned.m64n192k16.f32.bf16.bf16 "
    "{%0, %1, %2, %3, %4, %5, %6, %7, %8, %9, %10, %11, %12, %13, %14, %15, %16, %17, %18, %19, %20, %21, %22, %23, %24, %25, %26, %27, %28, %29, %30, %31, %32, %33, %34, %35, %36, %37, %38, %39, %40, %41, %42, %43, %44, %45, %46, %47, %48, %49, %50, %51, %52, %53, %54, %55, %56, %57, %58, %59, %60, %61, %62, %63, %64, %65, %66, %67, %68, %69, %70, %71, %72, %73, %74, %75, %76, %77, %78, %79, %80, %81, %82, %83, %84, %85, %86, %87, %88, %89, %90, %91, %92, %93, %94, %95}, {%96, %97, %98, %99}, %100, p, 1, 1, 1;\n}\n"
    : "+f"(d[0]), "+f"(d[1]), "+f"(d[2]), "+f"(d[3]), "+f"(d[4]), "+f"(d[5]), "+f"(d[6]), "+f"(d[7]), "+f"(d[8]), "+f"(d[9]), "+f"(d[10]), "+f"(d[11]), "+f"(d[12]), "+f"(d[13]), "+f"(d[14]), "+f"(d[15]), "+f"(d[16]), "+f"(d[17]), "+f"(d[18]), "+f"(d[19]), "+f"(d[20]), "+f"(d[21]), "+f"(d[22]), "+f"(d[23]), "+f"(d[24]), "+f"(d[25]), "+f"(d[26]), "+f"(d[27]), "+f"(d[28]), "+f"(d[29]), "+f"(d[30]), "+f"(d[31]), "+f"(d[32]), "+f"(d[33]), "+f"(d[34]), "+f"(d[35]), "+f"(d[36]), "+f"(d[37]), "+f"(d[38]), "+f"(d[39]), "+f"(d[40]), "+f"(d[41]), "+f"(d[42]), "+f"(d[43]), "+f"(d[44]), "+f"(d[45]), "+f"(d[46]), "+f"(d[47]), "+f"(d[48]), "+f"(d[49]), "+f"(d[50]), "+f"(d[51]), "+f"(d[52]), "+f"(d[53]), "+f"(d[54]), "+f"(d[55]), "+f"(d[56]), "+f"(d[57]), "+f"(d[58]), "+f"(d[59]), "+f"(d[60]), "+f"(d[61]), "+f"(d[62]), "+f"(d[63]), "+f"(d[64]), "+f"(d[65]), "+f"(d[66]), "+f"(d[67]), "+f"(d[68]), "+f"(d[69]), "+f"(d[70]), "+f"(d[71]), "+f"(d[72]), "+f"(d[73]), "+f"(d[74]), "+f"(d[75]), "+f"(d[76]), "+f"(d[77]), "+f"(d[78]), "+f"(d[79]), "+f"(d[80]), "+f"(d[81]), "+f"(d[82]), "+f"(d[83]), "+f"(d[84]), "+f"(d[85]), "+f"(d[86]), "+f"(d[87]), "+f"(d[88]), "+f"(d[89]), "+f"(d[90]), "+f"(d[91]), "+f"(d[92]), "+f"(d[93]), "+f"(d[94]), "+f"(d[95])
    : "r"(a[0]), "r"(a[1]), "r"(a[2]), "r"(a[3]), "l"(db), "r"(scale_d));
}
__device__ __forceinline__ void wg_rs48_tb(float* d, const uint32_t* a, uint64_t db, int scale_d) {
  asm volatile("{\n.reg .pred p;\nsetp.ne.b32 p, %29, 0;\n"
    "wgmma.mma_async.sync.aligned.m64n48k16.f32.bf16.bf16 "
    "{%0, %1, %2, %3, %4, %5, %6, %7, %8, %9, %10, %11, %12, %13, %14, %15, %16, %17, %18, %19, %20, %21, %22, %23}, {%24, %25, %26, %27}, %28, p, 1, 1, 1;\n}\n"
    : "+f"(d[0]), "+f"(d[1]), "+f"(d[2]), "+f"(d[3]), "+f"(d[4]), "+f"(d[5]), "+f"(d[6]), "+f"(d[7]), "+f"(d[8]), "+f"(d[9]), "+f"(d[10]), "+f"(d[11]), "+f"(d[12]), "+f"(d[13]), "+f"(d[14]), "+f"(d[15]), "+f"(d[16]), "+f"(d[17]), "+f"(d[18]), "+f"(d[19]), "+f"(d[20]), "+f"(d[21]), "+f"(d[22]), "+f"(d[23])
    : "r"(a[0]), "r"(a[1]), "r"(a[2]), "r"(a[3]), "l"(db), "r"(scale_d));
}

struct Params {
  const __nv_bfloat16 *par[4], *logdt, *dskip, *u, *wo;
  CUtensorMap m[M_COUNT];
};

#define CHUNK(i) ((c + (i)) & 7)
#define FLAG(kind, rr, cc) (&g_flag[((kind) * 128 + (rr) * 8 + (cc)) * 32])
#define SLOT(i) ((i) == 0 ? OFF_EXTRA : OFF_BLK - 256 + ((i) > 5 ? (i) - 6 : (i) - 1) * BLK)
__device__ __forceinline__ void load_quad(uint32_t* A, uint32_t addr) {
  A[0] = lds32v(addr); A[1] = lds32v(addr + 32); A[2] = lds32v(addr - 32); A[3] = lds32v(addr);
}

__device__ __forceinline__ bool y_transpose(uint32_t sb, int w5, int lane, uint32_t ytag) {
  const int mi = lane >> 3, rw = lane & 7;
  const uint32_t sa = sb + OFF_EXTRA + (w5 * 16 + rw) * 128 + ((mi ^ rw) << 4), da = sb + SLOT(3) + (8 * mi + rw) * 160 + w5 * 32;
  const uint32_t ym = lane < 4 ? 0x10001u : 0u;
  bar_sync(7, 160);
  uint32_t v[8][4], bad = 0;
  #pragma unroll
  for (int q = 0; q < 8; q++) ldsm4t(v[q], (sa ^ ((q & 1) * 64 + ((q >> 1) & 1) * 16)) + ((q >> 1) & 1) * 10240 + (q >> 2) * 1024);
  #pragma unroll
  for (int q = 0; q < 8; q++) {
    bad |= (v[q][0] ^ ytag) | (v[q][2] ^ ytag);
    stsm4(da + (q & 3) * 5120 + (q >> 2) * 16, v[q][0] & ~ym, v[q][1], v[q][2] & ~ym, v[q][3]);
  }
  fence_async();
  uint32_t any;
  asm volatile("{\n.reg .pred p;\nsetp.ne.u32 p, %1, 0;\nbarrier.red.or.pred p, 7, 160, p;\nselp.u32 %0, 1, 0, p;\n}" : "=r"(any) : "r"(bad & ym) : "memory");
  return any;
}

__global__ void __launch_bounds__(512, 1) fused_kernel(const __grid_constant__ Params prm) {
  extern __shared__ unsigned char smem_raw[];
  uint32_t raw[5][2], pd;
  if ((threadIdx.x >> 7) == 2) {
    const int ch = (blockIdx.x & 7) * 80 + (blockIdx.x >> 3) * 5, od = threadIdx.x & 1;
    #pragma unroll
    for (int e = 0; e < 2; e++) {
      const __nv_bfloat16* pp = prm.par[2 * e + od] + ch * 128 + (threadIdx.x & 126);
      #pragma unroll
      for (int q = 0; q < 5; q++) asm volatile("ld.global.nc.u32 %0, [%1];" : "=r"(raw[q][e]) : "l"(pp + q * 128));
    }
    asm volatile("ld.global.nc.u16 %0, [%1];" : "=r"(pd) : "l"(((threadIdx.x & 8) ? prm.dskip : prm.logdt) + ch + min(threadIdx.x & 7, 4)));
  }
  constexpr uint32_t sb = SB0;
  const int tid = threadIdx.x, lane = tid & 31;
  const int warp = __shfl_sync(0xffffffff, tid >> 5, 0), wg = warp >> 2, w4 = warp & 3;
  const int cta = blockIdx.x, r = cta >> 3, c = cta & 7;
  if (smem_u32(smem_raw) != SB0) return;
#define BAR(i) (sb + OFF_BAR + 8 * (i))
  const bool sw64 = ((c + 1) & 2) != 0;

  const CUtensorMap* mwp = &prm.m[sw64 ? M_W64 : M_W128];
  const int mcol = (c * 80 + (c & 1) * 16) >> (sw64 ? 5 : 6), rcol = c * 80 + ((c & 1) ? 0 : 64);
  if (warp == 12 && elect_one()) {
    #pragma unroll
    for (int i = 0; i < 5; i++) mbar_init(BAR(BR_FULL + i), 1);
    asm volatile("fence.mbarrier_init.release.cluster;" ::: "memory");
    if (EN_ATT) {
      mbar_expect_tx(BAR(BR_FULL), W_SLOT + 16384);
      tma4d(sb, mwp, BAR(BR_FULL), 0, 0, mcol, 0);
      tma2d(sb + OFF_X, &prm.m[M_X], BAR(BR_FULL), 0, r * 128);
      tma3d(sb + 12288, &prm.m[M_WR], BAR(BR_FULL), rcol, 0, 0);
      mbar_expect_tx(BAR(BR_FULL + 1), W_SLOT);
      tma4d(sb + W_SLOT, mwp, BAR(BR_FULL + 1), 0, 32, mcol, 0);
      tma3d(sb + W_SLOT + 12288, &prm.m[M_WR], BAR(BR_FULL + 1), rcol, 32, 0);
      TS(24);
    }
  }
  if (warp == 13 && elect_one()) {
    asm volatile("prefetch.tensormap [%0];" :: "l"(&prm.m[M_X]) : "memory");
    asm volatile("prefetch.tensormap [%0];" :: "l"(&prm.m[M_WR]) : "memory");
  }
  if (wg == 3) {
    asm volatile("setmaxnreg.dec.sync.aligned.u32 56;");
    const int tid = rtid(), lane = tid & 31;
    if (warp == 12) {
      asm volatile("bar.arrive 0, 512;" ::: "memory");
      if (EN_ATT && elect_one()) {
        #pragma unroll
        for (int kb = 2; kb < 5; kb++) {
          mbar_expect_tx(BAR(BR_FULL + kb), (kb & 1) ? W_SLOT : W_SLOT + 16384);
          if (!(kb & 1)) tma2d(sb + OFF_X + kb * 8192, &prm.m[M_X], BAR(BR_FULL + kb), kb * 32, r * 128);
          tma4d(sb + kb * W_SLOT, mwp, BAR(BR_FULL + kb), 0, kb * 32, mcol, 0);
          tma3d(sb + kb * W_SLOT + 12288, &prm.m[M_WR], BAR(BR_FULL + kb), rcol, kb * 32, 0);
        }
      }
      bar_sync(6, 128);
      if (elect_one()) {
        if (EN_SSM) { mbar_expect_tx(BAR(BR_UIN), 20480); tma2d(sb + OFF_UT, &prm.m[M_U], BAR(BR_UIN), c * 80, r * 128); }
        if (EN_ATT) {
          uint32_t st = sb, fb = BAR(BR_FULL), ph = 0, xs = sb + OFF_X;
          #pragma unroll 1
          for (int k = 160; k < 640; k += 32) {
            mbar_wait(fb + 8 * (BR_EMPTY - BR_FULL), ph);
            mbar_expect_tx(fb, (k & 32) ? W_SLOT : W_SLOT + 16384);
            tma4d(st, mwp, fb, 0, k, mcol, 0);
            if (!(k & 32)) { tma2d(xs, &prm.m[M_X], fb, k, r * 128); xs += 16384; if (xs == sb + OFF_BAR) xs = sb + OFF_X; }
            tma3d(st + 12288, &prm.m[M_WR], fb, rcol, k, 0);
            st += W_SLOT; fb += 8;
            if (st == sb + OFF_X) { st = sb; fb = BAR(BR_FULL); ph ^= 1; }
          }
          asm volatile("cp.async.bulk.prefetch.L2.global [%0], 6400;" :: "l"(prm.wo + cta * 3200) : "memory");
        }
      }
      __syncwarp();
      if (EN_ATT) {
      mbar_wait(BAR(BR_EPOCH), 0);
      const unsigned epoch = lds32(sb + OFF_EPOCH);
      const unsigned* fo = FLAG(3, r, lane & 7);
      unsigned seen = __ballot_sync(0xffffffff, ld_rlx(lane < 16 ? fo : FLAG(0, lane & 15, c)) == epoch);
      mbar_wait(BAR(BR_GEMM), 0);
      if (elect_one()) {
        mbar_expect_tx(BAR(BR_WO), 8 * 10240);
        mbar_expect_tx(BAR(BR_KVP), 61440);
        mbar_expect_tx(BAR(BR_WOR), 20480);
        #pragma unroll 1
        for (int i = 0; i < 4; i++) tma2d(sb + OFF_WOR + i * 5120, &prm.m[M_WOR], BAR(BR_WOR), 512 + c * 16, i * 160);
      }
      mbar_wait(BAR(BR_PUB), 0);
      if ((seen >> 16) != 0xffffu) poll_all(FLAG(0, lane & 15, c), epoch);
      if (elect_one()) { TS(23); bulk_ld(sb + OFF_KVP, &g_kvp[c * 16 * 240], 61440, BAR(BR_KVP)); }
      mbar_wait(BAR(BR_OSTG), 0);
      if (elect_one()) {
        bulk_st(&g_o[cta * 1280], sb + OFF_EXTRA, 20480);
        bulk_commit();
        bulk_wait0();
        st_rlx(FLAG(3, r, c), epoch);
        mbar_arrive(BAR(BR_OEMPTY));
        TS(20);
        #pragma unroll 1
        for (int i = 0; i < 8; i++) tma2d(sb + i * 10240, &prm.m[M_WO], BAR(BR_WO), c * 64, CHUNK(i) * 80);
      }
      __syncwarp();
      #pragma unroll 1
      for (int i = 1; i < 8; i++) {
        const int src = CHUNK(i);
        if (!((seen >> src) & 1)) seen = poll_bit(fo, epoch, 1u << src);
        if (i > 5) mbar_wait(BAR(BR_OEMPTY - 5) + 8 * i, 0);
        else if (EN_SSM && i != 2 && i != 3) mbar_wait(i == 1 ? BAR(BR_KS + 1) : BAR(BR_FREE - 4) + 8 * i, 0);
        if (elect_one()) {
          mbar_expect_tx(BAR(BR_OFULL) + 8 * i, 20480);
          bulk_ld(sb + SLOT(i), &g_o[(r * 8 + src) * 1280], 20480, BAR(BR_OFULL) + 8 * i);
          if (i == 1) TS(21);
          if (i == 7) TS(22);
        }
        __syncwarp();
      }
      if (lane == 0) { DUMP(20, 30); }
      }
    } else {
      const int hw = warp - 13, ht = tid - 416;
      if (hw == 2 && elect_one()) {
        #pragma unroll
        for (int i = 5; i < BR_COUNT; i++) mbar_init(BAR(i), i == BR_WOR ? 1 : i == BR_GEMM ? 8 : i == BR_OEMPTY ? 9 : i < BR_EMPTY ? 1 : i < BR_OEMPTY ? 2 : i < BR_Y ? 8 : i < BR_DRDY ? 4 : 3);
        asm volatile("fence.mbarrier_init.release.cluster;" ::: "memory");
      }
      __syncwarp();
      asm volatile("bar.arrive 0, 512;" ::: "memory");
      if (EN_SSM && hw == 2) asm volatile("bar.arrive 8, 160;" ::: "memory");
      const unsigned epoch = hw == 0 ? ld_rlx(&g_epoch[cta]) + 1 : 0;
      bar_sync(5, 96);
      asm volatile("bar.arrive 6, 128;" ::: "memory");
      if (hw == 1 && elect_one()) {
        #pragma unroll
        for (int i = M_U; i < M_COUNT; i++) asm volatile("prefetch.tensormap [%0];" :: "l"(&prm.m[i]) : "memory");
      }
      if (ht == 0) {
        st_rlx(&g_epoch[cta], epoch);
        sts32(sb + OFF_EPOCH, epoch);
        mbar_arrive(BAR(BR_EPOCH));
      }
      if (EN_SSM) {
      const int mi = lane >> 3, rw = lane & 7, ch0 = c * 80 + r * 5;
      const bool early_u = hw == 0 && __all_sync(0xffffffff, ld_acq(FLAG(1, lane & 15, c)) == epoch);
      mbar_wait(BAR(BR_UIN), 0);
      if (ht == 0) TS(36);
      #pragma unroll 1
      for (int h = 0; h < 2; h++) {
        const uint32_t sa = sb + OFF_UT + h * 10240 + (8 * mi + rw) * 160 + hw * 16, da = sb + OFF_UT + h * 10240 + (hw * 8 + rw) * 128 + ((mi ^ rw ^ h) << 4);
        uint32_t v[8][4];
        #pragma unroll
        for (int q = 0; q < 8; q++) if (q < 6 || hw == 0) ldsm4t(v[q], sa + (q & 1) * 5120 + (q >> 1) * 48);
        bar_sync(5, 96);
        #pragma unroll
        for (int q = 0; q < 8; q++) if (q < 6 || hw == 0) stsm4((da ^ ((q & 1) * 64)) + (q >> 1) * 3072, v[q][0], v[q][1], v[q][2], v[q][3]);
      }
      fence_async();
      bar_sync(5, 96);
      if (hw == 0) {
        if (elect_one()) {
          tma2d_st(&prm.m[M_SA], sb + OFF_UT, r * 128, c * 80);
          tma2d_st(&prm.m[M_SA], sb + OFF_UT + 10240, r * 128 + 64, c * 80);
          bulk_commit(); bulk_wait0_read();
          mbar_arrive(BAR(BR_UOUT));
          TS(37);
          bulk_wait0();
          st_rel(FLAG(1, r, c), epoch);
          TS(30);
        }
        __syncwarp();
        if (!early_u) poll_all_acq(FLAG(1, lane & 15, c), epoch);
      }
      #pragma unroll 1
      for (int k = 0; k < 5; k++) {
        if (k == 0 || k == 3) {
          const int p = k != 0;
          if (hw == 0) {
            if (!p) {
              if (elect_one()) {
                fence_async_g();
                mbar_expect_tx(BAR(BR_U), 12288);
                #pragma unroll 1
                for (int q = 0; q < 3; q++) bulk_ld(sb + OFF_BLK + q * q * BLK, g_uy + (ch0 + q * q) * 2048, 4096, BAR(BR_U));
                TS(31);
              }
              __syncwarp();
            }
            mbar_wait(BAR(p ? BR_U2 : BR_U), 0);
          }
          bar_sync(5, 96);
        }
        const int l3 = (hw + k) % 3 * 32 + lane;
        const uint32_t blk = sb + OFF_BLK + ((0x32410 >> (4 * k)) & 7) * BLK, o = blk + B_D + l3 * 16;
        float P[34];
        P[0] = 0.f;
        #pragma unroll
        for (int q = 0; q < 5; q++) {
          const int ch = 2 * l3 - 3 + q;
          uint32_t v[4];
          lds128(v, blk + (uint32_t)((ch * 16) ^ ((ch * 2) & 0x10)));
          #pragma unroll
          for (int e = 0; e < 8; e++) {
            const int i = 8 * q + e - 4;
            if (i >= 0 && i < 33) P[i + 1] = P[i] + ((e & 1) ? bf_hi(v[e >> 1]) : bf_lo(v[e >> 1]));
          }
        }
#define WIN(lo, hi, e) (P[21 + (e) - (lo)] - P[20 + (e) - (hi)])
#define WIN8(lo, hi, b) pack2(WIN(lo, hi, b), WIN(lo, hi, b + 1)), pack2(WIN(lo, hi, b + 2), WIN(lo, hi, b + 3)), pack2(WIN(lo, hi, b + 4), WIN(lo, hi, b + 5)), pack2(WIN(lo, hi, b + 6), WIN(lo, hi, b + 7))
        if (l3 < 64) {
          sts128(o + B_D9, WIN8(12, 20, 0)); sts128(o + B_D9 + 1024, WIN8(12, 20, 8));
          sts128(o + B_D7, WIN8(5, 11, 0)); sts128(o + B_D7 + 1024, WIN8(5, 11, 8));
        }
        sts128(o + B_D5, WIN8(6, 10, 0)); sts128(o + B_D5 + 1552, WIN8(6, 10, 8));
        sts128(o, WIN8(3, 5, 0)); sts128(o + 1552, WIN8(3, 5, 8));
        if (l3 < 2) sts128(blk + B_D + l3 * B_D5 + 1536, 0, 0, 0, 0);
      }
      __syncwarp();
      if (lane == 0) mbar_arrive(BAR(BR_DRDY));
      if (ht == 0) TS(32);
      if (hw == 0) {
        const bool early = __all_sync(0xffffffff, ld_rlx(FLAG(2, lane & 15, c)) == epoch);
        #pragma unroll 1
        for (int p = 0; p < 2; p++) {
          mbar_wait(BAR(BR_Y) + 8 * p, 0);
          if (elect_one()) {
            bulk_st(g_uy + (640 + ch0 + 4 * p) * 2048, sb + OFF_BLK + (3 + p) * BLK, p ? 4096 : 16384);
            bulk_commit(); bulk_wait0_read();
            mbar_arrive(BAR(BR_FREE) + 8 * p);
          }
          __syncwarp();
        }
        if (elect_one()) { bulk_wait0(); st_rlx(FLAG(2, r, c), epoch); TS(33); }
        __syncwarp();
        if (!early) poll_all(FLAG(2, lane & 15, c), epoch);
        if (EN_ATT) mbar_wait(BAR(BR_OEMPTY), 0);
        #pragma unroll 1
        for (int n = 0; n < 64; n++) {
          if (elect_one()) {
            mbar_expect_tx(BAR(BR_YIN), 20480);
            tma2d(sb + OFF_EXTRA, &prm.m[M_SA], BAR(BR_YIN), r * 128, 640 + c * 80);
            tma2d(sb + OFF_EXTRA + 10240, &prm.m[M_SA], BAR(BR_YIN), r * 128 + 64, 640 + c * 80);
            TS(34);
          }
          __syncwarp();
          if (EN_ATT) mbar_wait(BAR(BR_OEMPTY + 3), 0);
          mbar_wait(BAR(BR_YIN), n & 1);
          if (lane == 0) TS(38);
          if (!y_transpose(sb, 4, lane, (epoch & 1u) * 0x10001u)) break;
          FIXCNT
        }
      if (elect_one()) {
        TS(39);
        tma2d_st(&prm.m[M_OUT], sb + SLOT(3), c * 80, r * 128);
        bulk_commit(); bulk_wait0_read();
        TS(35); DUMP(30, 40); DUMP(0, 1);
      }
      }
      }
    }
  } else {
  if (wg < 2) {
    asm volatile("setmaxnreg.inc.sync.aligned.u32 160;");
    bar_sync(0, 512);
    if (EN_ATT) {
    float am[96], ar[24];
    {
      const bool lead = (rtid() & 127) == 0;
      constexpr uint64_t dr0 = mkdesc(SB0 + 12288, 1024, 256, 3);
      const uint64_t dbc = sw64 ? mkdesc(SB0, 2048, 512, 2) : mkdesc(SB0, 4096, 1024, 1);
      const uint32_t kst = __shfl_sync(0xffffffff, sw64 ? 64 : 128, 0), bh = __shfl_sync(0xffffffff, (uint32_t)(dbc >> 32), 0);
      const uint64_t db0 = desc2(__shfl_sync(0xffffffff, (uint32_t)dbc, 0), bh);
      uint32_t ph = 0;
      const int ln = rtid() & 31;
      const uint32_t xa = sb + OFF_X + (warp * 16 + (ln & 15)) * 128 + (((ln >> 4) ^ (ln & 7)) << 4);
      uint32_t A[8];
      mbar_wait(BAR(BR_FULL), 0);
      if (lead && wg == 0) TS(1);
      ldsm4(A, xa); ldsm4(A + 4, xa ^ 32);
      wg_fence();
      wg_rs48_tb(ar, A, dr0, 0); wg_rs192_tb(am, A, db0, 0);
      wg_commit();
      uint32_t wp = 0, fb = BAR(BR_FULL), xk = xa;
      #pragma unroll 1
      for (int kb = 1; kb < 20; kb++) {
        const uint64_t d0 = desc2((uint32_t)dr0 + wp + 32, dr0 >> 32), d1 = desc2((uint32_t)db0 + wp + kst, bh);
        const uint32_t eb = fb + 8 * (BR_EMPTY - BR_FULL);
        wp += W_SLOT >> 4; fb += 8;
        if (wp == 5 * (W_SLOT >> 4)) { wp = 0; fb = BAR(BR_FULL); ph ^= 1; }
        wg_fence();
        wg_rs48_tb(ar, A + 4, d0, 1);
        wg_rs192_tb(am, A + 4, d1, 1);
        wg_commit();
        xk ^= 64;
        if (!(kb & 1)) { xk += 16384; if (xk >= sb + OFF_BAR) xk -= 49152; }
        mbar_wait(fb, ph);
        wg_wait<1>();
        ldsm4(A, xk);
        wg_fence();
        wg_rs48_tb(ar, A, desc2((uint32_t)dr0 + wp, dr0 >> 32), 1);
        wg_rs192_tb(am, A, desc2((uint32_t)db0 + wp, bh), 1);
        wg_commit();
        wg_wait<1>();
        ldsm4(A + 4, xk ^ 32);
        if (lead && kb < 16) mbar_arrive(eb);
      }
      wg_fence();
      wg_rs48_tb(ar, A + 4, dr0 + 4 * (W_SLOT >> 4) + 32, 1);
      wg_rs192_tb(am, A + 4, desc2((uint32_t)db0 + 4 * (W_SLOT >> 4) + kst, bh), 1);
      wg_commit();
      wg_wait<0>();
      if (ln == 0) mbar_arrive(BAR(BR_GEMM));
      pin<96>(am); pin<24>(ar);
    }
    const int tid = rtid(), lane = tid & 31, tq = lane & 3;
    if (tid == 0) TS(2);
#define QV(j, e) ((j) < 8 ? am[4 * (j) + (e)] : ar[4 * ((j) - 8) + (e)])
#define KV_(j, e) ((j) < 8 ? am[32 + 4 * (j) + (e)] : ar[8 + 4 * ((j) - 8) + (e)])
#define VV(j, e) ((j) < 8 ? am[64 + 4 * (j) + (e)] : ar[16 + 4 * ((j) - 8) + (e)])
    {
      bar_sync(1, 256);
      const uint32_t ro = sb + (uint32_t)((warp * 16 + (lane & 15)) * 16);
      const int l0 = 2 * (c & 1) + (lane >> 4);
      const uint32_t ones = (tq == 0) ? 0x00003f80u : 0u;
#define PV(j) pack2(VV(j, 0), VV(j, 1)), pack2(VV(j, 2), VV(j, 3))
#define PK(j) pack2(phi(KV_(j, 0)), phi(KV_(j, 1))), pack2(phi(KV_(j, 2)), phi(KV_(j, 3)))
      stsm4(ro + OFF_V + (5 + 6 * (lane >> 4)) * 2048, ones, ones, ones, ones);
      #pragma unroll
      for (int j = 0; j < 10; j += 2) {
        const int l = (j == 8 && (c & 1)) ? l0 - 2 : l0 + j;
        stsm4(ro + OFF_V + (l + (l >= 5)) * 2048, PV(j), PV(j + 1));
        stsm4(ro + OFF_PK + l * 2048, PK(j), PK(j + 1));
      }
    }
    fence_async();
    bar_sync(1, 256);
    if (tid == 0) TS(3);
    mbar_wait(BAR(BR_EPOCH), 0);
    const unsigned epoch = lds32(sb + OFF_EPOCH);
    {
      float kv[24]; zero<24>(kv);
      constexpr uint64_t da = mkdesc(SB0 + OFF_PK, 128, 2048, 0), db = mkdesc(SB0 + OFF_V, 128, 2048, 0);
      wg_fence();
      #pragma unroll
      for (int s = 0; s < 8; s++) wg_ss48_tt(kv, desc2((uint32_t)da + wg * 640 + s * 16, da >> 32), desc2((uint32_t)db + wg * 768 + s * 16, db >> 32), s != 0);
      wg_commit();
      wg_wait<0>();
      pin<24>(kv);
      if (tid == 0) TS(15);
      if (w4 < 3) {
        const uint32_t wb = sb + OFF_KVS + (wg * 3 + w4) * 1536 + (lane & 15) * 96;
        #pragma unroll
        for (int j = 0; j < 6; j += 2)
          stsm4(wb + (j + (lane >> 4)) * 16, pack2(kv[4 * j], kv[4 * j + 1]), pack2(kv[4 * j + 2], kv[4 * j + 3]),
                pack2(kv[4 * j + 4], kv[4 * j + 5]), pack2(kv[4 * j + 6], kv[4 * j + 7]));
        __syncwarp();
        const int dl = w4 * 16 + (lane & 15), hl = dl >= 20;
        uint32_t v[4], z[4];
        lds128(v, wb + (3 * hl + (lane >> 4)) * 16);
        lds64(z, wb + 32 + 8 * hl); z[2] = lds32(wb + 80); z[3] = epoch & 1u;
        if (dl < 40) {
          uint4* dst = &g_kvp[(c * 16 + r) * 240 + wg * 40 + dl];
          v[3] = (v[3] & ~1u) | z[3];
          st128_rlx(dst + (lane >> 4) * 80, v);
          if (lane < 16) st128_rlx(dst + 160, z);
        }
      }
    }
    bar_sync(1, 256);
    if (tid == 0) { st_rlx(FLAG(0, r, c), epoch); mbar_arrive(BAR(BR_PUB)); TS(4); }
    const int kvi = (tid >= 80) + (tid >= 160) + (tid >= 240), kd = tid - 80 * kvi;
    const int khd = kd / 20, kt0 = 5 * (khd >> 1) + 2 * (khd & 1);
    const uint32_t rb = sb + OFF_KVB + kd * 16;
    if (kvi < 3) {
      #pragma unroll 1
      for (int m = kvi; m < 7; m += 3) { const int q = kt0 + 3 + m; sts128(rb + (q >= 10 ? q - 10 : q) * 1280, 0, 0, 0, 0); }
    }
    uint32_t qa[20];
    {
      const float sc = 1.44269504089f + __uint_as_float(lds32(sb + OFF_EPOCH) ^ epoch);
      #pragma unroll
      for (int j = 0; j < 10; j++) { qa[2 * j] = pack2(phi(QV(j, 0), sc), phi(QV(j, 1), sc)); qa[2 * j + 1] = pack2(phi(QV(j, 2), sc), phi(QV(j, 3), sc)); }
    }
    if (tid == 0) TS(5);
    if (warp == 7) mbar_wait(BAR(BR_KVP), 0);
    bar_sync(1, 256);
    if (tid == 0) TS(6);
    if (kvi < 3) {
      float s[8];
      zero<8>(s);
      uint32_t bad = 0;
      #pragma unroll 4
      for (int i = 0; i < 16; i += 2) {
        uint32_t w[4], x[4];
        lds128(w, sb + OFF_KVP + tid * 16 + i * 3840); lds128(x, sb + OFF_KVP + tid * 16 + i * 3840 + 3840);
        bad |= (w[3] ^ epoch) | (x[3] ^ epoch);
        #pragma unroll
        for (int e = 0; e < 4; e++) {
          asm("add.rn.bf16x2 %0, %0, %1;" : "+r"(w[e]) : "r"(x[e]));
          s[2 * e] += bf_lo(w[e]); s[2 * e + 1] += bf_hi(w[e]);
        }
      }
      if (__builtin_expect(bad & 1u, 0)) {
        zero<8>(s);
        #pragma unroll 1
        for (int i = 0; i < 16; i++) {
          uint32_t w[4] = {0, 0, 0, ~epoch};
          fix128_w3(w, &g_kvp[(c * 16 + i) * 240 + tid], epoch, 1u);
          #pragma unroll
          for (int e = 0; e < 4; e++) { s[2 * e] += bf_lo(w[e]); s[2 * e + 1] += bf_hi(w[e]); }
        }
        FIXCNT
      }
      const uint32_t p0 = pack2(s[0], s[1]), p1 = pack2(s[2], s[3]), p2 = pack2(s[4], s[5]), p3 = pack2(s[6], s[7]);
      if (kvi < 2) sts128(rb + (kt0 + (khd & 1) + kvi) * 1280, p0, p1, p2, p3);
      else {
        const bool od = khd & 1;
        sts128(rb + (5 * (khd >> 1) + 2) * 1280, od ? 0u : p0, od ? 0u : p1, od ? p0 : 0u, od ? p1 : 0u);
        const uint32_t zz = (p2 & 0xffffu) << (16 * (khd & 1));
        sts128(rb + 10 * 1280, khd < 2 ? zz : 0u, khd < 2 ? 0u : zz, 0u, 0u);
      }
    }
    fence_async();
    bar_sync(1, 256);
    if (tid == 0) TS(7);
    {
      float oa[44]; zero<44>(oa);
      constexpr uint64_t db = mkdesc(SB0 + OFF_KVB, 128, 1280, 0);
      wg_fence();
      #pragma unroll
      for (int s = 0; s < 5; s++) wg_rs88_tb(oa, &qa[4 * s], desc2((uint32_t)db + ((s == 4 && (c & 1)) ? 0 : (s + (c & 1)) * 16), db >> 32), s != 0);
      wg_commit();
      wg_wait<0>();
      pin<44>(oa);
      if (tid == 0) TS(13);
      float rc[4], rd[2][4];
      #pragma unroll
      for (int e = 0; e < 4; e++) asm("rcp.approx.ftz.f32 %0, %1;" : "=f"(rc[e]) : "f"(oa[40 + e] + 1e-6f));
      #pragma unroll
      for (int h = 0; h < 4; h++) {
        rd[0][h] = __shfl_sync(0xffffffff, rc[h & 1], (lane & 28) | (h >> 1));
        rd[1][h] = __shfl_sync(0xffffffff, rc[2 + (h & 1)], (lane & 28) | (h >> 1));
      }
      #pragma unroll
      for (int j = 0; j < 10; j++) {
        #pragma unroll
        for (int h = 0; h < 2; h++) {
          float f;
          if (j == 2) f = tq < 2 ? rd[h][0] : rd[h][1];
          else if (j == 7) f = tq < 2 ? rd[h][2] : rd[h][3];
          else f = rd[h][(8 * j) / 20];
          qa[2 * j + h] = pack2(oa[4 * j + 2 * h] * f, oa[4 * j + 2 * h + 1] * f);
        }
      }
      const uint32_t m0 = (lane & 7) == ((2 * w4) & 7), m1 = (lane & 7) == 2 * w4 + 1;
      const uint32_t oa_ = sb + OFF_EXTRA + (lane >> 4) * 2048 + (warp * 16 + (lane & 15)) * 16;
      bar_sync(1, 256);
#define TAG(v, m) (((v) & ~(m)) | (epoch & (m)))
      #pragma unroll
      for (int s = 0; s < 5; s++) stsm4(oa_ + s * 4096, TAG(qa[4 * s], m0), TAG(qa[4 * s + 1], m1), TAG(qa[4 * s + 2], m0), TAG(qa[4 * s + 3], m1));
    }
    fence_async();
    __syncwarp();
    if (lane == 0) mbar_arrive(BAR(BR_OSTG));
    if (tid == 0) TS(8);
    }
    asm volatile("setmaxnreg.dec.sync.aligned.u32 136;");
  } else {
    const int g = lane >> 2, tq = lane & 3, t7 = tid & 127;
    asm volatile("bar.arrive 0, 512;" ::: "memory");
    if (EN_SSM) {
    {
      #pragma unroll 1
      for (int k = 0; k < 4; k++) {
        const uint32_t z = sb + OFF_BLK + k * BLK + t7 * 16;
        sts128(z + B_TBL, 0, 0, 0, 0); sts128(z + B_TBL + 2048, 0, 0, 0, 0);
      }
      if (t7 < 80) sts128(sb + OFF_BLK + (t7 >> 4) * BLK - 256 + (t7 & 15) * 16, 0, 0, 0, 0);
      const uint32_t ea = sb + OFF_BLK + (2 + (w4 & 1)) * BLK + (lane >> 4) * 7168 + ((lane >> 3) & 1) * 256 + (lane & 7) * 16 + (w4 >> 1) * 2048;
      constexpr uint64_t dE = mkdesc(SB0 + OFF_BLK + 2 * BLK, 128, 512, 0);
      const uint32_t xa = sb + OFF_BLK + 18560 + t7 * 8, xr_ = sb + OFF_BLK + 18560 + (t7 ^ 64) * 8;
      uint32_t pr[5][2];
      #pragma unroll
      for (int q = 0; q < 5; q++) {
        #pragma unroll
        for (int e = 0; e < 2; e++) pr[q][e] = __byte_perm(raw[q][e], __shfl_xor_sync(0xffffffff, raw[q][e], 1), (lane & 1) ? 0x3276 : 0x5410);
        const uint32_t m = __reduce_max_sync(0xffffffff, max(raw[q][1] & 0x7fffu, (raw[q][1] >> 16) & 0x7fffu));
        if (lane == 0) sts32(sb + OFF_EPOCH + 64 + q * 16 + w4 * 4, m);
      }
      bar_sync(4, 128);
      if (t7 == 0) TS(40);
      const int j = (w4 & 1) * 16 + (w4 >> 1) * 8 + g, i2 = tq < 2 ? 64 * tq + j : 32 * (tq - 2) + j;
      const uint32_t e2 = B_TBL + 4 * (tq < 2 ? T_F3 + (((i2 - 1) & 1) ? 80 : 0) + ((i2 - 1) >> 1) + 16 : T_F2 + (i2 & 1) * 96 + (i2 >> 1));
      const uint32_t e1 = tq < 2 ? (i2 ? e2 - 64 : B_TBL + 4 * (T_F2 + 175)) : B_TBL + 4 * (i2 ? T_F2 + ((2 * i2 - 1) & 3) * 48 + ((2 * i2 - 1) >> 2) : 16 + 511);
      const uint32_t e0 = B_TBL + (16 + 8 * j + 2 * tq) * 4;
      const float dtl = bf_round(expf(bf_lo(pd)));
      float hd[9];
      auto head = [&](int q) {
        const uint32_t pa0 = pr[0][0], pc0 = pr[0][1];
        const float dt = __shfl_sync(0xffffffff, dtl, q);
        #pragma unroll
        for (int e = 0; e < 2; e++) { pr[0][e] = pr[1][e]; pr[1][e] = pr[2][e]; pr[2][e] = pr[3][e]; pr[3][e] = pr[4][e]; }
        uint32_t mm[4];
        lds128(mm, sb + OFF_EPOCH + 64 + q * 16);
        const uint32_t ex = min(max(max(max(mm[0], mm[1]), max(mm[2], mm[3])) >> 7, 1u), 253u);
        const float sc = __uint_as_float((254u - ex) << 23);
        const float lr = -bf_round(expf(bf_lo(pa0))) * dt * 1.44269504089f;
        const float tn = bf_hi(pa0) * dt * 0.15915494309f;
        cexp_t(lr, -tn, hd[0], hd[1]);
        cexp_t(lr * 8.f, tn * 8.f, hd[2], hd[3]);
        cexp_t(lr * 64.f, tn * 64.f, hd[4], hd[5]);
        hd[6] = bf_lo(pc0) * sc; hd[7] = -bf_hi(pc0) * sc;
        hd[8] = 2.f * dt * __uint_as_float(ex << 23);
      };
      head(0);
      #pragma unroll 1
      for (int it = 0; it < 5; it++) {
        const int k = it;
        const uint32_t blk = sb + OFF_BLK + k * BLK;
        float fac = 0.f;
        float ka[24]; zero<24>(ka);
        {
          if (it == 4) {
            mbar_wait(BAR(BR_UOUT), 0);
            sts128(sb + OFF_UT + B_TBL + t7 * 16, 0, 0, 0, 0); sts128(sb + OFF_UT + B_TBL + 2048 + t7 * 16, 0, 0, 0, 0);
          }
          const uint32_t ga = ea + 4096 - (w4 >> 1) * 512;
#define PUT4(i, a, b, c_, d) sts128(((i) < 8 ? ea + ((i) >> 1) * 512 : ga + (((i) - 8) >> 1) * 512) + ((i) & 1) * 128, a, b, c_, d)
          float z2r, z2i, z4r, z4i, xr[8], xi[8], gr[8], gi[8], wr[9], wi[9];
          const float z1r = hd[0], z1i = hd[1];
          xr[1] = hd[2]; xi[1] = hd[3]; wr[0] = hd[4]; wi[0] = hd[5];
          fac = hd[8];
          xr[0] = 1.f; xi[0] = 0.f;
          csq(xr[1], xi[1], xr[2], xi[2]); cmul(xr[2], xi[2], xr[1], xi[1], xr[3], xi[3]);
          csq(xr[2], xi[2], xr[4], xi[4]);
          #pragma unroll
          for (int b = 1; b < 4; b++) cmul(xr[4], xi[4], xr[b], xi[b], xr[4 + b], xi[4 + b]);
          csq(wr[0], wi[0], wr[1], wi[1]); cmul(wr[1], wi[1], wr[0], wi[0], wr[2], wi[2]);
          csq(wr[1], wi[1], wr[3], wi[3]); csq(wr[3], wi[3], wr[4], wi[4]);
          cmul(wr[4], wi[4], wr[3], wi[3], wr[5], wi[5]); csq(wr[4], wi[4], wr[6], wi[6]);
          cmul(wr[6], wi[6], wr[4], wi[4], wr[7], wi[7]); csq(wr[6], wi[6], wr[8], wi[8]);
          uint32_t R[4], I[4], PR[4], PI[4];
          #pragma unroll
          for (int b = 0; b < 4; b++) { R[b] = packh(xr[2 * b], xr[2 * b + 1]); I[b] = packh(xi[2 * b], xi[2 * b + 1]); }
          PUT4(0, R[0], R[1], R[2], R[3]); PUT4(1, I[0], I[1], I[2], I[3]);
          #pragma unroll
          for (int i = 0; i < 3; i++) {
            const uint32_t z = packh(wr[i], wi[i]);
            #pragma unroll
            for (int b = 0; b < 4; b++) hcm2(R[b], I[b], z, PR[b], PI[b]);
            PUT4(2 * i + 2, PR[0], PR[1], PR[2], PR[3]); PUT4(2 * i + 3, PI[0], PI[1], PI[2], PI[3]);
          }
          gr[0] = hd[6]; gi[0] = hd[7];
          csq(z1r, z1i, z2r, z2i); csq(z2r, z2i, z4r, z4i);
          cmul(gr[0], gi[0], z1r, z1i, gr[1], gi[1]);
          cmul(gr[0], gi[0], z2r, z2i, gr[2], gi[2]); cmul(gr[1], gi[1], z2r, z2i, gr[3], gi[3]);
          #pragma unroll
          for (int b = 0; b < 4; b++) cmul(gr[b], gi[b], z4r, z4i, gr[4 + b], gi[4 + b]);
          PUT4(8, packh(gr[0], gr[1]), packh(gr[2], gr[3]), packh(gr[4], gr[5]), packh(gr[6], gr[7]));
          PUT4(9, packh(gi[0], gi[1]), packh(gi[2], gi[3]), packh(gi[4], gi[5]), packh(gi[6], gi[7]));
          {
            const uint32_t z = packh(wr[3], wi[3]), a4r = packh(gr[0], gr[4]), a4i = packh(gi[0], gi[4]);
            hcm2c(packh(gr[0], gr[2]), packh(gi[0], gi[2]), z, PR[0], PI[0]);
            hcm2c(packh(gr[4], gr[6]), packh(gi[4], gi[6]), z, PR[1], PI[1]);
            hcm2c(a4r, a4i, packh(wr[4], wi[4]), PR[2], PI[2]);
            hcm2c(a4r, a4i, packh(wr[5], wi[5]), PR[3], PI[3]);
            PUT4(10, PR[0], PR[1], PR[2], PR[3]); PUT4(11, PI[0], PI[1], PI[2], PI[3]);
            float hr, hi_;
            cmul(gr[0], gi[0], wr[3], -wi[3], hr, hi_);
            const uint32_t cr = packh(gr[0], hr), ci = packh(gi[0], hi_);
            #pragma unroll
            for (int i = 0; i < 3; i++) hcm2c(cr, ci, packh(wr[6 + i], wi[6 + i]), PR[i], PI[i]);
            PUT4(12, PR[0], PR[1], PR[2], 0u); PUT4(13, PI[0], PI[1], PI[2], 0u);
          }
          fence_async();
          bar_sync(4, 128);
          wg_fence();
          #pragma unroll
          for (int s = 0; s < 8; s++) {
            const uint64_t d = dE + (s >> 2) * (BLK >> 4) + ((s >> 1) & 1) * 448 + (s & 1) * 16;
            wg_ss48_tt_h(ka, d, d + 256, s != 0);
          }
          wg_commit();
        }
        const float dsk = bf_lo(__shfl_sync(0xffffffff, pd, 8 + (it & 7)));
        head(min(it + 1, 4));
        pin<9>(hd);
        wg_wait<0>();
        pin<24>(ka);
        float kk[6];
        const bool up = w4 >= 2;
        #pragma unroll
        for (int n = 0; n < 3; n++) {
          sts64f(xa + n * BLK, up ? ka[12 + 4 * n] : ka[4 * n + 2], up ? ka[13 + 4 * n] : ka[4 * n + 3]);
          kk[2 * n] = up ? ka[14 + 4 * n] : ka[4 * n]; kk[2 * n + 1] = up ? ka[15 + 4 * n] : ka[4 * n + 1];
        }
        if (it) bar_sync(4, 128); else bar_sync(8, 160);
          if (it == 4 && w4 == 0) {
            mbar_wait(BAR(BR_U), 0);
            if (elect_one()) {
              mbar_expect_tx(BAR(BR_U2), 8192);
              bulk_ld(blk - 2 * BLK, g_uy + (c * 80 + r * 5 + 2) * 2048, 4096, BAR(BR_U2)); bulk_ld(blk - BLK, g_uy + (c * 80 + r * 5 + 3) * 2048, 4096, BAR(BR_U2));
            }
            __syncwarp();
          }
        #pragma unroll
        for (int n = 0; n < 3; n++) {
          uint32_t o[2]; lds64(o, xr_ + n * BLK);
          kk[2 * n] = (kk[2 * n] + __uint_as_float(o[0])) * fac; kk[2 * n + 1] = (kk[2 * n + 1] + __uint_as_float(o[1])) * fac;
        }
        if (t7 == 0) kk[0] += dsk;
        {
          const uint32_t v = pack2(kk[1], kk[0]), vh = v >> 16;
          const uint32_t u = pack2(kk[2], kk[3]), w = pack2(kk[4], kk[5]), uu = pack2(kk[2], kk[2]), us = pack2(kk[3], kk[2]);
          const uint32_t x = tq < 2 ? w : u, xh = x >> 16;
          sts32(blk + e0 + 4, v); sts16(blk + e0, vh); sts16(blk + e0 + 10, v);
          sts16(blk + e1, x); sts16(blk + e1 + 6, x); sts16(blk + e2, xh); sts16(blk + e2 + 6, xh);
          if (tq < 2) {
            const uint32_t pb = blk + e0 + 1024 + 8 * tq;
            sts32(pb + 4, uu); sts32(pb + 8, us); sts16(pb + 14, us);
            if (i2) { sts16(pb - 4, u); sts32(pb, uu); }
          }
          if (i2 == 0) {
            const uint32_t tb = blk + B_TBL;
            if (tq == 0) { sts16(tb + (16 + 256) * 4, u); sts16(tb + (T_S + 3) * 4, w); sts32(tb + (T_S + 4) * 4, pack2(kk[4], kk[4])); sts16(tb + (T_S + 5) * 4 + 2, w); }
            else { sts32(tb + 528 * 4, uu); sts32(tb + 529 * 4, uu); sts32(tb + 530 * 4, uu); sts16(tb + 531 * 4 + 2, u); sts16(tb + (T_F3 + 80 + 63) * 4, w); }
          }
        }
        if (t7 == 0) TS(49 + it);
      }
    }
    asm volatile("setmaxnreg.inc.sync.aligned.u32 136;");
    if (t7 == 0) TS(41);
    bar_sync(4, 128);
    if (t7 == 0) mbar_arrive(BAR(BR_KS));
    }
  }
  const int tid = rtid(), lane = tid & 31, g = lane >> 2, tq = lane & 3, t7 = tid & 127;
  mbar_wait(BAR(BR_EPOCH), 0);
  const unsigned epoch = lds32(sb + OFF_EPOCH);
  const uint32_t ytag = (epoch & 1u) * 0x10001u, ym = lane < 4 ? 0x10001u : 0u;
  if (EN_ATT && wg == 1) {
    uint32_t v[10][4];
    mbar_wait(BAR(BR_WOR), 0);
    #pragma unroll
    for (int q = 0; q < 10; q++) lds128(v[q], sb + OFF_WOR + CHUNK(2 * w4 + q / 5) * 2560 + (q % 5) * 512 + lane * 16);
    bar_sync(3, 128);
    #pragma unroll
    for (int q = 0; q < 10; q++) sts128(sb + OFF_WOR + (q * 16 + (lane >> 1)) * 128 + (((2 * w4 + (lane & 1)) ^ ((lane >> 1) & 7)) << 4), v[q][0], v[q][1], v[q][2], v[q][3]);
    fence_async();
  }
  if (EN_SSM && wg != 1) {
    mbar_wait(BAR(BR_KS), 0);
    mbar_wait(BAR(BR_U), 0);
    if (EN_ATT) mbar_wait(BAR(BR_GEMM), 0);
    if (tid == 256) TS(42);
    {
      const int pass = wg >> 1;
      const int k = pass ? w4 : 4;
      if (k & 2) mbar_wait(BAR(BR_U2), 0);
      const uint32_t blk = sb + OFF_BLK + k * BLK, tb = blk + B_TBL + (uint32_t)((g - 2 * tq) * 4);
      float acc[16][4];
      zero<64>(&acc[0][0]);
      const int kl = 16 * (lane >> 4) + 2 * (lane & 7) + ((lane >> 3) & 1);
      {
        auto ubase = [&](int sh) { const int q = kl - 2 * sh; return blk + (uint32_t)((q * 16) ^ ((q * 2) & 0x10)); };
#define LDQ(A, sh) _Pragma("unroll") for (int m = 0; m < 4; m++) load_quad(A[m], tb + (16 + 16 * (sh) + 128 * m) * 4);
#define LDB(B, ub, h) _Pragma("unroll") for (int p = 0; p < 4; p++) ldsm4(B[p], (ub) + (4 * (h) + p) * 512);
#define MLO(A, B) _Pragma("unroll") for (int m = 0; m < 4; m++) _Pragma("unroll") for (int cc = 0; cc < 8; cc++) mma16816(acc[cc + m], A[m], &B[cc >> 1][(cc & 1) * 2]);
#define MHI(A, B) _Pragma("unroll") for (int m = 0; m < 4; m++) _Pragma("unroll") for (int cc = 0; cc < 8 - m; cc++) mma16816(acc[8 + cc + m], A[m], &B[cc >> 1][(cc & 1) * 2]);
        int p_ = pass ? 0 : w4;
        const int pe = pass ? 4 : w4 + 1;
        uint32_t A[4][4], A2[4][4], Bl[4][4], Bh[4][4];
        uint32_t ub = ubase(p_ + 4);
        LDQ(A, p_ + 4) LDB(Bl, ub, 0)
        #pragma unroll 1
        for (; p_ < pe; p_++) {
          LDB(Bh, ub, 1)
          MLO(A, Bl)
          ub = ubase(p_);
          LDQ(A2, p_) LDB(Bl, ub, 0)
          MHI(A, Bh)
          LDB(Bh, ub, 1)
          load_quad(A[0], tb + (16 + 512 + 16 * (p_ & 1)) * 4); load_quad(A[1], tb + (T_S + 16 * (p_ & 1)) * 4);
          MLO(A2, Bl)
          if (p_ < 2) {
            #pragma unroll
            for (int cc = 0; cc < 8; cc++) mma16816(acc[cc + 4], A[0], &Bl[cc >> 1][(cc & 1) * 2]);
            #pragma unroll
            for (int cc = 0; cc < 4; cc++) mma16816(acc[cc + 12], A[0], &Bh[cc >> 1][(cc & 1) * 2]);
            #pragma unroll
            for (int cc = 0; cc < 8; cc++) mma16816(acc[cc + 8], A[1], &Bl[cc >> 1][(cc & 1) * 2]);
          }
          const int pn = ((p_ + 1) & 3) + 4;
          ub = ubase(pn);
          LDQ(A, pn) LDB(Bl, ub, 0)
          MHI(A2, Bh)
        }
      }
      if (t7 == 0) TS(pass ? 60 : 16);
      mbar_wait(BAR(BR_DRDY), 0);
      {
        const int ih = (lane >> 3) & 1;
        const uint32_t dl = blk + B_D + (uint32_t)(((lane >> 4) * 8 + (lane & 7)) * 16);
        const uint32_t d0_ = dl + ih * 1552, d8_ = dl + (ih ? 0 : 1536), d3_ = dl + B_D7 + ih * 1024;
        auto cls2 = [&](uint32_t da, uint32_t ta) {
          uint32_t B[6][2], A[6][4];
          #pragma unroll
          for (int e = 0; e < 6; e++) { B[e][0] = lds32v(ta + (e + 4) * 32); B[e][1] = lds32v(ta + (e + 3) * 32); }
          #pragma unroll
          for (int kk = 0; kk < 6; kk++) ldsm4t(A[kk], da + kk * 256);
          #pragma unroll
          for (int e = 0; e < 6; e++)
            #pragma unroll
            for (int kk = 0; kk < 6; kk++) if (2 * kk + e + 4 < 16) mma16816(acc[2 * kk + e + 4], A[kk], B[e]);
        };
        auto cls3 = [&](uint32_t da, uint32_t ta) {
          uint32_t B[8][2], A[4][4];
          #pragma unroll
          for (int e = 0; e < 8; e++) { B[e][0] = lds32v(ta + (e + 8) * 32); B[e][1] = lds32v(ta + (e + 7) * 32); }
          #pragma unroll
          for (int kk = 0; kk < 4; kk++) ldsm4t(A[kk], da + kk * 256);
          #pragma unroll
          for (int kk = 0; kk < 4; kk++)
            #pragma unroll
            for (int e = 0; e < 8; e++) if (2 * kk + e + 8 < 16) mma16816(acc[2 * kk + e + 8], A[kk], B[e]);
        };
        if (pass) {
          #pragma unroll 1
          for (int a = 0; a < 2; a++) {
            cls2(d0_ + a * B_D5, tb + (T_F2 + 48 * a - 32) * 4);
            cls2(d8_ + a * B_D5, tb + (T_F2 + 48 * a + 64) * 4);
            cls3(d3_ + a * 2048, tb + (T_F3 + 80 * a - 64) * 4);
          }
        } else {
          cls2(((w4 & 2) ? d8_ : d0_) + (w4 & 1) * B_D5, tb + (T_F2 + 48 * w4 - 32) * 4);
          if (w4 >= 2) cls3(d3_ + (w4 - 2) * 2048, tb + (T_F3 + 80 * (w4 - 2) - 64) * 4);
        }
      }
      if (t7 == 0) TS(pass ? 61 : 17);
      const uint32_t ya = (pass ? sb + OFF_BLK + 3 * BLK + w4 * 4096 : blk) + (uint32_t)((kl * 16) ^ ((kl * 2) & 0x10));
#define YTAG(v) (((v) & ~ym) | (ytag & ym))
#define STY(p) stsm4t(ya + (p) * 512, YTAG(pack2(acc[2 * (p)][0], acc[2 * (p)][1])), pack2(acc[2 * (p)][2], acc[2 * (p)][3]), \
                      YTAG(pack2(acc[2 * (p) + 1][0], acc[2 * (p) + 1][1])), pack2(acc[2 * (p) + 1][2], acc[2 * (p) + 1][3]))
      if (pass == 0) {
        const uint32_t xw = blk + 4096 + w4 * 4096 + lane * 16, xr = blk + 4096 + w4 * 1024 + lane * 16;
        #pragma unroll
        for (int h = 0; h < 2; h++) {
          bar_sync(2, 128);
          #pragma unroll
          for (int i = 0; i < 8; i++)
            sts128(xw + i * 512, __float_as_uint(acc[8 * h + i][0]), __float_as_uint(acc[8 * h + i][1]), __float_as_uint(acc[8 * h + i][2]), __float_as_uint(acc[8 * h + i][3]));
          bar_sync(2, 128);
          float y[8];
          #pragma unroll
          for (int i = 0; i < 8; i++) {
            uint32_t o[4]; lds128(o, xr + (i >> 1) * 4096 + (i & 1) * 512);
            #pragma unroll
            for (int e = 0; e < 4; e++) y[4 * (i & 1) + e] = i < 2 ? __uint_as_float(o[e]) : y[4 * (i & 1) + e] + __uint_as_float(o[e]);
          }
          stsm4t(ya + (4 * h + w4) * 512, YTAG(pack2(y[0], y[1])), pack2(y[2], y[3]), YTAG(pack2(y[4], y[5])), pack2(y[6], y[7]));
        }
      } else {
        fence_async();
        bar_sync(4, 128);
        if (t7 == 0) mbar_arrive(BAR(BR_KS + 1));
        #pragma unroll
        for (int p = 0; p < 8; p++) STY(p);
      }
      fence_async();
      __syncwarp();
      if (lane == 0) mbar_arrive(BAR(BR_Y + 1) - 8 * pass);
      if (t7 == 0) TS(pass ? 62 : 18);
    }
  }
  if (wg < 2) {
    if (EN_ATT) {
    float oc[40]; zero<40>(oc);
    {
      constexpr uint64_t dw0 = mkdesc(SB0, OFF_WOR, 1024, 1), da0 = mkdesc(SB0, 2048, 128, 0);
      const uint32_t ck = sb + tid * 32 + ((lane >> 2) << 2), ck2 = ck + (wg ? 0 : 16384);
      uint32_t bad = 0;
      auto tile = [&](int i, uint32_t so) {
        const uint32_t al = (uint32_t)da0 + wg * 64 + (so >> 4), wl = (uint32_t)dw0 + i * 640 - (i >> 1) * (1278 << 16);
        wg_fence();
        #pragma unroll
        for (int s = 0; s < 5; s++) wg_ss80_tb(oc, desc2(al + s * 256, da0 >> 32), desc2(wl + s * 128, dw0 >> 32), (i | s) != 0);
        wg_commit();
        bad |= (lds32(ck + so) ^ epoch) | (lds32(ck + so + 8192) ^ epoch) | (lds32(ck2 + so) ^ epoch);
      };
      if (w4 == 0) {
        if (EN_SSM) mbar_wait(BAR(BR_Y), 0);
        mbar_wait(BAR(BR_WO), 0);
      }
      bar_sync(1, 256);
      if (tid == 0) TS(9);
      tile(0, SLOT(0));
      #pragma unroll 1
      for (int i = 1; i < 8; i++) {
        mbar_wait(BAR(BR_OFULL) + 8 * i, 0);
        tile(i, SLOT(i));
        wg_wait<1>();
        if (lane == 0) mbar_arrive(BAR(BR_OEMPTY - 1) + 8 * i);
      }
      #pragma unroll 1
      for (int n = 0; n < 56; n++) {
        const int i = n & 7;
        if (i == 0) {
          uint32_t any;
          asm volatile("{\n.reg .pred p;\nsetp.ne.u32 p, %1, 0;\nbarrier.red.or.pred p, 1, 256, p;\nselp.u32 %0, 1, 0, p;\n}" : "=r"(any) : "r"(bad & 1u) : "memory");
          if (!any) break;
          bad = 0;
          FIXCNT
        }
        wg_wait<0>();
        bar_sync(1, 256);
        if (tid == 0) { mbar_expect_tx(BAR(BR_RETRY), 20480); bulk_ld(sb + SLOT(2), &g_o[(r * 8 + CHUNK(i)) * 1280], 20480, BAR(BR_RETRY)); }
        mbar_wait(BAR(BR_RETRY), n & 1);
        tile(i, SLOT(2));
      }
      wg_wait<0>();
      pin<40>(oc);
    }
    if (tid == 0) TS(10);
    {
      const int row = w4 * 16 + (lane & 15);
      const uint32_t ob = sb + OFF_BLK + 3 * BLK + wg * 10240;
      #pragma unroll
      for (int j = 0; j < 8; j += 2)
        stsm4(ob + row * 128 + (((j + (lane >> 4)) ^ (row & 7)) << 4), pack2(oc[4 * j], oc[4 * j + 1]), pack2(oc[4 * j + 2], oc[4 * j + 3]),
              pack2(oc[4 * j + 4], oc[4 * j + 5]), pack2(oc[4 * j + 6], oc[4 * j + 7]));
      stsm4(ob + 8192 + row * 32 + (lane >> 4) * 16, pack2(oc[32], oc[33]), pack2(oc[34], oc[35]), pack2(oc[36], oc[37]), pack2(oc[38], oc[39]));
      fence_async();
      bar_sync(2 + wg, 128);
      if (w4 == 0 && elect_one()) {
        tma2d_st(&prm.m[M_O64], ob, 640 + c * 64, r * 128 + wg * 64);
        tma2d_st(&prm.m[M_O16], ob + 8192, 1152 + c * 16, r * 128 + wg * 64);
        bulk_commit(); bulk_wait0_read();
        if (wg == 0) { TS(11); DUMP(0, 20); }
      }
    }
    }
  } else if (EN_SSM) {
    if (t7 == 0) DUMP(40, 64);
    #pragma unroll 1
    for (int n = 0; n < 64; n++) if (!y_transpose(sb, w4, lane, ytag)) break;
  }
  }
}

typedef CUresult (*EncFn)(CUtensorMap*, CUtensorMapDataType, cuuint32_t, void*, const cuuint64_t*, const cuuint64_t*, const cuuint32_t*,
                          const cuuint32_t*, CUtensorMapInterleave, CUtensorMapSwizzle, CUtensorMapL2promotion, CUtensorMapFloatOOBfill);
static void mkmap(EncFn enc, CUtensorMap* m, const void* base, int rank, const cuuint64_t* dims, const cuuint64_t* strides, const cuuint32_t* box, CUtensorMapSwizzle swz) {
  cuuint32_t es[5] = {1, 1, 1, 1, 1};
  enc(m, CU_TENSOR_MAP_DATA_TYPE_BFLOAT16, rank, const_cast<void*>(base), dims, strides, box, es, CU_TENSOR_MAP_INTERLEAVE_NONE, swz,
      CU_TENSOR_MAP_L2_PROMOTION_L2_128B, CU_TENSOR_MAP_FLOAT_OOB_FILL_NONE);
}

extern "C" void kernel_launch(void* const* d_in, const int* in_sizes, int n_in, void* d_out, int out_size) {
  void* fn = nullptr; cudaDriverEntryPointQueryResult qr;
  cudaGetDriverEntryPoint("cuTensorMapEncodeTiled", &fn, cudaEnableDefault, &qr);
  EncFn enc = (EncFn)fn;
  void* uy = nullptr; cudaGetSymbolAddress(&uy, g_uy);
  const cuuint64_t dx[2] = {640, 2048}, sx[1] = {1280};
  const cuuint32_t bx[2] = {64, 128}, bu[2] = {80, 128};
  const cuuint64_t dw[3] = {640, 640, 3}, sw[2] = {3840, 1280};
  const cuuint32_t br[3] = {16, 32, 3};
  const cuuint64_t dwa[4] = {64, 640, 10, 3}, swa[3] = {3840, 128, 1280}, dwb[4] = {32, 640, 20, 3}, swb[3] = {3840, 64, 1280};
  const cuuint32_t bwa[4] = {64, 32, 1, 3}, bwb[4] = {32, 32, 2, 3};
  const cuuint64_t dwo[2] = {640, 640};
  const cuuint32_t bwo[2] = {64, 80}, bwr[2] = {16, 160}, bo64[2] = {64, 64}, bo16[2] = {16, 64};
  const cuuint64_t dsa[2] = {2048, 1280}, ssa[1] = {4096};
  const cuuint32_t bsa[2] = {64, 80};
  const cuuint64_t dout[2] = {1280, 2048}, sout[1] = {2560};
  Params prm;
  mkmap(enc, &prm.m[M_X], d_in[7], 2, dx, sx, bx, CU_TENSOR_MAP_SWIZZLE_128B);
  mkmap(enc, &prm.m[M_W128], d_in[8], 4, dwa, swa, bwa, CU_TENSOR_MAP_SWIZZLE_128B);
  mkmap(enc, &prm.m[M_W64], d_in[8], 4, dwb, swb, bwb, CU_TENSOR_MAP_SWIZZLE_64B);
  mkmap(enc, &prm.m[M_WR], d_in[8], 3, dw, sw, br, CU_TENSOR_MAP_SWIZZLE_32B);
  mkmap(enc, &prm.m[M_U], d_in[0], 2, dx, sx, bu, CU_TENSOR_MAP_SWIZZLE_NONE);
  mkmap(enc, &prm.m[M_WO], d_in[9], 2, dwo, sx, bwo, CU_TENSOR_MAP_SWIZZLE_128B);
  mkmap(enc, &prm.m[M_WOR], d_in[9], 2, dwo, sx, bwr, CU_TENSOR_MAP_SWIZZLE_NONE);
  mkmap(enc, &prm.m[M_O64], d_out, 2, dout, sout, bo64, CU_TENSOR_MAP_SWIZZLE_128B);
  mkmap(enc, &prm.m[M_O16], d_out, 2, dout, sout, bo16, CU_TENSOR_MAP_SWIZZLE_NONE);
  mkmap(enc, &prm.m[M_SA], uy, 2, dsa, ssa, bsa, CU_TENSOR_MAP_SWIZZLE_128B);
  mkmap(enc, &prm.m[M_OUT], d_out, 2, dout, sout, bu, CU_TENSOR_MAP_SWIZZLE_NONE);
  prm.u = (const __nv_bfloat16*)d_in[0]; prm.wo = (const __nv_bfloat16*)d_in[9];
  for (int i = 0; i < 4; i++) prm.par[i] = (const __nv_bfloat16*)d_in[1 + i];
  prm.logdt = (const __nv_bfloat16*)d_in[5]; prm.dskip = (const __nv_bfloat16*)d_in[6];
  cudaFuncSetAttribute(fused_kernel, cudaFuncAttributeMaxDynamicSharedMemorySize, SMEM_BYTES);
  fused_kernel<<<128, 512, SMEM_BYTES, cudaStreamPerThread>>>(prm);
}
```

```cpp
#include <cuda_runtime.h>
#include <cuda_bf16.h>
#include <cuda_fp16.h>
#include <cuda.h>
#include <stdint.h>

#define EN_ATT 1
#define EN_SSM 1

__device__ __align__(1024) __nv_bfloat16 g_uy[2 * 640 * 2048];
__device__ __align__(128) uint4 g_kvp[8 * 16 * 240];
__device__ __align__(128) uint4 g_o[128 * 1280];
__device__ __align__(128) unsigned g_flag[4 * 128 * 32];
__device__ unsigned g_epoch[128];
#define TS(i) do {} while (0)
#define DUMP(lo, hi) do {} while (0)
#define FIXCNT

constexpr uint32_t SB0 = 1024;
constexpr uint32_t W_SLOT = 15360, OFF_X = 76800;
constexpr uint32_t OFF_WOR = 81920, OFF_KVP = 10240, OFF_KVS = 71680, OFF_PK = 10240, OFF_V = 30720, OFF_EXTRA = 102400, OFF_KVB = OFF_EXTRA;
constexpr uint32_t OFF_BAR = 125952, OFF_BLK = 128000, BLK = 20480;
constexpr uint32_t B_D = 4096, B_D5 = 3088, B_D7 = 6176, B_D9 = 8224, B_TBL = 14400;
constexpr int T_S = 576, T_F2 = 624, T_F3 = 816;
constexpr uint32_t OFF_UT = OFF_BLK + 4 * BLK;
constexpr uint32_t SMEM_BYTES = OFF_BLK + 5 * BLK;
enum { BR_FULL = 0, BR_WO = 5, BR_PUB = 6, BR_KVP = 7, BR_U = 8, BR_U2 = 9, BR_GEMM = 10, BR_UIN = 11, BR_YIN = 12, BR_EPOCH = 13,
       BR_FREE = 14, BR_RETRY = 16, BR_KS = 17, BR_UOUT = 19, BR_OFULL = 19  , BR_EMPTY = 27, BR_OEMPTY = 32, BR_OSTG = 39,
       BR_Y = 40, BR_DRDY = 42, BR_COUNT = 44 };
constexpr uint32_t OFF_EPOCH = OFF_BAR + 8 * BR_COUNT;
enum { M_X, M_W128, M_W64, M_WR, M_U, M_WO, M_O64, M_O16, M_SA, M_OUT, M_COUNT };

__device__ __forceinline__ long long clk64() { long long t; asm volatile("mov.u64 %0, %%clock64;" : "=l"(t) :: "memory"); return t; }
__device__ __forceinline__ uint32_t smem_u32(const void* p) { return (uint32_t)__cvta_generic_to_shared(p); }
__host__ __device__ constexpr uint64_t mkdesc(uint32_t addr, uint32_t lbo, uint32_t sbo, uint32_t swz) {
  return (uint64_t)((addr & 0x3FFFF) >> 4) | ((uint64_t)(lbo >> 4) << 16) | ((uint64_t)(sbo >> 4) << 32) | ((uint64_t)swz << 62);
}
__device__ __forceinline__ uint64_t desc2(uint32_t lo, uint32_t hi) { uint64_t d; asm("mov.b64 %0, {%1, %2};" : "=l"(d) : "r"(lo), "r"(hi)); return d; }
__device__ __forceinline__ void mbar_init(uint32_t bar, uint32_t cnt) { asm volatile("mbarrier.init.shared::cta.b64 [%0], %1;" :: "r"(bar), "r"(cnt) : "memory"); }
__device__ __forceinline__ void mbar_expect_tx(uint32_t bar, uint32_t bytes) { asm volatile("mbarrier.arrive.expect_tx.shared::cta.b64 _, [%0], %1;" :: "r"(bar), "r"(bytes) : "memory"); }
__device__ __forceinline__ void mbar_arrive(uint32_t bar) { asm volatile("mbarrier.arrive.shared::cta.b64 _, [%0];" :: "r"(bar) : "memory"); }
__device__ __forceinline__ void mbar_wait(uint32_t bar, uint32_t parity) {
  asm volatile("{\n.reg .pred p;\n.reg .u32 c;\nmov.u32 c, 0;\n"
    "WL:\nmbarrier.try_wait.parity.shared::cta.b64 p, [%0], %1;\n@p bra WD;\n"
    "add.u32 c, c, 1;\nsetp.lt.u32 p, c, 200000;\n@p bra WL;\nWD:\n}" :: "r"(bar), "r"(parity) : "memory");
}
__device__ __forceinline__ void poll_all(const unsigned* p, unsigned val) {
  asm volatile("{\n.reg .pred p;\n.reg .u32 c, v;\nmov.u32 c, 0;\n"
    "PL:\nld.relaxed.gpu.global.u32 v, [%0];\nsetp.eq.u32 p, v, %1;\nvote.sync.all.pred p, p, 0xffffffff;\n@p bra PD;\n"
    "add.u32 c, c, 1;\nsetp.lt.u32 p, c, 100000;\n@p bra PL;\nPD:\n}" :: "l"(p), "r"(val) : "memory");
}
__device__ __forceinline__ void poll_all_acq(const unsigned* p, unsigned val) {
  asm volatile("{\n.reg .pred p;\n.reg .u32 c, v;\nmov.u32 c, 0;\n"
    "PL:\nld.acquire.gpu.global.u32 v, [%0];\nsetp.eq.u32 p, v, %1;\nvote.sync.all.pred p, p, 0xffffffff;\n@p bra PD;\n"
    "nanosleep.u32 300;\nadd.u32 c, c, 1;\nsetp.lt.u32 p, c, 100000;\n@p bra PL;\nPD:\n}" :: "l"(p), "r"(val) : "memory");
}
__device__ __forceinline__ unsigned poll_bit(const unsigned* p, unsigned val, unsigned mask) {
  unsigned bal;
  asm volatile("{\n.reg .pred p;\n.reg .u32 c, v;\nmov.u32 c, 0;\n"
    "PL:\nld.relaxed.gpu.global.u32 v, [%1];\nsetp.eq.u32 p, v, %2;\nvote.sync.ballot.b32 %0, p, 0xffffffff;\n"
    "and.b32 v, %0, %3;\nsetp.ne.u32 p, v, 0;\n@p bra PD;\n"
    "add.u32 c, c, 1;\nsetp.lt.u32 p, c, 100000;\n@p bra PL;\nPD:\n}" : "=&r"(bal) : "l"(p), "r"(val), "r"(mask) : "memory");
  return bal;
}
__device__ __forceinline__ void fix128_w3(uint32_t* v, const void* p, uint32_t tag, uint32_t mask) {
  asm volatile("{\n.reg .pred p;\n.reg .u32 c, x;\n.reg .b128 t;\n.reg .b64 lo, hi;\nmov.u32 c, 0;\n"
    "FL:\nxor.b32 x, %3, %5;\nand.b32 x, x, %6;\nsetp.eq.u32 p, x, 0;\n@p bra FD;\n"
    "ld.relaxed.gpu.global.b128 t, [%4];\nmov.b128 {lo, hi}, t;\nmov.b64 {%0, %1}, lo;\nmov.b64 {%2, %3}, hi;\n"
    "add.u32 c, c, 1;\nsetp.lt.u32 p, c, 100000;\n@p bra FL;\nFD:\n}"
    : "+r"(v[0]), "+r"(v[1]), "+r"(v[2]), "+r"(v[3]) : "l"(p), "r"(tag), "r"(mask) : "memory");
}
__device__ __forceinline__ bool elect_one() {
  uint32_t p; asm volatile("{\n.reg .pred P;\nelect.sync _|P, 0xffffffff;\nselp.u32 %0, 1, 0, P;\n}" : "=r"(p)); return p;
}
__device__ __forceinline__ void bar_sync(int id, int n) { asm volatile("bar.sync %0, %1;" :: "r"(id), "r"(n) : "memory"); }
__device__ __forceinline__ void fence_async() { asm volatile("fence.proxy.async.shared::cta;" ::: "memory"); }
__device__ __forceinline__ void fence_async_g() { asm volatile("fence.proxy.async.global;" ::: "memory"); }
__device__ __forceinline__ void tma2d(uint32_t dst, const CUtensorMap* m, uint32_t bar, int c0, int c1) {
  asm volatile("cp.async.bulk.tensor.2d.shared::cluster.global.mbarrier::complete_tx::bytes [%0], [%1, {%3, %4}], [%2];"
    :: "r"(dst), "l"(m), "r"(bar), "r"(c0), "r"(c1) : "memory");
}
__device__ __forceinline__ void tma3d(uint32_t dst, const CUtensorMap* m, uint32_t bar, int c0, int c1, int c2) {
  asm volatile("cp.async.bulk.tensor.3d.shared::cluster.global.mbarrier::complete_tx::bytes [%0], [%1, {%3, %4, %5}], [%2];"
    :: "r"(dst), "l"(m), "r"(bar), "r"(c0), "r"(c1), "r"(c2) : "memory");
}
__device__ __forceinline__ void tma4d(uint32_t dst, const CUtensorMap* m, uint32_t bar, int c0, int c1, int c2, int c3) {
  asm volatile("cp.async.bulk.tensor.4d.shared::cluster.global.mbarrier::complete_tx::bytes [%0], [%1, {%3, %4, %5, %6}], [%2];"
    :: "r"(dst), "l"(m), "r"(bar), "r"(c0), "r"(c1), "r"(c2), "r"(c3) : "memory");
}
__device__ __forceinline__ void tma2d_st(const CUtensorMap* m, uint32_t src, int c0, int c1) {
  asm volatile("cp.async.bulk.tensor.2d.global.shared::cta.bulk_group [%0, {%2, %3}], [%1];"
    :: "l"(m), "r"(src), "r"(c0), "r"(c1) : "memory");
}
__device__ __forceinline__ void bulk_ld(uint32_t dst, const void* src, uint32_t bytes, uint32_t bar) {
  asm volatile("cp.async.bulk.shared::cluster.global.mbarrier::complete_tx::bytes [%0], [%1], %2, [%3];"
    :: "r"(dst), "l"(src), "r"(bytes), "r"(bar) : "memory");
}
__device__ __forceinline__ void bulk_st(void* dst, uint32_t src, uint32_t bytes) {
  asm volatile("cp.async.bulk.global.shared::cta.bulk_group [%0], [%1], %2;" :: "l"(dst), "r"(src), "r"(bytes) : "memory");
}
__device__ __forceinline__ void bulk_commit() { asm volatile("cp.async.bulk.commit_group;" ::: "memory"); }
__device__ __forceinline__ void bulk_wait0() { asm volatile("cp.async.bulk.wait_group 0;" ::: "memory"); }
__device__ __forceinline__ void bulk_wait0_read() { asm volatile("cp.async.bulk.wait_group.read 0;" ::: "memory"); }
__device__ __forceinline__ unsigned ld_rlx(const unsigned* p) { unsigned v; asm volatile("ld.relaxed.gpu.global.u32 %0, [%1];" : "=r"(v) : "l"(p) : "memory"); return v; }
__device__ __forceinline__ unsigned ld_acq(const unsigned* p) { unsigned v; asm volatile("ld.acquire.gpu.global.u32 %0, [%1];" : "=r"(v) : "l"(p) : "memory"); return v; }
__device__ __forceinline__ void st_rlx(unsigned* p, unsigned v) { asm volatile("st.relaxed.gpu.global.u32 [%0], %1;" :: "l"(p), "r"(v) : "memory"); }
__device__ __forceinline__ void st_rel(unsigned* p, unsigned v) { asm volatile("st.release.gpu.global.u32 [%0], %1;" :: "l"(p), "r"(v) : "memory"); }
__device__ __forceinline__ void st128_rlx(void* p, const uint32_t* v) {
  asm volatile("{\n.reg .b128 t;\n.reg .b64 lo, hi;\nmov.b64 lo, {%1, %2};\nmov.b64 hi, {%3, %4};\nmov.b128 t, {lo, hi};\n"
    "st.relaxed.gpu.global.b128 [%0], t;\n}" :: "l"(p), "r"(v[0]), "r"(v[1]), "r"(v[2]), "r"(v[3]) : "memory");
}
__device__ __forceinline__ uint32_t lds32(uint32_t a) { uint32_t v; asm volatile("ld.shared.u32 %0, [%1];" : "=r"(v) : "r"(a) : "memory"); return v; }
__device__ __forceinline__ uint32_t lds32v(uint32_t a) { uint32_t v; asm volatile("ld.volatile.shared.u32 %0, [%1];" : "=r"(v) : "r"(a) : "memory"); return v; }
__device__ __forceinline__ void lds128(uint32_t* v, uint32_t a) { asm volatile("ld.shared.v4.u32 {%0,%1,%2,%3}, [%4];" : "=r"(v[0]), "=r"(v[1]), "=r"(v[2]), "=r"(v[3]) : "r"(a) : "memory"); }
__device__ __forceinline__ void sts32(uint32_t a, uint32_t v) { asm volatile("st.shared.u32 [%0], %1;" :: "r"(a), "r"(v) : "memory"); }
__device__ __forceinline__ void sts16(uint32_t a, uint32_t v) { asm volatile("st.shared.u16 [%0], %1;" :: "r"(a), "h"((uint16_t)v) : "memory"); }
__device__ __forceinline__ void sts64f(uint32_t a, float x, float y) { asm volatile("st.shared.v2.f32 [%0], {%1,%2};" :: "r"(a), "f"(x), "f"(y) : "memory"); }
__device__ __forceinline__ void sts128(uint32_t a, uint32_t x, uint32_t y, uint32_t z, uint32_t w) { asm volatile("st.shared.v4.u32 [%0], {%1,%2,%3,%4};" :: "r"(a), "r"(x), "r"(y), "r"(z), "r"(w) : "memory"); }
__device__ __forceinline__ void stsm4(uint32_t a, uint32_t r0, uint32_t r1, uint32_t r2, uint32_t r3) {
  asm volatile("stmatrix.sync.aligned.m8n8.x4.shared.b16 [%0], {%1,%2,%3,%4};" :: "r"(a), "r"(r0), "r"(r1), "r"(r2), "r"(r3) : "memory");
}
__device__ __forceinline__ void stsm4t(uint32_t a, uint32_t r0, uint32_t r1, uint32_t r2, uint32_t r3) {
  asm volatile("stmatrix.sync.aligned.m8n8.x4.trans.shared.b16 [%0], {%1,%2,%3,%4};" :: "r"(a), "r"(r0), "r"(r1), "r"(r2), "r"(r3) : "memory");
}
__device__ __forceinline__ void ldsm4t(uint32_t* r, uint32_t a) {
  asm volatile("ldmatrix.sync.aligned.m8n8.x4.trans.shared.b16 {%0,%1,%2,%3}, [%4];" : "=r"(r[0]), "=r"(r[1]), "=r"(r[2]), "=r"(r[3]) : "r"(a) : "memory");
}
__device__ __forceinline__ void ldsm4(uint32_t* r, uint32_t a) {
  asm volatile("ldmatrix.sync.aligned.m8n8.x4.shared.b16 {%0,%1,%2,%3}, [%4];" : "=r"(r[0]), "=r"(r[1]), "=r"(r[2]), "=r"(r[3]) : "r"(a) : "memory");
}
__device__ __forceinline__ void mma16816(float* d, const uint32_t* a, const uint32_t* b) {
  asm volatile("mma.sync.aligned.m16n8k16.row.col.f32.bf16.bf16.f32 {%0,%1,%2,%3}, {%4,%5,%6,%7}, {%8,%9}, {%0,%1,%2,%3};"
    : "+f"(d[0]), "+f"(d[1]), "+f"(d[2]), "+f"(d[3]) : "r"(a[0]), "r"(a[1]), "r"(a[2]), "r"(a[3]), "r"(b[0]), "r"(b[1]));
}
__device__ __forceinline__ uint32_t pack2(float lo, float hi) { uint32_t r; asm("cvt.rn.bf16x2.f32 %0, %1, %2;" : "=r"(r) : "f"(hi), "f"(lo)); return r; }
__device__ __forceinline__ uint32_t packh(float lo, float hi) { uint32_t r; asm("cvt.rn.f16x2.f32 %0, %1, %2;" : "=r"(r) : "f"(hi), "f"(lo)); return r; }
__device__ __forceinline__ void hcm2(uint32_t xr, uint32_t xi, uint32_t z, uint32_t& pr, uint32_t& pi) {
  const __half2 a = *reinterpret_cast<__half2*>(&xr), b = *reinterpret_cast<__half2*>(&xi), zz = *reinterpret_cast<__half2*>(&z);
  const __half2 re = __hfma2(__hneg2(b), __high2half2(zz), __hmul2(a, __low2half2(zz)));
  const __half2 im = __hfma2(a, __high2half2(zz), __hmul2(b, __low2half2(zz)));
  pr = *reinterpret_cast<const uint32_t*>(&re); pi = *reinterpret_cast<const uint32_t*>(&im);
}
__device__ __forceinline__ void hcm2c(uint32_t xr, uint32_t xi, uint32_t z, uint32_t& pr, uint32_t& pi) {
  const __half2 a = *reinterpret_cast<__half2*>(&xr), b = *reinterpret_cast<__half2*>(&xi), zz = *reinterpret_cast<__half2*>(&z);
  const __half2 re = __hfma2(b, __high2half2(zz), __hmul2(a, __low2half2(zz)));
  const __half2 im = __hfma2(__hneg2(a), __high2half2(zz), __hmul2(b, __low2half2(zz)));
  pr = *reinterpret_cast<const uint32_t*>(&re); pi = *reinterpret_cast<const uint32_t*>(&im);
}
__device__ __forceinline__ void lds64(uint32_t* v, uint32_t a) { asm volatile("ld.shared.v2.u32 {%0,%1}, [%2];" : "=r"(v[0]), "=r"(v[1]) : "r"(a) : "memory"); }
__device__ __forceinline__ float bf_lo(uint32_t v) { return __uint_as_float(v << 16); }
__device__ __forceinline__ float bf_hi(uint32_t v) { return __uint_as_float(v & 0xffff0000u); }
__device__ __forceinline__ float bf_round(float x) { return bf_lo(pack2(x, 0.f)); }
__device__ __forceinline__ float ex2(float x) { float r; asm("ex2.approx.ftz.f32 %0, %1;" : "=f"(r) : "f"(x)); return r; }
__device__ __forceinline__ float phi(float t, float l2e = 1.44269504089f) {
  float e = ex2(t * l2e) + 1e-6f;
  asm("{\n.reg .pred p;\nsetp.gt.f32 p, %1, 0f00000000;\n@p add.f32 %0, %1, 0f3F800008;\n}" : "+f"(e) : "f"(t));
  return e;
}
__device__ __forceinline__ void wg_fence() { asm volatile("wgmma.fence.sync.aligned;" ::: "memory"); }
__device__ __forceinline__ void wg_commit() { asm volatile("wgmma.commit_group.sync.aligned;" ::: "memory"); }
template <int N> __device__ __forceinline__ void wg_wait() { asm volatile("wgmma.wait_group.sync.aligned %0;" :: "n"(N) : "memory"); }
template <int N> __device__ __forceinline__ void pin(float* a) {
  #pragma unroll
  for (int i = 0; i < N; i++) asm volatile("" : "+f"(a[i]) :: "memory");
}
__device__ __forceinline__ int rtid() { int t; asm volatile("mov.u32 %0, %%tid.x;" : "=r"(t)); return t; }
template <int N> __device__ __forceinline__ void zero(float* a) {
  #pragma unroll
  for (int i = 0; i < N; i++) asm volatile("mov.b32 %0, 0;" : "=f"(a[i]));
}
__device__ __forceinline__ void cexp_t(float lg2mag, float turns, float& re, float& im) {
  float m = ex2(lg2mag);
  float fr = (turns - __fadd_rn(__fadd_rn(turns, 12582912.f), -12582912.f)) * 6.283185307f;
  re = m * __cosf(fr); im = m * __sinf(fr);
}
__device__ __forceinline__ void csq(float ar, float ai, float& cr, float& ci) {
  const float t = ar + ar;
  cr = fmaf(ar, ar, -ai * ai); ci = t * ai;
}
__device__ __forceinline__ void cmul(float ar, float ai, float br, float bi, float& cr, float& ci) {
  cr = fmaf(ar, br, -ai * bi); ci = fmaf(ar, bi, ai * br);
}

__device__ __forceinline__ void wg_ss48_tt(float* d, uint64_t da, uint64_t db, int scale_d) {
  asm volatile("{\n.reg .pred p;\nsetp.ne.b32 p, %26, 0;\n"
    "wgmma.mma_async.sync.aligned.m64n48k16.f32.bf16.bf16 "
    "{%0, %1, %2, %3, %4, %5, %6, %7, %8, %9, %10, %11, %12, %13, %14, %15, %16, %17, %18, %19, %20, %21, %22, %23}, %24, %25, p, 1, 1, 1, 1;\n}\n"
    : "+f"(d[0]), "+f"(d[1]), "+f"(d[2]), "+f"(d[3]), "+f"(d[4]), "+f"(d[5]), "+f"(d[6]), "+f"(d[7]), "+f"(d[8]), "+f"(d[9]), "+f"(d[10]), "+f"(d[11]), "+f"(d[12]), "+f"(d[13]), "+f"(d[14]), "+f"(d[15]), "+f"(d[16]), "+f"(d[17]), "+f"(d[18]), "+f"(d[19]), "+f"(d[20]), "+f"(d[21]), "+f"(d[22]), "+f"(d[23])
    : "l"(da), "l"(db), "r"(scale_d));
}
__device__ __forceinline__ void wg_rs88_tb(float* d, const uint32_t* a, uint64_t db, int scale_d) {
  asm volatile("{\n.reg .pred p;\nsetp.ne.b32 p, %49, 0;\n"
    "wgmma.mma_async.sync.aligned.m64n88k16.f32.bf16.bf16 "
    "{%0, %1, %2, %3, %4, %5, %6, %7, %8, %9, %10, %11, %12, %13, %14, %15, %16, %17, %18, %19, %20, %21, %22, %23, %24, %25, %26, %27, %28, %29, %30, %31, %32, %33, %34, %35, %36, %37, %38, %39, %40, %41, %42, %43}, {%44, %45, %46, %47}, %48, p, 1, 1, 1;\n}\n"
    : "+f"(d[0]), "+f"(d[1]), "+f"(d[2]), "+f"(d[3]), "+f"(d[4]), "+f"(d[5]), "+f"(d[6]), "+f"(d[7]), "+f"(d[8]), "+f"(d[9]), "+f"(d[10]), "+f"(d[11]), "+f"(d[12]), "+f"(d[13]), "+f"(d[14]), "+f"(d[15]), "+f"(d[16]), "+f"(d[17]), "+f"(d[18]), "+f"(d[19]), "+f"(d[20]), "+f"(d[21]), "+f"(d[22]), "+f"(d[23]), "+f"(d[24]), "+f"(d[25]), "+f"(d[26]), "+f"(d[27]), "+f"(d[28]), "+f"(d[29]), "+f"(d[30]), "+f"(d[31]), "+f"(d[32]), "+f"(d[33]), "+f"(d[34]), "+f"(d[35]), "+f"(d[36]), "+f"(d[37]), "+f"(d[38]), "+f"(d[39]), "+f"(d[40]), "+f"(d[41]), "+f"(d[42]), "+f"(d[43])
    : "r"(a[0]), "r"(a[1]), "r"(a[2]), "r"(a[3]), "l"(db), "r"(scale_d));
}
__device__ __forceinline__ void wg_ss80_tb(float* d, uint64_t da, uint64_t db, int scale_d) {
  asm volatile("{\n.reg .pred p;\nsetp.ne.b32 p, %42, 0;\n"
    "wgmma.mma_async.sync.aligned.m64n80k16.f32.bf16.bf16 "
    "{%0, %1, %2, %3, %4, %5, %6, %7, %8, %9, %10, %11, %12, %13, %14, %15, %16, %17, %18, %19, %20, %21, %22, %23, %24, %25, %26, %27, %28, %29, %30, %31, %32, %33, %34, %35, %36, %37, %38, %39}, %40, %41, p, 1, 1, 0, 1;\n}\n"
    : "+f"(d[0]), "+f"(d[1]), "+f"(d[2]), "+f"(d[3]), "+f"(d[4]), "+f"(d[5]), "+f"(d[6]), "+f"(d[7]), "+f"(d[8]), "+f"(d[9]), "+f"(d[10]), "+f"(d[11]), "+f"(d[12]), "+f"(d[13]), "+f"(d[14]), "+f"(d[15]), "+f"(d[16]), "+f"(d[17]), "+f"(d[18]), "+f"(d[19]), "+f"(d[20]), "+f"(d[21]), "+f"(d[22]), "+f"(d[23]), "+f"(d[24]), "+f"(d[25]), "+f"(d[26]), "+f"(d[27]), "+f"(d[28]), "+f"(d[29]), "+f"(d[30]), "+f"(d[31]), "+f"(d[32]), "+f"(d[33]), "+f"(d[34]), "+f"(d[35]), "+f"(d[36]), "+f"(d[37]), "+f"(d[38]), "+f"(d[39])
    : "l"(da), "l"(db), "r"(scale_d));
}
__device__ __forceinline__ void wg_ss48_tt_h(float* d, uint64_t da, uint64_t db, int scale_d) {
  asm volatile("{\n.reg .pred p;\nsetp.ne.b32 p, %26, 0;\n"
    "wgmma.mma_async.sync.aligned.m64n48k16.f32.f16.f16 "
    "{%0, %1, %2, %3, %4, %5, %6, %7, %8, %9, %10, %11, %12, %13, %14, %15, %16, %17, %18, %19, %20, %21, %22, %23}, %24, %25, p, 1, 1, 1, 1;\n}\n"
    : "+f"(d[0]), "+f"(d[1]), "+f"(d[2]), "+f"(d[3]), "+f"(d[4]), "+f"(d[5]), "+f"(d[6]), "+f"(d[7]), "+f"(d[8]), "+f"(d[9]), "+f"(d[10]), "+f"(d[11]), "+f"(d[12]), "+f"(d[13]), "+f"(d[14]), "+f"(d[15]), "+f"(d[16]), "+f"(d[17]), "+f"(d[18]), "+f"(d[19]), "+f"(d[20]), "+f"(d[21]), "+f"(d[22]), "+f"(d[23])
    : "l"(da), "l"(db), "r"(scale_d));
}
__device__ __forceinline__ void wg_rs192_tb(float* d, const uint32_t* a, uint64_t db, int scale_d) {
  asm volatile("{\n.reg .pred p;\nsetp.ne.b32 p, %101, 0;\n"
    "wgmma.mma_async.sync.aligned.m64n192k16.f32.bf16.bf16 "
    "{%0, %1, %2, %3, %4, %5, %6, %7, %8, %9, %10, %11, %12, %13, %14, %15, %16, %17, %18, %19, %20, %21, %22, %23, %24, %25, %26, %27, %28, %29, %30, %31, %32, %33, %34, %35, %36, %37, %38, %39, %40, %41, %42, %43, %44, %45, %46, %47, %48, %49, %50, %51, %52, %53, %54, %55, %56, %57, %58, %59, %60, %61, %62, %63, %64, %65, %66, %67, %68, %69, %70, %71, %72, %73, %74, %75, %76, %77, %78, %79, %80, %81, %82, %83, %84, %85, %86, %87, %88, %89, %90, %91, %92, %93, %94, %95}, {%96, %97, %98, %99}, %100, p, 1, 1, 1;\n}\n"
    : "+f"(d[0]), "+f"(d[1]), "+f"(d[2]), "+f"(d[3]), "+f"(d[4]), "+f"(d[5]), "+f"(d[6]), "+f"(d[7]), "+f"(d[8]), "+f"(d[9]), "+f"(d[10]), "+f"(d[11]), "+f"(d[12]), "+f"(d[13]), "+f"(d[14]), "+f"(d[15]), "+f"(d[16]), "+f"(d[17]), "+f"(d[18]), "+f"(d[19]), "+f"(d[20]), "+f"(d[21]), "+f"(d[22]), "+f"(d[23]), "+f"(d[24]), "+f"(d[25]), "+f"(d[26]), "+f"(d[27]), "+f"(d[28]), "+f"(d[29]), "+f"(d[30]), "+f"(d[31]), "+f"(d[32]), "+f"(d[33]), "+f"(d[34]), "+f"(d[35]), "+f"(d[36]), "+f"(d[37]), "+f"(d[38]), "+f"(d[39]), "+f"(d[40]), "+f"(d[41]), "+f"(d[42]), "+f"(d[43]), "+f"(d[44]), "+f"(d[45]), "+f"(d[46]), "+f"(d[47]), "+f"(d[48]), "+f"(d[49]), "+f"(d[50]), "+f"(d[51]), "+f"(d[52]), "+f"(d[53]), "+f"(d[54]), "+f"(d[55]), "+f"(d[56]), "+f"(d[57]), "+f"(d[58]), "+f"(d[59]), "+f"(d[60]), "+f"(d[61]), "+f"(d[62]), "+f"(d[63]), "+f"(d[64]), "+f"(d[65]), "+f"(d[66]), "+f"(d[67]), "+f"(d[68]), "+f"(d[69]), "+f"(d[70]), "+f"(d[71]), "+f"(d[72]), "+f"(d[73]), "+f"(d[74]), "+f"(d[75]), "+f"(d[76]), "+f"(d[77]), "+f"(d[78]), "+f"(d[79]), "+f"(d[80]), "+f"(d[81]), "+f"(d[82]), "+f"(d[83]), "+f"(d[84]), "+f"(d[85]), "+f"(d[86]), "+f"(d[87]), "+f"(d[88]), "+f"(d[89]), "+f"(d[90]), "+f"(d[91]), "+f"(d[92]), "+f"(d[93]), "+f"(d[94]), "+f"(d[95])
    : "r"(a[0]), "r"(a[1]), "r"(a[2]), "r"(a[3]), "l"(db), "r"(scale_d));
}
__device__ __forceinline__ void wg_rs48_tb(float* d, const uint32_t* a, uint64_t db, int scale_d) {
  asm volatile("{\n.reg .pred p;\nsetp.ne.b32 p, %29, 0;\n"
    "wgmma.mma_async.sync.aligned.m64n48k16.f32.bf16.bf16 "
    "{%0, %1, %2, %3, %4, %5, %6, %7, %8, %9, %10, %11, %12, %13, %14, %15, %16, %17, %18, %19, %20, %21, %22, %23}, {%24, %25, %26, %27}, %28, p, 1, 1, 1;\n}\n"
    : "+f"(d[0]), "+f"(d[1]), "+f"(d[2]), "+f"(d[3]), "+f"(d[4]), "+f"(d[5]), "+f"(d[6]), "+f"(d[7]), "+f"(d[8]), "+f"(d[9]), "+f"(d[10]), "+f"(d[11]), "+f"(d[12]), "+f"(d[13]), "+f"(d[14]), "+f"(d[15]), "+f"(d[16]), "+f"(d[17]), "+f"(d[18]), "+f"(d[19]), "+f"(d[20]), "+f"(d[21]), "+f"(d[22]), "+f"(d[23])
    : "r"(a[0]), "r"(a[1]), "r"(a[2]), "r"(a[3]), "l"(db), "r"(scale_d));
}

struct Params {
  const __nv_bfloat16 *par[4], *logdt, *dskip, *u, *wo;
  CUtensorMap m[M_COUNT];
};

#define CHUNK(i) ((c + (i)) & 7)
#define FLAG(kind, rr, cc) (&g_flag[((kind) * 128 + (rr) * 8 + (cc)) * 32])
#define SLOT(i) ((i) == 0 ? OFF_EXTRA : OFF_BLK - 256 + ((i) > 5 ? (i) - 6 : (i) - 1) * BLK)
__device__ __forceinline__ void load_quad(uint32_t* A, uint32_t addr) {
  A[0] = lds32v(addr); A[1] = lds32v(addr + 32); A[2] = lds32v(addr - 32); A[3] = lds32v(addr);
}

__device__ __forceinline__ bool y_transpose(uint32_t sb, int w5, int lane, uint32_t ytag) {
  const int mi = lane >> 3, rw = lane & 7;
  const uint32_t sa = sb + OFF_EXTRA + (w5 * 16 + rw) * 128 + ((mi ^ rw) << 4), da = sb + SLOT(3) + (8 * mi + rw) * 160 + w5 * 32;
  const uint32_t ym = lane < 4 ? 0x10001u : 0u;
  bar_sync(7, 160);
  uint32_t v[8][4], bad = 0;
  #pragma unroll
  for (int q = 0; q < 8; q++) ldsm4t(v[q], (sa ^ ((q & 1) * 64 + ((q >> 1) & 1) * 16)) + ((q >> 1) & 1) * 10240 + (q >> 2) * 1024);
  #pragma unroll
  for (int q = 0; q < 8; q++) {
    bad |= (v[q][0] ^ ytag) | (v[q][2] ^ ytag);
    stsm4(da + (q & 3) * 5120 + (q >> 2) * 16, v[q][0] & ~ym, v[q][1], v[q][2] & ~ym, v[q][3]);
  }
  fence_async();
  uint32_t any;
  asm volatile("{\n.reg .pred p;\nsetp.ne.u32 p, %1, 0;\nbarrier.red.or.pred p, 7, 160, p;\nselp.u32 %0, 1, 0, p;\n}" : "=r"(any) : "r"(bad & ym) : "memory");
  return any;
}

__global__ void __launch_bounds__(512, 1) fused_kernel(const __grid_constant__ Params prm) {
  extern __shared__ unsigned char smem_raw[];
  uint32_t raw[5][2], pd;
  if ((threadIdx.x >> 7) == 2) {
    const int ch = (blockIdx.x & 7) * 80 + (blockIdx.x >> 3) * 5, od = threadIdx.x & 1;
    #pragma unroll
    for (int e = 0; e < 2; e++) {
      const __nv_bfloat16* pp = prm.par[2 * e + od] + ch * 128 + (threadIdx.x & 126);
      #pragma unroll
      for (int q = 0; q < 5; q++) asm volatile("ld.global.nc.u32 %0, [%1];" : "=r"(raw[q][e]) : "l"(pp + q * 128));
    }
    asm volatile("ld.global.nc.u16 %0, [%1];" : "=r"(pd) : "l"(((threadIdx.x & 8) ? prm.dskip : prm.logdt) + ch + min(threadIdx.x & 7, 4)));
  }
  constexpr uint32_t sb = SB0;
  const int tid = threadIdx.x, lane = tid & 31;
  const int warp = __shfl_sync(0xffffffff, tid >> 5, 0), wg = warp >> 2, w4 = warp & 3;
  const int cta = blockIdx.x, r = cta >> 3, c = cta & 7;
  if (smem_u32(smem_raw) != SB0) return;
#define BAR(i) (sb + OFF_BAR + 8 * (i))
  const bool sw64 = ((c + 1) & 2) != 0;

  const CUtensorMap* mwp = &prm.m[sw64 ? M_W64 : M_W128];
  const int mcol = (c * 80 + (c & 1) * 16) >> (sw64 ? 5 : 6), rcol = c * 80 + ((c & 1) ? 0 : 64);
  if (warp == 12 && elect_one()) {
    #pragma unroll
    for (int i = 0; i < 5; i++) mbar_init(BAR(BR_FULL + i), 1);
    asm volatile("fence.mbarrier_init.release.cluster;" ::: "memory");
    if (EN_ATT) {
      mbar_expect_tx(BAR(BR_FULL), W_SLOT + 16384);
      tma4d(sb, mwp, BAR(BR_FULL), 0, 0, mcol, 0);
      tma2d(sb + OFF_X, &prm.m[M_X], BAR(BR_FULL), 0, r * 128);
      tma3d(sb + 12288, &prm.m[M_WR], BAR(BR_FULL), rcol, 0, 0);
      mbar_expect_tx(BAR(BR_FULL + 1), W_SLOT);
      tma4d(sb + W_SLOT, mwp, BAR(BR_FULL + 1), 0, 32, mcol, 0);
      tma3d(sb + W_SLOT + 12288, &prm.m[M_WR], BAR(BR_FULL + 1), rcol, 32, 0);
      TS(24);
    }
  }
  if (warp == 13 && elect_one()) {
    asm volatile("prefetch.tensormap [%0];" :: "l"(&prm.m[M_X]) : "memory");
    asm volatile("prefetch.tensormap [%0];" :: "l"(&prm.m[M_WR]) : "memory");
  }
  if (wg == 3) {
    asm volatile("setmaxnreg.dec.sync.aligned.u32 56;");
    const int tid = rtid(), lane = tid & 31;
    if (warp == 12) {
      asm volatile("bar.arrive 0, 512;" ::: "memory");
      if (EN_ATT && elect_one()) {
        #pragma unroll
        for (int kb = 2; kb < 5; kb++) {
          mbar_expect_tx(BAR(BR_FULL + kb), (kb & 1) ? W_SLOT : W_SLOT + 16384);
          if (!(kb & 1)) tma2d(sb + OFF_X + kb * 8192, &prm.m[M_X], BAR(BR_FULL + kb), kb * 32, r * 128);
          tma4d(sb + kb * W_SLOT, mwp, BAR(BR_FULL + kb), 0, kb * 32, mcol, 0);
          tma3d(sb + kb * W_SLOT + 12288, &prm.m[M_WR], BAR(BR_FULL + kb), rcol, kb * 32, 0);
        }
      }
      bar_sync(6, 128);
      if (elect_one()) {
        if (EN_SSM) { mbar_expect_tx(BAR(BR_UIN), 20480); tma2d(sb + OFF_UT, &prm.m[M_U], BAR(BR_UIN), c * 80, r * 128); }
        if (EN_ATT) {
          uint32_t st = sb, fb = BAR(BR_FULL), ph = 0, xs = sb + OFF_X;
          #pragma unroll 1
          for (int k = 160; k < 640; k += 32) {
            mbar_wait(fb + 8 * (BR_EMPTY - BR_FULL), ph);
            mbar_expect_tx(fb, (k & 32) ? W_SLOT : W_SLOT + 16384);
            tma4d(st, mwp, fb, 0, k, mcol, 0);
            if (!(k & 32)) { tma2d(xs, &prm.m[M_X], fb, k, r * 128); xs += 16384; if (xs == sb + OFF_BAR) xs = sb + OFF_X; }
            tma3d(st + 12288, &prm.m[M_WR], fb, rcol, k, 0);
            st += W_SLOT; fb += 8;
            if (st == sb + OFF_X) { st = sb; fb = BAR(BR_FULL); ph ^= 1; }
          }
          asm volatile("cp.async.bulk.prefetch.L2.global [%0], 6400;" :: "l"(prm.wo + cta * 3200) : "memory");
        }
      }
      __syncwarp();
      if (EN_ATT) {
      mbar_wait(BAR(BR_EPOCH), 0);
      const unsigned epoch = lds32(sb + OFF_EPOCH);
      const unsigned* fo = FLAG(3, r, lane & 7);
      unsigned seen = __ballot_sync(0xffffffff, ld_rlx(lane < 16 ? fo : FLAG(0, lane & 15, c)) == epoch);
      mbar_wait(BAR(BR_GEMM), 0);
      if (elect_one()) {
        mbar_expect_tx(BAR(BR_WO), 8 * 10240);
        mbar_expect_tx(BAR(BR_KVP), 61440);
      }
      {
        uint32_t ds = sb + OFF_WOR + (lane >> 3) * 128 + (((lane & 7) ^ (lane >> 3)) << 4);
        #pragma unroll 1
        for (int h = 0; h < 2; h++) {
          const int i = (lane & 6) + h;
          const char* gs = reinterpret_cast<const char*>(prm.wo) + (size_t)((lane >> 3) + CHUNK(i) * 80) * 1280 + 1024 + c * 32 + (lane & 1) * 16;
          #pragma unroll 2
          for (int q = 0; q < 20; q++) {
            asm volatile("cp.async.cg.shared.global [%0], [%1], 16;" :: "r"(ds), "l"(gs) : "memory");
            ds = (ds + 512) ^ 64; gs += 5120;
          }
        }
      }
      mbar_wait(BAR(BR_PUB), 0);
      if ((seen >> 16) != 0xffffu) poll_all(FLAG(0, lane & 15, c), epoch);
      if (elect_one()) { TS(23); bulk_ld(sb + OFF_KVP, &g_kvp[c * 16 * 240], 61440, BAR(BR_KVP)); }
      asm volatile("cp.async.wait_all;" ::: "memory");
      fence_async();
      mbar_arrive(BAR(BR_WO));
      mbar_wait(BAR(BR_OSTG), 0);
      if (elect_one()) {
        bulk_st(&g_o[cta * 1280], sb + OFF_EXTRA, 20480);
        bulk_commit();
        bulk_wait0();
        st_rlx(FLAG(3, r, c), epoch);
        mbar_arrive(BAR(BR_OEMPTY));
        TS(20);
        #pragma unroll 1
        for (int i = 0; i < 8; i++) tma2d(sb + i * 10240, &prm.m[M_WO], BAR(BR_WO), c * 64, CHUNK(i) * 80);
      }
      __syncwarp();
      #pragma unroll 1
      for (int i = 1; i < 8; i++) {
        const int src = CHUNK(i);
        if (!((seen >> src) & 1)) seen = poll_bit(fo, epoch, 1u << src);
        if (i > 5) mbar_wait(BAR(BR_OEMPTY - 5) + 8 * i, 0);
        else if (EN_SSM && i != 2 && i != 3) mbar_wait(i == 1 ? BAR(BR_KS + 1) : BAR(BR_FREE - 4) + 8 * i, 0);
        if (elect_one()) {
          mbar_expect_tx(BAR(BR_OFULL) + 8 * i, 20480);
          bulk_ld(sb + SLOT(i), &g_o[(r * 8 + src) * 1280], 20480, BAR(BR_OFULL) + 8 * i);
          if (i == 1) TS(21);
          if (i == 7) TS(22);
        }
        __syncwarp();
      }
      if (lane == 0) { DUMP(20, 30); }
      }
    } else {
      const int hw = warp - 13, ht = tid - 416;
      if (hw == 2 && elect_one()) {
        #pragma unroll
        for (int i = 5; i <= BR_DRDY; i++) mbar_init(BAR(i), i == BR_WO ? 33 : i == BR_GEMM ? 8 : i == BR_OEMPTY ? 9 : i < BR_EMPTY ? 1 : i < BR_OEMPTY ? 2 : i < BR_Y ? 8 : i < BR_DRDY ? 4 : 3);
        asm volatile("fence.mbarrier_init.release.cluster;" ::: "memory");
      }
      __syncwarp();
      asm volatile("bar.arrive 0, 512;" ::: "memory");
      if (EN_SSM && hw == 2) asm volatile("bar.arrive 8, 160;" ::: "memory");
      const unsigned epoch = hw == 0 ? ld_rlx(&g_epoch[cta]) + 1 : 0;
      if (ht < 80) sts128(sb + OFF_BLK + (ht >> 4) * BLK - 256 + (ht & 15) * 16, 0, 0, 0, 0);
      bar_sync(5, 96);
      asm volatile("bar.arrive 6, 128;" ::: "memory");
      if (hw == 1 && elect_one()) {
        #pragma unroll
        for (int i = M_U; i < M_COUNT; i++) asm volatile("prefetch.tensormap [%0];" :: "l"(&prm.m[i]) : "memory");
      }
      if (ht == 0) {
        st_rlx(&g_epoch[cta], epoch);
        sts32(sb + OFF_EPOCH, epoch);
        mbar_arrive(BAR(BR_EPOCH));
      }
      if (EN_SSM) {
      const int mi = lane >> 3, rw = lane & 7, ch0 = c * 80 + r * 5;
      const bool early_u = hw == 0 && __all_sync(0xffffffff, ld_acq(FLAG(1, lane & 15, c)) == epoch);
      mbar_wait(BAR(BR_UIN), 0);
      if (ht == 0) TS(36);
      #pragma unroll 1
      for (int h = 0; h < 2; h++) {
        const uint32_t sa = sb + OFF_UT + h * 10240 + (8 * mi + rw) * 160 + hw * 16, da = sb + OFF_UT + h * 10240 + (hw * 8 + rw) * 128 + ((mi ^ rw ^ h) << 4);
        uint32_t v[8][4];
        #pragma unroll
        for (int q = 0; q < 8; q++) if (q < 6 || hw == 0) ldsm4t(v[q], sa + (q & 1) * 5120 + (q >> 1) * 48);
        bar_sync(5, 96);
        #pragma unroll
        for (int q = 0; q < 8; q++) if (q < 6 || hw == 0) stsm4((da ^ ((q & 1) * 64)) + (q >> 1) * 3072, v[q][0], v[q][1], v[q][2], v[q][3]);
      }
      fence_async();
      bar_sync(5, 96);
      if (hw == 0) {
        if (elect_one()) {
          tma2d_st(&prm.m[M_SA], sb + OFF_UT, r * 128, c * 80);
          tma2d_st(&prm.m[M_SA], sb + OFF_UT + 10240, r * 128 + 64, c * 80);
          bulk_commit(); bulk_wait0_read();
          mbar_arrive(BAR(BR_UOUT));
          TS(37);
          bulk_wait0();
          st_rel(FLAG(1, r, c), epoch);
          TS(30);
        }
        __syncwarp();
        if (!early_u) poll_all_acq(FLAG(1, lane & 15, c), epoch);
      }
      #pragma unroll 1
      for (int k = 0; k < 5; k++) {
        if (k == 0 || k == 3) {
          const int p = k != 0;
          if (hw == 0) {
            if (!p) {
              if (elect_one()) {
                fence_async_g();
                mbar_expect_tx(BAR(BR_U), 12288);
                #pragma unroll 1
                for (int q = 0; q < 3; q++) bulk_ld(sb + OFF_BLK + q * q * BLK, g_uy + (ch0 + q * q) * 2048, 4096, BAR(BR_U));
                TS(31);
              }
              __syncwarp();
            }
            mbar_wait(BAR(p ? BR_U2 : BR_U), 0);
          }
          bar_sync(5, 96);
        }
        const int l3 = (hw + k) % 3 * 32 + lane;
        const uint32_t blk = sb + OFF_BLK + ((0x32410 >> (4 * k)) & 7) * BLK, o = blk + B_D + l3 * 16;
        float P[34];
        P[0] = 0.f;
        #pragma unroll
        for (int q = 0; q < 5; q++) {
          const int ch = 2 * l3 - 3 + q;
          uint32_t v[4];
          lds128(v, blk + (uint32_t)((ch * 16) ^ ((ch * 2) & 0x10)));
          #pragma unroll
          for (int e = 0; e < 8; e++) {
            const int i = 8 * q + e - 4;
            if (i >= 0 && i < 33) P[i + 1] = P[i] + ((e & 1) ? bf_hi(v[e >> 1]) : bf_lo(v[e >> 1]));
          }
        }
#define WIN(lo, hi, e) (P[21 + (e) - (lo)] - P[20 + (e) - (hi)])
#define WIN8(lo, hi, b) pack2(WIN(lo, hi, b), WIN(lo, hi, b + 1)), pack2(WIN(lo, hi, b + 2), WIN(lo, hi, b + 3)), pack2(WIN(lo, hi, b + 4), WIN(lo, hi, b + 5)), pack2(WIN(lo, hi, b + 6), WIN(lo, hi, b + 7))
        if (l3 < 64) {
          sts128(o + B_D9, WIN8(12, 20, 0)); sts128(o + B_D9 + 1024, WIN8(12, 20, 8));
          sts128(o + B_D7, WIN8(5, 11, 0)); sts128(o + B_D7 + 1024, WIN8(5, 11, 8));
        }
        sts128(o + B_D5, WIN8(6, 10, 0)); sts128(o + B_D5 + 1552, WIN8(6, 10, 8));
        sts128(o, WIN8(3, 5, 0)); sts128(o + 1552, WIN8(3, 5, 8));
        if (l3 < 2) sts128(blk + B_D + l3 * B_D5 + 1536, 0, 0, 0, 0);
      }
      __syncwarp();
      if (lane == 0) mbar_arrive(BAR(BR_DRDY));
      if (ht == 0) TS(32);
      if (hw == 0) {
        const bool early = __all_sync(0xffffffff, ld_rlx(FLAG(2, lane & 15, c)) == epoch);
        #pragma unroll 1
        for (int p = 0; p < 2; p++) {
          mbar_wait(BAR(BR_Y) + 8 * p, 0);
          if (elect_one()) {
            bulk_st(g_uy + (640 + ch0 + 4 * p) * 2048, sb + OFF_BLK + (3 + p) * BLK, p ? 4096 : 16384);
            bulk_commit(); bulk_wait0_read();
            mbar_arrive(BAR(BR_FREE) + 8 * p);
          }
          __syncwarp();
        }
        if (elect_one()) { bulk_wait0(); st_rlx(FLAG(2, r, c), epoch); TS(33); }
        __syncwarp();
        if (!early) poll_all(FLAG(2, lane & 15, c), epoch);
        if (EN_ATT) mbar_wait(BAR(BR_OEMPTY), 0);
        #pragma unroll 1
        for (int n = 0; n < 64; n++) {
          if (elect_one()) {
            mbar_expect_tx(BAR(BR_YIN), 20480);
            tma2d(sb + OFF_EXTRA, &prm.m[M_SA], BAR(BR_YIN), r * 128, 640 + c * 80);
            tma2d(sb + OFF_EXTRA + 10240, &prm.m[M_SA], BAR(BR_YIN), r * 128 + 64, 640 + c * 80);
            TS(34);
          }
          __syncwarp();
          if (EN_ATT) mbar_wait(BAR(BR_OEMPTY + 3), 0);
          mbar_wait(BAR(BR_YIN), n & 1);
          if (lane == 0) TS(38);
          if (!y_transpose(sb, 4, lane, (epoch & 1u) * 0x10001u)) break;
          FIXCNT
        }
      if (elect_one()) {
        TS(39);
        tma2d_st(&prm.m[M_OUT], sb + SLOT(3), c * 80, r * 128);
        bulk_commit(); bulk_wait0_read();
        TS(35); DUMP(30, 40); DUMP(0, 1);
      }
      }
      }
    }
  } else {
  if (wg < 2) {
    asm volatile("setmaxnreg.inc.sync.aligned.u32 160;");
    bar_sync(0, 512);
    if (EN_ATT) {
    float am[96], ar[24];
    {
      const bool lead = (rtid() & 127) == 0;
      constexpr uint64_t dr0 = mkdesc(SB0 + 12288, 1024, 256, 3);
      const uint64_t dbc = sw64 ? mkdesc(SB0, 2048, 512, 2) : mkdesc(SB0, 4096, 1024, 1);
      const uint32_t kst = __shfl_sync(0xffffffff, sw64 ? 64 : 128, 0), bh = __shfl_sync(0xffffffff, (uint32_t)(dbc >> 32), 0);
      const uint64_t db0 = desc2(__shfl_sync(0xffffffff, (uint32_t)dbc, 0), bh);
      uint32_t ph = 0;
      const int ln = rtid() & 31;
      const uint32_t xa = sb + OFF_X + (warp * 16 + (ln & 15)) * 128 + (((ln >> 4) ^ (ln & 7)) << 4);
      uint32_t A[8];
      mbar_wait(BAR(BR_FULL), 0);
      if (lead && wg == 0) TS(1);
      ldsm4(A, xa); ldsm4(A + 4, xa ^ 32);
      wg_fence();
      wg_rs48_tb(ar, A, dr0, 0); wg_rs192_tb(am, A, db0, 0);
      wg_commit();
      uint32_t wp = 0, fb = BAR(BR_FULL), xk = xa;
      #pragma unroll 1
      for (int kb = 1; kb < 20; kb++) {
        const uint64_t d0 = desc2((uint32_t)dr0 + wp + 32, dr0 >> 32), d1 = desc2((uint32_t)db0 + wp + kst, bh);
        const uint32_t eb = fb + 8 * (BR_EMPTY - BR_FULL);
        wp += W_SLOT >> 4; fb += 8;
        if (wp == 5 * (W_SLOT >> 4)) { wp = 0; fb = BAR(BR_FULL); ph ^= 1; }
        wg_fence();
        wg_rs48_tb(ar, A + 4, d0, 1);
        wg_rs192_tb(am, A + 4, d1, 1);
        wg_commit();
        xk ^= 64;
        if (!(kb & 1)) { xk += 16384; if (xk >= sb + OFF_BAR) xk -= 49152; }
        mbar_wait(fb, ph);
        wg_wait<1>();
        ldsm4(A, xk);
        wg_fence();
        wg_rs48_tb(ar, A, desc2((uint32_t)dr0 + wp, dr0 >> 32), 1);
        wg_rs192_tb(am, A, desc2((uint32_t)db0 + wp, bh), 1);
        wg_commit();
        wg_wait<1>();
        ldsm4(A + 4, xk ^ 32);
        if (lead && kb < 16) mbar_arrive(eb);
      }
      wg_fence();
      wg_rs48_tb(ar, A + 4, dr0 + 4 * (W_SLOT >> 4) + 32, 1);
      wg_rs192_tb(am, A + 4, desc2((uint32_t)db0 + 4 * (W_SLOT >> 4) + kst, bh), 1);
      wg_commit();
      wg_wait<0>();
      if (ln == 0) mbar_arrive(BAR(BR_GEMM));
      pin<96>(am); pin<24>(ar);
    }
    const int tid = rtid(), lane = tid & 31, tq = lane & 3;
    if (tid == 0) TS(2);
#define QV(j, e) ((j) < 8 ? am[4 * (j) + (e)] : ar[4 * ((j) - 8) + (e)])
#define KV_(j, e) ((j) < 8 ? am[32 + 4 * (j) + (e)] : ar[8 + 4 * ((j) - 8) + (e)])
#define VV(j, e) ((j) < 8 ? am[64 + 4 * (j) + (e)] : ar[16 + 4 * ((j) - 8) + (e)])
    {
      bar_sync(1, 256);
      const uint32_t ro = sb + (uint32_t)((warp * 16 + (lane & 15)) * 16);
      const int l0 = 2 * (c & 1) + (lane >> 4);
      const uint32_t ones = (tq == 0) ? 0x00003f80u : 0u;
#define PV(j) pack2(VV(j, 0), VV(j, 1)), pack2(VV(j, 2), VV(j, 3))
#define PK(j) pack2(phi(KV_(j, 0)), phi(KV_(j, 1))), pack2(phi(KV_(j, 2)), phi(KV_(j, 3)))
      stsm4(ro + OFF_V + (5 + 6 * (lane >> 4)) * 2048, ones, ones, ones, ones);
      #pragma unroll
      for (int j = 0; j < 10; j += 2) {
        const int l = (j == 8 && (c & 1)) ? l0 - 2 : l0 + j;
        stsm4(ro + OFF_V + (l + (l >= 5)) * 2048, PV(j), PV(j + 1));
        stsm4(ro + OFF_PK + l * 2048, PK(j), PK(j + 1));
      }
    }
    fence_async();
    bar_sync(1, 256);
    if (tid == 0) TS(3);
    mbar_wait(BAR(BR_EPOCH), 0);
    const unsigned epoch = lds32(sb + OFF_EPOCH);
    {
      float kv[24]; zero<24>(kv);
      constexpr uint64_t da = mkdesc(SB0 + OFF_PK, 128, 2048, 0), db = mkdesc(SB0 + OFF_V, 128, 2048, 0);
      wg_fence();
      #pragma unroll
      for (int s = 0; s < 8; s++) wg_ss48_tt(kv, desc2((uint32_t)da + wg * 640 + s * 16, da >> 32), desc2((uint32_t)db + wg * 768 + s * 16, db >> 32), s != 0);
      wg_commit();
      wg_wait<0>();
      pin<24>(kv);
      if (tid == 0) TS(15);
      if (w4 < 3) {
        const uint32_t wb = sb + OFF_KVS + (wg * 3 + w4) * 1536 + (lane & 15) * 96;
        #pragma unroll
        for (int j = 0; j < 6; j += 2)
          stsm4(wb + (j + (lane >> 4)) * 16, pack2(kv[4 * j], kv[4 * j + 1]), pack2(kv[4 * j + 2], kv[4 * j + 3]),
                pack2(kv[4 * j + 4], kv[4 * j + 5]), pack2(kv[4 * j + 6], kv[4 * j + 7]));
        __syncwarp();
        const int dl = w4 * 16 + (lane & 15), hl = dl >= 20;
        uint32_t v[4], z[4];
        lds128(v, wb + (3 * hl + (lane >> 4)) * 16);
        lds64(z, wb + 32 + 8 * hl); z[2] = lds32(wb + 80); z[3] = epoch & 1u;
        if (dl < 40) {
          uint4* dst = &g_kvp[(c * 16 + r) * 240 + wg * 40 + dl];
          v[3] = (v[3] & ~1u) | z[3];
          st128_rlx(dst + (lane >> 4) * 80, v);
          if (lane < 16) st128_rlx(dst + 160, z);
        }
      }
    }
    bar_sync(1, 256);
    if (tid == 0) { st_rlx(FLAG(0, r, c), epoch); mbar_arrive(BAR(BR_PUB)); TS(4); }
    const int kvi = (tid >= 80) + (tid >= 160) + (tid >= 240), kd = tid - 80 * kvi;
    const int khd = kd / 20, kt0 = 5 * (khd >> 1) + 2 * (khd & 1);
    const uint32_t rb = sb + OFF_KVB + kd * 16;
    if (kvi < 3) {
      #pragma unroll 1
      for (int m = kvi; m < 7; m += 3) { const int q = kt0 + 3 + m; sts128(rb + (q >= 10 ? q - 10 : q) * 1280, 0, 0, 0, 0); }
    }
    uint32_t qa[20];
    {
      const float sc = 1.44269504089f + __uint_as_float(lds32(sb + OFF_EPOCH) ^ epoch);
      #pragma unroll
      for (int j = 0; j < 10; j++) { qa[2 * j] = pack2(phi(QV(j, 0), sc), phi(QV(j, 1), sc)); qa[2 * j + 1] = pack2(phi(QV(j, 2), sc), phi(QV(j, 3), sc)); }
    }
    if (tid == 0) TS(5);
    if (warp == 7) mbar_wait(BAR(BR_KVP), 0);
    bar_sync(1, 256);
    if (tid == 0) TS(6);
    if (kvi < 3) {
      float s[8];
      zero<8>(s);
      uint32_t bad = 0;
      #pragma unroll 4
      for (int i = 0; i < 16; i += 2) {
        uint32_t w[4], x[4];
        lds128(w, sb + OFF_KVP + tid * 16 + i * 3840); lds128(x, sb + OFF_KVP + tid * 16 + i * 3840 + 3840);
        bad |= (w[3] ^ epoch) | (x[3] ^ epoch);
        #pragma unroll
        for (int e = 0; e < 4; e++) {
          asm("add.rn.bf16x2 %0, %0, %1;" : "+r"(w[e]) : "r"(x[e]));
          s[2 * e] += bf_lo(w[e]); s[2 * e + 1] += bf_hi(w[e]);
        }
      }
      if (__builtin_expect(bad & 1u, 0)) {
        zero<8>(s);
        #pragma unroll 1
        for (int i = 0; i < 16; i++) {
          uint32_t w[4] = {0, 0, 0, ~epoch};
          fix128_w3(w, &g_kvp[(c * 16 + i) * 240 + tid], epoch, 1u);
          #pragma unroll
          for (int e = 0; e < 4; e++) { s[2 * e] += bf_lo(w[e]); s[2 * e + 1] += bf_hi(w[e]); }
        }
        FIXCNT
      }
      const uint32_t p0 = pack2(s[0], s[1]), p1 = pack2(s[2], s[3]), p2 = pack2(s[4], s[5]), p3 = pack2(s[6], s[7]);
      if (kvi < 2) sts128(rb + (kt0 + (khd & 1) + kvi) * 1280, p0, p1, p2, p3);
      else {
        const bool od = khd & 1;
        sts128(rb + (5 * (khd >> 1) + 2) * 1280, od ? 0u : p0, od ? 0u : p1, od ? p0 : 0u, od ? p1 : 0u);
        const uint32_t zz = (p2 & 0xffffu) << (16 * (khd & 1));
        sts128(rb + 10 * 1280, khd < 2 ? zz : 0u, khd < 2 ? 0u : zz, 0u, 0u);
      }
    }
    fence_async();
    bar_sync(1, 256);
    if (tid == 0) TS(7);
    {
      float oa[44]; zero<44>(oa);
      constexpr uint64_t db = mkdesc(SB0 + OFF_KVB, 128, 1280, 0);
      wg_fence();
      #pragma unroll
      for (int s = 0; s < 5; s++) wg_rs88_tb(oa, &qa[4 * s], desc2((uint32_t)db + ((s == 4 && (c & 1)) ? 0 : (s + (c & 1)) * 16), db >> 32), s != 0);
      wg_commit();
      wg_wait<0>();
      pin<44>(oa);
      if (tid == 0) TS(13);
      float rc[4], rd[2][4];
      #pragma unroll
      for (int e = 0; e < 4; e++) asm("rcp.approx.ftz.f32 %0, %1;" : "=f"(rc[e]) : "f"(oa[40 + e] + 1e-6f));
      #pragma unroll
      for (int h = 0; h < 4; h++) {
        rd[0][h] = __shfl_sync(0xffffffff, rc[h & 1], (lane & 28) | (h >> 1));
        rd[1][h] = __shfl_sync(0xffffffff, rc[2 + (h & 1)], (lane & 28) | (h >> 1));
      }
      #pragma unroll
      for (int j = 0; j < 10; j++) {
        #pragma unroll
        for (int h = 0; h < 2; h++) {
          float f;
          if (j == 2) f = tq < 2 ? rd[h][0] : rd[h][1];
          else if (j == 7) f = tq < 2 ? rd[h][2] : rd[h][3];
          else f = rd[h][(8 * j) / 20];
          qa[2 * j + h] = pack2(oa[4 * j + 2 * h] * f, oa[4 * j + 2 * h + 1] * f);
        }
      }
      const uint32_t m0 = (lane & 7) == ((2 * w4) & 7), m1 = (lane & 7) == 2 * w4 + 1;
      const uint32_t oa_ = sb + OFF_EXTRA + (lane >> 4) * 2048 + (warp * 16 + (lane & 15)) * 16;
      bar_sync(1, 256);
#define TAG(v, m) (((v) & ~(m)) | (epoch & (m)))
      #pragma unroll
      for (int s = 0; s < 5; s++) stsm4(oa_ + s * 4096, TAG(qa[4 * s], m0), TAG(qa[4 * s + 1], m1), TAG(qa[4 * s + 2], m0), TAG(qa[4 * s + 3], m1));
    }
    fence_async();
    __syncwarp();
    if (lane == 0) mbar_arrive(BAR(BR_OSTG));
    if (tid == 0) TS(8);
    }
    asm volatile("setmaxnreg.dec.sync.aligned.u32 136;");
  } else {
    const int g = lane >> 2, tq = lane & 3, t7 = tid & 127;
    asm volatile("bar.arrive 0, 512;" ::: "memory");
    if (EN_SSM) {
    {
      #pragma unroll 1
      for (int k = 0; k < 4; k++) {
        const uint32_t z = sb + OFF_BLK + k * BLK + t7 * 16;
        sts128(z + B_TBL, 0, 0, 0, 0); sts128(z + B_TBL + 2048, 0, 0, 0, 0);
      }
      const uint32_t ea = sb + OFF_BLK + (2 + (w4 & 1)) * BLK + (lane >> 4) * 7168 + ((lane >> 3) & 1) * 256 + (lane & 7) * 16 + (w4 >> 1) * 2048;
      constexpr uint64_t dE = mkdesc(SB0 + OFF_BLK + 2 * BLK, 128, 512, 0);
      const uint32_t xa = sb + OFF_BLK + 18560 + t7 * 8, xr_ = sb + OFF_BLK + 18560 + (t7 ^ 64) * 8;
      uint32_t pr[5][2];
      #pragma unroll
      for (int q = 0; q < 5; q++) {
        #pragma unroll
        for (int e = 0; e < 2; e++) pr[q][e] = __byte_perm(raw[q][e], __shfl_xor_sync(0xffffffff, raw[q][e], 1), (lane & 1) ? 0x3276 : 0x5410);
        const uint32_t m = __reduce_max_sync(0xffffffff, max(raw[q][1] & 0x7fffu, (raw[q][1] >> 16) & 0x7fffu));
        if (lane == 0) sts32(sb + OFF_EPOCH + 64 + q * 16 + w4 * 4, m);
      }
      bar_sync(4, 128);
      if (t7 == 0) TS(40);
      const int j = (w4 & 1) * 16 + (w4 >> 1) * 8 + g, i2 = tq < 2 ? 64 * tq + j : 32 * (tq - 2) + j;
      const uint32_t e2 = B_TBL + 4 * (tq < 2 ? T_F3 + (((i2 - 1) & 1) ? 80 : 0) + ((i2 - 1) >> 1) + 16 : T_F2 + (i2 & 1) * 96 + (i2 >> 1));
      const uint32_t e1 = tq < 2 ? (i2 ? e2 - 64 : B_TBL + 4 * (T_F2 + 175)) : B_TBL + 4 * (i2 ? T_F2 + ((2 * i2 - 1) & 3) * 48 + ((2 * i2 - 1) >> 2) : 16 + 511);
      const uint32_t e0 = B_TBL + (16 + 8 * j + 2 * tq) * 4;
      const float dtl = bf_round(expf(bf_lo(pd)));
      float hd[9];
      auto head = [&](int q) {
        const uint32_t pa0 = pr[0][0], pc0 = pr[0][1];
        const float dt = __shfl_sync(0xffffffff, dtl, q);
        #pragma unroll
        for (int e = 0; e < 2; e++) { pr[0][e] = pr[1][e]; pr[1][e] = pr[2][e]; pr[2][e] = pr[3][e]; pr[3][e] = pr[4][e]; }
        uint32_t mm[4];
        lds128(mm, sb + OFF_EPOCH + 64 + q * 16);
        const uint32_t ex = min(max(max(max(mm[0], mm[1]), max(mm[2], mm[3])) >> 7, 1u), 253u);
        const float sc = __uint_as_float((254u - ex) << 23);
        const float lr = -bf_round(expf(bf_lo(pa0))) * dt * 1.44269504089f;
        const float tn = bf_hi(pa0) * dt * 0.15915494309f;
        cexp_t(lr, -tn, hd[0], hd[1]);
        cexp_t(lr * 8.f, tn * 8.f, hd[2], hd[3]);
        cexp_t(lr * 64.f, tn * 64.f, hd[4], hd[5]);
        hd[6] = bf_lo(pc0) * sc; hd[7] = -bf_hi(pc0) * sc;
        hd[8] = 2.f * dt * __uint_as_float(ex << 23);
      };
      head(0);
      #pragma unroll 1
      for (int it = 0; it < 5; it++) {
        const int k = it;
        const uint32_t blk = sb + OFF_BLK + k * BLK;
        float fac = 0.f;
        float ka[24]; zero<24>(ka);
        {
          if (it == 4) {
            mbar_wait(BAR(BR_UOUT), 0);
            sts128(sb + OFF_UT + B_TBL + t7 * 16, 0, 0, 0, 0); sts128(sb + OFF_UT + B_TBL + 2048 + t7 * 16, 0, 0, 0, 0);
          }
          const uint32_t ga = ea + 4096 - (w4 >> 1) * 512;
#define PUT4(i, a, b, c_, d) sts128(((i) < 8 ? ea + ((i) >> 1) * 512 : ga + (((i) - 8) >> 1) * 512) + ((i) & 1) * 128, a, b, c_, d)
          float z2r, z2i, z4r, z4i, xr[8], xi[8], gr[8], gi[8], wr[9], wi[9];
          const float z1r = hd[0], z1i = hd[1];
          xr[1] = hd[2]; xi[1] = hd[3]; wr[0] = hd[4]; wi[0] = hd[5];
          fac = hd[8];
          xr[0] = 1.f; xi[0] = 0.f;
          csq(xr[1], xi[1], xr[2], xi[2]); cmul(xr[2], xi[2], xr[1], xi[1], xr[3], xi[3]);
          csq(xr[2], xi[2], xr[4], xi[4]);
          #pragma unroll
          for (int b = 1; b < 4; b++) cmul(xr[4], xi[4], xr[b], xi[b], xr[4 + b], xi[4 + b]);
          csq(wr[0], wi[0], wr[1], wi[1]); cmul(wr[1], wi[1], wr[0], wi[0], wr[2], wi[2]);
          csq(wr[1], wi[1], wr[3], wi[3]); csq(wr[3], wi[3], wr[4], wi[4]);
          cmul(wr[4], wi[4], wr[3], wi[3], wr[5], wi[5]); csq(wr[4], wi[4], wr[6], wi[6]);
          cmul(wr[6], wi[6], wr[4], wi[4], wr[7], wi[7]); csq(wr[6], wi[6], wr[8], wi[8]);
          uint32_t R[4], I[4], PR[4], PI[4];
          #pragma unroll
          for (int b = 0; b < 4; b++) { R[b] = packh(xr[2 * b], xr[2 * b + 1]); I[b] = packh(xi[2 * b], xi[2 * b + 1]); }
          PUT4(0, R[0], R[1], R[2], R[3]); PUT4(1, I[0], I[1], I[2], I[3]);
          #pragma unroll
          for (int i = 0; i < 3; i++) {
            const uint32_t z = packh(wr[i], wi[i]);
            #pragma unroll
            for (int b = 0; b < 4; b++) hcm2(R[b], I[b], z, PR[b], PI[b]);
            PUT4(2 * i + 2, PR[0], PR[1], PR[2], PR[3]); PUT4(2 * i + 3, PI[0], PI[1], PI[2], PI[3]);
          }
          gr[0] = hd[6]; gi[0] = hd[7];
          csq(z1r, z1i, z2r, z2i); csq(z2r, z2i, z4r, z4i);
          cmul(gr[0], gi[0], z1r, z1i, gr[1], gi[1]);
          cmul(gr[0], gi[0], z2r, z2i, gr[2], gi[2]); cmul(gr[1], gi[1], z2r, z2i, gr[3], gi[3]);
          #pragma unroll
          for (int b = 0; b < 4; b++) cmul(gr[b], gi[b], z4r, z4i, gr[4 + b], gi[4 + b]);
          PUT4(8, packh(gr[0], gr[1]), packh(gr[2], gr[3]), packh(gr[4], gr[5]), packh(gr[6], gr[7]));
          PUT4(9, packh(gi[0], gi[1]), packh(gi[2], gi[3]), packh(gi[4], gi[5]), packh(gi[6], gi[7]));
          {
            const uint32_t z = packh(wr[3], wi[3]), a4r = packh(gr[0], gr[4]), a4i = packh(gi[0], gi[4]);
            hcm2c(packh(gr[0], gr[2]), packh(gi[0], gi[2]), z, PR[0], PI[0]);
            hcm2c(packh(gr[4], gr[6]), packh(gi[4], gi[6]), z, PR[1], PI[1]);
            hcm2c(a4r, a4i, packh(wr[4], wi[4]), PR[2], PI[2]);
            hcm2c(a4r, a4i, packh(wr[5], wi[5]), PR[3], PI[3]);
            PUT4(10, PR[0], PR[1], PR[2], PR[3]); PUT4(11, PI[0], PI[1], PI[2], PI[3]);
            float hr, hi_;
            cmul(gr[0], gi[0], wr[3], -wi[3], hr, hi_);
            const uint32_t cr = packh(gr[0], hr), ci = packh(gi[0], hi_);
            #pragma unroll
            for (int i = 0; i < 3; i++) hcm2c(cr, ci, packh(wr[6 + i], wi[6 + i]), PR[i], PI[i]);
            PUT4(12, PR[0], PR[1], PR[2], 0u); PUT4(13, PI[0], PI[1], PI[2], 0u);
          }
          fence_async();
          bar_sync(4, 128);
          wg_fence();
          #pragma unroll
          for (int s = 0; s < 8; s++) {
            const uint64_t d = dE + (s >> 2) * (BLK >> 4) + ((s >> 1) & 1) * 448 + (s & 1) * 16;
            wg_ss48_tt_h(ka, d, d + 256, s != 0);
          }
          wg_commit();
        }
        const float dsk = bf_lo(__shfl_sync(0xffffffff, pd, 8 + (it & 7)));
        head(min(it + 1, 4));
        pin<9>(hd);
        wg_wait<0>();
        pin<24>(ka);
        float kk[6];
        const bool up = w4 >= 2;
        #pragma unroll
        for (int n = 0; n < 3; n++) {
          sts64f(xa + n * BLK, up ? ka[12 + 4 * n] : ka[4 * n + 2], up ? ka[13 + 4 * n] : ka[4 * n + 3]);
          kk[2 * n] = up ? ka[14 + 4 * n] : ka[4 * n]; kk[2 * n + 1] = up ? ka[15 + 4 * n] : ka[4 * n + 1];
        }
        if (it) bar_sync(4, 128); else bar_sync(8, 160);
          if (it == 4 && w4 == 0) {
            mbar_wait(BAR(BR_U), 0);
            if (elect_one()) {
              mbar_expect_tx(BAR(BR_U2), 8192);
              bulk_ld(blk - 2 * BLK, g_uy + (c * 80 + r * 5 + 2) * 2048, 4096, BAR(BR_U2)); bulk_ld(blk - BLK, g_uy + (c * 80 + r * 5 + 3) * 2048, 4096, BAR(BR_U2));
            }
            __syncwarp();
          }
        #pragma unroll
        for (int n = 0; n < 3; n++) {
          uint32_t o[2]; lds64(o, xr_ + n * BLK);
          kk[2 * n] = (kk[2 * n] + __uint_as_float(o[0])) * fac; kk[2 * n + 1] = (kk[2 * n + 1] + __uint_as_float(o[1])) * fac;
        }
        if (t7 == 0) kk[0] += dsk;
        {
          const uint32_t v = pack2(kk[1], kk[0]), vh = v >> 16;
          const uint32_t u = pack2(kk[2], kk[3]), w = pack2(kk[4], kk[5]), uu = pack2(kk[2], kk[2]), us = pack2(kk[3], kk[2]);
          const uint32_t x = tq < 2 ? w : u, xh = x >> 16;
          sts32(blk + e0 + 4, v); sts16(blk + e0, vh); sts16(blk + e0 + 10, v);
          sts16(blk + e1, x); sts16(blk + e1 + 6, x); sts16(blk + e2, xh); sts16(blk + e2 + 6, xh);
          if (tq < 2) {
            const uint32_t pb = blk + e0 + 1024 + 8 * tq;
            sts32(pb + 4, uu); sts32(pb + 8, us); sts16(pb + 14, us);
            if (i2) { sts16(pb - 4, u); sts32(pb, uu); }
          }
          if (i2 == 0) {
            const uint32_t tb = blk + B_TBL;
            if (tq == 0) { sts16(tb + (16 + 256) * 4, u); sts16(tb + (T_S + 3) * 4, w); sts32(tb + (T_S + 4) * 4, pack2(kk[4], kk[4])); sts16(tb + (T_S + 5) * 4 + 2, w); }
            else { sts32(tb + 528 * 4, uu); sts32(tb + 529 * 4, uu); sts32(tb + 530 * 4, uu); sts16(tb + 531 * 4 + 2, u); sts16(tb + (T_F3 + 80 + 63) * 4, w); }
          }
        }
        if (t7 == 0) TS(49 + it);
      }
    }
    asm volatile("setmaxnreg.inc.sync.aligned.u32 136;");
    if (t7 == 0) TS(41);
    bar_sync(4, 128);
    if (t7 == 0) mbar_arrive(BAR(BR_KS));
    }
  }
  const int tid = rtid(), lane = tid & 31, g = lane >> 2, tq = lane & 3, t7 = tid & 127;
  mbar_wait(BAR(BR_EPOCH), 0);
  const unsigned epoch = lds32(sb + OFF_EPOCH);
  const uint32_t ytag = (epoch & 1u) * 0x10001u, ym = lane < 4 ? 0x10001u : 0u;
  if (EN_SSM && wg != 1) {
    mbar_wait(BAR(BR_KS), 0);
    mbar_wait(BAR(BR_U), 0);
    if (EN_ATT) mbar_wait(BAR(BR_GEMM), 0);
    if (tid == 256) TS(42);
    {
      const int pass = wg >> 1;
      const int k = pass ? w4 : 4;
      if (k & 2) mbar_wait(BAR(BR_U2), 0);
      const uint32_t blk = sb + OFF_BLK + k * BLK, tb = blk + B_TBL + (uint32_t)((g - 2 * tq) * 4);
      float acc[16][4];
      zero<64>(&acc[0][0]);
      const int kl = 16 * (lane >> 4) + 2 * (lane & 7) + ((lane >> 3) & 1);
      {
        auto ubase = [&](int sh) { const int q = kl - 2 * sh; return blk + (uint32_t)((q * 16) ^ ((q * 2) & 0x10)); };
#define LDQ(A, sh) _Pragma("unroll") for (int m = 0; m < 4; m++) load_quad(A[m], tb + (16 + 16 * (sh) + 128 * m) * 4);
#define LDB(B, ub, h) _Pragma("unroll") for (int p = 0; p < 4; p++) ldsm4(B[p], (ub) + (4 * (h) + p) * 512);
#define MLO(A, B) _Pragma("unroll") for (int m = 0; m < 4; m++) _Pragma("unroll") for (int cc = 0; cc < 8; cc++) mma16816(acc[cc + m], A[m], &B[cc >> 1][(cc & 1) * 2]);
#define MHI(A, B) _Pragma("unroll") for (int m = 0; m < 4; m++) _Pragma("unroll") for (int cc = 0; cc < 8 - m; cc++) mma16816(acc[8 + cc + m], A[m], &B[cc >> 1][(cc & 1) * 2]);
        int p_ = pass ? 0 : w4;
        const int pe = pass ? 4 : w4 + 1;
        uint32_t A[4][4], A2[4][4], Bl[4][4], Bh[4][4];
        uint32_t ub = ubase(p_ + 4);
        LDQ(A, p_ + 4) LDB(Bl, ub, 0)
        #pragma unroll 1
        for (; p_ < pe; p_++) {
          LDB(Bh, ub, 1)
          MLO(A, Bl)
          ub = ubase(p_);
          LDQ(A2, p_) LDB(Bl, ub, 0)
          MHI(A, Bh)
          LDB(Bh, ub, 1)
          load_quad(A[0], tb + (16 + 512 + 16 * (p_ & 1)) * 4); load_quad(A[1], tb + (T_S + 16 * (p_ & 1)) * 4);
          MLO(A2, Bl)
          if (p_ < 2) {
            #pragma unroll
            for (int cc = 0; cc < 8; cc++) mma16816(acc[cc + 4], A[0], &Bl[cc >> 1][(cc & 1) * 2]);
            #pragma unroll
            for (int cc = 0; cc < 4; cc++) mma16816(acc[cc + 12], A[0], &Bh[cc >> 1][(cc & 1) * 2]);
            #pragma unroll
            for (int cc = 0; cc < 8; cc++) mma16816(acc[cc + 8], A[1], &Bl[cc >> 1][(cc & 1) * 2]);
          }
          const int pn = ((p_ + 1) & 3) + 4;
          ub = ubase(pn);
          LDQ(A, pn) LDB(Bl, ub, 0)
          MHI(A2, Bh)
        }
      }
      if (t7 == 0) TS(pass ? 60 : 16);
      mbar_wait(BAR(BR_DRDY), 0);
      {
        const int ih = (lane >> 3) & 1;
        const uint32_t dl = blk + B_D + (uint32_t)(((lane >> 4) * 8 + (lane & 7)) * 16);
        const uint32_t d0_ = dl + ih * 1552, d8_ = dl + (ih ? 0 : 1536), d3_ = dl + B_D7 + ih * 1024;
        auto cls2 = [&](uint32_t da, uint32_t ta) {
          uint32_t B[6][2], A[6][4];
          #pragma unroll
          for (int e = 0; e < 6; e++) { B[e][0] = lds32v(ta + (e + 4) * 32); B[e][1] = lds32v(ta + (e + 3) * 32); }
          #pragma unroll
          for (int kk = 0; kk < 6; kk++) ldsm4t(A[kk], da + kk * 256);
          #pragma unroll
          for (int e = 0; e < 6; e++)
            #pragma unroll
            for (int kk = 0; kk < 6; kk++) if (2 * kk + e + 4 < 16) mma16816(acc[2 * kk + e + 4], A[kk], B[e]);
        };
        auto cls3 = [&](uint32_t da, uint32_t ta) {
          uint32_t B[8][2], A[4][4];
          #pragma unroll
          for (int e = 0; e < 8; e++) { B[e][0] = lds32v(ta + (e + 8) * 32); B[e][1] = lds32v(ta + (e + 7) * 32); }
          #pragma unroll
          for (int kk = 0; kk < 4; kk++) ldsm4t(A[kk], da + kk * 256);
          #pragma unroll
          for (int kk = 0; kk < 4; kk++)
            #pragma unroll
            for (int e = 0; e < 8; e++) if (2 * kk + e + 8 < 16) mma16816(acc[2 * kk + e + 8], A[kk], B[e]);
        };
        if (pass) {
          #pragma unroll 1
          for (int a = 0; a < 2; a++) {
            cls2(d0_ + a * B_D5, tb + (T_F2 + 48 * a - 32) * 4);
            cls2(d8_ + a * B_D5, tb + (T_F2 + 48 * a + 64) * 4);
            cls3(d3_ + a * 2048, tb + (T_F3 + 80 * a - 64) * 4);
          }
        } else {
          cls2(((w4 & 2) ? d8_ : d0_) + (w4 & 1) * B_D5, tb + (T_F2 + 48 * w4 - 32) * 4);
          if (w4 >= 2) cls3(d3_ + (w4 - 2) * 2048, tb + (T_F3 + 80 * (w4 - 2) - 64) * 4);
        }
      }
      if (t7 == 0) TS(pass ? 61 : 17);
      const uint32_t ya = (pass ? sb + OFF_BLK + 3 * BLK + w4 * 4096 : blk) + (uint32_t)((kl * 16) ^ ((kl * 2) & 0x10));
#define YTAG(v) (((v) & ~ym) | (ytag & ym))
#define STY(p) stsm4t(ya + (p) * 512, YTAG(pack2(acc[2 * (p)][0], acc[2 * (p)][1])), pack2(acc[2 * (p)][2], acc[2 * (p)][3]), \
                      YTAG(pack2(acc[2 * (p) + 1][0], acc[2 * (p) + 1][1])), pack2(acc[2 * (p) + 1][2], acc[2 * (p) + 1][3]))
      if (pass == 0) {
        const uint32_t xw = blk + 4096 + w4 * 4096 + lane * 16, xr = blk + 4096 + w4 * 1024 + lane * 16;
        #pragma unroll
        for (int h = 0; h < 2; h++) {
          bar_sync(2, 128);
          #pragma unroll
          for (int i = 0; i < 8; i++)
            sts128(xw + i * 512, __float_as_uint(acc[8 * h + i][0]), __float_as_uint(acc[8 * h + i][1]), __float_as_uint(acc[8 * h + i][2]), __float_as_uint(acc[8 * h + i][3]));
          bar_sync(2, 128);
          float y[8];
          #pragma unroll
          for (int i = 0; i < 8; i++) {
            uint32_t o[4]; lds128(o, xr + (i >> 1) * 4096 + (i & 1) * 512);
            #pragma unroll
            for (int e = 0; e < 4; e++) y[4 * (i & 1) + e] = i < 2 ? __uint_as_float(o[e]) : y[4 * (i & 1) + e] + __uint_as_float(o[e]);
          }
          stsm4t(ya + (4 * h + w4) * 512, YTAG(pack2(y[0], y[1])), pack2(y[2], y[3]), YTAG(pack2(y[4], y[5])), pack2(y[6], y[7]));
        }
      } else {
        fence_async();
        bar_sync(4, 128);
        if (t7 == 0) mbar_arrive(BAR(BR_KS + 1));
        #pragma unroll
        for (int p = 0; p < 8; p++) STY(p);
      }
      fence_async();
      __syncwarp();
      if (lane == 0) mbar_arrive(BAR(BR_Y + 1) - 8 * pass);
      if (t7 == 0) TS(pass ? 62 : 18);
    }
  }
  if (wg < 2) {
    if (EN_ATT) {
    float oc[40]; zero<40>(oc);
    {
      constexpr uint64_t dw0 = mkdesc(SB0, OFF_WOR, 1024, 1), da0 = mkdesc(SB0, 2048, 128, 0);
      const uint32_t ck = sb + tid * 32 + ((lane >> 2) << 2), ck2 = ck + (wg ? 0 : 16384);
      uint32_t bad = 0;
      auto tile = [&](int i, uint32_t so) {
        const uint32_t al = (uint32_t)da0 + wg * 64 + (so >> 4), wl = (uint32_t)dw0 + i * 640 - (i >> 1) * (1278 << 16);
        wg_fence();
        #pragma unroll
        for (int s = 0; s < 5; s++) wg_ss80_tb(oc, desc2(al + s * 256, da0 >> 32), desc2(wl + s * 128, dw0 >> 32), (i | s) != 0);
        wg_commit();
        bad |= (lds32(ck + so) ^ epoch) | (lds32(ck + so + 8192) ^ epoch) | (lds32(ck2 + so) ^ epoch);
      };
      if (w4 == 0) {
        if (EN_SSM) mbar_wait(BAR(BR_Y), 0);
        mbar_wait(BAR(BR_WO), 0);
      }
      bar_sync(1, 256);
      if (tid == 0) TS(9);
      tile(0, SLOT(0));
      #pragma unroll 1
      for (int i = 1; i < 8; i++) {
        mbar_wait(BAR(BR_OFULL) + 8 * i, 0);
        tile(i, SLOT(i));
        wg_wait<1>();
        if (lane == 0) mbar_arrive(BAR(BR_OEMPTY - 1) + 8 * i);
      }
      #pragma unroll 1
      for (int n = 0; n < 56; n++) {
        const int i = n & 7;
        if (i == 0) {
          uint32_t any;
          asm volatile("{\n.reg .pred p;\nsetp.ne.u32 p, %1, 0;\nbarrier.red.or.pred p, 1, 256, p;\nselp.u32 %0, 1, 0, p;\n}" : "=r"(any) : "r"(bad & 1u) : "memory");
          if (!any) break;
          bad = 0;
          FIXCNT
        }
        wg_wait<0>();
        bar_sync(1, 256);
        if (tid == 0) { mbar_expect_tx(BAR(BR_RETRY), 20480); bulk_ld(sb + SLOT(2), &g_o[(r * 8 + CHUNK(i)) * 1280], 20480, BAR(BR_RETRY)); }
        mbar_wait(BAR(BR_RETRY), n & 1);
        tile(i, SLOT(2));
      }
      wg_wait<0>();
      pin<40>(oc);
    }
    if (tid == 0) TS(10);
    {
      const int row = w4 * 16 + (lane & 15);
      const uint32_t ob = sb + OFF_BLK + 3 * BLK + wg * 10240;
      #pragma unroll
      for (int j = 0; j < 8; j += 2)
        stsm4(ob + row * 128 + (((j + (lane >> 4)) ^ (row & 7)) << 4), pack2(oc[4 * j], oc[4 * j + 1]), pack2(oc[4 * j + 2], oc[4 * j + 3]),
              pack2(oc[4 * j + 4], oc[4 * j + 5]), pack2(oc[4 * j + 6], oc[4 * j + 7]));
      stsm4(ob + 8192 + row * 32 + (lane >> 4) * 16, pack2(oc[32], oc[33]), pack2(oc[34], oc[35]), pack2(oc[36], oc[37]), pack2(oc[38], oc[39]));
      fence_async();
      bar_sync(2 + wg, 128);
      if (w4 == 0 && elect_one()) {
        tma2d_st(&prm.m[M_O64], ob, 640 + c * 64, r * 128 + wg * 64);
        tma2d_st(&prm.m[M_O16], ob + 8192, 1152 + c * 16, r * 128 + wg * 64);
        bulk_commit(); bulk_wait0_read();
        if (wg == 0) { TS(11); DUMP(0, 20); }
      }
    }
    }
  } else if (EN_SSM) {
    if (t7 == 0) DUMP(40, 64);
    #pragma unroll 1
    for (int n = 0; n < 64; n++) if (!y_transpose(sb, w4, lane, ytag)) break;
  }
  }
}

typedef CUresult (*EncFn)(CUtensorMap*, CUtensorMapDataType, cuuint32_t, void*, const cuuint64_t*, const cuuint64_t*, const cuuint32_t*,
                          const cuuint32_t*, CUtensorMapInterleave, CUtensorMapSwizzle, CUtensorMapL2promotion, CUtensorMapFloatOOBfill);
static void mkmap(EncFn enc, CUtensorMap* m, const void* base, int rank, const cuuint64_t* dims, const cuuint64_t* strides, const cuuint32_t* box, CUtensorMapSwizzle swz) {
  cuuint32_t es[5] = {1, 1, 1, 1, 1};
  enc(m, CU_TENSOR_MAP_DATA_TYPE_BFLOAT16, rank, const_cast<void*>(base), dims, strides, box, es, CU_TENSOR_MAP_INTERLEAVE_NONE, swz,
      CU_TENSOR_MAP_L2_PROMOTION_L2_128B, CU_TENSOR_MAP_FLOAT_OOB_FILL_NONE);
}

extern "C" void kernel_launch(void* const* d_in, const int* in_sizes, int n_in, void* d_out, int out_size) {
  void* fn = nullptr; cudaDriverEntryPointQueryResult qr;
  cudaGetDriverEntryPoint("cuTensorMapEncodeTiled", &fn, cudaEnableDefault, &qr);
  EncFn enc = (EncFn)fn;
  void* uy = nullptr; cudaGetSymbolAddress(&uy, g_uy);
  const cuuint64_t dx[2] = {640, 2048}, sx[1] = {1280};
  const cuuint32_t bx[2] = {64, 128}, bu[2] = {80, 128};
  const cuuint64_t dw[3] = {640, 640, 3}, sw[2] = {3840, 1280};
  const cuuint32_t br[3] = {16, 32, 3};
  const cuuint64_t dwa[4] = {64, 640, 10, 3}, swa[3] = {3840, 128, 1280}, dwb[4] = {32, 640, 20, 3}, swb[3] = {3840, 64, 1280};
  const cuuint32_t bwa[4] = {64, 32, 1, 3}, bwb[4] = {32, 32, 2, 3};
  const cuuint64_t dwo[2] = {640, 640};
  const cuuint32_t bwo[2] = {64, 80}, bo64[2] = {64, 64}, bo16[2] = {16, 64};
  const cuuint64_t dsa[2] = {2048, 1280}, ssa[1] = {4096};
  const cuuint32_t bsa[2] = {64, 80};
  const cuuint64_t dout[2] = {1280, 2048}, sout[1] = {2560};
  Params prm;
  mkmap(enc, &prm.m[M_X], d_in[7], 2, dx, sx, bx, CU_TENSOR_MAP_SWIZZLE_128B);
  mkmap(enc, &prm.m[M_W128], d_in[8], 4, dwa, swa, bwa, CU_TENSOR_MAP_SWIZZLE_128B);
  mkmap(enc, &prm.m[M_W64], d_in[8], 4, dwb, swb, bwb, CU_TENSOR_MAP_SWIZZLE_64B);
  mkmap(enc, &prm.m[M_WR], d_in[8], 3, dw, sw, br, CU_TENSOR_MAP_SWIZZLE_32B);
  mkmap(enc, &prm.m[M_U], d_in[0], 2, dx, sx, bu, CU_TENSOR_MAP_SWIZZLE_NONE);
  mkmap(enc, &prm.m[M_WO], d_in[9], 2, dwo, sx, bwo, CU_TENSOR_MAP_SWIZZLE_128B);
  mkmap(enc, &prm.m[M_O64], d_out, 2, dout, sout, bo64, CU_TENSOR_MAP_SWIZZLE_128B);
  mkmap(enc, &prm.m[M_O16], d_out, 2, dout, sout, bo16, CU_TENSOR_MAP_SWIZZLE_NONE);
  mkmap(enc, &prm.m[M_SA], uy, 2, dsa, ssa, bsa, CU_TENSOR_MAP_SWIZZLE_128B);
  mkmap(enc, &prm.m[M_OUT], d_out, 2, dout, sout, bu, CU_TENSOR_MAP_SWIZZLE_NONE);
  prm.u = (const __nv_bfloat16*)d_in[0]; prm.wo = (const __nv_bfloat16*)d_in[9];
  for (int i = 0; i < 4; i++) prm.par[i] = (const __nv_bfloat16*)d_in[1 + i];
  prm.logdt = (const __nv_bfloat16*)d_in[5]; prm.dskip = (const __nv_bfloat16*)d_in[6];
  cudaFuncSetAttribute(fused_kernel, cudaFuncAttributeMaxDynamicSharedMemorySize, SMEM_BYTES);
  fused_kernel<<<128, 512, SMEM_BYTES, cudaStreamPerThread>>>(prm);
}
```

```cpp
#include <cuda_runtime.h>
#include <cuda_bf16.h>
#include <cuda_fp16.h>
#include <cuda.h>
#include <stdint.h>

#define EN_ATT 1
#define EN_SSM 1

__device__ __align__(1024) __nv_bfloat16 g_uy[2 * 640 * 2048];
__device__ __align__(128) uint4 g_kvp[8 * 16 * 240];
__device__ __align__(128) uint4 g_o[128 * 1280];
__device__ __align__(128) unsigned g_flag[5 * 128 * 32];
__device__ unsigned g_epoch[128];
#define TS(i) do {} while (0)
#define DUMP(lo, hi) do {} while (0)
#define FIXCNT

constexpr uint32_t SB0 = 1024;
constexpr uint32_t W_SLOT = 15360, OFF_X = 76800;
constexpr uint32_t OFF_WOR = 81920, OFF_KVP = 10240, OFF_KVS = 71680, OFF_PK = 10240, OFF_V = 30720, OFF_EXTRA = 102400, OFF_KVB = OFF_EXTRA, OFF_OWN = 61440;
constexpr uint32_t OFF_BAR = 125952, OFF_BLK = 128000, BLK = 20480;
constexpr uint32_t B_D = 4096, B_D5 = 3088, B_D7 = 6176, B_D9 = 8224, B_TBL = 14400;
constexpr int T_S = 576, T_F2 = 624, T_F3 = 816;
constexpr uint32_t OFF_UT = OFF_BLK + 4 * BLK;
constexpr uint32_t SMEM_BYTES = OFF_BLK + 5 * BLK;
enum { BR_FULL = 0, BR_WO = 5, BR_PUB = 6, BR_KVP = 7, BR_U = 8, BR_U2 = 9, BR_GEMM = 10, BR_UIN = 11, BR_YIN = 12, BR_EPOCH = 13,
       BR_FREE = 14, BR_RETRY = 16, BR_KS = 17, BR_UOUT = 19, BR_OFULL = 19  , BR_EMPTY = 27, BR_OEMPTY = 32, BR_OSTG = 39,
       BR_Y = 40, BR_DRDY = 42, BR_YIN2 = 43, BR_WO2 = 44, BR_COUNT = 46 };
constexpr uint32_t OFF_EPOCH = OFF_BAR + 8 * BR_COUNT;
enum { M_X, M_W128, M_W64, M_WR, M_U, M_WO, M_O64, M_O16, M_SA, M_SY, M_SZ, M_COUNT };

__device__ __forceinline__ long long clk64() { long long t; asm volatile("mov.u64 %0, %%clock64;" : "=l"(t) :: "memory"); return t; }
__device__ __forceinline__ uint32_t smem_u32(const void* p) { return (uint32_t)__cvta_generic_to_shared(p); }
__host__ __device__ constexpr uint64_t mkdesc(uint32_t addr, uint32_t lbo, uint32_t sbo, uint32_t swz) {
  return (uint64_t)((addr & 0x3FFFF) >> 4) | ((uint64_t)(lbo >> 4) << 16) | ((uint64_t)(sbo >> 4) << 32) | ((uint64_t)swz << 62);
}
__device__ __forceinline__ uint64_t desc2(uint32_t lo, uint32_t hi) { uint64_t d; asm("mov.b64 %0, {%1, %2};" : "=l"(d) : "r"(lo), "r"(hi)); return d; }
__device__ __forceinline__ void mbar_init(uint32_t bar, uint32_t cnt) { asm volatile("mbarrier.init.shared::cta.b64 [%0], %1;" :: "r"(bar), "r"(cnt) : "memory"); }
__device__ __forceinline__ void mbar_expect_tx(uint32_t bar, uint32_t bytes) { asm volatile("mbarrier.arrive.expect_tx.shared::cta.b64 _, [%0], %1;" :: "r"(bar), "r"(bytes) : "memory"); }
__device__ __forceinline__ void mbar_arrive(uint32_t bar) { asm volatile("mbarrier.arrive.shared::cta.b64 _, [%0];" :: "r"(bar) : "memory"); }
__device__ __forceinline__ void mbar_wait(uint32_t bar, uint32_t parity) {
  asm volatile("{\n.reg .pred p;\n.reg .u32 c;\nmov.u32 c, 0;\n"
    "WL:\nmbarrier.try_wait.parity.shared::cta.b64 p, [%0], %1;\n@p bra WD;\n"
    "add.u32 c, c, 1;\nsetp.lt.u32 p, c, 200000;\n@p bra WL;\nWD:\n}" :: "r"(bar), "r"(parity) : "memory");
}
__device__ __forceinline__ void poll_all(const unsigned* p, unsigned val) {
  asm volatile("{\n.reg .pred p;\n.reg .u32 c, v;\nmov.u32 c, 0;\n"
    "PL:\nld.relaxed.gpu.global.u32 v, [%0];\nsetp.eq.u32 p, v, %1;\nvote.sync.all.pred p, p, 0xffffffff;\n@p bra PD;\n"
    "add.u32 c, c, 1;\nsetp.lt.u32 p, c, 100000;\n@p bra PL;\nPD:\n}" :: "l"(p), "r"(val) : "memory");
}
__device__ __forceinline__ void poll_all_acq(const unsigned* p, unsigned val) {
  asm volatile("{\n.reg .pred p;\n.reg .u32 c, v;\nmov.u32 c, 0;\n"
    "PL:\nld.acquire.gpu.global.u32 v, [%0];\nsetp.eq.u32 p, v, %1;\nvote.sync.all.pred p, p, 0xffffffff;\n@p bra PD;\n"
    "nanosleep.u32 300;\nadd.u32 c, c, 1;\nsetp.lt.u32 p, c, 100000;\n@p bra PL;\nPD:\n}" :: "l"(p), "r"(val) : "memory");
}
__device__ __forceinline__ unsigned poll_bit(const unsigned* p, unsigned val, unsigned mask) {
  unsigned bal;
  asm volatile("{\n.reg .pred p;\n.reg .u32 c, v;\nmov.u32 c, 0;\n"
    "PL:\nld.relaxed.gpu.global.u32 v, [%1];\nsetp.eq.u32 p, v, %2;\nvote.sync.ballot.b32 %0, p, 0xffffffff;\n"
    "and.b32 v, %0, %3;\nsetp.ne.u32 p, v, 0;\n@p bra PD;\n"
    "add.u32 c, c, 1;\nsetp.lt.u32 p, c, 100000;\n@p bra PL;\nPD:\n}" : "=&r"(bal) : "l"(p), "r"(val), "r"(mask) : "memory");
  return bal;
}
__device__ __forceinline__ void fix128_w3(uint32_t* v, const void* p, uint32_t tag, uint32_t mask) {
  asm volatile("{\n.reg .pred p;\n.reg .u32 c, x;\n.reg .b128 t;\n.reg .b64 lo, hi;\nmov.u32 c, 0;\n"
    "FL:\nxor.b32 x, %3, %5;\nand.b32 x, x, %6;\nsetp.eq.u32 p, x, 0;\n@p bra FD;\n"
    "ld.relaxed.gpu.global.b128 t, [%4];\nmov.b128 {lo, hi}, t;\nmov.b64 {%0, %1}, lo;\nmov.b64 {%2, %3}, hi;\n"
    "add.u32 c, c, 1;\nsetp.lt.u32 p, c, 100000;\n@p bra FL;\nFD:\n}"
    : "+r"(v[0]), "+r"(v[1]), "+r"(v[2]), "+r"(v[3]) : "l"(p), "r"(tag), "r"(mask) : "memory");
}
__device__ __forceinline__ bool elect_one() {
  uint32_t p; asm volatile("{\n.reg .pred P;\nelect.sync _|P, 0xffffffff;\nselp.u32 %0, 1, 0, P;\n}" : "=r"(p)); return p;
}
__device__ __forceinline__ void bar_sync(int id, int n) { asm volatile("bar.sync %0, %1;" :: "r"(id), "r"(n) : "memory"); }
__device__ __forceinline__ void fence_async() { asm volatile("fence.proxy.async.shared::cta;" ::: "memory"); }
__device__ __forceinline__ void fence_async_g() { asm volatile("fence.proxy.async.global;" ::: "memory"); }
__device__ __forceinline__ void tma2d(uint32_t dst, const CUtensorMap* m, uint32_t bar, int c0, int c1) {
  asm volatile("cp.async.bulk.tensor.2d.shared::cluster.global.mbarrier::complete_tx::bytes [%0], [%1, {%3, %4}], [%2];"
    :: "r"(dst), "l"(m), "r"(bar), "r"(c0), "r"(c1) : "memory");
}
__device__ __forceinline__ void tma3d(uint32_t dst, const CUtensorMap* m, uint32_t bar, int c0, int c1, int c2) {
  asm volatile("cp.async.bulk.tensor.3d.shared::cluster.global.mbarrier::complete_tx::bytes [%0], [%1, {%3, %4, %5}], [%2];"
    :: "r"(dst), "l"(m), "r"(bar), "r"(c0), "r"(c1), "r"(c2) : "memory");
}
__device__ __forceinline__ void tma4d(uint32_t dst, const CUtensorMap* m, uint32_t bar, int c0, int c1, int c2, int c3) {
  asm volatile("cp.async.bulk.tensor.4d.shared::cluster.global.mbarrier::complete_tx::bytes [%0], [%1, {%3, %4, %5, %6}], [%2];"
    :: "r"(dst), "l"(m), "r"(bar), "r"(c0), "r"(c1), "r"(c2), "r"(c3) : "memory");
}
__device__ __forceinline__ void tma2d_st(const CUtensorMap* m, uint32_t src, int c0, int c1) {
  asm volatile("cp.async.bulk.tensor.2d.global.shared::cta.bulk_group [%0, {%2, %3}], [%1];"
    :: "l"(m), "r"(src), "r"(c0), "r"(c1) : "memory");
}
__device__ __forceinline__ void bulk_ld(uint32_t dst, const void* src, uint32_t bytes, uint32_t bar) {
  asm volatile("cp.async.bulk.shared::cluster.global.mbarrier::complete_tx::bytes [%0], [%1], %2, [%3];"
    :: "r"(dst), "l"(src), "r"(bytes), "r"(bar) : "memory");
}
__device__ __forceinline__ void bulk_st(void* dst, uint32_t src, uint32_t bytes) {
  asm volatile("cp.async.bulk.global.shared::cta.bulk_group [%0], [%1], %2;" :: "l"(dst), "r"(src), "r"(bytes) : "memory");
}
__device__ __forceinline__ void bulk_commit() { asm volatile("cp.async.bulk.commit_group;" ::: "memory"); }
__device__ __forceinline__ void bulk_wait0() { asm volatile("cp.async.bulk.wait_group 0;" ::: "memory"); }
__device__ __forceinline__ void bulk_wait0_read() { asm volatile("cp.async.bulk.wait_group.read 0;" ::: "memory"); }
__device__ __forceinline__ unsigned ld_rlx(const unsigned* p) { unsigned v; asm volatile("ld.relaxed.gpu.global.u32 %0, [%1];" : "=r"(v) : "l"(p) : "memory"); return v; }
__device__ __forceinline__ unsigned ld_acq(const unsigned* p) { unsigned v; asm volatile("ld.acquire.gpu.global.u32 %0, [%1];" : "=r"(v) : "l"(p) : "memory"); return v; }
__device__ __forceinline__ void st_rlx(unsigned* p, unsigned v) { asm volatile("st.relaxed.gpu.global.u32 [%0], %1;" :: "l"(p), "r"(v) : "memory"); }
__device__ __forceinline__ void st_rel(unsigned* p, unsigned v) { asm volatile("st.release.gpu.global.u32 [%0], %1;" :: "l"(p), "r"(v) : "memory"); }
__device__ __forceinline__ void st128_rlx(void* p, const uint32_t* v) {
  asm volatile("{\n.reg .b128 t;\n.reg .b64 lo, hi;\nmov.b64 lo, {%1, %2};\nmov.b64 hi, {%3, %4};\nmov.b128 t, {lo, hi};\n"
    "st.relaxed.gpu.global.b128 [%0], t;\n}" :: "l"(p), "r"(v[0]), "r"(v[1]), "r"(v[2]), "r"(v[3]) : "memory");
}
__device__ __forceinline__ uint32_t lds32(uint32_t a) { uint32_t v; asm volatile("ld.shared.u32 %0, [%1];" : "=r"(v) : "r"(a) : "memory"); return v; }
__device__ __forceinline__ uint32_t lds32v(uint32_t a) { uint32_t v; asm volatile("ld.volatile.shared.u32 %0, [%1];" : "=r"(v) : "r"(a) : "memory"); return v; }
__device__ __forceinline__ void lds128(uint32_t* v, uint32_t a) { asm volatile("ld.shared.v4.u32 {%0,%1,%2,%3}, [%4];" : "=r"(v[0]), "=r"(v[1]), "=r"(v[2]), "=r"(v[3]) : "r"(a) : "memory"); }
__device__ __forceinline__ void sts32(uint32_t a, uint32_t v) { asm volatile("st.shared.u32 [%0], %1;" :: "r"(a), "r"(v) : "memory"); }
__device__ __forceinline__ void sts16(uint32_t a, uint32_t v) { asm volatile("st.shared.u16 [%0], %1;" :: "r"(a), "h"((uint16_t)v) : "memory"); }
__device__ __forceinline__ void sts64f(uint32_t a, float x, float y) { asm volatile("st.shared.v2.f32 [%0], {%1,%2};" :: "r"(a), "f"(x), "f"(y) : "memory"); }
__device__ __forceinline__ void sts128(uint32_t a, uint32_t x, uint32_t y, uint32_t z, uint32_t w) { asm volatile("st.shared.v4.u32 [%0], {%1,%2,%3,%4};" :: "r"(a), "r"(x), "r"(y), "r"(z), "r"(w) : "memory"); }
__device__ __forceinline__ void stsm4(uint32_t a, uint32_t r0, uint32_t r1, uint32_t r2, uint32_t r3) {
  asm volatile("stmatrix.sync.aligned.m8n8.x4.shared.b16 [%0], {%1,%2,%3,%4};" :: "r"(a), "r"(r0), "r"(r1), "r"(r2), "r"(r3) : "memory");
}
__device__ __forceinline__ void stsm4t(uint32_t a, uint32_t r0, uint32_t r1, uint32_t r2, uint32_t r3) {
  asm volatile("stmatrix.sync.aligned.m8n8.x4.trans.shared.b16 [%0], {%1,%2,%3,%4};" :: "r"(a), "r"(r0), "r"(r1), "r"(r2), "r"(r3) : "memory");
}
__device__ __forceinline__ void ldsm4t(uint32_t* r, uint32_t a) {
  asm volatile("ldmatrix.sync.aligned.m8n8.x4.trans.shared.b16 {%0,%1,%2,%3}, [%4];" : "=r"(r[0]), "=r"(r[1]), "=r"(r[2]), "=r"(r[3]) : "r"(a) : "memory");
}
__device__ __forceinline__ void ldsm4(uint32_t* r, uint32_t a) {
  asm volatile("ldmatrix.sync.aligned.m8n8.x4.shared.b16 {%0,%1,%2,%3}, [%4];" : "=r"(r[0]), "=r"(r[1]), "=r"(r[2]), "=r"(r[3]) : "r"(a) : "memory");
}
__device__ __forceinline__ void mma16816(float* d, const uint32_t* a, const uint32_t* b) {
  asm volatile("mma.sync.aligned.m16n8k16.row.col.f32.bf16.bf16.f32 {%0,%1,%2,%3}, {%4,%5,%6,%7}, {%8,%9}, {%0,%1,%2,%3};"
    : "+f"(d[0]), "+f"(d[1]), "+f"(d[2]), "+f"(d[3]) : "r"(a[0]), "r"(a[1]), "r"(a[2]), "r"(a[3]), "r"(b[0]), "r"(b[1]));
}
__device__ __forceinline__ uint32_t pack2(float lo, float hi) { uint32_t r; asm("cvt.rn.bf16x2.f32 %0, %1, %2;" : "=r"(r) : "f"(hi), "f"(lo)); return r; }
__device__ __forceinline__ uint32_t packh(float lo, float hi) { uint32_t r; asm("cvt.rn.f16x2.f32 %0, %1, %2;" : "=r"(r) : "f"(hi), "f"(lo)); return r; }
__device__ __forceinline__ void hcm2(uint32_t xr, uint32_t xi, uint32_t z, uint32_t& pr, uint32_t& pi) {
  const __half2 a = *reinterpret_cast<__half2*>(&xr), b = *reinterpret_cast<__half2*>(&xi), zz = *reinterpret_cast<__half2*>(&z);
  const __half2 re = __hfma2(__hneg2(b), __high2half2(zz), __hmul2(a, __low2half2(zz)));
  const __half2 im = __hfma2(a, __high2half2(zz), __hmul2(b, __low2half2(zz)));
  pr = *reinterpret_cast<const uint32_t*>(&re); pi = *reinterpret_cast<const uint32_t*>(&im);
}
__device__ __forceinline__ void hcm2c(uint32_t xr, uint32_t xi, uint32_t z, uint32_t& pr, uint32_t& pi) {
  const __half2 a = *reinterpret_cast<__half2*>(&xr), b = *reinterpret_cast<__half2*>(&xi), zz = *reinterpret_cast<__half2*>(&z);
  const __half2 re = __hfma2(b, __high2half2(zz), __hmul2(a, __low2half2(zz)));
  const __half2 im = __hfma2(__hneg2(a), __high2half2(zz), __hmul2(b, __low2half2(zz)));
  pr = *reinterpret_cast<const uint32_t*>(&re); pi = *reinterpret_cast<const uint32_t*>(&im);
}
__device__ __forceinline__ void lds64(uint32_t* v, uint32_t a) { asm volatile("ld.shared.v2.u32 {%0,%1}, [%2];" : "=r"(v[0]), "=r"(v[1]) : "r"(a) : "memory"); }
__device__ __forceinline__ float bf_lo(uint32_t v) { return __uint_as_float(v << 16); }
__device__ __forceinline__ float bf_hi(uint32_t v) { return __uint_as_float(v & 0xffff0000u); }
__device__ __forceinline__ float bf_round(float x) { return bf_lo(pack2(x, 0.f)); }
__device__ __forceinline__ float ex2(float x) { float r; asm("ex2.approx.ftz.f32 %0, %1;" : "=f"(r) : "f"(x)); return r; }
__device__ __forceinline__ float phi(float t, float l2e = 1.44269504089f) {
  float e = ex2(t * l2e) + 1e-6f;
  asm("{\n.reg .pred p;\nsetp.gt.f32 p, %1, 0f00000000;\n@p add.f32 %0, %1, 0f3F800008;\n}" : "+f"(e) : "f"(t));
  return e;
}
__device__ __forceinline__ void wg_fence() { asm volatile("wgmma.fence.sync.aligned;" ::: "memory"); }
__device__ __forceinline__ void wg_commit() { asm volatile("wgmma.commit_group.sync.aligned;" ::: "memory"); }
template <int N> __device__ __forceinline__ void wg_wait() { asm volatile("wgmma.wait_group.sync.aligned %0;" :: "n"(N) : "memory"); }
template <int N> __device__ __forceinline__ void pin(float* a) {
  #pragma unroll
  for (int i = 0; i < N; i++) asm volatile("" : "+f"(a[i]) :: "memory");
}
__device__ __forceinline__ int rtid() { int t; asm volatile("mov.u32 %0, %%tid.x;" : "=r"(t)); return t; }
template <int N> __device__ __forceinline__ void zero(float* a) {
  #pragma unroll
  for (int i = 0; i < N; i++) asm volatile("mov.b32 %0, 0;" : "=f"(a[i]));
}
__device__ __forceinline__ void cexp_t(float lg2mag, float turns, float& re, float& im) {
  float m = ex2(lg2mag);
  float fr = (turns - __fadd_rn(__fadd_rn(turns, 12582912.f), -12582912.f)) * 6.283185307f;
  re = m * __cosf(fr); im = m * __sinf(fr);
}
__device__ __forceinline__ void csq(float ar, float ai, float& cr, float& ci) {
  const float t = ar + ar;
  cr = fmaf(ar, ar, -ai * ai); ci = t * ai;
}
__device__ __forceinline__ void cmul(float ar, float ai, float br, float bi, float& cr, float& ci) {
  cr = fmaf(ar, br, -ai * bi); ci = fmaf(ar, bi, ai * br);
}

__device__ __forceinline__ void wg_ss48_tt(float* d, uint64_t da, uint64_t db, int scale_d) {
  asm volatile("{\n.reg .pred p;\nsetp.ne.b32 p, %26, 0;\n"
    "wgmma.mma_async.sync.aligned.m64n48k16.f32.bf16.bf16 "
    "{%0, %1, %2, %3, %4, %5, %6, %7, %8, %9, %10, %11, %12, %13, %14, %15, %16, %17, %18, %19, %20, %21, %22, %23}, %24, %25, p, 1, 1, 1, 1;\n}\n"
    : "+f"(d[0]), "+f"(d[1]), "+f"(d[2]), "+f"(d[3]), "+f"(d[4]), "+f"(d[5]), "+f"(d[6]), "+f"(d[7]), "+f"(d[8]), "+f"(d[9]), "+f"(d[10]), "+f"(d[11]), "+f"(d[12]), "+f"(d[13]), "+f"(d[14]), "+f"(d[15]), "+f"(d[16]), "+f"(d[17]), "+f"(d[18]), "+f"(d[19]), "+f"(d[20]), "+f"(d[21]), "+f"(d[22]), "+f"(d[23])
    : "l"(da), "l"(db), "r"(scale_d));
}
__device__ __forceinline__ void wg_rs88_tb(float* d, const uint32_t* a, uint64_t db, int scale_d) {
  asm volatile("{\n.reg .pred p;\nsetp.ne.b32 p, %49, 0;\n"
    "wgmma.mma_async.sync.aligned.m64n88k16.f32.bf16.bf16 "
    "{%0, %1, %2, %3, %4, %5, %6, %7, %8, %9, %10, %11, %12, %13, %14, %15, %16, %17, %18, %19, %20, %21, %22, %23, %24, %25, %26, %27, %28, %29, %30, %31, %32, %33, %34, %35, %36, %37, %38, %39, %40, %41, %42, %43}, {%44, %45, %46, %47}, %48, p, 1, 1, 1;\n}\n"
    : "+f"(d[0]), "+f"(d[1]), "+f"(d[2]), "+f"(d[3]), "+f"(d[4]), "+f"(d[5]), "+f"(d[6]), "+f"(d[7]), "+f"(d[8]), "+f"(d[9]), "+f"(d[10]), "+f"(d[11]), "+f"(d[12]), "+f"(d[13]), "+f"(d[14]), "+f"(d[15]), "+f"(d[16]), "+f"(d[17]), "+f"(d[18]), "+f"(d[19]), "+f"(d[20]), "+f"(d[21]), "+f"(d[22]), "+f"(d[23]), "+f"(d[24]), "+f"(d[25]), "+f"(d[26]), "+f"(d[27]), "+f"(d[28]), "+f"(d[29]), "+f"(d[30]), "+f"(d[31]), "+f"(d[32]), "+f"(d[33]), "+f"(d[34]), "+f"(d[35]), "+f"(d[36]), "+f"(d[37]), "+f"(d[38]), "+f"(d[39]), "+f"(d[40]), "+f"(d[41]), "+f"(d[42]), "+f"(d[43])
    : "r"(a[0]), "r"(a[1]), "r"(a[2]), "r"(a[3]), "l"(db), "r"(scale_d));
}
__device__ __forceinline__ void wg_ss80_tb(float* d, uint64_t da, uint64_t db, int scale_d) {
  asm volatile("{\n.reg .pred p;\nsetp.ne.b32 p, %42, 0;\n"
    "wgmma.mma_async.sync.aligned.m64n80k16.f32.bf16.bf16 "
    "{%0, %1, %2, %3, %4, %5, %6, %7, %8, %9, %10, %11, %12, %13, %14, %15, %16, %17, %18, %19, %20, %21, %22, %23, %24, %25, %26, %27, %28, %29, %30, %31, %32, %33, %34, %35, %36, %37, %38, %39}, %40, %41, p, 1, 1, 0, 1;\n}\n"
    : "+f"(d[0]), "+f"(d[1]), "+f"(d[2]), "+f"(d[3]), "+f"(d[4]), "+f"(d[5]), "+f"(d[6]), "+f"(d[7]), "+f"(d[8]), "+f"(d[9]), "+f"(d[10]), "+f"(d[11]), "+f"(d[12]), "+f"(d[13]), "+f"(d[14]), "+f"(d[15]), "+f"(d[16]), "+f"(d[17]), "+f"(d[18]), "+f"(d[19]), "+f"(d[20]), "+f"(d[21]), "+f"(d[22]), "+f"(d[23]), "+f"(d[24]), "+f"(d[25]), "+f"(d[26]), "+f"(d[27]), "+f"(d[28]), "+f"(d[29]), "+f"(d[30]), "+f"(d[31]), "+f"(d[32]), "+f"(d[33]), "+f"(d[34]), "+f"(d[35]), "+f"(d[36]), "+f"(d[37]), "+f"(d[38]), "+f"(d[39])
    : "l"(da), "l"(db), "r"(scale_d));
}
__device__ __forceinline__ void wg_ss48_tt_h(float* d, uint64_t da, uint64_t db, int scale_d) {
  asm volatile("{\n.reg .pred p;\nsetp.ne.b32 p, %26, 0;\n"
    "wgmma.mma_async.sync.aligned.m64n48k16.f32.f16.f16 "
    "{%0, %1, %2, %3, %4, %5, %6, %7, %8, %9, %10, %11, %12, %13, %14, %15, %16, %17, %18, %19, %20, %21, %22, %23}, %24, %25, p, 1, 1, 1, 1;\n}\n"
    : "+f"(d[0]), "+f"(d[1]), "+f"(d[2]), "+f"(d[3]), "+f"(d[4]), "+f"(d[5]), "+f"(d[6]), "+f"(d[7]), "+f"(d[8]), "+f"(d[9]), "+f"(d[10]), "+f"(d[11]), "+f"(d[12]), "+f"(d[13]), "+f"(d[14]), "+f"(d[15]), "+f"(d[16]), "+f"(d[17]), "+f"(d[18]), "+f"(d[19]), "+f"(d[20]), "+f"(d[21]), "+f"(d[22]), "+f"(d[23])
    : "l"(da), "l"(db), "r"(scale_d));
}
__device__ __forceinline__ void wg_rs192_tb(float* d, const uint32_t* a, uint64_t db, int scale_d) {
  asm volatile("{\n.reg .pred p;\nsetp.ne.b32 p, %101, 0;\n"
    "wgmma.mma_async.sync.aligned.m64n192k16.f32.bf16.bf16 "
    "{%0, %1, %2, %3, %4, %5, %6, %7, %8, %9, %10, %11, %12, %13, %14, %15, %16, %17, %18, %19, %20, %21, %22, %23, %24, %25, %26, %27, %28, %29, %30, %31, %32, %33, %34, %35, %36, %37, %38, %39, %40, %41, %42, %43, %44, %45, %46, %47, %48, %49, %50, %51, %52, %53, %54, %55, %56, %57, %58, %59, %60, %61, %62, %63, %64, %65, %66, %67, %68, %69, %70, %71, %72, %73, %74, %75, %76, %77, %78, %79, %80, %81, %82, %83, %84, %85, %86, %87, %88, %89, %90, %91, %92, %93, %94, %95}, {%96, %97, %98, %99}, %100, p, 1, 1, 1;\n}\n"
    : "+f"(d[0]), "+f"(d[1]), "+f"(d[2]), "+f"(d[3]), "+f"(d[4]), "+f"(d[5]), "+f"(d[6]), "+f"(d[7]), "+f"(d[8]), "+f"(d[9]), "+f"(d[10]), "+f"(d[11]), "+f"(d[12]), "+f"(d[13]), "+f"(d[14]), "+f"(d[15]), "+f"(d[16]), "+f"(d[17]), "+f"(d[18]), "+f"(d[19]), "+f"(d[20]), "+f"(d[21]), "+f"(d[22]), "+f"(d[23]), "+f"(d[24]), "+f"(d[25]), "+f"(d[26]), "+f"(d[27]), "+f"(d[28]), "+f"(d[29]), "+f"(d[30]), "+f"(d[31]), "+f"(d[32]), "+f"(d[33]), "+f"(d[34]), "+f"(d[35]), "+f"(d[36]), "+f"(d[37]), "+f"(d[38]), "+f"(d[39]), "+f"(d[40]), "+f"(d[41]), "+f"(d[42]), "+f"(d[43]), "+f"(d[44]), "+f"(d[45]), "+f"(d[46]), "+f"(d[47]), "+f"(d[48]), "+f"(d[49]), "+f"(d[50]), "+f"(d[51]), "+f"(d[52]), "+f"(d[53]), "+f"(d[54]), "+f"(d[55]), "+f"(d[56]), "+f"(d[57]), "+f"(d[58]), "+f"(d[59]), "+f"(d[60]), "+f"(d[61]), "+f"(d[62]), "+f"(d[63]), "+f"(d[64]), "+f"(d[65]), "+f"(d[66]), "+f"(d[67]), "+f"(d[68]), "+f"(d[69]), "+f"(d[70]), "+f"(d[71]), "+f"(d[72]), "+f"(d[73]), "+f"(d[74]), "+f"(d[75]), "+f"(d[76]), "+f"(d[77]), "+f"(d[78]), "+f"(d[79]), "+f"(d[80]), "+f"(d[81]), "+f"(d[82]), "+f"(d[83]), "+f"(d[84]), "+f"(d[85]), "+f"(d[86]), "+f"(d[87]), "+f"(d[88]), "+f"(d[89]), "+f"(d[90]), "+f"(d[91]), "+f"(d[92]), "+f"(d[93]), "+f"(d[94]), "+f"(d[95])
    : "r"(a[0]), "r"(a[1]), "r"(a[2]), "r"(a[3]), "l"(db), "r"(scale_d));
}
__device__ __forceinline__ void wg_rs48_tb(float* d, const uint32_t* a, uint64_t db, int scale_d) {
  asm volatile("{\n.reg .pred p;\nsetp.ne.b32 p, %29, 0;\n"
    "wgmma.mma_async.sync.aligned.m64n48k16.f32.bf16.bf16 "
    "{%0, %1, %2, %3, %4, %5, %6, %7, %8, %9, %10, %11, %12, %13, %14, %15, %16, %17, %18, %19, %20, %21, %22, %23}, {%24, %25, %26, %27}, %28, p, 1, 1, 1;\n}\n"
    : "+f"(d[0]), "+f"(d[1]), "+f"(d[2]), "+f"(d[3]), "+f"(d[4]), "+f"(d[5]), "+f"(d[6]), "+f"(d[7]), "+f"(d[8]), "+f"(d[9]), "+f"(d[10]), "+f"(d[11]), "+f"(d[12]), "+f"(d[13]), "+f"(d[14]), "+f"(d[15]), "+f"(d[16]), "+f"(d[17]), "+f"(d[18]), "+f"(d[19]), "+f"(d[20]), "+f"(d[21]), "+f"(d[22]), "+f"(d[23])
    : "r"(a[0]), "r"(a[1]), "r"(a[2]), "r"(a[3]), "l"(db), "r"(scale_d));
}

struct Params {
  const __nv_bfloat16 *par[4], *logdt, *dskip, *u, *wo;
  CUtensorMap m[M_COUNT];
};

#define CHUNK(i) ((c + (i)) & 7)
#define CHAN(k) (c * 80 + ((k) < 4 ? r * 4 + (k) : 64 + r))
#define FLAG(kind, rr, cc) (&g_flag[((kind) * 128 + (rr) * 8 + (cc)) * 32])
#define SLOT(i) ((i) == 0 ? OFF_OWN : OFF_BLK - 256 + ((i) > 5 ? (i) - 6 : (i) - 1) * BLK)
__device__ __forceinline__ void load_quad(uint32_t* A, uint32_t addr) {
  A[0] = lds32v(addr); A[1] = lds32v(addr + 32); A[2] = lds32v(addr - 32); A[3] = lds32v(addr);
}

__global__ void __launch_bounds__(512, 1) fused_kernel(const __grid_constant__ Params prm) {
  extern __shared__ unsigned char smem_raw[];
  uint32_t raw[5][2], pd;
  if ((threadIdx.x >> 7) == 2) {
    const int r = blockIdx.x >> 3, c = blockIdx.x & 7;
    #pragma unroll
    for (int e = 0; e < 2; e++) {
      const __nv_bfloat16* pp = prm.par[2 * e + (threadIdx.x & 1)] + (threadIdx.x & 126);
      #pragma unroll
      for (int q = 0; q < 5; q++) asm volatile("ld.global.nc.u32 %0, [%1];" : "=r"(raw[q][e]) : "l"(pp + CHAN(q) * 128));
    }
    asm volatile("ld.global.nc.u16 %0, [%1];" : "=r"(pd) : "l"(((threadIdx.x & 8) ? prm.dskip : prm.logdt) + CHAN(threadIdx.x & 7)));
  }
  constexpr uint32_t sb = SB0;
  const int tid = threadIdx.x, lane = tid & 31;
  const int warp = __shfl_sync(0xffffffff, tid >> 5, 0), wg = warp >> 2, w4 = warp & 3;
  const int cta = blockIdx.x, r = cta >> 3, c = cta & 7;
  if (smem_u32(smem_raw) != SB0) return;
#define BAR(i) (sb + OFF_BAR + 8 * (i))
  const bool sw64 = ((c + 1) & 2) != 0;

  const CUtensorMap* mwp = &prm.m[sw64 ? M_W64 : M_W128];
  const int mcol = (c * 80 + (c & 1) * 16) >> (sw64 ? 5 : 6), rcol = c * 80 + ((c & 1) ? 0 : 64);
  if (warp == 12 && elect_one()) {
    #pragma unroll
    for (int i = 0; i < 5; i++) mbar_init(BAR(BR_FULL + i), 1);
    asm volatile("fence.mbarrier_init.release.cluster;" ::: "memory");
    if (EN_ATT) {
      mbar_expect_tx(BAR(BR_FULL), W_SLOT + 16384);
      tma4d(sb, mwp, BAR(BR_FULL), 0, 0, mcol, 0);
      tma2d(sb + OFF_X, &prm.m[M_X], BAR(BR_FULL), 0, r * 128);
      tma3d(sb + 12288, &prm.m[M_WR], BAR(BR_FULL), rcol, 0, 0);
      mbar_expect_tx(BAR(BR_FULL + 1), W_SLOT);
      tma4d(sb + W_SLOT, mwp, BAR(BR_FULL + 1), 0, 32, mcol, 0);
      tma3d(sb + W_SLOT + 12288, &prm.m[M_WR], BAR(BR_FULL + 1), rcol, 32, 0);
      TS(24);
    }
  }
  if (warp == 13 && elect_one()) {
    asm volatile("prefetch.tensormap [%0];" :: "l"(&prm.m[M_X]) : "memory");
    asm volatile("prefetch.tensormap [%0];" :: "l"(&prm.m[M_WR]) : "memory");
  }
  if (wg == 3) {
    asm volatile("setmaxnreg.dec.sync.aligned.u32 56;");
    const int tid = rtid(), lane = tid & 31;
    if (warp == 12) {
      asm volatile("bar.arrive 0, 512;" ::: "memory");
      if (EN_ATT && elect_one()) {
        #pragma unroll
        for (int kb = 2; kb < 5; kb++) {
          mbar_expect_tx(BAR(BR_FULL + kb), (kb & 1) ? W_SLOT : W_SLOT + 16384);
          if (!(kb & 1)) tma2d(sb + OFF_X + kb * 8192, &prm.m[M_X], BAR(BR_FULL + kb), kb * 32, r * 128);
          tma4d(sb + kb * W_SLOT, mwp, BAR(BR_FULL + kb), 0, kb * 32, mcol, 0);
          tma3d(sb + kb * W_SLOT + 12288, &prm.m[M_WR], BAR(BR_FULL + kb), rcol, kb * 32, 0);
        }
      }
      bar_sync(6, 128);
      if (elect_one()) {
        if (EN_SSM) { mbar_expect_tx(BAR(BR_UIN), 20480); tma2d(sb + OFF_UT, &prm.m[M_U], BAR(BR_UIN), c * 80, r * 128); }
        if (EN_ATT) {
          uint32_t st = sb, fb = BAR(BR_FULL), ph = 0, xs = sb + OFF_X;
          #pragma unroll 1
          for (int k = 160; k < 640; k += 32) {
            mbar_wait(fb + 8 * (BR_EMPTY - BR_FULL), ph);
            mbar_expect_tx(fb, (k & 32) ? W_SLOT : W_SLOT + 16384);
            tma4d(st, mwp, fb, 0, k, mcol, 0);
            if (!(k & 32)) { tma2d(xs, &prm.m[M_X], fb, k, r * 128); xs += 16384; if (xs == sb + OFF_BAR) xs = sb + OFF_X; }
            tma3d(st + 12288, &prm.m[M_WR], fb, rcol, k, 0);
            st += W_SLOT; fb += 8;
            if (st == sb + OFF_X) { st = sb; fb = BAR(BR_FULL); ph ^= 1; }
          }
          asm volatile("cp.async.bulk.prefetch.L2.global [%0], 6400;" :: "l"(prm.wo + cta * 3200) : "memory");
        }
      }
      __syncwarp();
      if (EN_ATT) {
      mbar_wait(BAR(BR_EPOCH), 0);
      const unsigned epoch = lds32(sb + OFF_EPOCH);
      const unsigned* fo = FLAG(3, r, lane & 7);
      unsigned seen = __ballot_sync(0xffffffff, ld_rlx(lane < 16 ? fo : FLAG(0, lane & 15, c)) == epoch);
      mbar_wait(BAR(BR_GEMM), 0);
      if (elect_one()) {
        mbar_expect_tx(BAR(BR_WO), 6 * 10240);
        mbar_expect_tx(BAR(BR_WO2), 2 * 10240);
        mbar_expect_tx(BAR(BR_KVP), 61440);
      }
      {
        uint32_t ds = sb + OFF_WOR + (lane >> 3) * 128 + (((lane & 7) ^ (lane >> 3)) << 4);
        #pragma unroll 1
        for (int h = 0; h < 2; h++) {
          const int i = (lane & 6) + h;
          const char* gs = reinterpret_cast<const char*>(prm.wo) + (size_t)((lane >> 3) + CHUNK(i) * 80) * 1280 + 1024 + c * 32 + (lane & 1) * 16;
          #pragma unroll 2
          for (int q = 0; q < 20; q++) {
            asm volatile("cp.async.cg.shared.global [%0], [%1], 16;" :: "r"(ds), "l"(gs) : "memory");
            ds = (ds + 512) ^ 64; gs += 5120;
          }
        }
      }
      mbar_wait(BAR(BR_PUB), 0);
      if ((seen >> 16) != 0xffffu) poll_all(FLAG(0, lane & 15, c), epoch);
      if (elect_one()) { TS(23); bulk_ld(sb + OFF_KVP, &g_kvp[c * 16 * 240], 61440, BAR(BR_KVP)); }
      asm volatile("cp.async.wait_all;" ::: "memory");
      fence_async();
      mbar_arrive(BAR(BR_WO));
      mbar_wait(BAR(BR_OSTG), 0);
      if (elect_one()) {
        bulk_st(&g_o[cta * 1280], sb + OFF_OWN, 20480);
        bulk_commit();
        bulk_wait0();
        st_rlx(FLAG(3, r, c), epoch);
        TS(20);
        #pragma unroll 1
        for (int i = 0; i < 6; i++) tma2d(sb + i * 10240, &prm.m[M_WO], BAR(BR_WO), c * 64, CHUNK(i) * 80);
      }
      __syncwarp();
      #pragma unroll 1
      for (int i = 1; i < 8; i++) {
        const int src = CHUNK(i);
        if (!((seen >> src) & 1)) seen = poll_bit(fo, epoch, 1u << src);
        if (i == 6) {
          mbar_wait(BAR(BR_OEMPTY), 0);
          if (elect_one()) { tma2d(sb + OFF_OWN, &prm.m[M_WO], BAR(BR_WO2), c * 64, CHUNK(6) * 80); tma2d(sb + OFF_OWN + 10240, &prm.m[M_WO], BAR(BR_WO2), c * 64, CHUNK(7) * 80); }
        }
        if (i > 5) mbar_wait(BAR(BR_OEMPTY - 5) + 8 * i, 0);
        else if (EN_SSM && i != 2 && i != 3) mbar_wait(i == 1 ? BAR(BR_KS + 1) : BAR(BR_FREE - 4) + 8 * i, 0);
        if (elect_one()) {
          mbar_expect_tx(BAR(BR_OFULL) + 8 * i, 20480);
          bulk_ld(sb + SLOT(i), &g_o[(r * 8 + src) * 1280], 20480, BAR(BR_OFULL) + 8 * i);
          if (i == 1) TS(21);
          if (i == 7) TS(22);
        }
        __syncwarp();
      }
      if (lane == 0) { DUMP(20, 30); }
      }
    } else {
      const int hw = warp - 13, ht = tid - 416;
      if (hw == 2 && elect_one()) {
        #pragma unroll
        for (int i = 5; i <= BR_WO2; i++) mbar_init(BAR(i), i > BR_DRDY ? 1 : i == BR_WO ? 33 : i == BR_GEMM ? 8 : i < BR_EMPTY ? 1 : i < BR_OEMPTY ? 2 : i < BR_Y ? 8 : i < BR_DRDY ? 4 : 3);
        asm volatile("fence.mbarrier_init.release.cluster;" ::: "memory");
      }
      __syncwarp();
      asm volatile("bar.arrive 0, 512;" ::: "memory");
      if (EN_SSM && hw == 2) asm volatile("bar.arrive 8, 160;" ::: "memory");
      const unsigned epoch = hw == 0 ? ld_rlx(&g_epoch[cta]) + 1 : 0;
      if (ht < 80) sts128(sb + OFF_BLK + (ht >> 4) * BLK - 256 + (ht & 15) * 16, 0, 0, 0, 0);
      bar_sync(5, 96);
      asm volatile("bar.arrive 6, 128;" ::: "memory");
      if (hw == 1 && elect_one()) {
        #pragma unroll
        for (int i = M_U; i < M_COUNT; i++) asm volatile("prefetch.tensormap [%0];" :: "l"(&prm.m[i]) : "memory");
      }
      if (ht == 0) {
        st_rlx(&g_epoch[cta], epoch);
        sts32(sb + OFF_EPOCH, epoch);
        mbar_arrive(BAR(BR_EPOCH));
      }
      if (EN_SSM) {
      const int mi = lane >> 3, rw = lane & 7;
      const bool early_u = hw == 0 && __all_sync(0xffffffff, ld_acq(FLAG(1, lane & 15, c)) == epoch);
      mbar_wait(BAR(BR_UIN), 0);
      if (ht == 0) TS(36);
      #pragma unroll 1
      for (int h = 0; h < 2; h++) {
        const uint32_t sa = sb + OFF_UT + h * 10240 + (8 * mi + rw) * 160 + hw * 16, da = sb + OFF_UT + h * 10240 + (hw * 8 + rw) * 128 + ((mi ^ rw ^ h) << 4);
        uint32_t v[8][4];
        #pragma unroll
        for (int q = 0; q < 8; q++) if (q < 6 || hw == 0) ldsm4t(v[q], sa + (q & 1) * 5120 + (q >> 1) * 48);
        bar_sync(5, 96);
        #pragma unroll
        for (int q = 0; q < 8; q++) if (q < 6 || hw == 0) stsm4((da ^ ((q & 1) * 64)) + (q >> 1) * 3072, v[q][0], v[q][1], v[q][2], v[q][3]);
      }
      fence_async();
      bar_sync(5, 96);
      if (hw == 0) {
        if (elect_one()) {
          tma2d_st(&prm.m[M_SA], sb + OFF_UT, r * 128, c * 80);
          tma2d_st(&prm.m[M_SA], sb + OFF_UT + 10240, r * 128 + 64, c * 80);
          bulk_commit(); bulk_wait0_read();
          mbar_arrive(BAR(BR_UOUT));
          TS(37);
          bulk_wait0();
          st_rel(FLAG(1, r, c), epoch);
          TS(30);
        }
        __syncwarp();
        if (!early_u) poll_all_acq(FLAG(1, lane & 15, c), epoch);
      }
      #pragma unroll 1
      for (int k = 0; k < 5; k++) {
        if (k == 0 || k == 3) {
          const int p = k != 0;
          if (hw == 0) {
            if (!p) {
              if (elect_one()) {
                fence_async_g();
                mbar_expect_tx(BAR(BR_U), 12288);
                #pragma unroll 1
                for (int q = 0; q < 3; q++) bulk_ld(sb + OFF_BLK + q * q * BLK, g_uy + CHAN(q * q) * 2048, 4096, BAR(BR_U));
                TS(31);
              }
              __syncwarp();
            }
            mbar_wait(BAR(p ? BR_U2 : BR_U), 0);
          }
          bar_sync(5, 96);
        }
        const int l3 = (hw + k) % 3 * 32 + lane;
        const uint32_t blk = sb + OFF_BLK + ((0x32410 >> (4 * k)) & 7) * BLK, o = blk + B_D + l3 * 16;
        float P[34];
        P[0] = 0.f;
        #pragma unroll
        for (int q = 0; q < 5; q++) {
          const int ch = 2 * l3 - 3 + q;
          uint32_t v[4];
          lds128(v, blk + (uint32_t)((ch * 16) ^ ((ch * 2) & 0x10)));
          #pragma unroll
          for (int e = 0; e < 8; e++) {
            const int i = 8 * q + e - 4;
            if (i >= 0 && i < 33) P[i + 1] = P[i] + ((e & 1) ? bf_hi(v[e >> 1]) : bf_lo(v[e >> 1]));
          }
        }
#define WIN(lo, hi, e) (P[21 + (e) - (lo)] - P[20 + (e) - (hi)])
#define WIN8(lo, hi, b) pack2(WIN(lo, hi, b), WIN(lo, hi, b + 1)), pack2(WIN(lo, hi, b + 2), WIN(lo, hi, b + 3)), pack2(WIN(lo, hi, b + 4), WIN(lo, hi, b + 5)), pack2(WIN(lo, hi, b + 6), WIN(lo, hi, b + 7))
        if (l3 < 64) {
          sts128(o + B_D9, WIN8(12, 20, 0)); sts128(o + B_D9 + 1024, WIN8(12, 20, 8));
          sts128(o + B_D7, WIN8(5, 11, 0)); sts128(o + B_D7 + 1024, WIN8(5, 11, 8));
        }
        sts128(o + B_D5, WIN8(6, 10, 0)); sts128(o + B_D5 + 1552, WIN8(6, 10, 8));
        sts128(o, WIN8(3, 5, 0)); sts128(o + 1552, WIN8(3, 5, 8));
        if (l3 < 2) sts128(blk + B_D + l3 * B_D5 + 1536, 0, 0, 0, 0);
      }
      __syncwarp();
      if (lane == 0) mbar_arrive(BAR(BR_DRDY));
      if (ht == 0) TS(32);
      if (hw == 0) {
        const bool early = __all_sync(0xffffffff, ld_rlx(FLAG(lane < 16 ? 4 : 2, lane & 15, c)) == epoch);
        const uint32_t ym = lane < 4 ? 0x10001u : 0u, ytag = (epoch & 1u) * 0x10001u, yb = sb + OFF_EXTRA + 16384;
        mbar_wait(BAR(BR_Y + 1), 0);
        if (elect_one()) {
          bulk_st(g_uy + (640 + CHAN(4)) * 2048, sb + OFF_BLK + 4 * BLK, 4096);
          bulk_commit(); bulk_wait0_read();
          mbar_arrive(BAR(BR_FREE + 1));
          bulk_wait0();
          st_rlx(FLAG(4, r, c), epoch);
          TS(33);
        }
        __syncwarp();
        if (!early) poll_all(FLAG(4, lane & 15, c), epoch);
        uint32_t v[8][4];
        #pragma unroll 1
        for (int n = 0; n < 64; n++) {
          if (elect_one()) {
            mbar_expect_tx(BAR(BR_YIN2), 4096);
            tma2d(yb, &prm.m[M_SZ], BAR(BR_YIN2), r * 128, 640 + c * 80 + 64);
            tma2d(yb + 2048, &prm.m[M_SZ], BAR(BR_YIN2), r * 128 + 64, 640 + c * 80 + 64);
            TS(34);
          }
          __syncwarp();
          mbar_wait(BAR(BR_YIN2), n & 1);
          uint32_t bad = 0;
          #pragma unroll
          for (int q = 0; q < 8; q++) {
            ldsm4t(v[q], yb + rw * 128 + ((mi ^ rw ^ ((q & 1) * 4) ^ ((q >> 1) & 1)) << 4) + ((q >> 1) & 1) * 2048 + (q >> 2) * 1024);
            bad |= (v[q][0] ^ ytag) | (v[q][2] ^ ytag);
          }
          if (!__any_sync(0xffffffff, bad & ym)) break;
          FIXCNT
        }
        #pragma unroll
        for (int q = 0; q < 8; q++) stsm4(yb + lane * 32 + (q & 3) * 1024 + (q >> 2) * 16, v[q][0] & ~ym, v[q][1], v[q][2] & ~ym, v[q][3]);
        fence_async();
        __syncwarp();
        if (elect_one()) {
          TS(39);
          tma2d_st(&prm.m[M_O16], yb, c * 80 + 64, r * 128);
          tma2d_st(&prm.m[M_O16], yb + 2048, c * 80 + 64, r * 128 + 64);
          bulk_commit(); bulk_wait0_read();
          TS(35); DUMP(30, 40); DUMP(0, 1);
        }
      }
      }
    }
  } else {
  if (wg < 2) {
    asm volatile("setmaxnreg.inc.sync.aligned.u32 160;");
    bar_sync(0, 512);
    if (EN_ATT) {
    float am[96], ar[24];
    {
      const bool lead = (rtid() & 127) == 0;
      constexpr uint64_t dr0 = mkdesc(SB0 + 12288, 1024, 256, 3);
      const uint64_t dbc = sw64 ? mkdesc(SB0, 2048, 512, 2) : mkdesc(SB0, 4096, 1024, 1);
      const uint32_t kst = __shfl_sync(0xffffffff, sw64 ? 64 : 128, 0), bh = __shfl_sync(0xffffffff, (uint32_t)(dbc >> 32), 0);
      const uint64_t db0 = desc2(__shfl_sync(0xffffffff, (uint32_t)dbc, 0), bh);
      uint32_t ph = 0;
      const int ln = rtid() & 31;
      const uint32_t xa = sb + OFF_X + (warp * 16 + (ln & 15)) * 128 + (((ln >> 4) ^ (ln & 7)) << 4);
      uint32_t A[8];
      mbar_wait(BAR(BR_FULL), 0);
      if (lead && wg == 0) TS(1);
      ldsm4(A, xa); ldsm4(A + 4, xa ^ 32);
      wg_fence();
      wg_rs48_tb(ar, A, dr0, 0); wg_rs192_tb(am, A, db0, 0);
      wg_commit();
      uint32_t wp = 0, fb = BAR(BR_FULL), xk = xa;
      #pragma unroll 1
      for (int kb = 1; kb < 20; kb++) {
        const uint64_t d0 = desc2((uint32_t)dr0 + wp + 32, dr0 >> 32), d1 = desc2((uint32_t)db0 + wp + kst, bh);
        const uint32_t eb = fb + 8 * (BR_EMPTY - BR_FULL);
        wp += W_SLOT >> 4; fb += 8;
        if (wp == 5 * (W_SLOT >> 4)) { wp = 0; fb = BAR(BR_FULL); ph ^= 1; }
        wg_fence();
        wg_rs48_tb(ar, A + 4, d0, 1);
        wg_rs192_tb(am, A + 4, d1, 1);
        wg_commit();
        xk ^= 64;
        if (!(kb & 1)) { xk += 16384; if (xk >= sb + OFF_BAR) xk -= 49152; }
        mbar_wait(fb, ph);
        wg_wait<1>();
        ldsm4(A, xk);
        wg_fence();
        wg_rs48_tb(ar, A, desc2((uint32_t)dr0 + wp, dr0 >> 32), 1);
        wg_rs192_tb(am, A, desc2((uint32_t)db0 + wp, bh), 1);
        wg_commit();
        wg_wait<1>();
        ldsm4(A + 4, xk ^ 32);
        if (lead && kb < 16) mbar_arrive(eb);
      }
      wg_fence();
      wg_rs48_tb(ar, A + 4, dr0 + 4 * (W_SLOT >> 4) + 32, 1);
      wg_rs192_tb(am, A + 4, desc2((uint32_t)db0 + 4 * (W_SLOT >> 4) + kst, bh), 1);
      wg_commit();
      wg_wait<0>();
      if (ln == 0) mbar_arrive(BAR(BR_GEMM));
      pin<96>(am); pin<24>(ar);
    }
    const int tid = rtid(), lane = tid & 31, tq = lane & 3;
    if (tid == 0) TS(2);
#define QV(j, e) ((j) < 8 ? am[4 * (j) + (e)] : ar[4 * ((j) - 8) + (e)])
#define KV_(j, e) ((j) < 8 ? am[32 + 4 * (j) + (e)] : ar[8 + 4 * ((j) - 8) + (e)])
#define VV(j, e) ((j) < 8 ? am[64 + 4 * (j) + (e)] : ar[16 + 4 * ((j) - 8) + (e)])
    {
      bar_sync(1, 256);
      const uint32_t ro = sb + (uint32_t)((warp * 16 + (lane & 15)) * 16);
      const int l0 = 2 * (c & 1) + (lane >> 4);
      const uint32_t ones = (tq == 0) ? 0x00003f80u : 0u;
#define PV(j) pack2(VV(j, 0), VV(j, 1)), pack2(VV(j, 2), VV(j, 3))
#define PK(j) pack2(phi(KV_(j, 0)), phi(KV_(j, 1))), pack2(phi(KV_(j, 2)), phi(KV_(j, 3)))
      stsm4(ro + OFF_V + (5 + 6 * (lane >> 4)) * 2048, ones, ones, ones, ones);
      #pragma unroll
      for (int j = 0; j < 10; j += 2) {
        const int l = (j == 8 && (c & 1)) ? l0 - 2 : l0 + j;
        stsm4(ro + OFF_V + (l + (l >= 5)) * 2048, PV(j), PV(j + 1));
        stsm4(ro + OFF_PK + l * 2048, PK(j), PK(j + 1));
      }
    }
    fence_async();
    bar_sync(1, 256);
    if (tid == 0) TS(3);
    mbar_wait(BAR(BR_EPOCH), 0);
    const unsigned epoch = lds32(sb + OFF_EPOCH);
    {
      float kv[24]; zero<24>(kv);
      constexpr uint64_t da = mkdesc(SB0 + OFF_PK, 128, 2048, 0), db = mkdesc(SB0 + OFF_V, 128, 2048, 0);
      wg_fence();
      #pragma unroll
      for (int s = 0; s < 8; s++) wg_ss48_tt(kv, desc2((uint32_t)da + wg * 640 + s * 16, da >> 32), desc2((uint32_t)db + wg * 768 + s * 16, db >> 32), s != 0);
      wg_commit();
      wg_wait<0>();
      pin<24>(kv);
      if (tid == 0) TS(15);
      if (w4 < 3) {
        const uint32_t wb = sb + OFF_KVS + (wg * 3 + w4) * 1536 + (lane & 15) * 96;
        #pragma unroll
        for (int j = 0; j < 6; j += 2)
          stsm4(wb + (j + (lane >> 4)) * 16, pack2(kv[4 * j], kv[4 * j + 1]), pack2(kv[4 * j + 2], kv[4 * j + 3]),
                pack2(kv[4 * j + 4], kv[4 * j + 5]), pack2(kv[4 * j + 6], kv[4 * j + 7]));
        __syncwarp();
        const int dl = w4 * 16 + (lane & 15), hl = dl >= 20;
        uint32_t v[4], z[4];
        lds128(v, wb + (3 * hl + (lane >> 4)) * 16);
        lds64(z, wb + 32 + 8 * hl); z[2] = lds32(wb + 80); z[3] = epoch & 1u;
        if (dl < 40) {
          uint4* dst = &g_kvp[(c * 16 + r) * 240 + wg * 40 + dl];
          v[3] = (v[3] & ~1u) | z[3];
          st128_rlx(dst + (lane >> 4) * 80, v);
          if (lane < 16) st128_rlx(dst + 160, z);
        }
      }
    }
    bar_sync(1, 256);
    if (tid == 0) { st_rlx(FLAG(0, r, c), epoch); mbar_arrive(BAR(BR_PUB)); TS(4); }
    const int kvi = (tid >= 80) + (tid >= 160) + (tid >= 240), kd = tid - 80 * kvi;
    const int khd = kd / 20, kt0 = 5 * (khd >> 1) + 2 * (khd & 1);
    const uint32_t rb = sb + OFF_KVB + kd * 16;
    if (kvi < 3) {
      #pragma unroll 1
      for (int m = kvi; m < 7; m += 3) { const int q = kt0 + 3 + m; sts128(rb + (q >= 10 ? q - 10 : q) * 1280, 0, 0, 0, 0); }
    }
    uint32_t qa[20];
    {
      const float sc = 1.44269504089f + __uint_as_float(lds32(sb + OFF_EPOCH) ^ epoch);
      #pragma unroll
      for (int j = 0; j < 10; j++) { qa[2 * j] = pack2(phi(QV(j, 0), sc), phi(QV(j, 1), sc)); qa[2 * j + 1] = pack2(phi(QV(j, 2), sc), phi(QV(j, 3), sc)); }
    }
    if (tid == 0) TS(5);
    if (warp == 7) mbar_wait(BAR(BR_KVP), 0);
    bar_sync(1, 256);
    if (tid == 0) TS(6);
    if (kvi < 3) {
      float s[8];
      zero<8>(s);
      uint32_t bad = 0;
      #pragma unroll 4
      for (int i = 0; i < 16; i += 2) {
        uint32_t w[4], x[4];
        lds128(w, sb + OFF_KVP + tid * 16 + i * 3840); lds128(x, sb + OFF_KVP + tid * 16 + i * 3840 + 3840);
        bad |= (w[3] ^ epoch) | (x[3] ^ epoch);
        #pragma unroll
        for (int e = 0; e < 4; e++) {
          asm("add.rn.bf16x2 %0, %0, %1;" : "+r"(w[e]) : "r"(x[e]));
          s[2 * e] += bf_lo(w[e]); s[2 * e + 1] += bf_hi(w[e]);
        }
      }
      if (__builtin_expect(bad & 1u, 0)) {
        zero<8>(s);
        #pragma unroll 1
        for (int i = 0; i < 16; i++) {
          uint32_t w[4] = {0, 0, 0, ~epoch};
          fix128_w3(w, &g_kvp[(c * 16 + i) * 240 + tid], epoch, 1u);
          #pragma unroll
          for (int e = 0; e < 4; e++) { s[2 * e] += bf_lo(w[e]); s[2 * e + 1] += bf_hi(w[e]); }
        }
        FIXCNT
      }
      const uint32_t p0 = pack2(s[0], s[1]), p1 = pack2(s[2], s[3]), p2 = pack2(s[4], s[5]), p3 = pack2(s[6], s[7]);
      if (kvi < 2) sts128(rb + (kt0 + (khd & 1) + kvi) * 1280, p0, p1, p2, p3);
      else {
        const bool od = khd & 1;
        sts128(rb + (5 * (khd >> 1) + 2) * 1280, od ? 0u : p0, od ? 0u : p1, od ? p0 : 0u, od ? p1 : 0u);
        const uint32_t zz = (p2 & 0xffffu) << (16 * (khd & 1));
        sts128(rb + 10 * 1280, khd < 2 ? zz : 0u, khd < 2 ? 0u : zz, 0u, 0u);
      }
    }
    fence_async();
    bar_sync(1, 256);
    if (tid == 0) TS(7);
    {
      float oa[44]; zero<44>(oa);
      constexpr uint64_t db = mkdesc(SB0 + OFF_KVB, 128, 1280, 0);
      wg_fence();
      #pragma unroll
      for (int s = 0; s < 5; s++) wg_rs88_tb(oa, &qa[4 * s], desc2((uint32_t)db + ((s == 4 && (c & 1)) ? 0 : (s + (c & 1)) * 16), db >> 32), s != 0);
      wg_commit();
      wg_wait<0>();
      pin<44>(oa);
      if (tid == 0) TS(13);
      float rc[4], rd[2][4];
      #pragma unroll
      for (int e = 0; e < 4; e++) asm("rcp.approx.ftz.f32 %0, %1;" : "=f"(rc[e]) : "f"(oa[40 + e] + 1e-6f));
      #pragma unroll
      for (int h = 0; h < 4; h++) {
        rd[0][h] = __shfl_sync(0xffffffff, rc[h & 1], (lane & 28) | (h >> 1));
        rd[1][h] = __shfl_sync(0xffffffff, rc[2 + (h & 1)], (lane & 28) | (h >> 1));
      }
      #pragma unroll
      for (int j = 0; j < 10; j++) {
        #pragma unroll
        for (int h = 0; h < 2; h++) {
          float f;
          if (j == 2) f = tq < 2 ? rd[h][0] : rd[h][1];
          else if (j == 7) f = tq < 2 ? rd[h][2] : rd[h][3];
          else f = rd[h][(8 * j) / 20];
          qa[2 * j + h] = pack2(oa[4 * j + 2 * h] * f, oa[4 * j + 2 * h + 1] * f);
        }
      }
      const uint32_t m0 = (lane & 7) == ((2 * w4) & 7), m1 = (lane & 7) == 2 * w4 + 1;
      const uint32_t oa_ = sb + OFF_OWN + (lane >> 4) * 2048 + (warp * 16 + (lane & 15)) * 16;
#define TAG(v, m) (((v) & ~(m)) | (epoch & (m)))
      #pragma unroll
      for (int s = 0; s < 5; s++) stsm4(oa_ + s * 4096, TAG(qa[4 * s], m0), TAG(qa[4 * s + 1], m1), TAG(qa[4 * s + 2], m0), TAG(qa[4 * s + 3], m1));
    }
    fence_async();
    __syncwarp();
    if (lane == 0) mbar_arrive(BAR(BR_OSTG));
    if (tid == 0) TS(8);
    }
    asm volatile("setmaxnreg.dec.sync.aligned.u32 136;");
  } else {
    const int g = lane >> 2, tq = lane & 3, t7 = tid & 127;
    asm volatile("bar.arrive 0, 512;" ::: "memory");
    if (EN_SSM) {
    {
      #pragma unroll 1
      for (int k = 0; k < 4; k++) {
        const uint32_t z = sb + OFF_BLK + k * BLK + t7 * 16;
        sts128(z + B_TBL, 0, 0, 0, 0); sts128(z + B_TBL + 2048, 0, 0, 0, 0);
      }
      const uint32_t ea = sb + OFF_BLK + (2 + (w4 & 1)) * BLK + (lane >> 4) * 7168 + ((lane >> 3) & 1) * 256 + (lane & 7) * 16 + (w4 >> 1) * 2048;
      constexpr uint64_t dE = mkdesc(SB0 + OFF_BLK + 2 * BLK, 128, 512, 0);
      const uint32_t xa = sb + OFF_BLK + 18560 + t7 * 8, xr_ = sb + OFF_BLK + 18560 + (t7 ^ 64) * 8;
      uint32_t pr[5][2];
      #pragma unroll
      for (int q = 0; q < 5; q++) {
        #pragma unroll
        for (int e = 0; e < 2; e++) pr[q][e] = __byte_perm(raw[q][e], __shfl_xor_sync(0xffffffff, raw[q][e], 1), (lane & 1) ? 0x3276 : 0x5410);
        const uint32_t m = __reduce_max_sync(0xffffffff, max(raw[q][1] & 0x7fffu, (raw[q][1] >> 16) & 0x7fffu));
        if (lane == 0) sts32(sb + OFF_EPOCH + 64 + q * 16 + w4 * 4, m);
      }
      bar_sync(4, 128);
      if (t7 == 0) TS(40);
      const int j = (w4 & 1) * 16 + (w4 >> 1) * 8 + g, i2 = tq < 2 ? 64 * tq + j : 32 * (tq - 2) + j;
      const uint32_t e2 = B_TBL + 4 * (tq < 2 ? T_F3 + (((i2 - 1) & 1) ? 80 : 0) + ((i2 - 1) >> 1) + 16 : T_F2 + (i2 & 1) * 96 + (i2 >> 1));
      const uint32_t e1 = tq < 2 ? (i2 ? e2 - 64 : B_TBL + 4 * (T_F2 + 175)) : B_TBL + 4 * (i2 ? T_F2 + ((2 * i2 - 1) & 3) * 48 + ((2 * i2 - 1) >> 2) : 16 + 511);
      const uint32_t e0 = B_TBL + (16 + 8 * j + 2 * tq) * 4;
      const float dtl = bf_round(expf(bf_lo(pd)));
      float hd[9];
      auto head = [&](int q) {
        const uint32_t pa0 = pr[0][0], pc0 = pr[0][1];
        const float dt = __shfl_sync(0xffffffff, dtl, q);
        #pragma unroll
        for (int e = 0; e < 2; e++) { pr[0][e] = pr[1][e]; pr[1][e] = pr[2][e]; pr[2][e] = pr[3][e]; pr[3][e] = pr[4][e]; }
        uint32_t mm[4];
        lds128(mm, sb + OFF_EPOCH + 64 + q * 16);
        const uint32_t ex = min(max(max(max(mm[0], mm[1]), max(mm[2], mm[3])) >> 7, 1u), 253u);
        const float sc = __uint_as_float((254u - ex) << 23);
        const float lr = -bf_round(expf(bf_lo(pa0))) * dt * 1.44269504089f;
        const float tn = bf_hi(pa0) * dt * 0.15915494309f;
        cexp_t(lr, -tn, hd[0], hd[1]);
        cexp_t(lr * 8.f, tn * 8.f, hd[2], hd[3]);
        cexp_t(lr * 64.f, tn * 64.f, hd[4], hd[5]);
        hd[6] = bf_lo(pc0) * sc; hd[7] = -bf_hi(pc0) * sc;
        hd[8] = 2.f * dt * __uint_as_float(ex << 23);
      };
      head(0);
      #pragma unroll 1
      for (int it = 0; it < 5; it++) {
        const int k = it;
        const uint32_t blk = sb + OFF_BLK + k * BLK;
        float fac = 0.f;
        float ka[24]; zero<24>(ka);
        {
          if (it == 4) {
            mbar_wait(BAR(BR_UOUT), 0);
            sts128(sb + OFF_UT + B_TBL + t7 * 16, 0, 0, 0, 0); sts128(sb + OFF_UT + B_TBL + 2048 + t7 * 16, 0, 0, 0, 0);
          }
          const uint32_t ga = ea + 4096 - (w4 >> 1) * 512;
#define PUT4(i, a, b, c_, d) sts128(((i) < 8 ? ea + ((i) >> 1) * 512 : ga + (((i) - 8) >> 1) * 512) + ((i) & 1) * 128, a, b, c_, d)
          float z2r, z2i, z4r, z4i, xr[8], xi[8], gr[8], gi[8], wr[9], wi[9];
          const float z1r = hd[0], z1i = hd[1];
          xr[1] = hd[2]; xi[1] = hd[3]; wr[0] = hd[4]; wi[0] = hd[5];
          fac = hd[8];
          xr[0] = 1.f; xi[0] = 0.f;
          csq(xr[1], xi[1], xr[2], xi[2]); cmul(xr[2], xi[2], xr[1], xi[1], xr[3], xi[3]);
          csq(xr[2], xi[2], xr[4], xi[4]);
          #pragma unroll
          for (int b = 1; b < 4; b++) cmul(xr[4], xi[4], xr[b], xi[b], xr[4 + b], xi[4 + b]);
          csq(wr[0], wi[0], wr[1], wi[1]); cmul(wr[1], wi[1], wr[0], wi[0], wr[2], wi[2]);
          csq(wr[1], wi[1], wr[3], wi[3]); csq(wr[3], wi[3], wr[4], wi[4]);
          cmul(wr[4], wi[4], wr[3], wi[3], wr[5], wi[5]); csq(wr[4], wi[4], wr[6], wi[6]);
          cmul(wr[6], wi[6], wr[4], wi[4], wr[7], wi[7]); csq(wr[6], wi[6], wr[8], wi[8]);
          uint32_t R[4], I[4], PR[4], PI[4];
          #pragma unroll
          for (int b = 0; b < 4; b++) { R[b] = packh(xr[2 * b], xr[2 * b + 1]); I[b] = packh(xi[2 * b], xi[2 * b + 1]); }
          PUT4(0, R[0], R[1], R[2], R[3]); PUT4(1, I[0], I[1], I[2], I[3]);
          #pragma unroll
          for (int i = 0; i < 3; i++) {
            const uint32_t z = packh(wr[i], wi[i]);
            #pragma unroll
            for (int b = 0; b < 4; b++) hcm2(R[b], I[b], z, PR[b], PI[b]);
            PUT4(2 * i + 2, PR[0], PR[1], PR[2], PR[3]); PUT4(2 * i + 3, PI[0], PI[1], PI[2], PI[3]);
          }
          gr[0] = hd[6]; gi[0] = hd[7];
          csq(z1r, z1i, z2r, z2i); csq(z2r, z2i, z4r, z4i);
          cmul(gr[0], gi[0], z1r, z1i, gr[1], gi[1]);
          cmul(gr[0], gi[0], z2r, z2i, gr[2], gi[2]); cmul(gr[1], gi[1], z2r, z2i, gr[3], gi[3]);
          #pragma unroll
          for (int b = 0; b < 4; b++) cmul(gr[b], gi[b], z4r, z4i, gr[4 + b], gi[4 + b]);
          PUT4(8, packh(gr[0], gr[1]), packh(gr[2], gr[3]), packh(gr[4], gr[5]), packh(gr[6], gr[7]));
          PUT4(9, packh(gi[0], gi[1]), packh(gi[2], gi[3]), packh(gi[4], gi[5]), packh(gi[6], gi[7]));
          {
            const uint32_t z = packh(wr[3], wi[3]), a4r = packh(gr[0], gr[4]), a4i = packh(gi[0], gi[4]);
            hcm2c(packh(gr[0], gr[2]), packh(gi[0], gi[2]), z, PR[0], PI[0]);
            hcm2c(packh(gr[4], gr[6]), packh(gi[4], gi[6]), z, PR[1], PI[1]);
            hcm2c(a4r, a4i, packh(wr[4], wi[4]), PR[2], PI[2]);
            hcm2c(a4r, a4i, packh(wr[5], wi[5]), PR[3], PI[3]);
            PUT4(10, PR[0], PR[1], PR[2], PR[3]); PUT4(11, PI[0], PI[1], PI[2], PI[3]);
            float hr, hi_;
            cmul(gr[0], gi[0], wr[3], -wi[3], hr, hi_);
            const uint32_t cr = packh(gr[0], hr), ci = packh(gi[0], hi_);
            #pragma unroll
            for (int i = 0; i < 3; i++) hcm2c(cr, ci, packh(wr[6 + i], wi[6 + i]), PR[i], PI[i]);
            PUT4(12, PR[0], PR[1], PR[2], 0u); PUT4(13, PI[0], PI[1], PI[2], 0u);
          }
          fence_async();
          bar_sync(4, 128);
          wg_fence();
          #pragma unroll
          for (int s = 0; s < 8; s++) {
            const uint64_t d = dE + (s >> 2) * (BLK >> 4) + ((s >> 1) & 1) * 448 + (s & 1) * 16;
            wg_ss48_tt_h(ka, d, d + 256, s != 0);
          }
          wg_commit();
        }
        const float dsk = bf_lo(__shfl_sync(0xffffffff, pd, 8 + (it & 7)));
        head(min(it + 1, 4));
        pin<9>(hd);
        wg_wait<0>();
        pin<24>(ka);
        float kk[6];
        const bool up = w4 >= 2;
        #pragma unroll
        for (int n = 0; n < 3; n++) {
          sts64f(xa + n * BLK, up ? ka[12 + 4 * n] : ka[4 * n + 2], up ? ka[13 + 4 * n] : ka[4 * n + 3]);
          kk[2 * n] = up ? ka[14 + 4 * n] : ka[4 * n]; kk[2 * n + 1] = up ? ka[15 + 4 * n] : ka[4 * n + 1];
        }
        if (it) bar_sync(4, 128); else bar_sync(8, 160);
          if (it == 4 && w4 == 0) {
            mbar_wait(BAR(BR_U), 0);
            if (elect_one()) {
              mbar_expect_tx(BAR(BR_U2), 8192);
              bulk_ld(blk - 2 * BLK, g_uy + CHAN(2) * 2048, 4096, BAR(BR_U2)); bulk_ld(blk - BLK, g_uy + CHAN(3) * 2048, 4096, BAR(BR_U2));
            }
            __syncwarp();
          }
        #pragma unroll
        for (int n = 0; n < 3; n++) {
          uint32_t o[2]; lds64(o, xr_ + n * BLK);
          kk[2 * n] = (kk[2 * n] + __uint_as_float(o[0])) * fac; kk[2 * n + 1] = (kk[2 * n + 1] + __uint_as_float(o[1])) * fac;
        }
        if (t7 == 0) kk[0] += dsk;
        {
          const uint32_t v = pack2(kk[1], kk[0]), vh = v >> 16;
          const uint32_t u = pack2(kk[2], kk[3]), w = pack2(kk[4], kk[5]), uu = pack2(kk[2], kk[2]), us = pack2(kk[3], kk[2]);
          const uint32_t x = tq < 2 ? w : u, xh = x >> 16;
          sts32(blk + e0 + 4, v); sts16(blk + e0, vh); sts16(blk + e0 + 10, v);
          sts16(blk + e1, x); sts16(blk + e1 + 6, x); sts16(blk + e2, xh); sts16(blk + e2 + 6, xh);
          if (tq < 2) {
            const uint32_t pb = blk + e0 + 1024 + 8 * tq;
            sts32(pb + 4, uu); sts32(pb + 8, us); sts16(pb + 14, us);
            if (i2) { sts16(pb - 4, u); sts32(pb, uu); }
          }
          if (i2 == 0) {
            const uint32_t tb = blk + B_TBL;
            if (tq == 0) { sts16(tb + (16 + 256) * 4, u); sts16(tb + (T_S + 3) * 4, w); sts32(tb + (T_S + 4) * 4, pack2(kk[4], kk[4])); sts16(tb + (T_S + 5) * 4 + 2, w); }
            else { sts32(tb + 528 * 4, uu); sts32(tb + 529 * 4, uu); sts32(tb + 530 * 4, uu); sts16(tb + 531 * 4 + 2, u); sts16(tb + (T_F3 + 80 + 63) * 4, w); }
          }
        }
        if (t7 == 0) TS(49 + it);
      }
    }
    asm volatile("setmaxnreg.inc.sync.aligned.u32 136;");
    if (t7 == 0) TS(41);
    bar_sync(4, 128);
    if (t7 == 0) mbar_arrive(BAR(BR_KS));
    }
  }
  const int tid = rtid(), lane = tid & 31, g = lane >> 2, tq = lane & 3, t7 = tid & 127;
  mbar_wait(BAR(BR_EPOCH), 0);
  const unsigned epoch = lds32(sb + OFF_EPOCH);
  const uint32_t ytag = (epoch & 1u) * 0x10001u, ym = lane < 4 ? 0x10001u : 0u;
  if (EN_SSM && wg != 1) {
    mbar_wait(BAR(BR_KS), 0);
    mbar_wait(BAR(BR_U), 0);
    if (EN_ATT) mbar_wait(BAR(BR_GEMM), 0);
    if (tid == 256) TS(42);
    {
      const int pass = wg >> 1;
      const int k = pass ? w4 : 4;
      if (k & 2) mbar_wait(BAR(BR_U2), 0);
      const uint32_t blk = sb + OFF_BLK + k * BLK, tb = blk + B_TBL + (uint32_t)((g - 2 * tq) * 4);
      float acc[16][4];
      zero<64>(&acc[0][0]);
      const int kl = 16 * (lane >> 4) + 2 * (lane & 7) + ((lane >> 3) & 1);
      {
        auto ubase = [&](int sh) { const int q = kl - 2 * sh; return blk + (uint32_t)((q * 16) ^ ((q * 2) & 0x10)); };
#define LDQ(A, sh) _Pragma("unroll") for (int m = 0; m < 4; m++) load_quad(A[m], tb + (16 + 16 * (sh) + 128 * m) * 4);
#define LDB(B, ub, h) _Pragma("unroll") for (int p = 0; p < 4; p++) ldsm4(B[p], (ub) + (4 * (h) + p) * 512);
#define MLO(A, B) _Pragma("unroll") for (int m = 0; m < 4; m++) _Pragma("unroll") for (int cc = 0; cc < 8; cc++) mma16816(acc[cc + m], A[m], &B[cc >> 1][(cc & 1) * 2]);
#define MHI(A, B) _Pragma("unroll") for (int m = 0; m < 4; m++) _Pragma("unroll") for (int cc = 0; cc < 8 - m; cc++) mma16816(acc[8 + cc + m], A[m], &B[cc >> 1][(cc & 1) * 2]);
        int p_ = pass ? 0 : w4;
        const int pe = pass ? 4 : w4 + 1;
        uint32_t A[4][4], A2[4][4], Bl[4][4], Bh[4][4];
        uint32_t ub = ubase(p_ + 4);
        LDQ(A, p_ + 4) LDB(Bl, ub, 0)
        #pragma unroll 1
        for (; p_ < pe; p_++) {
          LDB(Bh, ub, 1)
          MLO(A, Bl)
          ub = ubase(p_);
          LDQ(A2, p_) LDB(Bl, ub, 0)
          MHI(A, Bh)
          LDB(Bh, ub, 1)
          load_quad(A[0], tb + (16 + 512 + 16 * (p_ & 1)) * 4); load_quad(A[1], tb + (T_S + 16 * (p_ & 1)) * 4);
          MLO(A2, Bl)
          if (p_ < 2) {
            #pragma unroll
            for (int cc = 0; cc < 8; cc++) mma16816(acc[cc + 4], A[0], &Bl[cc >> 1][(cc & 1) * 2]);
            #pragma unroll
            for (int cc = 0; cc < 4; cc++) mma16816(acc[cc + 12], A[0], &Bh[cc >> 1][(cc & 1) * 2]);
            #pragma unroll
            for (int cc = 0; cc < 8; cc++) mma16816(acc[cc + 8], A[1], &Bl[cc >> 1][(cc & 1) * 2]);
          }
          const int pn = ((p_ + 1) & 3) + 4;
          ub = ubase(pn);
          LDQ(A, pn) LDB(Bl, ub, 0)
          MHI(A2, Bh)
        }
      }
      if (t7 == 0) TS(pass ? 60 : 16);
      mbar_wait(BAR(BR_DRDY), 0);
      {
        const int ih = (lane >> 3) & 1;
        const uint32_t dl = blk + B_D + (uint32_t)(((lane >> 4) * 8 + (lane & 7)) * 16);
        const uint32_t d0_ = dl + ih * 1552, d8_ = dl + (ih ? 0 : 1536), d3_ = dl + B_D7 + ih * 1024;
        auto cls2 = [&](uint32_t da, uint32_t ta) {
          uint32_t B[6][2], A[6][4];
          #pragma unroll
          for (int e = 0; e < 6; e++) { B[e][0] = lds32v(ta + (e + 4) * 32); B[e][1] = lds32v(ta + (e + 3) * 32); }
          #pragma unroll
          for (int kk = 0; kk < 6; kk++) ldsm4t(A[kk], da + kk * 256);
          #pragma unroll
          for (int e = 0; e < 6; e++)
            #pragma unroll
            for (int kk = 0; kk < 6; kk++) if (2 * kk + e + 4 < 16) mma16816(acc[2 * kk + e + 4], A[kk], B[e]);
        };
        auto cls3 = [&](uint32_t da, uint32_t ta) {
          uint32_t B[8][2], A[4][4];
          #pragma unroll
          for (int e = 0; e < 8; e++) { B[e][0] = lds32v(ta + (e + 8) * 32); B[e][1] = lds32v(ta + (e + 7) * 32); }
          #pragma unroll
          for (int kk = 0; kk < 4; kk++) ldsm4t(A[kk], da + kk * 256);
          #pragma unroll
          for (int kk = 0; kk < 4; kk++)
            #pragma unroll
            for (int e = 0; e < 8; e++) if (2 * kk + e + 8 < 16) mma16816(acc[2 * kk + e + 8], A[kk], B[e]);
        };
        if (pass) {
          #pragma unroll 1
          for (int a = 0; a < 2; a++) {
            cls2(d0_ + a * B_D5, tb + (T_F2 + 48 * a - 32) * 4);
            cls2(d8_ + a * B_D5, tb + (T_F2 + 48 * a + 64) * 4);
            cls3(d3_ + a * 2048, tb + (T_F3 + 80 * a - 64) * 4);
          }
        } else {
          cls2(((w4 & 2) ? d8_ : d0_) + (w4 & 1) * B_D5, tb + (T_F2 + 48 * w4 - 32) * 4);
          if (w4 >= 2) cls3(d3_ + (w4 - 2) * 2048, tb + (T_F3 + 80 * (w4 - 2) - 64) * 4);
        }
      }
      if (t7 == 0) TS(pass ? 61 : 17);
      const uint32_t ya = (pass ? sb + OFF_BLK + 3 * BLK + w4 * 4096 : blk) + (uint32_t)((kl * 16) ^ ((kl * 2) & 0x10));
#define YTAG(v) (((v) & ~ym) | (ytag & ym))
#define STY(p) stsm4t(ya + (p) * 512, YTAG(pack2(acc[2 * (p)][0], acc[2 * (p)][1])), pack2(acc[2 * (p)][2], acc[2 * (p)][3]), \
                      YTAG(pack2(acc[2 * (p) + 1][0], acc[2 * (p) + 1][1])), pack2(acc[2 * (p) + 1][2], acc[2 * (p) + 1][3]))
      if (pass == 0) {
        const uint32_t xw = blk + 4096 + w4 * 4096 + lane * 16, xr = blk + 4096 + w4 * 1024 + lane * 16;
        #pragma unroll
        for (int h = 0; h < 2; h++) {
          bar_sync(2, 128);
          #pragma unroll
          for (int i = 0; i < 8; i++)
            sts128(xw + i * 512, __float_as_uint(acc[8 * h + i][0]), __float_as_uint(acc[8 * h + i][1]), __float_as_uint(acc[8 * h + i][2]), __float_as_uint(acc[8 * h + i][3]));
          bar_sync(2, 128);
          float y[8];
          #pragma unroll
          for (int i = 0; i < 8; i++) {
            uint32_t o[4]; lds128(o, xr + (i >> 1) * 4096 + (i & 1) * 512);
            #pragma unroll
            for (int e = 0; e < 4; e++) y[4 * (i & 1) + e] = i < 2 ? __uint_as_float(o[e]) : y[4 * (i & 1) + e] + __uint_as_float(o[e]);
          }
          stsm4t(ya + (4 * h + w4) * 512, YTAG(pack2(y[0], y[1])), pack2(y[2], y[3]), YTAG(pack2(y[4], y[5])), pack2(y[6], y[7]));
        }
      } else {
        fence_async();
        bar_sync(4, 128);
        if (t7 == 0) mbar_arrive(BAR(BR_KS + 1));
        #pragma unroll
        for (int p = 0; p < 8; p++) STY(p);
      }
      fence_async();
      __syncwarp();
      if (lane == 0) mbar_arrive(BAR(BR_Y + 1) - 8 * pass);
      if (t7 == 0) TS(pass ? 62 : 18);
    }
  }
  if (wg < 2) {
    if (EN_ATT) {
    float oc[40]; zero<40>(oc);
    {
      constexpr uint64_t dw0 = mkdesc(SB0, OFF_WOR, 1024, 1), da0 = mkdesc(SB0, 2048, 128, 0);
      const uint32_t ck = sb + tid * 32 + ((lane >> 2) << 2), ck2 = ck + (wg ? 0 : 16384);
      uint32_t bad = 0;
      auto tile = [&](int i, uint32_t so) {
        const uint32_t al = (uint32_t)da0 + wg * 64 + (so >> 4), wl = (uint32_t)dw0 + i * 640 - (i >> 1) * (1278 << 16);
        wg_fence();
        #pragma unroll
        for (int s = 0; s < 5; s++) wg_ss80_tb(oc, desc2(al + s * 256, da0 >> 32), desc2(wl + s * 128, dw0 >> 32), (i | s) != 0);
        wg_commit();
        bad |= (lds32(ck + so) ^ epoch) | (lds32(ck + so + 8192) ^ epoch) | (lds32(ck2 + so) ^ epoch);
      };
      if (w4 == 0) {
        if (EN_SSM) mbar_wait(BAR(BR_Y), 0);
        mbar_wait(BAR(BR_WO), 0);
      }
      bar_sync(1, 256);
      if (tid == 0) TS(9);
      tile(0, SLOT(0));
      #pragma unroll 1
      for (int i = 1; i < 8; i++) {
        mbar_wait(BAR(BR_OFULL) + 8 * i, 0);
        if (i == 6) mbar_wait(BAR(BR_WO2), 0);
        tile(i, SLOT(i));
        wg_wait<1>();
        if (lane == 0) mbar_arrive(BAR(BR_OEMPTY - 1) + 8 * i);
      }
      #pragma unroll 1
      for (int n = 0; n < 56; n++) {
        const int i = n & 7;
        if (i == 0) {
          uint32_t any;
          asm volatile("{\n.reg .pred p;\nsetp.ne.u32 p, %1, 0;\nbarrier.red.or.pred p, 1, 256, p;\nselp.u32 %0, 1, 0, p;\n}" : "=r"(any) : "r"(bad & 1u) : "memory");
          if (!any) break;
          bad = 0;
          FIXCNT
        }
        wg_wait<0>();
        bar_sync(1, 256);
        if (tid == 0) { mbar_expect_tx(BAR(BR_RETRY), 20480); bulk_ld(sb + SLOT(2), &g_o[(r * 8 + CHUNK(i)) * 1280], 20480, BAR(BR_RETRY)); }
        mbar_wait(BAR(BR_RETRY), n & 1);
        tile(i, SLOT(2));
      }
      wg_wait<0>();
      pin<40>(oc);
    }
    if (tid == 0) TS(10);
    {
      const int row = w4 * 16 + (lane & 15);
      const uint32_t ob = sb + OFF_BLK + 3 * BLK + wg * 10240;
      #pragma unroll
      for (int j = 0; j < 8; j += 2)
        stsm4(ob + row * 128 + (((j + (lane >> 4)) ^ (row & 7)) << 4), pack2(oc[4 * j], oc[4 * j + 1]), pack2(oc[4 * j + 2], oc[4 * j + 3]),
              pack2(oc[4 * j + 4], oc[4 * j + 5]), pack2(oc[4 * j + 6], oc[4 * j + 7]));
      stsm4(ob + 8192 + row * 32 + (lane >> 4) * 16, pack2(oc[32], oc[33]), pack2(oc[34], oc[35]), pack2(oc[36], oc[37]), pack2(oc[38], oc[39]));
      fence_async();
      bar_sync(2 + wg, 128);
      if (w4 == 0 && elect_one()) {
        tma2d_st(&prm.m[M_O64], ob, 640 + c * 64, r * 128 + wg * 64);
        tma2d_st(&prm.m[M_O16], ob + 8192, 1152 + c * 16, r * 128 + wg * 64);
        bulk_commit(); bulk_wait0_read();
        if (wg == 0) { TS(11); DUMP(0, 20); }
      }
    }
    }
  } else if (EN_SSM) {
    const uint32_t yb = sb + OFF_EXTRA;
    const int mi = lane >> 3, rw = lane & 7;
    if (w4 == 0) {
      mbar_wait(BAR(BR_Y), 0);
      if (elect_one()) {
        bulk_st(g_uy + (640 + CHAN(0)) * 2048, sb + OFF_BLK + 3 * BLK, 16384);
        bulk_commit(); bulk_wait0_read();
        mbar_arrive(BAR(BR_FREE));
        bulk_wait0();
        st_rlx(FLAG(2, r, c), epoch);
      }
      __syncwarp();
      poll_all(FLAG(2, lane & 15, c), epoch);
      if (EN_ATT) mbar_wait(BAR(BR_OSTG), 0);
    }
    uint32_t v[8][4];
    #pragma unroll 1
    for (int n = 0; n < 64; n++) {
      if (w4 == 0) {
        if (elect_one()) {
          mbar_expect_tx(BAR(BR_YIN), 16384);
          tma2d(yb, &prm.m[M_SY], BAR(BR_YIN), r * 128, 640 + c * 80);
          tma2d(yb + 8192, &prm.m[M_SY], BAR(BR_YIN), r * 128 + 64, 640 + c * 80);
          TS(55);
        }
        __syncwarp();
        mbar_wait(BAR(BR_YIN), n & 1);
      }
      bar_sync(4, 128);
      uint32_t bad = 0, any;
      #pragma unroll
      for (int q = 0; q < 8; q++) {
        ldsm4t(v[q], yb + (w4 * 16 + rw) * 128 + ((mi ^ rw ^ ((q & 1) * 4) ^ ((q >> 1) & 1)) << 4) + ((q >> 1) & 1) * 8192 + (q >> 2) * 1024);
        bad |= (v[q][0] ^ ytag) | (v[q][2] ^ ytag);
      }
      asm volatile("{\n.reg .pred p;\nsetp.ne.u32 p, %1, 0;\nbarrier.red.or.pred p, 4, 128, p;\nselp.u32 %0, 1, 0, p;\n}" : "=r"(any) : "r"(bad & ym) : "memory");
      if (!any) break;
      FIXCNT
    }
    #pragma unroll
    for (int q = 0; q < 8; q++) stsm4(yb + lane * 128 + (((2 * w4 + (q >> 2)) ^ rw) << 4) + (q & 3) * 4096, v[q][0] & ~ym, v[q][1], v[q][2] & ~ym, v[q][3]);
    fence_async();
    bar_sync(4, 128);
    if (w4 == 0 && elect_one()) {
      tma2d_st(&prm.m[M_O64], yb, c * 80, r * 128);
      tma2d_st(&prm.m[M_O64], yb + 8192, c * 80, r * 128 + 64);
      bulk_commit(); bulk_wait0_read();
      TS(56); DUMP(40, 64);
    }
  }
  }
}

typedef CUresult (*EncFn)(CUtensorMap*, CUtensorMapDataType, cuuint32_t, void*, const cuuint64_t*, const cuuint64_t*, const cuuint32_t*,
                          const cuuint32_t*, CUtensorMapInterleave, CUtensorMapSwizzle, CUtensorMapL2promotion, CUtensorMapFloatOOBfill);
static void mkmap(EncFn enc, CUtensorMap* m, const void* base, int rank, const cuuint64_t* dims, const cuuint64_t* strides, const cuuint32_t* box, CUtensorMapSwizzle swz) {
  cuuint32_t es[5] = {1, 1, 1, 1, 1};
  enc(m, CU_TENSOR_MAP_DATA_TYPE_BFLOAT16, rank, const_cast<void*>(base), dims, strides, box, es, CU_TENSOR_MAP_INTERLEAVE_NONE, swz,
      CU_TENSOR_MAP_L2_PROMOTION_L2_128B, CU_TENSOR_MAP_FLOAT_OOB_FILL_NONE);
}

extern "C" void kernel_launch(void* const* d_in, const int* in_sizes, int n_in, void* d_out, int out_size) {
  void* fn = nullptr; cudaDriverEntryPointQueryResult qr;
  cudaGetDriverEntryPoint("cuTensorMapEncodeTiled", &fn, cudaEnableDefault, &qr);
  EncFn enc = (EncFn)fn;
  void* uy = nullptr; cudaGetSymbolAddress(&uy, g_uy);
  const cuuint64_t dx[2] = {640, 2048}, sx[1] = {1280};
  const cuuint32_t bx[2] = {64, 128}, bu[2] = {80, 128};
  const cuuint64_t dw[3] = {640, 640, 3}, sw[2] = {3840, 1280};
  const cuuint32_t br[3] = {16, 32, 3};
  const cuuint64_t dwa[4] = {64, 640, 10, 3}, swa[3] = {3840, 128, 1280}, dwb[4] = {32, 640, 20, 3}, swb[3] = {3840, 64, 1280};
  const cuuint32_t bwa[4] = {64, 32, 1, 3}, bwb[4] = {32, 32, 2, 3};
  const cuuint64_t dwo[2] = {640, 640};
  const cuuint32_t bwo[2] = {64, 80}, bo64[2] = {64, 64}, bo16[2] = {16, 64};
  const cuuint64_t dsa[2] = {2048, 1280}, ssa[1] = {4096};
  const cuuint32_t bsa[2] = {64, 80}, bsy[2] = {64, 64}, bsz[2] = {64, 16};
  const cuuint64_t dout[2] = {1280, 2048}, sout[1] = {2560};
  Params prm;
  mkmap(enc, &prm.m[M_X], d_in[7], 2, dx, sx, bx, CU_TENSOR_MAP_SWIZZLE_128B);
  mkmap(enc, &prm.m[M_W128], d_in[8], 4, dwa, swa, bwa, CU_TENSOR_MAP_SWIZZLE_128B);
  mkmap(enc, &prm.m[M_W64], d_in[8], 4, dwb, swb, bwb, CU_TENSOR_MAP_SWIZZLE_64B);
  mkmap(enc, &prm.m[M_WR], d_in[8], 3, dw, sw, br, CU_TENSOR_MAP_SWIZZLE_32B);
  mkmap(enc, &prm.m[M_U], d_in[0], 2, dx, sx, bu, CU_TENSOR_MAP_SWIZZLE_NONE);
  mkmap(enc, &prm.m[M_WO], d_in[9], 2, dwo, sx, bwo, CU_TENSOR_MAP_SWIZZLE_128B);
  mkmap(enc, &prm.m[M_O64], d_out, 2, dout, sout, bo64, CU_TENSOR_MAP_SWIZZLE_128B);
  mkmap(enc, &prm.m[M_O16], d_out, 2, dout, sout, bo16, CU_TENSOR_MAP_SWIZZLE_NONE);
  mkmap(enc, &prm.m[M_SA], uy, 2, dsa, ssa, bsa, CU_TENSOR_MAP_SWIZZLE_128B);
  mkmap(enc, &prm.m[M_SY], uy, 2, dsa, ssa, bsy, CU_TENSOR_MAP_SWIZZLE_128B);
  mkmap(enc, &prm.m[M_SZ], uy, 2, dsa, ssa, bsz, CU_TENSOR_MAP_SWIZZLE_128B);
  prm.u = (const __nv_bfloat16*)d_in[0]; prm.wo = (const __nv_bfloat16*)d_in[9];
  for (int i = 0; i < 4; i++) prm.par[i] = (const __nv_bfloat16*)d_in[1 + i];
  prm.logdt = (const __nv_bfloat16*)d_in[5]; prm.dskip = (const __nv_bfloat16*)d_in[6];
  cudaFuncSetAttribute(fused_kernel, cudaFuncAttributeMaxDynamicSharedMemorySize, SMEM_BYTES);
  fused_kernel<<<128, 512, SMEM_BYTES, cudaStreamPerThread>>>(prm);
}
```
